```python
import torch

def _softmax(x, axis=-1):
    return torch.softmax(x, dim=axis)
def _gelu(x):
    return torch.nn.functional.gelu(x, approximate="tanh")
def _silu(x):
    return torch.nn.functional.silu(x)
def _sigmoid(x):
    return torch.sigmoid(x)
def _layernorm(x, axis=-1, eps=1e-5):
    m = x.mean(dim=axis, keepdim=True)
    v = x.var(dim=axis, keepdim=True, unbiased=False)
    return (x - m) / torch.sqrt(v + eps)
def _scatter_add(tgt, idx, src, axis=0):
    return tgt.clone().index_add_(axis, idx, src)
def _segment_sum(src, seg, n):
    out = torch.zeros((n,) + src.shape[1:], dtype=src.dtype)
    return out.index_add_(0, seg, src)
def _pad(x, pw):
    flat = tuple(v for pair in reversed(pw) for v in pair)
    return torch.nn.functional.pad(x, flat)

kernel_name = 'gated_mix__sliding_local_dilated__compressed_kv_cla__prompt'

def setup_inputs():

    _w = (lambda a: (lambda t: t.to(torch.bfloat16) if t.is_floating_point() else t)(torch.as_tensor(a)))
    def _A_setup():
        B, S, D = 1, 2048, 576
        return {
            "x": _w((lambda *s: torch.randn(*s, dtype=torch.bfloat16) * 0.05)(B, S, D)),
            "wqkv": _w((lambda *s: torch.randn(*s, dtype=torch.bfloat16) * 1.6)(D, 3 * D)),
            "wo": _w((lambda *s: torch.randn(*s, dtype=torch.bfloat16) * 0.05)(D, D)),
        }
    _A_in = _A_setup()

    def _B_setup():
        B, H, Sq, Sk, D, M = 1, 32, 2048, 2048, 128, 576
        Dc = 4 * D
        return {
            "x": _w((lambda *s: torch.randn(*s, dtype=torch.bfloat16) * 0.05)(B, Sq, M)),
            "c_kv": _w((lambda *s: torch.randn(*s, dtype=torch.bfloat16) * 1.6)(B, Sk, Dc)),
            "w_q": _w((lambda *s: torch.randn(*s, dtype=torch.bfloat16) * 6.4)(M, H, D) * (M ** -0.5)),
            "w_uk": _w((lambda *s: torch.randn(*s, dtype=torch.bfloat16) * 6.4)(Dc, H, D) * (Dc ** -0.5)),
            "w_uv": _w((lambda *s: torch.randn(*s, dtype=torch.bfloat16) * 1.6)(Dc, H, D) * (Dc ** -0.5)),
            "w_o": _w((lambda *s: torch.randn(*s, dtype=torch.bfloat16) * 1.6)(H, D, M) * ((H * D) ** -0.5)),
        }
    _B_in = _B_setup()

    return {
        "A_x": _A_in["x"],
        "A_wqkv": _A_in["wqkv"],
        "A_wo": _A_in["wo"],
        "B_x": _B_in["x"],
        "B_c_kv": _B_in["c_kv"],
        "B_w_q": _B_in["w_q"],
        "B_w_uk": _B_in["w_uk"],
        "B_w_uv": _B_in["w_uv"],
        "B_w_o": _B_in["w_o"],
        "gate_w": _w((lambda *s: torch.randn(*s, dtype=torch.bfloat16) * 0.05)(576) * 16.0),
    }

def reference(A_x, A_wqkv, A_wo, B_x, B_c_kv, B_w_q, B_w_uk, B_w_uv, B_w_o, gate_w):
    def _A_ref(x, wqkv, wo):
        B, S, D = x.shape
        H = 32; Dh = D // H
        W, dil = 8, 2
        qkv = (lambda x, *d: x.permute(*d))((x @ wqkv).reshape(B, S, 3, H, Dh), 2, 0, 3, 1, 4)
        q, k, v = qkv[0], qkv[1], qkv[2]
        scale = Dh ** -0.5
        pos = torch.arange(S)
        off = torch.arange(W) * dil
        idx = pos[:, None] - off[None, :]
        mask = idx >= 0
        idx_c = torch.where(mask, idx, 0).reshape(-1)
        kg = k[:, :, idx_c, :].reshape(B, H, S, W, Dh)
        vg = v[:, :, idx_c, :].reshape(B, H, S, W, Dh)
        logits = torch.einsum("bhsd,bhswd->bhsw", q, kg) * scale
        logits = torch.where(mask[None, None, :, :], logits, -1e9)
        attn = _softmax(logits, axis=-1)
        o = torch.einsum("bhsw,bhswd->bhsd", attn, vg)
        return (lambda x, *d: x.permute(*d))(o, 0, 2, 1, 3).reshape(B, S, D) @ wo

    def _B_ref(x, c_kv, w_q, w_uk, w_uv, w_o):
        B, Sq, M = x.shape[0], x.shape[1], x.shape[2]
        Sk = c_kv.shape[1]
        H, D = w_q.shape[1], w_q.shape[2]
        q = torch.einsum("bqm,mhd->bhqd", x, w_q)
        k = torch.einsum("bkc,chd->bhkd", c_kv, w_uk)
        v = torch.einsum("bkc,chd->bhkd", c_kv, w_uv)
        scores = torch.einsum("bhqd,bhkd->bhqk", q, k) * (D ** -0.5)
        off = Sk - Sq
        qi = torch.arange(Sq)[:, None]
        kj = torch.arange(Sk)[None, :]
        cmask = kj <= (qi + off)
        scores = torch.where(cmask[None, None], scores, -1e9)
        p = _softmax(scores, axis=-1)
        ctx = torch.einsum("bhqk,bhkd->bhqd", p, v)
        return torch.einsum("bhqd,hdm->bqm", ctx, w_o)

    x = A_x
    g = _sigmoid((x * gate_w).sum(-1, keepdims=True))
    a = _A_ref(x, A_wqkv, A_wo)
    b = _B_ref(x, B_c_kv, B_w_q, B_w_uk, B_w_uv, B_w_o)
    return g * a + (1 - g) * b
```

```cpp
#include <cuda_runtime.h>
#include <cuda_bf16.h>
#include <cuda.h>
#include <stdint.h>

typedef __nv_bfloat16 bf16;

constexpr int S_LEN = 2048, DM = 576, DC = 512, HDIM = 4096, NQKVA = 1728, KCAT = 4672;
constexpr int NCLUSTER = 66;

__device__ __align__(1024) bf16 g_K[S_LEN * HDIM];
__device__ __align__(1024) bf16 g_V[S_LEN * HDIM];
__device__ __align__(1024) bf16 g_QKVA[S_LEN * NQKVA];
__device__ __align__(1024) bf16 g_ctx[S_LEN * KCAT];
__device__ float g_gate[S_LEN];
__device__ __align__(1024) float4 g_part[32 * 4 * 4 * 9 * 256];
__device__ unsigned int g_cnt[32];

__device__ __forceinline__ uint32_t smem_u32(const void* p) { return (uint32_t)__cvta_generic_to_shared(p); }
__device__ __forceinline__ void mbar_init(uint32_t a, uint32_t c) {
  asm volatile("mbarrier.init.shared::cta.b64 [%0], %1;" ::"r"(a), "r"(c));
}
__device__ __forceinline__ void mbar_expect(uint32_t a, uint32_t b) {
  asm volatile("mbarrier.arrive.expect_tx.shared::cta.b64 _, [%0], %1;" ::"r"(a), "r"(b) : "memory");
}
#define SPIN_LIMIT "4194304"
__device__ __forceinline__ void mbar_wait(uint32_t a, uint32_t parity) {
  asm volatile(
      "{\n.reg .pred p;\n.reg .u32 n;\n"
      "mbarrier.try_wait.parity.shared::cta.b64 p, [%0], %1;\n"
      "@p bra DONE;\n"
      "mov.u32 n, 0;\n"
      "LOOP:\n"
      "mbarrier.try_wait.parity.shared::cta.b64 p, [%0], %1;\n"
      "@p bra DONE;\n"
      "add.u32 n, n, 1;\n"
      "setp.lt.u32 p, n, " SPIN_LIMIT ";\n"
      "@p bra LOOP;\n"
      "DONE:\n}" ::"r"(a), "r"(parity) : "memory");
}
__device__ __forceinline__ void mbar_arrive(uint32_t a) {
  asm volatile("mbarrier.arrive.shared::cta.b64 _, [%0];" ::"r"(a) : "memory");
}
__device__ __forceinline__ void mbar_arrive_cluster(uint32_t a, uint32_t cta) {
  asm volatile("{\n.reg .b32 r;\nmapa.shared::cluster.u32 r, %0, %1;\nmbarrier.arrive.shared::cluster.b64 _, [r];\n}" ::"r"(a),
               "r"(cta) : "memory");
}
__device__ __forceinline__ void tma2d(uint32_t dst, const CUtensorMap* m, uint32_t bar, int c0, int c1) {
  asm volatile("cp.async.bulk.tensor.2d.shared::cluster.global.mbarrier::complete_tx::bytes [%0], [%1, {%3, %4}], [%2];" ::"r"(dst),
               "l"(m), "r"(bar), "r"(c0), "r"(c1) : "memory");
}
__device__ __forceinline__ void tma2d_mc(uint32_t dst, const CUtensorMap* m, uint32_t bar, int c0, int c1, uint16_t mask) {
  asm volatile(
      "cp.async.bulk.tensor.2d.shared::cluster.global.mbarrier::complete_tx::bytes.multicast::cluster [%0], [%1, {%3, %4}], [%2], %5;" ::"r"(dst),
      "l"(m), "r"(bar), "r"(c0), "r"(c1), "h"(mask) : "memory");
}
__device__ __forceinline__ void tma3d_mc(uint32_t dst, const CUtensorMap* m, uint32_t bar, int c0, int c1, int c2, uint16_t mask) {
  asm volatile(
      "cp.async.bulk.tensor.3d.shared::cluster.global.mbarrier::complete_tx::bytes.multicast::cluster [%0], [%1, {%3, %4, %5}], [%2], %6;" ::"r"(dst),
      "l"(m), "r"(bar), "r"(c0), "r"(c1), "r"(c2), "h"(mask) : "memory");
}
__device__ __forceinline__ void prefetch_tmap(const CUtensorMap* m) {
  asm volatile("prefetch.tensormap [%0];" ::"l"(m) : "memory");
}
__device__ __forceinline__ void cluster_sync() {
  asm volatile("barrier.cluster.arrive.aligned;\nbarrier.cluster.wait.aligned;" ::: "memory");
}
__device__ __forceinline__ uint32_t cluster_rank() {
  uint32_t r;
  asm volatile("mov.u32 %0, %%cluster_ctarank;" : "=r"(r));
  return r;
}
__device__ __forceinline__ void wg_fence() { asm volatile("wgmma.fence.sync.aligned;" ::: "memory"); }
__device__ __forceinline__ void wg_commit() { asm volatile("wgmma.commit_group.sync.aligned;" ::: "memory"); }
template <int N>
__device__ __forceinline__ void wg_wait() { asm volatile("wgmma.wait_group.sync.aligned %0;" ::"n"(N) : "memory"); }
template <int N>
__device__ __forceinline__ void reg_alloc() { asm volatile("setmaxnreg.inc.sync.aligned.u32 %0;" ::"n"(N)); }
template <int N>
__device__ __forceinline__ void reg_dealloc() { asm volatile("setmaxnreg.dec.sync.aligned.u32 %0;" ::"n"(N)); }
__device__ __forceinline__ void bar_sync(int id, int n) { asm volatile("bar.sync %0, %1;" ::"r"(id), "r"(n) : "memory"); }
__device__ __forceinline__ void bar_arrive(int id, int n) { asm volatile("bar.arrive %0, %1;" ::"r"(id), "r"(n) : "memory"); }
template <int NT>
__device__ __forceinline__ void fence_regs(float (&d)[NT]) {
#pragma unroll
  for (int i = 0; i < NT; i++) asm volatile("" : "+f"(d[i])::"memory");
}
template <int NT>
__device__ __forceinline__ void fence_regs(uint32_t (&d)[NT]) {
#pragma unroll
  for (int i = 0; i < NT; i++) asm volatile("" : "+r"(d[i])::"memory");
}
__device__ __forceinline__ uint64_t make_desc(uint32_t saddr, uint32_t lbo, uint32_t sbo, uint32_t layout) {
  return (uint64_t)((saddr & 0x3FFFF) >> 4) | ((uint64_t)(lbo >> 4) << 16) | ((uint64_t)(sbo >> 4) << 32) | ((uint64_t)layout << 62);
}
__device__ __forceinline__ uint32_t pack_bf16(float lo, float hi) {
  uint32_t r;
  asm("cvt.rn.bf16x2.f32 %0, %1, %2;" : "=r"(r) : "f"(hi), "f"(lo));
  return r;
}
__device__ __forceinline__ float ex2(float x) {
  float r;
  asm("ex2.approx.ftz.f32 %0, %1;" : "=f"(r) : "f"(x));
  return r;
}
__device__ __forceinline__ void st_v4(void* p, uint32_t a, uint32_t b, uint32_t c, uint32_t d) {
  asm volatile("st.global.v4.b32 [%0], {%1, %2, %3, %4};" ::"l"(p), "r"(a), "r"(b), "r"(c), "r"(d) : "memory");
}
__device__ __forceinline__ float bf_lo(uint32_t v) { return __uint_as_float(v << 16); }
__device__ __forceinline__ float bf_hi(uint32_t v) { return __uint_as_float(v & 0xFFFF0000u); }

__device__ __forceinline__ void quad_transpose(uint32_t& a0, uint32_t& a1, uint32_t& a2, uint32_t& a3, int q) {
  const bool o1 = q & 1, o2 = q & 2;
  uint32_t t0 = o1 ? a0 : a1, t1 = o1 ? a2 : a3;
  t0 = __shfl_xor_sync(0xffffffffu, t0, 1);
  t1 = __shfl_xor_sync(0xffffffffu, t1, 1);
  if (o1) { a0 = t0; a2 = t1; } else { a1 = t0; a3 = t1; }
  t0 = o2 ? a0 : a2;
  t1 = o2 ? a1 : a3;
  t0 = __shfl_xor_sync(0xffffffffu, t0, 2);
  t1 = __shfl_xor_sync(0xffffffffu, t1, 2);
  if (o2) { a0 = t0; a1 = t1; } else { a2 = t0; a3 = t1; }
}

template<int TB, int OFF, int NT>
__device__ __forceinline__ void wgmma_ss_n256(float (&d)[NT], uint64_t da, uint64_t db, int scale_d) {
  asm volatile("{\n.reg .pred p;\nsetp.ne.b32 p, %130, 0;\n"
    "wgmma.mma_async.sync.aligned.m64n256k16.f32.bf16.bf16 {%0, %1, %2, %3, %4, %5, %6, %7, %8, %9, %10, %11, %12, %13, %14, %15, %16, %17, %18, %19, %20, %21, %22, %23, %24, %25, %26, %27, %28, %29, %30, %31, %32, %33, %34, %35, %36, %37, %38, %39, %40, %41, %42, %43, %44, %45, %46, %47, %48, %49, %50, %51, %52, %53, %54, %55, %56, %57, %58, %59, %60, %61, %62, %63, %64, %65, %66, %67, %68, %69, %70, %71, %72, %73, %74, %75, %76, %77, %78, %79, %80, %81, %82, %83, %84, %85, %86, %87, %88, %89, %90, %91, %92, %93, %94, %95, %96, %97, %98, %99, %100, %101, %102, %103, %104, %105, %106, %107, %108, %109, %110, %111, %112, %113, %114, %115, %116, %117, %118, %119, %120, %121, %122, %123, %124, %125, %126, %127}, %128, %129, p, 1, 1, 0, %131;\n}\n"
    : "+f"(d[OFF+0]), "+f"(d[OFF+1]), "+f"(d[OFF+2]), "+f"(d[OFF+3]), "+f"(d[OFF+4]), "+f"(d[OFF+5]), "+f"(d[OFF+6]), "+f"(d[OFF+7]), "+f"(d[OFF+8]), "+f"(d[OFF+9]), "+f"(d[OFF+10]), "+f"(d[OFF+11]), "+f"(d[OFF+12]), "+f"(d[OFF+13]), "+f"(d[OFF+14]), "+f"(d[OFF+15]), "+f"(d[OFF+16]), "+f"(d[OFF+17]), "+f"(d[OFF+18]), "+f"(d[OFF+19]), "+f"(d[OFF+20]), "+f"(d[OFF+21]), "+f"(d[OFF+22]), "+f"(d[OFF+23]), "+f"(d[OFF+24]), "+f"(d[OFF+25]), "+f"(d[OFF+26]), "+f"(d[OFF+27]), "+f"(d[OFF+28]), "+f"(d[OFF+29]), "+f"(d[OFF+30]), "+f"(d[OFF+31]), "+f"(d[OFF+32]), "+f"(d[OFF+33]), "+f"(d[OFF+34]), "+f"(d[OFF+35]), "+f"(d[OFF+36]), "+f"(d[OFF+37]), "+f"(d[OFF+38]), "+f"(d[OFF+39]), "+f"(d[OFF+40]), "+f"(d[OFF+41]), "+f"(d[OFF+42]), "+f"(d[OFF+43]), "+f"(d[OFF+44]), "+f"(d[OFF+45]), "+f"(d[OFF+46]), "+f"(d[OFF+47]), "+f"(d[OFF+48]), "+f"(d[OFF+49]), "+f"(d[OFF+50]), "+f"(d[OFF+51]), "+f"(d[OFF+52]), "+f"(d[OFF+53]), "+f"(d[OFF+54]), "+f"(d[OFF+55]), "+f"(d[OFF+56]), "+f"(d[OFF+57]), "+f"(d[OFF+58]), "+f"(d[OFF+59]), "+f"(d[OFF+60]), "+f"(d[OFF+61]), "+f"(d[OFF+62]), "+f"(d[OFF+63]), "+f"(d[OFF+64]), "+f"(d[OFF+65]), "+f"(d[OFF+66]), "+f"(d[OFF+67]), "+f"(d[OFF+68]), "+f"(d[OFF+69]), "+f"(d[OFF+70]), "+f"(d[OFF+71]), "+f"(d[OFF+72]), "+f"(d[OFF+73]), "+f"(d[OFF+74]), "+f"(d[OFF+75]), "+f"(d[OFF+76]), "+f"(d[OFF+77]), "+f"(d[OFF+78]), "+f"(d[OFF+79]), "+f"(d[OFF+80]), "+f"(d[OFF+81]), "+f"(d[OFF+82]), "+f"(d[OFF+83]), "+f"(d[OFF+84]), "+f"(d[OFF+85]), "+f"(d[OFF+86]), "+f"(d[OFF+87]), "+f"(d[OFF+88]), "+f"(d[OFF+89]), "+f"(d[OFF+90]), "+f"(d[OFF+91]), "+f"(d[OFF+92]), "+f"(d[OFF+93]), "+f"(d[OFF+94]), "+f"(d[OFF+95]), "+f"(d[OFF+96]), "+f"(d[OFF+97]), "+f"(d[OFF+98]), "+f"(d[OFF+99]), "+f"(d[OFF+100]), "+f"(d[OFF+101]), "+f"(d[OFF+102]), "+f"(d[OFF+103]), "+f"(d[OFF+104]), "+f"(d[OFF+105]), "+f"(d[OFF+106]), "+f"(d[OFF+107]), "+f"(d[OFF+108]), "+f"(d[OFF+109]), "+f"(d[OFF+110]), "+f"(d[OFF+111]), "+f"(d[OFF+112]), "+f"(d[OFF+113]), "+f"(d[OFF+114]), "+f"(d[OFF+115]), "+f"(d[OFF+116]), "+f"(d[OFF+117]), "+f"(d[OFF+118]), "+f"(d[OFF+119]), "+f"(d[OFF+120]), "+f"(d[OFF+121]), "+f"(d[OFF+122]), "+f"(d[OFF+123]), "+f"(d[OFF+124]), "+f"(d[OFF+125]), "+f"(d[OFF+126]), "+f"(d[OFF+127])
    : "l"(da), "l"(db), "r"(scale_d), "n"(TB));
}
template<int TB, int OFF, int NT>
__device__ __forceinline__ void wgmma_ss_n192(float (&d)[NT], uint64_t da, uint64_t db, int scale_d) {
  asm volatile("{\n.reg .pred p;\nsetp.ne.b32 p, %98, 0;\n"
    "wgmma.mma_async.sync.aligned.m64n192k16.f32.bf16.bf16 {%0, %1, %2, %3, %4, %5, %6, %7, %8, %9, %10, %11, %12, %13, %14, %15, %16, %17, %18, %19, %20, %21, %22, %23, %24, %25, %26, %27, %28, %29, %30, %31, %32, %33, %34, %35, %36, %37, %38, %39, %40, %41, %42, %43, %44, %45, %46, %47, %48, %49, %50, %51, %52, %53, %54, %55, %56, %57, %58, %59, %60, %61, %62, %63, %64, %65, %66, %67, %68, %69, %70, %71, %72, %73, %74, %75, %76, %77, %78, %79, %80, %81, %82, %83, %84, %85, %86, %87, %88, %89, %90, %91, %92, %93, %94, %95}, %96, %97, p, 1, 1, 0, %99;\n}\n"
    : "+f"(d[OFF+0]), "+f"(d[OFF+1]), "+f"(d[OFF+2]), "+f"(d[OFF+3]), "+f"(d[OFF+4]), "+f"(d[OFF+5]), "+f"(d[OFF+6]), "+f"(d[OFF+7]), "+f"(d[OFF+8]), "+f"(d[OFF+9]), "+f"(d[OFF+10]), "+f"(d[OFF+11]), "+f"(d[OFF+12]), "+f"(d[OFF+13]), "+f"(d[OFF+14]), "+f"(d[OFF+15]), "+f"(d[OFF+16]), "+f"(d[OFF+17]), "+f"(d[OFF+18]), "+f"(d[OFF+19]), "+f"(d[OFF+20]), "+f"(d[OFF+21]), "+f"(d[OFF+22]), "+f"(d[OFF+23]), "+f"(d[OFF+24]), "+f"(d[OFF+25]), "+f"(d[OFF+26]), "+f"(d[OFF+27]), "+f"(d[OFF+28]), "+f"(d[OFF+29]), "+f"(d[OFF+30]), "+f"(d[OFF+31]), "+f"(d[OFF+32]), "+f"(d[OFF+33]), "+f"(d[OFF+34]), "+f"(d[OFF+35]), "+f"(d[OFF+36]), "+f"(d[OFF+37]), "+f"(d[OFF+38]), "+f"(d[OFF+39]), "+f"(d[OFF+40]), "+f"(d[OFF+41]), "+f"(d[OFF+42]), "+f"(d[OFF+43]), "+f"(d[OFF+44]), "+f"(d[OFF+45]), "+f"(d[OFF+46]), "+f"(d[OFF+47]), "+f"(d[OFF+48]), "+f"(d[OFF+49]), "+f"(d[OFF+50]), "+f"(d[OFF+51]), "+f"(d[OFF+52]), "+f"(d[OFF+53]), "+f"(d[OFF+54]), "+f"(d[OFF+55]), "+f"(d[OFF+56]), "+f"(d[OFF+57]), "+f"(d[OFF+58]), "+f"(d[OFF+59]), "+f"(d[OFF+60]), "+f"(d[OFF+61]), "+f"(d[OFF+62]), "+f"(d[OFF+63]), "+f"(d[OFF+64]), "+f"(d[OFF+65]), "+f"(d[OFF+66]), "+f"(d[OFF+67]), "+f"(d[OFF+68]), "+f"(d[OFF+69]), "+f"(d[OFF+70]), "+f"(d[OFF+71]), "+f"(d[OFF+72]), "+f"(d[OFF+73]), "+f"(d[OFF+74]), "+f"(d[OFF+75]), "+f"(d[OFF+76]), "+f"(d[OFF+77]), "+f"(d[OFF+78]), "+f"(d[OFF+79]), "+f"(d[OFF+80]), "+f"(d[OFF+81]), "+f"(d[OFF+82]), "+f"(d[OFF+83]), "+f"(d[OFF+84]), "+f"(d[OFF+85]), "+f"(d[OFF+86]), "+f"(d[OFF+87]), "+f"(d[OFF+88]), "+f"(d[OFF+89]), "+f"(d[OFF+90]), "+f"(d[OFF+91]), "+f"(d[OFF+92]), "+f"(d[OFF+93]), "+f"(d[OFF+94]), "+f"(d[OFF+95])
    : "l"(da), "l"(db), "r"(scale_d), "n"(TB));
}
template<int TB, int OFF, int NT>
__device__ __forceinline__ void wgmma_ss_n128(float (&d)[NT], uint64_t da, uint64_t db, int scale_d) {
  asm volatile("{\n.reg .pred p;\nsetp.ne.b32 p, %66, 0;\n"
    "wgmma.mma_async.sync.aligned.m64n128k16.f32.bf16.bf16 {%0, %1, %2, %3, %4, %5, %6, %7, %8, %9, %10, %11, %12, %13, %14, %15, %16, %17, %18, %19, %20, %21, %22, %23, %24, %25, %26, %27, %28, %29, %30, %31, %32, %33, %34, %35, %36, %37, %38, %39, %40, %41, %42, %43, %44, %45, %46, %47, %48, %49, %50, %51, %52, %53, %54, %55, %56, %57, %58, %59, %60, %61, %62, %63}, %64, %65, p, 1, 1, 0, %67;\n}\n"
    : "+f"(d[OFF+0]), "+f"(d[OFF+1]), "+f"(d[OFF+2]), "+f"(d[OFF+3]), "+f"(d[OFF+4]), "+f"(d[OFF+5]), "+f"(d[OFF+6]), "+f"(d[OFF+7]), "+f"(d[OFF+8]), "+f"(d[OFF+9]), "+f"(d[OFF+10]), "+f"(d[OFF+11]), "+f"(d[OFF+12]), "+f"(d[OFF+13]), "+f"(d[OFF+14]), "+f"(d[OFF+15]), "+f"(d[OFF+16]), "+f"(d[OFF+17]), "+f"(d[OFF+18]), "+f"(d[OFF+19]), "+f"(d[OFF+20]), "+f"(d[OFF+21]), "+f"(d[OFF+22]), "+f"(d[OFF+23]), "+f"(d[OFF+24]), "+f"(d[OFF+25]), "+f"(d[OFF+26]), "+f"(d[OFF+27]), "+f"(d[OFF+28]), "+f"(d[OFF+29]), "+f"(d[OFF+30]), "+f"(d[OFF+31]), "+f"(d[OFF+32]), "+f"(d[OFF+33]), "+f"(d[OFF+34]), "+f"(d[OFF+35]), "+f"(d[OFF+36]), "+f"(d[OFF+37]), "+f"(d[OFF+38]), "+f"(d[OFF+39]), "+f"(d[OFF+40]), "+f"(d[OFF+41]), "+f"(d[OFF+42]), "+f"(d[OFF+43]), "+f"(d[OFF+44]), "+f"(d[OFF+45]), "+f"(d[OFF+46]), "+f"(d[OFF+47]), "+f"(d[OFF+48]), "+f"(d[OFF+49]), "+f"(d[OFF+50]), "+f"(d[OFF+51]), "+f"(d[OFF+52]), "+f"(d[OFF+53]), "+f"(d[OFF+54]), "+f"(d[OFF+55]), "+f"(d[OFF+56]), "+f"(d[OFF+57]), "+f"(d[OFF+58]), "+f"(d[OFF+59]), "+f"(d[OFF+60]), "+f"(d[OFF+61]), "+f"(d[OFF+62]), "+f"(d[OFF+63])
    : "l"(da), "l"(db), "r"(scale_d), "n"(TB));
}
template<int TB, int OFF, int NT>
__device__ __forceinline__ void wgmma_ss_n32(float (&d)[NT], uint64_t da, uint64_t db, int scale_d) {
  asm volatile("{\n.reg .pred p;\nsetp.ne.b32 p, %18, 0;\n"
    "wgmma.mma_async.sync.aligned.m64n32k16.f32.bf16.bf16 {%0, %1, %2, %3, %4, %5, %6, %7, %8, %9, %10, %11, %12, %13, %14, %15}, %16, %17, p, 1, 1, 0, %19;\n}\n"
    : "+f"(d[OFF+0]), "+f"(d[OFF+1]), "+f"(d[OFF+2]), "+f"(d[OFF+3]), "+f"(d[OFF+4]), "+f"(d[OFF+5]), "+f"(d[OFF+6]), "+f"(d[OFF+7]), "+f"(d[OFF+8]), "+f"(d[OFF+9]), "+f"(d[OFF+10]), "+f"(d[OFF+11]), "+f"(d[OFF+12]), "+f"(d[OFF+13]), "+f"(d[OFF+14]), "+f"(d[OFF+15])
    : "l"(da), "l"(db), "r"(scale_d), "n"(TB));
}
template<int TB, int OFF, int NT>
__device__ __forceinline__ void wgmma_rs_n128(float (&d)[NT], uint32_t a0, uint32_t a1, uint32_t a2, uint32_t a3, uint64_t db, int scale_d) {
  asm volatile("{\n.reg .pred p;\nsetp.ne.b32 p, %69, 0;\n"
    "wgmma.mma_async.sync.aligned.m64n128k16.f32.bf16.bf16 {%0, %1, %2, %3, %4, %5, %6, %7, %8, %9, %10, %11, %12, %13, %14, %15, %16, %17, %18, %19, %20, %21, %22, %23, %24, %25, %26, %27, %28, %29, %30, %31, %32, %33, %34, %35, %36, %37, %38, %39, %40, %41, %42, %43, %44, %45, %46, %47, %48, %49, %50, %51, %52, %53, %54, %55, %56, %57, %58, %59, %60, %61, %62, %63}, {%64, %65, %66, %67}, %68, p, 1, 1, %70;\n}\n"
    : "+f"(d[OFF+0]), "+f"(d[OFF+1]), "+f"(d[OFF+2]), "+f"(d[OFF+3]), "+f"(d[OFF+4]), "+f"(d[OFF+5]), "+f"(d[OFF+6]), "+f"(d[OFF+7]), "+f"(d[OFF+8]), "+f"(d[OFF+9]), "+f"(d[OFF+10]), "+f"(d[OFF+11]), "+f"(d[OFF+12]), "+f"(d[OFF+13]), "+f"(d[OFF+14]), "+f"(d[OFF+15]), "+f"(d[OFF+16]), "+f"(d[OFF+17]), "+f"(d[OFF+18]), "+f"(d[OFF+19]), "+f"(d[OFF+20]), "+f"(d[OFF+21]), "+f"(d[OFF+22]), "+f"(d[OFF+23]), "+f"(d[OFF+24]), "+f"(d[OFF+25]), "+f"(d[OFF+26]), "+f"(d[OFF+27]), "+f"(d[OFF+28]), "+f"(d[OFF+29]), "+f"(d[OFF+30]), "+f"(d[OFF+31]), "+f"(d[OFF+32]), "+f"(d[OFF+33]), "+f"(d[OFF+34]), "+f"(d[OFF+35]), "+f"(d[OFF+36]), "+f"(d[OFF+37]), "+f"(d[OFF+38]), "+f"(d[OFF+39]), "+f"(d[OFF+40]), "+f"(d[OFF+41]), "+f"(d[OFF+42]), "+f"(d[OFF+43]), "+f"(d[OFF+44]), "+f"(d[OFF+45]), "+f"(d[OFF+46]), "+f"(d[OFF+47]), "+f"(d[OFF+48]), "+f"(d[OFF+49]), "+f"(d[OFF+50]), "+f"(d[OFF+51]), "+f"(d[OFF+52]), "+f"(d[OFF+53]), "+f"(d[OFF+54]), "+f"(d[OFF+55]), "+f"(d[OFF+56]), "+f"(d[OFF+57]), "+f"(d[OFF+58]), "+f"(d[OFF+59]), "+f"(d[OFF+60]), "+f"(d[OFF+61]), "+f"(d[OFF+62]), "+f"(d[OFF+63])
    : "r"(a0), "r"(a1), "r"(a2), "r"(a3), "l"(db), "r"(scale_d), "n"(TB));
}
template<int TB, int OFF, int NT>
__device__ __forceinline__ void wgmma_rs_n64(float (&d)[NT], uint32_t a0, uint32_t a1, uint32_t a2, uint32_t a3, uint64_t db, int scale_d) {
  asm volatile("{\n.reg .pred p;\nsetp.ne.b32 p, %37, 0;\n"
    "wgmma.mma_async.sync.aligned.m64n64k16.f32.bf16.bf16 {%0, %1, %2, %3, %4, %5, %6, %7, %8, %9, %10, %11, %12, %13, %14, %15, %16, %17, %18, %19, %20, %21, %22, %23, %24, %25, %26, %27, %28, %29, %30, %31}, {%32, %33, %34, %35}, %36, p, 1, 1, %38;\n}\n"
    : "+f"(d[OFF+0]), "+f"(d[OFF+1]), "+f"(d[OFF+2]), "+f"(d[OFF+3]), "+f"(d[OFF+4]), "+f"(d[OFF+5]), "+f"(d[OFF+6]), "+f"(d[OFF+7]), "+f"(d[OFF+8]), "+f"(d[OFF+9]), "+f"(d[OFF+10]), "+f"(d[OFF+11]), "+f"(d[OFF+12]), "+f"(d[OFF+13]), "+f"(d[OFF+14]), "+f"(d[OFF+15]), "+f"(d[OFF+16]), "+f"(d[OFF+17]), "+f"(d[OFF+18]), "+f"(d[OFF+19]), "+f"(d[OFF+20]), "+f"(d[OFF+21]), "+f"(d[OFF+22]), "+f"(d[OFF+23]), "+f"(d[OFF+24]), "+f"(d[OFF+25]), "+f"(d[OFF+26]), "+f"(d[OFF+27]), "+f"(d[OFF+28]), "+f"(d[OFF+29]), "+f"(d[OFF+30]), "+f"(d[OFF+31])
    : "r"(a0), "r"(a1), "r"(a2), "r"(a3), "l"(db), "r"(scale_d), "n"(TB));
}

constexpr int K1_BST = 5;
constexpr int K1_MAXJOBS = 6;
constexpr int K1_SMEM = 9 * 16384 + K1_BST * 16384 + 1024 + 256;
struct alignas(64) K1Params {
  CUtensorMap tmA[2];
  CUtensorMap tmW[3];
  uint16_t jobs[NCLUSTER][K1_MAXJOBS];
};

template <int NCH>
__device__ __forceinline__ void k1_tile(float (&acc)[128], uint32_t job, uint32_t sA, uint32_t sB, uint32_t bAf, uint32_t bAe, uint32_t bBf, uint32_t bBe,
                                        uint32_t& bs, uint32_t& bph, uint32_t& aph, int wg, int warp, int lane, uint32_t rank) {
  const int a_sel = (job >> 1) & 1, mpair = (job >> 2) & 7, w_sel = (job >> 5) & 3, chunk0 = (job >> 7) & 127;
  const bool newA = (job >> 14) & 1, lastA = (job >> 15) & 1;
  const int KC = a_sel ? 9 : 8;
  const bool sig = (lane == 0) && (warp < 2);
  uint32_t prev_bs = 0;
  for (int kc = 0; kc < KC; kc++) {
    if (newA) {
      mbar_wait(bAf + kc * 8, (aph >> kc) & 1);
      aph ^= (1u << kc);
    }
    const uint64_t da = make_desc(sA + kc * 16384 + wg * 8192, 16, 1024, 1);
#pragma unroll
    for (int half = 0; half < 2; half++) {
      mbar_wait(bBf + bs * 8, bph);
      const uint64_t db = make_desc(sB + bs * 16384, 2048, 1024, 1);
      wg_fence();
#pragma unroll
      for (int kk = 0; kk < 2; kk++) {
        const int sd = (kc | half | kk) ? 1 : 0;
        if constexpr (NCH == 4)
          wgmma_ss_n256<1, 0>(acc, da + (uint64_t)((half * 2 + kk) * 2), db + (uint64_t)(kk * (NCH * 2048 / 16)), sd);
        else
          wgmma_ss_n192<1, 0>(acc, da + (uint64_t)((half * 2 + kk) * 2), db + (uint64_t)(kk * (NCH * 2048 / 16)), sd);
      }
      wg_commit();
      if (kc | half) {
        wg_wait<1>();
        if (sig) mbar_arrive_cluster(bBe + prev_bs * 8, warp);
        if (half == 0 && lastA && lane == 0 && warp == 2) mbar_arrive(bAe + (kc - 1) * 8);
      }
      prev_bs = bs;
      if (++bs == K1_BST) { bs = 0; bph ^= 1; }
    }
  }
  wg_wait<0>();
  fence_regs(acc);
  if (sig) mbar_arrive_cluster(bBe + prev_bs * 8, warp);
  if (lastA && lane == 0 && warp == 2) mbar_arrive(bAe + (KC - 1) * 8);
  bf16* out = (w_sel == 0) ? g_K : (w_sel == 1) ? g_V : g_QKVA;
  const int ld = (w_sel == 2) ? NQKVA : HDIM;
  const int row = mpair * 256 + rank * 128 + wg * 64 + warp * 16 + (lane >> 2);
  bf16* p0 = out + (size_t)row * ld + chunk0 * 64 + (lane & 3) * 8;
  bf16* p1 = p0 + (size_t)8 * ld;
#pragma unroll
  for (int G = 0; G < NCH * 2; G++) {
    uint32_t a0 = pack_bf16(acc[G * 16 + 0], acc[G * 16 + 1]), a1 = pack_bf16(acc[G * 16 + 4], acc[G * 16 + 5]);
    uint32_t a2 = pack_bf16(acc[G * 16 + 8], acc[G * 16 + 9]), a3 = pack_bf16(acc[G * 16 + 12], acc[G * 16 + 13]);
    uint32_t b0 = pack_bf16(acc[G * 16 + 2], acc[G * 16 + 3]), b1 = pack_bf16(acc[G * 16 + 6], acc[G * 16 + 7]);
    uint32_t b2 = pack_bf16(acc[G * 16 + 10], acc[G * 16 + 11]), b3 = pack_bf16(acc[G * 16 + 14], acc[G * 16 + 15]);
    if constexpr (NCH == 3) {
      quad_transpose(a0, a1, a2, a3, lane & 3);
      quad_transpose(b0, b1, b2, b3, lane & 3);
    }
    st_v4(p0 + G * 32, a0, a1, a2, a3);
    st_v4(p1 + G * 32, b0, b1, b2, b3);
  }
}

__global__ void __cluster_dims__(2, 1, 1) __launch_bounds__(384, 1)
k1_proj(const __grid_constant__ K1Params p, const bf16* __restrict__ x, const bf16* __restrict__ gate_w) {
  extern __shared__ uint8_t smem_raw[];
  const uint32_t sbase = (smem_u32(smem_raw) + 1023) & ~1023u;
  const uint32_t sA = sbase, sB = sbase + 9 * 16384, sBar = sB + K1_BST * 16384;
  const uint32_t bAf = sBar, bAe = sBar + 72, bBf = sBar + 144, bBe = bBf + K1_BST * 8;
  const int tid = threadIdx.x, warp_g = tid >> 5, lane = tid & 31;
  const uint32_t rank = cluster_rank();
  const int cl = blockIdx.x >> 1;
  if (tid == 0) {
    for (int i = 0; i < 9; i++) { mbar_init(bAf + i * 8, 1); mbar_init(bAe + i * 8, 2); }
    for (int i = 0; i < K1_BST; i++) { mbar_init(bBf + i * 8, 1); mbar_init(bBe + i * 8, 4); }
    asm volatile("fence.mbarrier_init.release.cluster;" ::: "memory");
  }
  __syncthreads();
  cluster_sync();

  if (warp_g >= 8) {
    reg_dealloc<40>();
    if (warp_g == 8) {
      if (lane == 0) {
        uint32_t bs = 0, bph = 1, aph = 0x1FF;
        for (int ji = 0; ji < K1_MAXJOBS; ji++) {
          const uint32_t job = p.jobs[cl][ji];
          if (!(job & 1)) break;
          const int a_sel = (job >> 1) & 1, mpair = (job >> 2) & 7, w_sel = (job >> 5) & 3, chunk0 = (job >> 7) & 127;
          const bool newA = (job >> 14) & 1;
          const int KC = a_sel ? 9 : 8;
          const uint32_t halfbytes = (w_sel == 2) ? 3 * 2048 : 4 * 2048;
          for (int kc = 0; kc < KC; kc++) {
            if (newA) {
              mbar_wait(bAe + kc * 8, (aph >> kc) & 1);
              aph ^= (1u << kc);
              mbar_expect(bAf + kc * 8, 16384);
              tma2d(sA + kc * 16384, &p.tmA[a_sel], bAf + kc * 8, kc * 64, mpair * 256 + rank * 128);
            }
            for (int half = 0; half < 2; half++) {
              mbar_wait(bBe + bs * 8, bph);
              mbar_expect(bBf + bs * 8, 2 * halfbytes);
              tma3d_mc(sB + bs * 16384 + rank * halfbytes, &p.tmW[w_sel], bBf + bs * 8, 0, kc * 64 + half * 32 + rank * 16, chunk0, 3);
              if (++bs == K1_BST) { bs = 0; bph ^= 1; }
            }
          }
        }
      }
    } else {
      const int gw = blockIdx.x * 3 + (warp_g - 9);
      if (gw == 0) g_cnt[lane] = 0;
      const uint32_t* gw2 = reinterpret_cast<const uint32_t*>(gate_w);
      for (int row = gw; row < S_LEN; row += NCLUSTER * 2 * 3) {
        const uint32_t* xr = reinterpret_cast<const uint32_t*>(x + (size_t)row * DM);
        float s = 0.f;
#pragma unroll
        for (int i = 0; i < 9; i++) {
          const uint32_t a = __ldg(xr + lane + 32 * i), b = __ldg(gw2 + lane + 32 * i);
          s = fmaf(bf_lo(a), bf_lo(b), s);
          s = fmaf(bf_hi(a), bf_hi(b), s);
        }
#pragma unroll
        for (int o = 16; o; o >>= 1) s += __shfl_xor_sync(0xffffffffu, s, o);
        if (lane == 0) g_gate[row] = 1.f / (1.f + __expf(-s));
      }
    }
    __syncwarp();
    cluster_sync();
  } else {
    reg_alloc<232>();
    const int wg = warp_g >> 2, warp = warp_g & 3;
    uint32_t bs = 0, bph = 0, aph = 0;
    float acc[128];
    for (int ji = 0; ji < K1_MAXJOBS; ji++) {
      const uint32_t job = p.jobs[cl][ji];
      if (!(job & 1)) break;
      if (((job >> 5) & 3) == 2)
        k1_tile<3>(acc, job, sA, sB, bAf, bAe, bBf, bBe, bs, bph, aph, wg, warp, lane, rank);
      else
        k1_tile<4>(acc, job, sA, sB, bAf, bAe, bBf, bBe, bs, bph, aph, wg, warp, lane, rank);
    }
    cluster_sync();
  }
}

constexpr int K2_NST = 7;
constexpr int K2_MAXITEMS = 8;
constexpr int K2_SMEM = K2_NST * 32768 + 1024 + 256;
struct alignas(64) K2Params {
  CUtensorMap tmX, tmWq, tmK, tmV;
  uint8_t items[NCLUSTER][K2_MAXITEMS];
  uint8_t nitems[NCLUSTER];
};

struct Cursor {
  uint32_t s, ph;
  __device__ __forceinline__ void next() {
    if (++s == K2_NST) { s = 0; ph ^= 1; }
  }
};

__device__ __forceinline__ void local_attention(int gw, int nwarps, int lane) {
  const float scale_l2 = 0.23570226039551584f * 1.4426950408889634f;
  const bf16* lbase = g_QKVA + lane * 18;
#pragma unroll 1
  for (int row = gw; row < S_LEN; row += nwarps) {
    const bf16* base = lbase + (size_t)row * NQKVA;
    uint32_t qv[9];
#pragma unroll
    for (int i = 0; i < 9; i++) qv[i] = *reinterpret_cast<const uint32_t*>(base + 2 * i);
    float lg[8];
    float mx = -INFINITY;
#pragma unroll
    for (int w = 0; w < 8; w++) {
      const bf16* kb = lbase + (size_t)max(row - 2 * w, 0) * NQKVA + 576;
      float s = 0.f;
#pragma unroll
      for (int i = 0; i < 9; i++) {
        const uint32_t kv = *reinterpret_cast<const uint32_t*>(kb + 2 * i);
        s = fmaf(bf_lo(qv[i]), bf_lo(kv), s);
        s = fmaf(bf_hi(qv[i]), bf_hi(kv), s);
      }
      if (row - 2 * w < 0) s = -INFINITY;
      lg[w] = s;
      mx = fmaxf(mx, s);
    }
    float sum = 0.f;
#pragma unroll
    for (int w = 0; w < 8; w++) {
      lg[w] = ex2((lg[w] - mx) * scale_l2);
      sum += lg[w];
    }
    const float f = g_gate[row] / sum;
    float o[18];
#pragma unroll
    for (int i = 0; i < 18; i++) o[i] = 0.f;
#pragma unroll
    for (int w = 0; w < 8; w++) {
      const bf16* vb = lbase + (size_t)max(row - 2 * w, 0) * NQKVA + 1152;
#pragma unroll
      for (int i = 0; i < 9; i++) {
        const uint32_t vv = *reinterpret_cast<const uint32_t*>(vb + 2 * i);
        o[2 * i] = fmaf(lg[w], bf_lo(vv), o[2 * i]);
        o[2 * i + 1] = fmaf(lg[w], bf_hi(vv), o[2 * i + 1]);
      }
    }
    bf16* op = g_ctx + (size_t)row * KCAT + HDIM + lane * 18;
#pragma unroll
    for (int i = 0; i < 9; i++) *reinterpret_cast<uint32_t*>(op + 2 * i) = pack_bf16(o[2 * i] * f, o[2 * i + 1] * f);
  }
}

__global__ void __cluster_dims__(2, 1, 1) __launch_bounds__(384, 1) k2_attn(const __grid_constant__ K2Params p) {
  extern __shared__ uint8_t smem_raw[];
  const uint32_t sbase = (smem_u32(smem_raw) + 1023) & ~1023u;
  const uint32_t sBar = sbase + K2_NST * 32768;
  const uint32_t bF = sBar, bE = sBar + K2_NST * 8;
  const int tid = threadIdx.x, warp_g = tid >> 5, lane = tid & 31;
  const uint32_t rank = cluster_rank();
  const int cl = blockIdx.x >> 1;
  if (tid == 0) {
    for (int i = 0; i < K2_NST; i++) { mbar_init(bF + i * 8, 1); mbar_init(bE + i * 8, 4); }
    asm volatile("fence.mbarrier_init.release.cluster;" ::: "memory");
  }
  __syncthreads();
  cluster_sync();
  const int nitems = p.nitems[cl];

  if (warp_g >= 8) {
    reg_dealloc<56>();
    if (warp_g == 8) {
      if (lane == 0) {
        Cursor c{0, 1};
        for (int it = 0; it < nitems; it++) {
          const int item = p.items[cl][it];
          const int h = item >> 3, j = item & 7;
          const int blk = 2 * j + (int)(rank ^ (it & 1));
          const int col = h * 128 + rank * 64;
          for (int ks = 0; ks < 9; ks++) {
            mbar_wait(bE + c.s * 8, c.ph);
            mbar_expect(bF + c.s * 8, 32768);
            const uint32_t st = sbase + c.s * 32768;
            tma2d(st, &p.tmX, bF + c.s * 8, ks * 64, blk * 128);
            tma2d_mc(st + 16384 + rank * 8192, &p.tmWq, bF + c.s * 8, col, ks * 64, 3);
            c.next();
          }
          const int nb = 2 * j + 2;
          for (int n = nb - 1; n >= -1; n--) {
            if (n >= 0) {
              mbar_wait(bE + c.s * 8, c.ph);
              mbar_expect(bF + c.s * 8, 32768);
              tma2d_mc(sbase + c.s * 32768 + rank * 16384, &p.tmK, bF + c.s * 8, col, n * 128, 3);
              c.next();
            }
            if (n < nb - 1) {
              mbar_wait(bE + c.s * 8, c.ph);
              mbar_expect(bF + c.s * 8, 32768);
              tma2d_mc(sbase + c.s * 32768 + rank * 16384, &p.tmV, bF + c.s * 8, col, (n + 1) * 128, 3);
              c.next();
            }
          }
        }
      }
    } else {
      local_attention(blockIdx.x * 3 + (warp_g - 9), NCLUSTER * 2 * 3, lane);
    }
    __syncwarp();
    cluster_sync();
  } else {
    reg_alloc<224>();
    const int wg = warp_g >> 2, warp = warp_g & 3, q = lane & 3;
    const bool sig = (lane == 0) && (warp < 2);
    const int mybar = 1 + wg, otherbar = 2 - wg;
    const float cl2 = 0.08838834764831845f * 1.4426950408889634f;
    float S[64], O[64];
    uint32_t P[32], Q[32];
    float m0 = 0.f, m1 = 0.f, l0 = 0.f, l1 = 0.f;
    int prev_row = 0, prev_h = 0, prev_single = 0;
    Cursor c{0, 0};
    if (wg == 1) bar_arrive(1, 256);

#define RELEASE(cur) do { if (sig) mbar_arrive_cluster(bE + (cur).s * 8, warp); } while (0)
#define ISSUE_PV(cur, first)                                                                                   \
  do {                                                                                                         \
    const uint64_t dv = make_desc(sbase + (cur).s * 32768, 16384, 1024, 1);                                    \
    _Pragma("unroll") for (int t = 0; t < 8; t++)                                                              \
        wgmma_rs_n128<1, 0>(O, P[4 * t], P[4 * t + 1], P[4 * t + 2], P[4 * t + 3], dv + (uint64_t)(t * 128), (t > 0) ? 1 : !(first)); \
  } while (0)
#define ISSUE_QK(cur)                                                                                          \
  do {                                                                                                         \
    const uint64_t dk = make_desc(sbase + (cur).s * 32768, 16, 1024, 1);                                       \
    _Pragma("unroll") for (int t = 0; t < 8; t++)                                                              \
        wgmma_rs_n128<0, 0>(S, Q[4 * t], Q[4 * t + 1], Q[4 * t + 2], Q[4 * t + 3], dk + (uint64_t)((t >> 2) * 1024 + (t & 3) * 2), t > 0); \
  } while (0)
#define ISSUE_QP(cur, first)                                                                                   \
  do {                                                                                                         \
    const uint64_t dx = make_desc(sbase + (cur).s * 32768 + wg * 8192, 16, 1024, 1);                           \
    const uint64_t dw = make_desc(sbase + (cur).s * 32768 + 16384, 8192, 1024, 1);                             \
    _Pragma("unroll") for (int t = 0; t < 4; t++)                                                              \
        wgmma_ss_n128<1, 0>(S, dx + (uint64_t)(t * 2), dw + (uint64_t)(t * 128), (t > 0) ? 1 : !(first));      \
  } while (0)
#define EPILOGUE()                                                                                             \
  do {                                                                                                         \
    l0 += __shfl_xor_sync(0xffffffffu, l0, 1);                                                                 \
    l0 += __shfl_xor_sync(0xffffffffu, l0, 2);                                                                 \
    l1 += __shfl_xor_sync(0xffffffffu, l1, 1);                                                                 \
    l1 += __shfl_xor_sync(0xffffffffu, l1, 2);                                                                 \
    const float f0 = (1.f - g_gate[prev_row]) / l0, f1 = (1.f - g_gate[prev_row + 8]) / l1;                    \
    bf16* o0 = g_ctx + (size_t)prev_row * KCAT + prev_h * 128 + q * 8;                                         \
    bf16* o1 = o0 + (size_t)8 * KCAT;                                                                          \
    _Pragma("unroll") for (int G = 0; G < 4; G++) {                                                            \
      st_v4(o0 + G * 32, pack_bf16(O[G * 16 + 0] * f0, O[G * 16 + 1] * f0), pack_bf16(O[G * 16 + 4] * f0, O[G * 16 + 5] * f0), \
            pack_bf16(O[G * 16 + 8] * f0, O[G * 16 + 9] * f0), pack_bf16(O[G * 16 + 12] * f0, O[G * 16 + 13] * f0)); \
      st_v4(o1 + G * 32, pack_bf16(O[G * 16 + 2] * f1, O[G * 16 + 3] * f1), pack_bf16(O[G * 16 + 6] * f1, O[G * 16 + 7] * f1), \
            pack_bf16(O[G * 16 + 10] * f1, O[G * 16 + 11] * f1), pack_bf16(O[G * 16 + 14] * f1, O[G * 16 + 15] * f1)); \
    }                                                                                                          \
  } while (0)

    for (int it = 0; it < nitems; it++) {
      const int item = p.items[cl][it];
      const int h = item >> 3, j = item & 7;
      const int hi = (int)(rank ^ (it & 1));
      const int nblk = 2 * j + 1 + hi;
      {
        Cursor cv = c;
        if (it > 0) { mbar_wait(bF + cv.s * 8, cv.ph); c.next(); }
        Cursor c0 = c; c.next();
        Cursor c1 = c; c.next();
        Cursor c2 = c; c.next();
        mbar_wait(bF + c0.s * 8, c0.ph);
        mbar_wait(bF + c1.s * 8, c1.ph);
        mbar_wait(bF + c2.s * 8, c2.ph);
        bar_sync(mybar, 256);
        wg_fence();
        if (it > 0) ISSUE_PV(cv, prev_single);
        wg_commit();
        ISSUE_QP(c0, true);
        ISSUE_QP(c1, false);
        ISSUE_QP(c2, false);
        wg_commit();
        bar_arrive(otherbar, 256);
        wg_wait<1>();
        fence_regs(O);
        if (it > 0) {
          RELEASE(cv);
          EPILOGUE();
        }
        wg_wait<0>();
        RELEASE(c0); RELEASE(c1); RELEASE(c2);
      }
#pragma unroll 1
      for (int tt = 0; tt < 2; tt++) {
        Cursor c0 = c; c.next();
        Cursor c1 = c; c.next();
        Cursor c2 = c; c.next();
        mbar_wait(bF + c0.s * 8, c0.ph);
        mbar_wait(bF + c1.s * 8, c1.ph);
        mbar_wait(bF + c2.s * 8, c2.ph);
        bar_sync(mybar, 256);
        wg_fence();
        ISSUE_QP(c0, false);
        ISSUE_QP(c1, false);
        ISSUE_QP(c2, false);
        wg_commit();
        bar_arrive(otherbar, 256);
        wg_wait<0>();
        RELEASE(c0); RELEASE(c1); RELEASE(c2);
      }
      fence_regs(S);
#pragma unroll
      for (int G = 0; G < 4; G++) {
        uint32_t a0 = pack_bf16(S[G * 16 + 0], S[G * 16 + 1]), a1 = pack_bf16(S[G * 16 + 4], S[G * 16 + 5]);
        uint32_t a2 = pack_bf16(S[G * 16 + 8], S[G * 16 + 9]), a3 = pack_bf16(S[G * 16 + 12], S[G * 16 + 13]);
        uint32_t b0 = pack_bf16(S[G * 16 + 2], S[G * 16 + 3]), b1 = pack_bf16(S[G * 16 + 6], S[G * 16 + 7]);
        uint32_t b2 = pack_bf16(S[G * 16 + 10], S[G * 16 + 11]), b3 = pack_bf16(S[G * 16 + 14], S[G * 16 + 15]);
        quad_transpose(a0, a1, a2, a3, q);
        quad_transpose(b0, b1, b2, b3, q);
        Q[G * 8 + 0] = a0; Q[G * 8 + 1] = b0; Q[G * 8 + 2] = a1; Q[G * 8 + 3] = b1;
        Q[G * 8 + 4] = a2; Q[G * 8 + 5] = b2; Q[G * 8 + 6] = a3; Q[G * 8 + 7] = b3;
      }
      {
        Cursor cs0 = c, cs1 = c;
        if (!hi) { mbar_wait(bF + cs0.s * 8, cs0.ph); c.next(); }
        Cursor ck = c; c.next();
        mbar_wait(bF + ck.s * 8, ck.ph);
        if (!hi) { cs1 = c; mbar_wait(bF + cs1.s * 8, cs1.ph); c.next(); }
        bar_sync(mybar, 256);
        if (!hi) { RELEASE(cs0); RELEASE(cs1); }
        wg_fence();
        ISSUE_QK(ck);
        wg_commit();
        bar_arrive(otherbar, 256);
        wg_wait<0>();
        fence_regs(S);
        RELEASE(ck);
        const int r0 = wg * 64 + warp * 16 + (lane >> 2);
#pragma unroll
        for (int jj = 0; jj < 16; jj++) {
          const int cc = jj * 8 + 2 * q;
          if (cc > r0) S[jj * 4 + 0] = -INFINITY;
          if (cc + 1 > r0) S[jj * 4 + 1] = -INFINITY;
          if (cc > r0 + 8) S[jj * 4 + 2] = -INFINITY;
          if (cc + 1 > r0 + 8) S[jj * 4 + 3] = -INFINITY;
        }
        float mx0 = fmaxf(S[0], S[1]), mx1 = fmaxf(S[2], S[3]);
#pragma unroll
        for (int jj = 1; jj < 16; jj++) {
          mx0 = fmaxf(mx0, fmaxf(S[jj * 4 + 0], S[jj * 4 + 1]));
          mx1 = fmaxf(mx1, fmaxf(S[jj * 4 + 2], S[jj * 4 + 3]));
        }
        mx0 = fmaxf(mx0, __shfl_xor_sync(0xffffffffu, mx0, 1));
        mx1 = fmaxf(mx1, __shfl_xor_sync(0xffffffffu, mx1, 1));
        mx0 = fmaxf(mx0, __shfl_xor_sync(0xffffffffu, mx0, 2));
        mx1 = fmaxf(mx1, __shfl_xor_sync(0xffffffffu, mx1, 2));
        m0 = mx0; m1 = mx1;
        const float mc0 = m0 * cl2, mc1 = m1 * cl2;
        l0 = 0.f; l1 = 0.f;
#pragma unroll
        for (int jj = 0; jj < 16; jj++) {
          const float e0 = ex2(fmaf(S[jj * 4 + 0], cl2, -mc0)), e1 = ex2(fmaf(S[jj * 4 + 1], cl2, -mc0));
          const float e2 = ex2(fmaf(S[jj * 4 + 2], cl2, -mc1)), e3 = ex2(fmaf(S[jj * 4 + 3], cl2, -mc1));
          l0 += e0 + e1;
          l1 += e2 + e3;
          P[jj * 2 + 0] = pack_bf16(e0, e1);
          P[jj * 2 + 1] = pack_bf16(e2, e3);
        }
      }
#pragma unroll 1
      for (int n = 1; n < nblk; n++) {
        Cursor ck = c; c.next();
        Cursor cv = c; c.next();
        mbar_wait(bF + ck.s * 8, ck.ph);
        mbar_wait(bF + cv.s * 8, cv.ph);
        bar_sync(mybar, 256);
        wg_fence();
        ISSUE_QK(ck);
        wg_commit();
        ISSUE_PV(cv, n == 1);
        wg_commit();
        bar_arrive(otherbar, 256);
        wg_wait<1>();
        fence_regs(S);
        RELEASE(ck);
        float mx0 = fmaxf(S[0], S[1]), mx1 = fmaxf(S[2], S[3]);
#pragma unroll
        for (int jj = 1; jj < 16; jj++) {
          mx0 = fmaxf(mx0, fmaxf(S[jj * 4 + 0], S[jj * 4 + 1]));
          mx1 = fmaxf(mx1, fmaxf(S[jj * 4 + 2], S[jj * 4 + 3]));
        }
        mx0 = fmaxf(mx0, __shfl_xor_sync(0xffffffffu, mx0, 1));
        mx1 = fmaxf(mx1, __shfl_xor_sync(0xffffffffu, mx1, 1));
        mx0 = fmaxf(mx0, __shfl_xor_sync(0xffffffffu, mx0, 2));
        mx1 = fmaxf(mx1, __shfl_xor_sync(0xffffffffu, mx1, 2));
        mx0 = fmaxf(mx0, m0);
        mx1 = fmaxf(mx1, m1);
        const float sc0 = ex2((m0 - mx0) * cl2), sc1 = ex2((m1 - mx1) * cl2);
        m0 = mx0; m1 = mx1;
        const float mc0 = m0 * cl2, mc1 = m1 * cl2;
        float s0 = 0.f, s1 = 0.f;
#pragma unroll
        for (int jj = 0; jj < 16; jj++) {
          S[jj * 4 + 0] = ex2(fmaf(S[jj * 4 + 0], cl2, -mc0));
          S[jj * 4 + 1] = ex2(fmaf(S[jj * 4 + 1], cl2, -mc0));
          S[jj * 4 + 2] = ex2(fmaf(S[jj * 4 + 2], cl2, -mc1));
          S[jj * 4 + 3] = ex2(fmaf(S[jj * 4 + 3], cl2, -mc1));
          s0 += S[jj * 4 + 0] + S[jj * 4 + 1];
          s1 += S[jj * 4 + 2] + S[jj * 4 + 3];
        }
        l0 = fmaf(l0, sc0, s0);
        l1 = fmaf(l1, sc1, s1);
        wg_wait<0>();
        fence_regs(O);
        fence_regs(P);
        RELEASE(cv);
#pragma unroll
        for (int jj = 0; jj < 16; jj++) {
          O[jj * 4 + 0] *= sc0;
          O[jj * 4 + 1] *= sc0;
          O[jj * 4 + 2] *= sc1;
          O[jj * 4 + 3] *= sc1;
          P[jj * 2 + 0] = pack_bf16(S[jj * 4 + 0], S[jj * 4 + 1]);
          P[jj * 2 + 1] = pack_bf16(S[jj * 4 + 2], S[jj * 4 + 3]);
        }
      }
      prev_row = (2 * j + hi) * 128 + wg * 64 + warp * 16 + (lane >> 2);
      prev_h = h;
      prev_single = (nblk == 1);
    }
    if (nitems > 0) {
      Cursor cv = c;
      mbar_wait(bF + cv.s * 8, cv.ph);
      bar_sync(mybar, 256);
      wg_fence();
      ISSUE_PV(cv, prev_single);
      wg_commit();
      if (wg == 0) bar_arrive(otherbar, 256);
      wg_wait<0>();
      fence_regs(O);
      RELEASE(cv);
      EPILOGUE();
    }
    cluster_sync();
  }
}

constexpr int K3_NST = 4;
constexpr int K3_STAGE = 16384 + 32768 + 4096;
constexpr int K3_SMEM = K3_NST * K3_STAGE + 1024 + 256;
struct alignas(64) K3Params {
  CUtensorMap tmA, tmW[2], tmWt[2];
};

__global__ void __cluster_dims__(2, 1, 1) __launch_bounds__(384, 1) k3_out(const __grid_constant__ K3Params p, bf16* __restrict__ out) {
  extern __shared__ uint8_t smem_raw[];
  const uint32_t sbase = (smem_u32(smem_raw) + 1023) & ~1023u;
  const uint32_t sBar = sbase + K3_NST * K3_STAGE;
  const uint32_t bF = sBar, bE = sBar + K3_NST * 8;
  const int tid = threadIdx.x, warp_g = tid >> 5, lane = tid & 31;
  const uint32_t rank = cluster_rank();
  const int cl = blockIdx.x >> 1;
  const int mblk = (cl >> 3) * 2 + rank, nhalf = (cl >> 2) & 1, ks = cl & 3;
  const int k0 = ks * 18, k1 = (ks == 3) ? 73 : k0 + 18;
  if (tid == 0) {
    for (int i = 0; i < K3_NST; i++) { mbar_init(bF + i * 8, 1); mbar_init(bE + i * 8, 4); }
    asm volatile("fence.mbarrier_init.release.cluster;" ::: "memory");
  }
  __syncthreads();
  cluster_sync();

  if (warp_g >= 8) {
    reg_dealloc<40>();
    if (warp_g == 8 && lane == 0) {
      uint32_t s = 0, ph = 1;
      for (int k = k0; k < k1; k++) {
        mbar_wait(bE + s * 8, ph);
        mbar_expect(bF + s * 8, K3_STAGE);
        const uint32_t st = sbase + s * K3_STAGE;
        const int sel = (k >= 64), kr = (sel ? (k - 64) : k) * 64 + rank * 32;
        tma2d(st, &p.tmA, bF + s * 8, k * 64, mblk * 128);
        tma3d_mc(st + 16384 + rank * 16384, &p.tmW[sel], bF + s * 8, 0, kr, nhalf * 4, 3);
        tma2d_mc(st + 49152 + rank * 2048, &p.tmWt[sel], bF + s * 8, 512 + nhalf * 32, kr, 3);
        if (++s == K3_NST) { s = 0; ph ^= 1; }
      }
    }
    __syncwarp();
    cluster_sync();
  } else {
    reg_alloc<232>();
    const int wg = warp_g >> 2, warp = warp_g & 3, q = lane & 3;
    const bool sig = (lane == 0) && (warp < 2);
    float acc[144];
    uint32_t s = 0, ph = 0, prev = 0;
    for (int k = k0; k < k1; k++) {
      mbar_wait(bF + s * 8, ph);
      const uint32_t st = sbase + s * K3_STAGE;
      const uint64_t da = make_desc(st + wg * 8192, 16, 1024, 1);
      const uint64_t db = make_desc(st + 16384, 4096, 1024, 1);
      const uint64_t dt = make_desc(st + 49152, 16, 512, 2);
      wg_fence();
#pragma unroll
      for (int t = 0; t < 4; t++) {
        const int sd = (t > 0) || (k > k0);
        wgmma_ss_n256<1, 0>(acc, da + (uint64_t)(t * 2), db + (uint64_t)((t >> 1) * 1024 + (t & 1) * 128), sd);
        wgmma_ss_n32<1, 128>(acc, da + (uint64_t)(t * 2), dt + (uint64_t)(t * 64), sd);
      }
      wg_commit();
      if (k > k0) {
        wg_wait<1>();
        if (sig) mbar_arrive_cluster(bE + prev * 8, warp);
      }
      prev = s;
      if (++s == K3_NST) { s = 0; ph ^= 1; }
    }
    wg_wait<0>();
    fence_regs(acc);
    const int tile = mblk * 2 + nhalf;
    float4* wp = g_part + (size_t)((tile * 4 + ks) * 4) * 9 * 256 + tid;
#pragma unroll
    for (int d = 0; d < 4; d++) {
      if (d != ks) {
#pragma unroll
        for (int i = 0; i < 8; i++)
          __stcg(wp + (d * 9 + i) * 256, make_float4(acc[d * 32 + i * 4], acc[d * 32 + i * 4 + 1], acc[d * 32 + i * 4 + 2], acc[d * 32 + i * 4 + 3]));
        __stcg(wp + (d * 9 + 8) * 256, make_float4(acc[128 + d * 4], acc[128 + d * 4 + 1], acc[128 + d * 4 + 2], acc[128 + d * 4 + 3]));
      }
    }
    __threadfence();
    bar_sync(1, 256);
    if (tid == 0) {
      atomicAdd(&g_cnt[tile], 1u);
      uint32_t v, spins = 0;
      do {
        asm volatile("ld.acquire.gpu.global.u32 %0, [%1];" : "=r"(v) : "l"(&g_cnt[tile]) : "memory");
      } while (v < 4 && ++spins < (1u << 24));
    }
    bar_sync(1, 256);
    float r[36];
#pragma unroll
    for (int d = 0; d < 4; d++) {
      if (d == ks) {
#pragma unroll
        for (int i = 0; i < 32; i++) r[i] = acc[d * 32 + i];
#pragma unroll
        for (int i = 0; i < 4; i++) r[32 + i] = acc[128 + d * 4 + i];
      }
    }
#pragma unroll
    for (int sI = 1; sI < 4; sI++) {
      const int src = (ks + sI) & 3;
      const float4* rp = g_part + (size_t)(((tile * 4 + src) * 4) + ks) * 9 * 256 + tid;
#pragma unroll
      for (int i = 0; i < 9; i++) {
        const float4 v = __ldcg(rp + i * 256);
        r[i * 4] += v.x; r[i * 4 + 1] += v.y; r[i * 4 + 2] += v.z; r[i * 4 + 3] += v.w;
      }
    }
    const int row = mblk * 128 + wg * 64 + warp * 16 + (lane >> 2);
    bf16* o0 = out + (size_t)row * DM + nhalf * 256 + ks * 64 + 2 * q;
#pragma unroll
    for (int i = 0; i < 8; i++) {
      *reinterpret_cast<uint32_t*>(o0 + i * 8) = pack_bf16(r[i * 4], r[i * 4 + 1]);
      *reinterpret_cast<uint32_t*>(o0 + 8 * DM + i * 8) = pack_bf16(r[i * 4 + 2], r[i * 4 + 3]);
    }
    bf16* o1 = out + (size_t)row * DM + 512 + nhalf * 32 + ks * 8 + 2 * q;
    *reinterpret_cast<uint32_t*>(o1) = pack_bf16(r[32], r[33]);
    *reinterpret_cast<uint32_t*>(o1 + 8 * DM) = pack_bf16(r[34], r[35]);
    cluster_sync();
  }
}

typedef CUresult (*EncFn)(CUtensorMap*, CUtensorMapDataType, cuuint32_t, void*, const cuuint64_t*, const cuuint64_t*, const cuuint32_t*,
                          const cuuint32_t*, CUtensorMapInterleave, CUtensorMapSwizzle, CUtensorMapL2promotion, CUtensorMapFloatOOBfill);

static void enc2d(EncFn enc, CUtensorMap* m, const void* ptr, uint64_t cols, uint64_t rows, uint32_t bc, uint32_t br,
                  CUtensorMapSwizzle sw = CU_TENSOR_MAP_SWIZZLE_128B) {
  cuuint64_t gd[2] = {cols, rows}, gs[1] = {cols * 2};
  cuuint32_t bx[2] = {bc, br}, es[2] = {1, 1};
  enc(m, CU_TENSOR_MAP_DATA_TYPE_BFLOAT16, 2, const_cast<void*>(ptr), gd, gs, bx, es, CU_TENSOR_MAP_INTERLEAVE_NONE, sw,
      CU_TENSOR_MAP_L2_PROMOTION_L2_256B, CU_TENSOR_MAP_FLOAT_OOB_FILL_NONE);
}
static void enc3d(EncFn enc, CUtensorMap* m, const void* ptr, uint64_t cols, uint64_t rows, uint32_t br, uint32_t bch) {
  cuuint64_t gd[3] = {64, rows, cols / 64}, gs[2] = {cols * 2, 128};
  cuuint32_t bx[3] = {64, br, bch}, es[3] = {1, 1, 1};
  enc(m, CU_TENSOR_MAP_DATA_TYPE_BFLOAT16, 3, const_cast<void*>(ptr), gd, gs, bx, es, CU_TENSOR_MAP_INTERLEAVE_NONE,
      CU_TENSOR_MAP_SWIZZLE_128B, CU_TENSOR_MAP_L2_PROMOTION_L2_256B, CU_TENSOR_MAP_FLOAT_OOB_FILL_NONE);
}

static void build_k1_jobs(K1Params& p) {
  int cnt[NCLUSTER];
  for (int c = 0; c < NCLUSTER; c++) {
    cnt[c] = 0;
    for (int i = 0; i < K1_MAXJOBS; i++) p.jobs[c][i] = 0;
  }
  auto add = [&](int c, int a_sel, int mp, int w_sel, int chunk0) {
    p.jobs[c][cnt[c]++] = (uint16_t)(1 | (a_sel << 1) | (mp << 2) | (w_sel << 5) | (chunk0 << 7));
  };
  for (int c = 0; c < 48; c++) {
    const int mp = c / 6;
    for (int i = 0; i < 5; i++) {
      const int t = (c % 6) * 5 + i;
      add(c, 0, mp, t / 16, (t % 16) * 4);
    }
  }
  for (int c = 48; c < 52; c++)
    for (int i = 0; i < 4; i++) {
      const int mp = (c - 48) * 2 + i / 2, t = 30 + (i & 1);
      add(c, 0, mp, t / 16, (t % 16) * 4);
    }
  for (int i = 0; i < 72; i++) {
    const int c = (i < 70) ? 52 + i / 5 : 48 + (i - 70);
    add(c, 1, i / 9, 2, (i % 9) * 3);
  }
  for (int c = 0; c < NCLUSTER; c++)
    for (int i = 0; i < cnt[c]; i++) {
      const int key = p.jobs[c][i] & 0x1E;
      if (i == 0 || (p.jobs[c][i - 1] & 0x1E) != key) p.jobs[c][i] |= (1 << 14);
      if (i == cnt[c] - 1 || (p.jobs[c][i + 1] & 0x1E) != key) p.jobs[c][i] |= (1 << 15);
    }
}

static void build_k2_items(K2Params& p) {
  double load[NCLUSTER];
  for (int c = 0; c < NCLUSTER; c++) { load[c] = 0; p.nitems[c] = 0; }
  for (int j = 7; j >= 0; j--)
    for (int h = 0; h < 32; h++) {
      int best = 0;
      for (int c = 1; c < NCLUSTER; c++)
        if (load[c] < load[best] - 1e-9) best = c;
      p.items[best][p.nitems[best]++] = (uint8_t)(h * 8 + j);
      load[best] += 2.0 * j + 1.5 + 2.25 + 0.4;
    }
}

extern "C" void kernel_launch(void* const* d_in, const int* in_sizes, int n_in, void* d_out, int out_size) {
  const bf16* x = (const bf16*)d_in[0];
  const bf16* wqkv = (const bf16*)d_in[1];
  const bf16* wo = (const bf16*)d_in[2];
  const bf16* ckv = (const bf16*)d_in[4];
  const bf16* w_q = (const bf16*)d_in[5];
  const bf16* w_uk = (const bf16*)d_in[6];
  const bf16* w_uv = (const bf16*)d_in[7];
  const bf16* w_o = (const bf16*)d_in[8];
  const bf16* gate_w = (const bf16*)d_in[9];

  EncFn enc = nullptr;
  cudaDriverEntryPointQueryResult qr;
  cudaGetDriverEntryPoint("cuTensorMapEncodeTiled", (void**)&enc, cudaEnableDefault, &qr);
  void *pK, *pV, *pCtx;
  cudaGetSymbolAddress(&pK, g_K);
  cudaGetSymbolAddress(&pV, g_V);
  cudaGetSymbolAddress(&pCtx, g_ctx);

  static K1Params p1;
  static K2Params p2;
  static K3Params p3;
  enc2d(enc, &p1.tmA[0], ckv, DC, S_LEN, 64, 128);
  enc2d(enc, &p1.tmA[1], x, DM, S_LEN, 64, 128);
  enc3d(enc, &p1.tmW[0], w_uk, HDIM, DC, 16, 4);
  enc3d(enc, &p1.tmW[1], w_uv, HDIM, DC, 16, 4);
  enc3d(enc, &p1.tmW[2], wqkv, NQKVA, DM, 16, 3);
  build_k1_jobs(p1);
  enc2d(enc, &p2.tmX, x, DM, S_LEN, 64, 128);
  enc2d(enc, &p2.tmWq, w_q, HDIM, DM, 64, 64);
  enc2d(enc, &p2.tmK, pK, HDIM, S_LEN, 64, 128);
  enc2d(enc, &p2.tmV, pV, HDIM, S_LEN, 64, 128);
  build_k2_items(p2);
  enc2d(enc, &p3.tmA, pCtx, KCAT, S_LEN, 64, 128);
  enc3d(enc, &p3.tmW[0], w_o, DM, HDIM, 32, 4);
  enc3d(enc, &p3.tmW[1], wo, DM, DM, 32, 4);
  enc2d(enc, &p3.tmWt[0], w_o, DM, HDIM, 32, 32, CU_TENSOR_MAP_SWIZZLE_64B);
  enc2d(enc, &p3.tmWt[1], wo, DM, DM, 32, 32, CU_TENSOR_MAP_SWIZZLE_64B);

  cudaFuncSetAttribute(k1_proj, cudaFuncAttributeMaxDynamicSharedMemorySize, K1_SMEM);
  cudaFuncSetAttribute(k2_attn, cudaFuncAttributeMaxDynamicSharedMemorySize, K2_SMEM);
  cudaFuncSetAttribute(k3_out, cudaFuncAttributeMaxDynamicSharedMemorySize, K3_SMEM);

  k1_proj<<<NCLUSTER * 2, 384, K1_SMEM>>>(p1, x, gate_w);
  k2_attn<<<NCLUSTER * 2, 384, K2_SMEM>>>(p2);
  k3_out<<<128, 384, K3_SMEM>>>(p3, (bf16*)d_out);
}
```

```cpp
#include <cuda_runtime.h>
#include <cuda_bf16.h>
#include <cuda.h>
#include <stdint.h>

typedef __nv_bfloat16 bf16;

constexpr int S_LEN = 2048, DM = 576, DC = 512, HDIM = 4096, NQKVA = 1728, KCAT = 4672;
constexpr int NCLUSTER = 66;

__device__ __align__(1024) bf16 g_Q[S_LEN * HDIM];
__device__ __align__(1024) bf16 g_K[S_LEN * HDIM];
__device__ __align__(1024) bf16 g_V[S_LEN * HDIM];
__device__ __align__(1024) bf16 g_QKVA[S_LEN * NQKVA + 64];
__device__ __align__(1024) bf16 g_ctx[S_LEN * KCAT];
__device__ float g_gate[S_LEN];
__device__ __align__(1024) float4 g_part[32 * 4 * 4 * 9 * 256];
__device__ unsigned int g_cnt[32];
__device__ unsigned int g_flag[32];

__device__ __forceinline__ uint32_t smem_u32(const void* p) { return (uint32_t)__cvta_generic_to_shared(p); }
__device__ __forceinline__ void mbar_init(uint32_t a, uint32_t c) {
  asm volatile("mbarrier.init.shared::cta.b64 [%0], %1;" ::"r"(a), "r"(c));
}
__device__ __forceinline__ void mbar_expect(uint32_t a, uint32_t b) {
  asm volatile("mbarrier.arrive.expect_tx.shared::cta.b64 _, [%0], %1;" ::"r"(a), "r"(b) : "memory");
}
#define TS(k, i)
#define TSC(k, i)
#define SPIN_LIMIT "4194304"
__device__ __forceinline__ void mbar_wait(uint32_t a, uint32_t parity) {
  asm volatile(
      "{\n.reg .pred p;\n.reg .u32 n;\n"
      "mbarrier.try_wait.parity.shared::cta.b64 p, [%0], %1;\n"
      "@p bra DONE;\n"
      "mov.u32 n, 0;\n"
      "LOOP:\n"
      "mbarrier.try_wait.parity.shared::cta.b64 p, [%0], %1;\n"
      "@p bra DONE;\n"
      "add.u32 n, n, 1;\n"
      "setp.lt.u32 p, n, " SPIN_LIMIT ";\n"
      "@p bra LOOP;\n"
      "DONE:\n}" ::"r"(a), "r"(parity) : "memory");
}
__device__ __forceinline__ void mbar_arrive(uint32_t a) {
  asm volatile("mbarrier.arrive.shared::cta.b64 _, [%0];" ::"r"(a) : "memory");
}
__device__ __forceinline__ void mbar_arrive_cluster(uint32_t a, uint32_t cta) {
  asm volatile("{\n.reg .b32 r;\nmapa.shared::cluster.u32 r, %0, %1;\nmbarrier.arrive.shared::cluster.b64 _, [r];\n}" ::"r"(a),
               "r"(cta) : "memory");
}
__device__ __forceinline__ void tma2d(uint32_t dst, const CUtensorMap* m, uint32_t bar, int c0, int c1) {
  asm volatile("cp.async.bulk.tensor.2d.shared::cluster.global.mbarrier::complete_tx::bytes [%0], [%1, {%3, %4}], [%2];" ::"r"(dst),
               "l"(m), "r"(bar), "r"(c0), "r"(c1) : "memory");
}
__device__ __forceinline__ void tma2d_mc(uint32_t dst, const CUtensorMap* m, uint32_t bar, int c0, int c1, uint16_t mask) {
  asm volatile(
      "cp.async.bulk.tensor.2d.shared::cluster.global.mbarrier::complete_tx::bytes.multicast::cluster [%0], [%1, {%3, %4}], [%2], %5;" ::"r"(dst),
      "l"(m), "r"(bar), "r"(c0), "r"(c1), "h"(mask) : "memory");
}
__device__ __forceinline__ void tma3d_mc(uint32_t dst, const CUtensorMap* m, uint32_t bar, int c0, int c1, int c2, uint16_t mask) {
  asm volatile(
      "cp.async.bulk.tensor.3d.shared::cluster.global.mbarrier::complete_tx::bytes.multicast::cluster [%0], [%1, {%3, %4, %5}], [%2], %6;" ::"r"(dst),
      "l"(m), "r"(bar), "r"(c0), "r"(c1), "r"(c2), "h"(mask) : "memory");
}
__device__ __forceinline__ void tma3d(uint32_t dst, const CUtensorMap* m, uint32_t bar, int c0, int c1, int c2) {
  asm volatile(
      "cp.async.bulk.tensor.3d.shared::cluster.global.mbarrier::complete_tx::bytes [%0], [%1, {%3, %4, %5}], [%2];" ::"r"(dst),
      "l"(m), "r"(bar), "r"(c0), "r"(c1), "r"(c2) : "memory");
}
__device__ __forceinline__ void tma_pf2d(const CUtensorMap* m, int c0, int c1) {
  asm volatile("cp.async.bulk.prefetch.tensor.2d.L2.global [%0, {%1, %2}];" ::"l"(m), "r"(c0), "r"(c1) : "memory");
}
__device__ __forceinline__ void tma_pf3d(const CUtensorMap* m, int c0, int c1, int c2) {
  asm volatile("cp.async.bulk.prefetch.tensor.3d.L2.global [%0, {%1, %2, %3}];" ::"l"(m), "r"(c0), "r"(c1), "r"(c2) : "memory");
}
__device__ __forceinline__ void prefetch_tmap(const CUtensorMap* m) {
  asm volatile("prefetch.tensormap [%0];" ::"l"(m) : "memory");
}
__device__ __forceinline__ void cluster_sync() {
  asm volatile("barrier.cluster.arrive.aligned;\nbarrier.cluster.wait.aligned;" ::: "memory");
}
__device__ __forceinline__ uint32_t cluster_rank() {
  uint32_t r;
  asm volatile("mov.u32 %0, %%cluster_ctarank;" : "=r"(r));
  return r;
}
__device__ __forceinline__ void pdl_wait() { asm volatile("griddepcontrol.wait;" ::: "memory"); }
__device__ __forceinline__ void pdl_launch() { asm volatile("griddepcontrol.launch_dependents;" ::: "memory"); }
__device__ __forceinline__ void ldsm_x4(uint32_t& r0, uint32_t& r1, uint32_t& r2, uint32_t& r3, uint32_t addr) {
  asm volatile("ldmatrix.sync.aligned.m8n8.x4.shared.b16 {%0, %1, %2, %3}, [%4];" : "=r"(r0), "=r"(r1), "=r"(r2), "=r"(r3) : "r"(addr) : "memory");
}
__device__ __forceinline__ void wg_fence() { asm volatile("wgmma.fence.sync.aligned;" ::: "memory"); }
__device__ __forceinline__ void wg_commit() { asm volatile("wgmma.commit_group.sync.aligned;" ::: "memory"); }
template <int N>
__device__ __forceinline__ void wg_wait() { asm volatile("wgmma.wait_group.sync.aligned %0;" ::"n"(N) : "memory"); }
template <int N>
__device__ __forceinline__ void reg_alloc() { asm volatile("setmaxnreg.inc.sync.aligned.u32 %0;" ::"n"(N)); }
template <int N>
__device__ __forceinline__ void reg_dealloc() { asm volatile("setmaxnreg.dec.sync.aligned.u32 %0;" ::"n"(N)); }
__device__ __forceinline__ void bar_sync(int id, int n) { asm volatile("bar.sync %0, %1;" ::"r"(id), "r"(n) : "memory"); }
__device__ __forceinline__ void bar_arrive(int id, int n) { asm volatile("bar.arrive %0, %1;" ::"r"(id), "r"(n) : "memory"); }
template <int NT>
__device__ __forceinline__ void fence_regs(float (&d)[NT]) {
#pragma unroll
  for (int i = 0; i < NT; i++) asm volatile("" : "+f"(d[i])::"memory");
}
template <int NT>
__device__ __forceinline__ void fence_regs(uint32_t (&d)[NT]) {
#pragma unroll
  for (int i = 0; i < NT; i++) asm volatile("" : "+r"(d[i])::"memory");
}
__device__ __forceinline__ uint64_t make_desc(uint32_t saddr, uint32_t lbo, uint32_t sbo, uint32_t layout) {
  return (uint64_t)((saddr & 0x3FFFF) >> 4) | ((uint64_t)(lbo >> 4) << 16) | ((uint64_t)(sbo >> 4) << 32) | ((uint64_t)layout << 62);
}
__device__ __forceinline__ uint32_t pack_bf16(float lo, float hi) {
  uint32_t r;
  asm("cvt.rn.bf16x2.f32 %0, %1, %2;" : "=r"(r) : "f"(hi), "f"(lo));
  return r;
}
__device__ __forceinline__ float ex2(float x) {
  float r;
  asm("ex2.approx.ftz.f32 %0, %1;" : "=f"(r) : "f"(x));
  return r;
}
__device__ __forceinline__ void st_v4(void* p, uint32_t a, uint32_t b, uint32_t c, uint32_t d) {
#define ST_MOD ""
  asm volatile("st.global" ST_MOD ".v4.b32 [%0], {%1, %2, %3, %4};" ::"l"(p), "r"(a), "r"(b), "r"(c), "r"(d) : "memory");
}
__device__ __forceinline__ float bf_lo(uint32_t v) { return __uint_as_float(v << 16); }
__device__ __forceinline__ float bf_hi(uint32_t v) { return __uint_as_float(v & 0xFFFF0000u); }

__device__ __forceinline__ void quad_transpose(uint32_t& a0, uint32_t& a1, uint32_t& a2, uint32_t& a3, int q) {
  const bool o1 = q & 1, o2 = q & 2;
  uint32_t t0 = o1 ? a0 : a1, t1 = o1 ? a2 : a3;
  t0 = __shfl_xor_sync(0xffffffffu, t0, 1);
  t1 = __shfl_xor_sync(0xffffffffu, t1, 1);
  if (o1) { a0 = t0; a2 = t1; } else { a1 = t0; a3 = t1; }
  t0 = o2 ? a0 : a2;
  t1 = o2 ? a1 : a3;
  t0 = __shfl_xor_sync(0xffffffffu, t0, 2);
  t1 = __shfl_xor_sync(0xffffffffu, t1, 2);
  if (o2) { a0 = t0; a1 = t1; } else { a2 = t0; a3 = t1; }
}

template<int TB, int OFF, int NT>
__device__ __forceinline__ void wgmma_ss_n256(float (&d)[NT], uint64_t da, uint64_t db, int scale_d) {
  asm volatile("{\n.reg .pred p;\nsetp.ne.b32 p, %130, 0;\n"
    "wgmma.mma_async.sync.aligned.m64n256k16.f32.bf16.bf16 {%0, %1, %2, %3, %4, %5, %6, %7, %8, %9, %10, %11, %12, %13, %14, %15, %16, %17, %18, %19, %20, %21, %22, %23, %24, %25, %26, %27, %28, %29, %30, %31, %32, %33, %34, %35, %36, %37, %38, %39, %40, %41, %42, %43, %44, %45, %46, %47, %48, %49, %50, %51, %52, %53, %54, %55, %56, %57, %58, %59, %60, %61, %62, %63, %64, %65, %66, %67, %68, %69, %70, %71, %72, %73, %74, %75, %76, %77, %78, %79, %80, %81, %82, %83, %84, %85, %86, %87, %88, %89, %90, %91, %92, %93, %94, %95, %96, %97, %98, %99, %100, %101, %102, %103, %104, %105, %106, %107, %108, %109, %110, %111, %112, %113, %114, %115, %116, %117, %118, %119, %120, %121, %122, %123, %124, %125, %126, %127}, %128, %129, p, 1, 1, 0, %131;\n}\n"
    : "+f"(d[OFF+0]), "+f"(d[OFF+1]), "+f"(d[OFF+2]), "+f"(d[OFF+3]), "+f"(d[OFF+4]), "+f"(d[OFF+5]), "+f"(d[OFF+6]), "+f"(d[OFF+7]), "+f"(d[OFF+8]), "+f"(d[OFF+9]), "+f"(d[OFF+10]), "+f"(d[OFF+11]), "+f"(d[OFF+12]), "+f"(d[OFF+13]), "+f"(d[OFF+14]), "+f"(d[OFF+15]), "+f"(d[OFF+16]), "+f"(d[OFF+17]), "+f"(d[OFF+18]), "+f"(d[OFF+19]), "+f"(d[OFF+20]), "+f"(d[OFF+21]), "+f"(d[OFF+22]), "+f"(d[OFF+23]), "+f"(d[OFF+24]), "+f"(d[OFF+25]), "+f"(d[OFF+26]), "+f"(d[OFF+27]), "+f"(d[OFF+28]), "+f"(d[OFF+29]), "+f"(d[OFF+30]), "+f"(d[OFF+31]), "+f"(d[OFF+32]), "+f"(d[OFF+33]), "+f"(d[OFF+34]), "+f"(d[OFF+35]), "+f"(d[OFF+36]), "+f"(d[OFF+37]), "+f"(d[OFF+38]), "+f"(d[OFF+39]), "+f"(d[OFF+40]), "+f"(d[OFF+41]), "+f"(d[OFF+42]), "+f"(d[OFF+43]), "+f"(d[OFF+44]), "+f"(d[OFF+45]), "+f"(d[OFF+46]), "+f"(d[OFF+47]), "+f"(d[OFF+48]), "+f"(d[OFF+49]), "+f"(d[OFF+50]), "+f"(d[OFF+51]), "+f"(d[OFF+52]), "+f"(d[OFF+53]), "+f"(d[OFF+54]), "+f"(d[OFF+55]), "+f"(d[OFF+56]), "+f"(d[OFF+57]), "+f"(d[OFF+58]), "+f"(d[OFF+59]), "+f"(d[OFF+60]), "+f"(d[OFF+61]), "+f"(d[OFF+62]), "+f"(d[OFF+63]), "+f"(d[OFF+64]), "+f"(d[OFF+65]), "+f"(d[OFF+66]), "+f"(d[OFF+67]), "+f"(d[OFF+68]), "+f"(d[OFF+69]), "+f"(d[OFF+70]), "+f"(d[OFF+71]), "+f"(d[OFF+72]), "+f"(d[OFF+73]), "+f"(d[OFF+74]), "+f"(d[OFF+75]), "+f"(d[OFF+76]), "+f"(d[OFF+77]), "+f"(d[OFF+78]), "+f"(d[OFF+79]), "+f"(d[OFF+80]), "+f"(d[OFF+81]), "+f"(d[OFF+82]), "+f"(d[OFF+83]), "+f"(d[OFF+84]), "+f"(d[OFF+85]), "+f"(d[OFF+86]), "+f"(d[OFF+87]), "+f"(d[OFF+88]), "+f"(d[OFF+89]), "+f"(d[OFF+90]), "+f"(d[OFF+91]), "+f"(d[OFF+92]), "+f"(d[OFF+93]), "+f"(d[OFF+94]), "+f"(d[OFF+95]), "+f"(d[OFF+96]), "+f"(d[OFF+97]), "+f"(d[OFF+98]), "+f"(d[OFF+99]), "+f"(d[OFF+100]), "+f"(d[OFF+101]), "+f"(d[OFF+102]), "+f"(d[OFF+103]), "+f"(d[OFF+104]), "+f"(d[OFF+105]), "+f"(d[OFF+106]), "+f"(d[OFF+107]), "+f"(d[OFF+108]), "+f"(d[OFF+109]), "+f"(d[OFF+110]), "+f"(d[OFF+111]), "+f"(d[OFF+112]), "+f"(d[OFF+113]), "+f"(d[OFF+114]), "+f"(d[OFF+115]), "+f"(d[OFF+116]), "+f"(d[OFF+117]), "+f"(d[OFF+118]), "+f"(d[OFF+119]), "+f"(d[OFF+120]), "+f"(d[OFF+121]), "+f"(d[OFF+122]), "+f"(d[OFF+123]), "+f"(d[OFF+124]), "+f"(d[OFF+125]), "+f"(d[OFF+126]), "+f"(d[OFF+127])
    : "l"(da), "l"(db), "r"(scale_d), "n"(TB));
}
template<int TB, int OFF, int NT>
__device__ __forceinline__ void wgmma_ss_n192(float (&d)[NT], uint64_t da, uint64_t db, int scale_d) {
  asm volatile("{\n.reg .pred p;\nsetp.ne.b32 p, %98, 0;\n"
    "wgmma.mma_async.sync.aligned.m64n192k16.f32.bf16.bf16 {%0, %1, %2, %3, %4, %5, %6, %7, %8, %9, %10, %11, %12, %13, %14, %15, %16, %17, %18, %19, %20, %21, %22, %23, %24, %25, %26, %27, %28, %29, %30, %31, %32, %33, %34, %35, %36, %37, %38, %39, %40, %41, %42, %43, %44, %45, %46, %47, %48, %49, %50, %51, %52, %53, %54, %55, %56, %57, %58, %59, %60, %61, %62, %63, %64, %65, %66, %67, %68, %69, %70, %71, %72, %73, %74, %75, %76, %77, %78, %79, %80, %81, %82, %83, %84, %85, %86, %87, %88, %89, %90, %91, %92, %93, %94, %95}, %96, %97, p, 1, 1, 0, %99;\n}\n"
    : "+f"(d[OFF+0]), "+f"(d[OFF+1]), "+f"(d[OFF+2]), "+f"(d[OFF+3]), "+f"(d[OFF+4]), "+f"(d[OFF+5]), "+f"(d[OFF+6]), "+f"(d[OFF+7]), "+f"(d[OFF+8]), "+f"(d[OFF+9]), "+f"(d[OFF+10]), "+f"(d[OFF+11]), "+f"(d[OFF+12]), "+f"(d[OFF+13]), "+f"(d[OFF+14]), "+f"(d[OFF+15]), "+f"(d[OFF+16]), "+f"(d[OFF+17]), "+f"(d[OFF+18]), "+f"(d[OFF+19]), "+f"(d[OFF+20]), "+f"(d[OFF+21]), "+f"(d[OFF+22]), "+f"(d[OFF+23]), "+f"(d[OFF+24]), "+f"(d[OFF+25]), "+f"(d[OFF+26]), "+f"(d[OFF+27]), "+f"(d[OFF+28]), "+f"(d[OFF+29]), "+f"(d[OFF+30]), "+f"(d[OFF+31]), "+f"(d[OFF+32]), "+f"(d[OFF+33]), "+f"(d[OFF+34]), "+f"(d[OFF+35]), "+f"(d[OFF+36]), "+f"(d[OFF+37]), "+f"(d[OFF+38]), "+f"(d[OFF+39]), "+f"(d[OFF+40]), "+f"(d[OFF+41]), "+f"(d[OFF+42]), "+f"(d[OFF+43]), "+f"(d[OFF+44]), "+f"(d[OFF+45]), "+f"(d[OFF+46]), "+f"(d[OFF+47]), "+f"(d[OFF+48]), "+f"(d[OFF+49]), "+f"(d[OFF+50]), "+f"(d[OFF+51]), "+f"(d[OFF+52]), "+f"(d[OFF+53]), "+f"(d[OFF+54]), "+f"(d[OFF+55]), "+f"(d[OFF+56]), "+f"(d[OFF+57]), "+f"(d[OFF+58]), "+f"(d[OFF+59]), "+f"(d[OFF+60]), "+f"(d[OFF+61]), "+f"(d[OFF+62]), "+f"(d[OFF+63]), "+f"(d[OFF+64]), "+f"(d[OFF+65]), "+f"(d[OFF+66]), "+f"(d[OFF+67]), "+f"(d[OFF+68]), "+f"(d[OFF+69]), "+f"(d[OFF+70]), "+f"(d[OFF+71]), "+f"(d[OFF+72]), "+f"(d[OFF+73]), "+f"(d[OFF+74]), "+f"(d[OFF+75]), "+f"(d[OFF+76]), "+f"(d[OFF+77]), "+f"(d[OFF+78]), "+f"(d[OFF+79]), "+f"(d[OFF+80]), "+f"(d[OFF+81]), "+f"(d[OFF+82]), "+f"(d[OFF+83]), "+f"(d[OFF+84]), "+f"(d[OFF+85]), "+f"(d[OFF+86]), "+f"(d[OFF+87]), "+f"(d[OFF+88]), "+f"(d[OFF+89]), "+f"(d[OFF+90]), "+f"(d[OFF+91]), "+f"(d[OFF+92]), "+f"(d[OFF+93]), "+f"(d[OFF+94]), "+f"(d[OFF+95])
    : "l"(da), "l"(db), "r"(scale_d), "n"(TB));
}
template<int TB, int OFF, int NT>
__device__ __forceinline__ void wgmma_ss_n128(float (&d)[NT], uint64_t da, uint64_t db, int scale_d) {
  asm volatile("{\n.reg .pred p;\nsetp.ne.b32 p, %66, 0;\n"
    "wgmma.mma_async.sync.aligned.m64n128k16.f32.bf16.bf16 {%0, %1, %2, %3, %4, %5, %6, %7, %8, %9, %10, %11, %12, %13, %14, %15, %16, %17, %18, %19, %20, %21, %22, %23, %24, %25, %26, %27, %28, %29, %30, %31, %32, %33, %34, %35, %36, %37, %38, %39, %40, %41, %42, %43, %44, %45, %46, %47, %48, %49, %50, %51, %52, %53, %54, %55, %56, %57, %58, %59, %60, %61, %62, %63}, %64, %65, p, 1, 1, 0, %67;\n}\n"
    : "+f"(d[OFF+0]), "+f"(d[OFF+1]), "+f"(d[OFF+2]), "+f"(d[OFF+3]), "+f"(d[OFF+4]), "+f"(d[OFF+5]), "+f"(d[OFF+6]), "+f"(d[OFF+7]), "+f"(d[OFF+8]), "+f"(d[OFF+9]), "+f"(d[OFF+10]), "+f"(d[OFF+11]), "+f"(d[OFF+12]), "+f"(d[OFF+13]), "+f"(d[OFF+14]), "+f"(d[OFF+15]), "+f"(d[OFF+16]), "+f"(d[OFF+17]), "+f"(d[OFF+18]), "+f"(d[OFF+19]), "+f"(d[OFF+20]), "+f"(d[OFF+21]), "+f"(d[OFF+22]), "+f"(d[OFF+23]), "+f"(d[OFF+24]), "+f"(d[OFF+25]), "+f"(d[OFF+26]), "+f"(d[OFF+27]), "+f"(d[OFF+28]), "+f"(d[OFF+29]), "+f"(d[OFF+30]), "+f"(d[OFF+31]), "+f"(d[OFF+32]), "+f"(d[OFF+33]), "+f"(d[OFF+34]), "+f"(d[OFF+35]), "+f"(d[OFF+36]), "+f"(d[OFF+37]), "+f"(d[OFF+38]), "+f"(d[OFF+39]), "+f"(d[OFF+40]), "+f"(d[OFF+41]), "+f"(d[OFF+42]), "+f"(d[OFF+43]), "+f"(d[OFF+44]), "+f"(d[OFF+45]), "+f"(d[OFF+46]), "+f"(d[OFF+47]), "+f"(d[OFF+48]), "+f"(d[OFF+49]), "+f"(d[OFF+50]), "+f"(d[OFF+51]), "+f"(d[OFF+52]), "+f"(d[OFF+53]), "+f"(d[OFF+54]), "+f"(d[OFF+55]), "+f"(d[OFF+56]), "+f"(d[OFF+57]), "+f"(d[OFF+58]), "+f"(d[OFF+59]), "+f"(d[OFF+60]), "+f"(d[OFF+61]), "+f"(d[OFF+62]), "+f"(d[OFF+63])
    : "l"(da), "l"(db), "r"(scale_d), "n"(TB));
}
template<int TB, int OFF, int NT>
__device__ __forceinline__ void wgmma_ss_n32(float (&d)[NT], uint64_t da, uint64_t db, int scale_d) {
  asm volatile("{\n.reg .pred p;\nsetp.ne.b32 p, %18, 0;\n"
    "wgmma.mma_async.sync.aligned.m64n32k16.f32.bf16.bf16 {%0, %1, %2, %3, %4, %5, %6, %7, %8, %9, %10, %11, %12, %13, %14, %15}, %16, %17, p, 1, 1, 0, %19;\n}\n"
    : "+f"(d[OFF+0]), "+f"(d[OFF+1]), "+f"(d[OFF+2]), "+f"(d[OFF+3]), "+f"(d[OFF+4]), "+f"(d[OFF+5]), "+f"(d[OFF+6]), "+f"(d[OFF+7]), "+f"(d[OFF+8]), "+f"(d[OFF+9]), "+f"(d[OFF+10]), "+f"(d[OFF+11]), "+f"(d[OFF+12]), "+f"(d[OFF+13]), "+f"(d[OFF+14]), "+f"(d[OFF+15])
    : "l"(da), "l"(db), "r"(scale_d), "n"(TB));
}
template<int TB, int OFF, int NT>
__device__ __forceinline__ void wgmma_rs_n128(float (&d)[NT], uint32_t a0, uint32_t a1, uint32_t a2, uint32_t a3, uint64_t db, int scale_d) {
  asm volatile("{\n.reg .pred p;\nsetp.ne.b32 p, %69, 0;\n"
    "wgmma.mma_async.sync.aligned.m64n128k16.f32.bf16.bf16 {%0, %1, %2, %3, %4, %5, %6, %7, %8, %9, %10, %11, %12, %13, %14, %15, %16, %17, %18, %19, %20, %21, %22, %23, %24, %25, %26, %27, %28, %29, %30, %31, %32, %33, %34, %35, %36, %37, %38, %39, %40, %41, %42, %43, %44, %45, %46, %47, %48, %49, %50, %51, %52, %53, %54, %55, %56, %57, %58, %59, %60, %61, %62, %63}, {%64, %65, %66, %67}, %68, p, 1, 1, %70;\n}\n"
    : "+f"(d[OFF+0]), "+f"(d[OFF+1]), "+f"(d[OFF+2]), "+f"(d[OFF+3]), "+f"(d[OFF+4]), "+f"(d[OFF+5]), "+f"(d[OFF+6]), "+f"(d[OFF+7]), "+f"(d[OFF+8]), "+f"(d[OFF+9]), "+f"(d[OFF+10]), "+f"(d[OFF+11]), "+f"(d[OFF+12]), "+f"(d[OFF+13]), "+f"(d[OFF+14]), "+f"(d[OFF+15]), "+f"(d[OFF+16]), "+f"(d[OFF+17]), "+f"(d[OFF+18]), "+f"(d[OFF+19]), "+f"(d[OFF+20]), "+f"(d[OFF+21]), "+f"(d[OFF+22]), "+f"(d[OFF+23]), "+f"(d[OFF+24]), "+f"(d[OFF+25]), "+f"(d[OFF+26]), "+f"(d[OFF+27]), "+f"(d[OFF+28]), "+f"(d[OFF+29]), "+f"(d[OFF+30]), "+f"(d[OFF+31]), "+f"(d[OFF+32]), "+f"(d[OFF+33]), "+f"(d[OFF+34]), "+f"(d[OFF+35]), "+f"(d[OFF+36]), "+f"(d[OFF+37]), "+f"(d[OFF+38]), "+f"(d[OFF+39]), "+f"(d[OFF+40]), "+f"(d[OFF+41]), "+f"(d[OFF+42]), "+f"(d[OFF+43]), "+f"(d[OFF+44]), "+f"(d[OFF+45]), "+f"(d[OFF+46]), "+f"(d[OFF+47]), "+f"(d[OFF+48]), "+f"(d[OFF+49]), "+f"(d[OFF+50]), "+f"(d[OFF+51]), "+f"(d[OFF+52]), "+f"(d[OFF+53]), "+f"(d[OFF+54]), "+f"(d[OFF+55]), "+f"(d[OFF+56]), "+f"(d[OFF+57]), "+f"(d[OFF+58]), "+f"(d[OFF+59]), "+f"(d[OFF+60]), "+f"(d[OFF+61]), "+f"(d[OFF+62]), "+f"(d[OFF+63])
    : "r"(a0), "r"(a1), "r"(a2), "r"(a3), "l"(db), "r"(scale_d), "n"(TB));
}
template<int TB, int OFF, int NT>
__device__ __forceinline__ void wgmma_rs_n64(float (&d)[NT], uint32_t a0, uint32_t a1, uint32_t a2, uint32_t a3, uint64_t db, int scale_d) {
  asm volatile("{\n.reg .pred p;\nsetp.ne.b32 p, %37, 0;\n"
    "wgmma.mma_async.sync.aligned.m64n64k16.f32.bf16.bf16 {%0, %1, %2, %3, %4, %5, %6, %7, %8, %9, %10, %11, %12, %13, %14, %15, %16, %17, %18, %19, %20, %21, %22, %23, %24, %25, %26, %27, %28, %29, %30, %31}, {%32, %33, %34, %35}, %36, p, 1, 1, %38;\n}\n"
    : "+f"(d[OFF+0]), "+f"(d[OFF+1]), "+f"(d[OFF+2]), "+f"(d[OFF+3]), "+f"(d[OFF+4]), "+f"(d[OFF+5]), "+f"(d[OFF+6]), "+f"(d[OFF+7]), "+f"(d[OFF+8]), "+f"(d[OFF+9]), "+f"(d[OFF+10]), "+f"(d[OFF+11]), "+f"(d[OFF+12]), "+f"(d[OFF+13]), "+f"(d[OFF+14]), "+f"(d[OFF+15]), "+f"(d[OFF+16]), "+f"(d[OFF+17]), "+f"(d[OFF+18]), "+f"(d[OFF+19]), "+f"(d[OFF+20]), "+f"(d[OFF+21]), "+f"(d[OFF+22]), "+f"(d[OFF+23]), "+f"(d[OFF+24]), "+f"(d[OFF+25]), "+f"(d[OFF+26]), "+f"(d[OFF+27]), "+f"(d[OFF+28]), "+f"(d[OFF+29]), "+f"(d[OFF+30]), "+f"(d[OFF+31])
    : "r"(a0), "r"(a1), "r"(a2), "r"(a3), "l"(db), "r"(scale_d), "n"(TB));
}

__device__ __forceinline__ void wait_flag(const unsigned int* f, uint32_t target) {
  uint32_t v;
#pragma unroll 1
  for (uint32_t spins = 0; spins < (1u << 22); spins++) {
    asm volatile("ld.acquire.gpu.global.u32 %0, [%1];" : "=r"(v) : "l"(f) : "memory");
    if (v >= target) break;
    __nanosleep(100);
  }
}
__device__ __forceinline__ uint32_t lds32(uint32_t a) {
  uint32_t v;
  asm volatile("ld.shared.u32 %0, [%1];" : "=r"(v) : "r"(a) : "memory");
  return v;
}
__device__ __forceinline__ float gate_row(int row, int lane, const bf16* __restrict__ x, const bf16* __restrict__ gate_w) {
  const uint32_t* xr = reinterpret_cast<const uint32_t*>(x + (size_t)row * DM);
  const uint32_t* gw2 = reinterpret_cast<const uint32_t*>(gate_w);
  float gs = 0.f;
#pragma unroll
  for (int i = 0; i < 9; i++) {
    const uint32_t a = __ldg(xr + lane + 32 * i), b = __ldg(gw2 + lane + 32 * i);
    gs = fmaf(bf_lo(a), bf_lo(b), gs);
    gs = fmaf(bf_hi(a), bf_hi(b), gs);
  }
#pragma unroll
  for (int o = 16; o; o >>= 1) gs += __shfl_xor_sync(0xffffffffu, gs, o);
  const float g = 1.f / (1.f + __expf(-gs));
  if (lane == 0) g_gate[row] = g;
  return g;
}
__device__ __forceinline__ void local_rows2(int row, uint32_t srow, int lane, float g0, float g1) {
  const float scale_l2 = 0.23570226039551584f * 1.4426950408889634f;
  const uint32_t srow0 = srow;
  float q[2][18], o[2][18], mx[2], sum[2];
#pragma unroll
  for (int r = 0; r < 2; r++) {
#pragma unroll
    for (int i = 0; i < 9; i++) {
      const uint32_t v = lds32(srow + r * 3456 + 4 * i);
      q[r][2 * i] = bf_lo(v);
      q[r][2 * i + 1] = bf_hi(v);
      o[r][2 * i] = 0.f;
      o[r][2 * i + 1] = 0.f;
    }
    mx[r] = -INFINITY;
    sum[r] = 0.f;
  }
  const int nw = min(8, (row >> 1) + 1);
#pragma unroll 1
  for (int w = 0; w < nw; w++, srow -= 2 * 3456) {
#pragma unroll
    for (int r = 0; r < 2; r++) {
      float s0 = 0.f, s1 = 0.f, s2 = 0.f;
#pragma unroll
      for (int i = 0; i < 3; i++) {
        const uint32_t k0 = lds32(srow + r * 3456 + 1152 + 4 * i), k1 = lds32(srow + r * 3456 + 1164 + 4 * i), k2 = lds32(srow + r * 3456 + 1176 + 4 * i);
        s0 = fmaf(q[r][2 * i], bf_lo(k0), s0);
        s1 = fmaf(q[r][6 + 2 * i], bf_lo(k1), s1);
        s2 = fmaf(q[r][12 + 2 * i], bf_lo(k2), s2);
        s0 = fmaf(q[r][2 * i + 1], bf_hi(k0), s0);
        s1 = fmaf(q[r][6 + 2 * i + 1], bf_hi(k1), s1);
        s2 = fmaf(q[r][12 + 2 * i + 1], bf_hi(k2), s2);
      }
      const float s = s0 + s1 + s2;
      const float mn = fmaxf(mx[r], s);
      const float sc = ex2((mx[r] - mn) * scale_l2), pw = ex2((s - mn) * scale_l2);
      mx[r] = mn;
      sum[r] = fmaf(sum[r], sc, pw);
#pragma unroll
      for (int i = 0; i < 9; i++) {
        const uint32_t vv = lds32(srow + r * 3456 + 2304 + 4 * i);
        o[r][2 * i] = fmaf(pw, bf_lo(vv), o[r][2 * i] * sc);
        o[r][2 * i + 1] = fmaf(pw, bf_hi(vv), o[r][2 * i + 1] * sc);
      }
    }
  }
#pragma unroll
  for (int r = 0; r < 2; r++) {
    const float f = (r ? g1 : g0) / sum[r];
#pragma unroll
    for (int i = 0; i < 9; i++)
      asm volatile("st.shared.u32 [%0], %1;" ::"r"(srow0 + r * 3456 + 4 * i), "r"(pack_bf16(o[r][2 * i] * f, o[r][2 * i + 1] * f)) : "memory");
  }
  __syncwarp();
  const uint32_t sb = srow0 - lane * 36;
#pragma unroll
  for (int t = 0; t < 5; t++) {
    const int c = t * 32 + lane;
    if (c < 144) {
      const int r = c >= 72, cc = c - r * 72;
      uint32_t a, b, d, e;
      asm volatile("ld.shared.v4.u32 {%0, %1, %2, %3}, [%4];" : "=r"(a), "=r"(b), "=r"(d), "=r"(e) : "r"(sb + r * 3456 + cc * 16) : "memory");
      st_v4(g_ctx + (size_t)(row + r) * KCAT + HDIM + cc * 8, a, b, d, e);
    }
  }
}

#define K1_NST 6
constexpr int K1_BST = K1_NST;
constexpr int K1_MAXJOBS = 10;
constexpr int K1_SMEM = 8 * 16384 + K1_BST * 16384 + 1024 + 512;
constexpr uint32_t K1_FLAG_TARGET = 7 * 8;
struct alignas(64) K1Params {
  CUtensorMap tmA[2];
  CUtensorMap tmW[4];
  uint16_t jobs[NCLUSTER][K1_MAXJOBS];
};

struct K1State {
  uint32_t bs, bph, aph;
  bf16* pp;
  int pld8;
  int png;
  int pflag;
};
__device__ __forceinline__ void k1_flag(const K1State& st, int lane) {
  if (st.pflag >= 0) {
    __threadfence();
    __syncwarp();
    if (lane == 0) atomicAdd(&g_flag[st.pflag], 1u);
  }
}

__device__ __forceinline__ void k1_tile(float (&acc)[128], uint32_t (&pk)[64], K1State& st, uint32_t job, uint32_t sA, uint32_t sB,
                                        uint32_t bAf, uint32_t bAe, uint32_t bBf, uint32_t bBe, int wg, int warp, int lane, uint32_t rank) {
  const int a_sel = (job >> 2) & 1, mpair = (job >> 3) & 7, w_sel = (job >> 6) & 3, chunk0 = (job >> 8) & 63;
  const bool newA = (job >> 14) & 1, lastA = (job >> 15) & 1;
  const bool sig = (lane == 0) && (warp < 2);
  const bool siga = lastA && (lane == 0) && (warp == 2);
  const int KC = 8 + a_sel;
  uint32_t prev_bs = 0, prev2_bs = 0, a8_bs = 0;
#pragma unroll
  for (int kc = 0; kc < 9; kc++) {
    if (kc >= KC) break;
    uint32_t abase = sA + kc * 16384;
    if (kc == 8) {
      mbar_wait(bBf + st.bs * 8, st.bph);
      a8_bs = st.bs;
      abase = sB + st.bs * 16384;
      if (++st.bs == K1_BST) { st.bs = 0; st.bph ^= 1; }
    } else if (newA) {
      mbar_wait(bAf + kc * 8, st.aph);
    }
    const uint64_t da = make_desc(abase + wg * 8192, 16, 1024, 1);
#pragma unroll
    for (int ks = 0; ks < 2; ks++) {
      mbar_wait(bBf + st.bs * 8, st.bph);
      const uint64_t db = make_desc(sB + st.bs * 16384, 2048, 1024, 1);
      wg_fence();
      wgmma_ss_n256<1, 0>(acc, da + (uint64_t)(ks * 4), db, (ks > 0) ? 1 : (kc > 0));
      wgmma_ss_n256<1, 0>(acc, da + (uint64_t)(ks * 4 + 2), db + (uint64_t)512, 1);
      wg_commit();
      const int PO = (kc < 8 ? kc : 0) * 8;
      wg_wait<1>();
      if (ks > 0 || kc > 0) {
        if (sig) mbar_arrive_cluster(bBe + prev_bs * 8, warp);
        if (ks == 0 && siga) mbar_arrive(bAe + (kc - 1) * 8);
      }
      if (kc < st.png) st_v4(st.pp + kc * 32 + ks * st.pld8, pk[PO + ks * 4], pk[PO + ks * 4 + 1], pk[PO + ks * 4 + 2], pk[PO + ks * 4 + 3]);
      prev_bs = st.bs;
      if (++st.bs == K1_BST) { st.bs = 0; st.bph ^= 1; }
    }
  }
  if (newA) st.aph ^= 1;
  k1_flag(st, lane);
  wg_wait<0>();
  fence_regs(acc);
  if (sig) {
    mbar_arrive_cluster(bBe + prev_bs * 8, warp);
    if (a_sel) mbar_arrive_cluster(bBe + a8_bs * 8, warp);
  }
  if (siga && !a_sel) mbar_arrive(bAe + 7 * 8);
  const bool isA = (w_sel == 2);
  bf16* out = (w_sel == 0) ? g_K : (w_sel == 1) ? g_V : isA ? g_QKVA : g_Q;
  const int ld = isA ? NQKVA : HDIM;
  const int row = mpair * 256 + rank * 128 + wg * 64 + warp * 16 + (lane >> 2);
  st.pp = out + (size_t)row * ld + chunk0 * 64 + (lane & 3) * 8;
  st.pld8 = 8 * ld;
  st.png = ((job & 3) + 1) * 2;
  st.pflag = isA ? (mpair * 2 + (int)rank) : -1;
#pragma unroll
  for (int G = 0; G < 8; G++) {
    pk[G * 8 + 0] = pack_bf16(acc[G * 16 + 0], acc[G * 16 + 1]);
    pk[G * 8 + 1] = pack_bf16(acc[G * 16 + 4], acc[G * 16 + 5]);
    pk[G * 8 + 2] = pack_bf16(acc[G * 16 + 8], acc[G * 16 + 9]);
    pk[G * 8 + 3] = pack_bf16(acc[G * 16 + 12], acc[G * 16 + 13]);
    pk[G * 8 + 4] = pack_bf16(acc[G * 16 + 2], acc[G * 16 + 3]);
    pk[G * 8 + 5] = pack_bf16(acc[G * 16 + 6], acc[G * 16 + 7]);
    pk[G * 8 + 6] = pack_bf16(acc[G * 16 + 10], acc[G * 16 + 11]);
    pk[G * 8 + 7] = pack_bf16(acc[G * 16 + 14], acc[G * 16 + 15]);
  }
  if (isA) {
#pragma unroll
    for (int G = 0; G < 16; G++) quad_transpose(pk[G * 4 + 0], pk[G * 4 + 1], pk[G * 4 + 2], pk[G * 4 + 3], lane & 3);
  }
}

__global__ void __cluster_dims__(2, 1, 1) __launch_bounds__(384, 1)
k1_proj(const __grid_constant__ K1Params p, const bf16* __restrict__ x, const bf16* __restrict__ gate_w) {
  extern __shared__ uint8_t smem_raw[];
  const uint32_t sbase = (smem_u32(smem_raw) + 1023) & ~1023u;
  const uint32_t sA = sbase, sB = sbase + 8 * 16384, sBar = sB + K1_BST * 16384;
  const uint32_t bAf = sBar, bAe = sBar + 64, bBf = sBar + 128, bBe = bBf + K1_BST * 8, bL = bBe + K1_BST * 8, sGate = sBar + 256;
  const int tid = threadIdx.x, warp_g = tid >> 5, lane = tid & 31;
  const uint32_t rank = cluster_rank();
  const int cl = blockIdx.x >> 1;
  if (tid == 0) {
    for (int i = 0; i < 8; i++) { mbar_init(bAf + i * 8, 1); mbar_init(bAe + i * 8, 2); }
    for (int i = 0; i < K1_BST; i++) { mbar_init(bBf + i * 8, 1); mbar_init(bBe + i * 8, 4); }
    mbar_init(bL, 1);
    asm volatile("fence.mbarrier_init.release.cluster;" ::: "memory");
  }
  __syncthreads();
  cluster_sync();
  pdl_launch();
  const int lr0 = blockIdx.x * 16, lrs = max(lr0 - 14, 0);

  if (warp_g >= 8) {
    reg_dealloc<40>();
    if (warp_g == 8) {
      if (lane == 0) {
        uint32_t bs = 0, bph = 1, aph = 1;
        for (int ji = 0; ji < K1_MAXJOBS; ji++) {
          const uint32_t job = p.jobs[cl][ji];
          if (!(job & 3)) break;
          const int a_sel = (job >> 2) & 1, mpair = (job >> 3) & 7, chunk0 = (job >> 8) & 63;
          const bool newA = (job >> 14) & 1;
          const int KC = a_sel ? 9 : 8;
          const uint32_t halfbytes = 8192;
          const CUtensorMap* tw = &p.tmW[(job >> 6) & 3];
          {
            const uint32_t njob = (ji + 1 < K1_MAXJOBS) ? p.jobs[cl][ji + 1] : 0;
            if (njob & 3) {
              const int nst = ((njob >> 2) & 1) ? 18 : 16;
              for (int t = (cl < 64) ? (cl & 7) : 0; t < nst; t += (cl < 64) ? 8 : 1)
                tma_pf3d(&p.tmW[(njob >> 6) & 3], 0, t * 32 + rank * 16, (njob >> 8) & 63);
            }
          }
          for (int kc = 0; kc < KC; kc++) {
            if (kc == 8) {
              mbar_wait(bBe + bs * 8, bph);
              mbar_expect(bBf + bs * 8, 16384);
              tma2d(sB + bs * 16384, &p.tmA[1], bBf + bs * 8, 512, mpair * 256 + rank * 128);
              if (++bs == K1_BST) { bs = 0; bph ^= 1; }
            } else if (newA) {
              mbar_wait(bAe + kc * 8, aph);
              mbar_expect(bAf + kc * 8, 16384);
              tma2d(sA + kc * 16384, &p.tmA[a_sel], bAf + kc * 8, kc * 64, mpair * 256 + rank * 128);
            }
            for (int kk = 0; kk < 2; kk++) {
              mbar_wait(bBe + bs * 8, bph);
              mbar_expect(bBf + bs * 8, 2 * halfbytes);
              tma3d_mc(sB + bs * 16384 + rank * halfbytes, tw, bBf + bs * 8, 0, kc * 64 + kk * 32 + rank * 16, chunk0, 3);
              if (++bs == K1_BST) { bs = 0; bph ^= 1; }
            }
          }
          if (newA) aph ^= 1;
        }
        if (lr0 < S_LEN) {
          wait_flag(&g_flag[lr0 >> 7], K1_FLAG_TARGET);
          wait_flag(&g_flag[lrs >> 7], K1_FLAG_TARGET);
          asm volatile("fence.proxy.async;" ::: "memory");
          for (int kc = 0; kc < 7; kc++) mbar_wait(bAe + kc * 8, aph);
          const uint32_t bytes = (lr0 + 16 - lrs) * (NQKVA * 2);
          mbar_expect(bL, bytes);
          asm volatile("cp.async.bulk.shared::cluster.global.mbarrier::complete_tx::bytes [%0], [%1], %2, [%3];" ::"r"(sA),
                       "l"(g_QKVA + (size_t)lrs * NQKVA), "r"(bytes), "r"(bL) : "memory");
        }
      }
    } else {
      if (warp_g == 9 && blockIdx.x == 0) g_cnt[lane] = 0;
      if (lr0 < S_LEN) {
#pragma unroll 1
        for (int i = warp_g - 9; i < 16; i += 3) {
          const float g = gate_row(lr0 + i, lane, x, gate_w);
          if (lane == 0) asm volatile("st.shared.f32 [%0], %1;" ::"r"(sGate + i * 4), "f"(g) : "memory");
        }
        bar_arrive(2, 256 + 96);
      }
    }
    __syncwarp();
    cluster_sync();
  } else {
    reg_alloc<232>();
    const int wg = warp_g >> 2, warp = warp_g & 3;
    K1State st{0, 0, 0, nullptr, 0, 0, -1};
    float acc[128];
    uint32_t pk[64];
    if (wg == 0) { TS(0, 0); TSC(0, 2); }
#pragma unroll 1
    for (int ji = 0; ji < K1_MAXJOBS; ji++) {
      const uint32_t job = p.jobs[cl][ji];
      if (!(job & 3)) break;
      k1_tile(acc, pk, st, job, sA, sB, bAf, bAe, bBf, bBe, wg, warp, lane, rank);
    }
#pragma unroll
    for (int G = 0; G < 8; G++)
      if (G < st.png) {
        st_v4(st.pp + G * 32, pk[G * 8], pk[G * 8 + 1], pk[G * 8 + 2], pk[G * 8 + 3]);
        st_v4(st.pp + G * 32 + st.pld8, pk[G * 8 + 4], pk[G * 8 + 5], pk[G * 8 + 6], pk[G * 8 + 7]);
      }
    k1_flag(st, lane);
    if (wg == 0) { TS(0, 1); TSC(0, 3); }
    if (lr0 < S_LEN) {
      const int row = lr0 + warp_g * 2;
      if (wg == 0) TS(1, 5);
      bar_sync(2, 256 + 96);
      const float gate0 = __uint_as_float(lds32(sGate + warp_g * 8)), gate1 = __uint_as_float(lds32(sGate + warp_g * 8 + 4));
      mbar_wait(bL, 0);
      if (wg == 0) TS(1, 6);
      local_rows2(row, sA + (row - lrs) * (NQKVA * 2) + lane * 36, lane, gate0, gate1);
    }
    cluster_sync();
  }
}

constexpr int K2_NST = 7;
constexpr int K2_MAXITEMS = 12;
constexpr int K2_SMEM = K2_NST * 32768 + 1024 + 256;
struct alignas(64) K2Params {
  CUtensorMap tmQ, tmK, tmV;
  uint8_t items[NCLUSTER][K2_MAXITEMS];
  uint8_t nitems[NCLUSTER];
};

struct Cursor {
  uint32_t s, ph;
  __device__ __forceinline__ void next() {
    if (++s == K2_NST) { s = 0; ph ^= 1; }
  }
};

__global__ void __cluster_dims__(2, 1, 1) __launch_bounds__(384, 1) k2_attn(const __grid_constant__ K2Params p) {
  extern __shared__ uint8_t smem_raw[];
  const uint32_t sbase = (smem_u32(smem_raw) + 1023) & ~1023u;
  const uint32_t sBar = sbase + K2_NST * 32768;
  const uint32_t bF = sBar, bE = sBar + K2_NST * 8;
  const int tid = threadIdx.x, warp_g = tid >> 5, lane = tid & 31;
  const uint32_t rank = cluster_rank();
  const int cl = blockIdx.x >> 1;
  if (tid == 0) {
    for (int i = 0; i < K2_NST; i++) { mbar_init(bF + i * 8, 1); mbar_init(bE + i * 8, 4); }
    asm volatile("fence.mbarrier_init.release.cluster;" ::: "memory");
    prefetch_tmap(&p.tmQ); prefetch_tmap(&p.tmK); prefetch_tmap(&p.tmV);
  }
  __syncthreads();
  cluster_sync();
  pdl_wait();
  pdl_launch();
  const int nitems = p.nitems[cl];

  if (warp_g >= 8) {
    reg_dealloc<40>();
    if (warp_g == 8) {
      if (lane == 0) {
        Cursor c{0, 1};
        int pcol = 0;
        for (int it = 0; it < nitems; it++) {
          const int item = p.items[cl][it];
          const int h = item >> 3, j = item & 7;
          const int blk = 2 * j + (int)(rank ^ (it & 1));
          const int col = h * 128 + rank * 64;
          const int nb = 2 * j + 2;
          mbar_wait(bE + c.s * 8, c.ph);
          mbar_expect(bF + c.s * 8, 32768);
          tma2d(sbase + c.s * 32768, &p.tmQ, bF + c.s * 8, h * 128, blk * 128);
          tma2d(sbase + c.s * 32768 + 16384, &p.tmQ, bF + c.s * 8, h * 128 + 64, blk * 128);
          c.next();
          for (int n = nb - 1; n >= 0; n--) {
            mbar_wait(bE + c.s * 8, c.ph);
            mbar_expect(bF + c.s * 8, 32768);
            tma2d_mc(sbase + c.s * 32768 + rank * 16384, &p.tmK, bF + c.s * 8, col, n * 128, 3);
            c.next();
            if (n < nb - 1 || it > 0) {
              mbar_wait(bE + c.s * 8, c.ph);
              mbar_expect(bF + c.s * 8, 32768);
              if (n < nb - 1)
                tma2d_mc(sbase + c.s * 32768 + rank * 16384, &p.tmV, bF + c.s * 8, col, (n + 1) * 128, 3);
              else
                tma2d_mc(sbase + c.s * 32768 + rank * 16384, &p.tmV, bF + c.s * 8, pcol, 0, 3);
              c.next();
            }
          }
          pcol = col;
        }
        mbar_wait(bE + c.s * 8, c.ph);
        mbar_expect(bF + c.s * 8, 32768);
        tma2d_mc(sbase + c.s * 32768 + rank * 16384, &p.tmV, bF + c.s * 8, pcol, 0, 3);
      }
    } else if (warp_g == 9 && blockIdx.x == 0) {
      g_flag[lane] = 0;
    }
    __syncwarp();
    cluster_sync();
  } else {
    reg_alloc<232>();
    const int wg = warp_g >> 2, warp = warp_g & 3, q = lane & 3;
    const bool sig = (lane == 0) && (warp < 2);
    const int mybar = 1 + wg, otherbar = 2 - wg;
    const float cl2 = 0.08838834764831845f * 1.4426950408889634f;
    float S[64], O[64];
    uint32_t P[32], Q[32];
    float m0 = 0.f, m1 = 0.f, l0 = 0.f, l1 = 0.f;
    int prev_row = 0, prev_h = 0, prev_single = 0;
    Cursor c{0, 0};
    if (wg == 1) bar_arrive(1, 256);
    if (wg == 0) { TS(1, 0); TSC(1, 2); }

#define TURN_SYNC() bar_sync(mybar, 256)
#define TURN_ARRIVE() bar_arrive(otherbar, 256)
#define RELEASE(cur) do { if (sig) mbar_arrive_cluster(bE + (cur).s * 8, warp); } while (0)
#define ISSUE_PV(cur, first)                                                                                   \
  do {                                                                                                         \
    const uint64_t dv = make_desc(sbase + (cur).s * 32768, 16384, 1024, 1);                                    \
    _Pragma("unroll") for (int t = 0; t < 8; t++)                                                              \
        wgmma_rs_n128<1, 0>(O, P[4 * t], P[4 * t + 1], P[4 * t + 2], P[4 * t + 3], dv + (uint64_t)(t * 128), (t > 0) ? 1 : !(first)); \
  } while (0)
#define ISSUE_QK(cur)                                                                                          \
  do {                                                                                                         \
    const uint64_t dk = make_desc(sbase + (cur).s * 32768, 16, 1024, 1);                                       \
    _Pragma("unroll") for (int t = 0; t < 8; t++)                                                              \
        wgmma_rs_n128<0, 0>(S, Q[4 * t], Q[4 * t + 1], Q[4 * t + 2], Q[4 * t + 3], dk + (uint64_t)((t >> 2) * 1024 + (t & 3) * 2), t > 0); \
  } while (0)
#define EPILOGUE()                                                                                             \
  do {                                                                                                         \
    l0 += __shfl_xor_sync(0xffffffffu, l0, 1);                                                                 \
    l0 += __shfl_xor_sync(0xffffffffu, l0, 2);                                                                 \
    l1 += __shfl_xor_sync(0xffffffffu, l1, 1);                                                                 \
    l1 += __shfl_xor_sync(0xffffffffu, l1, 2);                                                                 \
    const float f0 = gf0 / l0, f1 = gf1 / l1;                                                                  \
    bf16* o0 = g_ctx + (size_t)prev_row * KCAT + prev_h * 128 + q * 8;                                         \
    bf16* o1 = o0 + (size_t)8 * KCAT;                                                                          \
    _Pragma("unroll") for (int G = 0; G < 4; G++) {                                                            \
      st_v4(o0 + G * 32, pack_bf16(O[G * 16 + 0] * f0, O[G * 16 + 1] * f0), pack_bf16(O[G * 16 + 4] * f0, O[G * 16 + 5] * f0), \
            pack_bf16(O[G * 16 + 8] * f0, O[G * 16 + 9] * f0), pack_bf16(O[G * 16 + 12] * f0, O[G * 16 + 13] * f0)); \
      st_v4(o1 + G * 32, pack_bf16(O[G * 16 + 2] * f1, O[G * 16 + 3] * f1), pack_bf16(O[G * 16 + 6] * f1, O[G * 16 + 7] * f1), \
            pack_bf16(O[G * 16 + 10] * f1, O[G * 16 + 11] * f1), pack_bf16(O[G * 16 + 14] * f1, O[G * 16 + 15] * f1)); \
    }                                                                                                          \
  } while (0)

    for (int it = 0; it < nitems; it++) {
      const int item = p.items[cl][it];
      const int h = item >> 3, j = item & 7;
      const int hi = (int)(rank ^ (it & 1));
      const int nblk = 2 * j + 1 + hi;
      {
        const float gf0 = 1.f - g_gate[prev_row], gf1 = 1.f - g_gate[prev_row + 8];
        Cursor cq = c; c.next();
        mbar_wait(bF + cq.s * 8, cq.ph);
        {
          const int r = wg * 64 + warp * 16 + (lane & 7) + ((lane >> 3) & 1) * 8;
          const uint32_t qa = sbase + cq.s * 32768 + r * 128;
#pragma unroll
          for (int t = 0; t < 8; t++)
            ldsm_x4(Q[4 * t], Q[4 * t + 1], Q[4 * t + 2], Q[4 * t + 3], qa + (t >> 2) * 16384 + ((((t & 3) * 2 + (lane >> 4)) ^ (lane & 7)) << 4));
        }
        Cursor ck = c; c.next();
        Cursor cs0 = ck, cs1 = ck, cv = c;
        mbar_wait(bF + ck.s * 8, ck.ph);
        if (it > 0) { mbar_wait(bF + cv.s * 8, cv.ph); c.next(); }
        if (!hi) {
          ck = c; c.next();
          cs1 = c; c.next();
          mbar_wait(bF + ck.s * 8, ck.ph);
          mbar_wait(bF + cs1.s * 8, cs1.ph);
        }
        TURN_SYNC();
        wg_fence();
        ISSUE_QK(ck);
        wg_commit();
        if (it > 0) ISSUE_PV(cv, prev_single);
        wg_commit();
        TURN_ARRIVE();
        RELEASE(cq);
        if (!hi) { RELEASE(cs0); RELEASE(cs1); }
        wg_wait<1>();
        fence_regs(S);
        RELEASE(ck);
        const int r0 = wg * 64 + warp * 16 + (lane >> 2);
#pragma unroll
        for (int jj = 0; jj < 16; jj++) {
          const int cc = jj * 8 + 2 * q;
          if (cc > r0) S[jj * 4 + 0] = -INFINITY;
          if (cc + 1 > r0) S[jj * 4 + 1] = -INFINITY;
          if (cc > r0 + 8) S[jj * 4 + 2] = -INFINITY;
          if (cc + 1 > r0 + 8) S[jj * 4 + 3] = -INFINITY;
        }
        float mx0 = fmaxf(S[0], S[1]), mx1 = fmaxf(S[2], S[3]);
#pragma unroll
        for (int jj = 1; jj < 16; jj++) {
          mx0 = fmaxf(mx0, fmaxf(S[jj * 4 + 0], S[jj * 4 + 1]));
          mx1 = fmaxf(mx1, fmaxf(S[jj * 4 + 2], S[jj * 4 + 3]));
        }
        mx0 = fmaxf(mx0, __shfl_xor_sync(0xffffffffu, mx0, 1));
        mx1 = fmaxf(mx1, __shfl_xor_sync(0xffffffffu, mx1, 1));
        mx0 = fmaxf(mx0, __shfl_xor_sync(0xffffffffu, mx0, 2));
        mx1 = fmaxf(mx1, __shfl_xor_sync(0xffffffffu, mx1, 2));
        m0 = mx0; m1 = mx1;
        const float mc0 = m0 * cl2, mc1 = m1 * cl2;
        float s0 = 0.f, s1 = 0.f;
#pragma unroll
        for (int jj = 0; jj < 16; jj++) {
          S[jj * 4 + 0] = ex2(fmaf(S[jj * 4 + 0], cl2, -mc0));
          S[jj * 4 + 1] = ex2(fmaf(S[jj * 4 + 1], cl2, -mc0));
          S[jj * 4 + 2] = ex2(fmaf(S[jj * 4 + 2], cl2, -mc1));
          S[jj * 4 + 3] = ex2(fmaf(S[jj * 4 + 3], cl2, -mc1));
          s0 += S[jj * 4 + 0] + S[jj * 4 + 1];
          s1 += S[jj * 4 + 2] + S[jj * 4 + 3];
        }
        fence_regs(S);
        wg_wait<0>();
        fence_regs(O);
        fence_regs(P);
        if (it > 0) {
          RELEASE(cv);
          EPILOGUE();
        }
        l0 = s0; l1 = s1;
#pragma unroll
        for (int jj = 0; jj < 16; jj++) {
          P[jj * 2 + 0] = pack_bf16(S[jj * 4 + 0], S[jj * 4 + 1]);
          P[jj * 2 + 1] = pack_bf16(S[jj * 4 + 2], S[jj * 4 + 3]);
        }
      }
#pragma unroll 1
      for (int n = 1; n < nblk; n++) {
        Cursor ck = c; c.next();
        Cursor cv = c; c.next();
        mbar_wait(bF + ck.s * 8, ck.ph);
        mbar_wait(bF + cv.s * 8, cv.ph);
        TURN_SYNC();
        wg_fence();
        ISSUE_QK(ck);
        wg_commit();
        ISSUE_PV(cv, n == 1);
        wg_commit();
        TURN_ARRIVE();
        wg_wait<1>();
        fence_regs(S);
        RELEASE(ck);
        float mx0 = fmaxf(S[0], S[1]), mx1 = fmaxf(S[2], S[3]);
#pragma unroll
        for (int jj = 1; jj < 16; jj++) {
          mx0 = fmaxf(mx0, fmaxf(S[jj * 4 + 0], S[jj * 4 + 1]));
          mx1 = fmaxf(mx1, fmaxf(S[jj * 4 + 2], S[jj * 4 + 3]));
        }
        mx0 = fmaxf(mx0, __shfl_xor_sync(0xffffffffu, mx0, 1));
        mx1 = fmaxf(mx1, __shfl_xor_sync(0xffffffffu, mx1, 1));
        mx0 = fmaxf(mx0, __shfl_xor_sync(0xffffffffu, mx0, 2));
        mx1 = fmaxf(mx1, __shfl_xor_sync(0xffffffffu, mx1, 2));
        mx0 = fmaxf(mx0, m0);
        mx1 = fmaxf(mx1, m1);
        const float sc0 = ex2((m0 - mx0) * cl2), sc1 = ex2((m1 - mx1) * cl2);
        m0 = mx0; m1 = mx1;
        const float mc0 = m0 * cl2, mc1 = m1 * cl2;
        float s0 = 0.f, s1 = 0.f;
#pragma unroll
        for (int jj = 0; jj < 16; jj++) {
          S[jj * 4 + 0] = ex2(fmaf(S[jj * 4 + 0], cl2, -mc0));
          S[jj * 4 + 1] = ex2(fmaf(S[jj * 4 + 1], cl2, -mc0));
          S[jj * 4 + 2] = ex2(fmaf(S[jj * 4 + 2], cl2, -mc1));
          S[jj * 4 + 3] = ex2(fmaf(S[jj * 4 + 3], cl2, -mc1));
          s0 += S[jj * 4 + 0] + S[jj * 4 + 1];
          s1 += S[jj * 4 + 2] + S[jj * 4 + 3];
        }
        l0 = fmaf(l0, sc0, s0);
        l1 = fmaf(l1, sc1, s1);
        fence_regs(S);
        wg_wait<0>();
        fence_regs(O);
        fence_regs(P);
        RELEASE(cv);
#pragma unroll
        for (int jj = 0; jj < 16; jj++) {
          O[jj * 4 + 0] *= sc0;
          O[jj * 4 + 1] *= sc0;
          O[jj * 4 + 2] *= sc1;
          O[jj * 4 + 3] *= sc1;
          P[jj * 2 + 0] = pack_bf16(S[jj * 4 + 0], S[jj * 4 + 1]);
          P[jj * 2 + 1] = pack_bf16(S[jj * 4 + 2], S[jj * 4 + 3]);
        }
      }
      prev_row = (2 * j + hi) * 128 + wg * 64 + warp * 16 + (lane >> 2);
      prev_h = h;
      prev_single = (nblk == 1);
    }
    {
      const float gf0 = 1.f - g_gate[prev_row], gf1 = 1.f - g_gate[prev_row + 8];
      Cursor cv = c;
      mbar_wait(bF + cv.s * 8, cv.ph);
      TURN_SYNC();
      wg_fence();
      ISSUE_PV(cv, prev_single);
      wg_commit();
      if (wg == 0) TURN_ARRIVE();
      wg_wait<0>();
      fence_regs(O);
      EPILOGUE();
    }
    if (wg == 1) { TS(1, 1); TSC(1, 3); }
    cluster_sync();
  }
}

constexpr int K3_NST = 4;
constexpr int K3_STAGE = 16384 + 32768 + 4096;
constexpr int K3_SMEM = K3_NST * K3_STAGE + 1024 + 256;
struct alignas(64) K3Params {
  CUtensorMap tmA, tmW[2], tmWt[2];
};

__global__ void __cluster_dims__(2, 1, 1) __launch_bounds__(384, 1) k3_out(const __grid_constant__ K3Params p, bf16* __restrict__ out) {
  extern __shared__ uint8_t smem_raw[];
  const uint32_t sbase = (smem_u32(smem_raw) + 1023) & ~1023u;
  const uint32_t sBar = sbase + K3_NST * K3_STAGE;
  const uint32_t bF = sBar, bE = sBar + K3_NST * 8;
  const int tid = threadIdx.x, warp_g = tid >> 5, lane = tid & 31;
  const uint32_t rank = cluster_rank();
  const int cl = blockIdx.x >> 1;
  const int mblk = (cl >> 3) * 2 + rank, nhalf = (cl >> 2) & 1, ks = cl & 3;
  const int k0 = ks * 18, k1 = (ks == 3) ? 73 : k0 + 18;
  if (tid == 0) {
    for (int i = 0; i < K3_NST; i++) { mbar_init(bF + i * 8, 1); mbar_init(bE + i * 8, 4); }
    asm volatile("fence.mbarrier_init.release.cluster;" ::: "memory");
  }
  __syncthreads();
  cluster_sync();

  if (warp_g >= 8) {
    reg_dealloc<40>();
    if (warp_g == 8) {
      if (lane == 0) {
        pdl_wait();
        uint32_t s = 0, ph = 1;
        for (int k = k0; k < k1; k++) {
          mbar_wait(bE + s * 8, ph);
          mbar_expect(bF + s * 8, K3_STAGE);
          const uint32_t st = sbase + s * K3_STAGE;
          const int sel = (k >= 64), kr = (sel ? (k - 64) : k) * 64 + rank * 32;
          tma2d(st, &p.tmA, bF + s * 8, k * 64, mblk * 128);
          tma3d_mc(st + 16384 + rank * 16384, &p.tmW[sel], bF + s * 8, 0, kr, nhalf * 4, 3);
          tma2d_mc(st + 49152 + rank * 2048, &p.tmWt[sel], bF + s * 8, 512 + nhalf * 32, kr, 3);
          if (++s == K3_NST) { s = 0; ph ^= 1; }
        }
      }
    }
    __syncwarp();
    cluster_sync();
  } else {
    reg_alloc<232>();
    pdl_wait();
    const int wg = warp_g >> 2, warp = warp_g & 3, q = lane & 3;
    const bool sig = (lane == 0) && (warp < 2);
    float acc[144];
    uint32_t s = 0, ph = 0, prev = 0;
    if (wg == 0) { TS(2, 0); TSC(2, 2); }
    for (int k = k0; k < k1; k++) {
      mbar_wait(bF + s * 8, ph);
      const uint32_t st = sbase + s * K3_STAGE;
      const uint64_t da = make_desc(st + wg * 8192, 16, 1024, 1);
      const uint64_t db = make_desc(st + 16384, 4096, 1024, 1);
      const uint64_t dt = make_desc(st + 49152, 16, 512, 2);
      wg_fence();
#pragma unroll
      for (int t = 0; t < 4; t++) {
        const int sd = (t > 0) || (k > k0);
        wgmma_ss_n256<1, 0>(acc, da + (uint64_t)(t * 2), db + (uint64_t)((t >> 1) * 1024 + (t & 1) * 128), sd);
        wgmma_ss_n32<1, 128>(acc, da + (uint64_t)(t * 2), dt + (uint64_t)(t * 64), sd);
      }
      wg_commit();
      if (k > k0) {
        wg_wait<1>();
        if (sig) mbar_arrive_cluster(bE + prev * 8, warp);
      }
      prev = s;
      if (++s == K3_NST) { s = 0; ph ^= 1; }
    }
    wg_wait<0>();
    fence_regs(acc);
    if (wg == 0) TS(2, 4);
    const int tile = mblk * 2 + nhalf;
    float4* wp = g_part + (size_t)((tile * 4 + ks) * 4) * 9 * 256 + tid;
#pragma unroll
    for (int d = 0; d < 4; d++) {
      if (d != ks) {
#pragma unroll
        for (int i = 0; i < 8; i++)
          __stcg(wp + (d * 9 + i) * 256, make_float4(acc[d * 32 + i * 4], acc[d * 32 + i * 4 + 1], acc[d * 32 + i * 4 + 2], acc[d * 32 + i * 4 + 3]));
        __stcg(wp + (d * 9 + 8) * 256, make_float4(acc[128 + d * 4], acc[128 + d * 4 + 1], acc[128 + d * 4 + 2], acc[128 + d * 4 + 3]));
      }
    }
    __threadfence();
    bar_sync(1, 256);
    if (wg == 0) TS(2, 5);
    if (tid == 0) {
      atomicAdd(&g_cnt[tile], 1u);
      uint32_t v, spins = 0;
      do {
        asm volatile("ld.acquire.gpu.global.u32 %0, [%1];" : "=r"(v) : "l"(&g_cnt[tile]) : "memory");
      } while (v < 4 && ++spins < (1u << 24));
    }
    bar_sync(1, 256);
    if (wg == 0) TS(2, 6);
    float r[36];
#pragma unroll
    for (int d = 0; d < 4; d++) {
      if (d == ks) {
#pragma unroll
        for (int i = 0; i < 32; i++) r[i] = acc[d * 32 + i];
#pragma unroll
        for (int i = 0; i < 4; i++) r[32 + i] = acc[128 + d * 4 + i];
      }
    }
#pragma unroll
    for (int sI = 1; sI < 4; sI++) {
      const int src = (ks + sI) & 3;
      const float4* rp = g_part + (size_t)(((tile * 4 + src) * 4) + ks) * 9 * 256 + tid;
#pragma unroll
      for (int i = 0; i < 9; i++) {
        const float4 v = __ldcg(rp + i * 256);
        r[i * 4] += v.x; r[i * 4 + 1] += v.y; r[i * 4 + 2] += v.z; r[i * 4 + 3] += v.w;
      }
    }
    const int row = mblk * 128 + wg * 64 + warp * 16 + (lane >> 2);
    bf16* o0 = out + (size_t)row * DM + nhalf * 256 + ks * 64 + 8 * q;
#pragma unroll
    for (int G = 0; G < 2; G++) {
      uint32_t a0 = pack_bf16(r[G * 16], r[G * 16 + 1]), a1 = pack_bf16(r[G * 16 + 4], r[G * 16 + 5]);
      uint32_t a2 = pack_bf16(r[G * 16 + 8], r[G * 16 + 9]), a3 = pack_bf16(r[G * 16 + 12], r[G * 16 + 13]);
      uint32_t b0 = pack_bf16(r[G * 16 + 2], r[G * 16 + 3]), b1 = pack_bf16(r[G * 16 + 6], r[G * 16 + 7]);
      uint32_t b2 = pack_bf16(r[G * 16 + 10], r[G * 16 + 11]), b3 = pack_bf16(r[G * 16 + 14], r[G * 16 + 15]);
      quad_transpose(a0, a1, a2, a3, q);
      quad_transpose(b0, b1, b2, b3, q);
      st_v4(o0 + G * 32, a0, a1, a2, a3);
      st_v4(o0 + 8 * DM + G * 32, b0, b1, b2, b3);
    }
    {
      uint32_t t0 = pack_bf16(r[32], r[33]), t1 = pack_bf16(r[34], r[35]), t2 = 0, t3 = 0;
      quad_transpose(t0, t1, t2, t3, q);
      if (q < 2) st_v4(out + (size_t)(row + q * 8) * DM + 512 + nhalf * 32 + ks * 8, t0, t1, t2, t3);
    }
    if (wg == 0) { TS(2, 1); TSC(2, 3); }
    cluster_sync();
  }
}

typedef CUresult (*EncFn)(CUtensorMap*, CUtensorMapDataType, cuuint32_t, void*, const cuuint64_t*, const cuuint64_t*, const cuuint32_t*,
                          const cuuint32_t*, CUtensorMapInterleave, CUtensorMapSwizzle, CUtensorMapL2promotion, CUtensorMapFloatOOBfill);

static void enc2d(EncFn enc, CUtensorMap* m, const void* ptr, uint64_t cols, uint64_t rows, uint32_t bc, uint32_t br,
                  CUtensorMapSwizzle sw = CU_TENSOR_MAP_SWIZZLE_128B) {
  cuuint64_t gd[2] = {cols, rows}, gs[1] = {cols * 2};
  cuuint32_t bx[2] = {bc, br}, es[2] = {1, 1};
  enc(m, CU_TENSOR_MAP_DATA_TYPE_BFLOAT16, 2, const_cast<void*>(ptr), gd, gs, bx, es, CU_TENSOR_MAP_INTERLEAVE_NONE, sw,
      CU_TENSOR_MAP_L2_PROMOTION_L2_256B, CU_TENSOR_MAP_FLOAT_OOB_FILL_NONE);
}
static void enc3d(EncFn enc, CUtensorMap* m, const void* ptr, uint64_t cols, uint64_t rows, uint32_t br, uint32_t bch) {
  cuuint64_t gd[3] = {64, rows, cols / 64}, gs[2] = {cols * 2, 128};
  cuuint32_t bx[3] = {64, br, bch}, es[3] = {1, 1, 1};
  enc(m, CU_TENSOR_MAP_DATA_TYPE_BFLOAT16, 3, const_cast<void*>(ptr), gd, gs, bx, es, CU_TENSOR_MAP_INTERLEAVE_NONE,
      CU_TENSOR_MAP_SWIZZLE_128B, CU_TENSOR_MAP_L2_PROMOTION_L2_256B, CU_TENSOR_MAP_FLOAT_OOB_FILL_NONE);
}

static void build_k1_jobs(K1Params& p) {
  int cnt[NCLUSTER];
  for (int c = 0; c < NCLUSTER; c++) {
    cnt[c] = 0;
    for (int i = 0; i < K1_MAXJOBS; i++) p.jobs[c][i] = 0;
  }
  auto add = [&](int c, int nch, int a_sel, int mp, int w_sel, int chunk0) {
    p.jobs[c][cnt[c]++] = (uint16_t)((nch - 1) | (a_sel << 2) | (mp << 3) | (w_sel << 6) | (chunk0 << 8));
  };
  for (int mp = 0; mp < 8; mp++) {
    for (int g = 0; g < 4; g++)
      for (int i = 0; i < 7; i++) add(g * 8 + mp, 4, 0, mp, g & 1, (2 + 2 * i + (g >> 1)) * 4);
    add(32 + mp, 3, 1, mp, 2, 24);
    add(32 + mp, 4, 1, mp, 3, 0 * 4);
    add(32 + mp, 4, 1, mp, 3, 1 * 4);
    for (int t = 0; t < 4; t++) add(32 + mp, 4, 0, mp, t & 1, (t >> 1) * 4);
    for (int g = 0; g < 2; g++) {
      for (int i = 0; i < 3; i++) add((5 + g) * 8 + mp, 4, 1, mp, 2, (g * 3 + i) * 4);
      for (int i = 0; i < 3; i++) add((5 + g) * 8 + mp, 4, 1, mp, 3, (2 + g * 3 + i) * 4);
    }
    for (int i = 0; i < 6; i++) add(56 + mp, 4, 1, mp, 3, (8 + i) * 4);
    add(64 + mp / 4, 4, 1, mp, 3, 14 * 4);
    if (mp & 1) add(64 + mp / 4, 4, 1, mp, 3, 15 * 4);
    else add(56 + mp, 4, 1, mp, 3, 15 * 4);
  }
  for (int cc = 0; cc < NCLUSTER; cc++)
    for (int i = 0; i < cnt[cc]; i++) {
      const int key = p.jobs[cc][i] & 0x3C;
      if (i == 0 || (p.jobs[cc][i - 1] & 0x3C) != key) p.jobs[cc][i] |= (1 << 14);
      if (i == cnt[cc] - 1 || (p.jobs[cc][i + 1] & 0x3C) != key) p.jobs[cc][i] |= (1 << 15);
    }
}

#define K2_HG 32
static void build_k2_items(K2Params& p) {
  double load[NCLUSTER];
  for (int c = 0; c < NCLUSTER; c++) { load[c] = 0; p.nitems[c] = 0; }
  for (int hg = 32 / K2_HG - 1; hg >= 0; hg--)
    for (int j = 7; j >= 0; j--)
      for (int hh = K2_HG - 1; hh >= 0; hh--) {
        const int h = hg * K2_HG + hh;
        int best = 0;
        for (int c = 1; c < NCLUSTER; c++)
          if (load[c] < load[best] - 1e-9) best = c;
        p.items[best][p.nitems[best]++] = (uint8_t)(h * 8 + j);
        load[best] += 2.0 * j + 1.5 + 0.5;
      }
}

extern "C" void kernel_launch(void* const* d_in, const int* in_sizes, int n_in, void* d_out, int out_size) {
  const bf16* x = (const bf16*)d_in[0];
  const bf16* wqkv = (const bf16*)d_in[1];
  const bf16* wo = (const bf16*)d_in[2];
  const bf16* ckv = (const bf16*)d_in[4];
  const bf16* w_q = (const bf16*)d_in[5];
  const bf16* w_uk = (const bf16*)d_in[6];
  const bf16* w_uv = (const bf16*)d_in[7];
  const bf16* w_o = (const bf16*)d_in[8];
  const bf16* gate_w = (const bf16*)d_in[9];

  EncFn enc = nullptr;
  cudaDriverEntryPointQueryResult qr;
  cudaGetDriverEntryPoint("cuTensorMapEncodeTiled", (void**)&enc, cudaEnableDefault, &qr);
  void *pQ, *pK, *pV, *pCtx;
  cudaGetSymbolAddress(&pQ, g_Q);
  cudaGetSymbolAddress(&pK, g_K);
  cudaGetSymbolAddress(&pV, g_V);
  cudaGetSymbolAddress(&pCtx, g_ctx);

  static K1Params p1;
  static K2Params p2;
  static K3Params p3;
  enc2d(enc, &p1.tmA[0], ckv, DC, S_LEN, 64, 128);
  enc2d(enc, &p1.tmA[1], x, DM, S_LEN, 64, 128);
  enc3d(enc, &p1.tmW[0], w_uk, HDIM, DC, 16, 4);
  enc3d(enc, &p1.tmW[1], w_uv, HDIM, DC, 16, 4);
  enc3d(enc, &p1.tmW[2], wqkv, NQKVA, DM, 16, 4);
  enc3d(enc, &p1.tmW[3], w_q, HDIM, DM, 16, 4);
  build_k1_jobs(p1);
  enc2d(enc, &p2.tmQ, pQ, HDIM, S_LEN, 64, 128);
  enc2d(enc, &p2.tmK, pK, HDIM, S_LEN, 64, 128);
  enc2d(enc, &p2.tmV, pV, HDIM, S_LEN, 64, 128);
  build_k2_items(p2);
  enc2d(enc, &p3.tmA, pCtx, KCAT, S_LEN, 64, 128);
  enc3d(enc, &p3.tmW[0], w_o, DM, HDIM, 32, 4);
  enc3d(enc, &p3.tmW[1], wo, DM, DM, 32, 4);
  enc2d(enc, &p3.tmWt[0], w_o, DM, HDIM, 32, 32, CU_TENSOR_MAP_SWIZZLE_64B);
  enc2d(enc, &p3.tmWt[1], wo, DM, DM, 32, 32, CU_TENSOR_MAP_SWIZZLE_64B);

  cudaFuncSetAttribute(k1_proj, cudaFuncAttributeMaxDynamicSharedMemorySize, K1_SMEM);
  cudaFuncSetAttribute(k2_attn, cudaFuncAttributeMaxDynamicSharedMemorySize, K2_SMEM);
  cudaFuncSetAttribute(k3_out, cudaFuncAttributeMaxDynamicSharedMemorySize, K3_SMEM);

  k1_proj<<<NCLUSTER * 2, 384, K1_SMEM>>>(p1, x, gate_w);
  cudaLaunchConfig_t cfg = {};
  cudaLaunchAttribute at[1];
  at[0].id = cudaLaunchAttributeProgrammaticStreamSerialization;
  at[0].val.programmaticStreamSerializationAllowed = 1;
  cfg.attrs = at;
  cfg.numAttrs = 1;
  cfg.stream = cudaStreamPerThread;
  cfg.blockDim = dim3(384);
  cfg.gridDim = dim3(NCLUSTER * 2);
  cfg.dynamicSmemBytes = K2_SMEM;
  cudaLaunchKernelEx(&cfg, k2_attn, p2);
  cfg.gridDim = dim3(128);
  cfg.dynamicSmemBytes = K3_SMEM;
  cudaLaunchKernelEx(&cfg, k3_out, p3, (bf16*)d_out);
}
```

```cpp
#include <cuda_runtime.h>
#include <cuda_bf16.h>
#include <cuda.h>
#include <stdint.h>

typedef __nv_bfloat16 bf16;

constexpr int S_LEN = 2048, DM = 576, DC = 512, HDIM = 4096, NQKVA = 1728, KCAT = 4672;
constexpr int NCLUSTER = 66;

__device__ __align__(1024) bf16 g_Q[S_LEN * HDIM];
__device__ __align__(1024) bf16 g_K[S_LEN * HDIM];
__device__ __align__(1024) bf16 g_V[S_LEN * HDIM];
__device__ __align__(1024) bf16 g_QKVA[S_LEN * NQKVA + 64];
__device__ __align__(1024) bf16 g_ctx[S_LEN * KCAT];
__device__ float g_gate[S_LEN];
__device__ __align__(1024) float4 g_part[32 * 4 * 4 * 9 * 256];
__device__ unsigned int g_cnt[32];
__device__ unsigned int g_flag[32];
__device__ unsigned int g_rdy[32];

__device__ __forceinline__ uint32_t smem_u32(const void* p) { return (uint32_t)__cvta_generic_to_shared(p); }
__device__ __forceinline__ void mbar_init(uint32_t a, uint32_t c) {
  asm volatile("mbarrier.init.shared::cta.b64 [%0], %1;" ::"r"(a), "r"(c));
}
__device__ __forceinline__ void mbar_expect(uint32_t a, uint32_t b) {
  asm volatile("mbarrier.arrive.expect_tx.shared::cta.b64 _, [%0], %1;" ::"r"(a), "r"(b) : "memory");
}
#define TS(k, i)
#define TSC(k, i)
#define TSM(k)
#define SPIN_LIMIT "4194304"
__device__ __forceinline__ void mbar_wait(uint32_t a, uint32_t parity) {
  asm volatile(
      "{\n.reg .pred p;\n.reg .u32 n;\n"
      "mbarrier.try_wait.parity.shared::cta.b64 p, [%0], %1;\n"
      "@p bra DONE;\n"
      "mov.u32 n, 0;\n"
      "LOOP:\n"
      "mbarrier.try_wait.parity.shared::cta.b64 p, [%0], %1;\n"
      "@p bra DONE;\n"
      "add.u32 n, n, 1;\n"
      "setp.lt.u32 p, n, " SPIN_LIMIT ";\n"
      "@p bra LOOP;\n"
      "DONE:\n}" ::"r"(a), "r"(parity) : "memory");
}
__device__ __forceinline__ void mbar_arrive(uint32_t a) {
  asm volatile("mbarrier.arrive.shared::cta.b64 _, [%0];" ::"r"(a) : "memory");
}
__device__ __forceinline__ void mbar_arrive_cluster(uint32_t a, uint32_t cta) {
  asm volatile("{\n.reg .b32 r;\nmapa.shared::cluster.u32 r, %0, %1;\nmbarrier.arrive.shared::cluster.b64 _, [r];\n}" ::"r"(a),
               "r"(cta) : "memory");
}
__device__ __forceinline__ void tma2d(uint32_t dst, const CUtensorMap* m, uint32_t bar, int c0, int c1) {
  asm volatile("cp.async.bulk.tensor.2d.shared::cluster.global.mbarrier::complete_tx::bytes [%0], [%1, {%3, %4}], [%2];" ::"r"(dst),
               "l"(m), "r"(bar), "r"(c0), "r"(c1) : "memory");
}
__device__ __forceinline__ void tma2d_mc(uint32_t dst, const CUtensorMap* m, uint32_t bar, int c0, int c1, uint16_t mask) {
  asm volatile(
      "cp.async.bulk.tensor.2d.shared::cluster.global.mbarrier::complete_tx::bytes.multicast::cluster [%0], [%1, {%3, %4}], [%2], %5;" ::"r"(dst),
      "l"(m), "r"(bar), "r"(c0), "r"(c1), "h"(mask) : "memory");
}
__device__ __forceinline__ void tma3d_mc(uint32_t dst, const CUtensorMap* m, uint32_t bar, int c0, int c1, int c2, uint16_t mask) {
  asm volatile(
      "cp.async.bulk.tensor.3d.shared::cluster.global.mbarrier::complete_tx::bytes.multicast::cluster [%0], [%1, {%3, %4, %5}], [%2], %6;" ::"r"(dst),
      "l"(m), "r"(bar), "r"(c0), "r"(c1), "r"(c2), "h"(mask) : "memory");
}
__device__ __forceinline__ void tma3d(uint32_t dst, const CUtensorMap* m, uint32_t bar, int c0, int c1, int c2) {
  asm volatile(
      "cp.async.bulk.tensor.3d.shared::cluster.global.mbarrier::complete_tx::bytes [%0], [%1, {%3, %4, %5}], [%2];" ::"r"(dst),
      "l"(m), "r"(bar), "r"(c0), "r"(c1), "r"(c2) : "memory");
}
__device__ __forceinline__ void tma_pf2d(const CUtensorMap* m, int c0, int c1) {
  asm volatile("cp.async.bulk.prefetch.tensor.2d.L2.global [%0, {%1, %2}];" ::"l"(m), "r"(c0), "r"(c1) : "memory");
}
__device__ __forceinline__ void tma_pf3d(const CUtensorMap* m, int c0, int c1, int c2) {
  asm volatile("cp.async.bulk.prefetch.tensor.3d.L2.global [%0, {%1, %2, %3}];" ::"l"(m), "r"(c0), "r"(c1), "r"(c2) : "memory");
}
__device__ __forceinline__ void prefetch_tmap(const CUtensorMap* m) {
  asm volatile("prefetch.tensormap [%0];" ::"l"(m) : "memory");
}
__device__ __forceinline__ void cluster_sync() {
  asm volatile("barrier.cluster.arrive.aligned;\nbarrier.cluster.wait.aligned;" ::: "memory");
}
__device__ __forceinline__ uint32_t cluster_rank() {
  uint32_t r;
  asm volatile("mov.u32 %0, %%cluster_ctarank;" : "=r"(r));
  return r;
}
__device__ __forceinline__ void pdl_wait() { asm volatile("griddepcontrol.wait;" ::: "memory"); }
__device__ __forceinline__ void pdl_launch() { asm volatile("griddepcontrol.launch_dependents;" ::: "memory"); }
__device__ __forceinline__ void ldsm_x4(uint32_t& r0, uint32_t& r1, uint32_t& r2, uint32_t& r3, uint32_t addr) {
  asm volatile("ldmatrix.sync.aligned.m8n8.x4.shared.b16 {%0, %1, %2, %3}, [%4];" : "=r"(r0), "=r"(r1), "=r"(r2), "=r"(r3) : "r"(addr) : "memory");
}
__device__ __forceinline__ void wg_fence() { asm volatile("wgmma.fence.sync.aligned;" ::: "memory"); }
__device__ __forceinline__ void wg_commit() { asm volatile("wgmma.commit_group.sync.aligned;" ::: "memory"); }
template <int N>
__device__ __forceinline__ void wg_wait() { asm volatile("wgmma.wait_group.sync.aligned %0;" ::"n"(N) : "memory"); }
template <int N>
__device__ __forceinline__ void reg_alloc() { asm volatile("setmaxnreg.inc.sync.aligned.u32 %0;" ::"n"(N)); }
template <int N>
__device__ __forceinline__ void reg_dealloc() { asm volatile("setmaxnreg.dec.sync.aligned.u32 %0;" ::"n"(N)); }
__device__ __forceinline__ void bar_sync(int id, int n) { asm volatile("bar.sync %0, %1;" ::"r"(id), "r"(n) : "memory"); }
__device__ __forceinline__ void bar_arrive(int id, int n) { asm volatile("bar.arrive %0, %1;" ::"r"(id), "r"(n) : "memory"); }
template <int NT>
__device__ __forceinline__ void fence_regs(float (&d)[NT]) {
#pragma unroll
  for (int i = 0; i < NT; i++) asm volatile("" : "+f"(d[i])::"memory");
}
template <int NT>
__device__ __forceinline__ void fence_regs(uint32_t (&d)[NT]) {
#pragma unroll
  for (int i = 0; i < NT; i++) asm volatile("" : "+r"(d[i])::"memory");
}
__device__ __forceinline__ uint64_t make_desc(uint32_t saddr, uint32_t lbo, uint32_t sbo, uint32_t layout) {
  return (uint64_t)((saddr & 0x3FFFF) >> 4) | ((uint64_t)(lbo >> 4) << 16) | ((uint64_t)(sbo >> 4) << 32) | ((uint64_t)layout << 62);
}
__device__ __forceinline__ uint32_t pack_bf16(float lo, float hi) {
  uint32_t r;
  asm("cvt.rn.bf16x2.f32 %0, %1, %2;" : "=r"(r) : "f"(hi), "f"(lo));
  return r;
}
__device__ __forceinline__ float ex2(float x) {
  float r;
  asm("ex2.approx.ftz.f32 %0, %1;" : "=f"(r) : "f"(x));
  return r;
}
__device__ __forceinline__ void st_v4(void* p, uint32_t a, uint32_t b, uint32_t c, uint32_t d) {
#define ST_MOD ""
  asm volatile("st.global" ST_MOD ".v4.b32 [%0], {%1, %2, %3, %4};" ::"l"(p), "r"(a), "r"(b), "r"(c), "r"(d) : "memory");
}
__device__ __forceinline__ float bf_lo(uint32_t v) { return __uint_as_float(v << 16); }
__device__ __forceinline__ float bf_hi(uint32_t v) { return __uint_as_float(v & 0xFFFF0000u); }

__device__ __forceinline__ void quad_transpose(uint32_t& a0, uint32_t& a1, uint32_t& a2, uint32_t& a3, int q) {
  const bool o1 = q & 1, o2 = q & 2;
  uint32_t t0 = o1 ? a0 : a1, t1 = o1 ? a2 : a3;
  t0 = __shfl_xor_sync(0xffffffffu, t0, 1);
  t1 = __shfl_xor_sync(0xffffffffu, t1, 1);
  if (o1) { a0 = t0; a2 = t1; } else { a1 = t0; a3 = t1; }
  t0 = o2 ? a0 : a2;
  t1 = o2 ? a1 : a3;
  t0 = __shfl_xor_sync(0xffffffffu, t0, 2);
  t1 = __shfl_xor_sync(0xffffffffu, t1, 2);
  if (o2) { a0 = t0; a1 = t1; } else { a2 = t0; a3 = t1; }
}

template<int TB, int OFF, int NT>
__device__ __forceinline__ void wgmma_ss_n256(float (&d)[NT], uint64_t da, uint64_t db, int scale_d) {
  asm volatile("{\n.reg .pred p;\nsetp.ne.b32 p, %130, 0;\n"
    "wgmma.mma_async.sync.aligned.m64n256k16.f32.bf16.bf16 {%0, %1, %2, %3, %4, %5, %6, %7, %8, %9, %10, %11, %12, %13, %14, %15, %16, %17, %18, %19, %20, %21, %22, %23, %24, %25, %26, %27, %28, %29, %30, %31, %32, %33, %34, %35, %36, %37, %38, %39, %40, %41, %42, %43, %44, %45, %46, %47, %48, %49, %50, %51, %52, %53, %54, %55, %56, %57, %58, %59, %60, %61, %62, %63, %64, %65, %66, %67, %68, %69, %70, %71, %72, %73, %74, %75, %76, %77, %78, %79, %80, %81, %82, %83, %84, %85, %86, %87, %88, %89, %90, %91, %92, %93, %94, %95, %96, %97, %98, %99, %100, %101, %102, %103, %104, %105, %106, %107, %108, %109, %110, %111, %112, %113, %114, %115, %116, %117, %118, %119, %120, %121, %122, %123, %124, %125, %126, %127}, %128, %129, p, 1, 1, 0, %131;\n}\n"
    : "+f"(d[OFF+0]), "+f"(d[OFF+1]), "+f"(d[OFF+2]), "+f"(d[OFF+3]), "+f"(d[OFF+4]), "+f"(d[OFF+5]), "+f"(d[OFF+6]), "+f"(d[OFF+7]), "+f"(d[OFF+8]), "+f"(d[OFF+9]), "+f"(d[OFF+10]), "+f"(d[OFF+11]), "+f"(d[OFF+12]), "+f"(d[OFF+13]), "+f"(d[OFF+14]), "+f"(d[OFF+15]), "+f"(d[OFF+16]), "+f"(d[OFF+17]), "+f"(d[OFF+18]), "+f"(d[OFF+19]), "+f"(d[OFF+20]), "+f"(d[OFF+21]), "+f"(d[OFF+22]), "+f"(d[OFF+23]), "+f"(d[OFF+24]), "+f"(d[OFF+25]), "+f"(d[OFF+26]), "+f"(d[OFF+27]), "+f"(d[OFF+28]), "+f"(d[OFF+29]), "+f"(d[OFF+30]), "+f"(d[OFF+31]), "+f"(d[OFF+32]), "+f"(d[OFF+33]), "+f"(d[OFF+34]), "+f"(d[OFF+35]), "+f"(d[OFF+36]), "+f"(d[OFF+37]), "+f"(d[OFF+38]), "+f"(d[OFF+39]), "+f"(d[OFF+40]), "+f"(d[OFF+41]), "+f"(d[OFF+42]), "+f"(d[OFF+43]), "+f"(d[OFF+44]), "+f"(d[OFF+45]), "+f"(d[OFF+46]), "+f"(d[OFF+47]), "+f"(d[OFF+48]), "+f"(d[OFF+49]), "+f"(d[OFF+50]), "+f"(d[OFF+51]), "+f"(d[OFF+52]), "+f"(d[OFF+53]), "+f"(d[OFF+54]), "+f"(d[OFF+55]), "+f"(d[OFF+56]), "+f"(d[OFF+57]), "+f"(d[OFF+58]), "+f"(d[OFF+59]), "+f"(d[OFF+60]), "+f"(d[OFF+61]), "+f"(d[OFF+62]), "+f"(d[OFF+63]), "+f"(d[OFF+64]), "+f"(d[OFF+65]), "+f"(d[OFF+66]), "+f"(d[OFF+67]), "+f"(d[OFF+68]), "+f"(d[OFF+69]), "+f"(d[OFF+70]), "+f"(d[OFF+71]), "+f"(d[OFF+72]), "+f"(d[OFF+73]), "+f"(d[OFF+74]), "+f"(d[OFF+75]), "+f"(d[OFF+76]), "+f"(d[OFF+77]), "+f"(d[OFF+78]), "+f"(d[OFF+79]), "+f"(d[OFF+80]), "+f"(d[OFF+81]), "+f"(d[OFF+82]), "+f"(d[OFF+83]), "+f"(d[OFF+84]), "+f"(d[OFF+85]), "+f"(d[OFF+86]), "+f"(d[OFF+87]), "+f"(d[OFF+88]), "+f"(d[OFF+89]), "+f"(d[OFF+90]), "+f"(d[OFF+91]), "+f"(d[OFF+92]), "+f"(d[OFF+93]), "+f"(d[OFF+94]), "+f"(d[OFF+95]), "+f"(d[OFF+96]), "+f"(d[OFF+97]), "+f"(d[OFF+98]), "+f"(d[OFF+99]), "+f"(d[OFF+100]), "+f"(d[OFF+101]), "+f"(d[OFF+102]), "+f"(d[OFF+103]), "+f"(d[OFF+104]), "+f"(d[OFF+105]), "+f"(d[OFF+106]), "+f"(d[OFF+107]), "+f"(d[OFF+108]), "+f"(d[OFF+109]), "+f"(d[OFF+110]), "+f"(d[OFF+111]), "+f"(d[OFF+112]), "+f"(d[OFF+113]), "+f"(d[OFF+114]), "+f"(d[OFF+115]), "+f"(d[OFF+116]), "+f"(d[OFF+117]), "+f"(d[OFF+118]), "+f"(d[OFF+119]), "+f"(d[OFF+120]), "+f"(d[OFF+121]), "+f"(d[OFF+122]), "+f"(d[OFF+123]), "+f"(d[OFF+124]), "+f"(d[OFF+125]), "+f"(d[OFF+126]), "+f"(d[OFF+127])
    : "l"(da), "l"(db), "r"(scale_d), "n"(TB));
}
template<int TB, int OFF, int NT>
__device__ __forceinline__ void wgmma_ss_n192(float (&d)[NT], uint64_t da, uint64_t db, int scale_d) {
  asm volatile("{\n.reg .pred p;\nsetp.ne.b32 p, %98, 0;\n"
    "wgmma.mma_async.sync.aligned.m64n192k16.f32.bf16.bf16 {%0, %1, %2, %3, %4, %5, %6, %7, %8, %9, %10, %11, %12, %13, %14, %15, %16, %17, %18, %19, %20, %21, %22, %23, %24, %25, %26, %27, %28, %29, %30, %31, %32, %33, %34, %35, %36, %37, %38, %39, %40, %41, %42, %43, %44, %45, %46, %47, %48, %49, %50, %51, %52, %53, %54, %55, %56, %57, %58, %59, %60, %61, %62, %63, %64, %65, %66, %67, %68, %69, %70, %71, %72, %73, %74, %75, %76, %77, %78, %79, %80, %81, %82, %83, %84, %85, %86, %87, %88, %89, %90, %91, %92, %93, %94, %95}, %96, %97, p, 1, 1, 0, %99;\n}\n"
    : "+f"(d[OFF+0]), "+f"(d[OFF+1]), "+f"(d[OFF+2]), "+f"(d[OFF+3]), "+f"(d[OFF+4]), "+f"(d[OFF+5]), "+f"(d[OFF+6]), "+f"(d[OFF+7]), "+f"(d[OFF+8]), "+f"(d[OFF+9]), "+f"(d[OFF+10]), "+f"(d[OFF+11]), "+f"(d[OFF+12]), "+f"(d[OFF+13]), "+f"(d[OFF+14]), "+f"(d[OFF+15]), "+f"(d[OFF+16]), "+f"(d[OFF+17]), "+f"(d[OFF+18]), "+f"(d[OFF+19]), "+f"(d[OFF+20]), "+f"(d[OFF+21]), "+f"(d[OFF+22]), "+f"(d[OFF+23]), "+f"(d[OFF+24]), "+f"(d[OFF+25]), "+f"(d[OFF+26]), "+f"(d[OFF+27]), "+f"(d[OFF+28]), "+f"(d[OFF+29]), "+f"(d[OFF+30]), "+f"(d[OFF+31]), "+f"(d[OFF+32]), "+f"(d[OFF+33]), "+f"(d[OFF+34]), "+f"(d[OFF+35]), "+f"(d[OFF+36]), "+f"(d[OFF+37]), "+f"(d[OFF+38]), "+f"(d[OFF+39]), "+f"(d[OFF+40]), "+f"(d[OFF+41]), "+f"(d[OFF+42]), "+f"(d[OFF+43]), "+f"(d[OFF+44]), "+f"(d[OFF+45]), "+f"(d[OFF+46]), "+f"(d[OFF+47]), "+f"(d[OFF+48]), "+f"(d[OFF+49]), "+f"(d[OFF+50]), "+f"(d[OFF+51]), "+f"(d[OFF+52]), "+f"(d[OFF+53]), "+f"(d[OFF+54]), "+f"(d[OFF+55]), "+f"(d[OFF+56]), "+f"(d[OFF+57]), "+f"(d[OFF+58]), "+f"(d[OFF+59]), "+f"(d[OFF+60]), "+f"(d[OFF+61]), "+f"(d[OFF+62]), "+f"(d[OFF+63]), "+f"(d[OFF+64]), "+f"(d[OFF+65]), "+f"(d[OFF+66]), "+f"(d[OFF+67]), "+f"(d[OFF+68]), "+f"(d[OFF+69]), "+f"(d[OFF+70]), "+f"(d[OFF+71]), "+f"(d[OFF+72]), "+f"(d[OFF+73]), "+f"(d[OFF+74]), "+f"(d[OFF+75]), "+f"(d[OFF+76]), "+f"(d[OFF+77]), "+f"(d[OFF+78]), "+f"(d[OFF+79]), "+f"(d[OFF+80]), "+f"(d[OFF+81]), "+f"(d[OFF+82]), "+f"(d[OFF+83]), "+f"(d[OFF+84]), "+f"(d[OFF+85]), "+f"(d[OFF+86]), "+f"(d[OFF+87]), "+f"(d[OFF+88]), "+f"(d[OFF+89]), "+f"(d[OFF+90]), "+f"(d[OFF+91]), "+f"(d[OFF+92]), "+f"(d[OFF+93]), "+f"(d[OFF+94]), "+f"(d[OFF+95])
    : "l"(da), "l"(db), "r"(scale_d), "n"(TB));
}
template<int TB, int OFF, int NT>
__device__ __forceinline__ void wgmma_ss_n128(float (&d)[NT], uint64_t da, uint64_t db, int scale_d) {
  asm volatile("{\n.reg .pred p;\nsetp.ne.b32 p, %66, 0;\n"
    "wgmma.mma_async.sync.aligned.m64n128k16.f32.bf16.bf16 {%0, %1, %2, %3, %4, %5, %6, %7, %8, %9, %10, %11, %12, %13, %14, %15, %16, %17, %18, %19, %20, %21, %22, %23, %24, %25, %26, %27, %28, %29, %30, %31, %32, %33, %34, %35, %36, %37, %38, %39, %40, %41, %42, %43, %44, %45, %46, %47, %48, %49, %50, %51, %52, %53, %54, %55, %56, %57, %58, %59, %60, %61, %62, %63}, %64, %65, p, 1, 1, 0, %67;\n}\n"
    : "+f"(d[OFF+0]), "+f"(d[OFF+1]), "+f"(d[OFF+2]), "+f"(d[OFF+3]), "+f"(d[OFF+4]), "+f"(d[OFF+5]), "+f"(d[OFF+6]), "+f"(d[OFF+7]), "+f"(d[OFF+8]), "+f"(d[OFF+9]), "+f"(d[OFF+10]), "+f"(d[OFF+11]), "+f"(d[OFF+12]), "+f"(d[OFF+13]), "+f"(d[OFF+14]), "+f"(d[OFF+15]), "+f"(d[OFF+16]), "+f"(d[OFF+17]), "+f"(d[OFF+18]), "+f"(d[OFF+19]), "+f"(d[OFF+20]), "+f"(d[OFF+21]), "+f"(d[OFF+22]), "+f"(d[OFF+23]), "+f"(d[OFF+24]), "+f"(d[OFF+25]), "+f"(d[OFF+26]), "+f"(d[OFF+27]), "+f"(d[OFF+28]), "+f"(d[OFF+29]), "+f"(d[OFF+30]), "+f"(d[OFF+31]), "+f"(d[OFF+32]), "+f"(d[OFF+33]), "+f"(d[OFF+34]), "+f"(d[OFF+35]), "+f"(d[OFF+36]), "+f"(d[OFF+37]), "+f"(d[OFF+38]), "+f"(d[OFF+39]), "+f"(d[OFF+40]), "+f"(d[OFF+41]), "+f"(d[OFF+42]), "+f"(d[OFF+43]), "+f"(d[OFF+44]), "+f"(d[OFF+45]), "+f"(d[OFF+46]), "+f"(d[OFF+47]), "+f"(d[OFF+48]), "+f"(d[OFF+49]), "+f"(d[OFF+50]), "+f"(d[OFF+51]), "+f"(d[OFF+52]), "+f"(d[OFF+53]), "+f"(d[OFF+54]), "+f"(d[OFF+55]), "+f"(d[OFF+56]), "+f"(d[OFF+57]), "+f"(d[OFF+58]), "+f"(d[OFF+59]), "+f"(d[OFF+60]), "+f"(d[OFF+61]), "+f"(d[OFF+62]), "+f"(d[OFF+63])
    : "l"(da), "l"(db), "r"(scale_d), "n"(TB));
}
template<int TB, int OFF, int NT>
__device__ __forceinline__ void wgmma_ss_n32(float (&d)[NT], uint64_t da, uint64_t db, int scale_d) {
  asm volatile("{\n.reg .pred p;\nsetp.ne.b32 p, %18, 0;\n"
    "wgmma.mma_async.sync.aligned.m64n32k16.f32.bf16.bf16 {%0, %1, %2, %3, %4, %5, %6, %7, %8, %9, %10, %11, %12, %13, %14, %15}, %16, %17, p, 1, 1, 0, %19;\n}\n"
    : "+f"(d[OFF+0]), "+f"(d[OFF+1]), "+f"(d[OFF+2]), "+f"(d[OFF+3]), "+f"(d[OFF+4]), "+f"(d[OFF+5]), "+f"(d[OFF+6]), "+f"(d[OFF+7]), "+f"(d[OFF+8]), "+f"(d[OFF+9]), "+f"(d[OFF+10]), "+f"(d[OFF+11]), "+f"(d[OFF+12]), "+f"(d[OFF+13]), "+f"(d[OFF+14]), "+f"(d[OFF+15])
    : "l"(da), "l"(db), "r"(scale_d), "n"(TB));
}
template<int TB, int OFF, int NT>
__device__ __forceinline__ void wgmma_rs_n128(float (&d)[NT], uint32_t a0, uint32_t a1, uint32_t a2, uint32_t a3, uint64_t db, int scale_d) {
  asm volatile("{\n.reg .pred p;\nsetp.ne.b32 p, %69, 0;\n"
    "wgmma.mma_async.sync.aligned.m64n128k16.f32.bf16.bf16 {%0, %1, %2, %3, %4, %5, %6, %7, %8, %9, %10, %11, %12, %13, %14, %15, %16, %17, %18, %19, %20, %21, %22, %23, %24, %25, %26, %27, %28, %29, %30, %31, %32, %33, %34, %35, %36, %37, %38, %39, %40, %41, %42, %43, %44, %45, %46, %47, %48, %49, %50, %51, %52, %53, %54, %55, %56, %57, %58, %59, %60, %61, %62, %63}, {%64, %65, %66, %67}, %68, p, 1, 1, %70;\n}\n"
    : "+f"(d[OFF+0]), "+f"(d[OFF+1]), "+f"(d[OFF+2]), "+f"(d[OFF+3]), "+f"(d[OFF+4]), "+f"(d[OFF+5]), "+f"(d[OFF+6]), "+f"(d[OFF+7]), "+f"(d[OFF+8]), "+f"(d[OFF+9]), "+f"(d[OFF+10]), "+f"(d[OFF+11]), "+f"(d[OFF+12]), "+f"(d[OFF+13]), "+f"(d[OFF+14]), "+f"(d[OFF+15]), "+f"(d[OFF+16]), "+f"(d[OFF+17]), "+f"(d[OFF+18]), "+f"(d[OFF+19]), "+f"(d[OFF+20]), "+f"(d[OFF+21]), "+f"(d[OFF+22]), "+f"(d[OFF+23]), "+f"(d[OFF+24]), "+f"(d[OFF+25]), "+f"(d[OFF+26]), "+f"(d[OFF+27]), "+f"(d[OFF+28]), "+f"(d[OFF+29]), "+f"(d[OFF+30]), "+f"(d[OFF+31]), "+f"(d[OFF+32]), "+f"(d[OFF+33]), "+f"(d[OFF+34]), "+f"(d[OFF+35]), "+f"(d[OFF+36]), "+f"(d[OFF+37]), "+f"(d[OFF+38]), "+f"(d[OFF+39]), "+f"(d[OFF+40]), "+f"(d[OFF+41]), "+f"(d[OFF+42]), "+f"(d[OFF+43]), "+f"(d[OFF+44]), "+f"(d[OFF+45]), "+f"(d[OFF+46]), "+f"(d[OFF+47]), "+f"(d[OFF+48]), "+f"(d[OFF+49]), "+f"(d[OFF+50]), "+f"(d[OFF+51]), "+f"(d[OFF+52]), "+f"(d[OFF+53]), "+f"(d[OFF+54]), "+f"(d[OFF+55]), "+f"(d[OFF+56]), "+f"(d[OFF+57]), "+f"(d[OFF+58]), "+f"(d[OFF+59]), "+f"(d[OFF+60]), "+f"(d[OFF+61]), "+f"(d[OFF+62]), "+f"(d[OFF+63])
    : "r"(a0), "r"(a1), "r"(a2), "r"(a3), "l"(db), "r"(scale_d), "n"(TB));
}
template<int TB, int OFF, int NT>
__device__ __forceinline__ void wgmma_rs_n64(float (&d)[NT], uint32_t a0, uint32_t a1, uint32_t a2, uint32_t a3, uint64_t db, int scale_d) {
  asm volatile("{\n.reg .pred p;\nsetp.ne.b32 p, %37, 0;\n"
    "wgmma.mma_async.sync.aligned.m64n64k16.f32.bf16.bf16 {%0, %1, %2, %3, %4, %5, %6, %7, %8, %9, %10, %11, %12, %13, %14, %15, %16, %17, %18, %19, %20, %21, %22, %23, %24, %25, %26, %27, %28, %29, %30, %31}, {%32, %33, %34, %35}, %36, p, 1, 1, %38;\n}\n"
    : "+f"(d[OFF+0]), "+f"(d[OFF+1]), "+f"(d[OFF+2]), "+f"(d[OFF+3]), "+f"(d[OFF+4]), "+f"(d[OFF+5]), "+f"(d[OFF+6]), "+f"(d[OFF+7]), "+f"(d[OFF+8]), "+f"(d[OFF+9]), "+f"(d[OFF+10]), "+f"(d[OFF+11]), "+f"(d[OFF+12]), "+f"(d[OFF+13]), "+f"(d[OFF+14]), "+f"(d[OFF+15]), "+f"(d[OFF+16]), "+f"(d[OFF+17]), "+f"(d[OFF+18]), "+f"(d[OFF+19]), "+f"(d[OFF+20]), "+f"(d[OFF+21]), "+f"(d[OFF+22]), "+f"(d[OFF+23]), "+f"(d[OFF+24]), "+f"(d[OFF+25]), "+f"(d[OFF+26]), "+f"(d[OFF+27]), "+f"(d[OFF+28]), "+f"(d[OFF+29]), "+f"(d[OFF+30]), "+f"(d[OFF+31])
    : "r"(a0), "r"(a1), "r"(a2), "r"(a3), "l"(db), "r"(scale_d), "n"(TB));
}

__device__ __forceinline__ void wait_flag(const unsigned int* f, uint32_t target) {
  uint32_t v;
#pragma unroll 1
  for (uint32_t spins = 0; spins < (1u << 22); spins++) {
    asm volatile("ld.acquire.gpu.global.u32 %0, [%1];" : "=r"(v) : "l"(f) : "memory");
    if (v >= target) break;
    __nanosleep(100);
  }
}
__device__ __forceinline__ uint32_t lds32(uint32_t a) {
  uint32_t v;
  asm volatile("ld.shared.u32 %0, [%1];" : "=r"(v) : "r"(a) : "memory");
  return v;
}
__device__ __forceinline__ float gate_row(int row, int lane, const bf16* __restrict__ x, const bf16* __restrict__ gate_w) {
  const uint32_t* xr = reinterpret_cast<const uint32_t*>(x + (size_t)row * DM);
  const uint32_t* gw2 = reinterpret_cast<const uint32_t*>(gate_w);
  float gs = 0.f;
#pragma unroll
  for (int i = 0; i < 9; i++) {
    const uint32_t a = __ldg(xr + lane + 32 * i), b = __ldg(gw2 + lane + 32 * i);
    gs = fmaf(bf_lo(a), bf_lo(b), gs);
    gs = fmaf(bf_hi(a), bf_hi(b), gs);
  }
#pragma unroll
  for (int o = 16; o; o >>= 1) gs += __shfl_xor_sync(0xffffffffu, gs, o);
  const float g = 1.f / (1.f + __expf(-gs));
  if (lane == 0) g_gate[row] = g;
  return g;
}
__device__ __forceinline__ void local_rows2(int row, uint32_t srow, int lane, float g0, float g1) {
  const float scale_l2 = 0.23570226039551584f * 1.4426950408889634f;
  const uint32_t srow0 = srow;
  float q[2][18], o[2][18], mx[2], sum[2];
#pragma unroll
  for (int r = 0; r < 2; r++) {
#pragma unroll
    for (int i = 0; i < 9; i++) {
      const uint32_t v = lds32(srow + r * 3456 + 4 * i);
      q[r][2 * i] = bf_lo(v);
      q[r][2 * i + 1] = bf_hi(v);
      o[r][2 * i] = 0.f;
      o[r][2 * i + 1] = 0.f;
    }
    mx[r] = -INFINITY;
    sum[r] = 0.f;
  }
  const int nw = min(8, (row >> 1) + 1);
#pragma unroll 1
  for (int w = 0; w < nw; w++, srow -= 2 * 3456) {
#pragma unroll
    for (int r = 0; r < 2; r++) {
      float s0 = 0.f, s1 = 0.f, s2 = 0.f;
#pragma unroll
      for (int i = 0; i < 3; i++) {
        const uint32_t k0 = lds32(srow + r * 3456 + 1152 + 4 * i), k1 = lds32(srow + r * 3456 + 1164 + 4 * i), k2 = lds32(srow + r * 3456 + 1176 + 4 * i);
        s0 = fmaf(q[r][2 * i], bf_lo(k0), s0);
        s1 = fmaf(q[r][6 + 2 * i], bf_lo(k1), s1);
        s2 = fmaf(q[r][12 + 2 * i], bf_lo(k2), s2);
        s0 = fmaf(q[r][2 * i + 1], bf_hi(k0), s0);
        s1 = fmaf(q[r][6 + 2 * i + 1], bf_hi(k1), s1);
        s2 = fmaf(q[r][12 + 2 * i + 1], bf_hi(k2), s2);
      }
      const float s = s0 + s1 + s2;
      const float mn = fmaxf(mx[r], s);
      const float sc = ex2((mx[r] - mn) * scale_l2), pw = ex2((s - mn) * scale_l2);
      mx[r] = mn;
      sum[r] = fmaf(sum[r], sc, pw);
#pragma unroll
      for (int i = 0; i < 9; i++) {
        const uint32_t vv = lds32(srow + r * 3456 + 2304 + 4 * i);
        o[r][2 * i] = fmaf(pw, bf_lo(vv), o[r][2 * i] * sc);
        o[r][2 * i + 1] = fmaf(pw, bf_hi(vv), o[r][2 * i + 1] * sc);
      }
    }
  }
#pragma unroll
  for (int r = 0; r < 2; r++) {
    const float f = (r ? g1 : g0) / sum[r];
#pragma unroll
    for (int i = 0; i < 9; i++)
      asm volatile("st.shared.u32 [%0], %1;" ::"r"(srow0 + r * 3456 + 4 * i), "r"(pack_bf16(o[r][2 * i] * f, o[r][2 * i + 1] * f)) : "memory");
  }
  __syncwarp();
  const uint32_t sb = srow0 - lane * 36;
#pragma unroll
  for (int t = 0; t < 5; t++) {
    const int c = t * 32 + lane;
    if (c < 144) {
      const int r = c >= 72, cc = c - r * 72;
      uint32_t a, b, d, e;
      asm volatile("ld.shared.v4.u32 {%0, %1, %2, %3}, [%4];" : "=r"(a), "=r"(b), "=r"(d), "=r"(e) : "r"(sb + r * 3456 + cc * 16) : "memory");
      st_v4(g_ctx + (size_t)(row + r) * KCAT + HDIM + cc * 8, a, b, d, e);
    }
  }
}

#define K1_NST 6
constexpr int K1_BST = K1_NST;
constexpr int K1_MAXJOBS = 10;
constexpr int K1_SMEM = 8 * 16384 + K1_BST * 16384 + 1024 + 512;
constexpr uint32_t K1_FLAG_TARGET = 7;
constexpr uint32_t RDY_TARGET = 48;
constexpr uint32_t GATE_TARGET = 128 * 3;
struct alignas(64) K1Params {
  CUtensorMap tmA[2];
  CUtensorMap tmW[4];
  uint16_t jobs[NCLUSTER][K1_MAXJOBS];
};

struct K1State {
  uint32_t bs, bph, aph;
  bf16* pp;
  int pld8;
  int png;
};
__device__ __forceinline__ void k1_flag(const K1State& st, int lane, uint32_t bS) {
  if (st.png) {
    __syncwarp();
    if (lane == 0) mbar_arrive(bS);
  }
}

__device__ __forceinline__ void k1_tile(float (&acc)[128], uint32_t (&pk)[64], K1State& st, uint32_t job, uint32_t sA, uint32_t sB,
                                        uint32_t bAf, uint32_t bAe, uint32_t bBf, uint32_t bBe, int wg, int warp, int lane, uint32_t rank) {
  const int a_sel = (job >> 2) & 1, mpair = (job >> 3) & 7, w_sel = (job >> 6) & 3, chunk0 = (job >> 8) & 63;
  const bool newA = (job >> 14) & 1, lastA = (job >> 15) & 1;
  const bool sig = (lane == 0) && (warp < 2);
  const bool siga = lastA && (lane == 0) && (warp == 2);
  const int KC = 8 + a_sel;
  uint32_t prev_bs = 0, prev2_bs = 0, a8_bs = 0;
#pragma unroll
  for (int kc = 0; kc < 9; kc++) {
    if (kc >= KC) break;
    uint32_t abase = sA + kc * 16384;
    if (kc == 8) {
      mbar_wait(bBf + st.bs * 8, st.bph);
      a8_bs = st.bs;
      abase = sB + st.bs * 16384;
      if (++st.bs == K1_BST) { st.bs = 0; st.bph ^= 1; }
    } else if (newA) {
      mbar_wait(bAf + kc * 8, st.aph);
    }
    const uint64_t da = make_desc(abase + wg * 8192, 16, 1024, 1);
#pragma unroll
    for (int ks = 0; ks < 2; ks++) {
      mbar_wait(bBf + st.bs * 8, st.bph);
      const uint64_t db = make_desc(sB + st.bs * 16384, 2048, 1024, 1);
      wg_fence();
      wgmma_ss_n256<1, 0>(acc, da + (uint64_t)(ks * 4), db, (ks > 0) ? 1 : (kc > 0));
      wgmma_ss_n256<1, 0>(acc, da + (uint64_t)(ks * 4 + 2), db + (uint64_t)512, 1);
      wg_commit();
      const int PO = (kc < 8 ? kc : 0) * 8;
      wg_wait<1>();
      if (ks > 0 || kc > 0) {
        if (sig) mbar_arrive_cluster(bBe + prev_bs * 8, warp);
        if (ks == 0 && siga) mbar_arrive(bAe + (kc - 1) * 8);
      }
      if (kc < st.png) st_v4(st.pp + kc * 32 + ks * st.pld8, pk[PO + ks * 4], pk[PO + ks * 4 + 1], pk[PO + ks * 4 + 2], pk[PO + ks * 4 + 3]);
      prev_bs = st.bs;
      if (++st.bs == K1_BST) { st.bs = 0; st.bph ^= 1; }
    }
  }
  if (newA) st.aph ^= 1;
  k1_flag(st, lane, bBe + K1_BST * 8 + 8);
  wg_wait<0>();
  fence_regs(acc);
  if (sig) {
    mbar_arrive_cluster(bBe + prev_bs * 8, warp);
    if (a_sel) mbar_arrive_cluster(bBe + a8_bs * 8, warp);
  }
  if (siga && !a_sel) mbar_arrive(bAe + 7 * 8);
  const bool isA = (w_sel == 2);
  bf16* out = (w_sel == 0) ? g_K : (w_sel == 1) ? g_V : isA ? g_QKVA : g_Q;
  const int ld = isA ? NQKVA : HDIM;
  const int row = mpair * 256 + rank * 128 + wg * 64 + warp * 16 + (lane >> 2);
  st.pp = out + (size_t)row * ld + chunk0 * 64 + (lane & 3) * 8;
  st.pld8 = 8 * ld;
  st.png = ((job & 3) + 1) * 2;
#pragma unroll
  for (int G = 0; G < 8; G++) {
    pk[G * 8 + 0] = pack_bf16(acc[G * 16 + 0], acc[G * 16 + 1]);
    pk[G * 8 + 1] = pack_bf16(acc[G * 16 + 4], acc[G * 16 + 5]);
    pk[G * 8 + 2] = pack_bf16(acc[G * 16 + 8], acc[G * 16 + 9]);
    pk[G * 8 + 3] = pack_bf16(acc[G * 16 + 12], acc[G * 16 + 13]);
    pk[G * 8 + 4] = pack_bf16(acc[G * 16 + 2], acc[G * 16 + 3]);
    pk[G * 8 + 5] = pack_bf16(acc[G * 16 + 6], acc[G * 16 + 7]);
    pk[G * 8 + 6] = pack_bf16(acc[G * 16 + 10], acc[G * 16 + 11]);
    pk[G * 8 + 7] = pack_bf16(acc[G * 16 + 14], acc[G * 16 + 15]);
  }
  if (isA) {
#pragma unroll
    for (int G = 0; G < 16; G++) quad_transpose(pk[G * 4 + 0], pk[G * 4 + 1], pk[G * 4 + 2], pk[G * 4 + 3], lane & 3);
  }
}

__global__ void __cluster_dims__(2, 1, 1) __launch_bounds__(384, 1)
k1_proj(const __grid_constant__ K1Params p, const bf16* __restrict__ x, const bf16* __restrict__ gate_w) {
  extern __shared__ uint8_t smem_raw[];
  const uint32_t sbase = (smem_u32(smem_raw) + 1023) & ~1023u;
  const uint32_t sA = sbase, sB = sbase + 8 * 16384, sBar = sB + K1_BST * 16384;
  const uint32_t bAf = sBar, bAe = sBar + 64, bBf = sBar + 128, bBe = bBf + K1_BST * 8, bL = bBe + K1_BST * 8, bS = bL + 8, sGate = sBar + 256;
  const int tid = threadIdx.x, warp_g = tid >> 5, lane = tid & 31;
  const uint32_t rank = cluster_rank();
  const int cl = blockIdx.x >> 1;
  TSM(0);
  if (tid == 0) {
    for (int i = 0; i < 8; i++) { mbar_init(bAf + i * 8, 1); mbar_init(bAe + i * 8, 2); }
    for (int i = 0; i < K1_BST; i++) { mbar_init(bBf + i * 8, 1); mbar_init(bBe + i * 8, 4); }
    mbar_init(bL, 1);
    mbar_init(bS, 8);
    asm volatile("fence.mbarrier_init.release.cluster;" ::: "memory");
  }
  __syncthreads();
  cluster_sync();
  pdl_launch();
  const int lr0 = blockIdx.x * 16, lrs = max(lr0 - 14, 0);

  if (warp_g >= 8) {
    reg_dealloc<40>();
    if (warp_g == 8) {
      if (lane == 0) {
        uint32_t bs = 0, bph = 1, aph = 1;
        for (int ji = 0; ji < K1_MAXJOBS; ji++) {
          const uint32_t job = p.jobs[cl][ji];
          if (!(job & 3)) break;
          const int a_sel = (job >> 2) & 1, mpair = (job >> 3) & 7, chunk0 = (job >> 8) & 63;
          const bool newA = (job >> 14) & 1;
          const int KC = a_sel ? 9 : 8;
          const uint32_t halfbytes = 8192;
          const CUtensorMap* tw = &p.tmW[(job >> 6) & 3];
          {
            const uint32_t njob = (ji + 1 < K1_MAXJOBS) ? p.jobs[cl][ji + 1] : 0;
            if (njob & 3) {
              const int nst = ((njob >> 2) & 1) ? 18 : 16;
              for (int t = (cl < 64) ? (cl & 7) : 0; t < nst; t += (cl < 64) ? 8 : 1)
                tma_pf3d(&p.tmW[(njob >> 6) & 3], 0, t * 32 + rank * 16, (njob >> 8) & 63);
            }
          }
          for (int kc = 0; kc < KC; kc++) {
            if (kc == 8) {
              mbar_wait(bBe + bs * 8, bph);
              mbar_expect(bBf + bs * 8, 16384);
              tma2d(sB + bs * 16384, &p.tmA[1], bBf + bs * 8, 512, mpair * 256 + rank * 128);
              if (++bs == K1_BST) { bs = 0; bph ^= 1; }
            } else if (newA) {
              mbar_wait(bAe + kc * 8, aph);
              mbar_expect(bAf + kc * 8, 16384);
              tma2d(sA + kc * 16384, &p.tmA[a_sel], bAf + kc * 8, kc * 64, mpair * 256 + rank * 128);
            }
            for (int kk = 0; kk < 2; kk++) {
              mbar_wait(bBe + bs * 8, bph);
              mbar_expect(bBf + bs * 8, 2 * halfbytes);
              tma3d_mc(sB + bs * 16384 + rank * halfbytes, tw, bBf + bs * 8, 0, kc * 64 + kk * 32 + rank * 16, chunk0, 3);
              if (++bs == K1_BST) { bs = 0; bph ^= 1; }
            }
          }
          if (newA) aph ^= 1;
        }
        if (lr0 < S_LEN) {
          wait_flag(&g_flag[lr0 >> 7], K1_FLAG_TARGET);
          wait_flag(&g_flag[lrs >> 7], K1_FLAG_TARGET);
          asm volatile("fence.proxy.async;" ::: "memory");
          for (int kc = 0; kc < 7; kc++) mbar_wait(bAe + kc * 8, aph);
          const uint32_t bytes = (lr0 + 16 - lrs) * (NQKVA * 2);
          mbar_expect(bL, bytes);
          asm volatile("cp.async.bulk.shared::cluster.global.mbarrier::complete_tx::bytes [%0], [%1], %2, [%3];" ::"r"(sA),
                       "l"(g_QKVA + (size_t)lrs * NQKVA), "r"(bytes), "r"(bL) : "memory");
        }
      }
    } else {
      if (warp_g == 9 && blockIdx.x == 0) g_cnt[lane] = 0;
      if (lr0 < S_LEN) {
#pragma unroll 1
        for (int i = warp_g - 9; i < 16; i += 3) {
          const float g = gate_row(lr0 + i, lane, x, gate_w);
          if (lane == 0) asm volatile("st.shared.f32 [%0], %1;" ::"r"(sGate + i * 4), "f"(g) : "memory");
        }
        bar_arrive(2, 256 + 96);
        if (lane == 0) {
          __threadfence();
          atomicAdd(&g_rdy[16], 1u);
        }
      }
      if (warp_g == 9 && lane == 0) {
#pragma unroll 1
        for (int ji = 0; ji < K1_MAXJOBS; ji++) {
          const uint32_t job = p.jobs[cl][ji];
          if (!(job & 3)) break;
          mbar_wait(bS, ji & 1);
          __threadfence();
          atomicAdd((((job >> 6) & 3) == 2) ? &g_flag[((job >> 3) & 7) * 2 + rank] : &g_rdy[(job >> 10) & 15], 1u);
        }
      }
    }
    __syncwarp();
    cluster_sync();
  } else {
    reg_alloc<232>();
    const int wg = warp_g >> 2, warp = warp_g & 3;
    K1State st{0, 0, 0, nullptr, 0, 0};
    float acc[128];
    uint32_t pk[64];
    if (wg == 0) { TS(0, 0); TSC(0, 2); }
#pragma unroll 1
    for (int ji = 0; ji < K1_MAXJOBS; ji++) {
      const uint32_t job = p.jobs[cl][ji];
      if (!(job & 3)) break;
      k1_tile(acc, pk, st, job, sA, sB, bAf, bAe, bBf, bBe, wg, warp, lane, rank);
    }
#pragma unroll
    for (int G = 0; G < 8; G++)
      if (G < st.png) {
        st_v4(st.pp + G * 32, pk[G * 8], pk[G * 8 + 1], pk[G * 8 + 2], pk[G * 8 + 3]);
        st_v4(st.pp + G * 32 + st.pld8, pk[G * 8 + 4], pk[G * 8 + 5], pk[G * 8 + 6], pk[G * 8 + 7]);
      }
    k1_flag(st, lane, bS);
    if (wg == 0) { TS(0, 1); TSC(0, 3); }
    if (lr0 < S_LEN) {
      const int row = lr0 + warp_g * 2;
      if (wg == 0) TS(1, 5);
      bar_sync(2, 256 + 96);
      const float gate0 = __uint_as_float(lds32(sGate + warp_g * 8)), gate1 = __uint_as_float(lds32(sGate + warp_g * 8 + 4));
      mbar_wait(bL, 0);
      if (wg == 0) TS(1, 6);
      local_rows2(row, sA + (row - lrs) * (NQKVA * 2) + lane * 36, lane, gate0, gate1);
    }
    cluster_sync();
  }
}

constexpr int K2_NST = 7;
constexpr uint32_t K2_END = 0x100;
constexpr int K2_SMEM = K2_NST * 32768 + 1024 + 256;
struct alignas(64) K2Params {
  CUtensorMap tmQ, tmK, tmV;
  uint8_t order[256];
};

struct Cursor {
  uint32_t s, ph;
  __device__ __forceinline__ void next() {
    if (++s == K2_NST) { s = 0; ph ^= 1; }
  }
};

__global__ void __cluster_dims__(2, 1, 1) __launch_bounds__(384, 1) k2_attn(const __grid_constant__ K2Params p) {
  extern __shared__ uint8_t smem_raw[];
  const uint32_t sbase = (smem_u32(smem_raw) + 1023) & ~1023u;
  const uint32_t sBar = sbase + K2_NST * 32768;
  const uint32_t bF = sBar, bE = sBar + K2_NST * 8, bT = sBar + 128, sTick = sBar + 144, sItem = sBar + 160;
  const int tid = threadIdx.x, warp_g = tid >> 5, lane = tid & 31;
  const uint32_t rank = cluster_rank();
  const int cl = blockIdx.x >> 1;
  TSM(1);
  if (tid == 0) {
    for (int i = 0; i < K2_NST; i++) { mbar_init(bF + i * 8, 1); mbar_init(bE + i * 8, 4); }
    mbar_init(bT, 1); mbar_init(bT + 8, 1);
    asm volatile("fence.mbarrier_init.release.cluster;" ::: "memory");
    prefetch_tmap(&p.tmQ); prefetch_tmap(&p.tmK); prefetch_tmap(&p.tmV);
  }
  __syncthreads();
  cluster_sync();
  pdl_launch();

  if (warp_g >= 8) {
    reg_dealloc<40>();
    if (warp_g == 8) {
      if (lane == 0) {
        Cursor c{0, 1};
        int pcol = 0;
        uint32_t seen = 0, tick = cl;
        wait_flag(&g_rdy[16], GATE_TARGET);
#pragma unroll 1
        for (int it = 0;; it++) {
          const uint32_t item = (tick < 256) ? p.order[tick] : K2_END;
          mbar_wait(bE + c.s * 8, c.ph);
          asm volatile("st.shared.u32 [%0], %1;" ::"r"(sItem + (it & 3) * 4), "r"(item) : "memory");
          if (item == K2_END) break;
          const int h = item >> 3, j = item & 7;
          const int blk = 2 * j + (int)(rank ^ (it & 1));
          const int col = h * 128 + rank * 64;
          const int nb = 2 * j + 2;
          if (!((seen >> (h >> 1)) & 1)) {
            wait_flag(&g_rdy[h >> 1], RDY_TARGET);
            asm volatile("fence.proxy.async;" ::: "memory");
            seen |= 1u << (h >> 1);
          }
          mbar_expect(bF + c.s * 8, 32768);
          tma2d(sbase + c.s * 32768, &p.tmQ, bF + c.s * 8, h * 128, blk * 128);
          tma2d(sbase + c.s * 32768 + 16384, &p.tmQ, bF + c.s * 8, h * 128 + 64, blk * 128);
          c.next();
#pragma unroll 1
          for (int n = nb - 1; n >= 0; n--) {
            if (n == 0 && rank == 0) tick = atomicAdd(&g_rdy[17], 1u) + NCLUSTER;
            mbar_wait(bE + c.s * 8, c.ph);
            mbar_expect(bF + c.s * 8, 32768);
            tma2d_mc(sbase + c.s * 32768 + rank * 16384, &p.tmK, bF + c.s * 8, col, n * 128, 3);
            c.next();
            if (n < nb - 1 || it > 0) {
              mbar_wait(bE + c.s * 8, c.ph);
              mbar_expect(bF + c.s * 8, 32768);
              if (n < nb - 1)
                tma2d_mc(sbase + c.s * 32768 + rank * 16384, &p.tmV, bF + c.s * 8, col, (n + 1) * 128, 3);
              else
                tma2d_mc(sbase + c.s * 32768 + rank * 16384, &p.tmV, bF + c.s * 8, pcol, 0, 3);
              c.next();
            }
          }
          pcol = col;
          if (rank == 0) {
            asm volatile(
                "{\n.reg .b32 a, b;\nmapa.shared::cluster.u32 a, %0, 1;\nmapa.shared::cluster.u32 b, %1, 1;\n"
                "st.async.shared::cluster.mbarrier::complete_tx::bytes.u32 [a], %2, [b];\n}" ::"r"(sTick + (it & 1) * 4),
                "r"(bT + (it & 1) * 8), "r"(tick) : "memory");
          } else {
            mbar_expect(bT + (it & 1) * 8, 4);
            mbar_wait(bT + (it & 1) * 8, (it >> 1) & 1);
            tick = lds32(sTick + (it & 1) * 4);
          }
        }
        mbar_expect(bF + c.s * 8, 32768);
        tma2d_mc(sbase + c.s * 32768 + rank * 16384, &p.tmV, bF + c.s * 8, pcol, 0, 3);
      }
    } else if (warp_g == 9 && blockIdx.x == 0) {
      pdl_wait();
      g_flag[lane] = 0;
    }
    __syncwarp();
    cluster_sync();
  } else {
    reg_alloc<232>();
    const int wg = warp_g >> 2, warp = warp_g & 3, q = lane & 3;
    const bool sig = (lane == 0) && (warp < 2);
    const int mybar = 1 + wg, otherbar = 2 - wg;
    const float cl2 = 0.08838834764831845f * 1.4426950408889634f;
    float S[64], O[64];
    uint32_t P[32], Q[32];
    float m0 = 0.f, m1 = 0.f, l0 = 0.f, l1 = 0.f;
    int prev_row = 0, prev_h = 0, prev_single = 0;
    Cursor c{0, 0};
    if (wg == 1) bar_arrive(1, 256);
    if (wg == 0) { TS(1, 0); TSC(1, 2); }

#define TURN_SYNC() bar_sync(mybar, 256)
#define TURN_ARRIVE() bar_arrive(otherbar, 256)
#define RELEASE(cur) do { if (sig) mbar_arrive_cluster(bE + (cur).s * 8, warp); } while (0)
#define ISSUE_PV(cur, first)                                                                                   \
  do {                                                                                                         \
    const uint64_t dv = make_desc(sbase + (cur).s * 32768, 16384, 1024, 1);                                    \
    _Pragma("unroll") for (int t = 0; t < 8; t++)                                                              \
        wgmma_rs_n128<1, 0>(O, P[4 * t], P[4 * t + 1], P[4 * t + 2], P[4 * t + 3], dv + (uint64_t)(t * 128), (t > 0) ? 1 : !(first)); \
  } while (0)
#define ISSUE_QK(cur)                                                                                          \
  do {                                                                                                         \
    const uint64_t dk = make_desc(sbase + (cur).s * 32768, 16, 1024, 1);                                       \
    _Pragma("unroll") for (int t = 0; t < 8; t++)                                                              \
        wgmma_rs_n128<0, 0>(S, Q[4 * t], Q[4 * t + 1], Q[4 * t + 2], Q[4 * t + 3], dk + (uint64_t)((t >> 2) * 1024 + (t & 3) * 2), t > 0); \
  } while (0)
#define EPILOGUE()                                                                                             \
  do {                                                                                                         \
    l0 += __shfl_xor_sync(0xffffffffu, l0, 1);                                                                 \
    l0 += __shfl_xor_sync(0xffffffffu, l0, 2);                                                                 \
    l1 += __shfl_xor_sync(0xffffffffu, l1, 1);                                                                 \
    l1 += __shfl_xor_sync(0xffffffffu, l1, 2);                                                                 \
    const float f0 = gf0 / l0, f1 = gf1 / l1;                                                                  \
    bf16* o0 = g_ctx + (size_t)prev_row * KCAT + prev_h * 128 + q * 8;                                         \
    bf16* o1 = o0 + (size_t)8 * KCAT;                                                                          \
    _Pragma("unroll") for (int G = 0; G < 4; G++) {                                                            \
      st_v4(o0 + G * 32, pack_bf16(O[G * 16 + 0] * f0, O[G * 16 + 1] * f0), pack_bf16(O[G * 16 + 4] * f0, O[G * 16 + 5] * f0), \
            pack_bf16(O[G * 16 + 8] * f0, O[G * 16 + 9] * f0), pack_bf16(O[G * 16 + 12] * f0, O[G * 16 + 13] * f0)); \
      st_v4(o1 + G * 32, pack_bf16(O[G * 16 + 2] * f1, O[G * 16 + 3] * f1), pack_bf16(O[G * 16 + 6] * f1, O[G * 16 + 7] * f1), \
            pack_bf16(O[G * 16 + 10] * f1, O[G * 16 + 11] * f1), pack_bf16(O[G * 16 + 14] * f1, O[G * 16 + 15] * f1)); \
    }                                                                                                          \
  } while (0)

#pragma unroll 1
    for (int it = 0;; it++) {
      mbar_wait(bF + c.s * 8, c.ph);
      const uint32_t item = lds32(sItem + (it & 3) * 4);
      if (item == K2_END) break;
      const int h = item >> 3, j = item & 7;
      const int hi = (int)(rank ^ (it & 1));
      const int nblk = 2 * j + 1 + hi;
      {
        const float gf0 = 1.f - g_gate[prev_row], gf1 = 1.f - g_gate[prev_row + 8];
        Cursor cq = c; c.next();
        {
          const int r = wg * 64 + warp * 16 + (lane & 7) + ((lane >> 3) & 1) * 8;
          const uint32_t qa = sbase + cq.s * 32768 + r * 128;
#pragma unroll
          for (int t = 0; t < 8; t++)
            ldsm_x4(Q[4 * t], Q[4 * t + 1], Q[4 * t + 2], Q[4 * t + 3], qa + (t >> 2) * 16384 + ((((t & 3) * 2 + (lane >> 4)) ^ (lane & 7)) << 4));
        }
        Cursor ck = c; c.next();
        Cursor cs0 = ck, cs1 = ck, cv = c;
        mbar_wait(bF + ck.s * 8, ck.ph);
        if (it > 0) { mbar_wait(bF + cv.s * 8, cv.ph); c.next(); }
        if (!hi) {
          ck = c; c.next();
          cs1 = c; c.next();
          mbar_wait(bF + ck.s * 8, ck.ph);
          mbar_wait(bF + cs1.s * 8, cs1.ph);
        }
        TURN_SYNC();
        wg_fence();
        ISSUE_QK(ck);
        wg_commit();
        if (it > 0) ISSUE_PV(cv, prev_single);
        wg_commit();
        TURN_ARRIVE();
        RELEASE(cq);
        if (!hi) { RELEASE(cs0); RELEASE(cs1); }
        wg_wait<1>();
        fence_regs(S);
        RELEASE(ck);
        const int r0 = wg * 64 + warp * 16 + (lane >> 2);
#pragma unroll
        for (int jj = 0; jj < 16; jj++) {
          const int cc = jj * 8 + 2 * q;
          if (cc > r0) S[jj * 4 + 0] = -INFINITY;
          if (cc + 1 > r0) S[jj * 4 + 1] = -INFINITY;
          if (cc > r0 + 8) S[jj * 4 + 2] = -INFINITY;
          if (cc + 1 > r0 + 8) S[jj * 4 + 3] = -INFINITY;
        }
        float mx0 = fmaxf(S[0], S[1]), mx1 = fmaxf(S[2], S[3]);
#pragma unroll
        for (int jj = 1; jj < 16; jj++) {
          mx0 = fmaxf(mx0, fmaxf(S[jj * 4 + 0], S[jj * 4 + 1]));
          mx1 = fmaxf(mx1, fmaxf(S[jj * 4 + 2], S[jj * 4 + 3]));
        }
        mx0 = fmaxf(mx0, __shfl_xor_sync(0xffffffffu, mx0, 1));
        mx1 = fmaxf(mx1, __shfl_xor_sync(0xffffffffu, mx1, 1));
        mx0 = fmaxf(mx0, __shfl_xor_sync(0xffffffffu, mx0, 2));
        mx1 = fmaxf(mx1, __shfl_xor_sync(0xffffffffu, mx1, 2));
        m0 = mx0; m1 = mx1;
        const float mc0 = m0 * cl2, mc1 = m1 * cl2;
        float s0 = 0.f, s1 = 0.f;
#pragma unroll
        for (int jj = 0; jj < 16; jj++) {
          S[jj * 4 + 0] = ex2(fmaf(S[jj * 4 + 0], cl2, -mc0));
          S[jj * 4 + 1] = ex2(fmaf(S[jj * 4 + 1], cl2, -mc0));
          S[jj * 4 + 2] = ex2(fmaf(S[jj * 4 + 2], cl2, -mc1));
          S[jj * 4 + 3] = ex2(fmaf(S[jj * 4 + 3], cl2, -mc1));
          s0 += S[jj * 4 + 0] + S[jj * 4 + 1];
          s1 += S[jj * 4 + 2] + S[jj * 4 + 3];
        }
        fence_regs(S);
        wg_wait<0>();
        fence_regs(O);
        fence_regs(P);
        if (it > 0) {
          RELEASE(cv);
          EPILOGUE();
        }
        l0 = s0; l1 = s1;
#pragma unroll
        for (int jj = 0; jj < 16; jj++) {
          P[jj * 2 + 0] = pack_bf16(S[jj * 4 + 0], S[jj * 4 + 1]);
          P[jj * 2 + 1] = pack_bf16(S[jj * 4 + 2], S[jj * 4 + 3]);
        }
      }
#pragma unroll 1
      for (int n = 1; n < nblk; n++) {
        Cursor ck = c; c.next();
        Cursor cv = c; c.next();
        mbar_wait(bF + ck.s * 8, ck.ph);
        mbar_wait(bF + cv.s * 8, cv.ph);
        TURN_SYNC();
        wg_fence();
        ISSUE_QK(ck);
        wg_commit();
        ISSUE_PV(cv, n == 1);
        wg_commit();
        TURN_ARRIVE();
        wg_wait<1>();
        fence_regs(S);
        RELEASE(ck);
        float mx0 = fmaxf(S[0], S[1]), mx1 = fmaxf(S[2], S[3]);
#pragma unroll
        for (int jj = 1; jj < 16; jj++) {
          mx0 = fmaxf(mx0, fmaxf(S[jj * 4 + 0], S[jj * 4 + 1]));
          mx1 = fmaxf(mx1, fmaxf(S[jj * 4 + 2], S[jj * 4 + 3]));
        }
        mx0 = fmaxf(mx0, __shfl_xor_sync(0xffffffffu, mx0, 1));
        mx1 = fmaxf(mx1, __shfl_xor_sync(0xffffffffu, mx1, 1));
        mx0 = fmaxf(mx0, __shfl_xor_sync(0xffffffffu, mx0, 2));
        mx1 = fmaxf(mx1, __shfl_xor_sync(0xffffffffu, mx1, 2));
        mx0 = fmaxf(mx0, m0);
        mx1 = fmaxf(mx1, m1);
        const float sc0 = ex2((m0 - mx0) * cl2), sc1 = ex2((m1 - mx1) * cl2);
        m0 = mx0; m1 = mx1;
        const float mc0 = m0 * cl2, mc1 = m1 * cl2;
        float s0 = 0.f, s1 = 0.f;
#pragma unroll
        for (int jj = 0; jj < 16; jj++) {
          S[jj * 4 + 0] = ex2(fmaf(S[jj * 4 + 0], cl2, -mc0));
          S[jj * 4 + 1] = ex2(fmaf(S[jj * 4 + 1], cl2, -mc0));
          S[jj * 4 + 2] = ex2(fmaf(S[jj * 4 + 2], cl2, -mc1));
          S[jj * 4 + 3] = ex2(fmaf(S[jj * 4 + 3], cl2, -mc1));
          s0 += S[jj * 4 + 0] + S[jj * 4 + 1];
          s1 += S[jj * 4 + 2] + S[jj * 4 + 3];
        }
        l0 = fmaf(l0, sc0, s0);
        l1 = fmaf(l1, sc1, s1);
        fence_regs(S);
        wg_wait<0>();
        fence_regs(O);
        fence_regs(P);
        RELEASE(cv);
#pragma unroll
        for (int jj = 0; jj < 16; jj++) {
          O[jj * 4 + 0] *= sc0;
          O[jj * 4 + 1] *= sc0;
          O[jj * 4 + 2] *= sc1;
          O[jj * 4 + 3] *= sc1;
          P[jj * 2 + 0] = pack_bf16(S[jj * 4 + 0], S[jj * 4 + 1]);
          P[jj * 2 + 1] = pack_bf16(S[jj * 4 + 2], S[jj * 4 + 3]);
        }
      }
      prev_row = (2 * j + hi) * 128 + wg * 64 + warp * 16 + (lane >> 2);
      prev_h = h;
      prev_single = (nblk == 1);
    }
    {
      const float gf0 = 1.f - g_gate[prev_row], gf1 = 1.f - g_gate[prev_row + 8];
      Cursor cv = c;
      TURN_SYNC();
      wg_fence();
      ISSUE_PV(cv, prev_single);
      wg_commit();
      if (wg == 0) TURN_ARRIVE();
      wg_wait<0>();
      fence_regs(O);
      EPILOGUE();
    }
    if (wg == 1) { TS(1, 1); TSC(1, 3); }
    cluster_sync();
  }
}

constexpr int K3_NST = 4;
constexpr int K3_STAGE = 16384 + 32768 + 4096;
constexpr int K3_SMEM = K3_NST * K3_STAGE + 1024 + 256;
struct alignas(64) K3Params {
  CUtensorMap tmA, tmW[2], tmWt[2];
};

__global__ void __cluster_dims__(2, 1, 1) __launch_bounds__(384, 1) k3_out(const __grid_constant__ K3Params p, bf16* __restrict__ out) {
  extern __shared__ uint8_t smem_raw[];
  const uint32_t sbase = (smem_u32(smem_raw) + 1023) & ~1023u;
  const uint32_t sBar = sbase + K3_NST * K3_STAGE;
  const uint32_t bF = sBar, bE = sBar + K3_NST * 8;
  const int tid = threadIdx.x, warp_g = tid >> 5, lane = tid & 31;
  const uint32_t rank = cluster_rank();
  const int cl = blockIdx.x >> 1;
  const int mblk = (cl >> 3) * 2 + rank, nhalf = (cl >> 2) & 1, ks = cl & 3;
  const int k0 = ks * 18, k1 = (ks == 3) ? 73 : k0 + 18;
  TSM(2);
  if (tid == 0) {
    for (int i = 0; i < K3_NST; i++) { mbar_init(bF + i * 8, 1); mbar_init(bE + i * 8, 4); }
    asm volatile("fence.mbarrier_init.release.cluster;" ::: "memory");
  }
  __syncthreads();
  cluster_sync();

  if (warp_g >= 8) {
    reg_dealloc<40>();
    if (warp_g == 8) {
      if (lane == 0) {
        pdl_wait();
        uint32_t s = 0, ph = 1;
        for (int k = k0; k < k1; k++) {
          mbar_wait(bE + s * 8, ph);
          mbar_expect(bF + s * 8, K3_STAGE);
          const uint32_t st = sbase + s * K3_STAGE;
          const int sel = (k >= 64), kr = (sel ? (k - 64) : k) * 64 + rank * 32;
          tma2d(st, &p.tmA, bF + s * 8, k * 64, mblk * 128);
          tma3d_mc(st + 16384 + rank * 16384, &p.tmW[sel], bF + s * 8, 0, kr, nhalf * 4, 3);
          tma2d_mc(st + 49152 + rank * 2048, &p.tmWt[sel], bF + s * 8, 512 + nhalf * 32, kr, 3);
          if (++s == K3_NST) { s = 0; ph ^= 1; }
        }
      }
    } else if (warp_g == 9 && blockIdx.x == 0) {
      pdl_wait();
      g_rdy[lane] = 0;
    }
    __syncwarp();
    cluster_sync();
  } else {
    reg_alloc<232>();
    pdl_wait();
    const int wg = warp_g >> 2, warp = warp_g & 3, q = lane & 3;
    const bool sig = (lane == 0) && (warp < 2);
    float acc[144];
    uint32_t s = 0, ph = 0, prev = 0;
    if (wg == 0) { TS(2, 0); TSC(2, 2); }
    for (int k = k0; k < k1; k++) {
      mbar_wait(bF + s * 8, ph);
      const uint32_t st = sbase + s * K3_STAGE;
      const uint64_t da = make_desc(st + wg * 8192, 16, 1024, 1);
      const uint64_t db = make_desc(st + 16384, 4096, 1024, 1);
      const uint64_t dt = make_desc(st + 49152, 16, 512, 2);
      wg_fence();
#pragma unroll
      for (int t = 0; t < 4; t++) {
        const int sd = (t > 0) || (k > k0);
        wgmma_ss_n256<1, 0>(acc, da + (uint64_t)(t * 2), db + (uint64_t)((t >> 1) * 1024 + (t & 1) * 128), sd);
        wgmma_ss_n32<1, 128>(acc, da + (uint64_t)(t * 2), dt + (uint64_t)(t * 64), sd);
      }
      wg_commit();
      if (k > k0) {
        wg_wait<1>();
        if (sig) mbar_arrive_cluster(bE + prev * 8, warp);
      }
      prev = s;
      if (++s == K3_NST) { s = 0; ph ^= 1; }
    }
    wg_wait<0>();
    fence_regs(acc);
    if (wg == 0) TS(2, 4);
    const int tile = mblk * 2 + nhalf;
    float4* wp = g_part + (size_t)((tile * 4 + ks) * 4) * 9 * 256 + tid;
#pragma unroll
    for (int d = 0; d < 4; d++) {
      if (d != ks) {
#pragma unroll
        for (int i = 0; i < 8; i++)
          __stcg(wp + (d * 9 + i) * 256, make_float4(acc[d * 32 + i * 4], acc[d * 32 + i * 4 + 1], acc[d * 32 + i * 4 + 2], acc[d * 32 + i * 4 + 3]));
        __stcg(wp + (d * 9 + 8) * 256, make_float4(acc[128 + d * 4], acc[128 + d * 4 + 1], acc[128 + d * 4 + 2], acc[128 + d * 4 + 3]));
      }
    }
    __threadfence();
    bar_sync(1, 256);
    if (wg == 0) TS(2, 5);
    if (tid == 0) {
      atomicAdd(&g_cnt[tile], 1u);
      uint32_t v, spins = 0;
      do {
        asm volatile("ld.acquire.gpu.global.u32 %0, [%1];" : "=r"(v) : "l"(&g_cnt[tile]) : "memory");
      } while (v < 4 && ++spins < (1u << 24));
    }
    bar_sync(1, 256);
    if (wg == 0) TS(2, 6);
    float r[36];
#pragma unroll
    for (int d = 0; d < 4; d++) {
      if (d == ks) {
#pragma unroll
        for (int i = 0; i < 32; i++) r[i] = acc[d * 32 + i];
#pragma unroll
        for (int i = 0; i < 4; i++) r[32 + i] = acc[128 + d * 4 + i];
      }
    }
#pragma unroll
    for (int sI = 1; sI < 4; sI++) {
      const int src = (ks + sI) & 3;
      const float4* rp = g_part + (size_t)(((tile * 4 + src) * 4) + ks) * 9 * 256 + tid;
#pragma unroll
      for (int i = 0; i < 9; i++) {
        const float4 v = __ldcg(rp + i * 256);
        r[i * 4] += v.x; r[i * 4 + 1] += v.y; r[i * 4 + 2] += v.z; r[i * 4 + 3] += v.w;
      }
    }
    const int row = mblk * 128 + wg * 64 + warp * 16 + (lane >> 2);
    bf16* o0 = out + (size_t)row * DM + nhalf * 256 + ks * 64 + 8 * q;
#pragma unroll
    for (int G = 0; G < 2; G++) {
      uint32_t a0 = pack_bf16(r[G * 16], r[G * 16 + 1]), a1 = pack_bf16(r[G * 16 + 4], r[G * 16 + 5]);
      uint32_t a2 = pack_bf16(r[G * 16 + 8], r[G * 16 + 9]), a3 = pack_bf16(r[G * 16 + 12], r[G * 16 + 13]);
      uint32_t b0 = pack_bf16(r[G * 16 + 2], r[G * 16 + 3]), b1 = pack_bf16(r[G * 16 + 6], r[G * 16 + 7]);
      uint32_t b2 = pack_bf16(r[G * 16 + 10], r[G * 16 + 11]), b3 = pack_bf16(r[G * 16 + 14], r[G * 16 + 15]);
      quad_transpose(a0, a1, a2, a3, q);
      quad_transpose(b0, b1, b2, b3, q);
      st_v4(o0 + G * 32, a0, a1, a2, a3);
      st_v4(o0 + 8 * DM + G * 32, b0, b1, b2, b3);
    }
    {
      uint32_t t0 = pack_bf16(r[32], r[33]), t1 = pack_bf16(r[34], r[35]), t2 = 0, t3 = 0;
      quad_transpose(t0, t1, t2, t3, q);
      if (q < 2) st_v4(out + (size_t)(row + q * 8) * DM + 512 + nhalf * 32 + ks * 8, t0, t1, t2, t3);
    }
    if (wg == 0) { TS(2, 1); TSC(2, 3); }
    cluster_sync();
  }
}

typedef CUresult (*EncFn)(CUtensorMap*, CUtensorMapDataType, cuuint32_t, void*, const cuuint64_t*, const cuuint64_t*, const cuuint32_t*,
                          const cuuint32_t*, CUtensorMapInterleave, CUtensorMapSwizzle, CUtensorMapL2promotion, CUtensorMapFloatOOBfill);

static void enc2d(EncFn enc, CUtensorMap* m, const void* ptr, uint64_t cols, uint64_t rows, uint32_t bc, uint32_t br,
                  CUtensorMapSwizzle sw = CU_TENSOR_MAP_SWIZZLE_128B) {
  cuuint64_t gd[2] = {cols, rows}, gs[1] = {cols * 2};
  cuuint32_t bx[2] = {bc, br}, es[2] = {1, 1};
  enc(m, CU_TENSOR_MAP_DATA_TYPE_BFLOAT16, 2, const_cast<void*>(ptr), gd, gs, bx, es, CU_TENSOR_MAP_INTERLEAVE_NONE, sw,
      CU_TENSOR_MAP_L2_PROMOTION_L2_256B, CU_TENSOR_MAP_FLOAT_OOB_FILL_NONE);
}
static void enc3d(EncFn enc, CUtensorMap* m, const void* ptr, uint64_t cols, uint64_t rows, uint32_t br, uint32_t bch) {
  cuuint64_t gd[3] = {64, rows, cols / 64}, gs[2] = {cols * 2, 128};
  cuuint32_t bx[3] = {64, br, bch}, es[3] = {1, 1, 1};
  enc(m, CU_TENSOR_MAP_DATA_TYPE_BFLOAT16, 3, const_cast<void*>(ptr), gd, gs, bx, es, CU_TENSOR_MAP_INTERLEAVE_NONE,
      CU_TENSOR_MAP_SWIZZLE_128B, CU_TENSOR_MAP_L2_PROMOTION_L2_256B, CU_TENSOR_MAP_FLOAT_OOB_FILL_NONE);
}

static void build_k1_jobs(K1Params& p) {
  int cnt[NCLUSTER];
  for (int c = 0; c < NCLUSTER; c++) {
    cnt[c] = 0;
    for (int i = 0; i < K1_MAXJOBS; i++) p.jobs[c][i] = 0;
  }
  auto add = [&](int c, int nch, int a_sel, int mp, int w_sel, int chunk0) {
    p.jobs[c][cnt[c]++] = (uint16_t)((nch - 1) | (a_sel << 2) | (mp << 3) | (w_sel << 6) | (chunk0 << 8));
  };
  for (int mp = 0; mp < 8; mp++) {
    for (int g = 0; g < 4; g++)
      for (int i = 0; i < 7; i++) add(g * 8 + mp, 4, 0, mp, g & 1, (2 + 2 * i + (g >> 1)) * 4);
    add(32 + mp, 3, 1, mp, 2, 24);
    add(32 + mp, 4, 1, mp, 3, 0 * 4);
    add(32 + mp, 4, 1, mp, 3, 1 * 4);
    for (int t = 0; t < 4; t++) add(32 + mp, 4, 0, mp, t & 1, (t >> 1) * 4);
    for (int g = 0; g < 2; g++) {
      for (int i = 0; i < 3; i++) add((5 + g) * 8 + mp, 4, 1, mp, 2, (g * 3 + i) * 4);
      for (int i = 0; i < 3; i++) add((5 + g) * 8 + mp, 4, 1, mp, 3, (2 + g * 3 + i) * 4);
    }
    for (int i = 0; i < 6; i++) add(56 + mp, 4, 1, mp, 3, (8 + i) * 4);
    add(64 + mp / 4, 4, 1, mp, 3, 14 * 4);
    if (mp & 1) add(64 + mp / 4, 4, 1, mp, 3, 15 * 4);
    else add(56 + mp, 4, 1, mp, 3, 15 * 4);
  }
  for (int cc = 0; cc < NCLUSTER; cc++)
    for (int i = 0; i < cnt[cc]; i++) {
      const int key = p.jobs[cc][i] & 0x3C;
      if (i == 0 || (p.jobs[cc][i - 1] & 0x3C) != key) p.jobs[cc][i] |= (1 << 14);
      if (i == cnt[cc] - 1 || (p.jobs[cc][i + 1] & 0x3C) != key) p.jobs[cc][i] |= (1 << 15);
    }
}

static void build_k2_items(K2Params& p) {
  static const int hp_order[16] = {8, 9, 10, 2, 5, 11, 3, 6, 12, 4, 7, 13, 14, 15, 0, 1};
  int n = 0;
  for (int i = 0; i < 64; i++) p.order[n++] = (uint8_t)((hp_order[i >> 2] * 2 + (i & 1)) * 8 + 7 - ((i >> 1) & 1));
  for (int j = 5; j >= 0; j--)
    for (int i = 0; i < 32; i++) p.order[n++] = (uint8_t)((hp_order[i >> 1] * 2 + (i & 1)) * 8 + j);
}

extern "C" void kernel_launch(void* const* d_in, const int* in_sizes, int n_in, void* d_out, int out_size) {
  const bf16* x = (const bf16*)d_in[0];
  const bf16* wqkv = (const bf16*)d_in[1];
  const bf16* wo = (const bf16*)d_in[2];
  const bf16* ckv = (const bf16*)d_in[4];
  const bf16* w_q = (const bf16*)d_in[5];
  const bf16* w_uk = (const bf16*)d_in[6];
  const bf16* w_uv = (const bf16*)d_in[7];
  const bf16* w_o = (const bf16*)d_in[8];
  const bf16* gate_w = (const bf16*)d_in[9];

  EncFn enc = nullptr;
  cudaDriverEntryPointQueryResult qr;
  cudaGetDriverEntryPoint("cuTensorMapEncodeTiled", (void**)&enc, cudaEnableDefault, &qr);
  void *pQ, *pK, *pV, *pCtx;
  cudaGetSymbolAddress(&pQ, g_Q);
  cudaGetSymbolAddress(&pK, g_K);
  cudaGetSymbolAddress(&pV, g_V);
  cudaGetSymbolAddress(&pCtx, g_ctx);

  static K1Params p1;
  static K2Params p2;
  static K3Params p3;
  enc2d(enc, &p1.tmA[0], ckv, DC, S_LEN, 64, 128);
  enc2d(enc, &p1.tmA[1], x, DM, S_LEN, 64, 128);
  enc3d(enc, &p1.tmW[0], w_uk, HDIM, DC, 16, 4);
  enc3d(enc, &p1.tmW[1], w_uv, HDIM, DC, 16, 4);
  enc3d(enc, &p1.tmW[2], wqkv, NQKVA, DM, 16, 4);
  enc3d(enc, &p1.tmW[3], w_q, HDIM, DM, 16, 4);
  build_k1_jobs(p1);
  enc2d(enc, &p2.tmQ, pQ, HDIM, S_LEN, 64, 128);
  enc2d(enc, &p2.tmK, pK, HDIM, S_LEN, 64, 128);
  enc2d(enc, &p2.tmV, pV, HDIM, S_LEN, 64, 128);
  build_k2_items(p2);
  enc2d(enc, &p3.tmA, pCtx, KCAT, S_LEN, 64, 128);
  enc3d(enc, &p3.tmW[0], w_o, DM, HDIM, 32, 4);
  enc3d(enc, &p3.tmW[1], wo, DM, DM, 32, 4);
  enc2d(enc, &p3.tmWt[0], w_o, DM, HDIM, 32, 32, CU_TENSOR_MAP_SWIZZLE_64B);
  enc2d(enc, &p3.tmWt[1], wo, DM, DM, 32, 32, CU_TENSOR_MAP_SWIZZLE_64B);

  cudaFuncSetAttribute(k1_proj, cudaFuncAttributeMaxDynamicSharedMemorySize, K1_SMEM);
  cudaFuncSetAttribute(k2_attn, cudaFuncAttributeMaxDynamicSharedMemorySize, K2_SMEM);
  cudaFuncSetAttribute(k3_out, cudaFuncAttributeMaxDynamicSharedMemorySize, K3_SMEM);

  k1_proj<<<NCLUSTER * 2, 384, K1_SMEM>>>(p1, x, gate_w);
  cudaLaunchConfig_t cfg = {};
  cudaLaunchAttribute at[1];
  at[0].id = cudaLaunchAttributeProgrammaticStreamSerialization;
  at[0].val.programmaticStreamSerializationAllowed = 1;
  cfg.attrs = at;
  cfg.numAttrs = 1;
  cfg.stream = cudaStreamPerThread;
  cfg.blockDim = dim3(384);
  cfg.gridDim = dim3(NCLUSTER * 2);
  cfg.dynamicSmemBytes = K2_SMEM;
  cudaLaunchKernelEx(&cfg, k2_attn, p2);
  cfg.gridDim = dim3(128);
  cfg.dynamicSmemBytes = K3_SMEM;
  cudaLaunchKernelEx(&cfg, k3_out, p3, (bf16*)d_out);
}
```

```cpp
#include <cuda_runtime.h>
#include <cuda_bf16.h>
#include <cuda.h>
#include <stdint.h>

typedef __nv_bfloat16 bf16;

constexpr int S_LEN = 2048, DM = 576, DC = 512, HDIM = 4096, NQKVA = 1728, KCAT = 4672;
constexpr int NCLUSTER = 66;

__device__ __align__(1024) bf16 g_Q[S_LEN * HDIM];
__device__ __align__(1024) bf16 g_K[S_LEN * HDIM];
__device__ __align__(1024) bf16 g_V[S_LEN * HDIM];
__device__ __align__(1024) bf16 g_QKVA[S_LEN * NQKVA + 64];
__device__ __align__(1024) bf16 g_ctx[S_LEN * KCAT];
__device__ float g_gate[S_LEN];
__device__ __align__(1024) float4 g_part[32 * 4 * 4 * 9 * 256];
__device__ unsigned int g_sync[128];
constexpr int F_QKVA = 0, F_HP = 16, F_CTX = 32, F_XCH = 64, F_GATE = 96, F_TICK = 97, F_DONE = 98;

__device__ __forceinline__ uint32_t smem_u32(const void* p) { return (uint32_t)__cvta_generic_to_shared(p); }
__device__ __forceinline__ void mbar_init(uint32_t a, uint32_t c) {
  asm volatile("mbarrier.init.shared::cta.b64 [%0], %1;" ::"r"(a), "r"(c));
}
__device__ __forceinline__ void mbar_expect(uint32_t a, uint32_t b) {
  asm volatile("mbarrier.arrive.expect_tx.shared::cta.b64 _, [%0], %1;" ::"r"(a), "r"(b) : "memory");
}
#define TS(k, i)
#define TSC(k, i)
#define TSM(k)
#define SPIN_LIMIT "4194304"
__device__ __forceinline__ void mbar_wait(uint32_t a, uint32_t parity) {
  asm volatile(
      "{\n.reg .pred p;\n.reg .u32 n;\n"
      "mbarrier.try_wait.parity.shared::cta.b64 p, [%0], %1;\n"
      "@p bra DONE;\n"
      "mov.u32 n, 0;\n"
      "LOOP:\n"
      "mbarrier.try_wait.parity.shared::cta.b64 p, [%0], %1;\n"
      "@p bra DONE;\n"
      "add.u32 n, n, 1;\n"
      "setp.lt.u32 p, n, " SPIN_LIMIT ";\n"
      "@p bra LOOP;\n"
      "DONE:\n}" ::"r"(a), "r"(parity) : "memory");
}
__device__ __forceinline__ void mbar_arrive(uint32_t a) {
  asm volatile("mbarrier.arrive.shared::cta.b64 _, [%0];" ::"r"(a) : "memory");
}
__device__ __forceinline__ void mbar_arrive_cluster(uint32_t a, uint32_t cta) {
  asm volatile("{\n.reg .b32 r;\nmapa.shared::cluster.u32 r, %0, %1;\nmbarrier.arrive.shared::cluster.b64 _, [r];\n}" ::"r"(a),
               "r"(cta) : "memory");
}
__device__ __forceinline__ void tma2d(uint32_t dst, const CUtensorMap* m, uint32_t bar, int c0, int c1) {
  asm volatile("cp.async.bulk.tensor.2d.shared::cluster.global.mbarrier::complete_tx::bytes [%0], [%1, {%3, %4}], [%2];" ::"r"(dst),
               "l"(m), "r"(bar), "r"(c0), "r"(c1) : "memory");
}
__device__ __forceinline__ void tma2d_mc(uint32_t dst, const CUtensorMap* m, uint32_t bar, int c0, int c1, uint16_t mask) {
  asm volatile(
      "cp.async.bulk.tensor.2d.shared::cluster.global.mbarrier::complete_tx::bytes.multicast::cluster [%0], [%1, {%3, %4}], [%2], %5;" ::"r"(dst),
      "l"(m), "r"(bar), "r"(c0), "r"(c1), "h"(mask) : "memory");
}
__device__ __forceinline__ void tma3d_mc(uint32_t dst, const CUtensorMap* m, uint32_t bar, int c0, int c1, int c2, uint16_t mask) {
  asm volatile(
      "cp.async.bulk.tensor.3d.shared::cluster.global.mbarrier::complete_tx::bytes.multicast::cluster [%0], [%1, {%3, %4, %5}], [%2], %6;" ::"r"(dst),
      "l"(m), "r"(bar), "r"(c0), "r"(c1), "r"(c2), "h"(mask) : "memory");
}
__device__ __forceinline__ void tma3d(uint32_t dst, const CUtensorMap* m, uint32_t bar, int c0, int c1, int c2) {
  asm volatile(
      "cp.async.bulk.tensor.3d.shared::cluster.global.mbarrier::complete_tx::bytes [%0], [%1, {%3, %4, %5}], [%2];" ::"r"(dst),
      "l"(m), "r"(bar), "r"(c0), "r"(c1), "r"(c2) : "memory");
}
__device__ __forceinline__ void tma_pf2d(const CUtensorMap* m, int c0, int c1) {
  asm volatile("cp.async.bulk.prefetch.tensor.2d.L2.global [%0, {%1, %2}];" ::"l"(m), "r"(c0), "r"(c1) : "memory");
}
__device__ __forceinline__ void tma_pf3d(const CUtensorMap* m, int c0, int c1, int c2) {
  asm volatile("cp.async.bulk.prefetch.tensor.3d.L2.global [%0, {%1, %2, %3}];" ::"l"(m), "r"(c0), "r"(c1), "r"(c2) : "memory");
}
__device__ __forceinline__ void prefetch_tmap(const CUtensorMap* m) {
  asm volatile("prefetch.tensormap [%0];" ::"l"(m) : "memory");
}
__device__ __forceinline__ void cluster_sync() {
  asm volatile("barrier.cluster.arrive.aligned;\nbarrier.cluster.wait.aligned;" ::: "memory");
}
__device__ __forceinline__ uint32_t cluster_rank() {
  uint32_t r;
  asm volatile("mov.u32 %0, %%cluster_ctarank;" : "=r"(r));
  return r;
}
__device__ __forceinline__ void pdl_wait() { asm volatile("griddepcontrol.wait;" ::: "memory"); }
__device__ __forceinline__ void pdl_launch() { asm volatile("griddepcontrol.launch_dependents;" ::: "memory"); }
__device__ __forceinline__ void ldsm_x4(uint32_t& r0, uint32_t& r1, uint32_t& r2, uint32_t& r3, uint32_t addr) {
  asm volatile("ldmatrix.sync.aligned.m8n8.x4.shared.b16 {%0, %1, %2, %3}, [%4];" : "=r"(r0), "=r"(r1), "=r"(r2), "=r"(r3) : "r"(addr) : "memory");
}
__device__ __forceinline__ void wg_fence() { asm volatile("wgmma.fence.sync.aligned;" ::: "memory"); }
__device__ __forceinline__ void wg_commit() { asm volatile("wgmma.commit_group.sync.aligned;" ::: "memory"); }
template <int N>
__device__ __forceinline__ void wg_wait() { asm volatile("wgmma.wait_group.sync.aligned %0;" ::"n"(N) : "memory"); }
template <int N>
__device__ __forceinline__ void reg_alloc() { asm volatile("setmaxnreg.inc.sync.aligned.u32 %0;" ::"n"(N)); }
template <int N>
__device__ __forceinline__ void reg_dealloc() { asm volatile("setmaxnreg.dec.sync.aligned.u32 %0;" ::"n"(N)); }
__device__ __forceinline__ void bar_sync(int id, int n) { asm volatile("bar.sync %0, %1;" ::"r"(id), "r"(n) : "memory"); }
__device__ __forceinline__ void bar_arrive(int id, int n) { asm volatile("bar.arrive %0, %1;" ::"r"(id), "r"(n) : "memory"); }
template <int NT>
__device__ __forceinline__ void fence_regs(float (&d)[NT]) {
#pragma unroll
  for (int i = 0; i < NT; i++) asm volatile("" : "+f"(d[i])::"memory");
}
template <int NT>
__device__ __forceinline__ void fence_regs(uint32_t (&d)[NT]) {
#pragma unroll
  for (int i = 0; i < NT; i++) asm volatile("" : "+r"(d[i])::"memory");
}
__device__ __forceinline__ uint64_t make_desc(uint32_t saddr, uint32_t lbo, uint32_t sbo, uint32_t layout) {
  return (uint64_t)((saddr & 0x3FFFF) >> 4) | ((uint64_t)(lbo >> 4) << 16) | ((uint64_t)(sbo >> 4) << 32) | ((uint64_t)layout << 62);
}
__device__ __forceinline__ uint32_t pack_bf16(float lo, float hi) {
  uint32_t r;
  asm("cvt.rn.bf16x2.f32 %0, %1, %2;" : "=r"(r) : "f"(hi), "f"(lo));
  return r;
}
__device__ __forceinline__ float ex2(float x) {
  float r;
  asm("ex2.approx.ftz.f32 %0, %1;" : "=f"(r) : "f"(x));
  return r;
}
__device__ __forceinline__ void st_v4(void* p, uint32_t a, uint32_t b, uint32_t c, uint32_t d) {
#define ST_MOD ""
  asm volatile("st.global" ST_MOD ".v4.b32 [%0], {%1, %2, %3, %4};" ::"l"(p), "r"(a), "r"(b), "r"(c), "r"(d) : "memory");
}
__device__ __forceinline__ float bf_lo(uint32_t v) { return __uint_as_float(v << 16); }
__device__ __forceinline__ float bf_hi(uint32_t v) { return __uint_as_float(v & 0xFFFF0000u); }

__device__ __forceinline__ void quad_transpose(uint32_t& a0, uint32_t& a1, uint32_t& a2, uint32_t& a3, int q) {
  const bool o1 = q & 1, o2 = q & 2;
  uint32_t t0 = o1 ? a0 : a1, t1 = o1 ? a2 : a3;
  t0 = __shfl_xor_sync(0xffffffffu, t0, 1);
  t1 = __shfl_xor_sync(0xffffffffu, t1, 1);
  if (o1) { a0 = t0; a2 = t1; } else { a1 = t0; a3 = t1; }
  t0 = o2 ? a0 : a2;
  t1 = o2 ? a1 : a3;
  t0 = __shfl_xor_sync(0xffffffffu, t0, 2);
  t1 = __shfl_xor_sync(0xffffffffu, t1, 2);
  if (o2) { a0 = t0; a1 = t1; } else { a2 = t0; a3 = t1; }
}

template<int TB, int OFF, int NT>
__device__ __forceinline__ void wgmma_ss_n256(float (&d)[NT], uint64_t da, uint64_t db, int scale_d) {
  asm volatile("{\n.reg .pred p;\nsetp.ne.b32 p, %130, 0;\n"
    "wgmma.mma_async.sync.aligned.m64n256k16.f32.bf16.bf16 {%0, %1, %2, %3, %4, %5, %6, %7, %8, %9, %10, %11, %12, %13, %14, %15, %16, %17, %18, %19, %20, %21, %22, %23, %24, %25, %26, %27, %28, %29, %30, %31, %32, %33, %34, %35, %36, %37, %38, %39, %40, %41, %42, %43, %44, %45, %46, %47, %48, %49, %50, %51, %52, %53, %54, %55, %56, %57, %58, %59, %60, %61, %62, %63, %64, %65, %66, %67, %68, %69, %70, %71, %72, %73, %74, %75, %76, %77, %78, %79, %80, %81, %82, %83, %84, %85, %86, %87, %88, %89, %90, %91, %92, %93, %94, %95, %96, %97, %98, %99, %100, %101, %102, %103, %104, %105, %106, %107, %108, %109, %110, %111, %112, %113, %114, %115, %116, %117, %118, %119, %120, %121, %122, %123, %124, %125, %126, %127}, %128, %129, p, 1, 1, 0, %131;\n}\n"
    : "+f"(d[OFF+0]), "+f"(d[OFF+1]), "+f"(d[OFF+2]), "+f"(d[OFF+3]), "+f"(d[OFF+4]), "+f"(d[OFF+5]), "+f"(d[OFF+6]), "+f"(d[OFF+7]), "+f"(d[OFF+8]), "+f"(d[OFF+9]), "+f"(d[OFF+10]), "+f"(d[OFF+11]), "+f"(d[OFF+12]), "+f"(d[OFF+13]), "+f"(d[OFF+14]), "+f"(d[OFF+15]), "+f"(d[OFF+16]), "+f"(d[OFF+17]), "+f"(d[OFF+18]), "+f"(d[OFF+19]), "+f"(d[OFF+20]), "+f"(d[OFF+21]), "+f"(d[OFF+22]), "+f"(d[OFF+23]), "+f"(d[OFF+24]), "+f"(d[OFF+25]), "+f"(d[OFF+26]), "+f"(d[OFF+27]), "+f"(d[OFF+28]), "+f"(d[OFF+29]), "+f"(d[OFF+30]), "+f"(d[OFF+31]), "+f"(d[OFF+32]), "+f"(d[OFF+33]), "+f"(d[OFF+34]), "+f"(d[OFF+35]), "+f"(d[OFF+36]), "+f"(d[OFF+37]), "+f"(d[OFF+38]), "+f"(d[OFF+39]), "+f"(d[OFF+40]), "+f"(d[OFF+41]), "+f"(d[OFF+42]), "+f"(d[OFF+43]), "+f"(d[OFF+44]), "+f"(d[OFF+45]), "+f"(d[OFF+46]), "+f"(d[OFF+47]), "+f"(d[OFF+48]), "+f"(d[OFF+49]), "+f"(d[OFF+50]), "+f"(d[OFF+51]), "+f"(d[OFF+52]), "+f"(d[OFF+53]), "+f"(d[OFF+54]), "+f"(d[OFF+55]), "+f"(d[OFF+56]), "+f"(d[OFF+57]), "+f"(d[OFF+58]), "+f"(d[OFF+59]), "+f"(d[OFF+60]), "+f"(d[OFF+61]), "+f"(d[OFF+62]), "+f"(d[OFF+63]), "+f"(d[OFF+64]), "+f"(d[OFF+65]), "+f"(d[OFF+66]), "+f"(d[OFF+67]), "+f"(d[OFF+68]), "+f"(d[OFF+69]), "+f"(d[OFF+70]), "+f"(d[OFF+71]), "+f"(d[OFF+72]), "+f"(d[OFF+73]), "+f"(d[OFF+74]), "+f"(d[OFF+75]), "+f"(d[OFF+76]), "+f"(d[OFF+77]), "+f"(d[OFF+78]), "+f"(d[OFF+79]), "+f"(d[OFF+80]), "+f"(d[OFF+81]), "+f"(d[OFF+82]), "+f"(d[OFF+83]), "+f"(d[OFF+84]), "+f"(d[OFF+85]), "+f"(d[OFF+86]), "+f"(d[OFF+87]), "+f"(d[OFF+88]), "+f"(d[OFF+89]), "+f"(d[OFF+90]), "+f"(d[OFF+91]), "+f"(d[OFF+92]), "+f"(d[OFF+93]), "+f"(d[OFF+94]), "+f"(d[OFF+95]), "+f"(d[OFF+96]), "+f"(d[OFF+97]), "+f"(d[OFF+98]), "+f"(d[OFF+99]), "+f"(d[OFF+100]), "+f"(d[OFF+101]), "+f"(d[OFF+102]), "+f"(d[OFF+103]), "+f"(d[OFF+104]), "+f"(d[OFF+105]), "+f"(d[OFF+106]), "+f"(d[OFF+107]), "+f"(d[OFF+108]), "+f"(d[OFF+109]), "+f"(d[OFF+110]), "+f"(d[OFF+111]), "+f"(d[OFF+112]), "+f"(d[OFF+113]), "+f"(d[OFF+114]), "+f"(d[OFF+115]), "+f"(d[OFF+116]), "+f"(d[OFF+117]), "+f"(d[OFF+118]), "+f"(d[OFF+119]), "+f"(d[OFF+120]), "+f"(d[OFF+121]), "+f"(d[OFF+122]), "+f"(d[OFF+123]), "+f"(d[OFF+124]), "+f"(d[OFF+125]), "+f"(d[OFF+126]), "+f"(d[OFF+127])
    : "l"(da), "l"(db), "r"(scale_d), "n"(TB));
}
template<int TB, int OFF, int NT>
__device__ __forceinline__ void wgmma_ss_n192(float (&d)[NT], uint64_t da, uint64_t db, int scale_d) {
  asm volatile("{\n.reg .pred p;\nsetp.ne.b32 p, %98, 0;\n"
    "wgmma.mma_async.sync.aligned.m64n192k16.f32.bf16.bf16 {%0, %1, %2, %3, %4, %5, %6, %7, %8, %9, %10, %11, %12, %13, %14, %15, %16, %17, %18, %19, %20, %21, %22, %23, %24, %25, %26, %27, %28, %29, %30, %31, %32, %33, %34, %35, %36, %37, %38, %39, %40, %41, %42, %43, %44, %45, %46, %47, %48, %49, %50, %51, %52, %53, %54, %55, %56, %57, %58, %59, %60, %61, %62, %63, %64, %65, %66, %67, %68, %69, %70, %71, %72, %73, %74, %75, %76, %77, %78, %79, %80, %81, %82, %83, %84, %85, %86, %87, %88, %89, %90, %91, %92, %93, %94, %95}, %96, %97, p, 1, 1, 0, %99;\n}\n"
    : "+f"(d[OFF+0]), "+f"(d[OFF+1]), "+f"(d[OFF+2]), "+f"(d[OFF+3]), "+f"(d[OFF+4]), "+f"(d[OFF+5]), "+f"(d[OFF+6]), "+f"(d[OFF+7]), "+f"(d[OFF+8]), "+f"(d[OFF+9]), "+f"(d[OFF+10]), "+f"(d[OFF+11]), "+f"(d[OFF+12]), "+f"(d[OFF+13]), "+f"(d[OFF+14]), "+f"(d[OFF+15]), "+f"(d[OFF+16]), "+f"(d[OFF+17]), "+f"(d[OFF+18]), "+f"(d[OFF+19]), "+f"(d[OFF+20]), "+f"(d[OFF+21]), "+f"(d[OFF+22]), "+f"(d[OFF+23]), "+f"(d[OFF+24]), "+f"(d[OFF+25]), "+f"(d[OFF+26]), "+f"(d[OFF+27]), "+f"(d[OFF+28]), "+f"(d[OFF+29]), "+f"(d[OFF+30]), "+f"(d[OFF+31]), "+f"(d[OFF+32]), "+f"(d[OFF+33]), "+f"(d[OFF+34]), "+f"(d[OFF+35]), "+f"(d[OFF+36]), "+f"(d[OFF+37]), "+f"(d[OFF+38]), "+f"(d[OFF+39]), "+f"(d[OFF+40]), "+f"(d[OFF+41]), "+f"(d[OFF+42]), "+f"(d[OFF+43]), "+f"(d[OFF+44]), "+f"(d[OFF+45]), "+f"(d[OFF+46]), "+f"(d[OFF+47]), "+f"(d[OFF+48]), "+f"(d[OFF+49]), "+f"(d[OFF+50]), "+f"(d[OFF+51]), "+f"(d[OFF+52]), "+f"(d[OFF+53]), "+f"(d[OFF+54]), "+f"(d[OFF+55]), "+f"(d[OFF+56]), "+f"(d[OFF+57]), "+f"(d[OFF+58]), "+f"(d[OFF+59]), "+f"(d[OFF+60]), "+f"(d[OFF+61]), "+f"(d[OFF+62]), "+f"(d[OFF+63]), "+f"(d[OFF+64]), "+f"(d[OFF+65]), "+f"(d[OFF+66]), "+f"(d[OFF+67]), "+f"(d[OFF+68]), "+f"(d[OFF+69]), "+f"(d[OFF+70]), "+f"(d[OFF+71]), "+f"(d[OFF+72]), "+f"(d[OFF+73]), "+f"(d[OFF+74]), "+f"(d[OFF+75]), "+f"(d[OFF+76]), "+f"(d[OFF+77]), "+f"(d[OFF+78]), "+f"(d[OFF+79]), "+f"(d[OFF+80]), "+f"(d[OFF+81]), "+f"(d[OFF+82]), "+f"(d[OFF+83]), "+f"(d[OFF+84]), "+f"(d[OFF+85]), "+f"(d[OFF+86]), "+f"(d[OFF+87]), "+f"(d[OFF+88]), "+f"(d[OFF+89]), "+f"(d[OFF+90]), "+f"(d[OFF+91]), "+f"(d[OFF+92]), "+f"(d[OFF+93]), "+f"(d[OFF+94]), "+f"(d[OFF+95])
    : "l"(da), "l"(db), "r"(scale_d), "n"(TB));
}
template<int TB, int OFF, int NT>
__device__ __forceinline__ void wgmma_ss_n128(float (&d)[NT], uint64_t da, uint64_t db, int scale_d) {
  asm volatile("{\n.reg .pred p;\nsetp.ne.b32 p, %66, 0;\n"
    "wgmma.mma_async.sync.aligned.m64n128k16.f32.bf16.bf16 {%0, %1, %2, %3, %4, %5, %6, %7, %8, %9, %10, %11, %12, %13, %14, %15, %16, %17, %18, %19, %20, %21, %22, %23, %24, %25, %26, %27, %28, %29, %30, %31, %32, %33, %34, %35, %36, %37, %38, %39, %40, %41, %42, %43, %44, %45, %46, %47, %48, %49, %50, %51, %52, %53, %54, %55, %56, %57, %58, %59, %60, %61, %62, %63}, %64, %65, p, 1, 1, 0, %67;\n}\n"
    : "+f"(d[OFF+0]), "+f"(d[OFF+1]), "+f"(d[OFF+2]), "+f"(d[OFF+3]), "+f"(d[OFF+4]), "+f"(d[OFF+5]), "+f"(d[OFF+6]), "+f"(d[OFF+7]), "+f"(d[OFF+8]), "+f"(d[OFF+9]), "+f"(d[OFF+10]), "+f"(d[OFF+11]), "+f"(d[OFF+12]), "+f"(d[OFF+13]), "+f"(d[OFF+14]), "+f"(d[OFF+15]), "+f"(d[OFF+16]), "+f"(d[OFF+17]), "+f"(d[OFF+18]), "+f"(d[OFF+19]), "+f"(d[OFF+20]), "+f"(d[OFF+21]), "+f"(d[OFF+22]), "+f"(d[OFF+23]), "+f"(d[OFF+24]), "+f"(d[OFF+25]), "+f"(d[OFF+26]), "+f"(d[OFF+27]), "+f"(d[OFF+28]), "+f"(d[OFF+29]), "+f"(d[OFF+30]), "+f"(d[OFF+31]), "+f"(d[OFF+32]), "+f"(d[OFF+33]), "+f"(d[OFF+34]), "+f"(d[OFF+35]), "+f"(d[OFF+36]), "+f"(d[OFF+37]), "+f"(d[OFF+38]), "+f"(d[OFF+39]), "+f"(d[OFF+40]), "+f"(d[OFF+41]), "+f"(d[OFF+42]), "+f"(d[OFF+43]), "+f"(d[OFF+44]), "+f"(d[OFF+45]), "+f"(d[OFF+46]), "+f"(d[OFF+47]), "+f"(d[OFF+48]), "+f"(d[OFF+49]), "+f"(d[OFF+50]), "+f"(d[OFF+51]), "+f"(d[OFF+52]), "+f"(d[OFF+53]), "+f"(d[OFF+54]), "+f"(d[OFF+55]), "+f"(d[OFF+56]), "+f"(d[OFF+57]), "+f"(d[OFF+58]), "+f"(d[OFF+59]), "+f"(d[OFF+60]), "+f"(d[OFF+61]), "+f"(d[OFF+62]), "+f"(d[OFF+63])
    : "l"(da), "l"(db), "r"(scale_d), "n"(TB));
}
template<int TB, int OFF, int NT>
__device__ __forceinline__ void wgmma_ss_n32(float (&d)[NT], uint64_t da, uint64_t db, int scale_d) {
  asm volatile("{\n.reg .pred p;\nsetp.ne.b32 p, %18, 0;\n"
    "wgmma.mma_async.sync.aligned.m64n32k16.f32.bf16.bf16 {%0, %1, %2, %3, %4, %5, %6, %7, %8, %9, %10, %11, %12, %13, %14, %15}, %16, %17, p, 1, 1, 0, %19;\n}\n"
    : "+f"(d[OFF+0]), "+f"(d[OFF+1]), "+f"(d[OFF+2]), "+f"(d[OFF+3]), "+f"(d[OFF+4]), "+f"(d[OFF+5]), "+f"(d[OFF+6]), "+f"(d[OFF+7]), "+f"(d[OFF+8]), "+f"(d[OFF+9]), "+f"(d[OFF+10]), "+f"(d[OFF+11]), "+f"(d[OFF+12]), "+f"(d[OFF+13]), "+f"(d[OFF+14]), "+f"(d[OFF+15])
    : "l"(da), "l"(db), "r"(scale_d), "n"(TB));
}
template<int TB, int OFF, int NT>
__device__ __forceinline__ void wgmma_rs_n128(float (&d)[NT], uint32_t a0, uint32_t a1, uint32_t a2, uint32_t a3, uint64_t db, int scale_d) {
  asm volatile("{\n.reg .pred p;\nsetp.ne.b32 p, %69, 0;\n"
    "wgmma.mma_async.sync.aligned.m64n128k16.f32.bf16.bf16 {%0, %1, %2, %3, %4, %5, %6, %7, %8, %9, %10, %11, %12, %13, %14, %15, %16, %17, %18, %19, %20, %21, %22, %23, %24, %25, %26, %27, %28, %29, %30, %31, %32, %33, %34, %35, %36, %37, %38, %39, %40, %41, %42, %43, %44, %45, %46, %47, %48, %49, %50, %51, %52, %53, %54, %55, %56, %57, %58, %59, %60, %61, %62, %63}, {%64, %65, %66, %67}, %68, p, 1, 1, %70;\n}\n"
    : "+f"(d[OFF+0]), "+f"(d[OFF+1]), "+f"(d[OFF+2]), "+f"(d[OFF+3]), "+f"(d[OFF+4]), "+f"(d[OFF+5]), "+f"(d[OFF+6]), "+f"(d[OFF+7]), "+f"(d[OFF+8]), "+f"(d[OFF+9]), "+f"(d[OFF+10]), "+f"(d[OFF+11]), "+f"(d[OFF+12]), "+f"(d[OFF+13]), "+f"(d[OFF+14]), "+f"(d[OFF+15]), "+f"(d[OFF+16]), "+f"(d[OFF+17]), "+f"(d[OFF+18]), "+f"(d[OFF+19]), "+f"(d[OFF+20]), "+f"(d[OFF+21]), "+f"(d[OFF+22]), "+f"(d[OFF+23]), "+f"(d[OFF+24]), "+f"(d[OFF+25]), "+f"(d[OFF+26]), "+f"(d[OFF+27]), "+f"(d[OFF+28]), "+f"(d[OFF+29]), "+f"(d[OFF+30]), "+f"(d[OFF+31]), "+f"(d[OFF+32]), "+f"(d[OFF+33]), "+f"(d[OFF+34]), "+f"(d[OFF+35]), "+f"(d[OFF+36]), "+f"(d[OFF+37]), "+f"(d[OFF+38]), "+f"(d[OFF+39]), "+f"(d[OFF+40]), "+f"(d[OFF+41]), "+f"(d[OFF+42]), "+f"(d[OFF+43]), "+f"(d[OFF+44]), "+f"(d[OFF+45]), "+f"(d[OFF+46]), "+f"(d[OFF+47]), "+f"(d[OFF+48]), "+f"(d[OFF+49]), "+f"(d[OFF+50]), "+f"(d[OFF+51]), "+f"(d[OFF+52]), "+f"(d[OFF+53]), "+f"(d[OFF+54]), "+f"(d[OFF+55]), "+f"(d[OFF+56]), "+f"(d[OFF+57]), "+f"(d[OFF+58]), "+f"(d[OFF+59]), "+f"(d[OFF+60]), "+f"(d[OFF+61]), "+f"(d[OFF+62]), "+f"(d[OFF+63])
    : "r"(a0), "r"(a1), "r"(a2), "r"(a3), "l"(db), "r"(scale_d), "n"(TB));
}
template<int TB, int OFF, int NT>
__device__ __forceinline__ void wgmma_rs_n64(float (&d)[NT], uint32_t a0, uint32_t a1, uint32_t a2, uint32_t a3, uint64_t db, int scale_d) {
  asm volatile("{\n.reg .pred p;\nsetp.ne.b32 p, %37, 0;\n"
    "wgmma.mma_async.sync.aligned.m64n64k16.f32.bf16.bf16 {%0, %1, %2, %3, %4, %5, %6, %7, %8, %9, %10, %11, %12, %13, %14, %15, %16, %17, %18, %19, %20, %21, %22, %23, %24, %25, %26, %27, %28, %29, %30, %31}, {%32, %33, %34, %35}, %36, p, 1, 1, %38;\n}\n"
    : "+f"(d[OFF+0]), "+f"(d[OFF+1]), "+f"(d[OFF+2]), "+f"(d[OFF+3]), "+f"(d[OFF+4]), "+f"(d[OFF+5]), "+f"(d[OFF+6]), "+f"(d[OFF+7]), "+f"(d[OFF+8]), "+f"(d[OFF+9]), "+f"(d[OFF+10]), "+f"(d[OFF+11]), "+f"(d[OFF+12]), "+f"(d[OFF+13]), "+f"(d[OFF+14]), "+f"(d[OFF+15]), "+f"(d[OFF+16]), "+f"(d[OFF+17]), "+f"(d[OFF+18]), "+f"(d[OFF+19]), "+f"(d[OFF+20]), "+f"(d[OFF+21]), "+f"(d[OFF+22]), "+f"(d[OFF+23]), "+f"(d[OFF+24]), "+f"(d[OFF+25]), "+f"(d[OFF+26]), "+f"(d[OFF+27]), "+f"(d[OFF+28]), "+f"(d[OFF+29]), "+f"(d[OFF+30]), "+f"(d[OFF+31])
    : "r"(a0), "r"(a1), "r"(a2), "r"(a3), "l"(db), "r"(scale_d), "n"(TB));
}

__device__ __forceinline__ void wait_flag(const unsigned int* f, uint32_t target) {
  uint32_t v;
#pragma unroll 1
  for (uint32_t spins = 0; spins < (1u << 22); spins++) {
    asm volatile("ld.acquire.gpu.global.u32 %0, [%1];" : "=r"(v) : "l"(f) : "memory");
    if (v >= target) break;
    __nanosleep(100);
  }
}
__device__ __forceinline__ uint32_t lds32(uint32_t a) {
  uint32_t v;
  asm volatile("ld.shared.u32 %0, [%1];" : "=r"(v) : "r"(a) : "memory");
  return v;
}
__device__ __forceinline__ float gate_row(int row, int lane, const bf16* __restrict__ x, const bf16* __restrict__ gate_w) {
  const uint32_t* xr = reinterpret_cast<const uint32_t*>(x + (size_t)row * DM);
  const uint32_t* gw2 = reinterpret_cast<const uint32_t*>(gate_w);
  float gs = 0.f;
#pragma unroll
  for (int i = 0; i < 9; i++) {
    const uint32_t a = __ldg(xr + lane + 32 * i), b = __ldg(gw2 + lane + 32 * i);
    gs = fmaf(bf_lo(a), bf_lo(b), gs);
    gs = fmaf(bf_hi(a), bf_hi(b), gs);
  }
#pragma unroll
  for (int o = 16; o; o >>= 1) gs += __shfl_xor_sync(0xffffffffu, gs, o);
  const float g = 1.f / (1.f + __expf(-gs));
  if (lane == 0) g_gate[row] = g;
  return g;
}
__device__ __forceinline__ void local_rows2(int row, uint32_t srow, int lane, float g0, float g1) {
  const float scale_l2 = 0.23570226039551584f * 1.4426950408889634f;
  const uint32_t srow0 = srow;
  float q[2][18], o[2][18], mx[2], sum[2];
#pragma unroll
  for (int r = 0; r < 2; r++) {
#pragma unroll
    for (int i = 0; i < 9; i++) {
      const uint32_t v = lds32(srow + r * 3456 + 4 * i);
      q[r][2 * i] = bf_lo(v);
      q[r][2 * i + 1] = bf_hi(v);
      o[r][2 * i] = 0.f;
      o[r][2 * i + 1] = 0.f;
    }
    mx[r] = -INFINITY;
    sum[r] = 0.f;
  }
  const int nw = min(8, (row >> 1) + 1);
#pragma unroll 1
  for (int w = 0; w < nw; w++, srow -= 2 * 3456) {
#pragma unroll
    for (int r = 0; r < 2; r++) {
      float s0 = 0.f, s1 = 0.f, s2 = 0.f;
#pragma unroll
      for (int i = 0; i < 3; i++) {
        const uint32_t k0 = lds32(srow + r * 3456 + 1152 + 4 * i), k1 = lds32(srow + r * 3456 + 1164 + 4 * i), k2 = lds32(srow + r * 3456 + 1176 + 4 * i);
        s0 = fmaf(q[r][2 * i], bf_lo(k0), s0);
        s1 = fmaf(q[r][6 + 2 * i], bf_lo(k1), s1);
        s2 = fmaf(q[r][12 + 2 * i], bf_lo(k2), s2);
        s0 = fmaf(q[r][2 * i + 1], bf_hi(k0), s0);
        s1 = fmaf(q[r][6 + 2 * i + 1], bf_hi(k1), s1);
        s2 = fmaf(q[r][12 + 2 * i + 1], bf_hi(k2), s2);
      }
      const float s = s0 + s1 + s2;
      const float mn = fmaxf(mx[r], s);
      const float sc = ex2((mx[r] - mn) * scale_l2), pw = ex2((s - mn) * scale_l2);
      mx[r] = mn;
      sum[r] = fmaf(sum[r], sc, pw);
#pragma unroll
      for (int i = 0; i < 9; i++) {
        const uint32_t vv = lds32(srow + r * 3456 + 2304 + 4 * i);
        o[r][2 * i] = fmaf(pw, bf_lo(vv), o[r][2 * i] * sc);
        o[r][2 * i + 1] = fmaf(pw, bf_hi(vv), o[r][2 * i + 1] * sc);
      }
    }
  }
#pragma unroll
  for (int r = 0; r < 2; r++) {
    const float f = (r ? g1 : g0) / sum[r];
#pragma unroll
    for (int i = 0; i < 9; i++)
      asm volatile("st.shared.u32 [%0], %1;" ::"r"(srow0 + r * 3456 + 4 * i), "r"(pack_bf16(o[r][2 * i] * f, o[r][2 * i + 1] * f)) : "memory");
  }
  __syncwarp();
  const uint32_t sb = srow0 - lane * 36;
#pragma unroll
  for (int t = 0; t < 5; t++) {
    const int c = t * 32 + lane;
    if (c < 144) {
      const int r = c >= 72, cc = c - r * 72;
      uint32_t a, b, d, e;
      asm volatile("ld.shared.v4.u32 {%0, %1, %2, %3}, [%4];" : "=r"(a), "=r"(b), "=r"(d), "=r"(e) : "r"(sb + r * 3456 + cc * 16) : "memory");
      st_v4(g_ctx + (size_t)(row + r) * KCAT + HDIM + cc * 8, a, b, d, e);
    }
  }
}

#define K1_NST 6
constexpr int K1_BST = K1_NST;
constexpr int K1_MAXJOBS = 10;
constexpr uint32_t K1_FLAG_TARGET = 7;
constexpr uint32_t RDY_TARGET = 48;
constexpr uint32_t GATE_TARGET = 128 * 3;
struct alignas(64) Params {
  CUtensorMap tmA[2];
  CUtensorMap tmW[4];
  CUtensorMap tmQ, tmK, tmV;
  CUtensorMap tmC, tmO[2], tmOt[2];
  uint16_t jobs[NCLUSTER][K1_MAXJOBS];
  uint8_t order[256];
};

struct K1State {
  uint32_t bs, bph, aph;
  bf16* pp;
  int pld8;
  int png;
};
__device__ __forceinline__ void k1_flag(const K1State& st, int lane, uint32_t bS) {
  if (st.png) {
    __syncwarp();
    if (lane == 0) mbar_arrive(bS);
  }
}

__device__ __forceinline__ void k1_tile(float (&acc)[128], uint32_t (&pk)[64], K1State& st, uint32_t job, uint32_t sA, uint32_t sB,
                                        uint32_t bAf, uint32_t bAe, uint32_t bBf, uint32_t bBe, uint32_t bS, int wg, int warp, int lane, uint32_t rank) {
  const int a_sel = (job >> 2) & 1, mpair = (job >> 3) & 7, w_sel = (job >> 6) & 3, chunk0 = (job >> 8) & 63;
  const bool newA = (job >> 14) & 1, lastA = (job >> 15) & 1;
  const bool sig = (lane == 0) && (warp < 2);
  const bool siga = lastA && (lane == 0) && (warp == 2);
  const int KC = 8 + a_sel;
  uint32_t prev_bs = 0, prev2_bs = 0, a8_bs = 0;
#pragma unroll
  for (int kc = 0; kc < 9; kc++) {
    if (kc >= KC) break;
    uint32_t abase = sA + kc * 16384;
    if (kc == 8) {
      mbar_wait(bBf + st.bs * 8, st.bph);
      a8_bs = st.bs;
      abase = sB + st.bs * 16384;
      if (++st.bs == K1_BST) { st.bs = 0; st.bph ^= 1; }
    } else if (newA) {
      mbar_wait(bAf + kc * 8, st.aph);
    }
    const uint64_t da = make_desc(abase + wg * 8192, 16, 1024, 1);
#pragma unroll
    for (int ks = 0; ks < 2; ks++) {
      mbar_wait(bBf + st.bs * 8, st.bph);
      const uint64_t db = make_desc(sB + st.bs * 16384, 2048, 1024, 1);
      wg_fence();
      wgmma_ss_n256<1, 0>(acc, da + (uint64_t)(ks * 4), db, (ks > 0) ? 1 : (kc > 0));
      wgmma_ss_n256<1, 0>(acc, da + (uint64_t)(ks * 4 + 2), db + (uint64_t)512, 1);
      wg_commit();
      const int PO = (kc < 8 ? kc : 0) * 8;
      wg_wait<1>();
      if (ks > 0 || kc > 0) {
        if (sig) mbar_arrive_cluster(bBe + prev_bs * 8, warp);
        if (ks == 0 && siga) mbar_arrive(bAe + (kc - 1) * 8);
      }
      if (kc < st.png) st_v4(st.pp + kc * 32 + ks * st.pld8, pk[PO + ks * 4], pk[PO + ks * 4 + 1], pk[PO + ks * 4 + 2], pk[PO + ks * 4 + 3]);
      prev_bs = st.bs;
      if (++st.bs == K1_BST) { st.bs = 0; st.bph ^= 1; }
    }
  }
  if (newA) st.aph ^= 1;
  k1_flag(st, lane, bS);
  wg_wait<0>();
  fence_regs(acc);
  if (sig) {
    mbar_arrive_cluster(bBe + prev_bs * 8, warp);
    if (a_sel) mbar_arrive_cluster(bBe + a8_bs * 8, warp);
  }
  if (siga && !a_sel) mbar_arrive(bAe + 7 * 8);
  const bool isA = (w_sel == 2);
  bf16* out = (w_sel == 0) ? g_K : (w_sel == 1) ? g_V : isA ? g_QKVA : g_Q;
  const int ld = isA ? NQKVA : HDIM;
  const int row = mpair * 256 + rank * 128 + wg * 64 + warp * 16 + (lane >> 2);
  st.pp = out + (size_t)row * ld + chunk0 * 64 + (lane & 3) * 8;
  st.pld8 = 8 * ld;
  st.png = ((job & 3) + 1) * 2;
#pragma unroll
  for (int G = 0; G < 8; G++) {
    pk[G * 8 + 0] = pack_bf16(acc[G * 16 + 0], acc[G * 16 + 1]);
    pk[G * 8 + 1] = pack_bf16(acc[G * 16 + 4], acc[G * 16 + 5]);
    pk[G * 8 + 2] = pack_bf16(acc[G * 16 + 8], acc[G * 16 + 9]);
    pk[G * 8 + 3] = pack_bf16(acc[G * 16 + 12], acc[G * 16 + 13]);
    pk[G * 8 + 4] = pack_bf16(acc[G * 16 + 2], acc[G * 16 + 3]);
    pk[G * 8 + 5] = pack_bf16(acc[G * 16 + 6], acc[G * 16 + 7]);
    pk[G * 8 + 6] = pack_bf16(acc[G * 16 + 10], acc[G * 16 + 11]);
    pk[G * 8 + 7] = pack_bf16(acc[G * 16 + 14], acc[G * 16 + 15]);
  }
  if (isA) {
#pragma unroll
    for (int G = 0; G < 16; G++) quad_transpose(pk[G * 4 + 0], pk[G * 4 + 1], pk[G * 4 + 2], pk[G * 4 + 3], lane & 3);
  }
}

constexpr int K2_NST = 7;
constexpr uint32_t K2_END = 0x100;
constexpr int K3_NST = 4;
constexpr int K3_STAGE = 16384 + 32768 + 4096;
constexpr int SMEM_DATA = 7 * 32768;
constexpr int SMEM_BYTES = SMEM_DATA + 1024 + 768;

struct Cursor {
  uint32_t s, ph;
  __device__ __forceinline__ void next() {
    if (++s == K2_NST) { s = 0; ph ^= 1; }
  }
};

#define TURN_SYNC() bar_sync(mybar, 256)
#define TURN_ARRIVE() bar_arrive(otherbar, 256)
#define RELEASE(cur) do { if (sig) mbar_arrive_cluster(bE + (cur).s * 8, warp); } while (0)
#define ISSUE_PV(cur, first)                                                                                   \
  do {                                                                                                         \
    const uint64_t dv = make_desc(sbase + (cur).s * 32768, 16384, 1024, 1);                                    \
    _Pragma("unroll") for (int t = 0; t < 8; t++)                                                              \
        wgmma_rs_n128<1, 0>(O, P[4 * t], P[4 * t + 1], P[4 * t + 2], P[4 * t + 3], dv + (uint64_t)(t * 128), (t > 0) ? 1 : !(first)); \
  } while (0)
#define ISSUE_QK(cur)                                                                                          \
  do {                                                                                                         \
    const uint64_t dk = make_desc(sbase + (cur).s * 32768, 16, 1024, 1);                                       \
    _Pragma("unroll") for (int t = 0; t < 8; t++)                                                              \
        wgmma_rs_n128<0, 0>(S, Q[4 * t], Q[4 * t + 1], Q[4 * t + 2], Q[4 * t + 3], dk + (uint64_t)((t >> 2) * 1024 + (t & 3) * 2), t > 0); \
  } while (0)
#define EPILOGUE()                                                                                             \
  do {                                                                                                         \
    l0 += __shfl_xor_sync(0xffffffffu, l0, 1);                                                                 \
    l0 += __shfl_xor_sync(0xffffffffu, l0, 2);                                                                 \
    l1 += __shfl_xor_sync(0xffffffffu, l1, 1);                                                                 \
    l1 += __shfl_xor_sync(0xffffffffu, l1, 2);                                                                 \
    const float f0 = gf0 / l0, f1 = gf1 / l1;                                                                  \
    bf16* o0 = g_ctx + (size_t)prev_row * KCAT + prev_h * 128 + q * 8;                                         \
    bf16* o1 = o0 + (size_t)8 * KCAT;                                                                          \
    _Pragma("unroll") for (int G = 0; G < 4; G++) {                                                            \
      st_v4(o0 + G * 32, pack_bf16(O[G * 16 + 0] * f0, O[G * 16 + 1] * f0), pack_bf16(O[G * 16 + 4] * f0, O[G * 16 + 5] * f0), \
            pack_bf16(O[G * 16 + 8] * f0, O[G * 16 + 9] * f0), pack_bf16(O[G * 16 + 12] * f0, O[G * 16 + 13] * f0)); \
      st_v4(o1 + G * 32, pack_bf16(O[G * 16 + 2] * f1, O[G * 16 + 3] * f1), pack_bf16(O[G * 16 + 6] * f1, O[G * 16 + 7] * f1), \
            pack_bf16(O[G * 16 + 10] * f1, O[G * 16 + 11] * f1), pack_bf16(O[G * 16 + 14] * f1, O[G * 16 + 15] * f1)); \
    }                                                                                                          \
  } while (0)

__global__ void __cluster_dims__(2, 1, 1) __launch_bounds__(384, 1)
fused_kernel(const __grid_constant__ Params p, const bf16* __restrict__ x, const bf16* __restrict__ gate_w, bf16* __restrict__ out) {
  extern __shared__ uint8_t smem_raw[];
  const uint32_t sbase = (smem_u32(smem_raw) + 1023) & ~1023u;
  const uint32_t sB = sbase, sA = sbase + K1_BST * 16384, sBar = sbase + SMEM_DATA;
  const uint32_t bAf = sBar, bAe = sBar + 64, bBf = sBar + 128, bBe = sBar + 176, bL = sBar + 224, bS = sBar + 232;
  const uint32_t bF = sBar + 256, bE = sBar + 320, bT = sBar + 384, sTick = sBar + 400, sItem = sBar + 416, bS2 = sBar + 448;
  const uint32_t b3F = sBar + 512, b3E = sBar + 544, sGate = sBar + 576;
  const int tid = threadIdx.x, warp_g = __shfl_sync(0xffffffffu, tid >> 5, 0), lane = tid & 31;
  const uint32_t rank = cluster_rank();
  const int cl = blockIdx.x >> 1;
  TSM(0);
  if (tid == 0) {
    for (int i = 0; i < 8; i++) { mbar_init(bAf + i * 8, 1); mbar_init(bAe + i * 8, 2); }
    for (int i = 0; i < K1_BST; i++) { mbar_init(bBf + i * 8, 1); mbar_init(bBe + i * 8, 4); }
    mbar_init(bL, 1);
    mbar_init(bS, 8);
    for (int i = 0; i < K2_NST; i++) { mbar_init(bF + i * 8, 1); mbar_init(bE + i * 8, 4); }
    mbar_init(bT, 1); mbar_init(bT + 8, 1);
    mbar_init(bS2, 8);
    for (int i = 0; i < K3_NST; i++) { mbar_init(b3F + i * 8, 1); mbar_init(b3E + i * 8, 4); }
    asm volatile("fence.mbarrier_init.release.cluster;" ::: "memory");
  }
  __syncthreads();
  cluster_sync();
  const int lr0 = blockIdx.x * 16, lrs = max(lr0 - 14, 0);

  if (warp_g >= 8) {
    reg_dealloc<40>();
    if (warp_g == 8) {
      if (lane == 0) {
        uint32_t bs = 0, bph = 1, aph = 1;
        for (int ji = 0; ji < K1_MAXJOBS; ji++) {
          const uint32_t job = p.jobs[cl][ji];
          if (!(job & 3)) break;
          const int a_sel = (job >> 2) & 1, mpair = (job >> 3) & 7, chunk0 = (job >> 8) & 63;
          const bool newA = (job >> 14) & 1;
          const int KC = a_sel ? 9 : 8;
          const uint32_t halfbytes = 8192;
          const CUtensorMap* tw = &p.tmW[(job >> 6) & 3];
          {
            const uint32_t njob = (ji + 1 < K1_MAXJOBS) ? p.jobs[cl][ji + 1] : 0;
            if (njob & 3) {
              const int nst = ((njob >> 2) & 1) ? 18 : 16;
              for (int t = (cl < 64) ? (cl & 7) : 0; t < nst; t += (cl < 64) ? 8 : 1)
                tma_pf3d(&p.tmW[(njob >> 6) & 3], 0, t * 32 + rank * 16, (njob >> 8) & 63);
            }
          }
          for (int kc = 0; kc < KC; kc++) {
            if (kc == 8) {
              mbar_wait(bBe + bs * 8, bph);
              mbar_expect(bBf + bs * 8, 16384);
              tma2d(sB + bs * 16384, &p.tmA[1], bBf + bs * 8, 512, mpair * 256 + rank * 128);
              if (++bs == K1_BST) { bs = 0; bph ^= 1; }
            } else if (newA) {
              mbar_wait(bAe + kc * 8, aph);
              mbar_expect(bAf + kc * 8, 16384);
              tma2d(sA + kc * 16384, &p.tmA[a_sel], bAf + kc * 8, kc * 64, mpair * 256 + rank * 128);
            }
            for (int kk = 0; kk < 2; kk++) {
              mbar_wait(bBe + bs * 8, bph);
              mbar_expect(bBf + bs * 8, 2 * halfbytes);
              tma3d_mc(sB + bs * 16384 + rank * halfbytes, tw, bBf + bs * 8, 0, kc * 64 + kk * 32 + rank * 16, chunk0, 3);
              if (++bs == K1_BST) { bs = 0; bph ^= 1; }
            }
          }
          if (newA) aph ^= 1;
        }
        prefetch_tmap(&p.tmQ); prefetch_tmap(&p.tmK); prefetch_tmap(&p.tmV);
        if (lr0 < S_LEN) {
          wait_flag(&g_sync[F_QKVA + (lr0 >> 7)], K1_FLAG_TARGET);
          wait_flag(&g_sync[F_QKVA + (lrs >> 7)], K1_FLAG_TARGET);
          asm volatile("fence.proxy.async;" ::: "memory");
          const uint32_t bytes = (lr0 + 16 - lrs) * (NQKVA * 2);
          mbar_expect(bL, bytes);
          for (uint32_t o = 0; o < bytes; o += 16384) {
            mbar_wait(bAe + (o >> 14) * 8, aph);
            asm volatile("cp.async.bulk.shared::cluster.global.mbarrier::complete_tx::bytes [%0], [%1], %2, [%3];" ::"r"(sA + o),
                         "l"(reinterpret_cast<const char*>(g_QKVA + (size_t)lrs * NQKVA) + o), "r"(min(bytes - o, 16384u)), "r"(bL) : "memory");
          }
        }
        Cursor c{0, 0};
        int pcol = 0;
        uint32_t seen = 0, tick = cl;
        wait_flag(&g_sync[F_GATE], GATE_TARGET);
#pragma unroll 1
        for (int it = 0;; it++) {
          const uint32_t item = (tick < 256) ? p.order[tick] : (K2_END | min(tick - 256, 255u));
          asm volatile("st.shared.u32 [%0], %1;" ::"r"(sItem + (it & 7) * 4), "r"(item) : "memory");
          if (item >= K2_END) break;
          const int h = item >> 3, j = item & 7;
          const int blk = 2 * j + (int)(rank ^ (it & 1));
          const int col = h * 128 + rank * 64;
          const int nb = 2 * j + 2;
          if (!((seen >> (h >> 1)) & 1)) {
            wait_flag(&g_sync[F_HP + (h >> 1)], RDY_TARGET);
            asm volatile("fence.proxy.async;" ::: "memory");
            seen |= 1u << (h >> 1);
          }
          mbar_wait(bE + c.s * 8, c.ph);
          mbar_expect(bF + c.s * 8, 32768);
          tma2d(sbase + c.s * 32768, &p.tmQ, bF + c.s * 8, h * 128, blk * 128);
          tma2d(sbase + c.s * 32768 + 16384, &p.tmQ, bF + c.s * 8, h * 128 + 64, blk * 128);
          c.next();
#pragma unroll 1
          for (int n = nb - 1; n >= 0; n--) {
            if (n == 0 && rank == 0) tick = atomicAdd(&g_sync[F_TICK], 1u) + NCLUSTER;
            mbar_wait(bE + c.s * 8, c.ph);
            mbar_expect(bF + c.s * 8, 32768);
            tma2d_mc(sbase + c.s * 32768 + rank * 16384, &p.tmK, bF + c.s * 8, col, n * 128, 3);
            c.next();
            if (n < nb - 1 || it > 0) {
              mbar_wait(bE + c.s * 8, c.ph);
              mbar_expect(bF + c.s * 8, 32768);
              if (n < nb - 1)
                tma2d_mc(sbase + c.s * 32768 + rank * 16384, &p.tmV, bF + c.s * 8, col, (n + 1) * 128, 3);
              else
                tma2d_mc(sbase + c.s * 32768 + rank * 16384, &p.tmV, bF + c.s * 8, pcol, 0, 3);
              c.next();
            }
          }
          pcol = col;
          if (rank == 0) {
            asm volatile(
                "{\n.reg .b32 a, b;\nmapa.shared::cluster.u32 a, %0, 1;\nmapa.shared::cluster.u32 b, %1, 1;\n"
                "st.async.shared::cluster.mbarrier::complete_tx::bytes.u32 [a], %2, [b];\n}" ::"r"(sTick + (it & 1) * 4),
                "r"(bT + (it & 1) * 8), "r"(tick) : "memory");
          } else {
            mbar_expect(bT + (it & 1) * 8, 4);
            mbar_wait(bT + (it & 1) * 8, (it >> 1) & 1);
            tick = lds32(sTick + (it & 1) * 4);
          }
        }
        mbar_wait(bE + c.s * 8, c.ph);
        mbar_expect(bF + c.s * 8, 32768);
        tma2d_mc(sbase + c.s * 32768 + rank * 16384, &p.tmV, bF + c.s * 8, pcol, 0, 3);
        const uint32_t unit = tick - 256;
        if (unit < 64) {
          const int mp = 7 - (int)(unit >> 3), mblk = mp * 2 + rank, nhalf = (unit >> 2) & 1, ks = unit & 3;
          const int k0 = ks * 18, k1 = (ks == 3) ? 73 : k0 + 18;
          uint32_t s = 0, ph = 0;
          for (int k = k0; k < k1; k++) {
            mbar_wait(b3E + s * 8, ph);
            mbar_expect(b3F + s * 8, K3_STAGE);
            const uint32_t st = sbase + s * K3_STAGE;
            const int sel = (k >= 64), kr = (sel ? (k - 64) : k) * 64 + rank * 32;
            tma3d_mc(st + 16384 + rank * 16384, &p.tmO[sel], b3F + s * 8, 0, kr, nhalf * 4, 3);
            tma2d_mc(st + 49152 + rank * 2048, &p.tmOt[sel], b3F + s * 8, 512 + nhalf * 32, kr, 3);
            if (k == k0) {
              wait_flag(&g_sync[F_CTX + mp * 4 + ks], (ks == 3) ? 26 : 18);
              asm volatile("fence.proxy.async;" ::: "memory");
            }
            tma2d(st, &p.tmC, b3F + s * 8, k * 64, mblk * 128);
            if (++s == K3_NST) { s = 0; ph ^= 1; }
          }
        }
      }
    } else {
      if (lr0 < S_LEN) {
#pragma unroll 1
        for (int i = warp_g - 9; i < 16; i += 3) {
          const float g = gate_row(lr0 + i, lane, x, gate_w);
          if (lane == 0) asm volatile("st.shared.f32 [%0], %1;" ::"r"(sGate + i * 4), "f"(g) : "memory");
        }
        bar_arrive(3, 256 + 96);
        if (lane == 0) {
          __threadfence();
          atomicAdd(&g_sync[F_GATE], 1u);
        }
      }
      if (warp_g == 9 && lane == 0) {
#pragma unroll 1
        for (int ji = 0; ji < K1_MAXJOBS; ji++) {
          const uint32_t job = p.jobs[cl][ji];
          if (!(job & 3)) break;
          mbar_wait(bS, ji & 1);
          __threadfence();
          atomicAdd(&g_sync[(((job >> 6) & 3) == 2) ? (F_QKVA + ((job >> 3) & 7) * 2 + rank) : (F_HP + ((job >> 10) & 15))], 1u);
        }
#pragma unroll 1
        for (int it = 0;; it++) {
          mbar_wait(bS2, it & 1);
          const uint32_t item = lds32(sItem + (it & 7) * 4), nxt = lds32(sItem + ((it + 1) & 7) * 4);
          __threadfence();
          atomicAdd(&g_sync[F_CTX + (item & 7) * 4 + (item >> 3) / 9], 1u);
          if (nxt >= K2_END) break;
        }
      } else if (warp_g == 10 && lr0 < S_LEN) {
        bar_sync(5, 256 + 32);
        if (lane == 0) {
          __threadfence();
          atomicAdd(&g_sync[F_CTX + (lr0 >> 8) * 4 + 3], 1u);
        }
      }
    }
    __syncwarp();
    cluster_sync();
    if (tid == 256) {
      __threadfence();
      if (atomicAdd(&g_sync[F_DONE], 1u) == 2 * NCLUSTER - 1)
        for (int i = 0; i < 128; i++) g_sync[i] = 0;
    }
  } else {
    reg_alloc<232>();
    const int wg = warp_g >> 2, warp = warp_g & 3, q = lane & 3;
    const bool sig = (lane == 0) && (warp < 2);
    {
      K1State st{0, 0, 0, nullptr, 0, 0};
      float acc[128];
      uint32_t pk[64];
      if (wg == 0) { TS(0, 0); TSC(0, 2); }
#pragma unroll 1
      for (int ji = 0; ji < K1_MAXJOBS; ji++) {
        const uint32_t job = p.jobs[cl][ji];
        if (!(job & 3)) break;
        k1_tile(acc, pk, st, job, sA, sB, bAf, bAe, bBf, bBe, bS, wg, warp, lane, rank);
      }
      if (sig)
        for (int i = 0; i < 3; i++) mbar_arrive_cluster(bE + i * 8, warp);
#pragma unroll
      for (int G = 0; G < 8; G++)
        if (G < st.png) {
          st_v4(st.pp + G * 32, pk[G * 8], pk[G * 8 + 1], pk[G * 8 + 2], pk[G * 8 + 3]);
          st_v4(st.pp + G * 32 + st.pld8, pk[G * 8 + 4], pk[G * 8 + 5], pk[G * 8 + 6], pk[G * 8 + 7]);
        }
      k1_flag(st, lane, bS);
      if (wg == 0) { TS(0, 1); TSC(0, 3); }
      if (lr0 < S_LEN) {
        const int row = lr0 + warp_g * 2;
        if (wg == 0) TS(1, 5);
        bar_sync(3, 256 + 96);
        const float gate0 = __uint_as_float(lds32(sGate + warp_g * 8)), gate1 = __uint_as_float(lds32(sGate + warp_g * 8 + 4));
        mbar_wait(bL, 0);
        if (wg == 0) TS(1, 6);
        local_rows2(row, sA + (row - lrs) * (NQKVA * 2) + lane * 36, lane, gate0, gate1);
        bar_arrive(5, 256 + 32);
        asm volatile("fence.proxy.async.shared::cta;" ::: "memory");
        bar_sync(4, 256);
      }
      if (sig)
        for (int i = 3; i < K2_NST; i++) mbar_arrive_cluster(bE + i * 8, warp);
    }
    __syncwarp();
    uint32_t item;
    {
      const int mybar = 1 + wg, otherbar = 2 - wg;
      const float cl2 = 0.08838834764831845f * 1.4426950408889634f;
      float S[64], O[64];
      uint32_t P[32], Q[32];
#pragma unroll
      for (int i = 0; i < 64; i++) { S[i] = 0.f; O[i] = 1.f; }
#pragma unroll
      for (int i = 0; i < 32; i++) P[i] = 0;
      float m0 = 0.f, m1 = 0.f, l0 = 0.f, l1 = 0.f;
      int prev_row = 0, prev_h = 0, prev_single = 0;
      Cursor c{0, 0};
      if (wg == 1) bar_arrive(1, 256);
      if (wg == 0) { TS(1, 0); TSC(1, 2); }
#pragma unroll 1
      for (int it = 0;; it++) {
        mbar_wait(bF + c.s * 8, c.ph);
        item = lds32(sItem + (it & 7) * 4);
        if (item >= K2_END) break;
        const int h = item >> 3, j = item & 7;
        const int hi = (int)(rank ^ (it & 1));
        const int nblk = 2 * j + 1 + hi;
        {
          const float gf0 = 1.f - g_gate[prev_row], gf1 = 1.f - g_gate[prev_row + 8];
          Cursor cq = c; c.next();
          {
            const int r = wg * 64 + warp * 16 + (lane & 7) + ((lane >> 3) & 1) * 8;
            const uint32_t qa = sbase + cq.s * 32768 + r * 128;
#pragma unroll
            for (int t = 0; t < 8; t++)
              ldsm_x4(Q[4 * t], Q[4 * t + 1], Q[4 * t + 2], Q[4 * t + 3], qa + (t >> 2) * 16384 + ((((t & 3) * 2 + (lane >> 4)) ^ (lane & 7)) << 4));
          }
          Cursor ck = c; c.next();
          Cursor cs0 = ck, cs1 = ck, cv = c;
          mbar_wait(bF + ck.s * 8, ck.ph);
          if (it > 0) { mbar_wait(bF + cv.s * 8, cv.ph); c.next(); }
          if (!hi) {
            ck = c; c.next();
            cs1 = c; c.next();
            mbar_wait(bF + ck.s * 8, ck.ph);
            mbar_wait(bF + cs1.s * 8, cs1.ph);
          }
          TURN_SYNC();
          wg_fence();
          ISSUE_QK(ck);
          wg_commit();
          if (it > 0) ISSUE_PV(cv, prev_single);
          wg_commit();
          TURN_ARRIVE();
          RELEASE(cq);
          if (!hi) { RELEASE(cs0); RELEASE(cs1); }
          wg_wait<1>();
          fence_regs(S);
          RELEASE(ck);
          const int r0 = wg * 64 + warp * 16 + (lane >> 2);
#pragma unroll
          for (int jj = 0; jj < 16; jj++) {
            const int cc = jj * 8 + 2 * q;
            if (cc > r0) S[jj * 4 + 0] = -INFINITY;
            if (cc + 1 > r0) S[jj * 4 + 1] = -INFINITY;
            if (cc > r0 + 8) S[jj * 4 + 2] = -INFINITY;
            if (cc + 1 > r0 + 8) S[jj * 4 + 3] = -INFINITY;
          }
          float mx0 = fmaxf(S[0], S[1]), mx1 = fmaxf(S[2], S[3]);
#pragma unroll
          for (int jj = 1; jj < 16; jj++) {
            mx0 = fmaxf(mx0, fmaxf(S[jj * 4 + 0], S[jj * 4 + 1]));
            mx1 = fmaxf(mx1, fmaxf(S[jj * 4 + 2], S[jj * 4 + 3]));
          }
          mx0 = fmaxf(mx0, __shfl_xor_sync(0xffffffffu, mx0, 1));
          mx1 = fmaxf(mx1, __shfl_xor_sync(0xffffffffu, mx1, 1));
          mx0 = fmaxf(mx0, __shfl_xor_sync(0xffffffffu, mx0, 2));
          mx1 = fmaxf(mx1, __shfl_xor_sync(0xffffffffu, mx1, 2));
          m0 = mx0; m1 = mx1;
          const float mc0 = m0 * cl2, mc1 = m1 * cl2;
          float s0 = 0.f, s1 = 0.f;
#pragma unroll
          for (int jj = 0; jj < 16; jj++) {
            S[jj * 4 + 0] = ex2(fmaf(S[jj * 4 + 0], cl2, -mc0));
            S[jj * 4 + 1] = ex2(fmaf(S[jj * 4 + 1], cl2, -mc0));
            S[jj * 4 + 2] = ex2(fmaf(S[jj * 4 + 2], cl2, -mc1));
            S[jj * 4 + 3] = ex2(fmaf(S[jj * 4 + 3], cl2, -mc1));
            s0 += S[jj * 4 + 0] + S[jj * 4 + 1];
            s1 += S[jj * 4 + 2] + S[jj * 4 + 3];
          }
          fence_regs(S);
          wg_wait<0>();
          fence_regs(O);
          fence_regs(P);
          if (it > 0) {
            RELEASE(cv);
            EPILOGUE();
            __syncwarp();
            if (lane == 0) mbar_arrive(bS2);
          }
          l0 = s0; l1 = s1;
#pragma unroll
          for (int jj = 0; jj < 16; jj++) {
            P[jj * 2 + 0] = pack_bf16(S[jj * 4 + 0], S[jj * 4 + 1]);
            P[jj * 2 + 1] = pack_bf16(S[jj * 4 + 2], S[jj * 4 + 3]);
          }
        }
#pragma unroll 1
        for (int n = 1; n < nblk; n++) {
          Cursor ck = c; c.next();
          Cursor cv = c; c.next();
          mbar_wait(bF + ck.s * 8, ck.ph);
          mbar_wait(bF + cv.s * 8, cv.ph);
          TURN_SYNC();
          wg_fence();
          ISSUE_QK(ck);
          wg_commit();
          ISSUE_PV(cv, n == 1);
          wg_commit();
          TURN_ARRIVE();
          wg_wait<1>();
          fence_regs(S);
          RELEASE(ck);
          float mx0 = fmaxf(S[0], S[1]), mx1 = fmaxf(S[2], S[3]);
#pragma unroll
          for (int jj = 1; jj < 16; jj++) {
            mx0 = fmaxf(mx0, fmaxf(S[jj * 4 + 0], S[jj * 4 + 1]));
            mx1 = fmaxf(mx1, fmaxf(S[jj * 4 + 2], S[jj * 4 + 3]));
          }
          mx0 = fmaxf(mx0, __shfl_xor_sync(0xffffffffu, mx0, 1));
          mx1 = fmaxf(mx1, __shfl_xor_sync(0xffffffffu, mx1, 1));
          mx0 = fmaxf(mx0, __shfl_xor_sync(0xffffffffu, mx0, 2));
          mx1 = fmaxf(mx1, __shfl_xor_sync(0xffffffffu, mx1, 2));
          mx0 = fmaxf(mx0, m0);
          mx1 = fmaxf(mx1, m1);
          const float sc0 = ex2((m0 - mx0) * cl2), sc1 = ex2((m1 - mx1) * cl2);
          m0 = mx0; m1 = mx1;
          const float mc0 = m0 * cl2, mc1 = m1 * cl2;
          float s0 = 0.f, s1 = 0.f;
#pragma unroll
          for (int jj = 0; jj < 16; jj++) {
            S[jj * 4 + 0] = ex2(fmaf(S[jj * 4 + 0], cl2, -mc0));
            S[jj * 4 + 1] = ex2(fmaf(S[jj * 4 + 1], cl2, -mc0));
            S[jj * 4 + 2] = ex2(fmaf(S[jj * 4 + 2], cl2, -mc1));
            S[jj * 4 + 3] = ex2(fmaf(S[jj * 4 + 3], cl2, -mc1));
            s0 += S[jj * 4 + 0] + S[jj * 4 + 1];
            s1 += S[jj * 4 + 2] + S[jj * 4 + 3];
          }
          l0 = fmaf(l0, sc0, s0);
          l1 = fmaf(l1, sc1, s1);
          fence_regs(S);
          wg_wait<0>();
          fence_regs(O);
          fence_regs(P);
          RELEASE(cv);
#pragma unroll
          for (int jj = 0; jj < 16; jj++) {
            O[jj * 4 + 0] *= sc0;
            O[jj * 4 + 1] *= sc0;
            O[jj * 4 + 2] *= sc1;
            O[jj * 4 + 3] *= sc1;
            P[jj * 2 + 0] = pack_bf16(S[jj * 4 + 0], S[jj * 4 + 1]);
            P[jj * 2 + 1] = pack_bf16(S[jj * 4 + 2], S[jj * 4 + 3]);
          }
        }
        prev_row = (2 * j + hi) * 128 + wg * 64 + warp * 16 + (lane >> 2);
        prev_h = h;
        prev_single = (nblk == 1);
      }
      {
        const float gf0 = 1.f - g_gate[prev_row], gf1 = 1.f - g_gate[prev_row + 8];
        Cursor cv = c;
        TURN_SYNC();
        wg_fence();
        ISSUE_PV(cv, prev_single);
        wg_commit();
        if (wg == 0) TURN_ARRIVE();
        wg_wait<0>();
        fence_regs(O);
        if (sig)
          for (int i = 0; i < K3_NST; i++) mbar_arrive_cluster(b3E + i * 8, warp);
        EPILOGUE();
        __syncwarp();
        if (lane == 0) mbar_arrive(bS2);
      }
      if (wg == 1) { TS(1, 1); TSC(1, 3); }
    }
    __syncwarp();
    const uint32_t unit = item & 255;
    if (unit < 64) {
      const int mblk = (7 - (int)(unit >> 3)) * 2 + rank, nhalf = (unit >> 2) & 1, ks = unit & 3;
      const int k0 = ks * 18, k1 = (ks == 3) ? 73 : k0 + 18;
      float acc[144];
#pragma unroll
      for (int i = 0; i < 144; i++) acc[i] = 0.f;
      uint32_t s = 0, ph = 0, prev = 0;
      if (wg == 0) { TS(2, 0); TSC(2, 2); }
      for (int k = k0; k < k1; k++) {
        mbar_wait(b3F + s * 8, ph);
        const uint32_t st = sbase + s * K3_STAGE;
        const uint64_t da = make_desc(st + wg * 8192, 16, 1024, 1);
        const uint64_t db = make_desc(st + 16384, 4096, 1024, 1);
        const uint64_t dt = make_desc(st + 49152, 16, 512, 2);
        wg_fence();
#pragma unroll
        for (int t = 0; t < 4; t++) {
          const int sd = (t > 0) || (k > k0);
          wgmma_ss_n256<1, 0>(acc, da + (uint64_t)(t * 2), db + (uint64_t)((t >> 1) * 1024 + (t & 1) * 128), sd);
          wgmma_ss_n32<1, 128>(acc, da + (uint64_t)(t * 2), dt + (uint64_t)(t * 64), sd);
        }
        wg_commit();
        if (k > k0) {
          wg_wait<1>();
          if (sig) mbar_arrive_cluster(b3E + prev * 8, warp);
        }
        prev = s;
        if (++s == K3_NST) { s = 0; ph ^= 1; }
      }
      wg_wait<0>();
      fence_regs(acc);
      if (wg == 0) TS(2, 4);
      const int tile = mblk * 2 + nhalf;
      float4* wp = g_part + (size_t)((tile * 4 + ks) * 4) * 9 * 256 + tid;
#pragma unroll
      for (int d = 0; d < 4; d++) {
        if (d != ks) {
#pragma unroll
          for (int i = 0; i < 8; i++)
            __stcg(wp + (d * 9 + i) * 256, make_float4(acc[d * 32 + i * 4], acc[d * 32 + i * 4 + 1], acc[d * 32 + i * 4 + 2], acc[d * 32 + i * 4 + 3]));
          __stcg(wp + (d * 9 + 8) * 256, make_float4(acc[128 + d * 4], acc[128 + d * 4 + 1], acc[128 + d * 4 + 2], acc[128 + d * 4 + 3]));
        }
      }
      __threadfence();
      bar_sync(4, 256);
      if (wg == 0) TS(2, 5);
      if (tid == 0) {
        atomicAdd(&g_sync[F_XCH + tile], 1u);
        uint32_t v, spins = 0;
        do {
          asm volatile("ld.acquire.gpu.global.u32 %0, [%1];" : "=r"(v) : "l"(&g_sync[F_XCH + tile]) : "memory");
        } while (v < 4 && ++spins < (1u << 24));
      }
      bar_sync(4, 256);
      if (wg == 0) TS(2, 6);
      float r[36];
#pragma unroll
      for (int d = 0; d < 4; d++) {
        if (d == ks) {
#pragma unroll
          for (int i = 0; i < 32; i++) r[i] = acc[d * 32 + i];
#pragma unroll
          for (int i = 0; i < 4; i++) r[32 + i] = acc[128 + d * 4 + i];
        }
      }
#pragma unroll
      for (int sI = 1; sI < 4; sI++) {
        const int src = (ks + sI) & 3;
        const float4* rp = g_part + (size_t)(((tile * 4 + src) * 4) + ks) * 9 * 256 + tid;
#pragma unroll
        for (int i = 0; i < 9; i++) {
          const float4 v = __ldcg(rp + i * 256);
          r[i * 4] += v.x; r[i * 4 + 1] += v.y; r[i * 4 + 2] += v.z; r[i * 4 + 3] += v.w;
        }
      }
      const int row = mblk * 128 + wg * 64 + warp * 16 + (lane >> 2);
      bf16* o0 = out + (size_t)row * DM + nhalf * 256 + ks * 64 + 8 * q;
#pragma unroll
      for (int G = 0; G < 2; G++) {
        uint32_t a0 = pack_bf16(r[G * 16], r[G * 16 + 1]), a1 = pack_bf16(r[G * 16 + 4], r[G * 16 + 5]);
        uint32_t a2 = pack_bf16(r[G * 16 + 8], r[G * 16 + 9]), a3 = pack_bf16(r[G * 16 + 12], r[G * 16 + 13]);
        uint32_t b0 = pack_bf16(r[G * 16 + 2], r[G * 16 + 3]), b1 = pack_bf16(r[G * 16 + 6], r[G * 16 + 7]);
        uint32_t b2 = pack_bf16(r[G * 16 + 10], r[G * 16 + 11]), b3 = pack_bf16(r[G * 16 + 14], r[G * 16 + 15]);
        quad_transpose(a0, a1, a2, a3, q);
        quad_transpose(b0, b1, b2, b3, q);
        st_v4(o0 + G * 32, a0, a1, a2, a3);
        st_v4(o0 + 8 * DM + G * 32, b0, b1, b2, b3);
      }
      {
        uint32_t t0 = pack_bf16(r[32], r[33]), t1 = pack_bf16(r[34], r[35]), t2 = 0, t3 = 0;
        quad_transpose(t0, t1, t2, t3, q);
        if (q < 2) st_v4(out + (size_t)(row + q * 8) * DM + 512 + nhalf * 32 + ks * 8, t0, t1, t2, t3);
      }
    }
    if (wg == 0) { TS(2, 1); TSC(2, 3); }
    cluster_sync();
  }
}

typedef CUresult (*EncFn)(CUtensorMap*, CUtensorMapDataType, cuuint32_t, void*, const cuuint64_t*, const cuuint64_t*, const cuuint32_t*,
                          const cuuint32_t*, CUtensorMapInterleave, CUtensorMapSwizzle, CUtensorMapL2promotion, CUtensorMapFloatOOBfill);

static void enc2d(EncFn enc, CUtensorMap* m, const void* ptr, uint64_t cols, uint64_t rows, uint32_t bc, uint32_t br,
                  CUtensorMapSwizzle sw = CU_TENSOR_MAP_SWIZZLE_128B) {
  cuuint64_t gd[2] = {cols, rows}, gs[1] = {cols * 2};
  cuuint32_t bx[2] = {bc, br}, es[2] = {1, 1};
  enc(m, CU_TENSOR_MAP_DATA_TYPE_BFLOAT16, 2, const_cast<void*>(ptr), gd, gs, bx, es, CU_TENSOR_MAP_INTERLEAVE_NONE, sw,
      CU_TENSOR_MAP_L2_PROMOTION_L2_256B, CU_TENSOR_MAP_FLOAT_OOB_FILL_NONE);
}
static void enc3d(EncFn enc, CUtensorMap* m, const void* ptr, uint64_t cols, uint64_t rows, uint32_t br, uint32_t bch) {
  cuuint64_t gd[3] = {64, rows, cols / 64}, gs[2] = {cols * 2, 128};
  cuuint32_t bx[3] = {64, br, bch}, es[3] = {1, 1, 1};
  enc(m, CU_TENSOR_MAP_DATA_TYPE_BFLOAT16, 3, const_cast<void*>(ptr), gd, gs, bx, es, CU_TENSOR_MAP_INTERLEAVE_NONE,
      CU_TENSOR_MAP_SWIZZLE_128B, CU_TENSOR_MAP_L2_PROMOTION_L2_256B, CU_TENSOR_MAP_FLOAT_OOB_FILL_NONE);
}

static void build_k1_jobs(Params& p) {
  int cnt[NCLUSTER];
  for (int c = 0; c < NCLUSTER; c++) {
    cnt[c] = 0;
    for (int i = 0; i < K1_MAXJOBS; i++) p.jobs[c][i] = 0;
  }
  auto add = [&](int c, int nch, int a_sel, int mp, int w_sel, int chunk0) {
    p.jobs[c][cnt[c]++] = (uint16_t)((nch - 1) | (a_sel << 2) | (mp << 3) | (w_sel << 6) | (chunk0 << 8));
  };
  for (int mp = 0; mp < 8; mp++) {
    for (int g = 0; g < 4; g++)
      for (int i = 0; i < 7; i++) add(g * 8 + mp, 4, 0, mp, g & 1, (2 + 2 * i + (g >> 1)) * 4);
    add(32 + mp, 3, 1, mp, 2, 24);
    add(32 + mp, 4, 1, mp, 3, 0 * 4);
    add(32 + mp, 4, 1, mp, 3, 1 * 4);
    for (int t = 0; t < 4; t++) add(32 + mp, 4, 0, mp, t & 1, (t >> 1) * 4);
    for (int g = 0; g < 2; g++) {
      for (int i = 0; i < 3; i++) add((5 + g) * 8 + mp, 4, 1, mp, 2, (g * 3 + i) * 4);
      for (int i = 0; i < 3; i++) add((5 + g) * 8 + mp, 4, 1, mp, 3, (2 + g * 3 + i) * 4);
    }
    for (int i = 0; i < 6; i++) add(56 + mp, 4, 1, mp, 3, (8 + i) * 4);
    add(64 + mp / 4, 4, 1, mp, 3, 14 * 4);
    if (mp & 1) add(64 + mp / 4, 4, 1, mp, 3, 15 * 4);
    else add(56 + mp, 4, 1, mp, 3, 15 * 4);
  }
  for (int cc = 0; cc < NCLUSTER; cc++)
    for (int i = 0; i < cnt[cc]; i++) {
      const int key = p.jobs[cc][i] & 0x3C;
      if (i == 0 || (p.jobs[cc][i - 1] & 0x3C) != key) p.jobs[cc][i] |= (1 << 14);
      if (i == cnt[cc] - 1 || (p.jobs[cc][i + 1] & 0x3C) != key) p.jobs[cc][i] |= (1 << 15);
    }
}

static void build_k2_items(Params& p) {
  static const int hp_order[16] = {8, 9, 10, 2, 5, 11, 3, 6, 12, 4, 7, 13, 14, 15, 0, 1};
  int n = 0;
  for (int i = 0; i < 64; i++) p.order[n++] = (uint8_t)((hp_order[i >> 2] * 2 + (i & 1)) * 8 + 7 - ((i >> 1) & 1));
  for (int j = 5; j >= 0; j--)
    for (int i = 0; i < 32; i++) p.order[n++] = (uint8_t)((hp_order[i >> 1] * 2 + (i & 1)) * 8 + j);
}

extern "C" void kernel_launch(void* const* d_in, const int* in_sizes, int n_in, void* d_out, int out_size) {
  const bf16* x = (const bf16*)d_in[0];
  const bf16* wqkv = (const bf16*)d_in[1];
  const bf16* wo = (const bf16*)d_in[2];
  const bf16* ckv = (const bf16*)d_in[4];
  const bf16* w_q = (const bf16*)d_in[5];
  const bf16* w_uk = (const bf16*)d_in[6];
  const bf16* w_uv = (const bf16*)d_in[7];
  const bf16* w_o = (const bf16*)d_in[8];
  const bf16* gate_w = (const bf16*)d_in[9];

  EncFn enc = nullptr;
  cudaDriverEntryPointQueryResult qr;
  cudaGetDriverEntryPoint("cuTensorMapEncodeTiled", (void**)&enc, cudaEnableDefault, &qr);
  void *pQ, *pK, *pV, *pCtx;
  cudaGetSymbolAddress(&pQ, g_Q);
  cudaGetSymbolAddress(&pK, g_K);
  cudaGetSymbolAddress(&pV, g_V);
  cudaGetSymbolAddress(&pCtx, g_ctx);

  static Params p;
  enc2d(enc, &p.tmA[0], ckv, DC, S_LEN, 64, 128);
  enc2d(enc, &p.tmA[1], x, DM, S_LEN, 64, 128);
  enc3d(enc, &p.tmW[0], w_uk, HDIM, DC, 16, 4);
  enc3d(enc, &p.tmW[1], w_uv, HDIM, DC, 16, 4);
  enc3d(enc, &p.tmW[2], wqkv, NQKVA, DM, 16, 4);
  enc3d(enc, &p.tmW[3], w_q, HDIM, DM, 16, 4);
  build_k1_jobs(p);
  enc2d(enc, &p.tmQ, pQ, HDIM, S_LEN, 64, 128);
  enc2d(enc, &p.tmK, pK, HDIM, S_LEN, 64, 128);
  enc2d(enc, &p.tmV, pV, HDIM, S_LEN, 64, 128);
  build_k2_items(p);
  enc2d(enc, &p.tmC, pCtx, KCAT, S_LEN, 64, 128);
  enc3d(enc, &p.tmO[0], w_o, DM, HDIM, 32, 4);
  enc3d(enc, &p.tmO[1], wo, DM, DM, 32, 4);
  enc2d(enc, &p.tmOt[0], w_o, DM, HDIM, 32, 32, CU_TENSOR_MAP_SWIZZLE_64B);
  enc2d(enc, &p.tmOt[1], wo, DM, DM, 32, 32, CU_TENSOR_MAP_SWIZZLE_64B);

  cudaFuncSetAttribute(fused_kernel, cudaFuncAttributeMaxDynamicSharedMemorySize, SMEM_BYTES);
  fused_kernel<<<NCLUSTER * 2, 384, SMEM_BYTES>>>(p, x, gate_w, (bf16*)d_out);
}
```

```cpp
#include <cuda_runtime.h>
#include <cuda_bf16.h>
#include <cuda.h>
#include <stdint.h>

typedef __nv_bfloat16 bf16;

constexpr int S_LEN = 2048, DM = 576, DC = 512, HDIM = 4096, NQKVA = 1728, KCAT = 4672;
constexpr int NCLUSTER = 66;

__device__ __align__(1024) bf16 g_Q[S_LEN * HDIM];
__device__ __align__(1024) bf16 g_K[S_LEN * HDIM];
__device__ __align__(1024) bf16 g_V[S_LEN * HDIM];
__device__ __align__(1024) bf16 g_QKVA[S_LEN * NQKVA + 64];
__device__ __align__(1024) bf16 g_ctx[S_LEN * KCAT];
__device__ float g_gate[S_LEN];
__device__ __align__(1024) float4 g_part[32 * 4 * 4 * 9 * 256];
__device__ __align__(16) unsigned int g_sync[128];
constexpr int F_QKVA = 0, F_HP = 16, F_CTX = 32, F_XCH = 64, F_GATE = 96, F_TICK = 97, F_DONE = 98;

__device__ __forceinline__ uint32_t smem_u32(const void* p) { return (uint32_t)__cvta_generic_to_shared(p); }
__device__ __forceinline__ void mbar_init(uint32_t a, uint32_t c) {
  asm volatile("mbarrier.init.shared::cta.b64 [%0], %1;" ::"r"(a), "r"(c));
}
__device__ __forceinline__ void mbar_expect(uint32_t a, uint32_t b) {
  asm volatile("mbarrier.arrive.expect_tx.shared::cta.b64 _, [%0], %1;" ::"r"(a), "r"(b) : "memory");
}
#define TS(k, i)
#define TSC(k, i)
#define TSM(k)
#define SPIN_LIMIT "4194304"
__device__ __forceinline__ void mbar_wait(uint32_t a, uint32_t parity) {
  asm volatile(
      "{\n.reg .pred p;\n.reg .u32 n;\n"
      "mbarrier.try_wait.parity.shared::cta.b64 p, [%0], %1;\n"
      "@p bra DONE;\n"
      "mov.u32 n, 0;\n"
      "LOOP:\n"
      "mbarrier.try_wait.parity.shared::cta.b64 p, [%0], %1;\n"
      "@p bra DONE;\n"
      "add.u32 n, n, 1;\n"
      "setp.lt.u32 p, n, " SPIN_LIMIT ";\n"
      "@p bra LOOP;\n"
      "DONE:\n}" ::"r"(a), "r"(parity) : "memory");
}
__device__ __forceinline__ void mbar_arrive(uint32_t a) {
  asm volatile("mbarrier.arrive.shared::cta.b64 _, [%0];" ::"r"(a) : "memory");
}
__device__ __forceinline__ void mbar_arrive_cluster(uint32_t a, uint32_t cta) {
  asm volatile("{\n.reg .b32 r;\nmapa.shared::cluster.u32 r, %0, %1;\nmbarrier.arrive.shared::cluster.b64 _, [r];\n}" ::"r"(a),
               "r"(cta) : "memory");
}
__device__ __forceinline__ void mbar_arrive_cluster_if(uint32_t a, uint32_t cta, bool pred) {
  asm volatile("{\n.reg .b32 r;\n.reg .pred p;\nsetp.ne.u32 p, %2, 0;\nmapa.shared::cluster.u32 r, %0, %1;\n@p mbarrier.arrive.shared::cluster.b64 _, [r];\n}" ::"r"(a),
               "r"(cta), "r"((uint32_t)pred) : "memory");
}
__device__ __forceinline__ void mbar_arrive_if(uint32_t a, bool pred) {
  asm volatile("{\n.reg .pred p;\nsetp.ne.u32 p, %1, 0;\n@p mbarrier.arrive.shared::cta.b64 _, [%0];\n}" ::"r"(a), "r"((uint32_t)pred) : "memory");
}
__device__ __forceinline__ void tma2d(uint32_t dst, const CUtensorMap* m, uint32_t bar, int c0, int c1) {
  asm volatile("cp.async.bulk.tensor.2d.shared::cluster.global.mbarrier::complete_tx::bytes [%0], [%1, {%3, %4}], [%2];" ::"r"(dst),
               "l"(m), "r"(bar), "r"(c0), "r"(c1) : "memory");
}
__device__ __forceinline__ void tma2d_mc(uint32_t dst, const CUtensorMap* m, uint32_t bar, int c0, int c1, uint16_t mask) {
  asm volatile(
      "cp.async.bulk.tensor.2d.shared::cluster.global.mbarrier::complete_tx::bytes.multicast::cluster [%0], [%1, {%3, %4}], [%2], %5;" ::"r"(dst),
      "l"(m), "r"(bar), "r"(c0), "r"(c1), "h"(mask) : "memory");
}
__device__ __forceinline__ void tma3d_mc(uint32_t dst, const CUtensorMap* m, uint32_t bar, int c0, int c1, int c2, uint16_t mask) {
  asm volatile(
      "cp.async.bulk.tensor.3d.shared::cluster.global.mbarrier::complete_tx::bytes.multicast::cluster [%0], [%1, {%3, %4, %5}], [%2], %6;" ::"r"(dst),
      "l"(m), "r"(bar), "r"(c0), "r"(c1), "r"(c2), "h"(mask) : "memory");
}
__device__ __forceinline__ void tma3d(uint32_t dst, const CUtensorMap* m, uint32_t bar, int c0, int c1, int c2) {
  asm volatile(
      "cp.async.bulk.tensor.3d.shared::cluster.global.mbarrier::complete_tx::bytes [%0], [%1, {%3, %4, %5}], [%2];" ::"r"(dst),
      "l"(m), "r"(bar), "r"(c0), "r"(c1), "r"(c2) : "memory");
}
__device__ __forceinline__ void tma_pf2d(const CUtensorMap* m, int c0, int c1) {
  asm volatile("cp.async.bulk.prefetch.tensor.2d.L2.global [%0, {%1, %2}];" ::"l"(m), "r"(c0), "r"(c1) : "memory");
}
__device__ __forceinline__ void tma_pf3d(const CUtensorMap* m, int c0, int c1, int c2) {
  asm volatile("cp.async.bulk.prefetch.tensor.3d.L2.global [%0, {%1, %2, %3}];" ::"l"(m), "r"(c0), "r"(c1), "r"(c2) : "memory");
}
__device__ __forceinline__ void prefetch_tmap(const CUtensorMap* m) {
  asm volatile("prefetch.tensormap [%0];" ::"l"(m) : "memory");
}
__device__ __forceinline__ void cluster_sync() {
  asm volatile("barrier.cluster.arrive.aligned;\nbarrier.cluster.wait.aligned;" ::: "memory");
}
__device__ __forceinline__ uint32_t cluster_rank() {
  uint32_t r;
  asm volatile("mov.u32 %0, %%cluster_ctarank;" : "=r"(r));
  return r;
}
__device__ __forceinline__ bool elect_one() {
  uint32_t p;
  asm volatile("{\n.reg .pred q;\nelect.sync _|q, 0xffffffff;\nselp.u32 %0, 1, 0, q;\n}" : "=r"(p));
  return p;
}
__device__ __forceinline__ void pdl_wait() { asm volatile("griddepcontrol.wait;" ::: "memory"); }
__device__ __forceinline__ void pdl_launch() { asm volatile("griddepcontrol.launch_dependents;" ::: "memory"); }
__device__ __forceinline__ void ldsm_x4(uint32_t& r0, uint32_t& r1, uint32_t& r2, uint32_t& r3, uint32_t addr) {
  asm volatile("ldmatrix.sync.aligned.m8n8.x4.shared.b16 {%0, %1, %2, %3}, [%4];" : "=r"(r0), "=r"(r1), "=r"(r2), "=r"(r3) : "r"(addr) : "memory");
}
__device__ __forceinline__ void wg_fence() { asm volatile("wgmma.fence.sync.aligned;" ::: "memory"); }
__device__ __forceinline__ void wg_commit() { asm volatile("wgmma.commit_group.sync.aligned;" ::: "memory"); }
template <int N>
__device__ __forceinline__ void wg_wait() { asm volatile("wgmma.wait_group.sync.aligned %0;" ::"n"(N) : "memory"); }
template <int N>
__device__ __forceinline__ void reg_alloc() { asm volatile("setmaxnreg.inc.sync.aligned.u32 %0;" ::"n"(N)); }
template <int N>
__device__ __forceinline__ void reg_dealloc() { asm volatile("setmaxnreg.dec.sync.aligned.u32 %0;" ::"n"(N)); }
__device__ __forceinline__ void bar_sync(int id, int n) { asm volatile("bar.sync %0, %1;" ::"r"(id), "r"(n) : "memory"); }
__device__ __forceinline__ void bar_arrive(int id, int n) { asm volatile("bar.arrive %0, %1;" ::"r"(id), "r"(n) : "memory"); }
template <int NT>
__device__ __forceinline__ void fence_regs(float (&d)[NT]) {
#pragma unroll
  for (int i = 0; i < NT; i++) asm volatile("" : "+f"(d[i])::"memory");
}
template <int NT>
__device__ __forceinline__ void fence_regs(uint32_t (&d)[NT]) {
#pragma unroll
  for (int i = 0; i < NT; i++) asm volatile("" : "+r"(d[i])::"memory");
}
__device__ __forceinline__ uint64_t make_desc(uint32_t saddr, uint32_t lbo, uint32_t sbo, uint32_t layout) {
  return (uint64_t)((saddr & 0x3FFFF) >> 4) | ((uint64_t)(lbo >> 4) << 16) | ((uint64_t)(sbo >> 4) << 32) | ((uint64_t)layout << 62);
}
__device__ __forceinline__ uint32_t pack_bf16(float lo, float hi) {
  uint32_t r;
  asm("cvt.rn.bf16x2.f32 %0, %1, %2;" : "=r"(r) : "f"(hi), "f"(lo));
  return r;
}
__device__ __forceinline__ float ex2(float x) {
  float r;
  asm("ex2.approx.ftz.f32 %0, %1;" : "=f"(r) : "f"(x));
  return r;
}
__device__ __forceinline__ void st_v4(void* p, uint32_t a, uint32_t b, uint32_t c, uint32_t d) {
#define ST_MOD ""
  asm volatile("st.global" ST_MOD ".v4.b32 [%0], {%1, %2, %3, %4};" ::"l"(p), "r"(a), "r"(b), "r"(c), "r"(d) : "memory");
}
__device__ __forceinline__ float bf_lo(uint32_t v) { return __uint_as_float(v << 16); }
__device__ __forceinline__ float bf_hi(uint32_t v) { return __uint_as_float(v & 0xFFFF0000u); }

__device__ __forceinline__ void quad_transpose(uint32_t& a0, uint32_t& a1, uint32_t& a2, uint32_t& a3, int q) {
  const bool o1 = q & 1, o2 = q & 2;
  uint32_t t0 = o1 ? a0 : a1, t1 = o1 ? a2 : a3;
  t0 = __shfl_xor_sync(0xffffffffu, t0, 1);
  t1 = __shfl_xor_sync(0xffffffffu, t1, 1);
  if (o1) { a0 = t0; a2 = t1; } else { a1 = t0; a3 = t1; }
  t0 = o2 ? a0 : a2;
  t1 = o2 ? a1 : a3;
  t0 = __shfl_xor_sync(0xffffffffu, t0, 2);
  t1 = __shfl_xor_sync(0xffffffffu, t1, 2);
  if (o2) { a0 = t0; a1 = t1; } else { a2 = t0; a3 = t1; }
}

template<int TB, int OFF, int NT>
__device__ __forceinline__ void wgmma_ss_n256(float (&d)[NT], uint64_t da, uint64_t db, int scale_d) {
  asm volatile("{\n.reg .pred p;\nsetp.ne.b32 p, %130, 0;\n"
    "wgmma.mma_async.sync.aligned.m64n256k16.f32.bf16.bf16 {%0, %1, %2, %3, %4, %5, %6, %7, %8, %9, %10, %11, %12, %13, %14, %15, %16, %17, %18, %19, %20, %21, %22, %23, %24, %25, %26, %27, %28, %29, %30, %31, %32, %33, %34, %35, %36, %37, %38, %39, %40, %41, %42, %43, %44, %45, %46, %47, %48, %49, %50, %51, %52, %53, %54, %55, %56, %57, %58, %59, %60, %61, %62, %63, %64, %65, %66, %67, %68, %69, %70, %71, %72, %73, %74, %75, %76, %77, %78, %79, %80, %81, %82, %83, %84, %85, %86, %87, %88, %89, %90, %91, %92, %93, %94, %95, %96, %97, %98, %99, %100, %101, %102, %103, %104, %105, %106, %107, %108, %109, %110, %111, %112, %113, %114, %115, %116, %117, %118, %119, %120, %121, %122, %123, %124, %125, %126, %127}, %128, %129, p, 1, 1, 0, %131;\n}\n"
    : "+f"(d[OFF+0]), "+f"(d[OFF+1]), "+f"(d[OFF+2]), "+f"(d[OFF+3]), "+f"(d[OFF+4]), "+f"(d[OFF+5]), "+f"(d[OFF+6]), "+f"(d[OFF+7]), "+f"(d[OFF+8]), "+f"(d[OFF+9]), "+f"(d[OFF+10]), "+f"(d[OFF+11]), "+f"(d[OFF+12]), "+f"(d[OFF+13]), "+f"(d[OFF+14]), "+f"(d[OFF+15]), "+f"(d[OFF+16]), "+f"(d[OFF+17]), "+f"(d[OFF+18]), "+f"(d[OFF+19]), "+f"(d[OFF+20]), "+f"(d[OFF+21]), "+f"(d[OFF+22]), "+f"(d[OFF+23]), "+f"(d[OFF+24]), "+f"(d[OFF+25]), "+f"(d[OFF+26]), "+f"(d[OFF+27]), "+f"(d[OFF+28]), "+f"(d[OFF+29]), "+f"(d[OFF+30]), "+f"(d[OFF+31]), "+f"(d[OFF+32]), "+f"(d[OFF+33]), "+f"(d[OFF+34]), "+f"(d[OFF+35]), "+f"(d[OFF+36]), "+f"(d[OFF+37]), "+f"(d[OFF+38]), "+f"(d[OFF+39]), "+f"(d[OFF+40]), "+f"(d[OFF+41]), "+f"(d[OFF+42]), "+f"(d[OFF+43]), "+f"(d[OFF+44]), "+f"(d[OFF+45]), "+f"(d[OFF+46]), "+f"(d[OFF+47]), "+f"(d[OFF+48]), "+f"(d[OFF+49]), "+f"(d[OFF+50]), "+f"(d[OFF+51]), "+f"(d[OFF+52]), "+f"(d[OFF+53]), "+f"(d[OFF+54]), "+f"(d[OFF+55]), "+f"(d[OFF+56]), "+f"(d[OFF+57]), "+f"(d[OFF+58]), "+f"(d[OFF+59]), "+f"(d[OFF+60]), "+f"(d[OFF+61]), "+f"(d[OFF+62]), "+f"(d[OFF+63]), "+f"(d[OFF+64]), "+f"(d[OFF+65]), "+f"(d[OFF+66]), "+f"(d[OFF+67]), "+f"(d[OFF+68]), "+f"(d[OFF+69]), "+f"(d[OFF+70]), "+f"(d[OFF+71]), "+f"(d[OFF+72]), "+f"(d[OFF+73]), "+f"(d[OFF+74]), "+f"(d[OFF+75]), "+f"(d[OFF+76]), "+f"(d[OFF+77]), "+f"(d[OFF+78]), "+f"(d[OFF+79]), "+f"(d[OFF+80]), "+f"(d[OFF+81]), "+f"(d[OFF+82]), "+f"(d[OFF+83]), "+f"(d[OFF+84]), "+f"(d[OFF+85]), "+f"(d[OFF+86]), "+f"(d[OFF+87]), "+f"(d[OFF+88]), "+f"(d[OFF+89]), "+f"(d[OFF+90]), "+f"(d[OFF+91]), "+f"(d[OFF+92]), "+f"(d[OFF+93]), "+f"(d[OFF+94]), "+f"(d[OFF+95]), "+f"(d[OFF+96]), "+f"(d[OFF+97]), "+f"(d[OFF+98]), "+f"(d[OFF+99]), "+f"(d[OFF+100]), "+f"(d[OFF+101]), "+f"(d[OFF+102]), "+f"(d[OFF+103]), "+f"(d[OFF+104]), "+f"(d[OFF+105]), "+f"(d[OFF+106]), "+f"(d[OFF+107]), "+f"(d[OFF+108]), "+f"(d[OFF+109]), "+f"(d[OFF+110]), "+f"(d[OFF+111]), "+f"(d[OFF+112]), "+f"(d[OFF+113]), "+f"(d[OFF+114]), "+f"(d[OFF+115]), "+f"(d[OFF+116]), "+f"(d[OFF+117]), "+f"(d[OFF+118]), "+f"(d[OFF+119]), "+f"(d[OFF+120]), "+f"(d[OFF+121]), "+f"(d[OFF+122]), "+f"(d[OFF+123]), "+f"(d[OFF+124]), "+f"(d[OFF+125]), "+f"(d[OFF+126]), "+f"(d[OFF+127])
    : "l"(da), "l"(db), "r"(scale_d), "n"(TB));
}
template<int TB, int OFF, int NT>
__device__ __forceinline__ void wgmma_ss_n192(float (&d)[NT], uint64_t da, uint64_t db, int scale_d) {
  asm volatile("{\n.reg .pred p;\nsetp.ne.b32 p, %98, 0;\n"
    "wgmma.mma_async.sync.aligned.m64n192k16.f32.bf16.bf16 {%0, %1, %2, %3, %4, %5, %6, %7, %8, %9, %10, %11, %12, %13, %14, %15, %16, %17, %18, %19, %20, %21, %22, %23, %24, %25, %26, %27, %28, %29, %30, %31, %32, %33, %34, %35, %36, %37, %38, %39, %40, %41, %42, %43, %44, %45, %46, %47, %48, %49, %50, %51, %52, %53, %54, %55, %56, %57, %58, %59, %60, %61, %62, %63, %64, %65, %66, %67, %68, %69, %70, %71, %72, %73, %74, %75, %76, %77, %78, %79, %80, %81, %82, %83, %84, %85, %86, %87, %88, %89, %90, %91, %92, %93, %94, %95}, %96, %97, p, 1, 1, 0, %99;\n}\n"
    : "+f"(d[OFF+0]), "+f"(d[OFF+1]), "+f"(d[OFF+2]), "+f"(d[OFF+3]), "+f"(d[OFF+4]), "+f"(d[OFF+5]), "+f"(d[OFF+6]), "+f"(d[OFF+7]), "+f"(d[OFF+8]), "+f"(d[OFF+9]), "+f"(d[OFF+10]), "+f"(d[OFF+11]), "+f"(d[OFF+12]), "+f"(d[OFF+13]), "+f"(d[OFF+14]), "+f"(d[OFF+15]), "+f"(d[OFF+16]), "+f"(d[OFF+17]), "+f"(d[OFF+18]), "+f"(d[OFF+19]), "+f"(d[OFF+20]), "+f"(d[OFF+21]), "+f"(d[OFF+22]), "+f"(d[OFF+23]), "+f"(d[OFF+24]), "+f"(d[OFF+25]), "+f"(d[OFF+26]), "+f"(d[OFF+27]), "+f"(d[OFF+28]), "+f"(d[OFF+29]), "+f"(d[OFF+30]), "+f"(d[OFF+31]), "+f"(d[OFF+32]), "+f"(d[OFF+33]), "+f"(d[OFF+34]), "+f"(d[OFF+35]), "+f"(d[OFF+36]), "+f"(d[OFF+37]), "+f"(d[OFF+38]), "+f"(d[OFF+39]), "+f"(d[OFF+40]), "+f"(d[OFF+41]), "+f"(d[OFF+42]), "+f"(d[OFF+43]), "+f"(d[OFF+44]), "+f"(d[OFF+45]), "+f"(d[OFF+46]), "+f"(d[OFF+47]), "+f"(d[OFF+48]), "+f"(d[OFF+49]), "+f"(d[OFF+50]), "+f"(d[OFF+51]), "+f"(d[OFF+52]), "+f"(d[OFF+53]), "+f"(d[OFF+54]), "+f"(d[OFF+55]), "+f"(d[OFF+56]), "+f"(d[OFF+57]), "+f"(d[OFF+58]), "+f"(d[OFF+59]), "+f"(d[OFF+60]), "+f"(d[OFF+61]), "+f"(d[OFF+62]), "+f"(d[OFF+63]), "+f"(d[OFF+64]), "+f"(d[OFF+65]), "+f"(d[OFF+66]), "+f"(d[OFF+67]), "+f"(d[OFF+68]), "+f"(d[OFF+69]), "+f"(d[OFF+70]), "+f"(d[OFF+71]), "+f"(d[OFF+72]), "+f"(d[OFF+73]), "+f"(d[OFF+74]), "+f"(d[OFF+75]), "+f"(d[OFF+76]), "+f"(d[OFF+77]), "+f"(d[OFF+78]), "+f"(d[OFF+79]), "+f"(d[OFF+80]), "+f"(d[OFF+81]), "+f"(d[OFF+82]), "+f"(d[OFF+83]), "+f"(d[OFF+84]), "+f"(d[OFF+85]), "+f"(d[OFF+86]), "+f"(d[OFF+87]), "+f"(d[OFF+88]), "+f"(d[OFF+89]), "+f"(d[OFF+90]), "+f"(d[OFF+91]), "+f"(d[OFF+92]), "+f"(d[OFF+93]), "+f"(d[OFF+94]), "+f"(d[OFF+95])
    : "l"(da), "l"(db), "r"(scale_d), "n"(TB));
}
template<int TB, int OFF, int NT>
__device__ __forceinline__ void wgmma_ss_n128(float (&d)[NT], uint64_t da, uint64_t db, int scale_d) {
  asm volatile("{\n.reg .pred p;\nsetp.ne.b32 p, %66, 0;\n"
    "wgmma.mma_async.sync.aligned.m64n128k16.f32.bf16.bf16 {%0, %1, %2, %3, %4, %5, %6, %7, %8, %9, %10, %11, %12, %13, %14, %15, %16, %17, %18, %19, %20, %21, %22, %23, %24, %25, %26, %27, %28, %29, %30, %31, %32, %33, %34, %35, %36, %37, %38, %39, %40, %41, %42, %43, %44, %45, %46, %47, %48, %49, %50, %51, %52, %53, %54, %55, %56, %57, %58, %59, %60, %61, %62, %63}, %64, %65, p, 1, 1, 0, %67;\n}\n"
    : "+f"(d[OFF+0]), "+f"(d[OFF+1]), "+f"(d[OFF+2]), "+f"(d[OFF+3]), "+f"(d[OFF+4]), "+f"(d[OFF+5]), "+f"(d[OFF+6]), "+f"(d[OFF+7]), "+f"(d[OFF+8]), "+f"(d[OFF+9]), "+f"(d[OFF+10]), "+f"(d[OFF+11]), "+f"(d[OFF+12]), "+f"(d[OFF+13]), "+f"(d[OFF+14]), "+f"(d[OFF+15]), "+f"(d[OFF+16]), "+f"(d[OFF+17]), "+f"(d[OFF+18]), "+f"(d[OFF+19]), "+f"(d[OFF+20]), "+f"(d[OFF+21]), "+f"(d[OFF+22]), "+f"(d[OFF+23]), "+f"(d[OFF+24]), "+f"(d[OFF+25]), "+f"(d[OFF+26]), "+f"(d[OFF+27]), "+f"(d[OFF+28]), "+f"(d[OFF+29]), "+f"(d[OFF+30]), "+f"(d[OFF+31]), "+f"(d[OFF+32]), "+f"(d[OFF+33]), "+f"(d[OFF+34]), "+f"(d[OFF+35]), "+f"(d[OFF+36]), "+f"(d[OFF+37]), "+f"(d[OFF+38]), "+f"(d[OFF+39]), "+f"(d[OFF+40]), "+f"(d[OFF+41]), "+f"(d[OFF+42]), "+f"(d[OFF+43]), "+f"(d[OFF+44]), "+f"(d[OFF+45]), "+f"(d[OFF+46]), "+f"(d[OFF+47]), "+f"(d[OFF+48]), "+f"(d[OFF+49]), "+f"(d[OFF+50]), "+f"(d[OFF+51]), "+f"(d[OFF+52]), "+f"(d[OFF+53]), "+f"(d[OFF+54]), "+f"(d[OFF+55]), "+f"(d[OFF+56]), "+f"(d[OFF+57]), "+f"(d[OFF+58]), "+f"(d[OFF+59]), "+f"(d[OFF+60]), "+f"(d[OFF+61]), "+f"(d[OFF+62]), "+f"(d[OFF+63])
    : "l"(da), "l"(db), "r"(scale_d), "n"(TB));
}
template<int TB, int OFF, int NT>
__device__ __forceinline__ void wgmma_ss_n32(float (&d)[NT], uint64_t da, uint64_t db, int scale_d) {
  asm volatile("{\n.reg .pred p;\nsetp.ne.b32 p, %18, 0;\n"
    "wgmma.mma_async.sync.aligned.m64n32k16.f32.bf16.bf16 {%0, %1, %2, %3, %4, %5, %6, %7, %8, %9, %10, %11, %12, %13, %14, %15}, %16, %17, p, 1, 1, 0, %19;\n}\n"
    : "+f"(d[OFF+0]), "+f"(d[OFF+1]), "+f"(d[OFF+2]), "+f"(d[OFF+3]), "+f"(d[OFF+4]), "+f"(d[OFF+5]), "+f"(d[OFF+6]), "+f"(d[OFF+7]), "+f"(d[OFF+8]), "+f"(d[OFF+9]), "+f"(d[OFF+10]), "+f"(d[OFF+11]), "+f"(d[OFF+12]), "+f"(d[OFF+13]), "+f"(d[OFF+14]), "+f"(d[OFF+15])
    : "l"(da), "l"(db), "r"(scale_d), "n"(TB));
}
template<int TB, int OFF, int NT>
__device__ __forceinline__ void wgmma_rs_n128(float (&d)[NT], uint32_t a0, uint32_t a1, uint32_t a2, uint32_t a3, uint64_t db, int scale_d) {
  asm volatile("{\n.reg .pred p;\nsetp.ne.b32 p, %69, 0;\n"
    "wgmma.mma_async.sync.aligned.m64n128k16.f32.bf16.bf16 {%0, %1, %2, %3, %4, %5, %6, %7, %8, %9, %10, %11, %12, %13, %14, %15, %16, %17, %18, %19, %20, %21, %22, %23, %24, %25, %26, %27, %28, %29, %30, %31, %32, %33, %34, %35, %36, %37, %38, %39, %40, %41, %42, %43, %44, %45, %46, %47, %48, %49, %50, %51, %52, %53, %54, %55, %56, %57, %58, %59, %60, %61, %62, %63}, {%64, %65, %66, %67}, %68, p, 1, 1, %70;\n}\n"
    : "+f"(d[OFF+0]), "+f"(d[OFF+1]), "+f"(d[OFF+2]), "+f"(d[OFF+3]), "+f"(d[OFF+4]), "+f"(d[OFF+5]), "+f"(d[OFF+6]), "+f"(d[OFF+7]), "+f"(d[OFF+8]), "+f"(d[OFF+9]), "+f"(d[OFF+10]), "+f"(d[OFF+11]), "+f"(d[OFF+12]), "+f"(d[OFF+13]), "+f"(d[OFF+14]), "+f"(d[OFF+15]), "+f"(d[OFF+16]), "+f"(d[OFF+17]), "+f"(d[OFF+18]), "+f"(d[OFF+19]), "+f"(d[OFF+20]), "+f"(d[OFF+21]), "+f"(d[OFF+22]), "+f"(d[OFF+23]), "+f"(d[OFF+24]), "+f"(d[OFF+25]), "+f"(d[OFF+26]), "+f"(d[OFF+27]), "+f"(d[OFF+28]), "+f"(d[OFF+29]), "+f"(d[OFF+30]), "+f"(d[OFF+31]), "+f"(d[OFF+32]), "+f"(d[OFF+33]), "+f"(d[OFF+34]), "+f"(d[OFF+35]), "+f"(d[OFF+36]), "+f"(d[OFF+37]), "+f"(d[OFF+38]), "+f"(d[OFF+39]), "+f"(d[OFF+40]), "+f"(d[OFF+41]), "+f"(d[OFF+42]), "+f"(d[OFF+43]), "+f"(d[OFF+44]), "+f"(d[OFF+45]), "+f"(d[OFF+46]), "+f"(d[OFF+47]), "+f"(d[OFF+48]), "+f"(d[OFF+49]), "+f"(d[OFF+50]), "+f"(d[OFF+51]), "+f"(d[OFF+52]), "+f"(d[OFF+53]), "+f"(d[OFF+54]), "+f"(d[OFF+55]), "+f"(d[OFF+56]), "+f"(d[OFF+57]), "+f"(d[OFF+58]), "+f"(d[OFF+59]), "+f"(d[OFF+60]), "+f"(d[OFF+61]), "+f"(d[OFF+62]), "+f"(d[OFF+63])
    : "r"(a0), "r"(a1), "r"(a2), "r"(a3), "l"(db), "r"(scale_d), "n"(TB));
}
template<int TB, int OFF, int NT>
__device__ __forceinline__ void wgmma_rs_n64(float (&d)[NT], uint32_t a0, uint32_t a1, uint32_t a2, uint32_t a3, uint64_t db, int scale_d) {
  asm volatile("{\n.reg .pred p;\nsetp.ne.b32 p, %37, 0;\n"
    "wgmma.mma_async.sync.aligned.m64n64k16.f32.bf16.bf16 {%0, %1, %2, %3, %4, %5, %6, %7, %8, %9, %10, %11, %12, %13, %14, %15, %16, %17, %18, %19, %20, %21, %22, %23, %24, %25, %26, %27, %28, %29, %30, %31}, {%32, %33, %34, %35}, %36, p, 1, 1, %38;\n}\n"
    : "+f"(d[OFF+0]), "+f"(d[OFF+1]), "+f"(d[OFF+2]), "+f"(d[OFF+3]), "+f"(d[OFF+4]), "+f"(d[OFF+5]), "+f"(d[OFF+6]), "+f"(d[OFF+7]), "+f"(d[OFF+8]), "+f"(d[OFF+9]), "+f"(d[OFF+10]), "+f"(d[OFF+11]), "+f"(d[OFF+12]), "+f"(d[OFF+13]), "+f"(d[OFF+14]), "+f"(d[OFF+15]), "+f"(d[OFF+16]), "+f"(d[OFF+17]), "+f"(d[OFF+18]), "+f"(d[OFF+19]), "+f"(d[OFF+20]), "+f"(d[OFF+21]), "+f"(d[OFF+22]), "+f"(d[OFF+23]), "+f"(d[OFF+24]), "+f"(d[OFF+25]), "+f"(d[OFF+26]), "+f"(d[OFF+27]), "+f"(d[OFF+28]), "+f"(d[OFF+29]), "+f"(d[OFF+30]), "+f"(d[OFF+31])
    : "r"(a0), "r"(a1), "r"(a2), "r"(a3), "l"(db), "r"(scale_d), "n"(TB));
}

__device__ __forceinline__ void wait_flag(const unsigned int* f, uint32_t target) {
  uint32_t v;
#pragma unroll 1
  for (uint32_t spins = 0; spins < (1u << 22); spins++) {
    asm volatile("ld.acquire.gpu.global.u32 %0, [%1];" : "=r"(v) : "l"(f) : "memory");
    if (v >= target) break;
    __nanosleep(100);
  }
}
__device__ __forceinline__ uint32_t lds32(uint32_t a) {
  uint32_t v;
  asm volatile("ld.shared.u32 %0, [%1];" : "=r"(v) : "r"(a) : "memory");
  return v;
}
__device__ __forceinline__ float gate_row(int row, int lane, const bf16* __restrict__ x, const bf16* __restrict__ gate_w) {
  const uint32_t* xr = reinterpret_cast<const uint32_t*>(x + (size_t)row * DM);
  const uint32_t* gw2 = reinterpret_cast<const uint32_t*>(gate_w);
  float gs = 0.f;
#pragma unroll
  for (int i = 0; i < 9; i++) {
    const uint32_t a = __ldg(xr + lane + 32 * i), b = __ldg(gw2 + lane + 32 * i);
    gs = fmaf(bf_lo(a), bf_lo(b), gs);
    gs = fmaf(bf_hi(a), bf_hi(b), gs);
  }
#pragma unroll
  for (int o = 16; o; o >>= 1) gs += __shfl_xor_sync(0xffffffffu, gs, o);
  const float g = 1.f / (1.f + __expf(-gs));
  if (lane == 0) g_gate[row] = g;
  return g;
}
#define LA_UNROLL 1
__device__ __forceinline__ void local_rows2(int rb, uint32_t sb, uint32_t scr, int lane, float ga, float gb) {
  const float scale_l2 = 0.23570226039551584f * 1.4426950408889634f;
  constexpr uint32_t RS = NQKVA * 2;
  constexpr int U = LA_UNROLL;
  float ma = -INFINITY, mb = -INFINITY;
  {
    float qa[18], qb[18];
#pragma unroll
    for (int i = 0; i < 9; i++) {
      const uint32_t u = lds32(sb - 2 * RS + 4 * i), v = lds32(sb + 4 * i);
      qa[2 * i] = bf_lo(u); qa[2 * i + 1] = bf_hi(u);
      qb[2 * i] = bf_lo(v); qb[2 * i + 1] = bf_hi(v);
    }
#pragma unroll U
    for (int t = 0; t < 9; t++) {
      const bool ok = rb - 2 * t >= 0;
      const uint32_t ka = sb + 1152 - (ok ? 2 * t : 0) * RS;
      float a0 = 0.f, a1 = 0.f, b0 = 0.f, b1 = 0.f;
#pragma unroll
      for (int i = 0; i < 9; i++) {
        const uint32_t k = lds32(ka + 4 * i);
        const float lo = bf_lo(k), hi = bf_hi(k);
        a0 = fmaf(qa[2 * i], lo, a0); a1 = fmaf(qa[2 * i + 1], hi, a1);
        b0 = fmaf(qb[2 * i], lo, b0); b1 = fmaf(qb[2 * i + 1], hi, b1);
      }
      a0 = (ok && t > 0) ? a0 + a1 : -INFINITY;
      b0 = (ok && t < 8) ? b0 + b1 : -INFINITY;
      ma = fmaxf(ma, a0);
      mb = fmaxf(mb, b0);
      asm volatile("st.shared.v2.f32 [%0], {%1, %2};" ::"r"(scr + t * 256), "f"(a0), "f"(b0) : "memory");
    }
  }
  float oa[18], ob[18], sa = 0.f, sb2 = 0.f;
#pragma unroll
  for (int i = 0; i < 18; i++) { oa[i] = 0.f; ob[i] = 0.f; }
#pragma unroll U
  for (int t = 0; t < 9; t++) {
    const uint32_t va = sb + 2304 - ((rb - 2 * t >= 0) ? 2 * t : 0) * RS;
    float wa, wb;
    asm volatile("ld.shared.v2.f32 {%0, %1}, [%2];" : "=f"(wa), "=f"(wb) : "r"(scr + t * 256) : "memory");
    wa = ex2((wa - ma) * scale_l2);
    wb = ex2((wb - mb) * scale_l2);
    sa += wa;
    sb2 += wb;
#pragma unroll
    for (int i = 0; i < 9; i++) {
      const uint32_t v = lds32(va + 4 * i);
      const float lo = bf_lo(v), hi = bf_hi(v);
      oa[2 * i] = fmaf(wa, lo, oa[2 * i]); oa[2 * i + 1] = fmaf(wa, hi, oa[2 * i + 1]);
      ob[2 * i] = fmaf(wb, lo, ob[2 * i]); ob[2 * i + 1] = fmaf(wb, hi, ob[2 * i + 1]);
    }
  }
  ga = __fdividef(ga, sa);
  gb = __fdividef(gb, sb2);
#pragma unroll
  for (int i = 0; i < 9; i++) {
    asm volatile("st.shared.u32 [%0], %1;" ::"r"(sb - 2 * RS + 4 * i), "r"(pack_bf16(oa[2 * i] * ga, oa[2 * i + 1] * ga)) : "memory");
    asm volatile("st.shared.u32 [%0], %1;" ::"r"(sb + 4 * i), "r"(pack_bf16(ob[2 * i] * gb, ob[2 * i + 1] * gb)) : "memory");
  }
  __syncwarp();
  const uint32_t s0 = sb - 2 * RS - lane * 36;
#pragma unroll
  for (int t = 0; t < 5; t++) {
    const int c = t * 32 + lane;
    if (c < 144) {
      const int r = c >= 72, cc = c - r * 72;
      uint32_t a, b, d, e;
      asm volatile("ld.shared.v4.u32 {%0, %1, %2, %3}, [%4];" : "=r"(a), "=r"(b), "=r"(d), "=r"(e) : "r"(s0 + r * 2 * RS + cc * 16) : "memory");
      st_v4(g_ctx + (size_t)(rb - 2 + 2 * r) * KCAT + HDIM + cc * 8, a, b, d, e);
    }
  }
}

#define K1_NST 6
constexpr int K1_BST = K1_NST;
constexpr int K1_MAXJOBS = 10;
constexpr uint32_t K1_FLAG_TARGET = 7;
constexpr uint32_t RDY_TARGET = 48;
constexpr uint32_t GATE_TARGET = 128 * 3;
struct alignas(64) Params {
  CUtensorMap tmA[2];
  CUtensorMap tmW[4];
  CUtensorMap tmQ, tmK, tmV;
  CUtensorMap tmC, tmO[2], tmOt[2];
  uint16_t jobs[NCLUSTER][K1_MAXJOBS];
  uint8_t order[256];
};

struct K1State {
  uint32_t bs, bph, aph;
  bf16* pp;
  int pld8;
  int png;
};
__device__ __forceinline__ void k1_flag(const K1State& st, int lane, uint32_t bS) {
  if (st.png) {
    __syncwarp();
    if (lane == 0) mbar_arrive(bS);
  }
}

__device__ __forceinline__ void k1_tile(float (&acc)[128], uint32_t (&pk)[64], K1State& st, uint32_t job, uint32_t sA, uint32_t sB,
                                        uint32_t bAf, uint32_t bAe, uint32_t bBf, uint32_t bBe, uint32_t bS, int wg, int warp, int lane, uint32_t rank) {
  const int a_sel = (job >> 2) & 1, mpair = (job >> 3) & 7, w_sel = (job >> 6) & 3, chunk0 = (job >> 8) & 63;
  const bool newA = (job >> 14) & 1, lastA = (job >> 15) & 1;
  const bool sig = (lane == 0) && (warp < 2);
  const bool siga = lastA && (lane == 0) && (warp == 2);
  const int KC = 8 + a_sel;
  uint32_t prev_bs = 0, prev2_bs = 0, a8_bs = 0;
#pragma unroll
  for (int kc = 0; kc < 9; kc++) {
    if (kc >= KC) break;
    uint32_t abase = sA + kc * 16384;
    if (kc == 8) {
      mbar_wait(bBf + st.bs * 8, st.bph);
      a8_bs = st.bs;
      abase = sB + st.bs * 16384;
      if (++st.bs == K1_BST) { st.bs = 0; st.bph ^= 1; }
    } else if (newA) {
      mbar_wait(bAf + kc * 8, st.aph);
    }
    const uint64_t da = make_desc(abase + wg * 8192, 16, 1024, 1);
#pragma unroll
    for (int ks = 0; ks < 2; ks++) {
      mbar_wait(bBf + st.bs * 8, st.bph);
      const uint64_t db = make_desc(sB + st.bs * 16384, 2048, 1024, 1);
      wg_fence();
      wgmma_ss_n256<1, 0>(acc, da + (uint64_t)(ks * 4), db, (ks > 0) ? 1 : (kc > 0));
      wgmma_ss_n256<1, 0>(acc, da + (uint64_t)(ks * 4 + 2), db + (uint64_t)512, 1);
      wg_commit();
      const int PO = (kc < 8 ? kc : 0) * 8;
      wg_wait<1>();
      if (ks > 0 || kc > 0) {
        if (sig) mbar_arrive_cluster(bBe + prev_bs * 8, warp);
        if (ks == 0 && siga) mbar_arrive(bAe + (kc - 1) * 8);
      }
      if (kc < st.png) st_v4(st.pp + kc * 32 + ks * st.pld8, pk[PO + ks * 4], pk[PO + ks * 4 + 1], pk[PO + ks * 4 + 2], pk[PO + ks * 4 + 3]);
      prev_bs = st.bs;
      if (++st.bs == K1_BST) { st.bs = 0; st.bph ^= 1; }
    }
  }
  if (newA) st.aph ^= 1;
  k1_flag(st, lane, bS);
  wg_wait<0>();
  fence_regs(acc);
  if (sig) {
    mbar_arrive_cluster(bBe + prev_bs * 8, warp);
    if (a_sel) mbar_arrive_cluster(bBe + a8_bs * 8, warp);
  }
  if (siga && !a_sel) mbar_arrive(bAe + 7 * 8);
  const bool isA = (w_sel == 2);
  bf16* out = (w_sel == 0) ? g_K : (w_sel == 1) ? g_V : isA ? g_QKVA : g_Q;
  const int ld = isA ? NQKVA : HDIM;
  const int row = mpair * 256 + rank * 128 + wg * 64 + warp * 16 + (lane >> 2);
  st.pp = out + (size_t)row * ld + chunk0 * 64 + (lane & 3) * 8;
  st.pld8 = 8 * ld;
  st.png = ((job & 3) + 1) * 2;
#pragma unroll
  for (int G = 0; G < 8; G++) {
    pk[G * 8 + 0] = pack_bf16(acc[G * 16 + 0], acc[G * 16 + 1]);
    pk[G * 8 + 1] = pack_bf16(acc[G * 16 + 4], acc[G * 16 + 5]);
    pk[G * 8 + 2] = pack_bf16(acc[G * 16 + 8], acc[G * 16 + 9]);
    pk[G * 8 + 3] = pack_bf16(acc[G * 16 + 12], acc[G * 16 + 13]);
    pk[G * 8 + 4] = pack_bf16(acc[G * 16 + 2], acc[G * 16 + 3]);
    pk[G * 8 + 5] = pack_bf16(acc[G * 16 + 6], acc[G * 16 + 7]);
    pk[G * 8 + 6] = pack_bf16(acc[G * 16 + 10], acc[G * 16 + 11]);
    pk[G * 8 + 7] = pack_bf16(acc[G * 16 + 14], acc[G * 16 + 15]);
  }
  if (isA) {
#pragma unroll
    for (int G = 0; G < 16; G++) quad_transpose(pk[G * 4 + 0], pk[G * 4 + 1], pk[G * 4 + 2], pk[G * 4 + 3], lane & 3);
  }
}

constexpr int K2_NST = 7;
constexpr uint32_t K2_END = 0x100;
constexpr int K3_NST = 4;
constexpr int K3_STAGE = 16384 + 32768 + 4096;
constexpr int SMEM_DATA = 7 * 32768;
constexpr int SMEM_BYTES = SMEM_DATA + 1024 + 768;

struct Cursor {
  uint32_t s, ph;
  __device__ __forceinline__ void next() {
    if (++s == K2_NST) { s = 0; ph ^= 1; }
  }
};

#define TURN_SYNC() bar_sync(mybar, 256)
#define TURN_ARRIVE() bar_arrive(otherbar, 256)
#define RELEASE_IF(cur, cond) mbar_arrive_cluster_if(bE + (cur).s * 8, warp & 1, sig && (cond))
#define RELEASE(cur) RELEASE_IF(cur, true)
#define ISSUE_PV(cur, first)                                                                                   \
  do {                                                                                                         \
    const uint64_t dv = make_desc(sbase + (cur).s * 32768, 16384, 1024, 1);                                    \
    _Pragma("unroll") for (int t = 0; t < 8; t++)                                                              \
        wgmma_rs_n128<1, 0>(O, P[4 * t], P[4 * t + 1], P[4 * t + 2], P[4 * t + 3], dv + (uint64_t)(t * 128), (t > 0) ? 1 : !(first)); \
  } while (0)
#define ISSUE_QK(cur)                                                                                          \
  do {                                                                                                         \
    const uint64_t dk = make_desc(sbase + (cur).s * 32768, 16, 1024, 1);                                       \
    _Pragma("unroll") for (int t = 0; t < 8; t++)                                                              \
        wgmma_rs_n128<0, 0>(S, Q[4 * t], Q[4 * t + 1], Q[4 * t + 2], Q[4 * t + 3], dk + (uint64_t)((t >> 2) * 1024 + (t & 3) * 2), t > 0); \
  } while (0)
#define EPILOGUE()                                                                                             \
  do {                                                                                                         \
    l0 += __shfl_xor_sync(0xffffffffu, l0, 1);                                                                 \
    l0 += __shfl_xor_sync(0xffffffffu, l0, 2);                                                                 \
    l1 += __shfl_xor_sync(0xffffffffu, l1, 1);                                                                 \
    l1 += __shfl_xor_sync(0xffffffffu, l1, 2);                                                                 \
    const float f0 = __fdividef(gf0, l0), f1 = __fdividef(gf1, l1);                                                                \
    bf16* o0 = g_ctx + (size_t)prev_row * KCAT + prev_h * 128 + q * 8;                                         \
    bf16* o1 = o0 + (size_t)8 * KCAT;                                                                          \
    _Pragma("unroll") for (int G = 0; G < 4; G++) {                                                            \
      st_v4(o0 + G * 32, pack_bf16(O[G * 16 + 0] * f0, O[G * 16 + 1] * f0), pack_bf16(O[G * 16 + 4] * f0, O[G * 16 + 5] * f0), \
            pack_bf16(O[G * 16 + 8] * f0, O[G * 16 + 9] * f0), pack_bf16(O[G * 16 + 12] * f0, O[G * 16 + 13] * f0)); \
      st_v4(o1 + G * 32, pack_bf16(O[G * 16 + 2] * f1, O[G * 16 + 3] * f1), pack_bf16(O[G * 16 + 6] * f1, O[G * 16 + 7] * f1), \
            pack_bf16(O[G * 16 + 10] * f1, O[G * 16 + 11] * f1), pack_bf16(O[G * 16 + 14] * f1, O[G * 16 + 15] * f1)); \
    }                                                                                                          \
  } while (0)

__global__ void __cluster_dims__(2, 1, 1) __launch_bounds__(384, 1)
fused_kernel(const __grid_constant__ Params p, const bf16* __restrict__ x, const bf16* __restrict__ gate_w, bf16* __restrict__ out) {
  extern __shared__ uint8_t smem_raw[];
  const uint32_t sbase = (smem_u32(smem_raw) + 1023) & ~1023u;
  const uint32_t sB = sbase, sA = sbase + K1_BST * 16384, sBar = sbase + SMEM_DATA;
  const uint32_t bAf = sBar, bAe = sBar + 64, bBf = sBar + 128, bBe = sBar + 176, bL = sBar + 224, bS = sBar + 232;
  const uint32_t bF = sBar + 256, bE = sBar + 320, bT = sBar + 384, sTick = sBar + 400, sItem = sBar + 416, bS2 = sBar + 448, bZ = sBar + 456;
  const uint32_t b3F = sBar + 512, b3E = sBar + 544, sGate = sBar + 576;
  const int tid = threadIdx.x, warp_g = __shfl_sync(0xffffffffu, tid >> 5, 0), lane = tid & 31;
  const uint32_t rank = cluster_rank();
  const int cl = blockIdx.x >> 1;
  TSM(0);
  if (tid == 0) {
    for (int i = 0; i < 8; i++) { mbar_init(bAf + i * 8, 1); mbar_init(bAe + i * 8, 2); }
    for (int i = 0; i < K1_BST; i++) { mbar_init(bBf + i * 8, 1); mbar_init(bBe + i * 8, 4); }
    mbar_init(bL, 1);
    mbar_init(bS, 8);
    for (int i = 0; i < K2_NST; i++) { mbar_init(bF + i * 8, 1); mbar_init(bE + i * 8, 4); }
    mbar_init(bT, 1); mbar_init(bT + 8, 1);
    mbar_init(bS2, 8);
    for (int i = 0; i < K3_NST; i++) { mbar_init(b3F + i * 8, 1); mbar_init(b3E + i * 8, 4); }
    asm volatile("fence.mbarrier_init.release.cluster;" ::: "memory");
  }
  __syncthreads();
  cluster_sync();
  const int lr0 = blockIdx.x * 16, lrs = max(lr0 - 14, 0);

  if (warp_g >= 8) {
    reg_dealloc<40>();
    if (warp_g == 8) {
      if (elect_one()) {
        uint32_t bs = 0, bph = 1, aph = 1;
#pragma unroll 1
        for (int ji = 0; ji < K1_MAXJOBS; ji++) {
          const uint32_t job = p.jobs[cl][ji];
          if (!(job & 3)) break;
          const int a_sel = (job >> 2) & 1, mpair = (job >> 3) & 7, chunk0 = (job >> 8) & 63;
          const bool newA = (job >> 14) & 1;
          const int KC = a_sel ? 9 : 8;
          const uint32_t halfbytes = 8192;
          const CUtensorMap* tw = &p.tmW[(job >> 6) & 3];
          {
            const uint32_t njob = (ji + 1 < K1_MAXJOBS) ? p.jobs[cl][ji + 1] : 0;
            if (njob & 3) {
              const int nst = ((njob >> 2) & 1) ? 18 : 16;
#pragma unroll 1
              for (int t = (cl < 64) ? (cl & 7) : 0; t < nst; t += (cl < 64) ? 8 : 1)
                tma_pf3d(&p.tmW[(njob >> 6) & 3], 0, t * 32 + rank * 16, (njob >> 8) & 63);
            }
          }
#pragma unroll 1
          for (int kc = 0; kc < KC; kc++) {
            if (kc == 8) {
              mbar_wait(bBe + bs * 8, bph);
              mbar_expect(bBf + bs * 8, 16384);
              tma2d(sB + bs * 16384, &p.tmA[1], bBf + bs * 8, 512, mpair * 256 + rank * 128);
              if (++bs == K1_BST) { bs = 0; bph ^= 1; }
            } else if (newA) {
              mbar_wait(bAe + kc * 8, aph);
              mbar_expect(bAf + kc * 8, 16384);
              tma2d(sA + kc * 16384, &p.tmA[a_sel], bAf + kc * 8, kc * 64, mpair * 256 + rank * 128);
            }
#pragma unroll 1
            for (int kk = 0; kk < 2; kk++) {
              mbar_wait(bBe + bs * 8, bph);
              mbar_expect(bBf + bs * 8, 2 * halfbytes);
              tma3d_mc(sB + bs * 16384 + rank * halfbytes, tw, bBf + bs * 8, 0, kc * 64 + kk * 32 + rank * 16, chunk0, 3);
              if (++bs == K1_BST) { bs = 0; bph ^= 1; }
            }
          }
          if (newA) aph ^= 1;
        }
        prefetch_tmap(&p.tmQ); prefetch_tmap(&p.tmK); prefetch_tmap(&p.tmV);
        if (lr0 < S_LEN) {
          wait_flag(&g_sync[F_QKVA + (lr0 >> 7)], K1_FLAG_TARGET);
          wait_flag(&g_sync[F_QKVA + (lrs >> 7)], K1_FLAG_TARGET);
          asm volatile("fence.proxy.async;" ::: "memory");
          const uint32_t bytes = (lr0 + 16 - lrs) * (NQKVA * 2);
          mbar_expect(bL, bytes);
#pragma unroll 1
          for (uint32_t o = 0; o < bytes; o += 16384) {
            mbar_wait(bAe + (o >> 14) * 8, aph);
            asm volatile("cp.async.bulk.shared::cluster.global.mbarrier::complete_tx::bytes [%0], [%1], %2, [%3];" ::"r"(sA + o),
                         "l"(reinterpret_cast<const char*>(g_QKVA + (size_t)lrs * NQKVA) + o), "r"(min(bytes - o, 16384u)), "r"(bL) : "memory");
          }
        }
        Cursor c{0, 0};
        int pcol = 0;
        uint32_t seen = 0, tick = cl;
        wait_flag(&g_sync[F_GATE], GATE_TARGET);
#pragma unroll 1
        for (int it = 0;; it++) {
          const uint32_t item = (tick < 256) ? p.order[tick] : (K2_END | min(tick - 256, 255u));
          asm volatile("st.shared.u32 [%0], %1;" ::"r"(sItem + (it & 7) * 4), "r"(item) : "memory");
          if (item >= K2_END) break;
          const int h = item >> 3, j = item & 7;
          const int blk = 2 * j + (int)(rank ^ (it & 1));
          const int col = h * 128 + rank * 64;
          const int nb = 2 * j + 2;
          if (!((seen >> (h >> 1)) & 1)) {
            wait_flag(&g_sync[F_HP + (h >> 1)], RDY_TARGET);
            asm volatile("fence.proxy.async;" ::: "memory");
            seen |= 1u << (h >> 1);
          }
          mbar_wait(bE + c.s * 8, c.ph);
          mbar_expect(bF + c.s * 8, 32768);
          tma2d(sbase + c.s * 32768, &p.tmQ, bF + c.s * 8, h * 128, blk * 128);
          tma2d(sbase + c.s * 32768 + 16384, &p.tmQ, bF + c.s * 8, h * 128 + 64, blk * 128);
          c.next();
#pragma unroll 1
          for (int n = nb - 1; n >= 0; n--) {
            if (n == 0 && rank == 0) tick = atomicAdd(&g_sync[F_TICK], 1u) + NCLUSTER;
            mbar_wait(bE + c.s * 8, c.ph);
            mbar_expect(bF + c.s * 8, 32768);
            tma2d_mc(sbase + c.s * 32768 + rank * 16384, &p.tmK, bF + c.s * 8, col, n * 128, 3);
            c.next();
            if (n < nb - 1 || it > 0) {
              mbar_wait(bE + c.s * 8, c.ph);
              mbar_expect(bF + c.s * 8, 32768);
              tma2d_mc(sbase + c.s * 32768 + rank * 16384, &p.tmV, bF + c.s * 8, (n < nb - 1) ? col : pcol, (n < nb - 1) ? (n + 1) * 128 : 0, 3);
              c.next();
            }
          }
          pcol = col;
          if (rank == 0) {
            asm volatile(
                "{\n.reg .b32 a, b;\nmapa.shared::cluster.u32 a, %0, 1;\nmapa.shared::cluster.u32 b, %1, 1;\n"
                "st.async.shared::cluster.mbarrier::complete_tx::bytes.u32 [a], %2, [b];\n}" ::"r"(sTick + (it & 1) * 4),
                "r"(bT + (it & 1) * 8), "r"(tick) : "memory");
          } else {
            mbar_expect(bT + (it & 1) * 8, 4);
            mbar_wait(bT + (it & 1) * 8, (it >> 1) & 1);
            tick = lds32(sTick + (it & 1) * 4);
          }
        }
        mbar_wait(bE + c.s * 8, c.ph);
        mbar_expect(bF + c.s * 8, 32768);
        tma2d_mc(sbase + c.s * 32768 + rank * 16384, &p.tmV, bF + c.s * 8, pcol, 0, 3);
        const uint32_t unit = tick - 256;
        if (unit < 64) {
          const int mp = 7 - (int)(unit >> 3), mblk = mp * 2 + rank, nhalf = (unit >> 2) & 1, ks = unit & 3;
          const int k0 = ks * 18, k1 = (ks == 3) ? 73 : k0 + 18;
          uint32_t s = 0, ph = 0;
#pragma unroll 1
          for (int k = k0; k < k1; k++) {
            mbar_wait(b3E + s * 8, ph);
            mbar_expect(b3F + s * 8, K3_STAGE);
            const uint32_t st = sbase + s * K3_STAGE;
            const int sel = (k >= 64), kr = (sel ? (k - 64) : k) * 64 + rank * 32;
            tma3d_mc(st + 16384 + rank * 16384, &p.tmO[sel], b3F + s * 8, 0, kr, nhalf * 4, 3);
            tma2d_mc(st + 49152 + rank * 2048, &p.tmOt[sel], b3F + s * 8, 512 + nhalf * 32, kr, 3);
            if (k == k0) {
              wait_flag(&g_sync[F_CTX + mp * 4 + ks], (ks == 3) ? 26 : 18);
              asm volatile("fence.proxy.async;" ::: "memory");
            }
            tma2d(st, &p.tmC, b3F + s * 8, k * 64, mblk * 128);
            if (++s == K3_NST) { s = 0; ph ^= 1; }
          }
        }
      }
    }
    __syncwarp();
    asm volatile("" ::: "memory");
    if (__shfl_sync(0xffffffffu, warp_g, 0) != 8) {
      if (lr0 < S_LEN) {
#pragma unroll 1
        for (int i = warp_g - 9; i < 16; i += 3) {
          const float g = gate_row(lr0 + i, lane, x, gate_w);
          if (lane == 0) asm volatile("st.shared.f32 [%0], %1;" ::"r"(sGate + i * 4), "f"(g) : "memory");
        }
        bar_arrive(3, 256 + 96);
        if (lane == 0) {
          __threadfence();
          atomicAdd(&g_sync[F_GATE], 1u);
        }
      }
      if (warp_g == 9 && lane == 0) {
#pragma unroll 1
        for (int ji = 0; ji < K1_MAXJOBS; ji++) {
          const uint32_t job = p.jobs[cl][ji];
          if (!(job & 3)) break;
          mbar_wait(bS, ji & 1);
          __threadfence();
          atomicAdd(&g_sync[(((job >> 6) & 3) == 2) ? (F_QKVA + ((job >> 3) & 7) * 2 + rank) : (F_HP + ((job >> 10) & 15))], 1u);
        }
#pragma unroll 1
        for (int it = 0;; it++) {
          mbar_wait(bS2, it & 1);
          const uint32_t item = lds32(sItem + (it & 7) * 4), nxt = lds32(sItem + ((it + 1) & 7) * 4);
          __threadfence();
          atomicAdd(&g_sync[F_CTX + (item & 7) * 4 + (item >> 3) / 9], 1u);
          if (nxt >= K2_END) break;
        }
      } else if (warp_g == 10 && lr0 < S_LEN) {
        bar_sync(5, 256 + 32);
        if (lane == 0) {
          __threadfence();
          atomicAdd(&g_sync[F_CTX + (lr0 >> 8) * 4 + 3], 1u);
        }
      }
    }
    __syncwarp();
    cluster_sync();
    if (warp_g == 8) {
      uint32_t v = 0;
      if (lane == 0) {
        __threadfence();
        v = atomicAdd(&g_sync[F_DONE], 1u);
      }
      if (__shfl_sync(0xffffffffu, v, 0) == 2 * NCLUSTER - 1) reinterpret_cast<uint4*>(g_sync)[lane] = make_uint4(0, 0, 0, 0);
    }
  } else {
    reg_alloc<232>();
    const int wg = warp_g >> 2, warp = warp_g & 3, q = lane & 3;
    const bool sig = (lane == 0) && (warp < 2);
    {
      K1State st{0, 0, 0, nullptr, 0, 0};
      float acc[128];
      uint32_t pk[64];
      if (wg == 0) { TS(0, 0); TSC(0, 2); }
#pragma unroll 1
      for (int ji = 0; ji < K1_MAXJOBS; ji++) {
        const uint32_t job = p.jobs[cl][ji];
        if (!(job & 3)) break;
        k1_tile(acc, pk, st, job, sA, sB, bAf, bAe, bBf, bBe, bS, wg, warp, lane, rank);
      }
#pragma unroll
      for (int i = 0; i < 3; i++)
        mbar_arrive_cluster_if(bE + i * 8, warp & 1, sig);
#pragma unroll
      for (int G = 0; G < 8; G++)
        if (G < st.png) {
          st_v4(st.pp + G * 32, pk[G * 8], pk[G * 8 + 1], pk[G * 8 + 2], pk[G * 8 + 3]);
          st_v4(st.pp + G * 32 + st.pld8, pk[G * 8 + 4], pk[G * 8 + 5], pk[G * 8 + 6], pk[G * 8 + 7]);
        }
      k1_flag(st, lane, bS);
      if (wg == 0) { TS(0, 1); TSC(0, 3); }
      if (lr0 < S_LEN) {
        const int ri = (warp_g >> 1) * 4 + (warp_g & 1) + 2, row = lr0 + ri;
        if (wg == 0) TS(1, 5);
        bar_sync(3, 256 + 96);
        const float gate0 = __uint_as_float(lds32(sGate + ri * 4 - 8)), gate1 = __uint_as_float(lds32(sGate + ri * 4));
        mbar_wait(bL, 0);
        if (wg == 0) TS(1, 6);
        local_rows2(row, sA + (row - lrs) * (NQKVA * 2) + lane * 36, sA + 106496 + warp_g * 2304 + lane * 8, lane, gate0, gate1);
        bar_arrive(5, 256 + 32);
        asm volatile("fence.proxy.async.shared::cta;" ::: "memory");
        bar_sync(4, 256);
      }
#pragma unroll
      for (int i = 3; i < K2_NST; i++) mbar_arrive_cluster_if(bE + i * 8, warp & 1, sig);
    }
    __syncwarp();
    uint32_t item;
    {
      const int mybar = 1 + wg, otherbar = 2 - wg;
      const float cl2 = 0.08838834764831845f * 1.4426950408889634f;
      float S[64], O[64];
      uint32_t P[32], Q[32];
#pragma unroll
      for (int i = 0; i < 64; i++) { S[i] = 0.f; O[i] = 1.f; }
#pragma unroll
      for (int i = 0; i < 32; i++) P[i] = 0;
      float m0 = 0.f, m1 = 0.f, l0 = 0.f, l1 = 0.f;
      int prev_row = 0, prev_h = 0, prev_single = 0;
      Cursor c{0, 0};
      if (wg == 1) bar_arrive(1, 256);
      if (wg == 0) { TS(1, 0); TSC(1, 2); }
#pragma unroll 1
      for (int it = 0;; it++) {
        mbar_wait(bF + c.s * 8, c.ph);
        item = lds32(sItem + (it & 7) * 4);
        if (item >= K2_END) break;
        const int h = item >> 3, j = item & 7;
        const int hi = (int)(rank ^ (it & 1));
        const int nblk = 2 * j + 1 + hi;
        {
          const float gf0 = 1.f - g_gate[prev_row], gf1 = 1.f - g_gate[prev_row + 8];
          Cursor cq = c; c.next();
          {
            const int r = wg * 64 + warp * 16 + (lane & 7) + ((lane >> 3) & 1) * 8;
            const uint32_t qa = sbase + cq.s * 32768 + r * 128;
#pragma unroll
            for (int t = 0; t < 8; t++)
              ldsm_x4(Q[4 * t], Q[4 * t + 1], Q[4 * t + 2], Q[4 * t + 3], qa + (t >> 2) * 16384 + ((((t & 3) * 2 + (lane >> 4)) ^ (lane & 7)) << 4));
          }
          Cursor ck = c; c.next();
          Cursor cs0 = ck, cs1 = ck, cv = c;
          mbar_wait(bF + ck.s * 8, ck.ph);
          if (it > 0) { mbar_wait(bF + cv.s * 8, cv.ph); c.next(); }
          if (!hi) {
            ck = c; c.next();
            cs1 = c; c.next();
            mbar_wait(bF + ck.s * 8, ck.ph);
            mbar_wait(bF + cs1.s * 8, cs1.ph);
          }
          TURN_SYNC();
          wg_fence();
          ISSUE_QK(ck);
          wg_commit();
          if (it > 0) ISSUE_PV(cv, prev_single);
          wg_commit();
          TURN_ARRIVE();
          RELEASE(cq);
          if (!hi) { RELEASE(cs0); RELEASE(cs1); }
          wg_wait<1>();
          fence_regs(S);
          RELEASE(ck);
          const int r0 = wg * 64 + warp * 16 + (lane >> 2);
#pragma unroll
          for (int jj = 0; jj < 16; jj++) {
            const int cc = jj * 8 + 2 * q;
            if (cc > r0) S[jj * 4 + 0] = -INFINITY;
            if (cc + 1 > r0) S[jj * 4 + 1] = -INFINITY;
            if (cc > r0 + 8) S[jj * 4 + 2] = -INFINITY;
            if (cc + 1 > r0 + 8) S[jj * 4 + 3] = -INFINITY;
          }
          float mx0 = fmaxf(S[0], S[1]), mx1 = fmaxf(S[2], S[3]);
#pragma unroll
          for (int jj = 1; jj < 16; jj++) {
            mx0 = fmaxf(mx0, fmaxf(S[jj * 4 + 0], S[jj * 4 + 1]));
            mx1 = fmaxf(mx1, fmaxf(S[jj * 4 + 2], S[jj * 4 + 3]));
          }
          mx0 = fmaxf(mx0, __shfl_xor_sync(0xffffffffu, mx0, 1));
          mx1 = fmaxf(mx1, __shfl_xor_sync(0xffffffffu, mx1, 1));
          mx0 = fmaxf(mx0, __shfl_xor_sync(0xffffffffu, mx0, 2));
          mx1 = fmaxf(mx1, __shfl_xor_sync(0xffffffffu, mx1, 2));
          m0 = mx0; m1 = mx1;
          const float mc0 = m0 * cl2, mc1 = m1 * cl2;
          float s0 = 0.f, s1 = 0.f;
#pragma unroll
          for (int jj = 0; jj < 16; jj++) {
            S[jj * 4 + 0] = ex2(fmaf(S[jj * 4 + 0], cl2, -mc0));
            S[jj * 4 + 1] = ex2(fmaf(S[jj * 4 + 1], cl2, -mc0));
            S[jj * 4 + 2] = ex2(fmaf(S[jj * 4 + 2], cl2, -mc1));
            S[jj * 4 + 3] = ex2(fmaf(S[jj * 4 + 3], cl2, -mc1));
            s0 += S[jj * 4 + 0] + S[jj * 4 + 1];
            s1 += S[jj * 4 + 2] + S[jj * 4 + 3];
          }
          fence_regs(S);
          wg_wait<0>();
          fence_regs(O);
          fence_regs(P);
          if (it > 0) {
            RELEASE(cv);
            EPILOGUE();
            __syncwarp();
            if (lane == 0) mbar_arrive(bS2);
          }
          l0 = s0; l1 = s1;
#pragma unroll
          for (int jj = 0; jj < 16; jj++) {
            P[jj * 2 + 0] = pack_bf16(S[jj * 4 + 0], S[jj * 4 + 1]);
            P[jj * 2 + 1] = pack_bf16(S[jj * 4 + 2], S[jj * 4 + 3]);
          }
        }
#pragma unroll 1
        for (int n = 1; n < nblk; n++) {
          Cursor ck = c; c.next();
          Cursor cv = c; c.next();
          mbar_wait(bF + ck.s * 8, ck.ph);
          mbar_wait(bF + cv.s * 8, cv.ph);
          TURN_SYNC();
          wg_fence();
          ISSUE_QK(ck);
          wg_commit();
          ISSUE_PV(cv, n == 1);
          wg_commit();
          TURN_ARRIVE();
          wg_wait<1>();
          fence_regs(S);
          RELEASE(ck);
          float mx0 = fmaxf(S[0], S[1]), mx1 = fmaxf(S[2], S[3]);
#pragma unroll
          for (int jj = 1; jj < 16; jj++) {
            mx0 = fmaxf(mx0, fmaxf(S[jj * 4 + 0], S[jj * 4 + 1]));
            mx1 = fmaxf(mx1, fmaxf(S[jj * 4 + 2], S[jj * 4 + 3]));
          }
          mx0 = fmaxf(mx0, __shfl_xor_sync(0xffffffffu, mx0, 1));
          mx1 = fmaxf(mx1, __shfl_xor_sync(0xffffffffu, mx1, 1));
          mx0 = fmaxf(mx0, __shfl_xor_sync(0xffffffffu, mx0, 2));
          mx1 = fmaxf(mx1, __shfl_xor_sync(0xffffffffu, mx1, 2));
          mx0 = fmaxf(mx0, m0);
          mx1 = fmaxf(mx1, m1);
          const float sc0 = ex2((m0 - mx0) * cl2), sc1 = ex2((m1 - mx1) * cl2);
          m0 = mx0; m1 = mx1;
          const float mc0 = m0 * cl2, mc1 = m1 * cl2;
          float s0 = 0.f, s1 = 0.f;
#pragma unroll
          for (int jj = 0; jj < 16; jj++) {
            S[jj * 4 + 0] = ex2(fmaf(S[jj * 4 + 0], cl2, -mc0));
            S[jj * 4 + 1] = ex2(fmaf(S[jj * 4 + 1], cl2, -mc0));
            S[jj * 4 + 2] = ex2(fmaf(S[jj * 4 + 2], cl2, -mc1));
            S[jj * 4 + 3] = ex2(fmaf(S[jj * 4 + 3], cl2, -mc1));
            s0 += S[jj * 4 + 0] + S[jj * 4 + 1];
            s1 += S[jj * 4 + 2] + S[jj * 4 + 3];
          }
          l0 = fmaf(l0, sc0, s0);
          l1 = fmaf(l1, sc1, s1);
          fence_regs(S);
          wg_wait<0>();
          fence_regs(O);
          fence_regs(P);
          RELEASE(cv);
#pragma unroll
          for (int jj = 0; jj < 16; jj++) {
            O[jj * 4 + 0] *= sc0;
            O[jj * 4 + 1] *= sc0;
            O[jj * 4 + 2] *= sc1;
            O[jj * 4 + 3] *= sc1;
            P[jj * 2 + 0] = pack_bf16(S[jj * 4 + 0], S[jj * 4 + 1]);
            P[jj * 2 + 1] = pack_bf16(S[jj * 4 + 2], S[jj * 4 + 3]);
          }
        }
        prev_row = (2 * j + hi) * 128 + wg * 64 + warp * 16 + (lane >> 2);
        prev_h = h;
        prev_single = (nblk == 1);
      }
      {
        const float gf0 = 1.f - g_gate[prev_row], gf1 = 1.f - g_gate[prev_row + 8];
        Cursor cv = c;
        TURN_SYNC();
        wg_fence();
        ISSUE_PV(cv, prev_single);
        wg_commit();
        if (wg == 0) TURN_ARRIVE();
        wg_wait<0>();
        fence_regs(O);
#pragma unroll
        for (int i = 0; i < K3_NST; i++)
          mbar_arrive_cluster_if(b3E + i * 8, warp & 1, sig);
        EPILOGUE();
        __syncwarp();
        if (lane == 0) mbar_arrive(bS2);
      }
      if (wg == 1) { TS(1, 1); TSC(1, 3); }
    }
    __syncwarp();
    const uint32_t unit = item & 255;
    if (unit < 64) {
      const int mblk = (7 - (int)(unit >> 3)) * 2 + rank, nhalf = (unit >> 2) & 1, ks = unit & 3;
      const int k0 = ks * 18, k1 = (ks == 3) ? 73 : k0 + 18;
      float acc[144];
      uint32_t s = 0, ph = 0, prev = 0;
      if (wg == 0) { TS(2, 0); TSC(2, 2); }
#pragma unroll 1
      for (int k = k0; k < k1; k++) {
        mbar_wait(b3F + s * 8, ph);
        const uint32_t st = sbase + s * K3_STAGE;
        const uint64_t da = make_desc(st + wg * 8192, 16, 1024, 1);
        const uint64_t db = make_desc(st + 16384, 4096, 1024, 1);
        const uint64_t dt = make_desc(st + 49152, 16, 512, 2);
        wg_fence();
#pragma unroll
        for (int t = 0; t < 4; t++) {
          const int sd = (t > 0) || (k > k0);
          wgmma_ss_n256<1, 0>(acc, da + (uint64_t)(t * 2), db + (uint64_t)((t >> 1) * 1024 + (t & 1) * 128), sd);
          wgmma_ss_n32<1, 128>(acc, da + (uint64_t)(t * 2), dt + (uint64_t)(t * 64), sd);
        }
        wg_commit();
        if (k > k0) {
          wg_wait<1>();
          if (sig) mbar_arrive_cluster(b3E + prev * 8, warp);
        }
        prev = s;
        if (++s == K3_NST) { s = 0; ph ^= 1; }
      }
      wg_wait<0>();
      fence_regs(acc);
      if (wg == 0) TS(2, 4);
      const int tile = mblk * 2 + nhalf;
      float4* wp = g_part + (size_t)((tile * 4 + ks) * 4) * 9 * 256 + tid;
#pragma unroll
      for (int d = 0; d < 4; d++) {
        if (d != ks) {
#pragma unroll
          for (int i = 0; i < 8; i++)
            __stcg(wp + (d * 9 + i) * 256, make_float4(acc[d * 32 + i * 4], acc[d * 32 + i * 4 + 1], acc[d * 32 + i * 4 + 2], acc[d * 32 + i * 4 + 3]));
          __stcg(wp + (d * 9 + 8) * 256, make_float4(acc[128 + d * 4], acc[128 + d * 4 + 1], acc[128 + d * 4 + 2], acc[128 + d * 4 + 3]));
        }
      }
      __threadfence();
      bar_sync(4, 256);
      if (wg == 0) TS(2, 5);
      if (tid == 0) {
        atomicAdd(&g_sync[F_XCH + tile], 1u);
        uint32_t v, spins = 0;
        do {
          asm volatile("ld.acquire.gpu.global.u32 %0, [%1];" : "=r"(v) : "l"(&g_sync[F_XCH + tile]) : "memory");
        } while (v < 4 && ++spins < (1u << 24));
      }
      bar_sync(4, 256);
      if (wg == 0) TS(2, 6);
      float r[36];
#pragma unroll
      for (int d = 0; d < 4; d++) {
        if (d == ks) {
#pragma unroll
          for (int i = 0; i < 32; i++) r[i] = acc[d * 32 + i];
#pragma unroll
          for (int i = 0; i < 4; i++) r[32 + i] = acc[128 + d * 4 + i];
        }
      }
#pragma unroll
      for (int sI = 1; sI < 4; sI++) {
        const int src = (ks + sI) & 3;
        const float4* rp = g_part + (size_t)(((tile * 4 + src) * 4) + ks) * 9 * 256 + tid;
#pragma unroll
        for (int i = 0; i < 9; i++) {
          const float4 v = __ldcg(rp + i * 256);
          r[i * 4] += v.x; r[i * 4 + 1] += v.y; r[i * 4 + 2] += v.z; r[i * 4 + 3] += v.w;
        }
      }
      const int row = mblk * 128 + wg * 64 + warp * 16 + (lane >> 2);
      bf16* o0 = out + (size_t)row * DM + nhalf * 256 + ks * 64 + 8 * q;
#pragma unroll
      for (int G = 0; G < 2; G++) {
        uint32_t a0 = pack_bf16(r[G * 16], r[G * 16 + 1]), a1 = pack_bf16(r[G * 16 + 4], r[G * 16 + 5]);
        uint32_t a2 = pack_bf16(r[G * 16 + 8], r[G * 16 + 9]), a3 = pack_bf16(r[G * 16 + 12], r[G * 16 + 13]);
        uint32_t b0 = pack_bf16(r[G * 16 + 2], r[G * 16 + 3]), b1 = pack_bf16(r[G * 16 + 6], r[G * 16 + 7]);
        uint32_t b2 = pack_bf16(r[G * 16 + 10], r[G * 16 + 11]), b3 = pack_bf16(r[G * 16 + 14], r[G * 16 + 15]);
        quad_transpose(a0, a1, a2, a3, q);
        quad_transpose(b0, b1, b2, b3, q);
        st_v4(o0 + G * 32, a0, a1, a2, a3);
        st_v4(o0 + 8 * DM + G * 32, b0, b1, b2, b3);
      }
      {
        uint32_t t0 = pack_bf16(r[32], r[33]), t1 = pack_bf16(r[34], r[35]), t2 = 0, t3 = 0;
        quad_transpose(t0, t1, t2, t3, q);
        if (q < 2) st_v4(out + (size_t)(row + q * 8) * DM + 512 + nhalf * 32 + ks * 8, t0, t1, t2, t3);
      }
    }
    if (wg == 0) { TS(2, 1); TSC(2, 3); }
    cluster_sync();
  }
}

typedef CUresult (*EncFn)(CUtensorMap*, CUtensorMapDataType, cuuint32_t, void*, const cuuint64_t*, const cuuint64_t*, const cuuint32_t*,
                          const cuuint32_t*, CUtensorMapInterleave, CUtensorMapSwizzle, CUtensorMapL2promotion, CUtensorMapFloatOOBfill);

static void enc2d(EncFn enc, CUtensorMap* m, const void* ptr, uint64_t cols, uint64_t rows, uint32_t bc, uint32_t br,
                  CUtensorMapSwizzle sw = CU_TENSOR_MAP_SWIZZLE_128B) {
  cuuint64_t gd[2] = {cols, rows}, gs[1] = {cols * 2};
  cuuint32_t bx[2] = {bc, br}, es[2] = {1, 1};
  enc(m, CU_TENSOR_MAP_DATA_TYPE_BFLOAT16, 2, const_cast<void*>(ptr), gd, gs, bx, es, CU_TENSOR_MAP_INTERLEAVE_NONE, sw,
      CU_TENSOR_MAP_L2_PROMOTION_L2_256B, CU_TENSOR_MAP_FLOAT_OOB_FILL_NONE);
}
static void enc3d(EncFn enc, CUtensorMap* m, const void* ptr, uint64_t cols, uint64_t rows, uint32_t br, uint32_t bch) {
  cuuint64_t gd[3] = {64, rows, cols / 64}, gs[2] = {cols * 2, 128};
  cuuint32_t bx[3] = {64, br, bch}, es[3] = {1, 1, 1};
  enc(m, CU_TENSOR_MAP_DATA_TYPE_BFLOAT16, 3, const_cast<void*>(ptr), gd, gs, bx, es, CU_TENSOR_MAP_INTERLEAVE_NONE,
      CU_TENSOR_MAP_SWIZZLE_128B, CU_TENSOR_MAP_L2_PROMOTION_L2_256B, CU_TENSOR_MAP_FLOAT_OOB_FILL_NONE);
}

static void build_k1_jobs(Params& p) {
  int cnt[NCLUSTER];
  for (int c = 0; c < NCLUSTER; c++) {
    cnt[c] = 0;
    for (int i = 0; i < K1_MAXJOBS; i++) p.jobs[c][i] = 0;
  }
  auto add = [&](int c, int nch, int a_sel, int mp, int w_sel, int chunk0) {
    p.jobs[c][cnt[c]++] = (uint16_t)((nch - 1) | (a_sel << 2) | (mp << 3) | (w_sel << 6) | (chunk0 << 8));
  };
  for (int mp = 0; mp < 8; mp++) {
    for (int g = 0; g < 4; g++)
      for (int i = 0; i < 7; i++) add(g * 8 + mp, 4, 0, mp, g & 1, (2 + 2 * i + (g >> 1)) * 4);
    add(32 + mp, 3, 1, mp, 2, 24);
    add(32 + mp, 4, 1, mp, 3, 0 * 4);
    add(32 + mp, 4, 1, mp, 3, 1 * 4);
    for (int t = 0; t < 4; t++) add(32 + mp, 4, 0, mp, t & 1, (t >> 1) * 4);
    for (int g = 0; g < 2; g++) {
      for (int i = 0; i < 3; i++) add((5 + g) * 8 + mp, 4, 1, mp, 2, (g * 3 + i) * 4);
      for (int i = 0; i < 3; i++) add((5 + g) * 8 + mp, 4, 1, mp, 3, (2 + g * 3 + i) * 4);
    }
    for (int i = 0; i < 6; i++) add(56 + mp, 4, 1, mp, 3, (8 + i) * 4);
    add(64 + mp / 4, 4, 1, mp, 3, 14 * 4);
    if (mp & 1) add(64 + mp / 4, 4, 1, mp, 3, 15 * 4);
    else add(56 + mp, 4, 1, mp, 3, 15 * 4);
  }
  for (int cc = 0; cc < NCLUSTER; cc++)
    for (int i = 0; i < cnt[cc]; i++) {
      const int key = p.jobs[cc][i] & 0x3C;
      if (i == 0 || (p.jobs[cc][i - 1] & 0x3C) != key) p.jobs[cc][i] |= (1 << 14);
      if (i == cnt[cc] - 1 || (p.jobs[cc][i + 1] & 0x3C) != key) p.jobs[cc][i] |= (1 << 15);
    }
}

static void build_k2_items(Params& p) {
  static const int hp_order[16] = {8, 9, 10, 2, 5, 11, 3, 6, 12, 4, 7, 13, 14, 15, 0, 1};
  int n = 0;
  for (int i = 0; i < 64; i++) p.order[n++] = (uint8_t)((hp_order[i >> 2] * 2 + (i & 1)) * 8 + 7 - ((i >> 1) & 1));
  for (int j = 5; j >= 0; j--)
    for (int i = 0; i < 32; i++) p.order[n++] = (uint8_t)((hp_order[i >> 1] * 2 + (i & 1)) * 8 + j);
}

extern "C" void kernel_launch(void* const* d_in, const int* in_sizes, int n_in, void* d_out, int out_size) {
  const bf16* x = (const bf16*)d_in[0];
  const bf16* wqkv = (const bf16*)d_in[1];
  const bf16* wo = (const bf16*)d_in[2];
  const bf16* ckv = (const bf16*)d_in[4];
  const bf16* w_q = (const bf16*)d_in[5];
  const bf16* w_uk = (const bf16*)d_in[6];
  const bf16* w_uv = (const bf16*)d_in[7];
  const bf16* w_o = (const bf16*)d_in[8];
  const bf16* gate_w = (const bf16*)d_in[9];

  EncFn enc = nullptr;
  cudaDriverEntryPointQueryResult qr;
  cudaGetDriverEntryPoint("cuTensorMapEncodeTiled", (void**)&enc, cudaEnableDefault, &qr);
  void *pQ, *pK, *pV, *pCtx;
  cudaGetSymbolAddress(&pQ, g_Q);
  cudaGetSymbolAddress(&pK, g_K);
  cudaGetSymbolAddress(&pV, g_V);
  cudaGetSymbolAddress(&pCtx, g_ctx);

  static Params p;
  enc2d(enc, &p.tmA[0], ckv, DC, S_LEN, 64, 128);
  enc2d(enc, &p.tmA[1], x, DM, S_LEN, 64, 128);
  enc3d(enc, &p.tmW[0], w_uk, HDIM, DC, 16, 4);
  enc3d(enc, &p.tmW[1], w_uv, HDIM, DC, 16, 4);
  enc3d(enc, &p.tmW[2], wqkv, NQKVA, DM, 16, 4);
  enc3d(enc, &p.tmW[3], w_q, HDIM, DM, 16, 4);
  build_k1_jobs(p);
  enc2d(enc, &p.tmQ, pQ, HDIM, S_LEN, 64, 128);
  enc2d(enc, &p.tmK, pK, HDIM, S_LEN, 64, 128);
  enc2d(enc, &p.tmV, pV, HDIM, S_LEN, 64, 128);
  build_k2_items(p);
  enc2d(enc, &p.tmC, pCtx, KCAT, S_LEN, 64, 128);
  enc3d(enc, &p.tmO[0], w_o, DM, HDIM, 32, 4);
  enc3d(enc, &p.tmO[1], wo, DM, DM, 32, 4);
  enc2d(enc, &p.tmOt[0], w_o, DM, HDIM, 32, 32, CU_TENSOR_MAP_SWIZZLE_64B);
  enc2d(enc, &p.tmOt[1], wo, DM, DM, 32, 32, CU_TENSOR_MAP_SWIZZLE_64B);

  cudaFuncSetAttribute(fused_kernel, cudaFuncAttributeMaxDynamicSharedMemorySize, SMEM_BYTES);
  fused_kernel<<<NCLUSTER * 2, 384, SMEM_BYTES>>>(p, x, gate_w, (bf16*)d_out);
}
```

```cpp
#include <cuda_runtime.h>
#include <cuda_bf16.h>
#include <cuda.h>
#include <stdint.h>

typedef __nv_bfloat16 bf16;

constexpr int S_LEN = 2048, DM = 576, DC = 512, HDIM = 4096, NQKVA = 1728, KCAT = 4672;
constexpr int NCLUSTER = 66;

__device__ __align__(1024) bf16 g_Q[S_LEN * HDIM];
__device__ __align__(1024) bf16 g_K[S_LEN * HDIM];
__device__ __align__(1024) bf16 g_V[S_LEN * HDIM];
__device__ __align__(1024) bf16 g_QKVA[S_LEN * NQKVA + 64];
__device__ __align__(1024) bf16 g_ctx[S_LEN * KCAT];
__device__ float g_gate[S_LEN];
__device__ __align__(1024) float4 g_part[32 * 4 * 4 * 9 * 256];
__device__ __align__(16) unsigned int g_sync[128];
constexpr int F_QKVA = 0, F_HP = 16, F_CTX = 32, F_XCH = 64, F_GATE = 96, F_TICK = 97, F_DONE = 98;

__device__ __forceinline__ uint32_t smem_u32(const void* p) { return (uint32_t)__cvta_generic_to_shared(p); }
__device__ __forceinline__ void mbar_init(uint32_t a, uint32_t c) {
  asm volatile("mbarrier.init.shared::cta.b64 [%0], %1;" ::"r"(a), "r"(c));
}
__device__ __forceinline__ void mbar_expect(uint32_t a, uint32_t b) {
  asm volatile("mbarrier.arrive.expect_tx.shared::cta.b64 _, [%0], %1;" ::"r"(a), "r"(b) : "memory");
}
#define TS(k, i)
#define TSC(k, i)
#define TSM(k)
#define BSEG(i)
#define SPIN_LIMIT "4194304"
__device__ __forceinline__ void mbar_wait(uint32_t a, uint32_t parity) {
  asm volatile(
      "{\n.reg .pred p;\n.reg .u32 n;\n"
      "mbarrier.try_wait.parity.shared::cta.b64 p, [%0], %1;\n"
      "@p bra DONE;\n"
      "mov.u32 n, 0;\n"
      "LOOP:\n"
      "mbarrier.try_wait.parity.shared::cta.b64 p, [%0], %1;\n"
      "@p bra DONE;\n"
      "add.u32 n, n, 1;\n"
      "setp.lt.u32 p, n, " SPIN_LIMIT ";\n"
      "@p bra LOOP;\n"
      "DONE:\n}" ::"r"(a), "r"(parity) : "memory");
}
__device__ __forceinline__ void mbar_arrive(uint32_t a) {
  asm volatile("mbarrier.arrive.shared::cta.b64 _, [%0];" ::"r"(a) : "memory");
}
__device__ __forceinline__ void mbar_arrive_cluster(uint32_t a, uint32_t cta) {
  asm volatile("{\n.reg .b32 r;\nmapa.shared::cluster.u32 r, %0, %1;\nmbarrier.arrive.shared::cluster.b64 _, [r];\n}" ::"r"(a),
               "r"(cta) : "memory");
}
__device__ __forceinline__ void mbar_arrive_cluster_if(uint32_t a, uint32_t cta, bool pred) {
  asm volatile("{\n.reg .b32 r;\n.reg .pred p;\nsetp.ne.u32 p, %2, 0;\nmapa.shared::cluster.u32 r, %0, %1;\n@p mbarrier.arrive.shared::cluster.b64 _, [r];\n}" ::"r"(a),
               "r"(cta), "r"((uint32_t)pred) : "memory");
}
__device__ __forceinline__ void mbar_arrive_if(uint32_t a, bool pred) {
  asm volatile("{\n.reg .pred p;\nsetp.ne.u32 p, %1, 0;\n@p mbarrier.arrive.shared::cta.b64 _, [%0];\n}" ::"r"(a), "r"((uint32_t)pred) : "memory");
}
__device__ __forceinline__ void tma2d(uint32_t dst, const CUtensorMap* m, uint32_t bar, int c0, int c1) {
  asm volatile("cp.async.bulk.tensor.2d.shared::cluster.global.mbarrier::complete_tx::bytes [%0], [%1, {%3, %4}], [%2];" ::"r"(dst),
               "l"(m), "r"(bar), "r"(c0), "r"(c1) : "memory");
}
__device__ __forceinline__ void tma2d_mc(uint32_t dst, const CUtensorMap* m, uint32_t bar, int c0, int c1, uint16_t mask) {
  asm volatile(
      "cp.async.bulk.tensor.2d.shared::cluster.global.mbarrier::complete_tx::bytes.multicast::cluster [%0], [%1, {%3, %4}], [%2], %5;" ::"r"(dst),
      "l"(m), "r"(bar), "r"(c0), "r"(c1), "h"(mask) : "memory");
}
__device__ __forceinline__ void tma3d_mc(uint32_t dst, const CUtensorMap* m, uint32_t bar, int c0, int c1, int c2, uint16_t mask) {
  asm volatile(
      "cp.async.bulk.tensor.3d.shared::cluster.global.mbarrier::complete_tx::bytes.multicast::cluster [%0], [%1, {%3, %4, %5}], [%2], %6;" ::"r"(dst),
      "l"(m), "r"(bar), "r"(c0), "r"(c1), "r"(c2), "h"(mask) : "memory");
}
__device__ __forceinline__ void tma3d(uint32_t dst, const CUtensorMap* m, uint32_t bar, int c0, int c1, int c2) {
  asm volatile(
      "cp.async.bulk.tensor.3d.shared::cluster.global.mbarrier::complete_tx::bytes [%0], [%1, {%3, %4, %5}], [%2];" ::"r"(dst),
      "l"(m), "r"(bar), "r"(c0), "r"(c1), "r"(c2) : "memory");
}
__device__ __forceinline__ void tma_pf2d(const CUtensorMap* m, int c0, int c1) {
  asm volatile("cp.async.bulk.prefetch.tensor.2d.L2.global [%0, {%1, %2}];" ::"l"(m), "r"(c0), "r"(c1) : "memory");
}
__device__ __forceinline__ void tma_pf3d(const CUtensorMap* m, int c0, int c1, int c2) {
  asm volatile("cp.async.bulk.prefetch.tensor.3d.L2.global [%0, {%1, %2, %3}];" ::"l"(m), "r"(c0), "r"(c1), "r"(c2) : "memory");
}
__device__ __forceinline__ void prefetch_tmap(const CUtensorMap* m) {
  asm volatile("prefetch.tensormap [%0];" ::"l"(m) : "memory");
}
__device__ __forceinline__ void cluster_sync() {
  asm volatile("barrier.cluster.arrive.aligned;\nbarrier.cluster.wait.aligned;" ::: "memory");
}
__device__ __forceinline__ uint32_t cluster_rank() {
  uint32_t r;
  asm volatile("mov.u32 %0, %%cluster_ctarank;" : "=r"(r));
  return r;
}
__device__ __forceinline__ bool elect_one() {
  uint32_t p;
  asm volatile("{\n.reg .pred q;\nelect.sync _|q, 0xffffffff;\nselp.u32 %0, 1, 0, q;\n}" : "=r"(p));
  return p;
}
__device__ __forceinline__ void pdl_wait() { asm volatile("griddepcontrol.wait;" ::: "memory"); }
__device__ __forceinline__ void pdl_launch() { asm volatile("griddepcontrol.launch_dependents;" ::: "memory"); }
__device__ __forceinline__ void ldsm_x4(uint32_t& r0, uint32_t& r1, uint32_t& r2, uint32_t& r3, uint32_t addr) {
  asm volatile("ldmatrix.sync.aligned.m8n8.x4.shared.b16 {%0, %1, %2, %3}, [%4];" : "=r"(r0), "=r"(r1), "=r"(r2), "=r"(r3) : "r"(addr) : "memory");
}
__device__ __forceinline__ void wg_fence() { asm volatile("wgmma.fence.sync.aligned;" ::: "memory"); }
__device__ __forceinline__ void wg_commit() { asm volatile("wgmma.commit_group.sync.aligned;" ::: "memory"); }
template <int N>
__device__ __forceinline__ void wg_wait() { asm volatile("wgmma.wait_group.sync.aligned %0;" ::"n"(N) : "memory"); }
template <int N>
__device__ __forceinline__ void reg_alloc() { asm volatile("setmaxnreg.inc.sync.aligned.u32 %0;" ::"n"(N)); }
template <int N>
__device__ __forceinline__ void reg_dealloc() { asm volatile("setmaxnreg.dec.sync.aligned.u32 %0;" ::"n"(N)); }
__device__ __forceinline__ void bar_sync(int id, int n) { asm volatile("bar.sync %0, %1;" ::"r"(id), "r"(n) : "memory"); }
__device__ __forceinline__ void bar_arrive(int id, int n) { asm volatile("bar.arrive %0, %1;" ::"r"(id), "r"(n) : "memory"); }
template <int NT>
__device__ __forceinline__ void fence_regs(float (&d)[NT]) {
#pragma unroll
  for (int i = 0; i < NT; i++) asm volatile("" : "+f"(d[i])::"memory");
}
template <int NT>
__device__ __forceinline__ void fence_regs(uint32_t (&d)[NT]) {
#pragma unroll
  for (int i = 0; i < NT; i++) asm volatile("" : "+r"(d[i])::"memory");
}
__device__ __forceinline__ uint64_t make_desc(uint32_t saddr, uint32_t lbo, uint32_t sbo, uint32_t layout) {
  return (uint64_t)((saddr & 0x3FFFF) >> 4) | ((uint64_t)(lbo >> 4) << 16) | ((uint64_t)(sbo >> 4) << 32) | ((uint64_t)layout << 62);
}
__device__ __forceinline__ uint32_t pack_bf16(float lo, float hi) {
  uint32_t r;
  asm("cvt.rn.bf16x2.f32 %0, %1, %2;" : "=r"(r) : "f"(hi), "f"(lo));
  return r;
}
__device__ __forceinline__ float ex2(float x) {
  float r;
  asm("ex2.approx.ftz.f32 %0, %1;" : "=f"(r) : "f"(x));
  return r;
}
__device__ __forceinline__ void st_v4(void* p, uint32_t a, uint32_t b, uint32_t c, uint32_t d) {
#define ST_MOD ""
  asm volatile("st.global" ST_MOD ".v4.b32 [%0], {%1, %2, %3, %4};" ::"l"(p), "r"(a), "r"(b), "r"(c), "r"(d) : "memory");
}
__device__ __forceinline__ float bf_lo(uint32_t v) { return __uint_as_float(v << 16); }
__device__ __forceinline__ float bf_hi(uint32_t v) { return __uint_as_float(v & 0xFFFF0000u); }

__device__ __forceinline__ void quad_transpose(uint32_t& a0, uint32_t& a1, uint32_t& a2, uint32_t& a3, int q) {
  const bool o1 = q & 1, o2 = q & 2;
  uint32_t t0 = o1 ? a0 : a1, t1 = o1 ? a2 : a3;
  t0 = __shfl_xor_sync(0xffffffffu, t0, 1);
  t1 = __shfl_xor_sync(0xffffffffu, t1, 1);
  if (o1) { a0 = t0; a2 = t1; } else { a1 = t0; a3 = t1; }
  t0 = o2 ? a0 : a2;
  t1 = o2 ? a1 : a3;
  t0 = __shfl_xor_sync(0xffffffffu, t0, 2);
  t1 = __shfl_xor_sync(0xffffffffu, t1, 2);
  if (o2) { a0 = t0; a1 = t1; } else { a2 = t0; a3 = t1; }
}

template<int TB, int OFF, int NT>
__device__ __forceinline__ void wgmma_ss_n256(float (&d)[NT], uint64_t da, uint64_t db, int scale_d) {
  asm volatile("{\n.reg .pred p;\nsetp.ne.b32 p, %130, 0;\n"
    "wgmma.mma_async.sync.aligned.m64n256k16.f32.bf16.bf16 {%0, %1, %2, %3, %4, %5, %6, %7, %8, %9, %10, %11, %12, %13, %14, %15, %16, %17, %18, %19, %20, %21, %22, %23, %24, %25, %26, %27, %28, %29, %30, %31, %32, %33, %34, %35, %36, %37, %38, %39, %40, %41, %42, %43, %44, %45, %46, %47, %48, %49, %50, %51, %52, %53, %54, %55, %56, %57, %58, %59, %60, %61, %62, %63, %64, %65, %66, %67, %68, %69, %70, %71, %72, %73, %74, %75, %76, %77, %78, %79, %80, %81, %82, %83, %84, %85, %86, %87, %88, %89, %90, %91, %92, %93, %94, %95, %96, %97, %98, %99, %100, %101, %102, %103, %104, %105, %106, %107, %108, %109, %110, %111, %112, %113, %114, %115, %116, %117, %118, %119, %120, %121, %122, %123, %124, %125, %126, %127}, %128, %129, p, 1, 1, 0, %131;\n}\n"
    : "+f"(d[OFF+0]), "+f"(d[OFF+1]), "+f"(d[OFF+2]), "+f"(d[OFF+3]), "+f"(d[OFF+4]), "+f"(d[OFF+5]), "+f"(d[OFF+6]), "+f"(d[OFF+7]), "+f"(d[OFF+8]), "+f"(d[OFF+9]), "+f"(d[OFF+10]), "+f"(d[OFF+11]), "+f"(d[OFF+12]), "+f"(d[OFF+13]), "+f"(d[OFF+14]), "+f"(d[OFF+15]), "+f"(d[OFF+16]), "+f"(d[OFF+17]), "+f"(d[OFF+18]), "+f"(d[OFF+19]), "+f"(d[OFF+20]), "+f"(d[OFF+21]), "+f"(d[OFF+22]), "+f"(d[OFF+23]), "+f"(d[OFF+24]), "+f"(d[OFF+25]), "+f"(d[OFF+26]), "+f"(d[OFF+27]), "+f"(d[OFF+28]), "+f"(d[OFF+29]), "+f"(d[OFF+30]), "+f"(d[OFF+31]), "+f"(d[OFF+32]), "+f"(d[OFF+33]), "+f"(d[OFF+34]), "+f"(d[OFF+35]), "+f"(d[OFF+36]), "+f"(d[OFF+37]), "+f"(d[OFF+38]), "+f"(d[OFF+39]), "+f"(d[OFF+40]), "+f"(d[OFF+41]), "+f"(d[OFF+42]), "+f"(d[OFF+43]), "+f"(d[OFF+44]), "+f"(d[OFF+45]), "+f"(d[OFF+46]), "+f"(d[OFF+47]), "+f"(d[OFF+48]), "+f"(d[OFF+49]), "+f"(d[OFF+50]), "+f"(d[OFF+51]), "+f"(d[OFF+52]), "+f"(d[OFF+53]), "+f"(d[OFF+54]), "+f"(d[OFF+55]), "+f"(d[OFF+56]), "+f"(d[OFF+57]), "+f"(d[OFF+58]), "+f"(d[OFF+59]), "+f"(d[OFF+60]), "+f"(d[OFF+61]), "+f"(d[OFF+62]), "+f"(d[OFF+63]), "+f"(d[OFF+64]), "+f"(d[OFF+65]), "+f"(d[OFF+66]), "+f"(d[OFF+67]), "+f"(d[OFF+68]), "+f"(d[OFF+69]), "+f"(d[OFF+70]), "+f"(d[OFF+71]), "+f"(d[OFF+72]), "+f"(d[OFF+73]), "+f"(d[OFF+74]), "+f"(d[OFF+75]), "+f"(d[OFF+76]), "+f"(d[OFF+77]), "+f"(d[OFF+78]), "+f"(d[OFF+79]), "+f"(d[OFF+80]), "+f"(d[OFF+81]), "+f"(d[OFF+82]), "+f"(d[OFF+83]), "+f"(d[OFF+84]), "+f"(d[OFF+85]), "+f"(d[OFF+86]), "+f"(d[OFF+87]), "+f"(d[OFF+88]), "+f"(d[OFF+89]), "+f"(d[OFF+90]), "+f"(d[OFF+91]), "+f"(d[OFF+92]), "+f"(d[OFF+93]), "+f"(d[OFF+94]), "+f"(d[OFF+95]), "+f"(d[OFF+96]), "+f"(d[OFF+97]), "+f"(d[OFF+98]), "+f"(d[OFF+99]), "+f"(d[OFF+100]), "+f"(d[OFF+101]), "+f"(d[OFF+102]), "+f"(d[OFF+103]), "+f"(d[OFF+104]), "+f"(d[OFF+105]), "+f"(d[OFF+106]), "+f"(d[OFF+107]), "+f"(d[OFF+108]), "+f"(d[OFF+109]), "+f"(d[OFF+110]), "+f"(d[OFF+111]), "+f"(d[OFF+112]), "+f"(d[OFF+113]), "+f"(d[OFF+114]), "+f"(d[OFF+115]), "+f"(d[OFF+116]), "+f"(d[OFF+117]), "+f"(d[OFF+118]), "+f"(d[OFF+119]), "+f"(d[OFF+120]), "+f"(d[OFF+121]), "+f"(d[OFF+122]), "+f"(d[OFF+123]), "+f"(d[OFF+124]), "+f"(d[OFF+125]), "+f"(d[OFF+126]), "+f"(d[OFF+127])
    : "l"(da), "l"(db), "r"(scale_d), "n"(TB));
}
template<int TB, int OFF, int NT>
__device__ __forceinline__ void wgmma_ss_n192(float (&d)[NT], uint64_t da, uint64_t db, int scale_d) {
  asm volatile("{\n.reg .pred p;\nsetp.ne.b32 p, %98, 0;\n"
    "wgmma.mma_async.sync.aligned.m64n192k16.f32.bf16.bf16 {%0, %1, %2, %3, %4, %5, %6, %7, %8, %9, %10, %11, %12, %13, %14, %15, %16, %17, %18, %19, %20, %21, %22, %23, %24, %25, %26, %27, %28, %29, %30, %31, %32, %33, %34, %35, %36, %37, %38, %39, %40, %41, %42, %43, %44, %45, %46, %47, %48, %49, %50, %51, %52, %53, %54, %55, %56, %57, %58, %59, %60, %61, %62, %63, %64, %65, %66, %67, %68, %69, %70, %71, %72, %73, %74, %75, %76, %77, %78, %79, %80, %81, %82, %83, %84, %85, %86, %87, %88, %89, %90, %91, %92, %93, %94, %95}, %96, %97, p, 1, 1, 0, %99;\n}\n"
    : "+f"(d[OFF+0]), "+f"(d[OFF+1]), "+f"(d[OFF+2]), "+f"(d[OFF+3]), "+f"(d[OFF+4]), "+f"(d[OFF+5]), "+f"(d[OFF+6]), "+f"(d[OFF+7]), "+f"(d[OFF+8]), "+f"(d[OFF+9]), "+f"(d[OFF+10]), "+f"(d[OFF+11]), "+f"(d[OFF+12]), "+f"(d[OFF+13]), "+f"(d[OFF+14]), "+f"(d[OFF+15]), "+f"(d[OFF+16]), "+f"(d[OFF+17]), "+f"(d[OFF+18]), "+f"(d[OFF+19]), "+f"(d[OFF+20]), "+f"(d[OFF+21]), "+f"(d[OFF+22]), "+f"(d[OFF+23]), "+f"(d[OFF+24]), "+f"(d[OFF+25]), "+f"(d[OFF+26]), "+f"(d[OFF+27]), "+f"(d[OFF+28]), "+f"(d[OFF+29]), "+f"(d[OFF+30]), "+f"(d[OFF+31]), "+f"(d[OFF+32]), "+f"(d[OFF+33]), "+f"(d[OFF+34]), "+f"(d[OFF+35]), "+f"(d[OFF+36]), "+f"(d[OFF+37]), "+f"(d[OFF+38]), "+f"(d[OFF+39]), "+f"(d[OFF+40]), "+f"(d[OFF+41]), "+f"(d[OFF+42]), "+f"(d[OFF+43]), "+f"(d[OFF+44]), "+f"(d[OFF+45]), "+f"(d[OFF+46]), "+f"(d[OFF+47]), "+f"(d[OFF+48]), "+f"(d[OFF+49]), "+f"(d[OFF+50]), "+f"(d[OFF+51]), "+f"(d[OFF+52]), "+f"(d[OFF+53]), "+f"(d[OFF+54]), "+f"(d[OFF+55]), "+f"(d[OFF+56]), "+f"(d[OFF+57]), "+f"(d[OFF+58]), "+f"(d[OFF+59]), "+f"(d[OFF+60]), "+f"(d[OFF+61]), "+f"(d[OFF+62]), "+f"(d[OFF+63]), "+f"(d[OFF+64]), "+f"(d[OFF+65]), "+f"(d[OFF+66]), "+f"(d[OFF+67]), "+f"(d[OFF+68]), "+f"(d[OFF+69]), "+f"(d[OFF+70]), "+f"(d[OFF+71]), "+f"(d[OFF+72]), "+f"(d[OFF+73]), "+f"(d[OFF+74]), "+f"(d[OFF+75]), "+f"(d[OFF+76]), "+f"(d[OFF+77]), "+f"(d[OFF+78]), "+f"(d[OFF+79]), "+f"(d[OFF+80]), "+f"(d[OFF+81]), "+f"(d[OFF+82]), "+f"(d[OFF+83]), "+f"(d[OFF+84]), "+f"(d[OFF+85]), "+f"(d[OFF+86]), "+f"(d[OFF+87]), "+f"(d[OFF+88]), "+f"(d[OFF+89]), "+f"(d[OFF+90]), "+f"(d[OFF+91]), "+f"(d[OFF+92]), "+f"(d[OFF+93]), "+f"(d[OFF+94]), "+f"(d[OFF+95])
    : "l"(da), "l"(db), "r"(scale_d), "n"(TB));
}
template<int TB, int OFF, int NT>
__device__ __forceinline__ void wgmma_ss_n128(float (&d)[NT], uint64_t da, uint64_t db, int scale_d) {
  asm volatile("{\n.reg .pred p;\nsetp.ne.b32 p, %66, 0;\n"
    "wgmma.mma_async.sync.aligned.m64n128k16.f32.bf16.bf16 {%0, %1, %2, %3, %4, %5, %6, %7, %8, %9, %10, %11, %12, %13, %14, %15, %16, %17, %18, %19, %20, %21, %22, %23, %24, %25, %26, %27, %28, %29, %30, %31, %32, %33, %34, %35, %36, %37, %38, %39, %40, %41, %42, %43, %44, %45, %46, %47, %48, %49, %50, %51, %52, %53, %54, %55, %56, %57, %58, %59, %60, %61, %62, %63}, %64, %65, p, 1, 1, 0, %67;\n}\n"
    : "+f"(d[OFF+0]), "+f"(d[OFF+1]), "+f"(d[OFF+2]), "+f"(d[OFF+3]), "+f"(d[OFF+4]), "+f"(d[OFF+5]), "+f"(d[OFF+6]), "+f"(d[OFF+7]), "+f"(d[OFF+8]), "+f"(d[OFF+9]), "+f"(d[OFF+10]), "+f"(d[OFF+11]), "+f"(d[OFF+12]), "+f"(d[OFF+13]), "+f"(d[OFF+14]), "+f"(d[OFF+15]), "+f"(d[OFF+16]), "+f"(d[OFF+17]), "+f"(d[OFF+18]), "+f"(d[OFF+19]), "+f"(d[OFF+20]), "+f"(d[OFF+21]), "+f"(d[OFF+22]), "+f"(d[OFF+23]), "+f"(d[OFF+24]), "+f"(d[OFF+25]), "+f"(d[OFF+26]), "+f"(d[OFF+27]), "+f"(d[OFF+28]), "+f"(d[OFF+29]), "+f"(d[OFF+30]), "+f"(d[OFF+31]), "+f"(d[OFF+32]), "+f"(d[OFF+33]), "+f"(d[OFF+34]), "+f"(d[OFF+35]), "+f"(d[OFF+36]), "+f"(d[OFF+37]), "+f"(d[OFF+38]), "+f"(d[OFF+39]), "+f"(d[OFF+40]), "+f"(d[OFF+41]), "+f"(d[OFF+42]), "+f"(d[OFF+43]), "+f"(d[OFF+44]), "+f"(d[OFF+45]), "+f"(d[OFF+46]), "+f"(d[OFF+47]), "+f"(d[OFF+48]), "+f"(d[OFF+49]), "+f"(d[OFF+50]), "+f"(d[OFF+51]), "+f"(d[OFF+52]), "+f"(d[OFF+53]), "+f"(d[OFF+54]), "+f"(d[OFF+55]), "+f"(d[OFF+56]), "+f"(d[OFF+57]), "+f"(d[OFF+58]), "+f"(d[OFF+59]), "+f"(d[OFF+60]), "+f"(d[OFF+61]), "+f"(d[OFF+62]), "+f"(d[OFF+63])
    : "l"(da), "l"(db), "r"(scale_d), "n"(TB));
}
template<int TB, int OFF, int NT>
__device__ __forceinline__ void wgmma_ss_n32(float (&d)[NT], uint64_t da, uint64_t db, int scale_d) {
  asm volatile("{\n.reg .pred p;\nsetp.ne.b32 p, %18, 0;\n"
    "wgmma.mma_async.sync.aligned.m64n32k16.f32.bf16.bf16 {%0, %1, %2, %3, %4, %5, %6, %7, %8, %9, %10, %11, %12, %13, %14, %15}, %16, %17, p, 1, 1, 0, %19;\n}\n"
    : "+f"(d[OFF+0]), "+f"(d[OFF+1]), "+f"(d[OFF+2]), "+f"(d[OFF+3]), "+f"(d[OFF+4]), "+f"(d[OFF+5]), "+f"(d[OFF+6]), "+f"(d[OFF+7]), "+f"(d[OFF+8]), "+f"(d[OFF+9]), "+f"(d[OFF+10]), "+f"(d[OFF+11]), "+f"(d[OFF+12]), "+f"(d[OFF+13]), "+f"(d[OFF+14]), "+f"(d[OFF+15])
    : "l"(da), "l"(db), "r"(scale_d), "n"(TB));
}
template<int TB, int OFF, int NT>
__device__ __forceinline__ void wgmma_rs_n128(float (&d)[NT], uint32_t a0, uint32_t a1, uint32_t a2, uint32_t a3, uint64_t db, int scale_d) {
  asm volatile("{\n.reg .pred p;\nsetp.ne.b32 p, %69, 0;\n"
    "wgmma.mma_async.sync.aligned.m64n128k16.f32.bf16.bf16 {%0, %1, %2, %3, %4, %5, %6, %7, %8, %9, %10, %11, %12, %13, %14, %15, %16, %17, %18, %19, %20, %21, %22, %23, %24, %25, %26, %27, %28, %29, %30, %31, %32, %33, %34, %35, %36, %37, %38, %39, %40, %41, %42, %43, %44, %45, %46, %47, %48, %49, %50, %51, %52, %53, %54, %55, %56, %57, %58, %59, %60, %61, %62, %63}, {%64, %65, %66, %67}, %68, p, 1, 1, %70;\n}\n"
    : "+f"(d[OFF+0]), "+f"(d[OFF+1]), "+f"(d[OFF+2]), "+f"(d[OFF+3]), "+f"(d[OFF+4]), "+f"(d[OFF+5]), "+f"(d[OFF+6]), "+f"(d[OFF+7]), "+f"(d[OFF+8]), "+f"(d[OFF+9]), "+f"(d[OFF+10]), "+f"(d[OFF+11]), "+f"(d[OFF+12]), "+f"(d[OFF+13]), "+f"(d[OFF+14]), "+f"(d[OFF+15]), "+f"(d[OFF+16]), "+f"(d[OFF+17]), "+f"(d[OFF+18]), "+f"(d[OFF+19]), "+f"(d[OFF+20]), "+f"(d[OFF+21]), "+f"(d[OFF+22]), "+f"(d[OFF+23]), "+f"(d[OFF+24]), "+f"(d[OFF+25]), "+f"(d[OFF+26]), "+f"(d[OFF+27]), "+f"(d[OFF+28]), "+f"(d[OFF+29]), "+f"(d[OFF+30]), "+f"(d[OFF+31]), "+f"(d[OFF+32]), "+f"(d[OFF+33]), "+f"(d[OFF+34]), "+f"(d[OFF+35]), "+f"(d[OFF+36]), "+f"(d[OFF+37]), "+f"(d[OFF+38]), "+f"(d[OFF+39]), "+f"(d[OFF+40]), "+f"(d[OFF+41]), "+f"(d[OFF+42]), "+f"(d[OFF+43]), "+f"(d[OFF+44]), "+f"(d[OFF+45]), "+f"(d[OFF+46]), "+f"(d[OFF+47]), "+f"(d[OFF+48]), "+f"(d[OFF+49]), "+f"(d[OFF+50]), "+f"(d[OFF+51]), "+f"(d[OFF+52]), "+f"(d[OFF+53]), "+f"(d[OFF+54]), "+f"(d[OFF+55]), "+f"(d[OFF+56]), "+f"(d[OFF+57]), "+f"(d[OFF+58]), "+f"(d[OFF+59]), "+f"(d[OFF+60]), "+f"(d[OFF+61]), "+f"(d[OFF+62]), "+f"(d[OFF+63])
    : "r"(a0), "r"(a1), "r"(a2), "r"(a3), "l"(db), "r"(scale_d), "n"(TB));
}
template<int TB, int OFF, int NT>
__device__ __forceinline__ void wgmma_rs_n64(float (&d)[NT], uint32_t a0, uint32_t a1, uint32_t a2, uint32_t a3, uint64_t db, int scale_d) {
  asm volatile("{\n.reg .pred p;\nsetp.ne.b32 p, %37, 0;\n"
    "wgmma.mma_async.sync.aligned.m64n64k16.f32.bf16.bf16 {%0, %1, %2, %3, %4, %5, %6, %7, %8, %9, %10, %11, %12, %13, %14, %15, %16, %17, %18, %19, %20, %21, %22, %23, %24, %25, %26, %27, %28, %29, %30, %31}, {%32, %33, %34, %35}, %36, p, 1, 1, %38;\n}\n"
    : "+f"(d[OFF+0]), "+f"(d[OFF+1]), "+f"(d[OFF+2]), "+f"(d[OFF+3]), "+f"(d[OFF+4]), "+f"(d[OFF+5]), "+f"(d[OFF+6]), "+f"(d[OFF+7]), "+f"(d[OFF+8]), "+f"(d[OFF+9]), "+f"(d[OFF+10]), "+f"(d[OFF+11]), "+f"(d[OFF+12]), "+f"(d[OFF+13]), "+f"(d[OFF+14]), "+f"(d[OFF+15]), "+f"(d[OFF+16]), "+f"(d[OFF+17]), "+f"(d[OFF+18]), "+f"(d[OFF+19]), "+f"(d[OFF+20]), "+f"(d[OFF+21]), "+f"(d[OFF+22]), "+f"(d[OFF+23]), "+f"(d[OFF+24]), "+f"(d[OFF+25]), "+f"(d[OFF+26]), "+f"(d[OFF+27]), "+f"(d[OFF+28]), "+f"(d[OFF+29]), "+f"(d[OFF+30]), "+f"(d[OFF+31])
    : "r"(a0), "r"(a1), "r"(a2), "r"(a3), "l"(db), "r"(scale_d), "n"(TB));
}

__device__ __forceinline__ void wait_flag(const unsigned int* f, uint32_t target) {
  uint32_t v;
#pragma unroll 1
  for (uint32_t spins = 0; spins < (1u << 22); spins++) {
    asm volatile("ld.acquire.gpu.global.u32 %0, [%1];" : "=r"(v) : "l"(f) : "memory");
    if (v >= target) break;
    __nanosleep(100);
  }
}
__device__ __forceinline__ uint32_t lds32(uint32_t a) {
  uint32_t v;
  asm volatile("ld.shared.u32 %0, [%1];" : "=r"(v) : "r"(a) : "memory");
  return v;
}
__device__ __forceinline__ float gate_row(int row, int lane, const bf16* __restrict__ x, const bf16* __restrict__ gate_w) {
  const uint32_t* xr = reinterpret_cast<const uint32_t*>(x + (size_t)row * DM);
  const uint32_t* gw2 = reinterpret_cast<const uint32_t*>(gate_w);
  float gs = 0.f;
#pragma unroll
  for (int i = 0; i < 9; i++) {
    const uint32_t a = __ldg(xr + lane + 32 * i), b = __ldg(gw2 + lane + 32 * i);
    gs = fmaf(bf_lo(a), bf_lo(b), gs);
    gs = fmaf(bf_hi(a), bf_hi(b), gs);
  }
#pragma unroll
  for (int o = 16; o; o >>= 1) gs += __shfl_xor_sync(0xffffffffu, gs, o);
  const float g = 1.f / (1.f + __expf(-gs));
  if (lane == 0) g_gate[row] = g;
  return g;
}
#define LA_UNROLL 1
__device__ __forceinline__ void local_rows2(int rb, int ri, uint32_t sL, uint32_t bL2, int lane, float ga, float gb) {
  const float scale_l2 = 0.23570226039551584f * 1.4426950408889634f;
  constexpr int U = LA_UNROLL;
  const uint32_t sq = sL + (30 + ri) * 1152;
  const uint32_t kb = sL + (14 + ri) * 1152 + lane * 36;
  float ma = -INFINITY, mb = -INFINITY;
  {
    float qa[18], qb[18];
#pragma unroll
    for (int i = 0; i < 9; i++) {
      const uint32_t u = lds32(sq - 2304 + lane * 36 + 4 * i), v = lds32(sq + lane * 36 + 4 * i);
      qa[2 * i] = bf_lo(u); qa[2 * i + 1] = bf_hi(u);
      qb[2 * i] = bf_lo(v); qb[2 * i + 1] = bf_hi(v);
    }
    __syncwarp();
#pragma unroll U
    for (int t = 0; t < 9; t++) {
      const bool ok = rb - 2 * t >= 0;
      float a0 = 0.f, a1 = 0.f, b0 = 0.f, b1 = 0.f;
#pragma unroll
      for (int i = 0; i < 9; i++) {
        const uint32_t k = lds32(kb - t * 2304 + 4 * i);
        const float lo = bf_lo(k), hi = bf_hi(k);
        a0 = fmaf(qa[2 * i], lo, a0); a1 = fmaf(qa[2 * i + 1], hi, a1);
        b0 = fmaf(qb[2 * i], lo, b0); b1 = fmaf(qb[2 * i + 1], hi, b1);
      }
      a0 = (ok && t > 0) ? a0 + a1 : -INFINITY;
      b0 = (ok && t < 8) ? b0 + b1 : -INFINITY;
      ma = fmaxf(ma, a0);
      mb = fmaxf(mb, b0);
      asm volatile("st.shared.f32 [%0], %1;" ::"r"(sq - 2304 + t * 128 + lane * 4), "f"(a0) : "memory");
      asm volatile("st.shared.f32 [%0], %1;" ::"r"(sq + t * 128 + lane * 4), "f"(b0) : "memory");
    }
  }
  float oa[18], ob[18], sa = 0.f, sb = 0.f;
#pragma unroll
  for (int i = 0; i < 18; i++) { oa[i] = 0.f; ob[i] = 0.f; }
  mbar_wait(bL2, 0);
#pragma unroll U
  for (int t = 0; t < 9; t++) {
    const float wa = ex2((__uint_as_float(lds32(sq - 2304 + t * 128 + lane * 4)) - ma) * scale_l2);
    const float wb = ex2((__uint_as_float(lds32(sq + t * 128 + lane * 4)) - mb) * scale_l2);
    sa += wa;
    sb += wb;
#pragma unroll
    for (int i = 0; i < 9; i++) {
      const uint32_t v = lds32(kb + 46 * 1152 - t * 2304 + 4 * i);
      const float lo = bf_lo(v), hi = bf_hi(v);
      oa[2 * i] = fmaf(wa, lo, oa[2 * i]); oa[2 * i + 1] = fmaf(wa, hi, oa[2 * i + 1]);
      ob[2 * i] = fmaf(wb, lo, ob[2 * i]); ob[2 * i + 1] = fmaf(wb, hi, ob[2 * i + 1]);
    }
  }
  ga = __fdividef(ga, sa);
  gb = __fdividef(gb, sb);
  __syncwarp();
#pragma unroll
  for (int i = 0; i < 9; i++) {
    asm volatile("st.shared.u32 [%0], %1;" ::"r"(sq - 2304 + lane * 36 + 4 * i), "r"(pack_bf16(oa[2 * i] * ga, oa[2 * i + 1] * ga)) : "memory");
    asm volatile("st.shared.u32 [%0], %1;" ::"r"(sq + lane * 36 + 4 * i), "r"(pack_bf16(ob[2 * i] * gb, ob[2 * i + 1] * gb)) : "memory");
  }
  __syncwarp();
  uint32_t w[5][4];
#pragma unroll
  for (int t = 0; t < 5; t++) {
    const int c = min(t * 32 + lane, 143), r = c >= 72;
    asm volatile("ld.shared.v4.u32 {%0, %1, %2, %3}, [%4];" : "=r"(w[t][0]), "=r"(w[t][1]), "=r"(w[t][2]), "=r"(w[t][3])
                 : "r"(sq - 2304 + r * 2304 + (c - r * 72) * 16) : "memory");
  }
  asm volatile("fence.proxy.async.shared::cta;" ::: "memory");
  bar_arrive(4, 256 + 32);
#pragma unroll
  for (int t = 0; t < 5; t++) {
    const int c = min(t * 32 + lane, 143), r = c >= 72;
    st_v4(g_ctx + (size_t)(rb - 2 + 2 * r) * KCAT + HDIM + (c - r * 72) * 8, w[t][0], w[t][1], w[t][2], w[t][3]);
  }
}

#define K1_NST 6
constexpr int K1_BST = K1_NST;
constexpr int K1_MAXJOBS = 10;
constexpr uint32_t K1_FLAG_TARGET = 7;
constexpr uint32_t RDY_TARGET = 48;
constexpr uint32_t GATE_TARGET = 128 * 3;
struct alignas(64) Params {
  CUtensorMap tmA[2];
  CUtensorMap tmW[4];
  CUtensorMap tmQ, tmK, tmV;
  CUtensorMap tmL[2];
  CUtensorMap tmC, tmO[2], tmOt[2];
  uint16_t jobs[NCLUSTER][K1_MAXJOBS];
  uint8_t order[256];
};

struct K1State {
  uint32_t bs, bph, aph;
  bf16* pp;
  int pld8;
  int png;
};
__device__ __forceinline__ void k1_flag(const K1State& st, int lane, uint32_t bS) {
  if (st.png) {
    __syncwarp();
    if (lane == 0) mbar_arrive(bS);
  }
}

__device__ __forceinline__ void k1_tile(float (&acc)[128], uint32_t (&pk)[64], K1State& st, uint32_t job, uint32_t sA, uint32_t sB,
                                        uint32_t bAf, uint32_t bAe, uint32_t bBf, uint32_t bBe, uint32_t bS, int wg, int warp, int lane, uint32_t rank) {
  const int a_sel = (job >> 2) & 1, mpair = (job >> 3) & 7, w_sel = (job >> 6) & 3, chunk0 = (job >> 8) & 63;
  const bool newA = (job >> 14) & 1, lastA = (job >> 15) & 1;
  const bool sig = (lane == 0) && (warp < 2);
  const bool siga = lastA && (lane == 0) && (warp == 2);
  const int KC = 8 + a_sel;
  uint32_t prev_bs = 0, prev2_bs = 0, a8_bs = 0;
#pragma unroll
  for (int kc = 0; kc < 9; kc++) {
    if (kc >= KC) break;
    uint32_t abase = sA + ((kc + 2) & 7) * 16384;
    if (kc == 8) {
      mbar_wait(bBf + st.bs * 8, st.bph);
      a8_bs = st.bs;
      abase = sB + st.bs * 16384;
      if (++st.bs == K1_BST) { st.bs = 0; st.bph ^= 1; }
    } else if (newA) {
      mbar_wait(bAf + kc * 8, st.aph);
    }
    const uint64_t da = make_desc(abase + wg * 8192, 16, 1024, 1);
#pragma unroll
    for (int ks = 0; ks < 2; ks++) {
      mbar_wait(bBf + st.bs * 8, st.bph);
      const uint64_t db = make_desc(sB + st.bs * 16384, 2048, 1024, 1);
      wg_fence();
      wgmma_ss_n256<1, 0>(acc, da + (uint64_t)(ks * 4), db, (ks > 0) ? 1 : (kc > 0));
      wgmma_ss_n256<1, 0>(acc, da + (uint64_t)(ks * 4 + 2), db + (uint64_t)512, 1);
      wg_commit();
      const int PO = (kc < 8 ? kc : 0) * 8;
      wg_wait<1>();
      if (ks > 0 || kc > 0) {
        if (sig) mbar_arrive_cluster(bBe + prev_bs * 8, warp);
        if (ks == 0 && siga) mbar_arrive(bAe + (kc - 1) * 8);
      }
      if (kc < st.png) st_v4(st.pp + kc * 32 + ks * st.pld8, pk[PO + ks * 4], pk[PO + ks * 4 + 1], pk[PO + ks * 4 + 2], pk[PO + ks * 4 + 3]);
      prev_bs = st.bs;
      if (++st.bs == K1_BST) { st.bs = 0; st.bph ^= 1; }
    }
  }
  if (newA) st.aph ^= 1;
  k1_flag(st, lane, bS);
  wg_wait<0>();
  fence_regs(acc);
  if (sig) {
    mbar_arrive_cluster(bBe + prev_bs * 8, warp);
    if (a_sel) mbar_arrive_cluster(bBe + a8_bs * 8, warp);
  }
  if (siga && !a_sel) mbar_arrive(bAe + 7 * 8);
  const bool isA = (w_sel == 2);
  bf16* out = (w_sel == 0) ? g_K : (w_sel == 1) ? g_V : isA ? g_QKVA : g_Q;
  const int ld = isA ? NQKVA : HDIM;
  const int row = mpair * 256 + rank * 128 + wg * 64 + warp * 16 + (lane >> 2);
  st.pp = out + (size_t)row * ld + chunk0 * 64 + (lane & 3) * 8;
  st.pld8 = 8 * ld;
  st.png = ((job & 3) + 1) * 2;
#pragma unroll
  for (int G = 0; G < 8; G++) {
    pk[G * 8 + 0] = pack_bf16(acc[G * 16 + 0], acc[G * 16 + 1]);
    pk[G * 8 + 1] = pack_bf16(acc[G * 16 + 4], acc[G * 16 + 5]);
    pk[G * 8 + 2] = pack_bf16(acc[G * 16 + 8], acc[G * 16 + 9]);
    pk[G * 8 + 3] = pack_bf16(acc[G * 16 + 12], acc[G * 16 + 13]);
    pk[G * 8 + 4] = pack_bf16(acc[G * 16 + 2], acc[G * 16 + 3]);
    pk[G * 8 + 5] = pack_bf16(acc[G * 16 + 6], acc[G * 16 + 7]);
    pk[G * 8 + 6] = pack_bf16(acc[G * 16 + 10], acc[G * 16 + 11]);
    pk[G * 8 + 7] = pack_bf16(acc[G * 16 + 14], acc[G * 16 + 15]);
  }
  if (isA) {
#pragma unroll
    for (int G = 0; G < 16; G++) quad_transpose(pk[G * 4 + 0], pk[G * 4 + 1], pk[G * 4 + 2], pk[G * 4 + 3], lane & 3);
  }
}

constexpr int K2_NST = 7;
constexpr uint32_t K2_END = 0x100;
constexpr int K3_NST = 4;
constexpr int K3_STAGE = 16384 + 32768 + 4096;
constexpr int SMEM_DATA = 7 * 32768;
constexpr int SMEM_BYTES = SMEM_DATA + 1024 + 768;

struct Cursor {
  uint32_t s, ph;
  __device__ __forceinline__ void next() {
    if (++s == K2_NST) { s = 0; ph ^= 1; }
  }
};

#define TURN_SYNC() bar_sync(mybar, 256)
#define TURN_ARRIVE() bar_arrive(otherbar, 256)
#define RELEASE_IF(cur, cond) mbar_arrive_cluster_if(bE + (cur).s * 8, warp & 1, sig && (cond))
#define RELEASE(cur) RELEASE_IF(cur, true)
#define ISSUE_PV(cur, first)                                                                                   \
  do {                                                                                                         \
    const uint64_t dv = make_desc(sbase + (cur).s * 32768, 16384, 1024, 1);                                    \
    _Pragma("unroll") for (int t = 0; t < 8; t++)                                                              \
        wgmma_rs_n128<1, 0>(O, P[4 * t], P[4 * t + 1], P[4 * t + 2], P[4 * t + 3], dv + (uint64_t)(t * 128), (t > 0) ? 1 : !(first)); \
  } while (0)
#define ISSUE_QK(cur)                                                                                          \
  do {                                                                                                         \
    const uint64_t dk = make_desc(sbase + (cur).s * 32768, 16, 1024, 1);                                       \
    _Pragma("unroll") for (int t = 0; t < 8; t++)                                                              \
        wgmma_rs_n128<0, 0>(S, Q[4 * t], Q[4 * t + 1], Q[4 * t + 2], Q[4 * t + 3], dk + (uint64_t)((t >> 2) * 1024 + (t & 3) * 2), t > 0); \
  } while (0)
#define EPILOGUE()                                                                                             \
  do {                                                                                                         \
    l0 += __shfl_xor_sync(0xffffffffu, l0, 1);                                                                 \
    l0 += __shfl_xor_sync(0xffffffffu, l0, 2);                                                                 \
    l1 += __shfl_xor_sync(0xffffffffu, l1, 1);                                                                 \
    l1 += __shfl_xor_sync(0xffffffffu, l1, 2);                                                                 \
    const float f0 = __fdividef(gf0, l0), f1 = __fdividef(gf1, l1);                                                                \
    bf16* o0 = g_ctx + (size_t)prev_row * KCAT + prev_h * 128 + q * 8;                                         \
    bf16* o1 = o0 + (size_t)8 * KCAT;                                                                          \
    _Pragma("unroll") for (int G = 0; G < 4; G++) {                                                            \
      st_v4(o0 + G * 32, pack_bf16(O[G * 16 + 0] * f0, O[G * 16 + 1] * f0), pack_bf16(O[G * 16 + 4] * f0, O[G * 16 + 5] * f0), \
            pack_bf16(O[G * 16 + 8] * f0, O[G * 16 + 9] * f0), pack_bf16(O[G * 16 + 12] * f0, O[G * 16 + 13] * f0)); \
      st_v4(o1 + G * 32, pack_bf16(O[G * 16 + 2] * f1, O[G * 16 + 3] * f1), pack_bf16(O[G * 16 + 6] * f1, O[G * 16 + 7] * f1), \
            pack_bf16(O[G * 16 + 10] * f1, O[G * 16 + 11] * f1), pack_bf16(O[G * 16 + 14] * f1, O[G * 16 + 15] * f1)); \
    }                                                                                                          \
  } while (0)

__global__ void __cluster_dims__(2, 1, 1) __launch_bounds__(384, 1)
fused_kernel(const __grid_constant__ Params p, const bf16* __restrict__ x, const bf16* __restrict__ gate_w, bf16* __restrict__ out) {
  extern __shared__ uint8_t smem_raw[];
  const uint32_t sbase = (smem_u32(smem_raw) + 1023) & ~1023u;
  const uint32_t sB = sbase, sA = sbase + K1_BST * 16384, sBar = sbase + SMEM_DATA;
  const uint32_t bAf = sBar, bAe = sBar + 64, bBf = sBar + 128, bBe = sBar + 176, bL = sBar + 224, bS = sBar + 232, bL2 = sBar + 240, sL = sA + 32768;
  const uint32_t bF = sBar + 256, bE = sBar + 320, bT = sBar + 384, sTick = sBar + 400, sItem = sBar + 416, bS2 = sBar + 448, bR = sBar + 456, bLast = sBar + 464;
  const uint32_t b3F = sBar + 512, b3E = sBar + 544, sGate = sBar + 576;
  const int tid = threadIdx.x, warp_g = __shfl_sync(0xffffffffu, tid >> 5, 0), lane = tid & 31;
  const uint32_t rank = cluster_rank();
  const int cl = blockIdx.x >> 1;
  TSM(0);
  if (tid == 0) {
    for (int i = 0; i < 8; i++) { mbar_init(bAf + i * 8, 1); mbar_init(bAe + i * 8, 2); }
    for (int i = 0; i < K1_BST; i++) { mbar_init(bBf + i * 8, 1); mbar_init(bBe + i * 8, 4); }
    mbar_init(bL, 1);
    mbar_init(bL2, 1);
    mbar_init(bR, 1);
    mbar_init(bLast, 1);
    mbar_init(bS, 8);
    for (int i = 0; i < K2_NST; i++) { mbar_init(bF + i * 8, 1); mbar_init(bE + i * 8, 4); }
    mbar_init(bT, 1); mbar_init(bT + 8, 1);
    mbar_init(bS2, 8);
    for (int i = 0; i < K3_NST; i++) { mbar_init(b3F + i * 8, 1); mbar_init(b3E + i * 8, 4); }
    asm volatile("fence.mbarrier_init.release.cluster;" ::: "memory");
  }
  __syncthreads();
  cluster_sync();
  const int lr0 = blockIdx.x * 16;

  if (warp_g >= 8) {
    reg_dealloc<40>();
    if (warp_g == 8) {
      if (elect_one()) {
        uint32_t bs = 0, bph = 1, aph = 1;
#pragma unroll 1
        for (int ji = 0; ji < K1_MAXJOBS; ji++) {
          const uint32_t job = p.jobs[cl][ji];
          if (!(job & 3)) break;
          const int a_sel = (job >> 2) & 1, mpair = (job >> 3) & 7, chunk0 = (job >> 8) & 63;
          const bool newA = (job >> 14) & 1;
          const int KC = a_sel ? 9 : 8;
          const uint32_t halfbytes = 8192;
          const bool lastjob = (ji + 1 == K1_MAXJOBS) || !(p.jobs[cl][ji + 1] & 3);
          const CUtensorMap* tw = &p.tmW[(job >> 6) & 3];
          {
            const uint32_t njob = (ji + 1 < K1_MAXJOBS) ? p.jobs[cl][ji + 1] : 0;
            if (!(njob & 3) && !newA) mbar_arrive(bLast);
            if (njob & 3) {
              const int nst = ((njob >> 2) & 1) ? 18 : 16;
#pragma unroll 1
              for (int t = (cl < 64) ? (cl & 7) : 0; t < nst; t += (cl < 64) ? 8 : 1)
                tma_pf3d(&p.tmW[(njob >> 6) & 3], 0, t * 32 + rank * 16, (njob >> 8) & 63);
            }
          }
#pragma unroll 1
          for (int kc = 0; kc < KC; kc++) {
            if (kc == 8) {
              mbar_wait(bBe + bs * 8, bph);
              mbar_expect(bBf + bs * 8, 16384);
              tma2d(sB + bs * 16384, &p.tmA[1], bBf + bs * 8, 512, mpair * 256 + rank * 128);
              if (++bs == K1_BST) { bs = 0; bph ^= 1; }
            } else if (newA) {
              mbar_wait(bAe + kc * 8, aph);
              mbar_expect(bAf + kc * 8, 16384);
              tma2d(sA + ((kc + 2) & 7) * 16384, &p.tmA[a_sel], bAf + kc * 8, kc * 64, mpair * 256 + rank * 128);
              if (kc == 7 && lastjob) mbar_arrive(bLast);
            }
#pragma unroll 1
            for (int kk = 0; kk < 2; kk++) {
              mbar_wait(bBe + bs * 8, bph);
              mbar_expect(bBf + bs * 8, 2 * halfbytes);
              tma3d_mc(sB + bs * 16384 + rank * halfbytes, tw, bBf + bs * 8, 0, kc * 64 + kk * 32 + rank * 16, chunk0, 3);
              if (++bs == K1_BST) { bs = 0; bph ^= 1; }
            }
          }
          if (newA) aph ^= 1;
        }
        Cursor c{0, 0};
        int pcol = 0;
        uint32_t tick = cl, seen = 1u << (p.order[cl] >> 4);
        mbar_wait(bR, 0);
        asm volatile("fence.proxy.async.global;" ::: "memory");
#pragma unroll 1
        for (int it = 0;; it++) {
          const uint32_t item = (tick < 256) ? p.order[tick] : (K2_END | min(tick - 256, 255u));
          asm volatile("st.shared.u32 [%0], %1;" ::"r"(sItem + (it & 7) * 4), "r"(item) : "memory");
          if (item >= K2_END) break;
          const int h = item >> 3, j = item & 7;
          const int blk = 2 * j + (int)(rank ^ (it & 1));
          const int col = h * 128 + rank * 64;
          const int nb = 2 * j + 2;
          if (!((seen >> (h >> 1)) & 1)) {
            wait_flag(&g_sync[F_HP + (h >> 1)], RDY_TARGET);
            asm volatile("fence.proxy.async.global;" ::: "memory");
            seen |= 1u << (h >> 1);
          }
          mbar_wait(bE + c.s * 8, c.ph);
          mbar_expect(bF + c.s * 8, 32768);
          tma2d(sbase + c.s * 32768, &p.tmQ, bF + c.s * 8, h * 128, blk * 128);
          tma2d(sbase + c.s * 32768 + 16384, &p.tmQ, bF + c.s * 8, h * 128 + 64, blk * 128);
          c.next();
#pragma unroll 1
          for (int n = nb - 1; n >= 0; n--) {
            if (n == 0 && rank == 0) tick = atomicAdd(&g_sync[F_TICK], 1u) + NCLUSTER;
            mbar_wait(bE + c.s * 8, c.ph);
            mbar_expect(bF + c.s * 8, 32768);
            tma2d_mc(sbase + c.s * 32768 + rank * 16384, &p.tmK, bF + c.s * 8, col, n * 128, 3);
            c.next();
            if (n < nb - 1 || it > 0) {
              mbar_wait(bE + c.s * 8, c.ph);
              mbar_expect(bF + c.s * 8, 32768);
              tma2d_mc(sbase + c.s * 32768 + rank * 16384, &p.tmV, bF + c.s * 8, (n < nb - 1) ? col : pcol, (n < nb - 1) ? (n + 1) * 128 : 0, 3);
              c.next();
            }
          }
          pcol = col;
          if (rank == 0) {
            asm volatile(
                "{\n.reg .b32 a, b;\nmapa.shared::cluster.u32 a, %0, 1;\nmapa.shared::cluster.u32 b, %1, 1;\n"
                "st.async.shared::cluster.mbarrier::complete_tx::bytes.u32 [a], %2, [b];\n}" ::"r"(sTick + (it & 1) * 4),
                "r"(bT + (it & 1) * 8), "r"(tick) : "memory");
          } else {
            mbar_expect(bT + (it & 1) * 8, 4);
            mbar_wait(bT + (it & 1) * 8, (it >> 1) & 1);
            tick = lds32(sTick + (it & 1) * 4);
          }
        }
        mbar_wait(bE + c.s * 8, c.ph);
        mbar_expect(bF + c.s * 8, 32768);
        tma2d_mc(sbase + c.s * 32768 + rank * 16384, &p.tmV, bF + c.s * 8, pcol, 0, 3);
        const uint32_t unit = tick - 256;
        if (unit < 64) {
          const int mp = 7 - (int)(unit >> 3), mblk = mp * 2 + rank, nhalf = (unit >> 2) & 1, ks = unit & 3;
          const int k0 = ks * 18, k1 = (ks == 3) ? 73 : k0 + 18;
          uint32_t s = 0, ph = 0;
#pragma unroll 1
          for (int k = k0; k < k1; k++) {
            mbar_wait(b3E + s * 8, ph);
            mbar_expect(b3F + s * 8, K3_STAGE);
            const uint32_t st = sbase + s * K3_STAGE;
            const int sel = (k >= 64), kr = (sel ? (k - 64) : k) * 64 + rank * 32;
            tma3d_mc(st + 16384 + rank * 16384, &p.tmO[sel], b3F + s * 8, 0, kr, nhalf * 4, 3);
            tma2d_mc(st + 49152 + rank * 2048, &p.tmOt[sel], b3F + s * 8, 512 + nhalf * 32, kr, 3);
            if (k == k0) {
              wait_flag(&g_sync[F_CTX + mp * 4 + ks], (ks == 3) ? 26 : 18);
              asm volatile("fence.proxy.async.global;" ::: "memory");
            }
            tma2d(st, &p.tmC, b3F + s * 8, k * 64, mblk * 128);
            if (++s == K3_NST) { s = 0; ph ^= 1; }
          }
        }
      }
    }
    __syncwarp();
    asm volatile("" ::: "memory");
    if (__shfl_sync(0xffffffffu, warp_g, 0) != 8) {
      if (lr0 < S_LEN) {
#pragma unroll 1
        for (int i = warp_g - 9; i < 16; i += 3) {
          const float g = gate_row(lr0 + i, lane, x, gate_w);
          if (lane == 0) asm volatile("st.shared.f32 [%0], %1;" ::"r"(sGate + i * 4), "f"(g) : "memory");
        }
        bar_arrive(3, 256 + 96);
        if (lane == 0) {
          __threadfence();
          atomicAdd(&g_sync[F_GATE], 1u);
        }
      }
      if (warp_g == 9 && lane == 0) {
#pragma unroll 1
        for (int ji = 0; ji < K1_MAXJOBS; ji++) {
          const uint32_t job = p.jobs[cl][ji];
          if (!(job & 3)) break;
          mbar_wait(bS, ji & 1);
          __threadfence();
          atomicAdd(&g_sync[(((job >> 6) & 3) == 2) ? (F_QKVA + ((job >> 3) & 7) * 2 + rank) : (F_HP + ((job >> 10) & 15))], 1u);
        }
#pragma unroll 1
        for (int it = 0;; it++) {
          mbar_wait(bS2, it & 1);
          const uint32_t item = lds32(sItem + (it & 7) * 4), nxt = lds32(sItem + ((it + 1) & 7) * 4);
          __threadfence();
          atomicAdd(&g_sync[F_CTX + (item & 7) * 4 + (item >> 3) / 9], 1u);
          if (nxt >= K2_END) break;
        }
      } else if (warp_g == 11) {
        if (lane == 0) {
          prefetch_tmap(&p.tmQ); prefetch_tmap(&p.tmK); prefetch_tmap(&p.tmV);
          wait_flag(&g_sync[F_GATE], GATE_TARGET);
          wait_flag(&g_sync[F_HP + (p.order[cl] >> 4)], RDY_TARGET);
          mbar_arrive(bR);
        }
        __syncwarp();
        bar_sync(4, 256 + 32);
        if (lane < 12) mbar_arrive_cluster(bE + (4 + lane % 3) * 8, (lane / 3) & 1);
      } else if (warp_g == 10 && lr0 < S_LEN) {
        if (elect_one()) {
          prefetch_tmap(&p.tmL[0]); prefetch_tmap(&p.tmL[1]);
          uint32_t aph = 1;
#pragma unroll 1
          for (int ji = 0; ji < K1_MAXJOBS; ji++) aph ^= (p.jobs[cl][ji] >> 14) & 1;
          wait_flag(&g_sync[F_QKVA + (lr0 >> 7)], K1_FLAG_TARGET);
          wait_flag(&g_sync[F_QKVA + (max(lr0 - 14, 0) >> 7)], K1_FLAG_TARGET);
          asm volatile("fence.proxy.async.global;" ::: "memory");
          mbar_wait(bLast, 0);
#pragma unroll 1
          for (int kc = 0; kc < 6; kc++) {
            mbar_wait(bAe + kc * 8, aph);
            if (kc == 3) {
              mbar_expect(bL, 46 * 1152);
              tma3d(sL, &p.tmL[0], bL, 0, 9, lr0 - 14);
              tma3d(sL + 30 * 1152, &p.tmL[1], bL, 0, 0, lr0);
            }
          }
          mbar_expect(bL2, 30 * 1152);
          tma3d(sL + 46 * 1152, &p.tmL[0], bL2, 0, 18, lr0 - 14);
        }
        __syncwarp();
        bar_sync(5, 256 + 32);
        if (lane == 0) {
          __threadfence();
          atomicAdd(&g_sync[F_CTX + (lr0 >> 8) * 4 + 3], 1u);
        }
      }
    }
    __syncwarp();
    cluster_sync();
    if (warp_g == 8) {
      uint32_t v = 0;
      if (lane == 0) {
        __threadfence();
        v = atomicAdd(&g_sync[F_DONE], 1u);
      }
      if (__shfl_sync(0xffffffffu, v, 0) == 2 * NCLUSTER - 1) reinterpret_cast<uint4*>(g_sync)[lane] = make_uint4(0, 0, 0, 0);
    }
  } else {
    reg_alloc<232>();
    const int wg = warp_g >> 2, warp = warp_g & 3, q = lane & 3;
    const bool sig = (lane == 0) && (warp < 2);
    {
      K1State st{0, 0, 0, nullptr, 0, 0};
      float acc[128];
      uint32_t pk[64];
      if (wg == 0) { TS(0, 0); TSC(0, 2); }
#pragma unroll 1
      for (int ji = 0; ji < K1_MAXJOBS; ji++) {
        const uint32_t job = p.jobs[cl][ji];
        if (!(job & 3)) break;
        k1_tile(acc, pk, st, job, sA, sB, bAf, bAe, bBf, bBe, bS, wg, warp, lane, rank);
      }
#pragma unroll
      for (int i = 0; i < 4; i++)
        mbar_arrive_cluster_if(bE + i * 8, warp & 1, sig);
#pragma unroll
      for (int G = 0; G < 8; G++)
        if (G < st.png) {
          st_v4(st.pp + G * 32, pk[G * 8], pk[G * 8 + 1], pk[G * 8 + 2], pk[G * 8 + 3]);
          st_v4(st.pp + G * 32 + st.pld8, pk[G * 8 + 4], pk[G * 8 + 5], pk[G * 8 + 6], pk[G * 8 + 7]);
        }
      k1_flag(st, lane, bS);
      if (wg == 0) { TS(0, 1); TSC(0, 3); }
      if (lr0 < S_LEN) {
        const int ri = (warp_g >> 1) * 4 + (warp_g & 1) + 2, row = lr0 + ri;
        if (wg == 0) TS(1, 5);
        bar_sync(3, 256 + 96);
        const float gate0 = __uint_as_float(lds32(sGate + ri * 4 - 8)), gate1 = __uint_as_float(lds32(sGate + ri * 4));
        mbar_wait(bL, 0);
        if (wg == 0) TS(1, 6);
        local_rows2(row, ri, sL, bL2, lane, gate0, gate1);
        bar_arrive(5, 256 + 32);
      } else {
        bar_arrive(4, 256 + 32);
      }
    }
    __syncwarp();
    uint32_t item;
    {
      const int mybar = 1 + wg, otherbar = 2 - wg;
      const float cl2 = 0.08838834764831845f * 1.4426950408889634f;
      float S[64], O[64];
      uint32_t P[32], Q[32];
#pragma unroll
      for (int i = 0; i < 64; i++) { S[i] = 0.f; O[i] = 1.f; }
#pragma unroll
      for (int i = 0; i < 32; i++) P[i] = 0;
      float m0 = 0.f, m1 = 0.f, l0 = 0.f, l1 = 0.f;
      int prev_row = 0, prev_h = 0, prev_single = 0;
      Cursor c{0, 0};
      if (wg == 1) bar_arrive(1, 256);
      if (wg == 0) { TS(1, 0); TSC(1, 2); }
#pragma unroll 1
      for (int it = 0;; it++) {
        mbar_wait(bF + c.s * 8, c.ph);
        item = lds32(sItem + (it & 7) * 4);
        if (item >= K2_END) break;
        const int h = item >> 3, j = item & 7;
        const int hi = (int)(rank ^ (it & 1));
        const int nblk = 2 * j + 1 + hi;
        {
          const float gf0 = 1.f - g_gate[prev_row], gf1 = 1.f - g_gate[prev_row + 8];
          Cursor cq = c; c.next();
          {
            const int r = wg * 64 + warp * 16 + (lane & 7) + ((lane >> 3) & 1) * 8;
            const uint32_t qa = sbase + cq.s * 32768 + r * 128;
#pragma unroll
            for (int t = 0; t < 8; t++)
              ldsm_x4(Q[4 * t], Q[4 * t + 1], Q[4 * t + 2], Q[4 * t + 3], qa + (t >> 2) * 16384 + ((((t & 3) * 2 + (lane >> 4)) ^ (lane & 7)) << 4));
          }
          Cursor ck = c; c.next();
          Cursor cs0 = ck, cs1 = ck, cv = c;
          mbar_wait(bF + ck.s * 8, ck.ph);
          if (it > 0) { mbar_wait(bF + cv.s * 8, cv.ph); c.next(); }
          if (!hi) {
            ck = c; c.next();
            cs1 = c; c.next();
            mbar_wait(bF + ck.s * 8, ck.ph);
            mbar_wait(bF + cs1.s * 8, cs1.ph);
          }
          if (it == 0) BSEG(4); else BSEG(0);
          TURN_SYNC();
          wg_fence();
          ISSUE_QK(ck);
          wg_commit();
          if (it > 0) ISSUE_PV(cv, prev_single);
          wg_commit();
          TURN_ARRIVE();
          RELEASE(cq);
          if (!hi) { RELEASE(cs0); RELEASE(cs1); }
          wg_wait<1>();
          fence_regs(S);
          RELEASE(ck);
          const int r0 = wg * 64 + warp * 16 + (lane >> 2);
#pragma unroll
          for (int jj = 0; jj < 16; jj++) {
            const int cc = jj * 8 + 2 * q;
            if (cc > r0) S[jj * 4 + 0] = -INFINITY;
            if (cc + 1 > r0) S[jj * 4 + 1] = -INFINITY;
            if (cc > r0 + 8) S[jj * 4 + 2] = -INFINITY;
            if (cc + 1 > r0 + 8) S[jj * 4 + 3] = -INFINITY;
          }
          float mx0 = fmaxf(S[0], S[1]), mx1 = fmaxf(S[2], S[3]);
#pragma unroll
          for (int jj = 1; jj < 16; jj++) {
            mx0 = fmaxf(mx0, fmaxf(S[jj * 4 + 0], S[jj * 4 + 1]));
            mx1 = fmaxf(mx1, fmaxf(S[jj * 4 + 2], S[jj * 4 + 3]));
          }
          mx0 = fmaxf(mx0, __shfl_xor_sync(0xffffffffu, mx0, 1));
          mx1 = fmaxf(mx1, __shfl_xor_sync(0xffffffffu, mx1, 1));
          mx0 = fmaxf(mx0, __shfl_xor_sync(0xffffffffu, mx0, 2));
          mx1 = fmaxf(mx1, __shfl_xor_sync(0xffffffffu, mx1, 2));
          m0 = mx0; m1 = mx1;
          const float mc0 = m0 * cl2, mc1 = m1 * cl2;
          float s0 = 0.f, s1 = 0.f;
#pragma unroll
          for (int jj = 0; jj < 16; jj++) {
            S[jj * 4 + 0] = ex2(fmaf(S[jj * 4 + 0], cl2, -mc0));
            S[jj * 4 + 1] = ex2(fmaf(S[jj * 4 + 1], cl2, -mc0));
            S[jj * 4 + 2] = ex2(fmaf(S[jj * 4 + 2], cl2, -mc1));
            S[jj * 4 + 3] = ex2(fmaf(S[jj * 4 + 3], cl2, -mc1));
            s0 += S[jj * 4 + 0] + S[jj * 4 + 1];
            s1 += S[jj * 4 + 2] + S[jj * 4 + 3];
          }
          fence_regs(S);
          wg_wait<0>();
          fence_regs(O);
          fence_regs(P);
          if (it > 0) {
            RELEASE(cv);
            EPILOGUE();
            __syncwarp();
            if (lane == 0) mbar_arrive(bS2);
          }
          l0 = s0; l1 = s1;
#pragma unroll
          for (int jj = 0; jj < 16; jj++) {
            P[jj * 2 + 0] = pack_bf16(S[jj * 4 + 0], S[jj * 4 + 1]);
            P[jj * 2 + 1] = pack_bf16(S[jj * 4 + 2], S[jj * 4 + 3]);
          }
        }
        if (it == 0) BSEG(5); else BSEG(1);
#pragma unroll 1
        for (int n = 1; n < nblk; n++) {
          Cursor ck = c; c.next();
          Cursor cv = c; c.next();
          mbar_wait(bF + ck.s * 8, ck.ph);
          mbar_wait(bF + cv.s * 8, cv.ph);
          TURN_SYNC();
          wg_fence();
          ISSUE_QK(ck);
          wg_commit();
          ISSUE_PV(cv, n == 1);
          wg_commit();
          TURN_ARRIVE();
          wg_wait<1>();
          fence_regs(S);
          RELEASE(ck);
          float mx0 = fmaxf(S[0], S[1]), mx1 = fmaxf(S[2], S[3]);
#pragma unroll
          for (int jj = 1; jj < 16; jj++) {
            mx0 = fmaxf(mx0, fmaxf(S[jj * 4 + 0], S[jj * 4 + 1]));
            mx1 = fmaxf(mx1, fmaxf(S[jj * 4 + 2], S[jj * 4 + 3]));
          }
          mx0 = fmaxf(mx0, __shfl_xor_sync(0xffffffffu, mx0, 1));
          mx1 = fmaxf(mx1, __shfl_xor_sync(0xffffffffu, mx1, 1));
          mx0 = fmaxf(mx0, __shfl_xor_sync(0xffffffffu, mx0, 2));
          mx1 = fmaxf(mx1, __shfl_xor_sync(0xffffffffu, mx1, 2));
          mx0 = fmaxf(mx0, m0);
          mx1 = fmaxf(mx1, m1);
          const float sc0 = ex2((m0 - mx0) * cl2), sc1 = ex2((m1 - mx1) * cl2);
          m0 = mx0; m1 = mx1;
          const float mc0 = m0 * cl2, mc1 = m1 * cl2;
          float s0 = 0.f, s1 = 0.f;
#pragma unroll
          for (int jj = 0; jj < 16; jj++) {
            S[jj * 4 + 0] = ex2(fmaf(S[jj * 4 + 0], cl2, -mc0));
            S[jj * 4 + 1] = ex2(fmaf(S[jj * 4 + 1], cl2, -mc0));
            S[jj * 4 + 2] = ex2(fmaf(S[jj * 4 + 2], cl2, -mc1));
            S[jj * 4 + 3] = ex2(fmaf(S[jj * 4 + 3], cl2, -mc1));
            s0 += S[jj * 4 + 0] + S[jj * 4 + 1];
            s1 += S[jj * 4 + 2] + S[jj * 4 + 3];
          }
          l0 = fmaf(l0, sc0, s0);
          l1 = fmaf(l1, sc1, s1);
          fence_regs(S);
          wg_wait<0>();
          fence_regs(O);
          fence_regs(P);
          RELEASE(cv);
#pragma unroll
          for (int jj = 0; jj < 16; jj++) {
            O[jj * 4 + 0] *= sc0;
            O[jj * 4 + 1] *= sc0;
            O[jj * 4 + 2] *= sc1;
            O[jj * 4 + 3] *= sc1;
            P[jj * 2 + 0] = pack_bf16(S[jj * 4 + 0], S[jj * 4 + 1]);
            P[jj * 2 + 1] = pack_bf16(S[jj * 4 + 2], S[jj * 4 + 3]);
          }
        }
        BSEG(2);
        prev_row = (2 * j + hi) * 128 + wg * 64 + warp * 16 + (lane >> 2);
        prev_h = h;
        prev_single = (nblk == 1);
      }
      {
        const float gf0 = 1.f - g_gate[prev_row], gf1 = 1.f - g_gate[prev_row + 8];
        Cursor cv = c;
        TURN_SYNC();
        wg_fence();
        ISSUE_PV(cv, prev_single);
        wg_commit();
        if (wg == 0) TURN_ARRIVE();
        wg_wait<0>();
        fence_regs(O);
#pragma unroll
        for (int i = 0; i < K3_NST; i++)
          mbar_arrive_cluster_if(b3E + i * 8, warp & 1, sig);
        EPILOGUE();
        __syncwarp();
        if (lane == 0) mbar_arrive(bS2);
      }
      if (wg == 1) { TS(1, 1); TSC(1, 3); }
    }
    __syncwarp();
    const uint32_t unit = item & 255;
    if (unit < 64) {
      const int mblk = (7 - (int)(unit >> 3)) * 2 + rank, nhalf = (unit >> 2) & 1, ks = unit & 3;
      const int k0 = ks * 18, k1 = (ks == 3) ? 73 : k0 + 18;
      float acc[144];
      uint32_t s = 0, ph = 0, prev = 0;
      if (wg == 0) { TS(2, 0); TSC(2, 2); }
#pragma unroll 1
      for (int k = k0; k < k1; k++) {
        mbar_wait(b3F + s * 8, ph);
        const uint32_t st = sbase + s * K3_STAGE;
        const uint64_t da = make_desc(st + wg * 8192, 16, 1024, 1);
        const uint64_t db = make_desc(st + 16384, 4096, 1024, 1);
        const uint64_t dt = make_desc(st + 49152, 16, 512, 2);
        wg_fence();
#pragma unroll
        for (int t = 0; t < 4; t++) {
          const int sd = (t > 0) || (k > k0);
          wgmma_ss_n256<1, 0>(acc, da + (uint64_t)(t * 2), db + (uint64_t)((t >> 1) * 1024 + (t & 1) * 128), sd);
          wgmma_ss_n32<1, 128>(acc, da + (uint64_t)(t * 2), dt + (uint64_t)(t * 64), sd);
        }
        wg_commit();
        if (k > k0) {
          wg_wait<1>();
          if (sig) mbar_arrive_cluster(b3E + prev * 8, warp);
        }
        prev = s;
        if (++s == K3_NST) { s = 0; ph ^= 1; }
      }
      wg_wait<0>();
      fence_regs(acc);
      if (wg == 0) TS(2, 4);
      const int tile = mblk * 2 + nhalf;
      float4* wp = g_part + (size_t)((tile * 4 + ks) * 4) * 9 * 256 + tid;
#pragma unroll
      for (int d = 0; d < 4; d++) {
        if (d != ks) {
#pragma unroll
          for (int i = 0; i < 8; i++)
            __stcg(wp + (d * 9 + i) * 256, make_float4(acc[d * 32 + i * 4], acc[d * 32 + i * 4 + 1], acc[d * 32 + i * 4 + 2], acc[d * 32 + i * 4 + 3]));
          __stcg(wp + (d * 9 + 8) * 256, make_float4(acc[128 + d * 4], acc[128 + d * 4 + 1], acc[128 + d * 4 + 2], acc[128 + d * 4 + 3]));
        }
      }
      __threadfence();
      bar_sync(6, 256);
      if (wg == 0) TS(2, 5);
      if (tid == 0) {
        atomicAdd(&g_sync[F_XCH + tile], 1u);
        uint32_t v, spins = 0;
        do {
          asm volatile("ld.acquire.gpu.global.u32 %0, [%1];" : "=r"(v) : "l"(&g_sync[F_XCH + tile]) : "memory");
        } while (v < 4 && ++spins < (1u << 24));
      }
      bar_sync(6, 256);
      if (wg == 0) TS(2, 6);
      float r[36];
#pragma unroll
      for (int d = 0; d < 4; d++) {
        if (d == ks) {
#pragma unroll
          for (int i = 0; i < 32; i++) r[i] = acc[d * 32 + i];
#pragma unroll
          for (int i = 0; i < 4; i++) r[32 + i] = acc[128 + d * 4 + i];
        }
      }
#pragma unroll
      for (int sI = 1; sI < 4; sI++) {
        const int src = (ks + sI) & 3;
        const float4* rp = g_part + (size_t)(((tile * 4 + src) * 4) + ks) * 9 * 256 + tid;
#pragma unroll
        for (int i = 0; i < 9; i++) {
          const float4 v = __ldcg(rp + i * 256);
          r[i * 4] += v.x; r[i * 4 + 1] += v.y; r[i * 4 + 2] += v.z; r[i * 4 + 3] += v.w;
        }
      }
      const int row = mblk * 128 + wg * 64 + warp * 16 + (lane >> 2);
      bf16* o0 = out + (size_t)row * DM + nhalf * 256 + ks * 64 + 8 * q;
#pragma unroll
      for (int G = 0; G < 2; G++) {
        uint32_t a0 = pack_bf16(r[G * 16], r[G * 16 + 1]), a1 = pack_bf16(r[G * 16 + 4], r[G * 16 + 5]);
        uint32_t a2 = pack_bf16(r[G * 16 + 8], r[G * 16 + 9]), a3 = pack_bf16(r[G * 16 + 12], r[G * 16 + 13]);
        uint32_t b0 = pack_bf16(r[G * 16 + 2], r[G * 16 + 3]), b1 = pack_bf16(r[G * 16 + 6], r[G * 16 + 7]);
        uint32_t b2 = pack_bf16(r[G * 16 + 10], r[G * 16 + 11]), b3 = pack_bf16(r[G * 16 + 14], r[G * 16 + 15]);
        quad_transpose(a0, a1, a2, a3, q);
        quad_transpose(b0, b1, b2, b3, q);
        st_v4(o0 + G * 32, a0, a1, a2, a3);
        st_v4(o0 + 8 * DM + G * 32, b0, b1, b2, b3);
      }
      {
        uint32_t t0 = pack_bf16(r[32], r[33]), t1 = pack_bf16(r[34], r[35]), t2 = 0, t3 = 0;
        quad_transpose(t0, t1, t2, t3, q);
        if (q < 2) st_v4(out + (size_t)(row + q * 8) * DM + 512 + nhalf * 32 + ks * 8, t0, t1, t2, t3);
      }
    }
    if (wg == 0) { TS(2, 1); TSC(2, 3); }
    cluster_sync();
  }
}

typedef CUresult (*EncFn)(CUtensorMap*, CUtensorMapDataType, cuuint32_t, void*, const cuuint64_t*, const cuuint64_t*, const cuuint32_t*,
                          const cuuint32_t*, CUtensorMapInterleave, CUtensorMapSwizzle, CUtensorMapL2promotion, CUtensorMapFloatOOBfill);

static void enc2d(EncFn enc, CUtensorMap* m, const void* ptr, uint64_t cols, uint64_t rows, uint32_t bc, uint32_t br,
                  CUtensorMapSwizzle sw = CU_TENSOR_MAP_SWIZZLE_128B) {
  cuuint64_t gd[2] = {cols, rows}, gs[1] = {cols * 2};
  cuuint32_t bx[2] = {bc, br}, es[2] = {1, 1};
  enc(m, CU_TENSOR_MAP_DATA_TYPE_BFLOAT16, 2, const_cast<void*>(ptr), gd, gs, bx, es, CU_TENSOR_MAP_INTERLEAVE_NONE, sw,
      CU_TENSOR_MAP_L2_PROMOTION_L2_256B, CU_TENSOR_MAP_FLOAT_OOB_FILL_NONE);
}
static void enc3d(EncFn enc, CUtensorMap* m, const void* ptr, uint64_t cols, uint64_t rows, uint32_t br, uint32_t bch) {
  cuuint64_t gd[3] = {64, rows, cols / 64}, gs[2] = {cols * 2, 128};
  cuuint32_t bx[3] = {64, br, bch}, es[3] = {1, 1, 1};
  enc(m, CU_TENSOR_MAP_DATA_TYPE_BFLOAT16, 3, const_cast<void*>(ptr), gd, gs, bx, es, CU_TENSOR_MAP_INTERLEAVE_NONE,
      CU_TENSOR_MAP_SWIZZLE_128B, CU_TENSOR_MAP_L2_PROMOTION_L2_256B, CU_TENSOR_MAP_FLOAT_OOB_FILL_NONE);
}

static void build_k1_jobs(Params& p) {
  int cnt[NCLUSTER];
  for (int c = 0; c < NCLUSTER; c++) {
    cnt[c] = 0;
    for (int i = 0; i < K1_MAXJOBS; i++) p.jobs[c][i] = 0;
  }
  auto add = [&](int c, int nch, int a_sel, int mp, int w_sel, int chunk0) {
    p.jobs[c][cnt[c]++] = (uint16_t)((nch - 1) | (a_sel << 2) | (mp << 3) | (w_sel << 6) | (chunk0 << 8));
  };
  for (int mp = 0; mp < 8; mp++) {
    for (int g = 0; g < 4; g++)
      for (int i = 0; i < 7; i++) add(g * 8 + mp, 4, 0, mp, g & 1, (2 + 2 * i + (g >> 1)) * 4);
    add(32 + mp, 3, 1, mp, 2, 24);
    add(32 + mp, 4, 1, mp, 3, 0 * 4);
    add(32 + mp, 4, 1, mp, 3, 1 * 4);
    for (int t = 0; t < 4; t++) add(32 + mp, 4, 0, mp, t & 1, (t >> 1) * 4);
    for (int g = 0; g < 2; g++) {
      for (int i = 0; i < 3; i++) add((5 + g) * 8 + mp, 4, 1, mp, 2, (g * 3 + i) * 4);
      for (int i = 0; i < 3; i++) add((5 + g) * 8 + mp, 4, 1, mp, 3, (2 + g * 3 + i) * 4);
    }
    for (int i = 0; i < 6; i++) add(56 + mp, 4, 1, mp, 3, (8 + i) * 4);
    add(64 + mp / 4, 4, 1, mp, 3, 14 * 4);
    if (mp & 1) add(64 + mp / 4, 4, 1, mp, 3, 15 * 4);
    else add(56 + mp, 4, 1, mp, 3, 15 * 4);
  }
  for (int cc = 0; cc < NCLUSTER; cc++)
    for (int i = 0; i < cnt[cc]; i++) {
      const int key = p.jobs[cc][i] & 0x3C;
      if (i == 0 || (p.jobs[cc][i - 1] & 0x3C) != key) p.jobs[cc][i] |= (1 << 14);
      if (i == cnt[cc] - 1 || (p.jobs[cc][i + 1] & 0x3C) != key) p.jobs[cc][i] |= (1 << 15);
    }
}

static void build_k2_items(Params& p) {
  static const int hp_order[16] = {8, 9, 10, 2, 5, 11, 3, 6, 12, 4, 7, 13, 14, 15, 0, 1};
  int n = 0;
  for (int i = 0; i < 64; i++) p.order[n++] = (uint8_t)((hp_order[i >> 2] * 2 + (i & 1)) * 8 + 7 - ((i >> 1) & 1));
  for (int j = 5; j >= 0; j--)
    for (int i = 0; i < 32; i++) p.order[n++] = (uint8_t)((hp_order[i >> 1] * 2 + (i & 1)) * 8 + j);
}

extern "C" void kernel_launch(void* const* d_in, const int* in_sizes, int n_in, void* d_out, int out_size) {
  const bf16* x = (const bf16*)d_in[0];
  const bf16* wqkv = (const bf16*)d_in[1];
  const bf16* wo = (const bf16*)d_in[2];
  const bf16* ckv = (const bf16*)d_in[4];
  const bf16* w_q = (const bf16*)d_in[5];
  const bf16* w_uk = (const bf16*)d_in[6];
  const bf16* w_uv = (const bf16*)d_in[7];
  const bf16* w_o = (const bf16*)d_in[8];
  const bf16* gate_w = (const bf16*)d_in[9];

  EncFn enc = nullptr;
  cudaDriverEntryPointQueryResult qr;
  cudaGetDriverEntryPoint("cuTensorMapEncodeTiled", (void**)&enc, cudaEnableDefault, &qr);
  void *pQ, *pK, *pV, *pCtx, *pQA;
  cudaGetSymbolAddress(&pQA, g_QKVA);
  cudaGetSymbolAddress(&pQ, g_Q);
  cudaGetSymbolAddress(&pK, g_K);
  cudaGetSymbolAddress(&pV, g_V);
  cudaGetSymbolAddress(&pCtx, g_ctx);

  static Params p;
  enc2d(enc, &p.tmA[0], ckv, DC, S_LEN, 64, 128);
  enc2d(enc, &p.tmA[1], x, DM, S_LEN, 64, 128);
  enc3d(enc, &p.tmW[0], w_uk, HDIM, DC, 16, 4);
  enc3d(enc, &p.tmW[1], w_uv, HDIM, DC, 16, 4);
  enc3d(enc, &p.tmW[2], wqkv, NQKVA, DM, 16, 4);
  enc3d(enc, &p.tmW[3], w_q, HDIM, DM, 16, 4);
  build_k1_jobs(p);
  enc2d(enc, &p.tmQ, pQ, HDIM, S_LEN, 64, 128);
  enc2d(enc, &p.tmK, pK, HDIM, S_LEN, 64, 128);
  enc2d(enc, &p.tmV, pV, HDIM, S_LEN, 64, 128);
  build_k2_items(p);
  for (int i = 0; i < 2; i++) {
    cuuint64_t gd[3] = {64, 27, S_LEN}, gs[2] = {128, NQKVA * 2};
    cuuint32_t bx[3] = {64, 9, i ? 16u : 30u}, es[3] = {1, 1, 1};
    enc(&p.tmL[i], CU_TENSOR_MAP_DATA_TYPE_BFLOAT16, 3, pQA, gd, gs, bx, es, CU_TENSOR_MAP_INTERLEAVE_NONE, CU_TENSOR_MAP_SWIZZLE_NONE,
        CU_TENSOR_MAP_L2_PROMOTION_L2_256B, CU_TENSOR_MAP_FLOAT_OOB_FILL_NONE);
  }
  enc2d(enc, &p.tmC, pCtx, KCAT, S_LEN, 64, 128);
  enc3d(enc, &p.tmO[0], w_o, DM, HDIM, 32, 4);
  enc3d(enc, &p.tmO[1], wo, DM, DM, 32, 4);
  enc2d(enc, &p.tmOt[0], w_o, DM, HDIM, 32, 32, CU_TENSOR_MAP_SWIZZLE_64B);
  enc2d(enc, &p.tmOt[1], wo, DM, DM, 32, 32, CU_TENSOR_MAP_SWIZZLE_64B);

  cudaFuncSetAttribute(fused_kernel, cudaFuncAttributeMaxDynamicSharedMemorySize, SMEM_BYTES);
  fused_kernel<<<NCLUSTER * 2, 384, SMEM_BYTES>>>(p, x, gate_w, (bf16*)d_out);
}
```

```cpp
#include <cuda_runtime.h>
#include <cuda_bf16.h>
#include <cuda.h>
#include <stdint.h>

typedef __nv_bfloat16 bf16;

constexpr int S_LEN = 2048, DM = 576, DC = 512, HDIM = 4096, NQKVA = 1728, KCAT = 4672;
constexpr int NCLUSTER = 66;

__device__ __align__(1024) bf16 g_Q[S_LEN * HDIM];
__device__ __align__(1024) bf16 g_K[S_LEN * HDIM];
__device__ __align__(1024) bf16 g_V[S_LEN * HDIM];
__device__ __align__(1024) bf16 g_QKVA[S_LEN * NQKVA + 64];
__device__ __align__(1024) bf16 g_ctx[S_LEN * KCAT];
__device__ float g_gate[S_LEN];
__device__ __align__(1024) float4 g_part[32 * 4 * 4 * 9 * 256];
__device__ __align__(16) unsigned int g_sync[128];
constexpr int F_QKVA = 0, F_HP = 16, F_CTX = 32, F_XCH = 64, F_GATE = 96, F_TICK = 97, F_DONE = 98;

__device__ __forceinline__ uint32_t smem_u32(const void* p) { return (uint32_t)__cvta_generic_to_shared(p); }
__device__ __forceinline__ void mbar_init(uint32_t a, uint32_t c) {
  asm volatile("mbarrier.init.shared::cta.b64 [%0], %1;" ::"r"(a), "r"(c));
}
__device__ __forceinline__ void mbar_expect(uint32_t a, uint32_t b) {
  asm volatile("mbarrier.arrive.expect_tx.shared::cta.b64 _, [%0], %1;" ::"r"(a), "r"(b) : "memory");
}
#define TS(k, i)
#define TSC(k, i)
#define TSM(k)
#define BSEG(i)
#define SPIN_LIMIT "4194304"
__device__ __forceinline__ void mbar_wait(uint32_t a, uint32_t parity) {
  asm volatile(
      "{\n.reg .pred p;\n.reg .u32 n;\n"
      "mbarrier.try_wait.parity.shared::cta.b64 p, [%0], %1;\n"
      "@p bra DONE;\n"
      "mov.u32 n, 0;\n"
      "LOOP:\n"
      "mbarrier.try_wait.parity.shared::cta.b64 p, [%0], %1;\n"
      "@p bra DONE;\n"
      "add.u32 n, n, 1;\n"
      "setp.lt.u32 p, n, " SPIN_LIMIT ";\n"
      "@p bra LOOP;\n"
      "DONE:\n}" ::"r"(a), "r"(parity) : "memory");
}
__device__ __forceinline__ void mbar_arrive(uint32_t a) {
  asm volatile("mbarrier.arrive.shared::cta.b64 _, [%0];" ::"r"(a) : "memory");
}
__device__ __forceinline__ void mbar_arrive_cluster(uint32_t a, uint32_t cta) {
  asm volatile("{\n.reg .b32 r;\nmapa.shared::cluster.u32 r, %0, %1;\nmbarrier.arrive.shared::cluster.b64 _, [r];\n}" ::"r"(a),
               "r"(cta) : "memory");
}
__device__ __forceinline__ void mbar_arrive_cluster_if(uint32_t a, uint32_t cta, bool pred) {
  asm volatile("{\n.reg .b32 r;\n.reg .pred p;\nsetp.ne.u32 p, %2, 0;\nmapa.shared::cluster.u32 r, %0, %1;\n@p mbarrier.arrive.shared::cluster.b64 _, [r];\n}" ::"r"(a),
               "r"(cta), "r"((uint32_t)pred) : "memory");
}
__device__ __forceinline__ void mbar_arrive_if(uint32_t a, bool pred) {
  asm volatile("{\n.reg .pred p;\nsetp.ne.u32 p, %1, 0;\n@p mbarrier.arrive.shared::cta.b64 _, [%0];\n}" ::"r"(a), "r"((uint32_t)pred) : "memory");
}
__device__ __forceinline__ void tma2d(uint32_t dst, const CUtensorMap* m, uint32_t bar, int c0, int c1) {
  asm volatile("cp.async.bulk.tensor.2d.shared::cluster.global.mbarrier::complete_tx::bytes [%0], [%1, {%3, %4}], [%2];" ::"r"(dst),
               "l"(m), "r"(bar), "r"(c0), "r"(c1) : "memory");
}
__device__ __forceinline__ void tma2d_mc(uint32_t dst, const CUtensorMap* m, uint32_t bar, int c0, int c1, uint16_t mask) {
  asm volatile(
      "cp.async.bulk.tensor.2d.shared::cluster.global.mbarrier::complete_tx::bytes.multicast::cluster [%0], [%1, {%3, %4}], [%2], %5;" ::"r"(dst),
      "l"(m), "r"(bar), "r"(c0), "r"(c1), "h"(mask) : "memory");
}
__device__ __forceinline__ void tma3d_mc(uint32_t dst, const CUtensorMap* m, uint32_t bar, int c0, int c1, int c2, uint16_t mask) {
  asm volatile(
      "cp.async.bulk.tensor.3d.shared::cluster.global.mbarrier::complete_tx::bytes.multicast::cluster [%0], [%1, {%3, %4, %5}], [%2], %6;" ::"r"(dst),
      "l"(m), "r"(bar), "r"(c0), "r"(c1), "r"(c2), "h"(mask) : "memory");
}
__device__ __forceinline__ void tma3d(uint32_t dst, const CUtensorMap* m, uint32_t bar, int c0, int c1, int c2) {
  asm volatile(
      "cp.async.bulk.tensor.3d.shared::cluster.global.mbarrier::complete_tx::bytes [%0], [%1, {%3, %4, %5}], [%2];" ::"r"(dst),
      "l"(m), "r"(bar), "r"(c0), "r"(c1), "r"(c2) : "memory");
}
__device__ __forceinline__ void tma_pf2d(const CUtensorMap* m, int c0, int c1) {
  asm volatile("cp.async.bulk.prefetch.tensor.2d.L2.global [%0, {%1, %2}];" ::"l"(m), "r"(c0), "r"(c1) : "memory");
}
__device__ __forceinline__ void tma_pf3d(const CUtensorMap* m, int c0, int c1, int c2) {
  asm volatile("cp.async.bulk.prefetch.tensor.3d.L2.global [%0, {%1, %2, %3}];" ::"l"(m), "r"(c0), "r"(c1), "r"(c2) : "memory");
}
__device__ __forceinline__ void prefetch_tmap(const CUtensorMap* m) {
  asm volatile("prefetch.tensormap [%0];" ::"l"(m) : "memory");
}
__device__ __forceinline__ void cluster_sync() {
  asm volatile("barrier.cluster.arrive.aligned;\nbarrier.cluster.wait.aligned;" ::: "memory");
}
__device__ __forceinline__ uint32_t cluster_rank() {
  uint32_t r;
  asm volatile("mov.u32 %0, %%cluster_ctarank;" : "=r"(r));
  return r;
}
__device__ __forceinline__ bool elect_one() {
  uint32_t p;
  asm volatile("{\n.reg .pred q;\nelect.sync _|q, 0xffffffff;\nselp.u32 %0, 1, 0, q;\n}" : "=r"(p));
  return p;
}
__device__ __forceinline__ void pdl_wait() { asm volatile("griddepcontrol.wait;" ::: "memory"); }
__device__ __forceinline__ void pdl_launch() { asm volatile("griddepcontrol.launch_dependents;" ::: "memory"); }
__device__ __forceinline__ void ldsm_x4(uint32_t& r0, uint32_t& r1, uint32_t& r2, uint32_t& r3, uint32_t addr) {
  asm volatile("ldmatrix.sync.aligned.m8n8.x4.shared.b16 {%0, %1, %2, %3}, [%4];" : "=r"(r0), "=r"(r1), "=r"(r2), "=r"(r3) : "r"(addr) : "memory");
}
__device__ __forceinline__ void wg_fence() { asm volatile("wgmma.fence.sync.aligned;" ::: "memory"); }
__device__ __forceinline__ void wg_commit() { asm volatile("wgmma.commit_group.sync.aligned;" ::: "memory"); }
template <int N>
__device__ __forceinline__ void wg_wait() { asm volatile("wgmma.wait_group.sync.aligned %0;" ::"n"(N) : "memory"); }
template <int N>
__device__ __forceinline__ void reg_alloc() { asm volatile("setmaxnreg.inc.sync.aligned.u32 %0;" ::"n"(N)); }
template <int N>
__device__ __forceinline__ void reg_dealloc() { asm volatile("setmaxnreg.dec.sync.aligned.u32 %0;" ::"n"(N)); }
__device__ __forceinline__ void bar_sync(int id, int n) { asm volatile("bar.sync %0, %1;" ::"r"(id), "r"(n) : "memory"); }
__device__ __forceinline__ void bar_arrive(int id, int n) { asm volatile("bar.arrive %0, %1;" ::"r"(id), "r"(n) : "memory"); }
template <int NT>
__device__ __forceinline__ void fence_regs(float (&d)[NT]) {
#pragma unroll
  for (int i = 0; i < NT; i++) asm volatile("" : "+f"(d[i])::"memory");
}
template <int NT>
__device__ __forceinline__ void fence_regs(uint32_t (&d)[NT]) {
#pragma unroll
  for (int i = 0; i < NT; i++) asm volatile("" : "+r"(d[i])::"memory");
}
__device__ __forceinline__ uint64_t make_desc(uint32_t saddr, uint32_t lbo, uint32_t sbo, uint32_t layout) {
  return (uint64_t)((saddr & 0x3FFFF) >> 4) | ((uint64_t)(lbo >> 4) << 16) | ((uint64_t)(sbo >> 4) << 32) | ((uint64_t)layout << 62);
}
__device__ __forceinline__ uint32_t pack_bf16(float lo, float hi) {
  uint32_t r;
  asm("cvt.rn.bf16x2.f32 %0, %1, %2;" : "=r"(r) : "f"(hi), "f"(lo));
  return r;
}
__device__ __forceinline__ float ex2(float x) {
  float r;
  asm("ex2.approx.ftz.f32 %0, %1;" : "=f"(r) : "f"(x));
  return r;
}
__device__ __forceinline__ void st_v4(void* p, uint32_t a, uint32_t b, uint32_t c, uint32_t d) {
#define ST_MOD ""
  asm volatile("st.global" ST_MOD ".v4.b32 [%0], {%1, %2, %3, %4};" ::"l"(p), "r"(a), "r"(b), "r"(c), "r"(d) : "memory");
}
__device__ __forceinline__ float bf_lo(uint32_t v) { return __uint_as_float(v << 16); }
__device__ __forceinline__ float bf_hi(uint32_t v) { return __uint_as_float(v & 0xFFFF0000u); }

__device__ __forceinline__ void quad_transpose(uint32_t& a0, uint32_t& a1, uint32_t& a2, uint32_t& a3, int q) {
  const bool o1 = q & 1, o2 = q & 2;
  uint32_t t0 = o1 ? a0 : a1, t1 = o1 ? a2 : a3;
  t0 = __shfl_xor_sync(0xffffffffu, t0, 1);
  t1 = __shfl_xor_sync(0xffffffffu, t1, 1);
  if (o1) { a0 = t0; a2 = t1; } else { a1 = t0; a3 = t1; }
  t0 = o2 ? a0 : a2;
  t1 = o2 ? a1 : a3;
  t0 = __shfl_xor_sync(0xffffffffu, t0, 2);
  t1 = __shfl_xor_sync(0xffffffffu, t1, 2);
  if (o2) { a0 = t0; a1 = t1; } else { a2 = t0; a3 = t1; }
}

template<int TB, int OFF, int NT>
__device__ __forceinline__ void wgmma_ss_n256(float (&d)[NT], uint64_t da, uint64_t db, int scale_d) {
  asm volatile("{\n.reg .pred p;\nsetp.ne.b32 p, %130, 0;\n"
    "wgmma.mma_async.sync.aligned.m64n256k16.f32.bf16.bf16 {%0, %1, %2, %3, %4, %5, %6, %7, %8, %9, %10, %11, %12, %13, %14, %15, %16, %17, %18, %19, %20, %21, %22, %23, %24, %25, %26, %27, %28, %29, %30, %31, %32, %33, %34, %35, %36, %37, %38, %39, %40, %41, %42, %43, %44, %45, %46, %47, %48, %49, %50, %51, %52, %53, %54, %55, %56, %57, %58, %59, %60, %61, %62, %63, %64, %65, %66, %67, %68, %69, %70, %71, %72, %73, %74, %75, %76, %77, %78, %79, %80, %81, %82, %83, %84, %85, %86, %87, %88, %89, %90, %91, %92, %93, %94, %95, %96, %97, %98, %99, %100, %101, %102, %103, %104, %105, %106, %107, %108, %109, %110, %111, %112, %113, %114, %115, %116, %117, %118, %119, %120, %121, %122, %123, %124, %125, %126, %127}, %128, %129, p, 1, 1, 0, %131;\n}\n"
    : "+f"(d[OFF+0]), "+f"(d[OFF+1]), "+f"(d[OFF+2]), "+f"(d[OFF+3]), "+f"(d[OFF+4]), "+f"(d[OFF+5]), "+f"(d[OFF+6]), "+f"(d[OFF+7]), "+f"(d[OFF+8]), "+f"(d[OFF+9]), "+f"(d[OFF+10]), "+f"(d[OFF+11]), "+f"(d[OFF+12]), "+f"(d[OFF+13]), "+f"(d[OFF+14]), "+f"(d[OFF+15]), "+f"(d[OFF+16]), "+f"(d[OFF+17]), "+f"(d[OFF+18]), "+f"(d[OFF+19]), "+f"(d[OFF+20]), "+f"(d[OFF+21]), "+f"(d[OFF+22]), "+f"(d[OFF+23]), "+f"(d[OFF+24]), "+f"(d[OFF+25]), "+f"(d[OFF+26]), "+f"(d[OFF+27]), "+f"(d[OFF+28]), "+f"(d[OFF+29]), "+f"(d[OFF+30]), "+f"(d[OFF+31]), "+f"(d[OFF+32]), "+f"(d[OFF+33]), "+f"(d[OFF+34]), "+f"(d[OFF+35]), "+f"(d[OFF+36]), "+f"(d[OFF+37]), "+f"(d[OFF+38]), "+f"(d[OFF+39]), "+f"(d[OFF+40]), "+f"(d[OFF+41]), "+f"(d[OFF+42]), "+f"(d[OFF+43]), "+f"(d[OFF+44]), "+f"(d[OFF+45]), "+f"(d[OFF+46]), "+f"(d[OFF+47]), "+f"(d[OFF+48]), "+f"(d[OFF+49]), "+f"(d[OFF+50]), "+f"(d[OFF+51]), "+f"(d[OFF+52]), "+f"(d[OFF+53]), "+f"(d[OFF+54]), "+f"(d[OFF+55]), "+f"(d[OFF+56]), "+f"(d[OFF+57]), "+f"(d[OFF+58]), "+f"(d[OFF+59]), "+f"(d[OFF+60]), "+f"(d[OFF+61]), "+f"(d[OFF+62]), "+f"(d[OFF+63]), "+f"(d[OFF+64]), "+f"(d[OFF+65]), "+f"(d[OFF+66]), "+f"(d[OFF+67]), "+f"(d[OFF+68]), "+f"(d[OFF+69]), "+f"(d[OFF+70]), "+f"(d[OFF+71]), "+f"(d[OFF+72]), "+f"(d[OFF+73]), "+f"(d[OFF+74]), "+f"(d[OFF+75]), "+f"(d[OFF+76]), "+f"(d[OFF+77]), "+f"(d[OFF+78]), "+f"(d[OFF+79]), "+f"(d[OFF+80]), "+f"(d[OFF+81]), "+f"(d[OFF+82]), "+f"(d[OFF+83]), "+f"(d[OFF+84]), "+f"(d[OFF+85]), "+f"(d[OFF+86]), "+f"(d[OFF+87]), "+f"(d[OFF+88]), "+f"(d[OFF+89]), "+f"(d[OFF+90]), "+f"(d[OFF+91]), "+f"(d[OFF+92]), "+f"(d[OFF+93]), "+f"(d[OFF+94]), "+f"(d[OFF+95]), "+f"(d[OFF+96]), "+f"(d[OFF+97]), "+f"(d[OFF+98]), "+f"(d[OFF+99]), "+f"(d[OFF+100]), "+f"(d[OFF+101]), "+f"(d[OFF+102]), "+f"(d[OFF+103]), "+f"(d[OFF+104]), "+f"(d[OFF+105]), "+f"(d[OFF+106]), "+f"(d[OFF+107]), "+f"(d[OFF+108]), "+f"(d[OFF+109]), "+f"(d[OFF+110]), "+f"(d[OFF+111]), "+f"(d[OFF+112]), "+f"(d[OFF+113]), "+f"(d[OFF+114]), "+f"(d[OFF+115]), "+f"(d[OFF+116]), "+f"(d[OFF+117]), "+f"(d[OFF+118]), "+f"(d[OFF+119]), "+f"(d[OFF+120]), "+f"(d[OFF+121]), "+f"(d[OFF+122]), "+f"(d[OFF+123]), "+f"(d[OFF+124]), "+f"(d[OFF+125]), "+f"(d[OFF+126]), "+f"(d[OFF+127])
    : "l"(da), "l"(db), "r"(scale_d), "n"(TB));
}
template<int TB, int OFF, int NT>
__device__ __forceinline__ void wgmma_ss_n192(float (&d)[NT], uint64_t da, uint64_t db, int scale_d) {
  asm volatile("{\n.reg .pred p;\nsetp.ne.b32 p, %98, 0;\n"
    "wgmma.mma_async.sync.aligned.m64n192k16.f32.bf16.bf16 {%0, %1, %2, %3, %4, %5, %6, %7, %8, %9, %10, %11, %12, %13, %14, %15, %16, %17, %18, %19, %20, %21, %22, %23, %24, %25, %26, %27, %28, %29, %30, %31, %32, %33, %34, %35, %36, %37, %38, %39, %40, %41, %42, %43, %44, %45, %46, %47, %48, %49, %50, %51, %52, %53, %54, %55, %56, %57, %58, %59, %60, %61, %62, %63, %64, %65, %66, %67, %68, %69, %70, %71, %72, %73, %74, %75, %76, %77, %78, %79, %80, %81, %82, %83, %84, %85, %86, %87, %88, %89, %90, %91, %92, %93, %94, %95}, %96, %97, p, 1, 1, 0, %99;\n}\n"
    : "+f"(d[OFF+0]), "+f"(d[OFF+1]), "+f"(d[OFF+2]), "+f"(d[OFF+3]), "+f"(d[OFF+4]), "+f"(d[OFF+5]), "+f"(d[OFF+6]), "+f"(d[OFF+7]), "+f"(d[OFF+8]), "+f"(d[OFF+9]), "+f"(d[OFF+10]), "+f"(d[OFF+11]), "+f"(d[OFF+12]), "+f"(d[OFF+13]), "+f"(d[OFF+14]), "+f"(d[OFF+15]), "+f"(d[OFF+16]), "+f"(d[OFF+17]), "+f"(d[OFF+18]), "+f"(d[OFF+19]), "+f"(d[OFF+20]), "+f"(d[OFF+21]), "+f"(d[OFF+22]), "+f"(d[OFF+23]), "+f"(d[OFF+24]), "+f"(d[OFF+25]), "+f"(d[OFF+26]), "+f"(d[OFF+27]), "+f"(d[OFF+28]), "+f"(d[OFF+29]), "+f"(d[OFF+30]), "+f"(d[OFF+31]), "+f"(d[OFF+32]), "+f"(d[OFF+33]), "+f"(d[OFF+34]), "+f"(d[OFF+35]), "+f"(d[OFF+36]), "+f"(d[OFF+37]), "+f"(d[OFF+38]), "+f"(d[OFF+39]), "+f"(d[OFF+40]), "+f"(d[OFF+41]), "+f"(d[OFF+42]), "+f"(d[OFF+43]), "+f"(d[OFF+44]), "+f"(d[OFF+45]), "+f"(d[OFF+46]), "+f"(d[OFF+47]), "+f"(d[OFF+48]), "+f"(d[OFF+49]), "+f"(d[OFF+50]), "+f"(d[OFF+51]), "+f"(d[OFF+52]), "+f"(d[OFF+53]), "+f"(d[OFF+54]), "+f"(d[OFF+55]), "+f"(d[OFF+56]), "+f"(d[OFF+57]), "+f"(d[OFF+58]), "+f"(d[OFF+59]), "+f"(d[OFF+60]), "+f"(d[OFF+61]), "+f"(d[OFF+62]), "+f"(d[OFF+63]), "+f"(d[OFF+64]), "+f"(d[OFF+65]), "+f"(d[OFF+66]), "+f"(d[OFF+67]), "+f"(d[OFF+68]), "+f"(d[OFF+69]), "+f"(d[OFF+70]), "+f"(d[OFF+71]), "+f"(d[OFF+72]), "+f"(d[OFF+73]), "+f"(d[OFF+74]), "+f"(d[OFF+75]), "+f"(d[OFF+76]), "+f"(d[OFF+77]), "+f"(d[OFF+78]), "+f"(d[OFF+79]), "+f"(d[OFF+80]), "+f"(d[OFF+81]), "+f"(d[OFF+82]), "+f"(d[OFF+83]), "+f"(d[OFF+84]), "+f"(d[OFF+85]), "+f"(d[OFF+86]), "+f"(d[OFF+87]), "+f"(d[OFF+88]), "+f"(d[OFF+89]), "+f"(d[OFF+90]), "+f"(d[OFF+91]), "+f"(d[OFF+92]), "+f"(d[OFF+93]), "+f"(d[OFF+94]), "+f"(d[OFF+95])
    : "l"(da), "l"(db), "r"(scale_d), "n"(TB));
}
template<int TB, int OFF, int NT>
__device__ __forceinline__ void wgmma_ss_n128(float (&d)[NT], uint64_t da, uint64_t db, int scale_d) {
  asm volatile("{\n.reg .pred p;\nsetp.ne.b32 p, %66, 0;\n"
    "wgmma.mma_async.sync.aligned.m64n128k16.f32.bf16.bf16 {%0, %1, %2, %3, %4, %5, %6, %7, %8, %9, %10, %11, %12, %13, %14, %15, %16, %17, %18, %19, %20, %21, %22, %23, %24, %25, %26, %27, %28, %29, %30, %31, %32, %33, %34, %35, %36, %37, %38, %39, %40, %41, %42, %43, %44, %45, %46, %47, %48, %49, %50, %51, %52, %53, %54, %55, %56, %57, %58, %59, %60, %61, %62, %63}, %64, %65, p, 1, 1, 0, %67;\n}\n"
    : "+f"(d[OFF+0]), "+f"(d[OFF+1]), "+f"(d[OFF+2]), "+f"(d[OFF+3]), "+f"(d[OFF+4]), "+f"(d[OFF+5]), "+f"(d[OFF+6]), "+f"(d[OFF+7]), "+f"(d[OFF+8]), "+f"(d[OFF+9]), "+f"(d[OFF+10]), "+f"(d[OFF+11]), "+f"(d[OFF+12]), "+f"(d[OFF+13]), "+f"(d[OFF+14]), "+f"(d[OFF+15]), "+f"(d[OFF+16]), "+f"(d[OFF+17]), "+f"(d[OFF+18]), "+f"(d[OFF+19]), "+f"(d[OFF+20]), "+f"(d[OFF+21]), "+f"(d[OFF+22]), "+f"(d[OFF+23]), "+f"(d[OFF+24]), "+f"(d[OFF+25]), "+f"(d[OFF+26]), "+f"(d[OFF+27]), "+f"(d[OFF+28]), "+f"(d[OFF+29]), "+f"(d[OFF+30]), "+f"(d[OFF+31]), "+f"(d[OFF+32]), "+f"(d[OFF+33]), "+f"(d[OFF+34]), "+f"(d[OFF+35]), "+f"(d[OFF+36]), "+f"(d[OFF+37]), "+f"(d[OFF+38]), "+f"(d[OFF+39]), "+f"(d[OFF+40]), "+f"(d[OFF+41]), "+f"(d[OFF+42]), "+f"(d[OFF+43]), "+f"(d[OFF+44]), "+f"(d[OFF+45]), "+f"(d[OFF+46]), "+f"(d[OFF+47]), "+f"(d[OFF+48]), "+f"(d[OFF+49]), "+f"(d[OFF+50]), "+f"(d[OFF+51]), "+f"(d[OFF+52]), "+f"(d[OFF+53]), "+f"(d[OFF+54]), "+f"(d[OFF+55]), "+f"(d[OFF+56]), "+f"(d[OFF+57]), "+f"(d[OFF+58]), "+f"(d[OFF+59]), "+f"(d[OFF+60]), "+f"(d[OFF+61]), "+f"(d[OFF+62]), "+f"(d[OFF+63])
    : "l"(da), "l"(db), "r"(scale_d), "n"(TB));
}
template<int TB, int OFF, int NT>
__device__ __forceinline__ void wgmma_ss_n32(float (&d)[NT], uint64_t da, uint64_t db, int scale_d) {
  asm volatile("{\n.reg .pred p;\nsetp.ne.b32 p, %18, 0;\n"
    "wgmma.mma_async.sync.aligned.m64n32k16.f32.bf16.bf16 {%0, %1, %2, %3, %4, %5, %6, %7, %8, %9, %10, %11, %12, %13, %14, %15}, %16, %17, p, 1, 1, 0, %19;\n}\n"
    : "+f"(d[OFF+0]), "+f"(d[OFF+1]), "+f"(d[OFF+2]), "+f"(d[OFF+3]), "+f"(d[OFF+4]), "+f"(d[OFF+5]), "+f"(d[OFF+6]), "+f"(d[OFF+7]), "+f"(d[OFF+8]), "+f"(d[OFF+9]), "+f"(d[OFF+10]), "+f"(d[OFF+11]), "+f"(d[OFF+12]), "+f"(d[OFF+13]), "+f"(d[OFF+14]), "+f"(d[OFF+15])
    : "l"(da), "l"(db), "r"(scale_d), "n"(TB));
}
template<int TB, int OFF, int NT>
__device__ __forceinline__ void wgmma_rs_n128(float (&d)[NT], uint32_t a0, uint32_t a1, uint32_t a2, uint32_t a3, uint64_t db, int scale_d) {
  asm volatile("{\n.reg .pred p;\nsetp.ne.b32 p, %69, 0;\n"
    "wgmma.mma_async.sync.aligned.m64n128k16.f32.bf16.bf16 {%0, %1, %2, %3, %4, %5, %6, %7, %8, %9, %10, %11, %12, %13, %14, %15, %16, %17, %18, %19, %20, %21, %22, %23, %24, %25, %26, %27, %28, %29, %30, %31, %32, %33, %34, %35, %36, %37, %38, %39, %40, %41, %42, %43, %44, %45, %46, %47, %48, %49, %50, %51, %52, %53, %54, %55, %56, %57, %58, %59, %60, %61, %62, %63}, {%64, %65, %66, %67}, %68, p, 1, 1, %70;\n}\n"
    : "+f"(d[OFF+0]), "+f"(d[OFF+1]), "+f"(d[OFF+2]), "+f"(d[OFF+3]), "+f"(d[OFF+4]), "+f"(d[OFF+5]), "+f"(d[OFF+6]), "+f"(d[OFF+7]), "+f"(d[OFF+8]), "+f"(d[OFF+9]), "+f"(d[OFF+10]), "+f"(d[OFF+11]), "+f"(d[OFF+12]), "+f"(d[OFF+13]), "+f"(d[OFF+14]), "+f"(d[OFF+15]), "+f"(d[OFF+16]), "+f"(d[OFF+17]), "+f"(d[OFF+18]), "+f"(d[OFF+19]), "+f"(d[OFF+20]), "+f"(d[OFF+21]), "+f"(d[OFF+22]), "+f"(d[OFF+23]), "+f"(d[OFF+24]), "+f"(d[OFF+25]), "+f"(d[OFF+26]), "+f"(d[OFF+27]), "+f"(d[OFF+28]), "+f"(d[OFF+29]), "+f"(d[OFF+30]), "+f"(d[OFF+31]), "+f"(d[OFF+32]), "+f"(d[OFF+33]), "+f"(d[OFF+34]), "+f"(d[OFF+35]), "+f"(d[OFF+36]), "+f"(d[OFF+37]), "+f"(d[OFF+38]), "+f"(d[OFF+39]), "+f"(d[OFF+40]), "+f"(d[OFF+41]), "+f"(d[OFF+42]), "+f"(d[OFF+43]), "+f"(d[OFF+44]), "+f"(d[OFF+45]), "+f"(d[OFF+46]), "+f"(d[OFF+47]), "+f"(d[OFF+48]), "+f"(d[OFF+49]), "+f"(d[OFF+50]), "+f"(d[OFF+51]), "+f"(d[OFF+52]), "+f"(d[OFF+53]), "+f"(d[OFF+54]), "+f"(d[OFF+55]), "+f"(d[OFF+56]), "+f"(d[OFF+57]), "+f"(d[OFF+58]), "+f"(d[OFF+59]), "+f"(d[OFF+60]), "+f"(d[OFF+61]), "+f"(d[OFF+62]), "+f"(d[OFF+63])
    : "r"(a0), "r"(a1), "r"(a2), "r"(a3), "l"(db), "r"(scale_d), "n"(TB));
}
template<int TB, int OFF, int NT>
__device__ __forceinline__ void wgmma_rs_n64(float (&d)[NT], uint32_t a0, uint32_t a1, uint32_t a2, uint32_t a3, uint64_t db, int scale_d) {
  asm volatile("{\n.reg .pred p;\nsetp.ne.b32 p, %37, 0;\n"
    "wgmma.mma_async.sync.aligned.m64n64k16.f32.bf16.bf16 {%0, %1, %2, %3, %4, %5, %6, %7, %8, %9, %10, %11, %12, %13, %14, %15, %16, %17, %18, %19, %20, %21, %22, %23, %24, %25, %26, %27, %28, %29, %30, %31}, {%32, %33, %34, %35}, %36, p, 1, 1, %38;\n}\n"
    : "+f"(d[OFF+0]), "+f"(d[OFF+1]), "+f"(d[OFF+2]), "+f"(d[OFF+3]), "+f"(d[OFF+4]), "+f"(d[OFF+5]), "+f"(d[OFF+6]), "+f"(d[OFF+7]), "+f"(d[OFF+8]), "+f"(d[OFF+9]), "+f"(d[OFF+10]), "+f"(d[OFF+11]), "+f"(d[OFF+12]), "+f"(d[OFF+13]), "+f"(d[OFF+14]), "+f"(d[OFF+15]), "+f"(d[OFF+16]), "+f"(d[OFF+17]), "+f"(d[OFF+18]), "+f"(d[OFF+19]), "+f"(d[OFF+20]), "+f"(d[OFF+21]), "+f"(d[OFF+22]), "+f"(d[OFF+23]), "+f"(d[OFF+24]), "+f"(d[OFF+25]), "+f"(d[OFF+26]), "+f"(d[OFF+27]), "+f"(d[OFF+28]), "+f"(d[OFF+29]), "+f"(d[OFF+30]), "+f"(d[OFF+31])
    : "r"(a0), "r"(a1), "r"(a2), "r"(a3), "l"(db), "r"(scale_d), "n"(TB));
}

__device__ __forceinline__ void wait_flag(const unsigned int* f, uint32_t target) {
  uint32_t v;
#pragma unroll 1
  for (uint32_t spins = 0; spins < (1u << 22); spins++) {
    asm volatile("ld.acquire.gpu.global.u32 %0, [%1];" : "=r"(v) : "l"(f) : "memory");
    if (v >= target) break;
    __nanosleep(100);
  }
}
__device__ __forceinline__ uint32_t lds32(uint32_t a) {
  uint32_t v;
  asm volatile("ld.shared.u32 %0, [%1];" : "=r"(v) : "r"(a) : "memory");
  return v;
}
__device__ __forceinline__ float gate_row(int row, int lane, const bf16* __restrict__ x, const bf16* __restrict__ gate_w) {
  const uint32_t* xr = reinterpret_cast<const uint32_t*>(x + (size_t)row * DM);
  const uint32_t* gw2 = reinterpret_cast<const uint32_t*>(gate_w);
  float gs = 0.f;
#pragma unroll
  for (int i = 0; i < 9; i++) {
    const uint32_t a = __ldg(xr + lane + 32 * i), b = __ldg(gw2 + lane + 32 * i);
    gs = fmaf(bf_lo(a), bf_lo(b), gs);
    gs = fmaf(bf_hi(a), bf_hi(b), gs);
  }
#pragma unroll
  for (int o = 16; o; o >>= 1) gs += __shfl_xor_sync(0xffffffffu, gs, o);
  const float g = 1.f / (1.f + __expf(-gs));
  if (lane == 0) g_gate[row] = g;
  return g;
}
#define LA_UNROLL 1
__device__ __forceinline__ void local_rows2(int rb, int ri, uint32_t sL, uint32_t bL2, int lane, float ga, float gb) {
  const float scale_l2 = 0.23570226039551584f * 1.4426950408889634f;
  constexpr int U = LA_UNROLL;
  const uint32_t sq = sL + (30 + ri) * 1152;
  const uint32_t kb = sL + (14 + ri) * 1152 + lane * 36;
  float ma = -INFINITY, mb = -INFINITY;
  {
    float qa[18], qb[18];
#pragma unroll
    for (int i = 0; i < 9; i++) {
      const uint32_t u = lds32(sq - 2304 + lane * 36 + 4 * i), v = lds32(sq + lane * 36 + 4 * i);
      qa[2 * i] = bf_lo(u); qa[2 * i + 1] = bf_hi(u);
      qb[2 * i] = bf_lo(v); qb[2 * i + 1] = bf_hi(v);
    }
    __syncwarp();
#pragma unroll U
    for (int t = 0; t < 9; t++) {
      const bool ok = rb - 2 * t >= 0;
      float a0 = 0.f, a1 = 0.f, b0 = 0.f, b1 = 0.f;
#pragma unroll
      for (int i = 0; i < 9; i++) {
        const uint32_t k = lds32(kb - t * 2304 + 4 * i);
        const float lo = bf_lo(k), hi = bf_hi(k);
        a0 = fmaf(qa[2 * i], lo, a0); a1 = fmaf(qa[2 * i + 1], hi, a1);
        b0 = fmaf(qb[2 * i], lo, b0); b1 = fmaf(qb[2 * i + 1], hi, b1);
      }
      a0 = (ok && t > 0) ? a0 + a1 : -INFINITY;
      b0 = (ok && t < 8) ? b0 + b1 : -INFINITY;
      ma = fmaxf(ma, a0);
      mb = fmaxf(mb, b0);
      asm volatile("st.shared.f32 [%0], %1;" ::"r"(sq - 2304 + t * 128 + lane * 4), "f"(a0) : "memory");
      asm volatile("st.shared.f32 [%0], %1;" ::"r"(sq + t * 128 + lane * 4), "f"(b0) : "memory");
    }
  }
  float oa[18], ob[18], sa = 0.f, sb = 0.f;
#pragma unroll
  for (int i = 0; i < 18; i++) { oa[i] = 0.f; ob[i] = 0.f; }
  mbar_wait(bL2, 0);
#pragma unroll U
  for (int t = 0; t < 9; t++) {
    const float wa = ex2((__uint_as_float(lds32(sq - 2304 + t * 128 + lane * 4)) - ma) * scale_l2);
    const float wb = ex2((__uint_as_float(lds32(sq + t * 128 + lane * 4)) - mb) * scale_l2);
    sa += wa;
    sb += wb;
#pragma unroll
    for (int i = 0; i < 9; i++) {
      const uint32_t v = lds32(kb + 46 * 1152 - t * 2304 + 4 * i);
      const float lo = bf_lo(v), hi = bf_hi(v);
      oa[2 * i] = fmaf(wa, lo, oa[2 * i]); oa[2 * i + 1] = fmaf(wa, hi, oa[2 * i + 1]);
      ob[2 * i] = fmaf(wb, lo, ob[2 * i]); ob[2 * i + 1] = fmaf(wb, hi, ob[2 * i + 1]);
    }
  }
  ga = __fdividef(ga, sa);
  gb = __fdividef(gb, sb);
  __syncwarp();
#pragma unroll
  for (int i = 0; i < 9; i++) {
    asm volatile("st.shared.u32 [%0], %1;" ::"r"(sq - 2304 + lane * 36 + 4 * i), "r"(pack_bf16(oa[2 * i] * ga, oa[2 * i + 1] * ga)) : "memory");
    asm volatile("st.shared.u32 [%0], %1;" ::"r"(sq + lane * 36 + 4 * i), "r"(pack_bf16(ob[2 * i] * gb, ob[2 * i + 1] * gb)) : "memory");
  }
  __syncwarp();
  uint32_t w[5][4];
#pragma unroll
  for (int t = 0; t < 5; t++) {
    const int c = min(t * 32 + lane, 143), r = c >= 72;
    asm volatile("ld.shared.v4.u32 {%0, %1, %2, %3}, [%4];" : "=r"(w[t][0]), "=r"(w[t][1]), "=r"(w[t][2]), "=r"(w[t][3])
                 : "r"(sq - 2304 + r * 2304 + (c - r * 72) * 16) : "memory");
  }
  asm volatile("fence.proxy.async.shared::cta;" ::: "memory");
  bar_arrive(4, 256 + 32);
#pragma unroll
  for (int t = 0; t < 5; t++) {
    const int c = min(t * 32 + lane, 143), r = c >= 72;
    st_v4(g_ctx + (size_t)(rb - 2 + 2 * r) * KCAT + HDIM + (c - r * 72) * 8, w[t][0], w[t][1], w[t][2], w[t][3]);
  }
}

#define K1_NST 6
constexpr int K1_BST = K1_NST;
constexpr int K1_MAXJOBS = 10;
constexpr uint32_t K1_FLAG_TARGET = 7;
constexpr uint32_t RDY_TARGET = 48;
constexpr uint32_t GATE_TARGET = 128 * 3;
struct alignas(64) Params {
  CUtensorMap tmA[2];
  CUtensorMap tmW[4];
  CUtensorMap tmQ, tmK, tmV;
  CUtensorMap tmL[2];
  CUtensorMap tmC, tmO[2], tmOt[2];
  uint16_t jobs[NCLUSTER][K1_MAXJOBS];
  uint8_t order[256];
};

struct K1State {
  uint32_t bs, bph, aph;
  bf16* pp;
  int pld8;
  int png;
};
__device__ __forceinline__ void k1_flag(const K1State& st, int lane, uint32_t bS) {
  if (st.png) {
    __syncwarp();
    if (lane == 0) mbar_arrive(bS);
  }
}

__device__ __forceinline__ void k1_tile(float (&acc)[128], uint32_t (&pk)[64], K1State& st, uint32_t job, uint32_t sA, uint32_t sB,
                                        uint32_t bAf, uint32_t bAe, uint32_t bBf, uint32_t bBe, uint32_t bS, int wg, int warp, int lane, uint32_t rank) {
  const int a_sel = (job >> 2) & 1, mpair = (job >> 3) & 7, w_sel = (job >> 6) & 3, chunk0 = (job >> 8) & 63;
  const bool newA = (job >> 14) & 1, lastA = (job >> 15) & 1;
  const bool sig = (lane == 0) && (warp < 2);
  const bool siga = lastA && (lane == 0) && (warp == 2);
  const int KC = 8 + a_sel;
  uint32_t prev_bs = 0, prev2_bs = 0, a8_bs = 0;
#pragma unroll
  for (int kc = 0; kc < 9; kc++) {
    if (kc >= KC) break;
    uint32_t abase = sA + ((kc + 2) & 7) * 16384;
    if (kc == 8) {
      mbar_wait(bBf + st.bs * 8, st.bph);
      a8_bs = st.bs;
      abase = sB + st.bs * 16384;
      if (++st.bs == K1_BST) { st.bs = 0; st.bph ^= 1; }
    } else if (newA) {
      mbar_wait(bAf + kc * 8, st.aph);
    }
    const uint64_t da = make_desc(abase + wg * 8192, 16, 1024, 1);
#pragma unroll
    for (int ks = 0; ks < 2; ks++) {
      mbar_wait(bBf + st.bs * 8, st.bph);
      const uint64_t db = make_desc(sB + st.bs * 16384, 2048, 1024, 1);
      wg_fence();
      wgmma_ss_n256<1, 0>(acc, da + (uint64_t)(ks * 4), db, (ks > 0) ? 1 : (kc > 0));
      wgmma_ss_n256<1, 0>(acc, da + (uint64_t)(ks * 4 + 2), db + (uint64_t)512, 1);
      wg_commit();
      const int PO = (kc < 8 ? kc : 0) * 8;
      wg_wait<1>();
      if (ks > 0 || kc > 0) {
        if (sig) mbar_arrive_cluster(bBe + prev_bs * 8, warp);
        if (ks == 0 && siga) mbar_arrive(bAe + (kc - 1) * 8);
      }
      if (kc < st.png) st_v4(st.pp + kc * 32 + ks * st.pld8, pk[PO + ks * 4], pk[PO + ks * 4 + 1], pk[PO + ks * 4 + 2], pk[PO + ks * 4 + 3]);
      prev_bs = st.bs;
      if (++st.bs == K1_BST) { st.bs = 0; st.bph ^= 1; }
    }
  }
  if (newA) st.aph ^= 1;
  k1_flag(st, lane, bS);
  wg_wait<0>();
  fence_regs(acc);
  if (sig) {
    mbar_arrive_cluster(bBe + prev_bs * 8, warp);
    if (a_sel) mbar_arrive_cluster(bBe + a8_bs * 8, warp);
  }
  if (siga && !a_sel) mbar_arrive(bAe + 7 * 8);
  const bool isA = (w_sel == 2);
  bf16* out = (w_sel == 0) ? g_K : (w_sel == 1) ? g_V : isA ? g_QKVA : g_Q;
  const int ld = isA ? NQKVA : HDIM;
  const int row = mpair * 256 + rank * 128 + wg * 64 + warp * 16 + (lane >> 2);
  st.pp = out + (size_t)row * ld + chunk0 * 64 + (lane & 3) * 8;
  st.pld8 = 8 * ld;
  st.png = ((job & 3) + 1) * 2;
#pragma unroll
  for (int G = 0; G < 8; G++) {
    pk[G * 8 + 0] = pack_bf16(acc[G * 16 + 0], acc[G * 16 + 1]);
    pk[G * 8 + 1] = pack_bf16(acc[G * 16 + 4], acc[G * 16 + 5]);
    pk[G * 8 + 2] = pack_bf16(acc[G * 16 + 8], acc[G * 16 + 9]);
    pk[G * 8 + 3] = pack_bf16(acc[G * 16 + 12], acc[G * 16 + 13]);
    pk[G * 8 + 4] = pack_bf16(acc[G * 16 + 2], acc[G * 16 + 3]);
    pk[G * 8 + 5] = pack_bf16(acc[G * 16 + 6], acc[G * 16 + 7]);
    pk[G * 8 + 6] = pack_bf16(acc[G * 16 + 10], acc[G * 16 + 11]);
    pk[G * 8 + 7] = pack_bf16(acc[G * 16 + 14], acc[G * 16 + 15]);
  }
  if (isA) {
#pragma unroll
    for (int G = 0; G < 16; G++) quad_transpose(pk[G * 4 + 0], pk[G * 4 + 1], pk[G * 4 + 2], pk[G * 4 + 3], lane & 3);
  }
}

#define HA(h) (h)
constexpr int K2_NST = 7;
constexpr uint32_t K2_END = 0x100;
constexpr int K3_NST = 4;
constexpr int K3_STAGE = 16384 + 32768 + 4096;
constexpr int SMEM_DATA = 7 * 32768;
constexpr int SMEM_BYTES = SMEM_DATA + 1024 + 768;

struct Cursor {
  uint32_t s, ph;
  __device__ __forceinline__ void next() {
    if (++s == K2_NST) { s = 0; ph ^= 1; }
  }
};

#define TURN_SYNC() bar_sync(mybar, 256)
#define TURN_ARRIVE() bar_arrive(otherbar, 256)
#define RELEASE_IF(cur, cond) mbar_arrive_cluster_if(bE + (cur).s * 8, warp & 1, sig && (cond))
#define RELEASE(cur) RELEASE_IF(cur, true)
#define ISSUE_PV(cur, first)                                                                                   \
  do {                                                                                                         \
    const uint64_t dv = make_desc(sbase + (cur).s * 32768, 16384, 1024, 1);                                    \
    _Pragma("unroll") for (int t = 0; t < 8; t++)                                                              \
        wgmma_rs_n128<1, 0>(O, P[4 * t], P[4 * t + 1], P[4 * t + 2], P[4 * t + 3], dv + (uint64_t)(t * 128), (t > 0) ? 1 : !(first)); \
  } while (0)
#define ISSUE_QK(cur)                                                                                          \
  do {                                                                                                         \
    const uint64_t dk = make_desc(sbase + (cur).s * 32768, 16, 1024, 1);                                       \
    _Pragma("unroll") for (int t = 0; t < 8; t++)                                                              \
        wgmma_rs_n128<0, 0>(S, Q[4 * t], Q[4 * t + 1], Q[4 * t + 2], Q[4 * t + 3], dk + (uint64_t)((t >> 2) * 1024 + (t & 3) * 2), t > 0); \
  } while (0)
#define EPILOGUE()                                                                                             \
  do {                                                                                                         \
    l0 += __shfl_xor_sync(0xffffffffu, l0, 1);                                                                 \
    l0 += __shfl_xor_sync(0xffffffffu, l0, 2);                                                                 \
    l1 += __shfl_xor_sync(0xffffffffu, l1, 1);                                                                 \
    l1 += __shfl_xor_sync(0xffffffffu, l1, 2);                                                                 \
    const float f0 = __fdividef(gf0, l0), f1 = __fdividef(gf1, l1);                                                                \
    bf16* o0 = g_ctx + (size_t)prev_row * KCAT + prev_h * 128 + q * 8;                                         \
    bf16* o1 = o0 + (size_t)8 * KCAT;                                                                          \
    _Pragma("unroll") for (int G = 0; G < 4; G++) {                                                            \
      st_v4(o0 + G * 32, pack_bf16(O[G * 16 + 0] * f0, O[G * 16 + 1] * f0), pack_bf16(O[G * 16 + 4] * f0, O[G * 16 + 5] * f0), \
            pack_bf16(O[G * 16 + 8] * f0, O[G * 16 + 9] * f0), pack_bf16(O[G * 16 + 12] * f0, O[G * 16 + 13] * f0)); \
      st_v4(o1 + G * 32, pack_bf16(O[G * 16 + 2] * f1, O[G * 16 + 3] * f1), pack_bf16(O[G * 16 + 6] * f1, O[G * 16 + 7] * f1), \
            pack_bf16(O[G * 16 + 10] * f1, O[G * 16 + 11] * f1), pack_bf16(O[G * 16 + 14] * f1, O[G * 16 + 15] * f1)); \
    }                                                                                                          \
  } while (0)

__global__ void __cluster_dims__(2, 1, 1) __launch_bounds__(384, 1)
fused_kernel(const __grid_constant__ Params p, const bf16* __restrict__ x, const bf16* __restrict__ gate_w, bf16* __restrict__ out) {
  extern __shared__ uint8_t smem_raw[];
  const uint32_t sbase = (smem_u32(smem_raw) + 1023) & ~1023u;
  const uint32_t sB = sbase, sA = sbase + K1_BST * 16384, sBar = sbase + SMEM_DATA;
  const uint32_t bAf = sBar, bAe = sBar + 64, bBf = sBar + 128, bBe = sBar + 176, bL = sBar + 224, bS = sBar + 232, bL2 = sBar + 240, sL = sA + 32768;
  const uint32_t bF = sBar + 256, bE = sBar + 320, bT = sBar + 384, sTick = sBar + 400, sItem = sBar + 416, bS2 = sBar + 448, bR = sBar + 456, bLast = sBar + 464;
  const uint32_t b3F = sBar + 512, b3E = sBar + 544, sGate = sBar + 576;
  const int tid = threadIdx.x, warp_g = __shfl_sync(0xffffffffu, tid >> 5, 0), lane = tid & 31;
  const uint32_t rank = cluster_rank();
  const int cl = blockIdx.x >> 1;
  TSM(0);
  if (tid == 0) {
    for (int i = 0; i < 8; i++) { mbar_init(bAf + i * 8, 1); mbar_init(bAe + i * 8, 2); }
    for (int i = 0; i < K1_BST; i++) { mbar_init(bBf + i * 8, 1); mbar_init(bBe + i * 8, 4); }
    mbar_init(bL, 1);
    mbar_init(bL2, 1);
    mbar_init(bR, 1);
    mbar_init(bLast, 1);
    mbar_init(bS, 8);
    for (int i = 0; i < K2_NST; i++) { mbar_init(bF + i * 8, 1); mbar_init(bE + i * 8, 4); }
    mbar_init(bT, 1); mbar_init(bT + 8, 1);
    mbar_init(bS2, 8);
    for (int i = 0; i < K3_NST; i++) { mbar_init(b3F + i * 8, 1); mbar_init(b3E + i * 8, 4); }
    asm volatile("fence.mbarrier_init.release.cluster;" ::: "memory");
  }
  __syncthreads();
  cluster_sync();
  const int lr0 = blockIdx.x * 16;

  if (warp_g >= 8) {
    reg_dealloc<40>();
    if (warp_g == 8) {
      if (elect_one()) {
        uint32_t bs = 0, bph = 1, aph = 1;
#pragma unroll 1
        for (int ji = 0; ji < K1_MAXJOBS; ji++) {
          const uint32_t job = p.jobs[cl][ji];
          if (!(job & 3)) break;
          const int a_sel = (job >> 2) & 1, mpair = (job >> 3) & 7, chunk0 = (job >> 8) & 63;
          const bool newA = (job >> 14) & 1;
          const int KC = a_sel ? 9 : 8;
          const uint32_t halfbytes = 8192;
          const bool lastjob = (ji + 1 == K1_MAXJOBS) || !(p.jobs[cl][ji + 1] & 3);
          const CUtensorMap* tw = &p.tmW[(job >> 6) & 3];
          {
            const uint32_t njob = (ji + 1 < K1_MAXJOBS) ? p.jobs[cl][ji + 1] : 0;
            if (!(njob & 3) && !newA) mbar_arrive(bLast);
            if (njob & 3) {
              const int nst = ((njob >> 2) & 1) ? 18 : 16;
#pragma unroll 1
              for (int t = (cl < 64) ? (cl & 7) : 0; t < nst; t += (cl < 64) ? 8 : 1)
                tma_pf3d(&p.tmW[(njob >> 6) & 3], 0, t * 32 + rank * 16, (njob >> 8) & 63);
            }
          }
#pragma unroll 1
          for (int kc = 0; kc < KC; kc++) {
            if (kc == 8) {
              mbar_wait(bBe + bs * 8, bph);
              mbar_expect(bBf + bs * 8, 16384);
              tma2d(sB + bs * 16384, &p.tmA[1], bBf + bs * 8, 512, mpair * 256 + rank * 128);
              if (++bs == K1_BST) { bs = 0; bph ^= 1; }
            } else if (newA) {
              mbar_wait(bAe + kc * 8, aph);
              mbar_expect(bAf + kc * 8, 16384);
              tma2d(sA + ((kc + 2) & 7) * 16384, &p.tmA[a_sel], bAf + kc * 8, kc * 64, mpair * 256 + rank * 128);
              if (kc == 7 && lastjob) mbar_arrive(bLast);
            }
#pragma unroll 1
            for (int kk = 0; kk < 2; kk++) {
              mbar_wait(bBe + bs * 8, bph);
              mbar_expect(bBf + bs * 8, 2 * halfbytes);
              tma3d_mc(sB + bs * 16384 + rank * halfbytes, tw, bBf + bs * 8, 0, kc * 64 + kk * 32 + rank * 16, chunk0, 3);
              if (++bs == K1_BST) { bs = 0; bph ^= 1; }
            }
          }
          if (newA) aph ^= 1;
        }
        Cursor c{0, 0};
        int pcol = 0;
        uint32_t tick = cl, seen = 1u << (p.order[cl] >> 4);
        mbar_wait(bR, 0);
        asm volatile("fence.proxy.async.global;" ::: "memory");
#pragma unroll 1
        for (int it = 0;; it++) {
          const uint32_t item = (tick < 256) ? p.order[tick] : (K2_END | min(tick - 256, 255u));
          asm volatile("st.shared.u32 [%0], %1;" ::"r"(sItem + (it & 7) * 4), "r"(item) : "memory");
          if (item >= K2_END) break;
          const int h = item >> 3, j = item & 7;
          const int blk = 2 * j + (int)(rank ^ (it & 1));
          const int col = HA(h) * 128 + rank * 64;
          const int nb = 2 * j + 2;
          if (!((seen >> (h >> 1)) & 1)) {
            wait_flag(&g_sync[F_HP + (h >> 1)], RDY_TARGET);
            asm volatile("fence.proxy.async.global;" ::: "memory");
            seen |= 1u << (h >> 1);
          }
          mbar_wait(bE + c.s * 8, c.ph);
          mbar_expect(bF + c.s * 8, 32768);
          tma2d(sbase + c.s * 32768, &p.tmQ, bF + c.s * 8, HA(h) * 128, blk * 128);
          tma2d(sbase + c.s * 32768 + 16384, &p.tmQ, bF + c.s * 8, HA(h) * 128 + 64, blk * 128);
          c.next();
#pragma unroll 1
          for (int n = nb - 1; n >= 0; n--) {
            if (n == 0 && rank == 0) tick = atomicAdd(&g_sync[F_TICK], 1u) + NCLUSTER;
            mbar_wait(bE + c.s * 8, c.ph);
            mbar_expect(bF + c.s * 8, 32768);
            tma2d_mc(sbase + c.s * 32768 + rank * 16384, &p.tmK, bF + c.s * 8, col, n * 128, 3);
            c.next();
            if (n < nb - 1 || it > 0) {
              mbar_wait(bE + c.s * 8, c.ph);
              mbar_expect(bF + c.s * 8, 32768);
              tma2d_mc(sbase + c.s * 32768 + rank * 16384, &p.tmV, bF + c.s * 8, (n < nb - 1) ? col : pcol, (n < nb - 1) ? (n + 1) * 128 : 0, 3);
              c.next();
            }
          }
          pcol = col;
          if (rank == 0) {
            asm volatile(
                "{\n.reg .b32 a, b;\nmapa.shared::cluster.u32 a, %0, 1;\nmapa.shared::cluster.u32 b, %1, 1;\n"
                "st.async.shared::cluster.mbarrier::complete_tx::bytes.u32 [a], %2, [b];\n}" ::"r"(sTick + (it & 1) * 4),
                "r"(bT + (it & 1) * 8), "r"(tick) : "memory");
          } else {
            mbar_expect(bT + (it & 1) * 8, 4);
            mbar_wait(bT + (it & 1) * 8, (it >> 1) & 1);
            tick = lds32(sTick + (it & 1) * 4);
          }
        }
        mbar_wait(bE + c.s * 8, c.ph);
        mbar_expect(bF + c.s * 8, 32768);
        tma2d_mc(sbase + c.s * 32768 + rank * 16384, &p.tmV, bF + c.s * 8, pcol, 0, 3);
        const uint32_t unit = tick - 256;
        if (unit < 64) {
          const int mp = 7 - (int)(unit >> 3), mblk = mp * 2 + rank, nhalf = (unit >> 2) & 1, ks = unit & 3;
          const int k0 = ks * 18, k1 = (ks == 3) ? 73 : k0 + 18;
          uint32_t s = 0, ph = 0;
#pragma unroll 1
          for (int k = k0; k < k1; k++) {
            mbar_wait(b3E + s * 8, ph);
            mbar_expect(b3F + s * 8, K3_STAGE);
            const uint32_t st = sbase + s * K3_STAGE;
            const int sel = (k >= 64), kr = (sel ? (k - 64) : k) * 64 + rank * 32;
            tma3d_mc(st + 16384 + rank * 16384, &p.tmO[sel], b3F + s * 8, 0, kr, nhalf * 4, 3);
            tma2d_mc(st + 49152 + rank * 2048, &p.tmOt[sel], b3F + s * 8, 512 + nhalf * 32, kr, 3);
            if (k == k0) {
              wait_flag(&g_sync[F_CTX + mp * 4 + ks], (ks == 3) ? 26 : 18);
              asm volatile("fence.proxy.async.global;" ::: "memory");
            }
            tma2d(st, &p.tmC, b3F + s * 8, k * 64, mblk * 128);
            if (++s == K3_NST) { s = 0; ph ^= 1; }
          }
        }
      }
    }
    __syncwarp();
    asm volatile("" ::: "memory");
    if (__shfl_sync(0xffffffffu, warp_g, 0) != 8) {
      if (lr0 < S_LEN) {
#pragma unroll 1
        for (int i = warp_g - 9; i < 16; i += 3) {
          const float g = gate_row(lr0 + i, lane, x, gate_w);
          if (lane == 0) asm volatile("st.shared.f32 [%0], %1;" ::"r"(sGate + i * 4), "f"(g) : "memory");
        }
        bar_arrive(3, 256 + 96);
        if (lane == 0) {
          __threadfence();
          atomicAdd(&g_sync[F_GATE], 1u);
        }
      }
      if (warp_g == 9 && lane == 0) {
#pragma unroll 1
        for (int ji = 0; ji < K1_MAXJOBS; ji++) {
          const uint32_t job = p.jobs[cl][ji];
          if (!(job & 3)) break;
          mbar_wait(bS, ji & 1);
          __threadfence();
          atomicAdd(&g_sync[(((job >> 6) & 3) == 2) ? (F_QKVA + ((job >> 3) & 7) * 2 + rank) : (F_HP + ((job >> 10) & 15))], 1u);
        }
#pragma unroll 1
        for (int it = 0;; it++) {
          mbar_wait(bS2, it & 1);
          const uint32_t item = lds32(sItem + (it & 7) * 4), nxt = lds32(sItem + ((it + 1) & 7) * 4);
          __threadfence();
          atomicAdd(&g_sync[F_CTX + (item & 7) * 4 + (item >> 3) / 9], 1u);
          if (nxt >= K2_END) break;
        }
      } else if (warp_g == 11) {
        if (lane == 0) {
          prefetch_tmap(&p.tmQ); prefetch_tmap(&p.tmK); prefetch_tmap(&p.tmV);
          wait_flag(&g_sync[F_GATE], GATE_TARGET);
          wait_flag(&g_sync[F_HP + (p.order[cl] >> 4)], RDY_TARGET);
          mbar_arrive(bR);
        }
        __syncwarp();
        bar_sync(4, 256 + 32);
        if (lane < 12) mbar_arrive_cluster(bE + (4 + lane % 3) * 8, (lane / 3) & 1);
      } else if (warp_g == 10 && lr0 < S_LEN) {
        if (elect_one()) {
          prefetch_tmap(&p.tmL[0]); prefetch_tmap(&p.tmL[1]);
          uint32_t aph = 1;
#pragma unroll 1
          for (int ji = 0; ji < K1_MAXJOBS; ji++) aph ^= (p.jobs[cl][ji] >> 14) & 1;
          wait_flag(&g_sync[F_QKVA + (lr0 >> 7)], K1_FLAG_TARGET);
          wait_flag(&g_sync[F_QKVA + (max(lr0 - 14, 0) >> 7)], K1_FLAG_TARGET);
          asm volatile("fence.proxy.async.global;" ::: "memory");
          mbar_wait(bLast, 0);
#pragma unroll 1
          for (int kc = 0; kc < 6; kc++) {
            mbar_wait(bAe + kc * 8, aph);
            if (kc == 3) {
              mbar_expect(bL, 46 * 1152);
              tma3d(sL, &p.tmL[0], bL, 0, 9, lr0 - 14);
              tma3d(sL + 30 * 1152, &p.tmL[1], bL, 0, 0, lr0);
            }
          }
          mbar_expect(bL2, 30 * 1152);
          tma3d(sL + 46 * 1152, &p.tmL[0], bL2, 0, 18, lr0 - 14);
        }
        __syncwarp();
        bar_sync(5, 256 + 32);
        if (lane == 0) {
          __threadfence();
          atomicAdd(&g_sync[F_CTX + (lr0 >> 8) * 4 + 3], 1u);
        }
      }
    }
    __syncwarp();
    cluster_sync();
    if (warp_g == 8) {
      uint32_t v = 0;
      if (lane == 0) {
        __threadfence();
        v = atomicAdd(&g_sync[F_DONE], 1u);
      }
      if (__shfl_sync(0xffffffffu, v, 0) == 2 * NCLUSTER - 1) reinterpret_cast<uint4*>(g_sync)[lane] = make_uint4(0, 0, 0, 0);
    }
  } else {
    reg_alloc<232>();
    const int wg = warp_g >> 2, warp = warp_g & 3, q = lane & 3;
    const bool sig = (lane == 0) && (warp < 2);
    {
      K1State st{0, 0, 0, nullptr, 0, 0};
      float acc[128];
      uint32_t pk[64];
      if (wg == 0) { TS(0, 0); TSC(0, 2); }
#pragma unroll 1
      for (int ji = 0; ji < K1_MAXJOBS; ji++) {
        const uint32_t job = p.jobs[cl][ji];
        if (!(job & 3)) break;
        k1_tile(acc, pk, st, job, sA, sB, bAf, bAe, bBf, bBe, bS, wg, warp, lane, rank);
      }
#pragma unroll
      for (int i = 0; i < 4; i++)
        mbar_arrive_cluster_if(bE + i * 8, warp & 1, sig);
#pragma unroll
      for (int G = 0; G < 8; G++)
        if (G < st.png) {
          st_v4(st.pp + G * 32, pk[G * 8], pk[G * 8 + 1], pk[G * 8 + 2], pk[G * 8 + 3]);
          st_v4(st.pp + G * 32 + st.pld8, pk[G * 8 + 4], pk[G * 8 + 5], pk[G * 8 + 6], pk[G * 8 + 7]);
        }
      k1_flag(st, lane, bS);
      if (wg == 0) { TS(0, 1); TSC(0, 3); }
      if (lr0 < S_LEN) {
        const int ri = (warp_g >> 1) * 4 + (warp_g & 1) + 2, row = lr0 + ri;
        if (wg == 0) TS(1, 5);
        bar_sync(3, 256 + 96);
        const float gate0 = __uint_as_float(lds32(sGate + ri * 4 - 8)), gate1 = __uint_as_float(lds32(sGate + ri * 4));
        mbar_wait(bL, 0);
        if (wg == 0) TS(1, 6);
        local_rows2(row, ri, sL, bL2, lane, gate0, gate1);
        bar_arrive(5, 256 + 32);
      } else {
        bar_arrive(4, 256 + 32);
      }
    }
    __syncwarp();
    uint32_t item;
    {
      const int mybar = 1 + wg, otherbar = 2 - wg;
      const float cl2 = 0.08838834764831845f * 1.4426950408889634f;
      float S[64], O[64];
      uint32_t P[32], Q[32];
#pragma unroll
      for (int i = 0; i < 64; i++) { S[i] = 0.f; O[i] = 1.f; }
#pragma unroll
      for (int i = 0; i < 32; i++) P[i] = 0;
      float m0 = 0.f, m1 = 0.f, l0 = 0.f, l1 = 0.f;
      int prev_row = 0, prev_h = 0, prev_single = 0;
      Cursor c{0, 0};
      if (wg == 1) bar_arrive(1, 256);
      if (wg == 0) { TS(1, 0); TSC(1, 2); }
#pragma unroll 1
      for (int it = 0;; it++) {
        mbar_wait(bF + c.s * 8, c.ph);
        item = lds32(sItem + (it & 7) * 4);
        if (item >= K2_END) break;
        const int h = item >> 3, j = item & 7;
        const int hi = (int)(rank ^ (it & 1));
        const int nblk = 2 * j + 1 + hi;
        {
          const float gf0 = 1.f - g_gate[prev_row], gf1 = 1.f - g_gate[prev_row + 8];
          Cursor cq = c; c.next();
          {
            const int r = wg * 64 + warp * 16 + (lane & 7) + ((lane >> 3) & 1) * 8;
            const uint32_t qa = sbase + cq.s * 32768 + r * 128;
#pragma unroll
            for (int t = 0; t < 8; t++)
              ldsm_x4(Q[4 * t], Q[4 * t + 1], Q[4 * t + 2], Q[4 * t + 3], qa + (t >> 2) * 16384 + ((((t & 3) * 2 + (lane >> 4)) ^ (lane & 7)) << 4));
          }
          Cursor ck = c; c.next();
          Cursor cs0 = ck, cs1 = ck, cv = c;
          mbar_wait(bF + ck.s * 8, ck.ph);
          if (it > 0) { mbar_wait(bF + cv.s * 8, cv.ph); c.next(); }
          if (!hi) {
            ck = c; c.next();
            cs1 = c; c.next();
            mbar_wait(bF + ck.s * 8, ck.ph);
            mbar_wait(bF + cs1.s * 8, cs1.ph);
          }
          if (it == 0) BSEG(4); else BSEG(0);
          TURN_SYNC();
          wg_fence();
          ISSUE_QK(ck);
          wg_commit();
          if (it > 0) ISSUE_PV(cv, prev_single);
          wg_commit();
          TURN_ARRIVE();
          RELEASE(cq);
          if (!hi) { RELEASE(cs0); RELEASE(cs1); }
          wg_wait<1>();
          fence_regs(S);
          RELEASE(ck);
          const int r0 = wg * 64 + warp * 16 + (lane >> 2);
#pragma unroll
          for (int jj = 0; jj < 16; jj++) {
            const int cc = jj * 8 + 2 * q;
            if (cc > r0) S[jj * 4 + 0] = -INFINITY;
            if (cc + 1 > r0) S[jj * 4 + 1] = -INFINITY;
            if (cc > r0 + 8) S[jj * 4 + 2] = -INFINITY;
            if (cc + 1 > r0 + 8) S[jj * 4 + 3] = -INFINITY;
          }
          float mx0 = fmaxf(S[0], S[1]), mx1 = fmaxf(S[2], S[3]);
#pragma unroll
          for (int jj = 1; jj < 16; jj++) {
            mx0 = fmaxf(mx0, fmaxf(S[jj * 4 + 0], S[jj * 4 + 1]));
            mx1 = fmaxf(mx1, fmaxf(S[jj * 4 + 2], S[jj * 4 + 3]));
          }
          mx0 = fmaxf(mx0, __shfl_xor_sync(0xffffffffu, mx0, 1));
          mx1 = fmaxf(mx1, __shfl_xor_sync(0xffffffffu, mx1, 1));
          mx0 = fmaxf(mx0, __shfl_xor_sync(0xffffffffu, mx0, 2));
          mx1 = fmaxf(mx1, __shfl_xor_sync(0xffffffffu, mx1, 2));
          m0 = mx0; m1 = mx1;
          const float mc0 = m0 * cl2, mc1 = m1 * cl2;
          float s0 = 0.f, s1 = 0.f;
#pragma unroll
          for (int jj = 0; jj < 16; jj++) {
            S[jj * 4 + 0] = ex2(fmaf(S[jj * 4 + 0], cl2, -mc0));
            S[jj * 4 + 1] = ex2(fmaf(S[jj * 4 + 1], cl2, -mc0));
            S[jj * 4 + 2] = ex2(fmaf(S[jj * 4 + 2], cl2, -mc1));
            S[jj * 4 + 3] = ex2(fmaf(S[jj * 4 + 3], cl2, -mc1));
            s0 += S[jj * 4 + 0] + S[jj * 4 + 1];
            s1 += S[jj * 4 + 2] + S[jj * 4 + 3];
          }
          fence_regs(S);
          wg_wait<0>();
          fence_regs(O);
          fence_regs(P);
          if (it > 0) {
            RELEASE(cv);
            EPILOGUE();
            __syncwarp();
            if (lane == 0) mbar_arrive(bS2);
          }
          l0 = s0; l1 = s1;
#pragma unroll
          for (int jj = 0; jj < 16; jj++) {
            P[jj * 2 + 0] = pack_bf16(S[jj * 4 + 0], S[jj * 4 + 1]);
            P[jj * 2 + 1] = pack_bf16(S[jj * 4 + 2], S[jj * 4 + 3]);
          }
        }
        if (it == 0) BSEG(5); else BSEG(1);
#pragma unroll 1
        for (int n = 1; n < nblk; n++) {
          Cursor ck = c; c.next();
          Cursor cv = c; c.next();
          mbar_wait(bF + ck.s * 8, ck.ph);
          mbar_wait(bF + cv.s * 8, cv.ph);
          TURN_SYNC();
          wg_fence();
          ISSUE_QK(ck);
          wg_commit();
          ISSUE_PV(cv, n == 1);
          wg_commit();
          TURN_ARRIVE();
          wg_wait<1>();
          fence_regs(S);
          RELEASE(ck);
          float mx0 = fmaxf(S[0], S[1]), mx1 = fmaxf(S[2], S[3]);
#pragma unroll
          for (int jj = 1; jj < 16; jj++) {
            mx0 = fmaxf(mx0, fmaxf(S[jj * 4 + 0], S[jj * 4 + 1]));
            mx1 = fmaxf(mx1, fmaxf(S[jj * 4 + 2], S[jj * 4 + 3]));
          }
          mx0 = fmaxf(mx0, __shfl_xor_sync(0xffffffffu, mx0, 1));
          mx1 = fmaxf(mx1, __shfl_xor_sync(0xffffffffu, mx1, 1));
          mx0 = fmaxf(mx0, __shfl_xor_sync(0xffffffffu, mx0, 2));
          mx1 = fmaxf(mx1, __shfl_xor_sync(0xffffffffu, mx1, 2));
          mx0 = fmaxf(mx0, m0);
          mx1 = fmaxf(mx1, m1);
          const float sc0 = ex2((m0 - mx0) * cl2), sc1 = ex2((m1 - mx1) * cl2);
          m0 = mx0; m1 = mx1;
          const float mc0 = m0 * cl2, mc1 = m1 * cl2;
          float s0 = 0.f, s1 = 0.f;
#pragma unroll
          for (int jj = 0; jj < 16; jj++) {
            S[jj * 4 + 0] = ex2(fmaf(S[jj * 4 + 0], cl2, -mc0));
            S[jj * 4 + 1] = ex2(fmaf(S[jj * 4 + 1], cl2, -mc0));
            S[jj * 4 + 2] = ex2(fmaf(S[jj * 4 + 2], cl2, -mc1));
            S[jj * 4 + 3] = ex2(fmaf(S[jj * 4 + 3], cl2, -mc1));
            s0 += S[jj * 4 + 0] + S[jj * 4 + 1];
            s1 += S[jj * 4 + 2] + S[jj * 4 + 3];
          }
          l0 = fmaf(l0, sc0, s0);
          l1 = fmaf(l1, sc1, s1);
          fence_regs(S);
          wg_wait<0>();
          fence_regs(O);
          fence_regs(P);
          RELEASE(cv);
#pragma unroll
          for (int jj = 0; jj < 16; jj++) {
            O[jj * 4 + 0] *= sc0;
            O[jj * 4 + 1] *= sc0;
            O[jj * 4 + 2] *= sc1;
            O[jj * 4 + 3] *= sc1;
            P[jj * 2 + 0] = pack_bf16(S[jj * 4 + 0], S[jj * 4 + 1]);
            P[jj * 2 + 1] = pack_bf16(S[jj * 4 + 2], S[jj * 4 + 3]);
          }
        }
        BSEG(2);
        prev_row = (2 * j + hi) * 128 + wg * 64 + warp * 16 + (lane >> 2);
        prev_h = h;
        prev_single = (nblk == 1);
      }
      {
        const float gf0 = 1.f - g_gate[prev_row], gf1 = 1.f - g_gate[prev_row + 8];
        Cursor cv = c;
        TURN_SYNC();
        wg_fence();
        ISSUE_PV(cv, prev_single);
        wg_commit();
        if (wg == 0) TURN_ARRIVE();
        wg_wait<0>();
        fence_regs(O);
#pragma unroll
        for (int i = 0; i < K3_NST; i++)
          mbar_arrive_cluster_if(b3E + i * 8, warp & 1, sig);
        EPILOGUE();
        __syncwarp();
        if (lane == 0) mbar_arrive(bS2);
      }
      if (wg == 1) { TS(1, 1); TSC(1, 3); }
    }
    __syncwarp();
    const uint32_t unit = item & 255;
    if (unit < 64) {
      const int mblk = (7 - (int)(unit >> 3)) * 2 + rank, nhalf = (unit >> 2) & 1, ks = unit & 3;
      const int k0 = ks * 18, k1 = (ks == 3) ? 73 : k0 + 18;
      float acc[144];
      uint32_t s = 0, ph = 0, prev = 0;
      if (wg == 0) { TS(2, 0); TSC(2, 2); }
#pragma unroll 1
      for (int k = k0; k < k1; k++) {
        mbar_wait(b3F + s * 8, ph);
        const uint32_t st = sbase + s * K3_STAGE;
        const uint64_t da = make_desc(st + wg * 8192, 16, 1024, 1);
        const uint64_t db = make_desc(st + 16384, 4096, 1024, 1);
        const uint64_t dt = make_desc(st + 49152, 16, 512, 2);
        wg_fence();
#pragma unroll
        for (int t = 0; t < 4; t++) {
          const int sd = (t > 0) || (k > k0);
          wgmma_ss_n256<1, 0>(acc, da + (uint64_t)(t * 2), db + (uint64_t)((t >> 1) * 1024 + (t & 1) * 128), sd);
          wgmma_ss_n32<1, 128>(acc, da + (uint64_t)(t * 2), dt + (uint64_t)(t * 64), sd);
        }
        wg_commit();
        if (k > k0) {
          wg_wait<1>();
          if (sig) mbar_arrive_cluster(b3E + prev * 8, warp);
        }
        prev = s;
        if (++s == K3_NST) { s = 0; ph ^= 1; }
      }
      wg_wait<0>();
      fence_regs(acc);
      if (wg == 0) TS(2, 4);
      const int tile = mblk * 2 + nhalf;
      float4* wp = g_part + (size_t)((tile * 4 + ks) * 4) * 9 * 256 + tid;
#pragma unroll
      for (int d = 0; d < 4; d++) {
        if (d != ks) {
#pragma unroll
          for (int i = 0; i < 8; i++)
            __stcg(wp + (d * 9 + i) * 256, make_float4(acc[d * 32 + i * 4], acc[d * 32 + i * 4 + 1], acc[d * 32 + i * 4 + 2], acc[d * 32 + i * 4 + 3]));
          __stcg(wp + (d * 9 + 8) * 256, make_float4(acc[128 + d * 4], acc[128 + d * 4 + 1], acc[128 + d * 4 + 2], acc[128 + d * 4 + 3]));
        }
      }
      __threadfence();
      bar_sync(6, 256);
      if (wg == 0) TS(2, 5);
      if (tid == 0) {
        atomicAdd(&g_sync[F_XCH + tile], 1u);
        uint32_t v, spins = 0;
        do {
          asm volatile("ld.acquire.gpu.global.u32 %0, [%1];" : "=r"(v) : "l"(&g_sync[F_XCH + tile]) : "memory");
        } while (v < 4 && ++spins < (1u << 24));
      }
      bar_sync(6, 256);
      if (wg == 0) TS(2, 6);
      float r[36];
#pragma unroll
      for (int d = 0; d < 4; d++) {
        if (d == ks) {
#pragma unroll
          for (int i = 0; i < 32; i++) r[i] = acc[d * 32 + i];
#pragma unroll
          for (int i = 0; i < 4; i++) r[32 + i] = acc[128 + d * 4 + i];
        }
      }
#pragma unroll
      for (int sI = 1; sI < 4; sI++) {
        const int src = (ks + sI) & 3;
        const float4* rp = g_part + (size_t)(((tile * 4 + src) * 4) + ks) * 9 * 256 + tid;
#pragma unroll
        for (int i = 0; i < 9; i++) {
          const float4 v = __ldcg(rp + i * 256);
          r[i * 4] += v.x; r[i * 4 + 1] += v.y; r[i * 4 + 2] += v.z; r[i * 4 + 3] += v.w;
        }
      }
      const int row = mblk * 128 + wg * 64 + warp * 16 + (lane >> 2);
      bf16* o0 = out + (size_t)row * DM + nhalf * 256 + ks * 64 + 8 * q;
#pragma unroll
      for (int G = 0; G < 2; G++) {
        uint32_t a0 = pack_bf16(r[G * 16], r[G * 16 + 1]), a1 = pack_bf16(r[G * 16 + 4], r[G * 16 + 5]);
        uint32_t a2 = pack_bf16(r[G * 16 + 8], r[G * 16 + 9]), a3 = pack_bf16(r[G * 16 + 12], r[G * 16 + 13]);
        uint32_t b0 = pack_bf16(r[G * 16 + 2], r[G * 16 + 3]), b1 = pack_bf16(r[G * 16 + 6], r[G * 16 + 7]);
        uint32_t b2 = pack_bf16(r[G * 16 + 10], r[G * 16 + 11]), b3 = pack_bf16(r[G * 16 + 14], r[G * 16 + 15]);
        quad_transpose(a0, a1, a2, a3, q);
        quad_transpose(b0, b1, b2, b3, q);
        st_v4(o0 + G * 32, a0, a1, a2, a3);
        st_v4(o0 + 8 * DM + G * 32, b0, b1, b2, b3);
      }
      {
        uint32_t t0 = pack_bf16(r[32], r[33]), t1 = pack_bf16(r[34], r[35]), t2 = 0, t3 = 0;
        quad_transpose(t0, t1, t2, t3, q);
        if (q < 2) st_v4(out + (size_t)(row + q * 8) * DM + 512 + nhalf * 32 + ks * 8, t0, t1, t2, t3);
      }
    }
    if (wg == 0) { TS(2, 1); TSC(2, 3); }
    cluster_sync();
  }
}

typedef CUresult (*EncFn)(CUtensorMap*, CUtensorMapDataType, cuuint32_t, void*, const cuuint64_t*, const cuuint64_t*, const cuuint32_t*,
                          const cuuint32_t*, CUtensorMapInterleave, CUtensorMapSwizzle, CUtensorMapL2promotion, CUtensorMapFloatOOBfill);

static void enc2d(EncFn enc, CUtensorMap* m, const void* ptr, uint64_t cols, uint64_t rows, uint32_t bc, uint32_t br,
                  CUtensorMapSwizzle sw = CU_TENSOR_MAP_SWIZZLE_128B) {
  cuuint64_t gd[2] = {cols, rows}, gs[1] = {cols * 2};
  cuuint32_t bx[2] = {bc, br}, es[2] = {1, 1};
  enc(m, CU_TENSOR_MAP_DATA_TYPE_BFLOAT16, 2, const_cast<void*>(ptr), gd, gs, bx, es, CU_TENSOR_MAP_INTERLEAVE_NONE, sw,
      CU_TENSOR_MAP_L2_PROMOTION_L2_256B, CU_TENSOR_MAP_FLOAT_OOB_FILL_NONE);
}
static void enc3d(EncFn enc, CUtensorMap* m, const void* ptr, uint64_t cols, uint64_t rows, uint32_t br, uint32_t bch) {
  cuuint64_t gd[3] = {64, rows, cols / 64}, gs[2] = {cols * 2, 128};
  cuuint32_t bx[3] = {64, br, bch}, es[3] = {1, 1, 1};
  enc(m, CU_TENSOR_MAP_DATA_TYPE_BFLOAT16, 3, const_cast<void*>(ptr), gd, gs, bx, es, CU_TENSOR_MAP_INTERLEAVE_NONE,
      CU_TENSOR_MAP_SWIZZLE_128B, CU_TENSOR_MAP_L2_PROMOTION_L2_256B, CU_TENSOR_MAP_FLOAT_OOB_FILL_NONE);
}

static void build_k1_jobs(Params& p) {
  int cnt[NCLUSTER];
  for (int c = 0; c < NCLUSTER; c++) {
    cnt[c] = 0;
    for (int i = 0; i < K1_MAXJOBS; i++) p.jobs[c][i] = 0;
  }
  auto add = [&](int c, int nch, int a_sel, int mp, int w_sel, int chunk0) {
    p.jobs[c][cnt[c]++] = (uint16_t)((nch - 1) | (a_sel << 2) | (mp << 3) | (w_sel << 6) | (chunk0 << 8));
  };
  for (int mp = 0; mp < 8; mp++) {
    for (int g = 0; g < 4; g++)
      for (int i = 0; i < 7; i++) add(g * 8 + mp, 4, 0, mp, g & 1, (2 + 2 * i + (g >> 1)) * 4);
    add(32 + mp, 3, 1, mp, 2, 24);
    add(32 + mp, 4, 1, mp, 3, 4 * 4);
    add(32 + mp, 4, 1, mp, 3, 6 * 4);
    for (int t = 0; t < 4; t++) add(32 + mp, 4, 0, mp, t & 1, (t >> 1) * 4);
    static const int q56[2][3] = {{8, 11, 13}, {9, 0, 14}}, q7[6] = {2, 3, 5, 7, 10, 12};
    for (int g = 0; g < 2; g++) {
      for (int i = 0; i < 3; i++) add((5 + g) * 8 + mp, 4, 1, mp, 2, (g * 3 + i) * 4);
      for (int i = 0; i < 3; i++) add((5 + g) * 8 + mp, 4, 1, mp, 3, q56[g][i] * 4);
    }
    for (int i = 0; i < 6; i++) add(56 + mp, 4, 1, mp, 3, q7[i] * 4);
    add(64 + mp / 4, 4, 1, mp, 3, 15 * 4);
    if (mp & 1) add(64 + mp / 4, 4, 1, mp, 3, 1 * 4);
    else add(56 + mp, 4, 1, mp, 3, 1 * 4);
  }
  for (int cc = 0; cc < NCLUSTER; cc++)
    for (int i = 0; i < cnt[cc]; i++) {
      const int key = p.jobs[cc][i] & 0x3C;
      if (i == 0 || (p.jobs[cc][i - 1] & 0x3C) != key) p.jobs[cc][i] |= (1 << 14);
      if (i == cnt[cc] - 1 || (p.jobs[cc][i + 1] & 0x3C) != key) p.jobs[cc][i] |= (1 << 15);
    }
}

static void build_k2_items(Params& p) {
  static const int late[7] = {11, 0, 12, 13, 14, 15, 1};
  bool used[256] = {};
  int nj[4] = {0, 0, 0, 0};
  const int cap[4] = {18, 18, 18, 12};
  for (int c = 0; c < NCLUSTER; c++) {
    const int g = c >> 3;
    int w = (g == 4 || (g == 7 && !(c & 1))) ? 3 : (g == 5 || g == 6 || g == 8) ? 2 : (c & 1);
    while (nj[w] >= cap[w]) w = (w + 1) & 3;
    const int i = nj[w]++;
    p.order[c] = (uint8_t)((4 + i) * 8 + 7 - w);
    used[p.order[c]] = true;
  }
  int n = NCLUSTER;
  for (int j = 7; j >= 5; j--)
    for (int i = 0; i < 14; i++) p.order[n++] = (uint8_t)((late[i >> 1] * 2 + (i & 1)) * 8 + j);
  for (int j = 4; j >= 0; j--)
    for (int h = 0; h < 32; h++)
      if (!used[h * 8 + j]) p.order[n++] = (uint8_t)(h * 8 + j);
}

extern "C" void kernel_launch(void* const* d_in, const int* in_sizes, int n_in, void* d_out, int out_size) {
  const bf16* x = (const bf16*)d_in[0];
  const bf16* wqkv = (const bf16*)d_in[1];
  const bf16* wo = (const bf16*)d_in[2];
  const bf16* ckv = (const bf16*)d_in[4];
  const bf16* w_q = (const bf16*)d_in[5];
  const bf16* w_uk = (const bf16*)d_in[6];
  const bf16* w_uv = (const bf16*)d_in[7];
  const bf16* w_o = (const bf16*)d_in[8];
  const bf16* gate_w = (const bf16*)d_in[9];

  EncFn enc = nullptr;
  cudaDriverEntryPointQueryResult qr;
  cudaGetDriverEntryPoint("cuTensorMapEncodeTiled", (void**)&enc, cudaEnableDefault, &qr);
  void *pQ, *pK, *pV, *pCtx, *pQA;
  cudaGetSymbolAddress(&pQ, g_Q);
  cudaGetSymbolAddress(&pQA, g_QKVA);
  cudaGetSymbolAddress(&pK, g_K);
  cudaGetSymbolAddress(&pV, g_V);
  cudaGetSymbolAddress(&pCtx, g_ctx);

  static Params p;
  enc2d(enc, &p.tmA[0], ckv, DC, S_LEN, 64, 128);
  enc2d(enc, &p.tmA[1], x, DM, S_LEN, 64, 128);
  enc3d(enc, &p.tmW[0], w_uk, HDIM, DC, 16, 4);
  enc3d(enc, &p.tmW[1], w_uv, HDIM, DC, 16, 4);
  enc3d(enc, &p.tmW[2], wqkv, NQKVA, DM, 16, 4);
  enc3d(enc, &p.tmW[3], w_q, HDIM, DM, 16, 4);
  build_k1_jobs(p);
  enc2d(enc, &p.tmQ, pQ, HDIM, S_LEN, 64, 128);
  enc2d(enc, &p.tmK, pK, HDIM, S_LEN, 64, 128);
  enc2d(enc, &p.tmV, pV, HDIM, S_LEN, 64, 128);
  build_k2_items(p);
  for (int i = 0; i < 2; i++) {
    cuuint64_t gd[3] = {64, 27, S_LEN}, gs[2] = {128, NQKVA * 2};
    cuuint32_t bx[3] = {64, 9, i ? 16u : 30u}, es[3] = {1, 1, 1};
    enc(&p.tmL[i], CU_TENSOR_MAP_DATA_TYPE_BFLOAT16, 3, pQA, gd, gs, bx, es, CU_TENSOR_MAP_INTERLEAVE_NONE, CU_TENSOR_MAP_SWIZZLE_NONE,
        CU_TENSOR_MAP_L2_PROMOTION_L2_256B, CU_TENSOR_MAP_FLOAT_OOB_FILL_NONE);
  }
  enc2d(enc, &p.tmC, pCtx, KCAT, S_LEN, 64, 128);
  enc3d(enc, &p.tmO[0], w_o, DM, HDIM, 32, 4);
  enc3d(enc, &p.tmO[1], wo, DM, DM, 32, 4);
  enc2d(enc, &p.tmOt[0], w_o, DM, HDIM, 32, 32, CU_TENSOR_MAP_SWIZZLE_64B);
  enc2d(enc, &p.tmOt[1], wo, DM, DM, 32, 32, CU_TENSOR_MAP_SWIZZLE_64B);

  cudaFuncSetAttribute(fused_kernel, cudaFuncAttributeMaxDynamicSharedMemorySize, SMEM_BYTES);
  fused_kernel<<<NCLUSTER * 2, 384, SMEM_BYTES>>>(p, x, gate_w, (bf16*)d_out);
}
```

```cpp
#include <cuda_runtime.h>
#include <cuda_bf16.h>
#include <cuda.h>
#include <stdint.h>

typedef __nv_bfloat16 bf16;

constexpr int S_LEN = 2048, DM = 576, DC = 512, HDIM = 4096, NQKVA = 1728, KCAT = 4672;
constexpr int NCLUSTER = 66;

__device__ __align__(1024) bf16 g_Q[S_LEN * HDIM];
__device__ __align__(1024) bf16 g_K[S_LEN * HDIM];
__device__ __align__(1024) bf16 g_V[S_LEN * HDIM];
__device__ __align__(1024) bf16 g_QKVA[S_LEN * NQKVA + 64];
__device__ __align__(1024) bf16 g_ctx[S_LEN * KCAT];
__device__ float g_gate[S_LEN];
__device__ __align__(1024) uint4 g_part[32 * 4 * 4 * 5 * 256];
__device__ __align__(16) unsigned int g_sync[384];
constexpr int F_QKVA = 0, F_HP = 16, F_CTX = 32, F_OA = 48, F_GATE = 96, F_TICK = 97, F_DONE = 98, F_XCH = 128;

__device__ __forceinline__ uint32_t smem_u32(const void* p) { return (uint32_t)__cvta_generic_to_shared(p); }
__device__ __forceinline__ void mbar_init(uint32_t a, uint32_t c) {
  asm volatile("mbarrier.init.shared::cta.b64 [%0], %1;" ::"r"(a), "r"(c));
}
__device__ __forceinline__ void mbar_expect(uint32_t a, uint32_t b) {
  asm volatile("mbarrier.arrive.expect_tx.shared::cta.b64 _, [%0], %1;" ::"r"(a), "r"(b) : "memory");
}
#define TS(k, i)
#define TSC(k, i)
#define TSM(k)
#define BSEG(i)
#define SPIN_LIMIT "4194304"
__device__ __forceinline__ void mbar_wait(uint32_t a, uint32_t parity) {
  asm volatile(
      "{\n.reg .pred p;\n.reg .u32 n;\n"
      "mbarrier.try_wait.parity.shared::cta.b64 p, [%0], %1;\n"
      "@p bra DONE;\n"
      "mov.u32 n, 0;\n"
      "LOOP:\n"
      "mbarrier.try_wait.parity.shared::cta.b64 p, [%0], %1;\n"
      "@p bra DONE;\n"
      "add.u32 n, n, 1;\n"
      "setp.lt.u32 p, n, " SPIN_LIMIT ";\n"
      "@p bra LOOP;\n"
      "DONE:\n}" ::"r"(a), "r"(parity) : "memory");
}
__device__ __forceinline__ void mbar_arrive(uint32_t a) {
  asm volatile("mbarrier.arrive.shared::cta.b64 _, [%0];" ::"r"(a) : "memory");
}
__device__ __forceinline__ void mbar_arrive_cluster(uint32_t a, uint32_t cta) {
  asm volatile("{\n.reg .b32 r;\nmapa.shared::cluster.u32 r, %0, %1;\nmbarrier.arrive.shared::cluster.b64 _, [r];\n}" ::"r"(a),
               "r"(cta) : "memory");
}
__device__ __forceinline__ void mbar_arrive_cluster_if(uint32_t a, uint32_t cta, bool pred) {
  asm volatile("{\n.reg .b32 r;\n.reg .pred p;\nsetp.ne.u32 p, %2, 0;\nmapa.shared::cluster.u32 r, %0, %1;\n@p mbarrier.arrive.shared::cluster.b64 _, [r];\n}" ::"r"(a),
               "r"(cta), "r"((uint32_t)pred) : "memory");
}
__device__ __forceinline__ void mbar_arrive_if(uint32_t a, bool pred) {
  asm volatile("{\n.reg .pred p;\nsetp.ne.u32 p, %1, 0;\n@p mbarrier.arrive.shared::cta.b64 _, [%0];\n}" ::"r"(a), "r"((uint32_t)pred) : "memory");
}
__device__ __forceinline__ void tma2d(uint32_t dst, const CUtensorMap* m, uint32_t bar, int c0, int c1) {
  asm volatile("cp.async.bulk.tensor.2d.shared::cluster.global.mbarrier::complete_tx::bytes [%0], [%1, {%3, %4}], [%2];" ::"r"(dst),
               "l"(m), "r"(bar), "r"(c0), "r"(c1) : "memory");
}
__device__ __forceinline__ void tma2d_mc(uint32_t dst, const CUtensorMap* m, uint32_t bar, int c0, int c1, uint16_t mask) {
  asm volatile(
      "cp.async.bulk.tensor.2d.shared::cluster.global.mbarrier::complete_tx::bytes.multicast::cluster [%0], [%1, {%3, %4}], [%2], %5;" ::"r"(dst),
      "l"(m), "r"(bar), "r"(c0), "r"(c1), "h"(mask) : "memory");
}
__device__ __forceinline__ void tma3d_mc(uint32_t dst, const CUtensorMap* m, uint32_t bar, int c0, int c1, int c2, uint16_t mask) {
  asm volatile(
      "cp.async.bulk.tensor.3d.shared::cluster.global.mbarrier::complete_tx::bytes.multicast::cluster [%0], [%1, {%3, %4, %5}], [%2], %6;" ::"r"(dst),
      "l"(m), "r"(bar), "r"(c0), "r"(c1), "r"(c2), "h"(mask) : "memory");
}
__device__ __forceinline__ void tma3d(uint32_t dst, const CUtensorMap* m, uint32_t bar, int c0, int c1, int c2) {
  asm volatile(
      "cp.async.bulk.tensor.3d.shared::cluster.global.mbarrier::complete_tx::bytes [%0], [%1, {%3, %4, %5}], [%2];" ::"r"(dst),
      "l"(m), "r"(bar), "r"(c0), "r"(c1), "r"(c2) : "memory");
}
__device__ __forceinline__ void tma_pf2d(const CUtensorMap* m, int c0, int c1) {
  asm volatile("cp.async.bulk.prefetch.tensor.2d.L2.global [%0, {%1, %2}];" ::"l"(m), "r"(c0), "r"(c1) : "memory");
}
__device__ __forceinline__ void tma_pf3d(const CUtensorMap* m, int c0, int c1, int c2) {
  asm volatile("cp.async.bulk.prefetch.tensor.3d.L2.global [%0, {%1, %2, %3}];" ::"l"(m), "r"(c0), "r"(c1), "r"(c2) : "memory");
}
__device__ __forceinline__ void prefetch_tmap(const CUtensorMap* m) {
  asm volatile("prefetch.tensormap [%0];" ::"l"(m) : "memory");
}
__device__ __forceinline__ void cluster_sync() {
  asm volatile("barrier.cluster.arrive.aligned;\nbarrier.cluster.wait.aligned;" ::: "memory");
}
__device__ __forceinline__ uint32_t cluster_rank() {
  uint32_t r;
  asm volatile("mov.u32 %0, %%cluster_ctarank;" : "=r"(r));
  return r;
}
__device__ __forceinline__ bool elect_one() {
  uint32_t p;
  asm volatile("{\n.reg .pred q;\nelect.sync _|q, 0xffffffff;\nselp.u32 %0, 1, 0, q;\n}" : "=r"(p));
  return p;
}
__device__ __forceinline__ void pdl_wait() { asm volatile("griddepcontrol.wait;" ::: "memory"); }
__device__ __forceinline__ void pdl_launch() { asm volatile("griddepcontrol.launch_dependents;" ::: "memory"); }
__device__ __forceinline__ void ldsm_x4(uint32_t& r0, uint32_t& r1, uint32_t& r2, uint32_t& r3, uint32_t addr) {
  asm volatile("ldmatrix.sync.aligned.m8n8.x4.shared.b16 {%0, %1, %2, %3}, [%4];" : "=r"(r0), "=r"(r1), "=r"(r2), "=r"(r3) : "r"(addr) : "memory");
}
__device__ __forceinline__ void wg_fence() { asm volatile("wgmma.fence.sync.aligned;" ::: "memory"); }
__device__ __forceinline__ void wg_commit() { asm volatile("wgmma.commit_group.sync.aligned;" ::: "memory"); }
template <int N>
__device__ __forceinline__ void wg_wait() { asm volatile("wgmma.wait_group.sync.aligned %0;" ::"n"(N) : "memory"); }
template <int N>
__device__ __forceinline__ void reg_alloc() { asm volatile("setmaxnreg.inc.sync.aligned.u32 %0;" ::"n"(N)); }
template <int N>
__device__ __forceinline__ void reg_dealloc() { asm volatile("setmaxnreg.dec.sync.aligned.u32 %0;" ::"n"(N)); }
__device__ __forceinline__ void bar_sync(int id, int n) { asm volatile("bar.sync %0, %1;" ::"r"(id), "r"(n) : "memory"); }
__device__ __forceinline__ void bar_arrive(int id, int n) { asm volatile("bar.arrive %0, %1;" ::"r"(id), "r"(n) : "memory"); }
template <int NT>
__device__ __forceinline__ void fence_regs(float (&d)[NT]) {
#pragma unroll
  for (int i = 0; i < NT; i++) asm volatile("" : "+f"(d[i])::"memory");
}
template <int NT>
__device__ __forceinline__ void fence_regs(uint32_t (&d)[NT]) {
#pragma unroll
  for (int i = 0; i < NT; i++) asm volatile("" : "+r"(d[i])::"memory");
}
__device__ __forceinline__ uint64_t make_desc(uint32_t saddr, uint32_t lbo, uint32_t sbo, uint32_t layout) {
  return (uint64_t)((saddr & 0x3FFFF) >> 4) | ((uint64_t)(lbo >> 4) << 16) | ((uint64_t)(sbo >> 4) << 32) | ((uint64_t)layout << 62);
}
__device__ __forceinline__ uint32_t pack_bf16(float lo, float hi) {
  uint32_t r;
  asm("cvt.rn.bf16x2.f32 %0, %1, %2;" : "=r"(r) : "f"(hi), "f"(lo));
  return r;
}
__device__ __forceinline__ float ex2(float x) {
  float r;
  asm("ex2.approx.ftz.f32 %0, %1;" : "=f"(r) : "f"(x));
  return r;
}
__device__ __forceinline__ void st_v4(void* p, uint32_t a, uint32_t b, uint32_t c, uint32_t d) {
#define ST_MOD ""
  asm volatile("st.global" ST_MOD ".v4.b32 [%0], {%1, %2, %3, %4};" ::"l"(p), "r"(a), "r"(b), "r"(c), "r"(d) : "memory");
}
__device__ __forceinline__ float bf_lo(uint32_t v) { return __uint_as_float(v << 16); }
__device__ __forceinline__ float bf_hi(uint32_t v) { return __uint_as_float(v & 0xFFFF0000u); }

__device__ __forceinline__ void quad_transpose(uint32_t& a0, uint32_t& a1, uint32_t& a2, uint32_t& a3, int q) {
  const bool o1 = q & 1, o2 = q & 2;
  uint32_t t0 = o1 ? a0 : a1, t1 = o1 ? a2 : a3;
  t0 = __shfl_xor_sync(0xffffffffu, t0, 1);
  t1 = __shfl_xor_sync(0xffffffffu, t1, 1);
  if (o1) { a0 = t0; a2 = t1; } else { a1 = t0; a3 = t1; }
  t0 = o2 ? a0 : a2;
  t1 = o2 ? a1 : a3;
  t0 = __shfl_xor_sync(0xffffffffu, t0, 2);
  t1 = __shfl_xor_sync(0xffffffffu, t1, 2);
  if (o2) { a0 = t0; a1 = t1; } else { a2 = t0; a3 = t1; }
}

template<int TB, int OFF, int NT>
__device__ __forceinline__ void wgmma_ss_n256(float (&d)[NT], uint64_t da, uint64_t db, int scale_d) {
  asm volatile("{\n.reg .pred p;\nsetp.ne.b32 p, %130, 0;\n"
    "wgmma.mma_async.sync.aligned.m64n256k16.f32.bf16.bf16 {%0, %1, %2, %3, %4, %5, %6, %7, %8, %9, %10, %11, %12, %13, %14, %15, %16, %17, %18, %19, %20, %21, %22, %23, %24, %25, %26, %27, %28, %29, %30, %31, %32, %33, %34, %35, %36, %37, %38, %39, %40, %41, %42, %43, %44, %45, %46, %47, %48, %49, %50, %51, %52, %53, %54, %55, %56, %57, %58, %59, %60, %61, %62, %63, %64, %65, %66, %67, %68, %69, %70, %71, %72, %73, %74, %75, %76, %77, %78, %79, %80, %81, %82, %83, %84, %85, %86, %87, %88, %89, %90, %91, %92, %93, %94, %95, %96, %97, %98, %99, %100, %101, %102, %103, %104, %105, %106, %107, %108, %109, %110, %111, %112, %113, %114, %115, %116, %117, %118, %119, %120, %121, %122, %123, %124, %125, %126, %127}, %128, %129, p, 1, 1, 0, %131;\n}\n"
    : "+f"(d[OFF+0]), "+f"(d[OFF+1]), "+f"(d[OFF+2]), "+f"(d[OFF+3]), "+f"(d[OFF+4]), "+f"(d[OFF+5]), "+f"(d[OFF+6]), "+f"(d[OFF+7]), "+f"(d[OFF+8]), "+f"(d[OFF+9]), "+f"(d[OFF+10]), "+f"(d[OFF+11]), "+f"(d[OFF+12]), "+f"(d[OFF+13]), "+f"(d[OFF+14]), "+f"(d[OFF+15]), "+f"(d[OFF+16]), "+f"(d[OFF+17]), "+f"(d[OFF+18]), "+f"(d[OFF+19]), "+f"(d[OFF+20]), "+f"(d[OFF+21]), "+f"(d[OFF+22]), "+f"(d[OFF+23]), "+f"(d[OFF+24]), "+f"(d[OFF+25]), "+f"(d[OFF+26]), "+f"(d[OFF+27]), "+f"(d[OFF+28]), "+f"(d[OFF+29]), "+f"(d[OFF+30]), "+f"(d[OFF+31]), "+f"(d[OFF+32]), "+f"(d[OFF+33]), "+f"(d[OFF+34]), "+f"(d[OFF+35]), "+f"(d[OFF+36]), "+f"(d[OFF+37]), "+f"(d[OFF+38]), "+f"(d[OFF+39]), "+f"(d[OFF+40]), "+f"(d[OFF+41]), "+f"(d[OFF+42]), "+f"(d[OFF+43]), "+f"(d[OFF+44]), "+f"(d[OFF+45]), "+f"(d[OFF+46]), "+f"(d[OFF+47]), "+f"(d[OFF+48]), "+f"(d[OFF+49]), "+f"(d[OFF+50]), "+f"(d[OFF+51]), "+f"(d[OFF+52]), "+f"(d[OFF+53]), "+f"(d[OFF+54]), "+f"(d[OFF+55]), "+f"(d[OFF+56]), "+f"(d[OFF+57]), "+f"(d[OFF+58]), "+f"(d[OFF+59]), "+f"(d[OFF+60]), "+f"(d[OFF+61]), "+f"(d[OFF+62]), "+f"(d[OFF+63]), "+f"(d[OFF+64]), "+f"(d[OFF+65]), "+f"(d[OFF+66]), "+f"(d[OFF+67]), "+f"(d[OFF+68]), "+f"(d[OFF+69]), "+f"(d[OFF+70]), "+f"(d[OFF+71]), "+f"(d[OFF+72]), "+f"(d[OFF+73]), "+f"(d[OFF+74]), "+f"(d[OFF+75]), "+f"(d[OFF+76]), "+f"(d[OFF+77]), "+f"(d[OFF+78]), "+f"(d[OFF+79]), "+f"(d[OFF+80]), "+f"(d[OFF+81]), "+f"(d[OFF+82]), "+f"(d[OFF+83]), "+f"(d[OFF+84]), "+f"(d[OFF+85]), "+f"(d[OFF+86]), "+f"(d[OFF+87]), "+f"(d[OFF+88]), "+f"(d[OFF+89]), "+f"(d[OFF+90]), "+f"(d[OFF+91]), "+f"(d[OFF+92]), "+f"(d[OFF+93]), "+f"(d[OFF+94]), "+f"(d[OFF+95]), "+f"(d[OFF+96]), "+f"(d[OFF+97]), "+f"(d[OFF+98]), "+f"(d[OFF+99]), "+f"(d[OFF+100]), "+f"(d[OFF+101]), "+f"(d[OFF+102]), "+f"(d[OFF+103]), "+f"(d[OFF+104]), "+f"(d[OFF+105]), "+f"(d[OFF+106]), "+f"(d[OFF+107]), "+f"(d[OFF+108]), "+f"(d[OFF+109]), "+f"(d[OFF+110]), "+f"(d[OFF+111]), "+f"(d[OFF+112]), "+f"(d[OFF+113]), "+f"(d[OFF+114]), "+f"(d[OFF+115]), "+f"(d[OFF+116]), "+f"(d[OFF+117]), "+f"(d[OFF+118]), "+f"(d[OFF+119]), "+f"(d[OFF+120]), "+f"(d[OFF+121]), "+f"(d[OFF+122]), "+f"(d[OFF+123]), "+f"(d[OFF+124]), "+f"(d[OFF+125]), "+f"(d[OFF+126]), "+f"(d[OFF+127])
    : "l"(da), "l"(db), "r"(scale_d), "n"(TB));
}
template<int TB, int OFF, int NT>
__device__ __forceinline__ void wgmma_ss_n192(float (&d)[NT], uint64_t da, uint64_t db, int scale_d) {
  asm volatile("{\n.reg .pred p;\nsetp.ne.b32 p, %98, 0;\n"
    "wgmma.mma_async.sync.aligned.m64n192k16.f32.bf16.bf16 {%0, %1, %2, %3, %4, %5, %6, %7, %8, %9, %10, %11, %12, %13, %14, %15, %16, %17, %18, %19, %20, %21, %22, %23, %24, %25, %26, %27, %28, %29, %30, %31, %32, %33, %34, %35, %36, %37, %38, %39, %40, %41, %42, %43, %44, %45, %46, %47, %48, %49, %50, %51, %52, %53, %54, %55, %56, %57, %58, %59, %60, %61, %62, %63, %64, %65, %66, %67, %68, %69, %70, %71, %72, %73, %74, %75, %76, %77, %78, %79, %80, %81, %82, %83, %84, %85, %86, %87, %88, %89, %90, %91, %92, %93, %94, %95}, %96, %97, p, 1, 1, 0, %99;\n}\n"
    : "+f"(d[OFF+0]), "+f"(d[OFF+1]), "+f"(d[OFF+2]), "+f"(d[OFF+3]), "+f"(d[OFF+4]), "+f"(d[OFF+5]), "+f"(d[OFF+6]), "+f"(d[OFF+7]), "+f"(d[OFF+8]), "+f"(d[OFF+9]), "+f"(d[OFF+10]), "+f"(d[OFF+11]), "+f"(d[OFF+12]), "+f"(d[OFF+13]), "+f"(d[OFF+14]), "+f"(d[OFF+15]), "+f"(d[OFF+16]), "+f"(d[OFF+17]), "+f"(d[OFF+18]), "+f"(d[OFF+19]), "+f"(d[OFF+20]), "+f"(d[OFF+21]), "+f"(d[OFF+22]), "+f"(d[OFF+23]), "+f"(d[OFF+24]), "+f"(d[OFF+25]), "+f"(d[OFF+26]), "+f"(d[OFF+27]), "+f"(d[OFF+28]), "+f"(d[OFF+29]), "+f"(d[OFF+30]), "+f"(d[OFF+31]), "+f"(d[OFF+32]), "+f"(d[OFF+33]), "+f"(d[OFF+34]), "+f"(d[OFF+35]), "+f"(d[OFF+36]), "+f"(d[OFF+37]), "+f"(d[OFF+38]), "+f"(d[OFF+39]), "+f"(d[OFF+40]), "+f"(d[OFF+41]), "+f"(d[OFF+42]), "+f"(d[OFF+43]), "+f"(d[OFF+44]), "+f"(d[OFF+45]), "+f"(d[OFF+46]), "+f"(d[OFF+47]), "+f"(d[OFF+48]), "+f"(d[OFF+49]), "+f"(d[OFF+50]), "+f"(d[OFF+51]), "+f"(d[OFF+52]), "+f"(d[OFF+53]), "+f"(d[OFF+54]), "+f"(d[OFF+55]), "+f"(d[OFF+56]), "+f"(d[OFF+57]), "+f"(d[OFF+58]), "+f"(d[OFF+59]), "+f"(d[OFF+60]), "+f"(d[OFF+61]), "+f"(d[OFF+62]), "+f"(d[OFF+63]), "+f"(d[OFF+64]), "+f"(d[OFF+65]), "+f"(d[OFF+66]), "+f"(d[OFF+67]), "+f"(d[OFF+68]), "+f"(d[OFF+69]), "+f"(d[OFF+70]), "+f"(d[OFF+71]), "+f"(d[OFF+72]), "+f"(d[OFF+73]), "+f"(d[OFF+74]), "+f"(d[OFF+75]), "+f"(d[OFF+76]), "+f"(d[OFF+77]), "+f"(d[OFF+78]), "+f"(d[OFF+79]), "+f"(d[OFF+80]), "+f"(d[OFF+81]), "+f"(d[OFF+82]), "+f"(d[OFF+83]), "+f"(d[OFF+84]), "+f"(d[OFF+85]), "+f"(d[OFF+86]), "+f"(d[OFF+87]), "+f"(d[OFF+88]), "+f"(d[OFF+89]), "+f"(d[OFF+90]), "+f"(d[OFF+91]), "+f"(d[OFF+92]), "+f"(d[OFF+93]), "+f"(d[OFF+94]), "+f"(d[OFF+95])
    : "l"(da), "l"(db), "r"(scale_d), "n"(TB));
}
template<int TB, int OFF, int NT>
__device__ __forceinline__ void wgmma_ss_n128(float (&d)[NT], uint64_t da, uint64_t db, int scale_d) {
  asm volatile("{\n.reg .pred p;\nsetp.ne.b32 p, %66, 0;\n"
    "wgmma.mma_async.sync.aligned.m64n128k16.f32.bf16.bf16 {%0, %1, %2, %3, %4, %5, %6, %7, %8, %9, %10, %11, %12, %13, %14, %15, %16, %17, %18, %19, %20, %21, %22, %23, %24, %25, %26, %27, %28, %29, %30, %31, %32, %33, %34, %35, %36, %37, %38, %39, %40, %41, %42, %43, %44, %45, %46, %47, %48, %49, %50, %51, %52, %53, %54, %55, %56, %57, %58, %59, %60, %61, %62, %63}, %64, %65, p, 1, 1, 0, %67;\n}\n"
    : "+f"(d[OFF+0]), "+f"(d[OFF+1]), "+f"(d[OFF+2]), "+f"(d[OFF+3]), "+f"(d[OFF+4]), "+f"(d[OFF+5]), "+f"(d[OFF+6]), "+f"(d[OFF+7]), "+f"(d[OFF+8]), "+f"(d[OFF+9]), "+f"(d[OFF+10]), "+f"(d[OFF+11]), "+f"(d[OFF+12]), "+f"(d[OFF+13]), "+f"(d[OFF+14]), "+f"(d[OFF+15]), "+f"(d[OFF+16]), "+f"(d[OFF+17]), "+f"(d[OFF+18]), "+f"(d[OFF+19]), "+f"(d[OFF+20]), "+f"(d[OFF+21]), "+f"(d[OFF+22]), "+f"(d[OFF+23]), "+f"(d[OFF+24]), "+f"(d[OFF+25]), "+f"(d[OFF+26]), "+f"(d[OFF+27]), "+f"(d[OFF+28]), "+f"(d[OFF+29]), "+f"(d[OFF+30]), "+f"(d[OFF+31]), "+f"(d[OFF+32]), "+f"(d[OFF+33]), "+f"(d[OFF+34]), "+f"(d[OFF+35]), "+f"(d[OFF+36]), "+f"(d[OFF+37]), "+f"(d[OFF+38]), "+f"(d[OFF+39]), "+f"(d[OFF+40]), "+f"(d[OFF+41]), "+f"(d[OFF+42]), "+f"(d[OFF+43]), "+f"(d[OFF+44]), "+f"(d[OFF+45]), "+f"(d[OFF+46]), "+f"(d[OFF+47]), "+f"(d[OFF+48]), "+f"(d[OFF+49]), "+f"(d[OFF+50]), "+f"(d[OFF+51]), "+f"(d[OFF+52]), "+f"(d[OFF+53]), "+f"(d[OFF+54]), "+f"(d[OFF+55]), "+f"(d[OFF+56]), "+f"(d[OFF+57]), "+f"(d[OFF+58]), "+f"(d[OFF+59]), "+f"(d[OFF+60]), "+f"(d[OFF+61]), "+f"(d[OFF+62]), "+f"(d[OFF+63])
    : "l"(da), "l"(db), "r"(scale_d), "n"(TB));
}
template<int TB, int OFF, int NT>
__device__ __forceinline__ void wgmma_ss_n32(float (&d)[NT], uint64_t da, uint64_t db, int scale_d) {
  asm volatile("{\n.reg .pred p;\nsetp.ne.b32 p, %18, 0;\n"
    "wgmma.mma_async.sync.aligned.m64n32k16.f32.bf16.bf16 {%0, %1, %2, %3, %4, %5, %6, %7, %8, %9, %10, %11, %12, %13, %14, %15}, %16, %17, p, 1, 1, 0, %19;\n}\n"
    : "+f"(d[OFF+0]), "+f"(d[OFF+1]), "+f"(d[OFF+2]), "+f"(d[OFF+3]), "+f"(d[OFF+4]), "+f"(d[OFF+5]), "+f"(d[OFF+6]), "+f"(d[OFF+7]), "+f"(d[OFF+8]), "+f"(d[OFF+9]), "+f"(d[OFF+10]), "+f"(d[OFF+11]), "+f"(d[OFF+12]), "+f"(d[OFF+13]), "+f"(d[OFF+14]), "+f"(d[OFF+15])
    : "l"(da), "l"(db), "r"(scale_d), "n"(TB));
}
template<int TB, int OFF, int NT>
__device__ __forceinline__ void wgmma_rs_n128(float (&d)[NT], uint32_t a0, uint32_t a1, uint32_t a2, uint32_t a3, uint64_t db, int scale_d) {
  asm volatile("{\n.reg .pred p;\nsetp.ne.b32 p, %69, 0;\n"
    "wgmma.mma_async.sync.aligned.m64n128k16.f32.bf16.bf16 {%0, %1, %2, %3, %4, %5, %6, %7, %8, %9, %10, %11, %12, %13, %14, %15, %16, %17, %18, %19, %20, %21, %22, %23, %24, %25, %26, %27, %28, %29, %30, %31, %32, %33, %34, %35, %36, %37, %38, %39, %40, %41, %42, %43, %44, %45, %46, %47, %48, %49, %50, %51, %52, %53, %54, %55, %56, %57, %58, %59, %60, %61, %62, %63}, {%64, %65, %66, %67}, %68, p, 1, 1, %70;\n}\n"
    : "+f"(d[OFF+0]), "+f"(d[OFF+1]), "+f"(d[OFF+2]), "+f"(d[OFF+3]), "+f"(d[OFF+4]), "+f"(d[OFF+5]), "+f"(d[OFF+6]), "+f"(d[OFF+7]), "+f"(d[OFF+8]), "+f"(d[OFF+9]), "+f"(d[OFF+10]), "+f"(d[OFF+11]), "+f"(d[OFF+12]), "+f"(d[OFF+13]), "+f"(d[OFF+14]), "+f"(d[OFF+15]), "+f"(d[OFF+16]), "+f"(d[OFF+17]), "+f"(d[OFF+18]), "+f"(d[OFF+19]), "+f"(d[OFF+20]), "+f"(d[OFF+21]), "+f"(d[OFF+22]), "+f"(d[OFF+23]), "+f"(d[OFF+24]), "+f"(d[OFF+25]), "+f"(d[OFF+26]), "+f"(d[OFF+27]), "+f"(d[OFF+28]), "+f"(d[OFF+29]), "+f"(d[OFF+30]), "+f"(d[OFF+31]), "+f"(d[OFF+32]), "+f"(d[OFF+33]), "+f"(d[OFF+34]), "+f"(d[OFF+35]), "+f"(d[OFF+36]), "+f"(d[OFF+37]), "+f"(d[OFF+38]), "+f"(d[OFF+39]), "+f"(d[OFF+40]), "+f"(d[OFF+41]), "+f"(d[OFF+42]), "+f"(d[OFF+43]), "+f"(d[OFF+44]), "+f"(d[OFF+45]), "+f"(d[OFF+46]), "+f"(d[OFF+47]), "+f"(d[OFF+48]), "+f"(d[OFF+49]), "+f"(d[OFF+50]), "+f"(d[OFF+51]), "+f"(d[OFF+52]), "+f"(d[OFF+53]), "+f"(d[OFF+54]), "+f"(d[OFF+55]), "+f"(d[OFF+56]), "+f"(d[OFF+57]), "+f"(d[OFF+58]), "+f"(d[OFF+59]), "+f"(d[OFF+60]), "+f"(d[OFF+61]), "+f"(d[OFF+62]), "+f"(d[OFF+63])
    : "r"(a0), "r"(a1), "r"(a2), "r"(a3), "l"(db), "r"(scale_d), "n"(TB));
}
template<int TB, int OFF, int NT>
__device__ __forceinline__ void wgmma_rs_n64(float (&d)[NT], uint32_t a0, uint32_t a1, uint32_t a2, uint32_t a3, uint64_t db, int scale_d) {
  asm volatile("{\n.reg .pred p;\nsetp.ne.b32 p, %37, 0;\n"
    "wgmma.mma_async.sync.aligned.m64n64k16.f32.bf16.bf16 {%0, %1, %2, %3, %4, %5, %6, %7, %8, %9, %10, %11, %12, %13, %14, %15, %16, %17, %18, %19, %20, %21, %22, %23, %24, %25, %26, %27, %28, %29, %30, %31}, {%32, %33, %34, %35}, %36, p, 1, 1, %38;\n}\n"
    : "+f"(d[OFF+0]), "+f"(d[OFF+1]), "+f"(d[OFF+2]), "+f"(d[OFF+3]), "+f"(d[OFF+4]), "+f"(d[OFF+5]), "+f"(d[OFF+6]), "+f"(d[OFF+7]), "+f"(d[OFF+8]), "+f"(d[OFF+9]), "+f"(d[OFF+10]), "+f"(d[OFF+11]), "+f"(d[OFF+12]), "+f"(d[OFF+13]), "+f"(d[OFF+14]), "+f"(d[OFF+15]), "+f"(d[OFF+16]), "+f"(d[OFF+17]), "+f"(d[OFF+18]), "+f"(d[OFF+19]), "+f"(d[OFF+20]), "+f"(d[OFF+21]), "+f"(d[OFF+22]), "+f"(d[OFF+23]), "+f"(d[OFF+24]), "+f"(d[OFF+25]), "+f"(d[OFF+26]), "+f"(d[OFF+27]), "+f"(d[OFF+28]), "+f"(d[OFF+29]), "+f"(d[OFF+30]), "+f"(d[OFF+31])
    : "r"(a0), "r"(a1), "r"(a2), "r"(a3), "l"(db), "r"(scale_d), "n"(TB));
}

__device__ __forceinline__ void wait_flag(const unsigned int* f, uint32_t target) {
  uint32_t v;
#pragma unroll 1
  for (uint32_t spins = 0; spins < (1u << 22); spins++) {
    asm volatile("ld.acquire.gpu.global.u32 %0, [%1];" : "=r"(v) : "l"(f) : "memory");
    if (v >= target) break;
    __nanosleep(100);
  }
}
__device__ __forceinline__ uint32_t lds32(uint32_t a) {
  uint32_t v;
  asm volatile("ld.shared.u32 %0, [%1];" : "=r"(v) : "r"(a) : "memory");
  return v;
}
__device__ __forceinline__ float gate_row(int row, int lane, const bf16* __restrict__ x, const bf16* __restrict__ gate_w) {
  const uint32_t* xr = reinterpret_cast<const uint32_t*>(x + (size_t)row * DM);
  const uint32_t* gw2 = reinterpret_cast<const uint32_t*>(gate_w);
  float gs = 0.f;
#pragma unroll
  for (int i = 0; i < 9; i++) {
    const uint32_t a = __ldg(xr + lane + 32 * i), b = __ldg(gw2 + lane + 32 * i);
    gs = fmaf(bf_lo(a), bf_lo(b), gs);
    gs = fmaf(bf_hi(a), bf_hi(b), gs);
  }
#pragma unroll
  for (int o = 16; o; o >>= 1) gs += __shfl_xor_sync(0xffffffffu, gs, o);
  const float g = 1.f / (1.f + __expf(-gs));
  if (lane == 0) g_gate[row] = g;
  return g;
}
#define LA_UNROLL 1
__device__ __forceinline__ void local_rows2(int rb, int ri, uint32_t sL, uint32_t bL2, int lane, float ga, float gb) {
  const float scale_l2 = 0.23570226039551584f * 1.4426950408889634f;
  constexpr int U = LA_UNROLL;
  const uint32_t sq = sL + (30 + ri) * 1152;
  const uint32_t kb = sL + (14 + ri) * 1152 + lane * 36;
  float ma = -INFINITY, mb = -INFINITY;
  {
    float qa[18], qb[18];
#pragma unroll
    for (int i = 0; i < 9; i++) {
      const uint32_t u = lds32(sq - 2304 + lane * 36 + 4 * i), v = lds32(sq + lane * 36 + 4 * i);
      qa[2 * i] = bf_lo(u); qa[2 * i + 1] = bf_hi(u);
      qb[2 * i] = bf_lo(v); qb[2 * i + 1] = bf_hi(v);
    }
    __syncwarp();
#pragma unroll U
    for (int t = 0; t < 9; t++) {
      const bool ok = rb - 2 * t >= 0;
      float a0 = 0.f, a1 = 0.f, b0 = 0.f, b1 = 0.f;
#pragma unroll
      for (int i = 0; i < 9; i++) {
        const uint32_t k = lds32(kb - t * 2304 + 4 * i);
        const float lo = bf_lo(k), hi = bf_hi(k);
        a0 = fmaf(qa[2 * i], lo, a0); a1 = fmaf(qa[2 * i + 1], hi, a1);
        b0 = fmaf(qb[2 * i], lo, b0); b1 = fmaf(qb[2 * i + 1], hi, b1);
      }
      a0 = (ok && t > 0) ? a0 + a1 : -INFINITY;
      b0 = (ok && t < 8) ? b0 + b1 : -INFINITY;
      ma = fmaxf(ma, a0);
      mb = fmaxf(mb, b0);
      asm volatile("st.shared.f32 [%0], %1;" ::"r"(sq - 2304 + t * 128 + lane * 4), "f"(a0) : "memory");
      asm volatile("st.shared.f32 [%0], %1;" ::"r"(sq + t * 128 + lane * 4), "f"(b0) : "memory");
    }
  }
  float oa[18], ob[18], sa = 0.f, sb = 0.f;
#pragma unroll
  for (int i = 0; i < 18; i++) { oa[i] = 0.f; ob[i] = 0.f; }
  mbar_wait(bL2, 0);
#pragma unroll U
  for (int t = 0; t < 9; t++) {
    const float wa = ex2((__uint_as_float(lds32(sq - 2304 + t * 128 + lane * 4)) - ma) * scale_l2);
    const float wb = ex2((__uint_as_float(lds32(sq + t * 128 + lane * 4)) - mb) * scale_l2);
    sa += wa;
    sb += wb;
#pragma unroll
    for (int i = 0; i < 9; i++) {
      const uint32_t v = lds32(kb + 46 * 1152 - t * 2304 + 4 * i);
      const float lo = bf_lo(v), hi = bf_hi(v);
      oa[2 * i] = fmaf(wa, lo, oa[2 * i]); oa[2 * i + 1] = fmaf(wa, hi, oa[2 * i + 1]);
      ob[2 * i] = fmaf(wb, lo, ob[2 * i]); ob[2 * i + 1] = fmaf(wb, hi, ob[2 * i + 1]);
    }
  }
  ga = __fdividef(ga, sa);
  gb = __fdividef(gb, sb);
  __syncwarp();
#pragma unroll
  for (int i = 0; i < 9; i++) {
    asm volatile("st.shared.u32 [%0], %1;" ::"r"(sq - 2304 + lane * 36 + 4 * i), "r"(pack_bf16(oa[2 * i] * ga, oa[2 * i + 1] * ga)) : "memory");
    asm volatile("st.shared.u32 [%0], %1;" ::"r"(sq + lane * 36 + 4 * i), "r"(pack_bf16(ob[2 * i] * gb, ob[2 * i + 1] * gb)) : "memory");
  }
  __syncwarp();
  uint32_t w[5][4];
#pragma unroll
  for (int t = 0; t < 5; t++) {
    const int c = min(t * 32 + lane, 143), r = c >= 72;
    asm volatile("ld.shared.v4.u32 {%0, %1, %2, %3}, [%4];" : "=r"(w[t][0]), "=r"(w[t][1]), "=r"(w[t][2]), "=r"(w[t][3])
                 : "r"(sq - 2304 + r * 2304 + (c - r * 72) * 16) : "memory");
  }
  asm volatile("fence.proxy.async.shared::cta;" ::: "memory");
  bar_arrive(4, 256 + 32);
#pragma unroll
  for (int t = 0; t < 5; t++) {
    const int c = min(t * 32 + lane, 143), r = c >= 72;
    st_v4(g_ctx + (size_t)(rb - 2 + 2 * r) * KCAT + HDIM + (c - r * 72) * 8, w[t][0], w[t][1], w[t][2], w[t][3]);
  }
}

#define K1_NST 6
constexpr int K1_BST = K1_NST;
constexpr int K1_MAXJOBS = 11;
constexpr uint32_t K1_FLAG_TARGET = 7;
constexpr uint32_t RDY_TARGET = 48;
constexpr uint32_t GATE_TARGET = 128 * 3;
struct alignas(64) Params {
  CUtensorMap tmA[2];
  CUtensorMap tmW[4];
  CUtensorMap tmQ, tmK, tmV;
  CUtensorMap tmL[2];
  CUtensorMap tmC, tmO[2], tmOt[2];
  uint16_t jobs[NCLUSTER][K1_MAXJOBS];
  uint8_t order[256];
};

struct K1State {
  uint32_t bs, bph, aph;
  bf16* pp;
  int pld8;
  int png;
};
__device__ __forceinline__ void k1_flag(const K1State& st, int lane, uint32_t bS) {
  if (st.png) {
    __syncwarp();
    if (lane == 0) mbar_arrive(bS);
  }
}

__device__ __forceinline__ void k1_tile(float (&acc)[128], uint32_t (&pk)[64], K1State& st, uint32_t job, uint32_t sA, uint32_t sB,
                                        uint32_t bAf, uint32_t bAe, uint32_t bBf, uint32_t bBe, uint32_t bS, int wg, int warp, int lane, uint32_t rank) {
  const int a_sel = (job >> 2) & 1, mpair = (job >> 3) & 7, w_sel = (job >> 6) & 3, chunk0 = (job >> 8) & 63;
  const bool newA = (job >> 14) & 1, lastA = (job >> 15) & 1;
  const bool sig = (lane == 0) && (warp < 2);
  const bool siga = lastA && (lane == 0) && (warp == 2);
  const int KC = 8 + a_sel;
  uint32_t prev_bs = 0, prev2_bs = 0, a8_bs = 0;
#pragma unroll
  for (int kc = 0; kc < 9; kc++) {
    if (kc >= KC) break;
    uint32_t abase = sA + ((kc + 2) & 7) * 16384;
    if (kc == 8) {
      mbar_wait(bBf + st.bs * 8, st.bph);
      a8_bs = st.bs;
      abase = sB + st.bs * 16384;
      if (++st.bs == K1_BST) { st.bs = 0; st.bph ^= 1; }
    } else if (newA) {
      mbar_wait(bAf + kc * 8, st.aph);
    }
    const uint64_t da = make_desc(abase + wg * 8192, 16, 1024, 1);
#pragma unroll
    for (int ks = 0; ks < 2; ks++) {
      mbar_wait(bBf + st.bs * 8, st.bph);
      const uint64_t db = make_desc(sB + st.bs * 16384, 2048, 1024, 1);
      wg_fence();
      wgmma_ss_n256<1, 0>(acc, da + (uint64_t)(ks * 4), db, (ks > 0) ? 1 : (kc > 0));
      wgmma_ss_n256<1, 0>(acc, da + (uint64_t)(ks * 4 + 2), db + (uint64_t)512, 1);
      wg_commit();
      const int PO = (kc < 8 ? kc : 0) * 8;
      wg_wait<1>();
      if (ks > 0 || kc > 0) {
        if (sig) mbar_arrive_cluster(bBe + prev_bs * 8, warp);
        if (ks == 0 && siga) mbar_arrive(bAe + (kc - 1) * 8);
      }
      if (kc < st.png) st_v4(st.pp + kc * 32 + ks * st.pld8, pk[PO + ks * 4], pk[PO + ks * 4 + 1], pk[PO + ks * 4 + 2], pk[PO + ks * 4 + 3]);
      prev_bs = st.bs;
      if (++st.bs == K1_BST) { st.bs = 0; st.bph ^= 1; }
    }
  }
  if (newA) st.aph ^= 1;
  k1_flag(st, lane, bS);
  wg_wait<0>();
  fence_regs(acc);
  if (sig) {
    mbar_arrive_cluster(bBe + prev_bs * 8, warp);
    if (a_sel) mbar_arrive_cluster(bBe + a8_bs * 8, warp);
  }
  if (siga && !a_sel) mbar_arrive(bAe + 7 * 8);
  const bool isA = (w_sel == 2);
  bf16* out = (w_sel == 0) ? g_K : (w_sel == 1) ? g_V : isA ? g_QKVA : g_Q;
  const int ld = isA ? NQKVA : HDIM;
  const int row = mpair * 256 + rank * 128 + wg * 64 + warp * 16 + (lane >> 2);
  st.pp = out + (size_t)row * ld + chunk0 * 64 + (lane & 3) * 8;
  st.pld8 = 8 * ld;
  st.png = ((job & 3) + 1) * 2;
#pragma unroll
  for (int G = 0; G < 8; G++) {
    pk[G * 8 + 0] = pack_bf16(acc[G * 16 + 0], acc[G * 16 + 1]);
    pk[G * 8 + 1] = pack_bf16(acc[G * 16 + 4], acc[G * 16 + 5]);
    pk[G * 8 + 2] = pack_bf16(acc[G * 16 + 8], acc[G * 16 + 9]);
    pk[G * 8 + 3] = pack_bf16(acc[G * 16 + 12], acc[G * 16 + 13]);
    pk[G * 8 + 4] = pack_bf16(acc[G * 16 + 2], acc[G * 16 + 3]);
    pk[G * 8 + 5] = pack_bf16(acc[G * 16 + 6], acc[G * 16 + 7]);
    pk[G * 8 + 6] = pack_bf16(acc[G * 16 + 10], acc[G * 16 + 11]);
    pk[G * 8 + 7] = pack_bf16(acc[G * 16 + 14], acc[G * 16 + 15]);
  }
  if (isA) {
#pragma unroll
    for (int G = 0; G < 16; G++) quad_transpose(pk[G * 4 + 0], pk[G * 4 + 1], pk[G * 4 + 2], pk[G * 4 + 3], lane & 3);
  }
}

#define HA(h) (h)
constexpr int K2_NST = 7;
constexpr uint32_t K2_END = 0x100;
constexpr int K3_NST = 4;
#define K3_P1 20
#define K3_P2 39
#define K3_P3 57
__device__ __forceinline__ uint32_t k3_rot(uint32_t sv) { return (0x00E9u >> (2 * sv)) & 3; }
__device__ __forceinline__ int k3_part(int i) { return (i == 0) ? 0 : (i == 1) ? K3_P1 : (i == 2) ? K3_P2 : (i == 3) ? K3_P3 : 73; }
constexpr int K3_STAGE = 16384 + 32768 + 4096;
constexpr int SMEM_DATA = 7 * 32768;
constexpr int SMEM_BYTES = SMEM_DATA + 1024 + 768;

struct Cursor {
  uint32_t s, ph;
  __device__ __forceinline__ void next() {
    if (++s == K2_NST) { s = 0; ph ^= 1; }
  }
};

#define TURN_SYNC() bar_sync(mybar, 256)
#define TURN_ARRIVE() bar_arrive(otherbar, 256)
#define RELEASE_IF(cur, cond) mbar_arrive_cluster_if(bE + (cur).s * 8, warp & 1, sig && (cond))
#define RELEASE(cur) RELEASE_IF(cur, true)
#define ISSUE_PV(cur, first)                                                                                   \
  do {                                                                                                         \
    const uint64_t dv = make_desc(sbase + (cur).s * 32768, 16384, 1024, 1);                                    \
    _Pragma("unroll") for (int t = 0; t < 8; t++)                                                              \
        wgmma_rs_n128<1, 0>(O, P[4 * t], P[4 * t + 1], P[4 * t + 2], P[4 * t + 3], dv + (uint64_t)(t * 128), (t > 0) ? 1 : !(first)); \
  } while (0)
#define ISSUE_QK(cur)                                                                                          \
  do {                                                                                                         \
    const uint64_t dk = make_desc(sbase + (cur).s * 32768, 16, 1024, 1);                                       \
    _Pragma("unroll") for (int t = 0; t < 8; t++)                                                              \
        wgmma_rs_n128<0, 0>(S, Q[4 * t], Q[4 * t + 1], Q[4 * t + 2], Q[4 * t + 3], dk + (uint64_t)((t >> 2) * 1024 + (t & 3) * 2), t > 0); \
  } while (0)
#define EPILOGUE()                                                                                             \
  do {                                                                                                         \
    l0 += __shfl_xor_sync(0xffffffffu, l0, 1);                                                                 \
    l0 += __shfl_xor_sync(0xffffffffu, l0, 2);                                                                 \
    l1 += __shfl_xor_sync(0xffffffffu, l1, 1);                                                                 \
    l1 += __shfl_xor_sync(0xffffffffu, l1, 2);                                                                 \
    const float f0 = __fdividef(gf0, l0), f1 = __fdividef(gf1, l1);                                                                \
    bf16* o0 = g_ctx + (size_t)prev_row * KCAT + prev_h * 128 + q * 8;                                         \
    bf16* o1 = o0 + (size_t)8 * KCAT;                                                                          \
    _Pragma("unroll") for (int G = 0; G < 4; G++) {                                                            \
      st_v4(o0 + G * 32, pack_bf16(O[G * 16 + 0] * f0, O[G * 16 + 1] * f0), pack_bf16(O[G * 16 + 4] * f0, O[G * 16 + 5] * f0), \
            pack_bf16(O[G * 16 + 8] * f0, O[G * 16 + 9] * f0), pack_bf16(O[G * 16 + 12] * f0, O[G * 16 + 13] * f0)); \
      st_v4(o1 + G * 32, pack_bf16(O[G * 16 + 2] * f1, O[G * 16 + 3] * f1), pack_bf16(O[G * 16 + 6] * f1, O[G * 16 + 7] * f1), \
            pack_bf16(O[G * 16 + 10] * f1, O[G * 16 + 11] * f1), pack_bf16(O[G * 16 + 14] * f1, O[G * 16 + 15] * f1)); \
    }                                                                                                          \
  } while (0)

__global__ void __cluster_dims__(2, 1, 1) __launch_bounds__(384, 1)
fused_kernel(const __grid_constant__ Params p, const bf16* __restrict__ x, const bf16* __restrict__ gate_w, bf16* __restrict__ out) {
  extern __shared__ uint8_t smem_raw[];
  const uint32_t sbase = (smem_u32(smem_raw) + 1023) & ~1023u;
  const uint32_t sB = sbase, sA = sbase + K1_BST * 16384, sBar = sbase + SMEM_DATA;
  const uint32_t bAf = sBar, bAe = sBar + 64, bBf = sBar + 128, bBe = sBar + 176, bL = sBar + 224, bS = sBar + 232, bL2 = sBar + 240, sL = sA + 32768;
  const uint32_t bF = sBar + 256, bE = sBar + 320, bT = sBar + 384, sTick = sBar + 400, sItem = sBar + 416, bS2 = sBar + 448, bR = sBar + 456, bLast = sBar + 464, bH = sBar + 472;
  const uint32_t b3F = sBar + 512, b3E = sBar + 544, sGate = sBar + 576;
  const int tid = threadIdx.x, warp_g = __shfl_sync(0xffffffffu, tid >> 5, 0), lane = tid & 31;
  const uint32_t rank = cluster_rank();
  const int cl = blockIdx.x >> 1;
  TSM(0);
  if (tid == 0) {
    for (int i = 0; i < 8; i++) { mbar_init(bAf + i * 8, 1); mbar_init(bAe + i * 8, 2); }
    for (int i = 0; i < K1_BST; i++) { mbar_init(bBf + i * 8, 1); mbar_init(bBe + i * 8, 4); }
    mbar_init(bL, 1);
    mbar_init(bL2, 1);
    mbar_init(bR, 1);
    mbar_init(bLast, 1);
    mbar_init(bH, 4);
    mbar_init(bS, 8);
    for (int i = 0; i < K2_NST; i++) { mbar_init(bF + i * 8, 1); mbar_init(bE + i * 8, 4); }
    mbar_init(bT, 1); mbar_init(bT + 8, 1);
    mbar_init(bS2, 8);
    for (int i = 0; i < K3_NST; i++) { mbar_init(b3F + i * 8, 1); mbar_init(b3E + i * 8, 4); }
    asm volatile("fence.mbarrier_init.release.cluster;" ::: "memory");
  }
  __syncthreads();
  cluster_sync();
  const int lr0 = blockIdx.x * 16;

  if (warp_g >= 8) {
    reg_dealloc<40>();
    if (warp_g == 8) {
      if (elect_one()) {
        uint32_t bs = 0, bph = 1, aph = 1;
#pragma unroll 1
        for (int ji = 0; ji < K1_MAXJOBS; ji++) {
          const uint32_t job = p.jobs[cl][ji];
          if (!(job & 3)) break;
          const int a_sel = (job >> 2) & 1, mpair = (job >> 3) & 7, chunk0 = (job >> 8) & 63;
          const bool newA = (job >> 14) & 1;
          const int KC = a_sel ? 9 : 8;
          const uint32_t halfbytes = 8192;
          const bool lastjob = (ji + 1 == K1_MAXJOBS) || !(p.jobs[cl][ji + 1] & 3);
          const CUtensorMap* tw = &p.tmW[(job >> 6) & 3];
          {
            const uint32_t njob = (ji + 1 < K1_MAXJOBS) ? p.jobs[cl][ji + 1] : 0;
            if (!(njob & 3) && !newA) mbar_arrive(bLast);
            if (njob & 3) {
              const int nst = ((njob >> 2) & 1) ? 18 : 16;
#pragma unroll 1
              for (int t = (cl < 64) ? (cl & 7) : 0; t < nst; t += (cl < 64) ? 8 : 1)
                tma_pf3d(&p.tmW[(njob >> 6) & 3], 0, t * 32 + rank * 16, (njob >> 8) & 63);
            }
          }
#pragma unroll 1
          for (int kc = 0; kc < KC; kc++) {
            if (kc == 8) {
              mbar_wait(bBe + bs * 8, bph);
              mbar_expect(bBf + bs * 8, 16384);
              tma2d(sB + bs * 16384, &p.tmA[1], bBf + bs * 8, 512, mpair * 256 + rank * 128);
              if (++bs == K1_BST) { bs = 0; bph ^= 1; }
            } else if (newA) {
              mbar_wait(bAe + kc * 8, aph);
              mbar_expect(bAf + kc * 8, 16384);
              tma2d(sA + ((kc + 2) & 7) * 16384, &p.tmA[a_sel], bAf + kc * 8, kc * 64, mpair * 256 + rank * 128);
              if (kc == 7 && lastjob) mbar_arrive(bLast);
            }
#pragma unroll 1
            for (int kk = 0; kk < 2; kk++) {
              mbar_wait(bBe + bs * 8, bph);
              mbar_expect(bBf + bs * 8, 2 * halfbytes);
              tma3d_mc(sB + bs * 16384 + rank * halfbytes, tw, bBf + bs * 8, 0, kc * 64 + kk * 32 + rank * 16, chunk0, 3);
              if (++bs == K1_BST) { bs = 0; bph ^= 1; }
            }
          }
          if (newA) aph ^= 1;
        }
        Cursor c{0, 0};
        int pcol = 0;
        uint32_t tick = cl, seen = 1u << (p.order[cl] >> 4);
        mbar_wait(bR, 0);
        asm volatile("fence.proxy.async.global;" ::: "memory");
#pragma unroll 1
        for (int it = 0;; it++) {
          const uint32_t item = (tick < 256) ? p.order[tick] : (K2_END | min(tick - 256, 255u));
          asm volatile("st.shared.u32 [%0], %1;" ::"r"(sItem + (it & 7) * 4), "r"(item) : "memory");
          if (item >= K2_END) break;
          const int h = item >> 3, j = item & 7;
          const int blk = 2 * j + (int)(rank ^ (it & 1));
          const int col = HA(h) * 128 + rank * 64;
          const int nb = 2 * j + 2;
          if (!((seen >> (h >> 1)) & 1)) {
            wait_flag(&g_sync[F_HP + (h >> 1)], RDY_TARGET);
            asm volatile("fence.proxy.async.global;" ::: "memory");
            seen |= 1u << (h >> 1);
          }
          mbar_wait(bE + c.s * 8, c.ph);
          mbar_expect(bF + c.s * 8, 32768);
          tma2d(sbase + c.s * 32768, &p.tmQ, bF + c.s * 8, HA(h) * 128, blk * 128);
          tma2d(sbase + c.s * 32768 + 16384, &p.tmQ, bF + c.s * 8, HA(h) * 128 + 64, blk * 128);
          c.next();
#pragma unroll 1
          for (int n = nb - 1; n >= 0; n--) {
            if (n == 0 && rank == 0) tick = atomicAdd(&g_sync[F_TICK], 1u) + NCLUSTER;
            mbar_wait(bE + c.s * 8, c.ph);
            mbar_expect(bF + c.s * 8, 32768);
            tma2d_mc(sbase + c.s * 32768 + rank * 16384, &p.tmK, bF + c.s * 8, col, n * 128, 3);
            c.next();
            if (n < nb - 1 || it > 0) {
              mbar_wait(bE + c.s * 8, c.ph);
              mbar_expect(bF + c.s * 8, 32768);
              tma2d_mc(sbase + c.s * 32768 + rank * 16384, &p.tmV, bF + c.s * 8, (n < nb - 1) ? col : pcol, (n < nb - 1) ? (n + 1) * 128 : 0, 3);
              c.next();
            }
          }
          pcol = col;
          if (rank == 0) {
            asm volatile(
                "{\n.reg .b32 a, b;\nmapa.shared::cluster.u32 a, %0, 1;\nmapa.shared::cluster.u32 b, %1, 1;\n"
                "st.async.shared::cluster.mbarrier::complete_tx::bytes.u32 [a], %2, [b];\n}" ::"r"(sTick + (it & 1) * 4),
                "r"(bT + (it & 1) * 8), "r"(tick) : "memory");
          } else {
            mbar_expect(bT + (it & 1) * 8, 4);
            mbar_wait(bT + (it & 1) * 8, (it >> 1) & 1);
            tick = lds32(sTick + (it & 1) * 4);
          }
        }
        mbar_wait(bE + c.s * 8, c.ph);
        mbar_expect(bF + c.s * 8, 32768);
        tma2d_mc(sbase + c.s * 32768 + rank * 16384, &p.tmV, bF + c.s * 8, pcol, 0, 3);
        const uint32_t unit = tick - 256;
        if (unit < 64) {
          const int mblk = (7 - (int)((unit >> 1) & 7)) * 2 + rank, nhalf = unit & 1, ks = unit >> 4;
          const uint32_t rot = k3_rot(c.s), nfree = ((0x1Au >> c.s) & 1) ? 2 : 3;
#pragma unroll 1
          for (int i = 0; i < K2_NST - 1; i++) {
            c.next();
            mbar_wait(bE + c.s * 8, c.ph);
          }
          uint32_t idx = 0, have = 0;
#pragma unroll 1
          for (int kk = k3_part(ks); kk < k3_part(ks + 1); kk++, idx++) {
            const uint32_t s = (rot + idx) & 3;
            if (idx >= nfree) mbar_wait((idx < 4) ? bH : b3E + s * 8, (idx < 4) ? 0 : (~idx >> 2) & 1);
            mbar_expect(b3F + s * 8, K3_STAGE);
            const uint32_t st = sbase + s * K3_STAGE;
            const int sel = (kk < 9), k = sel ? kk : kk - 9, kr = k * 64 + rank * 32;
            tma3d_mc(st + 16384 + rank * 16384, &p.tmO[sel], b3F + s * 8, 0, kr, nhalf * 4, 3);
            tma2d_mc(st + 49152 + rank * 2048, &p.tmOt[sel], b3F + s * 8, 512 + nhalf * 32, kr, 3);
            if (kk == 0) {
              wait_flag(&g_sync[F_OA + mblk], 8);
              asm volatile("fence.proxy.async.global;" ::: "memory");
            }
            if (!sel && !((have >> (k >> 1)) & 1)) {
#pragma unroll 1
              for (uint32_t spins = 0; spins < (1u << 22); spins++) {
                asm volatile("ld.acquire.gpu.global.u32 %0, [%1];" : "=r"(have) : "l"(&g_sync[F_CTX + mblk]) : "memory");
                if ((have >> (k >> 1)) & 1) break;
                __nanosleep(100);
              }
              asm volatile("fence.proxy.async.global;" ::: "memory");
            }
            tma2d(st, &p.tmC, b3F + s * 8, (sel ? 64 + k : k) * 64, mblk * 128);
          }
        }
      }
    }
    __syncwarp();
    asm volatile("" ::: "memory");
    if (__shfl_sync(0xffffffffu, warp_g, 0) != 8) {
      if (lr0 < S_LEN) {
#pragma unroll 1
        for (int i = warp_g - 9; i < 16; i += 3) {
          const float g = gate_row(lr0 + i, lane, x, gate_w);
          if (lane == 0) asm volatile("st.shared.f32 [%0], %1;" ::"r"(sGate + i * 4), "f"(g) : "memory");
        }
        bar_arrive(3, 256 + 96);
        if (lane == 0) {
          __threadfence();
          atomicAdd(&g_sync[F_GATE], 1u);
        }
      }
      if (warp_g == 9 && lane == 0) {
#pragma unroll 1
        for (int ji = 0; ji < K1_MAXJOBS; ji++) {
          const uint32_t job = p.jobs[cl][ji];
          if (!(job & 3)) break;
          mbar_wait(bS, ji & 1);
          __threadfence();
          atomicAdd(&g_sync[(((job >> 6) & 3) == 2) ? (F_QKVA + ((job >> 3) & 7) * 2 + rank) : (F_HP + ((job >> 10) & 15))], 1u);
        }
#pragma unroll 1
        for (int it = 0;; it++) {
          mbar_wait(bS2, it & 1);
          const uint32_t item = lds32(sItem + (it & 7) * 4), nxt = lds32(sItem + ((it + 1) & 7) * 4);
          __threadfence();
          atomicOr(&g_sync[F_CTX + (item & 7) * 2 + (rank ^ (it & 1))], 1u << (item >> 3));
          if (nxt >= K2_END) break;
        }
      } else if (warp_g == 11) {
        if (lane == 0) {
          prefetch_tmap(&p.tmQ); prefetch_tmap(&p.tmK); prefetch_tmap(&p.tmV);
          wait_flag(&g_sync[F_GATE], GATE_TARGET);
          wait_flag(&g_sync[F_HP + (p.order[cl] >> 4)], RDY_TARGET);
          mbar_arrive(bR);
        }
        __syncwarp();
        bar_sync(4, 256 + 32);
        if (lane < 12) mbar_arrive_cluster(bE + (4 + lane % 3) * 8, (lane / 3) & 1);
      } else if (warp_g == 10 && lr0 < S_LEN) {
        if (elect_one()) {
          prefetch_tmap(&p.tmL[0]); prefetch_tmap(&p.tmL[1]);
          uint32_t aph = 1;
#pragma unroll 1
          for (int ji = 0; ji < K1_MAXJOBS; ji++) aph ^= (p.jobs[cl][ji] >> 14) & 1;
          wait_flag(&g_sync[F_QKVA + (lr0 >> 7)], K1_FLAG_TARGET);
          wait_flag(&g_sync[F_QKVA + (max(lr0 - 14, 0) >> 7)], K1_FLAG_TARGET);
          asm volatile("fence.proxy.async.global;" ::: "memory");
          mbar_wait(bLast, 0);
#pragma unroll 1
          for (int kc = 0; kc < 6; kc++) {
            mbar_wait(bAe + kc * 8, aph);
            if (kc == 3) {
              mbar_expect(bL, 46 * 1152);
              tma3d(sL, &p.tmL[0], bL, 0, 9, lr0 - 14);
              tma3d(sL + 30 * 1152, &p.tmL[1], bL, 0, 0, lr0);
            }
          }
          mbar_expect(bL2, 30 * 1152);
          tma3d(sL + 46 * 1152, &p.tmL[0], bL2, 0, 18, lr0 - 14);
        }
        __syncwarp();
        bar_sync(5, 256 + 32);
        if (lane == 0) {
          __threadfence();
          atomicAdd(&g_sync[F_OA + (lr0 >> 7)], 1u);
        }
      }
    }
    __syncwarp();
    cluster_sync();
    if (warp_g == 8) {
      uint32_t v = 0;
      if (lane == 0) {
        __threadfence();
        v = atomicAdd(&g_sync[F_DONE], 1u);
      }
      if (__shfl_sync(0xffffffffu, v, 0) == 2 * NCLUSTER - 1)
        for (int i = 0; i < 3; i++) reinterpret_cast<uint4*>(g_sync)[i * 32 + lane] = make_uint4(0, 0, 0, 0);
    }
  } else {
    reg_alloc<232>();
    const int wg = warp_g >> 2, warp = warp_g & 3, q = lane & 3;
    const bool sig = (lane == 0) && (warp < 2);
    {
      K1State st{0, 0, 0, nullptr, 0, 0};
      float acc[128];
      uint32_t pk[64];
      if (wg == 0) { TS(0, 0); TSC(0, 2); }
#pragma unroll 1
      for (int ji = 0; ji < K1_MAXJOBS; ji++) {
        const uint32_t job = p.jobs[cl][ji];
        if (!(job & 3)) break;
        k1_tile(acc, pk, st, job, sA, sB, bAf, bAe, bBf, bBe, bS, wg, warp, lane, rank);
      }
#pragma unroll
      for (int i = 0; i < 4; i++)
        mbar_arrive_cluster_if(bE + i * 8, warp & 1, sig);
#pragma unroll
      for (int G = 0; G < 8; G++)
        if (G < st.png) {
          st_v4(st.pp + G * 32, pk[G * 8], pk[G * 8 + 1], pk[G * 8 + 2], pk[G * 8 + 3]);
          st_v4(st.pp + G * 32 + st.pld8, pk[G * 8 + 4], pk[G * 8 + 5], pk[G * 8 + 6], pk[G * 8 + 7]);
        }
      k1_flag(st, lane, bS);
      if (wg == 0) { TS(0, 1); TSC(0, 3); }
      if (lr0 < S_LEN) {
        const int ri = (warp_g >> 1) * 4 + (warp_g & 1) + 2, row = lr0 + ri;
        if (wg == 0) TS(1, 5);
        bar_sync(3, 256 + 96);
        const float gate0 = __uint_as_float(lds32(sGate + ri * 4 - 8)), gate1 = __uint_as_float(lds32(sGate + ri * 4));
        mbar_wait(bL, 0);
        if (wg == 0) TS(1, 6);
        local_rows2(row, ri, sL, bL2, lane, gate0, gate1);
        bar_arrive(5, 256 + 32);
      } else {
        bar_arrive(4, 256 + 32);
      }
    }
    __syncwarp();
    uint32_t item, rot;
    {
      const int mybar = 1 + wg, otherbar = 2 - wg;
      const float cl2 = 0.08838834764831845f * 1.4426950408889634f;
      float S[64], O[64];
      uint32_t P[32], Q[32];
#pragma unroll
      for (int i = 0; i < 64; i++) { S[i] = 0.f; O[i] = 1.f; }
#pragma unroll
      for (int i = 0; i < 32; i++) P[i] = 0;
      float m0 = 0.f, m1 = 0.f, l0 = 0.f, l1 = 0.f;
      int prev_row = 0, prev_h = 0, prev_single = 0;
      Cursor c{0, 0};
      if (wg == 1) bar_arrive(1, 256);
      if (wg == 0) { TS(1, 0); TSC(1, 2); }
#pragma unroll 1
      for (int it = 0;; it++) {
        mbar_wait(bF + c.s * 8, c.ph);
        item = lds32(sItem + (it & 7) * 4);
        if (item >= K2_END) break;
        const int h = item >> 3, j = item & 7;
        const int hi = (int)(rank ^ (it & 1));
        const int nblk = 2 * j + 1 + hi;
        {
          const float gf0 = 1.f - g_gate[prev_row], gf1 = 1.f - g_gate[prev_row + 8];
          Cursor cq = c; c.next();
          {
            const int r = wg * 64 + warp * 16 + (lane & 7) + ((lane >> 3) & 1) * 8;
            const uint32_t qa = sbase + cq.s * 32768 + r * 128;
#pragma unroll
            for (int t = 0; t < 8; t++)
              ldsm_x4(Q[4 * t], Q[4 * t + 1], Q[4 * t + 2], Q[4 * t + 3], qa + (t >> 2) * 16384 + ((((t & 3) * 2 + (lane >> 4)) ^ (lane & 7)) << 4));
          }
          Cursor ck = c; c.next();
          Cursor cs0 = ck, cs1 = ck, cv = c;
          mbar_wait(bF + ck.s * 8, ck.ph);
          if (it > 0) { mbar_wait(bF + cv.s * 8, cv.ph); c.next(); }
          if (!hi) {
            ck = c; c.next();
            cs1 = c; c.next();
            mbar_wait(bF + ck.s * 8, ck.ph);
            mbar_wait(bF + cs1.s * 8, cs1.ph);
          }
          if (it == 0) BSEG(4); else BSEG(0);
          TURN_SYNC();
          wg_fence();
          ISSUE_QK(ck);
          wg_commit();
          if (it > 0) ISSUE_PV(cv, prev_single);
          wg_commit();
          TURN_ARRIVE();
          RELEASE(cq);
          if (!hi) { RELEASE(cs0); RELEASE(cs1); }
          wg_wait<1>();
          fence_regs(S);
          RELEASE(ck);
          const int r0 = wg * 64 + warp * 16 + (lane >> 2);
#pragma unroll
          for (int jj = 0; jj < 16; jj++) {
            const int cc = jj * 8 + 2 * q;
            if (cc > r0) S[jj * 4 + 0] = -INFINITY;
            if (cc + 1 > r0) S[jj * 4 + 1] = -INFINITY;
            if (cc > r0 + 8) S[jj * 4 + 2] = -INFINITY;
            if (cc + 1 > r0 + 8) S[jj * 4 + 3] = -INFINITY;
          }
          float mx0 = fmaxf(S[0], S[1]), mx1 = fmaxf(S[2], S[3]);
#pragma unroll
          for (int jj = 1; jj < 16; jj++) {
            mx0 = fmaxf(mx0, fmaxf(S[jj * 4 + 0], S[jj * 4 + 1]));
            mx1 = fmaxf(mx1, fmaxf(S[jj * 4 + 2], S[jj * 4 + 3]));
          }
          mx0 = fmaxf(mx0, __shfl_xor_sync(0xffffffffu, mx0, 1));
          mx1 = fmaxf(mx1, __shfl_xor_sync(0xffffffffu, mx1, 1));
          mx0 = fmaxf(mx0, __shfl_xor_sync(0xffffffffu, mx0, 2));
          mx1 = fmaxf(mx1, __shfl_xor_sync(0xffffffffu, mx1, 2));
          m0 = mx0; m1 = mx1;
          const float mc0 = m0 * cl2, mc1 = m1 * cl2;
          float s0 = 0.f, s1 = 0.f;
#pragma unroll
          for (int jj = 0; jj < 16; jj++) {
            S[jj * 4 + 0] = ex2(fmaf(S[jj * 4 + 0], cl2, -mc0));
            S[jj * 4 + 1] = ex2(fmaf(S[jj * 4 + 1], cl2, -mc0));
            S[jj * 4 + 2] = ex2(fmaf(S[jj * 4 + 2], cl2, -mc1));
            S[jj * 4 + 3] = ex2(fmaf(S[jj * 4 + 3], cl2, -mc1));
            s0 += S[jj * 4 + 0] + S[jj * 4 + 1];
            s1 += S[jj * 4 + 2] + S[jj * 4 + 3];
          }
          fence_regs(S);
          wg_wait<0>();
          fence_regs(O);
          fence_regs(P);
          if (it > 0) {
            RELEASE(cv);
            EPILOGUE();
            __syncwarp();
            if (lane == 0) mbar_arrive(bS2);
          }
          l0 = s0; l1 = s1;
#pragma unroll
          for (int jj = 0; jj < 16; jj++) {
            P[jj * 2 + 0] = pack_bf16(S[jj * 4 + 0], S[jj * 4 + 1]);
            P[jj * 2 + 1] = pack_bf16(S[jj * 4 + 2], S[jj * 4 + 3]);
          }
        }
        if (it == 0) BSEG(5); else BSEG(1);
#pragma unroll 1
        for (int n = 1; n < nblk; n++) {
          Cursor ck = c; c.next();
          Cursor cv = c; c.next();
          mbar_wait(bF + ck.s * 8, ck.ph);
          mbar_wait(bF + cv.s * 8, cv.ph);
          TURN_SYNC();
          wg_fence();
          ISSUE_QK(ck);
          wg_commit();
          ISSUE_PV(cv, n == 1);
          wg_commit();
          TURN_ARRIVE();
          wg_wait<1>();
          fence_regs(S);
          RELEASE(ck);
          float mx0 = fmaxf(S[0], S[1]), mx1 = fmaxf(S[2], S[3]);
#pragma unroll
          for (int jj = 1; jj < 16; jj++) {
            mx0 = fmaxf(mx0, fmaxf(S[jj * 4 + 0], S[jj * 4 + 1]));
            mx1 = fmaxf(mx1, fmaxf(S[jj * 4 + 2], S[jj * 4 + 3]));
          }
          mx0 = fmaxf(mx0, __shfl_xor_sync(0xffffffffu, mx0, 1));
          mx1 = fmaxf(mx1, __shfl_xor_sync(0xffffffffu, mx1, 1));
          mx0 = fmaxf(mx0, __shfl_xor_sync(0xffffffffu, mx0, 2));
          mx1 = fmaxf(mx1, __shfl_xor_sync(0xffffffffu, mx1, 2));
          mx0 = fmaxf(mx0, m0);
          mx1 = fmaxf(mx1, m1);
          const float sc0 = ex2((m0 - mx0) * cl2), sc1 = ex2((m1 - mx1) * cl2);
          m0 = mx0; m1 = mx1;
          const float mc0 = m0 * cl2, mc1 = m1 * cl2;
          float s0 = 0.f, s1 = 0.f;
#pragma unroll
          for (int jj = 0; jj < 16; jj++) {
            S[jj * 4 + 0] = ex2(fmaf(S[jj * 4 + 0], cl2, -mc0));
            S[jj * 4 + 1] = ex2(fmaf(S[jj * 4 + 1], cl2, -mc0));
            S[jj * 4 + 2] = ex2(fmaf(S[jj * 4 + 2], cl2, -mc1));
            S[jj * 4 + 3] = ex2(fmaf(S[jj * 4 + 3], cl2, -mc1));
            s0 += S[jj * 4 + 0] + S[jj * 4 + 1];
            s1 += S[jj * 4 + 2] + S[jj * 4 + 3];
          }
          l0 = fmaf(l0, sc0, s0);
          l1 = fmaf(l1, sc1, s1);
          fence_regs(S);
          wg_wait<0>();
          fence_regs(O);
          fence_regs(P);
          RELEASE(cv);
#pragma unroll
          for (int jj = 0; jj < 16; jj++) {
            O[jj * 4 + 0] *= sc0;
            O[jj * 4 + 1] *= sc0;
            O[jj * 4 + 2] *= sc1;
            O[jj * 4 + 3] *= sc1;
            P[jj * 2 + 0] = pack_bf16(S[jj * 4 + 0], S[jj * 4 + 1]);
            P[jj * 2 + 1] = pack_bf16(S[jj * 4 + 2], S[jj * 4 + 3]);
          }
        }
        BSEG(2);
        prev_row = (2 * j + hi) * 128 + wg * 64 + warp * 16 + (lane >> 2);
        prev_h = h;
        prev_single = (nblk == 1);
      }
      {
        const float gf0 = 1.f - g_gate[prev_row], gf1 = 1.f - g_gate[prev_row + 8];
        Cursor cv = c;
        rot = k3_rot(c.s);
        TURN_SYNC();
        wg_fence();
        ISSUE_PV(cv, prev_single);
        wg_commit();
        if (wg == 0) TURN_ARRIVE();
        wg_wait<0>();
        fence_regs(O);
        mbar_arrive_cluster_if(bH, warp & 1, sig);
        EPILOGUE();
        __syncwarp();
        if (lane == 0) mbar_arrive(bS2);
      }
      if (wg == 1) { TS(1, 1); TSC(1, 3); }
    }
    __syncwarp();
    const uint32_t unit = item & 255;
    if (unit < 64) {
      const int mblk = (7 - (int)((unit >> 1) & 7)) * 2 + rank, nhalf = unit & 1, ks = unit >> 4;
      const int k0 = k3_part(ks), k1 = k3_part(ks + 1);
      float acc[144];
      uint32_t s = rot, ph = 0, prev = 0;
      if (wg == 0) { TS(2, 0); TSC(2, 2); }
#pragma unroll 1
      for (int k = k0; k < k1; k++) {
        mbar_wait(b3F + s * 8, ph);
        const uint32_t st = sbase + s * K3_STAGE;
        const uint64_t da = make_desc(st + wg * 8192, 16, 1024, 1);
        const uint64_t db = make_desc(st + 16384, 4096, 1024, 1);
        const uint64_t dt = make_desc(st + 49152, 16, 512, 2);
        wg_fence();
#pragma unroll
        for (int t = 0; t < 4; t++) {
          const int sd = (t > 0) || (k > k0);
          wgmma_ss_n256<1, 0>(acc, da + (uint64_t)(t * 2), db + (uint64_t)((t >> 1) * 1024 + (t & 1) * 128), sd);
          wgmma_ss_n32<1, 128>(acc, da + (uint64_t)(t * 2), dt + (uint64_t)(t * 64), sd);
        }
        wg_commit();
        if (k > k0) {
          wg_wait<1>();
          if (sig) mbar_arrive_cluster(b3E + prev * 8, warp);
        }
        prev = s;
        s = (s + 1) & 3;
        if (s == rot) ph ^= 1;
      }
      wg_wait<0>();
      fence_regs(acc);
      if (wg == 0) TS(2, 4);
      const int tile = mblk * 2 + nhalf;
      uint4* wp = g_part + (size_t)((tile * 4 + ks) * 4) * 5 * 256 + tid;
#pragma unroll
      for (int d = 0; d < 4; d++) {
        if (d != ks) {
#pragma unroll
          for (int i = 0; i < 4; i++)
            __stcg(wp + (d * 5 + i) * 256,
                   make_uint4(pack_bf16(acc[d * 32 + i * 8], acc[d * 32 + i * 8 + 1]), pack_bf16(acc[d * 32 + i * 8 + 2], acc[d * 32 + i * 8 + 3]),
                              pack_bf16(acc[d * 32 + i * 8 + 4], acc[d * 32 + i * 8 + 5]), pack_bf16(acc[d * 32 + i * 8 + 6], acc[d * 32 + i * 8 + 7])));
          __stcg(reinterpret_cast<uint2*>(wp - tid + (d * 5 + 4) * 256) + tid,
                 make_uint2(pack_bf16(acc[128 + d * 4], acc[128 + d * 4 + 1]), pack_bf16(acc[128 + d * 4 + 2], acc[128 + d * 4 + 3])));
        }
      }
      __threadfence();
      __syncwarp();
      if (wg == 0) TS(2, 5);
      if (lane == 0) {
        unsigned int* cnt = &g_sync[F_XCH + tile * 8 + warp_g];
        atomicAdd(cnt, 1u);
        uint32_t v, spins = 0;
        do {
          asm volatile("ld.acquire.gpu.global.u32 %0, [%1];" : "=r"(v) : "l"(cnt) : "memory");
        } while (v < 4 && ++spins < (1u << 24));
      }
      __syncwarp();
      if (wg == 0) TS(2, 6);
      float r[36];
#pragma unroll
      for (int d = 0; d < 4; d++) {
        if (d == ks) {
#pragma unroll
          for (int i = 0; i < 32; i++) r[i] = acc[d * 32 + i];
#pragma unroll
          for (int i = 0; i < 4; i++) r[32 + i] = acc[128 + d * 4 + i];
        }
      }
#pragma unroll
      for (int sI = 1; sI < 4; sI++) {
        const int src = (ks + sI) & 3;
        const uint4* rp = g_part + (size_t)(((tile * 4 + src) * 4) + ks) * 5 * 256;
#pragma unroll
        for (int i = 0; i < 4; i++) {
          const uint4 v = __ldcg(rp + i * 256 + tid);
          r[i * 8] += bf_lo(v.x); r[i * 8 + 1] += bf_hi(v.x); r[i * 8 + 2] += bf_lo(v.y); r[i * 8 + 3] += bf_hi(v.y);
          r[i * 8 + 4] += bf_lo(v.z); r[i * 8 + 5] += bf_hi(v.z); r[i * 8 + 6] += bf_lo(v.w); r[i * 8 + 7] += bf_hi(v.w);
        }
        const uint2 v = __ldcg(reinterpret_cast<const uint2*>(rp + 4 * 256) + tid);
        r[32] += bf_lo(v.x); r[33] += bf_hi(v.x); r[34] += bf_lo(v.y); r[35] += bf_hi(v.y);
      }
      const int row = mblk * 128 + wg * 64 + warp * 16 + (lane >> 2);
      bf16* o0 = out + (size_t)row * DM + nhalf * 256 + ks * 64 + 8 * q;
#pragma unroll
      for (int G = 0; G < 2; G++) {
        uint32_t a0 = pack_bf16(r[G * 16], r[G * 16 + 1]), a1 = pack_bf16(r[G * 16 + 4], r[G * 16 + 5]);
        uint32_t a2 = pack_bf16(r[G * 16 + 8], r[G * 16 + 9]), a3 = pack_bf16(r[G * 16 + 12], r[G * 16 + 13]);
        uint32_t b0 = pack_bf16(r[G * 16 + 2], r[G * 16 + 3]), b1 = pack_bf16(r[G * 16 + 6], r[G * 16 + 7]);
        uint32_t b2 = pack_bf16(r[G * 16 + 10], r[G * 16 + 11]), b3 = pack_bf16(r[G * 16 + 14], r[G * 16 + 15]);
        quad_transpose(a0, a1, a2, a3, q);
        quad_transpose(b0, b1, b2, b3, q);
        st_v4(o0 + G * 32, a0, a1, a2, a3);
        st_v4(o0 + 8 * DM + G * 32, b0, b1, b2, b3);
      }
      {
        uint32_t t0 = pack_bf16(r[32], r[33]), t1 = pack_bf16(r[34], r[35]), t2 = 0, t3 = 0;
        quad_transpose(t0, t1, t2, t3, q);
        if (q < 2) st_v4(out + (size_t)(row + q * 8) * DM + 512 + nhalf * 32 + ks * 8, t0, t1, t2, t3);
      }
    }
    if (wg == 0) { TS(2, 1); TSC(2, 3); }
    cluster_sync();
  }
}

typedef CUresult (*EncFn)(CUtensorMap*, CUtensorMapDataType, cuuint32_t, void*, const cuuint64_t*, const cuuint64_t*, const cuuint32_t*,
                          const cuuint32_t*, CUtensorMapInterleave, CUtensorMapSwizzle, CUtensorMapL2promotion, CUtensorMapFloatOOBfill);

static void enc2d(EncFn enc, CUtensorMap* m, const void* ptr, uint64_t cols, uint64_t rows, uint32_t bc, uint32_t br,
                  CUtensorMapSwizzle sw = CU_TENSOR_MAP_SWIZZLE_128B) {
  cuuint64_t gd[2] = {cols, rows}, gs[1] = {cols * 2};
  cuuint32_t bx[2] = {bc, br}, es[2] = {1, 1};
  enc(m, CU_TENSOR_MAP_DATA_TYPE_BFLOAT16, 2, const_cast<void*>(ptr), gd, gs, bx, es, CU_TENSOR_MAP_INTERLEAVE_NONE, sw,
      CU_TENSOR_MAP_L2_PROMOTION_L2_256B, CU_TENSOR_MAP_FLOAT_OOB_FILL_NONE);
}
static void enc3d(EncFn enc, CUtensorMap* m, const void* ptr, uint64_t cols, uint64_t rows, uint32_t br, uint32_t bch) {
  cuuint64_t gd[3] = {64, rows, cols / 64}, gs[2] = {cols * 2, 128};
  cuuint32_t bx[3] = {64, br, bch}, es[3] = {1, 1, 1};
  enc(m, CU_TENSOR_MAP_DATA_TYPE_BFLOAT16, 3, const_cast<void*>(ptr), gd, gs, bx, es, CU_TENSOR_MAP_INTERLEAVE_NONE,
      CU_TENSOR_MAP_SWIZZLE_128B, CU_TENSOR_MAP_L2_PROMOTION_L2_256B, CU_TENSOR_MAP_FLOAT_OOB_FILL_NONE);
}

static void build_k1_jobs(Params& p) {
  int cnt[NCLUSTER];
  for (int c = 0; c < NCLUSTER; c++) {
    cnt[c] = 0;
    for (int i = 0; i < K1_MAXJOBS; i++) p.jobs[c][i] = 0;
  }
  auto add = [&](int c, int nch, int a_sel, int mp, int w_sel, int chunk0) {
    p.jobs[c][cnt[c]++] = (uint16_t)((nch - 1) | (a_sel << 2) | (mp << 3) | (w_sel << 6) | (chunk0 << 8));
  };
  for (int mp = 0; mp < 8; mp++) {
    for (int g = 0; g < 4; g++)
      for (int i = 0; i < 4; i++) add(g * 8 + mp, 4, 0, mp, g & 1, (2 * i + (g >> 1)) * 4);
    for (int t = 0; t < 16; t++) add((t % 3) * 8 + mp, 4, 0, mp, t & 1, (8 + (t >> 1)) * 4);
    add(32 + mp, 3, 1, mp, 2, 24);
    add(32 + mp, 4, 1, mp, 3, 0 * 4);
    for (int g = 5; g < 8; g++)
      for (int i = 0; i < 2; i++) add(g * 8 + mp, 4, 1, mp, 2, ((g - 5) * 2 + i) * 4);
    for (int i = 1; i < 8; i++) add((4 + (i - 1) % 4) * 8 + mp, 4, 1, mp, 3, i * 4);
    for (int i = 8; i < 14; i++) add(56 + mp, 4, 1, mp, 3, i * 4);
    add(64 + mp / 4, 4, 1, mp, 3, 14 * 4);
    add(64 + mp / 4, 4, 1, mp, 3, 15 * 4);
  }
  for (int cc = 0; cc < NCLUSTER; cc++)
    for (int i = 0; i < cnt[cc]; i++) {
      const int key = p.jobs[cc][i] & 0x3C;
      if (i == 0 || (p.jobs[cc][i - 1] & 0x3C) != key) p.jobs[cc][i] |= (1 << 14);
      if (i == cnt[cc] - 1 || (p.jobs[cc][i + 1] & 0x3C) != key) p.jobs[cc][i] |= (1 << 15);
    }
}

static void build_k2_items(Params& p) {
  bool used[256] = {};
  int ne = 0, nl = 0;
  for (int c = 0; c < NCLUSTER; c++) {
    const int g = c >> 3;
    if (g >= 3 && g <= 6) { p.order[c] = (uint8_t)((ne & 7) * 8 + 7 - (ne >> 3)); ne++; }
    else if (g == 1 || g == 2) p.order[c] = (uint8_t)((8 + (c - 8)) * 8 + 7);
    else { p.order[c] = (uint8_t)(nl < 8 ? (24 + nl) * 8 + 7 : (nl < 16 ? (16 + nl) : (nl - 8)) * 8 + 6); nl++; }
    used[p.order[c]] = true;
  }
  int n = NCLUSTER;
  for (int j = 3; j >= 0; j--)
    for (int h = 0; h < 8; h++) p.order[n++] = (uint8_t)(h * 8 + j);
  for (int j = 7; j >= 0; j--)
    for (int h = 8; h < 32; h++)
      if (!used[h * 8 + j]) p.order[n++] = (uint8_t)(h * 8 + j);
}

extern "C" void kernel_launch(void* const* d_in, const int* in_sizes, int n_in, void* d_out, int out_size) {
  const bf16* x = (const bf16*)d_in[0];
  const bf16* wqkv = (const bf16*)d_in[1];
  const bf16* wo = (const bf16*)d_in[2];
  const bf16* ckv = (const bf16*)d_in[4];
  const bf16* w_q = (const bf16*)d_in[5];
  const bf16* w_uk = (const bf16*)d_in[6];
  const bf16* w_uv = (const bf16*)d_in[7];
  const bf16* w_o = (const bf16*)d_in[8];
  const bf16* gate_w = (const bf16*)d_in[9];

  EncFn enc = nullptr;
  cudaDriverEntryPointQueryResult qr;
  cudaGetDriverEntryPoint("cuTensorMapEncodeTiled", (void**)&enc, cudaEnableDefault, &qr);
  void *pQ, *pK, *pV, *pCtx, *pQA;
  cudaGetSymbolAddress(&pQ, g_Q);
  cudaGetSymbolAddress(&pQA, g_QKVA);
  cudaGetSymbolAddress(&pK, g_K);
  cudaGetSymbolAddress(&pV, g_V);
  cudaGetSymbolAddress(&pCtx, g_ctx);

  static Params p;
  enc2d(enc, &p.tmA[0], ckv, DC, S_LEN, 64, 128);
  enc2d(enc, &p.tmA[1], x, DM, S_LEN, 64, 128);
  enc3d(enc, &p.tmW[0], w_uk, HDIM, DC, 16, 4);
  enc3d(enc, &p.tmW[1], w_uv, HDIM, DC, 16, 4);
  enc3d(enc, &p.tmW[2], wqkv, NQKVA, DM, 16, 4);
  enc3d(enc, &p.tmW[3], w_q, HDIM, DM, 16, 4);
  build_k1_jobs(p);
  enc2d(enc, &p.tmQ, pQ, HDIM, S_LEN, 64, 128);
  enc2d(enc, &p.tmK, pK, HDIM, S_LEN, 64, 128);
  enc2d(enc, &p.tmV, pV, HDIM, S_LEN, 64, 128);
  build_k2_items(p);
  for (int i = 0; i < 2; i++) {
    cuuint64_t gd[3] = {64, 27, S_LEN}, gs[2] = {128, NQKVA * 2};
    cuuint32_t bx[3] = {64, 9, i ? 16u : 30u}, es[3] = {1, 1, 1};
    enc(&p.tmL[i], CU_TENSOR_MAP_DATA_TYPE_BFLOAT16, 3, pQA, gd, gs, bx, es, CU_TENSOR_MAP_INTERLEAVE_NONE, CU_TENSOR_MAP_SWIZZLE_NONE,
        CU_TENSOR_MAP_L2_PROMOTION_L2_256B, CU_TENSOR_MAP_FLOAT_OOB_FILL_NONE);
  }
  enc2d(enc, &p.tmC, pCtx, KCAT, S_LEN, 64, 128);
  enc3d(enc, &p.tmO[0], w_o, DM, HDIM, 32, 4);
  enc3d(enc, &p.tmO[1], wo, DM, DM, 32, 4);
  enc2d(enc, &p.tmOt[0], w_o, DM, HDIM, 32, 32, CU_TENSOR_MAP_SWIZZLE_64B);
  enc2d(enc, &p.tmOt[1], wo, DM, DM, 32, 32, CU_TENSOR_MAP_SWIZZLE_64B);

  cudaFuncSetAttribute(fused_kernel, cudaFuncAttributeMaxDynamicSharedMemorySize, SMEM_BYTES);
  fused_kernel<<<NCLUSTER * 2, 384, SMEM_BYTES>>>(p, x, gate_w, (bf16*)d_out);
}
```

```cpp
#include <cuda_runtime.h>
#include <cuda_bf16.h>
#include <cuda.h>
#include <stdint.h>

typedef __nv_bfloat16 bf16;

constexpr int S_LEN = 2048, DM = 576, DC = 512, HDIM = 4096, NQKVA = 1728, KCAT = 4672;
constexpr int NCLUSTER = 66;

__device__ __align__(1024) bf16 g_Q[S_LEN * HDIM];
__device__ __align__(1024) bf16 g_K[S_LEN * HDIM];
__device__ __align__(1024) bf16 g_V[S_LEN * HDIM];
__device__ __align__(1024) bf16 g_QKVA[S_LEN * NQKVA + 64];
__device__ __align__(1024) bf16 g_ctx[S_LEN * KCAT];
__device__ float g_gate[S_LEN];
__device__ __align__(1024) uint4 g_part[32 * 4 * 4 * 5 * 256];
__device__ __align__(16) unsigned int g_sync[384];
constexpr int F_QKVA = 0, F_HP = 16, F_CTX = 32, F_OA = 48, F_GATE = 96, F_TICK = 97, F_DONE = 98, F_XCH = 128;

__device__ __forceinline__ uint32_t smem_u32(const void* p) { return (uint32_t)__cvta_generic_to_shared(p); }
__device__ __forceinline__ void mbar_init(uint32_t a, uint32_t c) {
  asm volatile("mbarrier.init.shared::cta.b64 [%0], %1;" ::"r"(a), "r"(c));
}
__device__ __forceinline__ void mbar_expect(uint32_t a, uint32_t b) {
  asm volatile("mbarrier.arrive.expect_tx.shared::cta.b64 _, [%0], %1;" ::"r"(a), "r"(b) : "memory");
}
#define TS(k, i)
#define TSC(k, i)
#define TSM(k)
#define BSEG(i)
#define SPIN_LIMIT "4194304"
__device__ __forceinline__ void mbar_wait(uint32_t a, uint32_t parity) {
  asm volatile(
      "{\n.reg .pred p;\n.reg .u32 n;\n"
      "mbarrier.try_wait.parity.shared::cta.b64 p, [%0], %1;\n"
      "@p bra DONE;\n"
      "mov.u32 n, 0;\n"
      "LOOP:\n"
      "mbarrier.try_wait.parity.shared::cta.b64 p, [%0], %1;\n"
      "@p bra DONE;\n"
      "add.u32 n, n, 1;\n"
      "setp.lt.u32 p, n, " SPIN_LIMIT ";\n"
      "@p bra LOOP;\n"
      "DONE:\n}" ::"r"(a), "r"(parity) : "memory");
}
__device__ __forceinline__ void mbar_arrive(uint32_t a) {
  asm volatile("mbarrier.arrive.shared::cta.b64 _, [%0];" ::"r"(a) : "memory");
}
__device__ __forceinline__ void mbar_arrive_cluster(uint32_t a, uint32_t cta) {
  asm volatile("{\n.reg .b32 r;\nmapa.shared::cluster.u32 r, %0, %1;\nmbarrier.arrive.shared::cluster.b64 _, [r];\n}" ::"r"(a),
               "r"(cta) : "memory");
}
__device__ __forceinline__ void mbar_arrive_cluster_if(uint32_t a, uint32_t cta, bool pred) {
  asm volatile("{\n.reg .b32 r;\n.reg .pred p;\nsetp.ne.u32 p, %2, 0;\nmapa.shared::cluster.u32 r, %0, %1;\n@p mbarrier.arrive.shared::cluster.b64 _, [r];\n}" ::"r"(a),
               "r"(cta), "r"((uint32_t)pred) : "memory");
}
__device__ __forceinline__ void mbar_arrive_if(uint32_t a, bool pred) {
  asm volatile("{\n.reg .pred p;\nsetp.ne.u32 p, %1, 0;\n@p mbarrier.arrive.shared::cta.b64 _, [%0];\n}" ::"r"(a), "r"((uint32_t)pred) : "memory");
}
__device__ __forceinline__ void tma2d(uint32_t dst, const CUtensorMap* m, uint32_t bar, int c0, int c1) {
  asm volatile("cp.async.bulk.tensor.2d.shared::cluster.global.mbarrier::complete_tx::bytes [%0], [%1, {%3, %4}], [%2];" ::"r"(dst),
               "l"(m), "r"(bar), "r"(c0), "r"(c1) : "memory");
}
__device__ __forceinline__ void tma2d_mc(uint32_t dst, const CUtensorMap* m, uint32_t bar, int c0, int c1, uint16_t mask) {
  asm volatile(
      "cp.async.bulk.tensor.2d.shared::cluster.global.mbarrier::complete_tx::bytes.multicast::cluster [%0], [%1, {%3, %4}], [%2], %5;" ::"r"(dst),
      "l"(m), "r"(bar), "r"(c0), "r"(c1), "h"(mask) : "memory");
}
__device__ __forceinline__ void tma3d_mc(uint32_t dst, const CUtensorMap* m, uint32_t bar, int c0, int c1, int c2, uint16_t mask) {
  asm volatile(
      "cp.async.bulk.tensor.3d.shared::cluster.global.mbarrier::complete_tx::bytes.multicast::cluster [%0], [%1, {%3, %4, %5}], [%2], %6;" ::"r"(dst),
      "l"(m), "r"(bar), "r"(c0), "r"(c1), "r"(c2), "h"(mask) : "memory");
}
__device__ __forceinline__ void tma3d(uint32_t dst, const CUtensorMap* m, uint32_t bar, int c0, int c1, int c2) {
  asm volatile(
      "cp.async.bulk.tensor.3d.shared::cluster.global.mbarrier::complete_tx::bytes [%0], [%1, {%3, %4, %5}], [%2];" ::"r"(dst),
      "l"(m), "r"(bar), "r"(c0), "r"(c1), "r"(c2) : "memory");
}
__device__ __forceinline__ void tma_pf2d(const CUtensorMap* m, int c0, int c1) {
  asm volatile("cp.async.bulk.prefetch.tensor.2d.L2.global [%0, {%1, %2}];" ::"l"(m), "r"(c0), "r"(c1) : "memory");
}
__device__ __forceinline__ void tma_pf3d(const CUtensorMap* m, int c0, int c1, int c2) {
  asm volatile("cp.async.bulk.prefetch.tensor.3d.L2.global [%0, {%1, %2, %3}];" ::"l"(m), "r"(c0), "r"(c1), "r"(c2) : "memory");
}
__device__ __forceinline__ void prefetch_tmap(const CUtensorMap* m) {
  asm volatile("prefetch.tensormap [%0];" ::"l"(m) : "memory");
}
__device__ __forceinline__ void cluster_sync() {
  asm volatile("barrier.cluster.arrive.aligned;\nbarrier.cluster.wait.aligned;" ::: "memory");
}
__device__ __forceinline__ uint32_t cluster_rank() {
  uint32_t r;
  asm volatile("mov.u32 %0, %%cluster_ctarank;" : "=r"(r));
  return r;
}
__device__ __forceinline__ bool elect_one() {
  uint32_t p;
  asm volatile("{\n.reg .pred q;\nelect.sync _|q, 0xffffffff;\nselp.u32 %0, 1, 0, q;\n}" : "=r"(p));
  return p;
}
__device__ __forceinline__ void pdl_wait() { asm volatile("griddepcontrol.wait;" ::: "memory"); }
__device__ __forceinline__ void pdl_launch() { asm volatile("griddepcontrol.launch_dependents;" ::: "memory"); }
__device__ __forceinline__ void ldsm_x4(uint32_t& r0, uint32_t& r1, uint32_t& r2, uint32_t& r3, uint32_t addr) {
  asm volatile("ldmatrix.sync.aligned.m8n8.x4.shared.b16 {%0, %1, %2, %3}, [%4];" : "=r"(r0), "=r"(r1), "=r"(r2), "=r"(r3) : "r"(addr) : "memory");
}
__device__ __forceinline__ void wg_fence() { asm volatile("wgmma.fence.sync.aligned;" ::: "memory"); }
__device__ __forceinline__ void wg_commit() { asm volatile("wgmma.commit_group.sync.aligned;" ::: "memory"); }
template <int N>
__device__ __forceinline__ void wg_wait() { asm volatile("wgmma.wait_group.sync.aligned %0;" ::"n"(N) : "memory"); }
template <int N>
__device__ __forceinline__ void reg_alloc() { asm volatile("setmaxnreg.inc.sync.aligned.u32 %0;" ::"n"(N)); }
template <int N>
__device__ __forceinline__ void reg_dealloc() { asm volatile("setmaxnreg.dec.sync.aligned.u32 %0;" ::"n"(N)); }
__device__ __forceinline__ void bar_sync(int id, int n) { asm volatile("bar.sync %0, %1;" ::"r"(id), "r"(n) : "memory"); }
__device__ __forceinline__ void bar_arrive(int id, int n) { asm volatile("bar.arrive %0, %1;" ::"r"(id), "r"(n) : "memory"); }
template <int NT>
__device__ __forceinline__ void fence_regs(float (&d)[NT]) {
#pragma unroll
  for (int i = 0; i < NT; i++) asm volatile("" : "+f"(d[i])::"memory");
}
template <int NT>
__device__ __forceinline__ void fence_regs(uint32_t (&d)[NT]) {
#pragma unroll
  for (int i = 0; i < NT; i++) asm volatile("" : "+r"(d[i])::"memory");
}
__device__ __forceinline__ uint64_t make_desc(uint32_t saddr, uint32_t lbo, uint32_t sbo, uint32_t layout) {
  return (uint64_t)((saddr & 0x3FFFF) >> 4) | ((uint64_t)(lbo >> 4) << 16) | ((uint64_t)(sbo >> 4) << 32) | ((uint64_t)layout << 62);
}
__device__ __forceinline__ uint32_t pack_bf16(float lo, float hi) {
  uint32_t r;
  asm("cvt.rn.bf16x2.f32 %0, %1, %2;" : "=r"(r) : "f"(hi), "f"(lo));
  return r;
}
__device__ __forceinline__ float ex2(float x) {
  float r;
  asm("ex2.approx.ftz.f32 %0, %1;" : "=f"(r) : "f"(x));
  return r;
}
__device__ __forceinline__ void st_v4(void* p, uint32_t a, uint32_t b, uint32_t c, uint32_t d) {
#define ST_MOD ""
  asm volatile("st.global" ST_MOD ".v4.b32 [%0], {%1, %2, %3, %4};" ::"l"(p), "r"(a), "r"(b), "r"(c), "r"(d) : "memory");
}
__device__ __forceinline__ float bf_lo(uint32_t v) { return __uint_as_float(v << 16); }
__device__ __forceinline__ float bf_hi(uint32_t v) { return __uint_as_float(v & 0xFFFF0000u); }

__device__ __forceinline__ void quad_transpose(uint32_t& a0, uint32_t& a1, uint32_t& a2, uint32_t& a3, int q) {
  const bool o1 = q & 1, o2 = q & 2;
  uint32_t t0 = o1 ? a0 : a1, t1 = o1 ? a2 : a3;
  t0 = __shfl_xor_sync(0xffffffffu, t0, 1);
  t1 = __shfl_xor_sync(0xffffffffu, t1, 1);
  if (o1) { a0 = t0; a2 = t1; } else { a1 = t0; a3 = t1; }
  t0 = o2 ? a0 : a2;
  t1 = o2 ? a1 : a3;
  t0 = __shfl_xor_sync(0xffffffffu, t0, 2);
  t1 = __shfl_xor_sync(0xffffffffu, t1, 2);
  if (o2) { a0 = t0; a1 = t1; } else { a2 = t0; a3 = t1; }
}

template<int TB, int OFF, int NT>
__device__ __forceinline__ void wgmma_ss_n256(float (&d)[NT], uint64_t da, uint64_t db, int scale_d) {
  asm volatile("{\n.reg .pred p;\nsetp.ne.b32 p, %130, 0;\n"
    "wgmma.mma_async.sync.aligned.m64n256k16.f32.bf16.bf16 {%0, %1, %2, %3, %4, %5, %6, %7, %8, %9, %10, %11, %12, %13, %14, %15, %16, %17, %18, %19, %20, %21, %22, %23, %24, %25, %26, %27, %28, %29, %30, %31, %32, %33, %34, %35, %36, %37, %38, %39, %40, %41, %42, %43, %44, %45, %46, %47, %48, %49, %50, %51, %52, %53, %54, %55, %56, %57, %58, %59, %60, %61, %62, %63, %64, %65, %66, %67, %68, %69, %70, %71, %72, %73, %74, %75, %76, %77, %78, %79, %80, %81, %82, %83, %84, %85, %86, %87, %88, %89, %90, %91, %92, %93, %94, %95, %96, %97, %98, %99, %100, %101, %102, %103, %104, %105, %106, %107, %108, %109, %110, %111, %112, %113, %114, %115, %116, %117, %118, %119, %120, %121, %122, %123, %124, %125, %126, %127}, %128, %129, p, 1, 1, 0, %131;\n}\n"
    : "+f"(d[OFF+0]), "+f"(d[OFF+1]), "+f"(d[OFF+2]), "+f"(d[OFF+3]), "+f"(d[OFF+4]), "+f"(d[OFF+5]), "+f"(d[OFF+6]), "+f"(d[OFF+7]), "+f"(d[OFF+8]), "+f"(d[OFF+9]), "+f"(d[OFF+10]), "+f"(d[OFF+11]), "+f"(d[OFF+12]), "+f"(d[OFF+13]), "+f"(d[OFF+14]), "+f"(d[OFF+15]), "+f"(d[OFF+16]), "+f"(d[OFF+17]), "+f"(d[OFF+18]), "+f"(d[OFF+19]), "+f"(d[OFF+20]), "+f"(d[OFF+21]), "+f"(d[OFF+22]), "+f"(d[OFF+23]), "+f"(d[OFF+24]), "+f"(d[OFF+25]), "+f"(d[OFF+26]), "+f"(d[OFF+27]), "+f"(d[OFF+28]), "+f"(d[OFF+29]), "+f"(d[OFF+30]), "+f"(d[OFF+31]), "+f"(d[OFF+32]), "+f"(d[OFF+33]), "+f"(d[OFF+34]), "+f"(d[OFF+35]), "+f"(d[OFF+36]), "+f"(d[OFF+37]), "+f"(d[OFF+38]), "+f"(d[OFF+39]), "+f"(d[OFF+40]), "+f"(d[OFF+41]), "+f"(d[OFF+42]), "+f"(d[OFF+43]), "+f"(d[OFF+44]), "+f"(d[OFF+45]), "+f"(d[OFF+46]), "+f"(d[OFF+47]), "+f"(d[OFF+48]), "+f"(d[OFF+49]), "+f"(d[OFF+50]), "+f"(d[OFF+51]), "+f"(d[OFF+52]), "+f"(d[OFF+53]), "+f"(d[OFF+54]), "+f"(d[OFF+55]), "+f"(d[OFF+56]), "+f"(d[OFF+57]), "+f"(d[OFF+58]), "+f"(d[OFF+59]), "+f"(d[OFF+60]), "+f"(d[OFF+61]), "+f"(d[OFF+62]), "+f"(d[OFF+63]), "+f"(d[OFF+64]), "+f"(d[OFF+65]), "+f"(d[OFF+66]), "+f"(d[OFF+67]), "+f"(d[OFF+68]), "+f"(d[OFF+69]), "+f"(d[OFF+70]), "+f"(d[OFF+71]), "+f"(d[OFF+72]), "+f"(d[OFF+73]), "+f"(d[OFF+74]), "+f"(d[OFF+75]), "+f"(d[OFF+76]), "+f"(d[OFF+77]), "+f"(d[OFF+78]), "+f"(d[OFF+79]), "+f"(d[OFF+80]), "+f"(d[OFF+81]), "+f"(d[OFF+82]), "+f"(d[OFF+83]), "+f"(d[OFF+84]), "+f"(d[OFF+85]), "+f"(d[OFF+86]), "+f"(d[OFF+87]), "+f"(d[OFF+88]), "+f"(d[OFF+89]), "+f"(d[OFF+90]), "+f"(d[OFF+91]), "+f"(d[OFF+92]), "+f"(d[OFF+93]), "+f"(d[OFF+94]), "+f"(d[OFF+95]), "+f"(d[OFF+96]), "+f"(d[OFF+97]), "+f"(d[OFF+98]), "+f"(d[OFF+99]), "+f"(d[OFF+100]), "+f"(d[OFF+101]), "+f"(d[OFF+102]), "+f"(d[OFF+103]), "+f"(d[OFF+104]), "+f"(d[OFF+105]), "+f"(d[OFF+106]), "+f"(d[OFF+107]), "+f"(d[OFF+108]), "+f"(d[OFF+109]), "+f"(d[OFF+110]), "+f"(d[OFF+111]), "+f"(d[OFF+112]), "+f"(d[OFF+113]), "+f"(d[OFF+114]), "+f"(d[OFF+115]), "+f"(d[OFF+116]), "+f"(d[OFF+117]), "+f"(d[OFF+118]), "+f"(d[OFF+119]), "+f"(d[OFF+120]), "+f"(d[OFF+121]), "+f"(d[OFF+122]), "+f"(d[OFF+123]), "+f"(d[OFF+124]), "+f"(d[OFF+125]), "+f"(d[OFF+126]), "+f"(d[OFF+127])
    : "l"(da), "l"(db), "r"(scale_d), "n"(TB));
}
template<int TB, int OFF, int NT>
__device__ __forceinline__ void wgmma_ss_n192(float (&d)[NT], uint64_t da, uint64_t db, int scale_d) {
  asm volatile("{\n.reg .pred p;\nsetp.ne.b32 p, %98, 0;\n"
    "wgmma.mma_async.sync.aligned.m64n192k16.f32.bf16.bf16 {%0, %1, %2, %3, %4, %5, %6, %7, %8, %9, %10, %11, %12, %13, %14, %15, %16, %17, %18, %19, %20, %21, %22, %23, %24, %25, %26, %27, %28, %29, %30, %31, %32, %33, %34, %35, %36, %37, %38, %39, %40, %41, %42, %43, %44, %45, %46, %47, %48, %49, %50, %51, %52, %53, %54, %55, %56, %57, %58, %59, %60, %61, %62, %63, %64, %65, %66, %67, %68, %69, %70, %71, %72, %73, %74, %75, %76, %77, %78, %79, %80, %81, %82, %83, %84, %85, %86, %87, %88, %89, %90, %91, %92, %93, %94, %95}, %96, %97, p, 1, 1, 0, %99;\n}\n"
    : "+f"(d[OFF+0]), "+f"(d[OFF+1]), "+f"(d[OFF+2]), "+f"(d[OFF+3]), "+f"(d[OFF+4]), "+f"(d[OFF+5]), "+f"(d[OFF+6]), "+f"(d[OFF+7]), "+f"(d[OFF+8]), "+f"(d[OFF+9]), "+f"(d[OFF+10]), "+f"(d[OFF+11]), "+f"(d[OFF+12]), "+f"(d[OFF+13]), "+f"(d[OFF+14]), "+f"(d[OFF+15]), "+f"(d[OFF+16]), "+f"(d[OFF+17]), "+f"(d[OFF+18]), "+f"(d[OFF+19]), "+f"(d[OFF+20]), "+f"(d[OFF+21]), "+f"(d[OFF+22]), "+f"(d[OFF+23]), "+f"(d[OFF+24]), "+f"(d[OFF+25]), "+f"(d[OFF+26]), "+f"(d[OFF+27]), "+f"(d[OFF+28]), "+f"(d[OFF+29]), "+f"(d[OFF+30]), "+f"(d[OFF+31]), "+f"(d[OFF+32]), "+f"(d[OFF+33]), "+f"(d[OFF+34]), "+f"(d[OFF+35]), "+f"(d[OFF+36]), "+f"(d[OFF+37]), "+f"(d[OFF+38]), "+f"(d[OFF+39]), "+f"(d[OFF+40]), "+f"(d[OFF+41]), "+f"(d[OFF+42]), "+f"(d[OFF+43]), "+f"(d[OFF+44]), "+f"(d[OFF+45]), "+f"(d[OFF+46]), "+f"(d[OFF+47]), "+f"(d[OFF+48]), "+f"(d[OFF+49]), "+f"(d[OFF+50]), "+f"(d[OFF+51]), "+f"(d[OFF+52]), "+f"(d[OFF+53]), "+f"(d[OFF+54]), "+f"(d[OFF+55]), "+f"(d[OFF+56]), "+f"(d[OFF+57]), "+f"(d[OFF+58]), "+f"(d[OFF+59]), "+f"(d[OFF+60]), "+f"(d[OFF+61]), "+f"(d[OFF+62]), "+f"(d[OFF+63]), "+f"(d[OFF+64]), "+f"(d[OFF+65]), "+f"(d[OFF+66]), "+f"(d[OFF+67]), "+f"(d[OFF+68]), "+f"(d[OFF+69]), "+f"(d[OFF+70]), "+f"(d[OFF+71]), "+f"(d[OFF+72]), "+f"(d[OFF+73]), "+f"(d[OFF+74]), "+f"(d[OFF+75]), "+f"(d[OFF+76]), "+f"(d[OFF+77]), "+f"(d[OFF+78]), "+f"(d[OFF+79]), "+f"(d[OFF+80]), "+f"(d[OFF+81]), "+f"(d[OFF+82]), "+f"(d[OFF+83]), "+f"(d[OFF+84]), "+f"(d[OFF+85]), "+f"(d[OFF+86]), "+f"(d[OFF+87]), "+f"(d[OFF+88]), "+f"(d[OFF+89]), "+f"(d[OFF+90]), "+f"(d[OFF+91]), "+f"(d[OFF+92]), "+f"(d[OFF+93]), "+f"(d[OFF+94]), "+f"(d[OFF+95])
    : "l"(da), "l"(db), "r"(scale_d), "n"(TB));
}
template<int TB, int OFF, int NT>
__device__ __forceinline__ void wgmma_ss_n128(float (&d)[NT], uint64_t da, uint64_t db, int scale_d) {
  asm volatile("{\n.reg .pred p;\nsetp.ne.b32 p, %66, 0;\n"
    "wgmma.mma_async.sync.aligned.m64n128k16.f32.bf16.bf16 {%0, %1, %2, %3, %4, %5, %6, %7, %8, %9, %10, %11, %12, %13, %14, %15, %16, %17, %18, %19, %20, %21, %22, %23, %24, %25, %26, %27, %28, %29, %30, %31, %32, %33, %34, %35, %36, %37, %38, %39, %40, %41, %42, %43, %44, %45, %46, %47, %48, %49, %50, %51, %52, %53, %54, %55, %56, %57, %58, %59, %60, %61, %62, %63}, %64, %65, p, 1, 1, 0, %67;\n}\n"
    : "+f"(d[OFF+0]), "+f"(d[OFF+1]), "+f"(d[OFF+2]), "+f"(d[OFF+3]), "+f"(d[OFF+4]), "+f"(d[OFF+5]), "+f"(d[OFF+6]), "+f"(d[OFF+7]), "+f"(d[OFF+8]), "+f"(d[OFF+9]), "+f"(d[OFF+10]), "+f"(d[OFF+11]), "+f"(d[OFF+12]), "+f"(d[OFF+13]), "+f"(d[OFF+14]), "+f"(d[OFF+15]), "+f"(d[OFF+16]), "+f"(d[OFF+17]), "+f"(d[OFF+18]), "+f"(d[OFF+19]), "+f"(d[OFF+20]), "+f"(d[OFF+21]), "+f"(d[OFF+22]), "+f"(d[OFF+23]), "+f"(d[OFF+24]), "+f"(d[OFF+25]), "+f"(d[OFF+26]), "+f"(d[OFF+27]), "+f"(d[OFF+28]), "+f"(d[OFF+29]), "+f"(d[OFF+30]), "+f"(d[OFF+31]), "+f"(d[OFF+32]), "+f"(d[OFF+33]), "+f"(d[OFF+34]), "+f"(d[OFF+35]), "+f"(d[OFF+36]), "+f"(d[OFF+37]), "+f"(d[OFF+38]), "+f"(d[OFF+39]), "+f"(d[OFF+40]), "+f"(d[OFF+41]), "+f"(d[OFF+42]), "+f"(d[OFF+43]), "+f"(d[OFF+44]), "+f"(d[OFF+45]), "+f"(d[OFF+46]), "+f"(d[OFF+47]), "+f"(d[OFF+48]), "+f"(d[OFF+49]), "+f"(d[OFF+50]), "+f"(d[OFF+51]), "+f"(d[OFF+52]), "+f"(d[OFF+53]), "+f"(d[OFF+54]), "+f"(d[OFF+55]), "+f"(d[OFF+56]), "+f"(d[OFF+57]), "+f"(d[OFF+58]), "+f"(d[OFF+59]), "+f"(d[OFF+60]), "+f"(d[OFF+61]), "+f"(d[OFF+62]), "+f"(d[OFF+63])
    : "l"(da), "l"(db), "r"(scale_d), "n"(TB));
}
template<int TB, int OFF, int NT>
__device__ __forceinline__ void wgmma_ss_n32(float (&d)[NT], uint64_t da, uint64_t db, int scale_d) {
  asm volatile("{\n.reg .pred p;\nsetp.ne.b32 p, %18, 0;\n"
    "wgmma.mma_async.sync.aligned.m64n32k16.f32.bf16.bf16 {%0, %1, %2, %3, %4, %5, %6, %7, %8, %9, %10, %11, %12, %13, %14, %15}, %16, %17, p, 1, 1, 0, %19;\n}\n"
    : "+f"(d[OFF+0]), "+f"(d[OFF+1]), "+f"(d[OFF+2]), "+f"(d[OFF+3]), "+f"(d[OFF+4]), "+f"(d[OFF+5]), "+f"(d[OFF+6]), "+f"(d[OFF+7]), "+f"(d[OFF+8]), "+f"(d[OFF+9]), "+f"(d[OFF+10]), "+f"(d[OFF+11]), "+f"(d[OFF+12]), "+f"(d[OFF+13]), "+f"(d[OFF+14]), "+f"(d[OFF+15])
    : "l"(da), "l"(db), "r"(scale_d), "n"(TB));
}
template<int TB, int OFF, int NT>
__device__ __forceinline__ void wgmma_rs_n128(float (&d)[NT], uint32_t a0, uint32_t a1, uint32_t a2, uint32_t a3, uint64_t db, int scale_d) {
  asm volatile("{\n.reg .pred p;\nsetp.ne.b32 p, %69, 0;\n"
    "wgmma.mma_async.sync.aligned.m64n128k16.f32.bf16.bf16 {%0, %1, %2, %3, %4, %5, %6, %7, %8, %9, %10, %11, %12, %13, %14, %15, %16, %17, %18, %19, %20, %21, %22, %23, %24, %25, %26, %27, %28, %29, %30, %31, %32, %33, %34, %35, %36, %37, %38, %39, %40, %41, %42, %43, %44, %45, %46, %47, %48, %49, %50, %51, %52, %53, %54, %55, %56, %57, %58, %59, %60, %61, %62, %63}, {%64, %65, %66, %67}, %68, p, 1, 1, %70;\n}\n"
    : "+f"(d[OFF+0]), "+f"(d[OFF+1]), "+f"(d[OFF+2]), "+f"(d[OFF+3]), "+f"(d[OFF+4]), "+f"(d[OFF+5]), "+f"(d[OFF+6]), "+f"(d[OFF+7]), "+f"(d[OFF+8]), "+f"(d[OFF+9]), "+f"(d[OFF+10]), "+f"(d[OFF+11]), "+f"(d[OFF+12]), "+f"(d[OFF+13]), "+f"(d[OFF+14]), "+f"(d[OFF+15]), "+f"(d[OFF+16]), "+f"(d[OFF+17]), "+f"(d[OFF+18]), "+f"(d[OFF+19]), "+f"(d[OFF+20]), "+f"(d[OFF+21]), "+f"(d[OFF+22]), "+f"(d[OFF+23]), "+f"(d[OFF+24]), "+f"(d[OFF+25]), "+f"(d[OFF+26]), "+f"(d[OFF+27]), "+f"(d[OFF+28]), "+f"(d[OFF+29]), "+f"(d[OFF+30]), "+f"(d[OFF+31]), "+f"(d[OFF+32]), "+f"(d[OFF+33]), "+f"(d[OFF+34]), "+f"(d[OFF+35]), "+f"(d[OFF+36]), "+f"(d[OFF+37]), "+f"(d[OFF+38]), "+f"(d[OFF+39]), "+f"(d[OFF+40]), "+f"(d[OFF+41]), "+f"(d[OFF+42]), "+f"(d[OFF+43]), "+f"(d[OFF+44]), "+f"(d[OFF+45]), "+f"(d[OFF+46]), "+f"(d[OFF+47]), "+f"(d[OFF+48]), "+f"(d[OFF+49]), "+f"(d[OFF+50]), "+f"(d[OFF+51]), "+f"(d[OFF+52]), "+f"(d[OFF+53]), "+f"(d[OFF+54]), "+f"(d[OFF+55]), "+f"(d[OFF+56]), "+f"(d[OFF+57]), "+f"(d[OFF+58]), "+f"(d[OFF+59]), "+f"(d[OFF+60]), "+f"(d[OFF+61]), "+f"(d[OFF+62]), "+f"(d[OFF+63])
    : "r"(a0), "r"(a1), "r"(a2), "r"(a3), "l"(db), "r"(scale_d), "n"(TB));
}
template<int TB, int OFF, int NT>
__device__ __forceinline__ void wgmma_rs_n64(float (&d)[NT], uint32_t a0, uint32_t a1, uint32_t a2, uint32_t a3, uint64_t db, int scale_d) {
  asm volatile("{\n.reg .pred p;\nsetp.ne.b32 p, %37, 0;\n"
    "wgmma.mma_async.sync.aligned.m64n64k16.f32.bf16.bf16 {%0, %1, %2, %3, %4, %5, %6, %7, %8, %9, %10, %11, %12, %13, %14, %15, %16, %17, %18, %19, %20, %21, %22, %23, %24, %25, %26, %27, %28, %29, %30, %31}, {%32, %33, %34, %35}, %36, p, 1, 1, %38;\n}\n"
    : "+f"(d[OFF+0]), "+f"(d[OFF+1]), "+f"(d[OFF+2]), "+f"(d[OFF+3]), "+f"(d[OFF+4]), "+f"(d[OFF+5]), "+f"(d[OFF+6]), "+f"(d[OFF+7]), "+f"(d[OFF+8]), "+f"(d[OFF+9]), "+f"(d[OFF+10]), "+f"(d[OFF+11]), "+f"(d[OFF+12]), "+f"(d[OFF+13]), "+f"(d[OFF+14]), "+f"(d[OFF+15]), "+f"(d[OFF+16]), "+f"(d[OFF+17]), "+f"(d[OFF+18]), "+f"(d[OFF+19]), "+f"(d[OFF+20]), "+f"(d[OFF+21]), "+f"(d[OFF+22]), "+f"(d[OFF+23]), "+f"(d[OFF+24]), "+f"(d[OFF+25]), "+f"(d[OFF+26]), "+f"(d[OFF+27]), "+f"(d[OFF+28]), "+f"(d[OFF+29]), "+f"(d[OFF+30]), "+f"(d[OFF+31])
    : "r"(a0), "r"(a1), "r"(a2), "r"(a3), "l"(db), "r"(scale_d), "n"(TB));
}

__device__ __forceinline__ void wait_flag(const unsigned int* f, uint32_t target) {
  uint32_t v;
#pragma unroll 1
  for (uint32_t spins = 0; spins < (1u << 22); spins++) {
    asm volatile("ld.acquire.gpu.global.u32 %0, [%1];" : "=r"(v) : "l"(f) : "memory");
    if (v >= target) break;
    __nanosleep(100);
  }
}
__device__ __forceinline__ uint32_t lds32(uint32_t a) {
  uint32_t v;
  asm volatile("ld.shared.u32 %0, [%1];" : "=r"(v) : "r"(a) : "memory");
  return v;
}
__device__ __forceinline__ float gate_row(int row, int lane, const bf16* __restrict__ x, const bf16* __restrict__ gate_w) {
  const uint32_t* xr = reinterpret_cast<const uint32_t*>(x + (size_t)row * DM);
  const uint32_t* gw2 = reinterpret_cast<const uint32_t*>(gate_w);
  float gs = 0.f;
#pragma unroll
  for (int i = 0; i < 9; i++) {
    const uint32_t a = __ldg(xr + lane + 32 * i), b = __ldg(gw2 + lane + 32 * i);
    gs = fmaf(bf_lo(a), bf_lo(b), gs);
    gs = fmaf(bf_hi(a), bf_hi(b), gs);
  }
#pragma unroll
  for (int o = 16; o; o >>= 1) gs += __shfl_xor_sync(0xffffffffu, gs, o);
  const float g = 1.f / (1.f + __expf(-gs));
  if (lane == 0) g_gate[row] = g;
  return g;
}
#define LA_UNROLL 1
__device__ __forceinline__ void local_rows2(int rb, int ri, uint32_t sL, uint32_t bL2, int lane, float ga, float gb) {
  const float scale_l2 = 0.23570226039551584f * 1.4426950408889634f;
  constexpr int U = LA_UNROLL;
  const uint32_t sq = sL + (30 + ri) * 1152;
  const uint32_t kb = sL + (14 + ri) * 1152 + lane * 36;
  float ma = -INFINITY, mb = -INFINITY;
  {
    float qa[18], qb[18];
#pragma unroll
    for (int i = 0; i < 9; i++) {
      const uint32_t u = lds32(sq - 2304 + lane * 36 + 4 * i), v = lds32(sq + lane * 36 + 4 * i);
      qa[2 * i] = bf_lo(u); qa[2 * i + 1] = bf_hi(u);
      qb[2 * i] = bf_lo(v); qb[2 * i + 1] = bf_hi(v);
    }
    __syncwarp();
#pragma unroll U
    for (int t = 0; t < 9; t++) {
      const bool ok = rb - 2 * t >= 0;
      float a0 = 0.f, a1 = 0.f, b0 = 0.f, b1 = 0.f;
#pragma unroll
      for (int i = 0; i < 9; i++) {
        const uint32_t k = lds32(kb - t * 2304 + 4 * i);
        const float lo = bf_lo(k), hi = bf_hi(k);
        a0 = fmaf(qa[2 * i], lo, a0); a1 = fmaf(qa[2 * i + 1], hi, a1);
        b0 = fmaf(qb[2 * i], lo, b0); b1 = fmaf(qb[2 * i + 1], hi, b1);
      }
      a0 = (ok && t > 0) ? a0 + a1 : -INFINITY;
      b0 = (ok && t < 8) ? b0 + b1 : -INFINITY;
      ma = fmaxf(ma, a0);
      mb = fmaxf(mb, b0);
      asm volatile("st.shared.f32 [%0], %1;" ::"r"(sq - 2304 + t * 128 + lane * 4), "f"(a0) : "memory");
      asm volatile("st.shared.f32 [%0], %1;" ::"r"(sq + t * 128 + lane * 4), "f"(b0) : "memory");
    }
  }
  float oa[18], ob[18], sa = 0.f, sb = 0.f;
#pragma unroll
  for (int i = 0; i < 18; i++) { oa[i] = 0.f; ob[i] = 0.f; }
  mbar_wait(bL2, 0);
#pragma unroll U
  for (int t = 0; t < 9; t++) {
    const float wa = ex2((__uint_as_float(lds32(sq - 2304 + t * 128 + lane * 4)) - ma) * scale_l2);
    const float wb = ex2((__uint_as_float(lds32(sq + t * 128 + lane * 4)) - mb) * scale_l2);
    sa += wa;
    sb += wb;
#pragma unroll
    for (int i = 0; i < 9; i++) {
      const uint32_t v = lds32(kb + 46 * 1152 - t * 2304 + 4 * i);
      const float lo = bf_lo(v), hi = bf_hi(v);
      oa[2 * i] = fmaf(wa, lo, oa[2 * i]); oa[2 * i + 1] = fmaf(wa, hi, oa[2 * i + 1]);
      ob[2 * i] = fmaf(wb, lo, ob[2 * i]); ob[2 * i + 1] = fmaf(wb, hi, ob[2 * i + 1]);
    }
  }
  ga = __fdividef(ga, sa);
  gb = __fdividef(gb, sb);
  __syncwarp();
#pragma unroll
  for (int i = 0; i < 9; i++) {
    asm volatile("st.shared.u32 [%0], %1;" ::"r"(sq - 2304 + lane * 36 + 4 * i), "r"(pack_bf16(oa[2 * i] * ga, oa[2 * i + 1] * ga)) : "memory");
    asm volatile("st.shared.u32 [%0], %1;" ::"r"(sq + lane * 36 + 4 * i), "r"(pack_bf16(ob[2 * i] * gb, ob[2 * i + 1] * gb)) : "memory");
  }
  __syncwarp();
  uint32_t w[5][4];
#pragma unroll
  for (int t = 0; t < 5; t++) {
    const int c = min(t * 32 + lane, 143), r = c >= 72;
    asm volatile("ld.shared.v4.u32 {%0, %1, %2, %3}, [%4];" : "=r"(w[t][0]), "=r"(w[t][1]), "=r"(w[t][2]), "=r"(w[t][3])
                 : "r"(sq - 2304 + r * 2304 + (c - r * 72) * 16) : "memory");
  }
  asm volatile("fence.proxy.async.shared::cta;" ::: "memory");
  bar_arrive(4, 256 + 32);
#pragma unroll
  for (int t = 0; t < 5; t++) {
    const int c = min(t * 32 + lane, 143), r = c >= 72;
    st_v4(g_ctx + (size_t)(rb - 2 + 2 * r) * KCAT + HDIM + (c - r * 72) * 8, w[t][0], w[t][1], w[t][2], w[t][3]);
  }
}

#define K1_NST 6
constexpr int K1_BST = K1_NST;
constexpr int K1_MAXJOBS = 11;
constexpr uint32_t K1_FLAG_TARGET = 7;
constexpr uint32_t RDY_TARGET = 48;
constexpr uint32_t GATE_TARGET = 128 * 3;
struct alignas(64) Params {
  CUtensorMap tmA[2];
  CUtensorMap tmW[4];
  CUtensorMap tmQ, tmK, tmV;
  CUtensorMap tmL[2];
  CUtensorMap tmC, tmO[2], tmOt[2];
  uint16_t jobs[NCLUSTER][K1_MAXJOBS];
  uint8_t order[256];
};

struct K1State {
  uint32_t bs, bph, aph;
  bf16* pp;
  int pld8;
  int png;
};
__device__ __forceinline__ void k1_flag(const K1State& st, int lane, uint32_t bS) {
  if (st.png) {
    __syncwarp();
    if (lane == 0) mbar_arrive(bS);
  }
}

__device__ __forceinline__ void k1_tile(float (&acc)[128], uint32_t (&pk)[64], K1State& st, uint32_t job, uint32_t sA, uint32_t sB,
                                        uint32_t bAf, uint32_t bAe, uint32_t bBf, uint32_t bBe, uint32_t bS, int wg, int warp, int lane, uint32_t rank) {
  const int a_sel = (job >> 2) & 1, mpair = (job >> 3) & 7, w_sel = (job >> 6) & 3, chunk0 = (job >> 8) & 63;
  const bool newA = (job >> 14) & 1, lastA = (job >> 15) & 1;
  const bool sig = (lane == 0) && (warp < 2);
  const bool siga = lastA && (lane == 0) && (warp == 2);
  const int KC = 8 + a_sel;
  uint32_t prev_bs = 0, prev2_bs = 0, a8_bs = 0;
#pragma unroll
  for (int kc = 0; kc < 9; kc++) {
    if (kc >= KC) break;
    uint32_t abase = sA + ((kc + 2) & 7) * 16384;
    if (kc == 8) {
      mbar_wait(bBf + st.bs * 8, st.bph);
      a8_bs = st.bs;
      abase = sB + st.bs * 16384;
      if (++st.bs == K1_BST) { st.bs = 0; st.bph ^= 1; }
    } else if (newA) {
      mbar_wait(bAf + kc * 8, st.aph);
    }
    const uint64_t da = make_desc(abase + wg * 8192, 16, 1024, 1);
#pragma unroll
    for (int ks = 0; ks < 2; ks++) {
      mbar_wait(bBf + st.bs * 8, st.bph);
      const uint64_t db = make_desc(sB + st.bs * 16384, 2048, 1024, 1);
      wg_fence();
      wgmma_ss_n256<1, 0>(acc, da + (uint64_t)(ks * 4), db, (ks > 0) ? 1 : (kc > 0));
      wgmma_ss_n256<1, 0>(acc, da + (uint64_t)(ks * 4 + 2), db + (uint64_t)512, 1);
      wg_commit();
      const int PO = (kc < 8 ? kc : 0) * 8;
      wg_wait<1>();
      if (ks > 0 || kc > 0) {
        if (sig) mbar_arrive_cluster(bBe + prev_bs * 8, warp);
        if (ks == 0 && siga) mbar_arrive(bAe + (kc - 1) * 8);
      }
      if (kc < st.png) st_v4(st.pp + kc * 32 + ks * st.pld8, pk[PO + ks * 4], pk[PO + ks * 4 + 1], pk[PO + ks * 4 + 2], pk[PO + ks * 4 + 3]);
      prev_bs = st.bs;
      if (++st.bs == K1_BST) { st.bs = 0; st.bph ^= 1; }
    }
  }
  if (newA) st.aph ^= 1;
  k1_flag(st, lane, bS);
  wg_wait<0>();
  fence_regs(acc);
  if (sig) {
    mbar_arrive_cluster(bBe + prev_bs * 8, warp);
    if (a_sel) mbar_arrive_cluster(bBe + a8_bs * 8, warp);
  }
  if (siga && !a_sel) mbar_arrive(bAe + 7 * 8);
  const bool isA = (w_sel == 2);
  bf16* out = (w_sel == 0) ? g_K : (w_sel == 1) ? g_V : isA ? g_QKVA : g_Q;
  const int ld = isA ? NQKVA : HDIM;
  const int row = mpair * 256 + rank * 128 + wg * 64 + warp * 16 + (lane >> 2);
  st.pp = out + (size_t)row * ld + chunk0 * 64 + (lane & 3) * 8;
  st.pld8 = 8 * ld;
  st.png = ((job & 3) + 1) * 2;
#pragma unroll
  for (int G = 0; G < 8; G++) {
    pk[G * 8 + 0] = pack_bf16(acc[G * 16 + 0], acc[G * 16 + 1]);
    pk[G * 8 + 1] = pack_bf16(acc[G * 16 + 4], acc[G * 16 + 5]);
    pk[G * 8 + 2] = pack_bf16(acc[G * 16 + 8], acc[G * 16 + 9]);
    pk[G * 8 + 3] = pack_bf16(acc[G * 16 + 12], acc[G * 16 + 13]);
    pk[G * 8 + 4] = pack_bf16(acc[G * 16 + 2], acc[G * 16 + 3]);
    pk[G * 8 + 5] = pack_bf16(acc[G * 16 + 6], acc[G * 16 + 7]);
    pk[G * 8 + 6] = pack_bf16(acc[G * 16 + 10], acc[G * 16 + 11]);
    pk[G * 8 + 7] = pack_bf16(acc[G * 16 + 14], acc[G * 16 + 15]);
  }
  if (isA) {
#pragma unroll
    for (int G = 0; G < 16; G++) quad_transpose(pk[G * 4 + 0], pk[G * 4 + 1], pk[G * 4 + 2], pk[G * 4 + 3], lane & 3);
  }
}

#define HA(h) (h)
constexpr int K2_NST = 7;
constexpr uint32_t K2_END = 0x100;
constexpr int K3_NST = 4;
#define K3_P1 20
#define K3_P2 39
#define K3_P3 57
__device__ __forceinline__ uint32_t k3_rot(uint32_t sv) { return (0x00E9u >> (2 * sv)) & 3; }
__device__ __forceinline__ int k3_part(int i) { return (i == 0) ? 0 : (i == 1) ? K3_P1 : (i == 2) ? K3_P2 : (i == 3) ? K3_P3 : 73; }
constexpr int K3_STAGE = 16384 + 32768 + 4096;
constexpr int SMEM_DATA = 7 * 32768;
constexpr int SMEM_BYTES = SMEM_DATA + 1024 + 768;

struct Cursor {
  uint32_t s, ph;
  __device__ __forceinline__ void next() {
    if (++s == K2_NST) { s = 0; ph ^= 1; }
  }
};

#define TURN_SYNC() bar_sync(mybar, 256)
#define TURN_ARRIVE() bar_arrive(otherbar, 256)
#define RELEASE_IF(cur, cond) mbar_arrive_cluster_if(bE + (cur).s * 8, warp & 1, sig && (cond))
#define RELEASE(cur) RELEASE_IF(cur, true)
#define ISSUE_PV(cur, first)                                                                                   \
  do {                                                                                                         \
    const uint64_t dv = make_desc(sbase + (cur).s * 32768, 16384, 1024, 1);                                    \
    _Pragma("unroll") for (int t = 0; t < 8; t++)                                                              \
        wgmma_rs_n128<1, 0>(O, P[4 * t], P[4 * t + 1], P[4 * t + 2], P[4 * t + 3], dv + (uint64_t)(t * 128), (t > 0) ? 1 : !(first)); \
  } while (0)
#define RESCALE_O()                                                                                            \
  do {                                                                                                         \
    fence_regs(O);                                                                                             \
    _Pragma("unroll") for (int jj = 0; jj < 16; jj++) {                                                        \
      O[jj * 4 + 0] *= sc0; O[jj * 4 + 1] *= sc0; O[jj * 4 + 2] *= sc1; O[jj * 4 + 3] *= sc1;                  \
    }                                                                                                          \
    fence_regs(O);                                                                                             \
  } while (0)
#define ISSUE_QK(cur)                                                                                          \
  do {                                                                                                         \
    const uint64_t dk = make_desc(sbase + (cur).s * 32768, 16, 1024, 1);                                       \
    _Pragma("unroll") for (int t = 0; t < 8; t++)                                                              \
        wgmma_rs_n128<0, 0>(S, Q[4 * t], Q[4 * t + 1], Q[4 * t + 2], Q[4 * t + 3], dk + (uint64_t)((t >> 2) * 1024 + (t & 3) * 2), t > 0); \
  } while (0)
#define EPILOGUE()                                                                                             \
  do {                                                                                                         \
    l0 += __shfl_xor_sync(0xffffffffu, l0, 1);                                                                 \
    l0 += __shfl_xor_sync(0xffffffffu, l0, 2);                                                                 \
    l1 += __shfl_xor_sync(0xffffffffu, l1, 1);                                                                 \
    l1 += __shfl_xor_sync(0xffffffffu, l1, 2);                                                                 \
    const float f0 = __fdividef(gf0, l0), f1 = __fdividef(gf1, l1);                                                                \
    bf16* o0 = g_ctx + (size_t)prev_row * KCAT + prev_h * 128 + q * 8;                                         \
    bf16* o1 = o0 + (size_t)8 * KCAT;                                                                          \
    _Pragma("unroll") for (int G = 0; G < 4; G++) {                                                            \
      st_v4(o0 + G * 32, pack_bf16(O[G * 16 + 0] * f0, O[G * 16 + 1] * f0), pack_bf16(O[G * 16 + 4] * f0, O[G * 16 + 5] * f0), \
            pack_bf16(O[G * 16 + 8] * f0, O[G * 16 + 9] * f0), pack_bf16(O[G * 16 + 12] * f0, O[G * 16 + 13] * f0)); \
      st_v4(o1 + G * 32, pack_bf16(O[G * 16 + 2] * f1, O[G * 16 + 3] * f1), pack_bf16(O[G * 16 + 6] * f1, O[G * 16 + 7] * f1), \
            pack_bf16(O[G * 16 + 10] * f1, O[G * 16 + 11] * f1), pack_bf16(O[G * 16 + 14] * f1, O[G * 16 + 15] * f1)); \
    }                                                                                                          \
  } while (0)

__global__ void __cluster_dims__(2, 1, 1) __launch_bounds__(384, 1)
fused_kernel(const __grid_constant__ Params p, const bf16* __restrict__ x, const bf16* __restrict__ gate_w, bf16* __restrict__ out) {
  extern __shared__ uint8_t smem_raw[];
  const uint32_t sbase = (smem_u32(smem_raw) + 1023) & ~1023u;
  const uint32_t sB = sbase, sA = sbase + K1_BST * 16384, sBar = sbase + SMEM_DATA;
  const uint32_t bAf = sBar, bAe = sBar + 64, bBf = sBar + 128, bBe = sBar + 176, bL = sBar + 224, bS = sBar + 232, bL2 = sBar + 240, sL = sA + 32768;
  const uint32_t bF = sBar + 256, bE = sBar + 320, bT = sBar + 384, sTick = sBar + 400, sItem = sBar + 416, bS2 = sBar + 448, bR = sBar + 456, bLast = sBar + 464, bH = sBar + 472;
  const uint32_t b3F = sBar + 512, b3E = sBar + 544, sGate = sBar + 576;
  const int tid = threadIdx.x, warp_g = __shfl_sync(0xffffffffu, tid >> 5, 0), lane = tid & 31;
  const uint32_t rank = cluster_rank();
  const int cl = blockIdx.x >> 1;
  TSM(0);
  if (tid == 0) {
    for (int i = 0; i < 8; i++) { mbar_init(bAf + i * 8, 1); mbar_init(bAe + i * 8, 2); }
    for (int i = 0; i < K1_BST; i++) { mbar_init(bBf + i * 8, 1); mbar_init(bBe + i * 8, 4); }
    mbar_init(bL, 1);
    mbar_init(bL2, 1);
    mbar_init(bR, 1);
    mbar_init(bLast, 1);
    mbar_init(bH, 4);
    mbar_init(bS, 8);
    for (int i = 0; i < K2_NST; i++) { mbar_init(bF + i * 8, 1); mbar_init(bE + i * 8, 4); }
    mbar_init(bT, 1); mbar_init(bT + 8, 1);
    mbar_init(bS2, 8);
    for (int i = 0; i < K3_NST; i++) { mbar_init(b3F + i * 8, 1); mbar_init(b3E + i * 8, 4); }
    asm volatile("fence.mbarrier_init.release.cluster;" ::: "memory");
  }
  __syncthreads();
  cluster_sync();
  const int lr0 = blockIdx.x * 16;

  if (warp_g >= 8) {
    reg_dealloc<40>();
    if (warp_g == 8) {
      if (elect_one()) {
        uint32_t bs = 0, bph = 1, aph = 1;
#pragma unroll 1
        for (int ji = 0; ji < K1_MAXJOBS; ji++) {
          const uint32_t job = p.jobs[cl][ji];
          if (!(job & 3)) break;
          const int a_sel = (job >> 2) & 1, mpair = (job >> 3) & 7, chunk0 = (job >> 8) & 63;
          const bool newA = (job >> 14) & 1;
          const int KC = a_sel ? 9 : 8;
          const uint32_t halfbytes = 8192;
          const bool lastjob = (ji + 1 == K1_MAXJOBS) || !(p.jobs[cl][ji + 1] & 3);
          const CUtensorMap* tw = &p.tmW[(job >> 6) & 3];
          {
            const uint32_t njob = (ji + 1 < K1_MAXJOBS) ? p.jobs[cl][ji + 1] : 0;
            if (!(njob & 3) && !newA) mbar_arrive(bLast);
            if (njob & 3) {
              const int nst = ((njob >> 2) & 1) ? 18 : 16;
#pragma unroll 1
              for (int t = (cl < 64) ? (cl & 7) : 0; t < nst; t += (cl < 64) ? 8 : 1)
                tma_pf3d(&p.tmW[(njob >> 6) & 3], 0, t * 32 + rank * 16, (njob >> 8) & 63);
            }
          }
#pragma unroll 1
          for (int kc = 0; kc < KC; kc++) {
            if (kc == 8) {
              mbar_wait(bBe + bs * 8, bph);
              mbar_expect(bBf + bs * 8, 16384);
              tma2d(sB + bs * 16384, &p.tmA[1], bBf + bs * 8, 512, mpair * 256 + rank * 128);
              if (++bs == K1_BST) { bs = 0; bph ^= 1; }
            } else if (newA) {
              mbar_wait(bAe + kc * 8, aph);
              mbar_expect(bAf + kc * 8, 16384);
              tma2d(sA + ((kc + 2) & 7) * 16384, &p.tmA[a_sel], bAf + kc * 8, kc * 64, mpair * 256 + rank * 128);
              if (kc == 7 && lastjob) mbar_arrive(bLast);
            }
#pragma unroll 1
            for (int kk = 0; kk < 2; kk++) {
              mbar_wait(bBe + bs * 8, bph);
              mbar_expect(bBf + bs * 8, 2 * halfbytes);
              tma3d_mc(sB + bs * 16384 + rank * halfbytes, tw, bBf + bs * 8, 0, kc * 64 + kk * 32 + rank * 16, chunk0, 3);
              if (++bs == K1_BST) { bs = 0; bph ^= 1; }
            }
          }
          if (newA) aph ^= 1;
        }
        Cursor c{0, 0};
        int pcol = 0;
        uint32_t tick = cl, seen = 1u << (p.order[cl] >> 4);
        mbar_wait(bR, 0);
        asm volatile("fence.proxy.async.global;" ::: "memory");
#pragma unroll 1
        for (int it = 0;; it++) {
          const uint32_t item = (tick < 256) ? p.order[tick] : (K2_END | min(tick - 256, 255u));
          asm volatile("st.shared.u32 [%0], %1;" ::"r"(sItem + (it & 7) * 4), "r"(item) : "memory");
          if (item >= K2_END) break;
          const int h = item >> 3, j = item & 7;
          const int blk = 2 * j + (int)(rank ^ (it & 1));
          const int col = HA(h) * 128 + rank * 64;
          const int nb = 2 * j + 2;
          if (!((seen >> (h >> 1)) & 1)) {
            wait_flag(&g_sync[F_HP + (h >> 1)], RDY_TARGET);
            asm volatile("fence.proxy.async.global;" ::: "memory");
            seen |= 1u << (h >> 1);
          }
          mbar_wait(bE + c.s * 8, c.ph);
          mbar_expect(bF + c.s * 8, 32768);
          tma2d(sbase + c.s * 32768, &p.tmQ, bF + c.s * 8, HA(h) * 128, blk * 128);
          tma2d(sbase + c.s * 32768 + 16384, &p.tmQ, bF + c.s * 8, HA(h) * 128 + 64, blk * 128);
          c.next();
#pragma unroll 1
          for (int n = nb - 1; n >= 0; n--) {
            if (n == 0 && rank == 0) tick = atomicAdd(&g_sync[F_TICK], 1u) + NCLUSTER;
            mbar_wait(bE + c.s * 8, c.ph);
            mbar_expect(bF + c.s * 8, 32768);
            tma2d_mc(sbase + c.s * 32768 + rank * 16384, &p.tmK, bF + c.s * 8, col, n * 128, 3);
            c.next();
            if (n < nb - 1 || it > 0) {
              mbar_wait(bE + c.s * 8, c.ph);
              mbar_expect(bF + c.s * 8, 32768);
              tma2d_mc(sbase + c.s * 32768 + rank * 16384, &p.tmV, bF + c.s * 8, (n < nb - 1) ? col : pcol, (n < nb - 1) ? (n + 1) * 128 : 0, 3);
              c.next();
            }
          }
          pcol = col;
          if (rank == 0) {
            asm volatile(
                "{\n.reg .b32 a, b;\nmapa.shared::cluster.u32 a, %0, 1;\nmapa.shared::cluster.u32 b, %1, 1;\n"
                "st.async.shared::cluster.mbarrier::complete_tx::bytes.u32 [a], %2, [b];\n}" ::"r"(sTick + (it & 1) * 4),
                "r"(bT + (it & 1) * 8), "r"(tick) : "memory");
          } else {
            mbar_expect(bT + (it & 1) * 8, 4);
            mbar_wait(bT + (it & 1) * 8, (it >> 1) & 1);
            tick = lds32(sTick + (it & 1) * 4);
          }
        }
        mbar_wait(bE + c.s * 8, c.ph);
        mbar_expect(bF + c.s * 8, 32768);
        tma2d_mc(sbase + c.s * 32768 + rank * 16384, &p.tmV, bF + c.s * 8, pcol, 0, 3);
        const uint32_t unit = tick - 256;
        if (unit < 64) {
          const int mblk = (7 - (int)((unit >> 1) & 7)) * 2 + rank, nhalf = unit & 1, ks = unit >> 4;
          const uint32_t rot = k3_rot(c.s), nfree = ((0x1Au >> c.s) & 1) ? 2 : 3;
#pragma unroll 1
          for (int i = 0; i < K2_NST - 1; i++) {
            c.next();
            mbar_wait(bE + c.s * 8, c.ph);
          }
          uint32_t idx = 0, have = 0;
#pragma unroll 1
          for (int kk = k3_part(ks); kk < k3_part(ks + 1); kk++, idx++) {
            const uint32_t s = (rot + idx) & 3;
            if (idx >= nfree) mbar_wait((idx < 4) ? bH : b3E + s * 8, (idx < 4) ? 0 : (~idx >> 2) & 1);
            mbar_expect(b3F + s * 8, K3_STAGE);
            const uint32_t st = sbase + s * K3_STAGE;
            const int sel = (kk < 9), k = sel ? kk : kk - 9, kr = k * 64 + rank * 32;
            tma3d_mc(st + 16384 + rank * 16384, &p.tmO[sel], b3F + s * 8, 0, kr, nhalf * 4, 3);
            tma2d_mc(st + 49152 + rank * 2048, &p.tmOt[sel], b3F + s * 8, 512 + nhalf * 32, kr, 3);
            if (kk == 0) {
              wait_flag(&g_sync[F_OA + mblk], 8);
              asm volatile("fence.proxy.async.global;" ::: "memory");
            }
            if (!sel && !((have >> (k >> 1)) & 1)) {
#pragma unroll 1
              for (uint32_t spins = 0; spins < (1u << 22); spins++) {
                asm volatile("ld.acquire.gpu.global.u32 %0, [%1];" : "=r"(have) : "l"(&g_sync[F_CTX + mblk]) : "memory");
                if ((have >> (k >> 1)) & 1) break;
                __nanosleep(100);
              }
              asm volatile("fence.proxy.async.global;" ::: "memory");
            }
            tma2d(st, &p.tmC, b3F + s * 8, (sel ? 64 + k : k) * 64, mblk * 128);
          }
        }
      }
    }
    __syncwarp();
    asm volatile("" ::: "memory");
    if (__shfl_sync(0xffffffffu, warp_g, 0) != 8) {
      if (lr0 < S_LEN) {
#pragma unroll 1
        for (int i = warp_g - 9; i < 16; i += 3) {
          const float g = gate_row(lr0 + i, lane, x, gate_w);
          if (lane == 0) asm volatile("st.shared.f32 [%0], %1;" ::"r"(sGate + i * 4), "f"(g) : "memory");
        }
        bar_arrive(3, 256 + 96);
        if (lane == 0) {
          __threadfence();
          atomicAdd(&g_sync[F_GATE], 1u);
        }
      }
      if (warp_g == 9 && lane == 0) {
#pragma unroll 1
        for (int ji = 0; ji < K1_MAXJOBS; ji++) {
          const uint32_t job = p.jobs[cl][ji];
          if (!(job & 3)) break;
          mbar_wait(bS, ji & 1);
          __threadfence();
          atomicAdd(&g_sync[(((job >> 6) & 3) == 2) ? (F_QKVA + ((job >> 3) & 7) * 2 + rank) : (F_HP + ((job >> 10) & 15))], 1u);
        }
#pragma unroll 1
        for (int it = 0;; it++) {
          mbar_wait(bS2, it & 1);
          const uint32_t item = lds32(sItem + (it & 7) * 4), nxt = lds32(sItem + ((it + 1) & 7) * 4);
          __threadfence();
          atomicOr(&g_sync[F_CTX + (item & 7) * 2 + (rank ^ (it & 1))], 1u << (item >> 3));
          if (nxt >= K2_END) break;
        }
      } else if (warp_g == 11) {
        if (lane == 0) {
          prefetch_tmap(&p.tmQ); prefetch_tmap(&p.tmK); prefetch_tmap(&p.tmV);
          wait_flag(&g_sync[F_GATE], GATE_TARGET);
          wait_flag(&g_sync[F_HP + (p.order[cl] >> 4)], RDY_TARGET);
          mbar_arrive(bR);
        }
        __syncwarp();
        bar_sync(4, 256 + 32);
        if (lane < 12) mbar_arrive_cluster(bE + (4 + lane % 3) * 8, (lane / 3) & 1);
      } else if (warp_g == 10 && lr0 < S_LEN) {
        if (elect_one()) {
          prefetch_tmap(&p.tmL[0]); prefetch_tmap(&p.tmL[1]);
          uint32_t aph = 1;
#pragma unroll 1
          for (int ji = 0; ji < K1_MAXJOBS; ji++) aph ^= (p.jobs[cl][ji] >> 14) & 1;
          wait_flag(&g_sync[F_QKVA + (lr0 >> 7)], K1_FLAG_TARGET);
          wait_flag(&g_sync[F_QKVA + (max(lr0 - 14, 0) >> 7)], K1_FLAG_TARGET);
          asm volatile("fence.proxy.async.global;" ::: "memory");
          mbar_wait(bLast, 0);
#pragma unroll 1
          for (int kc = 0; kc < 6; kc++) {
            mbar_wait(bAe + kc * 8, aph);
            if (kc == 3) {
              mbar_expect(bL, 46 * 1152);
              tma3d(sL, &p.tmL[0], bL, 0, 9, lr0 - 14);
              tma3d(sL + 30 * 1152, &p.tmL[1], bL, 0, 0, lr0);
            }
          }
          mbar_expect(bL2, 30 * 1152);
          tma3d(sL + 46 * 1152, &p.tmL[0], bL2, 0, 18, lr0 - 14);
        }
        __syncwarp();
        bar_sync(5, 256 + 32);
        if (lane == 0) {
          __threadfence();
          atomicAdd(&g_sync[F_OA + (lr0 >> 7)], 1u);
        }
      }
    }
    __syncwarp();
    cluster_sync();
    if (warp_g == 8) {
      uint32_t v = 0;
      if (lane == 0) {
        __threadfence();
        v = atomicAdd(&g_sync[F_DONE], 1u);
      }
      if (__shfl_sync(0xffffffffu, v, 0) == 2 * NCLUSTER - 1)
        for (int i = 0; i < 3; i++) reinterpret_cast<uint4*>(g_sync)[i * 32 + lane] = make_uint4(0, 0, 0, 0);
    }
  } else {
    reg_alloc<232>();
    const int wg = warp_g >> 2, warp = warp_g & 3, q = lane & 3;
    const bool sig = (lane == 0) && (warp < 2);
    {
      K1State st{0, 0, 0, nullptr, 0, 0};
      float acc[128];
      uint32_t pk[64];
      if (wg == 0) { TS(0, 0); TSC(0, 2); }
#pragma unroll 1
      for (int ji = 0; ji < K1_MAXJOBS; ji++) {
        const uint32_t job = p.jobs[cl][ji];
        if (!(job & 3)) break;
        k1_tile(acc, pk, st, job, sA, sB, bAf, bAe, bBf, bBe, bS, wg, warp, lane, rank);
      }
#pragma unroll
      for (int i = 0; i < 4; i++)
        mbar_arrive_cluster_if(bE + i * 8, warp & 1, sig);
#pragma unroll
      for (int G = 0; G < 8; G++)
        if (G < st.png) {
          st_v4(st.pp + G * 32, pk[G * 8], pk[G * 8 + 1], pk[G * 8 + 2], pk[G * 8 + 3]);
          st_v4(st.pp + G * 32 + st.pld8, pk[G * 8 + 4], pk[G * 8 + 5], pk[G * 8 + 6], pk[G * 8 + 7]);
        }
      k1_flag(st, lane, bS);
      if (wg == 0) { TS(0, 1); TSC(0, 3); }
      if (lr0 < S_LEN) {
        const int ri = (warp_g >> 1) * 4 + (warp_g & 1) + 2, row = lr0 + ri;
        if (wg == 0) TS(1, 5);
        bar_sync(3, 256 + 96);
        const float gate0 = __uint_as_float(lds32(sGate + ri * 4 - 8)), gate1 = __uint_as_float(lds32(sGate + ri * 4));
        mbar_wait(bL, 0);
        if (wg == 0) TS(1, 6);
        local_rows2(row, ri, sL, bL2, lane, gate0, gate1);
        bar_arrive(5, 256 + 32);
      } else {
        bar_arrive(4, 256 + 32);
      }
    }
    __syncwarp();
    uint32_t item, rot;
    {
      const int mybar = 1 + wg, otherbar = 2 - wg;
      const float cl2 = 0.08838834764831845f * 1.4426950408889634f;
      float S[64], O[64];
      uint32_t P[32], Q[32];
      float m0 = 0.f, m1 = 0.f, l0 = 0.f, l1 = 0.f;
      int prev_row = 0, prev_h = 0, prev_single = 0;
      Cursor c{0, 0};
      if (wg == 1) bar_arrive(1, 256);
      if (wg == 0) { TS(1, 0); TSC(1, 2); }
#pragma unroll 1
      for (int it = 0;; it++) {
        mbar_wait(bF + c.s * 8, c.ph);
        item = lds32(sItem + (it & 7) * 4);
        const bool last = item >= K2_END;
        const int h = item >> 3, j = item & 7;
        const int hi = (int)(rank ^ (it & 1));
        const int nblk = 2 * j + 1 + hi;
        {
          const float gf0 = 1.f - g_gate[prev_row], gf1 = 1.f - g_gate[prev_row + 8];
          Cursor cq = c, ck = c, cs0 = c, cs1 = c, cv = c;
          rot = k3_rot(c.s);
          if (!last) {
            const int r = wg * 64 + warp * 16 + (lane & 7) + ((lane >> 3) & 1) * 8;
            const uint32_t qa = sbase + cq.s * 32768 + r * 128;
#pragma unroll
            for (int t = 0; t < 8; t++)
              ldsm_x4(Q[4 * t], Q[4 * t + 1], Q[4 * t + 2], Q[4 * t + 3], qa + (t >> 2) * 16384 + ((((t & 3) * 2 + (lane >> 4)) ^ (lane & 7)) << 4));
            c.next();
            ck = c; c.next();
            cs0 = ck; cv = c;
            mbar_wait(bF + ck.s * 8, ck.ph);
            if (it > 0) { mbar_wait(bF + cv.s * 8, cv.ph); c.next(); }
            if (!hi) {
              ck = c; c.next();
              cs1 = c; c.next();
              mbar_wait(bF + ck.s * 8, ck.ph);
              mbar_wait(bF + cs1.s * 8, cs1.ph);
            }
          }
          if (it == 0) BSEG(4); else BSEG(0);
          TURN_SYNC();
          if (it > 0) {
            wg_fence();
            ISSUE_PV(cv, prev_single);
            wg_commit();
          } else {
            wg_fence();
            wg_commit();
          }
          wg_fence();
          ISSUE_QK(ck);
          wg_commit();
          if (!(last && wg == 1)) TURN_ARRIVE();
          RELEASE_IF(cq, !last);
          RELEASE_IF(cs0, !last && !hi);
          RELEASE_IF(cs1, !last && !hi);
          wg_wait<1>();
          fence_regs(O);
          fence_regs(P);
          if (it > 0) {
            RELEASE_IF(cv, !last);
            mbar_arrive_cluster_if(bH, warp & 1, sig && last);
            EPILOGUE();
            __syncwarp();
            mbar_arrive_if(bS2, lane == 0);
          }
          wg_wait<0>();
          fence_regs(S);
          if (last) break;
          RELEASE(ck);
          float s0 = 0.f, s1 = 0.f;
          const int r0 = wg * 64 + warp * 16 + (lane >> 2);
#pragma unroll
          for (int jj = 0; jj < 16; jj++) {
            const int cc = jj * 8 + 2 * q;
            if (cc > r0) S[jj * 4 + 0] = -INFINITY;
            if (cc + 1 > r0) S[jj * 4 + 1] = -INFINITY;
            if (cc > r0 + 8) S[jj * 4 + 2] = -INFINITY;
            if (cc + 1 > r0 + 8) S[jj * 4 + 3] = -INFINITY;
          }
          float mx0 = fmaxf(S[0], S[1]), mx1 = fmaxf(S[2], S[3]);
#pragma unroll
          for (int jj = 1; jj < 16; jj++) {
            mx0 = fmaxf(mx0, fmaxf(S[jj * 4 + 0], S[jj * 4 + 1]));
            mx1 = fmaxf(mx1, fmaxf(S[jj * 4 + 2], S[jj * 4 + 3]));
          }
          mx0 = fmaxf(mx0, __shfl_xor_sync(0xffffffffu, mx0, 1));
          mx1 = fmaxf(mx1, __shfl_xor_sync(0xffffffffu, mx1, 1));
          mx0 = fmaxf(mx0, __shfl_xor_sync(0xffffffffu, mx0, 2));
          mx1 = fmaxf(mx1, __shfl_xor_sync(0xffffffffu, mx1, 2));
          m0 = mx0; m1 = mx1;
          const float mc0 = m0 * cl2, mc1 = m1 * cl2;
#pragma unroll
          for (int jj = 0; jj < 16; jj++) {
            S[jj * 4 + 0] = ex2(fmaf(S[jj * 4 + 0], cl2, -mc0));
            S[jj * 4 + 1] = ex2(fmaf(S[jj * 4 + 1], cl2, -mc0));
            S[jj * 4 + 2] = ex2(fmaf(S[jj * 4 + 2], cl2, -mc1));
            S[jj * 4 + 3] = ex2(fmaf(S[jj * 4 + 3], cl2, -mc1));
            s0 += S[jj * 4 + 0] + S[jj * 4 + 1];
            s1 += S[jj * 4 + 2] + S[jj * 4 + 3];
          }
          l0 = s0; l1 = s1;
#pragma unroll
          for (int jj = 0; jj < 16; jj++) {
            P[jj * 2 + 0] = pack_bf16(S[jj * 4 + 0], S[jj * 4 + 1]);
            P[jj * 2 + 1] = pack_bf16(S[jj * 4 + 2], S[jj * 4 + 3]);
          }
        }
        if (it == 0) BSEG(5); else BSEG(1);
#pragma unroll 1
        for (int n = 1; n < nblk; n++) {
          Cursor ck = c; c.next();
          Cursor cv = c; c.next();
          mbar_wait(bF + ck.s * 8, ck.ph);
          mbar_wait(bF + cv.s * 8, cv.ph);
          TURN_SYNC();
          wg_fence();
          ISSUE_QK(ck);
          wg_commit();
          ISSUE_PV(cv, n == 1);
          wg_commit();
          TURN_ARRIVE();
          wg_wait<1>();
          fence_regs(S);
          RELEASE(ck);
          float mx0 = fmaxf(S[0], S[1]), mx1 = fmaxf(S[2], S[3]);
#pragma unroll
          for (int jj = 1; jj < 16; jj++) {
            mx0 = fmaxf(mx0, fmaxf(S[jj * 4 + 0], S[jj * 4 + 1]));
            mx1 = fmaxf(mx1, fmaxf(S[jj * 4 + 2], S[jj * 4 + 3]));
          }
          mx0 = fmaxf(mx0, __shfl_xor_sync(0xffffffffu, mx0, 1));
          mx1 = fmaxf(mx1, __shfl_xor_sync(0xffffffffu, mx1, 1));
          mx0 = fmaxf(mx0, __shfl_xor_sync(0xffffffffu, mx0, 2));
          mx1 = fmaxf(mx1, __shfl_xor_sync(0xffffffffu, mx1, 2));
          mx0 = fmaxf(mx0, m0);
          mx1 = fmaxf(mx1, m1);
          const float sc0 = ex2((m0 - mx0) * cl2), sc1 = ex2((m1 - mx1) * cl2);
          m0 = mx0; m1 = mx1;
          const float mc0 = m0 * cl2, mc1 = m1 * cl2;
          float s0 = 0.f, s1 = 0.f;
#pragma unroll
          for (int jj = 0; jj < 16; jj++) {
            S[jj * 4 + 0] = ex2(fmaf(S[jj * 4 + 0], cl2, -mc0));
            S[jj * 4 + 1] = ex2(fmaf(S[jj * 4 + 1], cl2, -mc0));
            S[jj * 4 + 2] = ex2(fmaf(S[jj * 4 + 2], cl2, -mc1));
            S[jj * 4 + 3] = ex2(fmaf(S[jj * 4 + 3], cl2, -mc1));
            s0 += S[jj * 4 + 0] + S[jj * 4 + 1];
            s1 += S[jj * 4 + 2] + S[jj * 4 + 3];
          }
          l0 = fmaf(l0, sc0, s0);
          l1 = fmaf(l1, sc1, s1);
          fence_regs(S);
          wg_wait<0>();
          fence_regs(O);
          fence_regs(P);
          RELEASE(cv);
#pragma unroll
          for (int jj = 0; jj < 16; jj++) {
            O[jj * 4 + 0] *= sc0;
            O[jj * 4 + 1] *= sc0;
            O[jj * 4 + 2] *= sc1;
            O[jj * 4 + 3] *= sc1;
            P[jj * 2 + 0] = pack_bf16(S[jj * 4 + 0], S[jj * 4 + 1]);
            P[jj * 2 + 1] = pack_bf16(S[jj * 4 + 2], S[jj * 4 + 3]);
          }
        }
        BSEG(2);
        prev_row = (2 * j + hi) * 128 + wg * 64 + warp * 16 + (lane >> 2);
        prev_h = h;
        prev_single = (nblk == 1);
      }
      if (wg == 1) { TS(1, 1); TSC(1, 3); }
    }
    __syncwarp();
    const uint32_t unit = item & 255;
    if (unit < 64) {
      const int mblk = (7 - (int)((unit >> 1) & 7)) * 2 + rank, nhalf = unit & 1, ks = unit >> 4;
      const int k0 = k3_part(ks), k1 = k3_part(ks + 1);
      float acc[144];
      uint32_t s = rot, ph = 0, prev = 0;
      if (wg == 0) { TS(2, 0); TSC(2, 2); }
#pragma unroll 1
      for (int k = k0; k < k1; k++) {
        mbar_wait(b3F + s * 8, ph);
        const uint32_t st = sbase + s * K3_STAGE;
        const uint64_t da = make_desc(st + wg * 8192, 16, 1024, 1);
        const uint64_t db = make_desc(st + 16384, 4096, 1024, 1);
        const uint64_t dt = make_desc(st + 49152, 16, 512, 2);
        wg_fence();
#pragma unroll
        for (int t = 0; t < 4; t++) {
          const int sd = (t > 0) || (k > k0);
          wgmma_ss_n256<1, 0>(acc, da + (uint64_t)(t * 2), db + (uint64_t)((t >> 1) * 1024 + (t & 1) * 128), sd);
          wgmma_ss_n32<1, 128>(acc, da + (uint64_t)(t * 2), dt + (uint64_t)(t * 64), sd);
        }
        wg_commit();
        if (k > k0) {
          wg_wait<1>();
          if (sig) mbar_arrive_cluster(b3E + prev * 8, warp);
        }
        prev = s;
        s = (s + 1) & 3;
        if (s == rot) ph ^= 1;
      }
      wg_wait<0>();
      fence_regs(acc);
      if (wg == 0) TS(2, 4);
      const int tile = mblk * 2 + nhalf;
      uint4* wp = g_part + (size_t)((tile * 4 + ks) * 4) * 5 * 256 + tid;
      const uint32_t sown = sbase + wg * 8192 + (tid & 127) * 16;
#pragma unroll
      for (int d = 0; d < 4; d++) {
        if (d != ks) {
#pragma unroll
          for (int i = 0; i < 4; i++)
            __stcg(wp + (d * 5 + i) * 256,
                   make_uint4(pack_bf16(acc[d * 32 + i * 8], acc[d * 32 + i * 8 + 1]), pack_bf16(acc[d * 32 + i * 8 + 2], acc[d * 32 + i * 8 + 3]),
                              pack_bf16(acc[d * 32 + i * 8 + 4], acc[d * 32 + i * 8 + 5]), pack_bf16(acc[d * 32 + i * 8 + 6], acc[d * 32 + i * 8 + 7])));
          __stcg(reinterpret_cast<uint2*>(wp - tid + (d * 5 + 4) * 256) + tid,
                 make_uint2(pack_bf16(acc[128 + d * 4], acc[128 + d * 4 + 1]), pack_bf16(acc[128 + d * 4 + 2], acc[128 + d * 4 + 3])));
        } else {
#pragma unroll
          for (int i = 0; i < 9; i++) {
            const int o = (i < 8) ? d * 32 + i * 4 : 128 + d * 4;
            asm volatile("st.shared.v4.f32 [%0], {%1, %2, %3, %4};" ::"r"(sown + (i >> 2) * K3_STAGE + (i & 3) * 2048), "f"(acc[o]), "f"(acc[o + 1]), "f"(acc[o + 2]), "f"(acc[o + 3]) : "memory");
          }
        }
      }
      __threadfence();
      __syncwarp();
      if (wg == 0) TS(2, 5);
      if (lane == 0) {
        unsigned int* cnt = &g_sync[F_XCH + tile * 8 + warp_g];
        atomicAdd(cnt, 1u);
        uint32_t v, spins = 0;
        do {
          asm volatile("ld.acquire.gpu.global.u32 %0, [%1];" : "=r"(v) : "l"(cnt) : "memory");
        } while (v < 4 && ++spins < (1u << 24));
      }
      __syncwarp();
      if (wg == 0) TS(2, 6);
      float r[36];
#pragma unroll
      for (int i = 0; i < 9; i++)
        asm volatile("ld.shared.v4.f32 {%0, %1, %2, %3}, [%4];" : "=f"(r[i * 4]), "=f"(r[i * 4 + 1]), "=f"(r[i * 4 + 2]), "=f"(r[i * 4 + 3])
                     : "r"(sown + (i >> 2) * K3_STAGE + (i & 3) * 2048) : "memory");
#pragma unroll
      for (int sI = 1; sI < 4; sI++) {
        const int src = (ks + sI) & 3;
        const uint4* rp = g_part + (size_t)(((tile * 4 + src) * 4) + ks) * 5 * 256;
#pragma unroll
        for (int i = 0; i < 4; i++) {
          const uint4 v = __ldcg(rp + i * 256 + tid);
          r[i * 8] += bf_lo(v.x); r[i * 8 + 1] += bf_hi(v.x); r[i * 8 + 2] += bf_lo(v.y); r[i * 8 + 3] += bf_hi(v.y);
          r[i * 8 + 4] += bf_lo(v.z); r[i * 8 + 5] += bf_hi(v.z); r[i * 8 + 6] += bf_lo(v.w); r[i * 8 + 7] += bf_hi(v.w);
        }
        const uint2 v = __ldcg(reinterpret_cast<const uint2*>(rp + 4 * 256) + tid);
        r[32] += bf_lo(v.x); r[33] += bf_hi(v.x); r[34] += bf_lo(v.y); r[35] += bf_hi(v.y);
      }
      const int row = mblk * 128 + wg * 64 + warp * 16 + (lane >> 2);
      bf16* o0 = out + (size_t)row * DM + nhalf * 256 + ks * 64 + 8 * q;
#pragma unroll
      for (int G = 0; G < 2; G++) {
        uint32_t a0 = pack_bf16(r[G * 16], r[G * 16 + 1]), a1 = pack_bf16(r[G * 16 + 4], r[G * 16 + 5]);
        uint32_t a2 = pack_bf16(r[G * 16 + 8], r[G * 16 + 9]), a3 = pack_bf16(r[G * 16 + 12], r[G * 16 + 13]);
        uint32_t b0 = pack_bf16(r[G * 16 + 2], r[G * 16 + 3]), b1 = pack_bf16(r[G * 16 + 6], r[G * 16 + 7]);
        uint32_t b2 = pack_bf16(r[G * 16 + 10], r[G * 16 + 11]), b3 = pack_bf16(r[G * 16 + 14], r[G * 16 + 15]);
        quad_transpose(a0, a1, a2, a3, q);
        quad_transpose(b0, b1, b2, b3, q);
        st_v4(o0 + G * 32, a0, a1, a2, a3);
        st_v4(o0 + 8 * DM + G * 32, b0, b1, b2, b3);
      }
      {
        uint32_t t0 = pack_bf16(r[32], r[33]), t1 = pack_bf16(r[34], r[35]), t2 = 0, t3 = 0;
        quad_transpose(t0, t1, t2, t3, q);
        if (q < 2) st_v4(out + (size_t)(row + q * 8) * DM + 512 + nhalf * 32 + ks * 8, t0, t1, t2, t3);
      }
    }
    if (wg == 0) { TS(2, 1); TSC(2, 3); }
    cluster_sync();
  }
}

typedef CUresult (*EncFn)(CUtensorMap*, CUtensorMapDataType, cuuint32_t, void*, const cuuint64_t*, const cuuint64_t*, const cuuint32_t*,
                          const cuuint32_t*, CUtensorMapInterleave, CUtensorMapSwizzle, CUtensorMapL2promotion, CUtensorMapFloatOOBfill);

static void enc2d(EncFn enc, CUtensorMap* m, const void* ptr, uint64_t cols, uint64_t rows, uint32_t bc, uint32_t br,
                  CUtensorMapSwizzle sw = CU_TENSOR_MAP_SWIZZLE_128B) {
  cuuint64_t gd[2] = {cols, rows}, gs[1] = {cols * 2};
  cuuint32_t bx[2] = {bc, br}, es[2] = {1, 1};
  enc(m, CU_TENSOR_MAP_DATA_TYPE_BFLOAT16, 2, const_cast<void*>(ptr), gd, gs, bx, es, CU_TENSOR_MAP_INTERLEAVE_NONE, sw,
      CU_TENSOR_MAP_L2_PROMOTION_L2_256B, CU_TENSOR_MAP_FLOAT_OOB_FILL_NONE);
}
static void enc3d(EncFn enc, CUtensorMap* m, const void* ptr, uint64_t cols, uint64_t rows, uint32_t br, uint32_t bch) {
  cuuint64_t gd[3] = {64, rows, cols / 64}, gs[2] = {cols * 2, 128};
  cuuint32_t bx[3] = {64, br, bch}, es[3] = {1, 1, 1};
  enc(m, CU_TENSOR_MAP_DATA_TYPE_BFLOAT16, 3, const_cast<void*>(ptr), gd, gs, bx, es, CU_TENSOR_MAP_INTERLEAVE_NONE,
      CU_TENSOR_MAP_SWIZZLE_128B, CU_TENSOR_MAP_L2_PROMOTION_L2_256B, CU_TENSOR_MAP_FLOAT_OOB_FILL_NONE);
}

static void build_k1_jobs(Params& p) {
  int cnt[NCLUSTER];
  for (int c = 0; c < NCLUSTER; c++) {
    cnt[c] = 0;
    for (int i = 0; i < K1_MAXJOBS; i++) p.jobs[c][i] = 0;
  }
  auto add = [&](int c, int nch, int a_sel, int mp, int w_sel, int chunk0) {
    p.jobs[c][cnt[c]++] = (uint16_t)((nch - 1) | (a_sel << 2) | (mp << 3) | (w_sel << 6) | (chunk0 << 8));
  };
  for (int mp = 0; mp < 8; mp++) {
    for (int g = 0; g < 4; g++)
      for (int i = 0; i < 4; i++) add(g * 8 + mp, 4, 0, mp, g & 1, (2 * i + (g >> 1)) * 4);
    for (int t = 0; t < 16; t++) add((t % 3) * 8 + mp, 4, 0, mp, t & 1, (8 + (t >> 1)) * 4);
    add(32 + mp, 3, 1, mp, 2, 24);
    add(32 + mp, 4, 1, mp, 3, 0 * 4);
    for (int g = 5; g < 8; g++)
      for (int i = 0; i < 2; i++) add(g * 8 + mp, 4, 1, mp, 2, ((g - 5) * 2 + i) * 4);
    for (int i = 1; i < 8; i++) add((4 + (i - 1) % 4) * 8 + mp, 4, 1, mp, 3, i * 4);
    for (int i = 8; i < 14; i++) add(56 + mp, 4, 1, mp, 3, i * 4);
    add(64 + mp / 4, 4, 1, mp, 3, 14 * 4);
    add(64 + mp / 4, 4, 1, mp, 3, 15 * 4);
  }
  for (int cc = 0; cc < NCLUSTER; cc++)
    for (int i = 0; i < cnt[cc]; i++) {
      const int key = p.jobs[cc][i] & 0x3C;
      if (i == 0 || (p.jobs[cc][i - 1] & 0x3C) != key) p.jobs[cc][i] |= (1 << 14);
      if (i == cnt[cc] - 1 || (p.jobs[cc][i + 1] & 0x3C) != key) p.jobs[cc][i] |= (1 << 15);
    }
}

static void build_k2_items(Params& p) {
  bool used[256] = {};
  int ne = 0, nl = 0;
  for (int c = 0; c < NCLUSTER; c++) {
    const int g = c >> 3;
    if (g >= 3 && g <= 6) { p.order[c] = (uint8_t)((ne & 7) * 8 + 7 - (ne >> 3)); ne++; }
    else if (g == 1 || g == 2) p.order[c] = (uint8_t)((8 + (c - 8)) * 8 + 7);
    else { p.order[c] = (uint8_t)(nl < 8 ? (24 + nl) * 8 + 7 : (nl < 16 ? (16 + nl) : (nl - 8)) * 8 + 6); nl++; }
    used[p.order[c]] = true;
  }
  int n = NCLUSTER;
  for (int j = 3; j >= 0; j--)
    for (int h = 0; h < 8; h++) p.order[n++] = (uint8_t)(h * 8 + j);
  for (int j = 7; j >= 0; j--)
    for (int h = 8; h < 32; h++)
      if (!used[h * 8 + j]) p.order[n++] = (uint8_t)(h * 8 + j);
}

extern "C" void kernel_launch(void* const* d_in, const int* in_sizes, int n_in, void* d_out, int out_size) {
  const bf16* x = (const bf16*)d_in[0];
  const bf16* wqkv = (const bf16*)d_in[1];
  const bf16* wo = (const bf16*)d_in[2];
  const bf16* ckv = (const bf16*)d_in[4];
  const bf16* w_q = (const bf16*)d_in[5];
  const bf16* w_uk = (const bf16*)d_in[6];
  const bf16* w_uv = (const bf16*)d_in[7];
  const bf16* w_o = (const bf16*)d_in[8];
  const bf16* gate_w = (const bf16*)d_in[9];

  EncFn enc = nullptr;
  cudaDriverEntryPointQueryResult qr;
  cudaGetDriverEntryPoint("cuTensorMapEncodeTiled", (void**)&enc, cudaEnableDefault, &qr);
  void *pQ, *pK, *pV, *pCtx, *pQA;
  cudaGetSymbolAddress(&pQ, g_Q);
  cudaGetSymbolAddress(&pQA, g_QKVA);
  cudaGetSymbolAddress(&pK, g_K);
  cudaGetSymbolAddress(&pV, g_V);
  cudaGetSymbolAddress(&pCtx, g_ctx);

  static Params p;
  enc2d(enc, &p.tmA[0], ckv, DC, S_LEN, 64, 128);
  enc2d(enc, &p.tmA[1], x, DM, S_LEN, 64, 128);
  enc3d(enc, &p.tmW[0], w_uk, HDIM, DC, 16, 4);
  enc3d(enc, &p.tmW[1], w_uv, HDIM, DC, 16, 4);
  enc3d(enc, &p.tmW[2], wqkv, NQKVA, DM, 16, 4);
  enc3d(enc, &p.tmW[3], w_q, HDIM, DM, 16, 4);
  build_k1_jobs(p);
  enc2d(enc, &p.tmQ, pQ, HDIM, S_LEN, 64, 128);
  enc2d(enc, &p.tmK, pK, HDIM, S_LEN, 64, 128);
  enc2d(enc, &p.tmV, pV, HDIM, S_LEN, 64, 128);
  build_k2_items(p);
  for (int i = 0; i < 2; i++) {
    cuuint64_t gd[3] = {64, 27, S_LEN}, gs[2] = {128, NQKVA * 2};
    cuuint32_t bx[3] = {64, 9, i ? 16u : 30u}, es[3] = {1, 1, 1};
    enc(&p.tmL[i], CU_TENSOR_MAP_DATA_TYPE_BFLOAT16, 3, pQA, gd, gs, bx, es, CU_TENSOR_MAP_INTERLEAVE_NONE, CU_TENSOR_MAP_SWIZZLE_NONE,
        CU_TENSOR_MAP_L2_PROMOTION_L2_256B, CU_TENSOR_MAP_FLOAT_OOB_FILL_NONE);
  }
  enc2d(enc, &p.tmC, pCtx, KCAT, S_LEN, 64, 128);
  enc3d(enc, &p.tmO[0], w_o, DM, HDIM, 32, 4);
  enc3d(enc, &p.tmO[1], wo, DM, DM, 32, 4);
  enc2d(enc, &p.tmOt[0], w_o, DM, HDIM, 32, 32, CU_TENSOR_MAP_SWIZZLE_64B);
  enc2d(enc, &p.tmOt[1], wo, DM, DM, 32, 32, CU_TENSOR_MAP_SWIZZLE_64B);

  cudaFuncSetAttribute(fused_kernel, cudaFuncAttributeMaxDynamicSharedMemorySize, SMEM_BYTES);
  fused_kernel<<<NCLUSTER * 2, 384, SMEM_BYTES>>>(p, x, gate_w, (bf16*)d_out);
}
```

```cpp
#include <cuda_runtime.h>
#include <cuda_bf16.h>
#include <cuda.h>
#include <stdint.h>

typedef __nv_bfloat16 bf16;

constexpr int S_LEN = 2048, DM = 576, DC = 512, HDIM = 4096, NQKVA = 1728, KCAT = 4672;
constexpr int NCLUSTER = 66;

__device__ __align__(1024) bf16 g_Q[S_LEN * HDIM];
__device__ __align__(1024) bf16 g_K[S_LEN * HDIM];
__device__ __align__(1024) bf16 g_V[S_LEN * HDIM];
__device__ __align__(1024) bf16 g_QKVA[S_LEN * NQKVA + 64];
__device__ __align__(1024) bf16 g_ctx[S_LEN * KCAT];
__device__ float g_gate[S_LEN];
__device__ __align__(1024) uint4 g_part[32 * 4 * 4 * 5 * 256];
__device__ __align__(16) unsigned int g_sync[400];
constexpr int F_QKVA = 0, F_HP = 16, F_CTX = 32, F_OA = 48, F_GATE = 96, F_TICK = 97, F_DONE = 98, F_XCH = 128, F_EPOCH = 384;

__device__ __forceinline__ uint32_t smem_u32(const void* p) { return (uint32_t)__cvta_generic_to_shared(p); }
__device__ __forceinline__ void mbar_init(uint32_t a, uint32_t c) {
  asm volatile("mbarrier.init.shared::cta.b64 [%0], %1;" ::"r"(a), "r"(c));
}
__device__ __forceinline__ void mbar_expect(uint32_t a, uint32_t b) {
  asm volatile("mbarrier.arrive.expect_tx.shared::cta.b64 _, [%0], %1;" ::"r"(a), "r"(b) : "memory");
}
#define TS(k, i)
#define TSC(k, i)
#define TSM(k)
#define BSEG(i)
#define SPIN_LIMIT "4194304"
__device__ __forceinline__ void mbar_wait(uint32_t a, uint32_t parity) {
  asm volatile(
      "{\n.reg .pred p;\n.reg .u32 n;\n"
      "mbarrier.try_wait.parity.shared::cta.b64 p, [%0], %1;\n"
      "@p bra DONE;\n"
      "mov.u32 n, 0;\n"
      "LOOP:\n"
      "mbarrier.try_wait.parity.shared::cta.b64 p, [%0], %1;\n"
      "@p bra DONE;\n"
      "add.u32 n, n, 1;\n"
      "setp.lt.u32 p, n, " SPIN_LIMIT ";\n"
      "@p bra LOOP;\n"
      "DONE:\n}" ::"r"(a), "r"(parity) : "memory");
}
__device__ __forceinline__ void mbar_arrive(uint32_t a) {
  asm volatile("mbarrier.arrive.shared::cta.b64 _, [%0];" ::"r"(a) : "memory");
}
__device__ __forceinline__ void mbar_arrive_cluster(uint32_t a, uint32_t cta) {
  asm volatile("{\n.reg .b32 r;\nmapa.shared::cluster.u32 r, %0, %1;\nmbarrier.arrive.shared::cluster.b64 _, [r];\n}" ::"r"(a),
               "r"(cta) : "memory");
}
__device__ __forceinline__ void mbar_arrive_cluster_if(uint32_t a, uint32_t cta, bool pred) {
  asm volatile("{\n.reg .b32 r;\n.reg .pred p;\nsetp.ne.u32 p, %2, 0;\nmapa.shared::cluster.u32 r, %0, %1;\n@p mbarrier.arrive.shared::cluster.b64 _, [r];\n}" ::"r"(a),
               "r"(cta), "r"((uint32_t)pred) : "memory");
}
__device__ __forceinline__ void mbar_arrive_if(uint32_t a, bool pred) {
  asm volatile("{\n.reg .pred p;\nsetp.ne.u32 p, %1, 0;\n@p mbarrier.arrive.shared::cta.b64 _, [%0];\n}" ::"r"(a), "r"((uint32_t)pred) : "memory");
}
__device__ __forceinline__ void tma2d(uint32_t dst, const CUtensorMap* m, uint32_t bar, int c0, int c1) {
  asm volatile("cp.async.bulk.tensor.2d.shared::cluster.global.mbarrier::complete_tx::bytes [%0], [%1, {%3, %4}], [%2];" ::"r"(dst),
               "l"(m), "r"(bar), "r"(c0), "r"(c1) : "memory");
}
__device__ __forceinline__ void tma2d_mc(uint32_t dst, const CUtensorMap* m, uint32_t bar, int c0, int c1, uint16_t mask) {
  asm volatile(
      "cp.async.bulk.tensor.2d.shared::cluster.global.mbarrier::complete_tx::bytes.multicast::cluster [%0], [%1, {%3, %4}], [%2], %5;" ::"r"(dst),
      "l"(m), "r"(bar), "r"(c0), "r"(c1), "h"(mask) : "memory");
}
__device__ __forceinline__ void tma3d_mc(uint32_t dst, const CUtensorMap* m, uint32_t bar, int c0, int c1, int c2, uint16_t mask) {
  asm volatile(
      "cp.async.bulk.tensor.3d.shared::cluster.global.mbarrier::complete_tx::bytes.multicast::cluster [%0], [%1, {%3, %4, %5}], [%2], %6;" ::"r"(dst),
      "l"(m), "r"(bar), "r"(c0), "r"(c1), "r"(c2), "h"(mask) : "memory");
}
__device__ __forceinline__ void tma3d(uint32_t dst, const CUtensorMap* m, uint32_t bar, int c0, int c1, int c2) {
  asm volatile(
      "cp.async.bulk.tensor.3d.shared::cluster.global.mbarrier::complete_tx::bytes [%0], [%1, {%3, %4, %5}], [%2];" ::"r"(dst),
      "l"(m), "r"(bar), "r"(c0), "r"(c1), "r"(c2) : "memory");
}
__device__ __forceinline__ void tma_pf2d(const CUtensorMap* m, int c0, int c1) {
  asm volatile("cp.async.bulk.prefetch.tensor.2d.L2.global [%0, {%1, %2}];" ::"l"(m), "r"(c0), "r"(c1) : "memory");
}
__device__ __forceinline__ void tma_pf3d(const CUtensorMap* m, int c0, int c1, int c2) {
  asm volatile("cp.async.bulk.prefetch.tensor.3d.L2.global [%0, {%1, %2, %3}];" ::"l"(m), "r"(c0), "r"(c1), "r"(c2) : "memory");
}
__device__ __forceinline__ void prefetch_tmap(const CUtensorMap* m) {
  asm volatile("prefetch.tensormap [%0];" ::"l"(m) : "memory");
}
__device__ __forceinline__ void cluster_arrive() { asm volatile("barrier.cluster.arrive.relaxed.aligned;" ::: "memory"); }
__device__ __forceinline__ void cluster_wait() { asm volatile("barrier.cluster.wait.aligned;" ::: "memory"); }
__device__ __forceinline__ void cluster_sync() {
  cluster_arrive();
  cluster_wait();
}
__device__ __forceinline__ uint32_t cluster_rank() {
  uint32_t r;
  asm volatile("mov.u32 %0, %%cluster_ctarank;" : "=r"(r));
  return r;
}
__device__ __forceinline__ bool elect_one() {
  uint32_t p;
  asm volatile("{\n.reg .pred q;\nelect.sync _|q, 0xffffffff;\nselp.u32 %0, 1, 0, q;\n}" : "=r"(p));
  return p;
}
__device__ __forceinline__ void pdl_wait() { asm volatile("griddepcontrol.wait;" ::: "memory"); }
__device__ __forceinline__ void pdl_launch() { asm volatile("griddepcontrol.launch_dependents;" ::: "memory"); }
__device__ __forceinline__ void ldsm_x4(uint32_t& r0, uint32_t& r1, uint32_t& r2, uint32_t& r3, uint32_t addr) {
  asm volatile("ldmatrix.sync.aligned.m8n8.x4.shared.b16 {%0, %1, %2, %3}, [%4];" : "=r"(r0), "=r"(r1), "=r"(r2), "=r"(r3) : "r"(addr) : "memory");
}
__device__ __forceinline__ void wg_fence() { asm volatile("wgmma.fence.sync.aligned;" ::: "memory"); }
__device__ __forceinline__ void wg_commit() { asm volatile("wgmma.commit_group.sync.aligned;" ::: "memory"); }
template <int N>
__device__ __forceinline__ void wg_wait() { asm volatile("wgmma.wait_group.sync.aligned %0;" ::"n"(N) : "memory"); }
template <int N>
__device__ __forceinline__ void reg_alloc() { asm volatile("setmaxnreg.inc.sync.aligned.u32 %0;" ::"n"(N)); }
template <int N>
__device__ __forceinline__ void reg_dealloc() { asm volatile("setmaxnreg.dec.sync.aligned.u32 %0;" ::"n"(N)); }
__device__ __forceinline__ void bar_sync(int id, int n) { asm volatile("bar.sync %0, %1;" ::"r"(id), "r"(n) : "memory"); }
__device__ __forceinline__ void bar_arrive(int id, int n) { asm volatile("bar.arrive %0, %1;" ::"r"(id), "r"(n) : "memory"); }
template <int NT>
__device__ __forceinline__ void fence_regs(float (&d)[NT]) {
#pragma unroll
  for (int i = 0; i < NT; i++) asm volatile("" : "+f"(d[i])::"memory");
}
template <int NT>
__device__ __forceinline__ void fence_regs(uint32_t (&d)[NT]) {
#pragma unroll
  for (int i = 0; i < NT; i++) asm volatile("" : "+r"(d[i])::"memory");
}
__device__ __forceinline__ uint64_t make_desc(uint32_t saddr, uint32_t lbo, uint32_t sbo, uint32_t layout) {
  return (uint64_t)((saddr & 0x3FFFF) >> 4) | ((uint64_t)(lbo >> 4) << 16) | ((uint64_t)(sbo >> 4) << 32) | ((uint64_t)layout << 62);
}
__device__ __forceinline__ uint32_t pack_bf16(float lo, float hi) {
  uint32_t r;
  asm("cvt.rn.bf16x2.f32 %0, %1, %2;" : "=r"(r) : "f"(hi), "f"(lo));
  return r;
}
__device__ __forceinline__ float ex2(float x) {
  float r;
  asm("ex2.approx.ftz.f32 %0, %1;" : "=f"(r) : "f"(x));
  return r;
}
__device__ __forceinline__ void st_v4(void* p, uint32_t a, uint32_t b, uint32_t c, uint32_t d) {
#define ST_MOD ""
  asm volatile("st.global" ST_MOD ".v4.b32 [%0], {%1, %2, %3, %4};" ::"l"(p), "r"(a), "r"(b), "r"(c), "r"(d) : "memory");
}
__device__ __forceinline__ float bf_lo(uint32_t v) { return __uint_as_float(v << 16); }
__device__ __forceinline__ float bf_hi(uint32_t v) { return __uint_as_float(v & 0xFFFF0000u); }

__device__ __forceinline__ void quad_transpose(uint32_t& a0, uint32_t& a1, uint32_t& a2, uint32_t& a3, int q) {
  const bool o1 = q & 1, o2 = q & 2;
  uint32_t t0 = o1 ? a0 : a1, t1 = o1 ? a2 : a3;
  t0 = __shfl_xor_sync(0xffffffffu, t0, 1);
  t1 = __shfl_xor_sync(0xffffffffu, t1, 1);
  if (o1) { a0 = t0; a2 = t1; } else { a1 = t0; a3 = t1; }
  t0 = o2 ? a0 : a2;
  t1 = o2 ? a1 : a3;
  t0 = __shfl_xor_sync(0xffffffffu, t0, 2);
  t1 = __shfl_xor_sync(0xffffffffu, t1, 2);
  if (o2) { a0 = t0; a1 = t1; } else { a2 = t0; a3 = t1; }
}

template<int TB, int OFF, int NT>
__device__ __forceinline__ void wgmma_ss_n256(float (&d)[NT], uint64_t da, uint64_t db, int scale_d) {
  asm volatile("{\n.reg .pred p;\nsetp.ne.b32 p, %130, 0;\n"
    "wgmma.mma_async.sync.aligned.m64n256k16.f32.bf16.bf16 {%0, %1, %2, %3, %4, %5, %6, %7, %8, %9, %10, %11, %12, %13, %14, %15, %16, %17, %18, %19, %20, %21, %22, %23, %24, %25, %26, %27, %28, %29, %30, %31, %32, %33, %34, %35, %36, %37, %38, %39, %40, %41, %42, %43, %44, %45, %46, %47, %48, %49, %50, %51, %52, %53, %54, %55, %56, %57, %58, %59, %60, %61, %62, %63, %64, %65, %66, %67, %68, %69, %70, %71, %72, %73, %74, %75, %76, %77, %78, %79, %80, %81, %82, %83, %84, %85, %86, %87, %88, %89, %90, %91, %92, %93, %94, %95, %96, %97, %98, %99, %100, %101, %102, %103, %104, %105, %106, %107, %108, %109, %110, %111, %112, %113, %114, %115, %116, %117, %118, %119, %120, %121, %122, %123, %124, %125, %126, %127}, %128, %129, p, 1, 1, 0, %131;\n}\n"
    : "+f"(d[OFF+0]), "+f"(d[OFF+1]), "+f"(d[OFF+2]), "+f"(d[OFF+3]), "+f"(d[OFF+4]), "+f"(d[OFF+5]), "+f"(d[OFF+6]), "+f"(d[OFF+7]), "+f"(d[OFF+8]), "+f"(d[OFF+9]), "+f"(d[OFF+10]), "+f"(d[OFF+11]), "+f"(d[OFF+12]), "+f"(d[OFF+13]), "+f"(d[OFF+14]), "+f"(d[OFF+15]), "+f"(d[OFF+16]), "+f"(d[OFF+17]), "+f"(d[OFF+18]), "+f"(d[OFF+19]), "+f"(d[OFF+20]), "+f"(d[OFF+21]), "+f"(d[OFF+22]), "+f"(d[OFF+23]), "+f"(d[OFF+24]), "+f"(d[OFF+25]), "+f"(d[OFF+26]), "+f"(d[OFF+27]), "+f"(d[OFF+28]), "+f"(d[OFF+29]), "+f"(d[OFF+30]), "+f"(d[OFF+31]), "+f"(d[OFF+32]), "+f"(d[OFF+33]), "+f"(d[OFF+34]), "+f"(d[OFF+35]), "+f"(d[OFF+36]), "+f"(d[OFF+37]), "+f"(d[OFF+38]), "+f"(d[OFF+39]), "+f"(d[OFF+40]), "+f"(d[OFF+41]), "+f"(d[OFF+42]), "+f"(d[OFF+43]), "+f"(d[OFF+44]), "+f"(d[OFF+45]), "+f"(d[OFF+46]), "+f"(d[OFF+47]), "+f"(d[OFF+48]), "+f"(d[OFF+49]), "+f"(d[OFF+50]), "+f"(d[OFF+51]), "+f"(d[OFF+52]), "+f"(d[OFF+53]), "+f"(d[OFF+54]), "+f"(d[OFF+55]), "+f"(d[OFF+56]), "+f"(d[OFF+57]), "+f"(d[OFF+58]), "+f"(d[OFF+59]), "+f"(d[OFF+60]), "+f"(d[OFF+61]), "+f"(d[OFF+62]), "+f"(d[OFF+63]), "+f"(d[OFF+64]), "+f"(d[OFF+65]), "+f"(d[OFF+66]), "+f"(d[OFF+67]), "+f"(d[OFF+68]), "+f"(d[OFF+69]), "+f"(d[OFF+70]), "+f"(d[OFF+71]), "+f"(d[OFF+72]), "+f"(d[OFF+73]), "+f"(d[OFF+74]), "+f"(d[OFF+75]), "+f"(d[OFF+76]), "+f"(d[OFF+77]), "+f"(d[OFF+78]), "+f"(d[OFF+79]), "+f"(d[OFF+80]), "+f"(d[OFF+81]), "+f"(d[OFF+82]), "+f"(d[OFF+83]), "+f"(d[OFF+84]), "+f"(d[OFF+85]), "+f"(d[OFF+86]), "+f"(d[OFF+87]), "+f"(d[OFF+88]), "+f"(d[OFF+89]), "+f"(d[OFF+90]), "+f"(d[OFF+91]), "+f"(d[OFF+92]), "+f"(d[OFF+93]), "+f"(d[OFF+94]), "+f"(d[OFF+95]), "+f"(d[OFF+96]), "+f"(d[OFF+97]), "+f"(d[OFF+98]), "+f"(d[OFF+99]), "+f"(d[OFF+100]), "+f"(d[OFF+101]), "+f"(d[OFF+102]), "+f"(d[OFF+103]), "+f"(d[OFF+104]), "+f"(d[OFF+105]), "+f"(d[OFF+106]), "+f"(d[OFF+107]), "+f"(d[OFF+108]), "+f"(d[OFF+109]), "+f"(d[OFF+110]), "+f"(d[OFF+111]), "+f"(d[OFF+112]), "+f"(d[OFF+113]), "+f"(d[OFF+114]), "+f"(d[OFF+115]), "+f"(d[OFF+116]), "+f"(d[OFF+117]), "+f"(d[OFF+118]), "+f"(d[OFF+119]), "+f"(d[OFF+120]), "+f"(d[OFF+121]), "+f"(d[OFF+122]), "+f"(d[OFF+123]), "+f"(d[OFF+124]), "+f"(d[OFF+125]), "+f"(d[OFF+126]), "+f"(d[OFF+127])
    : "l"(da), "l"(db), "r"(scale_d), "n"(TB));
}
template<int TB, int OFF, int NT>
__device__ __forceinline__ void wgmma_ss_n192(float (&d)[NT], uint64_t da, uint64_t db, int scale_d) {
  asm volatile("{\n.reg .pred p;\nsetp.ne.b32 p, %98, 0;\n"
    "wgmma.mma_async.sync.aligned.m64n192k16.f32.bf16.bf16 {%0, %1, %2, %3, %4, %5, %6, %7, %8, %9, %10, %11, %12, %13, %14, %15, %16, %17, %18, %19, %20, %21, %22, %23, %24, %25, %26, %27, %28, %29, %30, %31, %32, %33, %34, %35, %36, %37, %38, %39, %40, %41, %42, %43, %44, %45, %46, %47, %48, %49, %50, %51, %52, %53, %54, %55, %56, %57, %58, %59, %60, %61, %62, %63, %64, %65, %66, %67, %68, %69, %70, %71, %72, %73, %74, %75, %76, %77, %78, %79, %80, %81, %82, %83, %84, %85, %86, %87, %88, %89, %90, %91, %92, %93, %94, %95}, %96, %97, p, 1, 1, 0, %99;\n}\n"
    : "+f"(d[OFF+0]), "+f"(d[OFF+1]), "+f"(d[OFF+2]), "+f"(d[OFF+3]), "+f"(d[OFF+4]), "+f"(d[OFF+5]), "+f"(d[OFF+6]), "+f"(d[OFF+7]), "+f"(d[OFF+8]), "+f"(d[OFF+9]), "+f"(d[OFF+10]), "+f"(d[OFF+11]), "+f"(d[OFF+12]), "+f"(d[OFF+13]), "+f"(d[OFF+14]), "+f"(d[OFF+15]), "+f"(d[OFF+16]), "+f"(d[OFF+17]), "+f"(d[OFF+18]), "+f"(d[OFF+19]), "+f"(d[OFF+20]), "+f"(d[OFF+21]), "+f"(d[OFF+22]), "+f"(d[OFF+23]), "+f"(d[OFF+24]), "+f"(d[OFF+25]), "+f"(d[OFF+26]), "+f"(d[OFF+27]), "+f"(d[OFF+28]), "+f"(d[OFF+29]), "+f"(d[OFF+30]), "+f"(d[OFF+31]), "+f"(d[OFF+32]), "+f"(d[OFF+33]), "+f"(d[OFF+34]), "+f"(d[OFF+35]), "+f"(d[OFF+36]), "+f"(d[OFF+37]), "+f"(d[OFF+38]), "+f"(d[OFF+39]), "+f"(d[OFF+40]), "+f"(d[OFF+41]), "+f"(d[OFF+42]), "+f"(d[OFF+43]), "+f"(d[OFF+44]), "+f"(d[OFF+45]), "+f"(d[OFF+46]), "+f"(d[OFF+47]), "+f"(d[OFF+48]), "+f"(d[OFF+49]), "+f"(d[OFF+50]), "+f"(d[OFF+51]), "+f"(d[OFF+52]), "+f"(d[OFF+53]), "+f"(d[OFF+54]), "+f"(d[OFF+55]), "+f"(d[OFF+56]), "+f"(d[OFF+57]), "+f"(d[OFF+58]), "+f"(d[OFF+59]), "+f"(d[OFF+60]), "+f"(d[OFF+61]), "+f"(d[OFF+62]), "+f"(d[OFF+63]), "+f"(d[OFF+64]), "+f"(d[OFF+65]), "+f"(d[OFF+66]), "+f"(d[OFF+67]), "+f"(d[OFF+68]), "+f"(d[OFF+69]), "+f"(d[OFF+70]), "+f"(d[OFF+71]), "+f"(d[OFF+72]), "+f"(d[OFF+73]), "+f"(d[OFF+74]), "+f"(d[OFF+75]), "+f"(d[OFF+76]), "+f"(d[OFF+77]), "+f"(d[OFF+78]), "+f"(d[OFF+79]), "+f"(d[OFF+80]), "+f"(d[OFF+81]), "+f"(d[OFF+82]), "+f"(d[OFF+83]), "+f"(d[OFF+84]), "+f"(d[OFF+85]), "+f"(d[OFF+86]), "+f"(d[OFF+87]), "+f"(d[OFF+88]), "+f"(d[OFF+89]), "+f"(d[OFF+90]), "+f"(d[OFF+91]), "+f"(d[OFF+92]), "+f"(d[OFF+93]), "+f"(d[OFF+94]), "+f"(d[OFF+95])
    : "l"(da), "l"(db), "r"(scale_d), "n"(TB));
}
template<int TB, int OFF, int NT>
__device__ __forceinline__ void wgmma_ss_n128(float (&d)[NT], uint64_t da, uint64_t db, int scale_d) {
  asm volatile("{\n.reg .pred p;\nsetp.ne.b32 p, %66, 0;\n"
    "wgmma.mma_async.sync.aligned.m64n128k16.f32.bf16.bf16 {%0, %1, %2, %3, %4, %5, %6, %7, %8, %9, %10, %11, %12, %13, %14, %15, %16, %17, %18, %19, %20, %21, %22, %23, %24, %25, %26, %27, %28, %29, %30, %31, %32, %33, %34, %35, %36, %37, %38, %39, %40, %41, %42, %43, %44, %45, %46, %47, %48, %49, %50, %51, %52, %53, %54, %55, %56, %57, %58, %59, %60, %61, %62, %63}, %64, %65, p, 1, 1, 0, %67;\n}\n"
    : "+f"(d[OFF+0]), "+f"(d[OFF+1]), "+f"(d[OFF+2]), "+f"(d[OFF+3]), "+f"(d[OFF+4]), "+f"(d[OFF+5]), "+f"(d[OFF+6]), "+f"(d[OFF+7]), "+f"(d[OFF+8]), "+f"(d[OFF+9]), "+f"(d[OFF+10]), "+f"(d[OFF+11]), "+f"(d[OFF+12]), "+f"(d[OFF+13]), "+f"(d[OFF+14]), "+f"(d[OFF+15]), "+f"(d[OFF+16]), "+f"(d[OFF+17]), "+f"(d[OFF+18]), "+f"(d[OFF+19]), "+f"(d[OFF+20]), "+f"(d[OFF+21]), "+f"(d[OFF+22]), "+f"(d[OFF+23]), "+f"(d[OFF+24]), "+f"(d[OFF+25]), "+f"(d[OFF+26]), "+f"(d[OFF+27]), "+f"(d[OFF+28]), "+f"(d[OFF+29]), "+f"(d[OFF+30]), "+f"(d[OFF+31]), "+f"(d[OFF+32]), "+f"(d[OFF+33]), "+f"(d[OFF+34]), "+f"(d[OFF+35]), "+f"(d[OFF+36]), "+f"(d[OFF+37]), "+f"(d[OFF+38]), "+f"(d[OFF+39]), "+f"(d[OFF+40]), "+f"(d[OFF+41]), "+f"(d[OFF+42]), "+f"(d[OFF+43]), "+f"(d[OFF+44]), "+f"(d[OFF+45]), "+f"(d[OFF+46]), "+f"(d[OFF+47]), "+f"(d[OFF+48]), "+f"(d[OFF+49]), "+f"(d[OFF+50]), "+f"(d[OFF+51]), "+f"(d[OFF+52]), "+f"(d[OFF+53]), "+f"(d[OFF+54]), "+f"(d[OFF+55]), "+f"(d[OFF+56]), "+f"(d[OFF+57]), "+f"(d[OFF+58]), "+f"(d[OFF+59]), "+f"(d[OFF+60]), "+f"(d[OFF+61]), "+f"(d[OFF+62]), "+f"(d[OFF+63])
    : "l"(da), "l"(db), "r"(scale_d), "n"(TB));
}
template<int TB, int OFF, int NT>
__device__ __forceinline__ void wgmma_ss_n32(float (&d)[NT], uint64_t da, uint64_t db, int scale_d) {
  asm volatile("{\n.reg .pred p;\nsetp.ne.b32 p, %18, 0;\n"
    "wgmma.mma_async.sync.aligned.m64n32k16.f32.bf16.bf16 {%0, %1, %2, %3, %4, %5, %6, %7, %8, %9, %10, %11, %12, %13, %14, %15}, %16, %17, p, 1, 1, 0, %19;\n}\n"
    : "+f"(d[OFF+0]), "+f"(d[OFF+1]), "+f"(d[OFF+2]), "+f"(d[OFF+3]), "+f"(d[OFF+4]), "+f"(d[OFF+5]), "+f"(d[OFF+6]), "+f"(d[OFF+7]), "+f"(d[OFF+8]), "+f"(d[OFF+9]), "+f"(d[OFF+10]), "+f"(d[OFF+11]), "+f"(d[OFF+12]), "+f"(d[OFF+13]), "+f"(d[OFF+14]), "+f"(d[OFF+15])
    : "l"(da), "l"(db), "r"(scale_d), "n"(TB));
}
template<int TB, int OFF, int NT>
__device__ __forceinline__ void wgmma_rs_n128(float (&d)[NT], uint32_t a0, uint32_t a1, uint32_t a2, uint32_t a3, uint64_t db, int scale_d) {
  asm volatile("{\n.reg .pred p;\nsetp.ne.b32 p, %69, 0;\n"
    "wgmma.mma_async.sync.aligned.m64n128k16.f32.bf16.bf16 {%0, %1, %2, %3, %4, %5, %6, %7, %8, %9, %10, %11, %12, %13, %14, %15, %16, %17, %18, %19, %20, %21, %22, %23, %24, %25, %26, %27, %28, %29, %30, %31, %32, %33, %34, %35, %36, %37, %38, %39, %40, %41, %42, %43, %44, %45, %46, %47, %48, %49, %50, %51, %52, %53, %54, %55, %56, %57, %58, %59, %60, %61, %62, %63}, {%64, %65, %66, %67}, %68, p, 1, 1, %70;\n}\n"
    : "+f"(d[OFF+0]), "+f"(d[OFF+1]), "+f"(d[OFF+2]), "+f"(d[OFF+3]), "+f"(d[OFF+4]), "+f"(d[OFF+5]), "+f"(d[OFF+6]), "+f"(d[OFF+7]), "+f"(d[OFF+8]), "+f"(d[OFF+9]), "+f"(d[OFF+10]), "+f"(d[OFF+11]), "+f"(d[OFF+12]), "+f"(d[OFF+13]), "+f"(d[OFF+14]), "+f"(d[OFF+15]), "+f"(d[OFF+16]), "+f"(d[OFF+17]), "+f"(d[OFF+18]), "+f"(d[OFF+19]), "+f"(d[OFF+20]), "+f"(d[OFF+21]), "+f"(d[OFF+22]), "+f"(d[OFF+23]), "+f"(d[OFF+24]), "+f"(d[OFF+25]), "+f"(d[OFF+26]), "+f"(d[OFF+27]), "+f"(d[OFF+28]), "+f"(d[OFF+29]), "+f"(d[OFF+30]), "+f"(d[OFF+31]), "+f"(d[OFF+32]), "+f"(d[OFF+33]), "+f"(d[OFF+34]), "+f"(d[OFF+35]), "+f"(d[OFF+36]), "+f"(d[OFF+37]), "+f"(d[OFF+38]), "+f"(d[OFF+39]), "+f"(d[OFF+40]), "+f"(d[OFF+41]), "+f"(d[OFF+42]), "+f"(d[OFF+43]), "+f"(d[OFF+44]), "+f"(d[OFF+45]), "+f"(d[OFF+46]), "+f"(d[OFF+47]), "+f"(d[OFF+48]), "+f"(d[OFF+49]), "+f"(d[OFF+50]), "+f"(d[OFF+51]), "+f"(d[OFF+52]), "+f"(d[OFF+53]), "+f"(d[OFF+54]), "+f"(d[OFF+55]), "+f"(d[OFF+56]), "+f"(d[OFF+57]), "+f"(d[OFF+58]), "+f"(d[OFF+59]), "+f"(d[OFF+60]), "+f"(d[OFF+61]), "+f"(d[OFF+62]), "+f"(d[OFF+63])
    : "r"(a0), "r"(a1), "r"(a2), "r"(a3), "l"(db), "r"(scale_d), "n"(TB));
}
template<int TB, int OFF, int NT>
__device__ __forceinline__ void wgmma_rs_n64(float (&d)[NT], uint32_t a0, uint32_t a1, uint32_t a2, uint32_t a3, uint64_t db, int scale_d) {
  asm volatile("{\n.reg .pred p;\nsetp.ne.b32 p, %37, 0;\n"
    "wgmma.mma_async.sync.aligned.m64n64k16.f32.bf16.bf16 {%0, %1, %2, %3, %4, %5, %6, %7, %8, %9, %10, %11, %12, %13, %14, %15, %16, %17, %18, %19, %20, %21, %22, %23, %24, %25, %26, %27, %28, %29, %30, %31}, {%32, %33, %34, %35}, %36, p, 1, 1, %38;\n}\n"
    : "+f"(d[OFF+0]), "+f"(d[OFF+1]), "+f"(d[OFF+2]), "+f"(d[OFF+3]), "+f"(d[OFF+4]), "+f"(d[OFF+5]), "+f"(d[OFF+6]), "+f"(d[OFF+7]), "+f"(d[OFF+8]), "+f"(d[OFF+9]), "+f"(d[OFF+10]), "+f"(d[OFF+11]), "+f"(d[OFF+12]), "+f"(d[OFF+13]), "+f"(d[OFF+14]), "+f"(d[OFF+15]), "+f"(d[OFF+16]), "+f"(d[OFF+17]), "+f"(d[OFF+18]), "+f"(d[OFF+19]), "+f"(d[OFF+20]), "+f"(d[OFF+21]), "+f"(d[OFF+22]), "+f"(d[OFF+23]), "+f"(d[OFF+24]), "+f"(d[OFF+25]), "+f"(d[OFF+26]), "+f"(d[OFF+27]), "+f"(d[OFF+28]), "+f"(d[OFF+29]), "+f"(d[OFF+30]), "+f"(d[OFF+31])
    : "r"(a0), "r"(a1), "r"(a2), "r"(a3), "l"(db), "r"(scale_d), "n"(TB));
}

__device__ __forceinline__ void wait_flag(const unsigned int* f, uint32_t target) {
  uint32_t v;
#pragma unroll 1
  for (uint32_t spins = 0; spins < (1u << 22); spins++) {
    asm volatile("ld.acquire.gpu.global.u32 %0, [%1];" : "=r"(v) : "l"(f) : "memory");
    if (v >= target) break;
    __nanosleep(100);
  }
}
__device__ __forceinline__ uint32_t lds32(uint32_t a) {
  uint32_t v;
  asm volatile("ld.shared.u32 %0, [%1];" : "=r"(v) : "r"(a) : "memory");
  return v;
}
__device__ __forceinline__ float gate_row(int row, int lane, const bf16* __restrict__ x, const bf16* __restrict__ gate_w) {
  const uint32_t* xr = reinterpret_cast<const uint32_t*>(x + (size_t)row * DM);
  const uint32_t* gw2 = reinterpret_cast<const uint32_t*>(gate_w);
  float gs = 0.f;
#pragma unroll
  for (int i = 0; i < 9; i++) {
    const uint32_t a = __ldg(xr + lane + 32 * i), b = __ldg(gw2 + lane + 32 * i);
    gs = fmaf(bf_lo(a), bf_lo(b), gs);
    gs = fmaf(bf_hi(a), bf_hi(b), gs);
  }
#pragma unroll
  for (int o = 16; o; o >>= 1) gs += __shfl_xor_sync(0xffffffffu, gs, o);
  const float g = 1.f / (1.f + __expf(-gs));
  if (lane == 0) g_gate[row] = g;
  return g;
}
#define LA_UNROLL 1
__device__ __forceinline__ void local_rows2(int rb, int ri, uint32_t sL, uint32_t bL2, int lane, float ga, float gb) {
  const float scale_l2 = 0.23570226039551584f * 1.4426950408889634f;
  constexpr int U = LA_UNROLL;
  const uint32_t sq = sL + (30 + ri) * 1152;
  const uint32_t kb = sL + (14 + ri) * 1152 + lane * 36;
  float ma = -INFINITY, mb = -INFINITY;
  {
    float qa[18], qb[18];
#pragma unroll
    for (int i = 0; i < 9; i++) {
      const uint32_t u = lds32(sq - 2304 + lane * 36 + 4 * i), v = lds32(sq + lane * 36 + 4 * i);
      qa[2 * i] = bf_lo(u); qa[2 * i + 1] = bf_hi(u);
      qb[2 * i] = bf_lo(v); qb[2 * i + 1] = bf_hi(v);
    }
    __syncwarp();
#pragma unroll U
    for (int t = 0; t < 9; t++) {
      const bool ok = rb - 2 * t >= 0;
      float a0 = 0.f, a1 = 0.f, b0 = 0.f, b1 = 0.f;
#pragma unroll
      for (int i = 0; i < 9; i++) {
        const uint32_t k = lds32(kb - t * 2304 + 4 * i);
        const float lo = bf_lo(k), hi = bf_hi(k);
        a0 = fmaf(qa[2 * i], lo, a0); a1 = fmaf(qa[2 * i + 1], hi, a1);
        b0 = fmaf(qb[2 * i], lo, b0); b1 = fmaf(qb[2 * i + 1], hi, b1);
      }
      a0 = (ok && t > 0) ? a0 + a1 : -INFINITY;
      b0 = (ok && t < 8) ? b0 + b1 : -INFINITY;
      ma = fmaxf(ma, a0);
      mb = fmaxf(mb, b0);
      asm volatile("st.shared.f32 [%0], %1;" ::"r"(sq - 2304 + t * 128 + lane * 4), "f"(a0) : "memory");
      asm volatile("st.shared.f32 [%0], %1;" ::"r"(sq + t * 128 + lane * 4), "f"(b0) : "memory");
    }
  }
  float oa[18], ob[18], sa = 0.f, sb = 0.f;
#pragma unroll
  for (int i = 0; i < 18; i++) { oa[i] = 0.f; ob[i] = 0.f; }
  mbar_wait(bL2, 0);
#pragma unroll U
  for (int t = 0; t < 9; t++) {
    const float wa = ex2((__uint_as_float(lds32(sq - 2304 + t * 128 + lane * 4)) - ma) * scale_l2);
    const float wb = ex2((__uint_as_float(lds32(sq + t * 128 + lane * 4)) - mb) * scale_l2);
    sa += wa;
    sb += wb;
#pragma unroll
    for (int i = 0; i < 9; i++) {
      const uint32_t v = lds32(kb + 46 * 1152 - t * 2304 + 4 * i);
      const float lo = bf_lo(v), hi = bf_hi(v);
      oa[2 * i] = fmaf(wa, lo, oa[2 * i]); oa[2 * i + 1] = fmaf(wa, hi, oa[2 * i + 1]);
      ob[2 * i] = fmaf(wb, lo, ob[2 * i]); ob[2 * i + 1] = fmaf(wb, hi, ob[2 * i + 1]);
    }
  }
  ga = __fdividef(ga, sa);
  gb = __fdividef(gb, sb);
  __syncwarp();
#pragma unroll
  for (int i = 0; i < 9; i++) {
    asm volatile("st.shared.u32 [%0], %1;" ::"r"(sq - 2304 + lane * 36 + 4 * i), "r"(pack_bf16(oa[2 * i] * ga, oa[2 * i + 1] * ga)) : "memory");
    asm volatile("st.shared.u32 [%0], %1;" ::"r"(sq + lane * 36 + 4 * i), "r"(pack_bf16(ob[2 * i] * gb, ob[2 * i + 1] * gb)) : "memory");
  }
  __syncwarp();
  uint32_t w[5][4];
#pragma unroll
  for (int t = 0; t < 5; t++) {
    const int c = min(t * 32 + lane, 143), r = c >= 72;
    asm volatile("ld.shared.v4.u32 {%0, %1, %2, %3}, [%4];" : "=r"(w[t][0]), "=r"(w[t][1]), "=r"(w[t][2]), "=r"(w[t][3])
                 : "r"(sq - 2304 + r * 2304 + (c - r * 72) * 16) : "memory");
  }
  asm volatile("fence.proxy.async.shared::cta;" ::: "memory");
  bar_arrive(4, 256 + 32);
#pragma unroll
  for (int t = 0; t < 5; t++) {
    const int c = min(t * 32 + lane, 143), r = c >= 72;
    st_v4(g_ctx + (size_t)(rb - 2 + 2 * r) * KCAT + HDIM + (c - r * 72) * 8, w[t][0], w[t][1], w[t][2], w[t][3]);
  }
}

#define K1_NST 6
constexpr int K1_BST = K1_NST;
constexpr int K1_MAXJOBS = 11;
constexpr uint32_t K1_FLAG_TARGET = 7;
constexpr uint32_t RDY_TARGET = 48;
constexpr uint32_t GATE_TARGET = 128 * 3;
struct alignas(64) Params {
  CUtensorMap tmA[2];
  CUtensorMap tmW[4];
  CUtensorMap tmQ, tmK, tmV;
  CUtensorMap tmL[2];
  CUtensorMap tmC, tmO[2], tmOt[2];
  uint16_t jobs[NCLUSTER][K1_MAXJOBS];
  uint8_t order[256];
};

struct K1State {
  uint32_t bs, bph, aph;
  bf16* pp;
  int pld8;
  int png;
};
__device__ __forceinline__ void k1_flag(const K1State& st, int lane, uint32_t bS) {
  if (st.png) {
    __syncwarp();
    if (lane == 0) mbar_arrive(bS);
  }
}

__device__ __forceinline__ void k1_tile(float (&acc)[128], uint32_t (&pk)[64], K1State& st, uint32_t job, uint32_t sA, uint32_t sB,
                                        uint32_t bAf, uint32_t bAe, uint32_t bBf, uint32_t bBe, uint32_t bS, int wg, int warp, int lane, uint32_t rank) {
  const int a_sel = (job >> 2) & 1, mpair = (job >> 3) & 7, w_sel = (job >> 6) & 3, chunk0 = (job >> 8) & 63;
  const bool newA = (job >> 14) & 1, lastA = (job >> 15) & 1;
  const bool sig = (lane == 0) && (warp < 2);
  const bool siga = lastA && (lane == 0) && (warp == 2);
  const int KC = 8 + a_sel;
  uint32_t prev_bs = 0, prev2_bs = 0, a8_bs = 0;
#pragma unroll
  for (int kc = 0; kc < 9; kc++) {
    if (kc >= KC) break;
    uint32_t abase = sA + ((kc + 2) & 7) * 16384;
    if (kc == 8) {
      mbar_wait(bBf + st.bs * 8, st.bph);
      a8_bs = st.bs;
      abase = sB + st.bs * 16384;
      if (++st.bs == K1_BST) { st.bs = 0; st.bph ^= 1; }
    } else if (newA) {
      mbar_wait(bAf + kc * 8, st.aph);
    }
    const uint64_t da = make_desc(abase + wg * 8192, 16, 1024, 1);
#pragma unroll
    for (int ks = 0; ks < 2; ks++) {
      mbar_wait(bBf + st.bs * 8, st.bph);
      const uint64_t db = make_desc(sB + st.bs * 16384, 2048, 1024, 1);
      wg_fence();
      wgmma_ss_n256<1, 0>(acc, da + (uint64_t)(ks * 4), db, (ks > 0) ? 1 : (kc > 0));
      wgmma_ss_n256<1, 0>(acc, da + (uint64_t)(ks * 4 + 2), db + (uint64_t)512, 1);
      wg_commit();
      const int PO = (kc < 8 ? kc : 0) * 8;
      wg_wait<1>();
      if (ks > 0 || kc > 0) {
        if (sig) mbar_arrive_cluster(bBe + prev_bs * 8, warp);
        if (ks == 0 && siga) mbar_arrive(bAe + (kc - 1) * 8);
      }
      if (kc < st.png) st_v4(st.pp + kc * 32 + ks * st.pld8, pk[PO + ks * 4], pk[PO + ks * 4 + 1], pk[PO + ks * 4 + 2], pk[PO + ks * 4 + 3]);
      prev_bs = st.bs;
      if (++st.bs == K1_BST) { st.bs = 0; st.bph ^= 1; }
    }
  }
  if (newA) st.aph ^= 1;
  k1_flag(st, lane, bS);
  wg_wait<0>();
  fence_regs(acc);
  if (sig) {
    mbar_arrive_cluster(bBe + prev_bs * 8, warp);
    if (a_sel) mbar_arrive_cluster(bBe + a8_bs * 8, warp);
  }
  if (siga && !a_sel) mbar_arrive(bAe + 7 * 8);
  const bool isA = (w_sel == 2);
  bf16* out = (w_sel == 0) ? g_K : (w_sel == 1) ? g_V : isA ? g_QKVA : g_Q;
  const int ld = isA ? NQKVA : HDIM;
  const int row = mpair * 256 + rank * 128 + wg * 64 + warp * 16 + (lane >> 2);
  st.pp = out + (size_t)row * ld + chunk0 * 64 + (lane & 3) * 8;
  st.pld8 = 8 * ld;
  st.png = ((job & 3) + 1) * 2;
#pragma unroll
  for (int G = 0; G < 8; G++) {
    pk[G * 8 + 0] = pack_bf16(acc[G * 16 + 0], acc[G * 16 + 1]);
    pk[G * 8 + 1] = pack_bf16(acc[G * 16 + 4], acc[G * 16 + 5]);
    pk[G * 8 + 2] = pack_bf16(acc[G * 16 + 8], acc[G * 16 + 9]);
    pk[G * 8 + 3] = pack_bf16(acc[G * 16 + 12], acc[G * 16 + 13]);
    pk[G * 8 + 4] = pack_bf16(acc[G * 16 + 2], acc[G * 16 + 3]);
    pk[G * 8 + 5] = pack_bf16(acc[G * 16 + 6], acc[G * 16 + 7]);
    pk[G * 8 + 6] = pack_bf16(acc[G * 16 + 10], acc[G * 16 + 11]);
    pk[G * 8 + 7] = pack_bf16(acc[G * 16 + 14], acc[G * 16 + 15]);
  }
  if (isA) {
#pragma unroll
    for (int G = 0; G < 16; G++) quad_transpose(pk[G * 4 + 0], pk[G * 4 + 1], pk[G * 4 + 2], pk[G * 4 + 3], lane & 3);
  }
}

#define HA(h) (h)
constexpr int K2_NST = 7;
constexpr uint32_t K2_END = 0x100;
constexpr int K3_NST = 4;
#define K3_P1 20
#define K3_P2 39
#define K3_P3 57
__device__ __forceinline__ uint32_t k3_rot(uint32_t sv) { return (0x00E9u >> (2 * sv)) & 3; }
__device__ __forceinline__ int k3_part(int i) { return (i == 0) ? 0 : (i == 1) ? K3_P1 : (i == 2) ? K3_P2 : (i == 3) ? K3_P3 : 73; }
constexpr int K3_STAGE = 16384 + 32768 + 4096;
constexpr int SMEM_DATA = 7 * 32768;
constexpr int SMEM_BYTES = SMEM_DATA + 1024 + 768;

struct Cursor {
  uint32_t s, ph;
  __device__ __forceinline__ void next() {
    if (++s == K2_NST) { s = 0; ph ^= 1; }
  }
};

#define TURN_SYNC() bar_sync(mybar, 256)
#define TURN_ARRIVE() bar_arrive(otherbar, 256)
#define RELEASE_IF(cur, cond) mbar_arrive_cluster_if(bE + (cur).s * 8, warp & 1, sig && (cond))
#define RELEASE(cur) RELEASE_IF(cur, true)
#define ISSUE_PV(cur, first)                                                                                   \
  do {                                                                                                         \
    const uint64_t dv = make_desc(sbase + (cur).s * 32768, 16384, 1024, 1);                                    \
    _Pragma("unroll") for (int t = 0; t < 8; t++)                                                              \
        wgmma_rs_n128<1, 0>(O, P[4 * t], P[4 * t + 1], P[4 * t + 2], P[4 * t + 3], dv + (uint64_t)(t * 128), (t > 0) ? 1 : !(first)); \
  } while (0)
#define RESCALE_O()                                                                                            \
  do {                                                                                                         \
    fence_regs(O);                                                                                             \
    _Pragma("unroll") for (int jj = 0; jj < 16; jj++) {                                                        \
      O[jj * 4 + 0] *= sc0; O[jj * 4 + 1] *= sc0; O[jj * 4 + 2] *= sc1; O[jj * 4 + 3] *= sc1;                  \
    }                                                                                                          \
    fence_regs(O);                                                                                             \
  } while (0)
#define ISSUE_QK(cur)                                                                                          \
  do {                                                                                                         \
    const uint64_t dk = make_desc(sbase + (cur).s * 32768, 16, 1024, 1);                                       \
    _Pragma("unroll") for (int t = 0; t < 8; t++)                                                              \
        wgmma_rs_n128<0, 0>(S, Q[4 * t], Q[4 * t + 1], Q[4 * t + 2], Q[4 * t + 3], dk + (uint64_t)((t >> 2) * 1024 + (t & 3) * 2), t > 0); \
  } while (0)
#define EPILOGUE()                                                                                             \
  do {                                                                                                         \
    l0 += __shfl_xor_sync(0xffffffffu, l0, 1);                                                                 \
    l0 += __shfl_xor_sync(0xffffffffu, l0, 2);                                                                 \
    l1 += __shfl_xor_sync(0xffffffffu, l1, 1);                                                                 \
    l1 += __shfl_xor_sync(0xffffffffu, l1, 2);                                                                 \
    const float f0 = __fdividef(gf0, l0), f1 = __fdividef(gf1, l1);                                                                \
    bf16* o0 = g_ctx + (size_t)prev_row * KCAT + prev_h * 128 + q * 8;                                         \
    bf16* o1 = o0 + (size_t)8 * KCAT;                                                                          \
    _Pragma("unroll") for (int G = 0; G < 4; G++) {                                                            \
      st_v4(o0 + G * 32, pack_bf16(O[G * 16 + 0] * f0, O[G * 16 + 1] * f0), pack_bf16(O[G * 16 + 4] * f0, O[G * 16 + 5] * f0), \
            pack_bf16(O[G * 16 + 8] * f0, O[G * 16 + 9] * f0), pack_bf16(O[G * 16 + 12] * f0, O[G * 16 + 13] * f0)); \
      st_v4(o1 + G * 32, pack_bf16(O[G * 16 + 2] * f1, O[G * 16 + 3] * f1), pack_bf16(O[G * 16 + 6] * f1, O[G * 16 + 7] * f1), \
            pack_bf16(O[G * 16 + 10] * f1, O[G * 16 + 11] * f1), pack_bf16(O[G * 16 + 14] * f1, O[G * 16 + 15] * f1)); \
    }                                                                                                          \
  } while (0)

__global__ void __cluster_dims__(2, 1, 1) __launch_bounds__(384, 1)
fused_kernel(const __grid_constant__ Params p, const bf16* __restrict__ x, const bf16* __restrict__ gate_w, bf16* __restrict__ out) {
  extern __shared__ uint8_t smem_raw[];
  const uint32_t sbase = (smem_u32(smem_raw) + 1023) & ~1023u;
  const uint32_t sB = sbase, sA = sbase + K1_BST * 16384, sBar = sbase + SMEM_DATA;
  const uint32_t bAf = sBar, bAe = sBar + 64, bBf = sBar + 128, bBe = sBar + 176, bL = sBar + 224, bS = sBar + 232, bL2 = sBar + 240, sL = sA + 32768;
  const uint32_t bF = sBar + 256, bE = sBar + 320, bT = sBar + 384, sTick = sBar + 400, sItem = sBar + 416, bS2 = sBar + 448, bR = sBar + 456, bLast = sBar + 464, bH = sBar + 472;
  const uint32_t b3F = sBar + 512, b3E = sBar + 544, sGate = sBar + 576;
  const int tid = threadIdx.x, warp_g = __shfl_sync(0xffffffffu, tid >> 5, 0), lane = tid & 31;
  const uint32_t rank = cluster_rank();
  const int cl = blockIdx.x >> 1;
  TSM(0);
  if (tid == 0) {
    for (int i = 0; i < 8; i++) { mbar_init(bAf + i * 8, 1); mbar_init(bAe + i * 8, 2); }
    for (int i = 0; i < K1_BST; i++) { mbar_init(bBf + i * 8, 1); mbar_init(bBe + i * 8, 4); }
    mbar_init(bL, 1);
    mbar_init(bL2, 1);
    mbar_init(bR, 1);
    mbar_init(bLast, 1);
    mbar_init(bH, 4);
    mbar_init(bS, 8);
    for (int i = 0; i < K2_NST; i++) { mbar_init(bF + i * 8, 1); mbar_init(bE + i * 8, 4); }
    mbar_init(bT, 1); mbar_init(bT + 8, 1);
    mbar_init(bS2, 8);
    for (int i = 0; i < K3_NST; i++) { mbar_init(b3F + i * 8, 1); mbar_init(b3E + i * 8, 4); }
    asm volatile("fence.mbarrier_init.release.cluster;" ::: "memory");
  }
  __syncthreads();
  cluster_sync();
  const int lr0 = blockIdx.x * 16;

  if (warp_g >= 8) {
    reg_dealloc<40>();
    if (warp_g == 8) {
      if (elect_one()) {
        uint32_t bs = 0, bph = 1, aph = 1;
#pragma unroll 1
        for (int ji = 0; ji < K1_MAXJOBS; ji++) {
          const uint32_t job = p.jobs[cl][ji];
          if (!(job & 3)) break;
          const int a_sel = (job >> 2) & 1, mpair = (job >> 3) & 7, chunk0 = (job >> 8) & 63;
          const bool newA = (job >> 14) & 1;
          const int KC = a_sel ? 9 : 8;
          const uint32_t halfbytes = 8192;
          const bool lastjob = (ji + 1 == K1_MAXJOBS) || !(p.jobs[cl][ji + 1] & 3);
          const CUtensorMap* tw = &p.tmW[(job >> 6) & 3];
          {
            const uint32_t njob = (ji + 1 < K1_MAXJOBS) ? p.jobs[cl][ji + 1] : 0;
            if (!(njob & 3) && !newA) mbar_arrive(bLast);
            if (njob & 3) {
              const int nst = ((njob >> 2) & 1) ? 18 : 16;
#pragma unroll 1
              for (int t = (cl < 64) ? (cl & 7) : 0; t < nst; t += (cl < 64) ? 8 : 1)
                tma_pf3d(&p.tmW[(njob >> 6) & 3], 0, t * 32 + rank * 16, (njob >> 8) & 63);
            }
          }
#pragma unroll 1
          for (int kc = 0; kc < KC; kc++) {
            if (kc == 8) {
              mbar_wait(bBe + bs * 8, bph);
              mbar_expect(bBf + bs * 8, 16384);
              tma2d(sB + bs * 16384, &p.tmA[1], bBf + bs * 8, 512, mpair * 256 + rank * 128);
              if (++bs == K1_BST) { bs = 0; bph ^= 1; }
            } else if (newA) {
              mbar_wait(bAe + kc * 8, aph);
              mbar_expect(bAf + kc * 8, 16384);
              tma2d(sA + ((kc + 2) & 7) * 16384, &p.tmA[a_sel], bAf + kc * 8, kc * 64, mpair * 256 + rank * 128);
              if (kc == 7 && lastjob) mbar_arrive(bLast);
            }
#pragma unroll 1
            for (int kk = 0; kk < 2; kk++) {
              mbar_wait(bBe + bs * 8, bph);
              mbar_expect(bBf + bs * 8, 2 * halfbytes);
              tma3d_mc(sB + bs * 16384 + rank * halfbytes, tw, bBf + bs * 8, 0, kc * 64 + kk * 32 + rank * 16, chunk0, 3);
              if (++bs == K1_BST) { bs = 0; bph ^= 1; }
            }
          }
          if (newA) aph ^= 1;
        }
        Cursor c{0, 0};
        int pcol = 0;
        uint32_t tick = cl, seen = 1u << (p.order[cl] >> 4);
        mbar_wait(bR, 0);
        asm volatile("fence.proxy.async.global;" ::: "memory");
#pragma unroll 1
        for (int it = 0;; it++) {
          const uint32_t item = (tick < 256) ? p.order[tick] : (K2_END | min(tick - 256, 255u));
          asm volatile("st.shared.u32 [%0], %1;" ::"r"(sItem + (it & 7) * 4), "r"(item) : "memory");
          if (item >= K2_END) break;
          const int h = item >> 3, j = item & 7;
          const int blk = 2 * j + (int)(rank ^ (it & 1));
          const int col = HA(h) * 128 + rank * 64;
          const int nb = 2 * j + 2;
          if (!((seen >> (h >> 1)) & 1)) {
            wait_flag(&g_sync[F_HP + (h >> 1)], RDY_TARGET);
            asm volatile("fence.proxy.async.global;" ::: "memory");
            seen |= 1u << (h >> 1);
          }
          mbar_wait(bE + c.s * 8, c.ph);
          mbar_expect(bF + c.s * 8, 32768);
          tma2d(sbase + c.s * 32768, &p.tmQ, bF + c.s * 8, HA(h) * 128, blk * 128);
          tma2d(sbase + c.s * 32768 + 16384, &p.tmQ, bF + c.s * 8, HA(h) * 128 + 64, blk * 128);
          c.next();
#pragma unroll 1
          for (int n = nb - 1; n >= 0; n--) {
            if (n == 0 && rank == 0) tick = atomicAdd(&g_sync[F_TICK], 1u) + NCLUSTER;
            mbar_wait(bE + c.s * 8, c.ph);
            mbar_expect(bF + c.s * 8, 32768);
            tma2d_mc(sbase + c.s * 32768 + rank * 16384, &p.tmK, bF + c.s * 8, col, n * 128, 3);
            c.next();
            if (n < nb - 1 || it > 0) {
              mbar_wait(bE + c.s * 8, c.ph);
              mbar_expect(bF + c.s * 8, 32768);
              tma2d_mc(sbase + c.s * 32768 + rank * 16384, &p.tmV, bF + c.s * 8, (n < nb - 1) ? col : pcol, (n < nb - 1) ? (n + 1) * 128 : 0, 3);
              c.next();
            }
          }
          pcol = col;
          if (rank == 0) {
            asm volatile(
                "{\n.reg .b32 a, b;\nmapa.shared::cluster.u32 a, %0, 1;\nmapa.shared::cluster.u32 b, %1, 1;\n"
                "st.async.shared::cluster.mbarrier::complete_tx::bytes.u32 [a], %2, [b];\n}" ::"r"(sTick + (it & 1) * 4),
                "r"(bT + (it & 1) * 8), "r"(tick) : "memory");
          } else {
            mbar_expect(bT + (it & 1) * 8, 4);
            mbar_wait(bT + (it & 1) * 8, (it >> 1) & 1);
            tick = lds32(sTick + (it & 1) * 4);
          }
        }
        mbar_wait(bE + c.s * 8, c.ph);
        mbar_expect(bF + c.s * 8, 32768);
        tma2d_mc(sbase + c.s * 32768 + rank * 16384, &p.tmV, bF + c.s * 8, pcol, 0, 3);
        const uint32_t unit = tick - 256;
        if (unit < 64) {
          const int mblk = (7 - (int)((unit >> 1) & 7)) * 2 + rank, nhalf = unit & 1, ks = unit >> 4;
          const uint32_t rot = k3_rot(c.s), nfree = ((0x1Au >> c.s) & 1) ? 2 : 3;
#pragma unroll 1
          for (int i = 0; i < K2_NST - 1; i++) {
            c.next();
            mbar_wait(bE + c.s * 8, c.ph);
          }
          uint32_t idx = 0, have = 0;
#pragma unroll 1
          for (int kk = k3_part(ks); kk < k3_part(ks + 1); kk++, idx++) {
            const uint32_t s = (rot + idx) & 3;
            if (idx >= nfree) mbar_wait((idx < 4) ? bH : b3E + s * 8, (idx < 4) ? 0 : (~idx >> 2) & 1);
            mbar_expect(b3F + s * 8, K3_STAGE);
            const uint32_t st = sbase + s * K3_STAGE;
            const int sel = (kk < 9), k = sel ? kk : kk - 9, kr = k * 64 + rank * 32;
            tma3d_mc(st + 16384 + rank * 16384, &p.tmO[sel], b3F + s * 8, 0, kr, nhalf * 4, 3);
            tma2d_mc(st + 49152 + rank * 2048, &p.tmOt[sel], b3F + s * 8, 512 + nhalf * 32, kr, 3);
            if (kk == 0) {
              wait_flag(&g_sync[F_OA + mblk], 8);
              asm volatile("fence.proxy.async.global;" ::: "memory");
            }
            if (!sel && !((have >> (k >> 1)) & 1)) {
#pragma unroll 1
              for (uint32_t spins = 0; spins < (1u << 22); spins++) {
                asm volatile("ld.acquire.gpu.global.u32 %0, [%1];" : "=r"(have) : "l"(&g_sync[F_CTX + mblk]) : "memory");
                if ((have >> (k >> 1)) & 1) break;
                __nanosleep(100);
              }
              asm volatile("fence.proxy.async.global;" ::: "memory");
            }
            tma2d(st, &p.tmC, b3F + s * 8, (sel ? 64 + k : k) * 64, mblk * 128);
          }
        }
      }
    }
    __syncwarp();
    if (warp_g == 8) {
      uint32_t v = 0;
      if (lane == 0) {
        __threadfence();
        v = atomicAdd(&g_sync[F_DONE], 1u);
      }
      if (__shfl_sync(0xffffffffu, v, 0) == 2 * NCLUSTER - 1) {
        reinterpret_cast<uint4*>(g_sync)[lane] = make_uint4(0, 0, 0, 0);
        if (lane == 0) g_sync[F_EPOCH] = lds32(sGate + 64) + 1;
      }
    }
    asm volatile("" ::: "memory");
    if (__shfl_sync(0xffffffffu, warp_g, 0) != 8) {
      if (lr0 < S_LEN) {
#pragma unroll 1
        for (int i = warp_g - 9; i < 16; i += 3) {
          const float g = gate_row(lr0 + i, lane, x, gate_w);
          if (lane == 0) asm volatile("st.shared.f32 [%0], %1;" ::"r"(sGate + i * 4), "f"(g) : "memory");
        }
        bar_arrive(3, 256 + 96);
        if (lane == 0) {
          __threadfence();
          atomicAdd(&g_sync[F_GATE], 1u);
        }
      }
      if (warp_g == 9 && lane == 0) {
#pragma unroll 1
        for (int ji = 0; ji < K1_MAXJOBS; ji++) {
          const uint32_t job = p.jobs[cl][ji];
          if (!(job & 3)) break;
          mbar_wait(bS, ji & 1);
          __threadfence();
          atomicAdd(&g_sync[(((job >> 6) & 3) == 2) ? (F_QKVA + ((job >> 3) & 7) * 2 + rank) : (F_HP + ((job >> 10) & 15))], 1u);
        }
#pragma unroll 1
        for (int it = 0;; it++) {
          mbar_wait(bS2, it & 1);
          const uint32_t item = lds32(sItem + (it & 7) * 4), nxt = lds32(sItem + ((it + 1) & 7) * 4);
          __threadfence();
          atomicOr(&g_sync[F_CTX + (item & 7) * 2 + (rank ^ (it & 1))], 1u << (item >> 3));
          if (nxt >= K2_END) break;
        }
      } else if (warp_g == 11) {
        if (lane == 0) {
          prefetch_tmap(&p.tmQ); prefetch_tmap(&p.tmK); prefetch_tmap(&p.tmV);
          asm volatile("st.shared.u32 [%0], %1;" ::"r"(sGate + 64), "r"(__ldcg(&g_sync[F_EPOCH])) : "memory");
          wait_flag(&g_sync[F_GATE], GATE_TARGET);
          wait_flag(&g_sync[F_HP + (p.order[cl] >> 4)], RDY_TARGET);
          mbar_arrive(bR);
        }
        __syncwarp();
        bar_sync(4, 256 + 32);
        if (lane < 12) mbar_arrive_cluster(bE + (4 + lane % 3) * 8, (lane / 3) & 1);
      } else if (warp_g == 10 && lr0 < S_LEN) {
        if (elect_one()) {
          prefetch_tmap(&p.tmL[0]); prefetch_tmap(&p.tmL[1]);
          uint32_t aph = 1;
#pragma unroll 1
          for (int ji = 0; ji < K1_MAXJOBS; ji++) aph ^= (p.jobs[cl][ji] >> 14) & 1;
          wait_flag(&g_sync[F_QKVA + (lr0 >> 7)], K1_FLAG_TARGET);
          wait_flag(&g_sync[F_QKVA + (max(lr0 - 14, 0) >> 7)], K1_FLAG_TARGET);
          asm volatile("fence.proxy.async.global;" ::: "memory");
          mbar_wait(bLast, 0);
#pragma unroll 1
          for (int kc = 0; kc < 6; kc++) {
            mbar_wait(bAe + kc * 8, aph);
            if (kc == 3) {
              mbar_expect(bL, 46 * 1152);
              tma3d(sL, &p.tmL[0], bL, 0, 9, lr0 - 14);
              tma3d(sL + 30 * 1152, &p.tmL[1], bL, 0, 0, lr0);
            }
          }
          mbar_expect(bL2, 30 * 1152);
          tma3d(sL + 46 * 1152, &p.tmL[0], bL2, 0, 18, lr0 - 14);
        }
        __syncwarp();
        bar_sync(5, 256 + 32);
        if (lane == 0) {
          __threadfence();
          atomicAdd(&g_sync[F_OA + (lr0 >> 7)], 1u);
        }
      }
    }
    __syncwarp();
    cluster_sync();
  } else {
    reg_alloc<232>();
    const int wg = warp_g >> 2, warp = warp_g & 3, q = lane & 3;
    const bool sig = (lane == 0) && (warp < 2);
    {
      K1State st{0, 0, 0, nullptr, 0, 0};
      float acc[128];
      uint32_t pk[64];
      if (wg == 0) { TS(0, 0); TSC(0, 2); }
#pragma unroll 1
      for (int ji = 0; ji < K1_MAXJOBS; ji++) {
        const uint32_t job = p.jobs[cl][ji];
        if (!(job & 3)) break;
        k1_tile(acc, pk, st, job, sA, sB, bAf, bAe, bBf, bBe, bS, wg, warp, lane, rank);
      }
#pragma unroll
      for (int i = 0; i < 4; i++)
        mbar_arrive_cluster_if(bE + i * 8, warp & 1, sig);
#pragma unroll
      for (int G = 0; G < 8; G++)
        if (G < st.png) {
          st_v4(st.pp + G * 32, pk[G * 8], pk[G * 8 + 1], pk[G * 8 + 2], pk[G * 8 + 3]);
          st_v4(st.pp + G * 32 + st.pld8, pk[G * 8 + 4], pk[G * 8 + 5], pk[G * 8 + 6], pk[G * 8 + 7]);
        }
      k1_flag(st, lane, bS);
      if (wg == 0) { TS(0, 1); TSC(0, 3); }
      if (lr0 < S_LEN) {
        const int ri = (warp_g >> 1) * 4 + (warp_g & 1) + 2, row = lr0 + ri;
        if (wg == 0) TS(1, 5);
        bar_sync(3, 256 + 96);
        const float gate0 = __uint_as_float(lds32(sGate + ri * 4 - 8)), gate1 = __uint_as_float(lds32(sGate + ri * 4));
        mbar_wait(bL, 0);
        if (wg == 0) TS(1, 6);
        local_rows2(row, ri, sL, bL2, lane, gate0, gate1);
        bar_arrive(5, 256 + 32);
      } else {
        bar_arrive(4, 256 + 32);
      }
    }
    __syncwarp();
    uint32_t item, rot;
    {
      const int mybar = 1 + wg, otherbar = 2 - wg;
      const float cl2 = 0.08838834764831845f * 1.4426950408889634f;
      float S[64], O[64];
      uint32_t P[32], Q[32];
      float m0 = 0.f, m1 = 0.f, l0 = 0.f, l1 = 0.f;
      int prev_row = 0, prev_h = 0, prev_single = 0;
      Cursor c{0, 0};
      if (wg == 1) bar_arrive(1, 256);
      if (wg == 0) { TS(1, 0); TSC(1, 2); }
#pragma unroll 1
      for (int it = 0;; it++) {
        mbar_wait(bF + c.s * 8, c.ph);
        item = lds32(sItem + (it & 7) * 4);
        const bool last = item >= K2_END;
        const int h = item >> 3, j = item & 7;
        const int hi = (int)(rank ^ (it & 1));
        const int nblk = 2 * j + 1 + hi;
        {
          const float gf0 = 1.f - g_gate[prev_row], gf1 = 1.f - g_gate[prev_row + 8];
          Cursor cq = c, ck = c, cs0 = c, cs1 = c, cv = c;
          rot = k3_rot(c.s);
          if (!last) {
            const int r = wg * 64 + warp * 16 + (lane & 7) + ((lane >> 3) & 1) * 8;
            const uint32_t qa = sbase + cq.s * 32768 + r * 128;
#pragma unroll
            for (int t = 0; t < 8; t++)
              ldsm_x4(Q[4 * t], Q[4 * t + 1], Q[4 * t + 2], Q[4 * t + 3], qa + (t >> 2) * 16384 + ((((t & 3) * 2 + (lane >> 4)) ^ (lane & 7)) << 4));
            c.next();
            ck = c; c.next();
            cs0 = ck; cv = c;
            mbar_wait(bF + ck.s * 8, ck.ph);
            if (it > 0) { mbar_wait(bF + cv.s * 8, cv.ph); c.next(); }
            if (!hi) {
              ck = c; c.next();
              cs1 = c; c.next();
              mbar_wait(bF + ck.s * 8, ck.ph);
              mbar_wait(bF + cs1.s * 8, cs1.ph);
            }
          }
          if (it == 0) BSEG(4); else BSEG(0);
          TURN_SYNC();
          if (it > 0) {
            wg_fence();
            ISSUE_PV(cv, prev_single);
            wg_commit();
          } else {
            wg_fence();
            wg_commit();
          }
          wg_fence();
          ISSUE_QK(ck);
          wg_commit();
          if (!(last && wg == 1)) TURN_ARRIVE();
          RELEASE_IF(cq, !last);
          RELEASE_IF(cs0, !last && !hi);
          RELEASE_IF(cs1, !last && !hi);
          wg_wait<1>();
          fence_regs(O);
          fence_regs(P);
          if (it > 0) {
            RELEASE_IF(cv, !last);
            mbar_arrive_cluster_if(bH, warp & 1, sig && last);
            EPILOGUE();
            __syncwarp();
            mbar_arrive_if(bS2, lane == 0);
          }
          wg_wait<0>();
          fence_regs(S);
          if (last) break;
          RELEASE(ck);
          float s0 = 0.f, s1 = 0.f;
          const int r0 = wg * 64 + warp * 16 + (lane >> 2);
#pragma unroll
          for (int jj = 0; jj < 16; jj++) {
            const int cc = jj * 8 + 2 * q;
            if (cc > r0) S[jj * 4 + 0] = -INFINITY;
            if (cc + 1 > r0) S[jj * 4 + 1] = -INFINITY;
            if (cc > r0 + 8) S[jj * 4 + 2] = -INFINITY;
            if (cc + 1 > r0 + 8) S[jj * 4 + 3] = -INFINITY;
          }
          float mx0 = fmaxf(S[0], S[1]), mx1 = fmaxf(S[2], S[3]);
#pragma unroll
          for (int jj = 1; jj < 16; jj++) {
            mx0 = fmaxf(mx0, fmaxf(S[jj * 4 + 0], S[jj * 4 + 1]));
            mx1 = fmaxf(mx1, fmaxf(S[jj * 4 + 2], S[jj * 4 + 3]));
          }
          mx0 = fmaxf(mx0, __shfl_xor_sync(0xffffffffu, mx0, 1));
          mx1 = fmaxf(mx1, __shfl_xor_sync(0xffffffffu, mx1, 1));
          mx0 = fmaxf(mx0, __shfl_xor_sync(0xffffffffu, mx0, 2));
          mx1 = fmaxf(mx1, __shfl_xor_sync(0xffffffffu, mx1, 2));
          m0 = mx0; m1 = mx1;
          const float mc0 = m0 * cl2, mc1 = m1 * cl2;
#pragma unroll
          for (int jj = 0; jj < 16; jj++) {
            S[jj * 4 + 0] = ex2(fmaf(S[jj * 4 + 0], cl2, -mc0));
            S[jj * 4 + 1] = ex2(fmaf(S[jj * 4 + 1], cl2, -mc0));
            S[jj * 4 + 2] = ex2(fmaf(S[jj * 4 + 2], cl2, -mc1));
            S[jj * 4 + 3] = ex2(fmaf(S[jj * 4 + 3], cl2, -mc1));
            s0 += S[jj * 4 + 0] + S[jj * 4 + 1];
            s1 += S[jj * 4 + 2] + S[jj * 4 + 3];
          }
          l0 = s0; l1 = s1;
#pragma unroll
          for (int jj = 0; jj < 16; jj++) {
            P[jj * 2 + 0] = pack_bf16(S[jj * 4 + 0], S[jj * 4 + 1]);
            P[jj * 2 + 1] = pack_bf16(S[jj * 4 + 2], S[jj * 4 + 3]);
          }
        }
        if (it == 0) BSEG(5); else BSEG(1);
#pragma unroll 1
        for (int n = 1; n < nblk; n++) {
          Cursor ck = c; c.next();
          Cursor cv = c; c.next();
          mbar_wait(bF + ck.s * 8, ck.ph);
          mbar_wait(bF + cv.s * 8, cv.ph);
          TURN_SYNC();
          wg_fence();
          ISSUE_QK(ck);
          wg_commit();
          ISSUE_PV(cv, n == 1);
          wg_commit();
          TURN_ARRIVE();
          wg_wait<1>();
          fence_regs(S);
          RELEASE(ck);
          float mx0 = fmaxf(S[0], S[1]), mx1 = fmaxf(S[2], S[3]);
#pragma unroll
          for (int jj = 1; jj < 16; jj++) {
            mx0 = fmaxf(mx0, fmaxf(S[jj * 4 + 0], S[jj * 4 + 1]));
            mx1 = fmaxf(mx1, fmaxf(S[jj * 4 + 2], S[jj * 4 + 3]));
          }
          mx0 = fmaxf(mx0, __shfl_xor_sync(0xffffffffu, mx0, 1));
          mx1 = fmaxf(mx1, __shfl_xor_sync(0xffffffffu, mx1, 1));
          mx0 = fmaxf(mx0, __shfl_xor_sync(0xffffffffu, mx0, 2));
          mx1 = fmaxf(mx1, __shfl_xor_sync(0xffffffffu, mx1, 2));
          mx0 = fmaxf(mx0, m0);
          mx1 = fmaxf(mx1, m1);
          const float sc0 = ex2((m0 - mx0) * cl2), sc1 = ex2((m1 - mx1) * cl2);
          m0 = mx0; m1 = mx1;
          const float mc0 = m0 * cl2, mc1 = m1 * cl2;
          float s0 = 0.f, s1 = 0.f;
#pragma unroll
          for (int jj = 0; jj < 16; jj++) {
            S[jj * 4 + 0] = ex2(fmaf(S[jj * 4 + 0], cl2, -mc0));
            S[jj * 4 + 1] = ex2(fmaf(S[jj * 4 + 1], cl2, -mc0));
            S[jj * 4 + 2] = ex2(fmaf(S[jj * 4 + 2], cl2, -mc1));
            S[jj * 4 + 3] = ex2(fmaf(S[jj * 4 + 3], cl2, -mc1));
            s0 += S[jj * 4 + 0] + S[jj * 4 + 1];
            s1 += S[jj * 4 + 2] + S[jj * 4 + 3];
          }
          l0 = fmaf(l0, sc0, s0);
          l1 = fmaf(l1, sc1, s1);
          fence_regs(S);
          wg_wait<0>();
          fence_regs(O);
          fence_regs(P);
          RELEASE(cv);
#pragma unroll
          for (int jj = 0; jj < 16; jj++) {
            O[jj * 4 + 0] *= sc0;
            O[jj * 4 + 1] *= sc0;
            O[jj * 4 + 2] *= sc1;
            O[jj * 4 + 3] *= sc1;
            P[jj * 2 + 0] = pack_bf16(S[jj * 4 + 0], S[jj * 4 + 1]);
            P[jj * 2 + 1] = pack_bf16(S[jj * 4 + 2], S[jj * 4 + 3]);
          }
        }
        BSEG(2);
        prev_row = (2 * j + hi) * 128 + wg * 64 + warp * 16 + (lane >> 2);
        prev_h = h;
        prev_single = (nblk == 1);
      }
      if (wg == 1) { TS(1, 1); TSC(1, 3); }
    }
    __syncwarp();
    const uint32_t unit = item & 255;
    if (unit < 64) {
      const int mblk = (7 - (int)((unit >> 1) & 7)) * 2 + rank, nhalf = unit & 1, ks = unit >> 4;
      const int k0 = k3_part(ks), k1 = k3_part(ks + 1);
      float acc[144];
      uint32_t s = rot, ph = 0, prev = 0;
      if (wg == 0) { TS(2, 0); TSC(2, 2); }
#pragma unroll 1
      for (int k = k0; k < k1; k++) {
        mbar_wait(b3F + s * 8, ph);
        const uint32_t st = sbase + s * K3_STAGE;
        const uint64_t da = make_desc(st + wg * 8192, 16, 1024, 1);
        const uint64_t db = make_desc(st + 16384, 4096, 1024, 1);
        const uint64_t dt = make_desc(st + 49152, 16, 512, 2);
        wg_fence();
#pragma unroll
        for (int t = 0; t < 4; t++) {
          const int sd = (t > 0) || (k > k0);
          wgmma_ss_n256<1, 0>(acc, da + (uint64_t)(t * 2), db + (uint64_t)((t >> 1) * 1024 + (t & 1) * 128), sd);
          wgmma_ss_n32<1, 128>(acc, da + (uint64_t)(t * 2), dt + (uint64_t)(t * 64), sd);
        }
        wg_commit();
        if (k > k0) {
          wg_wait<1>();
          if (sig) mbar_arrive_cluster(b3E + prev * 8, warp);
        }
        prev = s;
        s = (s + 1) & 3;
        if (s == rot) ph ^= 1;
      }
      wg_wait<0>();
      fence_regs(acc);
      cluster_arrive();
      if (wg == 0) TS(2, 4);
      const int tile = mblk * 2 + nhalf;
      uint4* wp = g_part + (size_t)((tile * 4 + ks) * 4) * 5 * 256 + tid;
      const uint32_t sown = sbase + wg * 8192 + (tid & 127) * 16;
#pragma unroll
      for (int d = 0; d < 4; d++) {
        if (d != ks) {
#pragma unroll
          for (int i = 0; i < 4; i++)
            __stcg(wp + (d * 5 + i) * 256,
                   make_uint4(pack_bf16(acc[d * 32 + i * 8], acc[d * 32 + i * 8 + 1]), pack_bf16(acc[d * 32 + i * 8 + 2], acc[d * 32 + i * 8 + 3]),
                              pack_bf16(acc[d * 32 + i * 8 + 4], acc[d * 32 + i * 8 + 5]), pack_bf16(acc[d * 32 + i * 8 + 6], acc[d * 32 + i * 8 + 7])));
          __stcg(reinterpret_cast<uint2*>(wp - tid + (d * 5 + 4) * 256) + tid,
                 make_uint2(pack_bf16(acc[128 + d * 4], acc[128 + d * 4 + 1]), pack_bf16(acc[128 + d * 4 + 2], acc[128 + d * 4 + 3])));
        } else {
#pragma unroll
          for (int i = 0; i < 9; i++) {
            const int o = (i < 8) ? d * 32 + i * 4 : 128 + d * 4;
            asm volatile("st.shared.v4.f32 [%0], {%1, %2, %3, %4};" ::"r"(sown + (i >> 2) * K3_STAGE + (i & 3) * 2048), "f"(acc[o]), "f"(acc[o + 1]), "f"(acc[o + 2]), "f"(acc[o + 3]) : "memory");
          }
        }
      }
      __threadfence();
      __syncwarp();
      if (wg == 0) TS(2, 5);
      if (lane == 0) {
        unsigned int* cnt = &g_sync[F_XCH + tile * 8 + warp_g];
        const uint32_t xtarget = lds32(sGate + 64) * 4 + 4;
        atomicAdd(cnt, 1u);
        uint32_t v, spins = 0;
        do {
          asm volatile("ld.acquire.gpu.global.u32 %0, [%1];" : "=r"(v) : "l"(cnt) : "memory");
        } while ((int)(v - xtarget) < 0 && ++spins < (1u << 24));
      }
      __syncwarp();
      if (wg == 0) TS(2, 6);
      float r[36];
#pragma unroll
      for (int i = 0; i < 9; i++)
        asm volatile("ld.shared.v4.f32 {%0, %1, %2, %3}, [%4];" : "=f"(r[i * 4]), "=f"(r[i * 4 + 1]), "=f"(r[i * 4 + 2]), "=f"(r[i * 4 + 3])
                     : "r"(sown + (i >> 2) * K3_STAGE + (i & 3) * 2048) : "memory");
#pragma unroll
      for (int sI = 1; sI < 4; sI++) {
        const int src = (ks + sI) & 3;
        const uint4* rp = g_part + (size_t)(((tile * 4 + src) * 4) + ks) * 5 * 256;
#pragma unroll
        for (int i = 0; i < 4; i++) {
          const uint4 v = __ldcg(rp + i * 256 + tid);
          r[i * 8] += bf_lo(v.x); r[i * 8 + 1] += bf_hi(v.x); r[i * 8 + 2] += bf_lo(v.y); r[i * 8 + 3] += bf_hi(v.y);
          r[i * 8 + 4] += bf_lo(v.z); r[i * 8 + 5] += bf_hi(v.z); r[i * 8 + 6] += bf_lo(v.w); r[i * 8 + 7] += bf_hi(v.w);
        }
        const uint2 v = __ldcg(reinterpret_cast<const uint2*>(rp + 4 * 256) + tid);
        r[32] += bf_lo(v.x); r[33] += bf_hi(v.x); r[34] += bf_lo(v.y); r[35] += bf_hi(v.y);
      }
      const int row = mblk * 128 + wg * 64 + warp * 16 + (lane >> 2);
      bf16* o0 = out + (size_t)row * DM + nhalf * 256 + ks * 64 + 8 * q;
#pragma unroll
      for (int G = 0; G < 2; G++) {
        uint32_t a0 = pack_bf16(r[G * 16], r[G * 16 + 1]), a1 = pack_bf16(r[G * 16 + 4], r[G * 16 + 5]);
        uint32_t a2 = pack_bf16(r[G * 16 + 8], r[G * 16 + 9]), a3 = pack_bf16(r[G * 16 + 12], r[G * 16 + 13]);
        uint32_t b0 = pack_bf16(r[G * 16 + 2], r[G * 16 + 3]), b1 = pack_bf16(r[G * 16 + 6], r[G * 16 + 7]);
        uint32_t b2 = pack_bf16(r[G * 16 + 10], r[G * 16 + 11]), b3 = pack_bf16(r[G * 16 + 14], r[G * 16 + 15]);
        quad_transpose(a0, a1, a2, a3, q);
        quad_transpose(b0, b1, b2, b3, q);
        st_v4(o0 + G * 32, a0, a1, a2, a3);
        st_v4(o0 + 8 * DM + G * 32, b0, b1, b2, b3);
      }
      {
        uint32_t t0 = pack_bf16(r[32], r[33]), t1 = pack_bf16(r[34], r[35]), t2 = 0, t3 = 0;
        quad_transpose(t0, t1, t2, t3, q);
        if (q < 2) st_v4(out + (size_t)(row + q * 8) * DM + 512 + nhalf * 32 + ks * 8, t0, t1, t2, t3);
      }
    } else {
      cluster_arrive();
    }
    if (wg == 0) { TS(2, 1); TSC(2, 3); }
    cluster_wait();
  }
}

typedef CUresult (*EncFn)(CUtensorMap*, CUtensorMapDataType, cuuint32_t, void*, const cuuint64_t*, const cuuint64_t*, const cuuint32_t*,
                          const cuuint32_t*, CUtensorMapInterleave, CUtensorMapSwizzle, CUtensorMapL2promotion, CUtensorMapFloatOOBfill);

static void enc2d(EncFn enc, CUtensorMap* m, const void* ptr, uint64_t cols, uint64_t rows, uint32_t bc, uint32_t br,
                  CUtensorMapSwizzle sw = CU_TENSOR_MAP_SWIZZLE_128B) {
  cuuint64_t gd[2] = {cols, rows}, gs[1] = {cols * 2};
  cuuint32_t bx[2] = {bc, br}, es[2] = {1, 1};
  enc(m, CU_TENSOR_MAP_DATA_TYPE_BFLOAT16, 2, const_cast<void*>(ptr), gd, gs, bx, es, CU_TENSOR_MAP_INTERLEAVE_NONE, sw,
      CU_TENSOR_MAP_L2_PROMOTION_L2_256B, CU_TENSOR_MAP_FLOAT_OOB_FILL_NONE);
}
static void enc3d(EncFn enc, CUtensorMap* m, const void* ptr, uint64_t cols, uint64_t rows, uint32_t br, uint32_t bch) {
  cuuint64_t gd[3] = {64, rows, cols / 64}, gs[2] = {cols * 2, 128};
  cuuint32_t bx[3] = {64, br, bch}, es[3] = {1, 1, 1};
  enc(m, CU_TENSOR_MAP_DATA_TYPE_BFLOAT16, 3, const_cast<void*>(ptr), gd, gs, bx, es, CU_TENSOR_MAP_INTERLEAVE_NONE,
      CU_TENSOR_MAP_SWIZZLE_128B, CU_TENSOR_MAP_L2_PROMOTION_L2_256B, CU_TENSOR_MAP_FLOAT_OOB_FILL_NONE);
}

static void build_k1_jobs(Params& p) {
  int cnt[NCLUSTER];
  for (int c = 0; c < NCLUSTER; c++) {
    cnt[c] = 0;
    for (int i = 0; i < K1_MAXJOBS; i++) p.jobs[c][i] = 0;
  }
  auto add = [&](int c, int nch, int a_sel, int mp, int w_sel, int chunk0) {
    p.jobs[c][cnt[c]++] = (uint16_t)((nch - 1) | (a_sel << 2) | (mp << 3) | (w_sel << 6) | (chunk0 << 8));
  };
  for (int mp = 0; mp < 8; mp++) {
    for (int g = 0; g < 4; g++)
      for (int i = 0; i < 4; i++) add(g * 8 + mp, 4, 0, mp, g & 1, (2 * i + (g >> 1)) * 4);
    for (int t = 0; t < 16; t++) add((t % 3) * 8 + mp, 4, 0, mp, t & 1, (8 + (t >> 1)) * 4);
    add(32 + mp, 3, 1, mp, 2, 24);
    add(32 + mp, 4, 1, mp, 3, 0 * 4);
    for (int g = 5; g < 8; g++)
      for (int i = 0; i < 2; i++) add(g * 8 + mp, 4, 1, mp, 2, ((g - 5) * 2 + i) * 4);
    for (int i = 1; i < 8; i++) add((4 + (i - 1) % 4) * 8 + mp, 4, 1, mp, 3, i * 4);
    for (int i = 8; i < 14; i++) add(56 + mp, 4, 1, mp, 3, i * 4);
    add(64 + mp / 4, 4, 1, mp, 3, 14 * 4);
    add(64 + mp / 4, 4, 1, mp, 3, 15 * 4);
  }
  for (int cc = 0; cc < NCLUSTER; cc++)
    for (int i = 0; i < cnt[cc]; i++) {
      const int key = p.jobs[cc][i] & 0x3C;
      if (i == 0 || (p.jobs[cc][i - 1] & 0x3C) != key) p.jobs[cc][i] |= (1 << 14);
      if (i == cnt[cc] - 1 || (p.jobs[cc][i + 1] & 0x3C) != key) p.jobs[cc][i] |= (1 << 15);
    }
}

static void build_k2_items(Params& p) {
  bool used[256] = {};
  int ne = 0, nl = 0;
  for (int c = 0; c < NCLUSTER; c++) {
    const int g = c >> 3;
    if (g >= 3 && g <= 6) { p.order[c] = (uint8_t)((ne & 7) * 8 + 7 - (ne >> 3)); ne++; }
    else if (g == 1 || g == 2) p.order[c] = (uint8_t)((8 + (c - 8)) * 8 + 7);
    else { p.order[c] = (uint8_t)(nl < 8 ? (24 + nl) * 8 + 7 : (nl < 16 ? (16 + nl) : (nl - 8)) * 8 + 6); nl++; }
    used[p.order[c]] = true;
  }
  int n = NCLUSTER;
  for (int j = 3; j >= 0; j--)
    for (int h = 0; h < 8; h++) p.order[n++] = (uint8_t)(h * 8 + j);
  for (int j = 7; j >= 0; j--)
    for (int h = 8; h < 32; h++)
      if (!used[h * 8 + j]) p.order[n++] = (uint8_t)(h * 8 + j);
}

extern "C" void kernel_launch(void* const* d_in, const int* in_sizes, int n_in, void* d_out, int out_size) {
  const bf16* x = (const bf16*)d_in[0];
  const bf16* wqkv = (const bf16*)d_in[1];
  const bf16* wo = (const bf16*)d_in[2];
  const bf16* ckv = (const bf16*)d_in[4];
  const bf16* w_q = (const bf16*)d_in[5];
  const bf16* w_uk = (const bf16*)d_in[6];
  const bf16* w_uv = (const bf16*)d_in[7];
  const bf16* w_o = (const bf16*)d_in[8];
  const bf16* gate_w = (const bf16*)d_in[9];

  EncFn enc = nullptr;
  cudaDriverEntryPointQueryResult qr;
  cudaGetDriverEntryPoint("cuTensorMapEncodeTiled", (void**)&enc, cudaEnableDefault, &qr);
  void *pQ, *pK, *pV, *pCtx, *pQA;
  cudaGetSymbolAddress(&pQ, g_Q);
  cudaGetSymbolAddress(&pQA, g_QKVA);
  cudaGetSymbolAddress(&pK, g_K);
  cudaGetSymbolAddress(&pV, g_V);
  cudaGetSymbolAddress(&pCtx, g_ctx);

  static Params p;
  enc2d(enc, &p.tmA[0], ckv, DC, S_LEN, 64, 128);
  enc2d(enc, &p.tmA[1], x, DM, S_LEN, 64, 128);
  enc3d(enc, &p.tmW[0], w_uk, HDIM, DC, 16, 4);
  enc3d(enc, &p.tmW[1], w_uv, HDIM, DC, 16, 4);
  enc3d(enc, &p.tmW[2], wqkv, NQKVA, DM, 16, 4);
  enc3d(enc, &p.tmW[3], w_q, HDIM, DM, 16, 4);
  build_k1_jobs(p);
  enc2d(enc, &p.tmQ, pQ, HDIM, S_LEN, 64, 128);
  enc2d(enc, &p.tmK, pK, HDIM, S_LEN, 64, 128);
  enc2d(enc, &p.tmV, pV, HDIM, S_LEN, 64, 128);
  build_k2_items(p);
  for (int i = 0; i < 2; i++) {
    cuuint64_t gd[3] = {64, 27, S_LEN}, gs[2] = {128, NQKVA * 2};
    cuuint32_t bx[3] = {64, 9, i ? 16u : 30u}, es[3] = {1, 1, 1};
    enc(&p.tmL[i], CU_TENSOR_MAP_DATA_TYPE_BFLOAT16, 3, pQA, gd, gs, bx, es, CU_TENSOR_MAP_INTERLEAVE_NONE, CU_TENSOR_MAP_SWIZZLE_NONE,
        CU_TENSOR_MAP_L2_PROMOTION_L2_256B, CU_TENSOR_MAP_FLOAT_OOB_FILL_NONE);
  }
  enc2d(enc, &p.tmC, pCtx, KCAT, S_LEN, 64, 128);
  enc3d(enc, &p.tmO[0], w_o, DM, HDIM, 32, 4);
  enc3d(enc, &p.tmO[1], wo, DM, DM, 32, 4);
  enc2d(enc, &p.tmOt[0], w_o, DM, HDIM, 32, 32, CU_TENSOR_MAP_SWIZZLE_64B);
  enc2d(enc, &p.tmOt[1], wo, DM, DM, 32, 32, CU_TENSOR_MAP_SWIZZLE_64B);

  cudaFuncSetAttribute(fused_kernel, cudaFuncAttributeMaxDynamicSharedMemorySize, SMEM_BYTES);
  fused_kernel<<<NCLUSTER * 2, 384, SMEM_BYTES>>>(p, x, gate_w, (bf16*)d_out);
}
```

```cpp
#include <cuda_runtime.h>
#include <cuda_bf16.h>
#include <cuda.h>
#include <stdint.h>

typedef __nv_bfloat16 bf16;

constexpr int S_LEN = 2048, DM = 576, DC = 512, HDIM = 4096, NQKVA = 1728, KCAT = 4672;
constexpr int NCLUSTER = 66;

__device__ __align__(1024) bf16 g_Q[S_LEN * HDIM];
__device__ __align__(1024) bf16 g_K[S_LEN * HDIM];
__device__ __align__(1024) bf16 g_V[S_LEN * HDIM];
__device__ __align__(1024) bf16 g_QKVA[S_LEN * NQKVA + 64];
__device__ __align__(1024) bf16 g_ctx[S_LEN * KCAT];
__device__ float g_gate[S_LEN];
__device__ __align__(1024) uint4 g_part[32 * 4 * 4 * 5 * 256];
__device__ __align__(16) unsigned int g_sync[400];
constexpr int F_QKVA = 0, F_HP = 16, F_CTX = 32, F_OA = 48, F_GATE = 96, F_TICK = 97, F_DONE = 98, F_XCH = 128, F_EPOCH = 384;

__device__ __forceinline__ uint32_t smem_u32(const void* p) { return (uint32_t)__cvta_generic_to_shared(p); }
__device__ __forceinline__ void mbar_init(uint32_t a, uint32_t c) {
  asm volatile("mbarrier.init.shared::cta.b64 [%0], %1;" ::"r"(a), "r"(c));
}
__device__ __forceinline__ void mbar_expect(uint32_t a, uint32_t b) {
  asm volatile("mbarrier.arrive.expect_tx.shared::cta.b64 _, [%0], %1;" ::"r"(a), "r"(b) : "memory");
}
#define TS(k, i)
#define TSC(k, i)
#define TSM(k)
#define BSEG(i)
#define SPIN_LIMIT "4194304"
__device__ __forceinline__ void mbar_wait(uint32_t a, uint32_t parity) {
  asm volatile(
      "{\n.reg .pred p;\n.reg .u32 n;\n"
      "mbarrier.try_wait.parity.shared::cta.b64 p, [%0], %1;\n"
      "@p bra DONE;\n"
      "mov.u32 n, 0;\n"
      "LOOP:\n"
      "mbarrier.try_wait.parity.shared::cta.b64 p, [%0], %1;\n"
      "@p bra DONE;\n"
      "add.u32 n, n, 1;\n"
      "setp.lt.u32 p, n, " SPIN_LIMIT ";\n"
      "@p bra LOOP;\n"
      "DONE:\n}" ::"r"(a), "r"(parity) : "memory");
}
__device__ __forceinline__ void mbar_arrive(uint32_t a) {
  asm volatile("mbarrier.arrive.shared::cta.b64 _, [%0];" ::"r"(a) : "memory");
}
__device__ __forceinline__ void mbar_arrive_cluster(uint32_t a, uint32_t cta) {
  asm volatile("{\n.reg .b32 r;\nmapa.shared::cluster.u32 r, %0, %1;\nmbarrier.arrive.shared::cluster.b64 _, [r];\n}" ::"r"(a),
               "r"(cta) : "memory");
}
__device__ __forceinline__ void mbar_arrive_cluster_if(uint32_t a, uint32_t cta, bool pred) {
  asm volatile("{\n.reg .b32 r;\n.reg .pred p;\nsetp.ne.u32 p, %2, 0;\nmapa.shared::cluster.u32 r, %0, %1;\n@p mbarrier.arrive.shared::cluster.b64 _, [r];\n}" ::"r"(a),
               "r"(cta), "r"((uint32_t)pred) : "memory");
}
__device__ __forceinline__ void mbar_arrive_cluster_after(uint32_t a, uint32_t cta, bool pred, float anchor) {
  asm volatile("{\n.reg .b32 r;\n.reg .pred p;\nsetp.ne.u32 p, %2, 0;\nsetp.leu.and.f32 p, %3, 0f7F800000, p;\n"
               "mapa.shared::cluster.u32 r, %0, %1;\n@p mbarrier.arrive.shared::cluster.b64 _, [r];\n}" ::"r"(a),
               "r"(cta), "r"((uint32_t)pred), "f"(anchor) : "memory");
}
__device__ __forceinline__ void mbar_arrive_if(uint32_t a, bool pred) {
  asm volatile("{\n.reg .pred p;\nsetp.ne.u32 p, %1, 0;\n@p mbarrier.arrive.shared::cta.b64 _, [%0];\n}" ::"r"(a), "r"((uint32_t)pred) : "memory");
}
__device__ __forceinline__ void tma2d(uint32_t dst, const CUtensorMap* m, uint32_t bar, int c0, int c1) {
  asm volatile("cp.async.bulk.tensor.2d.shared::cluster.global.mbarrier::complete_tx::bytes [%0], [%1, {%3, %4}], [%2];" ::"r"(dst),
               "l"(m), "r"(bar), "r"(c0), "r"(c1) : "memory");
}
__device__ __forceinline__ void tma2d_mc(uint32_t dst, const CUtensorMap* m, uint32_t bar, int c0, int c1, uint16_t mask) {
  asm volatile(
      "cp.async.bulk.tensor.2d.shared::cluster.global.mbarrier::complete_tx::bytes.multicast::cluster [%0], [%1, {%3, %4}], [%2], %5;" ::"r"(dst),
      "l"(m), "r"(bar), "r"(c0), "r"(c1), "h"(mask) : "memory");
}
__device__ __forceinline__ void tma3d_mc(uint32_t dst, const CUtensorMap* m, uint32_t bar, int c0, int c1, int c2, uint16_t mask) {
  asm volatile(
      "cp.async.bulk.tensor.3d.shared::cluster.global.mbarrier::complete_tx::bytes.multicast::cluster [%0], [%1, {%3, %4, %5}], [%2], %6;" ::"r"(dst),
      "l"(m), "r"(bar), "r"(c0), "r"(c1), "r"(c2), "h"(mask) : "memory");
}
__device__ __forceinline__ uint64_t policy_evict_first() {
  uint64_t p;
  asm volatile("createpolicy.fractional.L2::evict_first.b64 %0, 1.0;" : "=l"(p));
  return p;
}
__device__ __forceinline__ void tma3d_mc_h(uint32_t dst, const CUtensorMap* m, uint32_t bar, int c0, int c1, int c2, uint16_t mask, uint64_t pol) {
  asm volatile(
      "cp.async.bulk.tensor.3d.shared::cluster.global.mbarrier::complete_tx::bytes.multicast::cluster.L2::cache_hint [%0], [%1, {%3, %4, %5}], [%2], %6, %7;" ::"r"(dst),
      "l"(m), "r"(bar), "r"(c0), "r"(c1), "r"(c2), "h"(mask), "l"(pol) : "memory");
}
__device__ __forceinline__ void tma2d_h(uint32_t dst, const CUtensorMap* m, uint32_t bar, int c0, int c1, uint64_t pol) {
  asm volatile("cp.async.bulk.tensor.2d.shared::cluster.global.mbarrier::complete_tx::bytes.L2::cache_hint [%0], [%1, {%3, %4}], [%2], %5;" ::"r"(dst),
               "l"(m), "r"(bar), "r"(c0), "r"(c1), "l"(pol) : "memory");
}
__device__ __forceinline__ void tma3d(uint32_t dst, const CUtensorMap* m, uint32_t bar, int c0, int c1, int c2) {
  asm volatile(
      "cp.async.bulk.tensor.3d.shared::cluster.global.mbarrier::complete_tx::bytes [%0], [%1, {%3, %4, %5}], [%2];" ::"r"(dst),
      "l"(m), "r"(bar), "r"(c0), "r"(c1), "r"(c2) : "memory");
}
__device__ __forceinline__ void tma_pf2d(const CUtensorMap* m, int c0, int c1) {
  asm volatile("cp.async.bulk.prefetch.tensor.2d.L2.global [%0, {%1, %2}];" ::"l"(m), "r"(c0), "r"(c1) : "memory");
}
__device__ __forceinline__ void tma_pf3d(const CUtensorMap* m, int c0, int c1, int c2) {
  asm volatile("cp.async.bulk.prefetch.tensor.3d.L2.global [%0, {%1, %2, %3}];" ::"l"(m), "r"(c0), "r"(c1), "r"(c2) : "memory");
}
__device__ __forceinline__ void prefetch_tmap(const CUtensorMap* m) {
  asm volatile("prefetch.tensormap [%0];" ::"l"(m) : "memory");
}
__device__ __forceinline__ void cluster_arrive() { asm volatile("barrier.cluster.arrive.relaxed.aligned;" ::: "memory"); }
__device__ __forceinline__ void cluster_wait() { asm volatile("barrier.cluster.wait.aligned;" ::: "memory"); }
__device__ __forceinline__ void cluster_sync() {
  cluster_arrive();
  cluster_wait();
}
__device__ __forceinline__ uint32_t cluster_rank() {
  uint32_t r;
  asm volatile("mov.u32 %0, %%cluster_ctarank;" : "=r"(r));
  return r;
}
__device__ __forceinline__ bool elect_one() {
  uint32_t p;
  asm volatile("{\n.reg .pred q;\nelect.sync _|q, 0xffffffff;\nselp.u32 %0, 1, 0, q;\n}" : "=r"(p));
  return p;
}
__device__ __forceinline__ void pdl_wait() { asm volatile("griddepcontrol.wait;" ::: "memory"); }
__device__ __forceinline__ void pdl_launch() { asm volatile("griddepcontrol.launch_dependents;" ::: "memory"); }
__device__ __forceinline__ void ldsm_x4(uint32_t& r0, uint32_t& r1, uint32_t& r2, uint32_t& r3, uint32_t addr) {
  asm volatile("ldmatrix.sync.aligned.m8n8.x4.shared.b16 {%0, %1, %2, %3}, [%4];" : "=r"(r0), "=r"(r1), "=r"(r2), "=r"(r3) : "r"(addr) : "memory");
}
__device__ __forceinline__ void wg_fence() { asm volatile("wgmma.fence.sync.aligned;" ::: "memory"); }
__device__ __forceinline__ void wg_commit() { asm volatile("wgmma.commit_group.sync.aligned;" ::: "memory"); }
template <int N>
__device__ __forceinline__ void wg_wait() { asm volatile("wgmma.wait_group.sync.aligned %0;" ::"n"(N) : "memory"); }
template <int N>
__device__ __forceinline__ void reg_alloc() { asm volatile("setmaxnreg.inc.sync.aligned.u32 %0;" ::"n"(N)); }
template <int N>
__device__ __forceinline__ void reg_dealloc() { asm volatile("setmaxnreg.dec.sync.aligned.u32 %0;" ::"n"(N)); }
__device__ __forceinline__ void bar_sync(int id, int n) { asm volatile("bar.sync %0, %1;" ::"r"(id), "r"(n) : "memory"); }
__device__ __forceinline__ void bar_arrive(int id, int n) { asm volatile("bar.arrive %0, %1;" ::"r"(id), "r"(n) : "memory"); }
template <int NT>
__device__ __forceinline__ void fence_regs(float (&d)[NT]) {
#pragma unroll
  for (int i = 0; i < NT; i++) asm volatile("" : "+f"(d[i])::"memory");
}
template <int NT>
__device__ __forceinline__ void fence_regs(uint32_t (&d)[NT]) {
#pragma unroll
  for (int i = 0; i < NT; i++) asm volatile("" : "+r"(d[i])::"memory");
}
__device__ __forceinline__ uint64_t make_desc(uint32_t saddr, uint32_t lbo, uint32_t sbo, uint32_t layout) {
  return (uint64_t)((saddr & 0x3FFFF) >> 4) | ((uint64_t)(lbo >> 4) << 16) | ((uint64_t)(sbo >> 4) << 32) | ((uint64_t)layout << 62);
}
__device__ __forceinline__ uint32_t pack_bf16(float lo, float hi) {
  uint32_t r;
  asm("cvt.rn.bf16x2.f32 %0, %1, %2;" : "=r"(r) : "f"(hi), "f"(lo));
  return r;
}
__device__ __forceinline__ float ex2(float x) {
  float r;
  asm("ex2.approx.ftz.f32 %0, %1;" : "=f"(r) : "f"(x));
  return r;
}
__device__ __forceinline__ void st_v4(void* p, uint32_t a, uint32_t b, uint32_t c, uint32_t d) {
#define ST_MOD ".cs"
  asm volatile("st.global" ST_MOD ".v4.b32 [%0], {%1, %2, %3, %4};" ::"l"(p), "r"(a), "r"(b), "r"(c), "r"(d) : "memory");
}
#define STA_MOD ".cs"
__device__ __forceinline__ void st_v4a(void* p, uint32_t a, uint32_t b, uint32_t c, uint32_t d) {
  asm volatile("st.global" STA_MOD ".v4.b32 [%0], {%1, %2, %3, %4};" ::"l"(p), "r"(a), "r"(b), "r"(c), "r"(d) : "memory");
}
__device__ __forceinline__ float bf_lo(uint32_t v) { return __uint_as_float(v << 16); }
__device__ __forceinline__ float bf_hi(uint32_t v) { return __uint_as_float(v & 0xFFFF0000u); }

__device__ __forceinline__ void quad_transpose(uint32_t& a0, uint32_t& a1, uint32_t& a2, uint32_t& a3, int q) {
  const bool o1 = q & 1, o2 = q & 2;
  uint32_t t0 = o1 ? a0 : a1, t1 = o1 ? a2 : a3;
  t0 = __shfl_xor_sync(0xffffffffu, t0, 1);
  t1 = __shfl_xor_sync(0xffffffffu, t1, 1);
  if (o1) { a0 = t0; a2 = t1; } else { a1 = t0; a3 = t1; }
  t0 = o2 ? a0 : a2;
  t1 = o2 ? a1 : a3;
  t0 = __shfl_xor_sync(0xffffffffu, t0, 2);
  t1 = __shfl_xor_sync(0xffffffffu, t1, 2);
  if (o2) { a0 = t0; a1 = t1; } else { a2 = t0; a3 = t1; }
}

template<int TB, int OFF, int NT>
__device__ __forceinline__ void wgmma_ss_n256(float (&d)[NT], uint64_t da, uint64_t db, int scale_d) {
  asm volatile("{\n.reg .pred p;\nsetp.ne.b32 p, %130, 0;\n"
    "wgmma.mma_async.sync.aligned.m64n256k16.f32.bf16.bf16 {%0, %1, %2, %3, %4, %5, %6, %7, %8, %9, %10, %11, %12, %13, %14, %15, %16, %17, %18, %19, %20, %21, %22, %23, %24, %25, %26, %27, %28, %29, %30, %31, %32, %33, %34, %35, %36, %37, %38, %39, %40, %41, %42, %43, %44, %45, %46, %47, %48, %49, %50, %51, %52, %53, %54, %55, %56, %57, %58, %59, %60, %61, %62, %63, %64, %65, %66, %67, %68, %69, %70, %71, %72, %73, %74, %75, %76, %77, %78, %79, %80, %81, %82, %83, %84, %85, %86, %87, %88, %89, %90, %91, %92, %93, %94, %95, %96, %97, %98, %99, %100, %101, %102, %103, %104, %105, %106, %107, %108, %109, %110, %111, %112, %113, %114, %115, %116, %117, %118, %119, %120, %121, %122, %123, %124, %125, %126, %127}, %128, %129, p, 1, 1, 0, %131;\n}\n"
    : "+f"(d[OFF+0]), "+f"(d[OFF+1]), "+f"(d[OFF+2]), "+f"(d[OFF+3]), "+f"(d[OFF+4]), "+f"(d[OFF+5]), "+f"(d[OFF+6]), "+f"(d[OFF+7]), "+f"(d[OFF+8]), "+f"(d[OFF+9]), "+f"(d[OFF+10]), "+f"(d[OFF+11]), "+f"(d[OFF+12]), "+f"(d[OFF+13]), "+f"(d[OFF+14]), "+f"(d[OFF+15]), "+f"(d[OFF+16]), "+f"(d[OFF+17]), "+f"(d[OFF+18]), "+f"(d[OFF+19]), "+f"(d[OFF+20]), "+f"(d[OFF+21]), "+f"(d[OFF+22]), "+f"(d[OFF+23]), "+f"(d[OFF+24]), "+f"(d[OFF+25]), "+f"(d[OFF+26]), "+f"(d[OFF+27]), "+f"(d[OFF+28]), "+f"(d[OFF+29]), "+f"(d[OFF+30]), "+f"(d[OFF+31]), "+f"(d[OFF+32]), "+f"(d[OFF+33]), "+f"(d[OFF+34]), "+f"(d[OFF+35]), "+f"(d[OFF+36]), "+f"(d[OFF+37]), "+f"(d[OFF+38]), "+f"(d[OFF+39]), "+f"(d[OFF+40]), "+f"(d[OFF+41]), "+f"(d[OFF+42]), "+f"(d[OFF+43]), "+f"(d[OFF+44]), "+f"(d[OFF+45]), "+f"(d[OFF+46]), "+f"(d[OFF+47]), "+f"(d[OFF+48]), "+f"(d[OFF+49]), "+f"(d[OFF+50]), "+f"(d[OFF+51]), "+f"(d[OFF+52]), "+f"(d[OFF+53]), "+f"(d[OFF+54]), "+f"(d[OFF+55]), "+f"(d[OFF+56]), "+f"(d[OFF+57]), "+f"(d[OFF+58]), "+f"(d[OFF+59]), "+f"(d[OFF+60]), "+f"(d[OFF+61]), "+f"(d[OFF+62]), "+f"(d[OFF+63]), "+f"(d[OFF+64]), "+f"(d[OFF+65]), "+f"(d[OFF+66]), "+f"(d[OFF+67]), "+f"(d[OFF+68]), "+f"(d[OFF+69]), "+f"(d[OFF+70]), "+f"(d[OFF+71]), "+f"(d[OFF+72]), "+f"(d[OFF+73]), "+f"(d[OFF+74]), "+f"(d[OFF+75]), "+f"(d[OFF+76]), "+f"(d[OFF+77]), "+f"(d[OFF+78]), "+f"(d[OFF+79]), "+f"(d[OFF+80]), "+f"(d[OFF+81]), "+f"(d[OFF+82]), "+f"(d[OFF+83]), "+f"(d[OFF+84]), "+f"(d[OFF+85]), "+f"(d[OFF+86]), "+f"(d[OFF+87]), "+f"(d[OFF+88]), "+f"(d[OFF+89]), "+f"(d[OFF+90]), "+f"(d[OFF+91]), "+f"(d[OFF+92]), "+f"(d[OFF+93]), "+f"(d[OFF+94]), "+f"(d[OFF+95]), "+f"(d[OFF+96]), "+f"(d[OFF+97]), "+f"(d[OFF+98]), "+f"(d[OFF+99]), "+f"(d[OFF+100]), "+f"(d[OFF+101]), "+f"(d[OFF+102]), "+f"(d[OFF+103]), "+f"(d[OFF+104]), "+f"(d[OFF+105]), "+f"(d[OFF+106]), "+f"(d[OFF+107]), "+f"(d[OFF+108]), "+f"(d[OFF+109]), "+f"(d[OFF+110]), "+f"(d[OFF+111]), "+f"(d[OFF+112]), "+f"(d[OFF+113]), "+f"(d[OFF+114]), "+f"(d[OFF+115]), "+f"(d[OFF+116]), "+f"(d[OFF+117]), "+f"(d[OFF+118]), "+f"(d[OFF+119]), "+f"(d[OFF+120]), "+f"(d[OFF+121]), "+f"(d[OFF+122]), "+f"(d[OFF+123]), "+f"(d[OFF+124]), "+f"(d[OFF+125]), "+f"(d[OFF+126]), "+f"(d[OFF+127])
    : "l"(da), "l"(db), "r"(scale_d), "n"(TB));
}
template<int TB, int OFF, int NT>
__device__ __forceinline__ void wgmma_ss_n192(float (&d)[NT], uint64_t da, uint64_t db, int scale_d) {
  asm volatile("{\n.reg .pred p;\nsetp.ne.b32 p, %98, 0;\n"
    "wgmma.mma_async.sync.aligned.m64n192k16.f32.bf16.bf16 {%0, %1, %2, %3, %4, %5, %6, %7, %8, %9, %10, %11, %12, %13, %14, %15, %16, %17, %18, %19, %20, %21, %22, %23, %24, %25, %26, %27, %28, %29, %30, %31, %32, %33, %34, %35, %36, %37, %38, %39, %40, %41, %42, %43, %44, %45, %46, %47, %48, %49, %50, %51, %52, %53, %54, %55, %56, %57, %58, %59, %60, %61, %62, %63, %64, %65, %66, %67, %68, %69, %70, %71, %72, %73, %74, %75, %76, %77, %78, %79, %80, %81, %82, %83, %84, %85, %86, %87, %88, %89, %90, %91, %92, %93, %94, %95}, %96, %97, p, 1, 1, 0, %99;\n}\n"
    : "+f"(d[OFF+0]), "+f"(d[OFF+1]), "+f"(d[OFF+2]), "+f"(d[OFF+3]), "+f"(d[OFF+4]), "+f"(d[OFF+5]), "+f"(d[OFF+6]), "+f"(d[OFF+7]), "+f"(d[OFF+8]), "+f"(d[OFF+9]), "+f"(d[OFF+10]), "+f"(d[OFF+11]), "+f"(d[OFF+12]), "+f"(d[OFF+13]), "+f"(d[OFF+14]), "+f"(d[OFF+15]), "+f"(d[OFF+16]), "+f"(d[OFF+17]), "+f"(d[OFF+18]), "+f"(d[OFF+19]), "+f"(d[OFF+20]), "+f"(d[OFF+21]), "+f"(d[OFF+22]), "+f"(d[OFF+23]), "+f"(d[OFF+24]), "+f"(d[OFF+25]), "+f"(d[OFF+26]), "+f"(d[OFF+27]), "+f"(d[OFF+28]), "+f"(d[OFF+29]), "+f"(d[OFF+30]), "+f"(d[OFF+31]), "+f"(d[OFF+32]), "+f"(d[OFF+33]), "+f"(d[OFF+34]), "+f"(d[OFF+35]), "+f"(d[OFF+36]), "+f"(d[OFF+37]), "+f"(d[OFF+38]), "+f"(d[OFF+39]), "+f"(d[OFF+40]), "+f"(d[OFF+41]), "+f"(d[OFF+42]), "+f"(d[OFF+43]), "+f"(d[OFF+44]), "+f"(d[OFF+45]), "+f"(d[OFF+46]), "+f"(d[OFF+47]), "+f"(d[OFF+48]), "+f"(d[OFF+49]), "+f"(d[OFF+50]), "+f"(d[OFF+51]), "+f"(d[OFF+52]), "+f"(d[OFF+53]), "+f"(d[OFF+54]), "+f"(d[OFF+55]), "+f"(d[OFF+56]), "+f"(d[OFF+57]), "+f"(d[OFF+58]), "+f"(d[OFF+59]), "+f"(d[OFF+60]), "+f"(d[OFF+61]), "+f"(d[OFF+62]), "+f"(d[OFF+63]), "+f"(d[OFF+64]), "+f"(d[OFF+65]), "+f"(d[OFF+66]), "+f"(d[OFF+67]), "+f"(d[OFF+68]), "+f"(d[OFF+69]), "+f"(d[OFF+70]), "+f"(d[OFF+71]), "+f"(d[OFF+72]), "+f"(d[OFF+73]), "+f"(d[OFF+74]), "+f"(d[OFF+75]), "+f"(d[OFF+76]), "+f"(d[OFF+77]), "+f"(d[OFF+78]), "+f"(d[OFF+79]), "+f"(d[OFF+80]), "+f"(d[OFF+81]), "+f"(d[OFF+82]), "+f"(d[OFF+83]), "+f"(d[OFF+84]), "+f"(d[OFF+85]), "+f"(d[OFF+86]), "+f"(d[OFF+87]), "+f"(d[OFF+88]), "+f"(d[OFF+89]), "+f"(d[OFF+90]), "+f"(d[OFF+91]), "+f"(d[OFF+92]), "+f"(d[OFF+93]), "+f"(d[OFF+94]), "+f"(d[OFF+95])
    : "l"(da), "l"(db), "r"(scale_d), "n"(TB));
}
template<int TB, int OFF, int NT>
__device__ __forceinline__ void wgmma_ss_n128(float (&d)[NT], uint64_t da, uint64_t db, int scale_d) {
  asm volatile("{\n.reg .pred p;\nsetp.ne.b32 p, %66, 0;\n"
    "wgmma.mma_async.sync.aligned.m64n128k16.f32.bf16.bf16 {%0, %1, %2, %3, %4, %5, %6, %7, %8, %9, %10, %11, %12, %13, %14, %15, %16, %17, %18, %19, %20, %21, %22, %23, %24, %25, %26, %27, %28, %29, %30, %31, %32, %33, %34, %35, %36, %37, %38, %39, %40, %41, %42, %43, %44, %45, %46, %47, %48, %49, %50, %51, %52, %53, %54, %55, %56, %57, %58, %59, %60, %61, %62, %63}, %64, %65, p, 1, 1, 0, %67;\n}\n"
    : "+f"(d[OFF+0]), "+f"(d[OFF+1]), "+f"(d[OFF+2]), "+f"(d[OFF+3]), "+f"(d[OFF+4]), "+f"(d[OFF+5]), "+f"(d[OFF+6]), "+f"(d[OFF+7]), "+f"(d[OFF+8]), "+f"(d[OFF+9]), "+f"(d[OFF+10]), "+f"(d[OFF+11]), "+f"(d[OFF+12]), "+f"(d[OFF+13]), "+f"(d[OFF+14]), "+f"(d[OFF+15]), "+f"(d[OFF+16]), "+f"(d[OFF+17]), "+f"(d[OFF+18]), "+f"(d[OFF+19]), "+f"(d[OFF+20]), "+f"(d[OFF+21]), "+f"(d[OFF+22]), "+f"(d[OFF+23]), "+f"(d[OFF+24]), "+f"(d[OFF+25]), "+f"(d[OFF+26]), "+f"(d[OFF+27]), "+f"(d[OFF+28]), "+f"(d[OFF+29]), "+f"(d[OFF+30]), "+f"(d[OFF+31]), "+f"(d[OFF+32]), "+f"(d[OFF+33]), "+f"(d[OFF+34]), "+f"(d[OFF+35]), "+f"(d[OFF+36]), "+f"(d[OFF+37]), "+f"(d[OFF+38]), "+f"(d[OFF+39]), "+f"(d[OFF+40]), "+f"(d[OFF+41]), "+f"(d[OFF+42]), "+f"(d[OFF+43]), "+f"(d[OFF+44]), "+f"(d[OFF+45]), "+f"(d[OFF+46]), "+f"(d[OFF+47]), "+f"(d[OFF+48]), "+f"(d[OFF+49]), "+f"(d[OFF+50]), "+f"(d[OFF+51]), "+f"(d[OFF+52]), "+f"(d[OFF+53]), "+f"(d[OFF+54]), "+f"(d[OFF+55]), "+f"(d[OFF+56]), "+f"(d[OFF+57]), "+f"(d[OFF+58]), "+f"(d[OFF+59]), "+f"(d[OFF+60]), "+f"(d[OFF+61]), "+f"(d[OFF+62]), "+f"(d[OFF+63])
    : "l"(da), "l"(db), "r"(scale_d), "n"(TB));
}
template<int TB, int OFF, int NT>
__device__ __forceinline__ void wgmma_ss_n32(float (&d)[NT], uint64_t da, uint64_t db, int scale_d) {
  asm volatile("{\n.reg .pred p;\nsetp.ne.b32 p, %18, 0;\n"
    "wgmma.mma_async.sync.aligned.m64n32k16.f32.bf16.bf16 {%0, %1, %2, %3, %4, %5, %6, %7, %8, %9, %10, %11, %12, %13, %14, %15}, %16, %17, p, 1, 1, 0, %19;\n}\n"
    : "+f"(d[OFF+0]), "+f"(d[OFF+1]), "+f"(d[OFF+2]), "+f"(d[OFF+3]), "+f"(d[OFF+4]), "+f"(d[OFF+5]), "+f"(d[OFF+6]), "+f"(d[OFF+7]), "+f"(d[OFF+8]), "+f"(d[OFF+9]), "+f"(d[OFF+10]), "+f"(d[OFF+11]), "+f"(d[OFF+12]), "+f"(d[OFF+13]), "+f"(d[OFF+14]), "+f"(d[OFF+15])
    : "l"(da), "l"(db), "r"(scale_d), "n"(TB));
}
template<int TB, int OFF, int NT>
__device__ __forceinline__ void wgmma_rs_n128(float (&d)[NT], uint32_t a0, uint32_t a1, uint32_t a2, uint32_t a3, uint64_t db, int scale_d) {
  asm volatile("{\n.reg .pred p;\nsetp.ne.b32 p, %69, 0;\n"
    "wgmma.mma_async.sync.aligned.m64n128k16.f32.bf16.bf16 {%0, %1, %2, %3, %4, %5, %6, %7, %8, %9, %10, %11, %12, %13, %14, %15, %16, %17, %18, %19, %20, %21, %22, %23, %24, %25, %26, %27, %28, %29, %30, %31, %32, %33, %34, %35, %36, %37, %38, %39, %40, %41, %42, %43, %44, %45, %46, %47, %48, %49, %50, %51, %52, %53, %54, %55, %56, %57, %58, %59, %60, %61, %62, %63}, {%64, %65, %66, %67}, %68, p, 1, 1, %70;\n}\n"
    : "+f"(d[OFF+0]), "+f"(d[OFF+1]), "+f"(d[OFF+2]), "+f"(d[OFF+3]), "+f"(d[OFF+4]), "+f"(d[OFF+5]), "+f"(d[OFF+6]), "+f"(d[OFF+7]), "+f"(d[OFF+8]), "+f"(d[OFF+9]), "+f"(d[OFF+10]), "+f"(d[OFF+11]), "+f"(d[OFF+12]), "+f"(d[OFF+13]), "+f"(d[OFF+14]), "+f"(d[OFF+15]), "+f"(d[OFF+16]), "+f"(d[OFF+17]), "+f"(d[OFF+18]), "+f"(d[OFF+19]), "+f"(d[OFF+20]), "+f"(d[OFF+21]), "+f"(d[OFF+22]), "+f"(d[OFF+23]), "+f"(d[OFF+24]), "+f"(d[OFF+25]), "+f"(d[OFF+26]), "+f"(d[OFF+27]), "+f"(d[OFF+28]), "+f"(d[OFF+29]), "+f"(d[OFF+30]), "+f"(d[OFF+31]), "+f"(d[OFF+32]), "+f"(d[OFF+33]), "+f"(d[OFF+34]), "+f"(d[OFF+35]), "+f"(d[OFF+36]), "+f"(d[OFF+37]), "+f"(d[OFF+38]), "+f"(d[OFF+39]), "+f"(d[OFF+40]), "+f"(d[OFF+41]), "+f"(d[OFF+42]), "+f"(d[OFF+43]), "+f"(d[OFF+44]), "+f"(d[OFF+45]), "+f"(d[OFF+46]), "+f"(d[OFF+47]), "+f"(d[OFF+48]), "+f"(d[OFF+49]), "+f"(d[OFF+50]), "+f"(d[OFF+51]), "+f"(d[OFF+52]), "+f"(d[OFF+53]), "+f"(d[OFF+54]), "+f"(d[OFF+55]), "+f"(d[OFF+56]), "+f"(d[OFF+57]), "+f"(d[OFF+58]), "+f"(d[OFF+59]), "+f"(d[OFF+60]), "+f"(d[OFF+61]), "+f"(d[OFF+62]), "+f"(d[OFF+63])
    : "r"(a0), "r"(a1), "r"(a2), "r"(a3), "l"(db), "r"(scale_d), "n"(TB));
}
template<int TB, int OFF, int NT>
__device__ __forceinline__ void wgmma_rs_n64(float (&d)[NT], uint32_t a0, uint32_t a1, uint32_t a2, uint32_t a3, uint64_t db, int scale_d) {
  asm volatile("{\n.reg .pred p;\nsetp.ne.b32 p, %37, 0;\n"
    "wgmma.mma_async.sync.aligned.m64n64k16.f32.bf16.bf16 {%0, %1, %2, %3, %4, %5, %6, %7, %8, %9, %10, %11, %12, %13, %14, %15, %16, %17, %18, %19, %20, %21, %22, %23, %24, %25, %26, %27, %28, %29, %30, %31}, {%32, %33, %34, %35}, %36, p, 1, 1, %38;\n}\n"
    : "+f"(d[OFF+0]), "+f"(d[OFF+1]), "+f"(d[OFF+2]), "+f"(d[OFF+3]), "+f"(d[OFF+4]), "+f"(d[OFF+5]), "+f"(d[OFF+6]), "+f"(d[OFF+7]), "+f"(d[OFF+8]), "+f"(d[OFF+9]), "+f"(d[OFF+10]), "+f"(d[OFF+11]), "+f"(d[OFF+12]), "+f"(d[OFF+13]), "+f"(d[OFF+14]), "+f"(d[OFF+15]), "+f"(d[OFF+16]), "+f"(d[OFF+17]), "+f"(d[OFF+18]), "+f"(d[OFF+19]), "+f"(d[OFF+20]), "+f"(d[OFF+21]), "+f"(d[OFF+22]), "+f"(d[OFF+23]), "+f"(d[OFF+24]), "+f"(d[OFF+25]), "+f"(d[OFF+26]), "+f"(d[OFF+27]), "+f"(d[OFF+28]), "+f"(d[OFF+29]), "+f"(d[OFF+30]), "+f"(d[OFF+31])
    : "r"(a0), "r"(a1), "r"(a2), "r"(a3), "l"(db), "r"(scale_d), "n"(TB));
}

__device__ __forceinline__ void wait_flag(const unsigned int* f, uint32_t target) {
  uint32_t v;
#pragma unroll 1
  for (uint32_t spins = 0; spins < (1u << 22); spins++) {
    asm volatile("ld.acquire.gpu.global.u32 %0, [%1];" : "=r"(v) : "l"(f) : "memory");
    if (v >= target) break;
    __nanosleep(100);
  }
}
__device__ __forceinline__ uint32_t lds32(uint32_t a) {
  uint32_t v;
  asm volatile("ld.shared.u32 %0, [%1];" : "=r"(v) : "r"(a) : "memory");
  return v;
}
__device__ __forceinline__ float gate_row(int row, int lane, const bf16* __restrict__ x, const bf16* __restrict__ gate_w) {
  const uint32_t* xr = reinterpret_cast<const uint32_t*>(x + (size_t)row * DM);
  const uint32_t* gw2 = reinterpret_cast<const uint32_t*>(gate_w);
  float gs = 0.f;
#pragma unroll
  for (int i = 0; i < 9; i++) {
    const uint32_t a = __ldg(xr + lane + 32 * i), b = __ldg(gw2 + lane + 32 * i);
    gs = fmaf(bf_lo(a), bf_lo(b), gs);
    gs = fmaf(bf_hi(a), bf_hi(b), gs);
  }
#pragma unroll
  for (int o = 16; o; o >>= 1) gs += __shfl_xor_sync(0xffffffffu, gs, o);
  const float g = 1.f / (1.f + __expf(-gs));
  if (lane == 0) g_gate[row] = g;
  return g;
}
#define LA_UNROLL 9
__device__ __forceinline__ void local_rows2(int rb, int ri, uint32_t sL, uint32_t bL2, int lane, float ga, float gb) {
  const float scale_l2 = 0.23570226039551584f * 1.4426950408889634f;
  constexpr int U = LA_UNROLL;
  const uint32_t sq = sL + (30 + ri) * 1152;
  const uint32_t kb = sL + (14 + ri) * 1152 + lane * 36;
  float ma = -INFINITY, mb = -INFINITY;
  {
    float qa[18], qb[18];
#pragma unroll
    for (int i = 0; i < 9; i++) {
      const uint32_t u = lds32(sq - 2304 + lane * 36 + 4 * i), v = lds32(sq + lane * 36 + 4 * i);
      qa[2 * i] = bf_lo(u); qa[2 * i + 1] = bf_hi(u);
      qb[2 * i] = bf_lo(v); qb[2 * i + 1] = bf_hi(v);
    }
    __syncwarp();
#pragma unroll U
    for (int t = 0; t < 9; t++) {
      const bool ok = rb - 2 * t >= 0;
      float a0 = 0.f, a1 = 0.f, b0 = 0.f, b1 = 0.f;
#pragma unroll
      for (int i = 0; i < 9; i++) {
        const uint32_t k = lds32(kb - t * 2304 + 4 * i);
        const float lo = bf_lo(k), hi = bf_hi(k);
        a0 = fmaf(qa[2 * i], lo, a0); a1 = fmaf(qa[2 * i + 1], hi, a1);
        b0 = fmaf(qb[2 * i], lo, b0); b1 = fmaf(qb[2 * i + 1], hi, b1);
      }
      a0 = (ok && t > 0) ? a0 + a1 : -INFINITY;
      b0 = (ok && t < 8) ? b0 + b1 : -INFINITY;
      ma = fmaxf(ma, a0);
      mb = fmaxf(mb, b0);
      asm volatile("st.shared.f32 [%0], %1;" ::"r"(sq - 2304 + t * 128 + lane * 4), "f"(a0) : "memory");
      asm volatile("st.shared.f32 [%0], %1;" ::"r"(sq + t * 128 + lane * 4), "f"(b0) : "memory");
    }
  }
  float oa[18], ob[18], sa = 0.f, sb = 0.f;
#pragma unroll
  for (int i = 0; i < 18; i++) { oa[i] = 0.f; ob[i] = 0.f; }
  mbar_wait(bL2, 0);
#pragma unroll U
  for (int t = 0; t < 9; t++) {
    const float wa = ex2((__uint_as_float(lds32(sq - 2304 + t * 128 + lane * 4)) - ma) * scale_l2);
    const float wb = ex2((__uint_as_float(lds32(sq + t * 128 + lane * 4)) - mb) * scale_l2);
    sa += wa;
    sb += wb;
#pragma unroll
    for (int i = 0; i < 9; i++) {
      const uint32_t v = lds32(kb + 46 * 1152 - t * 2304 + 4 * i);
      const float lo = bf_lo(v), hi = bf_hi(v);
      oa[2 * i] = fmaf(wa, lo, oa[2 * i]); oa[2 * i + 1] = fmaf(wa, hi, oa[2 * i + 1]);
      ob[2 * i] = fmaf(wb, lo, ob[2 * i]); ob[2 * i + 1] = fmaf(wb, hi, ob[2 * i + 1]);
    }
  }
  ga = __fdividef(ga, sa);
  gb = __fdividef(gb, sb);
  __syncwarp();
#pragma unroll
  for (int i = 0; i < 9; i++) {
    asm volatile("st.shared.u32 [%0], %1;" ::"r"(sq - 2304 + lane * 36 + 4 * i), "r"(pack_bf16(oa[2 * i] * ga, oa[2 * i + 1] * ga)) : "memory");
    asm volatile("st.shared.u32 [%0], %1;" ::"r"(sq + lane * 36 + 4 * i), "r"(pack_bf16(ob[2 * i] * gb, ob[2 * i + 1] * gb)) : "memory");
  }
  __syncwarp();
  uint32_t w[5][4];
#pragma unroll
  for (int t = 0; t < 5; t++) {
    const int c = min(t * 32 + lane, 143), r = c >= 72;
    asm volatile("ld.shared.v4.u32 {%0, %1, %2, %3}, [%4];" : "=r"(w[t][0]), "=r"(w[t][1]), "=r"(w[t][2]), "=r"(w[t][3])
                 : "r"(sq - 2304 + r * 2304 + (c - r * 72) * 16) : "memory");
  }
  asm volatile("fence.proxy.async.shared::cta;" ::: "memory");
  bar_arrive(4, 256 + 32);
#pragma unroll
  for (int t = 0; t < 5; t++) {
    const int c = min(t * 32 + lane, 143), r = c >= 72;
    st_v4(g_ctx + (size_t)(rb - 2 + 2 * r) * KCAT + HDIM + (c - r * 72) * 8, w[t][0], w[t][1], w[t][2], w[t][3]);
  }
}

#define K1_NST 6
constexpr int K1_BST = K1_NST;
constexpr int K1_MAXJOBS = 11;
constexpr uint32_t K1_FLAG_TARGET = 7;
constexpr uint32_t RDY_TARGET = 48;
constexpr uint32_t GATE_TARGET = 128 * 3;
struct alignas(64) Params {
  CUtensorMap tmA[2];
  CUtensorMap tmW[4];
  CUtensorMap tmQ, tmK, tmV;
  CUtensorMap tmL[2];
  CUtensorMap tmC, tmO[2], tmOt[2];
  uint16_t jobs[NCLUSTER][K1_MAXJOBS];
  uint8_t order[256];
};

struct K1State {
  uint32_t bs, bph, aph;
  bf16* pp;
  int pld8;
  int png;
};
__device__ __forceinline__ void k1_flag(const K1State& st, int lane, uint32_t bS) {
  if (st.png) {
    __syncwarp();
    if (lane == 0) mbar_arrive(bS);
  }
}

__device__ __forceinline__ void k1_tile(float (&acc)[128], uint32_t (&pk)[64], K1State& st, uint32_t job, uint32_t sA, uint32_t sB,
                                        uint32_t bAf, uint32_t bAe, uint32_t bBf, uint32_t bBe, uint32_t bS, int wg, int warp, int lane, uint32_t rank) {
  const int a_sel = (job >> 2) & 1, mpair = (job >> 3) & 7, w_sel = (job >> 6) & 3, chunk0 = (job >> 8) & 63;
  const bool newA = (job >> 14) & 1, lastA = (job >> 15) & 1;
  const bool sig = (lane == 0) && (warp < 2);
  const bool siga = lastA && (lane == 0) && (warp == 2);
  const int KC = 8 + a_sel;
  uint32_t prev_bs = 0, prev2_bs = 0, a8_bs = 0;
#pragma unroll
  for (int kc = 0; kc < 9; kc++) {
    if (kc >= KC) break;
    uint32_t abase = sA + ((kc + 2) & 7) * 16384;
    if (kc == 8) {
      mbar_wait(bBf + st.bs * 8, st.bph);
      a8_bs = st.bs;
      abase = sB + st.bs * 16384;
      if (++st.bs == K1_BST) { st.bs = 0; st.bph ^= 1; }
    } else if (newA) {
      mbar_wait(bAf + kc * 8, st.aph);
    }
    const uint64_t da = make_desc(abase + wg * 8192, 16, 1024, 1);
#pragma unroll
    for (int ks = 0; ks < 2; ks++) {
      mbar_wait(bBf + st.bs * 8, st.bph);
      const uint64_t db = make_desc(sB + st.bs * 16384, 2048, 1024, 1);
      wg_fence();
      wgmma_ss_n256<1, 0>(acc, da + (uint64_t)(ks * 4), db, (ks > 0) ? 1 : (kc > 0));
      wgmma_ss_n256<1, 0>(acc, da + (uint64_t)(ks * 4 + 2), db + (uint64_t)512, 1);
      wg_commit();
      const int PO = (kc < 8 ? kc : 0) * 8;
      wg_wait<1>();
      if (ks > 0 || kc > 0) {
        if (sig) mbar_arrive_cluster(bBe + prev_bs * 8, warp);
        if (ks == 0 && siga) mbar_arrive(bAe + (kc - 1) * 8);
      }
      if (kc < st.png) st_v4a(st.pp + kc * 32 + ks * st.pld8, pk[PO + ks * 4], pk[PO + ks * 4 + 1], pk[PO + ks * 4 + 2], pk[PO + ks * 4 + 3]);
      prev_bs = st.bs;
      if (++st.bs == K1_BST) { st.bs = 0; st.bph ^= 1; }
    }
  }
  if (newA) st.aph ^= 1;
  k1_flag(st, lane, bS);
  wg_wait<0>();
  fence_regs(acc);
  if (sig) {
    mbar_arrive_cluster(bBe + prev_bs * 8, warp);
    if (a_sel) mbar_arrive_cluster(bBe + a8_bs * 8, warp);
  }
  if (siga && !a_sel) mbar_arrive(bAe + 7 * 8);
  const bool isA = (w_sel == 2);
  bf16* out = (w_sel == 0) ? g_K : (w_sel == 1) ? g_V : isA ? g_QKVA : g_Q;
  const int ld = isA ? NQKVA : HDIM;
  const int row = mpair * 256 + rank * 128 + wg * 64 + warp * 16 + (lane >> 2);
  st.pp = out + (size_t)row * ld + chunk0 * 64 + (lane & 3) * 8;
  st.pld8 = 8 * ld;
  st.png = ((job & 3) + 1) * 2;
#pragma unroll
  for (int G = 0; G < 8; G++) {
    pk[G * 8 + 0] = pack_bf16(acc[G * 16 + 0], acc[G * 16 + 1]);
    pk[G * 8 + 1] = pack_bf16(acc[G * 16 + 4], acc[G * 16 + 5]);
    pk[G * 8 + 2] = pack_bf16(acc[G * 16 + 8], acc[G * 16 + 9]);
    pk[G * 8 + 3] = pack_bf16(acc[G * 16 + 12], acc[G * 16 + 13]);
    pk[G * 8 + 4] = pack_bf16(acc[G * 16 + 2], acc[G * 16 + 3]);
    pk[G * 8 + 5] = pack_bf16(acc[G * 16 + 6], acc[G * 16 + 7]);
    pk[G * 8 + 6] = pack_bf16(acc[G * 16 + 10], acc[G * 16 + 11]);
    pk[G * 8 + 7] = pack_bf16(acc[G * 16 + 14], acc[G * 16 + 15]);
  }
  if (isA) {
#pragma unroll
    for (int G = 0; G < 16; G++) quad_transpose(pk[G * 4 + 0], pk[G * 4 + 1], pk[G * 4 + 2], pk[G * 4 + 3], lane & 3);
  }
}

#define HA(h) (h)
constexpr int K2_NST = 7;
constexpr uint32_t K2_END = 0x100;
#define PF_KC 7
#define FIRST_DRAW 3
#define ANCH 8
constexpr int K3_NST = 4;
#define K3_P1 20
#define K3_P2 39
#define K3_P3 57
__device__ __forceinline__ uint32_t k3_rot(uint32_t sv) { return (0x00E9u >> (2 * sv)) & 3; }
__device__ __forceinline__ int k3_part(int i) { return (i == 0) ? 0 : (i == 1) ? K3_P1 : (i == 2) ? K3_P2 : (i == 3) ? K3_P3 : 73; }
constexpr int K3_STAGE = 16384 + 32768 + 4096;
constexpr int SMEM_DATA = 7 * 32768;
constexpr int SMEM_BYTES = SMEM_DATA + 1024 + 768;

struct Cursor {
  uint32_t s, ph;
  __device__ __forceinline__ void next() {
    if (++s == K2_NST) { s = 0; ph ^= 1; }
  }
};

#define TURN_SYNC() bar_sync(mybar, 256)
#define TURN_ARRIVE() bar_arrive(otherbar, 256)
#define RELEASE_IF(cur, cond) mbar_arrive_cluster_if(bE + (cur).s * 8, warp & 1, sig && (cond))
#define RELEASE(cur) RELEASE_IF(cur, true)
#define ISSUE_PV(cur, first)                                                                                   \
  do {                                                                                                         \
    const uint64_t dv = make_desc(sbase + (cur).s * 32768, 16384, 1024, 1);                                    \
    _Pragma("unroll") for (int t = 0; t < 8; t++)                                                              \
        wgmma_rs_n128<1, 0>(O, P[4 * t], P[4 * t + 1], P[4 * t + 2], P[4 * t + 3], dv + (uint64_t)(t * 128), (t > 0) ? 1 : !(first)); \
  } while (0)
#define RESCALE_O()                                                                                            \
  do {                                                                                                         \
    fence_regs(O);                                                                                             \
    _Pragma("unroll") for (int jj = 0; jj < 16; jj++) {                                                        \
      O[jj * 4 + 0] *= sc0; O[jj * 4 + 1] *= sc0; O[jj * 4 + 2] *= sc1; O[jj * 4 + 3] *= sc1;                  \
    }                                                                                                          \
    fence_regs(O);                                                                                             \
  } while (0)
#define ISSUE_QK(cur)                                                                                          \
  do {                                                                                                         \
    const uint64_t dk = make_desc(sbase + (cur).s * 32768, 16, 1024, 1);                                       \
    _Pragma("unroll") for (int t = 0; t < 8; t++)                                                              \
        wgmma_rs_n128<0, 0>(S, Q[4 * t], Q[4 * t + 1], Q[4 * t + 2], Q[4 * t + 3], dk + (uint64_t)((t >> 2) * 1024 + (t & 3) * 2), t > 0); \
  } while (0)
#define EPILOGUE()                                                                                             \
  do {                                                                                                         \
    l0 += __shfl_xor_sync(0xffffffffu, l0, 1);                                                                 \
    l0 += __shfl_xor_sync(0xffffffffu, l0, 2);                                                                 \
    l1 += __shfl_xor_sync(0xffffffffu, l1, 1);                                                                 \
    l1 += __shfl_xor_sync(0xffffffffu, l1, 2);                                                                 \
    asm volatile("" : "+f"(gf0), "+f"(gf1));                                                                   \
    const float f0 = __fdividef(1.f - gf0, l0), f1 = __fdividef(1.f - gf1, l1);                                                                \
    bf16* o0 = g_ctx + (size_t)prev_row * KCAT + prev_h * 128 + q * 8;                                         \
    bf16* o1 = o0 + (size_t)8 * KCAT;                                                                          \
    _Pragma("unroll") for (int G = 0; G < 4; G++) {                                                            \
      st_v4(o0 + G * 32, pack_bf16(O[G * 16 + 0] * f0, O[G * 16 + 1] * f0), pack_bf16(O[G * 16 + 4] * f0, O[G * 16 + 5] * f0), \
            pack_bf16(O[G * 16 + 8] * f0, O[G * 16 + 9] * f0), pack_bf16(O[G * 16 + 12] * f0, O[G * 16 + 13] * f0)); \
      st_v4(o1 + G * 32, pack_bf16(O[G * 16 + 2] * f1, O[G * 16 + 3] * f1), pack_bf16(O[G * 16 + 6] * f1, O[G * 16 + 7] * f1), \
            pack_bf16(O[G * 16 + 10] * f1, O[G * 16 + 11] * f1), pack_bf16(O[G * 16 + 14] * f1, O[G * 16 + 15] * f1)); \
    }                                                                                                          \
  } while (0)

__global__ void __cluster_dims__(2, 1, 1) __launch_bounds__(384, 1)
fused_kernel(const __grid_constant__ Params p, const bf16* __restrict__ x, const bf16* __restrict__ gate_w, bf16* __restrict__ out) {
  extern __shared__ uint8_t smem_raw[];
  const uint32_t sbase = (smem_u32(smem_raw) + 1023) & ~1023u;
  const uint32_t sB = sbase, sA = sbase + K1_BST * 16384, sBar = sbase + SMEM_DATA;
  const uint32_t bAf = sBar, bAe = sBar + 64, bBf = sBar + 128, bBe = sBar + 176, bL = sBar + 224, bS = sBar + 232, bL2 = sBar + 240, sL = sA + 32768;
  const uint32_t bF = sBar + 256, bE = sBar + 320, bT = sBar + 384, sTick = sBar + 400, sItem = sBar + 416, bS2 = sBar + 448, bR = sBar + 456, bLast = sBar + 464, bH = sBar + 472, bT0 = sBar + 480;
  const uint32_t b3F = sBar + 512, b3E = sBar + 544, sGate = sBar + 576;
  const int tid = threadIdx.x, warp_g = __shfl_sync(0xffffffffu, tid >> 5, 0), lane = tid & 31;
  const uint32_t rank = cluster_rank();
  const int cl = blockIdx.x >> 1;
  TSM(0);
  if (tid == 0) {
    for (int i = 0; i < 8; i++) { mbar_init(bAf + i * 8, 1); mbar_init(bAe + i * 8, 2); }
    for (int i = 0; i < K1_BST; i++) { mbar_init(bBf + i * 8, 1); mbar_init(bBe + i * 8, 4); }
    mbar_init(bL, 1);
    mbar_init(bL2, 1);
    mbar_init(bR, 1);
    mbar_init(bLast, 1);
    mbar_init(bH, 4);
    mbar_init(bT0, 1);
    mbar_init(bS, 8);
    for (int i = 0; i < K2_NST; i++) { mbar_init(bF + i * 8, 1); mbar_init(bE + i * 8, 4); }
    mbar_init(bT, 1); mbar_init(bT + 8, 1);
    mbar_init(bS2, 8);
    for (int i = 0; i < K3_NST; i++) { mbar_init(b3F + i * 8, 1); mbar_init(b3E + i * 8, 4); }
    asm volatile("fence.mbarrier_init.release.cluster;" ::: "memory");
  }
  __syncthreads();
  cluster_sync();
  const int lr0 = blockIdx.x * 16;

  if (warp_g >= 8) {
    reg_dealloc<40>();
    if (warp_g == 8) {
      if (elect_one()) {
        uint32_t bs = 0, bph = 1, aph = 1;
#pragma unroll 1
        for (int ji = 0; ji < K1_MAXJOBS; ji++) {
          const uint32_t job = p.jobs[cl][ji];
          if (!(job & 3)) break;
          const int a_sel = (job >> 2) & 1, mpair = (job >> 3) & 7, chunk0 = (job >> 8) & 63;
          const bool newA = (job >> 14) & 1;
          const int KC = a_sel ? 9 : 8;
          const uint32_t halfbytes = 8192;
          const bool lastjob = (ji + 1 == K1_MAXJOBS) || !(p.jobs[cl][ji + 1] & 3);
          const CUtensorMap* tw = &p.tmW[(job >> 6) & 3];
          {
            const uint32_t njob = (ji + 1 < K1_MAXJOBS) ? p.jobs[cl][ji + 1] : 0;
            if (!(njob & 3) && !newA) mbar_arrive(bLast);
          }
#pragma unroll 1
          for (int kc = 0; kc < KC; kc++) {
            if (kc == ((ji == 0) ? PF_KC : 0) && !lastjob) {
              const uint32_t njob = p.jobs[cl][ji + 1];
              const int nst = ((njob >> 2) & 1) ? 18 : 16;
#pragma unroll 1
              for (int t = (cl < 64) ? (cl & 7) : 0; t < nst; t += (cl < 64) ? 8 : 1)
                tma_pf3d(&p.tmW[(njob >> 6) & 3], 0, t * 32 + rank * 16, (njob >> 8) & 63);
            }
            if (kc == 8) {
              mbar_wait(bBe + bs * 8, bph);
              mbar_expect(bBf + bs * 8, 16384);
              tma2d(sB + bs * 16384, &p.tmA[1], bBf + bs * 8, 512, mpair * 256 + rank * 128);
              if (++bs == K1_BST) { bs = 0; bph ^= 1; }
            } else if (newA) {
              mbar_wait(bAe + kc * 8, aph);
              mbar_expect(bAf + kc * 8, 16384);
              tma2d(sA + ((kc + 2) & 7) * 16384, &p.tmA[a_sel], bAf + kc * 8, kc * 64, mpair * 256 + rank * 128);
              if (kc == 7 && lastjob) mbar_arrive(bLast);
            }
#pragma unroll 1
            for (int kk = 0; kk < 2; kk++) {
              mbar_wait(bBe + bs * 8, bph);
              mbar_expect(bBf + bs * 8, 2 * halfbytes);
              tma3d_mc(sB + bs * 16384 + rank * halfbytes, tw, bBf + bs * 8, 0, kc * 64 + kk * 32 + rank * 16, chunk0, 3);
              if (++bs == K1_BST) { bs = 0; bph ^= 1; }
            }
          }
          if (newA) aph ^= 1;
        }
        Cursor c{0, 0};
        int pcol = 0;
        mbar_wait(bR, 0);
        uint32_t tick = lds32(sTick + 8), seen = 1u << (p.order[tick] >> 4);
        asm volatile("fence.proxy.async.global;" ::: "memory");
#pragma unroll 1
        for (int it = 0;; it++) {
          const uint32_t item = (tick < 256) ? p.order[tick] : (K2_END | min(tick - 256, 255u));
          asm volatile("st.shared.u32 [%0], %1;" ::"r"(sItem + (it & 7) * 4), "r"(item) : "memory");
          if (item >= K2_END) break;
          const int h = item >> 3, j = item & 7;
          const int blk = 2 * j + (int)(rank ^ (it & 1));
          const int col = HA(h) * 128 + rank * 64;
          const int nb = 2 * j + 2;
          if (!((seen >> (h >> 1)) & 1)) {
            wait_flag(&g_sync[F_HP + (h >> 1)], RDY_TARGET);
            asm volatile("fence.proxy.async.global;" ::: "memory");
            seen |= 1u << (h >> 1);
          }
          mbar_wait(bE + c.s * 8, c.ph);
          mbar_expect(bF + c.s * 8, 32768);
          tma2d(sbase + c.s * 32768, &p.tmQ, bF + c.s * 8, HA(h) * 128, blk * 128);
          tma2d(sbase + c.s * 32768 + 16384, &p.tmQ, bF + c.s * 8, HA(h) * 128 + 64, blk * 128);
          c.next();
#pragma unroll 1
          for (int n = nb - 1; n >= 0; n--) {
            if (n == 0 && rank == 0) tick = atomicAdd(&g_sync[F_TICK], 1u);
            mbar_wait(bE + c.s * 8, c.ph);
            mbar_expect(bF + c.s * 8, 32768);
            tma2d_mc(sbase + c.s * 32768 + rank * 16384, &p.tmK, bF + c.s * 8, col, n * 128, 3);
            c.next();
            if (n < nb - 1 || it > 0) {
              mbar_wait(bE + c.s * 8, c.ph);
              mbar_expect(bF + c.s * 8, 32768);
              tma2d_mc(sbase + c.s * 32768 + rank * 16384, &p.tmV, bF + c.s * 8, (n < nb - 1) ? col : pcol, (n < nb - 1) ? (n + 1) * 128 : 0, 3);
              c.next();
            }
          }
          pcol = col;
          if (rank == 0) {
            asm volatile(
                "{\n.reg .b32 a, b;\nmapa.shared::cluster.u32 a, %0, 1;\nmapa.shared::cluster.u32 b, %1, 1;\n"
                "st.async.shared::cluster.mbarrier::complete_tx::bytes.u32 [a], %2, [b];\n}" ::"r"(sTick + (it & 1) * 4),
                "r"(bT + (it & 1) * 8), "r"(tick) : "memory");
          } else {
            mbar_expect(bT + (it & 1) * 8, 4);
            mbar_wait(bT + (it & 1) * 8, (it >> 1) & 1);
            tick = lds32(sTick + (it & 1) * 4);
          }
        }
        mbar_wait(bE + c.s * 8, c.ph);
        mbar_expect(bF + c.s * 8, 32768);
        tma2d_mc(sbase + c.s * 32768 + rank * 16384, &p.tmV, bF + c.s * 8, pcol, 0, 3);
        const uint32_t unit = tick - 256;
        if (unit < 64) {
          const int mblk = (7 - (int)((unit >> 1) & 7)) * 2 + rank, nhalf = unit & 1, ks = unit >> 4;
          const uint32_t rot = k3_rot(c.s), nfree = ((0x1Au >> c.s) & 1) ? 2 : 3;
#pragma unroll 1
          for (int i = 0; i < K2_NST - 1; i++) {
            c.next();
            mbar_wait(bE + c.s * 8, c.ph);
          }
          uint32_t idx = 0, have = 0;
#pragma unroll 1
          for (int kk = k3_part(ks); kk < k3_part(ks + 1); kk++, idx++) {
            const uint32_t s = (rot + idx) & 3;
            if (idx >= nfree) mbar_wait((idx < 4) ? bH : b3E + s * 8, (idx < 4) ? 0 : (~idx >> 2) & 1);
            mbar_expect(b3F + s * 8, K3_STAGE);
            const uint32_t st = sbase + s * K3_STAGE;
            const int sel = (kk < 9), k = sel ? kk : kk - 9, kr = k * 64 + rank * 32;
            tma3d_mc(st + 16384 + rank * 16384, &p.tmO[sel], b3F + s * 8, 0, kr, nhalf * 4, 3);
            tma2d_mc(st + 49152 + rank * 2048, &p.tmOt[sel], b3F + s * 8, 512 + nhalf * 32, kr, 3);
            if (kk == 0) {
              wait_flag(&g_sync[F_OA + mblk], 8);
              asm volatile("fence.proxy.async.global;" ::: "memory");
            }
            if (!sel && !((have >> (k >> 1)) & 1)) {
#pragma unroll 1
              for (uint32_t spins = 0; spins < (1u << 22); spins++) {
                asm volatile("ld.acquire.gpu.global.u32 %0, [%1];" : "=r"(have) : "l"(&g_sync[F_CTX + mblk]) : "memory");
                if ((have >> (k >> 1)) & 1) break;
                __nanosleep(100);
              }
              asm volatile("fence.proxy.async.global;" ::: "memory");
            }
            tma2d(st, &p.tmC, b3F + s * 8, (sel ? 64 + k : k) * 64, mblk * 128);
          }
        }
      }
    }
    __syncwarp();
    if (warp_g == 8) {
      uint32_t v = 0;
      if (lane == 0) {
        __threadfence();
        v = atomicAdd(&g_sync[F_DONE], 1u);
      }
      if (__shfl_sync(0xffffffffu, v, 0) == 2 * NCLUSTER - 1) {
        reinterpret_cast<uint4*>(g_sync)[lane] = make_uint4(0, 0, 0, 0);
        if (lane == 0) g_sync[F_EPOCH] = lds32(sGate + 64) + 1;
      }
    }
    asm volatile("" ::: "memory");
    if (__shfl_sync(0xffffffffu, warp_g, 0) != 8) {
      if (lr0 < S_LEN) {
#pragma unroll 1
        for (int i = warp_g - 9; i < 16; i += 3) {
          const float g = gate_row(lr0 + i, lane, x, gate_w);
          if (lane == 0) asm volatile("st.shared.f32 [%0], %1;" ::"r"(sGate + i * 4), "f"(g) : "memory");
        }
        bar_arrive(3, 256 + 96);
        if (lane == 0) {
          __threadfence();
          atomicAdd(&g_sync[F_GATE], 1u);
        }
      }
      uint32_t aph = 1;
#pragma unroll 1
      for (int ji = 0; ji < K1_MAXJOBS; ji++) aph ^= (p.jobs[cl][ji] >> 14) & 1;
      if (warp_g == 9 && lane == 0) {
#pragma unroll 1
        for (int ji = 0; ji < K1_MAXJOBS; ji++) {
          const uint32_t job = p.jobs[cl][ji];
          if (!(job & 3)) break;
          mbar_wait(bS, ji & 1);
          __threadfence();
          atomicAdd(&g_sync[(((job >> 6) & 3) == 2) ? (F_QKVA + ((job >> 3) & 7) * 2 + rank) : (F_HP + ((job >> 10) & 15))], 1u);
        }
#pragma unroll 1
        for (int it = 0;; it++) {
          mbar_wait(bS2, it & 1);
          const uint32_t item = lds32(sItem + (it & 7) * 4), nxt = lds32(sItem + ((it + 1) & 7) * 4);
          __threadfence();
          atomicOr(&g_sync[F_CTX + (item & 7) * 2 + (rank ^ (it & 1))], 1u << (item >> 3));
          if (nxt >= K2_END) break;
        }
      } else if (warp_g == 11) {
        if (lane == 0) {
          prefetch_tmap(&p.tmQ); prefetch_tmap(&p.tmK); prefetch_tmap(&p.tmV);
          asm volatile("st.shared.u32 [%0], %1;" ::"r"(sGate + 64), "r"(__ldcg(&g_sync[F_EPOCH])) : "memory");
          wait_flag(&g_sync[F_GATE], GATE_TARGET);
          uint32_t tick;
          if (rank == 0) {
            mbar_wait(bLast, 0);
            mbar_wait(bAe + FIRST_DRAW * 8, aph);
            tick = atomicAdd(&g_sync[F_TICK], 1u);
            asm volatile("st.shared.u32 [%0], %1;" ::"r"(sTick + 8), "r"(tick) : "memory");
            asm volatile(
                "{\n.reg .b32 a, b;\nmapa.shared::cluster.u32 a, %0, 1;\nmapa.shared::cluster.u32 b, %1, 1;\n"
                "st.async.shared::cluster.mbarrier::complete_tx::bytes.u32 [a], %2, [b];\n}" ::"r"(sTick + 8), "r"(bT0), "r"(tick) : "memory");
          } else {
            mbar_expect(bT0, 4);
            mbar_wait(bT0, 0);
            tick = lds32(sTick + 8);
          }
          wait_flag(&g_sync[F_HP + (p.order[tick] >> 4)], RDY_TARGET);
          mbar_arrive(bR);
        }
        __syncwarp();
        bar_sync(4, 256 + 32);
        if (lane < 12) mbar_arrive_cluster(bE + (4 + lane % 3) * 8, (lane / 3) & 1);
      } else if (warp_g == 10 && lr0 < S_LEN) {
        if (elect_one()) {
          prefetch_tmap(&p.tmL[0]); prefetch_tmap(&p.tmL[1]);
          wait_flag(&g_sync[F_QKVA + (lr0 >> 7)], K1_FLAG_TARGET);
          wait_flag(&g_sync[F_QKVA + (max(lr0 - 14, 0) >> 7)], K1_FLAG_TARGET);
          asm volatile("fence.proxy.async.global;" ::: "memory");
          mbar_wait(bLast, 0);
#pragma unroll 1
          for (int kc = 0; kc < 6; kc++) {
            mbar_wait(bAe + kc * 8, aph);
            if (kc == 3) {
              mbar_expect(bL, 46 * 1152);
              tma3d(sL, &p.tmL[0], bL, 0, 9, lr0 - 14);
              tma3d(sL + 30 * 1152, &p.tmL[1], bL, 0, 0, lr0);
            }
          }
          mbar_expect(bL2, 30 * 1152);
          tma3d(sL + 46 * 1152, &p.tmL[0], bL2, 0, 18, lr0 - 14);
        }
        __syncwarp();
        bar_sync(5, 256 + 32);
        if (lane == 0) {
          __threadfence();
          atomicAdd(&g_sync[F_OA + (lr0 >> 7)], 1u);
        }
      }
    }
    __syncwarp();
    cluster_sync();
  } else {
    reg_alloc<232>();
    const int wg = warp_g >> 2, warp = warp_g & 3, q = lane & 3;
    const bool sig = (lane == 0) && (warp < 2);
    {
      K1State st{0, 0, 0, nullptr, 0, 0};
      float acc[128];
      uint32_t pk[64];
      if (wg == 0) { TS(0, 0); TSC(0, 2); }
#pragma unroll 1
      for (int ji = 0; ji < K1_MAXJOBS; ji++) {
        const uint32_t job = p.jobs[cl][ji];
        if (!(job & 3)) break;
        k1_tile(acc, pk, st, job, sA, sB, bAf, bAe, bBf, bBe, bS, wg, warp, lane, rank);
      }
#pragma unroll
      for (int i = 0; i < 4; i++)
        mbar_arrive_cluster_if(bE + i * 8, warp & 1, sig);
#pragma unroll
      for (int G = 0; G < 8; G++)
        if (G < st.png) {
          st_v4a(st.pp + G * 32, pk[G * 8], pk[G * 8 + 1], pk[G * 8 + 2], pk[G * 8 + 3]);
          st_v4a(st.pp + G * 32 + st.pld8, pk[G * 8 + 4], pk[G * 8 + 5], pk[G * 8 + 6], pk[G * 8 + 7]);
        }
      k1_flag(st, lane, bS);
      if (wg == 0) { TS(0, 1); TSC(0, 3); }
      if (lr0 < S_LEN) {
        const int ri = (warp_g >> 1) * 4 + (warp_g & 1) + 2, row = lr0 + ri;
        if (wg == 0) TS(1, 5);
        bar_sync(3, 256 + 96);
        const float gate0 = __uint_as_float(lds32(sGate + ri * 4 - 8)), gate1 = __uint_as_float(lds32(sGate + ri * 4));
        mbar_wait(bL, 0);
        if (wg == 0) TS(1, 6);
        local_rows2(row, ri, sL, bL2, lane, gate0, gate1);
        bar_arrive(5, 256 + 32);
      } else {
        bar_arrive(4, 256 + 32);
      }
    }
    __syncwarp();
    uint32_t item, rot;
    {
      const int mybar = 1 + wg, otherbar = 2 - wg;
      const float cl2 = 0.08838834764831845f * 1.4426950408889634f;
      float S[64], O[64];
      uint32_t P[32], Q[32];
      float m0 = 0.f, m1 = 0.f, l0 = 0.f, l1 = 0.f;
      int prev_row = 0, prev_h = 0, prev_single = 0;
      Cursor c{0, 0};
      if (wg == 1) bar_arrive(1, 256);
      if (wg == 0) { TS(1, 0); TSC(1, 2); }
#pragma unroll 1
      for (int it = 0;; it++) {
        mbar_wait(bF + c.s * 8, c.ph);
        item = lds32(sItem + (it & 7) * 4);
        const bool last = item >= K2_END;
        const int h = item >> 3, j = item & 7;
        const int hi = (int)(rank ^ (it & 1));
        const int nblk = 2 * j + 1 + hi;
        {
          float gf0, gf1;
          asm volatile("ld.global.f32 %0, [%1];" : "=f"(gf0) : "l"(g_gate + prev_row));
          asm volatile("ld.global.f32 %0, [%1];" : "=f"(gf1) : "l"(g_gate + prev_row + 8));
          Cursor cq = c, ck = c, cs0 = c, cs1 = c, cv = c;
          rot = k3_rot(c.s);
          if (!last) {
            const int r = wg * 64 + warp * 16 + (lane & 7) + ((lane >> 3) & 1) * 8;
            const uint32_t qa = sbase + cq.s * 32768 + r * 128;
#pragma unroll
            for (int t = 0; t < 8; t++)
              ldsm_x4(Q[4 * t], Q[4 * t + 1], Q[4 * t + 2], Q[4 * t + 3], qa + (t >> 2) * 16384 + ((((t & 3) * 2 + (lane >> 4)) ^ (lane & 7)) << 4));
            c.next();
            ck = c; c.next();
            cs0 = ck; cv = c;
            mbar_wait(bF + ck.s * 8, ck.ph);
            if (it > 0) { mbar_wait(bF + cv.s * 8, cv.ph); c.next(); }
            if (!hi) {
              ck = c; c.next();
              cs1 = c; c.next();
              mbar_wait(bF + ck.s * 8, ck.ph);
              mbar_wait(bF + cs1.s * 8, cs1.ph);
            }
          }
          if (it == 0) BSEG(4); else BSEG(0);
          TURN_SYNC();
          if (it > 0) {
            wg_fence();
            ISSUE_PV(cv, prev_single);
            wg_commit();
          } else {
            wg_fence();
            wg_commit();
          }
          wg_fence();
          ISSUE_QK(ck);
          wg_commit();
          if (!(last && wg == 1)) TURN_ARRIVE();
          RELEASE_IF(cq, !last);
          RELEASE_IF(cs0, !last && !hi);
          RELEASE_IF(cs1, !last && !hi);
          wg_wait<1>();
          fence_regs(O);
          fence_regs(P);
          if (it > 0) {
            RELEASE_IF(cv, !last);
            mbar_arrive_cluster_if(bH, warp & 1, sig && last);
            EPILOGUE();
            __syncwarp();
            mbar_arrive_if(bS2, lane == 0);
          }
          wg_wait<0>();
          fence_regs(S);
          if (last) break;
          RELEASE(ck);
          float s0 = 0.f, s1 = 0.f;
          const int r0 = wg * 64 + warp * 16 + (lane >> 2);
#pragma unroll
          for (int jj = 0; jj < 16; jj++) {
            const int cc = jj * 8 + 2 * q;
            if (cc > r0) S[jj * 4 + 0] = -INFINITY;
            if (cc + 1 > r0) S[jj * 4 + 1] = -INFINITY;
            if (cc > r0 + 8) S[jj * 4 + 2] = -INFINITY;
            if (cc + 1 > r0 + 8) S[jj * 4 + 3] = -INFINITY;
          }
          float mx0 = fmaxf(S[0], S[1]), mx1 = fmaxf(S[2], S[3]);
#pragma unroll
          for (int jj = 1; jj < 16; jj++) {
            mx0 = fmaxf(mx0, fmaxf(S[jj * 4 + 0], S[jj * 4 + 1]));
            mx1 = fmaxf(mx1, fmaxf(S[jj * 4 + 2], S[jj * 4 + 3]));
          }
          mx0 = fmaxf(mx0, __shfl_xor_sync(0xffffffffu, mx0, 1));
          mx1 = fmaxf(mx1, __shfl_xor_sync(0xffffffffu, mx1, 1));
          mx0 = fmaxf(mx0, __shfl_xor_sync(0xffffffffu, mx0, 2));
          mx1 = fmaxf(mx1, __shfl_xor_sync(0xffffffffu, mx1, 2));
          m0 = mx0; m1 = mx1;
          const float mc0 = m0 * cl2, mc1 = m1 * cl2;
#pragma unroll
          for (int jj = 0; jj < 16; jj++) {
            S[jj * 4 + 0] = ex2(fmaf(S[jj * 4 + 0], cl2, -mc0));
            S[jj * 4 + 1] = ex2(fmaf(S[jj * 4 + 1], cl2, -mc0));
            S[jj * 4 + 2] = ex2(fmaf(S[jj * 4 + 2], cl2, -mc1));
            S[jj * 4 + 3] = ex2(fmaf(S[jj * 4 + 3], cl2, -mc1));
            s0 += S[jj * 4 + 0] + S[jj * 4 + 1];
            s1 += S[jj * 4 + 2] + S[jj * 4 + 3];
          }
          l0 = s0; l1 = s1;
#pragma unroll
          for (int jj = 0; jj < 16; jj++) {
            P[jj * 2 + 0] = pack_bf16(S[jj * 4 + 0], S[jj * 4 + 1]);
            P[jj * 2 + 1] = pack_bf16(S[jj * 4 + 2], S[jj * 4 + 3]);
          }
        }
        if (it == 0) BSEG(5); else BSEG(1);
#pragma unroll 1
        for (int n = 1; n < nblk; n++) {
          Cursor ck = c; c.next();
          Cursor cv = c; c.next();
          mbar_wait(bF + ck.s * 8, ck.ph);
          mbar_wait(bF + cv.s * 8, cv.ph);
          TURN_SYNC();
          wg_fence();
          ISSUE_QK(ck);
          wg_commit();
          ISSUE_PV(cv, n == 1);
          wg_commit();
          TURN_ARRIVE();
          wg_wait<1>();
          fence_regs(S);
          float mx0 = fmaxf(S[0], S[1]), mx1 = fmaxf(S[2], S[3]);
#pragma unroll
          for (int jj = 1; jj < 16; jj++) {
            mx0 = fmaxf(mx0, fmaxf(S[jj * 4 + 0], S[jj * 4 + 1]));
            mx1 = fmaxf(mx1, fmaxf(S[jj * 4 + 2], S[jj * 4 + 3]));
          }
          mx0 = fmaxf(mx0, __shfl_xor_sync(0xffffffffu, mx0, 1));
          mx1 = fmaxf(mx1, __shfl_xor_sync(0xffffffffu, mx1, 1));
          mx0 = fmaxf(mx0, __shfl_xor_sync(0xffffffffu, mx0, 2));
          mx1 = fmaxf(mx1, __shfl_xor_sync(0xffffffffu, mx1, 2));
          mx0 = fmaxf(mx0, m0);
          mx1 = fmaxf(mx1, m1);
          const float sc0 = ex2((m0 - mx0) * cl2), sc1 = ex2((m1 - mx1) * cl2);
          m0 = mx0; m1 = mx1;
          const float mc0 = m0 * cl2, mc1 = m1 * cl2;
          float s0 = 0.f, s1 = 0.f;
#pragma unroll
          for (int jj = 0; jj < 16; jj++) {
            S[jj * 4 + 0] = ex2(fmaf(S[jj * 4 + 0], cl2, -mc0));
            S[jj * 4 + 1] = ex2(fmaf(S[jj * 4 + 1], cl2, -mc0));
            S[jj * 4 + 2] = ex2(fmaf(S[jj * 4 + 2], cl2, -mc1));
            S[jj * 4 + 3] = ex2(fmaf(S[jj * 4 + 3], cl2, -mc1));
            s0 += S[jj * 4 + 0] + S[jj * 4 + 1];
            s1 += S[jj * 4 + 2] + S[jj * 4 + 3];
          }
          l0 = fmaf(l0, sc0, s0);
          l1 = fmaf(l1, sc1, s1);
          mbar_arrive_cluster_after(bE + ck.s * 8, warp & 1, sig, (ANCH == 100) ? mx0 : (ANCH == 101) ? mx1 : S[ANCH & 63]);
          fence_regs(S);
          wg_wait<0>();
          fence_regs(O);
          fence_regs(P);
          RELEASE(cv);
#pragma unroll
          for (int jj = 0; jj < 16; jj++) {
            O[jj * 4 + 0] *= sc0;
            O[jj * 4 + 1] *= sc0;
            O[jj * 4 + 2] *= sc1;
            O[jj * 4 + 3] *= sc1;
            P[jj * 2 + 0] = pack_bf16(S[jj * 4 + 0], S[jj * 4 + 1]);
            P[jj * 2 + 1] = pack_bf16(S[jj * 4 + 2], S[jj * 4 + 3]);
          }
        }
        BSEG(2);
        prev_row = (2 * j + hi) * 128 + wg * 64 + warp * 16 + (lane >> 2);
        prev_h = h;
        prev_single = (nblk == 1);
      }
      if (wg == 1) { TS(1, 1); TSC(1, 3); }
    }
    __syncwarp();
    const uint32_t unit = item & 255;
    if (unit < 64) {
      const int mblk = (7 - (int)((unit >> 1) & 7)) * 2 + rank, nhalf = unit & 1, ks = unit >> 4;
      const int k0 = k3_part(ks), k1 = k3_part(ks + 1);
      float acc[144];
      uint32_t s = rot, ph = 0, prev = 0;
      if (wg == 0) { TS(2, 0); TSC(2, 2); }
#pragma unroll 1
      for (int k = k0; k < k1; k++) {
        mbar_wait(b3F + s * 8, ph);
        const uint32_t st = sbase + s * K3_STAGE;
        const uint64_t da = make_desc(st + wg * 8192, 16, 1024, 1);
        const uint64_t db = make_desc(st + 16384, 4096, 1024, 1);
        const uint64_t dt = make_desc(st + 49152, 16, 512, 2);
        wg_fence();
#pragma unroll
        for (int t = 0; t < 4; t++) {
          const int sd = (t > 0) || (k > k0);
          wgmma_ss_n256<1, 0>(acc, da + (uint64_t)(t * 2), db + (uint64_t)((t >> 1) * 1024 + (t & 1) * 128), sd);
          wgmma_ss_n32<1, 128>(acc, da + (uint64_t)(t * 2), dt + (uint64_t)(t * 64), sd);
        }
        wg_commit();
        if (k > k0) {
          wg_wait<1>();
          if (sig) mbar_arrive_cluster(b3E + prev * 8, warp);
        }
        prev = s;
        s = (s + 1) & 3;
        if (s == rot) ph ^= 1;
      }
      wg_wait<0>();
      fence_regs(acc);
      cluster_arrive();
      if (wg == 0) TS(2, 4);
      const int tile = mblk * 2 + nhalf;
      uint4* wp = g_part + (size_t)((tile * 4 + ks) * 4) * 5 * 256 + tid;
      const uint32_t sown = sbase + wg * 8192 + (tid & 127) * 16;
#pragma unroll
      for (int d = 0; d < 4; d++) {
        if (d != ks) {
#pragma unroll
          for (int i = 0; i < 4; i++)
            __stcg(wp + (d * 5 + i) * 256,
                   make_uint4(pack_bf16(acc[d * 32 + i * 8], acc[d * 32 + i * 8 + 1]), pack_bf16(acc[d * 32 + i * 8 + 2], acc[d * 32 + i * 8 + 3]),
                              pack_bf16(acc[d * 32 + i * 8 + 4], acc[d * 32 + i * 8 + 5]), pack_bf16(acc[d * 32 + i * 8 + 6], acc[d * 32 + i * 8 + 7])));
          __stcg(reinterpret_cast<uint2*>(wp - tid + (d * 5 + 4) * 256) + tid,
                 make_uint2(pack_bf16(acc[128 + d * 4], acc[128 + d * 4 + 1]), pack_bf16(acc[128 + d * 4 + 2], acc[128 + d * 4 + 3])));
        } else {
#pragma unroll
          for (int i = 0; i < 9; i++) {
            const int o = (i < 8) ? d * 32 + i * 4 : 128 + d * 4;
            asm volatile("st.shared.v4.f32 [%0], {%1, %2, %3, %4};" ::"r"(sown + (i >> 2) * K3_STAGE + (i & 3) * 2048), "f"(acc[o]), "f"(acc[o + 1]), "f"(acc[o + 2]), "f"(acc[o + 3]) : "memory");
          }
        }
      }
      __threadfence();
      __syncwarp();
      if (wg == 0) TS(2, 5);
      if (lane == 0) {
        unsigned int* cnt = &g_sync[F_XCH + tile * 8 + warp_g];
        const uint32_t xtarget = lds32(sGate + 64) * 4 + 4;
        atomicAdd(cnt, 1u);
        uint32_t v, spins = 0;
        do {
          asm volatile("ld.acquire.gpu.global.u32 %0, [%1];" : "=r"(v) : "l"(cnt) : "memory");
        } while ((int)(v - xtarget) < 0 && ++spins < (1u << 24));
      }
      __syncwarp();
      if (wg == 0) TS(2, 6);
      float r[36];
#pragma unroll
      for (int i = 0; i < 9; i++)
        asm volatile("ld.shared.v4.f32 {%0, %1, %2, %3}, [%4];" : "=f"(r[i * 4]), "=f"(r[i * 4 + 1]), "=f"(r[i * 4 + 2]), "=f"(r[i * 4 + 3])
                     : "r"(sown + (i >> 2) * K3_STAGE + (i & 3) * 2048) : "memory");
#pragma unroll
      for (int sI = 1; sI < 4; sI++) {
        const int src = (ks + sI) & 3;
        const uint4* rp = g_part + (size_t)(((tile * 4 + src) * 4) + ks) * 5 * 256;
#pragma unroll
        for (int i = 0; i < 4; i++) {
          const uint4 v = __ldcg(rp + i * 256 + tid);
          r[i * 8] += bf_lo(v.x); r[i * 8 + 1] += bf_hi(v.x); r[i * 8 + 2] += bf_lo(v.y); r[i * 8 + 3] += bf_hi(v.y);
          r[i * 8 + 4] += bf_lo(v.z); r[i * 8 + 5] += bf_hi(v.z); r[i * 8 + 6] += bf_lo(v.w); r[i * 8 + 7] += bf_hi(v.w);
        }
        const uint2 v = __ldcg(reinterpret_cast<const uint2*>(rp + 4 * 256) + tid);
        r[32] += bf_lo(v.x); r[33] += bf_hi(v.x); r[34] += bf_lo(v.y); r[35] += bf_hi(v.y);
      }
      const int row = mblk * 128 + wg * 64 + warp * 16 + (lane >> 2);
      bf16* o0 = out + (size_t)row * DM + nhalf * 256 + ks * 64 + 8 * q;
#pragma unroll
      for (int G = 0; G < 2; G++) {
        uint32_t a0 = pack_bf16(r[G * 16], r[G * 16 + 1]), a1 = pack_bf16(r[G * 16 + 4], r[G * 16 + 5]);
        uint32_t a2 = pack_bf16(r[G * 16 + 8], r[G * 16 + 9]), a3 = pack_bf16(r[G * 16 + 12], r[G * 16 + 13]);
        uint32_t b0 = pack_bf16(r[G * 16 + 2], r[G * 16 + 3]), b1 = pack_bf16(r[G * 16 + 6], r[G * 16 + 7]);
        uint32_t b2 = pack_bf16(r[G * 16 + 10], r[G * 16 + 11]), b3 = pack_bf16(r[G * 16 + 14], r[G * 16 + 15]);
        quad_transpose(a0, a1, a2, a3, q);
        quad_transpose(b0, b1, b2, b3, q);
        st_v4(o0 + G * 32, a0, a1, a2, a3);
        st_v4(o0 + 8 * DM + G * 32, b0, b1, b2, b3);
      }
      {
        uint32_t t0 = pack_bf16(r[32], r[33]), t1 = pack_bf16(r[34], r[35]), t2 = 0, t3 = 0;
        quad_transpose(t0, t1, t2, t3, q);
        if (q < 2) st_v4(out + (size_t)(row + q * 8) * DM + 512 + nhalf * 32 + ks * 8, t0, t1, t2, t3);
      }
    } else {
      cluster_arrive();
    }
    if (wg == 0) { TS(2, 1); TSC(2, 3); }
    cluster_wait();
  }
}

typedef CUresult (*EncFn)(CUtensorMap*, CUtensorMapDataType, cuuint32_t, void*, const cuuint64_t*, const cuuint64_t*, const cuuint32_t*,
                          const cuuint32_t*, CUtensorMapInterleave, CUtensorMapSwizzle, CUtensorMapL2promotion, CUtensorMapFloatOOBfill);

static void enc2d(EncFn enc, CUtensorMap* m, const void* ptr, uint64_t cols, uint64_t rows, uint32_t bc, uint32_t br,
                  CUtensorMapSwizzle sw = CU_TENSOR_MAP_SWIZZLE_128B) {
  cuuint64_t gd[2] = {cols, rows}, gs[1] = {cols * 2};
  cuuint32_t bx[2] = {bc, br}, es[2] = {1, 1};
  enc(m, CU_TENSOR_MAP_DATA_TYPE_BFLOAT16, 2, const_cast<void*>(ptr), gd, gs, bx, es, CU_TENSOR_MAP_INTERLEAVE_NONE, sw,
      CU_TENSOR_MAP_L2_PROMOTION_L2_256B, CU_TENSOR_MAP_FLOAT_OOB_FILL_NONE);
}
static void enc3d(EncFn enc, CUtensorMap* m, const void* ptr, uint64_t cols, uint64_t rows, uint32_t br, uint32_t bch) {
  cuuint64_t gd[3] = {64, rows, cols / 64}, gs[2] = {cols * 2, 128};
  cuuint32_t bx[3] = {64, br, bch}, es[3] = {1, 1, 1};
  enc(m, CU_TENSOR_MAP_DATA_TYPE_BFLOAT16, 3, const_cast<void*>(ptr), gd, gs, bx, es, CU_TENSOR_MAP_INTERLEAVE_NONE,
      CU_TENSOR_MAP_SWIZZLE_128B, CU_TENSOR_MAP_L2_PROMOTION_L2_256B, CU_TENSOR_MAP_FLOAT_OOB_FILL_NONE);
}

static int g_sched[10] = {11, 10, 7, 4, 4, 5, 6, 6, 8, 20};
static void build_k1_jobs(Params& p) {
  int cnt[NCLUSTER];
  for (int c = 0; c < NCLUSTER; c++) {
    cnt[c] = 0;
    for (int i = 0; i < K1_MAXJOBS; i++) p.jobs[c][i] = 0;
  }
  auto add = [&](int c, int nch, int a_sel, int mp, int w_sel, int chunk0) {
    p.jobs[c][cnt[c]++] = (uint16_t)((nch - 1) | (a_sel << 2) | (mp << 3) | (w_sel << 6) | (chunk0 << 8));
  };
  const int *cg = g_sched, *xg = g_sched + 4;
  for (int mp = 0; mp < 8; mp++) {
    int k = 0;
    for (int i = 0; i < K1_MAXJOBS; i++)
      for (int g = 0; g < 4; g++)
        if (i < cg[g]) { add(g * 8 + mp, 4, 0, mp, k & 1, (k >> 1) * 4); k++; }
    k = 0;
    for (int i = 0; i < K1_MAXJOBS; i++)
      for (int g = 0; g < 4; g++)
        if (i < xg[g]) {
          if (k < 7) add((4 + g) * 8 + mp, k == 0 ? 3 : 4, 1, mp, 2, k == 0 ? 24 : (k - 1) * 4);
          else add((4 + g) * 8 + mp, 4, 1, mp, 3, (k - 7) * 4);
          k++;
        }
    add(64 + mp / 4, 4, 1, mp, 3, 14 * 4);
    add(64 + mp / 4, 4, 1, mp, 3, 15 * 4);
  }
  for (int cc = 0; cc < NCLUSTER; cc++)
    for (int i = 0; i < cnt[cc]; i++) {
      const int key = p.jobs[cc][i] & 0x3C;
      if (i == 0 || (p.jobs[cc][i - 1] & 0x3C) != key) p.jobs[cc][i] |= (1 << 14);
      if (i == cnt[cc] - 1 || (p.jobs[cc][i + 1] & 0x3C) != key) p.jobs[cc][i] |= (1 << 15);
    }
}

static void build_k2_items(Params& p) {
  int n = 0;
  const int SCHED_N1 = g_sched[8], SCHED_N2 = g_sched[9];
  for (int j = 7; j >= 0; j--)
    for (int h = 0; h < SCHED_N1; h++) p.order[n++] = (uint8_t)(h * 8 + j);
  for (int j = 7; j >= 4; j--)
    for (int h = SCHED_N1; h < SCHED_N2; h++) p.order[n++] = (uint8_t)(h * 8 + j);
  for (int j = 7; j >= 0; j--)
    for (int h = SCHED_N1; h < 32; h++)
      if (!(h < SCHED_N2 && j >= 4)) p.order[n++] = (uint8_t)(h * 8 + j);
}

extern "C" void kernel_launch(void* const* d_in, const int* in_sizes, int n_in, void* d_out, int out_size) {
  const bf16* x = (const bf16*)d_in[0];
  const bf16* wqkv = (const bf16*)d_in[1];
  const bf16* wo = (const bf16*)d_in[2];
  const bf16* ckv = (const bf16*)d_in[4];
  const bf16* w_q = (const bf16*)d_in[5];
  const bf16* w_uk = (const bf16*)d_in[6];
  const bf16* w_uv = (const bf16*)d_in[7];
  const bf16* w_o = (const bf16*)d_in[8];
  const bf16* gate_w = (const bf16*)d_in[9];

  EncFn enc = nullptr;
  cudaDriverEntryPointQueryResult qr;
  cudaGetDriverEntryPoint("cuTensorMapEncodeTiled", (void**)&enc, cudaEnableDefault, &qr);
  void *pQ, *pK, *pV, *pCtx, *pQA;
  cudaGetSymbolAddress(&pQ, g_Q);
  cudaGetSymbolAddress(&pQA, g_QKVA);
  cudaGetSymbolAddress(&pK, g_K);
  cudaGetSymbolAddress(&pV, g_V);
  cudaGetSymbolAddress(&pCtx, g_ctx);

  static Params p;
  enc2d(enc, &p.tmA[0], ckv, DC, S_LEN, 64, 128);
  enc2d(enc, &p.tmA[1], x, DM, S_LEN, 64, 128);
  enc3d(enc, &p.tmW[0], w_uk, HDIM, DC, 16, 4);
  enc3d(enc, &p.tmW[1], w_uv, HDIM, DC, 16, 4);
  enc3d(enc, &p.tmW[2], wqkv, NQKVA, DM, 16, 4);
  enc3d(enc, &p.tmW[3], w_q, HDIM, DM, 16, 4);
  build_k1_jobs(p);
  enc2d(enc, &p.tmQ, pQ, HDIM, S_LEN, 64, 128);
  enc2d(enc, &p.tmK, pK, HDIM, S_LEN, 64, 128);
  enc2d(enc, &p.tmV, pV, HDIM, S_LEN, 64, 128);
  build_k2_items(p);
  for (int i = 0; i < 2; i++) {
    cuuint64_t gd[3] = {64, 27, S_LEN}, gs[2] = {128, NQKVA * 2};
    cuuint32_t bx[3] = {64, 9, i ? 16u : 30u}, es[3] = {1, 1, 1};
    enc(&p.tmL[i], CU_TENSOR_MAP_DATA_TYPE_BFLOAT16, 3, pQA, gd, gs, bx, es, CU_TENSOR_MAP_INTERLEAVE_NONE, CU_TENSOR_MAP_SWIZZLE_NONE,
        CU_TENSOR_MAP_L2_PROMOTION_L2_256B, CU_TENSOR_MAP_FLOAT_OOB_FILL_NONE);
  }
  enc2d(enc, &p.tmC, pCtx, KCAT, S_LEN, 64, 128);
  enc3d(enc, &p.tmO[0], w_o, DM, HDIM, 32, 4);
  enc3d(enc, &p.tmO[1], wo, DM, DM, 32, 4);
  enc2d(enc, &p.tmOt[0], w_o, DM, HDIM, 32, 32, CU_TENSOR_MAP_SWIZZLE_64B);
  enc2d(enc, &p.tmOt[1], wo, DM, DM, 32, 32, CU_TENSOR_MAP_SWIZZLE_64B);

  cudaFuncSetAttribute(fused_kernel, cudaFuncAttributeMaxDynamicSharedMemorySize, SMEM_BYTES);
  fused_kernel<<<NCLUSTER * 2, 384, SMEM_BYTES>>>(p, x, gate_w, (bf16*)d_out);
}
```

```cpp
#include <cuda_runtime.h>
#include <cuda_bf16.h>
#include <cuda.h>
#include <stdint.h>

typedef __nv_bfloat16 bf16;

constexpr int S_LEN = 2048, DM = 576, DC = 512, HDIM = 4096, NQKVA = 1728, KCAT = 4672;
constexpr int NCLUSTER = 66;

__device__ __align__(1024) bf16 g_Q[S_LEN * HDIM];
__device__ __align__(1024) bf16 g_K[S_LEN * HDIM];
__device__ __align__(1024) bf16 g_V[S_LEN * HDIM];
__device__ __align__(1024) bf16 g_QKVA[S_LEN * NQKVA + 64];
__device__ __align__(1024) bf16 g_ctx[S_LEN * KCAT];
__device__ float g_gate[S_LEN];
__device__ __align__(1024) uint4 g_part[32 * 4 * 4 * 5 * 256];
__device__ __align__(16) unsigned int g_sync[400];
constexpr int F_QKVA = 0, F_HP = 16, F_CTX = 32, F_OA = 48, F_GATE = 96, F_TICK = 97, F_DONE = 98, F_XCH = 128, F_EPOCH = 384;

__device__ __forceinline__ uint32_t smem_u32(const void* p) { return (uint32_t)__cvta_generic_to_shared(p); }
__device__ __forceinline__ void mbar_init(uint32_t a, uint32_t c) {
  asm volatile("mbarrier.init.shared::cta.b64 [%0], %1;" ::"r"(a), "r"(c));
}
__device__ __forceinline__ void mbar_expect(uint32_t a, uint32_t b) {
  asm volatile("mbarrier.arrive.expect_tx.shared::cta.b64 _, [%0], %1;" ::"r"(a), "r"(b) : "memory");
}
#define TS(k, i)
#define TSC(k, i)
#define TSM(k)
#define BSEG(i)
#define SPIN_LIMIT "4194304"
__device__ __forceinline__ void mbar_wait(uint32_t a, uint32_t parity) {
  asm volatile(
      "{\n.reg .pred p;\n.reg .u32 n;\n"
      "mbarrier.try_wait.parity.shared::cta.b64 p, [%0], %1;\n"
      "@p bra DONE;\n"
      "mov.u32 n, 0;\n"
      "LOOP:\n"
      "mbarrier.try_wait.parity.shared::cta.b64 p, [%0], %1;\n"
      "@p bra DONE;\n"
      "add.u32 n, n, 1;\n"
      "setp.lt.u32 p, n, " SPIN_LIMIT ";\n"
      "@p bra LOOP;\n"
      "DONE:\n}" ::"r"(a), "r"(parity) : "memory");
}
__device__ __forceinline__ void mbar_arrive(uint32_t a) {
  asm volatile("mbarrier.arrive.shared::cta.b64 _, [%0];" ::"r"(a) : "memory");
}
__device__ __forceinline__ void mbar_arrive_cluster(uint32_t a, uint32_t cta) {
  asm volatile("{\n.reg .b32 r;\nmapa.shared::cluster.u32 r, %0, %1;\nmbarrier.arrive.shared::cluster.b64 _, [r];\n}" ::"r"(a),
               "r"(cta) : "memory");
}
__device__ __forceinline__ void mbar_arrive_cluster_if(uint32_t a, uint32_t cta, bool pred) {
  asm volatile("{\n.reg .b32 r;\n.reg .pred p;\nsetp.ne.u32 p, %2, 0;\nmapa.shared::cluster.u32 r, %0, %1;\n@p mbarrier.arrive.shared::cluster.b64 _, [r];\n}" ::"r"(a),
               "r"(cta), "r"((uint32_t)pred) : "memory");
}
__device__ __forceinline__ void mbar_arrive_cluster_after(uint32_t a, uint32_t cta, bool pred, float anchor) {
  asm volatile("{\n.reg .b32 r;\n.reg .pred p;\nsetp.ne.u32 p, %2, 0;\nsetp.leu.and.f32 p, %3, 0f7F800000, p;\n"
               "mapa.shared::cluster.u32 r, %0, %1;\n@p mbarrier.arrive.shared::cluster.b64 _, [r];\n}" ::"r"(a),
               "r"(cta), "r"((uint32_t)pred), "f"(anchor) : "memory");
}
__device__ __forceinline__ void mbar_arrive_if(uint32_t a, bool pred) {
  asm volatile("{\n.reg .pred p;\nsetp.ne.u32 p, %1, 0;\n@p mbarrier.arrive.shared::cta.b64 _, [%0];\n}" ::"r"(a), "r"((uint32_t)pred) : "memory");
}
__device__ __forceinline__ void tma2d(uint32_t dst, const CUtensorMap* m, uint32_t bar, int c0, int c1) {
  asm volatile("cp.async.bulk.tensor.2d.shared::cluster.global.mbarrier::complete_tx::bytes [%0], [%1, {%3, %4}], [%2];" ::"r"(dst),
               "l"(m), "r"(bar), "r"(c0), "r"(c1) : "memory");
}
__device__ __forceinline__ void tma2d_mc(uint32_t dst, const CUtensorMap* m, uint32_t bar, int c0, int c1, uint16_t mask) {
  asm volatile(
      "cp.async.bulk.tensor.2d.shared::cluster.global.mbarrier::complete_tx::bytes.multicast::cluster [%0], [%1, {%3, %4}], [%2], %5;" ::"r"(dst),
      "l"(m), "r"(bar), "r"(c0), "r"(c1), "h"(mask) : "memory");
}
__device__ __forceinline__ void tma3d_mc(uint32_t dst, const CUtensorMap* m, uint32_t bar, int c0, int c1, int c2, uint16_t mask) {
  asm volatile(
      "cp.async.bulk.tensor.3d.shared::cluster.global.mbarrier::complete_tx::bytes.multicast::cluster [%0], [%1, {%3, %4, %5}], [%2], %6;" ::"r"(dst),
      "l"(m), "r"(bar), "r"(c0), "r"(c1), "r"(c2), "h"(mask) : "memory");
}
__device__ __forceinline__ uint64_t policy_evict_first() {
  uint64_t p;
  asm volatile("createpolicy.fractional.L2::evict_first.b64 %0, 1.0;" : "=l"(p));
  return p;
}
__device__ __forceinline__ void tma3d_mc_h(uint32_t dst, const CUtensorMap* m, uint32_t bar, int c0, int c1, int c2, uint16_t mask, uint64_t pol) {
  asm volatile(
      "cp.async.bulk.tensor.3d.shared::cluster.global.mbarrier::complete_tx::bytes.multicast::cluster.L2::cache_hint [%0], [%1, {%3, %4, %5}], [%2], %6, %7;" ::"r"(dst),
      "l"(m), "r"(bar), "r"(c0), "r"(c1), "r"(c2), "h"(mask), "l"(pol) : "memory");
}
__device__ __forceinline__ void tma2d_h(uint32_t dst, const CUtensorMap* m, uint32_t bar, int c0, int c1, uint64_t pol) {
  asm volatile("cp.async.bulk.tensor.2d.shared::cluster.global.mbarrier::complete_tx::bytes.L2::cache_hint [%0], [%1, {%3, %4}], [%2], %5;" ::"r"(dst),
               "l"(m), "r"(bar), "r"(c0), "r"(c1), "l"(pol) : "memory");
}
__device__ __forceinline__ void tma3d(uint32_t dst, const CUtensorMap* m, uint32_t bar, int c0, int c1, int c2) {
  asm volatile(
      "cp.async.bulk.tensor.3d.shared::cluster.global.mbarrier::complete_tx::bytes [%0], [%1, {%3, %4, %5}], [%2];" ::"r"(dst),
      "l"(m), "r"(bar), "r"(c0), "r"(c1), "r"(c2) : "memory");
}
__device__ __forceinline__ void tma_pf2d(const CUtensorMap* m, int c0, int c1) {
  asm volatile("cp.async.bulk.prefetch.tensor.2d.L2.global [%0, {%1, %2}];" ::"l"(m), "r"(c0), "r"(c1) : "memory");
}
__device__ __forceinline__ void tma_pf3d(const CUtensorMap* m, int c0, int c1, int c2) {
  asm volatile("cp.async.bulk.prefetch.tensor.3d.L2.global [%0, {%1, %2, %3}];" ::"l"(m), "r"(c0), "r"(c1), "r"(c2) : "memory");
}
__device__ __forceinline__ void prefetch_tmap(const CUtensorMap* m) {
  asm volatile("prefetch.tensormap [%0];" ::"l"(m) : "memory");
}
__device__ __forceinline__ void cluster_arrive() { asm volatile("barrier.cluster.arrive.relaxed.aligned;" ::: "memory"); }
__device__ __forceinline__ void cluster_wait() { asm volatile("barrier.cluster.wait.aligned;" ::: "memory"); }
__device__ __forceinline__ void cluster_sync() {
  cluster_arrive();
  cluster_wait();
}
__device__ __forceinline__ uint32_t cluster_rank() {
  uint32_t r;
  asm volatile("mov.u32 %0, %%cluster_ctarank;" : "=r"(r));
  return r;
}
__device__ __forceinline__ bool elect_one() {
  uint32_t p;
  asm volatile("{\n.reg .pred q;\nelect.sync _|q, 0xffffffff;\nselp.u32 %0, 1, 0, q;\n}" : "=r"(p));
  return p;
}
__device__ __forceinline__ void pdl_wait() { asm volatile("griddepcontrol.wait;" ::: "memory"); }
__device__ __forceinline__ void pdl_launch() { asm volatile("griddepcontrol.launch_dependents;" ::: "memory"); }
__device__ __forceinline__ void ldsm_x4(uint32_t& r0, uint32_t& r1, uint32_t& r2, uint32_t& r3, uint32_t addr) {
  asm volatile("ldmatrix.sync.aligned.m8n8.x4.shared.b16 {%0, %1, %2, %3}, [%4];" : "=r"(r0), "=r"(r1), "=r"(r2), "=r"(r3) : "r"(addr) : "memory");
}
__device__ __forceinline__ void wg_fence() { asm volatile("wgmma.fence.sync.aligned;" ::: "memory"); }
__device__ __forceinline__ void wg_commit() { asm volatile("wgmma.commit_group.sync.aligned;" ::: "memory"); }
template <int N>
__device__ __forceinline__ void wg_wait() { asm volatile("wgmma.wait_group.sync.aligned %0;" ::"n"(N) : "memory"); }
template <int N>
__device__ __forceinline__ void reg_alloc() { asm volatile("setmaxnreg.inc.sync.aligned.u32 %0;" ::"n"(N)); }
template <int N>
__device__ __forceinline__ void reg_dealloc() { asm volatile("setmaxnreg.dec.sync.aligned.u32 %0;" ::"n"(N)); }
__device__ __forceinline__ void bar_sync(int id, int n) { asm volatile("bar.sync %0, %1;" ::"r"(id), "r"(n) : "memory"); }
__device__ __forceinline__ void bar_arrive(int id, int n) { asm volatile("bar.arrive %0, %1;" ::"r"(id), "r"(n) : "memory"); }
template <int NT>
__device__ __forceinline__ void fence_regs(float (&d)[NT]) {
#pragma unroll
  for (int i = 0; i < NT; i++) asm volatile("" : "+f"(d[i])::"memory");
}
template <int NT>
__device__ __forceinline__ void fence_regs(uint32_t (&d)[NT]) {
#pragma unroll
  for (int i = 0; i < NT; i++) asm volatile("" : "+r"(d[i])::"memory");
}
__device__ __forceinline__ uint64_t make_desc(uint32_t saddr, uint32_t lbo, uint32_t sbo, uint32_t layout) {
  return (uint64_t)((saddr & 0x3FFFF) >> 4) | ((uint64_t)(lbo >> 4) << 16) | ((uint64_t)(sbo >> 4) << 32) | ((uint64_t)layout << 62);
}
__device__ __forceinline__ uint32_t pack_bf16(float lo, float hi) {
  uint32_t r;
  asm("cvt.rn.bf16x2.f32 %0, %1, %2;" : "=r"(r) : "f"(hi), "f"(lo));
  return r;
}
__device__ __forceinline__ float ex2(float x) {
  float r;
  asm("ex2.approx.ftz.f32 %0, %1;" : "=f"(r) : "f"(x));
  return r;
}
__device__ __forceinline__ void st_v4(void* p, uint32_t a, uint32_t b, uint32_t c, uint32_t d) {
#define ST_MOD ".cs"
  asm volatile("st.global" ST_MOD ".v4.b32 [%0], {%1, %2, %3, %4};" ::"l"(p), "r"(a), "r"(b), "r"(c), "r"(d) : "memory");
}
#define STA_MOD ".cs"
__device__ __forceinline__ void st_v4a(void* p, uint32_t a, uint32_t b, uint32_t c, uint32_t d) {
  asm volatile("st.global" STA_MOD ".v4.b32 [%0], {%1, %2, %3, %4};" ::"l"(p), "r"(a), "r"(b), "r"(c), "r"(d) : "memory");
}
__device__ __forceinline__ float bf_lo(uint32_t v) { return __uint_as_float(v << 16); }
__device__ __forceinline__ float bf_hi(uint32_t v) { return __uint_as_float(v & 0xFFFF0000u); }

__device__ __forceinline__ void quad_transpose(uint32_t& a0, uint32_t& a1, uint32_t& a2, uint32_t& a3, int q) {
  const bool o1 = q & 1, o2 = q & 2;
  uint32_t t0 = o1 ? a0 : a1, t1 = o1 ? a2 : a3;
  t0 = __shfl_xor_sync(0xffffffffu, t0, 1);
  t1 = __shfl_xor_sync(0xffffffffu, t1, 1);
  if (o1) { a0 = t0; a2 = t1; } else { a1 = t0; a3 = t1; }
  t0 = o2 ? a0 : a2;
  t1 = o2 ? a1 : a3;
  t0 = __shfl_xor_sync(0xffffffffu, t0, 2);
  t1 = __shfl_xor_sync(0xffffffffu, t1, 2);
  if (o2) { a0 = t0; a1 = t1; } else { a2 = t0; a3 = t1; }
}

template<int TB, int OFF, int NT>
__device__ __forceinline__ void wgmma_ss_n256(float (&d)[NT], uint64_t da, uint64_t db, int scale_d) {
  asm volatile("{\n.reg .pred p;\nsetp.ne.b32 p, %130, 0;\n"
    "wgmma.mma_async.sync.aligned.m64n256k16.f32.bf16.bf16 {%0, %1, %2, %3, %4, %5, %6, %7, %8, %9, %10, %11, %12, %13, %14, %15, %16, %17, %18, %19, %20, %21, %22, %23, %24, %25, %26, %27, %28, %29, %30, %31, %32, %33, %34, %35, %36, %37, %38, %39, %40, %41, %42, %43, %44, %45, %46, %47, %48, %49, %50, %51, %52, %53, %54, %55, %56, %57, %58, %59, %60, %61, %62, %63, %64, %65, %66, %67, %68, %69, %70, %71, %72, %73, %74, %75, %76, %77, %78, %79, %80, %81, %82, %83, %84, %85, %86, %87, %88, %89, %90, %91, %92, %93, %94, %95, %96, %97, %98, %99, %100, %101, %102, %103, %104, %105, %106, %107, %108, %109, %110, %111, %112, %113, %114, %115, %116, %117, %118, %119, %120, %121, %122, %123, %124, %125, %126, %127}, %128, %129, p, 1, 1, 0, %131;\n}\n"
    : "+f"(d[OFF+0]), "+f"(d[OFF+1]), "+f"(d[OFF+2]), "+f"(d[OFF+3]), "+f"(d[OFF+4]), "+f"(d[OFF+5]), "+f"(d[OFF+6]), "+f"(d[OFF+7]), "+f"(d[OFF+8]), "+f"(d[OFF+9]), "+f"(d[OFF+10]), "+f"(d[OFF+11]), "+f"(d[OFF+12]), "+f"(d[OFF+13]), "+f"(d[OFF+14]), "+f"(d[OFF+15]), "+f"(d[OFF+16]), "+f"(d[OFF+17]), "+f"(d[OFF+18]), "+f"(d[OFF+19]), "+f"(d[OFF+20]), "+f"(d[OFF+21]), "+f"(d[OFF+22]), "+f"(d[OFF+23]), "+f"(d[OFF+24]), "+f"(d[OFF+25]), "+f"(d[OFF+26]), "+f"(d[OFF+27]), "+f"(d[OFF+28]), "+f"(d[OFF+29]), "+f"(d[OFF+30]), "+f"(d[OFF+31]), "+f"(d[OFF+32]), "+f"(d[OFF+33]), "+f"(d[OFF+34]), "+f"(d[OFF+35]), "+f"(d[OFF+36]), "+f"(d[OFF+37]), "+f"(d[OFF+38]), "+f"(d[OFF+39]), "+f"(d[OFF+40]), "+f"(d[OFF+41]), "+f"(d[OFF+42]), "+f"(d[OFF+43]), "+f"(d[OFF+44]), "+f"(d[OFF+45]), "+f"(d[OFF+46]), "+f"(d[OFF+47]), "+f"(d[OFF+48]), "+f"(d[OFF+49]), "+f"(d[OFF+50]), "+f"(d[OFF+51]), "+f"(d[OFF+52]), "+f"(d[OFF+53]), "+f"(d[OFF+54]), "+f"(d[OFF+55]), "+f"(d[OFF+56]), "+f"(d[OFF+57]), "+f"(d[OFF+58]), "+f"(d[OFF+59]), "+f"(d[OFF+60]), "+f"(d[OFF+61]), "+f"(d[OFF+62]), "+f"(d[OFF+63]), "+f"(d[OFF+64]), "+f"(d[OFF+65]), "+f"(d[OFF+66]), "+f"(d[OFF+67]), "+f"(d[OFF+68]), "+f"(d[OFF+69]), "+f"(d[OFF+70]), "+f"(d[OFF+71]), "+f"(d[OFF+72]), "+f"(d[OFF+73]), "+f"(d[OFF+74]), "+f"(d[OFF+75]), "+f"(d[OFF+76]), "+f"(d[OFF+77]), "+f"(d[OFF+78]), "+f"(d[OFF+79]), "+f"(d[OFF+80]), "+f"(d[OFF+81]), "+f"(d[OFF+82]), "+f"(d[OFF+83]), "+f"(d[OFF+84]), "+f"(d[OFF+85]), "+f"(d[OFF+86]), "+f"(d[OFF+87]), "+f"(d[OFF+88]), "+f"(d[OFF+89]), "+f"(d[OFF+90]), "+f"(d[OFF+91]), "+f"(d[OFF+92]), "+f"(d[OFF+93]), "+f"(d[OFF+94]), "+f"(d[OFF+95]), "+f"(d[OFF+96]), "+f"(d[OFF+97]), "+f"(d[OFF+98]), "+f"(d[OFF+99]), "+f"(d[OFF+100]), "+f"(d[OFF+101]), "+f"(d[OFF+102]), "+f"(d[OFF+103]), "+f"(d[OFF+104]), "+f"(d[OFF+105]), "+f"(d[OFF+106]), "+f"(d[OFF+107]), "+f"(d[OFF+108]), "+f"(d[OFF+109]), "+f"(d[OFF+110]), "+f"(d[OFF+111]), "+f"(d[OFF+112]), "+f"(d[OFF+113]), "+f"(d[OFF+114]), "+f"(d[OFF+115]), "+f"(d[OFF+116]), "+f"(d[OFF+117]), "+f"(d[OFF+118]), "+f"(d[OFF+119]), "+f"(d[OFF+120]), "+f"(d[OFF+121]), "+f"(d[OFF+122]), "+f"(d[OFF+123]), "+f"(d[OFF+124]), "+f"(d[OFF+125]), "+f"(d[OFF+126]), "+f"(d[OFF+127])
    : "l"(da), "l"(db), "r"(scale_d), "n"(TB));
}
template<int TB, int OFF, int NT>
__device__ __forceinline__ void wgmma_ss_n192(float (&d)[NT], uint64_t da, uint64_t db, int scale_d) {
  asm volatile("{\n.reg .pred p;\nsetp.ne.b32 p, %98, 0;\n"
    "wgmma.mma_async.sync.aligned.m64n192k16.f32.bf16.bf16 {%0, %1, %2, %3, %4, %5, %6, %7, %8, %9, %10, %11, %12, %13, %14, %15, %16, %17, %18, %19, %20, %21, %22, %23, %24, %25, %26, %27, %28, %29, %30, %31, %32, %33, %34, %35, %36, %37, %38, %39, %40, %41, %42, %43, %44, %45, %46, %47, %48, %49, %50, %51, %52, %53, %54, %55, %56, %57, %58, %59, %60, %61, %62, %63, %64, %65, %66, %67, %68, %69, %70, %71, %72, %73, %74, %75, %76, %77, %78, %79, %80, %81, %82, %83, %84, %85, %86, %87, %88, %89, %90, %91, %92, %93, %94, %95}, %96, %97, p, 1, 1, 0, %99;\n}\n"
    : "+f"(d[OFF+0]), "+f"(d[OFF+1]), "+f"(d[OFF+2]), "+f"(d[OFF+3]), "+f"(d[OFF+4]), "+f"(d[OFF+5]), "+f"(d[OFF+6]), "+f"(d[OFF+7]), "+f"(d[OFF+8]), "+f"(d[OFF+9]), "+f"(d[OFF+10]), "+f"(d[OFF+11]), "+f"(d[OFF+12]), "+f"(d[OFF+13]), "+f"(d[OFF+14]), "+f"(d[OFF+15]), "+f"(d[OFF+16]), "+f"(d[OFF+17]), "+f"(d[OFF+18]), "+f"(d[OFF+19]), "+f"(d[OFF+20]), "+f"(d[OFF+21]), "+f"(d[OFF+22]), "+f"(d[OFF+23]), "+f"(d[OFF+24]), "+f"(d[OFF+25]), "+f"(d[OFF+26]), "+f"(d[OFF+27]), "+f"(d[OFF+28]), "+f"(d[OFF+29]), "+f"(d[OFF+30]), "+f"(d[OFF+31]), "+f"(d[OFF+32]), "+f"(d[OFF+33]), "+f"(d[OFF+34]), "+f"(d[OFF+35]), "+f"(d[OFF+36]), "+f"(d[OFF+37]), "+f"(d[OFF+38]), "+f"(d[OFF+39]), "+f"(d[OFF+40]), "+f"(d[OFF+41]), "+f"(d[OFF+42]), "+f"(d[OFF+43]), "+f"(d[OFF+44]), "+f"(d[OFF+45]), "+f"(d[OFF+46]), "+f"(d[OFF+47]), "+f"(d[OFF+48]), "+f"(d[OFF+49]), "+f"(d[OFF+50]), "+f"(d[OFF+51]), "+f"(d[OFF+52]), "+f"(d[OFF+53]), "+f"(d[OFF+54]), "+f"(d[OFF+55]), "+f"(d[OFF+56]), "+f"(d[OFF+57]), "+f"(d[OFF+58]), "+f"(d[OFF+59]), "+f"(d[OFF+60]), "+f"(d[OFF+61]), "+f"(d[OFF+62]), "+f"(d[OFF+63]), "+f"(d[OFF+64]), "+f"(d[OFF+65]), "+f"(d[OFF+66]), "+f"(d[OFF+67]), "+f"(d[OFF+68]), "+f"(d[OFF+69]), "+f"(d[OFF+70]), "+f"(d[OFF+71]), "+f"(d[OFF+72]), "+f"(d[OFF+73]), "+f"(d[OFF+74]), "+f"(d[OFF+75]), "+f"(d[OFF+76]), "+f"(d[OFF+77]), "+f"(d[OFF+78]), "+f"(d[OFF+79]), "+f"(d[OFF+80]), "+f"(d[OFF+81]), "+f"(d[OFF+82]), "+f"(d[OFF+83]), "+f"(d[OFF+84]), "+f"(d[OFF+85]), "+f"(d[OFF+86]), "+f"(d[OFF+87]), "+f"(d[OFF+88]), "+f"(d[OFF+89]), "+f"(d[OFF+90]), "+f"(d[OFF+91]), "+f"(d[OFF+92]), "+f"(d[OFF+93]), "+f"(d[OFF+94]), "+f"(d[OFF+95])
    : "l"(da), "l"(db), "r"(scale_d), "n"(TB));
}
template<int TB, int OFF, int NT>
__device__ __forceinline__ void wgmma_ss_n128(float (&d)[NT], uint64_t da, uint64_t db, int scale_d) {
  asm volatile("{\n.reg .pred p;\nsetp.ne.b32 p, %66, 0;\n"
    "wgmma.mma_async.sync.aligned.m64n128k16.f32.bf16.bf16 {%0, %1, %2, %3, %4, %5, %6, %7, %8, %9, %10, %11, %12, %13, %14, %15, %16, %17, %18, %19, %20, %21, %22, %23, %24, %25, %26, %27, %28, %29, %30, %31, %32, %33, %34, %35, %36, %37, %38, %39, %40, %41, %42, %43, %44, %45, %46, %47, %48, %49, %50, %51, %52, %53, %54, %55, %56, %57, %58, %59, %60, %61, %62, %63}, %64, %65, p, 1, 1, 0, %67;\n}\n"
    : "+f"(d[OFF+0]), "+f"(d[OFF+1]), "+f"(d[OFF+2]), "+f"(d[OFF+3]), "+f"(d[OFF+4]), "+f"(d[OFF+5]), "+f"(d[OFF+6]), "+f"(d[OFF+7]), "+f"(d[OFF+8]), "+f"(d[OFF+9]), "+f"(d[OFF+10]), "+f"(d[OFF+11]), "+f"(d[OFF+12]), "+f"(d[OFF+13]), "+f"(d[OFF+14]), "+f"(d[OFF+15]), "+f"(d[OFF+16]), "+f"(d[OFF+17]), "+f"(d[OFF+18]), "+f"(d[OFF+19]), "+f"(d[OFF+20]), "+f"(d[OFF+21]), "+f"(d[OFF+22]), "+f"(d[OFF+23]), "+f"(d[OFF+24]), "+f"(d[OFF+25]), "+f"(d[OFF+26]), "+f"(d[OFF+27]), "+f"(d[OFF+28]), "+f"(d[OFF+29]), "+f"(d[OFF+30]), "+f"(d[OFF+31]), "+f"(d[OFF+32]), "+f"(d[OFF+33]), "+f"(d[OFF+34]), "+f"(d[OFF+35]), "+f"(d[OFF+36]), "+f"(d[OFF+37]), "+f"(d[OFF+38]), "+f"(d[OFF+39]), "+f"(d[OFF+40]), "+f"(d[OFF+41]), "+f"(d[OFF+42]), "+f"(d[OFF+43]), "+f"(d[OFF+44]), "+f"(d[OFF+45]), "+f"(d[OFF+46]), "+f"(d[OFF+47]), "+f"(d[OFF+48]), "+f"(d[OFF+49]), "+f"(d[OFF+50]), "+f"(d[OFF+51]), "+f"(d[OFF+52]), "+f"(d[OFF+53]), "+f"(d[OFF+54]), "+f"(d[OFF+55]), "+f"(d[OFF+56]), "+f"(d[OFF+57]), "+f"(d[OFF+58]), "+f"(d[OFF+59]), "+f"(d[OFF+60]), "+f"(d[OFF+61]), "+f"(d[OFF+62]), "+f"(d[OFF+63])
    : "l"(da), "l"(db), "r"(scale_d), "n"(TB));
}
template<int TB, int OFF, int NT>
__device__ __forceinline__ void wgmma_ss_n32(float (&d)[NT], uint64_t da, uint64_t db, int scale_d) {
  asm volatile("{\n.reg .pred p;\nsetp.ne.b32 p, %18, 0;\n"
    "wgmma.mma_async.sync.aligned.m64n32k16.f32.bf16.bf16 {%0, %1, %2, %3, %4, %5, %6, %7, %8, %9, %10, %11, %12, %13, %14, %15}, %16, %17, p, 1, 1, 0, %19;\n}\n"
    : "+f"(d[OFF+0]), "+f"(d[OFF+1]), "+f"(d[OFF+2]), "+f"(d[OFF+3]), "+f"(d[OFF+4]), "+f"(d[OFF+5]), "+f"(d[OFF+6]), "+f"(d[OFF+7]), "+f"(d[OFF+8]), "+f"(d[OFF+9]), "+f"(d[OFF+10]), "+f"(d[OFF+11]), "+f"(d[OFF+12]), "+f"(d[OFF+13]), "+f"(d[OFF+14]), "+f"(d[OFF+15])
    : "l"(da), "l"(db), "r"(scale_d), "n"(TB));
}
template<int TB, int OFF, int NT>
__device__ __forceinline__ void wgmma_rs_n128(float (&d)[NT], uint32_t a0, uint32_t a1, uint32_t a2, uint32_t a3, uint64_t db, int scale_d) {
  asm volatile("{\n.reg .pred p;\nsetp.ne.b32 p, %69, 0;\n"
    "wgmma.mma_async.sync.aligned.m64n128k16.f32.bf16.bf16 {%0, %1, %2, %3, %4, %5, %6, %7, %8, %9, %10, %11, %12, %13, %14, %15, %16, %17, %18, %19, %20, %21, %22, %23, %24, %25, %26, %27, %28, %29, %30, %31, %32, %33, %34, %35, %36, %37, %38, %39, %40, %41, %42, %43, %44, %45, %46, %47, %48, %49, %50, %51, %52, %53, %54, %55, %56, %57, %58, %59, %60, %61, %62, %63}, {%64, %65, %66, %67}, %68, p, 1, 1, %70;\n}\n"
    : "+f"(d[OFF+0]), "+f"(d[OFF+1]), "+f"(d[OFF+2]), "+f"(d[OFF+3]), "+f"(d[OFF+4]), "+f"(d[OFF+5]), "+f"(d[OFF+6]), "+f"(d[OFF+7]), "+f"(d[OFF+8]), "+f"(d[OFF+9]), "+f"(d[OFF+10]), "+f"(d[OFF+11]), "+f"(d[OFF+12]), "+f"(d[OFF+13]), "+f"(d[OFF+14]), "+f"(d[OFF+15]), "+f"(d[OFF+16]), "+f"(d[OFF+17]), "+f"(d[OFF+18]), "+f"(d[OFF+19]), "+f"(d[OFF+20]), "+f"(d[OFF+21]), "+f"(d[OFF+22]), "+f"(d[OFF+23]), "+f"(d[OFF+24]), "+f"(d[OFF+25]), "+f"(d[OFF+26]), "+f"(d[OFF+27]), "+f"(d[OFF+28]), "+f"(d[OFF+29]), "+f"(d[OFF+30]), "+f"(d[OFF+31]), "+f"(d[OFF+32]), "+f"(d[OFF+33]), "+f"(d[OFF+34]), "+f"(d[OFF+35]), "+f"(d[OFF+36]), "+f"(d[OFF+37]), "+f"(d[OFF+38]), "+f"(d[OFF+39]), "+f"(d[OFF+40]), "+f"(d[OFF+41]), "+f"(d[OFF+42]), "+f"(d[OFF+43]), "+f"(d[OFF+44]), "+f"(d[OFF+45]), "+f"(d[OFF+46]), "+f"(d[OFF+47]), "+f"(d[OFF+48]), "+f"(d[OFF+49]), "+f"(d[OFF+50]), "+f"(d[OFF+51]), "+f"(d[OFF+52]), "+f"(d[OFF+53]), "+f"(d[OFF+54]), "+f"(d[OFF+55]), "+f"(d[OFF+56]), "+f"(d[OFF+57]), "+f"(d[OFF+58]), "+f"(d[OFF+59]), "+f"(d[OFF+60]), "+f"(d[OFF+61]), "+f"(d[OFF+62]), "+f"(d[OFF+63])
    : "r"(a0), "r"(a1), "r"(a2), "r"(a3), "l"(db), "r"(scale_d), "n"(TB));
}
template<int TB, int OFF, int NT>
__device__ __forceinline__ void wgmma_rs_n64(float (&d)[NT], uint32_t a0, uint32_t a1, uint32_t a2, uint32_t a3, uint64_t db, int scale_d) {
  asm volatile("{\n.reg .pred p;\nsetp.ne.b32 p, %37, 0;\n"
    "wgmma.mma_async.sync.aligned.m64n64k16.f32.bf16.bf16 {%0, %1, %2, %3, %4, %5, %6, %7, %8, %9, %10, %11, %12, %13, %14, %15, %16, %17, %18, %19, %20, %21, %22, %23, %24, %25, %26, %27, %28, %29, %30, %31}, {%32, %33, %34, %35}, %36, p, 1, 1, %38;\n}\n"
    : "+f"(d[OFF+0]), "+f"(d[OFF+1]), "+f"(d[OFF+2]), "+f"(d[OFF+3]), "+f"(d[OFF+4]), "+f"(d[OFF+5]), "+f"(d[OFF+6]), "+f"(d[OFF+7]), "+f"(d[OFF+8]), "+f"(d[OFF+9]), "+f"(d[OFF+10]), "+f"(d[OFF+11]), "+f"(d[OFF+12]), "+f"(d[OFF+13]), "+f"(d[OFF+14]), "+f"(d[OFF+15]), "+f"(d[OFF+16]), "+f"(d[OFF+17]), "+f"(d[OFF+18]), "+f"(d[OFF+19]), "+f"(d[OFF+20]), "+f"(d[OFF+21]), "+f"(d[OFF+22]), "+f"(d[OFF+23]), "+f"(d[OFF+24]), "+f"(d[OFF+25]), "+f"(d[OFF+26]), "+f"(d[OFF+27]), "+f"(d[OFF+28]), "+f"(d[OFF+29]), "+f"(d[OFF+30]), "+f"(d[OFF+31])
    : "r"(a0), "r"(a1), "r"(a2), "r"(a3), "l"(db), "r"(scale_d), "n"(TB));
}

__device__ __forceinline__ void wait_flag(const unsigned int* f, uint32_t target) {
  uint32_t v;
#pragma unroll 1
  for (uint32_t spins = 0; spins < (1u << 22); spins++) {
    asm volatile("ld.acquire.gpu.global.u32 %0, [%1];" : "=r"(v) : "l"(f) : "memory");
    if (v >= target) break;
    __nanosleep(100);
  }
}
__device__ __forceinline__ uint32_t lds32(uint32_t a) {
  uint32_t v;
  asm volatile("ld.shared.u32 %0, [%1];" : "=r"(v) : "r"(a) : "memory");
  return v;
}
__device__ __forceinline__ float gate_row(int row, int lane, const bf16* __restrict__ x, const bf16* __restrict__ gate_w) {
  const uint32_t* xr = reinterpret_cast<const uint32_t*>(x + (size_t)row * DM);
  const uint32_t* gw2 = reinterpret_cast<const uint32_t*>(gate_w);
  float gs = 0.f;
#pragma unroll
  for (int i = 0; i < 9; i++) {
    const uint32_t a = __ldg(xr + lane + 32 * i), b = __ldg(gw2 + lane + 32 * i);
    gs = fmaf(bf_lo(a), bf_lo(b), gs);
    gs = fmaf(bf_hi(a), bf_hi(b), gs);
  }
#pragma unroll
  for (int o = 16; o; o >>= 1) gs += __shfl_xor_sync(0xffffffffu, gs, o);
  const float g = 1.f / (1.f + __expf(-gs));
  if (lane == 0) g_gate[row] = g;
  return g;
}
#define LA_UNROLL 9
__device__ __forceinline__ void local_rows2(int rb, int ri, uint32_t sL, uint32_t bL2, int lane, float ga, float gb) {
  const float scale_l2 = 0.23570226039551584f * 1.4426950408889634f;
  constexpr int U = LA_UNROLL;
  const uint32_t sq = sL + (30 + ri) * 1152;
  const uint32_t kb = sL + (14 + ri) * 1152 + lane * 36;
  float ma = -INFINITY, mb = -INFINITY;
  {
    float qa[18], qb[18];
#pragma unroll
    for (int i = 0; i < 9; i++) {
      const uint32_t u = lds32(sq - 2304 + lane * 36 + 4 * i), v = lds32(sq + lane * 36 + 4 * i);
      qa[2 * i] = bf_lo(u); qa[2 * i + 1] = bf_hi(u);
      qb[2 * i] = bf_lo(v); qb[2 * i + 1] = bf_hi(v);
    }
    __syncwarp();
#pragma unroll U
    for (int t = 0; t < 9; t++) {
      const bool ok = rb - 2 * t >= 0;
      float a0 = 0.f, a1 = 0.f, b0 = 0.f, b1 = 0.f;
#pragma unroll
      for (int i = 0; i < 9; i++) {
        const uint32_t k = lds32(kb - t * 2304 + 4 * i);
        const float lo = bf_lo(k), hi = bf_hi(k);
        a0 = fmaf(qa[2 * i], lo, a0); a1 = fmaf(qa[2 * i + 1], hi, a1);
        b0 = fmaf(qb[2 * i], lo, b0); b1 = fmaf(qb[2 * i + 1], hi, b1);
      }
      a0 = (ok && t > 0) ? a0 + a1 : -INFINITY;
      b0 = (ok && t < 8) ? b0 + b1 : -INFINITY;
      ma = fmaxf(ma, a0);
      mb = fmaxf(mb, b0);
      asm volatile("st.shared.f32 [%0], %1;" ::"r"(sq - 2304 + t * 128 + lane * 4), "f"(a0) : "memory");
      asm volatile("st.shared.f32 [%0], %1;" ::"r"(sq + t * 128 + lane * 4), "f"(b0) : "memory");
    }
  }
  float oa[18], ob[18], sa = 0.f, sb = 0.f;
#pragma unroll
  for (int i = 0; i < 18; i++) { oa[i] = 0.f; ob[i] = 0.f; }
  mbar_wait(bL2, 0);
#pragma unroll U
  for (int t = 0; t < 9; t++) {
    const float wa = ex2((__uint_as_float(lds32(sq - 2304 + t * 128 + lane * 4)) - ma) * scale_l2);
    const float wb = ex2((__uint_as_float(lds32(sq + t * 128 + lane * 4)) - mb) * scale_l2);
    sa += wa;
    sb += wb;
#pragma unroll
    for (int i = 0; i < 9; i++) {
      const uint32_t v = lds32(kb + 46 * 1152 - t * 2304 + 4 * i);
      const float lo = bf_lo(v), hi = bf_hi(v);
      oa[2 * i] = fmaf(wa, lo, oa[2 * i]); oa[2 * i + 1] = fmaf(wa, hi, oa[2 * i + 1]);
      ob[2 * i] = fmaf(wb, lo, ob[2 * i]); ob[2 * i + 1] = fmaf(wb, hi, ob[2 * i + 1]);
    }
  }
  ga = __fdividef(ga, sa);
  gb = __fdividef(gb, sb);
  __syncwarp();
#pragma unroll
  for (int i = 0; i < 9; i++) {
    asm volatile("st.shared.u32 [%0], %1;" ::"r"(sq - 2304 + lane * 36 + 4 * i), "r"(pack_bf16(oa[2 * i] * ga, oa[2 * i + 1] * ga)) : "memory");
    asm volatile("st.shared.u32 [%0], %1;" ::"r"(sq + lane * 36 + 4 * i), "r"(pack_bf16(ob[2 * i] * gb, ob[2 * i + 1] * gb)) : "memory");
  }
  __syncwarp();
  uint32_t w[5][4];
#pragma unroll
  for (int t = 0; t < 5; t++) {
    const int c = min(t * 32 + lane, 143), r = c >= 72;
    asm volatile("ld.shared.v4.u32 {%0, %1, %2, %3}, [%4];" : "=r"(w[t][0]), "=r"(w[t][1]), "=r"(w[t][2]), "=r"(w[t][3])
                 : "r"(sq - 2304 + r * 2304 + (c - r * 72) * 16) : "memory");
  }
  asm volatile("fence.proxy.async.shared::cta;" ::: "memory");
  bar_arrive(4, 256 + 32);
#pragma unroll
  for (int t = 0; t < 5; t++) {
    const int c = min(t * 32 + lane, 143), r = c >= 72;
    st_v4(g_ctx + (size_t)(rb - 2 + 2 * r) * KCAT + HDIM + (c - r * 72) * 8, w[t][0], w[t][1], w[t][2], w[t][3]);
  }
}

#define K1_NST 6
constexpr int K1_BST = K1_NST;
constexpr int K1_MAXJOBS = 11;
constexpr uint32_t K1_FLAG_TARGET = 7;
constexpr uint32_t RDY_TARGET = 48;
constexpr uint32_t GATE_TARGET = 128 * 3;
struct alignas(64) Params {
  CUtensorMap tmA[2];
  CUtensorMap tmW[4];
  CUtensorMap tmQ, tmK, tmV;
  CUtensorMap tmL[2];
  CUtensorMap tmC, tmO[2], tmOt[2];
  uint16_t jobs[NCLUSTER][K1_MAXJOBS];
  uint8_t order[256];
  uint8_t unit[64][4];
};

struct K1State {
  uint32_t bs, bph, aph;
  bf16* pp;
  int pld8;
  int png;
};
__device__ __forceinline__ void k1_flag(const K1State& st, int lane, uint32_t bS) {
  if (st.png) {
    __syncwarp();
    if (lane == 0) mbar_arrive(bS);
  }
}

__device__ __forceinline__ void k1_tile(float (&acc)[128], uint32_t (&pk)[64], K1State& st, uint32_t job, uint32_t sA, uint32_t sB,
                                        uint32_t bAf, uint32_t bAe, uint32_t bBf, uint32_t bBe, uint32_t bS, int wg, int warp, int lane, uint32_t rank) {
  const int a_sel = (job >> 2) & 1, mpair = (job >> 3) & 7, w_sel = (job >> 6) & 3, chunk0 = (job >> 8) & 63;
  const bool newA = (job >> 14) & 1, lastA = (job >> 15) & 1;
  const bool sig = (lane == 0) && (warp < 2);
  const bool siga = lastA && (lane == 0) && (warp == 2);
  const int KC = 8 + a_sel;
  uint32_t prev_bs = 0, prev2_bs = 0, a8_bs = 0;
#pragma unroll
  for (int kc = 0; kc < 9; kc++) {
    if (kc >= KC) break;
    uint32_t abase = sA + ((kc + 2) & 7) * 16384;
    if (kc == 8) {
      mbar_wait(bBf + st.bs * 8, st.bph);
      a8_bs = st.bs;
      abase = sB + st.bs * 16384;
      if (++st.bs == K1_BST) { st.bs = 0; st.bph ^= 1; }
    } else if (newA) {
      mbar_wait(bAf + kc * 8, st.aph);
    }
    const uint64_t da = make_desc(abase + wg * 8192, 16, 1024, 1);
#pragma unroll
    for (int ks = 0; ks < 2; ks++) {
      mbar_wait(bBf + st.bs * 8, st.bph);
      const uint64_t db = make_desc(sB + st.bs * 16384, 2048, 1024, 1);
      wg_fence();
      wgmma_ss_n256<1, 0>(acc, da + (uint64_t)(ks * 4), db, (ks > 0) ? 1 : (kc > 0));
      wgmma_ss_n256<1, 0>(acc, da + (uint64_t)(ks * 4 + 2), db + (uint64_t)512, 1);
      wg_commit();
      const int PO = (kc < 8 ? kc : 0) * 8;
      wg_wait<1>();
      if (ks > 0 || kc > 0) {
        if (sig) mbar_arrive_cluster(bBe + prev_bs * 8, warp);
        if (ks == 0 && siga) mbar_arrive(bAe + (kc - 1) * 8);
      }
      if (kc < st.png) st_v4a(st.pp + kc * 32 + ks * st.pld8, pk[PO + ks * 4], pk[PO + ks * 4 + 1], pk[PO + ks * 4 + 2], pk[PO + ks * 4 + 3]);
      prev_bs = st.bs;
      if (++st.bs == K1_BST) { st.bs = 0; st.bph ^= 1; }
    }
  }
  if (newA) st.aph ^= 1;
  k1_flag(st, lane, bS);
  wg_wait<0>();
  fence_regs(acc);
  if (sig) {
    mbar_arrive_cluster(bBe + prev_bs * 8, warp);
    if (a_sel) mbar_arrive_cluster(bBe + a8_bs * 8, warp);
  }
  if (siga && !a_sel) mbar_arrive(bAe + 7 * 8);
  const bool isA = (w_sel == 2);
  bf16* out = (w_sel == 0) ? g_K : (w_sel == 1) ? g_V : isA ? g_QKVA : g_Q;
  const int ld = isA ? NQKVA : HDIM;
  const int row = mpair * 256 + rank * 128 + wg * 64 + warp * 16 + (lane >> 2);
  st.pp = out + (size_t)row * ld + chunk0 * 64 + (lane & 3) * 8;
  st.pld8 = 8 * ld;
  st.png = ((job & 3) + 1) * 2;
#pragma unroll
  for (int G = 0; G < 8; G++) {
    pk[G * 8 + 0] = pack_bf16(acc[G * 16 + 0], acc[G * 16 + 1]);
    pk[G * 8 + 1] = pack_bf16(acc[G * 16 + 4], acc[G * 16 + 5]);
    pk[G * 8 + 2] = pack_bf16(acc[G * 16 + 8], acc[G * 16 + 9]);
    pk[G * 8 + 3] = pack_bf16(acc[G * 16 + 12], acc[G * 16 + 13]);
    pk[G * 8 + 4] = pack_bf16(acc[G * 16 + 2], acc[G * 16 + 3]);
    pk[G * 8 + 5] = pack_bf16(acc[G * 16 + 6], acc[G * 16 + 7]);
    pk[G * 8 + 6] = pack_bf16(acc[G * 16 + 10], acc[G * 16 + 11]);
    pk[G * 8 + 7] = pack_bf16(acc[G * 16 + 14], acc[G * 16 + 15]);
  }
  if (isA) {
#pragma unroll
    for (int G = 0; G < 16; G++) quad_transpose(pk[G * 4 + 0], pk[G * 4 + 1], pk[G * 4 + 2], pk[G * 4 + 3], lane & 3);
  }
}

#define HA(h) (h)
constexpr int K2_NST = 7;
constexpr uint32_t K2_END = 0x100;
#define PF_KC 7
#define FIRST_DRAW 3
#define ANCH 8
constexpr int K3_NST = 4;
__device__ __forceinline__ uint32_t k3_rot(uint32_t sv) { return (0x00E9u >> (2 * sv)) & 3; }
constexpr int K3_STAGE = 16384 + 32768 + 4096;
constexpr int SMEM_DATA = 7 * 32768;
constexpr int SMEM_BYTES = SMEM_DATA + 1024 + 768;

struct Cursor {
  uint32_t s, ph;
  __device__ __forceinline__ void next() {
    if (++s == K2_NST) { s = 0; ph ^= 1; }
  }
};

#define TURN_SYNC() bar_sync(mybar, 256)
#define TURN_ARRIVE() bar_arrive(otherbar, 256)
#define RELEASE_IF(cur, cond) mbar_arrive_cluster_if(bE + (cur).s * 8, warp & 1, sig && (cond))
#define RELEASE(cur) RELEASE_IF(cur, true)
#define ISSUE_PV(cur, first)                                                                                   \
  do {                                                                                                         \
    const uint64_t dv = make_desc(sbase + (cur).s * 32768, 16384, 1024, 1);                                    \
    _Pragma("unroll") for (int t = 0; t < 8; t++)                                                              \
        wgmma_rs_n128<1, 0>(O, P[4 * t], P[4 * t + 1], P[4 * t + 2], P[4 * t + 3], dv + (uint64_t)(t * 128), (t > 0) ? 1 : !(first)); \
  } while (0)
#define RESCALE_O()                                                                                            \
  do {                                                                                                         \
    fence_regs(O);                                                                                             \
    _Pragma("unroll") for (int jj = 0; jj < 16; jj++) {                                                        \
      O[jj * 4 + 0] *= sc0; O[jj * 4 + 1] *= sc0; O[jj * 4 + 2] *= sc1; O[jj * 4 + 3] *= sc1;                  \
    }                                                                                                          \
    fence_regs(O);                                                                                             \
  } while (0)
#define ISSUE_QK(cur)                                                                                          \
  do {                                                                                                         \
    const uint64_t dk = make_desc(sbase + (cur).s * 32768, 16, 1024, 1);                                       \
    _Pragma("unroll") for (int t = 0; t < 8; t++)                                                              \
        wgmma_rs_n128<0, 0>(S, Q[4 * t], Q[4 * t + 1], Q[4 * t + 2], Q[4 * t + 3], dk + (uint64_t)((t >> 2) * 1024 + (t & 3) * 2), t > 0); \
  } while (0)
#define EPILOGUE()                                                                                             \
  do {                                                                                                         \
    l0 += __shfl_xor_sync(0xffffffffu, l0, 1);                                                                 \
    l0 += __shfl_xor_sync(0xffffffffu, l0, 2);                                                                 \
    l1 += __shfl_xor_sync(0xffffffffu, l1, 1);                                                                 \
    l1 += __shfl_xor_sync(0xffffffffu, l1, 2);                                                                 \
    asm volatile("" : "+f"(gf0), "+f"(gf1));                                                                   \
    const float f0 = __fdividef(1.f - gf0, l0), f1 = __fdividef(1.f - gf1, l1);                                                                \
    bf16* o0 = g_ctx + (size_t)prev_row * KCAT + prev_h * 128 + q * 8;                                         \
    bf16* o1 = o0 + (size_t)8 * KCAT;                                                                          \
    _Pragma("unroll") for (int G = 0; G < 4; G++) {                                                            \
      st_v4(o0 + G * 32, pack_bf16(O[G * 16 + 0] * f0, O[G * 16 + 1] * f0), pack_bf16(O[G * 16 + 4] * f0, O[G * 16 + 5] * f0), \
            pack_bf16(O[G * 16 + 8] * f0, O[G * 16 + 9] * f0), pack_bf16(O[G * 16 + 12] * f0, O[G * 16 + 13] * f0)); \
      st_v4(o1 + G * 32, pack_bf16(O[G * 16 + 2] * f1, O[G * 16 + 3] * f1), pack_bf16(O[G * 16 + 6] * f1, O[G * 16 + 7] * f1), \
            pack_bf16(O[G * 16 + 10] * f1, O[G * 16 + 11] * f1), pack_bf16(O[G * 16 + 14] * f1, O[G * 16 + 15] * f1)); \
    }                                                                                                          \
  } while (0)

__global__ void __cluster_dims__(2, 1, 1) __launch_bounds__(384, 1)
fused_kernel(const __grid_constant__ Params p, const bf16* __restrict__ x, const bf16* __restrict__ gate_w, bf16* __restrict__ out) {
  extern __shared__ uint8_t smem_raw[];
  const uint32_t sbase = (smem_u32(smem_raw) + 1023) & ~1023u;
  const uint32_t sB = sbase, sA = sbase + K1_BST * 16384, sBar = sbase + SMEM_DATA;
  const uint32_t bAf = sBar, bAe = sBar + 64, bBf = sBar + 128, bBe = sBar + 176, bL = sBar + 224, bS = sBar + 232, bL2 = sBar + 240, sL = sA + 32768;
  const uint32_t bF = sBar + 256, bE = sBar + 320, bT = sBar + 384, sTick = sBar + 400, sItem = sBar + 416, bS2 = sBar + 448, bR = sBar + 456, bLast = sBar + 464, bH = sBar + 472, bT0 = sBar + 480;
  const uint32_t b3F = sBar + 512, b3E = sBar + 544, sGate = sBar + 576;
  const int tid = threadIdx.x, warp_g = __shfl_sync(0xffffffffu, tid >> 5, 0), lane = tid & 31;
  const uint32_t rank = cluster_rank();
  const int cl = blockIdx.x >> 1;
  TSM(0);
  if (tid == 0) {
    for (int i = 0; i < 8; i++) { mbar_init(bAf + i * 8, 1); mbar_init(bAe + i * 8, 2); }
    for (int i = 0; i < K1_BST; i++) { mbar_init(bBf + i * 8, 1); mbar_init(bBe + i * 8, 4); }
    mbar_init(bL, 1);
    mbar_init(bL2, 1);
    mbar_init(bR, 1);
    mbar_init(bLast, 1);
    mbar_init(bH, 4);
    mbar_init(bT0, 1);
    mbar_init(bS, 8);
    for (int i = 0; i < K2_NST; i++) { mbar_init(bF + i * 8, 1); mbar_init(bE + i * 8, 4); }
    mbar_init(bT, 1); mbar_init(bT + 8, 1);
    mbar_init(bS2, 8);
    for (int i = 0; i < K3_NST; i++) { mbar_init(b3F + i * 8, 1); mbar_init(b3E + i * 8, 4); }
    asm volatile("fence.mbarrier_init.release.cluster;" ::: "memory");
  }
  __syncthreads();
  cluster_sync();
  const int lr0 = blockIdx.x * 16;

  if (warp_g >= 8) {
    reg_dealloc<40>();
    if (warp_g == 8) {
      if (elect_one()) {
        uint32_t bs = 0, bph = 1, aph = 1;
#pragma unroll 1
        for (int ji = 0; ji < K1_MAXJOBS; ji++) {
          const uint32_t job = p.jobs[cl][ji];
          if (!(job & 3)) break;
          const int a_sel = (job >> 2) & 1, mpair = (job >> 3) & 7, chunk0 = (job >> 8) & 63;
          const bool newA = (job >> 14) & 1;
          const int KC = a_sel ? 9 : 8;
          const uint32_t halfbytes = 8192;
          const bool lastjob = (ji + 1 == K1_MAXJOBS) || !(p.jobs[cl][ji + 1] & 3);
          const CUtensorMap* tw = &p.tmW[(job >> 6) & 3];
          {
            const uint32_t njob = (ji + 1 < K1_MAXJOBS) ? p.jobs[cl][ji + 1] : 0;
            if (!(njob & 3) && !newA) mbar_arrive(bLast);
          }
#pragma unroll 1
          for (int kc = 0; kc < KC; kc++) {
            if (kc == ((ji == 0) ? PF_KC : 0) && !lastjob) {
              const uint32_t njob = p.jobs[cl][ji + 1];
              const int nst = ((njob >> 2) & 1) ? 18 : 16;
#pragma unroll 1
              for (int t = (cl < 64) ? (cl & 7) : 0; t < nst; t += (cl < 64) ? 8 : 1)
                tma_pf3d(&p.tmW[(njob >> 6) & 3], 0, t * 32 + rank * 16, (njob >> 8) & 63);
            }
            if (kc == 8) {
              mbar_wait(bBe + bs * 8, bph);
              mbar_expect(bBf + bs * 8, 16384);
              tma2d(sB + bs * 16384, &p.tmA[1], bBf + bs * 8, 512, mpair * 256 + rank * 128);
              if (++bs == K1_BST) { bs = 0; bph ^= 1; }
            } else if (newA) {
              mbar_wait(bAe + kc * 8, aph);
              mbar_expect(bAf + kc * 8, 16384);
              tma2d(sA + ((kc + 2) & 7) * 16384, &p.tmA[a_sel], bAf + kc * 8, kc * 64, mpair * 256 + rank * 128);
              if (kc == 7 && lastjob) mbar_arrive(bLast);
            }
#pragma unroll 1
            for (int kk = 0; kk < 2; kk++) {
              mbar_wait(bBe + bs * 8, bph);
              mbar_expect(bBf + bs * 8, 2 * halfbytes);
              tma3d_mc(sB + bs * 16384 + rank * halfbytes, tw, bBf + bs * 8, 0, kc * 64 + kk * 32 + rank * 16, chunk0, 3);
              if (++bs == K1_BST) { bs = 0; bph ^= 1; }
            }
          }
          if (newA) aph ^= 1;
        }
        Cursor c{0, 0};
        int pcol = 0;
        mbar_wait(bR, 0);
        uint32_t tick = lds32(sTick + 8), seen = 1u << (p.order[tick] >> 4);
        asm volatile("fence.proxy.async.global;" ::: "memory");
#pragma unroll 1
        for (int it = 0;; it++) {
          const uint32_t item = (tick < 256) ? p.order[tick] : (K2_END | min(tick - 256, 255u));
          asm volatile("st.shared.u32 [%0], %1;" ::"r"(sItem + (it & 7) * 4), "r"(item) : "memory");
          if (item >= K2_END) break;
          const int h = item >> 3, j = item & 7;
          const int blk = 2 * j + (int)(rank ^ (it & 1));
          const int col = HA(h) * 128 + rank * 64;
          const int nb = 2 * j + 2;
          if (!((seen >> (h >> 1)) & 1)) {
            wait_flag(&g_sync[F_HP + (h >> 1)], RDY_TARGET);
            asm volatile("fence.proxy.async.global;" ::: "memory");
            seen |= 1u << (h >> 1);
          }
          mbar_wait(bE + c.s * 8, c.ph);
          mbar_expect(bF + c.s * 8, 32768);
          tma2d(sbase + c.s * 32768, &p.tmQ, bF + c.s * 8, HA(h) * 128, blk * 128);
          tma2d(sbase + c.s * 32768 + 16384, &p.tmQ, bF + c.s * 8, HA(h) * 128 + 64, blk * 128);
          c.next();
#pragma unroll 1
          for (int n = nb - 1; n >= 0; n--) {
            if (n == 0 && rank == 0) tick = atomicAdd(&g_sync[F_TICK], 1u);
            mbar_wait(bE + c.s * 8, c.ph);
            mbar_expect(bF + c.s * 8, 32768);
            tma2d_mc(sbase + c.s * 32768 + rank * 16384, &p.tmK, bF + c.s * 8, col, n * 128, 3);
            c.next();
            if (n < nb - 1 || it > 0) {
              mbar_wait(bE + c.s * 8, c.ph);
              mbar_expect(bF + c.s * 8, 32768);
              tma2d_mc(sbase + c.s * 32768 + rank * 16384, &p.tmV, bF + c.s * 8, (n < nb - 1) ? col : pcol, (n < nb - 1) ? (n + 1) * 128 : 0, 3);
              c.next();
            }
          }
          pcol = col;
          if (rank == 0) {
            asm volatile(
                "{\n.reg .b32 a, b;\nmapa.shared::cluster.u32 a, %0, 1;\nmapa.shared::cluster.u32 b, %1, 1;\n"
                "st.async.shared::cluster.mbarrier::complete_tx::bytes.u32 [a], %2, [b];\n}" ::"r"(sTick + (it & 1) * 4),
                "r"(bT + (it & 1) * 8), "r"(tick) : "memory");
          } else {
            mbar_expect(bT + (it & 1) * 8, 4);
            mbar_wait(bT + (it & 1) * 8, (it >> 1) & 1);
            tick = lds32(sTick + (it & 1) * 4);
          }
        }
        mbar_wait(bE + c.s * 8, c.ph);
        mbar_expect(bF + c.s * 8, 32768);
        tma2d_mc(sbase + c.s * 32768 + rank * 16384, &p.tmV, bF + c.s * 8, pcol, 0, 3);
        const uint32_t unit = tick - 256;
        if (unit < 64) {
          const int mblk = (7 - (p.unit[unit][0] >> 1)) * 2 + rank, nhalf = p.unit[unit][0] & 1;
          const uint32_t rot = k3_rot(c.s), nfree = ((0x1Au >> c.s) & 1) ? 2 : 3;
#pragma unroll 1
          for (int i = 0; i < K2_NST - 1; i++) {
            c.next();
            mbar_wait(bE + c.s * 8, c.ph);
          }
          uint32_t idx = 0, have = 0;
#pragma unroll 1
          for (int kk = p.unit[unit][2]; kk < p.unit[unit][3]; kk++, idx++) {
            const uint32_t s = (rot + idx) & 3;
            if (idx >= nfree) mbar_wait((idx < 4) ? bH : b3E + s * 8, (idx < 4) ? 0 : (~idx >> 2) & 1);
            mbar_expect(b3F + s * 8, K3_STAGE);
            const uint32_t st = sbase + s * K3_STAGE;
            const int sel = (kk < 9), k = sel ? kk : kk - 9, kr = k * 64 + rank * 32;
            tma3d_mc(st + 16384 + rank * 16384, &p.tmO[sel], b3F + s * 8, 0, kr, nhalf * 4, 3);
            tma2d_mc(st + 49152 + rank * 2048, &p.tmOt[sel], b3F + s * 8, 512 + nhalf * 32, kr, 3);
            if (kk == 0) {
              wait_flag(&g_sync[F_OA + mblk], 8);
              asm volatile("fence.proxy.async.global;" ::: "memory");
            }
            if (!sel && !((have >> (k >> 1)) & 1)) {
#pragma unroll 1
              for (uint32_t spins = 0; spins < (1u << 22); spins++) {
                asm volatile("ld.acquire.gpu.global.u32 %0, [%1];" : "=r"(have) : "l"(&g_sync[F_CTX + mblk]) : "memory");
                if ((have >> (k >> 1)) & 1) break;
                __nanosleep(100);
              }
              asm volatile("fence.proxy.async.global;" ::: "memory");
            }
            tma2d(st, &p.tmC, b3F + s * 8, (sel ? 64 + k : k) * 64, mblk * 128);
          }
        }
      }
    }
    __syncwarp();
    if (warp_g == 8) {
      uint32_t v = 0;
      if (lane == 0) {
        __threadfence();
        v = atomicAdd(&g_sync[F_DONE], 1u);
      }
      if (__shfl_sync(0xffffffffu, v, 0) == 2 * NCLUSTER - 1) {
        reinterpret_cast<uint4*>(g_sync)[lane] = make_uint4(0, 0, 0, 0);
        if (lane == 0) g_sync[F_EPOCH] = lds32(sGate + 64) + 1;
      }
    }
    asm volatile("" ::: "memory");
    if (__shfl_sync(0xffffffffu, warp_g, 0) != 8) {
      if (lr0 < S_LEN) {
#pragma unroll 1
        for (int i = warp_g - 9; i < 16; i += 3) {
          const float g = gate_row(lr0 + i, lane, x, gate_w);
          if (lane == 0) asm volatile("st.shared.f32 [%0], %1;" ::"r"(sGate + i * 4), "f"(g) : "memory");
        }
        bar_arrive(3, 256 + 96);
        if (lane == 0) {
          __threadfence();
          atomicAdd(&g_sync[F_GATE], 1u);
        }
      }
      uint32_t aph = 1;
#pragma unroll 1
      for (int ji = 0; ji < K1_MAXJOBS; ji++) aph ^= (p.jobs[cl][ji] >> 14) & 1;
      if (warp_g == 9 && lane == 0) {
#pragma unroll 1
        for (int ji = 0; ji < K1_MAXJOBS; ji++) {
          const uint32_t job = p.jobs[cl][ji];
          if (!(job & 3)) break;
          mbar_wait(bS, ji & 1);
          __threadfence();
          atomicAdd(&g_sync[(((job >> 6) & 3) == 2) ? (F_QKVA + ((job >> 3) & 7) * 2 + rank) : (F_HP + ((job >> 10) & 15))], 1u);
        }
#pragma unroll 1
        for (int it = 0;; it++) {
          mbar_wait(bS2, it & 1);
          const uint32_t item = lds32(sItem + (it & 7) * 4), nxt = lds32(sItem + ((it + 1) & 7) * 4);
          __threadfence();
          atomicOr(&g_sync[F_CTX + (item & 7) * 2 + (rank ^ (it & 1))], 1u << (item >> 3));
          if (nxt >= K2_END) break;
        }
      } else if (warp_g == 11) {
        if (lane == 0) {
          prefetch_tmap(&p.tmQ); prefetch_tmap(&p.tmK); prefetch_tmap(&p.tmV);
          asm volatile("st.shared.u32 [%0], %1;" ::"r"(sGate + 64), "r"(__ldcg(&g_sync[F_EPOCH])) : "memory");
          wait_flag(&g_sync[F_GATE], GATE_TARGET);
          uint32_t tick;
          if (rank == 0) {
            mbar_wait(bLast, 0);
            mbar_wait(bAe + FIRST_DRAW * 8, aph);
            tick = atomicAdd(&g_sync[F_TICK], 1u);
            asm volatile("st.shared.u32 [%0], %1;" ::"r"(sTick + 8), "r"(tick) : "memory");
            asm volatile(
                "{\n.reg .b32 a, b;\nmapa.shared::cluster.u32 a, %0, 1;\nmapa.shared::cluster.u32 b, %1, 1;\n"
                "st.async.shared::cluster.mbarrier::complete_tx::bytes.u32 [a], %2, [b];\n}" ::"r"(sTick + 8), "r"(bT0), "r"(tick) : "memory");
          } else {
            mbar_expect(bT0, 4);
            mbar_wait(bT0, 0);
            tick = lds32(sTick + 8);
          }
          wait_flag(&g_sync[F_HP + (p.order[tick] >> 4)], RDY_TARGET);
          mbar_arrive(bR);
        }
        __syncwarp();
        bar_sync(4, 256 + 32);
        if (lane < 12) mbar_arrive_cluster(bE + (4 + lane % 3) * 8, (lane / 3) & 1);
      } else if (warp_g == 10 && lr0 < S_LEN) {
        if (elect_one()) {
          prefetch_tmap(&p.tmL[0]); prefetch_tmap(&p.tmL[1]);
          wait_flag(&g_sync[F_QKVA + (lr0 >> 7)], K1_FLAG_TARGET);
          wait_flag(&g_sync[F_QKVA + (max(lr0 - 14, 0) >> 7)], K1_FLAG_TARGET);
          asm volatile("fence.proxy.async.global;" ::: "memory");
          mbar_wait(bLast, 0);
#pragma unroll 1
          for (int kc = 0; kc < 6; kc++) {
            mbar_wait(bAe + kc * 8, aph);
            if (kc == 3) {
              mbar_expect(bL, 46 * 1152);
              tma3d(sL, &p.tmL[0], bL, 0, 9, lr0 - 14);
              tma3d(sL + 30 * 1152, &p.tmL[1], bL, 0, 0, lr0);
            }
          }
          mbar_expect(bL2, 30 * 1152);
          tma3d(sL + 46 * 1152, &p.tmL[0], bL2, 0, 18, lr0 - 14);
        }
        __syncwarp();
        bar_sync(5, 256 + 32);
        if (lane == 0) {
          __threadfence();
          atomicAdd(&g_sync[F_OA + (lr0 >> 7)], 1u);
        }
      }
    }
    __syncwarp();
    cluster_sync();
  } else {
    reg_alloc<232>();
    const int wg = warp_g >> 2, warp = warp_g & 3, q = lane & 3;
    const bool sig = (lane == 0) && (warp < 2);
    {
      K1State st{0, 0, 0, nullptr, 0, 0};
      float acc[128];
      uint32_t pk[64];
      if (wg == 0) { TS(0, 0); TSC(0, 2); }
#pragma unroll 1
      for (int ji = 0; ji < K1_MAXJOBS; ji++) {
        const uint32_t job = p.jobs[cl][ji];
        if (!(job & 3)) break;
        k1_tile(acc, pk, st, job, sA, sB, bAf, bAe, bBf, bBe, bS, wg, warp, lane, rank);
      }
#pragma unroll
      for (int i = 0; i < 4; i++)
        mbar_arrive_cluster_if(bE + i * 8, warp & 1, sig);
#pragma unroll
      for (int G = 0; G < 8; G++)
        if (G < st.png) {
          st_v4a(st.pp + G * 32, pk[G * 8], pk[G * 8 + 1], pk[G * 8 + 2], pk[G * 8 + 3]);
          st_v4a(st.pp + G * 32 + st.pld8, pk[G * 8 + 4], pk[G * 8 + 5], pk[G * 8 + 6], pk[G * 8 + 7]);
        }
      k1_flag(st, lane, bS);
      if (wg == 0) { TS(0, 1); TSC(0, 3); }
      if (lr0 < S_LEN) {
        const int ri = (warp_g >> 1) * 4 + (warp_g & 1) + 2, row = lr0 + ri;
        if (wg == 0) TS(1, 5);
        bar_sync(3, 256 + 96);
        const float gate0 = __uint_as_float(lds32(sGate + ri * 4 - 8)), gate1 = __uint_as_float(lds32(sGate + ri * 4));
        mbar_wait(bL, 0);
        if (wg == 0) TS(1, 6);
        local_rows2(row, ri, sL, bL2, lane, gate0, gate1);
        bar_arrive(5, 256 + 32);
      } else {
        bar_arrive(4, 256 + 32);
      }
    }
    __syncwarp();
    uint32_t item, rot;
    {
      const int mybar = 1 + wg, otherbar = 2 - wg;
      const float cl2 = 0.08838834764831845f * 1.4426950408889634f;
      float S[64], O[64];
      uint32_t P[32], Q[32];
      float m0 = 0.f, m1 = 0.f, l0 = 0.f, l1 = 0.f;
      int prev_row = 0, prev_h = 0, prev_single = 0;
      Cursor c{0, 0};
      if (wg == 1) bar_arrive(1, 256);
      if (wg == 0) { TS(1, 0); TSC(1, 2); }
#pragma unroll 1
      for (int it = 0;; it++) {
        mbar_wait(bF + c.s * 8, c.ph);
        item = lds32(sItem + (it & 7) * 4);
        const bool last = item >= K2_END;
        const int h = item >> 3, j = item & 7;
        const int hi = (int)(rank ^ (it & 1));
        const int nblk = 2 * j + 1 + hi;
        {
          float gf0, gf1;
          asm volatile("ld.global.f32 %0, [%1];" : "=f"(gf0) : "l"(g_gate + prev_row));
          asm volatile("ld.global.f32 %0, [%1];" : "=f"(gf1) : "l"(g_gate + prev_row + 8));
          Cursor cq = c, ck = c, cs0 = c, cs1 = c, cv = c;
          rot = k3_rot(c.s);
          if (!last) {
            const int r = wg * 64 + warp * 16 + (lane & 7) + ((lane >> 3) & 1) * 8;
            const uint32_t qa = sbase + cq.s * 32768 + r * 128;
#pragma unroll
            for (int t = 0; t < 8; t++)
              ldsm_x4(Q[4 * t], Q[4 * t + 1], Q[4 * t + 2], Q[4 * t + 3], qa + (t >> 2) * 16384 + ((((t & 3) * 2 + (lane >> 4)) ^ (lane & 7)) << 4));
            c.next();
            ck = c; c.next();
            cs0 = ck; cv = c;
            mbar_wait(bF + ck.s * 8, ck.ph);
            if (it > 0) { mbar_wait(bF + cv.s * 8, cv.ph); c.next(); }
            if (!hi) {
              ck = c; c.next();
              cs1 = c; c.next();
              mbar_wait(bF + ck.s * 8, ck.ph);
              mbar_wait(bF + cs1.s * 8, cs1.ph);
            }
          }
          if (it == 0) BSEG(4); else BSEG(0);
          TURN_SYNC();
          if (it > 0) {
            wg_fence();
            ISSUE_PV(cv, prev_single);
            wg_commit();
          } else {
            wg_fence();
            wg_commit();
          }
          wg_fence();
          ISSUE_QK(ck);
          wg_commit();
          if (!(last && wg == 1)) TURN_ARRIVE();
          RELEASE_IF(cq, !last);
          RELEASE_IF(cs0, !last && !hi);
          RELEASE_IF(cs1, !last && !hi);
          wg_wait<1>();
          fence_regs(O);
          fence_regs(P);
          if (it > 0) {
            RELEASE_IF(cv, !last);
            mbar_arrive_cluster_if(bH, warp & 1, sig && last);
            EPILOGUE();
            __syncwarp();
            mbar_arrive_if(bS2, lane == 0);
          }
          wg_wait<0>();
          fence_regs(S);
          if (last) break;
          RELEASE(ck);
          float s0 = 0.f, s1 = 0.f;
          const int r0 = wg * 64 + warp * 16 + (lane >> 2);
#pragma unroll
          for (int jj = 0; jj < 16; jj++) {
            const int cc = jj * 8 + 2 * q;
            if (cc > r0) S[jj * 4 + 0] = -INFINITY;
            if (cc + 1 > r0) S[jj * 4 + 1] = -INFINITY;
            if (cc > r0 + 8) S[jj * 4 + 2] = -INFINITY;
            if (cc + 1 > r0 + 8) S[jj * 4 + 3] = -INFINITY;
          }
          float mx0 = fmaxf(S[0], S[1]), mx1 = fmaxf(S[2], S[3]);
#pragma unroll
          for (int jj = 1; jj < 16; jj++) {
            mx0 = fmaxf(mx0, fmaxf(S[jj * 4 + 0], S[jj * 4 + 1]));
            mx1 = fmaxf(mx1, fmaxf(S[jj * 4 + 2], S[jj * 4 + 3]));
          }
          mx0 = fmaxf(mx0, __shfl_xor_sync(0xffffffffu, mx0, 1));
          mx1 = fmaxf(mx1, __shfl_xor_sync(0xffffffffu, mx1, 1));
          mx0 = fmaxf(mx0, __shfl_xor_sync(0xffffffffu, mx0, 2));
          mx1 = fmaxf(mx1, __shfl_xor_sync(0xffffffffu, mx1, 2));
          m0 = mx0; m1 = mx1;
          const float mc0 = m0 * cl2, mc1 = m1 * cl2;
#pragma unroll
          for (int jj = 0; jj < 16; jj++) {
            S[jj * 4 + 0] = ex2(fmaf(S[jj * 4 + 0], cl2, -mc0));
            S[jj * 4 + 1] = ex2(fmaf(S[jj * 4 + 1], cl2, -mc0));
            S[jj * 4 + 2] = ex2(fmaf(S[jj * 4 + 2], cl2, -mc1));
            S[jj * 4 + 3] = ex2(fmaf(S[jj * 4 + 3], cl2, -mc1));
            s0 += S[jj * 4 + 0] + S[jj * 4 + 1];
            s1 += S[jj * 4 + 2] + S[jj * 4 + 3];
          }
          l0 = s0; l1 = s1;
#pragma unroll
          for (int jj = 0; jj < 16; jj++) {
            P[jj * 2 + 0] = pack_bf16(S[jj * 4 + 0], S[jj * 4 + 1]);
            P[jj * 2 + 1] = pack_bf16(S[jj * 4 + 2], S[jj * 4 + 3]);
          }
        }
        if (it == 0) BSEG(5); else BSEG(1);
#pragma unroll 1
        for (int n = 1; n < nblk; n++) {
          Cursor ck = c; c.next();
          Cursor cv = c; c.next();
          mbar_wait(bF + ck.s * 8, ck.ph);
          mbar_wait(bF + cv.s * 8, cv.ph);
          TURN_SYNC();
          wg_fence();
          ISSUE_QK(ck);
          wg_commit();
          ISSUE_PV(cv, n == 1);
          wg_commit();
          TURN_ARRIVE();
          wg_wait<1>();
          fence_regs(S);
          float mx0 = fmaxf(S[0], S[1]), mx1 = fmaxf(S[2], S[3]);
#pragma unroll
          for (int jj = 1; jj < 16; jj++) {
            mx0 = fmaxf(mx0, fmaxf(S[jj * 4 + 0], S[jj * 4 + 1]));
            mx1 = fmaxf(mx1, fmaxf(S[jj * 4 + 2], S[jj * 4 + 3]));
          }
          mx0 = fmaxf(mx0, __shfl_xor_sync(0xffffffffu, mx0, 1));
          mx1 = fmaxf(mx1, __shfl_xor_sync(0xffffffffu, mx1, 1));
          mx0 = fmaxf(mx0, __shfl_xor_sync(0xffffffffu, mx0, 2));
          mx1 = fmaxf(mx1, __shfl_xor_sync(0xffffffffu, mx1, 2));
          mx0 = fmaxf(mx0, m0);
          mx1 = fmaxf(mx1, m1);
          const float sc0 = ex2((m0 - mx0) * cl2), sc1 = ex2((m1 - mx1) * cl2);
          m0 = mx0; m1 = mx1;
          const float mc0 = m0 * cl2, mc1 = m1 * cl2;
          float s0 = 0.f, s1 = 0.f;
#pragma unroll
          for (int jj = 0; jj < 16; jj++) {
            S[jj * 4 + 0] = ex2(fmaf(S[jj * 4 + 0], cl2, -mc0));
            S[jj * 4 + 1] = ex2(fmaf(S[jj * 4 + 1], cl2, -mc0));
            S[jj * 4 + 2] = ex2(fmaf(S[jj * 4 + 2], cl2, -mc1));
            S[jj * 4 + 3] = ex2(fmaf(S[jj * 4 + 3], cl2, -mc1));
            s0 += S[jj * 4 + 0] + S[jj * 4 + 1];
            s1 += S[jj * 4 + 2] + S[jj * 4 + 3];
          }
          l0 = fmaf(l0, sc0, s0);
          l1 = fmaf(l1, sc1, s1);
          mbar_arrive_cluster_after(bE + ck.s * 8, warp & 1, sig, (ANCH == 100) ? mx0 : (ANCH == 101) ? mx1 : S[ANCH & 63]);
          fence_regs(S);
          wg_wait<0>();
          fence_regs(O);
          fence_regs(P);
          RELEASE(cv);
#pragma unroll
          for (int jj = 0; jj < 16; jj++) {
            O[jj * 4 + 0] *= sc0;
            O[jj * 4 + 1] *= sc0;
            O[jj * 4 + 2] *= sc1;
            O[jj * 4 + 3] *= sc1;
            P[jj * 2 + 0] = pack_bf16(S[jj * 4 + 0], S[jj * 4 + 1]);
            P[jj * 2 + 1] = pack_bf16(S[jj * 4 + 2], S[jj * 4 + 3]);
          }
        }
        BSEG(2);
        prev_row = (2 * j + hi) * 128 + wg * 64 + warp * 16 + (lane >> 2);
        prev_h = h;
        prev_single = (nblk == 1);
      }
      if (wg == 1) { TS(1, 1); TSC(1, 3); }
    }
    __syncwarp();
    const uint32_t unit = item & 255;
    if (unit < 64) {
      const int mblk = (7 - (p.unit[unit][0] >> 1)) * 2 + rank, nhalf = p.unit[unit][0] & 1, ks = p.unit[unit][1];
      const int k0 = p.unit[unit][2], k1 = p.unit[unit][3];
      float acc[144];
      uint32_t s = rot, ph = 0, prev = 0;
      if (wg == 0) { TS(2, 0); TSC(2, 2); }
#pragma unroll 1
      for (int k = k0; k < k1; k++) {
        mbar_wait(b3F + s * 8, ph);
        const uint32_t st = sbase + s * K3_STAGE;
        const uint64_t da = make_desc(st + wg * 8192, 16, 1024, 1);
        const uint64_t db = make_desc(st + 16384, 4096, 1024, 1);
        const uint64_t dt = make_desc(st + 49152, 16, 512, 2);
        wg_fence();
#pragma unroll
        for (int t = 0; t < 4; t++) {
          const int sd = (t > 0) || (k > k0);
          wgmma_ss_n256<1, 0>(acc, da + (uint64_t)(t * 2), db + (uint64_t)((t >> 1) * 1024 + (t & 1) * 128), sd);
          wgmma_ss_n32<1, 128>(acc, da + (uint64_t)(t * 2), dt + (uint64_t)(t * 64), sd);
        }
        wg_commit();
        if (k > k0) {
          wg_wait<1>();
          if (sig) mbar_arrive_cluster(b3E + prev * 8, warp);
        }
        prev = s;
        s = (s + 1) & 3;
        if (s == rot) ph ^= 1;
      }
      wg_wait<0>();
      fence_regs(acc);
      cluster_arrive();
      if (wg == 0) TS(2, 4);
      const int tile = mblk * 2 + nhalf;
      uint4* wp = g_part + (size_t)((tile * 4 + ks) * 4) * 5 * 256 + tid;
      const uint32_t sown = sbase + wg * 8192 + (tid & 127) * 16;
#pragma unroll
      for (int d = 0; d < 4; d++) {
        if (d != ks) {
#pragma unroll
          for (int i = 0; i < 4; i++)
            __stcg(wp + (d * 5 + i) * 256,
                   make_uint4(pack_bf16(acc[d * 32 + i * 8], acc[d * 32 + i * 8 + 1]), pack_bf16(acc[d * 32 + i * 8 + 2], acc[d * 32 + i * 8 + 3]),
                              pack_bf16(acc[d * 32 + i * 8 + 4], acc[d * 32 + i * 8 + 5]), pack_bf16(acc[d * 32 + i * 8 + 6], acc[d * 32 + i * 8 + 7])));
          __stcg(reinterpret_cast<uint2*>(wp - tid + (d * 5 + 4) * 256) + tid,
                 make_uint2(pack_bf16(acc[128 + d * 4], acc[128 + d * 4 + 1]), pack_bf16(acc[128 + d * 4 + 2], acc[128 + d * 4 + 3])));
        } else {
#pragma unroll
          for (int i = 0; i < 9; i++) {
            const int o = (i < 8) ? d * 32 + i * 4 : 128 + d * 4;
            asm volatile("st.shared.v4.f32 [%0], {%1, %2, %3, %4};" ::"r"(sown + (i >> 2) * K3_STAGE + (i & 3) * 2048), "f"(acc[o]), "f"(acc[o + 1]), "f"(acc[o + 2]), "f"(acc[o + 3]) : "memory");
          }
        }
      }
      __threadfence();
      __syncwarp();
      if (wg == 0) TS(2, 5);
      if (lane == 0) {
        unsigned int* cnt = &g_sync[F_XCH + tile * 8 + warp_g];
        const uint32_t xtarget = lds32(sGate + 64) * 4 + 4;
        atomicAdd(cnt, 1u);
        uint32_t v, spins = 0;
        do {
          asm volatile("ld.acquire.gpu.global.u32 %0, [%1];" : "=r"(v) : "l"(cnt) : "memory");
        } while ((int)(v - xtarget) < 0 && ++spins < (1u << 24));
      }
      __syncwarp();
      if (wg == 0) TS(2, 6);
      float r[36];
#pragma unroll
      for (int i = 0; i < 9; i++)
        asm volatile("ld.shared.v4.f32 {%0, %1, %2, %3}, [%4];" : "=f"(r[i * 4]), "=f"(r[i * 4 + 1]), "=f"(r[i * 4 + 2]), "=f"(r[i * 4 + 3])
                     : "r"(sown + (i >> 2) * K3_STAGE + (i & 3) * 2048) : "memory");
#pragma unroll
      for (int sI = 1; sI < 4; sI++) {
        const int src = (ks + sI) & 3;
        const uint4* rp = g_part + (size_t)(((tile * 4 + src) * 4) + ks) * 5 * 256;
#pragma unroll
        for (int i = 0; i < 4; i++) {
          const uint4 v = __ldcg(rp + i * 256 + tid);
          r[i * 8] += bf_lo(v.x); r[i * 8 + 1] += bf_hi(v.x); r[i * 8 + 2] += bf_lo(v.y); r[i * 8 + 3] += bf_hi(v.y);
          r[i * 8 + 4] += bf_lo(v.z); r[i * 8 + 5] += bf_hi(v.z); r[i * 8 + 6] += bf_lo(v.w); r[i * 8 + 7] += bf_hi(v.w);
        }
        const uint2 v = __ldcg(reinterpret_cast<const uint2*>(rp + 4 * 256) + tid);
        r[32] += bf_lo(v.x); r[33] += bf_hi(v.x); r[34] += bf_lo(v.y); r[35] += bf_hi(v.y);
      }
      const int row = mblk * 128 + wg * 64 + warp * 16 + (lane >> 2);
      bf16* o0 = out + (size_t)row * DM + nhalf * 256 + ks * 64 + 8 * q;
#pragma unroll
      for (int G = 0; G < 2; G++) {
        uint32_t a0 = pack_bf16(r[G * 16], r[G * 16 + 1]), a1 = pack_bf16(r[G * 16 + 4], r[G * 16 + 5]);
        uint32_t a2 = pack_bf16(r[G * 16 + 8], r[G * 16 + 9]), a3 = pack_bf16(r[G * 16 + 12], r[G * 16 + 13]);
        uint32_t b0 = pack_bf16(r[G * 16 + 2], r[G * 16 + 3]), b1 = pack_bf16(r[G * 16 + 6], r[G * 16 + 7]);
        uint32_t b2 = pack_bf16(r[G * 16 + 10], r[G * 16 + 11]), b3 = pack_bf16(r[G * 16 + 14], r[G * 16 + 15]);
        quad_transpose(a0, a1, a2, a3, q);
        quad_transpose(b0, b1, b2, b3, q);
        st_v4(o0 + G * 32, a0, a1, a2, a3);
        st_v4(o0 + 8 * DM + G * 32, b0, b1, b2, b3);
      }
      {
        uint32_t t0 = pack_bf16(r[32], r[33]), t1 = pack_bf16(r[34], r[35]), t2 = 0, t3 = 0;
        quad_transpose(t0, t1, t2, t3, q);
        if (q < 2) st_v4(out + (size_t)(row + q * 8) * DM + 512 + nhalf * 32 + ks * 8, t0, t1, t2, t3);
      }
    } else {
      cluster_arrive();
    }
    if (wg == 0) { TS(2, 1); TSC(2, 3); }
    cluster_wait();
  }
}

typedef CUresult (*EncFn)(CUtensorMap*, CUtensorMapDataType, cuuint32_t, void*, const cuuint64_t*, const cuuint64_t*, const cuuint32_t*,
                          const cuuint32_t*, CUtensorMapInterleave, CUtensorMapSwizzle, CUtensorMapL2promotion, CUtensorMapFloatOOBfill);

static void enc2d(EncFn enc, CUtensorMap* m, const void* ptr, uint64_t cols, uint64_t rows, uint32_t bc, uint32_t br,
                  CUtensorMapSwizzle sw = CU_TENSOR_MAP_SWIZZLE_128B) {
  cuuint64_t gd[2] = {cols, rows}, gs[1] = {cols * 2};
  cuuint32_t bx[2] = {bc, br}, es[2] = {1, 1};
  enc(m, CU_TENSOR_MAP_DATA_TYPE_BFLOAT16, 2, const_cast<void*>(ptr), gd, gs, bx, es, CU_TENSOR_MAP_INTERLEAVE_NONE, sw,
      CU_TENSOR_MAP_L2_PROMOTION_L2_256B, CU_TENSOR_MAP_FLOAT_OOB_FILL_NONE);
}
static void enc3d(EncFn enc, CUtensorMap* m, const void* ptr, uint64_t cols, uint64_t rows, uint32_t br, uint32_t bch) {
  cuuint64_t gd[3] = {64, rows, cols / 64}, gs[2] = {cols * 2, 128};
  cuuint32_t bx[3] = {64, br, bch}, es[3] = {1, 1, 1};
  enc(m, CU_TENSOR_MAP_DATA_TYPE_BFLOAT16, 3, const_cast<void*>(ptr), gd, gs, bx, es, CU_TENSOR_MAP_INTERLEAVE_NONE,
      CU_TENSOR_MAP_SWIZZLE_128B, CU_TENSOR_MAP_L2_PROMOTION_L2_256B, CU_TENSOR_MAP_FLOAT_OOB_FILL_NONE);
}

static int g_sched[10] = {11, 10, 7, 4, 4, 5, 6, 6, 8, 20};
static void build_k1_jobs(Params& p) {
  int cnt[NCLUSTER];
  for (int c = 0; c < NCLUSTER; c++) {
    cnt[c] = 0;
    for (int i = 0; i < K1_MAXJOBS; i++) p.jobs[c][i] = 0;
  }
  auto add = [&](int c, int nch, int a_sel, int mp, int w_sel, int chunk0) {
    p.jobs[c][cnt[c]++] = (uint16_t)((nch - 1) | (a_sel << 2) | (mp << 3) | (w_sel << 6) | (chunk0 << 8));
  };
  const int *cg = g_sched, *xg = g_sched + 4;
  for (int mp = 0; mp < 8; mp++) {
    int k = 0;
    for (int i = 0; i < K1_MAXJOBS; i++)
      for (int g = 0; g < 4; g++)
        if (i < cg[g]) { add(g * 8 + mp, 4, 0, mp, k & 1, (k >> 1) * 4); k++; }
    k = 0;
    for (int i = 0; i < K1_MAXJOBS; i++)
      for (int g = 0; g < 4; g++)
        if (i < xg[g]) {
          if (k < 7) add((4 + g) * 8 + mp, k == 0 ? 3 : 4, 1, mp, 2, k == 0 ? 24 : (k - 1) * 4);
          else add((4 + g) * 8 + mp, 4, 1, mp, 3, (k - 7) * 4);
          k++;
        }
    add(64 + mp / 4, 4, 1, mp, 3, 14 * 4);
    add(64 + mp / 4, 4, 1, mp, 3, 15 * 4);
  }
  for (int cc = 0; cc < NCLUSTER; cc++)
    for (int i = 0; i < cnt[cc]; i++) {
      const int key = p.jobs[cc][i] & 0x3C;
      if (i == 0 || (p.jobs[cc][i - 1] & 0x3C) != key) p.jobs[cc][i] |= (1 << 14);
      if (i == cnt[cc] - 1 || (p.jobs[cc][i + 1] & 0x3C) != key) p.jobs[cc][i] |= (1 << 15);
    }
}

static void build_k2_items(Params& p) {
  int n = 0;
  const int SCHED_N1 = g_sched[8], SCHED_N2 = g_sched[9];
  for (int j = 7; j >= 0; j--)
    for (int h = 0; h < SCHED_N1; h++) p.order[n++] = (uint8_t)(h * 8 + j);
  for (int j = 7; j >= 4; j--)
    for (int h = SCHED_N1; h < SCHED_N2; h++) p.order[n++] = (uint8_t)(h * 8 + j);
  for (int j = 7; j >= 0; j--)
    for (int h = SCHED_N1; h < 32; h++)
      if (!(h < SCHED_N2 && j >= 4)) p.order[n++] = (uint8_t)(h * 8 + j);
}

static void build_k3_units(Params& p) {
  float slope = 0.09f;
  for (int t = 0; t < 16; t++) {
    const int u[4] = {t, 31 - t, 32 + t, 63 - t};
    float acc = 0.f;
    int k0 = 0;
    for (int i = 0; i < 4; i++) {
      acc += 18.25f + slope * (31.5f - u[i]);
      const int k1 = (i == 3) ? 73 : (int)(acc + 0.5f);
      p.unit[u[i]][0] = (uint8_t)t; p.unit[u[i]][1] = (uint8_t)i; p.unit[u[i]][2] = (uint8_t)k0; p.unit[u[i]][3] = (uint8_t)k1;
      k0 = k1;
    }
  }
}

extern "C" void kernel_launch(void* const* d_in, const int* in_sizes, int n_in, void* d_out, int out_size) {
  const bf16* x = (const bf16*)d_in[0];
  const bf16* wqkv = (const bf16*)d_in[1];
  const bf16* wo = (const bf16*)d_in[2];
  const bf16* ckv = (const bf16*)d_in[4];
  const bf16* w_q = (const bf16*)d_in[5];
  const bf16* w_uk = (const bf16*)d_in[6];
  const bf16* w_uv = (const bf16*)d_in[7];
  const bf16* w_o = (const bf16*)d_in[8];
  const bf16* gate_w = (const bf16*)d_in[9];

  EncFn enc = nullptr;
  cudaDriverEntryPointQueryResult qr;
  cudaGetDriverEntryPoint("cuTensorMapEncodeTiled", (void**)&enc, cudaEnableDefault, &qr);
  void *pQ, *pK, *pV, *pCtx, *pQA;
  cudaGetSymbolAddress(&pQ, g_Q);
  cudaGetSymbolAddress(&pQA, g_QKVA);
  cudaGetSymbolAddress(&pK, g_K);
  cudaGetSymbolAddress(&pV, g_V);
  cudaGetSymbolAddress(&pCtx, g_ctx);

  static Params p;
  enc2d(enc, &p.tmA[0], ckv, DC, S_LEN, 64, 128);
  enc2d(enc, &p.tmA[1], x, DM, S_LEN, 64, 128);
  enc3d(enc, &p.tmW[0], w_uk, HDIM, DC, 16, 4);
  enc3d(enc, &p.tmW[1], w_uv, HDIM, DC, 16, 4);
  enc3d(enc, &p.tmW[2], wqkv, NQKVA, DM, 16, 4);
  enc3d(enc, &p.tmW[3], w_q, HDIM, DM, 16, 4);
  build_k1_jobs(p);
  enc2d(enc, &p.tmQ, pQ, HDIM, S_LEN, 64, 128);
  enc2d(enc, &p.tmK, pK, HDIM, S_LEN, 64, 128);
  enc2d(enc, &p.tmV, pV, HDIM, S_LEN, 64, 128);
  build_k2_items(p);
  build_k3_units(p);
  for (int i = 0; i < 2; i++) {
    cuuint64_t gd[3] = {64, 27, S_LEN}, gs[2] = {128, NQKVA * 2};
    cuuint32_t bx[3] = {64, 9, i ? 16u : 30u}, es[3] = {1, 1, 1};
    enc(&p.tmL[i], CU_TENSOR_MAP_DATA_TYPE_BFLOAT16, 3, pQA, gd, gs, bx, es, CU_TENSOR_MAP_INTERLEAVE_NONE, CU_TENSOR_MAP_SWIZZLE_NONE,
        CU_TENSOR_MAP_L2_PROMOTION_L2_256B, CU_TENSOR_MAP_FLOAT_OOB_FILL_NONE);
  }
  enc2d(enc, &p.tmC, pCtx, KCAT, S_LEN, 64, 128);
  enc3d(enc, &p.tmO[0], w_o, DM, HDIM, 32, 4);
  enc3d(enc, &p.tmO[1], wo, DM, DM, 32, 4);
  enc2d(enc, &p.tmOt[0], w_o, DM, HDIM, 32, 32, CU_TENSOR_MAP_SWIZZLE_64B);
  enc2d(enc, &p.tmOt[1], wo, DM, DM, 32, 32, CU_TENSOR_MAP_SWIZZLE_64B);

  cudaFuncSetAttribute(fused_kernel, cudaFuncAttributeMaxDynamicSharedMemorySize, SMEM_BYTES);
  fused_kernel<<<NCLUSTER * 2, 384, SMEM_BYTES>>>(p, x, gate_w, (bf16*)d_out);
}
```

```cpp
#include <cuda_runtime.h>
#include <cuda_bf16.h>
#include <cuda.h>
#include <stdint.h>

typedef __nv_bfloat16 bf16;

constexpr int S_LEN = 2048, DM = 576, DC = 512, HDIM = 4096, NQKVA = 1728, KCAT = 4672;
constexpr int NCLUSTER = 66;

__device__ __align__(1024) bf16 g_Q[S_LEN * HDIM];
__device__ __align__(1024) bf16 g_K[S_LEN * HDIM];
__device__ __align__(1024) bf16 g_V[S_LEN * HDIM];
__device__ __align__(1024) bf16 g_QKVA[S_LEN * NQKVA + 64];
__device__ __align__(1024) bf16 g_ctx[S_LEN * KCAT];
__device__ float g_gate[S_LEN];
__device__ __align__(1024) uint4 g_part[32 * 4 * 4 * 5 * 256];
__device__ __align__(16) unsigned int g_sync[400];
constexpr int F_QKVA = 0, F_HP = 16, F_CTX = 32, F_OA = 48, F_GATE = 96, F_TICK = 97, F_DONE = 98, F_XCH = 128, F_EPOCH = 384;

__device__ __forceinline__ uint32_t smem_u32(const void* p) { return (uint32_t)__cvta_generic_to_shared(p); }
__device__ __forceinline__ void mbar_init(uint32_t a, uint32_t c) {
  asm volatile("mbarrier.init.shared::cta.b64 [%0], %1;" ::"r"(a), "r"(c));
}
__device__ __forceinline__ void mbar_expect(uint32_t a, uint32_t b) {
  asm volatile("mbarrier.arrive.expect_tx.shared::cta.b64 _, [%0], %1;" ::"r"(a), "r"(b) : "memory");
}
#define TS(k, i)
#define TSC(k, i)
#define TSM(k)
#define BSEG(i)
#define SPIN_LIMIT "4194304"
__device__ __forceinline__ void mbar_wait(uint32_t a, uint32_t parity) {
  asm volatile(
      "{\n.reg .pred p;\n.reg .u32 n;\n"
      "mbarrier.try_wait.parity.shared::cta.b64 p, [%0], %1;\n"
      "@p bra DONE;\n"
      "mov.u32 n, 0;\n"
      "LOOP:\n"
      "mbarrier.try_wait.parity.shared::cta.b64 p, [%0], %1;\n"
      "@p bra DONE;\n"
      "add.u32 n, n, 1;\n"
      "setp.lt.u32 p, n, " SPIN_LIMIT ";\n"
      "@p bra LOOP;\n"
      "DONE:\n}" ::"r"(a), "r"(parity) : "memory");
}
__device__ __forceinline__ void mbar_arrive(uint32_t a) {
  asm volatile("mbarrier.arrive.shared::cta.b64 _, [%0];" ::"r"(a) : "memory");
}
__device__ __forceinline__ void mbar_arrive_cluster(uint32_t a, uint32_t cta) {
  asm volatile("{\n.reg .b32 r;\nmapa.shared::cluster.u32 r, %0, %1;\nmbarrier.arrive.shared::cluster.b64 _, [r];\n}" ::"r"(a),
               "r"(cta) : "memory");
}
__device__ __forceinline__ void mbar_arrive_cluster_if(uint32_t a, uint32_t cta, bool pred) {
  asm volatile("{\n.reg .b32 r;\n.reg .pred p;\nsetp.ne.u32 p, %2, 0;\nmapa.shared::cluster.u32 r, %0, %1;\n@p mbarrier.arrive.shared::cluster.b64 _, [r];\n}" ::"r"(a),
               "r"(cta), "r"((uint32_t)pred) : "memory");
}
__device__ __forceinline__ void mbar_arrive_cluster_after(uint32_t a, uint32_t cta, bool pred, float anchor) {
  asm volatile("{\n.reg .b32 r;\n.reg .pred p;\nsetp.ne.u32 p, %2, 0;\nsetp.leu.and.f32 p, %3, 0f7F800000, p;\n"
               "mapa.shared::cluster.u32 r, %0, %1;\n@p mbarrier.arrive.shared::cluster.b64 _, [r];\n}" ::"r"(a),
               "r"(cta), "r"((uint32_t)pred), "f"(anchor) : "memory");
}
__device__ __forceinline__ void anchor(float v, uint32_t pred) {
  asm volatile("{\n.reg .pred p;\nsetp.ne.u32 p, %1, 0;\n@p st.shared.f32 [%1], %0;\n}" ::"f"(v), "r"(pred) : "memory");
}
__device__ __forceinline__ void mbar_arrive_if(uint32_t a, bool pred) {
  asm volatile("{\n.reg .pred p;\nsetp.ne.u32 p, %1, 0;\n@p mbarrier.arrive.shared::cta.b64 _, [%0];\n}" ::"r"(a), "r"((uint32_t)pred) : "memory");
}
__device__ __forceinline__ void tma2d(uint32_t dst, const CUtensorMap* m, uint32_t bar, int c0, int c1) {
  asm volatile("cp.async.bulk.tensor.2d.shared::cluster.global.mbarrier::complete_tx::bytes [%0], [%1, {%3, %4}], [%2];" ::"r"(dst),
               "l"(m), "r"(bar), "r"(c0), "r"(c1) : "memory");
}
__device__ __forceinline__ void tma2d_mc(uint32_t dst, const CUtensorMap* m, uint32_t bar, int c0, int c1, uint16_t mask) {
  asm volatile(
      "cp.async.bulk.tensor.2d.shared::cluster.global.mbarrier::complete_tx::bytes.multicast::cluster [%0], [%1, {%3, %4}], [%2], %5;" ::"r"(dst),
      "l"(m), "r"(bar), "r"(c0), "r"(c1), "h"(mask) : "memory");
}
__device__ __forceinline__ void tma3d_mc(uint32_t dst, const CUtensorMap* m, uint32_t bar, int c0, int c1, int c2, uint16_t mask) {
  asm volatile(
      "cp.async.bulk.tensor.3d.shared::cluster.global.mbarrier::complete_tx::bytes.multicast::cluster [%0], [%1, {%3, %4, %5}], [%2], %6;" ::"r"(dst),
      "l"(m), "r"(bar), "r"(c0), "r"(c1), "r"(c2), "h"(mask) : "memory");
}
__device__ __forceinline__ uint64_t policy_evict_first() {
  uint64_t p;
  asm volatile("createpolicy.fractional.L2::evict_first.b64 %0, 1.0;" : "=l"(p));
  return p;
}
__device__ __forceinline__ void tma3d_mc_h(uint32_t dst, const CUtensorMap* m, uint32_t bar, int c0, int c1, int c2, uint16_t mask, uint64_t pol) {
  asm volatile(
      "cp.async.bulk.tensor.3d.shared::cluster.global.mbarrier::complete_tx::bytes.multicast::cluster.L2::cache_hint [%0], [%1, {%3, %4, %5}], [%2], %6, %7;" ::"r"(dst),
      "l"(m), "r"(bar), "r"(c0), "r"(c1), "r"(c2), "h"(mask), "l"(pol) : "memory");
}
__device__ __forceinline__ void tma2d_h(uint32_t dst, const CUtensorMap* m, uint32_t bar, int c0, int c1, uint64_t pol) {
  asm volatile("cp.async.bulk.tensor.2d.shared::cluster.global.mbarrier::complete_tx::bytes.L2::cache_hint [%0], [%1, {%3, %4}], [%2], %5;" ::"r"(dst),
               "l"(m), "r"(bar), "r"(c0), "r"(c1), "l"(pol) : "memory");
}
__device__ __forceinline__ void tma3d(uint32_t dst, const CUtensorMap* m, uint32_t bar, int c0, int c1, int c2) {
  asm volatile(
      "cp.async.bulk.tensor.3d.shared::cluster.global.mbarrier::complete_tx::bytes [%0], [%1, {%3, %4, %5}], [%2];" ::"r"(dst),
      "l"(m), "r"(bar), "r"(c0), "r"(c1), "r"(c2) : "memory");
}
__device__ __forceinline__ void tma_pf2d(const CUtensorMap* m, int c0, int c1) {
  asm volatile("cp.async.bulk.prefetch.tensor.2d.L2.global [%0, {%1, %2}];" ::"l"(m), "r"(c0), "r"(c1) : "memory");
}
__device__ __forceinline__ void tma_pf3d(const CUtensorMap* m, int c0, int c1, int c2) {
  asm volatile("cp.async.bulk.prefetch.tensor.3d.L2.global [%0, {%1, %2, %3}];" ::"l"(m), "r"(c0), "r"(c1), "r"(c2) : "memory");
}
__device__ __forceinline__ void prefetch_tmap(const CUtensorMap* m) {
  asm volatile("prefetch.tensormap [%0];" ::"l"(m) : "memory");
}
__device__ __forceinline__ void cluster_arrive() { asm volatile("barrier.cluster.arrive.relaxed.aligned;" ::: "memory"); }
__device__ __forceinline__ void cluster_wait() { asm volatile("barrier.cluster.wait.aligned;" ::: "memory"); }
__device__ __forceinline__ void cluster_sync() {
  cluster_arrive();
  cluster_wait();
}
__device__ __forceinline__ uint32_t cluster_rank() {
  uint32_t r;
  asm volatile("mov.u32 %0, %%cluster_ctarank;" : "=r"(r));
  return r;
}
__device__ __forceinline__ bool elect_one() {
  uint32_t p;
  asm volatile("{\n.reg .pred q;\nelect.sync _|q, 0xffffffff;\nselp.u32 %0, 1, 0, q;\n}" : "=r"(p));
  return p;
}
__device__ __forceinline__ void pdl_wait() { asm volatile("griddepcontrol.wait;" ::: "memory"); }
__device__ __forceinline__ void pdl_launch() { asm volatile("griddepcontrol.launch_dependents;" ::: "memory"); }
__device__ __forceinline__ void ldsm_x4(uint32_t& r0, uint32_t& r1, uint32_t& r2, uint32_t& r3, uint32_t addr) {
  asm volatile("ldmatrix.sync.aligned.m8n8.x4.shared.b16 {%0, %1, %2, %3}, [%4];" : "=r"(r0), "=r"(r1), "=r"(r2), "=r"(r3) : "r"(addr) : "memory");
}
__device__ __forceinline__ void wg_fence() { asm volatile("wgmma.fence.sync.aligned;" ::: "memory"); }
__device__ __forceinline__ void wg_commit() { asm volatile("wgmma.commit_group.sync.aligned;" ::: "memory"); }
template <int N>
__device__ __forceinline__ void wg_wait() { asm volatile("wgmma.wait_group.sync.aligned %0;" ::"n"(N) : "memory"); }
template <int N>
__device__ __forceinline__ void reg_alloc() { asm volatile("setmaxnreg.inc.sync.aligned.u32 %0;" ::"n"(N)); }
template <int N>
__device__ __forceinline__ void reg_dealloc() { asm volatile("setmaxnreg.dec.sync.aligned.u32 %0;" ::"n"(N)); }
__device__ __forceinline__ void bar_sync(int id, int n) { asm volatile("bar.sync %0, %1;" ::"r"(id), "r"(n) : "memory"); }
__device__ __forceinline__ void bar_arrive(int id, int n) { asm volatile("bar.arrive %0, %1;" ::"r"(id), "r"(n) : "memory"); }
template <int NT>
__device__ __forceinline__ void fence_regs(float (&d)[NT]) {
#pragma unroll
  for (int i = 0; i < NT; i++) asm volatile("" : "+f"(d[i])::"memory");
}
template <int NT>
__device__ __forceinline__ void fence_regs(uint32_t (&d)[NT]) {
#pragma unroll
  for (int i = 0; i < NT; i++) asm volatile("" : "+r"(d[i])::"memory");
}
__device__ __forceinline__ uint64_t make_desc(uint32_t saddr, uint32_t lbo, uint32_t sbo, uint32_t layout) {
  return (uint64_t)((saddr & 0x3FFFF) >> 4) | ((uint64_t)(lbo >> 4) << 16) | ((uint64_t)(sbo >> 4) << 32) | ((uint64_t)layout << 62);
}
__device__ __forceinline__ uint32_t pack_bf16(float lo, float hi) {
  uint32_t r;
  asm("cvt.rn.bf16x2.f32 %0, %1, %2;" : "=r"(r) : "f"(hi), "f"(lo));
  return r;
}
__device__ __forceinline__ float ex2(float x) {
  float r;
  asm("ex2.approx.ftz.f32 %0, %1;" : "=f"(r) : "f"(x));
  return r;
}
__device__ __forceinline__ void st_v4(void* p, uint32_t a, uint32_t b, uint32_t c, uint32_t d) {
#define ST_MOD ".cs"
  asm volatile("st.global" ST_MOD ".v4.b32 [%0], {%1, %2, %3, %4};" ::"l"(p), "r"(a), "r"(b), "r"(c), "r"(d) : "memory");
}
#define STA_MOD ".cs"
__device__ __forceinline__ void st_v4a(void* p, uint32_t a, uint32_t b, uint32_t c, uint32_t d) {
  asm volatile("st.global" STA_MOD ".v4.b32 [%0], {%1, %2, %3, %4};" ::"l"(p), "r"(a), "r"(b), "r"(c), "r"(d) : "memory");
}
__device__ __forceinline__ float bf_lo(uint32_t v) { return __uint_as_float(v << 16); }
__device__ __forceinline__ float bf_hi(uint32_t v) { return __uint_as_float(v & 0xFFFF0000u); }

__device__ __forceinline__ void quad_transpose(uint32_t& a0, uint32_t& a1, uint32_t& a2, uint32_t& a3, int q) {
  const bool o1 = q & 1, o2 = q & 2;
  uint32_t t0 = o1 ? a0 : a1, t1 = o1 ? a2 : a3;
  t0 = __shfl_xor_sync(0xffffffffu, t0, 1);
  t1 = __shfl_xor_sync(0xffffffffu, t1, 1);
  if (o1) { a0 = t0; a2 = t1; } else { a1 = t0; a3 = t1; }
  t0 = o2 ? a0 : a2;
  t1 = o2 ? a1 : a3;
  t0 = __shfl_xor_sync(0xffffffffu, t0, 2);
  t1 = __shfl_xor_sync(0xffffffffu, t1, 2);
  if (o2) { a0 = t0; a1 = t1; } else { a2 = t0; a3 = t1; }
}

template<int TB, int OFF, int NT>
__device__ __forceinline__ void wgmma_ss_n256(float (&d)[NT], uint64_t da, uint64_t db, int scale_d) {
  asm volatile("{\n.reg .pred p;\nsetp.ne.b32 p, %130, 0;\n"
    "wgmma.mma_async.sync.aligned.m64n256k16.f32.bf16.bf16 {%0, %1, %2, %3, %4, %5, %6, %7, %8, %9, %10, %11, %12, %13, %14, %15, %16, %17, %18, %19, %20, %21, %22, %23, %24, %25, %26, %27, %28, %29, %30, %31, %32, %33, %34, %35, %36, %37, %38, %39, %40, %41, %42, %43, %44, %45, %46, %47, %48, %49, %50, %51, %52, %53, %54, %55, %56, %57, %58, %59, %60, %61, %62, %63, %64, %65, %66, %67, %68, %69, %70, %71, %72, %73, %74, %75, %76, %77, %78, %79, %80, %81, %82, %83, %84, %85, %86, %87, %88, %89, %90, %91, %92, %93, %94, %95, %96, %97, %98, %99, %100, %101, %102, %103, %104, %105, %106, %107, %108, %109, %110, %111, %112, %113, %114, %115, %116, %117, %118, %119, %120, %121, %122, %123, %124, %125, %126, %127}, %128, %129, p, 1, 1, 0, %131;\n}\n"
    : "+f"(d[OFF+0]), "+f"(d[OFF+1]), "+f"(d[OFF+2]), "+f"(d[OFF+3]), "+f"(d[OFF+4]), "+f"(d[OFF+5]), "+f"(d[OFF+6]), "+f"(d[OFF+7]), "+f"(d[OFF+8]), "+f"(d[OFF+9]), "+f"(d[OFF+10]), "+f"(d[OFF+11]), "+f"(d[OFF+12]), "+f"(d[OFF+13]), "+f"(d[OFF+14]), "+f"(d[OFF+15]), "+f"(d[OFF+16]), "+f"(d[OFF+17]), "+f"(d[OFF+18]), "+f"(d[OFF+19]), "+f"(d[OFF+20]), "+f"(d[OFF+21]), "+f"(d[OFF+22]), "+f"(d[OFF+23]), "+f"(d[OFF+24]), "+f"(d[OFF+25]), "+f"(d[OFF+26]), "+f"(d[OFF+27]), "+f"(d[OFF+28]), "+f"(d[OFF+29]), "+f"(d[OFF+30]), "+f"(d[OFF+31]), "+f"(d[OFF+32]), "+f"(d[OFF+33]), "+f"(d[OFF+34]), "+f"(d[OFF+35]), "+f"(d[OFF+36]), "+f"(d[OFF+37]), "+f"(d[OFF+38]), "+f"(d[OFF+39]), "+f"(d[OFF+40]), "+f"(d[OFF+41]), "+f"(d[OFF+42]), "+f"(d[OFF+43]), "+f"(d[OFF+44]), "+f"(d[OFF+45]), "+f"(d[OFF+46]), "+f"(d[OFF+47]), "+f"(d[OFF+48]), "+f"(d[OFF+49]), "+f"(d[OFF+50]), "+f"(d[OFF+51]), "+f"(d[OFF+52]), "+f"(d[OFF+53]), "+f"(d[OFF+54]), "+f"(d[OFF+55]), "+f"(d[OFF+56]), "+f"(d[OFF+57]), "+f"(d[OFF+58]), "+f"(d[OFF+59]), "+f"(d[OFF+60]), "+f"(d[OFF+61]), "+f"(d[OFF+62]), "+f"(d[OFF+63]), "+f"(d[OFF+64]), "+f"(d[OFF+65]), "+f"(d[OFF+66]), "+f"(d[OFF+67]), "+f"(d[OFF+68]), "+f"(d[OFF+69]), "+f"(d[OFF+70]), "+f"(d[OFF+71]), "+f"(d[OFF+72]), "+f"(d[OFF+73]), "+f"(d[OFF+74]), "+f"(d[OFF+75]), "+f"(d[OFF+76]), "+f"(d[OFF+77]), "+f"(d[OFF+78]), "+f"(d[OFF+79]), "+f"(d[OFF+80]), "+f"(d[OFF+81]), "+f"(d[OFF+82]), "+f"(d[OFF+83]), "+f"(d[OFF+84]), "+f"(d[OFF+85]), "+f"(d[OFF+86]), "+f"(d[OFF+87]), "+f"(d[OFF+88]), "+f"(d[OFF+89]), "+f"(d[OFF+90]), "+f"(d[OFF+91]), "+f"(d[OFF+92]), "+f"(d[OFF+93]), "+f"(d[OFF+94]), "+f"(d[OFF+95]), "+f"(d[OFF+96]), "+f"(d[OFF+97]), "+f"(d[OFF+98]), "+f"(d[OFF+99]), "+f"(d[OFF+100]), "+f"(d[OFF+101]), "+f"(d[OFF+102]), "+f"(d[OFF+103]), "+f"(d[OFF+104]), "+f"(d[OFF+105]), "+f"(d[OFF+106]), "+f"(d[OFF+107]), "+f"(d[OFF+108]), "+f"(d[OFF+109]), "+f"(d[OFF+110]), "+f"(d[OFF+111]), "+f"(d[OFF+112]), "+f"(d[OFF+113]), "+f"(d[OFF+114]), "+f"(d[OFF+115]), "+f"(d[OFF+116]), "+f"(d[OFF+117]), "+f"(d[OFF+118]), "+f"(d[OFF+119]), "+f"(d[OFF+120]), "+f"(d[OFF+121]), "+f"(d[OFF+122]), "+f"(d[OFF+123]), "+f"(d[OFF+124]), "+f"(d[OFF+125]), "+f"(d[OFF+126]), "+f"(d[OFF+127])
    : "l"(da), "l"(db), "r"(scale_d), "n"(TB));
}
template<int TB, int OFF, int NT>
__device__ __forceinline__ void wgmma_ss_n192(float (&d)[NT], uint64_t da, uint64_t db, int scale_d) {
  asm volatile("{\n.reg .pred p;\nsetp.ne.b32 p, %98, 0;\n"
    "wgmma.mma_async.sync.aligned.m64n192k16.f32.bf16.bf16 {%0, %1, %2, %3, %4, %5, %6, %7, %8, %9, %10, %11, %12, %13, %14, %15, %16, %17, %18, %19, %20, %21, %22, %23, %24, %25, %26, %27, %28, %29, %30, %31, %32, %33, %34, %35, %36, %37, %38, %39, %40, %41, %42, %43, %44, %45, %46, %47, %48, %49, %50, %51, %52, %53, %54, %55, %56, %57, %58, %59, %60, %61, %62, %63, %64, %65, %66, %67, %68, %69, %70, %71, %72, %73, %74, %75, %76, %77, %78, %79, %80, %81, %82, %83, %84, %85, %86, %87, %88, %89, %90, %91, %92, %93, %94, %95}, %96, %97, p, 1, 1, 0, %99;\n}\n"
    : "+f"(d[OFF+0]), "+f"(d[OFF+1]), "+f"(d[OFF+2]), "+f"(d[OFF+3]), "+f"(d[OFF+4]), "+f"(d[OFF+5]), "+f"(d[OFF+6]), "+f"(d[OFF+7]), "+f"(d[OFF+8]), "+f"(d[OFF+9]), "+f"(d[OFF+10]), "+f"(d[OFF+11]), "+f"(d[OFF+12]), "+f"(d[OFF+13]), "+f"(d[OFF+14]), "+f"(d[OFF+15]), "+f"(d[OFF+16]), "+f"(d[OFF+17]), "+f"(d[OFF+18]), "+f"(d[OFF+19]), "+f"(d[OFF+20]), "+f"(d[OFF+21]), "+f"(d[OFF+22]), "+f"(d[OFF+23]), "+f"(d[OFF+24]), "+f"(d[OFF+25]), "+f"(d[OFF+26]), "+f"(d[OFF+27]), "+f"(d[OFF+28]), "+f"(d[OFF+29]), "+f"(d[OFF+30]), "+f"(d[OFF+31]), "+f"(d[OFF+32]), "+f"(d[OFF+33]), "+f"(d[OFF+34]), "+f"(d[OFF+35]), "+f"(d[OFF+36]), "+f"(d[OFF+37]), "+f"(d[OFF+38]), "+f"(d[OFF+39]), "+f"(d[OFF+40]), "+f"(d[OFF+41]), "+f"(d[OFF+42]), "+f"(d[OFF+43]), "+f"(d[OFF+44]), "+f"(d[OFF+45]), "+f"(d[OFF+46]), "+f"(d[OFF+47]), "+f"(d[OFF+48]), "+f"(d[OFF+49]), "+f"(d[OFF+50]), "+f"(d[OFF+51]), "+f"(d[OFF+52]), "+f"(d[OFF+53]), "+f"(d[OFF+54]), "+f"(d[OFF+55]), "+f"(d[OFF+56]), "+f"(d[OFF+57]), "+f"(d[OFF+58]), "+f"(d[OFF+59]), "+f"(d[OFF+60]), "+f"(d[OFF+61]), "+f"(d[OFF+62]), "+f"(d[OFF+63]), "+f"(d[OFF+64]), "+f"(d[OFF+65]), "+f"(d[OFF+66]), "+f"(d[OFF+67]), "+f"(d[OFF+68]), "+f"(d[OFF+69]), "+f"(d[OFF+70]), "+f"(d[OFF+71]), "+f"(d[OFF+72]), "+f"(d[OFF+73]), "+f"(d[OFF+74]), "+f"(d[OFF+75]), "+f"(d[OFF+76]), "+f"(d[OFF+77]), "+f"(d[OFF+78]), "+f"(d[OFF+79]), "+f"(d[OFF+80]), "+f"(d[OFF+81]), "+f"(d[OFF+82]), "+f"(d[OFF+83]), "+f"(d[OFF+84]), "+f"(d[OFF+85]), "+f"(d[OFF+86]), "+f"(d[OFF+87]), "+f"(d[OFF+88]), "+f"(d[OFF+89]), "+f"(d[OFF+90]), "+f"(d[OFF+91]), "+f"(d[OFF+92]), "+f"(d[OFF+93]), "+f"(d[OFF+94]), "+f"(d[OFF+95])
    : "l"(da), "l"(db), "r"(scale_d), "n"(TB));
}
template<int TB, int OFF, int NT>
__device__ __forceinline__ void wgmma_ss_n128(float (&d)[NT], uint64_t da, uint64_t db, int scale_d) {
  asm volatile("{\n.reg .pred p;\nsetp.ne.b32 p, %66, 0;\n"
    "wgmma.mma_async.sync.aligned.m64n128k16.f32.bf16.bf16 {%0, %1, %2, %3, %4, %5, %6, %7, %8, %9, %10, %11, %12, %13, %14, %15, %16, %17, %18, %19, %20, %21, %22, %23, %24, %25, %26, %27, %28, %29, %30, %31, %32, %33, %34, %35, %36, %37, %38, %39, %40, %41, %42, %43, %44, %45, %46, %47, %48, %49, %50, %51, %52, %53, %54, %55, %56, %57, %58, %59, %60, %61, %62, %63}, %64, %65, p, 1, 1, 0, %67;\n}\n"
    : "+f"(d[OFF+0]), "+f"(d[OFF+1]), "+f"(d[OFF+2]), "+f"(d[OFF+3]), "+f"(d[OFF+4]), "+f"(d[OFF+5]), "+f"(d[OFF+6]), "+f"(d[OFF+7]), "+f"(d[OFF+8]), "+f"(d[OFF+9]), "+f"(d[OFF+10]), "+f"(d[OFF+11]), "+f"(d[OFF+12]), "+f"(d[OFF+13]), "+f"(d[OFF+14]), "+f"(d[OFF+15]), "+f"(d[OFF+16]), "+f"(d[OFF+17]), "+f"(d[OFF+18]), "+f"(d[OFF+19]), "+f"(d[OFF+20]), "+f"(d[OFF+21]), "+f"(d[OFF+22]), "+f"(d[OFF+23]), "+f"(d[OFF+24]), "+f"(d[OFF+25]), "+f"(d[OFF+26]), "+f"(d[OFF+27]), "+f"(d[OFF+28]), "+f"(d[OFF+29]), "+f"(d[OFF+30]), "+f"(d[OFF+31]), "+f"(d[OFF+32]), "+f"(d[OFF+33]), "+f"(d[OFF+34]), "+f"(d[OFF+35]), "+f"(d[OFF+36]), "+f"(d[OFF+37]), "+f"(d[OFF+38]), "+f"(d[OFF+39]), "+f"(d[OFF+40]), "+f"(d[OFF+41]), "+f"(d[OFF+42]), "+f"(d[OFF+43]), "+f"(d[OFF+44]), "+f"(d[OFF+45]), "+f"(d[OFF+46]), "+f"(d[OFF+47]), "+f"(d[OFF+48]), "+f"(d[OFF+49]), "+f"(d[OFF+50]), "+f"(d[OFF+51]), "+f"(d[OFF+52]), "+f"(d[OFF+53]), "+f"(d[OFF+54]), "+f"(d[OFF+55]), "+f"(d[OFF+56]), "+f"(d[OFF+57]), "+f"(d[OFF+58]), "+f"(d[OFF+59]), "+f"(d[OFF+60]), "+f"(d[OFF+61]), "+f"(d[OFF+62]), "+f"(d[OFF+63])
    : "l"(da), "l"(db), "r"(scale_d), "n"(TB));
}
template<int TB, int OFF, int NT>
__device__ __forceinline__ void wgmma_ss_n32(float (&d)[NT], uint64_t da, uint64_t db, int scale_d) {
  asm volatile("{\n.reg .pred p;\nsetp.ne.b32 p, %18, 0;\n"
    "wgmma.mma_async.sync.aligned.m64n32k16.f32.bf16.bf16 {%0, %1, %2, %3, %4, %5, %6, %7, %8, %9, %10, %11, %12, %13, %14, %15}, %16, %17, p, 1, 1, 0, %19;\n}\n"
    : "+f"(d[OFF+0]), "+f"(d[OFF+1]), "+f"(d[OFF+2]), "+f"(d[OFF+3]), "+f"(d[OFF+4]), "+f"(d[OFF+5]), "+f"(d[OFF+6]), "+f"(d[OFF+7]), "+f"(d[OFF+8]), "+f"(d[OFF+9]), "+f"(d[OFF+10]), "+f"(d[OFF+11]), "+f"(d[OFF+12]), "+f"(d[OFF+13]), "+f"(d[OFF+14]), "+f"(d[OFF+15])
    : "l"(da), "l"(db), "r"(scale_d), "n"(TB));
}
template<int TB, int OFF, int NT>
__device__ __forceinline__ void wgmma_rs_n128(float (&d)[NT], uint32_t a0, uint32_t a1, uint32_t a2, uint32_t a3, uint64_t db, int scale_d) {
  asm volatile("{\n.reg .pred p;\nsetp.ne.b32 p, %69, 0;\n"
    "wgmma.mma_async.sync.aligned.m64n128k16.f32.bf16.bf16 {%0, %1, %2, %3, %4, %5, %6, %7, %8, %9, %10, %11, %12, %13, %14, %15, %16, %17, %18, %19, %20, %21, %22, %23, %24, %25, %26, %27, %28, %29, %30, %31, %32, %33, %34, %35, %36, %37, %38, %39, %40, %41, %42, %43, %44, %45, %46, %47, %48, %49, %50, %51, %52, %53, %54, %55, %56, %57, %58, %59, %60, %61, %62, %63}, {%64, %65, %66, %67}, %68, p, 1, 1, %70;\n}\n"
    : "+f"(d[OFF+0]), "+f"(d[OFF+1]), "+f"(d[OFF+2]), "+f"(d[OFF+3]), "+f"(d[OFF+4]), "+f"(d[OFF+5]), "+f"(d[OFF+6]), "+f"(d[OFF+7]), "+f"(d[OFF+8]), "+f"(d[OFF+9]), "+f"(d[OFF+10]), "+f"(d[OFF+11]), "+f"(d[OFF+12]), "+f"(d[OFF+13]), "+f"(d[OFF+14]), "+f"(d[OFF+15]), "+f"(d[OFF+16]), "+f"(d[OFF+17]), "+f"(d[OFF+18]), "+f"(d[OFF+19]), "+f"(d[OFF+20]), "+f"(d[OFF+21]), "+f"(d[OFF+22]), "+f"(d[OFF+23]), "+f"(d[OFF+24]), "+f"(d[OFF+25]), "+f"(d[OFF+26]), "+f"(d[OFF+27]), "+f"(d[OFF+28]), "+f"(d[OFF+29]), "+f"(d[OFF+30]), "+f"(d[OFF+31]), "+f"(d[OFF+32]), "+f"(d[OFF+33]), "+f"(d[OFF+34]), "+f"(d[OFF+35]), "+f"(d[OFF+36]), "+f"(d[OFF+37]), "+f"(d[OFF+38]), "+f"(d[OFF+39]), "+f"(d[OFF+40]), "+f"(d[OFF+41]), "+f"(d[OFF+42]), "+f"(d[OFF+43]), "+f"(d[OFF+44]), "+f"(d[OFF+45]), "+f"(d[OFF+46]), "+f"(d[OFF+47]), "+f"(d[OFF+48]), "+f"(d[OFF+49]), "+f"(d[OFF+50]), "+f"(d[OFF+51]), "+f"(d[OFF+52]), "+f"(d[OFF+53]), "+f"(d[OFF+54]), "+f"(d[OFF+55]), "+f"(d[OFF+56]), "+f"(d[OFF+57]), "+f"(d[OFF+58]), "+f"(d[OFF+59]), "+f"(d[OFF+60]), "+f"(d[OFF+61]), "+f"(d[OFF+62]), "+f"(d[OFF+63])
    : "r"(a0), "r"(a1), "r"(a2), "r"(a3), "l"(db), "r"(scale_d), "n"(TB));
}
template<int TB, int OFF, int NT>
__device__ __forceinline__ void wgmma_rs_n64(float (&d)[NT], uint32_t a0, uint32_t a1, uint32_t a2, uint32_t a3, uint64_t db, int scale_d) {
  asm volatile("{\n.reg .pred p;\nsetp.ne.b32 p, %37, 0;\n"
    "wgmma.mma_async.sync.aligned.m64n64k16.f32.bf16.bf16 {%0, %1, %2, %3, %4, %5, %6, %7, %8, %9, %10, %11, %12, %13, %14, %15, %16, %17, %18, %19, %20, %21, %22, %23, %24, %25, %26, %27, %28, %29, %30, %31}, {%32, %33, %34, %35}, %36, p, 1, 1, %38;\n}\n"
    : "+f"(d[OFF+0]), "+f"(d[OFF+1]), "+f"(d[OFF+2]), "+f"(d[OFF+3]), "+f"(d[OFF+4]), "+f"(d[OFF+5]), "+f"(d[OFF+6]), "+f"(d[OFF+7]), "+f"(d[OFF+8]), "+f"(d[OFF+9]), "+f"(d[OFF+10]), "+f"(d[OFF+11]), "+f"(d[OFF+12]), "+f"(d[OFF+13]), "+f"(d[OFF+14]), "+f"(d[OFF+15]), "+f"(d[OFF+16]), "+f"(d[OFF+17]), "+f"(d[OFF+18]), "+f"(d[OFF+19]), "+f"(d[OFF+20]), "+f"(d[OFF+21]), "+f"(d[OFF+22]), "+f"(d[OFF+23]), "+f"(d[OFF+24]), "+f"(d[OFF+25]), "+f"(d[OFF+26]), "+f"(d[OFF+27]), "+f"(d[OFF+28]), "+f"(d[OFF+29]), "+f"(d[OFF+30]), "+f"(d[OFF+31])
    : "r"(a0), "r"(a1), "r"(a2), "r"(a3), "l"(db), "r"(scale_d), "n"(TB));
}

__device__ __forceinline__ void wait_flag(const unsigned int* f, uint32_t target) {
  uint32_t v;
#pragma unroll 1
  for (uint32_t spins = 0; spins < (1u << 22); spins++) {
    asm volatile("ld.acquire.gpu.global.u32 %0, [%1];" : "=r"(v) : "l"(f) : "memory");
    if (v >= target) break;
    __nanosleep(100);
  }
}
__device__ __forceinline__ uint32_t lds32(uint32_t a) {
  uint32_t v;
  asm volatile("ld.shared.u32 %0, [%1];" : "=r"(v) : "r"(a) : "memory");
  return v;
}
__device__ __forceinline__ float gate_row(int row, int lane, const bf16* __restrict__ x, const bf16* __restrict__ gate_w) {
  const uint32_t* xr = reinterpret_cast<const uint32_t*>(x + (size_t)row * DM);
  const uint32_t* gw2 = reinterpret_cast<const uint32_t*>(gate_w);
  float gs = 0.f;
#pragma unroll
  for (int i = 0; i < 9; i++) {
    const uint32_t a = __ldg(xr + lane + 32 * i), b = __ldg(gw2 + lane + 32 * i);
    gs = fmaf(bf_lo(a), bf_lo(b), gs);
    gs = fmaf(bf_hi(a), bf_hi(b), gs);
  }
#pragma unroll
  for (int o = 16; o; o >>= 1) gs += __shfl_xor_sync(0xffffffffu, gs, o);
  const float g = 1.f / (1.f + __expf(-gs));
  if (lane == 0) g_gate[row] = g;
  return g;
}
#define LA_UNROLL 9
__device__ __forceinline__ void local_rows2(int rb, int ri, uint32_t sL, uint32_t bL2, int lane, float ga, float gb) {
  const float scale_l2 = 0.23570226039551584f * 1.4426950408889634f;
  constexpr int U = LA_UNROLL;
  const uint32_t sq = sL + (30 + ri) * 1152;
  const uint32_t kb = sL + (14 + ri) * 1152 + lane * 36;
  float ma = -INFINITY, mb = -INFINITY;
  {
    float qa[18], qb[18];
#pragma unroll
    for (int i = 0; i < 9; i++) {
      const uint32_t u = lds32(sq - 2304 + lane * 36 + 4 * i), v = lds32(sq + lane * 36 + 4 * i);
      qa[2 * i] = bf_lo(u); qa[2 * i + 1] = bf_hi(u);
      qb[2 * i] = bf_lo(v); qb[2 * i + 1] = bf_hi(v);
    }
    __syncwarp();
#pragma unroll U
    for (int t = 0; t < 9; t++) {
      const bool ok = rb - 2 * t >= 0;
      float a0 = 0.f, a1 = 0.f, b0 = 0.f, b1 = 0.f;
#pragma unroll
      for (int i = 0; i < 9; i++) {
        const uint32_t k = lds32(kb - t * 2304 + 4 * i);
        const float lo = bf_lo(k), hi = bf_hi(k);
        a0 = fmaf(qa[2 * i], lo, a0); a1 = fmaf(qa[2 * i + 1], hi, a1);
        b0 = fmaf(qb[2 * i], lo, b0); b1 = fmaf(qb[2 * i + 1], hi, b1);
      }
      a0 = (ok && t > 0) ? a0 + a1 : -INFINITY;
      b0 = (ok && t < 8) ? b0 + b1 : -INFINITY;
      ma = fmaxf(ma, a0);
      mb = fmaxf(mb, b0);
      asm volatile("st.shared.f32 [%0], %1;" ::"r"(sq - 2304 + t * 128 + lane * 4), "f"(a0) : "memory");
      asm volatile("st.shared.f32 [%0], %1;" ::"r"(sq + t * 128 + lane * 4), "f"(b0) : "memory");
    }
  }
  float oa[18], ob[18], sa = 0.f, sb = 0.f;
#pragma unroll
  for (int i = 0; i < 18; i++) { oa[i] = 0.f; ob[i] = 0.f; }
  mbar_wait(bL2, 0);
#pragma unroll U
  for (int t = 0; t < 9; t++) {
    const float wa = ex2((__uint_as_float(lds32(sq - 2304 + t * 128 + lane * 4)) - ma) * scale_l2);
    const float wb = ex2((__uint_as_float(lds32(sq + t * 128 + lane * 4)) - mb) * scale_l2);
    sa += wa;
    sb += wb;
#pragma unroll
    for (int i = 0; i < 9; i++) {
      const uint32_t v = lds32(kb + 46 * 1152 - t * 2304 + 4 * i);
      const float lo = bf_lo(v), hi = bf_hi(v);
      oa[2 * i] = fmaf(wa, lo, oa[2 * i]); oa[2 * i + 1] = fmaf(wa, hi, oa[2 * i + 1]);
      ob[2 * i] = fmaf(wb, lo, ob[2 * i]); ob[2 * i + 1] = fmaf(wb, hi, ob[2 * i + 1]);
    }
  }
  ga = __fdividef(ga, sa);
  gb = __fdividef(gb, sb);
  __syncwarp();
#pragma unroll
  for (int i = 0; i < 9; i++) {
    asm volatile("st.shared.u32 [%0], %1;" ::"r"(sq - 2304 + lane * 36 + 4 * i), "r"(pack_bf16(oa[2 * i] * ga, oa[2 * i + 1] * ga)) : "memory");
    asm volatile("st.shared.u32 [%0], %1;" ::"r"(sq + lane * 36 + 4 * i), "r"(pack_bf16(ob[2 * i] * gb, ob[2 * i + 1] * gb)) : "memory");
  }
  __syncwarp();
  uint32_t w[5][4];
#pragma unroll
  for (int t = 0; t < 5; t++) {
    const int c = min(t * 32 + lane, 143), r = c >= 72;
    asm volatile("ld.shared.v4.u32 {%0, %1, %2, %3}, [%4];" : "=r"(w[t][0]), "=r"(w[t][1]), "=r"(w[t][2]), "=r"(w[t][3])
                 : "r"(sq - 2304 + r * 2304 + (c - r * 72) * 16) : "memory");
  }
  asm volatile("fence.proxy.async.shared::cta;" ::: "memory");
  bar_arrive(4, 256 + 32);
#pragma unroll
  for (int t = 0; t < 5; t++) {
    const int c = min(t * 32 + lane, 143), r = c >= 72;
    st_v4(g_ctx + (size_t)(rb - 2 + 2 * r) * KCAT + HDIM + (c - r * 72) * 8, w[t][0], w[t][1], w[t][2], w[t][3]);
  }
}

#define K1_NST 6
constexpr int K1_BST = K1_NST;
constexpr int K1_MAXJOBS = 11;
constexpr uint32_t K1_FLAG_TARGET = 7;
constexpr uint32_t RDY_TARGET = 48;
constexpr uint32_t GATE_TARGET = 128 * 3;
struct alignas(64) Params {
  CUtensorMap tmA[2];
  CUtensorMap tmW[4];
  CUtensorMap tmQ, tmK, tmV;
  CUtensorMap tmL[2];
  CUtensorMap tmC, tmO[2], tmOt[2];
  uint16_t jobs[NCLUSTER][K1_MAXJOBS];
  uint8_t order[256];
  uint8_t unit[64][4];
};

struct K1State {
  uint32_t bs, bph, aph;
  bf16* pp;
  int pld8;
  int png;
};
__device__ __forceinline__ void k1_flag(const K1State& st, int lane, uint32_t bS) {
  if (st.png) {
    __syncwarp();
    if (lane == 0) mbar_arrive(bS);
  }
}

__device__ __forceinline__ void k1_tile(float (&acc)[128], uint32_t (&pk)[64], K1State& st, uint32_t job, uint32_t sA, uint32_t sB,
                                        uint32_t bAf, uint32_t bAe, uint32_t bBf, uint32_t bBe, uint32_t bS, int wg, int warp, int lane, uint32_t rank) {
  const int a_sel = (job >> 2) & 1, mpair = (job >> 3) & 7, w_sel = (job >> 6) & 3, chunk0 = (job >> 8) & 63;
  const bool newA = (job >> 14) & 1, lastA = (job >> 15) & 1;
  const bool sig = (lane == 0) && (warp < 2);
  const bool siga = lastA && (lane == 0) && (warp == 2);
  const int KC = 8 + a_sel;
  uint32_t prev_bs = 0, prev2_bs = 0, a8_bs = 0;
#pragma unroll
  for (int kc = 0; kc < 9; kc++) {
    if (kc >= KC) break;
    uint32_t abase = sA + ((kc + 2) & 7) * 16384;
    if (kc == 8) {
      mbar_wait(bBf + st.bs * 8, st.bph);
      a8_bs = st.bs;
      abase = sB + st.bs * 16384;
      if (++st.bs == K1_BST) { st.bs = 0; st.bph ^= 1; }
    } else if (newA) {
      mbar_wait(bAf + kc * 8, st.aph);
    }
    const uint64_t da = make_desc(abase + wg * 8192, 16, 1024, 1);
#pragma unroll
    for (int ks = 0; ks < 2; ks++) {
      mbar_wait(bBf + st.bs * 8, st.bph);
      const uint64_t db = make_desc(sB + st.bs * 16384, 2048, 1024, 1);
      wg_fence();
      wgmma_ss_n256<1, 0>(acc, da + (uint64_t)(ks * 4), db, (ks > 0) ? 1 : (kc > 0));
      wgmma_ss_n256<1, 0>(acc, da + (uint64_t)(ks * 4 + 2), db + (uint64_t)512, 1);
      wg_commit();
      const int PO = (kc < 8 ? kc : 0) * 8;
      wg_wait<1>();
      if (ks > 0 || kc > 0) {
        if (sig) mbar_arrive_cluster(bBe + prev_bs * 8, warp);
        if (ks == 0 && siga) mbar_arrive(bAe + (kc - 1) * 8);
      }
      if (kc < st.png) st_v4a(st.pp + kc * 32 + ks * st.pld8, pk[PO + ks * 4], pk[PO + ks * 4 + 1], pk[PO + ks * 4 + 2], pk[PO + ks * 4 + 3]);
      prev_bs = st.bs;
      if (++st.bs == K1_BST) { st.bs = 0; st.bph ^= 1; }
    }
  }
  if (newA) st.aph ^= 1;
  k1_flag(st, lane, bS);
  wg_wait<0>();
  fence_regs(acc);
  if (sig) {
    mbar_arrive_cluster(bBe + prev_bs * 8, warp);
    if (a_sel) mbar_arrive_cluster(bBe + a8_bs * 8, warp);
  }
  if (siga && !a_sel) mbar_arrive(bAe + 7 * 8);
  const bool isA = (w_sel == 2);
  bf16* out = (w_sel == 0) ? g_K : (w_sel == 1) ? g_V : isA ? g_QKVA : g_Q;
  const int ld = isA ? NQKVA : HDIM;
  const int row = mpair * 256 + rank * 128 + wg * 64 + warp * 16 + (lane >> 2);
  st.pp = out + (size_t)row * ld + chunk0 * 64 + (lane & 3) * 8;
  st.pld8 = 8 * ld;
  st.png = ((job & 3) + 1) * 2;
#pragma unroll
  for (int G = 0; G < 8; G++) {
    pk[G * 8 + 0] = pack_bf16(acc[G * 16 + 0], acc[G * 16 + 1]);
    pk[G * 8 + 1] = pack_bf16(acc[G * 16 + 4], acc[G * 16 + 5]);
    pk[G * 8 + 2] = pack_bf16(acc[G * 16 + 8], acc[G * 16 + 9]);
    pk[G * 8 + 3] = pack_bf16(acc[G * 16 + 12], acc[G * 16 + 13]);
    pk[G * 8 + 4] = pack_bf16(acc[G * 16 + 2], acc[G * 16 + 3]);
    pk[G * 8 + 5] = pack_bf16(acc[G * 16 + 6], acc[G * 16 + 7]);
    pk[G * 8 + 6] = pack_bf16(acc[G * 16 + 10], acc[G * 16 + 11]);
    pk[G * 8 + 7] = pack_bf16(acc[G * 16 + 14], acc[G * 16 + 15]);
  }
  if (isA) {
#pragma unroll
    for (int G = 0; G < 16; G++) quad_transpose(pk[G * 4 + 0], pk[G * 4 + 1], pk[G * 4 + 2], pk[G * 4 + 3], lane & 3);
  }
}

#define HA(h) (h)
constexpr int K2_NST = 7;
constexpr uint32_t K2_END = 0x100;
#define PF_KC 7
#define FIRST_DRAW 3
#define ANCH 8
#define PVM 0x8A
#define W0 63
#define SPEC 24
constexpr int K3_NST = 4;
__device__ __forceinline__ uint32_t k3_rot(uint32_t sv) { return (0x00E9u >> (2 * sv)) & 3; }
constexpr int K3_STAGE = 16384 + 32768 + 4096;
constexpr int SMEM_DATA = 7 * 32768;
constexpr int SMEM_BYTES = SMEM_DATA + 1024 + 768;

struct Cursor {
  uint32_t s, ph;
  __device__ __forceinline__ void next() {
    if (++s == K2_NST) { s = 0; ph ^= 1; }
  }
};

#define TURN_SYNC() bar_sync(mybar, 256)
#define TURN_ARRIVE() bar_arrive(otherbar, 256)
#define RELEASE_IF(cur, cond) mbar_arrive_cluster_if(bE + (cur).s * 8, warp & 1, sig && (cond))
#define RELEASE(cur) RELEASE_IF(cur, true)
#define ISSUE_PV(cur, first)                                                                                   \
  do {                                                                                                         \
    const uint64_t dv = make_desc(sbase + (cur).s * 32768, 16384, 1024, 1);                                    \
    _Pragma("unroll") for (int t = 0; t < 8; t++)                                                              \
        wgmma_rs_n128<1, 0>(O, P[4 * t], P[4 * t + 1], P[4 * t + 2], P[4 * t + 3], dv + (uint64_t)(t * 128), (t > 0) ? 1 : !(first)); \
  } while (0)
#define RESCALE_O()                                                                                            \
  do {                                                                                                         \
    fence_regs(O);                                                                                             \
    _Pragma("unroll") for (int jj = 0; jj < 16; jj++) {                                                        \
      O[jj * 4 + 0] *= sc0; O[jj * 4 + 1] *= sc0; O[jj * 4 + 2] *= sc1; O[jj * 4 + 3] *= sc1;                  \
    }                                                                                                          \
    fence_regs(O);                                                                                             \
  } while (0)
#define ISSUE_QK(cur)                                                                                          \
  do {                                                                                                         \
    const uint64_t dk = make_desc(sbase + (cur).s * 32768, 16, 1024, 1);                                       \
    _Pragma("unroll") for (int t = 0; t < 8; t++)                                                              \
        wgmma_rs_n128<0, 0>(S, Q[4 * t], Q[4 * t + 1], Q[4 * t + 2], Q[4 * t + 3], dk + (uint64_t)((t >> 2) * 1024 + (t & 3) * 2), t > 0); \
  } while (0)
#define EXPC(T)                                                                                                \
  do {                                                                                                         \
    if (T > 0 && ((PVM >> (T - 1)) & 1)) {                                                                     \
      if (!W0 && (PVM & ((1 << T) - 1)) == (1 << (T - 1))) mbar_arrive_cluster_after(bE + ck.s * 8, warp & 1, sig, s0 + s1); \
      else anchor((T & 2) ? s0 : s1, never);                                                                   \
      wg_wait<__builtin_popcount(PVM >> T) - 1>();                                                             \
      if ((PVM >> T) == (128 >> T)) { fence_regs(O); RELEASE(cv); }                                            \
    }                                                                                                          \
    _Pragma("unroll") for (int i = 4 * T; i < 4 * T + 4; i++) asm volatile("" : "+r"(P[i])::"memory");        \
    _Pragma("unroll") for (int jj = 2 * T; jj < 2 * T + 2; jj++) {                                             \
      const float e0 = ex2(S[jj * 4 + 0]), e1 = ex2(S[jj * 4 + 1]), e2 = ex2(S[jj * 4 + 2]), e3 = ex2(S[jj * 4 + 3]); \
      s0 += e0 + e1;                                                                                           \
      s1 += e2 + e3;                                                                                           \
      P[jj * 2 + 0] = pack_bf16(e0, e1);                                                                       \
      P[jj * 2 + 1] = pack_bf16(e2, e3);                                                                       \
    }                                                                                                          \
  } while (0)
#define EPILOGUE()                                                                                             \
  do {                                                                                                         \
    l0 += __shfl_xor_sync(0xffffffffu, l0, 1);                                                                 \
    l0 += __shfl_xor_sync(0xffffffffu, l0, 2);                                                                 \
    l1 += __shfl_xor_sync(0xffffffffu, l1, 1);                                                                 \
    l1 += __shfl_xor_sync(0xffffffffu, l1, 2);                                                                 \
    asm volatile("" : "+f"(gf0), "+f"(gf1));                                                                   \
    const float f0 = __fdividef(1.f - gf0, l0), f1 = __fdividef(1.f - gf1, l1);                                                                \
    bf16* o0 = g_ctx + (size_t)prev_row * KCAT + prev_h * 128 + q * 8;                                         \
    bf16* o1 = o0 + (size_t)8 * KCAT;                                                                          \
    _Pragma("unroll") for (int G = 0; G < 4; G++) {                                                            \
      st_v4(o0 + G * 32, pack_bf16(O[G * 16 + 0] * f0, O[G * 16 + 1] * f0), pack_bf16(O[G * 16 + 4] * f0, O[G * 16 + 5] * f0), \
            pack_bf16(O[G * 16 + 8] * f0, O[G * 16 + 9] * f0), pack_bf16(O[G * 16 + 12] * f0, O[G * 16 + 13] * f0)); \
      st_v4(o1 + G * 32, pack_bf16(O[G * 16 + 2] * f1, O[G * 16 + 3] * f1), pack_bf16(O[G * 16 + 6] * f1, O[G * 16 + 7] * f1), \
            pack_bf16(O[G * 16 + 10] * f1, O[G * 16 + 11] * f1), pack_bf16(O[G * 16 + 14] * f1, O[G * 16 + 15] * f1)); \
    }                                                                                                          \
  } while (0)

__global__ void __cluster_dims__(2, 1, 1) __launch_bounds__(384, 1)
fused_kernel(const __grid_constant__ Params p, const bf16* __restrict__ x, const bf16* __restrict__ gate_w, bf16* __restrict__ out) {
  extern __shared__ uint8_t smem_raw[];
  const uint32_t sbase = (smem_u32(smem_raw) + 1023) & ~1023u;
  const uint32_t sB = sbase, sA = sbase + K1_BST * 16384, sBar = sbase + SMEM_DATA;
  const uint32_t bAf = sBar, bAe = sBar + 64, bBf = sBar + 128, bBe = sBar + 176, bL = sBar + 224, bS = sBar + 232, bL2 = sBar + 240, sL = sA + 32768;
  const uint32_t bF = sBar + 256, bE = sBar + 320, bT = sBar + 384, sTick = sBar + 400, sItem = sBar + 416, bS2 = sBar + 448, bR = sBar + 456, bLast = sBar + 464, bH = sBar + 472, bT0 = sBar + 480;
  const uint32_t b3F = sBar + 512, b3E = sBar + 544, sGate = sBar + 576;
  const int tid = threadIdx.x, warp_g = __shfl_sync(0xffffffffu, tid >> 5, 0), lane = tid & 31;
  const uint32_t rank = cluster_rank();
  const int cl = blockIdx.x >> 1;
  TSM(0);
  if (tid == 0) {
    for (int i = 0; i < 8; i++) { mbar_init(bAf + i * 8, 1); mbar_init(bAe + i * 8, 2); }
    for (int i = 0; i < K1_BST; i++) { mbar_init(bBf + i * 8, 1); mbar_init(bBe + i * 8, 4); }
    mbar_init(bL, 1);
    mbar_init(bL2, 1);
    mbar_init(bR, 1);
    mbar_init(bLast, 1);
    mbar_init(bH, 4);
    mbar_init(bT0, 1);
    mbar_init(bS, 8);
    for (int i = 0; i < K2_NST; i++) { mbar_init(bF + i * 8, 1); mbar_init(bE + i * 8, 4); }
    mbar_init(bT, 1); mbar_init(bT + 8, 1);
    mbar_init(bS2, 8);
    for (int i = 0; i < K3_NST; i++) { mbar_init(b3F + i * 8, 1); mbar_init(b3E + i * 8, 4); }
    asm volatile("fence.mbarrier_init.release.cluster;" ::: "memory");
  }
  __syncthreads();
  cluster_sync();
  const int lr0 = blockIdx.x * 16;

  if (warp_g >= 8) {
    reg_dealloc<40>();
    if (warp_g == 8) {
      if (elect_one()) {
        uint32_t bs = 0, bph = 1, aph = 1;
#pragma unroll 1
        for (int ji = 0; ji < K1_MAXJOBS; ji++) {
          const uint32_t job = p.jobs[cl][ji];
          if (!(job & 3)) break;
          const int a_sel = (job >> 2) & 1, mpair = (job >> 3) & 7, chunk0 = (job >> 8) & 63;
          const bool newA = (job >> 14) & 1;
          const int KC = a_sel ? 9 : 8;
          const uint32_t halfbytes = 8192;
          const bool lastjob = (ji + 1 == K1_MAXJOBS) || !(p.jobs[cl][ji + 1] & 3);
          const CUtensorMap* tw = &p.tmW[(job >> 6) & 3];
          {
            const uint32_t njob = (ji + 1 < K1_MAXJOBS) ? p.jobs[cl][ji + 1] : 0;
            if (!(njob & 3) && !newA) mbar_arrive(bLast);
          }
#pragma unroll 1
          for (int kc = 0; kc < KC; kc++) {
            if (kc == ((ji == 0) ? PF_KC : 0) && !lastjob) {
              const uint32_t njob = p.jobs[cl][ji + 1];
              const int nst = ((njob >> 2) & 1) ? 18 : 16;
#pragma unroll 1
              for (int t = (cl < 64) ? (cl & 7) : 0; t < nst; t += (cl < 64) ? 8 : 1)
                tma_pf3d(&p.tmW[(njob >> 6) & 3], 0, t * 32 + rank * 16, (njob >> 8) & 63);
            }
            if (kc == 8) {
              mbar_wait(bBe + bs * 8, bph);
              mbar_expect(bBf + bs * 8, 16384);
              tma2d(sB + bs * 16384, &p.tmA[1], bBf + bs * 8, 512, mpair * 256 + rank * 128);
              if (++bs == K1_BST) { bs = 0; bph ^= 1; }
            } else if (newA) {
              mbar_wait(bAe + kc * 8, aph);
              mbar_expect(bAf + kc * 8, 16384);
              tma2d(sA + ((kc + 2) & 7) * 16384, &p.tmA[a_sel], bAf + kc * 8, kc * 64, mpair * 256 + rank * 128);
              if (kc == 7 && lastjob) mbar_arrive(bLast);
            }
#pragma unroll 1
            for (int kk = 0; kk < 2; kk++) {
              mbar_wait(bBe + bs * 8, bph);
              mbar_expect(bBf + bs * 8, 2 * halfbytes);
              tma3d_mc(sB + bs * 16384 + rank * halfbytes, tw, bBf + bs * 8, 0, kc * 64 + kk * 32 + rank * 16, chunk0, 3);
              if (++bs == K1_BST) { bs = 0; bph ^= 1; }
            }
          }
          if (newA) aph ^= 1;
        }
        Cursor c{0, 0};
        int pcol = 0;
        mbar_wait(bR, 0);
        uint32_t tick = lds32(sTick + 8), seen = 1u << (p.order[tick] >> 4);
        asm volatile("fence.proxy.async.global;" ::: "memory");
#pragma unroll 1
        for (int it = 0;; it++) {
          const uint32_t item = (tick < 256) ? p.order[tick] : (K2_END | min(tick - 256, 255u));
          asm volatile("st.shared.u32 [%0], %1;" ::"r"(sItem + (it & 7) * 4), "r"(item) : "memory");
          if (item >= K2_END) break;
          const int h = item >> 3, j = item & 7;
          const int blk = 2 * j + (int)(rank ^ (it & 1));
          const int col = HA(h) * 128 + rank * 64;
          const int nb = 2 * j + 2;
          if (!((seen >> (h >> 1)) & 1)) {
            wait_flag(&g_sync[F_HP + (h >> 1)], RDY_TARGET);
            asm volatile("fence.proxy.async.global;" ::: "memory");
            seen |= 1u << (h >> 1);
          }
          mbar_wait(bE + c.s * 8, c.ph);
          mbar_expect(bF + c.s * 8, 32768);
          tma2d(sbase + c.s * 32768, &p.tmQ, bF + c.s * 8, HA(h) * 128, blk * 128);
          tma2d(sbase + c.s * 32768 + 16384, &p.tmQ, bF + c.s * 8, HA(h) * 128 + 64, blk * 128);
          c.next();
#pragma unroll 1
          for (int n = nb - 1; n >= 0; n--) {
            if (n == 0 && rank == 0) tick = atomicAdd(&g_sync[F_TICK], 1u);
            mbar_wait(bE + c.s * 8, c.ph);
            mbar_expect(bF + c.s * 8, 32768);
            tma2d_mc(sbase + c.s * 32768 + rank * 16384, &p.tmK, bF + c.s * 8, col, n * 128, 3);
            c.next();
            if (n < nb - 1 || it > 0) {
              mbar_wait(bE + c.s * 8, c.ph);
              mbar_expect(bF + c.s * 8, 32768);
              tma2d_mc(sbase + c.s * 32768 + rank * 16384, &p.tmV, bF + c.s * 8, (n < nb - 1) ? col : pcol, (n < nb - 1) ? (n + 1) * 128 : 0, 3);
              c.next();
            }
          }
          pcol = col;
          if (rank == 0) {
            asm volatile(
                "{\n.reg .b32 a, b;\nmapa.shared::cluster.u32 a, %0, 1;\nmapa.shared::cluster.u32 b, %1, 1;\n"
                "st.async.shared::cluster.mbarrier::complete_tx::bytes.u32 [a], %2, [b];\n}" ::"r"(sTick + (it & 1) * 4),
                "r"(bT + (it & 1) * 8), "r"(tick) : "memory");
          } else {
            mbar_expect(bT + (it & 1) * 8, 4);
            mbar_wait(bT + (it & 1) * 8, (it >> 1) & 1);
            tick = lds32(sTick + (it & 1) * 4);
          }
        }
        mbar_wait(bE + c.s * 8, c.ph);
        mbar_expect(bF + c.s * 8, 32768);
        tma2d_mc(sbase + c.s * 32768 + rank * 16384, &p.tmV, bF + c.s * 8, pcol, 0, 3);
        const uint32_t unit = tick - 256;
        if (unit < 64) {
          const int mblk = (7 - (p.unit[unit][0] >> 1)) * 2 + rank, nhalf = p.unit[unit][0] & 1;
          const uint32_t rot = k3_rot(c.s), nfree = ((0x1Au >> c.s) & 1) ? 2 : 3;
#pragma unroll 1
          for (int i = 0; i < K2_NST - 1; i++) {
            c.next();
            mbar_wait(bE + c.s * 8, c.ph);
          }
          uint32_t idx = 0, have = 0;
#pragma unroll 1
          for (int kk = p.unit[unit][2]; kk < p.unit[unit][3]; kk++, idx++) {
            const uint32_t s = (rot + idx) & 3;
            if (idx >= nfree) mbar_wait((idx < 4) ? bH : b3E + s * 8, (idx < 4) ? 0 : (~idx >> 2) & 1);
            mbar_expect(b3F + s * 8, K3_STAGE);
            const uint32_t st = sbase + s * K3_STAGE;
            const int sel = (kk < 9), k = sel ? kk : kk - 9, kr = k * 64 + rank * 32;
            tma3d_mc(st + 16384 + rank * 16384, &p.tmO[sel], b3F + s * 8, 0, kr, nhalf * 4, 3);
            tma2d_mc(st + 49152 + rank * 2048, &p.tmOt[sel], b3F + s * 8, 512 + nhalf * 32, kr, 3);
            if (kk == 0) {
              wait_flag(&g_sync[F_OA + mblk], 8);
              asm volatile("fence.proxy.async.global;" ::: "memory");
            }
            if (!sel && !((have >> (k >> 1)) & 1)) {
#pragma unroll 1
              for (uint32_t spins = 0; spins < (1u << 22); spins++) {
                asm volatile("ld.acquire.gpu.global.u32 %0, [%1];" : "=r"(have) : "l"(&g_sync[F_CTX + mblk]) : "memory");
                if ((have >> (k >> 1)) & 1) break;
                __nanosleep(100);
              }
              asm volatile("fence.proxy.async.global;" ::: "memory");
            }
            tma2d(st, &p.tmC, b3F + s * 8, (sel ? 64 + k : k) * 64, mblk * 128);
          }
        }
      }
    }
    __syncwarp();
    if (warp_g == 8) {
      uint32_t v = 0;
      if (lane == 0) {
        __threadfence();
        v = atomicAdd(&g_sync[F_DONE], 1u);
      }
      if (__shfl_sync(0xffffffffu, v, 0) == 2 * NCLUSTER - 1) {
        reinterpret_cast<uint4*>(g_sync)[lane] = make_uint4(0, 0, 0, 0);
        if (lane == 0) g_sync[F_EPOCH] = lds32(sGate + 64) + 1;
      }
    }
    asm volatile("" ::: "memory");
    if (__shfl_sync(0xffffffffu, warp_g, 0) != 8) {
      if (lr0 < S_LEN) {
#pragma unroll 1
        for (int i = warp_g - 9; i < 16; i += 3) {
          const float g = gate_row(lr0 + i, lane, x, gate_w);
          if (lane == 0) asm volatile("st.shared.f32 [%0], %1;" ::"r"(sGate + i * 4), "f"(g) : "memory");
        }
        bar_arrive(3, 256 + 96);
        if (lane == 0) {
          __threadfence();
          atomicAdd(&g_sync[F_GATE], 1u);
        }
      }
      uint32_t aph = 1;
#pragma unroll 1
      for (int ji = 0; ji < K1_MAXJOBS; ji++) aph ^= (p.jobs[cl][ji] >> 14) & 1;
      if (warp_g == 9 && lane == 0) {
#pragma unroll 1
        for (int ji = 0; ji < K1_MAXJOBS; ji++) {
          const uint32_t job = p.jobs[cl][ji];
          if (!(job & 3)) break;
          mbar_wait(bS, ji & 1);
          __threadfence();
          atomicAdd(&g_sync[(((job >> 6) & 3) == 2) ? (F_QKVA + ((job >> 3) & 7) * 2 + rank) : (F_HP + ((job >> 10) & 15))], 1u);
        }
#pragma unroll 1
        for (int it = 0;; it++) {
          mbar_wait(bS2, it & 1);
          const uint32_t item = lds32(sItem + (it & 7) * 4), nxt = lds32(sItem + ((it + 1) & 7) * 4);
          __threadfence();
          atomicOr(&g_sync[F_CTX + (item & 7) * 2 + (rank ^ (it & 1))], 1u << (item >> 3));
          if (nxt >= K2_END) break;
        }
      } else if (warp_g == 11) {
        if (lane == 0) {
          prefetch_tmap(&p.tmQ); prefetch_tmap(&p.tmK); prefetch_tmap(&p.tmV);
          asm volatile("st.shared.u32 [%0], %1;" ::"r"(sGate + 64), "r"(__ldcg(&g_sync[F_EPOCH])) : "memory");
          wait_flag(&g_sync[F_GATE], GATE_TARGET);
          uint32_t tick;
          if (rank == 0) {
            mbar_wait(bLast, 0);
            mbar_wait(bAe + FIRST_DRAW * 8, aph);
            tick = atomicAdd(&g_sync[F_TICK], 1u);
            asm volatile("st.shared.u32 [%0], %1;" ::"r"(sTick + 8), "r"(tick) : "memory");
            asm volatile(
                "{\n.reg .b32 a, b;\nmapa.shared::cluster.u32 a, %0, 1;\nmapa.shared::cluster.u32 b, %1, 1;\n"
                "st.async.shared::cluster.mbarrier::complete_tx::bytes.u32 [a], %2, [b];\n}" ::"r"(sTick + 8), "r"(bT0), "r"(tick) : "memory");
          } else {
            mbar_expect(bT0, 4);
            mbar_wait(bT0, 0);
            tick = lds32(sTick + 8);
          }
          wait_flag(&g_sync[F_HP + (p.order[tick] >> 4)], RDY_TARGET);
          mbar_arrive(bR);
        }
        __syncwarp();
        bar_sync(4, 256 + 32);
        if (lane < 12) mbar_arrive_cluster(bE + (4 + lane % 3) * 8, (lane / 3) & 1);
      } else if (warp_g == 10 && lr0 < S_LEN) {
        if (elect_one()) {
          prefetch_tmap(&p.tmL[0]); prefetch_tmap(&p.tmL[1]);
          wait_flag(&g_sync[F_QKVA + (lr0 >> 7)], K1_FLAG_TARGET);
          wait_flag(&g_sync[F_QKVA + (max(lr0 - 14, 0) >> 7)], K1_FLAG_TARGET);
          asm volatile("fence.proxy.async.global;" ::: "memory");
          mbar_wait(bLast, 0);
#pragma unroll 1
          for (int kc = 0; kc < 6; kc++) {
            mbar_wait(bAe + kc * 8, aph);
            if (kc == 3) {
              mbar_expect(bL, 46 * 1152);
              tma3d(sL, &p.tmL[0], bL, 0, 9, lr0 - 14);
              tma3d(sL + 30 * 1152, &p.tmL[1], bL, 0, 0, lr0);
            }
          }
          mbar_expect(bL2, 30 * 1152);
          tma3d(sL + 46 * 1152, &p.tmL[0], bL2, 0, 18, lr0 - 14);
        }
        __syncwarp();
        bar_sync(5, 256 + 32);
        if (lane == 0) {
          __threadfence();
          atomicAdd(&g_sync[F_OA + (lr0 >> 7)], 1u);
        }
      }
    }
    __syncwarp();
    cluster_sync();
  } else {
    reg_alloc<232>();
    const int wg = warp_g >> 2, warp = warp_g & 3, q = lane & 3;
    const bool sig = (lane == 0) && (warp < 2);
    {
      K1State st{0, 0, 0, nullptr, 0, 0};
      float acc[128];
      uint32_t pk[64];
      if (wg == 0) { TS(0, 0); TSC(0, 2); }
#pragma unroll 1
      for (int ji = 0; ji < K1_MAXJOBS; ji++) {
        const uint32_t job = p.jobs[cl][ji];
        if (!(job & 3)) break;
        k1_tile(acc, pk, st, job, sA, sB, bAf, bAe, bBf, bBe, bS, wg, warp, lane, rank);
      }
#pragma unroll
      for (int i = 0; i < 4; i++)
        mbar_arrive_cluster_if(bE + i * 8, warp & 1, sig);
#pragma unroll
      for (int G = 0; G < 8; G++)
        if (G < st.png) {
          st_v4a(st.pp + G * 32, pk[G * 8], pk[G * 8 + 1], pk[G * 8 + 2], pk[G * 8 + 3]);
          st_v4a(st.pp + G * 32 + st.pld8, pk[G * 8 + 4], pk[G * 8 + 5], pk[G * 8 + 6], pk[G * 8 + 7]);
        }
      k1_flag(st, lane, bS);
      if (wg == 0) { TS(0, 1); TSC(0, 3); }
      if (lr0 < S_LEN) {
        const int ri = (warp_g >> 1) * 4 + (warp_g & 1) + 2, row = lr0 + ri;
        if (wg == 0) TS(1, 5);
        bar_sync(3, 256 + 96);
        const float gate0 = __uint_as_float(lds32(sGate + ri * 4 - 8)), gate1 = __uint_as_float(lds32(sGate + ri * 4));
        mbar_wait(bL, 0);
        if (wg == 0) TS(1, 6);
        local_rows2(row, ri, sL, bL2, lane, gate0, gate1);
        bar_arrive(5, 256 + 32);
      } else {
        bar_arrive(4, 256 + 32);
      }
    }
    __syncwarp();
    uint32_t item, rot;
    {
      const int mybar = 1 + wg, otherbar = 2 - wg;
      const uint32_t never = blockIdx.y;
      const float cl2 = 0.08838834764831845f * 1.4426950408889634f;
      float S[64], O[64];
      uint32_t P[32], Q[32];
      float m0 = 0.f, m1 = 0.f, l0 = 0.f, l1 = 0.f;
      int prev_row = 0, prev_h = 0, prev_single = 0;
      Cursor c{0, 0};
      if (wg == 1) bar_arrive(1, 256);
      if (wg == 0) { TS(1, 0); TSC(1, 2); }
#pragma unroll 1
      for (int it = 0;; it++) {
        mbar_wait(bF + c.s * 8, c.ph);
        item = lds32(sItem + (it & 7) * 4);
        if (it > 0) BSEG(7);
        const bool last = item >= K2_END;
        const int h = item >> 3, j = item & 7;
        const int hi = (int)(rank ^ (it & 1));
        const int nblk = 2 * j + 1 + hi;
        {
          float gf0, gf1;
          asm volatile("ld.global.f32 %0, [%1];" : "=f"(gf0) : "l"(g_gate + prev_row));
          asm volatile("ld.global.f32 %0, [%1];" : "=f"(gf1) : "l"(g_gate + prev_row + 8));
          Cursor cq = c, ck = c, cs0 = c, cs1 = c, cv = c;
          rot = k3_rot(c.s);
          if (!last) {
            const int r = wg * 64 + warp * 16 + (lane & 7) + ((lane >> 3) & 1) * 8;
            const uint32_t qa = sbase + cq.s * 32768 + r * 128;
#pragma unroll
            for (int t = 0; t < 8; t++)
              ldsm_x4(Q[4 * t], Q[4 * t + 1], Q[4 * t + 2], Q[4 * t + 3], qa + (t >> 2) * 16384 + ((((t & 3) * 2 + (lane >> 4)) ^ (lane & 7)) << 4));
            c.next();
            ck = c; c.next();
            cs0 = ck; cv = c;
            mbar_wait(bF + ck.s * 8, ck.ph);
            if (it > 0) BSEG(8);
            if (it > 0) { mbar_wait(bF + cv.s * 8, cv.ph); c.next(); }
            if (it > 0) BSEG(9);
            if (!hi) {
              ck = c; c.next();
              cs1 = c; c.next();
              mbar_wait(bF + ck.s * 8, ck.ph);
              mbar_wait(bF + cs1.s * 8, cs1.ph);
            }
          }
          if (it == 0) BSEG(4); else BSEG(0);
          TURN_SYNC();
          if (it > 0 && !last) BSEG(10);
          if (it > 0) {
            wg_fence();
            ISSUE_PV(cv, prev_single);
            wg_commit();
          } else {
            wg_fence();
            wg_commit();
          }
          wg_fence();
          ISSUE_QK(ck);
          wg_commit();
          if (!(last && wg == 1)) TURN_ARRIVE();
          RELEASE_IF(cq, !last);
          RELEASE_IF(cs0, !last && !hi);
          RELEASE_IF(cs1, !last && !hi);
          wg_wait<1>();
          fence_regs(O);
          fence_regs(P);
          if (it > 0) {
            RELEASE_IF(cv, !last);
            mbar_arrive_cluster_if(bH, warp & 1, sig && last);
            EPILOGUE();
            __syncwarp();
            mbar_arrive_if(bS2, lane == 0);
          }
          wg_wait<0>();
          fence_regs(S);
          if (last) break;
          if (it > 0) BSEG(11);
          RELEASE(ck);
          float s0 = 0.f, s1 = 0.f;
          const int r0 = wg * 64 + warp * 16 + (lane >> 2);
#pragma unroll
          for (int jj = 0; jj < 16; jj++) {
            const int cc = jj * 8 + 2 * q;
            if (cc > r0) S[jj * 4 + 0] = -INFINITY;
            if (cc + 1 > r0) S[jj * 4 + 1] = -INFINITY;
            if (cc > r0 + 8) S[jj * 4 + 2] = -INFINITY;
            if (cc + 1 > r0 + 8) S[jj * 4 + 3] = -INFINITY;
          }
          float mx0 = fmaxf(S[0], S[1]), mx1 = fmaxf(S[2], S[3]);
#pragma unroll
          for (int jj = 1; jj < 16; jj++) {
            mx0 = fmaxf(mx0, fmaxf(S[jj * 4 + 0], S[jj * 4 + 1]));
            mx1 = fmaxf(mx1, fmaxf(S[jj * 4 + 2], S[jj * 4 + 3]));
          }
          mx0 = fmaxf(mx0, __shfl_xor_sync(0xffffffffu, mx0, 1));
          mx1 = fmaxf(mx1, __shfl_xor_sync(0xffffffffu, mx1, 1));
          mx0 = fmaxf(mx0, __shfl_xor_sync(0xffffffffu, mx0, 2));
          mx1 = fmaxf(mx1, __shfl_xor_sync(0xffffffffu, mx1, 2));
          m0 = mx0; m1 = mx1;
          const float mc0 = m0 * cl2, mc1 = m1 * cl2;
          m0 = mc0; m1 = mc1;
#pragma unroll
          for (int jj = 0; jj < 16; jj++) {
            S[jj * 4 + 0] = ex2(fmaf(S[jj * 4 + 0], cl2, -mc0));
            S[jj * 4 + 1] = ex2(fmaf(S[jj * 4 + 1], cl2, -mc0));
            S[jj * 4 + 2] = ex2(fmaf(S[jj * 4 + 2], cl2, -mc1));
            S[jj * 4 + 3] = ex2(fmaf(S[jj * 4 + 3], cl2, -mc1));
            s0 += S[jj * 4 + 0] + S[jj * 4 + 1];
            s1 += S[jj * 4 + 2] + S[jj * 4 + 3];
          }
          l0 = s0; l1 = s1;
#pragma unroll
          for (int jj = 0; jj < 16; jj++) {
            P[jj * 2 + 0] = pack_bf16(S[jj * 4 + 0], S[jj * 4 + 1]);
            P[jj * 2 + 1] = pack_bf16(S[jj * 4 + 2], S[jj * 4 + 3]);
          }
        }
        if (it == 0) BSEG(5); else BSEG(1);
#pragma unroll 1
        for (int n = 1; n < nblk; n++) {
          Cursor ck = c; c.next();
          Cursor cv = c; c.next();
          mbar_wait(bF + ck.s * 8, ck.ph);
          mbar_wait(bF + cv.s * 8, cv.ph);
          TURN_SYNC();
          wg_fence();
          ISSUE_QK(ck);
          wg_commit();
          {
            const uint64_t dv = make_desc(sbase + cv.s * 32768, 16384, 1024, 1);
#pragma unroll
            for (int t = 0; t < 8; t++) {
              wgmma_rs_n128<1, 0>(O, P[4 * t], P[4 * t + 1], P[4 * t + 2], P[4 * t + 3], dv + (uint64_t)(t * 128), (t > 0) ? 1 : (n != 1));
              if ((PVM >> t) & 1) wg_commit();
            }
          }
          TURN_ARRIVE();
          float s0 = 0.f, s1 = 0.f;
          wg_wait<__builtin_popcount(PVM)>();
          fence_regs(S);
          RELEASE(ck);
#pragma unroll
          for (int jj = 0; jj < 16; jj++) {
            S[jj * 4 + 0] = fmaf(S[jj * 4 + 0], cl2, -m0);
            S[jj * 4 + 1] = fmaf(S[jj * 4 + 1], cl2, -m0);
            S[jj * 4 + 2] = fmaf(S[jj * 4 + 2], cl2, -m1);
            S[jj * 4 + 3] = fmaf(S[jj * 4 + 3], cl2, -m1);
          }
          anchor(S[W0], never);
          wg_wait<__builtin_popcount(PVM) - 1>();
          EXPC(0); EXPC(1); EXPC(2); EXPC(3); EXPC(4); EXPC(5); EXPC(6); EXPC(7);
          if (__any_sync(0xffffffffu, !(s0 + s1 <= (float)(1ull << SPEC)))) {
            float mx0 = fmaxf(S[0], S[1]), mx1 = fmaxf(S[2], S[3]);
#pragma unroll
            for (int jj = 1; jj < 16; jj++) {
              mx0 = fmaxf(mx0, fmaxf(S[jj * 4 + 0], S[jj * 4 + 1]));
              mx1 = fmaxf(mx1, fmaxf(S[jj * 4 + 2], S[jj * 4 + 3]));
            }
            mx0 = fmaxf(mx0, __shfl_xor_sync(0xffffffffu, mx0, 1));
            mx1 = fmaxf(mx1, __shfl_xor_sync(0xffffffffu, mx1, 1));
            mx0 = fmaxf(mx0, __shfl_xor_sync(0xffffffffu, mx0, 2));
            mx1 = fmaxf(mx1, __shfl_xor_sync(0xffffffffu, mx1, 2));
            mx0 = fmaxf(mx0, 0.f);
            mx1 = fmaxf(mx1, 0.f);
            m0 += mx0; m1 += mx1;
            const float sc0 = ex2(-mx0), sc1 = ex2(-mx1);
            l0 *= sc0; l1 *= sc1;
            s0 = 0.f; s1 = 0.f;
#pragma unroll
            for (int jj = 0; jj < 16; jj++) {
              const float e0 = ex2(S[jj * 4 + 0] - mx0), e1 = ex2(S[jj * 4 + 1] - mx0), e2 = ex2(S[jj * 4 + 2] - mx1), e3 = ex2(S[jj * 4 + 3] - mx1);
              s0 += e0 + e1;
              s1 += e2 + e3;
              P[jj * 2 + 0] = pack_bf16(e0, e1);
              P[jj * 2 + 1] = pack_bf16(e2, e3);
              O[jj * 4 + 0] *= sc0;
              O[jj * 4 + 1] *= sc0;
              O[jj * 4 + 2] *= sc1;
              O[jj * 4 + 3] *= sc1;
            }
          }
          l0 += s0;
          l1 += s1;
        }
        BSEG(2);
        prev_row = (2 * j + hi) * 128 + wg * 64 + warp * 16 + (lane >> 2);
        prev_h = h;
        prev_single = (nblk == 1);
      }
      if (wg == 1) { TS(1, 1); TSC(1, 3); }
    }
    __syncwarp();
    const uint32_t unit = item & 255;
    if (unit < 64) {
      const int mblk = (7 - (p.unit[unit][0] >> 1)) * 2 + rank, nhalf = p.unit[unit][0] & 1, ks = p.unit[unit][1];
      const int k0 = p.unit[unit][2], k1 = p.unit[unit][3];
      float acc[144];
      uint32_t s = rot, ph = 0, prev = 0;
      if (wg == 0) { TS(2, 0); TSC(2, 2); }
#pragma unroll 1
      for (int k = k0; k < k1; k++) {
        mbar_wait(b3F + s * 8, ph);
        const uint32_t st = sbase + s * K3_STAGE;
        const uint64_t da = make_desc(st + wg * 8192, 16, 1024, 1);
        const uint64_t db = make_desc(st + 16384, 4096, 1024, 1);
        const uint64_t dt = make_desc(st + 49152, 16, 512, 2);
        wg_fence();
#pragma unroll
        for (int t = 0; t < 4; t++) {
          const int sd = (t > 0) || (k > k0);
          wgmma_ss_n256<1, 0>(acc, da + (uint64_t)(t * 2), db + (uint64_t)((t >> 1) * 1024 + (t & 1) * 128), sd);
          wgmma_ss_n32<1, 128>(acc, da + (uint64_t)(t * 2), dt + (uint64_t)(t * 64), sd);
        }
        wg_commit();
        if (k > k0) {
          wg_wait<1>();
          if (sig) mbar_arrive_cluster(b3E + prev * 8, warp);
        }
        prev = s;
        s = (s + 1) & 3;
        if (s == rot) ph ^= 1;
      }
      wg_wait<0>();
      fence_regs(acc);
      cluster_arrive();
      if (wg == 0) TS(2, 4);
      const int tile = mblk * 2 + nhalf;
      uint4* wp = g_part + (size_t)((tile * 4 + ks) * 4) * 5 * 256 + tid;
      const uint32_t sown = sbase + wg * 8192 + (tid & 127) * 16;
#pragma unroll
      for (int d = 0; d < 4; d++) {
        if (d != ks) {
#pragma unroll
          for (int i = 0; i < 4; i++)
            __stcg(wp + (d * 5 + i) * 256,
                   make_uint4(pack_bf16(acc[d * 32 + i * 8], acc[d * 32 + i * 8 + 1]), pack_bf16(acc[d * 32 + i * 8 + 2], acc[d * 32 + i * 8 + 3]),
                              pack_bf16(acc[d * 32 + i * 8 + 4], acc[d * 32 + i * 8 + 5]), pack_bf16(acc[d * 32 + i * 8 + 6], acc[d * 32 + i * 8 + 7])));
          __stcg(reinterpret_cast<uint2*>(wp - tid + (d * 5 + 4) * 256) + tid,
                 make_uint2(pack_bf16(acc[128 + d * 4], acc[128 + d * 4 + 1]), pack_bf16(acc[128 + d * 4 + 2], acc[128 + d * 4 + 3])));
        } else {
#pragma unroll
          for (int i = 0; i < 9; i++) {
            const int o = (i < 8) ? d * 32 + i * 4 : 128 + d * 4;
            asm volatile("st.shared.v4.f32 [%0], {%1, %2, %3, %4};" ::"r"(sown + (i >> 2) * K3_STAGE + (i & 3) * 2048), "f"(acc[o]), "f"(acc[o + 1]), "f"(acc[o + 2]), "f"(acc[o + 3]) : "memory");
          }
        }
      }
      __threadfence();
      __syncwarp();
      if (wg == 0) TS(2, 5);
      if (lane == 0) {
        unsigned int* cnt = &g_sync[F_XCH + tile * 8 + warp_g];
        const uint32_t xtarget = lds32(sGate + 64) * 4 + 4;
        atomicAdd(cnt, 1u);
        uint32_t v, spins = 0;
        do {
          asm volatile("ld.acquire.gpu.global.u32 %0, [%1];" : "=r"(v) : "l"(cnt) : "memory");
        } while ((int)(v - xtarget) < 0 && ++spins < (1u << 24));
      }
      __syncwarp();
      if (wg == 0) TS(2, 6);
      float r[36];
#pragma unroll
      for (int i = 0; i < 9; i++)
        asm volatile("ld.shared.v4.f32 {%0, %1, %2, %3}, [%4];" : "=f"(r[i * 4]), "=f"(r[i * 4 + 1]), "=f"(r[i * 4 + 2]), "=f"(r[i * 4 + 3])
                     : "r"(sown + (i >> 2) * K3_STAGE + (i & 3) * 2048) : "memory");
#pragma unroll
      for (int sI = 1; sI < 4; sI++) {
        const int src = (ks + sI) & 3;
        const uint4* rp = g_part + (size_t)(((tile * 4 + src) * 4) + ks) * 5 * 256;
#pragma unroll
        for (int i = 0; i < 4; i++) {
          const uint4 v = __ldcg(rp + i * 256 + tid);
          r[i * 8] += bf_lo(v.x); r[i * 8 + 1] += bf_hi(v.x); r[i * 8 + 2] += bf_lo(v.y); r[i * 8 + 3] += bf_hi(v.y);
          r[i * 8 + 4] += bf_lo(v.z); r[i * 8 + 5] += bf_hi(v.z); r[i * 8 + 6] += bf_lo(v.w); r[i * 8 + 7] += bf_hi(v.w);
        }
        const uint2 v = __ldcg(reinterpret_cast<const uint2*>(rp + 4 * 256) + tid);
        r[32] += bf_lo(v.x); r[33] += bf_hi(v.x); r[34] += bf_lo(v.y); r[35] += bf_hi(v.y);
      }
      const int row = mblk * 128 + wg * 64 + warp * 16 + (lane >> 2);
      bf16* o0 = out + (size_t)row * DM + nhalf * 256 + ks * 64 + 8 * q;
#pragma unroll
      for (int G = 0; G < 2; G++) {
        uint32_t a0 = pack_bf16(r[G * 16], r[G * 16 + 1]), a1 = pack_bf16(r[G * 16 + 4], r[G * 16 + 5]);
        uint32_t a2 = pack_bf16(r[G * 16 + 8], r[G * 16 + 9]), a3 = pack_bf16(r[G * 16 + 12], r[G * 16 + 13]);
        uint32_t b0 = pack_bf16(r[G * 16 + 2], r[G * 16 + 3]), b1 = pack_bf16(r[G * 16 + 6], r[G * 16 + 7]);
        uint32_t b2 = pack_bf16(r[G * 16 + 10], r[G * 16 + 11]), b3 = pack_bf16(r[G * 16 + 14], r[G * 16 + 15]);
        quad_transpose(a0, a1, a2, a3, q);
        quad_transpose(b0, b1, b2, b3, q);
        st_v4(o0 + G * 32, a0, a1, a2, a3);
        st_v4(o0 + 8 * DM + G * 32, b0, b1, b2, b3);
      }
      {
        uint32_t t0 = pack_bf16(r[32], r[33]), t1 = pack_bf16(r[34], r[35]), t2 = 0, t3 = 0;
        quad_transpose(t0, t1, t2, t3, q);
        if (q < 2) st_v4(out + (size_t)(row + q * 8) * DM + 512 + nhalf * 32 + ks * 8, t0, t1, t2, t3);
      }
    } else {
      cluster_arrive();
    }
    if (wg == 0) { TS(2, 1); TSC(2, 3); }
    cluster_wait();
  }
}

typedef CUresult (*EncFn)(CUtensorMap*, CUtensorMapDataType, cuuint32_t, void*, const cuuint64_t*, const cuuint64_t*, const cuuint32_t*,
                          const cuuint32_t*, CUtensorMapInterleave, CUtensorMapSwizzle, CUtensorMapL2promotion, CUtensorMapFloatOOBfill);

static void enc2d(EncFn enc, CUtensorMap* m, const void* ptr, uint64_t cols, uint64_t rows, uint32_t bc, uint32_t br,
                  CUtensorMapSwizzle sw = CU_TENSOR_MAP_SWIZZLE_128B) {
  cuuint64_t gd[2] = {cols, rows}, gs[1] = {cols * 2};
  cuuint32_t bx[2] = {bc, br}, es[2] = {1, 1};
  enc(m, CU_TENSOR_MAP_DATA_TYPE_BFLOAT16, 2, const_cast<void*>(ptr), gd, gs, bx, es, CU_TENSOR_MAP_INTERLEAVE_NONE, sw,
      CU_TENSOR_MAP_L2_PROMOTION_L2_256B, CU_TENSOR_MAP_FLOAT_OOB_FILL_NONE);
}
static void enc3d(EncFn enc, CUtensorMap* m, const void* ptr, uint64_t cols, uint64_t rows, uint32_t br, uint32_t bch) {
  cuuint64_t gd[3] = {64, rows, cols / 64}, gs[2] = {cols * 2, 128};
  cuuint32_t bx[3] = {64, br, bch}, es[3] = {1, 1, 1};
  enc(m, CU_TENSOR_MAP_DATA_TYPE_BFLOAT16, 3, const_cast<void*>(ptr), gd, gs, bx, es, CU_TENSOR_MAP_INTERLEAVE_NONE,
      CU_TENSOR_MAP_SWIZZLE_128B, CU_TENSOR_MAP_L2_PROMOTION_L2_256B, CU_TENSOR_MAP_FLOAT_OOB_FILL_NONE);
}

static int g_sched[10] = {11, 10, 7, 4, 4, 5, 6, 6, 8, 20};
static void build_k1_jobs(Params& p) {
  int cnt[NCLUSTER];
  for (int c = 0; c < NCLUSTER; c++) {
    cnt[c] = 0;
    for (int i = 0; i < K1_MAXJOBS; i++) p.jobs[c][i] = 0;
  }
  auto add = [&](int c, int nch, int a_sel, int mp, int w_sel, int chunk0) {
    p.jobs[c][cnt[c]++] = (uint16_t)((nch - 1) | (a_sel << 2) | (mp << 3) | (w_sel << 6) | (chunk0 << 8));
  };
  const int *cg = g_sched, *xg = g_sched + 4;
  for (int mp = 0; mp < 8; mp++) {
    int k = 0;
    for (int i = 0; i < K1_MAXJOBS; i++)
      for (int g = 0; g < 4; g++)
        if (i < cg[g]) { add(g * 8 + mp, 4, 0, mp, k & 1, (k >> 1) * 4); k++; }
    k = 0;
    for (int i = 0; i < K1_MAXJOBS; i++)
      for (int g = 0; g < 4; g++)
        if (i < xg[g]) {
          if (k < 7) add((4 + g) * 8 + mp, k == 0 ? 3 : 4, 1, mp, 2, k == 0 ? 24 : (k - 1) * 4);
          else add((4 + g) * 8 + mp, 4, 1, mp, 3, (k - 7) * 4);
          k++;
        }
    add(64 + mp / 4, 4, 1, mp, 3, 14 * 4);
    add(64 + mp / 4, 4, 1, mp, 3, 15 * 4);
  }
  for (int cc = 0; cc < NCLUSTER; cc++)
    for (int i = 0; i < cnt[cc]; i++) {
      const int key = p.jobs[cc][i] & 0x3C;
      if (i == 0 || (p.jobs[cc][i - 1] & 0x3C) != key) p.jobs[cc][i] |= (1 << 14);
      if (i == cnt[cc] - 1 || (p.jobs[cc][i + 1] & 0x3C) != key) p.jobs[cc][i] |= (1 << 15);
    }
}

static void build_k2_items(Params& p) {
  int n = 0;
  const int SCHED_N1 = g_sched[8], SCHED_N2 = g_sched[9];
  for (int j = 7; j >= 0; j--)
    for (int h = 0; h < SCHED_N1; h++) p.order[n++] = (uint8_t)(h * 8 + j);
  for (int j = 7; j >= 4; j--)
    for (int h = SCHED_N1; h < SCHED_N2; h++) p.order[n++] = (uint8_t)(h * 8 + j);
  for (int j = 7; j >= 0; j--)
    for (int h = SCHED_N1; h < 32; h++)
      if (!(h < SCHED_N2 && j >= 4)) p.order[n++] = (uint8_t)(h * 8 + j);
}

static void build_k3_units(Params& p) {
  float slope = 0.09f;
  for (int t = 0; t < 16; t++) {
    const int u[4] = {t, 31 - t, 32 + t, 63 - t};
    float acc = 0.f;
    int k0 = 0;
    for (int i = 0; i < 4; i++) {
      acc += 18.25f + slope * (31.5f - u[i]);
      const int k1 = (i == 3) ? 73 : (int)(acc + 0.5f);
      p.unit[u[i]][0] = (uint8_t)t; p.unit[u[i]][1] = (uint8_t)i; p.unit[u[i]][2] = (uint8_t)k0; p.unit[u[i]][3] = (uint8_t)k1;
      k0 = k1;
    }
  }
}

extern "C" void kernel_launch(void* const* d_in, const int* in_sizes, int n_in, void* d_out, int out_size) {
  const bf16* x = (const bf16*)d_in[0];
  const bf16* wqkv = (const bf16*)d_in[1];
  const bf16* wo = (const bf16*)d_in[2];
  const bf16* ckv = (const bf16*)d_in[4];
  const bf16* w_q = (const bf16*)d_in[5];
  const bf16* w_uk = (const bf16*)d_in[6];
  const bf16* w_uv = (const bf16*)d_in[7];
  const bf16* w_o = (const bf16*)d_in[8];
  const bf16* gate_w = (const bf16*)d_in[9];

  EncFn enc = nullptr;
  cudaDriverEntryPointQueryResult qr;
  cudaGetDriverEntryPoint("cuTensorMapEncodeTiled", (void**)&enc, cudaEnableDefault, &qr);
  void *pQ, *pK, *pV, *pCtx, *pQA;
  cudaGetSymbolAddress(&pQ, g_Q);
  cudaGetSymbolAddress(&pQA, g_QKVA);
  cudaGetSymbolAddress(&pK, g_K);
  cudaGetSymbolAddress(&pV, g_V);
  cudaGetSymbolAddress(&pCtx, g_ctx);

  static Params p;
  enc2d(enc, &p.tmA[0], ckv, DC, S_LEN, 64, 128);
  enc2d(enc, &p.tmA[1], x, DM, S_LEN, 64, 128);
  enc3d(enc, &p.tmW[0], w_uk, HDIM, DC, 16, 4);
  enc3d(enc, &p.tmW[1], w_uv, HDIM, DC, 16, 4);
  enc3d(enc, &p.tmW[2], wqkv, NQKVA, DM, 16, 4);
  enc3d(enc, &p.tmW[3], w_q, HDIM, DM, 16, 4);
  build_k1_jobs(p);
  enc2d(enc, &p.tmQ, pQ, HDIM, S_LEN, 64, 128);
  enc2d(enc, &p.tmK, pK, HDIM, S_LEN, 64, 128);
  enc2d(enc, &p.tmV, pV, HDIM, S_LEN, 64, 128);
  build_k2_items(p);
  build_k3_units(p);
  for (int i = 0; i < 2; i++) {
    cuuint64_t gd[3] = {64, 27, S_LEN}, gs[2] = {128, NQKVA * 2};
    cuuint32_t bx[3] = {64, 9, i ? 16u : 30u}, es[3] = {1, 1, 1};
    enc(&p.tmL[i], CU_TENSOR_MAP_DATA_TYPE_BFLOAT16, 3, pQA, gd, gs, bx, es, CU_TENSOR_MAP_INTERLEAVE_NONE, CU_TENSOR_MAP_SWIZZLE_NONE,
        CU_TENSOR_MAP_L2_PROMOTION_L2_256B, CU_TENSOR_MAP_FLOAT_OOB_FILL_NONE);
  }
  enc2d(enc, &p.tmC, pCtx, KCAT, S_LEN, 64, 128);
  enc3d(enc, &p.tmO[0], w_o, DM, HDIM, 32, 4);
  enc3d(enc, &p.tmO[1], wo, DM, DM, 32, 4);
  enc2d(enc, &p.tmOt[0], w_o, DM, HDIM, 32, 32, CU_TENSOR_MAP_SWIZZLE_64B);
  enc2d(enc, &p.tmOt[1], wo, DM, DM, 32, 32, CU_TENSOR_MAP_SWIZZLE_64B);

  cudaFuncSetAttribute(fused_kernel, cudaFuncAttributeMaxDynamicSharedMemorySize, SMEM_BYTES);
  fused_kernel<<<NCLUSTER * 2, 384, SMEM_BYTES>>>(p, x, gate_w, (bf16*)d_out);
}
```

```cpp
#include <cuda_runtime.h>
#include <cuda_bf16.h>
#include <cuda.h>
#include <stdint.h>

typedef __nv_bfloat16 bf16;

constexpr int S_LEN = 2048, DM = 576, DC = 512, HDIM = 4096, NQKVA = 1728, KCAT = 4672;
constexpr int NCLUSTER = 66;

__device__ __align__(1024) bf16 g_Q[S_LEN * HDIM];
__device__ __align__(1024) bf16 g_K[S_LEN * HDIM];
__device__ __align__(1024) bf16 g_V[S_LEN * HDIM];
__device__ __align__(1024) bf16 g_QKVA[S_LEN * NQKVA + 64];
__device__ __align__(1024) bf16 g_ctx[S_LEN * KCAT];
__device__ float g_gate[S_LEN];
__device__ __align__(1024) uint4 g_part[32 * 4 * 4 * 5 * 256];
__device__ __align__(16) unsigned int g_sync[400];
constexpr int F_QKVA = 0, F_HP = 16, F_CTX = 32, F_OA = 48, F_GATE = 96, F_TICK = 97, F_DONE = 98, F_XCH = 128, F_EPOCH = 384;

__device__ __forceinline__ uint32_t smem_u32(const void* p) { return (uint32_t)__cvta_generic_to_shared(p); }
__device__ __forceinline__ void mbar_init(uint32_t a, uint32_t c) {
  asm volatile("mbarrier.init.shared::cta.b64 [%0], %1;" ::"r"(a), "r"(c));
}
__device__ __forceinline__ void mbar_expect(uint32_t a, uint32_t b) {
  asm volatile("mbarrier.arrive.expect_tx.shared::cta.b64 _, [%0], %1;" ::"r"(a), "r"(b) : "memory");
}
#define TS(k, i)
#define TSC(k, i)
#define TSM(k)
#define BSEG(i)
#define SPIN_LIMIT "4194304"
__device__ __forceinline__ void mbar_wait(uint32_t a, uint32_t parity) {
  asm volatile(
      "{\n.reg .pred p;\n.reg .u32 n;\n"
      "mbarrier.try_wait.parity.shared::cta.b64 p, [%0], %1;\n"
      "@p bra DONE;\n"
      "mov.u32 n, 0;\n"
      "LOOP:\n"
      "mbarrier.try_wait.parity.shared::cta.b64 p, [%0], %1;\n"
      "@p bra DONE;\n"
      "add.u32 n, n, 1;\n"
      "setp.lt.u32 p, n, " SPIN_LIMIT ";\n"
      "@p bra LOOP;\n"
      "DONE:\n}" ::"r"(a), "r"(parity) : "memory");
}
__device__ __forceinline__ void mbar_arrive(uint32_t a) {
  asm volatile("mbarrier.arrive.shared::cta.b64 _, [%0];" ::"r"(a) : "memory");
}
__device__ __forceinline__ void mbar_arrive_cluster(uint32_t a, uint32_t cta) {
  asm volatile("{\n.reg .b32 r;\nmapa.shared::cluster.u32 r, %0, %1;\nmbarrier.arrive.shared::cluster.b64 _, [r];\n}" ::"r"(a),
               "r"(cta) : "memory");
}
__device__ __forceinline__ void mbar_arrive_cluster_if(uint32_t a, uint32_t cta, bool pred) {
  asm volatile("{\n.reg .b32 r;\n.reg .pred p;\nsetp.ne.u32 p, %2, 0;\nmapa.shared::cluster.u32 r, %0, %1;\n@p mbarrier.arrive.shared::cluster.b64 _, [r];\n}" ::"r"(a),
               "r"(cta), "r"((uint32_t)pred) : "memory");
}
__device__ __forceinline__ void mbar_arrive_cluster_after(uint32_t a, uint32_t cta, bool pred, float anchor) {
  asm volatile("{\n.reg .b32 r;\n.reg .pred p;\nsetp.ne.u32 p, %2, 0;\nsetp.leu.and.f32 p, %3, 0f7F800000, p;\n"
               "mapa.shared::cluster.u32 r, %0, %1;\n@p mbarrier.arrive.shared::cluster.b64 _, [r];\n}" ::"r"(a),
               "r"(cta), "r"((uint32_t)pred), "f"(anchor) : "memory");
}
__device__ __forceinline__ void anchor(float v, uint32_t pred) {
  asm volatile("{\n.reg .pred p;\nsetp.ne.u32 p, %1, 0;\n@p st.shared.f32 [%1], %0;\n}" ::"f"(v), "r"(pred) : "memory");
}
__device__ __forceinline__ void mbar_arrive_if(uint32_t a, bool pred) {
  asm volatile("{\n.reg .pred p;\nsetp.ne.u32 p, %1, 0;\n@p mbarrier.arrive.shared::cta.b64 _, [%0];\n}" ::"r"(a), "r"((uint32_t)pred) : "memory");
}
__device__ __forceinline__ void tma2d(uint32_t dst, const CUtensorMap* m, uint32_t bar, int c0, int c1) {
  asm volatile("cp.async.bulk.tensor.2d.shared::cluster.global.mbarrier::complete_tx::bytes [%0], [%1, {%3, %4}], [%2];" ::"r"(dst),
               "l"(m), "r"(bar), "r"(c0), "r"(c1) : "memory");
}
__device__ __forceinline__ void tma2d_mc(uint32_t dst, const CUtensorMap* m, uint32_t bar, int c0, int c1, uint16_t mask) {
  asm volatile(
      "cp.async.bulk.tensor.2d.shared::cluster.global.mbarrier::complete_tx::bytes.multicast::cluster [%0], [%1, {%3, %4}], [%2], %5;" ::"r"(dst),
      "l"(m), "r"(bar), "r"(c0), "r"(c1), "h"(mask) : "memory");
}
__device__ __forceinline__ void tma3d_mc(uint32_t dst, const CUtensorMap* m, uint32_t bar, int c0, int c1, int c2, uint16_t mask) {
  asm volatile(
      "cp.async.bulk.tensor.3d.shared::cluster.global.mbarrier::complete_tx::bytes.multicast::cluster [%0], [%1, {%3, %4, %5}], [%2], %6;" ::"r"(dst),
      "l"(m), "r"(bar), "r"(c0), "r"(c1), "r"(c2), "h"(mask) : "memory");
}
__device__ __forceinline__ uint64_t policy_evict_first() {
  uint64_t p;
  asm volatile("createpolicy.fractional.L2::evict_first.b64 %0, 1.0;" : "=l"(p));
  return p;
}
__device__ __forceinline__ void tma3d_mc_h(uint32_t dst, const CUtensorMap* m, uint32_t bar, int c0, int c1, int c2, uint16_t mask, uint64_t pol) {
  asm volatile(
      "cp.async.bulk.tensor.3d.shared::cluster.global.mbarrier::complete_tx::bytes.multicast::cluster.L2::cache_hint [%0], [%1, {%3, %4, %5}], [%2], %6, %7;" ::"r"(dst),
      "l"(m), "r"(bar), "r"(c0), "r"(c1), "r"(c2), "h"(mask), "l"(pol) : "memory");
}
__device__ __forceinline__ void tma2d_h(uint32_t dst, const CUtensorMap* m, uint32_t bar, int c0, int c1, uint64_t pol) {
  asm volatile("cp.async.bulk.tensor.2d.shared::cluster.global.mbarrier::complete_tx::bytes.L2::cache_hint [%0], [%1, {%3, %4}], [%2], %5;" ::"r"(dst),
               "l"(m), "r"(bar), "r"(c0), "r"(c1), "l"(pol) : "memory");
}
__device__ __forceinline__ void tma3d(uint32_t dst, const CUtensorMap* m, uint32_t bar, int c0, int c1, int c2) {
  asm volatile(
      "cp.async.bulk.tensor.3d.shared::cluster.global.mbarrier::complete_tx::bytes [%0], [%1, {%3, %4, %5}], [%2];" ::"r"(dst),
      "l"(m), "r"(bar), "r"(c0), "r"(c1), "r"(c2) : "memory");
}
__device__ __forceinline__ void tma_pf2d(const CUtensorMap* m, int c0, int c1) {
  asm volatile("cp.async.bulk.prefetch.tensor.2d.L2.global [%0, {%1, %2}];" ::"l"(m), "r"(c0), "r"(c1) : "memory");
}
__device__ __forceinline__ void tma_pf3d(const CUtensorMap* m, int c0, int c1, int c2) {
  asm volatile("cp.async.bulk.prefetch.tensor.3d.L2.global [%0, {%1, %2, %3}];" ::"l"(m), "r"(c0), "r"(c1), "r"(c2) : "memory");
}
__device__ __forceinline__ void prefetch_tmap(const CUtensorMap* m) {
  asm volatile("prefetch.tensormap [%0];" ::"l"(m) : "memory");
}
__device__ __forceinline__ void cluster_arrive() { asm volatile("barrier.cluster.arrive.relaxed.aligned;" ::: "memory"); }
__device__ __forceinline__ void cluster_wait() { asm volatile("barrier.cluster.wait.aligned;" ::: "memory"); }
__device__ __forceinline__ void cluster_sync() {
  cluster_arrive();
  cluster_wait();
}
__device__ __forceinline__ uint32_t cluster_rank() {
  uint32_t r;
  asm volatile("mov.u32 %0, %%cluster_ctarank;" : "=r"(r));
  return r;
}
__device__ __forceinline__ bool elect_one() {
  uint32_t p;
  asm volatile("{\n.reg .pred q;\nelect.sync _|q, 0xffffffff;\nselp.u32 %0, 1, 0, q;\n}" : "=r"(p));
  return p;
}
__device__ __forceinline__ void pdl_wait() { asm volatile("griddepcontrol.wait;" ::: "memory"); }
__device__ __forceinline__ void pdl_launch() { asm volatile("griddepcontrol.launch_dependents;" ::: "memory"); }
__device__ __forceinline__ void ldsm_x4(uint32_t& r0, uint32_t& r1, uint32_t& r2, uint32_t& r3, uint32_t addr) {
  asm volatile("ldmatrix.sync.aligned.m8n8.x4.shared.b16 {%0, %1, %2, %3}, [%4];" : "=r"(r0), "=r"(r1), "=r"(r2), "=r"(r3) : "r"(addr) : "memory");
}
__device__ __forceinline__ void wg_fence() { asm volatile("wgmma.fence.sync.aligned;" ::: "memory"); }
__device__ __forceinline__ void wg_commit() { asm volatile("wgmma.commit_group.sync.aligned;" ::: "memory"); }
template <int N>
__device__ __forceinline__ void wg_wait() { asm volatile("wgmma.wait_group.sync.aligned %0;" ::"n"(N) : "memory"); }
template <int N>
__device__ __forceinline__ void reg_alloc() { asm volatile("setmaxnreg.inc.sync.aligned.u32 %0;" ::"n"(N)); }
template <int N>
__device__ __forceinline__ void reg_dealloc() { asm volatile("setmaxnreg.dec.sync.aligned.u32 %0;" ::"n"(N)); }
__device__ __forceinline__ void bar_sync(int id, int n) { asm volatile("bar.sync %0, %1;" ::"r"(id), "r"(n) : "memory"); }
__device__ __forceinline__ void bar_arrive(int id, int n) { asm volatile("bar.arrive %0, %1;" ::"r"(id), "r"(n) : "memory"); }
template <int NT>
__device__ __forceinline__ void fence_regs(float (&d)[NT]) {
#pragma unroll
  for (int i = 0; i < NT; i++) asm volatile("" : "+f"(d[i])::"memory");
}
template <int NT>
__device__ __forceinline__ void fence_regs(uint32_t (&d)[NT]) {
#pragma unroll
  for (int i = 0; i < NT; i++) asm volatile("" : "+r"(d[i])::"memory");
}
__device__ __forceinline__ uint64_t make_desc(uint32_t saddr, uint32_t lbo, uint32_t sbo, uint32_t layout) {
  return (uint64_t)((saddr & 0x3FFFF) >> 4) | ((uint64_t)(lbo >> 4) << 16) | ((uint64_t)(sbo >> 4) << 32) | ((uint64_t)layout << 62);
}
__device__ __forceinline__ uint32_t pack_bf16(float lo, float hi) {
  uint32_t r;
  asm("cvt.rn.bf16x2.f32 %0, %1, %2;" : "=r"(r) : "f"(hi), "f"(lo));
  return r;
}
__device__ __forceinline__ float ex2(float x) {
  float r;
  asm("ex2.approx.ftz.f32 %0, %1;" : "=f"(r) : "f"(x));
  return r;
}
__device__ __forceinline__ void st_v4(void* p, uint32_t a, uint32_t b, uint32_t c, uint32_t d) {
#define ST_MOD ".cs"
  asm volatile("st.global" ST_MOD ".v4.b32 [%0], {%1, %2, %3, %4};" ::"l"(p), "r"(a), "r"(b), "r"(c), "r"(d) : "memory");
}
#define STA_MOD ".cs"
__device__ __forceinline__ void st_v4a(void* p, uint32_t a, uint32_t b, uint32_t c, uint32_t d) {
  asm volatile("st.global" STA_MOD ".v4.b32 [%0], {%1, %2, %3, %4};" ::"l"(p), "r"(a), "r"(b), "r"(c), "r"(d) : "memory");
}
__device__ __forceinline__ float bf_lo(uint32_t v) { return __uint_as_float(v << 16); }
__device__ __forceinline__ float bf_hi(uint32_t v) { return __uint_as_float(v & 0xFFFF0000u); }

__device__ __forceinline__ void quad_transpose(uint32_t& a0, uint32_t& a1, uint32_t& a2, uint32_t& a3, int q) {
  const bool o1 = q & 1, o2 = q & 2;
  uint32_t t0 = o1 ? a0 : a1, t1 = o1 ? a2 : a3;
  t0 = __shfl_xor_sync(0xffffffffu, t0, 1);
  t1 = __shfl_xor_sync(0xffffffffu, t1, 1);
  if (o1) { a0 = t0; a2 = t1; } else { a1 = t0; a3 = t1; }
  t0 = o2 ? a0 : a2;
  t1 = o2 ? a1 : a3;
  t0 = __shfl_xor_sync(0xffffffffu, t0, 2);
  t1 = __shfl_xor_sync(0xffffffffu, t1, 2);
  if (o2) { a0 = t0; a1 = t1; } else { a2 = t0; a3 = t1; }
}

template<int TB, int OFF, int NT>
__device__ __forceinline__ void wgmma_ss_n256(float (&d)[NT], uint64_t da, uint64_t db, int scale_d) {
  asm volatile("{\n.reg .pred p;\nsetp.ne.b32 p, %130, 0;\n"
    "wgmma.mma_async.sync.aligned.m64n256k16.f32.bf16.bf16 {%0, %1, %2, %3, %4, %5, %6, %7, %8, %9, %10, %11, %12, %13, %14, %15, %16, %17, %18, %19, %20, %21, %22, %23, %24, %25, %26, %27, %28, %29, %30, %31, %32, %33, %34, %35, %36, %37, %38, %39, %40, %41, %42, %43, %44, %45, %46, %47, %48, %49, %50, %51, %52, %53, %54, %55, %56, %57, %58, %59, %60, %61, %62, %63, %64, %65, %66, %67, %68, %69, %70, %71, %72, %73, %74, %75, %76, %77, %78, %79, %80, %81, %82, %83, %84, %85, %86, %87, %88, %89, %90, %91, %92, %93, %94, %95, %96, %97, %98, %99, %100, %101, %102, %103, %104, %105, %106, %107, %108, %109, %110, %111, %112, %113, %114, %115, %116, %117, %118, %119, %120, %121, %122, %123, %124, %125, %126, %127}, %128, %129, p, 1, 1, 0, %131;\n}\n"
    : "+f"(d[OFF+0]), "+f"(d[OFF+1]), "+f"(d[OFF+2]), "+f"(d[OFF+3]), "+f"(d[OFF+4]), "+f"(d[OFF+5]), "+f"(d[OFF+6]), "+f"(d[OFF+7]), "+f"(d[OFF+8]), "+f"(d[OFF+9]), "+f"(d[OFF+10]), "+f"(d[OFF+11]), "+f"(d[OFF+12]), "+f"(d[OFF+13]), "+f"(d[OFF+14]), "+f"(d[OFF+15]), "+f"(d[OFF+16]), "+f"(d[OFF+17]), "+f"(d[OFF+18]), "+f"(d[OFF+19]), "+f"(d[OFF+20]), "+f"(d[OFF+21]), "+f"(d[OFF+22]), "+f"(d[OFF+23]), "+f"(d[OFF+24]), "+f"(d[OFF+25]), "+f"(d[OFF+26]), "+f"(d[OFF+27]), "+f"(d[OFF+28]), "+f"(d[OFF+29]), "+f"(d[OFF+30]), "+f"(d[OFF+31]), "+f"(d[OFF+32]), "+f"(d[OFF+33]), "+f"(d[OFF+34]), "+f"(d[OFF+35]), "+f"(d[OFF+36]), "+f"(d[OFF+37]), "+f"(d[OFF+38]), "+f"(d[OFF+39]), "+f"(d[OFF+40]), "+f"(d[OFF+41]), "+f"(d[OFF+42]), "+f"(d[OFF+43]), "+f"(d[OFF+44]), "+f"(d[OFF+45]), "+f"(d[OFF+46]), "+f"(d[OFF+47]), "+f"(d[OFF+48]), "+f"(d[OFF+49]), "+f"(d[OFF+50]), "+f"(d[OFF+51]), "+f"(d[OFF+52]), "+f"(d[OFF+53]), "+f"(d[OFF+54]), "+f"(d[OFF+55]), "+f"(d[OFF+56]), "+f"(d[OFF+57]), "+f"(d[OFF+58]), "+f"(d[OFF+59]), "+f"(d[OFF+60]), "+f"(d[OFF+61]), "+f"(d[OFF+62]), "+f"(d[OFF+63]), "+f"(d[OFF+64]), "+f"(d[OFF+65]), "+f"(d[OFF+66]), "+f"(d[OFF+67]), "+f"(d[OFF+68]), "+f"(d[OFF+69]), "+f"(d[OFF+70]), "+f"(d[OFF+71]), "+f"(d[OFF+72]), "+f"(d[OFF+73]), "+f"(d[OFF+74]), "+f"(d[OFF+75]), "+f"(d[OFF+76]), "+f"(d[OFF+77]), "+f"(d[OFF+78]), "+f"(d[OFF+79]), "+f"(d[OFF+80]), "+f"(d[OFF+81]), "+f"(d[OFF+82]), "+f"(d[OFF+83]), "+f"(d[OFF+84]), "+f"(d[OFF+85]), "+f"(d[OFF+86]), "+f"(d[OFF+87]), "+f"(d[OFF+88]), "+f"(d[OFF+89]), "+f"(d[OFF+90]), "+f"(d[OFF+91]), "+f"(d[OFF+92]), "+f"(d[OFF+93]), "+f"(d[OFF+94]), "+f"(d[OFF+95]), "+f"(d[OFF+96]), "+f"(d[OFF+97]), "+f"(d[OFF+98]), "+f"(d[OFF+99]), "+f"(d[OFF+100]), "+f"(d[OFF+101]), "+f"(d[OFF+102]), "+f"(d[OFF+103]), "+f"(d[OFF+104]), "+f"(d[OFF+105]), "+f"(d[OFF+106]), "+f"(d[OFF+107]), "+f"(d[OFF+108]), "+f"(d[OFF+109]), "+f"(d[OFF+110]), "+f"(d[OFF+111]), "+f"(d[OFF+112]), "+f"(d[OFF+113]), "+f"(d[OFF+114]), "+f"(d[OFF+115]), "+f"(d[OFF+116]), "+f"(d[OFF+117]), "+f"(d[OFF+118]), "+f"(d[OFF+119]), "+f"(d[OFF+120]), "+f"(d[OFF+121]), "+f"(d[OFF+122]), "+f"(d[OFF+123]), "+f"(d[OFF+124]), "+f"(d[OFF+125]), "+f"(d[OFF+126]), "+f"(d[OFF+127])
    : "l"(da), "l"(db), "r"(scale_d), "n"(TB));
}
template<int TB, int OFF, int NT>
__device__ __forceinline__ void wgmma_ss_n192(float (&d)[NT], uint64_t da, uint64_t db, int scale_d) {
  asm volatile("{\n.reg .pred p;\nsetp.ne.b32 p, %98, 0;\n"
    "wgmma.mma_async.sync.aligned.m64n192k16.f32.bf16.bf16 {%0, %1, %2, %3, %4, %5, %6, %7, %8, %9, %10, %11, %12, %13, %14, %15, %16, %17, %18, %19, %20, %21, %22, %23, %24, %25, %26, %27, %28, %29, %30, %31, %32, %33, %34, %35, %36, %37, %38, %39, %40, %41, %42, %43, %44, %45, %46, %47, %48, %49, %50, %51, %52, %53, %54, %55, %56, %57, %58, %59, %60, %61, %62, %63, %64, %65, %66, %67, %68, %69, %70, %71, %72, %73, %74, %75, %76, %77, %78, %79, %80, %81, %82, %83, %84, %85, %86, %87, %88, %89, %90, %91, %92, %93, %94, %95}, %96, %97, p, 1, 1, 0, %99;\n}\n"
    : "+f"(d[OFF+0]), "+f"(d[OFF+1]), "+f"(d[OFF+2]), "+f"(d[OFF+3]), "+f"(d[OFF+4]), "+f"(d[OFF+5]), "+f"(d[OFF+6]), "+f"(d[OFF+7]), "+f"(d[OFF+8]), "+f"(d[OFF+9]), "+f"(d[OFF+10]), "+f"(d[OFF+11]), "+f"(d[OFF+12]), "+f"(d[OFF+13]), "+f"(d[OFF+14]), "+f"(d[OFF+15]), "+f"(d[OFF+16]), "+f"(d[OFF+17]), "+f"(d[OFF+18]), "+f"(d[OFF+19]), "+f"(d[OFF+20]), "+f"(d[OFF+21]), "+f"(d[OFF+22]), "+f"(d[OFF+23]), "+f"(d[OFF+24]), "+f"(d[OFF+25]), "+f"(d[OFF+26]), "+f"(d[OFF+27]), "+f"(d[OFF+28]), "+f"(d[OFF+29]), "+f"(d[OFF+30]), "+f"(d[OFF+31]), "+f"(d[OFF+32]), "+f"(d[OFF+33]), "+f"(d[OFF+34]), "+f"(d[OFF+35]), "+f"(d[OFF+36]), "+f"(d[OFF+37]), "+f"(d[OFF+38]), "+f"(d[OFF+39]), "+f"(d[OFF+40]), "+f"(d[OFF+41]), "+f"(d[OFF+42]), "+f"(d[OFF+43]), "+f"(d[OFF+44]), "+f"(d[OFF+45]), "+f"(d[OFF+46]), "+f"(d[OFF+47]), "+f"(d[OFF+48]), "+f"(d[OFF+49]), "+f"(d[OFF+50]), "+f"(d[OFF+51]), "+f"(d[OFF+52]), "+f"(d[OFF+53]), "+f"(d[OFF+54]), "+f"(d[OFF+55]), "+f"(d[OFF+56]), "+f"(d[OFF+57]), "+f"(d[OFF+58]), "+f"(d[OFF+59]), "+f"(d[OFF+60]), "+f"(d[OFF+61]), "+f"(d[OFF+62]), "+f"(d[OFF+63]), "+f"(d[OFF+64]), "+f"(d[OFF+65]), "+f"(d[OFF+66]), "+f"(d[OFF+67]), "+f"(d[OFF+68]), "+f"(d[OFF+69]), "+f"(d[OFF+70]), "+f"(d[OFF+71]), "+f"(d[OFF+72]), "+f"(d[OFF+73]), "+f"(d[OFF+74]), "+f"(d[OFF+75]), "+f"(d[OFF+76]), "+f"(d[OFF+77]), "+f"(d[OFF+78]), "+f"(d[OFF+79]), "+f"(d[OFF+80]), "+f"(d[OFF+81]), "+f"(d[OFF+82]), "+f"(d[OFF+83]), "+f"(d[OFF+84]), "+f"(d[OFF+85]), "+f"(d[OFF+86]), "+f"(d[OFF+87]), "+f"(d[OFF+88]), "+f"(d[OFF+89]), "+f"(d[OFF+90]), "+f"(d[OFF+91]), "+f"(d[OFF+92]), "+f"(d[OFF+93]), "+f"(d[OFF+94]), "+f"(d[OFF+95])
    : "l"(da), "l"(db), "r"(scale_d), "n"(TB));
}
template<int TB, int OFF, int NT>
__device__ __forceinline__ void wgmma_ss_n128(float (&d)[NT], uint64_t da, uint64_t db, int scale_d) {
  asm volatile("{\n.reg .pred p;\nsetp.ne.b32 p, %66, 0;\n"
    "wgmma.mma_async.sync.aligned.m64n128k16.f32.bf16.bf16 {%0, %1, %2, %3, %4, %5, %6, %7, %8, %9, %10, %11, %12, %13, %14, %15, %16, %17, %18, %19, %20, %21, %22, %23, %24, %25, %26, %27, %28, %29, %30, %31, %32, %33, %34, %35, %36, %37, %38, %39, %40, %41, %42, %43, %44, %45, %46, %47, %48, %49, %50, %51, %52, %53, %54, %55, %56, %57, %58, %59, %60, %61, %62, %63}, %64, %65, p, 1, 1, 0, %67;\n}\n"
    : "+f"(d[OFF+0]), "+f"(d[OFF+1]), "+f"(d[OFF+2]), "+f"(d[OFF+3]), "+f"(d[OFF+4]), "+f"(d[OFF+5]), "+f"(d[OFF+6]), "+f"(d[OFF+7]), "+f"(d[OFF+8]), "+f"(d[OFF+9]), "+f"(d[OFF+10]), "+f"(d[OFF+11]), "+f"(d[OFF+12]), "+f"(d[OFF+13]), "+f"(d[OFF+14]), "+f"(d[OFF+15]), "+f"(d[OFF+16]), "+f"(d[OFF+17]), "+f"(d[OFF+18]), "+f"(d[OFF+19]), "+f"(d[OFF+20]), "+f"(d[OFF+21]), "+f"(d[OFF+22]), "+f"(d[OFF+23]), "+f"(d[OFF+24]), "+f"(d[OFF+25]), "+f"(d[OFF+26]), "+f"(d[OFF+27]), "+f"(d[OFF+28]), "+f"(d[OFF+29]), "+f"(d[OFF+30]), "+f"(d[OFF+31]), "+f"(d[OFF+32]), "+f"(d[OFF+33]), "+f"(d[OFF+34]), "+f"(d[OFF+35]), "+f"(d[OFF+36]), "+f"(d[OFF+37]), "+f"(d[OFF+38]), "+f"(d[OFF+39]), "+f"(d[OFF+40]), "+f"(d[OFF+41]), "+f"(d[OFF+42]), "+f"(d[OFF+43]), "+f"(d[OFF+44]), "+f"(d[OFF+45]), "+f"(d[OFF+46]), "+f"(d[OFF+47]), "+f"(d[OFF+48]), "+f"(d[OFF+49]), "+f"(d[OFF+50]), "+f"(d[OFF+51]), "+f"(d[OFF+52]), "+f"(d[OFF+53]), "+f"(d[OFF+54]), "+f"(d[OFF+55]), "+f"(d[OFF+56]), "+f"(d[OFF+57]), "+f"(d[OFF+58]), "+f"(d[OFF+59]), "+f"(d[OFF+60]), "+f"(d[OFF+61]), "+f"(d[OFF+62]), "+f"(d[OFF+63])
    : "l"(da), "l"(db), "r"(scale_d), "n"(TB));
}
template<int TB, int OFF, int NT>
__device__ __forceinline__ void wgmma_ss_n32(float (&d)[NT], uint64_t da, uint64_t db, int scale_d) {
  asm volatile("{\n.reg .pred p;\nsetp.ne.b32 p, %18, 0;\n"
    "wgmma.mma_async.sync.aligned.m64n32k16.f32.bf16.bf16 {%0, %1, %2, %3, %4, %5, %6, %7, %8, %9, %10, %11, %12, %13, %14, %15}, %16, %17, p, 1, 1, 0, %19;\n}\n"
    : "+f"(d[OFF+0]), "+f"(d[OFF+1]), "+f"(d[OFF+2]), "+f"(d[OFF+3]), "+f"(d[OFF+4]), "+f"(d[OFF+5]), "+f"(d[OFF+6]), "+f"(d[OFF+7]), "+f"(d[OFF+8]), "+f"(d[OFF+9]), "+f"(d[OFF+10]), "+f"(d[OFF+11]), "+f"(d[OFF+12]), "+f"(d[OFF+13]), "+f"(d[OFF+14]), "+f"(d[OFF+15])
    : "l"(da), "l"(db), "r"(scale_d), "n"(TB));
}
template<int TB, int OFF, int NT>
__device__ __forceinline__ void wgmma_rs_n128(float (&d)[NT], uint32_t a0, uint32_t a1, uint32_t a2, uint32_t a3, uint64_t db, int scale_d) {
  asm volatile("{\n.reg .pred p;\nsetp.ne.b32 p, %69, 0;\n"
    "wgmma.mma_async.sync.aligned.m64n128k16.f32.bf16.bf16 {%0, %1, %2, %3, %4, %5, %6, %7, %8, %9, %10, %11, %12, %13, %14, %15, %16, %17, %18, %19, %20, %21, %22, %23, %24, %25, %26, %27, %28, %29, %30, %31, %32, %33, %34, %35, %36, %37, %38, %39, %40, %41, %42, %43, %44, %45, %46, %47, %48, %49, %50, %51, %52, %53, %54, %55, %56, %57, %58, %59, %60, %61, %62, %63}, {%64, %65, %66, %67}, %68, p, 1, 1, %70;\n}\n"
    : "+f"(d[OFF+0]), "+f"(d[OFF+1]), "+f"(d[OFF+2]), "+f"(d[OFF+3]), "+f"(d[OFF+4]), "+f"(d[OFF+5]), "+f"(d[OFF+6]), "+f"(d[OFF+7]), "+f"(d[OFF+8]), "+f"(d[OFF+9]), "+f"(d[OFF+10]), "+f"(d[OFF+11]), "+f"(d[OFF+12]), "+f"(d[OFF+13]), "+f"(d[OFF+14]), "+f"(d[OFF+15]), "+f"(d[OFF+16]), "+f"(d[OFF+17]), "+f"(d[OFF+18]), "+f"(d[OFF+19]), "+f"(d[OFF+20]), "+f"(d[OFF+21]), "+f"(d[OFF+22]), "+f"(d[OFF+23]), "+f"(d[OFF+24]), "+f"(d[OFF+25]), "+f"(d[OFF+26]), "+f"(d[OFF+27]), "+f"(d[OFF+28]), "+f"(d[OFF+29]), "+f"(d[OFF+30]), "+f"(d[OFF+31]), "+f"(d[OFF+32]), "+f"(d[OFF+33]), "+f"(d[OFF+34]), "+f"(d[OFF+35]), "+f"(d[OFF+36]), "+f"(d[OFF+37]), "+f"(d[OFF+38]), "+f"(d[OFF+39]), "+f"(d[OFF+40]), "+f"(d[OFF+41]), "+f"(d[OFF+42]), "+f"(d[OFF+43]), "+f"(d[OFF+44]), "+f"(d[OFF+45]), "+f"(d[OFF+46]), "+f"(d[OFF+47]), "+f"(d[OFF+48]), "+f"(d[OFF+49]), "+f"(d[OFF+50]), "+f"(d[OFF+51]), "+f"(d[OFF+52]), "+f"(d[OFF+53]), "+f"(d[OFF+54]), "+f"(d[OFF+55]), "+f"(d[OFF+56]), "+f"(d[OFF+57]), "+f"(d[OFF+58]), "+f"(d[OFF+59]), "+f"(d[OFF+60]), "+f"(d[OFF+61]), "+f"(d[OFF+62]), "+f"(d[OFF+63])
    : "r"(a0), "r"(a1), "r"(a2), "r"(a3), "l"(db), "r"(scale_d), "n"(TB));
}
template<int TB, int OFF, int NT>
__device__ __forceinline__ void wgmma_rs_n64(float (&d)[NT], uint32_t a0, uint32_t a1, uint32_t a2, uint32_t a3, uint64_t db, int scale_d) {
  asm volatile("{\n.reg .pred p;\nsetp.ne.b32 p, %37, 0;\n"
    "wgmma.mma_async.sync.aligned.m64n64k16.f32.bf16.bf16 {%0, %1, %2, %3, %4, %5, %6, %7, %8, %9, %10, %11, %12, %13, %14, %15, %16, %17, %18, %19, %20, %21, %22, %23, %24, %25, %26, %27, %28, %29, %30, %31}, {%32, %33, %34, %35}, %36, p, 1, 1, %38;\n}\n"
    : "+f"(d[OFF+0]), "+f"(d[OFF+1]), "+f"(d[OFF+2]), "+f"(d[OFF+3]), "+f"(d[OFF+4]), "+f"(d[OFF+5]), "+f"(d[OFF+6]), "+f"(d[OFF+7]), "+f"(d[OFF+8]), "+f"(d[OFF+9]), "+f"(d[OFF+10]), "+f"(d[OFF+11]), "+f"(d[OFF+12]), "+f"(d[OFF+13]), "+f"(d[OFF+14]), "+f"(d[OFF+15]), "+f"(d[OFF+16]), "+f"(d[OFF+17]), "+f"(d[OFF+18]), "+f"(d[OFF+19]), "+f"(d[OFF+20]), "+f"(d[OFF+21]), "+f"(d[OFF+22]), "+f"(d[OFF+23]), "+f"(d[OFF+24]), "+f"(d[OFF+25]), "+f"(d[OFF+26]), "+f"(d[OFF+27]), "+f"(d[OFF+28]), "+f"(d[OFF+29]), "+f"(d[OFF+30]), "+f"(d[OFF+31])
    : "r"(a0), "r"(a1), "r"(a2), "r"(a3), "l"(db), "r"(scale_d), "n"(TB));
}

__device__ __forceinline__ void wait_flag(const unsigned int* f, uint32_t target) {
  uint32_t v;
#pragma unroll 1
  for (uint32_t spins = 0; spins < (1u << 22); spins++) {
    asm volatile("ld.acquire.gpu.global.u32 %0, [%1];" : "=r"(v) : "l"(f) : "memory");
    if (v >= target) break;
    __nanosleep(100);
  }
}
__device__ __forceinline__ uint32_t lds32(uint32_t a) {
  uint32_t v;
  asm volatile("ld.shared.u32 %0, [%1];" : "=r"(v) : "r"(a) : "memory");
  return v;
}
__device__ __forceinline__ float gate_row(int row, int lane, const bf16* __restrict__ x, const bf16* __restrict__ gate_w) {
  const uint32_t* xr = reinterpret_cast<const uint32_t*>(x + (size_t)row * DM);
  const uint32_t* gw2 = reinterpret_cast<const uint32_t*>(gate_w);
  float gs = 0.f;
#pragma unroll
  for (int i = 0; i < 9; i++) {
    const uint32_t a = __ldg(xr + lane + 32 * i), b = __ldg(gw2 + lane + 32 * i);
    gs = fmaf(bf_lo(a), bf_lo(b), gs);
    gs = fmaf(bf_hi(a), bf_hi(b), gs);
  }
#pragma unroll
  for (int o = 16; o; o >>= 1) gs += __shfl_xor_sync(0xffffffffu, gs, o);
  const float g = 1.f / (1.f + __expf(-gs));
  if (lane == 0) g_gate[row] = g;
  return g;
}
#define LA_UNROLL 9
__device__ __forceinline__ void local_rows2(int rb, int ri, uint32_t sL, uint32_t bL2, int lane, float ga, float gb) {
  const float scale_l2 = 0.23570226039551584f * 1.4426950408889634f;
  constexpr int U = LA_UNROLL;
  const uint32_t sq = sL + (30 + ri) * 1152;
  uint32_t kb[9];
#pragma unroll
  for (int i = 0; i < 9; i++) {
    const uint32_t c = lane * 9 + i;
    kb[i] = sL + (14 + ri) * 1152 + ((c & ~15u) | ((c & 3) << 2) | ((c >> 2) & 3)) * 4;
  }
  float ma = -INFINITY, mb = -INFINITY;
  {
    float qa[18], qb[18];
#pragma unroll
    for (int i = 0; i < 9; i++) {
      const uint32_t u = lds32(kb[i] + 16 * 1152 - 2304), v = lds32(kb[i] + 16 * 1152);
      qa[2 * i] = bf_lo(u); qa[2 * i + 1] = bf_hi(u);
      qb[2 * i] = bf_lo(v); qb[2 * i + 1] = bf_hi(v);
    }
    __syncwarp();
#pragma unroll U
    for (int t = 0; t < 9; t++) {
      const bool ok = rb - 2 * t >= 0;
      float a0 = 0.f, a1 = 0.f, b0 = 0.f, b1 = 0.f;
#pragma unroll
      for (int i = 0; i < 9; i++) {
        const uint32_t k = lds32(kb[i] - t * 2304);
        const float lo = bf_lo(k), hi = bf_hi(k);
        a0 = fmaf(qa[2 * i], lo, a0); a1 = fmaf(qa[2 * i + 1], hi, a1);
        b0 = fmaf(qb[2 * i], lo, b0); b1 = fmaf(qb[2 * i + 1], hi, b1);
      }
      a0 = (ok && t > 0) ? a0 + a1 : -INFINITY;
      b0 = (ok && t < 8) ? b0 + b1 : -INFINITY;
      ma = fmaxf(ma, a0);
      mb = fmaxf(mb, b0);
      asm volatile("st.shared.f32 [%0], %1;" ::"r"(sq - 2304 + t * 128 + lane * 4), "f"(a0) : "memory");
      asm volatile("st.shared.f32 [%0], %1;" ::"r"(sq + t * 128 + lane * 4), "f"(b0) : "memory");
    }
  }
  float oa[18], ob[18], sa = 0.f, sb = 0.f;
#pragma unroll
  for (int i = 0; i < 18; i++) { oa[i] = 0.f; ob[i] = 0.f; }
  mbar_wait(bL2, 0);
#pragma unroll U
  for (int t = 0; t < 9; t++) {
    const float wa = ex2((__uint_as_float(lds32(sq - 2304 + t * 128 + lane * 4)) - ma) * scale_l2);
    const float wb = ex2((__uint_as_float(lds32(sq + t * 128 + lane * 4)) - mb) * scale_l2);
    sa += wa;
    sb += wb;
#pragma unroll
    for (int i = 0; i < 9; i++) {
      const uint32_t v = lds32(kb[i] + 46 * 1152 - t * 2304);
      const float lo = bf_lo(v), hi = bf_hi(v);
      oa[2 * i] = fmaf(wa, lo, oa[2 * i]); oa[2 * i + 1] = fmaf(wa, hi, oa[2 * i + 1]);
      ob[2 * i] = fmaf(wb, lo, ob[2 * i]); ob[2 * i + 1] = fmaf(wb, hi, ob[2 * i + 1]);
    }
  }
  ga = __fdividef(ga, sa);
  gb = __fdividef(gb, sb);
  __syncwarp();
#pragma unroll
  for (int i = 0; i < 9; i++) {
    asm volatile("st.shared.u32 [%0], %1;" ::"r"(sq - 2304 + lane * 36 + 4 * i), "r"(pack_bf16(oa[2 * i] * ga, oa[2 * i + 1] * ga)) : "memory");
    asm volatile("st.shared.u32 [%0], %1;" ::"r"(sq + lane * 36 + 4 * i), "r"(pack_bf16(ob[2 * i] * gb, ob[2 * i + 1] * gb)) : "memory");
  }
  __syncwarp();
  uint32_t w[5][4];
#pragma unroll
  for (int t = 0; t < 5; t++) {
    const int c = min(t * 32 + lane, 143), r = c >= 72;
    asm volatile("ld.shared.v4.u32 {%0, %1, %2, %3}, [%4];" : "=r"(w[t][0]), "=r"(w[t][1]), "=r"(w[t][2]), "=r"(w[t][3])
                 : "r"(sq - 2304 + r * 2304 + (c - r * 72) * 16) : "memory");
  }
  asm volatile("fence.proxy.async.shared::cta;" ::: "memory");
  bar_arrive(4, 256 + 32);
#pragma unroll
  for (int t = 0; t < 5; t++) {
    const int c = min(t * 32 + lane, 143), r = c >= 72;
    st_v4(g_ctx + (size_t)(rb - 2 + 2 * r) * KCAT + HDIM + (c - r * 72) * 8, w[t][0], w[t][1], w[t][2], w[t][3]);
  }
}

#define K1_NST 6
constexpr int K1_BST = K1_NST;
constexpr int K1_MAXJOBS = 11;
constexpr uint32_t K1_FLAG_TARGET = 7;
constexpr uint32_t RDY_TARGET = 48;
constexpr uint32_t GATE_TARGET = 128 * 3;
struct alignas(64) Params {
  CUtensorMap tmA[2];
  CUtensorMap tmW[4];
  CUtensorMap tmQ, tmK, tmV;
  CUtensorMap tmL[2];
  CUtensorMap tmC, tmO[2], tmOt[2];
  uint16_t jobs[NCLUSTER][K1_MAXJOBS + 1];
  uint8_t order[256];
  uint8_t unit[64][4];
};

struct K1State {
  uint32_t bs, bph, aph;
  bf16* pp;
  int pld8;
  int png;
  int tn;
};
__device__ __forceinline__ void k1_flag(const K1State& st, int lane, uint32_t bS) {
  if (st.png) {
    __syncwarp();
    if (lane == 0) mbar_arrive(bS);
  }
}

__device__ __forceinline__ void k1_first(const K1State& st, uint32_t job, uint32_t bAf, uint32_t bBf) {
  if (job & 3) {
    if ((job >> 14) & 1) mbar_wait(bAf, st.aph);
    mbar_wait(bBf + st.bs * 8, st.bph);
  }
}
__device__ __forceinline__ void k1_tile(float (&acc)[128], uint32_t (&pk)[64], K1State& st, uint32_t job, uint32_t njob, uint32_t sA, uint32_t sB,
                                        uint32_t bAf, uint32_t bAe, uint32_t bBf, uint32_t bBe, uint32_t bS, int wg, int warp, int lane, uint32_t rank) {
  const int a_sel = (job >> 2) & 1, mpair = (job >> 3) & 7, w_sel = (job >> 6) & 3, chunk0 = (job >> 8) & 63;
  const bool newA = (job >> 14) & 1, lastA = (job >> 15) & 1;
  const bool sig = (lane == 0) && (warp < 2);
  const bool siga = lastA && (lane == 0) && (warp == 2);
  const int KC = 8 + a_sel;
  uint32_t prev_bs = 0, a8_bs = 0;
#pragma unroll
  for (int kc = 0; kc < 9; kc++) {
    if (kc >= KC) break;
    uint32_t abase = sA + ((kc + 2) & 7) * 16384;
    if (kc == 8) {
      mbar_wait(bBf + st.bs * 8, st.bph);
      a8_bs = st.bs;
      abase = sB + st.bs * 16384;
      if (++st.bs == K1_BST) { st.bs = 0; st.bph ^= 1; }
    } else if (newA && kc > 0) {
      mbar_wait(bAf + kc * 8, st.aph);
    }
    const uint64_t da = make_desc(abase + wg * 8192, 16, 1024, 1);
#pragma unroll
    for (int ks = 0; ks < 2; ks++) {
      if (ks > 0 || kc > 0) mbar_wait(bBf + st.bs * 8, st.bph);
      const uint64_t db = make_desc(sB + st.bs * 16384, 2048, 1024, 1);
      wg_fence();
      wgmma_ss_n256<1, 0>(acc, da + (uint64_t)(ks * 4), db, (ks > 0) ? 1 : (kc > 0));
      wgmma_ss_n256<1, 0>(acc, da + (uint64_t)(ks * 4 + 2), db + (uint64_t)512, 1);
      wg_commit();
      const int PO = (kc < 8 ? kc : 0) * 8;
      wg_wait<1>();
      if (ks > 0 || kc > 0) {
        if (sig) mbar_arrive_cluster(bBe + prev_bs * 8, warp);
        if (ks == 0 && siga) mbar_arrive(bAe + (kc - 1) * 8);
      }
      if (kc < st.png) st_v4a(st.pp + kc * 32 + ks * st.pld8, pk[PO + ks * 4], pk[PO + ks * 4 + 1], pk[PO + ks * 4 + 2], pk[PO + ks * 4 + 3]);
      prev_bs = st.bs;
      if (++st.bs == K1_BST) { st.bs = 0; st.bph ^= 1; }
    }
  }
  if (newA) st.aph ^= 1;
  k1_flag(st, lane, bS);
  const bool isA = (w_sel == 2);
  bf16* out = (w_sel == 0) ? g_K : (w_sel == 1) ? g_V : isA ? g_QKVA : g_Q;
  const int ld = isA ? NQKVA : HDIM;
  const int row = mpair * 256 + rank * 128 + wg * 64 + warp * 16 + (lane >> 2);
  st.pp = out + (size_t)row * ld + chunk0 * 64 + (lane & 3) * 8;
  st.pld8 = 8 * ld;
  st.png = ((job & 3) + 1) * 2;
  k1_first(st, njob, bAf, bBf);
  wg_wait<0>();
  fence_regs(acc);
  mbar_arrive_cluster_if(bBe + prev_bs * 8, warp & 1, sig);
  mbar_arrive_cluster_if(bBe + a8_bs * 8, warp & 1, sig && a_sel);
  mbar_arrive_if(bAe + 7 * 8, siga && !a_sel);
#pragma unroll
  for (int G = 0; G < 8; G++) {
    pk[G * 8 + 0] = pack_bf16(acc[G * 16 + 0], acc[G * 16 + 1]);
    pk[G * 8 + 1] = pack_bf16(acc[G * 16 + 4], acc[G * 16 + 5]);
    pk[G * 8 + 2] = pack_bf16(acc[G * 16 + 8], acc[G * 16 + 9]);
    pk[G * 8 + 3] = pack_bf16(acc[G * 16 + 12], acc[G * 16 + 13]);
    pk[G * 8 + 4] = pack_bf16(acc[G * 16 + 2], acc[G * 16 + 3]);
    pk[G * 8 + 5] = pack_bf16(acc[G * 16 + 6], acc[G * 16 + 7]);
    pk[G * 8 + 6] = pack_bf16(acc[G * 16 + 10], acc[G * 16 + 11]);
    pk[G * 8 + 7] = pack_bf16(acc[G * 16 + 14], acc[G * 16 + 15]);
  }
}

#define HA(h) (h)
constexpr int K2_NST = 7;
constexpr uint32_t K2_END = 0x100;
#define PF_KC 7
#define FIRST_DRAW 3
#define ANCH 8
#define PVM 0x8A
#define W0 63
#define SPEC 24
constexpr int K3_NST = 4;
__device__ __forceinline__ uint32_t k3_rot(uint32_t sv) { return (0x00E9u >> (2 * sv)) & 3; }
constexpr int K3_STAGE = 16384 + 32768 + 4096;
constexpr int SMEM_DATA = 7 * 32768;
constexpr int SMEM_BYTES = SMEM_DATA + 1024 + 768;

struct Cursor {
  uint32_t s, ph;
  __device__ __forceinline__ void next() {
    if (++s == K2_NST) { s = 0; ph ^= 1; }
  }
};

#define TURN_SYNC() bar_sync(mybar, 256)
#define TURN_ARRIVE() bar_arrive(otherbar, 256)
#define RELEASE_IF(cur, cond) mbar_arrive_cluster_if(bE + (cur).s * 8, warp & 1, sig && (cond))
#define RELEASE(cur) RELEASE_IF(cur, true)
#define ISSUE_PV(cur, first)                                                                                   \
  do {                                                                                                         \
    const uint64_t dv = make_desc(sbase + (cur).s * 32768, 16384, 1024, 1);                                    \
    _Pragma("unroll") for (int t = 0; t < 8; t++)                                                              \
        wgmma_rs_n128<1, 0>(O, P[4 * t], P[4 * t + 1], P[4 * t + 2], P[4 * t + 3], dv + (uint64_t)(t * 128), (t > 0) ? 1 : !(first)); \
  } while (0)
#define RESCALE_O()                                                                                            \
  do {                                                                                                         \
    fence_regs(O);                                                                                             \
    _Pragma("unroll") for (int jj = 0; jj < 16; jj++) {                                                        \
      O[jj * 4 + 0] *= sc0; O[jj * 4 + 1] *= sc0; O[jj * 4 + 2] *= sc1; O[jj * 4 + 3] *= sc1;                  \
    }                                                                                                          \
    fence_regs(O);                                                                                             \
  } while (0)
#define ISSUE_QK(cur)                                                                                          \
  do {                                                                                                         \
    const uint64_t dk = make_desc(sbase + (cur).s * 32768, 16, 1024, 1);                                       \
    _Pragma("unroll") for (int t = 0; t < 8; t++)                                                              \
        wgmma_rs_n128<0, 0>(S, Q[4 * t], Q[4 * t + 1], Q[4 * t + 2], Q[4 * t + 3], dk + (uint64_t)((t >> 2) * 1024 + (t & 3) * 2), t > 0); \
  } while (0)
#define EXPC(T)                                                                                                \
  do {                                                                                                         \
    if (T > 0 && ((PVM >> (T - 1)) & 1)) {                                                                     \
      if (!W0 && (PVM & ((1 << T) - 1)) == (1 << (T - 1))) mbar_arrive_cluster_after(bE + ck.s * 8, warp & 1, sig, s0 + s1); \
      else anchor((T & 2) ? s0 : s1, never);                                                                   \
      wg_wait<__builtin_popcount(PVM >> T) - 1>();                                                             \
      if ((PVM >> T) == (128 >> T)) { fence_regs(O); RELEASE(cv); }                                            \
    }                                                                                                          \
    _Pragma("unroll") for (int i = 4 * T; i < 4 * T + 4; i++) asm volatile("" : "+r"(P[i])::"memory");        \
    _Pragma("unroll") for (int jj = 2 * T; jj < 2 * T + 2; jj++) {                                             \
      const float e0 = ex2(S[jj * 4 + 0]), e1 = ex2(S[jj * 4 + 1]), e2 = ex2(S[jj * 4 + 2]), e3 = ex2(S[jj * 4 + 3]); \
      s0 += e0 + e1;                                                                                           \
      s1 += e2 + e3;                                                                                           \
      P[jj * 2 + 0] = pack_bf16(e0, e1);                                                                       \
      P[jj * 2 + 1] = pack_bf16(e2, e3);                                                                       \
    }                                                                                                          \
  } while (0)
#define EPILOGUE()                                                                                             \
  do {                                                                                                         \
    l0 += __shfl_xor_sync(0xffffffffu, l0, 1);                                                                 \
    l0 += __shfl_xor_sync(0xffffffffu, l0, 2);                                                                 \
    l1 += __shfl_xor_sync(0xffffffffu, l1, 1);                                                                 \
    l1 += __shfl_xor_sync(0xffffffffu, l1, 2);                                                                 \
    asm volatile("" : "+f"(gf0), "+f"(gf1));                                                                   \
    const float f0 = __fdividef(1.f - gf0, l0), f1 = __fdividef(1.f - gf1, l1);                                                                \
    bf16* o0 = g_ctx + (size_t)prev_row * KCAT + prev_h * 128 + q * 8;                                         \
    bf16* o1 = o0 + (size_t)8 * KCAT;                                                                          \
    _Pragma("unroll") for (int G = 0; G < 4; G++) {                                                            \
      st_v4(o0 + G * 32, pack_bf16(O[G * 16 + 0] * f0, O[G * 16 + 1] * f0), pack_bf16(O[G * 16 + 4] * f0, O[G * 16 + 5] * f0), \
            pack_bf16(O[G * 16 + 8] * f0, O[G * 16 + 9] * f0), pack_bf16(O[G * 16 + 12] * f0, O[G * 16 + 13] * f0)); \
      st_v4(o1 + G * 32, pack_bf16(O[G * 16 + 2] * f1, O[G * 16 + 3] * f1), pack_bf16(O[G * 16 + 6] * f1, O[G * 16 + 7] * f1), \
            pack_bf16(O[G * 16 + 10] * f1, O[G * 16 + 11] * f1), pack_bf16(O[G * 16 + 14] * f1, O[G * 16 + 15] * f1)); \
    }                                                                                                          \
  } while (0)

__global__ void __cluster_dims__(2, 1, 1) __launch_bounds__(384, 1)
fused_kernel(const __grid_constant__ Params p, const bf16* __restrict__ x, const bf16* __restrict__ gate_w, bf16* __restrict__ out) {
  extern __shared__ uint8_t smem_raw[];
  const uint32_t sbase = (smem_u32(smem_raw) + 1023) & ~1023u;
  const uint32_t sB = sbase, sA = sbase + K1_BST * 16384, sBar = sbase + SMEM_DATA;
  const uint32_t bAf = sBar, bAe = sBar + 64, bBf = sBar + 128, bBe = sBar + 176, bL = sBar + 224, bS = sBar + 232, bL2 = sBar + 240, sL = sA + 32768;
  const uint32_t bF = sBar + 256, bE = sBar + 320, bT = sBar + 384, sTick = sBar + 400, sItem = sBar + 416, bS2 = sBar + 448, bR = sBar + 456, bLast = sBar + 464, bH = sBar + 472, bT0 = sBar + 480;
  const uint32_t b3F = sBar + 512, b3E = sBar + 544, sGate = sBar + 576;
  const int tid = threadIdx.x, warp_g = __shfl_sync(0xffffffffu, tid >> 5, 0), lane = tid & 31;
  const uint32_t rank = cluster_rank();
  const int cl = blockIdx.x >> 1;
  TSM(0);
  if (tid == 0) {
    for (int i = 0; i < 8; i++) { mbar_init(bAf + i * 8, 1); mbar_init(bAe + i * 8, 2); }
    for (int i = 0; i < K1_BST; i++) { mbar_init(bBf + i * 8, 1); mbar_init(bBe + i * 8, 4); }
    mbar_init(bL, 1);
    mbar_init(bL2, 1);
    mbar_init(bR, 1);
    mbar_init(bLast, 1);
    mbar_init(bH, 4);
    mbar_init(bT0, 1);
    mbar_init(bS, 8);
    for (int i = 0; i < K2_NST; i++) { mbar_init(bF + i * 8, 1); mbar_init(bE + i * 8, 4); }
    mbar_init(bT, 1); mbar_init(bT + 8, 1);
    mbar_init(bS2, 8);
    for (int i = 0; i < K3_NST; i++) { mbar_init(b3F + i * 8, 1); mbar_init(b3E + i * 8, 4); }
    asm volatile("fence.mbarrier_init.release.cluster;" ::: "memory");
  }
  __syncthreads();
  cluster_sync();
  const int lr0 = blockIdx.x * 16;

  if (warp_g >= 8) {
    reg_dealloc<40>();
    if (warp_g == 8) {
      if (elect_one()) {
        uint32_t bs = 0, bph = 1, aph = 1;
#pragma unroll 1
        for (int ji = 0; ji < K1_MAXJOBS; ji++) {
          const uint32_t job = p.jobs[cl][ji];
          if (!(job & 3)) break;
          const int a_sel = (job >> 2) & 1, mpair = (job >> 3) & 7, chunk0 = (job >> 8) & 63;
          const bool newA = (job >> 14) & 1;
          const int KC = a_sel ? 9 : 8;
          const uint32_t halfbytes = 8192;
          const bool lastjob = (ji + 1 == K1_MAXJOBS) || !(p.jobs[cl][ji + 1] & 3);
          const CUtensorMap* tw = &p.tmW[(job >> 6) & 3];
          {
            const uint32_t njob = (ji + 1 < K1_MAXJOBS) ? p.jobs[cl][ji + 1] : 0;
            if (!(njob & 3) && !newA) mbar_arrive(bLast);
          }
#pragma unroll 1
          for (int kc = 0; kc < KC; kc++) {
            if (kc == ((ji == 0) ? PF_KC : 0) && !lastjob) {
              const uint32_t njob = p.jobs[cl][ji + 1];
              const int nst = ((njob >> 2) & 1) ? 18 : 16;
#pragma unroll 1
              for (int t = (cl < 64) ? (cl & 7) : 0; t < nst; t += (cl < 64) ? 8 : 1)
                tma_pf3d(&p.tmW[(njob >> 6) & 3], 0, t * 32 + rank * 16, (njob >> 8) & 63);
            }
            if (kc == 8) {
              mbar_wait(bBe + bs * 8, bph);
              mbar_expect(bBf + bs * 8, 16384);
              tma2d(sB + bs * 16384, &p.tmA[1], bBf + bs * 8, 512, mpair * 256 + rank * 128);
              if (++bs == K1_BST) { bs = 0; bph ^= 1; }
            } else if (newA) {
              mbar_wait(bAe + kc * 8, aph);
              mbar_expect(bAf + kc * 8, 16384);
              tma2d(sA + ((kc + 2) & 7) * 16384, &p.tmA[a_sel], bAf + kc * 8, kc * 64, mpair * 256 + rank * 128);
              if (kc == 7 && lastjob) mbar_arrive(bLast);
            }
#pragma unroll 1
            for (int kk = 0; kk < 2; kk++) {
              mbar_wait(bBe + bs * 8, bph);
              mbar_expect(bBf + bs * 8, 2 * halfbytes);
              tma3d_mc(sB + bs * 16384 + rank * halfbytes, tw, bBf + bs * 8, 0, kc * 64 + kk * 32 + rank * 16, chunk0, 3);
              if (++bs == K1_BST) { bs = 0; bph ^= 1; }
            }
          }
          if (newA) aph ^= 1;
        }
        Cursor c{0, 0};
        int pcol = 0;
        mbar_wait(bR, 0);
        uint32_t tick = lds32(sTick + 8), seen = 1u << (p.order[tick] >> 4);
        asm volatile("fence.proxy.async.global;" ::: "memory");
#pragma unroll 1
        for (int it = 0;; it++) {
          const uint32_t item = (tick < 256) ? p.order[tick] : (K2_END | min(tick - 256, 255u));
          asm volatile("st.shared.u32 [%0], %1;" ::"r"(sItem + (it & 7) * 4), "r"(item) : "memory");
          if (item >= K2_END) break;
          const int h = item >> 3, j = item & 7;
          const int blk = 2 * j + (int)(rank ^ (it & 1));
          const int col = HA(h) * 128 + rank * 64;
          const int nb = 2 * j + 2;
          if (!((seen >> (h >> 1)) & 1)) {
            wait_flag(&g_sync[F_HP + (h >> 1)], RDY_TARGET);
            asm volatile("fence.proxy.async.global;" ::: "memory");
            seen |= 1u << (h >> 1);
          }
          mbar_wait(bE + c.s * 8, c.ph);
          mbar_expect(bF + c.s * 8, 32768);
          tma2d(sbase + c.s * 32768, &p.tmQ, bF + c.s * 8, HA(h) * 128, blk * 128);
          tma2d(sbase + c.s * 32768 + 16384, &p.tmQ, bF + c.s * 8, HA(h) * 128 + 64, blk * 128);
          c.next();
#pragma unroll 1
          for (int n = nb - 1; n >= 0; n--) {
            if (n == 0 && rank == 0) tick = atomicAdd(&g_sync[F_TICK], 1u);
            mbar_wait(bE + c.s * 8, c.ph);
            mbar_expect(bF + c.s * 8, 32768);
            tma2d_mc(sbase + c.s * 32768 + rank * 16384, &p.tmK, bF + c.s * 8, col, n * 128, 3);
            c.next();
            if (n < nb - 1 || it > 0) {
              mbar_wait(bE + c.s * 8, c.ph);
              mbar_expect(bF + c.s * 8, 32768);
              tma2d_mc(sbase + c.s * 32768 + rank * 16384, &p.tmV, bF + c.s * 8, (n < nb - 1) ? col : pcol, (n < nb - 1) ? (n + 1) * 128 : 0, 3);
              c.next();
            }
          }
          pcol = col;
          if (rank == 0) {
            asm volatile(
                "{\n.reg .b32 a, b;\nmapa.shared::cluster.u32 a, %0, 1;\nmapa.shared::cluster.u32 b, %1, 1;\n"
                "st.async.shared::cluster.mbarrier::complete_tx::bytes.u32 [a], %2, [b];\n}" ::"r"(sTick + (it & 1) * 4),
                "r"(bT + (it & 1) * 8), "r"(tick) : "memory");
          } else {
            mbar_expect(bT + (it & 1) * 8, 4);
            mbar_wait(bT + (it & 1) * 8, (it >> 1) & 1);
            tick = lds32(sTick + (it & 1) * 4);
          }
        }
        mbar_wait(bE + c.s * 8, c.ph);
        mbar_expect(bF + c.s * 8, 32768);
        tma2d_mc(sbase + c.s * 32768 + rank * 16384, &p.tmV, bF + c.s * 8, pcol, 0, 3);
        const uint32_t unit = tick - 256;
        if (unit < 64) {
          const int mblk = (7 - (p.unit[unit][0] >> 1)) * 2 + rank, nhalf = p.unit[unit][0] & 1;
          const uint32_t rot = k3_rot(c.s), nfree = ((0x1Au >> c.s) & 1) ? 2 : 3;
#pragma unroll 1
          for (int i = 0; i < K2_NST - 1; i++) {
            c.next();
            mbar_wait(bE + c.s * 8, c.ph);
          }
          uint32_t idx = 0, have = 0;
#pragma unroll 1
          for (int kk = p.unit[unit][2]; kk < p.unit[unit][3]; kk++, idx++) {
            const uint32_t s = (rot + idx) & 3;
            if (idx >= nfree) mbar_wait((idx < 4) ? bH : b3E + s * 8, (idx < 4) ? 0 : (~idx >> 2) & 1);
            mbar_expect(b3F + s * 8, K3_STAGE);
            const uint32_t st = sbase + s * K3_STAGE;
            const int sel = (kk < 9), k = sel ? kk : kk - 9, kr = k * 64 + rank * 32;
            tma3d_mc(st + 16384 + rank * 16384, &p.tmO[sel], b3F + s * 8, 0, kr, nhalf * 4, 3);
            tma2d_mc(st + 49152 + rank * 2048, &p.tmOt[sel], b3F + s * 8, 512 + nhalf * 32, kr, 3);
            if (kk == 0) {
              wait_flag(&g_sync[F_OA + mblk], 8);
              asm volatile("fence.proxy.async.global;" ::: "memory");
            }
            if (!sel && !((have >> (k >> 1)) & 1)) {
#pragma unroll 1
              for (uint32_t spins = 0; spins < (1u << 22); spins++) {
                asm volatile("ld.acquire.gpu.global.u32 %0, [%1];" : "=r"(have) : "l"(&g_sync[F_CTX + mblk]) : "memory");
                if ((have >> (k >> 1)) & 1) break;
                __nanosleep(100);
              }
              asm volatile("fence.proxy.async.global;" ::: "memory");
            }
            tma2d(st, &p.tmC, b3F + s * 8, (sel ? 64 + k : k) * 64, mblk * 128);
          }
        }
      }
    }
    __syncwarp();
    if (warp_g == 8) {
      uint32_t v = 0;
      if (lane == 0) {
        __threadfence();
        v = atomicAdd(&g_sync[F_DONE], 1u);
      }
      if (__shfl_sync(0xffffffffu, v, 0) == 2 * NCLUSTER - 1) {
        reinterpret_cast<uint4*>(g_sync)[lane] = make_uint4(0, 0, 0, 0);
        if (lane == 0) g_sync[F_EPOCH] = lds32(sGate + 64) + 1;
      }
    }
    asm volatile("" ::: "memory");
    if (__shfl_sync(0xffffffffu, warp_g, 0) != 8) {
      if (lr0 < S_LEN) {
#pragma unroll 1
        for (int i = warp_g - 9; i < 16; i += 3) {
          const float g = gate_row(lr0 + i, lane, x, gate_w);
          if (lane == 0) asm volatile("st.shared.f32 [%0], %1;" ::"r"(sGate + i * 4), "f"(g) : "memory");
        }
        bar_arrive(3, 256 + 96);
        if (lane == 0) {
          __threadfence();
          atomicAdd(&g_sync[F_GATE], 1u);
        }
      }
      uint32_t aph = 1;
#pragma unroll 1
      for (int ji = 0; ji < K1_MAXJOBS; ji++) aph ^= (p.jobs[cl][ji] >> 14) & 1;
      if (warp_g == 9 && lane == 0) {
#pragma unroll 1
        for (int ji = 0; ji < K1_MAXJOBS; ji++) {
          const uint32_t job = p.jobs[cl][ji];
          if (!(job & 3)) break;
          mbar_wait(bS, ji & 1);
          __threadfence();
          atomicAdd(&g_sync[(((job >> 6) & 3) == 2) ? (F_QKVA + ((job >> 3) & 7) * 2 + rank) : (F_HP + ((job >> 10) & 15))], 1u);
        }
#pragma unroll 1
        for (int it = 0;; it++) {
          mbar_wait(bS2, it & 1);
          const uint32_t item = lds32(sItem + (it & 7) * 4), nxt = lds32(sItem + ((it + 1) & 7) * 4);
          __threadfence();
          atomicOr(&g_sync[F_CTX + (item & 7) * 2 + (rank ^ (it & 1))], 1u << (item >> 3));
          if (nxt >= K2_END) break;
        }
      } else if (warp_g == 11) {
        if (lane == 0) {
          prefetch_tmap(&p.tmQ); prefetch_tmap(&p.tmK); prefetch_tmap(&p.tmV);
          asm volatile("st.shared.u32 [%0], %1;" ::"r"(sGate + 64), "r"(__ldcg(&g_sync[F_EPOCH])) : "memory");
          wait_flag(&g_sync[F_GATE], GATE_TARGET);
          uint32_t tick;
          if (rank == 0) {
            mbar_wait(bLast, 0);
            mbar_wait(bAe + FIRST_DRAW * 8, aph);
            tick = atomicAdd(&g_sync[F_TICK], 1u);
            asm volatile("st.shared.u32 [%0], %1;" ::"r"(sTick + 8), "r"(tick) : "memory");
            asm volatile(
                "{\n.reg .b32 a, b;\nmapa.shared::cluster.u32 a, %0, 1;\nmapa.shared::cluster.u32 b, %1, 1;\n"
                "st.async.shared::cluster.mbarrier::complete_tx::bytes.u32 [a], %2, [b];\n}" ::"r"(sTick + 8), "r"(bT0), "r"(tick) : "memory");
          } else {
            mbar_expect(bT0, 4);
            mbar_wait(bT0, 0);
            tick = lds32(sTick + 8);
          }
          wait_flag(&g_sync[F_HP + (p.order[tick] >> 4)], RDY_TARGET);
          mbar_arrive(bR);
        }
        __syncwarp();
        bar_sync(4, 256 + 32);
        if (lane < 12) mbar_arrive_cluster(bE + (4 + lane % 3) * 8, (lane / 3) & 1);
      } else if (warp_g == 10 && lr0 < S_LEN) {
        if (elect_one()) {
          prefetch_tmap(&p.tmL[0]); prefetch_tmap(&p.tmL[1]);
          wait_flag(&g_sync[F_QKVA + (lr0 >> 7)], K1_FLAG_TARGET);
          wait_flag(&g_sync[F_QKVA + (max(lr0 - 14, 0) >> 7)], K1_FLAG_TARGET);
          asm volatile("fence.proxy.async.global;" ::: "memory");
          mbar_wait(bLast, 0);
#pragma unroll 1
          for (int kc = 0; kc < 6; kc++) {
            mbar_wait(bAe + kc * 8, aph);
            if (kc == 3) {
              mbar_expect(bL, 46 * 1152);
              tma3d(sL, &p.tmL[0], bL, 0, 9, lr0 - 14);
              tma3d(sL + 30 * 1152, &p.tmL[1], bL, 0, 0, lr0);
            }
          }
          mbar_expect(bL2, 30 * 1152);
          tma3d(sL + 46 * 1152, &p.tmL[0], bL2, 0, 18, lr0 - 14);
        }
        __syncwarp();
        bar_sync(5, 256 + 32);
        if (lane == 0) {
          __threadfence();
          atomicAdd(&g_sync[F_OA + (lr0 >> 7)], 1u);
        }
      }
    }
    __syncwarp();
    cluster_sync();
  } else {
    reg_alloc<232>();
    const int wg = warp_g >> 2, warp = warp_g & 3, q = lane & 3;
    const bool sig = (lane == 0) && (warp < 2);
    {
      K1State st{0, 0, 0, nullptr, 0, 0, 0};
      float acc[128];
      uint32_t pk[64];
      if (wg == 0) { TS(0, 0); TSC(0, 2); }
      uint32_t job = p.jobs[cl][0];
      k1_first(st, job, bAf, bBf);
#pragma unroll 1
      for (int ji = 0; job & 3; ji++) {
        const uint32_t njob = p.jobs[cl][ji + 1];
        k1_tile(acc, pk, st, job, njob, sA, sB, bAf, bAe, bBf, bBe, bS, wg, warp, lane, rank);
        job = njob;
      }
#pragma unroll
      for (int i = 0; i < 4; i++)
        mbar_arrive_cluster_if(bE + i * 8, warp & 1, sig);
#pragma unroll
      for (int G = 0; G < 8; G++)
        if (G < st.png) {
          st_v4a(st.pp + G * 32, pk[G * 8], pk[G * 8 + 1], pk[G * 8 + 2], pk[G * 8 + 3]);
          st_v4a(st.pp + G * 32 + st.pld8, pk[G * 8 + 4], pk[G * 8 + 5], pk[G * 8 + 6], pk[G * 8 + 7]);
        }
      k1_flag(st, lane, bS);
      if (wg == 0) { TS(0, 1); TSC(0, 3); }
      if (lr0 < S_LEN) {
        const int ri = (warp_g >> 1) * 4 + (warp_g & 1) + 2, row = lr0 + ri;
        if (wg == 0) TS(1, 5);
        bar_sync(3, 256 + 96);
        const float gate0 = __uint_as_float(lds32(sGate + ri * 4 - 8)), gate1 = __uint_as_float(lds32(sGate + ri * 4));
        mbar_wait(bL, 0);
        if (wg == 0) TS(1, 6);
        local_rows2(row, ri, sL, bL2, lane, gate0, gate1);
        bar_arrive(5, 256 + 32);
      } else {
        bar_arrive(4, 256 + 32);
      }
    }
    __syncwarp();
    uint32_t item, rot;
    {
      const int mybar = 1 + wg, otherbar = 2 - wg;
      const uint32_t never = blockIdx.y;
      const float cl2 = 0.08838834764831845f * 1.4426950408889634f;
      float S[64], O[64];
      uint32_t P[32], Q[32];
      float m0 = 0.f, m1 = 0.f, l0 = 0.f, l1 = 0.f;
      int prev_row = 0, prev_h = 0, prev_single = 0;
      Cursor c{0, 0};
      if (wg == 1) bar_arrive(1, 256);
      if (wg == 0) { TS(1, 0); TSC(1, 2); }
#pragma unroll 1
      for (int it = 0;; it++) {
        mbar_wait(bF + c.s * 8, c.ph);
        item = lds32(sItem + (it & 7) * 4);
        if (it > 0) BSEG(7);
        const bool last = item >= K2_END;
        const int h = item >> 3, j = item & 7;
        const int hi = (int)(rank ^ (it & 1));
        const int nblk = 2 * j + 1 + hi;
        {
          float gf0, gf1;
          asm volatile("ld.global.f32 %0, [%1];" : "=f"(gf0) : "l"(g_gate + prev_row));
          asm volatile("ld.global.f32 %0, [%1];" : "=f"(gf1) : "l"(g_gate + prev_row + 8));
          Cursor cq = c, ck = c, cs0 = c, cs1 = c, cv = c;
          rot = k3_rot(c.s);
          if (!last) {
            const int r = wg * 64 + warp * 16 + (lane & 7) + ((lane >> 3) & 1) * 8;
            const uint32_t qa = sbase + cq.s * 32768 + r * 128;
#pragma unroll
            for (int t = 0; t < 8; t++)
              ldsm_x4(Q[4 * t], Q[4 * t + 1], Q[4 * t + 2], Q[4 * t + 3], qa + (t >> 2) * 16384 + ((((t & 3) * 2 + (lane >> 4)) ^ (lane & 7)) << 4));
            c.next();
            ck = c; c.next();
            cs0 = ck; cv = c;
            mbar_wait(bF + ck.s * 8, ck.ph);
            if (it > 0) BSEG(8);
            if (it > 0) { mbar_wait(bF + cv.s * 8, cv.ph); c.next(); }
            if (it > 0) BSEG(9);
            if (!hi) {
              ck = c; c.next();
              cs1 = c; c.next();
              mbar_wait(bF + ck.s * 8, ck.ph);
              mbar_wait(bF + cs1.s * 8, cs1.ph);
            }
          }
          if (it == 0) BSEG(4); else BSEG(0);
          TURN_SYNC();
          if (it > 0 && !last) BSEG(10);
          if (it > 0) {
            wg_fence();
            ISSUE_PV(cv, prev_single);
            wg_commit();
          } else {
            wg_fence();
            wg_commit();
          }
          wg_fence();
          ISSUE_QK(ck);
          wg_commit();
          if (!(last && wg == 1)) TURN_ARRIVE();
          RELEASE_IF(cq, !last);
          RELEASE_IF(cs0, !last && !hi);
          RELEASE_IF(cs1, !last && !hi);
          wg_wait<1>();
          fence_regs(O);
          fence_regs(P);
          if (it > 0) {
            RELEASE_IF(cv, !last);
            mbar_arrive_cluster_if(bH, warp & 1, sig && last);
            EPILOGUE();
            __syncwarp();
            mbar_arrive_if(bS2, lane == 0);
          }
          wg_wait<0>();
          fence_regs(S);
          if (last) break;
          if (it > 0) BSEG(11);
          RELEASE(ck);
          float s0 = 0.f, s1 = 0.f;
          const int r0 = wg * 64 + warp * 16 + (lane >> 2);
#pragma unroll
          for (int jj = 0; jj < 16; jj++) {
            const int cc = jj * 8 + 2 * q;
            if (cc > r0) S[jj * 4 + 0] = -INFINITY;
            if (cc + 1 > r0) S[jj * 4 + 1] = -INFINITY;
            if (cc > r0 + 8) S[jj * 4 + 2] = -INFINITY;
            if (cc + 1 > r0 + 8) S[jj * 4 + 3] = -INFINITY;
          }
          float mx0 = fmaxf(S[0], S[1]), mx1 = fmaxf(S[2], S[3]);
#pragma unroll
          for (int jj = 1; jj < 16; jj++) {
            mx0 = fmaxf(mx0, fmaxf(S[jj * 4 + 0], S[jj * 4 + 1]));
            mx1 = fmaxf(mx1, fmaxf(S[jj * 4 + 2], S[jj * 4 + 3]));
          }
          mx0 = fmaxf(mx0, __shfl_xor_sync(0xffffffffu, mx0, 1));
          mx1 = fmaxf(mx1, __shfl_xor_sync(0xffffffffu, mx1, 1));
          mx0 = fmaxf(mx0, __shfl_xor_sync(0xffffffffu, mx0, 2));
          mx1 = fmaxf(mx1, __shfl_xor_sync(0xffffffffu, mx1, 2));
          m0 = mx0; m1 = mx1;
          const float mc0 = m0 * cl2, mc1 = m1 * cl2;
          m0 = mc0; m1 = mc1;
#pragma unroll
          for (int jj = 0; jj < 16; jj++) {
            S[jj * 4 + 0] = ex2(fmaf(S[jj * 4 + 0], cl2, -mc0));
            S[jj * 4 + 1] = ex2(fmaf(S[jj * 4 + 1], cl2, -mc0));
            S[jj * 4 + 2] = ex2(fmaf(S[jj * 4 + 2], cl2, -mc1));
            S[jj * 4 + 3] = ex2(fmaf(S[jj * 4 + 3], cl2, -mc1));
            s0 += S[jj * 4 + 0] + S[jj * 4 + 1];
            s1 += S[jj * 4 + 2] + S[jj * 4 + 3];
          }
          l0 = s0; l1 = s1;
#pragma unroll
          for (int jj = 0; jj < 16; jj++) {
            P[jj * 2 + 0] = pack_bf16(S[jj * 4 + 0], S[jj * 4 + 1]);
            P[jj * 2 + 1] = pack_bf16(S[jj * 4 + 2], S[jj * 4 + 3]);
          }
        }
        if (it == 0) BSEG(5); else BSEG(1);
#pragma unroll 1
        for (int n = 1; n < nblk; n++) {
          Cursor ck = c; c.next();
          Cursor cv = c; c.next();
          mbar_wait(bF + ck.s * 8, ck.ph);
          mbar_wait(bF + cv.s * 8, cv.ph);
          TURN_SYNC();
          wg_fence();
          ISSUE_QK(ck);
          wg_commit();
          {
            const uint64_t dv = make_desc(sbase + cv.s * 32768, 16384, 1024, 1);
#pragma unroll
            for (int t = 0; t < 8; t++) {
              wgmma_rs_n128<1, 0>(O, P[4 * t], P[4 * t + 1], P[4 * t + 2], P[4 * t + 3], dv + (uint64_t)(t * 128), (t > 0) ? 1 : (n != 1));
              if ((PVM >> t) & 1) wg_commit();
            }
          }
          TURN_ARRIVE();
          float s0 = 0.f, s1 = 0.f;
          wg_wait<__builtin_popcount(PVM)>();
          fence_regs(S);
          RELEASE(ck);
#pragma unroll
          for (int jj = 0; jj < 16; jj++) {
            S[jj * 4 + 0] = fmaf(S[jj * 4 + 0], cl2, -m0);
            S[jj * 4 + 1] = fmaf(S[jj * 4 + 1], cl2, -m0);
            S[jj * 4 + 2] = fmaf(S[jj * 4 + 2], cl2, -m1);
            S[jj * 4 + 3] = fmaf(S[jj * 4 + 3], cl2, -m1);
          }
          anchor(S[W0], never);
          wg_wait<__builtin_popcount(PVM) - 1>();
          EXPC(0); EXPC(1); EXPC(2); EXPC(3); EXPC(4); EXPC(5); EXPC(6); EXPC(7);
          if (__any_sync(0xffffffffu, !(s0 + s1 <= (float)(1ull << SPEC)))) {
            float mx0 = fmaxf(S[0], S[1]), mx1 = fmaxf(S[2], S[3]);
#pragma unroll
            for (int jj = 1; jj < 16; jj++) {
              mx0 = fmaxf(mx0, fmaxf(S[jj * 4 + 0], S[jj * 4 + 1]));
              mx1 = fmaxf(mx1, fmaxf(S[jj * 4 + 2], S[jj * 4 + 3]));
            }
            mx0 = fmaxf(mx0, __shfl_xor_sync(0xffffffffu, mx0, 1));
            mx1 = fmaxf(mx1, __shfl_xor_sync(0xffffffffu, mx1, 1));
            mx0 = fmaxf(mx0, __shfl_xor_sync(0xffffffffu, mx0, 2));
            mx1 = fmaxf(mx1, __shfl_xor_sync(0xffffffffu, mx1, 2));
            mx0 = fmaxf(mx0, 0.f);
            mx1 = fmaxf(mx1, 0.f);
            m0 += mx0; m1 += mx1;
            const float sc0 = ex2(-mx0), sc1 = ex2(-mx1);
            l0 *= sc0; l1 *= sc1;
            s0 = 0.f; s1 = 0.f;
#pragma unroll
            for (int jj = 0; jj < 16; jj++) {
              const float e0 = ex2(S[jj * 4 + 0] - mx0), e1 = ex2(S[jj * 4 + 1] - mx0), e2 = ex2(S[jj * 4 + 2] - mx1), e3 = ex2(S[jj * 4 + 3] - mx1);
              s0 += e0 + e1;
              s1 += e2 + e3;
              P[jj * 2 + 0] = pack_bf16(e0, e1);
              P[jj * 2 + 1] = pack_bf16(e2, e3);
              O[jj * 4 + 0] *= sc0;
              O[jj * 4 + 1] *= sc0;
              O[jj * 4 + 2] *= sc1;
              O[jj * 4 + 3] *= sc1;
            }
          }
          l0 += s0;
          l1 += s1;
        }
        BSEG(2);
        prev_row = (2 * j + hi) * 128 + wg * 64 + warp * 16 + (lane >> 2);
        prev_h = h;
        prev_single = (nblk == 1);
      }
      if (wg == 1) { TS(1, 1); TSC(1, 3); }
    }
    __syncwarp();
    const uint32_t unit = item & 255;
    if (unit < 64) {
      const int mblk = (7 - (p.unit[unit][0] >> 1)) * 2 + rank, nhalf = p.unit[unit][0] & 1, ks = p.unit[unit][1];
      const int k0 = p.unit[unit][2], k1 = p.unit[unit][3];
      float acc[144];
      uint32_t s = rot, ph = 0, prev = 0;
      if (wg == 0) { TS(2, 0); TSC(2, 2); }
#pragma unroll 1
      for (int k = k0; k < k1; k++) {
        mbar_wait(b3F + s * 8, ph);
        const uint32_t st = sbase + s * K3_STAGE;
        const uint64_t da = make_desc(st + wg * 8192, 16, 1024, 1);
        const uint64_t db = make_desc(st + 16384, 4096, 1024, 1);
        const uint64_t dt = make_desc(st + 49152, 16, 512, 2);
        wg_fence();
#pragma unroll
        for (int t = 0; t < 4; t++) {
          const int sd = (t > 0) || (k > k0);
          wgmma_ss_n256<1, 0>(acc, da + (uint64_t)(t * 2), db + (uint64_t)((t >> 1) * 1024 + (t & 1) * 128), sd);
          wgmma_ss_n32<1, 128>(acc, da + (uint64_t)(t * 2), dt + (uint64_t)(t * 64), sd);
        }
        wg_commit();
        if (k > k0) {
          wg_wait<1>();
          if (sig) mbar_arrive_cluster(b3E + prev * 8, warp);
        }
        prev = s;
        s = (s + 1) & 3;
        if (s == rot) ph ^= 1;
      }
      wg_wait<0>();
      fence_regs(acc);
      cluster_arrive();
      if (wg == 0) TS(2, 4);
      const int tile = mblk * 2 + nhalf;
      uint4* wp = g_part + (size_t)((tile * 4 + ks) * 4) * 5 * 256 + tid;
      const uint32_t sown = sbase + wg * 8192 + (tid & 127) * 16;
#pragma unroll
      for (int d = 0; d < 4; d++) {
        if (d != ks) {
#pragma unroll
          for (int i = 0; i < 4; i++)
            __stcg(wp + (d * 5 + i) * 256,
                   make_uint4(pack_bf16(acc[d * 32 + i * 8], acc[d * 32 + i * 8 + 1]), pack_bf16(acc[d * 32 + i * 8 + 2], acc[d * 32 + i * 8 + 3]),
                              pack_bf16(acc[d * 32 + i * 8 + 4], acc[d * 32 + i * 8 + 5]), pack_bf16(acc[d * 32 + i * 8 + 6], acc[d * 32 + i * 8 + 7])));
          __stcg(reinterpret_cast<uint2*>(wp - tid + (d * 5 + 4) * 256) + tid,
                 make_uint2(pack_bf16(acc[128 + d * 4], acc[128 + d * 4 + 1]), pack_bf16(acc[128 + d * 4 + 2], acc[128 + d * 4 + 3])));
        } else {
#pragma unroll
          for (int i = 0; i < 9; i++) {
            const int o = (i < 8) ? d * 32 + i * 4 : 128 + d * 4;
            asm volatile("st.shared.v4.f32 [%0], {%1, %2, %3, %4};" ::"r"(sown + (i >> 2) * K3_STAGE + (i & 3) * 2048), "f"(acc[o]), "f"(acc[o + 1]), "f"(acc[o + 2]), "f"(acc[o + 3]) : "memory");
          }
        }
      }
      __threadfence();
      __syncwarp();
      if (wg == 0) TS(2, 5);
      if (lane == 0) {
        unsigned int* cnt = &g_sync[F_XCH + tile * 8 + warp_g];
        const uint32_t xtarget = lds32(sGate + 64) * 4 + 4;
        atomicAdd(cnt, 1u);
        uint32_t v, spins = 0;
        do {
          asm volatile("ld.acquire.gpu.global.u32 %0, [%1];" : "=r"(v) : "l"(cnt) : "memory");
        } while ((int)(v - xtarget) < 0 && ++spins < (1u << 24));
      }
      __syncwarp();
      if (wg == 0) TS(2, 6);
      float r[36];
#pragma unroll
      for (int i = 0; i < 9; i++)
        asm volatile("ld.shared.v4.f32 {%0, %1, %2, %3}, [%4];" : "=f"(r[i * 4]), "=f"(r[i * 4 + 1]), "=f"(r[i * 4 + 2]), "=f"(r[i * 4 + 3])
                     : "r"(sown + (i >> 2) * K3_STAGE + (i & 3) * 2048) : "memory");
#pragma unroll
      for (int sI = 1; sI < 4; sI++) {
        const int src = (ks + sI) & 3;
        const uint4* rp = g_part + (size_t)(((tile * 4 + src) * 4) + ks) * 5 * 256;
#pragma unroll
        for (int i = 0; i < 4; i++) {
          const uint4 v = __ldcg(rp + i * 256 + tid);
          r[i * 8] += bf_lo(v.x); r[i * 8 + 1] += bf_hi(v.x); r[i * 8 + 2] += bf_lo(v.y); r[i * 8 + 3] += bf_hi(v.y);
          r[i * 8 + 4] += bf_lo(v.z); r[i * 8 + 5] += bf_hi(v.z); r[i * 8 + 6] += bf_lo(v.w); r[i * 8 + 7] += bf_hi(v.w);
        }
        const uint2 v = __ldcg(reinterpret_cast<const uint2*>(rp + 4 * 256) + tid);
        r[32] += bf_lo(v.x); r[33] += bf_hi(v.x); r[34] += bf_lo(v.y); r[35] += bf_hi(v.y);
      }
      const int row = mblk * 128 + wg * 64 + warp * 16 + (lane >> 2);
      bf16* o0 = out + (size_t)row * DM + nhalf * 256 + ks * 64 + 8 * q;
#pragma unroll
      for (int G = 0; G < 2; G++) {
        uint32_t a0 = pack_bf16(r[G * 16], r[G * 16 + 1]), a1 = pack_bf16(r[G * 16 + 4], r[G * 16 + 5]);
        uint32_t a2 = pack_bf16(r[G * 16 + 8], r[G * 16 + 9]), a3 = pack_bf16(r[G * 16 + 12], r[G * 16 + 13]);
        uint32_t b0 = pack_bf16(r[G * 16 + 2], r[G * 16 + 3]), b1 = pack_bf16(r[G * 16 + 6], r[G * 16 + 7]);
        uint32_t b2 = pack_bf16(r[G * 16 + 10], r[G * 16 + 11]), b3 = pack_bf16(r[G * 16 + 14], r[G * 16 + 15]);
        quad_transpose(a0, a1, a2, a3, q);
        quad_transpose(b0, b1, b2, b3, q);
        st_v4(o0 + G * 32, a0, a1, a2, a3);
        st_v4(o0 + 8 * DM + G * 32, b0, b1, b2, b3);
      }
      {
        uint32_t t0 = pack_bf16(r[32], r[33]), t1 = pack_bf16(r[34], r[35]), t2 = 0, t3 = 0;
        quad_transpose(t0, t1, t2, t3, q);
        if (q < 2) st_v4(out + (size_t)(row + q * 8) * DM + 512 + nhalf * 32 + ks * 8, t0, t1, t2, t3);
      }
    } else {
      cluster_arrive();
    }
    if (wg == 0) { TS(2, 1); TSC(2, 3); }
    cluster_wait();
  }
}

typedef CUresult (*EncFn)(CUtensorMap*, CUtensorMapDataType, cuuint32_t, void*, const cuuint64_t*, const cuuint64_t*, const cuuint32_t*,
                          const cuuint32_t*, CUtensorMapInterleave, CUtensorMapSwizzle, CUtensorMapL2promotion, CUtensorMapFloatOOBfill);

static void enc2d(EncFn enc, CUtensorMap* m, const void* ptr, uint64_t cols, uint64_t rows, uint32_t bc, uint32_t br,
                  CUtensorMapSwizzle sw = CU_TENSOR_MAP_SWIZZLE_128B) {
  cuuint64_t gd[2] = {cols, rows}, gs[1] = {cols * 2};
  cuuint32_t bx[2] = {bc, br}, es[2] = {1, 1};
  enc(m, CU_TENSOR_MAP_DATA_TYPE_BFLOAT16, 2, const_cast<void*>(ptr), gd, gs, bx, es, CU_TENSOR_MAP_INTERLEAVE_NONE, sw,
      CU_TENSOR_MAP_L2_PROMOTION_L2_256B, CU_TENSOR_MAP_FLOAT_OOB_FILL_NONE);
}
static void enc3d(EncFn enc, CUtensorMap* m, const void* ptr, uint64_t cols, uint64_t rows, uint32_t br, uint32_t bch) {
  cuuint64_t gd[3] = {64, rows, cols / 64}, gs[2] = {cols * 2, 128};
  cuuint32_t bx[3] = {64, br, bch}, es[3] = {1, 1, 1};
  enc(m, CU_TENSOR_MAP_DATA_TYPE_BFLOAT16, 3, const_cast<void*>(ptr), gd, gs, bx, es, CU_TENSOR_MAP_INTERLEAVE_NONE,
      CU_TENSOR_MAP_SWIZZLE_128B, CU_TENSOR_MAP_L2_PROMOTION_L2_256B, CU_TENSOR_MAP_FLOAT_OOB_FILL_NONE);
}

static int g_sched[10] = {11, 10, 7, 4, 4, 5, 6, 6, 8, 20};
static void build_k1_jobs(Params& p) {
  int cnt[NCLUSTER];
  for (int c = 0; c < NCLUSTER; c++) {
    cnt[c] = 0;
    for (int i = 0; i <= K1_MAXJOBS; i++) p.jobs[c][i] = 0;
  }
  auto add = [&](int c, int nch, int a_sel, int mp, int w_sel, int chunk0) {
    p.jobs[c][cnt[c]++] = (uint16_t)((nch - 1) | (a_sel << 2) | (mp << 3) | (w_sel << 6) | (chunk0 << 8));
  };
  const int *cg = g_sched, *xg = g_sched + 4;
  for (int mp = 0; mp < 8; mp++) {
    int k = 0;
    for (int i = 0; i < K1_MAXJOBS; i++)
      for (int g = 0; g < 4; g++)
        if (i < cg[g]) { add(g * 8 + mp, 4, 0, mp, k & 1, (k >> 1) * 4); k++; }
    k = 0;
    for (int i = 0; i < K1_MAXJOBS; i++)
      for (int g = 0; g < 4; g++)
        if (i < xg[g]) {
          if (k < 7) add((4 + g) * 8 + mp, k == 0 ? 3 : 4, 1, mp, 2, k == 0 ? 24 : (k - 1) * 4);
          else add((4 + g) * 8 + mp, 4, 1, mp, 3, (k - 7) * 4);
          k++;
        }
    add(64 + mp / 4, 4, 1, mp, 3, 14 * 4);
    add(64 + mp / 4, 4, 1, mp, 3, 15 * 4);
  }
  for (int cc = 0; cc < NCLUSTER; cc++)
    for (int i = 0; i < cnt[cc]; i++) {
      const int key = p.jobs[cc][i] & 0x3C;
      if (i == 0 || (p.jobs[cc][i - 1] & 0x3C) != key) p.jobs[cc][i] |= (1 << 14);
      if (i == cnt[cc] - 1 || (p.jobs[cc][i + 1] & 0x3C) != key) p.jobs[cc][i] |= (1 << 15);
    }
}

static void build_k2_items(Params& p) {
  int n = 0;
  const int SCHED_N1 = g_sched[8], SCHED_N2 = g_sched[9];
  for (int j = 7; j >= 0; j--)
    for (int h = 0; h < SCHED_N1; h++) p.order[n++] = (uint8_t)(h * 8 + j);
  for (int j = 7; j >= 4; j--)
    for (int h = SCHED_N1; h < SCHED_N2; h++) p.order[n++] = (uint8_t)(h * 8 + j);
  for (int j = 7; j >= 0; j--)
    for (int h = SCHED_N1; h < 32; h++)
      if (!(h < SCHED_N2 && j >= 4)) p.order[n++] = (uint8_t)(h * 8 + j);
}

static void build_k3_units(Params& p) {
  float slope = 0.09f;
  for (int t = 0; t < 16; t++) {
    const int u[4] = {t, 31 - t, 32 + t, 63 - t};
    float acc = 0.f;
    int k0 = 0;
    for (int i = 0; i < 4; i++) {
      acc += 18.25f + slope * (31.5f - u[i]);
      const int k1 = (i == 3) ? 73 : (int)(acc + 0.5f);
      p.unit[u[i]][0] = (uint8_t)t; p.unit[u[i]][1] = (uint8_t)i; p.unit[u[i]][2] = (uint8_t)k0; p.unit[u[i]][3] = (uint8_t)k1;
      k0 = k1;
    }
  }
}

extern "C" void kernel_launch(void* const* d_in, const int* in_sizes, int n_in, void* d_out, int out_size) {
  const bf16* x = (const bf16*)d_in[0];
  const bf16* wqkv = (const bf16*)d_in[1];
  const bf16* wo = (const bf16*)d_in[2];
  const bf16* ckv = (const bf16*)d_in[4];
  const bf16* w_q = (const bf16*)d_in[5];
  const bf16* w_uk = (const bf16*)d_in[6];
  const bf16* w_uv = (const bf16*)d_in[7];
  const bf16* w_o = (const bf16*)d_in[8];
  const bf16* gate_w = (const bf16*)d_in[9];

  EncFn enc = nullptr;
  cudaDriverEntryPointQueryResult qr;
  cudaGetDriverEntryPoint("cuTensorMapEncodeTiled", (void**)&enc, cudaEnableDefault, &qr);
  void *pQ, *pK, *pV, *pCtx, *pQA;
  cudaGetSymbolAddress(&pQ, g_Q);
  cudaGetSymbolAddress(&pQA, g_QKVA);
  cudaGetSymbolAddress(&pK, g_K);
  cudaGetSymbolAddress(&pV, g_V);
  cudaGetSymbolAddress(&pCtx, g_ctx);

  static Params p;
  enc2d(enc, &p.tmA[0], ckv, DC, S_LEN, 64, 128);
  enc2d(enc, &p.tmA[1], x, DM, S_LEN, 64, 128);
  enc3d(enc, &p.tmW[0], w_uk, HDIM, DC, 16, 4);
  enc3d(enc, &p.tmW[1], w_uv, HDIM, DC, 16, 4);
  enc3d(enc, &p.tmW[2], wqkv, NQKVA, DM, 16, 4);
  enc3d(enc, &p.tmW[3], w_q, HDIM, DM, 16, 4);
  build_k1_jobs(p);
  enc2d(enc, &p.tmQ, pQ, HDIM, S_LEN, 64, 128);
  enc2d(enc, &p.tmK, pK, HDIM, S_LEN, 64, 128);
  enc2d(enc, &p.tmV, pV, HDIM, S_LEN, 64, 128);
  build_k2_items(p);
  build_k3_units(p);
  for (int i = 0; i < 2; i++) {
    cuuint64_t gd[3] = {64, 27, S_LEN}, gs[2] = {128, NQKVA * 2};
    cuuint32_t bx[3] = {64, 9, i ? 16u : 30u}, es[3] = {1, 1, 1};
    enc(&p.tmL[i], CU_TENSOR_MAP_DATA_TYPE_BFLOAT16, 3, pQA, gd, gs, bx, es, CU_TENSOR_MAP_INTERLEAVE_NONE, CU_TENSOR_MAP_SWIZZLE_NONE,
        CU_TENSOR_MAP_L2_PROMOTION_L2_256B, CU_TENSOR_MAP_FLOAT_OOB_FILL_NONE);
  }
  enc2d(enc, &p.tmC, pCtx, KCAT, S_LEN, 64, 128);
  enc3d(enc, &p.tmO[0], w_o, DM, HDIM, 32, 4);
  enc3d(enc, &p.tmO[1], wo, DM, DM, 32, 4);
  enc2d(enc, &p.tmOt[0], w_o, DM, HDIM, 32, 32, CU_TENSOR_MAP_SWIZZLE_64B);
  enc2d(enc, &p.tmOt[1], wo, DM, DM, 32, 32, CU_TENSOR_MAP_SWIZZLE_64B);

  cudaFuncSetAttribute(fused_kernel, cudaFuncAttributeMaxDynamicSharedMemorySize, SMEM_BYTES);
  fused_kernel<<<NCLUSTER * 2, 384, SMEM_BYTES>>>(p, x, gate_w, (bf16*)d_out);
}
```

```cpp
#include <cuda_runtime.h>
#include <cuda_bf16.h>
#include <cuda.h>
#include <stdint.h>

typedef __nv_bfloat16 bf16;

constexpr int S_LEN = 2048, DM = 576, DC = 512, HDIM = 4096, NQKVA = 1728, KCAT = 4672;
constexpr int NCLUSTER = 66;

__device__ __align__(1024) bf16 g_Q[S_LEN * HDIM];
__device__ __align__(1024) bf16 g_K[S_LEN * HDIM];
__device__ __align__(1024) bf16 g_V[S_LEN * HDIM];
__device__ __align__(1024) bf16 g_QKVA[S_LEN * NQKVA + 64];
__device__ __align__(1024) bf16 g_ctx[S_LEN * KCAT];
__device__ float g_gate[S_LEN];
__device__ __align__(1024) uint4 g_part[32 * 4 * 4 * 5 * 256];
__device__ __align__(16) unsigned int g_sync[400];
constexpr int F_QKVA = 0, F_HP = 16, F_CTX = 32, F_OA = 48, F_GATE = 96, F_TICK = 97, F_DONE = 98, F_XCH = 128, F_EPOCH = 384;

__device__ __forceinline__ uint32_t smem_u32(const void* p) { return (uint32_t)__cvta_generic_to_shared(p); }
__device__ __forceinline__ void mbar_init(uint32_t a, uint32_t c) {
  asm volatile("mbarrier.init.shared::cta.b64 [%0], %1;" ::"r"(a), "r"(c));
}
__device__ __forceinline__ void mbar_expect(uint32_t a, uint32_t b) {
  asm volatile("mbarrier.arrive.expect_tx.shared::cta.b64 _, [%0], %1;" ::"r"(a), "r"(b) : "memory");
}
#define TS(k, i)
#define TSC(k, i)
#define TSM(k)
#define BSEG(i)
#define TB(k)
#define TRC(fl)
#define SPIN_LIMIT "4194304"
__device__ __forceinline__ void mbar_wait(uint32_t a, uint32_t parity) {
  asm volatile(
      "{\n.reg .pred p;\n.reg .u32 n;\n"
      "mbarrier.try_wait.parity.shared::cta.b64 p, [%0], %1;\n"
      "@p bra DONE;\n"
      "mov.u32 n, 0;\n"
      "LOOP:\n"
      "mbarrier.try_wait.parity.shared::cta.b64 p, [%0], %1;\n"
      "@p bra DONE;\n"
      "add.u32 n, n, 1;\n"
      "setp.lt.u32 p, n, " SPIN_LIMIT ";\n"
      "@p bra LOOP;\n"
      "DONE:\n}" ::"r"(a), "r"(parity) : "memory");
}
#define HINT 1
template <int NS>
__device__ __forceinline__ void mbar_wait_ns(uint32_t a, uint32_t parity) {
  asm volatile(
      "{\n.reg .pred p;\n.reg .u32 n;\n"
      "mov.u32 n, 0;\n"
      "LOOP:\n"
      "mbarrier.try_wait.parity.shared::cta.b64 p, [%0], %1, %2;\n"
      "@p bra DONE;\n"
      "add.u32 n, n, 1;\n"
      "setp.lt.u32 p, n, " SPIN_LIMIT ";\n"
      "@p bra LOOP;\n"
      "DONE:\n}" ::"r"(a), "r"(parity), "n"(NS) : "memory");
}
__device__ __forceinline__ void mbar_wait2(uint32_t a, uint32_t pa, uint32_t b, uint32_t pb) {
  asm volatile(
      "{\n.reg .pred p, q;\n.reg .u32 n;\n"
      "mov.u32 n, 0;\n"
      "LOOP:\n"
      "mbarrier.try_wait.parity.shared::cta.b64 p, [%0], %1;\n"
      "mbarrier.try_wait.parity.shared::cta.b64 q, [%2], %3;\n"
      "add.u32 n, n, 1;\n"
      "and.pred p, p, q;\n"
      "setp.lt.and.u32 p, n, " SPIN_LIMIT ", !p;\n"
      "@p bra LOOP;\n"
      "}" ::"r"(a), "r"(pa), "r"(b), "r"(pb) : "memory");
}
__device__ __forceinline__ uint32_t mbar_test(uint32_t a, uint32_t parity) {
  uint32_t r;
  asm volatile("{\n.reg .pred p;\nmbarrier.test_wait.parity.shared::cta.b64 p, [%1], %2;\nselp.u32 %0, 1, 0, p;\n}" : "=r"(r) : "r"(a), "r"(parity) : "memory");
  return r;
}
__device__ __forceinline__ void mbar_arrive(uint32_t a) {
  asm volatile("mbarrier.arrive.shared::cta.b64 _, [%0];" ::"r"(a) : "memory");
}
__device__ __forceinline__ void mbar_arrive_cluster(uint32_t a, uint32_t cta) {
  asm volatile("{\n.reg .b32 r;\nmapa.shared::cluster.u32 r, %0, %1;\nmbarrier.arrive.shared::cluster.b64 _, [r];\n}" ::"r"(a),
               "r"(cta) : "memory");
}
__device__ __forceinline__ void mbar_arrive_cluster_if(uint32_t a, uint32_t cta, bool pred) {
  asm volatile("{\n.reg .b32 r;\n.reg .pred p;\nsetp.ne.u32 p, %2, 0;\nmapa.shared::cluster.u32 r, %0, %1;\n@p mbarrier.arrive.shared::cluster.b64 _, [r];\n}" ::"r"(a),
               "r"(cta), "r"((uint32_t)pred) : "memory");
}
__device__ __forceinline__ void mbar_arrive_cluster_after(uint32_t a, uint32_t cta, bool pred, float anchor) {
  asm volatile("{\n.reg .b32 r;\n.reg .pred p;\nsetp.ne.u32 p, %2, 0;\nsetp.leu.and.f32 p, %3, 0f7F800000, p;\n"
               "mapa.shared::cluster.u32 r, %0, %1;\n@p mbarrier.arrive.shared::cluster.b64 _, [r];\n}" ::"r"(a),
               "r"(cta), "r"((uint32_t)pred), "f"(anchor) : "memory");
}
__device__ __forceinline__ void anchor(float v, uint32_t pred) {
  asm volatile("{\n.reg .pred p;\nsetp.ne.u32 p, %1, 0;\n@p st.shared.f32 [%1], %0;\n}" ::"f"(v), "r"(pred) : "memory");
}
__device__ __forceinline__ void mbar_arrive_if(uint32_t a, bool pred) {
  asm volatile("{\n.reg .pred p;\nsetp.ne.u32 p, %1, 0;\n@p mbarrier.arrive.shared::cta.b64 _, [%0];\n}" ::"r"(a), "r"((uint32_t)pred) : "memory");
}
__device__ __forceinline__ void tma2d(uint32_t dst, const CUtensorMap* m, uint32_t bar, int c0, int c1) {
  asm volatile("cp.async.bulk.tensor.2d.shared::cluster.global.mbarrier::complete_tx::bytes [%0], [%1, {%3, %4}], [%2];" ::"r"(dst),
               "l"(m), "r"(bar), "r"(c0), "r"(c1) : "memory");
}
__device__ __forceinline__ void tma2d_mc(uint32_t dst, const CUtensorMap* m, uint32_t bar, int c0, int c1, uint16_t mask) {
  asm volatile(
      "cp.async.bulk.tensor.2d.shared::cluster.global.mbarrier::complete_tx::bytes.multicast::cluster [%0], [%1, {%3, %4}], [%2], %5;" ::"r"(dst),
      "l"(m), "r"(bar), "r"(c0), "r"(c1), "h"(mask) : "memory");
}
__device__ __forceinline__ void tma3d_mc(uint32_t dst, const CUtensorMap* m, uint32_t bar, int c0, int c1, int c2, uint16_t mask) {
  asm volatile(
      "cp.async.bulk.tensor.3d.shared::cluster.global.mbarrier::complete_tx::bytes.multicast::cluster [%0], [%1, {%3, %4, %5}], [%2], %6;" ::"r"(dst),
      "l"(m), "r"(bar), "r"(c0), "r"(c1), "r"(c2), "h"(mask) : "memory");
}
__device__ __forceinline__ uint64_t policy_evict_first() {
  uint64_t p;
  asm volatile("createpolicy.fractional.L2::evict_first.b64 %0, 1.0;" : "=l"(p));
  return p;
}
__device__ __forceinline__ void tma3d_mc_h(uint32_t dst, const CUtensorMap* m, uint32_t bar, int c0, int c1, int c2, uint16_t mask, uint64_t pol) {
  asm volatile(
      "cp.async.bulk.tensor.3d.shared::cluster.global.mbarrier::complete_tx::bytes.multicast::cluster.L2::cache_hint [%0], [%1, {%3, %4, %5}], [%2], %6, %7;" ::"r"(dst),
      "l"(m), "r"(bar), "r"(c0), "r"(c1), "r"(c2), "h"(mask), "l"(pol) : "memory");
}
__device__ __forceinline__ void tma2d_h(uint32_t dst, const CUtensorMap* m, uint32_t bar, int c0, int c1, uint64_t pol) {
  asm volatile("cp.async.bulk.tensor.2d.shared::cluster.global.mbarrier::complete_tx::bytes.L2::cache_hint [%0], [%1, {%3, %4}], [%2], %5;" ::"r"(dst),
               "l"(m), "r"(bar), "r"(c0), "r"(c1), "l"(pol) : "memory");
}
__device__ __forceinline__ void tma3d(uint32_t dst, const CUtensorMap* m, uint32_t bar, int c0, int c1, int c2) {
  asm volatile(
      "cp.async.bulk.tensor.3d.shared::cluster.global.mbarrier::complete_tx::bytes [%0], [%1, {%3, %4, %5}], [%2];" ::"r"(dst),
      "l"(m), "r"(bar), "r"(c0), "r"(c1), "r"(c2) : "memory");
}
__device__ __forceinline__ void tma_pf2d(const CUtensorMap* m, int c0, int c1) {
  asm volatile("cp.async.bulk.prefetch.tensor.2d.L2.global [%0, {%1, %2}];" ::"l"(m), "r"(c0), "r"(c1) : "memory");
}
__device__ __forceinline__ void tma_pf3d(const CUtensorMap* m, int c0, int c1, int c2) {
  asm volatile("cp.async.bulk.prefetch.tensor.3d.L2.global [%0, {%1, %2, %3}];" ::"l"(m), "r"(c0), "r"(c1), "r"(c2) : "memory");
}
__device__ __forceinline__ void prefetch_tmap(const CUtensorMap* m) {
  asm volatile("prefetch.tensormap [%0];" ::"l"(m) : "memory");
}
__device__ __forceinline__ void cluster_arrive() { asm volatile("barrier.cluster.arrive.relaxed.aligned;" ::: "memory"); }
__device__ __forceinline__ void cluster_wait() { asm volatile("barrier.cluster.wait.aligned;" ::: "memory"); }
__device__ __forceinline__ void cluster_sync() {
  cluster_arrive();
  cluster_wait();
}
__device__ __forceinline__ uint32_t cluster_rank() {
  uint32_t r;
  asm volatile("mov.u32 %0, %%cluster_ctarank;" : "=r"(r));
  return r;
}
__device__ __forceinline__ bool elect_one() {
  uint32_t p;
  asm volatile("{\n.reg .pred q;\nelect.sync _|q, 0xffffffff;\nselp.u32 %0, 1, 0, q;\n}" : "=r"(p));
  return p;
}
__device__ __forceinline__ void pdl_wait() { asm volatile("griddepcontrol.wait;" ::: "memory"); }
__device__ __forceinline__ void pdl_launch() { asm volatile("griddepcontrol.launch_dependents;" ::: "memory"); }
__device__ __forceinline__ void ldsm_x4(uint32_t& r0, uint32_t& r1, uint32_t& r2, uint32_t& r3, uint32_t addr) {
  asm volatile("ldmatrix.sync.aligned.m8n8.x4.shared.b16 {%0, %1, %2, %3}, [%4];" : "=r"(r0), "=r"(r1), "=r"(r2), "=r"(r3) : "r"(addr) : "memory");
}
__device__ __forceinline__ void wg_fence() { asm volatile("wgmma.fence.sync.aligned;" ::: "memory"); }
__device__ __forceinline__ void wg_commit() { asm volatile("wgmma.commit_group.sync.aligned;" ::: "memory"); }
template <int N>
__device__ __forceinline__ void wg_wait() { asm volatile("wgmma.wait_group.sync.aligned %0;" ::"n"(N) : "memory"); }
template <int N>
__device__ __forceinline__ void reg_alloc() { asm volatile("setmaxnreg.inc.sync.aligned.u32 %0;" ::"n"(N)); }
template <int N>
__device__ __forceinline__ void reg_dealloc() { asm volatile("setmaxnreg.dec.sync.aligned.u32 %0;" ::"n"(N)); }
__device__ __forceinline__ void bar_sync(int id, int n) { asm volatile("bar.sync %0, %1;" ::"r"(id), "r"(n) : "memory"); }
__device__ __forceinline__ void bar_arrive(int id, int n) { asm volatile("bar.arrive %0, %1;" ::"r"(id), "r"(n) : "memory"); }
template <int NT>
__device__ __forceinline__ void fence_regs(float (&d)[NT]) {
#pragma unroll
  for (int i = 0; i < NT; i++) asm volatile("" : "+f"(d[i])::"memory");
}
template <int NT>
__device__ __forceinline__ void fence_regs(uint32_t (&d)[NT]) {
#pragma unroll
  for (int i = 0; i < NT; i++) asm volatile("" : "+r"(d[i])::"memory");
}
__device__ __forceinline__ uint64_t make_desc(uint32_t saddr, uint32_t lbo, uint32_t sbo, uint32_t layout) {
  return (uint64_t)((saddr & 0x3FFFF) >> 4) | ((uint64_t)(lbo >> 4) << 16) | ((uint64_t)(sbo >> 4) << 32) | ((uint64_t)layout << 62);
}
__device__ __forceinline__ uint32_t pack_bf16(float lo, float hi) {
  uint32_t r;
  asm("cvt.rn.bf16x2.f32 %0, %1, %2;" : "=r"(r) : "f"(hi), "f"(lo));
  return r;
}
__device__ __forceinline__ float ex2(float x) {
  float r;
  asm("ex2.approx.ftz.f32 %0, %1;" : "=f"(r) : "f"(x));
  return r;
}
__device__ __forceinline__ void st_v4(void* p, uint32_t a, uint32_t b, uint32_t c, uint32_t d) {
#define ST_MOD ".cs"
  asm volatile("st.global" ST_MOD ".v4.b32 [%0], {%1, %2, %3, %4};" ::"l"(p), "r"(a), "r"(b), "r"(c), "r"(d) : "memory");
}
#define STA_MOD ".cs"
__device__ __forceinline__ void st_v4a(void* p, uint32_t a, uint32_t b, uint32_t c, uint32_t d) {
  asm volatile("st.global" STA_MOD ".v4.b32 [%0], {%1, %2, %3, %4};" ::"l"(p), "r"(a), "r"(b), "r"(c), "r"(d) : "memory");
}
__device__ __forceinline__ float bf_lo(uint32_t v) { return __uint_as_float(v << 16); }
__device__ __forceinline__ float bf_hi(uint32_t v) { return __uint_as_float(v & 0xFFFF0000u); }

__device__ __forceinline__ void quad_transpose(uint32_t& a0, uint32_t& a1, uint32_t& a2, uint32_t& a3, int q) {
  const bool o1 = q & 1, o2 = q & 2;
  uint32_t t0 = o1 ? a0 : a1, t1 = o1 ? a2 : a3;
  t0 = __shfl_xor_sync(0xffffffffu, t0, 1);
  t1 = __shfl_xor_sync(0xffffffffu, t1, 1);
  if (o1) { a0 = t0; a2 = t1; } else { a1 = t0; a3 = t1; }
  t0 = o2 ? a0 : a2;
  t1 = o2 ? a1 : a3;
  t0 = __shfl_xor_sync(0xffffffffu, t0, 2);
  t1 = __shfl_xor_sync(0xffffffffu, t1, 2);
  if (o2) { a0 = t0; a1 = t1; } else { a2 = t0; a3 = t1; }
}

template<int TB, int OFF, int NT>
__device__ __forceinline__ void wgmma_ss_n256(float (&d)[NT], uint64_t da, uint64_t db, int scale_d) {
  asm volatile("{\n.reg .pred p;\nsetp.ne.b32 p, %130, 0;\n"
    "wgmma.mma_async.sync.aligned.m64n256k16.f32.bf16.bf16 {%0, %1, %2, %3, %4, %5, %6, %7, %8, %9, %10, %11, %12, %13, %14, %15, %16, %17, %18, %19, %20, %21, %22, %23, %24, %25, %26, %27, %28, %29, %30, %31, %32, %33, %34, %35, %36, %37, %38, %39, %40, %41, %42, %43, %44, %45, %46, %47, %48, %49, %50, %51, %52, %53, %54, %55, %56, %57, %58, %59, %60, %61, %62, %63, %64, %65, %66, %67, %68, %69, %70, %71, %72, %73, %74, %75, %76, %77, %78, %79, %80, %81, %82, %83, %84, %85, %86, %87, %88, %89, %90, %91, %92, %93, %94, %95, %96, %97, %98, %99, %100, %101, %102, %103, %104, %105, %106, %107, %108, %109, %110, %111, %112, %113, %114, %115, %116, %117, %118, %119, %120, %121, %122, %123, %124, %125, %126, %127}, %128, %129, p, 1, 1, 0, %131;\n}\n"
    : "+f"(d[OFF+0]), "+f"(d[OFF+1]), "+f"(d[OFF+2]), "+f"(d[OFF+3]), "+f"(d[OFF+4]), "+f"(d[OFF+5]), "+f"(d[OFF+6]), "+f"(d[OFF+7]), "+f"(d[OFF+8]), "+f"(d[OFF+9]), "+f"(d[OFF+10]), "+f"(d[OFF+11]), "+f"(d[OFF+12]), "+f"(d[OFF+13]), "+f"(d[OFF+14]), "+f"(d[OFF+15]), "+f"(d[OFF+16]), "+f"(d[OFF+17]), "+f"(d[OFF+18]), "+f"(d[OFF+19]), "+f"(d[OFF+20]), "+f"(d[OFF+21]), "+f"(d[OFF+22]), "+f"(d[OFF+23]), "+f"(d[OFF+24]), "+f"(d[OFF+25]), "+f"(d[OFF+26]), "+f"(d[OFF+27]), "+f"(d[OFF+28]), "+f"(d[OFF+29]), "+f"(d[OFF+30]), "+f"(d[OFF+31]), "+f"(d[OFF+32]), "+f"(d[OFF+33]), "+f"(d[OFF+34]), "+f"(d[OFF+35]), "+f"(d[OFF+36]), "+f"(d[OFF+37]), "+f"(d[OFF+38]), "+f"(d[OFF+39]), "+f"(d[OFF+40]), "+f"(d[OFF+41]), "+f"(d[OFF+42]), "+f"(d[OFF+43]), "+f"(d[OFF+44]), "+f"(d[OFF+45]), "+f"(d[OFF+46]), "+f"(d[OFF+47]), "+f"(d[OFF+48]), "+f"(d[OFF+49]), "+f"(d[OFF+50]), "+f"(d[OFF+51]), "+f"(d[OFF+52]), "+f"(d[OFF+53]), "+f"(d[OFF+54]), "+f"(d[OFF+55]), "+f"(d[OFF+56]), "+f"(d[OFF+57]), "+f"(d[OFF+58]), "+f"(d[OFF+59]), "+f"(d[OFF+60]), "+f"(d[OFF+61]), "+f"(d[OFF+62]), "+f"(d[OFF+63]), "+f"(d[OFF+64]), "+f"(d[OFF+65]), "+f"(d[OFF+66]), "+f"(d[OFF+67]), "+f"(d[OFF+68]), "+f"(d[OFF+69]), "+f"(d[OFF+70]), "+f"(d[OFF+71]), "+f"(d[OFF+72]), "+f"(d[OFF+73]), "+f"(d[OFF+74]), "+f"(d[OFF+75]), "+f"(d[OFF+76]), "+f"(d[OFF+77]), "+f"(d[OFF+78]), "+f"(d[OFF+79]), "+f"(d[OFF+80]), "+f"(d[OFF+81]), "+f"(d[OFF+82]), "+f"(d[OFF+83]), "+f"(d[OFF+84]), "+f"(d[OFF+85]), "+f"(d[OFF+86]), "+f"(d[OFF+87]), "+f"(d[OFF+88]), "+f"(d[OFF+89]), "+f"(d[OFF+90]), "+f"(d[OFF+91]), "+f"(d[OFF+92]), "+f"(d[OFF+93]), "+f"(d[OFF+94]), "+f"(d[OFF+95]), "+f"(d[OFF+96]), "+f"(d[OFF+97]), "+f"(d[OFF+98]), "+f"(d[OFF+99]), "+f"(d[OFF+100]), "+f"(d[OFF+101]), "+f"(d[OFF+102]), "+f"(d[OFF+103]), "+f"(d[OFF+104]), "+f"(d[OFF+105]), "+f"(d[OFF+106]), "+f"(d[OFF+107]), "+f"(d[OFF+108]), "+f"(d[OFF+109]), "+f"(d[OFF+110]), "+f"(d[OFF+111]), "+f"(d[OFF+112]), "+f"(d[OFF+113]), "+f"(d[OFF+114]), "+f"(d[OFF+115]), "+f"(d[OFF+116]), "+f"(d[OFF+117]), "+f"(d[OFF+118]), "+f"(d[OFF+119]), "+f"(d[OFF+120]), "+f"(d[OFF+121]), "+f"(d[OFF+122]), "+f"(d[OFF+123]), "+f"(d[OFF+124]), "+f"(d[OFF+125]), "+f"(d[OFF+126]), "+f"(d[OFF+127])
    : "l"(da), "l"(db), "r"(scale_d), "n"(TB));
}
template<int TB, int OFF, int NT>
__device__ __forceinline__ void wgmma_ss_n192(float (&d)[NT], uint64_t da, uint64_t db, int scale_d) {
  asm volatile("{\n.reg .pred p;\nsetp.ne.b32 p, %98, 0;\n"
    "wgmma.mma_async.sync.aligned.m64n192k16.f32.bf16.bf16 {%0, %1, %2, %3, %4, %5, %6, %7, %8, %9, %10, %11, %12, %13, %14, %15, %16, %17, %18, %19, %20, %21, %22, %23, %24, %25, %26, %27, %28, %29, %30, %31, %32, %33, %34, %35, %36, %37, %38, %39, %40, %41, %42, %43, %44, %45, %46, %47, %48, %49, %50, %51, %52, %53, %54, %55, %56, %57, %58, %59, %60, %61, %62, %63, %64, %65, %66, %67, %68, %69, %70, %71, %72, %73, %74, %75, %76, %77, %78, %79, %80, %81, %82, %83, %84, %85, %86, %87, %88, %89, %90, %91, %92, %93, %94, %95}, %96, %97, p, 1, 1, 0, %99;\n}\n"
    : "+f"(d[OFF+0]), "+f"(d[OFF+1]), "+f"(d[OFF+2]), "+f"(d[OFF+3]), "+f"(d[OFF+4]), "+f"(d[OFF+5]), "+f"(d[OFF+6]), "+f"(d[OFF+7]), "+f"(d[OFF+8]), "+f"(d[OFF+9]), "+f"(d[OFF+10]), "+f"(d[OFF+11]), "+f"(d[OFF+12]), "+f"(d[OFF+13]), "+f"(d[OFF+14]), "+f"(d[OFF+15]), "+f"(d[OFF+16]), "+f"(d[OFF+17]), "+f"(d[OFF+18]), "+f"(d[OFF+19]), "+f"(d[OFF+20]), "+f"(d[OFF+21]), "+f"(d[OFF+22]), "+f"(d[OFF+23]), "+f"(d[OFF+24]), "+f"(d[OFF+25]), "+f"(d[OFF+26]), "+f"(d[OFF+27]), "+f"(d[OFF+28]), "+f"(d[OFF+29]), "+f"(d[OFF+30]), "+f"(d[OFF+31]), "+f"(d[OFF+32]), "+f"(d[OFF+33]), "+f"(d[OFF+34]), "+f"(d[OFF+35]), "+f"(d[OFF+36]), "+f"(d[OFF+37]), "+f"(d[OFF+38]), "+f"(d[OFF+39]), "+f"(d[OFF+40]), "+f"(d[OFF+41]), "+f"(d[OFF+42]), "+f"(d[OFF+43]), "+f"(d[OFF+44]), "+f"(d[OFF+45]), "+f"(d[OFF+46]), "+f"(d[OFF+47]), "+f"(d[OFF+48]), "+f"(d[OFF+49]), "+f"(d[OFF+50]), "+f"(d[OFF+51]), "+f"(d[OFF+52]), "+f"(d[OFF+53]), "+f"(d[OFF+54]), "+f"(d[OFF+55]), "+f"(d[OFF+56]), "+f"(d[OFF+57]), "+f"(d[OFF+58]), "+f"(d[OFF+59]), "+f"(d[OFF+60]), "+f"(d[OFF+61]), "+f"(d[OFF+62]), "+f"(d[OFF+63]), "+f"(d[OFF+64]), "+f"(d[OFF+65]), "+f"(d[OFF+66]), "+f"(d[OFF+67]), "+f"(d[OFF+68]), "+f"(d[OFF+69]), "+f"(d[OFF+70]), "+f"(d[OFF+71]), "+f"(d[OFF+72]), "+f"(d[OFF+73]), "+f"(d[OFF+74]), "+f"(d[OFF+75]), "+f"(d[OFF+76]), "+f"(d[OFF+77]), "+f"(d[OFF+78]), "+f"(d[OFF+79]), "+f"(d[OFF+80]), "+f"(d[OFF+81]), "+f"(d[OFF+82]), "+f"(d[OFF+83]), "+f"(d[OFF+84]), "+f"(d[OFF+85]), "+f"(d[OFF+86]), "+f"(d[OFF+87]), "+f"(d[OFF+88]), "+f"(d[OFF+89]), "+f"(d[OFF+90]), "+f"(d[OFF+91]), "+f"(d[OFF+92]), "+f"(d[OFF+93]), "+f"(d[OFF+94]), "+f"(d[OFF+95])
    : "l"(da), "l"(db), "r"(scale_d), "n"(TB));
}
template<int TB, int OFF, int NT>
__device__ __forceinline__ void wgmma_ss_n128(float (&d)[NT], uint64_t da, uint64_t db, int scale_d) {
  asm volatile("{\n.reg .pred p;\nsetp.ne.b32 p, %66, 0;\n"
    "wgmma.mma_async.sync.aligned.m64n128k16.f32.bf16.bf16 {%0, %1, %2, %3, %4, %5, %6, %7, %8, %9, %10, %11, %12, %13, %14, %15, %16, %17, %18, %19, %20, %21, %22, %23, %24, %25, %26, %27, %28, %29, %30, %31, %32, %33, %34, %35, %36, %37, %38, %39, %40, %41, %42, %43, %44, %45, %46, %47, %48, %49, %50, %51, %52, %53, %54, %55, %56, %57, %58, %59, %60, %61, %62, %63}, %64, %65, p, 1, 1, 0, %67;\n}\n"
    : "+f"(d[OFF+0]), "+f"(d[OFF+1]), "+f"(d[OFF+2]), "+f"(d[OFF+3]), "+f"(d[OFF+4]), "+f"(d[OFF+5]), "+f"(d[OFF+6]), "+f"(d[OFF+7]), "+f"(d[OFF+8]), "+f"(d[OFF+9]), "+f"(d[OFF+10]), "+f"(d[OFF+11]), "+f"(d[OFF+12]), "+f"(d[OFF+13]), "+f"(d[OFF+14]), "+f"(d[OFF+15]), "+f"(d[OFF+16]), "+f"(d[OFF+17]), "+f"(d[OFF+18]), "+f"(d[OFF+19]), "+f"(d[OFF+20]), "+f"(d[OFF+21]), "+f"(d[OFF+22]), "+f"(d[OFF+23]), "+f"(d[OFF+24]), "+f"(d[OFF+25]), "+f"(d[OFF+26]), "+f"(d[OFF+27]), "+f"(d[OFF+28]), "+f"(d[OFF+29]), "+f"(d[OFF+30]), "+f"(d[OFF+31]), "+f"(d[OFF+32]), "+f"(d[OFF+33]), "+f"(d[OFF+34]), "+f"(d[OFF+35]), "+f"(d[OFF+36]), "+f"(d[OFF+37]), "+f"(d[OFF+38]), "+f"(d[OFF+39]), "+f"(d[OFF+40]), "+f"(d[OFF+41]), "+f"(d[OFF+42]), "+f"(d[OFF+43]), "+f"(d[OFF+44]), "+f"(d[OFF+45]), "+f"(d[OFF+46]), "+f"(d[OFF+47]), "+f"(d[OFF+48]), "+f"(d[OFF+49]), "+f"(d[OFF+50]), "+f"(d[OFF+51]), "+f"(d[OFF+52]), "+f"(d[OFF+53]), "+f"(d[OFF+54]), "+f"(d[OFF+55]), "+f"(d[OFF+56]), "+f"(d[OFF+57]), "+f"(d[OFF+58]), "+f"(d[OFF+59]), "+f"(d[OFF+60]), "+f"(d[OFF+61]), "+f"(d[OFF+62]), "+f"(d[OFF+63])
    : "l"(da), "l"(db), "r"(scale_d), "n"(TB));
}
template<int TB, int OFF, int NT>
__device__ __forceinline__ void wgmma_ss_n32(float (&d)[NT], uint64_t da, uint64_t db, int scale_d) {
  asm volatile("{\n.reg .pred p;\nsetp.ne.b32 p, %18, 0;\n"
    "wgmma.mma_async.sync.aligned.m64n32k16.f32.bf16.bf16 {%0, %1, %2, %3, %4, %5, %6, %7, %8, %9, %10, %11, %12, %13, %14, %15}, %16, %17, p, 1, 1, 0, %19;\n}\n"
    : "+f"(d[OFF+0]), "+f"(d[OFF+1]), "+f"(d[OFF+2]), "+f"(d[OFF+3]), "+f"(d[OFF+4]), "+f"(d[OFF+5]), "+f"(d[OFF+6]), "+f"(d[OFF+7]), "+f"(d[OFF+8]), "+f"(d[OFF+9]), "+f"(d[OFF+10]), "+f"(d[OFF+11]), "+f"(d[OFF+12]), "+f"(d[OFF+13]), "+f"(d[OFF+14]), "+f"(d[OFF+15])
    : "l"(da), "l"(db), "r"(scale_d), "n"(TB));
}
template<int TB, int OFF, int NT>
__device__ __forceinline__ void wgmma_rs_n128(float (&d)[NT], uint32_t a0, uint32_t a1, uint32_t a2, uint32_t a3, uint64_t db, int scale_d) {
  asm volatile("{\n.reg .pred p;\nsetp.ne.b32 p, %69, 0;\n"
    "wgmma.mma_async.sync.aligned.m64n128k16.f32.bf16.bf16 {%0, %1, %2, %3, %4, %5, %6, %7, %8, %9, %10, %11, %12, %13, %14, %15, %16, %17, %18, %19, %20, %21, %22, %23, %24, %25, %26, %27, %28, %29, %30, %31, %32, %33, %34, %35, %36, %37, %38, %39, %40, %41, %42, %43, %44, %45, %46, %47, %48, %49, %50, %51, %52, %53, %54, %55, %56, %57, %58, %59, %60, %61, %62, %63}, {%64, %65, %66, %67}, %68, p, 1, 1, %70;\n}\n"
    : "+f"(d[OFF+0]), "+f"(d[OFF+1]), "+f"(d[OFF+2]), "+f"(d[OFF+3]), "+f"(d[OFF+4]), "+f"(d[OFF+5]), "+f"(d[OFF+6]), "+f"(d[OFF+7]), "+f"(d[OFF+8]), "+f"(d[OFF+9]), "+f"(d[OFF+10]), "+f"(d[OFF+11]), "+f"(d[OFF+12]), "+f"(d[OFF+13]), "+f"(d[OFF+14]), "+f"(d[OFF+15]), "+f"(d[OFF+16]), "+f"(d[OFF+17]), "+f"(d[OFF+18]), "+f"(d[OFF+19]), "+f"(d[OFF+20]), "+f"(d[OFF+21]), "+f"(d[OFF+22]), "+f"(d[OFF+23]), "+f"(d[OFF+24]), "+f"(d[OFF+25]), "+f"(d[OFF+26]), "+f"(d[OFF+27]), "+f"(d[OFF+28]), "+f"(d[OFF+29]), "+f"(d[OFF+30]), "+f"(d[OFF+31]), "+f"(d[OFF+32]), "+f"(d[OFF+33]), "+f"(d[OFF+34]), "+f"(d[OFF+35]), "+f"(d[OFF+36]), "+f"(d[OFF+37]), "+f"(d[OFF+38]), "+f"(d[OFF+39]), "+f"(d[OFF+40]), "+f"(d[OFF+41]), "+f"(d[OFF+42]), "+f"(d[OFF+43]), "+f"(d[OFF+44]), "+f"(d[OFF+45]), "+f"(d[OFF+46]), "+f"(d[OFF+47]), "+f"(d[OFF+48]), "+f"(d[OFF+49]), "+f"(d[OFF+50]), "+f"(d[OFF+51]), "+f"(d[OFF+52]), "+f"(d[OFF+53]), "+f"(d[OFF+54]), "+f"(d[OFF+55]), "+f"(d[OFF+56]), "+f"(d[OFF+57]), "+f"(d[OFF+58]), "+f"(d[OFF+59]), "+f"(d[OFF+60]), "+f"(d[OFF+61]), "+f"(d[OFF+62]), "+f"(d[OFF+63])
    : "r"(a0), "r"(a1), "r"(a2), "r"(a3), "l"(db), "r"(scale_d), "n"(TB));
}
template<int TB, int OFF, int NT>
__device__ __forceinline__ void wgmma_rs_n64(float (&d)[NT], uint32_t a0, uint32_t a1, uint32_t a2, uint32_t a3, uint64_t db, int scale_d) {
  asm volatile("{\n.reg .pred p;\nsetp.ne.b32 p, %37, 0;\n"
    "wgmma.mma_async.sync.aligned.m64n64k16.f32.bf16.bf16 {%0, %1, %2, %3, %4, %5, %6, %7, %8, %9, %10, %11, %12, %13, %14, %15, %16, %17, %18, %19, %20, %21, %22, %23, %24, %25, %26, %27, %28, %29, %30, %31}, {%32, %33, %34, %35}, %36, p, 1, 1, %38;\n}\n"
    : "+f"(d[OFF+0]), "+f"(d[OFF+1]), "+f"(d[OFF+2]), "+f"(d[OFF+3]), "+f"(d[OFF+4]), "+f"(d[OFF+5]), "+f"(d[OFF+6]), "+f"(d[OFF+7]), "+f"(d[OFF+8]), "+f"(d[OFF+9]), "+f"(d[OFF+10]), "+f"(d[OFF+11]), "+f"(d[OFF+12]), "+f"(d[OFF+13]), "+f"(d[OFF+14]), "+f"(d[OFF+15]), "+f"(d[OFF+16]), "+f"(d[OFF+17]), "+f"(d[OFF+18]), "+f"(d[OFF+19]), "+f"(d[OFF+20]), "+f"(d[OFF+21]), "+f"(d[OFF+22]), "+f"(d[OFF+23]), "+f"(d[OFF+24]), "+f"(d[OFF+25]), "+f"(d[OFF+26]), "+f"(d[OFF+27]), "+f"(d[OFF+28]), "+f"(d[OFF+29]), "+f"(d[OFF+30]), "+f"(d[OFF+31])
    : "r"(a0), "r"(a1), "r"(a2), "r"(a3), "l"(db), "r"(scale_d), "n"(TB));
}

__device__ __forceinline__ void wait_flag(const unsigned int* f, uint32_t target) {
  uint32_t v;
#pragma unroll 1
  for (uint32_t spins = 0; spins < (1u << 22); spins++) {
    asm volatile("ld.acquire.gpu.global.u32 %0, [%1];" : "=r"(v) : "l"(f) : "memory");
    if (v >= target) break;
    __nanosleep(100);
  }
}
__device__ __forceinline__ uint32_t lds32(uint32_t a) {
  uint32_t v;
  asm volatile("ld.shared.u32 %0, [%1];" : "=r"(v) : "r"(a) : "memory");
  return v;
}
__device__ __forceinline__ float gate_row(int row, int lane, const bf16* __restrict__ x, const bf16* __restrict__ gate_w) {
  const uint32_t* xr = reinterpret_cast<const uint32_t*>(x + (size_t)row * DM);
  const uint32_t* gw2 = reinterpret_cast<const uint32_t*>(gate_w);
  float gs = 0.f;
#pragma unroll
  for (int i = 0; i < 9; i++) {
    const uint32_t a = __ldg(xr + lane + 32 * i), b = __ldg(gw2 + lane + 32 * i);
    gs = fmaf(bf_lo(a), bf_lo(b), gs);
    gs = fmaf(bf_hi(a), bf_hi(b), gs);
  }
#pragma unroll
  for (int o = 16; o; o >>= 1) gs += __shfl_xor_sync(0xffffffffu, gs, o);
  const float g = 1.f / (1.f + __expf(-gs));
  if (lane == 0) g_gate[row] = g;
  return g;
}
#define LA_UNROLL 9
__device__ __forceinline__ void local_rows2(int rb, int ri, uint32_t sL, uint32_t bL2, int lane, float ga, float gb) {
  const float scale_l2 = 0.23570226039551584f * 1.4426950408889634f;
  constexpr int U = LA_UNROLL;
  const uint32_t sq = sL + (30 + ri) * 1152;
  uint32_t kb[9];
#pragma unroll
  for (int i = 0; i < 9; i++) {
    const uint32_t c = lane * 9 + i;
    kb[i] = sL + (14 + ri) * 1152 + ((c & ~15u) | ((c & 3) << 2) | ((c >> 2) & 3)) * 4;
  }
  float ma = -INFINITY, mb = -INFINITY;
  {
    float qa[18], qb[18];
#pragma unroll
    for (int i = 0; i < 9; i++) {
      const uint32_t u = lds32(kb[i] + 16 * 1152 - 2304), v = lds32(kb[i] + 16 * 1152);
      qa[2 * i] = bf_lo(u); qa[2 * i + 1] = bf_hi(u);
      qb[2 * i] = bf_lo(v); qb[2 * i + 1] = bf_hi(v);
    }
    __syncwarp();
#pragma unroll U
    for (int t = 0; t < 9; t++) {
      const bool ok = rb - 2 * t >= 0;
      float a0 = 0.f, a1 = 0.f, b0 = 0.f, b1 = 0.f;
#pragma unroll
      for (int i = 0; i < 9; i++) {
        const uint32_t k = lds32(kb[i] - t * 2304);
        const float lo = bf_lo(k), hi = bf_hi(k);
        a0 = fmaf(qa[2 * i], lo, a0); a1 = fmaf(qa[2 * i + 1], hi, a1);
        b0 = fmaf(qb[2 * i], lo, b0); b1 = fmaf(qb[2 * i + 1], hi, b1);
      }
      a0 = (ok && t > 0) ? a0 + a1 : -INFINITY;
      b0 = (ok && t < 8) ? b0 + b1 : -INFINITY;
      ma = fmaxf(ma, a0);
      mb = fmaxf(mb, b0);
      asm volatile("st.shared.f32 [%0], %1;" ::"r"(sq - 2304 + t * 128 + lane * 4), "f"(a0) : "memory");
      asm volatile("st.shared.f32 [%0], %1;" ::"r"(sq + t * 128 + lane * 4), "f"(b0) : "memory");
    }
  }
  float oa[18], ob[18], sa = 0.f, sb = 0.f;
#pragma unroll
  for (int i = 0; i < 18; i++) { oa[i] = 0.f; ob[i] = 0.f; }
  mbar_wait(bL2, 0);
#pragma unroll U
  for (int t = 0; t < 9; t++) {
    const float wa = ex2((__uint_as_float(lds32(sq - 2304 + t * 128 + lane * 4)) - ma) * scale_l2);
    const float wb = ex2((__uint_as_float(lds32(sq + t * 128 + lane * 4)) - mb) * scale_l2);
    sa += wa;
    sb += wb;
#pragma unroll
    for (int i = 0; i < 9; i++) {
      const uint32_t v = lds32(kb[i] + 46 * 1152 - t * 2304);
      const float lo = bf_lo(v), hi = bf_hi(v);
      oa[2 * i] = fmaf(wa, lo, oa[2 * i]); oa[2 * i + 1] = fmaf(wa, hi, oa[2 * i + 1]);
      ob[2 * i] = fmaf(wb, lo, ob[2 * i]); ob[2 * i + 1] = fmaf(wb, hi, ob[2 * i + 1]);
    }
  }
  ga = __fdividef(ga, sa);
  gb = __fdividef(gb, sb);
  __syncwarp();
#pragma unroll
  for (int i = 0; i < 9; i++) {
    asm volatile("st.shared.u32 [%0], %1;" ::"r"(sq - 2304 + lane * 36 + 4 * i), "r"(pack_bf16(oa[2 * i] * ga, oa[2 * i + 1] * ga)) : "memory");
    asm volatile("st.shared.u32 [%0], %1;" ::"r"(sq + lane * 36 + 4 * i), "r"(pack_bf16(ob[2 * i] * gb, ob[2 * i + 1] * gb)) : "memory");
  }
  __syncwarp();
  uint32_t w[5][4];
#pragma unroll
  for (int t = 0; t < 5; t++) {
    const int c = min(t * 32 + lane, 143), r = c >= 72;
    asm volatile("ld.shared.v4.u32 {%0, %1, %2, %3}, [%4];" : "=r"(w[t][0]), "=r"(w[t][1]), "=r"(w[t][2]), "=r"(w[t][3])
                 : "r"(sq - 2304 + r * 2304 + (c - r * 72) * 16) : "memory");
  }
  asm volatile("fence.proxy.async.shared::cta;" ::: "memory");
  bar_arrive(4, 256 + 32);
#pragma unroll
  for (int t = 0; t < 5; t++) {
    const int c = min(t * 32 + lane, 143), r = c >= 72;
    st_v4(g_ctx + (size_t)(rb - 2 + 2 * r) * KCAT + HDIM + (c - r * 72) * 8, w[t][0], w[t][1], w[t][2], w[t][3]);
  }
}

#define K1_NST 6
constexpr int K1_BST = K1_NST;
constexpr int K1_MAXJOBS = 11;
constexpr uint32_t K1_FLAG_TARGET = 7;
constexpr uint32_t RDY_TARGET = 48;
constexpr uint32_t GATE_TARGET = 128 * 3;
struct alignas(64) Params {
  CUtensorMap tmA[2];
  CUtensorMap tmW[4];
  CUtensorMap tmQ, tmK, tmV;
  CUtensorMap tmL[2];
  CUtensorMap tmC, tmO[2], tmOt[2];
  uint16_t jobs[NCLUSTER][K1_MAXJOBS + 1];
  uint8_t order[256];
  uint8_t unit[64][4];
};

struct K1State {
  uint32_t bs, bph, aph;
  bf16* pp;
  int pld8;
  int png;
  int tn;
};
__device__ __forceinline__ void k1_flag(const K1State& st, int lane, uint32_t bS) {
  if (st.png) {
    __syncwarp();
    if (lane == 0) mbar_arrive(bS);
  }
}

__device__ __forceinline__ void k1_first(const K1State& st, uint32_t job, uint32_t bAf, uint32_t bBf) {
  if (job & 3) {
    if ((job >> 14) & 1) mbar_wait(bAf, st.aph);
    mbar_wait(bBf + st.bs * 8, st.bph);
  }
}
__device__ __forceinline__ void k1_tile(float (&acc)[128], uint32_t (&pk)[64], K1State& st, uint32_t job, uint32_t njob, uint32_t sA, uint32_t sB,
                                        uint32_t bAf, uint32_t bAe, uint32_t bBf, uint32_t bBe, uint32_t bS, int wg, int warp, int lane, uint32_t rank) {
  const int a_sel = (job >> 2) & 1, mpair = (job >> 3) & 7, w_sel = (job >> 6) & 3, chunk0 = (job >> 8) & 63;
  const bool newA = (job >> 14) & 1, lastA = (job >> 15) & 1;
  const bool sig = (lane == 0) && (warp < 2);
  const bool siga = lastA && (lane == 0) && (warp == 2);
  const int KC = 8 + a_sel;
  uint32_t prev_bs = 0, a8_bs = 0;
#pragma unroll
  for (int kc = 0; kc < 9; kc++) {
    if (kc >= KC) break;
    uint32_t abase = sA + ((kc + 2) & 7) * 16384;
    if (kc == 8) {
      mbar_wait(bBf + st.bs * 8, st.bph);
      a8_bs = st.bs;
      abase = sB + st.bs * 16384;
      if (++st.bs == K1_BST) { st.bs = 0; st.bph ^= 1; }
    } else if (newA && kc > 0) {
      mbar_wait(bAf + kc * 8, st.aph);
    }
    const uint64_t da = make_desc(abase + wg * 8192, 16, 1024, 1);
#pragma unroll
    for (int ks = 0; ks < 2; ks++) {
      if (ks > 0 || kc > 0) mbar_wait(bBf + st.bs * 8, st.bph);
      const uint64_t db = make_desc(sB + st.bs * 16384, 2048, 1024, 1);
      wg_fence();
      wgmma_ss_n256<1, 0>(acc, da + (uint64_t)(ks * 4), db, (ks > 0) ? 1 : (kc > 0));
      wgmma_ss_n256<1, 0>(acc, da + (uint64_t)(ks * 4 + 2), db + (uint64_t)512, 1);
      wg_commit();
      const int PO = (kc < 8 ? kc : 0) * 8;
      wg_wait<1>();
      if (ks > 0 || kc > 0) {
        if (sig) mbar_arrive_cluster(bBe + prev_bs * 8, warp);
        if (ks == 0 && siga) mbar_arrive(bAe + (kc - 1) * 8);
      }
      if (kc < st.png) st_v4a(st.pp + kc * 32 + ks * st.pld8, pk[PO + ks * 4], pk[PO + ks * 4 + 1], pk[PO + ks * 4 + 2], pk[PO + ks * 4 + 3]);
      prev_bs = st.bs;
      if (++st.bs == K1_BST) { st.bs = 0; st.bph ^= 1; }
    }
  }
  if (newA) st.aph ^= 1;
  k1_flag(st, lane, bS);
  const bool isA = (w_sel == 2);
  bf16* out = (w_sel == 0) ? g_K : (w_sel == 1) ? g_V : isA ? g_QKVA : g_Q;
  const int ld = isA ? NQKVA : HDIM;
  const int row = mpair * 256 + rank * 128 + wg * 64 + warp * 16 + (lane >> 2);
  st.pp = out + (size_t)row * ld + chunk0 * 64 + (lane & 3) * 8;
  st.pld8 = 8 * ld;
  st.png = ((job & 3) + 1) * 2;
  k1_first(st, njob, bAf, bBf);
  wg_wait<0>();
  fence_regs(acc);
  mbar_arrive_cluster_if(bBe + prev_bs * 8, warp & 1, sig);
  mbar_arrive_cluster_if(bBe + a8_bs * 8, warp & 1, sig && a_sel);
  mbar_arrive_if(bAe + 7 * 8, siga && !a_sel);
#pragma unroll
  for (int G = 0; G < 8; G++) {
    pk[G * 8 + 0] = pack_bf16(acc[G * 16 + 0], acc[G * 16 + 1]);
    pk[G * 8 + 1] = pack_bf16(acc[G * 16 + 4], acc[G * 16 + 5]);
    pk[G * 8 + 2] = pack_bf16(acc[G * 16 + 8], acc[G * 16 + 9]);
    pk[G * 8 + 3] = pack_bf16(acc[G * 16 + 12], acc[G * 16 + 13]);
    pk[G * 8 + 4] = pack_bf16(acc[G * 16 + 2], acc[G * 16 + 3]);
    pk[G * 8 + 5] = pack_bf16(acc[G * 16 + 6], acc[G * 16 + 7]);
    pk[G * 8 + 6] = pack_bf16(acc[G * 16 + 10], acc[G * 16 + 11]);
    pk[G * 8 + 7] = pack_bf16(acc[G * 16 + 14], acc[G * 16 + 15]);
  }
}

#define HA(h) (h)
constexpr int K2_NST = 7;
constexpr uint32_t K2_END = 0x100;
#define PF_KC 7
#define FIRST_DRAW 3
#define ANCH 8
#define HNS 1000
#define PNS 1000
#define PWAIT mbar_wait_ns<PNS>
#define PVM 0x8A
#define W0 63
#define SPEC 24
constexpr int K3_NST = 4;
__device__ __forceinline__ uint32_t k3_rot(uint32_t sv) { return (0x00E9u >> (2 * sv)) & 3; }
constexpr int K3_STAGE = 16384 + 32768 + 4096;
constexpr int SMEM_DATA = 7 * 32768;
constexpr int SMEM_BYTES = SMEM_DATA + 1024 + 768;

struct Cursor {
  uint32_t s, ph;
  __device__ __forceinline__ void next() {
    if (++s == K2_NST) { s = 0; ph ^= 1; }
  }
};

#define TURN_SYNC() bar_sync(mybar, 256)
#define TURN_ARRIVE() bar_arrive(otherbar, 256)
#define RELEASE_IF(cur, cond) mbar_arrive_cluster_if(bE + (cur).s * 8, warp & 1, sig && (cond))
#define RELEASE(cur) RELEASE_IF(cur, true)
#define ISSUE_PV(cur, first)                                                                                   \
  do {                                                                                                         \
    const uint64_t dv = make_desc(sbase + (cur).s * 32768, 16384, 1024, 1);                                    \
    _Pragma("unroll") for (int t = 0; t < 8; t++)                                                              \
        wgmma_rs_n128<1, 0>(O, P[4 * t], P[4 * t + 1], P[4 * t + 2], P[4 * t + 3], dv + (uint64_t)(t * 128), (t > 0) ? 1 : !(first)); \
  } while (0)
#define ISSUE_QK(cur)                                                                                          \
  do {                                                                                                         \
    const uint64_t dk = make_desc(sbase + (cur).s * 32768, 16, 1024, 1);                                       \
    _Pragma("unroll") for (int t = 0; t < 8; t++)                                                              \
        wgmma_rs_n128<0, 0>(S, Q[4 * t], Q[4 * t + 1], Q[4 * t + 2], Q[4 * t + 3], dk + (uint64_t)((t >> 2) * 1024 + (t & 3) * 2), t > 0); \
  } while (0)
#define SCALE(J0, J1)                                                                                          \
  do {                                                                                                         \
    _Pragma("unroll") for (int jj = J0; jj < J1; jj++) {                                                       \
      S[jj * 4 + 0] = fmaf(S[jj * 4 + 0], cl2, -m0);                                                           \
      S[jj * 4 + 1] = fmaf(S[jj * 4 + 1], cl2, -m0);                                                           \
      S[jj * 4 + 2] = fmaf(S[jj * 4 + 2], cl2, -m1);                                                           \
      S[jj * 4 + 3] = fmaf(S[jj * 4 + 3], cl2, -m1);                                                           \
    }                                                                                                          \
  } while (0)
#define EXPB(T)                                                                                                \
  do {                                                                                                         \
    _Pragma("unroll") for (int i = 4 * T; i < 4 * T + 4; i++) asm volatile("" : "+r"(P[i])::"memory");        \
    _Pragma("unroll") for (int jj = 2 * T; jj < 2 * T + 2; jj++) {                                             \
      const float e0 = ex2(S[jj * 4 + 0]), e1 = ex2(S[jj * 4 + 1]), e2 = ex2(S[jj * 4 + 2]), e3 = ex2(S[jj * 4 + 3]); \
      s0 += e0 + e1;                                                                                           \
      s1 += e2 + e3;                                                                                           \
      P[jj * 2 + 0] = pack_bf16(e0, e1);                                                                       \
      P[jj * 2 + 1] = pack_bf16(e2, e3);                                                                       \
    }                                                                                                          \
  } while (0)
#define EXPC(T)                                                                                                \
  do {                                                                                                         \
    if (T > 0 && ((PVM >> (T - 1)) & 1)) {                                                                     \
      anchor((T & 2) ? s0 : s1, never);                                                                        \
      wg_wait<__builtin_popcount(PVM >> T) - 1>();                                                             \
      if ((PVM >> T) == (128 >> T)) { fence_regs(O); RELEASE(cv); }                                            \
    }                                                                                                          \
    EXPB(T);                                                                                                   \
  } while (0)
#define MASK(G, g)                                                                                             \
  do {                                                                                                         \
    if ((g) * 8 > d) S[(G) * 4 + 0] = -INFINITY;                                                               \
    if ((g) * 8 + 1 > d) S[(G) * 4 + 1] = -INFINITY;                                                           \
    if ((g) * 8 - 8 > d) S[(G) * 4 + 2] = -INFINITY;                                                           \
    if ((g) * 8 - 7 > d) S[(G) * 4 + 3] = -INFINITY;                                                           \
  } while (0)
#define FIRST_REF()                                                                                            \
  do {                                                                                                         \
    m0 = fmaxf(S[0], S[1]);                                                                                    \
    m1 = fmaxf(S[2], S[3]);                                                                                    \
    m0 = fmaxf(m0, __shfl_xor_sync(0xffffffffu, m0, 1));                                                       \
    m1 = fmaxf(m1, __shfl_xor_sync(0xffffffffu, m1, 1));                                                       \
    m0 = fmaxf(m0, __shfl_xor_sync(0xffffffffu, m0, 2)) * cl2;                                                 \
    m1 = fmaxf(m1, __shfl_xor_sync(0xffffffffu, m1, 2)) * cl2;                                                 \
  } while (0)
#define STORE_O(G)                                                                                             \
  do {                                                                                                         \
    st_v4(g_ctx + eoff + (G) * 32, pack_bf16(O[(G) * 16 + 0] * f0, O[(G) * 16 + 1] * f0), pack_bf16(O[(G) * 16 + 4] * f0, O[(G) * 16 + 5] * f0), \
          pack_bf16(O[(G) * 16 + 8] * f0, O[(G) * 16 + 9] * f0), pack_bf16(O[(G) * 16 + 12] * f0, O[(G) * 16 + 13] * f0)); \
    st_v4(g_ctx + eoff + 8 * KCAT + (G) * 32, pack_bf16(O[(G) * 16 + 2] * f1, O[(G) * 16 + 3] * f1), pack_bf16(O[(G) * 16 + 6] * f1, O[(G) * 16 + 7] * f1), \
          pack_bf16(O[(G) * 16 + 10] * f1, O[(G) * 16 + 11] * f1), pack_bf16(O[(G) * 16 + 14] * f1, O[(G) * 16 + 15] * f1)); \
  } while (0)

__global__ void __cluster_dims__(2, 1, 1) __launch_bounds__(384, 1)
fused_kernel(const __grid_constant__ Params p, const bf16* __restrict__ x, const bf16* __restrict__ gate_w, bf16* __restrict__ out) {
  extern __shared__ uint8_t smem_raw[];
  const uint32_t sbase = (smem_u32(smem_raw) + 1023) & ~1023u;
  const uint32_t sB = sbase, sA = sbase + K1_BST * 16384, sBar = sbase + SMEM_DATA;
  const uint32_t bAf = sBar, bAe = sBar + 64, bBf = sBar + 128, bBe = sBar + 176, bL = sBar + 224, bS = sBar + 232, bL2 = sBar + 240, sL = sA + 32768;
  const uint32_t bF = sBar + 256, bE = sBar + 320, bT = sBar + 384, sTick = sBar + 400, sItem = sBar + 416, bS2 = sBar + 448, bR = sBar + 456, bLast = sBar + 464, bH = sBar + 472, bT0 = sBar + 480;
  const uint32_t b3F = sBar + 512, b3E = sBar + 544, sGate = sBar + 576;
  const int tid = threadIdx.x, warp_g = __shfl_sync(0xffffffffu, tid >> 5, 0), lane = tid & 31;
  const uint32_t rank = cluster_rank();
  const int cl = blockIdx.x >> 1;
  TSM(0);
  if (tid == 0) {
    for (int i = 0; i < 8; i++) { mbar_init(bAf + i * 8, 1); mbar_init(bAe + i * 8, 2); }
    for (int i = 0; i < K1_BST; i++) { mbar_init(bBf + i * 8, 1); mbar_init(bBe + i * 8, 4); }
    mbar_init(bL, 1);
    mbar_init(bL2, 1);
    mbar_init(bR, 1);
    mbar_init(bLast, 1);
    mbar_init(bH, 4);
    mbar_init(bT0, 1);
    mbar_init(bS, 8);
    for (int i = 0; i < K2_NST; i++) { mbar_init(bF + i * 8, 1); mbar_init(bE + i * 8, 4); }
    mbar_init(bT, 1); mbar_init(bT + 8, 1);
    mbar_init(bS2, 8);
    for (int i = 0; i < K3_NST; i++) { mbar_init(b3F + i * 8, 1); mbar_init(b3E + i * 8, 4); }
    asm volatile("fence.mbarrier_init.release.cluster;" ::: "memory");
  }
  __syncthreads();
  cluster_sync();
  const int lr0 = blockIdx.x * 16;

  if (warp_g >= 8) {
    reg_dealloc<40>();
    if (warp_g == 8) {
      if (elect_one()) {
        uint32_t bs = 0, bph = 1, aph = 1;
#pragma unroll 1
        for (int ji = 0; ji < K1_MAXJOBS; ji++) {
          const uint32_t job = p.jobs[cl][ji];
          if (!(job & 3)) break;
          const int a_sel = (job >> 2) & 1, mpair = (job >> 3) & 7, chunk0 = (job >> 8) & 63;
          const bool newA = (job >> 14) & 1;
          const int KC = a_sel ? 9 : 8;
          const uint32_t halfbytes = 8192;
          const bool lastjob = (ji + 1 == K1_MAXJOBS) || !(p.jobs[cl][ji + 1] & 3);
          const CUtensorMap* tw = &p.tmW[(job >> 6) & 3];
          {
            const uint32_t njob = (ji + 1 < K1_MAXJOBS) ? p.jobs[cl][ji + 1] : 0;
            if (!(njob & 3) && !newA) mbar_arrive(bLast);
          }
#pragma unroll 1
          for (int kc = 0; kc < KC; kc++) {
            if (kc == ((ji == 0) ? PF_KC : 0) && !lastjob) {
              const uint32_t njob = p.jobs[cl][ji + 1];
              const int nst = ((njob >> 2) & 1) ? 18 : 16;
#pragma unroll 1
              for (int t = (cl < 64) ? (cl & 7) : 0; t < nst; t += (cl < 64) ? 8 : 1)
                tma_pf3d(&p.tmW[(njob >> 6) & 3], 0, t * 32 + rank * 16, (njob >> 8) & 63);
            }
            if (kc == 8) {
              PWAIT(bBe + bs * 8, bph);
              mbar_expect(bBf + bs * 8, 16384);
              tma2d(sB + bs * 16384, &p.tmA[1], bBf + bs * 8, 512, mpair * 256 + rank * 128);
              if (++bs == K1_BST) { bs = 0; bph ^= 1; }
            } else if (newA) {
              PWAIT(bAe + kc * 8, aph);
              mbar_expect(bAf + kc * 8, 16384);
              tma2d(sA + ((kc + 2) & 7) * 16384, &p.tmA[a_sel], bAf + kc * 8, kc * 64, mpair * 256 + rank * 128);
              if (kc == 7 && lastjob) mbar_arrive(bLast);
            }
#pragma unroll 1
            for (int kk = 0; kk < 2; kk++) {
              PWAIT(bBe + bs * 8, bph);
              mbar_expect(bBf + bs * 8, 2 * halfbytes);
              tma3d_mc(sB + bs * 16384 + rank * halfbytes, tw, bBf + bs * 8, 0, kc * 64 + kk * 32 + rank * 16, chunk0, 3);
              if (++bs == K1_BST) { bs = 0; bph ^= 1; }
            }
          }
          if (newA) aph ^= 1;
        }
        Cursor c{0, 0};
        int pcol = 0;
        PWAIT(bR, 0);
        uint32_t tick = lds32(sTick + 8), seen = 1u << (p.order[tick] >> 4);
        asm volatile("fence.proxy.async.global;" ::: "memory");
#pragma unroll 1
        for (int it = 0;; it++) {
          const uint32_t item = (tick < 256) ? p.order[tick] : (K2_END | min(tick - 256, 255u));
          asm volatile("st.shared.u32 [%0], %1;" ::"r"(sItem + (it & 7) * 4), "r"(item) : "memory");
          if (item >= K2_END) break;
          const int h = item >> 3, j = item & 7;
          const int blk = 2 * j + (int)(rank ^ (it & 1));
          const int col = HA(h) * 128 + rank * 64;
          const int nb = 2 * j + 2;
          if (!((seen >> (h >> 1)) & 1)) {
            wait_flag(&g_sync[F_HP + (h >> 1)], RDY_TARGET);
            asm volatile("fence.proxy.async.global;" ::: "memory");
            seen |= 1u << (h >> 1);
          }
          PWAIT(bE + c.s * 8, c.ph);
          mbar_expect(bF + c.s * 8, 32768);
          tma2d(sbase + c.s * 32768, &p.tmQ, bF + c.s * 8, HA(h) * 128, blk * 128);
          tma2d(sbase + c.s * 32768 + 16384, &p.tmQ, bF + c.s * 8, HA(h) * 128 + 64, blk * 128);
          c.next();
#pragma unroll 1
          for (int n = nb - 1; n >= 0; n--) {
            if (n == 0 && rank == 0) tick = atomicAdd(&g_sync[F_TICK], 1u);
            PWAIT(bE + c.s * 8, c.ph);
            mbar_expect(bF + c.s * 8, 32768);
            tma2d_mc(sbase + c.s * 32768 + rank * 16384, &p.tmK, bF + c.s * 8, col, n * 128, 3);
            c.next();
            if (n < nb - 1 || it > 0) {
              PWAIT(bE + c.s * 8, c.ph);
              mbar_expect(bF + c.s * 8, 32768);
              tma2d_mc(sbase + c.s * 32768 + rank * 16384, &p.tmV, bF + c.s * 8, (n < nb - 1) ? col : pcol, (n < nb - 1) ? (n + 1) * 128 : 0, 3);
              c.next();
            }
          }
          pcol = col;
          if (rank == 0) {
            asm volatile(
                "{\n.reg .b32 a, b;\nmapa.shared::cluster.u32 a, %0, 1;\nmapa.shared::cluster.u32 b, %1, 1;\n"
                "st.async.shared::cluster.mbarrier::complete_tx::bytes.u32 [a], %2, [b];\n}" ::"r"(sTick + (it & 1) * 4),
                "r"(bT + (it & 1) * 8), "r"(tick) : "memory");
          } else {
            mbar_expect(bT + (it & 1) * 8, 4);
            PWAIT(bT + (it & 1) * 8, (it >> 1) & 1);
            tick = lds32(sTick + (it & 1) * 4);
          }
        }
        PWAIT(bE + c.s * 8, c.ph);
        mbar_expect(bF + c.s * 8, 32768);
        tma2d_mc(sbase + c.s * 32768 + rank * 16384, &p.tmV, bF + c.s * 8, pcol, 0, 3);
        const uint32_t unit = tick - 256;
        if (unit < 64) {
          const int mblk = (7 - (p.unit[unit][0] >> 1)) * 2 + rank, nhalf = p.unit[unit][0] & 1;
          const uint32_t rot = k3_rot(c.s), nfree = ((0x1Au >> c.s) & 1) ? 2 : 3;
#pragma unroll 1
          for (int i = 0; i < K2_NST - 1; i++) {
            c.next();
            PWAIT(bE + c.s * 8, c.ph);
          }
          uint32_t idx = 0, have = 0;
#pragma unroll 1
          for (int kk = p.unit[unit][2]; kk < p.unit[unit][3]; kk++, idx++) {
            const uint32_t s = (rot + idx) & 3;
            if (idx >= nfree) PWAIT((idx < 4) ? bH : b3E + s * 8, (idx < 4) ? 0 : (~idx >> 2) & 1);
            mbar_expect(b3F + s * 8, K3_STAGE);
            const uint32_t st = sbase + s * K3_STAGE;
            const int sel = (kk < 9), k = sel ? kk : kk - 9, kr = k * 64 + rank * 32;
            tma3d_mc(st + 16384 + rank * 16384, &p.tmO[sel], b3F + s * 8, 0, kr, nhalf * 4, 3);
            tma2d_mc(st + 49152 + rank * 2048, &p.tmOt[sel], b3F + s * 8, 512 + nhalf * 32, kr, 3);
            if (kk == 0) {
              wait_flag(&g_sync[F_OA + mblk], 8);
              asm volatile("fence.proxy.async.global;" ::: "memory");
            }
            if (!sel && !((have >> (k >> 1)) & 1)) {
#pragma unroll 1
              for (uint32_t spins = 0; spins < (1u << 22); spins++) {
                asm volatile("ld.acquire.gpu.global.u32 %0, [%1];" : "=r"(have) : "l"(&g_sync[F_CTX + mblk]) : "memory");
                if ((have >> (k >> 1)) & 1) break;
                __nanosleep(100);
              }
              asm volatile("fence.proxy.async.global;" ::: "memory");
            }
            tma2d(st, &p.tmC, b3F + s * 8, (sel ? 64 + k : k) * 64, mblk * 128);
          }
        }
      }
    }
    __syncwarp();
    if (warp_g == 8) {
      uint32_t v = 0;
      if (lane == 0) {
        __threadfence();
        v = atomicAdd(&g_sync[F_DONE], 1u);
      }
      if (__shfl_sync(0xffffffffu, v, 0) == 2 * NCLUSTER - 1) {
        reinterpret_cast<uint4*>(g_sync)[lane] = make_uint4(0, 0, 0, 0);
        if (lane == 0) g_sync[F_EPOCH] = lds32(sGate + 64) + 1;
      }
    }
    asm volatile("" ::: "memory");
    if (__shfl_sync(0xffffffffu, warp_g, 0) != 8) {
      if (lr0 < S_LEN) {
#pragma unroll 1
        for (int i = warp_g - 9; i < 16; i += 3) {
          const float g = gate_row(lr0 + i, lane, x, gate_w);
          if (lane == 0) asm volatile("st.shared.f32 [%0], %1;" ::"r"(sGate + i * 4), "f"(g) : "memory");
        }
        bar_arrive(3, 256 + 96);
        if (lane == 0) {
          __threadfence();
          atomicAdd(&g_sync[F_GATE], 1u);
        }
      }
      uint32_t aph = 1;
#pragma unroll 1
      for (int ji = 0; ji < K1_MAXJOBS; ji++) aph ^= (p.jobs[cl][ji] >> 14) & 1;
      if (warp_g == 9 && lane == 0) {
#pragma unroll 1
        for (int ji = 0; ji < K1_MAXJOBS; ji++) {
          const uint32_t job = p.jobs[cl][ji];
          if (!(job & 3)) break;
          mbar_wait_ns<HNS>(bS, ji & 1);
          __threadfence();
          atomicAdd(&g_sync[(((job >> 6) & 3) == 2) ? (F_QKVA + ((job >> 3) & 7) * 2 + rank) : (F_HP + ((job >> 10) & 15))], 1u);
        }
#pragma unroll 1
        for (int it = 0;; it++) {
          mbar_wait_ns<HNS>(bS2, it & 1);
          const uint32_t item = lds32(sItem + (it & 7) * 4), nxt = lds32(sItem + ((it + 1) & 7) * 4);
          __threadfence();
          atomicOr(&g_sync[F_CTX + (item & 7) * 2 + (rank ^ (it & 1))], 1u << (item >> 3));
          if (nxt >= K2_END) break;
        }
      } else if (warp_g == 11) {
        if (lane == 0) {
          prefetch_tmap(&p.tmQ); prefetch_tmap(&p.tmK); prefetch_tmap(&p.tmV);
          asm volatile("st.shared.u32 [%0], %1;" ::"r"(sGate + 64), "r"(__ldcg(&g_sync[F_EPOCH])) : "memory");
          wait_flag(&g_sync[F_GATE], GATE_TARGET);
          uint32_t tick;
          if (rank == 0) {
            mbar_wait_ns<HNS>(bLast, 0);
            mbar_wait_ns<HNS>(bAe + FIRST_DRAW * 8, aph);
            tick = atomicAdd(&g_sync[F_TICK], 1u);
            asm volatile("st.shared.u32 [%0], %1;" ::"r"(sTick + 8), "r"(tick) : "memory");
            asm volatile(
                "{\n.reg .b32 a, b;\nmapa.shared::cluster.u32 a, %0, 1;\nmapa.shared::cluster.u32 b, %1, 1;\n"
                "st.async.shared::cluster.mbarrier::complete_tx::bytes.u32 [a], %2, [b];\n}" ::"r"(sTick + 8), "r"(bT0), "r"(tick) : "memory");
          } else {
            mbar_expect(bT0, 4);
            mbar_wait_ns<HNS>(bT0, 0);
            tick = lds32(sTick + 8);
          }
          wait_flag(&g_sync[F_HP + (p.order[tick] >> 4)], RDY_TARGET);
          mbar_arrive(bR);
        }
        __syncwarp();
        bar_sync(4, 256 + 32);
        if (lane < 12) mbar_arrive_cluster(bE + (4 + lane % 3) * 8, (lane / 3) & 1);
      } else if (warp_g == 10 && lr0 < S_LEN) {
        if (elect_one()) {
          prefetch_tmap(&p.tmL[0]); prefetch_tmap(&p.tmL[1]);
          wait_flag(&g_sync[F_QKVA + (lr0 >> 7)], K1_FLAG_TARGET);
          wait_flag(&g_sync[F_QKVA + (max(lr0 - 14, 0) >> 7)], K1_FLAG_TARGET);
          asm volatile("fence.proxy.async.global;" ::: "memory");
          mbar_wait_ns<HNS>(bLast, 0);
#pragma unroll 1
          for (int kc = 0; kc < 6; kc++) {
            mbar_wait_ns<HNS>(bAe + kc * 8, aph);
            if (kc == 3) {
              mbar_expect(bL, 46 * 1152);
              tma3d(sL, &p.tmL[0], bL, 0, 9, lr0 - 14);
              tma3d(sL + 30 * 1152, &p.tmL[1], bL, 0, 0, lr0);
            }
          }
          mbar_expect(bL2, 30 * 1152);
          tma3d(sL + 46 * 1152, &p.tmL[0], bL2, 0, 18, lr0 - 14);
        }
        __syncwarp();
        bar_sync(5, 256 + 32);
        if (lane == 0) {
          __threadfence();
          atomicAdd(&g_sync[F_OA + (lr0 >> 7)], 1u);
        }
      }
    }
    __syncwarp();
    cluster_sync();
  } else {
    reg_alloc<232>();
    const int wg = warp_g >> 2, warp = warp_g & 3, q = lane & 3;
    const bool sig = (lane == 0) && (warp < 2);
    {
      K1State st{0, 0, 0, nullptr, 0, 0, 0};
      float acc[128];
      uint32_t pk[64];
      if (wg == 0) { TS(0, 0); TSC(0, 2); }
      uint32_t job = p.jobs[cl][0];
      k1_first(st, job, bAf, bBf);
#pragma unroll 1
      for (int ji = 0; job & 3; ji++) {
        const uint32_t njob = p.jobs[cl][ji + 1];
        k1_tile(acc, pk, st, job, njob, sA, sB, bAf, bAe, bBf, bBe, bS, wg, warp, lane, rank);
        job = njob;
      }
#pragma unroll
      for (int i = 0; i < 4; i++)
        mbar_arrive_cluster_if(bE + i * 8, warp & 1, sig);
#pragma unroll
      for (int G = 0; G < 8; G++)
        if (G < st.png) {
          st_v4a(st.pp + G * 32, pk[G * 8], pk[G * 8 + 1], pk[G * 8 + 2], pk[G * 8 + 3]);
          st_v4a(st.pp + G * 32 + st.pld8, pk[G * 8 + 4], pk[G * 8 + 5], pk[G * 8 + 6], pk[G * 8 + 7]);
        }
      k1_flag(st, lane, bS);
      if (wg == 0) { TS(0, 1); TSC(0, 3); }
      if (lr0 < S_LEN) {
        const int ri = (warp_g >> 1) * 4 + (warp_g & 1) + 2, row = lr0 + ri;
        if (wg == 0) TS(1, 5);
        bar_sync(3, 256 + 96);
        const float gate0 = __uint_as_float(lds32(sGate + ri * 4 - 8)), gate1 = __uint_as_float(lds32(sGate + ri * 4));
        mbar_wait(bL, 0);
        if (wg == 0) TS(1, 6);
        local_rows2(row, ri, sL, bL2, lane, gate0, gate1);
        bar_arrive(5, 256 + 32);
      } else {
        bar_arrive(4, 256 + 32);
      }
    }
    __syncwarp();
    uint32_t item, rot;
    {
      const int mybar = 1 + wg, otherbar = 2 - wg;
      const uint32_t never = blockIdx.y;
      const float cl2 = 0.08838834764831845f * 1.4426950408889634f;
      float S[64], O[64];
      uint32_t P[32], Q[32];
      float m0 = 0.f, m1 = 0.f, l0 = 1.f, l1 = 1.f, gf0 = 0.f, gf1 = 0.f;
      uint32_t eoff = 0, prev_single = 0;
      Cursor c{0, 0};
      if (wg == 1) bar_arrive(1, 256);
      if (wg == 0) { TS(1, 0); TSC(1, 2); }
#pragma unroll 1
      for (int it = 0;; it++) {
        TB(0);
        const int hi = (int)(rank ^ (it & 1));
        Cursor cq = c, ck, cv, cs0, cs1;
        rot = k3_rot(c.s);
        c.next();
        ck = c; c.next();
        cs0 = ck; cs1 = ck; cv = ck;
        if (it > 0) { cv = c; c.next(); }
        if (!hi) {
          ck = c; c.next();
          cs1 = c; c.next();
        }
        mbar_wait(bF + cq.s * 8, cq.ph);
        TB(1);
        item = lds32(sItem + (it & 7) * 4);
        {
          const uint32_t qa = sbase + cq.s * 32768 + (wg * 64 + warp * 16 + (lane & 15)) * 128;
#pragma unroll
          for (int t = 0; t < 8; t++)
            ldsm_x4(Q[4 * t], Q[4 * t + 1], Q[4 * t + 2], Q[4 * t + 3], qa + (t >> 2) * 16384 + ((((t & 3) * 2 + (lane >> 4)) ^ (lane & 7)) << 4));
        }
        const uint32_t rdy = mbar_test(bF + ck.s * 8, ck.ph) & mbar_test(bF + cv.s * 8, cv.ph);
        l0 += __shfl_xor_sync(0xffffffffu, l0, 1);
        l1 += __shfl_xor_sync(0xffffffffu, l1, 1);
        l0 += __shfl_xor_sync(0xffffffffu, l0, 2);
        l1 += __shfl_xor_sync(0xffffffffu, l1, 2);
        const bool last = item >= K2_END;
        if (last) {
          cv = cq; ck = cq;
        } else if (!rdy) {
          mbar_wait2(bF + ck.s * 8, ck.ph, bF + cv.s * 8, cv.ph);
        }
        TB(2);
        TURN_SYNC();
        TB(3);
        TRC(last ? 2 : 1);
        if (it > 0) {
          wg_fence();
          ISSUE_PV(cv, prev_single);
          wg_commit();
        } else {
          wg_fence();
          wg_commit();
        }
        wg_fence();
        ISSUE_QK(ck);
        wg_commit();
        if (!(last && wg == 1)) TURN_ARRIVE();
        RELEASE_IF(cq, !last);
        TB(4);
        asm volatile("" : "+f"(gf0), "+f"(gf1), "+f"(l0), "+f"(l1));
        const float f0 = __fdividef(1.f - gf0, l0), f1 = __fdividef(1.f - gf1, l1);
        wg_wait<1>();
        fence_regs(O);
        fence_regs(P);
        TB(5);
        if (it > 0) {
          RELEASE_IF(cv, !last);
          mbar_arrive_cluster_if(bH, warp & 1, sig && last);
          STORE_O(0); STORE_O(1); STORE_O(2); STORE_O(3);
          __syncwarp();
          mbar_arrive_if(bS2, lane == 0);
        }
        TB(6);
        if (!last) {
          const int row = (2 * (item & 7) + hi) * 128 + wg * 64 + warp * 16 + (lane >> 2);
          eoff = row * KCAT + (item >> 3) * 128 + q * 8;
          asm volatile("ld.global.f32 %0, [%1];" : "=f"(gf0) : "l"(g_gate + row));
          asm volatile("ld.global.f32 %0, [%1];" : "=f"(gf1) : "l"(g_gate + row + 8));
          if (!hi) {
            mbar_wait2(bF + cs0.s * 8, cs0.ph, bF + cs1.s * 8, cs1.ph);
            RELEASE(cs0);
            RELEASE(cs1);
          }
        }
        TB(7);
        wg_wait<0>();
        fence_regs(S);
        TB(8);
        if (last) break;
        RELEASE(ck);
        const int nblk = 2 * (item & 7) + 1 + hi;
        prev_single = (nblk == 1);
        float s0 = 0.f, s1 = 0.f;
        l0 = 0.f; l1 = 0.f;
        {
          const int d = warp * 16 + (lane >> 2) - 2 * q;
          if (wg == 0) {
            MASK(0, 0);
            FIRST_REF();
#pragma unroll
            for (int jj = 1; jj < 8; jj++) MASK(jj, jj);
            SCALE(0, 8);
            EXPB(0); EXPB(1); EXPB(2); EXPB(3);
#pragma unroll
            for (int i = 32; i < 64; i++) S[i] = -INFINITY;
#pragma unroll
            for (int i = 16; i < 32; i++) P[i] = 0;
          } else {
            FIRST_REF();
#pragma unroll
            for (int jj = 0; jj < 8; jj++) MASK(jj + 8, jj);
            SCALE(0, 16);
            EXPB(0); EXPB(1); EXPB(2); EXPB(3); EXPB(4); EXPB(5); EXPB(6); EXPB(7);
          }
        }
        fence_regs(P);
        TB(9);
#pragma unroll 1
        for (int n = 1;; n++) {
          if (__any_sync(0xffffffffu, !(s0 + s1 <= (float)(1ull << SPEC)))) {
            float mx0 = fmaxf(S[0], S[1]), mx1 = fmaxf(S[2], S[3]);
#pragma unroll
            for (int jj = 1; jj < 16; jj++) {
              mx0 = fmaxf(mx0, fmaxf(S[jj * 4 + 0], S[jj * 4 + 1]));
              mx1 = fmaxf(mx1, fmaxf(S[jj * 4 + 2], S[jj * 4 + 3]));
            }
            mx0 = fmaxf(mx0, __shfl_xor_sync(0xffffffffu, mx0, 1));
            mx1 = fmaxf(mx1, __shfl_xor_sync(0xffffffffu, mx1, 1));
            mx0 = fmaxf(mx0, __shfl_xor_sync(0xffffffffu, mx0, 2));
            mx1 = fmaxf(mx1, __shfl_xor_sync(0xffffffffu, mx1, 2));
            mx0 = fmaxf(mx0, 0.f);
            mx1 = fmaxf(mx1, 0.f);
            m0 += mx0; m1 += mx1;
            const float sc0 = ex2(-mx0), sc1 = ex2(-mx1);
            l0 *= sc0; l1 *= sc1;
            s0 = 0.f; s1 = 0.f;
#pragma unroll
            for (int jj = 0; jj < 16; jj++) {
              const float e0 = ex2(S[jj * 4 + 0] - mx0), e1 = ex2(S[jj * 4 + 1] - mx0), e2 = ex2(S[jj * 4 + 2] - mx1), e3 = ex2(S[jj * 4 + 3] - mx1);
              s0 += e0 + e1;
              s1 += e2 + e3;
              P[jj * 2 + 0] = pack_bf16(e0, e1);
              P[jj * 2 + 1] = pack_bf16(e2, e3);
              O[jj * 4 + 0] *= sc0;
              O[jj * 4 + 1] *= sc0;
              O[jj * 4 + 2] *= sc1;
              O[jj * 4 + 3] *= sc1;
            }
          }
          l0 += s0;
          l1 += s1;
          if (n >= nblk) break;
          ck = c; c.next();
          cv = c; c.next();
          mbar_wait(bF + ck.s * 8, ck.ph);
          mbar_wait(bF + cv.s * 8, cv.ph);
          TURN_SYNC();
          TRC(0);
          wg_fence();
          ISSUE_QK(ck);
          wg_commit();
          {
            const uint64_t dv = make_desc(sbase + cv.s * 32768, 16384, 1024, 1);
#pragma unroll
            for (int t = 0; t < 8; t++) {
              wgmma_rs_n128<1, 0>(O, P[4 * t], P[4 * t + 1], P[4 * t + 2], P[4 * t + 3], dv + (uint64_t)(t * 128), (t > 0) ? 1 : (n != 1));
              if ((PVM >> t) & 1) wg_commit();
            }
          }
          TURN_ARRIVE();
          s0 = 0.f; s1 = 0.f;
          wg_wait<__builtin_popcount(PVM)>();
          fence_regs(S);
          RELEASE(ck);
          SCALE(0, 16);
          anchor(S[W0], never);
          wg_wait<__builtin_popcount(PVM) - 1>();
          EXPC(0); EXPC(1); EXPC(2); EXPC(3); EXPC(4); EXPC(5); EXPC(6); EXPC(7);
        }
      }
      TRC(3);
      if (wg == 1) { TS(1, 1); TSC(1, 3); }
    }
    __syncwarp();
    const uint32_t unit = item & 255;
    if (unit < 64) {
      const int mblk = (7 - (p.unit[unit][0] >> 1)) * 2 + rank, nhalf = p.unit[unit][0] & 1, ks = p.unit[unit][1];
      const int k0 = p.unit[unit][2], k1 = p.unit[unit][3];
      float acc[144];
      uint32_t s = rot, ph = 0, prev = 0;
      if (wg == 0) { TS(2, 0); TSC(2, 2); }
#pragma unroll 1
      for (int k = k0; k < k1; k++) {
        mbar_wait(b3F + s * 8, ph);
        const uint32_t st = sbase + s * K3_STAGE;
        const uint64_t da = make_desc(st + wg * 8192, 16, 1024, 1);
        const uint64_t db = make_desc(st + 16384, 4096, 1024, 1);
        const uint64_t dt = make_desc(st + 49152, 16, 512, 2);
        wg_fence();
#pragma unroll
        for (int t = 0; t < 4; t++) {
          const int sd = (t > 0) || (k > k0);
          wgmma_ss_n256<1, 0>(acc, da + (uint64_t)(t * 2), db + (uint64_t)((t >> 1) * 1024 + (t & 1) * 128), sd);
          wgmma_ss_n32<1, 128>(acc, da + (uint64_t)(t * 2), dt + (uint64_t)(t * 64), sd);
        }
        wg_commit();
        if (k > k0) {
          wg_wait<1>();
          if (sig) mbar_arrive_cluster(b3E + prev * 8, warp);
        }
        prev = s;
        s = (s + 1) & 3;
        if (s == rot) ph ^= 1;
      }
      wg_wait<0>();
      fence_regs(acc);
      cluster_arrive();
      if (wg == 0) TS(2, 4);
      const int tile = mblk * 2 + nhalf;
      uint4* wp = g_part + (size_t)((tile * 4 + ks) * 4) * 5 * 256 + tid;
      const uint32_t sown = sbase + wg * 8192 + (tid & 127) * 16;
#pragma unroll
      for (int d = 0; d < 4; d++) {
        if (d != ks) {
#pragma unroll
          for (int i = 0; i < 4; i++)
            __stcg(wp + (d * 5 + i) * 256,
                   make_uint4(pack_bf16(acc[d * 32 + i * 8], acc[d * 32 + i * 8 + 1]), pack_bf16(acc[d * 32 + i * 8 + 2], acc[d * 32 + i * 8 + 3]),
                              pack_bf16(acc[d * 32 + i * 8 + 4], acc[d * 32 + i * 8 + 5]), pack_bf16(acc[d * 32 + i * 8 + 6], acc[d * 32 + i * 8 + 7])));
          __stcg(reinterpret_cast<uint2*>(wp - tid + (d * 5 + 4) * 256) + tid,
                 make_uint2(pack_bf16(acc[128 + d * 4], acc[128 + d * 4 + 1]), pack_bf16(acc[128 + d * 4 + 2], acc[128 + d * 4 + 3])));
        } else {
#pragma unroll
          for (int i = 0; i < 9; i++) {
            const int o = (i < 8) ? d * 32 + i * 4 : 128 + d * 4;
            asm volatile("st.shared.v4.f32 [%0], {%1, %2, %3, %4};" ::"r"(sown + (i >> 2) * K3_STAGE + (i & 3) * 2048), "f"(acc[o]), "f"(acc[o + 1]), "f"(acc[o + 2]), "f"(acc[o + 3]) : "memory");
          }
        }
      }
      __threadfence();
      __syncwarp();
      if (wg == 0) TS(2, 5);
      if (lane == 0) {
        unsigned int* cnt = &g_sync[F_XCH + tile * 8 + warp_g];
        const uint32_t xtarget = lds32(sGate + 64) * 4 + 4;
        atomicAdd(cnt, 1u);
        uint32_t v, spins = 0;
        do {
          asm volatile("ld.acquire.gpu.global.u32 %0, [%1];" : "=r"(v) : "l"(cnt) : "memory");
        } while ((int)(v - xtarget) < 0 && ++spins < (1u << 24));
      }
      __syncwarp();
      if (wg == 0) TS(2, 6);
      float r[36];
#pragma unroll
      for (int i = 0; i < 9; i++)
        asm volatile("ld.shared.v4.f32 {%0, %1, %2, %3}, [%4];" : "=f"(r[i * 4]), "=f"(r[i * 4 + 1]), "=f"(r[i * 4 + 2]), "=f"(r[i * 4 + 3])
                     : "r"(sown + (i >> 2) * K3_STAGE + (i & 3) * 2048) : "memory");
#pragma unroll
      for (int sI = 1; sI < 4; sI++) {
        const int src = (ks + sI) & 3;
        const uint4* rp = g_part + (size_t)(((tile * 4 + src) * 4) + ks) * 5 * 256;
#pragma unroll
        for (int i = 0; i < 4; i++) {
          const uint4 v = __ldcg(rp + i * 256 + tid);
          r[i * 8] += bf_lo(v.x); r[i * 8 + 1] += bf_hi(v.x); r[i * 8 + 2] += bf_lo(v.y); r[i * 8 + 3] += bf_hi(v.y);
          r[i * 8 + 4] += bf_lo(v.z); r[i * 8 + 5] += bf_hi(v.z); r[i * 8 + 6] += bf_lo(v.w); r[i * 8 + 7] += bf_hi(v.w);
        }
        const uint2 v = __ldcg(reinterpret_cast<const uint2*>(rp + 4 * 256) + tid);
        r[32] += bf_lo(v.x); r[33] += bf_hi(v.x); r[34] += bf_lo(v.y); r[35] += bf_hi(v.y);
      }
      const int row = mblk * 128 + wg * 64 + warp * 16 + (lane >> 2);
      bf16* o0 = out + (size_t)row * DM + nhalf * 256 + ks * 64 + 8 * q;
#pragma unroll
      for (int G = 0; G < 2; G++) {
        uint32_t a0 = pack_bf16(r[G * 16], r[G * 16 + 1]), a1 = pack_bf16(r[G * 16 + 4], r[G * 16 + 5]);
        uint32_t a2 = pack_bf16(r[G * 16 + 8], r[G * 16 + 9]), a3 = pack_bf16(r[G * 16 + 12], r[G * 16 + 13]);
        uint32_t b0 = pack_bf16(r[G * 16 + 2], r[G * 16 + 3]), b1 = pack_bf16(r[G * 16 + 6], r[G * 16 + 7]);
        uint32_t b2 = pack_bf16(r[G * 16 + 10], r[G * 16 + 11]), b3 = pack_bf16(r[G * 16 + 14], r[G * 16 + 15]);
        quad_transpose(a0, a1, a2, a3, q);
        quad_transpose(b0, b1, b2, b3, q);
        st_v4(o0 + G * 32, a0, a1, a2, a3);
        st_v4(o0 + 8 * DM + G * 32, b0, b1, b2, b3);
      }
      {
        uint32_t t0 = pack_bf16(r[32], r[33]), t1 = pack_bf16(r[34], r[35]), t2 = 0, t3 = 0;
        quad_transpose(t0, t1, t2, t3, q);
        if (q < 2) st_v4(out + (size_t)(row + q * 8) * DM + 512 + nhalf * 32 + ks * 8, t0, t1, t2, t3);
      }
    } else {
      cluster_arrive();
    }
    if (wg == 0) { TS(2, 1); TSC(2, 3); }
    cluster_wait();
  }
}

typedef CUresult (*EncFn)(CUtensorMap*, CUtensorMapDataType, cuuint32_t, void*, const cuuint64_t*, const cuuint64_t*, const cuuint32_t*,
                          const cuuint32_t*, CUtensorMapInterleave, CUtensorMapSwizzle, CUtensorMapL2promotion, CUtensorMapFloatOOBfill);

static void enc2d(EncFn enc, CUtensorMap* m, const void* ptr, uint64_t cols, uint64_t rows, uint32_t bc, uint32_t br,
                  CUtensorMapSwizzle sw = CU_TENSOR_MAP_SWIZZLE_128B) {
  cuuint64_t gd[2] = {cols, rows}, gs[1] = {cols * 2};
  cuuint32_t bx[2] = {bc, br}, es[2] = {1, 1};
  enc(m, CU_TENSOR_MAP_DATA_TYPE_BFLOAT16, 2, const_cast<void*>(ptr), gd, gs, bx, es, CU_TENSOR_MAP_INTERLEAVE_NONE, sw,
      CU_TENSOR_MAP_L2_PROMOTION_L2_256B, CU_TENSOR_MAP_FLOAT_OOB_FILL_NONE);
}
static void enc3d(EncFn enc, CUtensorMap* m, const void* ptr, uint64_t cols, uint64_t rows, uint32_t br, uint32_t bch) {
  cuuint64_t gd[3] = {64, rows, cols / 64}, gs[2] = {cols * 2, 128};
  cuuint32_t bx[3] = {64, br, bch}, es[3] = {1, 1, 1};
  enc(m, CU_TENSOR_MAP_DATA_TYPE_BFLOAT16, 3, const_cast<void*>(ptr), gd, gs, bx, es, CU_TENSOR_MAP_INTERLEAVE_NONE,
      CU_TENSOR_MAP_SWIZZLE_128B, CU_TENSOR_MAP_L2_PROMOTION_L2_256B, CU_TENSOR_MAP_FLOAT_OOB_FILL_NONE);
}

static int g_sched[10] = {11, 10, 7, 4, 4, 5, 6, 6, 8, 20};
static void build_k1_jobs(Params& p) {
  int cnt[NCLUSTER];
  for (int c = 0; c < NCLUSTER; c++) {
    cnt[c] = 0;
    for (int i = 0; i <= K1_MAXJOBS; i++) p.jobs[c][i] = 0;
  }
  auto add = [&](int c, int nch, int a_sel, int mp, int w_sel, int chunk0) {
    p.jobs[c][cnt[c]++] = (uint16_t)((nch - 1) | (a_sel << 2) | (mp << 3) | (w_sel << 6) | (chunk0 << 8));
  };
  const int *cg = g_sched, *xg = g_sched + 4;
  for (int mp = 0; mp < 8; mp++) {
    int k = 0;
    for (int i = 0; i < K1_MAXJOBS; i++)
      for (int g = 0; g < 4; g++)
        if (i < cg[g]) { add(g * 8 + mp, 4, 0, mp, k & 1, (k >> 1) * 4); k++; }
    k = 0;
    for (int i = 0; i < K1_MAXJOBS; i++)
      for (int g = 0; g < 4; g++)
        if (i < xg[g]) {
          if (k < 7) add((4 + g) * 8 + mp, k == 0 ? 3 : 4, 1, mp, 2, k == 0 ? 24 : (k - 1) * 4);
          else add((4 + g) * 8 + mp, 4, 1, mp, 3, (k - 7) * 4);
          k++;
        }
    add(64 + mp / 4, 4, 1, mp, 3, 14 * 4);
    add(64 + mp / 4, 4, 1, mp, 3, 15 * 4);
  }
  for (int cc = 0; cc < NCLUSTER; cc++)
    for (int i = 0; i < cnt[cc]; i++) {
      const int key = p.jobs[cc][i] & 0x3C;
      if (i == 0 || (p.jobs[cc][i - 1] & 0x3C) != key) p.jobs[cc][i] |= (1 << 14);
      if (i == cnt[cc] - 1 || (p.jobs[cc][i + 1] & 0x3C) != key) p.jobs[cc][i] |= (1 << 15);
    }
}

static void build_k2_items(Params& p) {
  int n = 0;
  const int SCHED_N1 = g_sched[8], SCHED_N2 = g_sched[9];
  for (int j = 7; j >= 0; j--)
    for (int h = 0; h < SCHED_N1; h++) p.order[n++] = (uint8_t)(h * 8 + j);
  for (int j = 7; j >= 4; j--)
    for (int h = SCHED_N1; h < SCHED_N2; h++) p.order[n++] = (uint8_t)(h * 8 + j);
  for (int j = 7; j >= 0; j--)
    for (int h = SCHED_N1; h < 32; h++)
      if (!(h < SCHED_N2 && j >= 4)) p.order[n++] = (uint8_t)(h * 8 + j);
}

static void build_k3_units(Params& p) {
  float slope = 0.09f;
  for (int t = 0; t < 16; t++) {
    const int u[4] = {t, 31 - t, 32 + t, 63 - t};
    float acc = 0.f;
    int k0 = 0;
    for (int i = 0; i < 4; i++) {
      acc += 18.25f + slope * (31.5f - u[i]);
      const int k1 = (i == 3) ? 73 : (int)(acc + 0.5f);
      p.unit[u[i]][0] = (uint8_t)t; p.unit[u[i]][1] = (uint8_t)i; p.unit[u[i]][2] = (uint8_t)k0; p.unit[u[i]][3] = (uint8_t)k1;
      k0 = k1;
    }
  }
}

extern "C" void kernel_launch(void* const* d_in, const int* in_sizes, int n_in, void* d_out, int out_size) {
  const bf16* x = (const bf16*)d_in[0];
  const bf16* wqkv = (const bf16*)d_in[1];
  const bf16* wo = (const bf16*)d_in[2];
  const bf16* ckv = (const bf16*)d_in[4];
  const bf16* w_q = (const bf16*)d_in[5];
  const bf16* w_uk = (const bf16*)d_in[6];
  const bf16* w_uv = (const bf16*)d_in[7];
  const bf16* w_o = (const bf16*)d_in[8];
  const bf16* gate_w = (const bf16*)d_in[9];

  EncFn enc = nullptr;
  cudaDriverEntryPointQueryResult qr;
  cudaGetDriverEntryPoint("cuTensorMapEncodeTiled", (void**)&enc, cudaEnableDefault, &qr);
  void *pQ, *pK, *pV, *pCtx, *pQA;
  cudaGetSymbolAddress(&pQ, g_Q);
  cudaGetSymbolAddress(&pQA, g_QKVA);
  cudaGetSymbolAddress(&pK, g_K);
  cudaGetSymbolAddress(&pV, g_V);
  cudaGetSymbolAddress(&pCtx, g_ctx);

  static Params p;
  enc2d(enc, &p.tmA[0], ckv, DC, S_LEN, 64, 128);
  enc2d(enc, &p.tmA[1], x, DM, S_LEN, 64, 128);
  enc3d(enc, &p.tmW[0], w_uk, HDIM, DC, 16, 4);
  enc3d(enc, &p.tmW[1], w_uv, HDIM, DC, 16, 4);
  enc3d(enc, &p.tmW[2], wqkv, NQKVA, DM, 16, 4);
  enc3d(enc, &p.tmW[3], w_q, HDIM, DM, 16, 4);
  build_k1_jobs(p);
  enc2d(enc, &p.tmQ, pQ, HDIM, S_LEN, 64, 128);
  enc2d(enc, &p.tmK, pK, HDIM, S_LEN, 64, 128);
  enc2d(enc, &p.tmV, pV, HDIM, S_LEN, 64, 128);
  build_k2_items(p);
  build_k3_units(p);
  for (int i = 0; i < 2; i++) {
    cuuint64_t gd[3] = {64, 27, S_LEN}, gs[2] = {128, NQKVA * 2};
    cuuint32_t bx[3] = {64, 9, i ? 16u : 30u}, es[3] = {1, 1, 1};
    enc(&p.tmL[i], CU_TENSOR_MAP_DATA_TYPE_BFLOAT16, 3, pQA, gd, gs, bx, es, CU_TENSOR_MAP_INTERLEAVE_NONE, CU_TENSOR_MAP_SWIZZLE_NONE,
        CU_TENSOR_MAP_L2_PROMOTION_L2_256B, CU_TENSOR_MAP_FLOAT_OOB_FILL_NONE);
  }
  enc2d(enc, &p.tmC, pCtx, KCAT, S_LEN, 64, 128);
  enc3d(enc, &p.tmO[0], w_o, DM, HDIM, 32, 4);
  enc3d(enc, &p.tmO[1], wo, DM, DM, 32, 4);
  enc2d(enc, &p.tmOt[0], w_o, DM, HDIM, 32, 32, CU_TENSOR_MAP_SWIZZLE_64B);
  enc2d(enc, &p.tmOt[1], wo, DM, DM, 32, 32, CU_TENSOR_MAP_SWIZZLE_64B);

  cudaFuncSetAttribute(fused_kernel, cudaFuncAttributeMaxDynamicSharedMemorySize, SMEM_BYTES);
  fused_kernel<<<NCLUSTER * 2, 384, SMEM_BYTES>>>(p, x, gate_w, (bf16*)d_out);
}
```

```cpp
#include <cuda_runtime.h>
#include <cuda_bf16.h>
#include <cuda.h>
#include <stdint.h>

typedef __nv_bfloat16 bf16;

constexpr int S_LEN = 2048, DM = 576, DC = 512, HDIM = 4096, NQKVA = 1728, KCAT = 4672;
constexpr int NCLUSTER = 66;

__device__ __align__(1024) bf16 g_Q[S_LEN * HDIM];
__device__ __align__(1024) bf16 g_K[S_LEN * HDIM];
__device__ __align__(1024) bf16 g_V[S_LEN * HDIM];
__device__ __align__(1024) bf16 g_QKVA[S_LEN * NQKVA + 64];
__device__ __align__(1024) bf16 g_ctx[S_LEN * KCAT];
__device__ float g_gate[S_LEN];
__device__ __align__(1024) uint4 g_part[32 * 4 * 4 * 5 * 256];
__device__ __align__(16) unsigned int g_sync[400];
constexpr int F_QKVA = 0, F_HP = 16, F_CTX = 32, F_OA = 48, F_GATE = 96, F_TICK = 97, F_DONE = 98, F_XCH = 128, F_EPOCH = 384;

__device__ __forceinline__ uint32_t smem_u32(const void* p) { return (uint32_t)__cvta_generic_to_shared(p); }
__device__ __forceinline__ void mbar_init(uint32_t a, uint32_t c) {
  asm volatile("mbarrier.init.shared::cta.b64 [%0], %1;" ::"r"(a), "r"(c));
}
__device__ __forceinline__ void mbar_expect(uint32_t a, uint32_t b) {
  asm volatile("mbarrier.arrive.expect_tx.shared::cta.b64 _, [%0], %1;" ::"r"(a), "r"(b) : "memory");
}
#define TS(k, i)
#define TSC(k, i)
#define TSM(k)
#define BSEG(i)
#define TB(k)
#define TRC(fl)
#define SPIN_LIMIT "4194304"
__device__ __forceinline__ void mbar_wait(uint32_t a, uint32_t parity) {
  asm volatile(
      "{\n.reg .pred p;\n.reg .u32 n;\n"
      "mbarrier.try_wait.parity.shared::cta.b64 p, [%0], %1;\n"
      "@p bra DONE;\n"
      "mov.u32 n, 0;\n"
      "LOOP:\n"
      "mbarrier.try_wait.parity.shared::cta.b64 p, [%0], %1;\n"
      "@p bra DONE;\n"
      "add.u32 n, n, 1;\n"
      "setp.lt.u32 p, n, " SPIN_LIMIT ";\n"
      "@p bra LOOP;\n"
      "DONE:\n}" ::"r"(a), "r"(parity) : "memory");
}
#define HINT 1
template <int NS>
__device__ __forceinline__ void mbar_wait_ns(uint32_t a, uint32_t parity) {
  asm volatile(
      "{\n.reg .pred p;\n.reg .u32 n;\n"
      "mov.u32 n, 0;\n"
      "LOOP:\n"
      "mbarrier.try_wait.parity.shared::cta.b64 p, [%0], %1, %2;\n"
      "@p bra DONE;\n"
      "add.u32 n, n, 1;\n"
      "setp.lt.u32 p, n, " SPIN_LIMIT ";\n"
      "@p bra LOOP;\n"
      "DONE:\n}" ::"r"(a), "r"(parity), "n"(NS) : "memory");
}
__device__ __forceinline__ void mbar_wait2(uint32_t a, uint32_t pa, uint32_t b, uint32_t pb) {
  asm volatile(
      "{\n.reg .pred p, q;\n.reg .u32 n;\n"
      "mov.u32 n, 0;\n"
      "LOOP:\n"
      "mbarrier.try_wait.parity.shared::cta.b64 p, [%0], %1;\n"
      "mbarrier.try_wait.parity.shared::cta.b64 q, [%2], %3;\n"
      "add.u32 n, n, 1;\n"
      "and.pred p, p, q;\n"
      "setp.lt.and.u32 p, n, " SPIN_LIMIT ", !p;\n"
      "@p bra LOOP;\n"
      "}" ::"r"(a), "r"(pa), "r"(b), "r"(pb) : "memory");
}
__device__ __forceinline__ uint32_t mbar_test(uint32_t a, uint32_t parity) {
  uint32_t r;
  asm volatile("{\n.reg .pred p;\nmbarrier.test_wait.parity.shared::cta.b64 p, [%1], %2;\nselp.u32 %0, 1, 0, p;\n}" : "=r"(r) : "r"(a), "r"(parity) : "memory");
  return r;
}
__device__ __forceinline__ void mbar_arrive(uint32_t a) {
  asm volatile("mbarrier.arrive.shared::cta.b64 _, [%0];" ::"r"(a) : "memory");
}
__device__ __forceinline__ void mbar_arrive_cluster(uint32_t a, uint32_t cta) {
  asm volatile("{\n.reg .b32 r;\nmapa.shared::cluster.u32 r, %0, %1;\nmbarrier.arrive.shared::cluster.b64 _, [r];\n}" ::"r"(a),
               "r"(cta) : "memory");
}
__device__ __forceinline__ void mbar_arrive_cluster_if(uint32_t a, uint32_t cta, bool pred) {
  asm volatile("{\n.reg .b32 r;\n.reg .pred p;\nsetp.ne.u32 p, %2, 0;\nmapa.shared::cluster.u32 r, %0, %1;\n@p mbarrier.arrive.shared::cluster.b64 _, [r];\n}" ::"r"(a),
               "r"(cta), "r"((uint32_t)pred) : "memory");
}
__device__ __forceinline__ void mbar_arrive_cluster_after(uint32_t a, uint32_t cta, bool pred, float anchor) {
  asm volatile("{\n.reg .b32 r;\n.reg .pred p;\nsetp.ne.u32 p, %2, 0;\nsetp.leu.and.f32 p, %3, 0f7F800000, p;\n"
               "mapa.shared::cluster.u32 r, %0, %1;\n@p mbarrier.arrive.shared::cluster.b64 _, [r];\n}" ::"r"(a),
               "r"(cta), "r"((uint32_t)pred), "f"(anchor) : "memory");
}
__device__ __forceinline__ void anchor(float v, uint32_t pred) {
  asm volatile("{\n.reg .pred p;\nsetp.ne.u32 p, %1, 0;\n@p st.shared.f32 [%1], %0;\n}" ::"f"(v), "r"(pred) : "memory");
}
__device__ __forceinline__ void mbar_arrive_if(uint32_t a, bool pred) {
  asm volatile("{\n.reg .pred p;\nsetp.ne.u32 p, %1, 0;\n@p mbarrier.arrive.shared::cta.b64 _, [%0];\n}" ::"r"(a), "r"((uint32_t)pred) : "memory");
}
__device__ __forceinline__ void tma2d(uint32_t dst, const CUtensorMap* m, uint32_t bar, int c0, int c1) {
  asm volatile("cp.async.bulk.tensor.2d.shared::cluster.global.mbarrier::complete_tx::bytes [%0], [%1, {%3, %4}], [%2];" ::"r"(dst),
               "l"(m), "r"(bar), "r"(c0), "r"(c1) : "memory");
}
__device__ __forceinline__ void tma2d_mc(uint32_t dst, const CUtensorMap* m, uint32_t bar, int c0, int c1, uint16_t mask) {
  asm volatile(
      "cp.async.bulk.tensor.2d.shared::cluster.global.mbarrier::complete_tx::bytes.multicast::cluster [%0], [%1, {%3, %4}], [%2], %5;" ::"r"(dst),
      "l"(m), "r"(bar), "r"(c0), "r"(c1), "h"(mask) : "memory");
}
__device__ __forceinline__ void tma3d_mc(uint32_t dst, const CUtensorMap* m, uint32_t bar, int c0, int c1, int c2, uint16_t mask) {
  asm volatile(
      "cp.async.bulk.tensor.3d.shared::cluster.global.mbarrier::complete_tx::bytes.multicast::cluster [%0], [%1, {%3, %4, %5}], [%2], %6;" ::"r"(dst),
      "l"(m), "r"(bar), "r"(c0), "r"(c1), "r"(c2), "h"(mask) : "memory");
}
__device__ __forceinline__ uint64_t policy_evict_first() {
  uint64_t p;
  asm volatile("createpolicy.fractional.L2::evict_first.b64 %0, 1.0;" : "=l"(p));
  return p;
}
__device__ __forceinline__ void tma3d_mc_h(uint32_t dst, const CUtensorMap* m, uint32_t bar, int c0, int c1, int c2, uint16_t mask, uint64_t pol) {
  asm volatile(
      "cp.async.bulk.tensor.3d.shared::cluster.global.mbarrier::complete_tx::bytes.multicast::cluster.L2::cache_hint [%0], [%1, {%3, %4, %5}], [%2], %6, %7;" ::"r"(dst),
      "l"(m), "r"(bar), "r"(c0), "r"(c1), "r"(c2), "h"(mask), "l"(pol) : "memory");
}
__device__ __forceinline__ void tma2d_h(uint32_t dst, const CUtensorMap* m, uint32_t bar, int c0, int c1, uint64_t pol) {
  asm volatile("cp.async.bulk.tensor.2d.shared::cluster.global.mbarrier::complete_tx::bytes.L2::cache_hint [%0], [%1, {%3, %4}], [%2], %5;" ::"r"(dst),
               "l"(m), "r"(bar), "r"(c0), "r"(c1), "l"(pol) : "memory");
}
__device__ __forceinline__ void tma3d(uint32_t dst, const CUtensorMap* m, uint32_t bar, int c0, int c1, int c2) {
  asm volatile(
      "cp.async.bulk.tensor.3d.shared::cluster.global.mbarrier::complete_tx::bytes [%0], [%1, {%3, %4, %5}], [%2];" ::"r"(dst),
      "l"(m), "r"(bar), "r"(c0), "r"(c1), "r"(c2) : "memory");
}
__device__ __forceinline__ void tma_pf2d(const CUtensorMap* m, int c0, int c1) {
  asm volatile("cp.async.bulk.prefetch.tensor.2d.L2.global [%0, {%1, %2}];" ::"l"(m), "r"(c0), "r"(c1) : "memory");
}
__device__ __forceinline__ void tma_pf3d(const CUtensorMap* m, int c0, int c1, int c2) {
  asm volatile("cp.async.bulk.prefetch.tensor.3d.L2.global [%0, {%1, %2, %3}];" ::"l"(m), "r"(c0), "r"(c1), "r"(c2) : "memory");
}
__device__ __forceinline__ void prefetch_tmap(const CUtensorMap* m) {
  asm volatile("prefetch.tensormap [%0];" ::"l"(m) : "memory");
}
__device__ __forceinline__ void cluster_arrive() { asm volatile("barrier.cluster.arrive.relaxed.aligned;" ::: "memory"); }
__device__ __forceinline__ void cluster_wait() { asm volatile("barrier.cluster.wait.aligned;" ::: "memory"); }
__device__ __forceinline__ void cluster_sync() {
  cluster_arrive();
  cluster_wait();
}
__device__ __forceinline__ uint32_t cluster_rank() {
  uint32_t r;
  asm volatile("mov.u32 %0, %%cluster_ctarank;" : "=r"(r));
  return r;
}
__device__ __forceinline__ bool elect_one() {
  uint32_t p;
  asm volatile("{\n.reg .pred q;\nelect.sync _|q, 0xffffffff;\nselp.u32 %0, 1, 0, q;\n}" : "=r"(p));
  return p;
}
__device__ __forceinline__ void pdl_wait() { asm volatile("griddepcontrol.wait;" ::: "memory"); }
__device__ __forceinline__ void pdl_launch() { asm volatile("griddepcontrol.launch_dependents;" ::: "memory"); }
__device__ __forceinline__ void ldsm_x4(uint32_t& r0, uint32_t& r1, uint32_t& r2, uint32_t& r3, uint32_t addr) {
  asm volatile("ldmatrix.sync.aligned.m8n8.x4.shared.b16 {%0, %1, %2, %3}, [%4];" : "=r"(r0), "=r"(r1), "=r"(r2), "=r"(r3) : "r"(addr) : "memory");
}
__device__ __forceinline__ void wg_fence() { asm volatile("wgmma.fence.sync.aligned;" ::: "memory"); }
__device__ __forceinline__ void wg_commit() { asm volatile("wgmma.commit_group.sync.aligned;" ::: "memory"); }
template <int N>
__device__ __forceinline__ void wg_wait() { asm volatile("wgmma.wait_group.sync.aligned %0;" ::"n"(N) : "memory"); }
template <int N>
__device__ __forceinline__ void reg_alloc() { asm volatile("setmaxnreg.inc.sync.aligned.u32 %0;" ::"n"(N)); }
template <int N>
__device__ __forceinline__ void reg_dealloc() { asm volatile("setmaxnreg.dec.sync.aligned.u32 %0;" ::"n"(N)); }
__device__ __forceinline__ void bar_sync(int id, int n) { asm volatile("bar.sync %0, %1;" ::"r"(id), "r"(n) : "memory"); }
__device__ __forceinline__ void bar_arrive(int id, int n) { asm volatile("bar.arrive %0, %1;" ::"r"(id), "r"(n) : "memory"); }
template <int NT>
__device__ __forceinline__ void fence_regs(float (&d)[NT]) {
#pragma unroll
  for (int i = 0; i < NT; i++) asm volatile("" : "+f"(d[i])::"memory");
}
template <int NT>
__device__ __forceinline__ void fence_regs(uint32_t (&d)[NT]) {
#pragma unroll
  for (int i = 0; i < NT; i++) asm volatile("" : "+r"(d[i])::"memory");
}
__device__ __forceinline__ uint64_t make_desc(uint32_t saddr, uint32_t lbo, uint32_t sbo, uint32_t layout) {
  return (uint64_t)((saddr & 0x3FFFF) >> 4) | ((uint64_t)(lbo >> 4) << 16) | ((uint64_t)(sbo >> 4) << 32) | ((uint64_t)layout << 62);
}
__device__ __forceinline__ uint32_t pack_bf16(float lo, float hi) {
  uint32_t r;
  asm("cvt.rn.bf16x2.f32 %0, %1, %2;" : "=r"(r) : "f"(hi), "f"(lo));
  return r;
}
__device__ __forceinline__ float ex2(float x) {
  float r;
  asm("ex2.approx.ftz.f32 %0, %1;" : "=f"(r) : "f"(x));
  return r;
}
__device__ __forceinline__ void st_v4(void* p, uint32_t a, uint32_t b, uint32_t c, uint32_t d) {
#define ST_MOD ".cs"
  asm volatile("st.global" ST_MOD ".v4.b32 [%0], {%1, %2, %3, %4};" ::"l"(p), "r"(a), "r"(b), "r"(c), "r"(d) : "memory");
}
#define STA_MOD ".cs"
__device__ __forceinline__ void st_v4a(void* p, uint32_t a, uint32_t b, uint32_t c, uint32_t d) {
  asm volatile("st.global" STA_MOD ".v4.b32 [%0], {%1, %2, %3, %4};" ::"l"(p), "r"(a), "r"(b), "r"(c), "r"(d) : "memory");
}
__device__ __forceinline__ float bf_lo(uint32_t v) { return __uint_as_float(v << 16); }
__device__ __forceinline__ float bf_hi(uint32_t v) { return __uint_as_float(v & 0xFFFF0000u); }

__device__ __forceinline__ void quad_transpose(uint32_t& a0, uint32_t& a1, uint32_t& a2, uint32_t& a3, int q) {
  const bool o1 = q & 1, o2 = q & 2;
  uint32_t t0 = o1 ? a0 : a1, t1 = o1 ? a2 : a3;
  t0 = __shfl_xor_sync(0xffffffffu, t0, 1);
  t1 = __shfl_xor_sync(0xffffffffu, t1, 1);
  if (o1) { a0 = t0; a2 = t1; } else { a1 = t0; a3 = t1; }
  t0 = o2 ? a0 : a2;
  t1 = o2 ? a1 : a3;
  t0 = __shfl_xor_sync(0xffffffffu, t0, 2);
  t1 = __shfl_xor_sync(0xffffffffu, t1, 2);
  if (o2) { a0 = t0; a1 = t1; } else { a2 = t0; a3 = t1; }
}

template<int TB, int OFF, int NT>
__device__ __forceinline__ void wgmma_ss_n256(float (&d)[NT], uint64_t da, uint64_t db, int scale_d) {
  asm volatile("{\n.reg .pred p;\nsetp.ne.b32 p, %130, 0;\n"
    "wgmma.mma_async.sync.aligned.m64n256k16.f32.bf16.bf16 {%0, %1, %2, %3, %4, %5, %6, %7, %8, %9, %10, %11, %12, %13, %14, %15, %16, %17, %18, %19, %20, %21, %22, %23, %24, %25, %26, %27, %28, %29, %30, %31, %32, %33, %34, %35, %36, %37, %38, %39, %40, %41, %42, %43, %44, %45, %46, %47, %48, %49, %50, %51, %52, %53, %54, %55, %56, %57, %58, %59, %60, %61, %62, %63, %64, %65, %66, %67, %68, %69, %70, %71, %72, %73, %74, %75, %76, %77, %78, %79, %80, %81, %82, %83, %84, %85, %86, %87, %88, %89, %90, %91, %92, %93, %94, %95, %96, %97, %98, %99, %100, %101, %102, %103, %104, %105, %106, %107, %108, %109, %110, %111, %112, %113, %114, %115, %116, %117, %118, %119, %120, %121, %122, %123, %124, %125, %126, %127}, %128, %129, p, 1, 1, 0, %131;\n}\n"
    : "+f"(d[OFF+0]), "+f"(d[OFF+1]), "+f"(d[OFF+2]), "+f"(d[OFF+3]), "+f"(d[OFF+4]), "+f"(d[OFF+5]), "+f"(d[OFF+6]), "+f"(d[OFF+7]), "+f"(d[OFF+8]), "+f"(d[OFF+9]), "+f"(d[OFF+10]), "+f"(d[OFF+11]), "+f"(d[OFF+12]), "+f"(d[OFF+13]), "+f"(d[OFF+14]), "+f"(d[OFF+15]), "+f"(d[OFF+16]), "+f"(d[OFF+17]), "+f"(d[OFF+18]), "+f"(d[OFF+19]), "+f"(d[OFF+20]), "+f"(d[OFF+21]), "+f"(d[OFF+22]), "+f"(d[OFF+23]), "+f"(d[OFF+24]), "+f"(d[OFF+25]), "+f"(d[OFF+26]), "+f"(d[OFF+27]), "+f"(d[OFF+28]), "+f"(d[OFF+29]), "+f"(d[OFF+30]), "+f"(d[OFF+31]), "+f"(d[OFF+32]), "+f"(d[OFF+33]), "+f"(d[OFF+34]), "+f"(d[OFF+35]), "+f"(d[OFF+36]), "+f"(d[OFF+37]), "+f"(d[OFF+38]), "+f"(d[OFF+39]), "+f"(d[OFF+40]), "+f"(d[OFF+41]), "+f"(d[OFF+42]), "+f"(d[OFF+43]), "+f"(d[OFF+44]), "+f"(d[OFF+45]), "+f"(d[OFF+46]), "+f"(d[OFF+47]), "+f"(d[OFF+48]), "+f"(d[OFF+49]), "+f"(d[OFF+50]), "+f"(d[OFF+51]), "+f"(d[OFF+52]), "+f"(d[OFF+53]), "+f"(d[OFF+54]), "+f"(d[OFF+55]), "+f"(d[OFF+56]), "+f"(d[OFF+57]), "+f"(d[OFF+58]), "+f"(d[OFF+59]), "+f"(d[OFF+60]), "+f"(d[OFF+61]), "+f"(d[OFF+62]), "+f"(d[OFF+63]), "+f"(d[OFF+64]), "+f"(d[OFF+65]), "+f"(d[OFF+66]), "+f"(d[OFF+67]), "+f"(d[OFF+68]), "+f"(d[OFF+69]), "+f"(d[OFF+70]), "+f"(d[OFF+71]), "+f"(d[OFF+72]), "+f"(d[OFF+73]), "+f"(d[OFF+74]), "+f"(d[OFF+75]), "+f"(d[OFF+76]), "+f"(d[OFF+77]), "+f"(d[OFF+78]), "+f"(d[OFF+79]), "+f"(d[OFF+80]), "+f"(d[OFF+81]), "+f"(d[OFF+82]), "+f"(d[OFF+83]), "+f"(d[OFF+84]), "+f"(d[OFF+85]), "+f"(d[OFF+86]), "+f"(d[OFF+87]), "+f"(d[OFF+88]), "+f"(d[OFF+89]), "+f"(d[OFF+90]), "+f"(d[OFF+91]), "+f"(d[OFF+92]), "+f"(d[OFF+93]), "+f"(d[OFF+94]), "+f"(d[OFF+95]), "+f"(d[OFF+96]), "+f"(d[OFF+97]), "+f"(d[OFF+98]), "+f"(d[OFF+99]), "+f"(d[OFF+100]), "+f"(d[OFF+101]), "+f"(d[OFF+102]), "+f"(d[OFF+103]), "+f"(d[OFF+104]), "+f"(d[OFF+105]), "+f"(d[OFF+106]), "+f"(d[OFF+107]), "+f"(d[OFF+108]), "+f"(d[OFF+109]), "+f"(d[OFF+110]), "+f"(d[OFF+111]), "+f"(d[OFF+112]), "+f"(d[OFF+113]), "+f"(d[OFF+114]), "+f"(d[OFF+115]), "+f"(d[OFF+116]), "+f"(d[OFF+117]), "+f"(d[OFF+118]), "+f"(d[OFF+119]), "+f"(d[OFF+120]), "+f"(d[OFF+121]), "+f"(d[OFF+122]), "+f"(d[OFF+123]), "+f"(d[OFF+124]), "+f"(d[OFF+125]), "+f"(d[OFF+126]), "+f"(d[OFF+127])
    : "l"(da), "l"(db), "r"(scale_d), "n"(TB));
}
template<int TB, int OFF, int NT>
__device__ __forceinline__ void wgmma_ss_n192(float (&d)[NT], uint64_t da, uint64_t db, int scale_d) {
  asm volatile("{\n.reg .pred p;\nsetp.ne.b32 p, %98, 0;\n"
    "wgmma.mma_async.sync.aligned.m64n192k16.f32.bf16.bf16 {%0, %1, %2, %3, %4, %5, %6, %7, %8, %9, %10, %11, %12, %13, %14, %15, %16, %17, %18, %19, %20, %21, %22, %23, %24, %25, %26, %27, %28, %29, %30, %31, %32, %33, %34, %35, %36, %37, %38, %39, %40, %41, %42, %43, %44, %45, %46, %47, %48, %49, %50, %51, %52, %53, %54, %55, %56, %57, %58, %59, %60, %61, %62, %63, %64, %65, %66, %67, %68, %69, %70, %71, %72, %73, %74, %75, %76, %77, %78, %79, %80, %81, %82, %83, %84, %85, %86, %87, %88, %89, %90, %91, %92, %93, %94, %95}, %96, %97, p, 1, 1, 0, %99;\n}\n"
    : "+f"(d[OFF+0]), "+f"(d[OFF+1]), "+f"(d[OFF+2]), "+f"(d[OFF+3]), "+f"(d[OFF+4]), "+f"(d[OFF+5]), "+f"(d[OFF+6]), "+f"(d[OFF+7]), "+f"(d[OFF+8]), "+f"(d[OFF+9]), "+f"(d[OFF+10]), "+f"(d[OFF+11]), "+f"(d[OFF+12]), "+f"(d[OFF+13]), "+f"(d[OFF+14]), "+f"(d[OFF+15]), "+f"(d[OFF+16]), "+f"(d[OFF+17]), "+f"(d[OFF+18]), "+f"(d[OFF+19]), "+f"(d[OFF+20]), "+f"(d[OFF+21]), "+f"(d[OFF+22]), "+f"(d[OFF+23]), "+f"(d[OFF+24]), "+f"(d[OFF+25]), "+f"(d[OFF+26]), "+f"(d[OFF+27]), "+f"(d[OFF+28]), "+f"(d[OFF+29]), "+f"(d[OFF+30]), "+f"(d[OFF+31]), "+f"(d[OFF+32]), "+f"(d[OFF+33]), "+f"(d[OFF+34]), "+f"(d[OFF+35]), "+f"(d[OFF+36]), "+f"(d[OFF+37]), "+f"(d[OFF+38]), "+f"(d[OFF+39]), "+f"(d[OFF+40]), "+f"(d[OFF+41]), "+f"(d[OFF+42]), "+f"(d[OFF+43]), "+f"(d[OFF+44]), "+f"(d[OFF+45]), "+f"(d[OFF+46]), "+f"(d[OFF+47]), "+f"(d[OFF+48]), "+f"(d[OFF+49]), "+f"(d[OFF+50]), "+f"(d[OFF+51]), "+f"(d[OFF+52]), "+f"(d[OFF+53]), "+f"(d[OFF+54]), "+f"(d[OFF+55]), "+f"(d[OFF+56]), "+f"(d[OFF+57]), "+f"(d[OFF+58]), "+f"(d[OFF+59]), "+f"(d[OFF+60]), "+f"(d[OFF+61]), "+f"(d[OFF+62]), "+f"(d[OFF+63]), "+f"(d[OFF+64]), "+f"(d[OFF+65]), "+f"(d[OFF+66]), "+f"(d[OFF+67]), "+f"(d[OFF+68]), "+f"(d[OFF+69]), "+f"(d[OFF+70]), "+f"(d[OFF+71]), "+f"(d[OFF+72]), "+f"(d[OFF+73]), "+f"(d[OFF+74]), "+f"(d[OFF+75]), "+f"(d[OFF+76]), "+f"(d[OFF+77]), "+f"(d[OFF+78]), "+f"(d[OFF+79]), "+f"(d[OFF+80]), "+f"(d[OFF+81]), "+f"(d[OFF+82]), "+f"(d[OFF+83]), "+f"(d[OFF+84]), "+f"(d[OFF+85]), "+f"(d[OFF+86]), "+f"(d[OFF+87]), "+f"(d[OFF+88]), "+f"(d[OFF+89]), "+f"(d[OFF+90]), "+f"(d[OFF+91]), "+f"(d[OFF+92]), "+f"(d[OFF+93]), "+f"(d[OFF+94]), "+f"(d[OFF+95])
    : "l"(da), "l"(db), "r"(scale_d), "n"(TB));
}
template<int TB, int OFF, int NT>
__device__ __forceinline__ void wgmma_ss_n128(float (&d)[NT], uint64_t da, uint64_t db, int scale_d) {
  asm volatile("{\n.reg .pred p;\nsetp.ne.b32 p, %66, 0;\n"
    "wgmma.mma_async.sync.aligned.m64n128k16.f32.bf16.bf16 {%0, %1, %2, %3, %4, %5, %6, %7, %8, %9, %10, %11, %12, %13, %14, %15, %16, %17, %18, %19, %20, %21, %22, %23, %24, %25, %26, %27, %28, %29, %30, %31, %32, %33, %34, %35, %36, %37, %38, %39, %40, %41, %42, %43, %44, %45, %46, %47, %48, %49, %50, %51, %52, %53, %54, %55, %56, %57, %58, %59, %60, %61, %62, %63}, %64, %65, p, 1, 1, 0, %67;\n}\n"
    : "+f"(d[OFF+0]), "+f"(d[OFF+1]), "+f"(d[OFF+2]), "+f"(d[OFF+3]), "+f"(d[OFF+4]), "+f"(d[OFF+5]), "+f"(d[OFF+6]), "+f"(d[OFF+7]), "+f"(d[OFF+8]), "+f"(d[OFF+9]), "+f"(d[OFF+10]), "+f"(d[OFF+11]), "+f"(d[OFF+12]), "+f"(d[OFF+13]), "+f"(d[OFF+14]), "+f"(d[OFF+15]), "+f"(d[OFF+16]), "+f"(d[OFF+17]), "+f"(d[OFF+18]), "+f"(d[OFF+19]), "+f"(d[OFF+20]), "+f"(d[OFF+21]), "+f"(d[OFF+22]), "+f"(d[OFF+23]), "+f"(d[OFF+24]), "+f"(d[OFF+25]), "+f"(d[OFF+26]), "+f"(d[OFF+27]), "+f"(d[OFF+28]), "+f"(d[OFF+29]), "+f"(d[OFF+30]), "+f"(d[OFF+31]), "+f"(d[OFF+32]), "+f"(d[OFF+33]), "+f"(d[OFF+34]), "+f"(d[OFF+35]), "+f"(d[OFF+36]), "+f"(d[OFF+37]), "+f"(d[OFF+38]), "+f"(d[OFF+39]), "+f"(d[OFF+40]), "+f"(d[OFF+41]), "+f"(d[OFF+42]), "+f"(d[OFF+43]), "+f"(d[OFF+44]), "+f"(d[OFF+45]), "+f"(d[OFF+46]), "+f"(d[OFF+47]), "+f"(d[OFF+48]), "+f"(d[OFF+49]), "+f"(d[OFF+50]), "+f"(d[OFF+51]), "+f"(d[OFF+52]), "+f"(d[OFF+53]), "+f"(d[OFF+54]), "+f"(d[OFF+55]), "+f"(d[OFF+56]), "+f"(d[OFF+57]), "+f"(d[OFF+58]), "+f"(d[OFF+59]), "+f"(d[OFF+60]), "+f"(d[OFF+61]), "+f"(d[OFF+62]), "+f"(d[OFF+63])
    : "l"(da), "l"(db), "r"(scale_d), "n"(TB));
}
template<int TB, int OFF, int NT>
__device__ __forceinline__ void wgmma_ss_n32(float (&d)[NT], uint64_t da, uint64_t db, int scale_d) {
  asm volatile("{\n.reg .pred p;\nsetp.ne.b32 p, %18, 0;\n"
    "wgmma.mma_async.sync.aligned.m64n32k16.f32.bf16.bf16 {%0, %1, %2, %3, %4, %5, %6, %7, %8, %9, %10, %11, %12, %13, %14, %15}, %16, %17, p, 1, 1, 0, %19;\n}\n"
    : "+f"(d[OFF+0]), "+f"(d[OFF+1]), "+f"(d[OFF+2]), "+f"(d[OFF+3]), "+f"(d[OFF+4]), "+f"(d[OFF+5]), "+f"(d[OFF+6]), "+f"(d[OFF+7]), "+f"(d[OFF+8]), "+f"(d[OFF+9]), "+f"(d[OFF+10]), "+f"(d[OFF+11]), "+f"(d[OFF+12]), "+f"(d[OFF+13]), "+f"(d[OFF+14]), "+f"(d[OFF+15])
    : "l"(da), "l"(db), "r"(scale_d), "n"(TB));
}
template<int TB, int OFF, int NT>
__device__ __forceinline__ void wgmma_rs_n128(float (&d)[NT], uint32_t a0, uint32_t a1, uint32_t a2, uint32_t a3, uint64_t db, int scale_d) {
  asm volatile("{\n.reg .pred p;\nsetp.ne.b32 p, %69, 0;\n"
    "wgmma.mma_async.sync.aligned.m64n128k16.f32.bf16.bf16 {%0, %1, %2, %3, %4, %5, %6, %7, %8, %9, %10, %11, %12, %13, %14, %15, %16, %17, %18, %19, %20, %21, %22, %23, %24, %25, %26, %27, %28, %29, %30, %31, %32, %33, %34, %35, %36, %37, %38, %39, %40, %41, %42, %43, %44, %45, %46, %47, %48, %49, %50, %51, %52, %53, %54, %55, %56, %57, %58, %59, %60, %61, %62, %63}, {%64, %65, %66, %67}, %68, p, 1, 1, %70;\n}\n"
    : "+f"(d[OFF+0]), "+f"(d[OFF+1]), "+f"(d[OFF+2]), "+f"(d[OFF+3]), "+f"(d[OFF+4]), "+f"(d[OFF+5]), "+f"(d[OFF+6]), "+f"(d[OFF+7]), "+f"(d[OFF+8]), "+f"(d[OFF+9]), "+f"(d[OFF+10]), "+f"(d[OFF+11]), "+f"(d[OFF+12]), "+f"(d[OFF+13]), "+f"(d[OFF+14]), "+f"(d[OFF+15]), "+f"(d[OFF+16]), "+f"(d[OFF+17]), "+f"(d[OFF+18]), "+f"(d[OFF+19]), "+f"(d[OFF+20]), "+f"(d[OFF+21]), "+f"(d[OFF+22]), "+f"(d[OFF+23]), "+f"(d[OFF+24]), "+f"(d[OFF+25]), "+f"(d[OFF+26]), "+f"(d[OFF+27]), "+f"(d[OFF+28]), "+f"(d[OFF+29]), "+f"(d[OFF+30]), "+f"(d[OFF+31]), "+f"(d[OFF+32]), "+f"(d[OFF+33]), "+f"(d[OFF+34]), "+f"(d[OFF+35]), "+f"(d[OFF+36]), "+f"(d[OFF+37]), "+f"(d[OFF+38]), "+f"(d[OFF+39]), "+f"(d[OFF+40]), "+f"(d[OFF+41]), "+f"(d[OFF+42]), "+f"(d[OFF+43]), "+f"(d[OFF+44]), "+f"(d[OFF+45]), "+f"(d[OFF+46]), "+f"(d[OFF+47]), "+f"(d[OFF+48]), "+f"(d[OFF+49]), "+f"(d[OFF+50]), "+f"(d[OFF+51]), "+f"(d[OFF+52]), "+f"(d[OFF+53]), "+f"(d[OFF+54]), "+f"(d[OFF+55]), "+f"(d[OFF+56]), "+f"(d[OFF+57]), "+f"(d[OFF+58]), "+f"(d[OFF+59]), "+f"(d[OFF+60]), "+f"(d[OFF+61]), "+f"(d[OFF+62]), "+f"(d[OFF+63])
    : "r"(a0), "r"(a1), "r"(a2), "r"(a3), "l"(db), "r"(scale_d), "n"(TB));
}
template<int TB, int OFF, int NT>
__device__ __forceinline__ void wgmma_rs_n64(float (&d)[NT], uint32_t a0, uint32_t a1, uint32_t a2, uint32_t a3, uint64_t db, int scale_d) {
  asm volatile("{\n.reg .pred p;\nsetp.ne.b32 p, %37, 0;\n"
    "wgmma.mma_async.sync.aligned.m64n64k16.f32.bf16.bf16 {%0, %1, %2, %3, %4, %5, %6, %7, %8, %9, %10, %11, %12, %13, %14, %15, %16, %17, %18, %19, %20, %21, %22, %23, %24, %25, %26, %27, %28, %29, %30, %31}, {%32, %33, %34, %35}, %36, p, 1, 1, %38;\n}\n"
    : "+f"(d[OFF+0]), "+f"(d[OFF+1]), "+f"(d[OFF+2]), "+f"(d[OFF+3]), "+f"(d[OFF+4]), "+f"(d[OFF+5]), "+f"(d[OFF+6]), "+f"(d[OFF+7]), "+f"(d[OFF+8]), "+f"(d[OFF+9]), "+f"(d[OFF+10]), "+f"(d[OFF+11]), "+f"(d[OFF+12]), "+f"(d[OFF+13]), "+f"(d[OFF+14]), "+f"(d[OFF+15]), "+f"(d[OFF+16]), "+f"(d[OFF+17]), "+f"(d[OFF+18]), "+f"(d[OFF+19]), "+f"(d[OFF+20]), "+f"(d[OFF+21]), "+f"(d[OFF+22]), "+f"(d[OFF+23]), "+f"(d[OFF+24]), "+f"(d[OFF+25]), "+f"(d[OFF+26]), "+f"(d[OFF+27]), "+f"(d[OFF+28]), "+f"(d[OFF+29]), "+f"(d[OFF+30]), "+f"(d[OFF+31])
    : "r"(a0), "r"(a1), "r"(a2), "r"(a3), "l"(db), "r"(scale_d), "n"(TB));
}

__device__ __forceinline__ void wait_flag(const unsigned int* f, uint32_t target) {
  uint32_t v;
#pragma unroll 1
  for (uint32_t spins = 0; spins < (1u << 22); spins++) {
    asm volatile("ld.acquire.gpu.global.u32 %0, [%1];" : "=r"(v) : "l"(f) : "memory");
    if (v >= target) break;
    __nanosleep(100);
  }
}
__device__ __forceinline__ uint32_t lds32(uint32_t a) {
  uint32_t v;
  asm volatile("ld.shared.u32 %0, [%1];" : "=r"(v) : "r"(a) : "memory");
  return v;
}
__device__ __forceinline__ float gate_row(int row, int lane, const bf16* __restrict__ x, const bf16* __restrict__ gate_w) {
  const uint32_t* xr = reinterpret_cast<const uint32_t*>(x + (size_t)row * DM);
  const uint32_t* gw2 = reinterpret_cast<const uint32_t*>(gate_w);
  float gs = 0.f;
#pragma unroll
  for (int i = 0; i < 9; i++) {
    const uint32_t a = __ldg(xr + lane + 32 * i), b = __ldg(gw2 + lane + 32 * i);
    gs = fmaf(bf_lo(a), bf_lo(b), gs);
    gs = fmaf(bf_hi(a), bf_hi(b), gs);
  }
#pragma unroll
  for (int o = 16; o; o >>= 1) gs += __shfl_xor_sync(0xffffffffu, gs, o);
  const float g = 1.f / (1.f + __expf(-gs));
  if (lane == 0) g_gate[row] = g;
  return g;
}
#define LA_UNROLL 9
__device__ __forceinline__ void local_rows2(int rb, int ri, uint32_t sL, uint32_t bL2, int lane, float ga, float gb) {
  const float scale_l2 = 0.23570226039551584f * 1.4426950408889634f;
  constexpr int U = LA_UNROLL;
  const uint32_t sq = sL + (30 + ri) * 1152;
  uint32_t kb[9];
#pragma unroll
  for (int i = 0; i < 9; i++) {
    const uint32_t c = lane * 9 + i;
    kb[i] = sL + (14 + ri) * 1152 + ((c & ~15u) | ((c & 3) << 2) | ((c >> 2) & 3)) * 4;
  }
  float ma = -INFINITY, mb = -INFINITY;
  {
    float qa[18], qb[18];
#pragma unroll
    for (int i = 0; i < 9; i++) {
      const uint32_t u = lds32(kb[i] + 16 * 1152 - 2304), v = lds32(kb[i] + 16 * 1152);
      qa[2 * i] = bf_lo(u); qa[2 * i + 1] = bf_hi(u);
      qb[2 * i] = bf_lo(v); qb[2 * i + 1] = bf_hi(v);
    }
    __syncwarp();
#pragma unroll U
    for (int t = 0; t < 9; t++) {
      const bool ok = rb - 2 * t >= 0;
      float a0 = 0.f, a1 = 0.f, b0 = 0.f, b1 = 0.f;
#pragma unroll
      for (int i = 0; i < 9; i++) {
        const uint32_t k = lds32(kb[i] - t * 2304);
        const float lo = bf_lo(k), hi = bf_hi(k);
        a0 = fmaf(qa[2 * i], lo, a0); a1 = fmaf(qa[2 * i + 1], hi, a1);
        b0 = fmaf(qb[2 * i], lo, b0); b1 = fmaf(qb[2 * i + 1], hi, b1);
      }
      a0 = (ok && t > 0) ? a0 + a1 : -INFINITY;
      b0 = (ok && t < 8) ? b0 + b1 : -INFINITY;
      ma = fmaxf(ma, a0);
      mb = fmaxf(mb, b0);
      asm volatile("st.shared.f32 [%0], %1;" ::"r"(sq - 2304 + t * 128 + lane * 4), "f"(a0) : "memory");
      asm volatile("st.shared.f32 [%0], %1;" ::"r"(sq + t * 128 + lane * 4), "f"(b0) : "memory");
    }
  }
  float oa[18], ob[18], sa = 0.f, sb = 0.f;
#pragma unroll
  for (int i = 0; i < 18; i++) { oa[i] = 0.f; ob[i] = 0.f; }
  mbar_wait(bL2, 0);
#pragma unroll U
  for (int t = 0; t < 9; t++) {
    const float wa = ex2((__uint_as_float(lds32(sq - 2304 + t * 128 + lane * 4)) - ma) * scale_l2);
    const float wb = ex2((__uint_as_float(lds32(sq + t * 128 + lane * 4)) - mb) * scale_l2);
    sa += wa;
    sb += wb;
#pragma unroll
    for (int i = 0; i < 9; i++) {
      const uint32_t v = lds32(kb[i] + 46 * 1152 - t * 2304);
      const float lo = bf_lo(v), hi = bf_hi(v);
      oa[2 * i] = fmaf(wa, lo, oa[2 * i]); oa[2 * i + 1] = fmaf(wa, hi, oa[2 * i + 1]);
      ob[2 * i] = fmaf(wb, lo, ob[2 * i]); ob[2 * i + 1] = fmaf(wb, hi, ob[2 * i + 1]);
    }
  }
  ga = __fdividef(ga, sa);
  gb = __fdividef(gb, sb);
  __syncwarp();
#pragma unroll
  for (int i = 0; i < 9; i++) {
    asm volatile("st.shared.u32 [%0], %1;" ::"r"(sq - 2304 + lane * 36 + 4 * i), "r"(pack_bf16(oa[2 * i] * ga, oa[2 * i + 1] * ga)) : "memory");
    asm volatile("st.shared.u32 [%0], %1;" ::"r"(sq + lane * 36 + 4 * i), "r"(pack_bf16(ob[2 * i] * gb, ob[2 * i + 1] * gb)) : "memory");
  }
  __syncwarp();
  uint32_t w[5][4];
#pragma unroll
  for (int t = 0; t < 5; t++) {
    const int c = min(t * 32 + lane, 143), r = c >= 72;
    asm volatile("ld.shared.v4.u32 {%0, %1, %2, %3}, [%4];" : "=r"(w[t][0]), "=r"(w[t][1]), "=r"(w[t][2]), "=r"(w[t][3])
                 : "r"(sq - 2304 + r * 2304 + (c - r * 72) * 16) : "memory");
  }
  asm volatile("fence.proxy.async.shared::cta;" ::: "memory");
  bar_arrive(4, 256 + 32);
#pragma unroll
  for (int t = 0; t < 5; t++) {
    const int c = min(t * 32 + lane, 143), r = c >= 72;
    st_v4(g_ctx + (size_t)(rb - 2 + 2 * r) * KCAT + HDIM + (c - r * 72) * 8, w[t][0], w[t][1], w[t][2], w[t][3]);
  }
}

#define K1_NST 6
constexpr int K1_BST = K1_NST;
constexpr int K1_MAXJOBS = 11;
constexpr uint32_t K1_FLAG_TARGET = 7;
constexpr uint32_t RDY_TARGET = 48;
constexpr uint32_t GATE_TARGET = 128 * 3;
struct alignas(64) Params {
  CUtensorMap tmA[2];
  CUtensorMap tmW[4];
  CUtensorMap tmQ, tmK, tmV;
  CUtensorMap tmL[2];
  CUtensorMap tmC, tmO[2], tmOt[2];
  uint16_t jobs[NCLUSTER][K1_MAXJOBS + 1];
  uint8_t order[256];
  uint8_t unit[64][8];
};

struct K1State {
  uint32_t bs, bph, aph;
  bf16* pp;
  int pld8;
  int png;
  int tn;
};
__device__ __forceinline__ void k1_flag(const K1State& st, int lane, uint32_t bS) {
  if (st.png) {
    __syncwarp();
    if (lane == 0) mbar_arrive(bS);
  }
}

__device__ __forceinline__ void k1_first(const K1State& st, uint32_t job, uint32_t bAf, uint32_t bBf) {
  if (job & 3) {
    if ((job >> 14) & 1) mbar_wait(bAf, st.aph);
    mbar_wait(bBf + st.bs * 8, st.bph);
  }
}
__device__ __forceinline__ void k1_tile(float (&acc)[128], uint32_t (&pk)[64], K1State& st, uint32_t job, uint32_t njob, uint32_t sA, uint32_t sB,
                                        uint32_t bAf, uint32_t bAe, uint32_t bBf, uint32_t bBe, uint32_t bS, int wg, int warp, int lane, uint32_t rank) {
  const int a_sel = (job >> 2) & 1, mpair = (job >> 3) & 7, w_sel = (job >> 6) & 3, chunk0 = (job >> 8) & 63;
  const bool newA = (job >> 14) & 1, lastA = (job >> 15) & 1;
  const bool sig = (lane == 0) && (warp < 2);
  const bool siga = lastA && (lane == 0) && (warp == 2);
  const int KC = 8 + a_sel;
  uint32_t prev_bs = 0, a8_bs = 0;
#pragma unroll
  for (int kc = 0; kc < 9; kc++) {
    if (kc >= KC) break;
    uint32_t abase = sA + ((kc + 2) & 7) * 16384;
    if (kc == 8) {
      mbar_wait(bBf + st.bs * 8, st.bph);
      a8_bs = st.bs;
      abase = sB + st.bs * 16384;
      if (++st.bs == K1_BST) { st.bs = 0; st.bph ^= 1; }
    } else if (newA && kc > 0) {
      mbar_wait(bAf + kc * 8, st.aph);
    }
    const uint64_t da = make_desc(abase + wg * 8192, 16, 1024, 1);
#pragma unroll
    for (int ks = 0; ks < 2; ks++) {
      if (ks > 0 || kc > 0) mbar_wait(bBf + st.bs * 8, st.bph);
      const uint64_t db = make_desc(sB + st.bs * 16384, 2048, 1024, 1);
      wg_fence();
      wgmma_ss_n256<1, 0>(acc, da + (uint64_t)(ks * 4), db, (ks > 0) ? 1 : (kc > 0));
      wgmma_ss_n256<1, 0>(acc, da + (uint64_t)(ks * 4 + 2), db + (uint64_t)512, 1);
      wg_commit();
      const int PO = (kc < 8 ? kc : 0) * 8;
      wg_wait<1>();
      if (ks > 0 || kc > 0) {
        if (sig) mbar_arrive_cluster(bBe + prev_bs * 8, warp);
        if (ks == 0 && siga) mbar_arrive(bAe + (kc - 1) * 8);
      }
      if (kc < st.png) st_v4a(st.pp + kc * 32 + ks * st.pld8, pk[PO + ks * 4], pk[PO + ks * 4 + 1], pk[PO + ks * 4 + 2], pk[PO + ks * 4 + 3]);
      prev_bs = st.bs;
      if (++st.bs == K1_BST) { st.bs = 0; st.bph ^= 1; }
    }
  }
  if (newA) st.aph ^= 1;
  k1_flag(st, lane, bS);
  const bool isA = (w_sel == 2);
  bf16* out = (w_sel == 0) ? g_K : (w_sel == 1) ? g_V : isA ? g_QKVA : g_Q;
  const int ld = isA ? NQKVA : HDIM;
  const int row = mpair * 256 + rank * 128 + wg * 64 + warp * 16 + (lane >> 2);
  st.pp = out + (size_t)row * ld + chunk0 * 64 + (lane & 3) * 8;
  st.pld8 = 8 * ld;
  st.png = ((job & 3) + 1) * 2;
  k1_first(st, njob, bAf, bBf);
  wg_wait<0>();
  fence_regs(acc);
  mbar_arrive_cluster_if(bBe + prev_bs * 8, warp & 1, sig);
  mbar_arrive_cluster_if(bBe + a8_bs * 8, warp & 1, sig && a_sel);
  mbar_arrive_if(bAe + 7 * 8, siga && !a_sel);
#pragma unroll
  for (int G = 0; G < 8; G++) {
    pk[G * 8 + 0] = pack_bf16(acc[G * 16 + 0], acc[G * 16 + 1]);
    pk[G * 8 + 1] = pack_bf16(acc[G * 16 + 4], acc[G * 16 + 5]);
    pk[G * 8 + 2] = pack_bf16(acc[G * 16 + 8], acc[G * 16 + 9]);
    pk[G * 8 + 3] = pack_bf16(acc[G * 16 + 12], acc[G * 16 + 13]);
    pk[G * 8 + 4] = pack_bf16(acc[G * 16 + 2], acc[G * 16 + 3]);
    pk[G * 8 + 5] = pack_bf16(acc[G * 16 + 6], acc[G * 16 + 7]);
    pk[G * 8 + 6] = pack_bf16(acc[G * 16 + 10], acc[G * 16 + 11]);
    pk[G * 8 + 7] = pack_bf16(acc[G * 16 + 14], acc[G * 16 + 15]);
  }
}

#define HA(h) (h)
constexpr int K2_NST = 7;
constexpr uint32_t K2_END = 0x100;
#define PF_KC 7
#define FIRST_DRAW 3
#define ANCH 8
#define HNS 1000
#define PNS 1000
#define PWAIT mbar_wait_ns<PNS>
#define PVM 0x8A
#define W0 63
#define SPEC 24
constexpr int K3_NST = 4;
__device__ __forceinline__ uint32_t k3_rot(uint32_t sv) { return (0x00E9u >> (2 * sv)) & 3; }
constexpr int K3_STAGE = 16384 + 32768 + 4096;
constexpr int SMEM_DATA = 7 * 32768;
constexpr int SMEM_BYTES = SMEM_DATA + 1024 + 768;

struct Cursor {
  uint32_t s, ph;
  __device__ __forceinline__ void next() {
    if (++s == K2_NST) { s = 0; ph ^= 1; }
  }
};

#define TURN_SYNC() bar_sync(mybar, 256)
#define TURN_ARRIVE() bar_arrive(otherbar, 256)
#define RELEASE_IF(cur, cond) mbar_arrive_cluster_if(bE + (cur).s * 8, warp & 1, sig && (cond))
#define RELEASE(cur) RELEASE_IF(cur, true)
#define ISSUE_PV(cur, first)                                                                                   \
  do {                                                                                                         \
    const uint64_t dv = make_desc(sbase + (cur).s * 32768, 16384, 1024, 1);                                    \
    _Pragma("unroll") for (int t = 0; t < 8; t++)                                                              \
        wgmma_rs_n128<1, 0>(O, P[4 * t], P[4 * t + 1], P[4 * t + 2], P[4 * t + 3], dv + (uint64_t)(t * 128), (t > 0) ? 1 : !(first)); \
  } while (0)
#define ISSUE_QK(cur)                                                                                          \
  do {                                                                                                         \
    const uint64_t dk = make_desc(sbase + (cur).s * 32768, 16, 1024, 1);                                       \
    _Pragma("unroll") for (int t = 0; t < 8; t++)                                                              \
        wgmma_rs_n128<0, 0>(S, Q[4 * t], Q[4 * t + 1], Q[4 * t + 2], Q[4 * t + 3], dk + (uint64_t)((t >> 2) * 1024 + (t & 3) * 2), t > 0); \
  } while (0)
#define SCALE(J0, J1)                                                                                          \
  do {                                                                                                         \
    _Pragma("unroll") for (int jj = J0; jj < J1; jj++) {                                                       \
      S[jj * 4 + 0] = fmaf(S[jj * 4 + 0], cl2, -m0);                                                           \
      S[jj * 4 + 1] = fmaf(S[jj * 4 + 1], cl2, -m0);                                                           \
      S[jj * 4 + 2] = fmaf(S[jj * 4 + 2], cl2, -m1);                                                           \
      S[jj * 4 + 3] = fmaf(S[jj * 4 + 3], cl2, -m1);                                                           \
    }                                                                                                          \
  } while (0)
#define EXPB(T)                                                                                                \
  do {                                                                                                         \
    _Pragma("unroll") for (int i = 4 * T; i < 4 * T + 4; i++) asm volatile("" : "+r"(P[i])::"memory");        \
    _Pragma("unroll") for (int jj = 2 * T; jj < 2 * T + 2; jj++) {                                             \
      const float e0 = ex2(S[jj * 4 + 0]), e1 = ex2(S[jj * 4 + 1]), e2 = ex2(S[jj * 4 + 2]), e3 = ex2(S[jj * 4 + 3]); \
      s0 += e0 + e1;                                                                                           \
      s1 += e2 + e3;                                                                                           \
      P[jj * 2 + 0] = pack_bf16(e0, e1);                                                                       \
      P[jj * 2 + 1] = pack_bf16(e2, e3);                                                                       \
    }                                                                                                          \
  } while (0)
#define EXPC(T)                                                                                                \
  do {                                                                                                         \
    if (T > 0 && ((PVM >> (T - 1)) & 1)) {                                                                     \
      anchor((T & 2) ? s0 : s1, never);                                                                        \
      wg_wait<__builtin_popcount(PVM >> T) - 1>();                                                             \
      if ((PVM >> T) == (128 >> T)) { fence_regs(O); RELEASE(cv); }                                            \
    }                                                                                                          \
    EXPB(T);                                                                                                   \
  } while (0)
#define MASK(G, g)                                                                                             \
  do {                                                                                                         \
    if ((g) * 8 > d) S[(G) * 4 + 0] = -INFINITY;                                                               \
    if ((g) * 8 + 1 > d) S[(G) * 4 + 1] = -INFINITY;                                                           \
    if ((g) * 8 - 8 > d) S[(G) * 4 + 2] = -INFINITY;                                                           \
    if ((g) * 8 - 7 > d) S[(G) * 4 + 3] = -INFINITY;                                                           \
  } while (0)
#define FIRST_REF()                                                                                            \
  do {                                                                                                         \
    m0 = fmaxf(S[0], S[1]);                                                                                    \
    m1 = fmaxf(S[2], S[3]);                                                                                    \
    m0 = fmaxf(m0, __shfl_xor_sync(0xffffffffu, m0, 1));                                                       \
    m1 = fmaxf(m1, __shfl_xor_sync(0xffffffffu, m1, 1));                                                       \
    m0 = fmaxf(m0, __shfl_xor_sync(0xffffffffu, m0, 2)) * cl2;                                                 \
    m1 = fmaxf(m1, __shfl_xor_sync(0xffffffffu, m1, 2)) * cl2;                                                 \
  } while (0)
#define STORE_O(G)                                                                                             \
  do {                                                                                                         \
    st_v4(g_ctx + eoff + (G) * 32, pack_bf16(O[(G) * 16 + 0] * f0, O[(G) * 16 + 1] * f0), pack_bf16(O[(G) * 16 + 4] * f0, O[(G) * 16 + 5] * f0), \
          pack_bf16(O[(G) * 16 + 8] * f0, O[(G) * 16 + 9] * f0), pack_bf16(O[(G) * 16 + 12] * f0, O[(G) * 16 + 13] * f0)); \
    st_v4(g_ctx + eoff + 8 * KCAT + (G) * 32, pack_bf16(O[(G) * 16 + 2] * f1, O[(G) * 16 + 3] * f1), pack_bf16(O[(G) * 16 + 6] * f1, O[(G) * 16 + 7] * f1), \
          pack_bf16(O[(G) * 16 + 10] * f1, O[(G) * 16 + 11] * f1), pack_bf16(O[(G) * 16 + 14] * f1, O[(G) * 16 + 15] * f1)); \
  } while (0)

__global__ void __cluster_dims__(2, 1, 1) __launch_bounds__(384, 1)
fused_kernel(const __grid_constant__ Params p, const bf16* __restrict__ x, const bf16* __restrict__ gate_w, bf16* __restrict__ out) {
  extern __shared__ uint8_t smem_raw[];
  const uint32_t sbase = (smem_u32(smem_raw) + 1023) & ~1023u;
  const uint32_t sB = sbase, sA = sbase + K1_BST * 16384, sBar = sbase + SMEM_DATA;
  const uint32_t bAf = sBar, bAe = sBar + 64, bBf = sBar + 128, bBe = sBar + 176, bL = sBar + 224, bS = sBar + 232, bL2 = sBar + 240, sL = sA + 32768;
  const uint32_t bF = sBar + 256, bE = sBar + 320, bT = sBar + 384, sTick = sBar + 400, sItem = sBar + 416, bS2 = sBar + 448, bR = sBar + 456, bLast = sBar + 464, bH = sBar + 472, bT0 = sBar + 480;
  const uint32_t b3F = sBar + 512, b3E = sBar + 544, sGate = sBar + 576;
  const int tid = threadIdx.x, warp_g = __shfl_sync(0xffffffffu, tid >> 5, 0), lane = tid & 31;
  const uint32_t rank = cluster_rank();
  const int cl = blockIdx.x >> 1;
  TSM(0);
  if (tid == 0) {
    for (int i = 0; i < 8; i++) { mbar_init(bAf + i * 8, 1); mbar_init(bAe + i * 8, 2); }
    for (int i = 0; i < K1_BST; i++) { mbar_init(bBf + i * 8, 1); mbar_init(bBe + i * 8, 4); }
    mbar_init(bL, 1);
    mbar_init(bL2, 1);
    mbar_init(bR, 1);
    mbar_init(bLast, 1);
    mbar_init(bH, 4);
    mbar_init(bT0, 1);
    mbar_init(bS, 8);
    for (int i = 0; i < K2_NST; i++) { mbar_init(bF + i * 8, 1); mbar_init(bE + i * 8, 4); }
    mbar_init(bT, 1); mbar_init(bT + 8, 1);
    mbar_init(bS2, 8);
    for (int i = 0; i < K3_NST; i++) { mbar_init(b3F + i * 8, 1); mbar_init(b3E + i * 8, 4); }
    asm volatile("fence.mbarrier_init.release.cluster;" ::: "memory");
  }
  __syncthreads();
  cluster_sync();
  const int lr0 = blockIdx.x * 16;

  if (warp_g >= 8) {
    reg_dealloc<40>();
    if (warp_g == 8) {
      if (elect_one()) {
        uint32_t bs = 0, bph = 1, aph = 1;
#pragma unroll 1
        for (int ji = 0; ji < K1_MAXJOBS; ji++) {
          const uint32_t job = p.jobs[cl][ji];
          if (!(job & 3)) break;
          const int a_sel = (job >> 2) & 1, mpair = (job >> 3) & 7, chunk0 = (job >> 8) & 63;
          const bool newA = (job >> 14) & 1;
          const int KC = a_sel ? 9 : 8;
          const uint32_t halfbytes = 8192;
          const bool lastjob = (ji + 1 == K1_MAXJOBS) || !(p.jobs[cl][ji + 1] & 3);
          const CUtensorMap* tw = &p.tmW[(job >> 6) & 3];
          {
            const uint32_t njob = (ji + 1 < K1_MAXJOBS) ? p.jobs[cl][ji + 1] : 0;
            if (!(njob & 3) && !newA) mbar_arrive(bLast);
          }
#pragma unroll 1
          for (int kc = 0; kc < KC; kc++) {
            if (kc == ((ji == 0) ? PF_KC : 0) && !lastjob) {
              const uint32_t njob = p.jobs[cl][ji + 1];
              const int nst = ((njob >> 2) & 1) ? 18 : 16;
#pragma unroll 1
              for (int t = (cl < 64) ? (cl & 7) : 0; t < nst; t += (cl < 64) ? 8 : 1)
                tma_pf3d(&p.tmW[(njob >> 6) & 3], 0, t * 32 + rank * 16, (njob >> 8) & 63);
            }
            if (kc == 8) {
              PWAIT(bBe + bs * 8, bph);
              mbar_expect(bBf + bs * 8, 16384);
              tma2d(sB + bs * 16384, &p.tmA[1], bBf + bs * 8, 512, mpair * 256 + rank * 128);
              if (++bs == K1_BST) { bs = 0; bph ^= 1; }
            } else if (newA) {
              PWAIT(bAe + kc * 8, aph);
              mbar_expect(bAf + kc * 8, 16384);
              tma2d(sA + ((kc + 2) & 7) * 16384, &p.tmA[a_sel], bAf + kc * 8, kc * 64, mpair * 256 + rank * 128);
              if (kc == 7 && lastjob) mbar_arrive(bLast);
            }
#pragma unroll 1
            for (int kk = 0; kk < 2; kk++) {
              PWAIT(bBe + bs * 8, bph);
              mbar_expect(bBf + bs * 8, 2 * halfbytes);
              tma3d_mc(sB + bs * 16384 + rank * halfbytes, tw, bBf + bs * 8, 0, kc * 64 + kk * 32 + rank * 16, chunk0, 3);
              if (++bs == K1_BST) { bs = 0; bph ^= 1; }
            }
          }
          if (newA) aph ^= 1;
        }
        Cursor c{0, 0};
        int pcol = 0;
        PWAIT(bR, 0);
        uint32_t tick = lds32(sTick + 8), seen = 1u << (p.order[tick] >> 4);
        asm volatile("fence.proxy.async.global;" ::: "memory");
#pragma unroll 1
        for (int it = 0;; it++) {
          const uint32_t item = (tick < 256) ? p.order[tick] : (K2_END | min(tick - 256, 255u));
          asm volatile("st.shared.u32 [%0], %1;" ::"r"(sItem + (it & 7) * 4), "r"(item) : "memory");
          if (item >= K2_END) break;
          const int h = item >> 3, j = item & 7;
          const int blk = 2 * j + (int)(rank ^ (it & 1));
          const int col = HA(h) * 128 + rank * 64;
          const int nb = 2 * j + 2;
          if (!((seen >> (h >> 1)) & 1)) {
            wait_flag(&g_sync[F_HP + (h >> 1)], RDY_TARGET);
            asm volatile("fence.proxy.async.global;" ::: "memory");
            seen |= 1u << (h >> 1);
          }
          PWAIT(bE + c.s * 8, c.ph);
          mbar_expect(bF + c.s * 8, 32768);
          tma2d(sbase + c.s * 32768, &p.tmQ, bF + c.s * 8, HA(h) * 128, blk * 128);
          tma2d(sbase + c.s * 32768 + 16384, &p.tmQ, bF + c.s * 8, HA(h) * 128 + 64, blk * 128);
          c.next();
#pragma unroll 1
          for (int n = nb - 1; n >= 0; n--) {
            if (n == 0 && rank == 0) tick = atomicAdd(&g_sync[F_TICK], 1u);
            PWAIT(bE + c.s * 8, c.ph);
            mbar_expect(bF + c.s * 8, 32768);
            tma2d_mc(sbase + c.s * 32768 + rank * 16384, &p.tmK, bF + c.s * 8, col, n * 128, 3);
            c.next();
            if (n < nb - 1 || it > 0) {
              PWAIT(bE + c.s * 8, c.ph);
              mbar_expect(bF + c.s * 8, 32768);
              tma2d_mc(sbase + c.s * 32768 + rank * 16384, &p.tmV, bF + c.s * 8, (n < nb - 1) ? col : pcol, (n < nb - 1) ? (n + 1) * 128 : 0, 3);
              c.next();
            }
          }
          pcol = col;
          if (rank == 0) {
            asm volatile(
                "{\n.reg .b32 a, b;\nmapa.shared::cluster.u32 a, %0, 1;\nmapa.shared::cluster.u32 b, %1, 1;\n"
                "st.async.shared::cluster.mbarrier::complete_tx::bytes.u32 [a], %2, [b];\n}" ::"r"(sTick + (it & 1) * 4),
                "r"(bT + (it & 1) * 8), "r"(tick) : "memory");
          } else {
            mbar_expect(bT + (it & 1) * 8, 4);
            PWAIT(bT + (it & 1) * 8, (it >> 1) & 1);
            tick = lds32(sTick + (it & 1) * 4);
          }
        }
        PWAIT(bE + c.s * 8, c.ph);
        mbar_expect(bF + c.s * 8, 32768);
        tma2d_mc(sbase + c.s * 32768 + rank * 16384, &p.tmV, bF + c.s * 8, pcol, 0, 3);
        const uint32_t unit = tick - 256;
        if (unit < 64) {
          const int mblk = (7 - (p.unit[unit][0] >> 1)) * 2 + rank, nhalf = p.unit[unit][0] & 1;
          const uint32_t rot = k3_rot(c.s), nfree = ((0x1Au >> c.s) & 1) ? 2 : 3;
#pragma unroll 1
          for (int i = 0; i < K2_NST - 1; i++) {
            c.next();
            PWAIT(bE + c.s * 8, c.ph);
          }
          uint32_t have = 0;
#pragma unroll 1
          for (uint32_t idx = 0; idx < p.unit[unit][2]; idx++) {
            const int kk = p.unit[unit][3] + idx + ((idx >= p.unit[unit][4]) ? p.unit[unit][5] : 0);
            const uint32_t s = (rot + idx) & 3;
            if (idx >= nfree) PWAIT((idx < 4) ? bH : b3E + s * 8, (idx < 4) ? 0 : (~idx >> 2) & 1);
            mbar_expect(b3F + s * 8, K3_STAGE);
            const uint32_t st = sbase + s * K3_STAGE;
            const int sel = (kk < 9), k = sel ? kk : kk - 9, kr = k * 64 + rank * 32;
            tma3d_mc(st + 16384 + rank * 16384, &p.tmO[sel], b3F + s * 8, 0, kr, nhalf * 4, 3);
            tma2d_mc(st + 49152 + rank * 2048, &p.tmOt[sel], b3F + s * 8, 512 + nhalf * 32, kr, 3);
            if (sel && idx == 0) {
              wait_flag(&g_sync[F_OA + mblk], 8);
              asm volatile("fence.proxy.async.global;" ::: "memory");
            }
            if (!sel && !((have >> (k >> 1)) & 1)) {
#pragma unroll 1
              for (uint32_t spins = 0; spins < (1u << 22); spins++) {
                asm volatile("ld.acquire.gpu.global.u32 %0, [%1];" : "=r"(have) : "l"(&g_sync[F_CTX + mblk]) : "memory");
                if ((have >> (k >> 1)) & 1) break;
                __nanosleep(100);
              }
              asm volatile("fence.proxy.async.global;" ::: "memory");
            }
            tma2d(st, &p.tmC, b3F + s * 8, (sel ? 64 + k : k) * 64, mblk * 128);
          }
        }
      }
    }
    __syncwarp();
    if (warp_g == 8) {
      uint32_t v = 0;
      if (lane == 0) {
        __threadfence();
        v = atomicAdd(&g_sync[F_DONE], 1u);
      }
      if (__shfl_sync(0xffffffffu, v, 0) == 2 * NCLUSTER - 1) {
        reinterpret_cast<uint4*>(g_sync)[lane] = make_uint4(0, 0, 0, 0);
        if (lane == 0) g_sync[F_EPOCH] = lds32(sGate + 64) + 1;
      }
    }
    asm volatile("" ::: "memory");
    if (__shfl_sync(0xffffffffu, warp_g, 0) != 8) {
      if (lr0 < S_LEN) {
#pragma unroll 1
        for (int i = warp_g - 9; i < 16; i += 3) {
          const float g = gate_row(lr0 + i, lane, x, gate_w);
          if (lane == 0) asm volatile("st.shared.f32 [%0], %1;" ::"r"(sGate + i * 4), "f"(g) : "memory");
        }
        bar_arrive(3, 256 + 96);
        if (lane == 0) {
          __threadfence();
          atomicAdd(&g_sync[F_GATE], 1u);
        }
      }
      uint32_t aph = 1;
#pragma unroll 1
      for (int ji = 0; ji < K1_MAXJOBS; ji++) aph ^= (p.jobs[cl][ji] >> 14) & 1;
      if (warp_g == 9 && lane == 0) {
#pragma unroll 1
        for (int ji = 0; ji < K1_MAXJOBS; ji++) {
          const uint32_t job = p.jobs[cl][ji];
          if (!(job & 3)) break;
          mbar_wait_ns<HNS>(bS, ji & 1);
          __threadfence();
          atomicAdd(&g_sync[(((job >> 6) & 3) == 2) ? (F_QKVA + ((job >> 3) & 7) * 2 + rank) : (F_HP + ((job >> 10) & 15))], 1u);
        }
#pragma unroll 1
        for (int it = 0;; it++) {
          mbar_wait_ns<HNS>(bS2, it & 1);
          const uint32_t item = lds32(sItem + (it & 7) * 4), nxt = lds32(sItem + ((it + 1) & 7) * 4);
          __threadfence();
          atomicOr(&g_sync[F_CTX + (item & 7) * 2 + (rank ^ (it & 1))], 1u << (item >> 3));
          if (nxt >= K2_END) break;
        }
      } else if (warp_g == 11) {
        if (lane == 0) {
          prefetch_tmap(&p.tmQ); prefetch_tmap(&p.tmK); prefetch_tmap(&p.tmV);
          asm volatile("st.shared.u32 [%0], %1;" ::"r"(sGate + 64), "r"(__ldcg(&g_sync[F_EPOCH])) : "memory");
          wait_flag(&g_sync[F_GATE], GATE_TARGET);
          uint32_t tick;
          if (rank == 0) {
            mbar_wait_ns<HNS>(bLast, 0);
            mbar_wait_ns<HNS>(bAe + FIRST_DRAW * 8, aph);
            tick = atomicAdd(&g_sync[F_TICK], 1u);
            asm volatile("st.shared.u32 [%0], %1;" ::"r"(sTick + 8), "r"(tick) : "memory");
            asm volatile(
                "{\n.reg .b32 a, b;\nmapa.shared::cluster.u32 a, %0, 1;\nmapa.shared::cluster.u32 b, %1, 1;\n"
                "st.async.shared::cluster.mbarrier::complete_tx::bytes.u32 [a], %2, [b];\n}" ::"r"(sTick + 8), "r"(bT0), "r"(tick) : "memory");
          } else {
            mbar_expect(bT0, 4);
            mbar_wait_ns<HNS>(bT0, 0);
            tick = lds32(sTick + 8);
          }
          wait_flag(&g_sync[F_HP + (p.order[tick] >> 4)], RDY_TARGET);
          mbar_arrive(bR);
        }
        __syncwarp();
        bar_sync(4, 256 + 32);
        if (lane < 12) mbar_arrive_cluster(bE + (4 + lane % 3) * 8, (lane / 3) & 1);
      } else if (warp_g == 10 && lr0 < S_LEN) {
        if (elect_one()) {
          prefetch_tmap(&p.tmL[0]); prefetch_tmap(&p.tmL[1]);
          wait_flag(&g_sync[F_QKVA + (lr0 >> 7)], K1_FLAG_TARGET);
          wait_flag(&g_sync[F_QKVA + (max(lr0 - 14, 0) >> 7)], K1_FLAG_TARGET);
          asm volatile("fence.proxy.async.global;" ::: "memory");
          mbar_wait_ns<HNS>(bLast, 0);
#pragma unroll 1
          for (int kc = 0; kc < 6; kc++) {
            mbar_wait_ns<HNS>(bAe + kc * 8, aph);
            if (kc == 3) {
              mbar_expect(bL, 46 * 1152);
              tma3d(sL, &p.tmL[0], bL, 0, 9, lr0 - 14);
              tma3d(sL + 30 * 1152, &p.tmL[1], bL, 0, 0, lr0);
            }
          }
          mbar_expect(bL2, 30 * 1152);
          tma3d(sL + 46 * 1152, &p.tmL[0], bL2, 0, 18, lr0 - 14);
        }
        __syncwarp();
        bar_sync(5, 256 + 32);
        if (lane == 0) {
          __threadfence();
          atomicAdd(&g_sync[F_OA + (lr0 >> 7)], 1u);
        }
      }
    }
    __syncwarp();
    cluster_sync();
  } else {
    reg_alloc<232>();
    const int wg = warp_g >> 2, warp = warp_g & 3, q = lane & 3;
    const bool sig = (lane == 0) && (warp < 2);
    {
      K1State st{0, 0, 0, nullptr, 0, 0, 0};
      float acc[128];
      uint32_t pk[64];
      if (wg == 0) { TS(0, 0); TSC(0, 2); }
      uint32_t job = p.jobs[cl][0];
      k1_first(st, job, bAf, bBf);
#pragma unroll 1
      for (int ji = 0; job & 3; ji++) {
        const uint32_t njob = p.jobs[cl][ji + 1];
        k1_tile(acc, pk, st, job, njob, sA, sB, bAf, bAe, bBf, bBe, bS, wg, warp, lane, rank);
        job = njob;
      }
#pragma unroll
      for (int i = 0; i < 4; i++)
        mbar_arrive_cluster_if(bE + i * 8, warp & 1, sig);
#pragma unroll
      for (int G = 0; G < 8; G++)
        if (G < st.png) {
          st_v4a(st.pp + G * 32, pk[G * 8], pk[G * 8 + 1], pk[G * 8 + 2], pk[G * 8 + 3]);
          st_v4a(st.pp + G * 32 + st.pld8, pk[G * 8 + 4], pk[G * 8 + 5], pk[G * 8 + 6], pk[G * 8 + 7]);
        }
      k1_flag(st, lane, bS);
      if (wg == 0) { TS(0, 1); TSC(0, 3); }
      if (lr0 < S_LEN) {
        const int ri = (warp_g >> 1) * 4 + (warp_g & 1) + 2, row = lr0 + ri;
        if (wg == 0) TS(1, 5);
        bar_sync(3, 256 + 96);
        const float gate0 = __uint_as_float(lds32(sGate + ri * 4 - 8)), gate1 = __uint_as_float(lds32(sGate + ri * 4));
        mbar_wait(bL, 0);
        if (wg == 0) TS(1, 6);
        local_rows2(row, ri, sL, bL2, lane, gate0, gate1);
        bar_arrive(5, 256 + 32);
      } else {
        bar_arrive(4, 256 + 32);
      }
    }
    __syncwarp();
    uint32_t item, rot;
    {
      const int mybar = 1 + wg, otherbar = 2 - wg;
      const uint32_t never = blockIdx.y;
      const float cl2 = 0.08838834764831845f * 1.4426950408889634f;
      float S[64], O[64];
      uint32_t P[32], Q[32];
      float m0 = 0.f, m1 = 0.f, l0 = 1.f, l1 = 1.f, gf0 = 0.f, gf1 = 0.f;
      uint32_t eoff = 0, prev_single = 0;
      Cursor c{0, 0};
      if (wg == 1) bar_arrive(1, 256);
      if (wg == 0) { TS(1, 0); TSC(1, 2); }
#pragma unroll 1
      for (int it = 0;; it++) {
        TB(0);
        const int hi = (int)(rank ^ (it & 1));
        Cursor cq = c, ck, cv, cs0, cs1;
        rot = k3_rot(c.s);
        c.next();
        ck = c; c.next();
        cs0 = ck; cs1 = ck; cv = ck;
        if (it > 0) { cv = c; c.next(); }
        if (!hi) {
          ck = c; c.next();
          cs1 = c; c.next();
        }
        mbar_wait(bF + cq.s * 8, cq.ph);
        TB(1);
        item = lds32(sItem + (it & 7) * 4);
        {
          const uint32_t qa = sbase + cq.s * 32768 + (wg * 64 + warp * 16 + (lane & 15)) * 128;
#pragma unroll
          for (int t = 0; t < 8; t++)
            ldsm_x4(Q[4 * t], Q[4 * t + 1], Q[4 * t + 2], Q[4 * t + 3], qa + (t >> 2) * 16384 + ((((t & 3) * 2 + (lane >> 4)) ^ (lane & 7)) << 4));
        }
        const uint32_t rdy = mbar_test(bF + ck.s * 8, ck.ph) & mbar_test(bF + cv.s * 8, cv.ph);
        l0 += __shfl_xor_sync(0xffffffffu, l0, 1);
        l1 += __shfl_xor_sync(0xffffffffu, l1, 1);
        l0 += __shfl_xor_sync(0xffffffffu, l0, 2);
        l1 += __shfl_xor_sync(0xffffffffu, l1, 2);
        const bool last = item >= K2_END;
        if (last) {
          cv = cq; ck = cq;
        } else if (!rdy) {
          mbar_wait2(bF + ck.s * 8, ck.ph, bF + cv.s * 8, cv.ph);
        }
        TB(2);
        TURN_SYNC();
        TB(3);
        TRC(last ? 2 : 1);
        if (it > 0) {
          wg_fence();
          ISSUE_PV(cv, prev_single);
          wg_commit();
        } else {
          wg_fence();
          wg_commit();
        }
        wg_fence();
        ISSUE_QK(ck);
        wg_commit();
        if (!(last && wg == 1)) TURN_ARRIVE();
        RELEASE_IF(cq, !last);
        TB(4);
        asm volatile("" : "+f"(gf0), "+f"(gf1), "+f"(l0), "+f"(l1));
        const float f0 = __fdividef(1.f - gf0, l0), f1 = __fdividef(1.f - gf1, l1);
        wg_wait<1>();
        fence_regs(O);
        fence_regs(P);
        TB(5);
        if (it > 0) {
          RELEASE_IF(cv, !last);
          mbar_arrive_cluster_if(bH, warp & 1, sig && last);
          STORE_O(0); STORE_O(1); STORE_O(2); STORE_O(3);
          __syncwarp();
          mbar_arrive_if(bS2, lane == 0);
        }
        TB(6);
        if (!last) {
          const int row = (2 * (item & 7) + hi) * 128 + wg * 64 + warp * 16 + (lane >> 2);
          eoff = row * KCAT + (item >> 3) * 128 + q * 8;
          asm volatile("ld.global.f32 %0, [%1];" : "=f"(gf0) : "l"(g_gate + row));
          asm volatile("ld.global.f32 %0, [%1];" : "=f"(gf1) : "l"(g_gate + row + 8));
          if (!hi) {
            mbar_wait2(bF + cs0.s * 8, cs0.ph, bF + cs1.s * 8, cs1.ph);
            RELEASE(cs0);
            RELEASE(cs1);
          }
        }
        TB(7);
        wg_wait<0>();
        fence_regs(S);
        TB(8);
        if (last) break;
        RELEASE(ck);
        const int nblk = 2 * (item & 7) + 1 + hi;
        prev_single = (nblk == 1);
        float s0 = 0.f, s1 = 0.f;
        l0 = 0.f; l1 = 0.f;
        {
          const int d = warp * 16 + (lane >> 2) - 2 * q;
          if (wg == 0) {
            MASK(0, 0);
            FIRST_REF();
#pragma unroll
            for (int jj = 1; jj < 8; jj++) MASK(jj, jj);
            SCALE(0, 8);
            EXPB(0); EXPB(1); EXPB(2); EXPB(3);
#pragma unroll
            for (int i = 32; i < 64; i++) S[i] = -INFINITY;
#pragma unroll
            for (int i = 16; i < 32; i++) P[i] = 0;
          } else {
            FIRST_REF();
#pragma unroll
            for (int jj = 0; jj < 8; jj++) MASK(jj + 8, jj);
            SCALE(0, 16);
            EXPB(0); EXPB(1); EXPB(2); EXPB(3); EXPB(4); EXPB(5); EXPB(6); EXPB(7);
          }
        }
        fence_regs(P);
        TB(9);
#pragma unroll 1
        for (int n = 1;; n++) {
          if (__any_sync(0xffffffffu, !(s0 + s1 <= (float)(1ull << SPEC)))) {
            float mx0 = fmaxf(S[0], S[1]), mx1 = fmaxf(S[2], S[3]);
#pragma unroll
            for (int jj = 1; jj < 16; jj++) {
              mx0 = fmaxf(mx0, fmaxf(S[jj * 4 + 0], S[jj * 4 + 1]));
              mx1 = fmaxf(mx1, fmaxf(S[jj * 4 + 2], S[jj * 4 + 3]));
            }
            mx0 = fmaxf(mx0, __shfl_xor_sync(0xffffffffu, mx0, 1));
            mx1 = fmaxf(mx1, __shfl_xor_sync(0xffffffffu, mx1, 1));
            mx0 = fmaxf(mx0, __shfl_xor_sync(0xffffffffu, mx0, 2));
            mx1 = fmaxf(mx1, __shfl_xor_sync(0xffffffffu, mx1, 2));
            mx0 = fmaxf(mx0, 0.f);
            mx1 = fmaxf(mx1, 0.f);
            m0 += mx0; m1 += mx1;
            const float sc0 = ex2(-mx0), sc1 = ex2(-mx1);
            l0 *= sc0; l1 *= sc1;
            s0 = 0.f; s1 = 0.f;
#pragma unroll
            for (int jj = 0; jj < 16; jj++) {
              const float e0 = ex2(S[jj * 4 + 0] - mx0), e1 = ex2(S[jj * 4 + 1] - mx0), e2 = ex2(S[jj * 4 + 2] - mx1), e3 = ex2(S[jj * 4 + 3] - mx1);
              s0 += e0 + e1;
              s1 += e2 + e3;
              P[jj * 2 + 0] = pack_bf16(e0, e1);
              P[jj * 2 + 1] = pack_bf16(e2, e3);
              O[jj * 4 + 0] *= sc0;
              O[jj * 4 + 1] *= sc0;
              O[jj * 4 + 2] *= sc1;
              O[jj * 4 + 3] *= sc1;
            }
          }
          l0 += s0;
          l1 += s1;
          if (n >= nblk) break;
          ck = c; c.next();
          cv = c; c.next();
          mbar_wait(bF + ck.s * 8, ck.ph);
          mbar_wait(bF + cv.s * 8, cv.ph);
          TURN_SYNC();
          TRC(0);
          wg_fence();
          ISSUE_QK(ck);
          wg_commit();
          {
            const uint64_t dv = make_desc(sbase + cv.s * 32768, 16384, 1024, 1);
#pragma unroll
            for (int t = 0; t < 8; t++) {
              wgmma_rs_n128<1, 0>(O, P[4 * t], P[4 * t + 1], P[4 * t + 2], P[4 * t + 3], dv + (uint64_t)(t * 128), (t > 0) ? 1 : (n != 1));
              if ((PVM >> t) & 1) wg_commit();
            }
          }
          TURN_ARRIVE();
          s0 = 0.f; s1 = 0.f;
          wg_wait<__builtin_popcount(PVM)>();
          fence_regs(S);
          RELEASE(ck);
          SCALE(0, 16);
          anchor(S[W0], never);
          wg_wait<__builtin_popcount(PVM) - 1>();
          EXPC(0); EXPC(1); EXPC(2); EXPC(3); EXPC(4); EXPC(5); EXPC(6); EXPC(7);
        }
      }
      TRC(3);
      if (wg == 1) { TS(1, 1); TSC(1, 3); }
    }
    __syncwarp();
    const uint32_t unit = item & 255;
    if (unit < 64) {
      const int mblk = (7 - (p.unit[unit][0] >> 1)) * 2 + rank, nhalf = p.unit[unit][0] & 1, ks = p.unit[unit][1];
      const int k0 = 0, k1 = p.unit[unit][2];
      float acc[144];
      uint32_t s = rot, ph = 0, prev = 0;
      if (wg == 0) { TS(2, 0); TSC(2, 2); }
#pragma unroll 1
      for (int k = k0; k < k1; k++) {
        mbar_wait(b3F + s * 8, ph);
        const uint32_t st = sbase + s * K3_STAGE;
        const uint64_t da = make_desc(st + wg * 8192, 16, 1024, 1);
        const uint64_t db = make_desc(st + 16384, 4096, 1024, 1);
        const uint64_t dt = make_desc(st + 49152, 16, 512, 2);
        wg_fence();
#pragma unroll
        for (int t = 0; t < 4; t++) {
          const int sd = (t > 0) || (k > k0);
          wgmma_ss_n256<1, 0>(acc, da + (uint64_t)(t * 2), db + (uint64_t)((t >> 1) * 1024 + (t & 1) * 128), sd);
          wgmma_ss_n32<1, 128>(acc, da + (uint64_t)(t * 2), dt + (uint64_t)(t * 64), sd);
        }
        wg_commit();
        if (k > k0) {
          wg_wait<1>();
          if (sig) mbar_arrive_cluster(b3E + prev * 8, warp);
        }
        prev = s;
        s = (s + 1) & 3;
        if (s == rot) ph ^= 1;
      }
      wg_wait<0>();
      fence_regs(acc);
      cluster_arrive();
      if (wg == 0) TS(2, 4);
      const int tile = mblk * 2 + nhalf;
      uint4* wp = g_part + (size_t)((tile * 4 + ks) * 4) * 5 * 256 + tid;
      const uint32_t sown = sbase + wg * 8192 + (tid & 127) * 16;
#pragma unroll
      for (int d = 0; d < 4; d++) {
        if (d != ks) {
#pragma unroll
          for (int i = 0; i < 4; i++)
            __stcg(wp + (d * 5 + i) * 256,
                   make_uint4(pack_bf16(acc[d * 32 + i * 8], acc[d * 32 + i * 8 + 1]), pack_bf16(acc[d * 32 + i * 8 + 2], acc[d * 32 + i * 8 + 3]),
                              pack_bf16(acc[d * 32 + i * 8 + 4], acc[d * 32 + i * 8 + 5]), pack_bf16(acc[d * 32 + i * 8 + 6], acc[d * 32 + i * 8 + 7])));
          __stcg(reinterpret_cast<uint2*>(wp - tid + (d * 5 + 4) * 256) + tid,
                 make_uint2(pack_bf16(acc[128 + d * 4], acc[128 + d * 4 + 1]), pack_bf16(acc[128 + d * 4 + 2], acc[128 + d * 4 + 3])));
        } else {
#pragma unroll
          for (int i = 0; i < 9; i++) {
            const int o = (i < 8) ? d * 32 + i * 4 : 128 + d * 4;
            asm volatile("st.shared.v4.f32 [%0], {%1, %2, %3, %4};" ::"r"(sown + (i >> 2) * K3_STAGE + (i & 3) * 2048), "f"(acc[o]), "f"(acc[o + 1]), "f"(acc[o + 2]), "f"(acc[o + 3]) : "memory");
          }
        }
      }
      __threadfence();
      __syncwarp();
      if (wg == 0) TS(2, 5);
      if (lane == 0) {
        unsigned int* cnt = &g_sync[F_XCH + tile * 8 + warp_g];
        const uint32_t xtarget = lds32(sGate + 64) * 4 + 4;
        atomicAdd(cnt, 1u);
        uint32_t v, spins = 0;
        do {
          asm volatile("ld.acquire.gpu.global.u32 %0, [%1];" : "=r"(v) : "l"(cnt) : "memory");
        } while ((int)(v - xtarget) < 0 && ++spins < (1u << 24));
      }
      __syncwarp();
      if (wg == 0) TS(2, 6);
      float r[36];
#pragma unroll
      for (int i = 0; i < 9; i++)
        asm volatile("ld.shared.v4.f32 {%0, %1, %2, %3}, [%4];" : "=f"(r[i * 4]), "=f"(r[i * 4 + 1]), "=f"(r[i * 4 + 2]), "=f"(r[i * 4 + 3])
                     : "r"(sown + (i >> 2) * K3_STAGE + (i & 3) * 2048) : "memory");
#pragma unroll
      for (int sI = 1; sI < 4; sI++) {
        const int src = (ks + sI) & 3;
        const uint4* rp = g_part + (size_t)(((tile * 4 + src) * 4) + ks) * 5 * 256;
#pragma unroll
        for (int i = 0; i < 4; i++) {
          const uint4 v = __ldcg(rp + i * 256 + tid);
          r[i * 8] += bf_lo(v.x); r[i * 8 + 1] += bf_hi(v.x); r[i * 8 + 2] += bf_lo(v.y); r[i * 8 + 3] += bf_hi(v.y);
          r[i * 8 + 4] += bf_lo(v.z); r[i * 8 + 5] += bf_hi(v.z); r[i * 8 + 6] += bf_lo(v.w); r[i * 8 + 7] += bf_hi(v.w);
        }
        const uint2 v = __ldcg(reinterpret_cast<const uint2*>(rp + 4 * 256) + tid);
        r[32] += bf_lo(v.x); r[33] += bf_hi(v.x); r[34] += bf_lo(v.y); r[35] += bf_hi(v.y);
      }
      const int row = mblk * 128 + wg * 64 + warp * 16 + (lane >> 2);
      bf16* o0 = out + (size_t)row * DM + nhalf * 256 + ks * 64 + 8 * q;
#pragma unroll
      for (int G = 0; G < 2; G++) {
        uint32_t a0 = pack_bf16(r[G * 16], r[G * 16 + 1]), a1 = pack_bf16(r[G * 16 + 4], r[G * 16 + 5]);
        uint32_t a2 = pack_bf16(r[G * 16 + 8], r[G * 16 + 9]), a3 = pack_bf16(r[G * 16 + 12], r[G * 16 + 13]);
        uint32_t b0 = pack_bf16(r[G * 16 + 2], r[G * 16 + 3]), b1 = pack_bf16(r[G * 16 + 6], r[G * 16 + 7]);
        uint32_t b2 = pack_bf16(r[G * 16 + 10], r[G * 16 + 11]), b3 = pack_bf16(r[G * 16 + 14], r[G * 16 + 15]);
        quad_transpose(a0, a1, a2, a3, q);
        quad_transpose(b0, b1, b2, b3, q);
        st_v4(o0 + G * 32, a0, a1, a2, a3);
        st_v4(o0 + 8 * DM + G * 32, b0, b1, b2, b3);
      }
      {
        uint32_t t0 = pack_bf16(r[32], r[33]), t1 = pack_bf16(r[34], r[35]), t2 = 0, t3 = 0;
        quad_transpose(t0, t1, t2, t3, q);
        if (q < 2) st_v4(out + (size_t)(row + q * 8) * DM + 512 + nhalf * 32 + ks * 8, t0, t1, t2, t3);
      }
    } else {
      cluster_arrive();
    }
    if (wg == 0) { TS(2, 1); TSC(2, 3); }
    cluster_wait();
  }
}

typedef CUresult (*EncFn)(CUtensorMap*, CUtensorMapDataType, cuuint32_t, void*, const cuuint64_t*, const cuuint64_t*, const cuuint32_t*,
                          const cuuint32_t*, CUtensorMapInterleave, CUtensorMapSwizzle, CUtensorMapL2promotion, CUtensorMapFloatOOBfill);

static void enc2d(EncFn enc, CUtensorMap* m, const void* ptr, uint64_t cols, uint64_t rows, uint32_t bc, uint32_t br,
                  CUtensorMapSwizzle sw = CU_TENSOR_MAP_SWIZZLE_128B) {
  cuuint64_t gd[2] = {cols, rows}, gs[1] = {cols * 2};
  cuuint32_t bx[2] = {bc, br}, es[2] = {1, 1};
  enc(m, CU_TENSOR_MAP_DATA_TYPE_BFLOAT16, 2, const_cast<void*>(ptr), gd, gs, bx, es, CU_TENSOR_MAP_INTERLEAVE_NONE, sw,
      CU_TENSOR_MAP_L2_PROMOTION_L2_256B, CU_TENSOR_MAP_FLOAT_OOB_FILL_NONE);
}
static void enc3d(EncFn enc, CUtensorMap* m, const void* ptr, uint64_t cols, uint64_t rows, uint32_t br, uint32_t bch) {
  cuuint64_t gd[3] = {64, rows, cols / 64}, gs[2] = {cols * 2, 128};
  cuuint32_t bx[3] = {64, br, bch}, es[3] = {1, 1, 1};
  enc(m, CU_TENSOR_MAP_DATA_TYPE_BFLOAT16, 3, const_cast<void*>(ptr), gd, gs, bx, es, CU_TENSOR_MAP_INTERLEAVE_NONE,
      CU_TENSOR_MAP_SWIZZLE_128B, CU_TENSOR_MAP_L2_PROMOTION_L2_256B, CU_TENSOR_MAP_FLOAT_OOB_FILL_NONE);
}

static int g_sched[10] = {11, 10, 7, 4, 4, 5, 6, 6, 8, 20};
static void build_k1_jobs(Params& p) {
  int cnt[NCLUSTER];
  for (int c = 0; c < NCLUSTER; c++) {
    cnt[c] = 0;
    for (int i = 0; i <= K1_MAXJOBS; i++) p.jobs[c][i] = 0;
  }
  auto add = [&](int c, int nch, int a_sel, int mp, int w_sel, int chunk0) {
    p.jobs[c][cnt[c]++] = (uint16_t)((nch - 1) | (a_sel << 2) | (mp << 3) | (w_sel << 6) | (chunk0 << 8));
  };
  const int *cg = g_sched, *xg = g_sched + 4;
  for (int mp = 0; mp < 8; mp++) {
    int k = 0;
    for (int i = 0; i < K1_MAXJOBS; i++)
      for (int g = 0; g < 4; g++)
        if (i < cg[g]) { add(g * 8 + mp, 4, 0, mp, k & 1, (k >> 1) * 4); k++; }
    k = 0;
    for (int i = 0; i < K1_MAXJOBS; i++)
      for (int g = 0; g < 4; g++)
        if (i < xg[g]) {
          if (k < 7) add((4 + g) * 8 + mp, k == 0 ? 3 : 4, 1, mp, 2, k == 0 ? 24 : (k - 1) * 4);
          else add((4 + g) * 8 + mp, 4, 1, mp, 3, (k - 7) * 4);
          k++;
        }
    add(64 + mp / 4, 4, 1, mp, 3, 14 * 4);
    add(64 + mp / 4, 4, 1, mp, 3, 15 * 4);
  }
  for (int cc = 0; cc < NCLUSTER; cc++)
    for (int i = 0; i < cnt[cc]; i++) {
      const int key = p.jobs[cc][i] & 0x3C;
      if (i == 0 || (p.jobs[cc][i - 1] & 0x3C) != key) p.jobs[cc][i] |= (1 << 14);
      if (i == cnt[cc] - 1 || (p.jobs[cc][i + 1] & 0x3C) != key) p.jobs[cc][i] |= (1 << 15);
    }
}

static void build_k2_items(Params& p) {
  int n = 0;
  const int SCHED_N1 = g_sched[8], SCHED_N2 = g_sched[9];
  for (int j = 7; j >= 0; j--)
    for (int h = 0; h < SCHED_N1; h++) p.order[n++] = (uint8_t)(h * 8 + j);
  for (int j = 7; j >= 4; j--)
    for (int h = SCHED_N1; h < SCHED_N2; h++) p.order[n++] = (uint8_t)(h * 8 + j);
  for (int j = 7; j >= 0; j--)
    for (int h = SCHED_N1; h < 32; h++)
      if (!(h < SCHED_N2 && j >= 4)) p.order[n++] = (uint8_t)(h * 8 + j);
}

static void build_k3_units(Params& p) {
  float slope = 0.045f;
  int NE = 25;
  for (int t = 0; t < 16; t++) {
    const int u[4] = {t, 31 - t, 32 + t, 63 - t};
    float acc = 0.f;
    int k0 = 0, l0 = NE;
    for (int i = 0; i < 4; i++) {
      acc += 18.25f + slope * (31.5f - u[i]);
      const int k1 = (i == 3) ? 73 : (int)(acc + 0.5f);
      const int e0 = NE * i / 4, e1 = NE * (i + 1) / 4;
      uint8_t* w = p.unit[u[i]];
      w[0] = (uint8_t)t; w[1] = (uint8_t)i; w[2] = (uint8_t)(k1 - k0); w[3] = (uint8_t)e0; w[4] = (uint8_t)(e1 - e0); w[5] = (uint8_t)(l0 - e1);
      l0 += (k1 - k0) - (e1 - e0);
      k0 = k1;
    }
  }
}

extern "C" void kernel_launch(void* const* d_in, const int* in_sizes, int n_in, void* d_out, int out_size) {
  const bf16* x = (const bf16*)d_in[0];
  const bf16* wqkv = (const bf16*)d_in[1];
  const bf16* wo = (const bf16*)d_in[2];
  const bf16* ckv = (const bf16*)d_in[4];
  const bf16* w_q = (const bf16*)d_in[5];
  const bf16* w_uk = (const bf16*)d_in[6];
  const bf16* w_uv = (const bf16*)d_in[7];
  const bf16* w_o = (const bf16*)d_in[8];
  const bf16* gate_w = (const bf16*)d_in[9];

  EncFn enc = nullptr;
  cudaDriverEntryPointQueryResult qr;
  cudaGetDriverEntryPoint("cuTensorMapEncodeTiled", (void**)&enc, cudaEnableDefault, &qr);
  void *pQ, *pK, *pV, *pCtx, *pQA;
  cudaGetSymbolAddress(&pQ, g_Q);
  cudaGetSymbolAddress(&pQA, g_QKVA);
  cudaGetSymbolAddress(&pK, g_K);
  cudaGetSymbolAddress(&pV, g_V);
  cudaGetSymbolAddress(&pCtx, g_ctx);

  static Params p;
  enc2d(enc, &p.tmA[0], ckv, DC, S_LEN, 64, 128);
  enc2d(enc, &p.tmA[1], x, DM, S_LEN, 64, 128);
  enc3d(enc, &p.tmW[0], w_uk, HDIM, DC, 16, 4);
  enc3d(enc, &p.tmW[1], w_uv, HDIM, DC, 16, 4);
  enc3d(enc, &p.tmW[2], wqkv, NQKVA, DM, 16, 4);
  enc3d(enc, &p.tmW[3], w_q, HDIM, DM, 16, 4);
  build_k1_jobs(p);
  enc2d(enc, &p.tmQ, pQ, HDIM, S_LEN, 64, 128);
  enc2d(enc, &p.tmK, pK, HDIM, S_LEN, 64, 128);
  enc2d(enc, &p.tmV, pV, HDIM, S_LEN, 64, 128);
  build_k2_items(p);
  build_k3_units(p);
  for (int i = 0; i < 2; i++) {
    cuuint64_t gd[3] = {64, 27, S_LEN}, gs[2] = {128, NQKVA * 2};
    cuuint32_t bx[3] = {64, 9, i ? 16u : 30u}, es[3] = {1, 1, 1};
    enc(&p.tmL[i], CU_TENSOR_MAP_DATA_TYPE_BFLOAT16, 3, pQA, gd, gs, bx, es, CU_TENSOR_MAP_INTERLEAVE_NONE, CU_TENSOR_MAP_SWIZZLE_NONE,
        CU_TENSOR_MAP_L2_PROMOTION_L2_256B, CU_TENSOR_MAP_FLOAT_OOB_FILL_NONE);
  }
  enc2d(enc, &p.tmC, pCtx, KCAT, S_LEN, 64, 128);
  enc3d(enc, &p.tmO[0], w_o, DM, HDIM, 32, 4);
  enc3d(enc, &p.tmO[1], wo, DM, DM, 32, 4);
  enc2d(enc, &p.tmOt[0], w_o, DM, HDIM, 32, 32, CU_TENSOR_MAP_SWIZZLE_64B);
  enc2d(enc, &p.tmOt[1], wo, DM, DM, 32, 32, CU_TENSOR_MAP_SWIZZLE_64B);

  cudaFuncSetAttribute(fused_kernel, cudaFuncAttributeMaxDynamicSharedMemorySize, SMEM_BYTES);
  fused_kernel<<<NCLUSTER * 2, 384, SMEM_BYTES>>>(p, x, gate_w, (bf16*)d_out);
}
```

```cpp
#include <cuda_runtime.h>
#include <cuda_bf16.h>
#include <cuda.h>
#include <stdint.h>

typedef __nv_bfloat16 bf16;

constexpr int S_LEN = 2048, DM = 576, DC = 512, HDIM = 4096, NQKVA = 1728, KCAT = 4672;
constexpr int NCLUSTER = 66;

__device__ __align__(1024) bf16 g_Q[S_LEN * HDIM];
__device__ __align__(1024) bf16 g_K[S_LEN * HDIM];
__device__ __align__(1024) bf16 g_V[S_LEN * HDIM];
__device__ __align__(1024) bf16 g_QKVA[S_LEN * NQKVA + 64];
__device__ __align__(1024) bf16 g_ctx[S_LEN * KCAT];
__device__ float g_gate[S_LEN];
__device__ __align__(1024) uint4 g_part[32 * 4 * 4 * 5 * 256];
__device__ __align__(16) unsigned int g_sync[400];
constexpr int F_QKVA = 0, F_HP = 16, F_CTX = 32, F_OA = 48, F_GATE = 96, F_TICK = 97, F_DONE = 98, F_XCH = 128, F_EPOCH = 384;

__device__ __forceinline__ uint32_t smem_u32(const void* p) { return (uint32_t)__cvta_generic_to_shared(p); }
__device__ __forceinline__ void mbar_init(uint32_t a, uint32_t c) {
  asm volatile("mbarrier.init.shared::cta.b64 [%0], %1;" ::"r"(a), "r"(c));
}
__device__ __forceinline__ void mbar_expect(uint32_t a, uint32_t b) {
  asm volatile("mbarrier.arrive.expect_tx.shared::cta.b64 _, [%0], %1;" ::"r"(a), "r"(b) : "memory");
}
#define TS(k, i)
#define TSC(k, i)
#define TSM(k)
#define BSEG(i)
#define TB(k)
#define TRC(fl)
#define SPIN_LIMIT "4194304"
__device__ __forceinline__ void mbar_wait(uint32_t a, uint32_t parity) {
  asm volatile(
      "{\n.reg .pred p;\n.reg .u32 n;\n"
      "mbarrier.try_wait.parity.shared::cta.b64 p, [%0], %1;\n"
      "@p bra DONE;\n"
      "mov.u32 n, 0;\n"
      "LOOP:\n"
      "mbarrier.try_wait.parity.shared::cta.b64 p, [%0], %1;\n"
      "@p bra DONE;\n"
      "add.u32 n, n, 1;\n"
      "setp.lt.u32 p, n, " SPIN_LIMIT ";\n"
      "@p bra LOOP;\n"
      "DONE:\n}" ::"r"(a), "r"(parity) : "memory");
}
template <int NS>
__device__ __forceinline__ void mbar_wait_ns(uint32_t a, uint32_t parity) {
  asm volatile(
      "{\n.reg .pred p;\n.reg .u32 n;\n"
      "mov.u32 n, 0;\n"
      "LOOP:\n"
      "mbarrier.try_wait.parity.shared::cta.b64 p, [%0], %1, %2;\n"
      "@p bra DONE;\n"
      "add.u32 n, n, 1;\n"
      "setp.lt.u32 p, n, " SPIN_LIMIT ";\n"
      "@p bra LOOP;\n"
      "DONE:\n}" ::"r"(a), "r"(parity), "n"(NS) : "memory");
}
__device__ __forceinline__ void mbar_wait2(uint32_t a, uint32_t pa, uint32_t b, uint32_t pb) {
  asm volatile(
      "{\n.reg .pred p, q;\n.reg .u32 n;\n"
      "mov.u32 n, 0;\n"
      "LOOP:\n"
      "mbarrier.try_wait.parity.shared::cta.b64 p, [%0], %1;\n"
      "mbarrier.try_wait.parity.shared::cta.b64 q, [%2], %3;\n"
      "add.u32 n, n, 1;\n"
      "and.pred p, p, q;\n"
      "setp.lt.and.u32 p, n, " SPIN_LIMIT ", !p;\n"
      "@p bra LOOP;\n"
      "}" ::"r"(a), "r"(pa), "r"(b), "r"(pb) : "memory");
}
__device__ __forceinline__ uint32_t mbar_test(uint32_t a, uint32_t parity) {
  uint32_t r;
  asm volatile("{\n.reg .pred p;\nmbarrier.test_wait.parity.shared::cta.b64 p, [%1], %2;\nselp.u32 %0, 1, 0, p;\n}" : "=r"(r) : "r"(a), "r"(parity) : "memory");
  return r;
}
__device__ __forceinline__ void mbar_arrive(uint32_t a) {
  asm volatile("mbarrier.arrive.shared::cta.b64 _, [%0];" ::"r"(a) : "memory");
}
__device__ __forceinline__ void mbar_arrive_cluster(uint32_t a, uint32_t cta) {
  asm volatile("{\n.reg .b32 r;\nmapa.shared::cluster.u32 r, %0, %1;\nmbarrier.arrive.shared::cluster.b64 _, [r];\n}" ::"r"(a),
               "r"(cta) : "memory");
}
__device__ __forceinline__ void mbar_arrive_cluster_if(uint32_t a, uint32_t cta, bool pred) {
  asm volatile("{\n.reg .b32 r;\n.reg .pred p;\nsetp.ne.u32 p, %2, 0;\nmapa.shared::cluster.u32 r, %0, %1;\n@p mbarrier.arrive.shared::cluster.b64 _, [r];\n}" ::"r"(a),
               "r"(cta), "r"((uint32_t)pred) : "memory");
}
__device__ __forceinline__ void anchor(float v, uint32_t pred) {
  asm volatile("{\n.reg .pred p;\nsetp.ne.u32 p, %1, 0;\n@p st.shared.f32 [%1], %0;\n}" ::"f"(v), "r"(pred) : "memory");
}
__device__ __forceinline__ void mbar_arrive_if(uint32_t a, bool pred) {
  asm volatile("{\n.reg .pred p;\nsetp.ne.u32 p, %1, 0;\n@p mbarrier.arrive.shared::cta.b64 _, [%0];\n}" ::"r"(a), "r"((uint32_t)pred) : "memory");
}
__device__ __forceinline__ void tma2d(uint32_t dst, const CUtensorMap* m, uint32_t bar, int c0, int c1) {
  asm volatile("cp.async.bulk.tensor.2d.shared::cluster.global.mbarrier::complete_tx::bytes [%0], [%1, {%3, %4}], [%2];" ::"r"(dst),
               "l"(m), "r"(bar), "r"(c0), "r"(c1) : "memory");
}
__device__ __forceinline__ void tma2d_mc(uint32_t dst, const CUtensorMap* m, uint32_t bar, int c0, int c1, uint16_t mask) {
  asm volatile(
      "cp.async.bulk.tensor.2d.shared::cluster.global.mbarrier::complete_tx::bytes.multicast::cluster [%0], [%1, {%3, %4}], [%2], %5;" ::"r"(dst),
      "l"(m), "r"(bar), "r"(c0), "r"(c1), "h"(mask) : "memory");
}
__device__ __forceinline__ void tma3d_mc(uint32_t dst, const CUtensorMap* m, uint32_t bar, int c0, int c1, int c2, uint16_t mask) {
  asm volatile(
      "cp.async.bulk.tensor.3d.shared::cluster.global.mbarrier::complete_tx::bytes.multicast::cluster [%0], [%1, {%3, %4, %5}], [%2], %6;" ::"r"(dst),
      "l"(m), "r"(bar), "r"(c0), "r"(c1), "r"(c2), "h"(mask) : "memory");
}
__device__ __forceinline__ void tma3d(uint32_t dst, const CUtensorMap* m, uint32_t bar, int c0, int c1, int c2) {
  asm volatile(
      "cp.async.bulk.tensor.3d.shared::cluster.global.mbarrier::complete_tx::bytes [%0], [%1, {%3, %4, %5}], [%2];" ::"r"(dst),
      "l"(m), "r"(bar), "r"(c0), "r"(c1), "r"(c2) : "memory");
}
__device__ __forceinline__ void tma_pf2d(const CUtensorMap* m, int c0, int c1) {
  asm volatile("cp.async.bulk.prefetch.tensor.2d.L2.global [%0, {%1, %2}];" ::"l"(m), "r"(c0), "r"(c1) : "memory");
}
__device__ __forceinline__ void tma_pf3d(const CUtensorMap* m, int c0, int c1, int c2) {
  asm volatile("cp.async.bulk.prefetch.tensor.3d.L2.global [%0, {%1, %2, %3}];" ::"l"(m), "r"(c0), "r"(c1), "r"(c2) : "memory");
}
__device__ __forceinline__ void prefetch_tmap(const CUtensorMap* m) {
  asm volatile("prefetch.tensormap [%0];" ::"l"(m) : "memory");
}
__device__ __forceinline__ void cluster_arrive() { asm volatile("barrier.cluster.arrive.relaxed.aligned;" ::: "memory"); }
__device__ __forceinline__ void cluster_wait() { asm volatile("barrier.cluster.wait.aligned;" ::: "memory"); }
__device__ __forceinline__ void cluster_sync() {
  cluster_arrive();
  cluster_wait();
}
__device__ __forceinline__ uint32_t cluster_rank() {
  uint32_t r;
  asm volatile("mov.u32 %0, %%cluster_ctarank;" : "=r"(r));
  return r;
}
__device__ __forceinline__ bool elect_one() {
  uint32_t p;
  asm volatile("{\n.reg .pred q;\nelect.sync _|q, 0xffffffff;\nselp.u32 %0, 1, 0, q;\n}" : "=r"(p));
  return p;
}
__device__ __forceinline__ void ldsm_x4(uint32_t& r0, uint32_t& r1, uint32_t& r2, uint32_t& r3, uint32_t addr) {
  asm volatile("ldmatrix.sync.aligned.m8n8.x4.shared.b16 {%0, %1, %2, %3}, [%4];" : "=r"(r0), "=r"(r1), "=r"(r2), "=r"(r3) : "r"(addr) : "memory");
}
__device__ __forceinline__ void wg_fence() { asm volatile("wgmma.fence.sync.aligned;" ::: "memory"); }
__device__ __forceinline__ void wg_commit() { asm volatile("wgmma.commit_group.sync.aligned;" ::: "memory"); }
template <int N>
__device__ __forceinline__ void wg_wait() { asm volatile("wgmma.wait_group.sync.aligned %0;" ::"n"(N) : "memory"); }
template <int N>
__device__ __forceinline__ void reg_alloc() { asm volatile("setmaxnreg.inc.sync.aligned.u32 %0;" ::"n"(N)); }
template <int N>
__device__ __forceinline__ void reg_dealloc() { asm volatile("setmaxnreg.dec.sync.aligned.u32 %0;" ::"n"(N)); }
__device__ __forceinline__ void bar_sync(int id, int n) { asm volatile("bar.sync %0, %1;" ::"r"(id), "r"(n) : "memory"); }
__device__ __forceinline__ void bar_arrive(int id, int n) { asm volatile("bar.arrive %0, %1;" ::"r"(id), "r"(n) : "memory"); }
template <int NT>
__device__ __forceinline__ void fence_regs(float (&d)[NT]) {
#pragma unroll
  for (int i = 0; i < NT; i++) asm volatile("" : "+f"(d[i])::"memory");
}
template <int NT>
__device__ __forceinline__ void fence_regs(uint32_t (&d)[NT]) {
#pragma unroll
  for (int i = 0; i < NT; i++) asm volatile("" : "+r"(d[i])::"memory");
}
__device__ __forceinline__ uint64_t make_desc(uint32_t saddr, uint32_t lbo, uint32_t sbo, uint32_t layout) {
  return (uint64_t)((saddr & 0x3FFFF) >> 4) | ((uint64_t)(lbo >> 4) << 16) | ((uint64_t)(sbo >> 4) << 32) | ((uint64_t)layout << 62);
}
__device__ __forceinline__ uint32_t pack_bf16(float lo, float hi) {
  uint32_t r;
  asm("cvt.rn.bf16x2.f32 %0, %1, %2;" : "=r"(r) : "f"(hi), "f"(lo));
  return r;
}
__device__ __forceinline__ float ex2(float x) {
  float r;
  asm("ex2.approx.ftz.f32 %0, %1;" : "=f"(r) : "f"(x));
  return r;
}
__device__ __forceinline__ void st_v4(void* p, uint32_t a, uint32_t b, uint32_t c, uint32_t d) {
#define ST_MOD ".cs"
  asm volatile("st.global" ST_MOD ".v4.b32 [%0], {%1, %2, %3, %4};" ::"l"(p), "r"(a), "r"(b), "r"(c), "r"(d) : "memory");
}
#define STA_MOD ".cs"
__device__ __forceinline__ void st_v4a(void* p, uint32_t a, uint32_t b, uint32_t c, uint32_t d) {
  asm volatile("st.global" STA_MOD ".v4.b32 [%0], {%1, %2, %3, %4};" ::"l"(p), "r"(a), "r"(b), "r"(c), "r"(d) : "memory");
}
__device__ __forceinline__ float bf_lo(uint32_t v) { return __uint_as_float(v << 16); }
__device__ __forceinline__ float bf_hi(uint32_t v) { return __uint_as_float(v & 0xFFFF0000u); }

__device__ __forceinline__ void quad_transpose(uint32_t& a0, uint32_t& a1, uint32_t& a2, uint32_t& a3, int q) {
  const bool o1 = q & 1, o2 = q & 2;
  uint32_t t0 = o1 ? a0 : a1, t1 = o1 ? a2 : a3;
  t0 = __shfl_xor_sync(0xffffffffu, t0, 1);
  t1 = __shfl_xor_sync(0xffffffffu, t1, 1);
  if (o1) { a0 = t0; a2 = t1; } else { a1 = t0; a3 = t1; }
  t0 = o2 ? a0 : a2;
  t1 = o2 ? a1 : a3;
  t0 = __shfl_xor_sync(0xffffffffu, t0, 2);
  t1 = __shfl_xor_sync(0xffffffffu, t1, 2);
  if (o2) { a0 = t0; a1 = t1; } else { a2 = t0; a3 = t1; }
}

template<int TB, int OFF, int NT>
__device__ __forceinline__ void wgmma_ss_n256(float (&d)[NT], uint64_t da, uint64_t db, int scale_d) {
  asm volatile("{\n.reg .pred p;\nsetp.ne.b32 p, %130, 0;\n"
    "wgmma.mma_async.sync.aligned.m64n256k16.f32.bf16.bf16 {%0, %1, %2, %3, %4, %5, %6, %7, %8, %9, %10, %11, %12, %13, %14, %15, %16, %17, %18, %19, %20, %21, %22, %23, %24, %25, %26, %27, %28, %29, %30, %31, %32, %33, %34, %35, %36, %37, %38, %39, %40, %41, %42, %43, %44, %45, %46, %47, %48, %49, %50, %51, %52, %53, %54, %55, %56, %57, %58, %59, %60, %61, %62, %63, %64, %65, %66, %67, %68, %69, %70, %71, %72, %73, %74, %75, %76, %77, %78, %79, %80, %81, %82, %83, %84, %85, %86, %87, %88, %89, %90, %91, %92, %93, %94, %95, %96, %97, %98, %99, %100, %101, %102, %103, %104, %105, %106, %107, %108, %109, %110, %111, %112, %113, %114, %115, %116, %117, %118, %119, %120, %121, %122, %123, %124, %125, %126, %127}, %128, %129, p, 1, 1, 0, %131;\n}\n"
    : "+f"(d[OFF+0]), "+f"(d[OFF+1]), "+f"(d[OFF+2]), "+f"(d[OFF+3]), "+f"(d[OFF+4]), "+f"(d[OFF+5]), "+f"(d[OFF+6]), "+f"(d[OFF+7]), "+f"(d[OFF+8]), "+f"(d[OFF+9]), "+f"(d[OFF+10]), "+f"(d[OFF+11]), "+f"(d[OFF+12]), "+f"(d[OFF+13]), "+f"(d[OFF+14]), "+f"(d[OFF+15]), "+f"(d[OFF+16]), "+f"(d[OFF+17]), "+f"(d[OFF+18]), "+f"(d[OFF+19]), "+f"(d[OFF+20]), "+f"(d[OFF+21]), "+f"(d[OFF+22]), "+f"(d[OFF+23]), "+f"(d[OFF+24]), "+f"(d[OFF+25]), "+f"(d[OFF+26]), "+f"(d[OFF+27]), "+f"(d[OFF+28]), "+f"(d[OFF+29]), "+f"(d[OFF+30]), "+f"(d[OFF+31]), "+f"(d[OFF+32]), "+f"(d[OFF+33]), "+f"(d[OFF+34]), "+f"(d[OFF+35]), "+f"(d[OFF+36]), "+f"(d[OFF+37]), "+f"(d[OFF+38]), "+f"(d[OFF+39]), "+f"(d[OFF+40]), "+f"(d[OFF+41]), "+f"(d[OFF+42]), "+f"(d[OFF+43]), "+f"(d[OFF+44]), "+f"(d[OFF+45]), "+f"(d[OFF+46]), "+f"(d[OFF+47]), "+f"(d[OFF+48]), "+f"(d[OFF+49]), "+f"(d[OFF+50]), "+f"(d[OFF+51]), "+f"(d[OFF+52]), "+f"(d[OFF+53]), "+f"(d[OFF+54]), "+f"(d[OFF+55]), "+f"(d[OFF+56]), "+f"(d[OFF+57]), "+f"(d[OFF+58]), "+f"(d[OFF+59]), "+f"(d[OFF+60]), "+f"(d[OFF+61]), "+f"(d[OFF+62]), "+f"(d[OFF+63]), "+f"(d[OFF+64]), "+f"(d[OFF+65]), "+f"(d[OFF+66]), "+f"(d[OFF+67]), "+f"(d[OFF+68]), "+f"(d[OFF+69]), "+f"(d[OFF+70]), "+f"(d[OFF+71]), "+f"(d[OFF+72]), "+f"(d[OFF+73]), "+f"(d[OFF+74]), "+f"(d[OFF+75]), "+f"(d[OFF+76]), "+f"(d[OFF+77]), "+f"(d[OFF+78]), "+f"(d[OFF+79]), "+f"(d[OFF+80]), "+f"(d[OFF+81]), "+f"(d[OFF+82]), "+f"(d[OFF+83]), "+f"(d[OFF+84]), "+f"(d[OFF+85]), "+f"(d[OFF+86]), "+f"(d[OFF+87]), "+f"(d[OFF+88]), "+f"(d[OFF+89]), "+f"(d[OFF+90]), "+f"(d[OFF+91]), "+f"(d[OFF+92]), "+f"(d[OFF+93]), "+f"(d[OFF+94]), "+f"(d[OFF+95]), "+f"(d[OFF+96]), "+f"(d[OFF+97]), "+f"(d[OFF+98]), "+f"(d[OFF+99]), "+f"(d[OFF+100]), "+f"(d[OFF+101]), "+f"(d[OFF+102]), "+f"(d[OFF+103]), "+f"(d[OFF+104]), "+f"(d[OFF+105]), "+f"(d[OFF+106]), "+f"(d[OFF+107]), "+f"(d[OFF+108]), "+f"(d[OFF+109]), "+f"(d[OFF+110]), "+f"(d[OFF+111]), "+f"(d[OFF+112]), "+f"(d[OFF+113]), "+f"(d[OFF+114]), "+f"(d[OFF+115]), "+f"(d[OFF+116]), "+f"(d[OFF+117]), "+f"(d[OFF+118]), "+f"(d[OFF+119]), "+f"(d[OFF+120]), "+f"(d[OFF+121]), "+f"(d[OFF+122]), "+f"(d[OFF+123]), "+f"(d[OFF+124]), "+f"(d[OFF+125]), "+f"(d[OFF+126]), "+f"(d[OFF+127])
    : "l"(da), "l"(db), "r"(scale_d), "n"(TB));
}
template<int TB, int OFF, int NT>
__device__ __forceinline__ void wgmma_ss_n32(float (&d)[NT], uint64_t da, uint64_t db, int scale_d) {
  asm volatile("{\n.reg .pred p;\nsetp.ne.b32 p, %18, 0;\n"
    "wgmma.mma_async.sync.aligned.m64n32k16.f32.bf16.bf16 {%0, %1, %2, %3, %4, %5, %6, %7, %8, %9, %10, %11, %12, %13, %14, %15}, %16, %17, p, 1, 1, 0, %19;\n}\n"
    : "+f"(d[OFF+0]), "+f"(d[OFF+1]), "+f"(d[OFF+2]), "+f"(d[OFF+3]), "+f"(d[OFF+4]), "+f"(d[OFF+5]), "+f"(d[OFF+6]), "+f"(d[OFF+7]), "+f"(d[OFF+8]), "+f"(d[OFF+9]), "+f"(d[OFF+10]), "+f"(d[OFF+11]), "+f"(d[OFF+12]), "+f"(d[OFF+13]), "+f"(d[OFF+14]), "+f"(d[OFF+15])
    : "l"(da), "l"(db), "r"(scale_d), "n"(TB));
}
template<int TB, int OFF, int NT>
__device__ __forceinline__ void wgmma_rs_n128(float (&d)[NT], uint32_t a0, uint32_t a1, uint32_t a2, uint32_t a3, uint64_t db, int scale_d) {
  asm volatile("{\n.reg .pred p;\nsetp.ne.b32 p, %69, 0;\n"
    "wgmma.mma_async.sync.aligned.m64n128k16.f32.bf16.bf16 {%0, %1, %2, %3, %4, %5, %6, %7, %8, %9, %10, %11, %12, %13, %14, %15, %16, %17, %18, %19, %20, %21, %22, %23, %24, %25, %26, %27, %28, %29, %30, %31, %32, %33, %34, %35, %36, %37, %38, %39, %40, %41, %42, %43, %44, %45, %46, %47, %48, %49, %50, %51, %52, %53, %54, %55, %56, %57, %58, %59, %60, %61, %62, %63}, {%64, %65, %66, %67}, %68, p, 1, 1, %70;\n}\n"
    : "+f"(d[OFF+0]), "+f"(d[OFF+1]), "+f"(d[OFF+2]), "+f"(d[OFF+3]), "+f"(d[OFF+4]), "+f"(d[OFF+5]), "+f"(d[OFF+6]), "+f"(d[OFF+7]), "+f"(d[OFF+8]), "+f"(d[OFF+9]), "+f"(d[OFF+10]), "+f"(d[OFF+11]), "+f"(d[OFF+12]), "+f"(d[OFF+13]), "+f"(d[OFF+14]), "+f"(d[OFF+15]), "+f"(d[OFF+16]), "+f"(d[OFF+17]), "+f"(d[OFF+18]), "+f"(d[OFF+19]), "+f"(d[OFF+20]), "+f"(d[OFF+21]), "+f"(d[OFF+22]), "+f"(d[OFF+23]), "+f"(d[OFF+24]), "+f"(d[OFF+25]), "+f"(d[OFF+26]), "+f"(d[OFF+27]), "+f"(d[OFF+28]), "+f"(d[OFF+29]), "+f"(d[OFF+30]), "+f"(d[OFF+31]), "+f"(d[OFF+32]), "+f"(d[OFF+33]), "+f"(d[OFF+34]), "+f"(d[OFF+35]), "+f"(d[OFF+36]), "+f"(d[OFF+37]), "+f"(d[OFF+38]), "+f"(d[OFF+39]), "+f"(d[OFF+40]), "+f"(d[OFF+41]), "+f"(d[OFF+42]), "+f"(d[OFF+43]), "+f"(d[OFF+44]), "+f"(d[OFF+45]), "+f"(d[OFF+46]), "+f"(d[OFF+47]), "+f"(d[OFF+48]), "+f"(d[OFF+49]), "+f"(d[OFF+50]), "+f"(d[OFF+51]), "+f"(d[OFF+52]), "+f"(d[OFF+53]), "+f"(d[OFF+54]), "+f"(d[OFF+55]), "+f"(d[OFF+56]), "+f"(d[OFF+57]), "+f"(d[OFF+58]), "+f"(d[OFF+59]), "+f"(d[OFF+60]), "+f"(d[OFF+61]), "+f"(d[OFF+62]), "+f"(d[OFF+63])
    : "r"(a0), "r"(a1), "r"(a2), "r"(a3), "l"(db), "r"(scale_d), "n"(TB));
}
template<int TB, int OFF, int NT>
__device__ __forceinline__ void wgmma_rs_n64(float (&d)[NT], uint32_t a0, uint32_t a1, uint32_t a2, uint32_t a3, uint64_t db, int scale_d) {
  asm volatile("{\n.reg .pred p;\nsetp.ne.b32 p, %37, 0;\n"
    "wgmma.mma_async.sync.aligned.m64n64k16.f32.bf16.bf16 {%0, %1, %2, %3, %4, %5, %6, %7, %8, %9, %10, %11, %12, %13, %14, %15, %16, %17, %18, %19, %20, %21, %22, %23, %24, %25, %26, %27, %28, %29, %30, %31}, {%32, %33, %34, %35}, %36, p, 1, 1, %38;\n}\n"
    : "+f"(d[OFF+0]), "+f"(d[OFF+1]), "+f"(d[OFF+2]), "+f"(d[OFF+3]), "+f"(d[OFF+4]), "+f"(d[OFF+5]), "+f"(d[OFF+6]), "+f"(d[OFF+7]), "+f"(d[OFF+8]), "+f"(d[OFF+9]), "+f"(d[OFF+10]), "+f"(d[OFF+11]), "+f"(d[OFF+12]), "+f"(d[OFF+13]), "+f"(d[OFF+14]), "+f"(d[OFF+15]), "+f"(d[OFF+16]), "+f"(d[OFF+17]), "+f"(d[OFF+18]), "+f"(d[OFF+19]), "+f"(d[OFF+20]), "+f"(d[OFF+21]), "+f"(d[OFF+22]), "+f"(d[OFF+23]), "+f"(d[OFF+24]), "+f"(d[OFF+25]), "+f"(d[OFF+26]), "+f"(d[OFF+27]), "+f"(d[OFF+28]), "+f"(d[OFF+29]), "+f"(d[OFF+30]), "+f"(d[OFF+31])
    : "r"(a0), "r"(a1), "r"(a2), "r"(a3), "l"(db), "r"(scale_d), "n"(TB));
}

__device__ __forceinline__ void wait_flag(const unsigned int* f, uint32_t target) {
  uint32_t v;
#pragma unroll 1
  for (uint32_t spins = 0; spins < (1u << 22); spins++) {
    asm volatile("ld.acquire.gpu.global.u32 %0, [%1];" : "=r"(v) : "l"(f) : "memory");
    if (v >= target) break;
    __nanosleep(100);
  }
}
__device__ __forceinline__ uint32_t lds32(uint32_t a) {
  uint32_t v;
  asm volatile("ld.shared.u32 %0, [%1];" : "=r"(v) : "r"(a) : "memory");
  return v;
}
__device__ __forceinline__ float gate_row(int row, int lane, const bf16* __restrict__ x, const bf16* __restrict__ gate_w) {
  const uint32_t* xr = reinterpret_cast<const uint32_t*>(x + (size_t)row * DM);
  const uint32_t* gw2 = reinterpret_cast<const uint32_t*>(gate_w);
  float gs = 0.f;
#pragma unroll
  for (int i = 0; i < 9; i++) {
    const uint32_t a = __ldg(xr + lane + 32 * i), b = __ldg(gw2 + lane + 32 * i);
    gs = fmaf(bf_lo(a), bf_lo(b), gs);
    gs = fmaf(bf_hi(a), bf_hi(b), gs);
  }
#pragma unroll
  for (int o = 16; o; o >>= 1) gs += __shfl_xor_sync(0xffffffffu, gs, o);
  const float g = 1.f / (1.f + __expf(-gs));
  if (lane == 0) g_gate[row] = g;
  return g;
}
#define LA_UNROLL 9
__device__ __forceinline__ void local_rows2(int rb, int ri, uint32_t sL, uint32_t bL2, int lane, float ga, float gb) {
  const float scale_l2 = 0.23570226039551584f * 1.4426950408889634f;
  constexpr int U = LA_UNROLL;
  const uint32_t sq = sL + (30 + ri) * 1152;
  uint32_t kb[9];
#pragma unroll
  for (int i = 0; i < 9; i++) {
    const uint32_t c = lane * 9 + i;
    kb[i] = sL + (14 + ri) * 1152 + ((c & ~15u) | ((c & 3) << 2) | ((c >> 2) & 3)) * 4;
  }
  float ma = -INFINITY, mb = -INFINITY;
  {
    float qa[18], qb[18];
#pragma unroll
    for (int i = 0; i < 9; i++) {
      const uint32_t u = lds32(kb[i] + 16 * 1152 - 2304), v = lds32(kb[i] + 16 * 1152);
      qa[2 * i] = bf_lo(u); qa[2 * i + 1] = bf_hi(u);
      qb[2 * i] = bf_lo(v); qb[2 * i + 1] = bf_hi(v);
    }
    __syncwarp();
#pragma unroll U
    for (int t = 0; t < 9; t++) {
      const bool ok = rb - 2 * t >= 0;
      float a0 = 0.f, a1 = 0.f, b0 = 0.f, b1 = 0.f;
#pragma unroll
      for (int i = 0; i < 9; i++) {
        const uint32_t k = lds32(kb[i] - t * 2304);
        const float lo = bf_lo(k), hi = bf_hi(k);
        a0 = fmaf(qa[2 * i], lo, a0); a1 = fmaf(qa[2 * i + 1], hi, a1);
        b0 = fmaf(qb[2 * i], lo, b0); b1 = fmaf(qb[2 * i + 1], hi, b1);
      }
      a0 = (ok && t > 0) ? a0 + a1 : -INFINITY;
      b0 = (ok && t < 8) ? b0 + b1 : -INFINITY;
      ma = fmaxf(ma, a0);
      mb = fmaxf(mb, b0);
      asm volatile("st.shared.f32 [%0], %1;" ::"r"(sq - 2304 + t * 128 + lane * 4), "f"(a0) : "memory");
      asm volatile("st.shared.f32 [%0], %1;" ::"r"(sq + t * 128 + lane * 4), "f"(b0) : "memory");
    }
  }
  float oa[18], ob[18], sa = 0.f, sb = 0.f;
#pragma unroll
  for (int i = 0; i < 18; i++) { oa[i] = 0.f; ob[i] = 0.f; }
  mbar_wait(bL2, 0);
#pragma unroll U
  for (int t = 0; t < 9; t++) {
    const float wa = ex2((__uint_as_float(lds32(sq - 2304 + t * 128 + lane * 4)) - ma) * scale_l2);
    const float wb = ex2((__uint_as_float(lds32(sq + t * 128 + lane * 4)) - mb) * scale_l2);
    sa += wa;
    sb += wb;
#pragma unroll
    for (int i = 0; i < 9; i++) {
      const uint32_t v = lds32(kb[i] + 46 * 1152 - t * 2304);
      const float lo = bf_lo(v), hi = bf_hi(v);
      oa[2 * i] = fmaf(wa, lo, oa[2 * i]); oa[2 * i + 1] = fmaf(wa, hi, oa[2 * i + 1]);
      ob[2 * i] = fmaf(wb, lo, ob[2 * i]); ob[2 * i + 1] = fmaf(wb, hi, ob[2 * i + 1]);
    }
  }
  ga = __fdividef(ga, sa);
  gb = __fdividef(gb, sb);
  __syncwarp();
#pragma unroll
  for (int i = 0; i < 9; i++) {
    asm volatile("st.shared.u32 [%0], %1;" ::"r"(sq - 2304 + lane * 36 + 4 * i), "r"(pack_bf16(oa[2 * i] * ga, oa[2 * i + 1] * ga)) : "memory");
    asm volatile("st.shared.u32 [%0], %1;" ::"r"(sq + lane * 36 + 4 * i), "r"(pack_bf16(ob[2 * i] * gb, ob[2 * i + 1] * gb)) : "memory");
  }
  __syncwarp();
  uint32_t w[5][4];
#pragma unroll
  for (int t = 0; t < 5; t++) {
    const int c = min(t * 32 + lane, 143), r = c >= 72;
    asm volatile("ld.shared.v4.u32 {%0, %1, %2, %3}, [%4];" : "=r"(w[t][0]), "=r"(w[t][1]), "=r"(w[t][2]), "=r"(w[t][3])
                 : "r"(sq - 2304 + r * 2304 + (c - r * 72) * 16) : "memory");
  }
  asm volatile("fence.proxy.async.shared::cta;" ::: "memory");
  bar_arrive(4, 256 + 32);
#pragma unroll
  for (int t = 0; t < 5; t++) {
    const int c = min(t * 32 + lane, 143), r = c >= 72;
    st_v4(g_ctx + (size_t)(rb - 2 + 2 * r) * KCAT + HDIM + (c - r * 72) * 8, w[t][0], w[t][1], w[t][2], w[t][3]);
  }
}

#define K1_NST 6
constexpr int K1_BST = K1_NST;
constexpr int K1_MAXJOBS = 11;
constexpr uint32_t K1_FLAG_TARGET = 7;
constexpr uint32_t RDY_TARGET = 48;
constexpr uint32_t GATE_TARGET = 128 * 3;
struct alignas(64) Params {
  CUtensorMap tmA[2];
  CUtensorMap tmW[4];
  CUtensorMap tmQ, tmK, tmV;
  CUtensorMap tmL[2];
  CUtensorMap tmC, tmO[2], tmOt[2];
  uint16_t jobs[NCLUSTER][K1_MAXJOBS + 1];
  uint8_t order[256];
  uint8_t unit[64][8];
};

struct K1State {
  uint32_t bs, bph, aph;
  bf16* pp;
  int pld8;
  int png;
  int tn;
  bool isq;
};
__device__ __forceinline__ void k1_flag(const K1State& st, int lane, uint32_t bS) {
  if (st.png) {
    __syncwarp();
    if (lane == 0) mbar_arrive(bS);
  }
}

__device__ __forceinline__ void scale_q4(uint32_t* v) {
#pragma unroll
  for (int i = 0; i < 4; i++)
    asm volatile("{\n.reg .b32 t;\nmul.rn.bf16x2 t, %0, %2;\nfma.rn.bf16x2 %0, %0, %1, t;\n}" : "+r"(v[i]) : "r"(0x3E033E03u), "r"(0xB9D8B9D8u));
}
__device__ __forceinline__ void k1_first(const K1State& st, uint32_t job, uint32_t bAf, uint32_t bBf) {
  if (job & 3) {
    if ((job >> 14) & 1) mbar_wait(bAf, st.aph);
    mbar_wait(bBf + st.bs * 8, st.bph);
  }
}
__device__ __forceinline__ void k1_tile(float (&acc)[128], uint32_t (&pk)[64], K1State& st, uint32_t job, uint32_t njob, uint32_t sA, uint32_t sB,
                                        uint32_t bAf, uint32_t bAe, uint32_t bBf, uint32_t bBe, uint32_t bS, int wg, int warp, int lane, uint32_t rank) {
  const int a_sel = (job >> 2) & 1, mpair = (job >> 3) & 7, w_sel = (job >> 6) & 3, chunk0 = (job >> 8) & 63;
  const bool newA = (job >> 14) & 1, lastA = (job >> 15) & 1;
  const bool sig = (lane == 0) && (warp < 2);
  const bool siga = lastA && (lane == 0) && (warp == 2);
  const int KC = 8 + a_sel;
  uint32_t prev_bs = 0, a8_bs = 0;
#pragma unroll
  for (int kc = 0; kc < 9; kc++) {
    if (kc >= KC) break;
    uint32_t abase = sA + ((kc + 2) & 7) * 16384;
    if (kc == 8) {
      mbar_wait(bBf + st.bs * 8, st.bph);
      a8_bs = st.bs;
      abase = sB + st.bs * 16384;
      if (++st.bs == K1_BST) { st.bs = 0; st.bph ^= 1; }
    } else if (newA && kc > 0) {
      mbar_wait(bAf + kc * 8, st.aph);
    }
    const uint64_t da = make_desc(abase + wg * 8192, 16, 1024, 1);
#pragma unroll
    for (int ks = 0; ks < 2; ks++) {
      if (ks > 0 || kc > 0) mbar_wait(bBf + st.bs * 8, st.bph);
      const uint64_t db = make_desc(sB + st.bs * 16384, 2048, 1024, 1);
      wg_fence();
      wgmma_ss_n256<1, 0>(acc, da + (uint64_t)(ks * 4), db, (ks > 0) ? 1 : (kc > 0));
      wgmma_ss_n256<1, 0>(acc, da + (uint64_t)(ks * 4 + 2), db + (uint64_t)512, 1);
      wg_commit();
      const int PO = (kc < 8 ? kc : 0) * 8;
      wg_wait<1>();
      if (ks > 0 || kc > 0) {
        if (sig) mbar_arrive_cluster(bBe + prev_bs * 8, warp);
        if (ks == 0 && siga) mbar_arrive(bAe + (kc - 1) * 8);
      }
      if (kc < 8 && st.isq) scale_q4(pk + PO + ks * 4);
      if (kc < st.png) st_v4a(st.pp + kc * 32 + ks * st.pld8, pk[PO + ks * 4], pk[PO + ks * 4 + 1], pk[PO + ks * 4 + 2], pk[PO + ks * 4 + 3]);
      prev_bs = st.bs;
      if (++st.bs == K1_BST) { st.bs = 0; st.bph ^= 1; }
    }
  }
  if (newA) st.aph ^= 1;
  k1_flag(st, lane, bS);
  const bool isA = (w_sel == 2);
  bf16* out = (w_sel == 0) ? g_K : (w_sel == 1) ? g_V : isA ? g_QKVA : g_Q;
  const int ld = isA ? NQKVA : HDIM;
  const int row = mpair * 256 + rank * 128 + wg * 64 + warp * 16 + (lane >> 2);
  st.pp = out + (size_t)row * ld + chunk0 * 64 + (lane & 3) * 8;
  st.pld8 = 8 * ld;
  st.png = ((job & 3) + 1) * 2;
  st.isq = (w_sel == 3);
  k1_first(st, njob, bAf, bBf);
  wg_wait<0>();
  fence_regs(acc);
  mbar_arrive_cluster_if(bBe + prev_bs * 8, warp & 1, sig);
  mbar_arrive_cluster_if(bBe + a8_bs * 8, warp & 1, sig && a_sel);
  mbar_arrive_if(bAe + 7 * 8, siga && !a_sel);
#pragma unroll
  for (int i = 0; i < 64; i++) {
    const int j = (i >> 3) * 16 + (i & 3) * 4 + ((i >> 2) & 1) * 2;
    pk[i] = pack_bf16(acc[j], acc[j + 1]);
  }
}

constexpr int K2_NST = 7;
constexpr uint32_t K2_END = 0x100;
#define PF_KC 7
#define FIRST_DRAW 3
#define PWAIT mbar_wait_ns<1000>
#define PVM 0x8A
#define W0 63
#define SPEC_HI 1.8446744073709552e19f
#define SPEC_LO 5.421010862427522e-20f
constexpr int K3_NST = 4;
__device__ __forceinline__ uint32_t k3_rot(uint32_t sv) { return (0x00E9u >> (2 * sv)) & 3; }
constexpr int K3_STAGE = 16384 + 32768 + 4096;
constexpr int SMEM_DATA = 7 * 32768;
constexpr int SMEM_BYTES = SMEM_DATA + 1024 + 768;

struct Cursor {
  uint32_t s, ph;
  __device__ __forceinline__ void next() {
    if (++s == K2_NST) { s = 0; ph ^= 1; }
  }
};

#define TURN_SYNC() bar_sync(mybar, 256)
#define TURN_ARRIVE() bar_arrive(otherbar, 256)
#define RELEASE_IF(cur, cond) mbar_arrive_cluster_if(bE + (cur).s * 8, warp & 1, sig && (cond))
#define RELEASE(cur) RELEASE_IF(cur, true)
#define ISSUE_PV(cur, first)                                                                                   \
  do {                                                                                                         \
    const uint64_t dv = make_desc(sbase + (cur).s * 32768, 16384, 1024, 1);                                    \
    _Pragma("unroll") for (int t = 0; t < 8; t++)                                                              \
        wgmma_rs_n128<1, 0>(O, P[4 * t], P[4 * t + 1], P[4 * t + 2], P[4 * t + 3], dv + (uint64_t)(t * 128), (t > 0) ? 1 : !(first)); \
  } while (0)
#define ISSUE_QK(cur)                                                                                          \
  do {                                                                                                         \
    const uint64_t dk = make_desc(sbase + (cur).s * 32768, 16, 1024, 1);                                       \
    _Pragma("unroll") for (int t = 0; t < 8; t++)                                                              \
        wgmma_rs_n128<0, 0>(S, Q[4 * t], Q[4 * t + 1], Q[4 * t + 2], Q[4 * t + 3], dk + (uint64_t)((t >> 2) * 1024 + (t & 3) * 2), t > 0); \
  } while (0)
#define EXPB(T)                                                                                                \
  do {                                                                                                         \
    _Pragma("unroll") for (int i = 4 * T; i < 4 * T + 4; i++) asm volatile("" : "+r"(P[i])::"memory");        \
    _Pragma("unroll") for (int jj = 2 * T; jj < 2 * T + 2; jj++) {                                             \
      const float e0 = ex2(S[jj * 4 + 0]), e1 = ex2(S[jj * 4 + 1]), e2 = ex2(S[jj * 4 + 2]), e3 = ex2(S[jj * 4 + 3]); \
      s0 += e0 + e1;                                                                                           \
      s1 += e2 + e3;                                                                                           \
      P[jj * 2 + 0] = pack_bf16(e0, e1);                                                                       \
      P[jj * 2 + 1] = pack_bf16(e2, e3);                                                                       \
    }                                                                                                          \
  } while (0)
#define EXPC(T)                                                                                                \
  do {                                                                                                         \
    if (T > 0 && ((PVM >> (T - 1)) & 1)) {                                                                     \
      anchor((T & 2) ? s0 : s1, never);                                                                        \
      wg_wait<__builtin_popcount(PVM >> T) - 1>();                                                             \
      if ((PVM >> T) == (128 >> T)) { fence_regs(O); RELEASE(cv); }                                            \
    }                                                                                                          \
    EXPB(T);                                                                                                   \
  } while (0)
#define MASK(G, g)                                                                                             \
  do {                                                                                                         \
    if ((g) * 8 > d) S[(G) * 4 + 0] = -INFINITY;                                                               \
    if ((g) * 8 + 1 > d) S[(G) * 4 + 1] = -INFINITY;                                                           \
    if ((g) * 8 - 8 > d) S[(G) * 4 + 2] = -INFINITY;                                                           \
    if ((g) * 8 - 7 > d) S[(G) * 4 + 3] = -INFINITY;                                                           \
  } while (0)
#define STORE_O(G)                                                                                             \
  do {                                                                                                         \
    st_v4(g_ctx + eoff + (G) * 32, pack_bf16(O[(G) * 16 + 0] * f0, O[(G) * 16 + 1] * f0), pack_bf16(O[(G) * 16 + 4] * f0, O[(G) * 16 + 5] * f0), \
          pack_bf16(O[(G) * 16 + 8] * f0, O[(G) * 16 + 9] * f0), pack_bf16(O[(G) * 16 + 12] * f0, O[(G) * 16 + 13] * f0)); \
    st_v4(g_ctx + eoff + 8 * KCAT + (G) * 32, pack_bf16(O[(G) * 16 + 2] * f1, O[(G) * 16 + 3] * f1), pack_bf16(O[(G) * 16 + 6] * f1, O[(G) * 16 + 7] * f1), \
          pack_bf16(O[(G) * 16 + 10] * f1, O[(G) * 16 + 11] * f1), pack_bf16(O[(G) * 16 + 14] * f1, O[(G) * 16 + 15] * f1)); \
  } while (0)

__global__ void __cluster_dims__(2, 1, 1) __launch_bounds__(384, 1)
fused_kernel(const __grid_constant__ Params p, const bf16* __restrict__ x, const bf16* __restrict__ gate_w, bf16* __restrict__ out) {
  extern __shared__ uint8_t smem_raw[];
  const uint32_t sbase = (smem_u32(smem_raw) + 1023) & ~1023u;
  const uint32_t sB = sbase, sA = sbase + K1_BST * 16384, sBar = sbase + SMEM_DATA;
  const uint32_t bAf = sBar, bAe = sBar + 64, bBf = sBar + 128, bBe = sBar + 176, bL = sBar + 224, bS = sBar + 232, bL2 = sBar + 240, sL = sA + 32768;
  const uint32_t bF = sBar + 256, bE = sBar + 320, bT = sBar + 384, sTick = sBar + 400, sItem = sBar + 416, bS2 = sBar + 448, bR = sBar + 456, bLast = sBar + 464, bH = sBar + 472, bT0 = sBar + 480;
  const uint32_t b3F = sBar + 512, b3E = sBar + 544, sGate = sBar + 576;
  const int tid = threadIdx.x, warp_g = __shfl_sync(0xffffffffu, tid >> 5, 0), lane = tid & 31;
  const uint32_t rank = cluster_rank();
  const int cl = blockIdx.x >> 1;
  TSM(0);
  if (tid == 0) {
    for (int i = 0; i < 8; i++) { mbar_init(bAf + i * 8, 1); mbar_init(bAe + i * 8, 2); }
    for (int i = 0; i < K1_BST; i++) { mbar_init(bBf + i * 8, 1); mbar_init(bBe + i * 8, 4); }
    mbar_init(bL, 1);
    mbar_init(bL2, 1);
    mbar_init(bR, 1);
    mbar_init(bLast, 1);
    mbar_init(bH, 4);
    mbar_init(bT0, 1);
    mbar_init(bS, 8);
    for (int i = 0; i < K2_NST; i++) { mbar_init(bF + i * 8, 1); mbar_init(bE + i * 8, 4); }
    mbar_init(bT, 1); mbar_init(bT + 8, 1);
    mbar_init(bS2, 8);
    for (int i = 0; i < K3_NST; i++) { mbar_init(b3F + i * 8, 1); mbar_init(b3E + i * 8, 4); }
    asm volatile("fence.mbarrier_init.release.cluster;" ::: "memory");
  }
  __syncthreads();
  cluster_sync();
  const int lr0 = blockIdx.x * 16;

  if (warp_g >= 8) {
    reg_dealloc<40>();
    if (warp_g == 8) {
      if (elect_one()) {
        uint32_t bs = 0, bph = 1, aph = 1;
#pragma unroll 1
        for (int ji = 0; ji < K1_MAXJOBS; ji++) {
          const uint32_t job = p.jobs[cl][ji];
          if (!(job & 3)) break;
          const int a_sel = (job >> 2) & 1, mpair = (job >> 3) & 7, chunk0 = (job >> 8) & 63;
          const bool newA = (job >> 14) & 1;
          const int KC = a_sel ? 9 : 8;
          const uint32_t halfbytes = 8192;
          const bool lastjob = (ji + 1 == K1_MAXJOBS) || !(p.jobs[cl][ji + 1] & 3);
          const CUtensorMap* tw = &p.tmW[(job >> 6) & 3];
          {
            const uint32_t njob = (ji + 1 < K1_MAXJOBS) ? p.jobs[cl][ji + 1] : 0;
            if (!(njob & 3) && !newA) mbar_arrive(bLast);
          }
#pragma unroll 1
          for (int kc = 0; kc < KC; kc++) {
            if (kc == ((ji == 0) ? PF_KC : 0) && !lastjob) {
              const uint32_t njob = p.jobs[cl][ji + 1];
              const int nst = ((njob >> 2) & 1) ? 18 : 16;
#pragma unroll 1
              for (int t = (cl < 64) ? (cl & 7) : 0; t < nst; t += (cl < 64) ? 8 : 1)
                tma_pf3d(&p.tmW[(njob >> 6) & 3], 0, t * 32 + rank * 16, (njob >> 8) & 63);
            }
            if (kc == 8) {
              PWAIT(bBe + bs * 8, bph);
              mbar_expect(bBf + bs * 8, 16384);
              tma2d(sB + bs * 16384, &p.tmA[1], bBf + bs * 8, 512, mpair * 256 + rank * 128);
              if (++bs == K1_BST) { bs = 0; bph ^= 1; }
            } else if (newA) {
              PWAIT(bAe + kc * 8, aph);
              mbar_expect(bAf + kc * 8, 16384);
              tma2d(sA + ((kc + 2) & 7) * 16384, &p.tmA[a_sel], bAf + kc * 8, kc * 64, mpair * 256 + rank * 128);
              if (kc == 7 && lastjob) mbar_arrive(bLast);
            }
#pragma unroll 1
            for (int kk = 0; kk < 2; kk++) {
              PWAIT(bBe + bs * 8, bph);
              mbar_expect(bBf + bs * 8, 2 * halfbytes);
              tma3d_mc(sB + bs * 16384 + rank * halfbytes, tw, bBf + bs * 8, 0, kc * 64 + kk * 32 + rank * 16, chunk0, 3);
              if (++bs == K1_BST) { bs = 0; bph ^= 1; }
            }
          }
          if (newA) aph ^= 1;
        }
        Cursor c{0, 0};
        int pcol = 0;
        PWAIT(bR, 0);
        uint32_t tick = lds32(sTick + 8), seen = 1u << (p.order[tick] >> 4);
        asm volatile("fence.proxy.async.global;" ::: "memory");
#pragma unroll 1
        for (int it = 0;; it++) {
          const uint32_t item = (tick < 256) ? p.order[tick] : (K2_END | min(tick - 256, 255u));
          asm volatile("st.shared.u32 [%0], %1;" ::"r"(sItem + (it & 7) * 4), "r"(item) : "memory");
          if (item >= K2_END) break;
          const int h = item >> 3, j = item & 7;
          const int blk = 2 * j + (int)(rank ^ (it & 1));
          const int col = h * 128 + rank * 64;
          const int nb = 2 * j + 2;
          if (!((seen >> (h >> 1)) & 1)) {
            wait_flag(&g_sync[F_HP + (h >> 1)], RDY_TARGET);
            asm volatile("fence.proxy.async.global;" ::: "memory");
            seen |= 1u << (h >> 1);
          }
          PWAIT(bE + c.s * 8, c.ph);
          mbar_expect(bF + c.s * 8, 32768);
          tma2d(sbase + c.s * 32768, &p.tmQ, bF + c.s * 8, h * 128, blk * 128);
          tma2d(sbase + c.s * 32768 + 16384, &p.tmQ, bF + c.s * 8, h * 128 + 64, blk * 128);
          c.next();
#pragma unroll 1
          for (int n = nb - 1; n >= 0; n--) {
            if (n == 0 && rank == 0) tick = atomicAdd(&g_sync[F_TICK], 1u);
            PWAIT(bE + c.s * 8, c.ph);
            mbar_expect(bF + c.s * 8, 32768);
            tma2d_mc(sbase + c.s * 32768 + rank * 16384, &p.tmK, bF + c.s * 8, col, n * 128, 3);
            c.next();
            if (n < nb - 1 || it > 0) {
              PWAIT(bE + c.s * 8, c.ph);
              mbar_expect(bF + c.s * 8, 32768);
              tma2d_mc(sbase + c.s * 32768 + rank * 16384, &p.tmV, bF + c.s * 8, (n < nb - 1) ? col : pcol, (n < nb - 1) ? (n + 1) * 128 : 0, 3);
              c.next();
            }
          }
          pcol = col;
          if (rank == 0) {
            asm volatile(
                "{\n.reg .b32 a, b;\nmapa.shared::cluster.u32 a, %0, 1;\nmapa.shared::cluster.u32 b, %1, 1;\n"
                "st.async.shared::cluster.mbarrier::complete_tx::bytes.u32 [a], %2, [b];\n}" ::"r"(sTick + (it & 1) * 4),
                "r"(bT + (it & 1) * 8), "r"(tick) : "memory");
          } else {
            mbar_expect(bT + (it & 1) * 8, 4);
            PWAIT(bT + (it & 1) * 8, (it >> 1) & 1);
            tick = lds32(sTick + (it & 1) * 4);
          }
        }
        PWAIT(bE + c.s * 8, c.ph);
        mbar_expect(bF + c.s * 8, 32768);
        tma2d_mc(sbase + c.s * 32768 + rank * 16384, &p.tmV, bF + c.s * 8, pcol, 0, 3);
        const uint32_t unit = tick - 256;
        if (unit < 64) {
          const int mblk = (7 - (p.unit[unit][0] >> 1)) * 2 + rank, nhalf = p.unit[unit][0] & 1;
          const uint32_t rot = k3_rot(c.s), nfree = ((0x1Au >> c.s) & 1) ? 2 : 3;
#pragma unroll 1
          for (int i = 0; i < K2_NST - 1; i++) {
            c.next();
            PWAIT(bE + c.s * 8, c.ph);
          }
          uint32_t have = 0;
#pragma unroll 1
          for (uint32_t idx = 0; idx < p.unit[unit][2]; idx++) {
            const int kk = p.unit[unit][3] + idx + ((idx >= p.unit[unit][4]) ? p.unit[unit][5] : 0);
            const uint32_t s = (rot + idx) & 3;
            if (idx >= nfree) PWAIT((idx < 4) ? bH : b3E + s * 8, (idx < 4) ? 0 : (~idx >> 2) & 1);
            mbar_expect(b3F + s * 8, K3_STAGE);
            const uint32_t st = sbase + s * K3_STAGE;
            const int sel = (kk < 9), k = sel ? kk : kk - 9, kr = k * 64 + rank * 32;
            tma3d_mc(st + 16384 + rank * 16384, &p.tmO[sel], b3F + s * 8, 0, kr, nhalf * 4, 3);
            tma2d_mc(st + 49152 + rank * 2048, &p.tmOt[sel], b3F + s * 8, 512 + nhalf * 32, kr, 3);
            if (sel && idx == 0) {
              wait_flag(&g_sync[F_OA + mblk], 8);
              asm volatile("fence.proxy.async.global;" ::: "memory");
            }
            if (!sel && !((have >> (k >> 1)) & 1)) {
#pragma unroll 1
              for (uint32_t spins = 0; spins < (1u << 22); spins++) {
                asm volatile("ld.acquire.gpu.global.u32 %0, [%1];" : "=r"(have) : "l"(&g_sync[F_CTX + mblk]) : "memory");
                if ((have >> (k >> 1)) & 1) break;
                __nanosleep(100);
              }
              asm volatile("fence.proxy.async.global;" ::: "memory");
            }
            tma2d(st, &p.tmC, b3F + s * 8, (sel ? 64 + k : k) * 64, mblk * 128);
          }
        }
      }
    }
    __syncwarp();
    if (warp_g == 8) {
      uint32_t v = 0;
      if (lane == 0) {
        __threadfence();
        v = atomicAdd(&g_sync[F_DONE], 1u);
      }
      if (__shfl_sync(0xffffffffu, v, 0) == 2 * NCLUSTER - 1) {
        reinterpret_cast<uint4*>(g_sync)[lane] = make_uint4(0, 0, 0, 0);
        if (lane == 0) g_sync[F_EPOCH] = lds32(sGate + 64) + 1;
      }
    }
    asm volatile("" ::: "memory");
    if (__shfl_sync(0xffffffffu, warp_g, 0) != 8) {
      if (lr0 < S_LEN) {
#pragma unroll 1
        for (int i = warp_g - 9; i < 16; i += 3) {
          const float g = gate_row(lr0 + i, lane, x, gate_w);
          if (lane == 0) asm volatile("st.shared.f32 [%0], %1;" ::"r"(sGate + i * 4), "f"(g) : "memory");
        }
        bar_arrive(3, 256 + 96);
        if (lane == 0) {
          __threadfence();
          atomicAdd(&g_sync[F_GATE], 1u);
        }
      }
      uint32_t aph = 1;
#pragma unroll 1
      for (int ji = 0; ji < K1_MAXJOBS; ji++) aph ^= (p.jobs[cl][ji] >> 14) & 1;
      if (warp_g == 9 && lane == 0) {
#pragma unroll 1
        for (int ji = 0; ji < K1_MAXJOBS; ji++) {
          const uint32_t job = p.jobs[cl][ji];
          if (!(job & 3)) break;
          PWAIT(bS, ji & 1);
          __threadfence();
          atomicAdd(&g_sync[(((job >> 6) & 3) == 2) ? (F_QKVA + ((job >> 3) & 7) * 2 + rank) : (F_HP + ((job >> 10) & 15))], 1u);
        }
#pragma unroll 1
        for (int it = 0;; it++) {
          PWAIT(bS2, it & 1);
          const uint32_t item = lds32(sItem + (it & 7) * 4), nxt = lds32(sItem + ((it + 1) & 7) * 4);
          __threadfence();
          atomicOr(&g_sync[F_CTX + (item & 7) * 2 + (rank ^ (it & 1))], 1u << (item >> 3));
          if (nxt >= K2_END) break;
        }
      } else if (warp_g == 11) {
        if (lane == 0) {
          prefetch_tmap(&p.tmQ); prefetch_tmap(&p.tmK); prefetch_tmap(&p.tmV);
          asm volatile("st.shared.u32 [%0], %1;" ::"r"(sGate + 64), "r"(__ldcg(&g_sync[F_EPOCH])) : "memory");
          wait_flag(&g_sync[F_GATE], GATE_TARGET);
          uint32_t tick;
          if (rank == 0) {
            PWAIT(bLast, 0);
            PWAIT(bAe + FIRST_DRAW * 8, aph);
            tick = atomicAdd(&g_sync[F_TICK], 1u);
            asm volatile("st.shared.u32 [%0], %1;" ::"r"(sTick + 8), "r"(tick) : "memory");
            asm volatile(
                "{\n.reg .b32 a, b;\nmapa.shared::cluster.u32 a, %0, 1;\nmapa.shared::cluster.u32 b, %1, 1;\n"
                "st.async.shared::cluster.mbarrier::complete_tx::bytes.u32 [a], %2, [b];\n}" ::"r"(sTick + 8), "r"(bT0), "r"(tick) : "memory");
          } else {
            mbar_expect(bT0, 4);
            PWAIT(bT0, 0);
            tick = lds32(sTick + 8);
          }
          wait_flag(&g_sync[F_HP + (p.order[tick] >> 4)], RDY_TARGET);
          mbar_arrive(bR);
        }
        __syncwarp();
        bar_sync(4, 256 + 32);
        if (lane < 12) mbar_arrive_cluster(bE + (4 + lane % 3) * 8, (lane / 3) & 1);
      } else if (warp_g == 10 && lr0 < S_LEN) {
        if (elect_one()) {
          prefetch_tmap(&p.tmL[0]); prefetch_tmap(&p.tmL[1]);
          wait_flag(&g_sync[F_QKVA + (lr0 >> 7)], K1_FLAG_TARGET);
          wait_flag(&g_sync[F_QKVA + (max(lr0 - 14, 0) >> 7)], K1_FLAG_TARGET);
          asm volatile("fence.proxy.async.global;" ::: "memory");
          PWAIT(bLast, 0);
#pragma unroll 1
          for (int kc = 0; kc < 6; kc++) {
            PWAIT(bAe + kc * 8, aph);
            if (kc == 3) {
              mbar_expect(bL, 46 * 1152);
              tma3d(sL, &p.tmL[0], bL, 0, 9, lr0 - 14);
              tma3d(sL + 30 * 1152, &p.tmL[1], bL, 0, 0, lr0);
            }
          }
          mbar_expect(bL2, 30 * 1152);
          tma3d(sL + 46 * 1152, &p.tmL[0], bL2, 0, 18, lr0 - 14);
        }
        __syncwarp();
        bar_sync(5, 256 + 32);
        if (lane == 0) {
          __threadfence();
          atomicAdd(&g_sync[F_OA + (lr0 >> 7)], 1u);
        }
      }
    }
    __syncwarp();
    cluster_sync();
  } else {
    reg_alloc<232>();
    const int wg = warp_g >> 2, warp = warp_g & 3, q = lane & 3;
    const bool sig = (lane == 0) && (warp < 2);
    {
      K1State st{0, 0, 0, nullptr, 0, 0, 0, false};
      float acc[128];
      uint32_t pk[64];
      if (wg == 0) { TS(0, 0); TSC(0, 2); }
      uint32_t job = p.jobs[cl][0];
      k1_first(st, job, bAf, bBf);
#pragma unroll 1
      for (int ji = 0; job & 3; ji++) {
        const uint32_t njob = p.jobs[cl][ji + 1];
        k1_tile(acc, pk, st, job, njob, sA, sB, bAf, bAe, bBf, bBe, bS, wg, warp, lane, rank);
        job = njob;
      }
#pragma unroll
      for (int i = 0; i < 4; i++)
        mbar_arrive_cluster_if(bE + i * 8, warp & 1, sig);
      if (st.isq) {
#pragma unroll
        for (int G = 0; G < 16; G++) scale_q4(pk + G * 4);
      }
#pragma unroll
      for (int G = 0; G < 8; G++)
        if (G < st.png) {
          st_v4a(st.pp + G * 32, pk[G * 8], pk[G * 8 + 1], pk[G * 8 + 2], pk[G * 8 + 3]);
          st_v4a(st.pp + G * 32 + st.pld8, pk[G * 8 + 4], pk[G * 8 + 5], pk[G * 8 + 6], pk[G * 8 + 7]);
        }
      k1_flag(st, lane, bS);
      if (wg == 0) { TS(0, 1); TSC(0, 3); }
      if (lr0 < S_LEN) {
        const int ri = (warp_g >> 1) * 4 + (warp_g & 1) + 2, row = lr0 + ri;
        if (wg == 0) TS(1, 5);
        bar_sync(3, 256 + 96);
        const float gate0 = __uint_as_float(lds32(sGate + ri * 4 - 8)), gate1 = __uint_as_float(lds32(sGate + ri * 4));
        mbar_wait(bL, 0);
        if (wg == 0) TS(1, 6);
        local_rows2(row, ri, sL, bL2, lane, gate0, gate1);
        bar_arrive(5, 256 + 32);
      } else {
        bar_arrive(4, 256 + 32);
      }
    }
    __syncwarp();
    uint32_t item, rot;
    {
      const int mybar = 1 + wg, otherbar = 2 - wg;
      const uint32_t never = blockIdx.y;
      float S[64], O[64];
      uint32_t P[32], Q[32];
      float m0 = 0.f, m1 = 0.f, l0 = 1.f, l1 = 1.f, gf0 = 0.f, gf1 = 0.f;
      uint32_t eoff = 0, prev_single = 0;
      Cursor c{0, 0};
      if (wg == 1) bar_arrive(1, 256);
      if (wg == 0) { TS(1, 0); TSC(1, 2); }
#pragma unroll 1
      for (int it = 0;; it++) {
        TB(0);
        const int hi = (int)(rank ^ (it & 1));
        Cursor cq = c, ck, cv, cs0, cs1;
        rot = k3_rot(c.s);
        c.next();
        ck = c; c.next();
        cs0 = ck; cs1 = ck; cv = ck;
        if (it > 0) { cv = c; c.next(); }
        if (!hi) {
          ck = c; c.next();
          cs1 = c; c.next();
        }
        mbar_wait(bF + cq.s * 8, cq.ph);
        TB(1);
        item = lds32(sItem + (it & 7) * 4);
        {
          const uint32_t qa = sbase + cq.s * 32768 + (wg * 64 + warp * 16 + (lane & 15)) * 128;
#pragma unroll
          for (int t = 0; t < 8; t++)
            ldsm_x4(Q[4 * t], Q[4 * t + 1], Q[4 * t + 2], Q[4 * t + 3], qa + (t >> 2) * 16384 + ((((t & 3) * 2 + (lane >> 4)) ^ (lane & 7)) << 4));
        }
        const uint32_t rdy = mbar_test(bF + ck.s * 8, ck.ph) & mbar_test(bF + cv.s * 8, cv.ph);
        l0 += __shfl_xor_sync(0xffffffffu, l0, 1);
        l1 += __shfl_xor_sync(0xffffffffu, l1, 1);
        l0 += __shfl_xor_sync(0xffffffffu, l0, 2);
        l1 += __shfl_xor_sync(0xffffffffu, l1, 2);
        const bool last = item >= K2_END;
        if (last) {
          cv = cq; ck = cq;
        } else if (!rdy) {
          mbar_wait2(bF + ck.s * 8, ck.ph, bF + cv.s * 8, cv.ph);
        }
        TB(2);
        TURN_SYNC();
        TB(3);
        TRC(last ? 2 : 1);
        if (it > 0) {
          wg_fence();
          ISSUE_PV(cv, prev_single);
          wg_commit();
        } else {
          wg_fence();
          wg_commit();
        }
        wg_fence();
        ISSUE_QK(ck);
        wg_commit();
        if (!(last && wg == 1)) TURN_ARRIVE();
        RELEASE_IF(cq, !last);
        TB(4);
        asm volatile("" : "+f"(gf0), "+f"(gf1), "+f"(l0), "+f"(l1));
        const float f0 = __fdividef(1.f - gf0, l0), f1 = __fdividef(1.f - gf1, l1);
        wg_wait<1>();
        fence_regs(O);
        fence_regs(P);
        TB(5);
        if (it > 0) {
          RELEASE_IF(cv, !last);
          mbar_arrive_cluster_if(bH, warp & 1, sig && last);
          STORE_O(0); STORE_O(1); STORE_O(2); STORE_O(3);
          __syncwarp();
          mbar_arrive_if(bS2, lane == 0);
        }
        TB(6);
        if (!last) {
          const int row = (2 * (item & 7) + hi) * 128 + wg * 64 + warp * 16 + (lane >> 2);
          eoff = row * KCAT + (item >> 3) * 128 + q * 8;
          asm volatile("ld.global.f32 %0, [%1];" : "=f"(gf0) : "l"(g_gate + row));
          asm volatile("ld.global.f32 %0, [%1];" : "=f"(gf1) : "l"(g_gate + row + 8));
          if (!hi) {
            mbar_wait2(bF + cs0.s * 8, cs0.ph, bF + cs1.s * 8, cs1.ph);
            RELEASE(cs0);
            RELEASE(cs1);
          }
        }
        TB(7);
        wg_wait<0>();
        fence_regs(S);
        TB(8);
        if (last) break;
        RELEASE(ck);
        const int nblk = 2 * (item & 7) + 1 + hi;
        prev_single = (nblk == 1);
        float s0 = 0.f, s1 = 0.f;
        l0 = 0.f; l1 = 0.f;
        m0 = 0.f; m1 = 0.f;
        bool shifted = false;
        {
          const int d = warp * 16 + (lane >> 2) - 2 * q;
          if (wg == 0) {
#pragma unroll
            for (int jj = 0; jj < 8; jj++) MASK(jj, jj);
            EXPB(0); EXPB(1); EXPB(2); EXPB(3);
#pragma unroll
            for (int i = 32; i < 64; i++) S[i] = -INFINITY;
#pragma unroll
            for (int i = 16; i < 32; i++) P[i] = 0;
          } else {
#pragma unroll
            for (int jj = 0; jj < 8; jj++) MASK(jj + 8, jj);
            EXPB(0); EXPB(1); EXPB(2); EXPB(3); EXPB(4); EXPB(5); EXPB(6); EXPB(7);
          }
        }
        float chk = (q == 0 && !(fminf(s0, s1) >= SPEC_LO)) ? INFINITY : s0 + s1;
        fence_regs(P);
        TB(9);
#pragma unroll 1
        for (int n = 1;; n++) {
          if (__any_sync(0xffffffffu, !(chk <= SPEC_HI))) {
            float mx0 = fmaxf(S[0], S[1]), mx1 = fmaxf(S[2], S[3]);
#pragma unroll
            for (int jj = 1; jj < 16; jj++) {
              mx0 = fmaxf(mx0, fmaxf(S[jj * 4 + 0], S[jj * 4 + 1]));
              mx1 = fmaxf(mx1, fmaxf(S[jj * 4 + 2], S[jj * 4 + 3]));
            }
            mx0 = fmaxf(mx0, __shfl_xor_sync(0xffffffffu, mx0, 1));
            mx1 = fmaxf(mx1, __shfl_xor_sync(0xffffffffu, mx1, 1));
            mx0 = fmaxf(mx0, __shfl_xor_sync(0xffffffffu, mx0, 2));
            mx1 = fmaxf(mx1, __shfl_xor_sync(0xffffffffu, mx1, 2));
            const float lo = (n == 1) ? -INFINITY : 0.f;
            mx0 = fmaxf(mx0, lo);
            mx1 = fmaxf(mx1, lo);
            m0 += mx0; m1 += mx1;
            shifted = true;
            const float sc0 = ex2(-fmaxf(mx0, 0.f)), sc1 = ex2(-fmaxf(mx1, 0.f));
            l0 *= sc0; l1 *= sc1;
            s0 = 0.f; s1 = 0.f;
#pragma unroll
            for (int jj = 0; jj < 16; jj++) {
              const float e0 = ex2(S[jj * 4 + 0] - mx0), e1 = ex2(S[jj * 4 + 1] - mx0), e2 = ex2(S[jj * 4 + 2] - mx1), e3 = ex2(S[jj * 4 + 3] - mx1);
              s0 += e0 + e1;
              s1 += e2 + e3;
              P[jj * 2 + 0] = pack_bf16(e0, e1);
              P[jj * 2 + 1] = pack_bf16(e2, e3);
              O[jj * 4 + 0] *= sc0;
              O[jj * 4 + 1] *= sc0;
              O[jj * 4 + 2] *= sc1;
              O[jj * 4 + 3] *= sc1;
            }
          }
          l0 += s0;
          l1 += s1;
          if (n >= nblk) break;
          ck = c; c.next();
          cv = c; c.next();
          mbar_wait(bF + ck.s * 8, ck.ph);
          mbar_wait(bF + cv.s * 8, cv.ph);
          TURN_SYNC();
          TRC(0);
          wg_fence();
          ISSUE_QK(ck);
          wg_commit();
          {
            const uint64_t dv = make_desc(sbase + cv.s * 32768, 16384, 1024, 1);
#pragma unroll
            for (int t = 0; t < 8; t++) {
              wgmma_rs_n128<1, 0>(O, P[4 * t], P[4 * t + 1], P[4 * t + 2], P[4 * t + 3], dv + (uint64_t)(t * 128), (t > 0) ? 1 : (n != 1));
              if ((PVM >> t) & 1) wg_commit();
            }
          }
          TURN_ARRIVE();
          s0 = 0.f; s1 = 0.f;
          wg_wait<__builtin_popcount(PVM)>();
          fence_regs(S);
          RELEASE(ck);
          if (shifted) {
#pragma unroll
            for (int i = 0; i < 64; i++) S[i] -= (i & 2) ? m1 : m0;
          }
          wg_wait<__builtin_popcount(PVM) - 1>();
          EXPC(0); EXPC(1); EXPC(2); EXPC(3); EXPC(4); EXPC(5); EXPC(6); EXPC(7);
          chk = s0 + s1;
        }
      }
      TRC(3);
      if (wg == 1) { TS(1, 1); TSC(1, 3); }
    }
    __syncwarp();
    const uint32_t unit = item & 255;
    if (unit < 64) {
      const int mblk = (7 - (p.unit[unit][0] >> 1)) * 2 + rank, nhalf = p.unit[unit][0] & 1, ks = p.unit[unit][1];
      const int k0 = 0, k1 = p.unit[unit][2];
      float acc[144];
      uint32_t s = rot, ph = 0, prev = 0;
      if (wg == 0) { TS(2, 0); TSC(2, 2); }
#pragma unroll 1
      for (int k = k0; k < k1; k++) {
        mbar_wait(b3F + s * 8, ph);
        const uint32_t st = sbase + s * K3_STAGE;
        const uint64_t da = make_desc(st + wg * 8192, 16, 1024, 1);
        const uint64_t db = make_desc(st + 16384, 4096, 1024, 1);
        const uint64_t dt = make_desc(st + 49152, 16, 512, 2);
        wg_fence();
#pragma unroll
        for (int t = 0; t < 4; t++) {
          const int sd = (t > 0) || (k > k0);
          wgmma_ss_n256<1, 0>(acc, da + (uint64_t)(t * 2), db + (uint64_t)((t >> 1) * 1024 + (t & 1) * 128), sd);
          wgmma_ss_n32<1, 128>(acc, da + (uint64_t)(t * 2), dt + (uint64_t)(t * 64), sd);
        }
        wg_commit();
        if (k > k0) {
          wg_wait<1>();
          if (sig) mbar_arrive_cluster(b3E + prev * 8, warp);
        }
        prev = s;
        s = (s + 1) & 3;
        if (s == rot) ph ^= 1;
      }
      wg_wait<0>();
      fence_regs(acc);
      cluster_arrive();
      if (wg == 0) TS(2, 4);
      const int tile = mblk * 2 + nhalf;
      uint4* wp = g_part + (size_t)((tile * 4 + ks) * 4) * 5 * 256 + tid;
      const uint32_t sown = sbase + wg * 8192 + (tid & 127) * 16;
#pragma unroll
      for (int d = 0; d < 4; d++) {
        if (d != ks) {
#pragma unroll
          for (int i = 0; i < 4; i++)
            __stcg(wp + (d * 5 + i) * 256,
                   make_uint4(pack_bf16(acc[d * 32 + i * 8], acc[d * 32 + i * 8 + 1]), pack_bf16(acc[d * 32 + i * 8 + 2], acc[d * 32 + i * 8 + 3]),
                              pack_bf16(acc[d * 32 + i * 8 + 4], acc[d * 32 + i * 8 + 5]), pack_bf16(acc[d * 32 + i * 8 + 6], acc[d * 32 + i * 8 + 7])));
          __stcg(reinterpret_cast<uint2*>(wp - tid + (d * 5 + 4) * 256) + tid,
                 make_uint2(pack_bf16(acc[128 + d * 4], acc[128 + d * 4 + 1]), pack_bf16(acc[128 + d * 4 + 2], acc[128 + d * 4 + 3])));
        } else {
#pragma unroll
          for (int i = 0; i < 9; i++) {
            const int o = (i < 8) ? d * 32 + i * 4 : 128 + d * 4;
            asm volatile("st.shared.v4.f32 [%0], {%1, %2, %3, %4};" ::"r"(sown + (i >> 2) * K3_STAGE + (i & 3) * 2048), "f"(acc[o]), "f"(acc[o + 1]), "f"(acc[o + 2]), "f"(acc[o + 3]) : "memory");
          }
        }
      }
      __threadfence();
      __syncwarp();
      if (wg == 0) TS(2, 5);
      if (lane == 0) {
        unsigned int* cnt = &g_sync[F_XCH + tile * 8 + warp_g];
        const uint32_t xtarget = lds32(sGate + 64) * 4 + 4;
        atomicAdd(cnt, 1u);
        uint32_t v, spins = 0;
        do {
          asm volatile("ld.acquire.gpu.global.u32 %0, [%1];" : "=r"(v) : "l"(cnt) : "memory");
        } while ((int)(v - xtarget) < 0 && ++spins < (1u << 24));
      }
      __syncwarp();
      if (wg == 0) TS(2, 6);
      float r[36];
#pragma unroll
      for (int i = 0; i < 9; i++)
        asm volatile("ld.shared.v4.f32 {%0, %1, %2, %3}, [%4];" : "=f"(r[i * 4]), "=f"(r[i * 4 + 1]), "=f"(r[i * 4 + 2]), "=f"(r[i * 4 + 3])
                     : "r"(sown + (i >> 2) * K3_STAGE + (i & 3) * 2048) : "memory");
#pragma unroll
      for (int sI = 1; sI < 4; sI++) {
        const int src = (ks + sI) & 3;
        const uint4* rp = g_part + (size_t)(((tile * 4 + src) * 4) + ks) * 5 * 256;
#pragma unroll
        for (int i = 0; i < 4; i++) {
          const uint4 v = __ldcg(rp + i * 256 + tid);
          r[i * 8] += bf_lo(v.x); r[i * 8 + 1] += bf_hi(v.x); r[i * 8 + 2] += bf_lo(v.y); r[i * 8 + 3] += bf_hi(v.y);
          r[i * 8 + 4] += bf_lo(v.z); r[i * 8 + 5] += bf_hi(v.z); r[i * 8 + 6] += bf_lo(v.w); r[i * 8 + 7] += bf_hi(v.w);
        }
        const uint2 v = __ldcg(reinterpret_cast<const uint2*>(rp + 4 * 256) + tid);
        r[32] += bf_lo(v.x); r[33] += bf_hi(v.x); r[34] += bf_lo(v.y); r[35] += bf_hi(v.y);
      }
      const int row = mblk * 128 + wg * 64 + warp * 16 + (lane >> 2);
      bf16* o0 = out + (size_t)row * DM + nhalf * 256 + ks * 64 + 8 * q;
#pragma unroll
      for (int G = 0; G < 2; G++) {
        uint32_t a0 = pack_bf16(r[G * 16], r[G * 16 + 1]), a1 = pack_bf16(r[G * 16 + 4], r[G * 16 + 5]);
        uint32_t a2 = pack_bf16(r[G * 16 + 8], r[G * 16 + 9]), a3 = pack_bf16(r[G * 16 + 12], r[G * 16 + 13]);
        uint32_t b0 = pack_bf16(r[G * 16 + 2], r[G * 16 + 3]), b1 = pack_bf16(r[G * 16 + 6], r[G * 16 + 7]);
        uint32_t b2 = pack_bf16(r[G * 16 + 10], r[G * 16 + 11]), b3 = pack_bf16(r[G * 16 + 14], r[G * 16 + 15]);
        quad_transpose(a0, a1, a2, a3, q);
        quad_transpose(b0, b1, b2, b3, q);
        st_v4(o0 + G * 32, a0, a1, a2, a3);
        st_v4(o0 + 8 * DM + G * 32, b0, b1, b2, b3);
      }
      {
        uint32_t t0 = pack_bf16(r[32], r[33]), t1 = pack_bf16(r[34], r[35]), t2 = 0, t3 = 0;
        quad_transpose(t0, t1, t2, t3, q);
        if (q < 2) st_v4(out + (size_t)(row + q * 8) * DM + 512 + nhalf * 32 + ks * 8, t0, t1, t2, t3);
      }
    } else {
      cluster_arrive();
    }
    if (wg == 0) { TS(2, 1); TSC(2, 3); }
    cluster_wait();
  }
}

typedef CUresult (*EncFn)(CUtensorMap*, CUtensorMapDataType, cuuint32_t, void*, const cuuint64_t*, const cuuint64_t*, const cuuint32_t*,
                          const cuuint32_t*, CUtensorMapInterleave, CUtensorMapSwizzle, CUtensorMapL2promotion, CUtensorMapFloatOOBfill);

static void enc2d(EncFn enc, CUtensorMap* m, const void* ptr, uint64_t cols, uint64_t rows, uint32_t bc, uint32_t br,
                  CUtensorMapSwizzle sw = CU_TENSOR_MAP_SWIZZLE_128B) {
  cuuint64_t gd[2] = {cols, rows}, gs[1] = {cols * 2};
  cuuint32_t bx[2] = {bc, br}, es[2] = {1, 1};
  enc(m, CU_TENSOR_MAP_DATA_TYPE_BFLOAT16, 2, const_cast<void*>(ptr), gd, gs, bx, es, CU_TENSOR_MAP_INTERLEAVE_NONE, sw,
      CU_TENSOR_MAP_L2_PROMOTION_L2_256B, CU_TENSOR_MAP_FLOAT_OOB_FILL_NONE);
}
static void enc3d(EncFn enc, CUtensorMap* m, const void* ptr, uint64_t cols, uint64_t rows, uint32_t br, uint32_t bch) {
  cuuint64_t gd[3] = {64, rows, cols / 64}, gs[2] = {cols * 2, 128};
  cuuint32_t bx[3] = {64, br, bch}, es[3] = {1, 1, 1};
  enc(m, CU_TENSOR_MAP_DATA_TYPE_BFLOAT16, 3, const_cast<void*>(ptr), gd, gs, bx, es, CU_TENSOR_MAP_INTERLEAVE_NONE,
      CU_TENSOR_MAP_SWIZZLE_128B, CU_TENSOR_MAP_L2_PROMOTION_L2_256B, CU_TENSOR_MAP_FLOAT_OOB_FILL_NONE);
}

static int g_sched[10] = {11, 10, 7, 4, 4, 5, 6, 6, 8, 20};
static void build_k1_jobs(Params& p) {
  int cnt[NCLUSTER];
  for (int c = 0; c < NCLUSTER; c++) {
    cnt[c] = 0;
    for (int i = 0; i <= K1_MAXJOBS; i++) p.jobs[c][i] = 0;
  }
  auto add = [&](int c, int nch, int a_sel, int mp, int w_sel, int chunk0) {
    p.jobs[c][cnt[c]++] = (uint16_t)((nch - 1) | (a_sel << 2) | (mp << 3) | (w_sel << 6) | (chunk0 << 8));
  };
  const int *cg = g_sched, *xg = g_sched + 4;
  for (int mp = 0; mp < 8; mp++) {
    int k = 0;
    for (int i = 0; i < K1_MAXJOBS; i++)
      for (int g = 0; g < 4; g++)
        if (i < cg[g]) { add(g * 8 + mp, 4, 0, mp, k & 1, (k >> 1) * 4); k++; }
    k = 0;
    for (int i = 0; i < K1_MAXJOBS; i++)
      for (int g = 0; g < 4; g++)
        if (i < xg[g]) {
          if (k < 7) add((4 + g) * 8 + mp, k == 0 ? 3 : 4, 1, mp, 2, k == 0 ? 24 : (k - 1) * 4);
          else add((4 + g) * 8 + mp, 4, 1, mp, 3, (k - 7) * 4);
          k++;
        }
    add(64 + mp / 4, 4, 1, mp, 3, 14 * 4);
    add(64 + mp / 4, 4, 1, mp, 3, 15 * 4);
  }
  for (int cc = 0; cc < NCLUSTER; cc++)
    for (int i = 0; i < cnt[cc]; i++) {
      const int key = p.jobs[cc][i] & 0x3C;
      if (i == 0 || (p.jobs[cc][i - 1] & 0x3C) != key) p.jobs[cc][i] |= (1 << 14);
      if (i == cnt[cc] - 1 || (p.jobs[cc][i + 1] & 0x3C) != key) p.jobs[cc][i] |= (1 << 15);
    }
}

static void build_k2_items(Params& p) {
  int n = 0;
  const int SCHED_N1 = g_sched[8], SCHED_N2 = g_sched[9];
  for (int j = 7; j >= 0; j--)
    for (int h = 0; h < SCHED_N1; h++) p.order[n++] = (uint8_t)(h * 8 + j);
  for (int j = 7; j >= 4; j--)
    for (int h = SCHED_N1; h < SCHED_N2; h++) p.order[n++] = (uint8_t)(h * 8 + j);
  for (int j = 7; j >= 0; j--)
    for (int h = SCHED_N1; h < 32; h++)
      if (!(h < SCHED_N2 && j >= 4)) p.order[n++] = (uint8_t)(h * 8 + j);
}

static void build_k3_units(Params& p) {
  float slope = 0.045f;
  int NE = 25;
  for (int t = 0; t < 16; t++) {
    const int u[4] = {t, 31 - t, 32 + t, 63 - t};
    float acc = 0.f;
    int k0 = 0, l0 = NE;
    for (int i = 0; i < 4; i++) {
      acc += 18.25f + slope * (31.5f - u[i]);
      const int k1 = (i == 3) ? 73 : (int)(acc + 0.5f);
      const int e0 = NE * i / 4, e1 = NE * (i + 1) / 4;
      uint8_t* w = p.unit[u[i]];
      w[0] = (uint8_t)t; w[1] = (uint8_t)i; w[2] = (uint8_t)(k1 - k0); w[3] = (uint8_t)e0; w[4] = (uint8_t)(e1 - e0); w[5] = (uint8_t)(l0 - e1);
      l0 += (k1 - k0) - (e1 - e0);
      k0 = k1;
    }
  }
}

extern "C" void kernel_launch(void* const* d_in, const int* in_sizes, int n_in, void* d_out, int out_size) {
  const bf16* x = (const bf16*)d_in[0];
  const bf16* wqkv = (const bf16*)d_in[1];
  const bf16* wo = (const bf16*)d_in[2];
  const bf16* ckv = (const bf16*)d_in[4];
  const bf16* w_q = (const bf16*)d_in[5];
  const bf16* w_uk = (const bf16*)d_in[6];
  const bf16* w_uv = (const bf16*)d_in[7];
  const bf16* w_o = (const bf16*)d_in[8];
  const bf16* gate_w = (const bf16*)d_in[9];

  EncFn enc = nullptr;
  cudaDriverEntryPointQueryResult qr;
  cudaGetDriverEntryPoint("cuTensorMapEncodeTiled", (void**)&enc, cudaEnableDefault, &qr);
  void *pQ, *pK, *pV, *pCtx, *pQA;
  cudaGetSymbolAddress(&pQ, g_Q);
  cudaGetSymbolAddress(&pQA, g_QKVA);
  cudaGetSymbolAddress(&pK, g_K);
  cudaGetSymbolAddress(&pV, g_V);
  cudaGetSymbolAddress(&pCtx, g_ctx);

  static Params p;
  enc2d(enc, &p.tmA[0], ckv, DC, S_LEN, 64, 128);
  enc2d(enc, &p.tmA[1], x, DM, S_LEN, 64, 128);
  enc3d(enc, &p.tmW[0], w_uk, HDIM, DC, 16, 4);
  enc3d(enc, &p.tmW[1], w_uv, HDIM, DC, 16, 4);
  enc3d(enc, &p.tmW[2], wqkv, NQKVA, DM, 16, 4);
  enc3d(enc, &p.tmW[3], w_q, HDIM, DM, 16, 4);
  build_k1_jobs(p);
  enc2d(enc, &p.tmQ, pQ, HDIM, S_LEN, 64, 128);
  enc2d(enc, &p.tmK, pK, HDIM, S_LEN, 64, 128);
  enc2d(enc, &p.tmV, pV, HDIM, S_LEN, 64, 128);
  build_k2_items(p);
  build_k3_units(p);
  for (int i = 0; i < 2; i++) {
    cuuint64_t gd[3] = {64, 27, S_LEN}, gs[2] = {128, NQKVA * 2};
    cuuint32_t bx[3] = {64, 9, i ? 16u : 30u}, es[3] = {1, 1, 1};
    enc(&p.tmL[i], CU_TENSOR_MAP_DATA_TYPE_BFLOAT16, 3, pQA, gd, gs, bx, es, CU_TENSOR_MAP_INTERLEAVE_NONE, CU_TENSOR_MAP_SWIZZLE_NONE,
        CU_TENSOR_MAP_L2_PROMOTION_L2_256B, CU_TENSOR_MAP_FLOAT_OOB_FILL_NONE);
  }
  enc2d(enc, &p.tmC, pCtx, KCAT, S_LEN, 64, 128);
  enc3d(enc, &p.tmO[0], w_o, DM, HDIM, 32, 4);
  enc3d(enc, &p.tmO[1], wo, DM, DM, 32, 4);
  enc2d(enc, &p.tmOt[0], w_o, DM, HDIM, 32, 32, CU_TENSOR_MAP_SWIZZLE_64B);
  enc2d(enc, &p.tmOt[1], wo, DM, DM, 32, 32, CU_TENSOR_MAP_SWIZZLE_64B);

  cudaFuncSetAttribute(fused_kernel, cudaFuncAttributeMaxDynamicSharedMemorySize, SMEM_BYTES);
  fused_kernel<<<NCLUSTER * 2, 384, SMEM_BYTES>>>(p, x, gate_w, (bf16*)d_out);
}
```

```cpp
#include <cuda_runtime.h>
#include <cuda_bf16.h>
#include <cuda.h>
#include <stdint.h>

typedef __nv_bfloat16 bf16;

constexpr int S_LEN = 2048, DM = 576, DC = 512, HDIM = 4096, NQKVA = 1728, KCAT = 4672;
constexpr int NCLUSTER = 66;

__device__ __align__(1024) bf16 g_Q[S_LEN * HDIM];
__device__ __align__(1024) bf16 g_K[S_LEN * HDIM];
__device__ __align__(1024) bf16 g_V[S_LEN * HDIM];
__device__ __align__(1024) bf16 g_QKVA[S_LEN * NQKVA + 64];
__device__ __align__(1024) bf16 g_ctx[S_LEN * KCAT];
__device__ float g_gate[S_LEN];
__device__ __align__(1024) uint4 g_part[32 * 4 * 4 * 5 * 256];
__device__ __align__(16) unsigned int g_sync[400];
constexpr int F_QKVA = 0, F_HP = 16, F_CTX = 32, F_OA = 48, F_GATE = 96, F_TICK = 97, F_DONE = 98, F_XCH = 128, F_EPOCH = 384;

__device__ __forceinline__ uint32_t smem_u32(const void* p) { return (uint32_t)__cvta_generic_to_shared(p); }
__device__ __forceinline__ void mbar_init(uint32_t a, uint32_t c) {
  asm volatile("mbarrier.init.shared::cta.b64 [%0], %1;" ::"r"(a), "r"(c));
}
__device__ __forceinline__ void mbar_expect(uint32_t a, uint32_t b) {
  asm volatile("mbarrier.arrive.expect_tx.shared::cta.b64 _, [%0], %1;" ::"r"(a), "r"(b) : "memory");
}
#define TS(k, i)
#define TSC(k, i)
#define TSM(k)
#define BSEG(i)
#define TB(k)
#define TRC(fl)
#define SPIN_LIMIT "4194304"
__device__ __forceinline__ void mbar_wait(uint32_t a, uint32_t parity) {
  asm volatile(
      "{\n.reg .pred p;\n.reg .u32 n;\n"
      "mbarrier.try_wait.parity.shared::cta.b64 p, [%0], %1;\n"
      "@p bra DONE;\n"
      "mov.u32 n, 0;\n"
      "LOOP:\n"
      "mbarrier.try_wait.parity.shared::cta.b64 p, [%0], %1;\n"
      "@p bra DONE;\n"
      "add.u32 n, n, 1;\n"
      "setp.lt.u32 p, n, " SPIN_LIMIT ";\n"
      "@p bra LOOP;\n"
      "DONE:\n}" ::"r"(a), "r"(parity) : "memory");
}
template <int NS>
__device__ __forceinline__ void mbar_wait_ns(uint32_t a, uint32_t parity) {
  asm volatile(
      "{\n.reg .pred p;\n.reg .u32 n;\n"
      "mov.u32 n, 0;\n"
      "LOOP:\n"
      "mbarrier.try_wait.parity.shared::cta.b64 p, [%0], %1, %2;\n"
      "@p bra DONE;\n"
      "add.u32 n, n, 1;\n"
      "setp.lt.u32 p, n, " SPIN_LIMIT ";\n"
      "@p bra LOOP;\n"
      "DONE:\n}" ::"r"(a), "r"(parity), "n"(NS) : "memory");
}
__device__ __forceinline__ void mbar_wait2(uint32_t a, uint32_t pa, uint32_t b, uint32_t pb) {
  asm volatile(
      "{\n.reg .pred p, q;\n.reg .u32 n;\n"
      "mov.u32 n, 0;\n"
      "LOOP:\n"
      "mbarrier.try_wait.parity.shared::cta.b64 p, [%0], %1;\n"
      "mbarrier.try_wait.parity.shared::cta.b64 q, [%2], %3;\n"
      "add.u32 n, n, 1;\n"
      "and.pred p, p, q;\n"
      "setp.lt.and.u32 p, n, " SPIN_LIMIT ", !p;\n"
      "@p bra LOOP;\n"
      "}" ::"r"(a), "r"(pa), "r"(b), "r"(pb) : "memory");
}
__device__ __forceinline__ uint32_t mbar_test(uint32_t a, uint32_t parity) {
  uint32_t r;
  asm volatile("{\n.reg .pred p;\nmbarrier.test_wait.parity.shared::cta.b64 p, [%1], %2;\nselp.u32 %0, 1, 0, p;\n}" : "=r"(r) : "r"(a), "r"(parity) : "memory");
  return r;
}
__device__ __forceinline__ void mbar_arrive(uint32_t a) {
  asm volatile("mbarrier.arrive.shared::cta.b64 _, [%0];" ::"r"(a) : "memory");
}
__device__ __forceinline__ void mbar_arrive_cluster(uint32_t a, uint32_t cta) {
  asm volatile("{\n.reg .b32 r;\nmapa.shared::cluster.u32 r, %0, %1;\nmbarrier.arrive.shared::cluster.b64 _, [r];\n}" ::"r"(a),
               "r"(cta) : "memory");
}
__device__ __forceinline__ void mbar_arrive_cluster_if(uint32_t a, uint32_t cta, bool pred) {
  asm volatile("{\n.reg .b32 r;\n.reg .pred p;\nsetp.ne.u32 p, %2, 0;\nmapa.shared::cluster.u32 r, %0, %1;\n@p mbarrier.arrive.shared::cluster.b64 _, [r];\n}" ::"r"(a),
               "r"(cta), "r"((uint32_t)pred) : "memory");
}
__device__ __forceinline__ void anchor(float v, uint32_t pred) {
  asm volatile("{\n.reg .pred p;\nsetp.ne.u32 p, %1, 0;\n@p st.shared.f32 [%1], %0;\n}" ::"f"(v), "r"(pred) : "memory");
}
__device__ __forceinline__ void mbar_arrive_if(uint32_t a, bool pred) {
  asm volatile("{\n.reg .pred p;\nsetp.ne.u32 p, %1, 0;\n@p mbarrier.arrive.shared::cta.b64 _, [%0];\n}" ::"r"(a), "r"((uint32_t)pred) : "memory");
}
__device__ __forceinline__ void tma2d(uint32_t dst, const CUtensorMap* m, uint32_t bar, int c0, int c1) {
  asm volatile("cp.async.bulk.tensor.2d.shared::cluster.global.mbarrier::complete_tx::bytes [%0], [%1, {%3, %4}], [%2];" ::"r"(dst),
               "l"(m), "r"(bar), "r"(c0), "r"(c1) : "memory");
}
__device__ __forceinline__ void tma2d_mc(uint32_t dst, const CUtensorMap* m, uint32_t bar, int c0, int c1, uint16_t mask) {
  asm volatile(
      "cp.async.bulk.tensor.2d.shared::cluster.global.mbarrier::complete_tx::bytes.multicast::cluster [%0], [%1, {%3, %4}], [%2], %5;" ::"r"(dst),
      "l"(m), "r"(bar), "r"(c0), "r"(c1), "h"(mask) : "memory");
}
__device__ __forceinline__ void tma3d_mc(uint32_t dst, const CUtensorMap* m, uint32_t bar, int c0, int c1, int c2, uint16_t mask) {
  asm volatile(
      "cp.async.bulk.tensor.3d.shared::cluster.global.mbarrier::complete_tx::bytes.multicast::cluster [%0], [%1, {%3, %4, %5}], [%2], %6;" ::"r"(dst),
      "l"(m), "r"(bar), "r"(c0), "r"(c1), "r"(c2), "h"(mask) : "memory");
}
__device__ __forceinline__ void tma3d(uint32_t dst, const CUtensorMap* m, uint32_t bar, int c0, int c1, int c2) {
  asm volatile(
      "cp.async.bulk.tensor.3d.shared::cluster.global.mbarrier::complete_tx::bytes [%0], [%1, {%3, %4, %5}], [%2];" ::"r"(dst),
      "l"(m), "r"(bar), "r"(c0), "r"(c1), "r"(c2) : "memory");
}
__device__ __forceinline__ void tma_pf2d(const CUtensorMap* m, int c0, int c1) {
  asm volatile("cp.async.bulk.prefetch.tensor.2d.L2.global [%0, {%1, %2}];" ::"l"(m), "r"(c0), "r"(c1) : "memory");
}
__device__ __forceinline__ void tma_pf3d(const CUtensorMap* m, int c0, int c1, int c2) {
  asm volatile("cp.async.bulk.prefetch.tensor.3d.L2.global [%0, {%1, %2, %3}];" ::"l"(m), "r"(c0), "r"(c1), "r"(c2) : "memory");
}
__device__ __forceinline__ void prefetch_tmap(const CUtensorMap* m) {
  asm volatile("prefetch.tensormap [%0];" ::"l"(m) : "memory");
}
__device__ __forceinline__ void cluster_arrive() { asm volatile("barrier.cluster.arrive.relaxed.aligned;" ::: "memory"); }
__device__ __forceinline__ void cluster_wait() { asm volatile("barrier.cluster.wait.aligned;" ::: "memory"); }
__device__ __forceinline__ void cluster_sync() {
  cluster_arrive();
  cluster_wait();
}
__device__ __forceinline__ uint32_t cluster_rank() {
  uint32_t r;
  asm volatile("mov.u32 %0, %%cluster_ctarank;" : "=r"(r));
  return r;
}
__device__ __forceinline__ bool elect_one() {
  uint32_t p;
  asm volatile("{\n.reg .pred q;\nelect.sync _|q, 0xffffffff;\nselp.u32 %0, 1, 0, q;\n}" : "=r"(p));
  return p;
}
__device__ __forceinline__ void ldsm_x4(uint32_t& r0, uint32_t& r1, uint32_t& r2, uint32_t& r3, uint32_t addr) {
  asm volatile("ldmatrix.sync.aligned.m8n8.x4.shared.b16 {%0, %1, %2, %3}, [%4];" : "=r"(r0), "=r"(r1), "=r"(r2), "=r"(r3) : "r"(addr) : "memory");
}
__device__ __forceinline__ void wg_fence() { asm volatile("wgmma.fence.sync.aligned;" ::: "memory"); }
__device__ __forceinline__ void wg_commit() { asm volatile("wgmma.commit_group.sync.aligned;" ::: "memory"); }
template <int N>
__device__ __forceinline__ void wg_wait() { asm volatile("wgmma.wait_group.sync.aligned %0;" ::"n"(N) : "memory"); }
template <int N>
__device__ __forceinline__ void reg_alloc() { asm volatile("setmaxnreg.inc.sync.aligned.u32 %0;" ::"n"(N)); }
template <int N>
__device__ __forceinline__ void reg_dealloc() { asm volatile("setmaxnreg.dec.sync.aligned.u32 %0;" ::"n"(N)); }
__device__ __forceinline__ void bar_sync(int id, int n) { asm volatile("bar.sync %0, %1;" ::"r"(id), "r"(n) : "memory"); }
__device__ __forceinline__ void bar_arrive(int id, int n) { asm volatile("bar.arrive %0, %1;" ::"r"(id), "r"(n) : "memory"); }
template <int NT>
__device__ __forceinline__ void fence_regs(float (&d)[NT]) {
#pragma unroll
  for (int i = 0; i < NT; i++) asm volatile("" : "+f"(d[i])::"memory");
}
template <int NT>
__device__ __forceinline__ void fence_regs(uint32_t (&d)[NT]) {
#pragma unroll
  for (int i = 0; i < NT; i++) asm volatile("" : "+r"(d[i])::"memory");
}
__device__ __forceinline__ uint64_t make_desc(uint32_t saddr, uint32_t lbo, uint32_t sbo, uint32_t layout) {
  return (uint64_t)((saddr & 0x3FFFF) >> 4) | ((uint64_t)(lbo >> 4) << 16) | ((uint64_t)(sbo >> 4) << 32) | ((uint64_t)layout << 62);
}
__device__ __forceinline__ uint32_t pack_bf16(float lo, float hi) {
  uint32_t r;
  asm("cvt.rn.bf16x2.f32 %0, %1, %2;" : "=r"(r) : "f"(hi), "f"(lo));
  return r;
}
__device__ __forceinline__ float ex2(float x) {
  float r;
  asm("ex2.approx.ftz.f32 %0, %1;" : "=f"(r) : "f"(x));
  return r;
}
__device__ __forceinline__ void st_v4(void* p, uint32_t a, uint32_t b, uint32_t c, uint32_t d) {
#define ST_MOD ".cs"
  asm volatile("st.global" ST_MOD ".v4.b32 [%0], {%1, %2, %3, %4};" ::"l"(p), "r"(a), "r"(b), "r"(c), "r"(d) : "memory");
}
#define STA_MOD ".cs"
__device__ __forceinline__ void st_v4a(void* p, uint32_t a, uint32_t b, uint32_t c, uint32_t d) {
  asm volatile("st.global" STA_MOD ".v4.b32 [%0], {%1, %2, %3, %4};" ::"l"(p), "r"(a), "r"(b), "r"(c), "r"(d) : "memory");
}
__device__ __forceinline__ float bf_lo(uint32_t v) { return __uint_as_float(v << 16); }
__device__ __forceinline__ float bf_hi(uint32_t v) { return __uint_as_float(v & 0xFFFF0000u); }

__device__ __forceinline__ void quad_transpose(uint32_t& a0, uint32_t& a1, uint32_t& a2, uint32_t& a3, int q) {
  const bool o1 = q & 1, o2 = q & 2;
  uint32_t t0 = o1 ? a0 : a1, t1 = o1 ? a2 : a3;
  t0 = __shfl_xor_sync(0xffffffffu, t0, 1);
  t1 = __shfl_xor_sync(0xffffffffu, t1, 1);
  if (o1) { a0 = t0; a2 = t1; } else { a1 = t0; a3 = t1; }
  t0 = o2 ? a0 : a2;
  t1 = o2 ? a1 : a3;
  t0 = __shfl_xor_sync(0xffffffffu, t0, 2);
  t1 = __shfl_xor_sync(0xffffffffu, t1, 2);
  if (o2) { a0 = t0; a1 = t1; } else { a2 = t0; a3 = t1; }
}

template<int TB, int OFF, int NT>
__device__ __forceinline__ void wgmma_ss_n256(float (&d)[NT], uint64_t da, uint64_t db, int scale_d) {
  asm volatile("{\n.reg .pred p;\nsetp.ne.b32 p, %130, 0;\n"
    "wgmma.mma_async.sync.aligned.m64n256k16.f32.bf16.bf16 {%0, %1, %2, %3, %4, %5, %6, %7, %8, %9, %10, %11, %12, %13, %14, %15, %16, %17, %18, %19, %20, %21, %22, %23, %24, %25, %26, %27, %28, %29, %30, %31, %32, %33, %34, %35, %36, %37, %38, %39, %40, %41, %42, %43, %44, %45, %46, %47, %48, %49, %50, %51, %52, %53, %54, %55, %56, %57, %58, %59, %60, %61, %62, %63, %64, %65, %66, %67, %68, %69, %70, %71, %72, %73, %74, %75, %76, %77, %78, %79, %80, %81, %82, %83, %84, %85, %86, %87, %88, %89, %90, %91, %92, %93, %94, %95, %96, %97, %98, %99, %100, %101, %102, %103, %104, %105, %106, %107, %108, %109, %110, %111, %112, %113, %114, %115, %116, %117, %118, %119, %120, %121, %122, %123, %124, %125, %126, %127}, %128, %129, p, 1, 1, 0, %131;\n}\n"
    : "+f"(d[OFF+0]), "+f"(d[OFF+1]), "+f"(d[OFF+2]), "+f"(d[OFF+3]), "+f"(d[OFF+4]), "+f"(d[OFF+5]), "+f"(d[OFF+6]), "+f"(d[OFF+7]), "+f"(d[OFF+8]), "+f"(d[OFF+9]), "+f"(d[OFF+10]), "+f"(d[OFF+11]), "+f"(d[OFF+12]), "+f"(d[OFF+13]), "+f"(d[OFF+14]), "+f"(d[OFF+15]), "+f"(d[OFF+16]), "+f"(d[OFF+17]), "+f"(d[OFF+18]), "+f"(d[OFF+19]), "+f"(d[OFF+20]), "+f"(d[OFF+21]), "+f"(d[OFF+22]), "+f"(d[OFF+23]), "+f"(d[OFF+24]), "+f"(d[OFF+25]), "+f"(d[OFF+26]), "+f"(d[OFF+27]), "+f"(d[OFF+28]), "+f"(d[OFF+29]), "+f"(d[OFF+30]), "+f"(d[OFF+31]), "+f"(d[OFF+32]), "+f"(d[OFF+33]), "+f"(d[OFF+34]), "+f"(d[OFF+35]), "+f"(d[OFF+36]), "+f"(d[OFF+37]), "+f"(d[OFF+38]), "+f"(d[OFF+39]), "+f"(d[OFF+40]), "+f"(d[OFF+41]), "+f"(d[OFF+42]), "+f"(d[OFF+43]), "+f"(d[OFF+44]), "+f"(d[OFF+45]), "+f"(d[OFF+46]), "+f"(d[OFF+47]), "+f"(d[OFF+48]), "+f"(d[OFF+49]), "+f"(d[OFF+50]), "+f"(d[OFF+51]), "+f"(d[OFF+52]), "+f"(d[OFF+53]), "+f"(d[OFF+54]), "+f"(d[OFF+55]), "+f"(d[OFF+56]), "+f"(d[OFF+57]), "+f"(d[OFF+58]), "+f"(d[OFF+59]), "+f"(d[OFF+60]), "+f"(d[OFF+61]), "+f"(d[OFF+62]), "+f"(d[OFF+63]), "+f"(d[OFF+64]), "+f"(d[OFF+65]), "+f"(d[OFF+66]), "+f"(d[OFF+67]), "+f"(d[OFF+68]), "+f"(d[OFF+69]), "+f"(d[OFF+70]), "+f"(d[OFF+71]), "+f"(d[OFF+72]), "+f"(d[OFF+73]), "+f"(d[OFF+74]), "+f"(d[OFF+75]), "+f"(d[OFF+76]), "+f"(d[OFF+77]), "+f"(d[OFF+78]), "+f"(d[OFF+79]), "+f"(d[OFF+80]), "+f"(d[OFF+81]), "+f"(d[OFF+82]), "+f"(d[OFF+83]), "+f"(d[OFF+84]), "+f"(d[OFF+85]), "+f"(d[OFF+86]), "+f"(d[OFF+87]), "+f"(d[OFF+88]), "+f"(d[OFF+89]), "+f"(d[OFF+90]), "+f"(d[OFF+91]), "+f"(d[OFF+92]), "+f"(d[OFF+93]), "+f"(d[OFF+94]), "+f"(d[OFF+95]), "+f"(d[OFF+96]), "+f"(d[OFF+97]), "+f"(d[OFF+98]), "+f"(d[OFF+99]), "+f"(d[OFF+100]), "+f"(d[OFF+101]), "+f"(d[OFF+102]), "+f"(d[OFF+103]), "+f"(d[OFF+104]), "+f"(d[OFF+105]), "+f"(d[OFF+106]), "+f"(d[OFF+107]), "+f"(d[OFF+108]), "+f"(d[OFF+109]), "+f"(d[OFF+110]), "+f"(d[OFF+111]), "+f"(d[OFF+112]), "+f"(d[OFF+113]), "+f"(d[OFF+114]), "+f"(d[OFF+115]), "+f"(d[OFF+116]), "+f"(d[OFF+117]), "+f"(d[OFF+118]), "+f"(d[OFF+119]), "+f"(d[OFF+120]), "+f"(d[OFF+121]), "+f"(d[OFF+122]), "+f"(d[OFF+123]), "+f"(d[OFF+124]), "+f"(d[OFF+125]), "+f"(d[OFF+126]), "+f"(d[OFF+127])
    : "l"(da), "l"(db), "r"(scale_d), "n"(TB));
}
template<int TB, int OFF, int NT>
__device__ __forceinline__ void wgmma_ss_n32(float (&d)[NT], uint64_t da, uint64_t db, int scale_d) {
  asm volatile("{\n.reg .pred p;\nsetp.ne.b32 p, %18, 0;\n"
    "wgmma.mma_async.sync.aligned.m64n32k16.f32.bf16.bf16 {%0, %1, %2, %3, %4, %5, %6, %7, %8, %9, %10, %11, %12, %13, %14, %15}, %16, %17, p, 1, 1, 0, %19;\n}\n"
    : "+f"(d[OFF+0]), "+f"(d[OFF+1]), "+f"(d[OFF+2]), "+f"(d[OFF+3]), "+f"(d[OFF+4]), "+f"(d[OFF+5]), "+f"(d[OFF+6]), "+f"(d[OFF+7]), "+f"(d[OFF+8]), "+f"(d[OFF+9]), "+f"(d[OFF+10]), "+f"(d[OFF+11]), "+f"(d[OFF+12]), "+f"(d[OFF+13]), "+f"(d[OFF+14]), "+f"(d[OFF+15])
    : "l"(da), "l"(db), "r"(scale_d), "n"(TB));
}
template<int TB, int OFF, int NT>
__device__ __forceinline__ void wgmma_rs_n128(float (&d)[NT], uint32_t a0, uint32_t a1, uint32_t a2, uint32_t a3, uint64_t db, int scale_d) {
  asm volatile("{\n.reg .pred p;\nsetp.ne.b32 p, %69, 0;\n"
    "wgmma.mma_async.sync.aligned.m64n128k16.f32.bf16.bf16 {%0, %1, %2, %3, %4, %5, %6, %7, %8, %9, %10, %11, %12, %13, %14, %15, %16, %17, %18, %19, %20, %21, %22, %23, %24, %25, %26, %27, %28, %29, %30, %31, %32, %33, %34, %35, %36, %37, %38, %39, %40, %41, %42, %43, %44, %45, %46, %47, %48, %49, %50, %51, %52, %53, %54, %55, %56, %57, %58, %59, %60, %61, %62, %63}, {%64, %65, %66, %67}, %68, p, 1, 1, %70;\n}\n"
    : "+f"(d[OFF+0]), "+f"(d[OFF+1]), "+f"(d[OFF+2]), "+f"(d[OFF+3]), "+f"(d[OFF+4]), "+f"(d[OFF+5]), "+f"(d[OFF+6]), "+f"(d[OFF+7]), "+f"(d[OFF+8]), "+f"(d[OFF+9]), "+f"(d[OFF+10]), "+f"(d[OFF+11]), "+f"(d[OFF+12]), "+f"(d[OFF+13]), "+f"(d[OFF+14]), "+f"(d[OFF+15]), "+f"(d[OFF+16]), "+f"(d[OFF+17]), "+f"(d[OFF+18]), "+f"(d[OFF+19]), "+f"(d[OFF+20]), "+f"(d[OFF+21]), "+f"(d[OFF+22]), "+f"(d[OFF+23]), "+f"(d[OFF+24]), "+f"(d[OFF+25]), "+f"(d[OFF+26]), "+f"(d[OFF+27]), "+f"(d[OFF+28]), "+f"(d[OFF+29]), "+f"(d[OFF+30]), "+f"(d[OFF+31]), "+f"(d[OFF+32]), "+f"(d[OFF+33]), "+f"(d[OFF+34]), "+f"(d[OFF+35]), "+f"(d[OFF+36]), "+f"(d[OFF+37]), "+f"(d[OFF+38]), "+f"(d[OFF+39]), "+f"(d[OFF+40]), "+f"(d[OFF+41]), "+f"(d[OFF+42]), "+f"(d[OFF+43]), "+f"(d[OFF+44]), "+f"(d[OFF+45]), "+f"(d[OFF+46]), "+f"(d[OFF+47]), "+f"(d[OFF+48]), "+f"(d[OFF+49]), "+f"(d[OFF+50]), "+f"(d[OFF+51]), "+f"(d[OFF+52]), "+f"(d[OFF+53]), "+f"(d[OFF+54]), "+f"(d[OFF+55]), "+f"(d[OFF+56]), "+f"(d[OFF+57]), "+f"(d[OFF+58]), "+f"(d[OFF+59]), "+f"(d[OFF+60]), "+f"(d[OFF+61]), "+f"(d[OFF+62]), "+f"(d[OFF+63])
    : "r"(a0), "r"(a1), "r"(a2), "r"(a3), "l"(db), "r"(scale_d), "n"(TB));
}
template<int TB, int OFF, int NT>
__device__ __forceinline__ void wgmma_rs_n64(float (&d)[NT], uint32_t a0, uint32_t a1, uint32_t a2, uint32_t a3, uint64_t db, int scale_d) {
  asm volatile("{\n.reg .pred p;\nsetp.ne.b32 p, %37, 0;\n"
    "wgmma.mma_async.sync.aligned.m64n64k16.f32.bf16.bf16 {%0, %1, %2, %3, %4, %5, %6, %7, %8, %9, %10, %11, %12, %13, %14, %15, %16, %17, %18, %19, %20, %21, %22, %23, %24, %25, %26, %27, %28, %29, %30, %31}, {%32, %33, %34, %35}, %36, p, 1, 1, %38;\n}\n"
    : "+f"(d[OFF+0]), "+f"(d[OFF+1]), "+f"(d[OFF+2]), "+f"(d[OFF+3]), "+f"(d[OFF+4]), "+f"(d[OFF+5]), "+f"(d[OFF+6]), "+f"(d[OFF+7]), "+f"(d[OFF+8]), "+f"(d[OFF+9]), "+f"(d[OFF+10]), "+f"(d[OFF+11]), "+f"(d[OFF+12]), "+f"(d[OFF+13]), "+f"(d[OFF+14]), "+f"(d[OFF+15]), "+f"(d[OFF+16]), "+f"(d[OFF+17]), "+f"(d[OFF+18]), "+f"(d[OFF+19]), "+f"(d[OFF+20]), "+f"(d[OFF+21]), "+f"(d[OFF+22]), "+f"(d[OFF+23]), "+f"(d[OFF+24]), "+f"(d[OFF+25]), "+f"(d[OFF+26]), "+f"(d[OFF+27]), "+f"(d[OFF+28]), "+f"(d[OFF+29]), "+f"(d[OFF+30]), "+f"(d[OFF+31])
    : "r"(a0), "r"(a1), "r"(a2), "r"(a3), "l"(db), "r"(scale_d), "n"(TB));
}

__device__ __forceinline__ void wait_flag(const unsigned int* f, uint32_t target) {
  uint32_t v;
#pragma unroll 1
  for (uint32_t spins = 0; spins < (1u << 22); spins++) {
    asm volatile("ld.acquire.gpu.global.u32 %0, [%1];" : "=r"(v) : "l"(f) : "memory");
    if (v >= target) break;
    __nanosleep(100);
  }
}
__device__ __forceinline__ uint32_t lds32(uint32_t a) {
  uint32_t v;
  asm volatile("ld.shared.u32 %0, [%1];" : "=r"(v) : "r"(a) : "memory");
  return v;
}
__device__ __forceinline__ float gate_row(int row, int lane, const bf16* __restrict__ x, const bf16* __restrict__ gate_w) {
  const uint32_t* xr = reinterpret_cast<const uint32_t*>(x + (size_t)row * DM);
  const uint32_t* gw2 = reinterpret_cast<const uint32_t*>(gate_w);
  float gs = 0.f;
#pragma unroll
  for (int i = 0; i < 9; i++) {
    const uint32_t a = __ldg(xr + lane + 32 * i), b = __ldg(gw2 + lane + 32 * i);
    gs = fmaf(bf_lo(a), bf_lo(b), gs);
    gs = fmaf(bf_hi(a), bf_hi(b), gs);
  }
#pragma unroll
  for (int o = 16; o; o >>= 1) gs += __shfl_xor_sync(0xffffffffu, gs, o);
  const float g = 1.f / (1.f + __expf(-gs));
  if (lane == 0) g_gate[row] = g;
  return g;
}
#define LA_UNROLL 9
__device__ __forceinline__ void local_rows2(int rb, int ri, uint32_t sL, uint32_t bL2, int lane, float ga, float gb) {
  const float scale_l2 = 0.23570226039551584f * 1.4426950408889634f;
  constexpr int U = LA_UNROLL;
  const uint32_t sq = sL + (30 + ri) * 1152;
  uint32_t kb[9];
#pragma unroll
  for (int i = 0; i < 9; i++) {
    const uint32_t c = lane * 9 + i;
    kb[i] = sL + (14 + ri) * 1152 + ((c & ~15u) | ((c & 3) << 2) | ((c >> 2) & 3)) * 4;
  }
  float ma = -INFINITY, mb = -INFINITY;
  {
    float qa[18], qb[18];
#pragma unroll
    for (int i = 0; i < 9; i++) {
      const uint32_t u = lds32(kb[i] + 16 * 1152 - 2304), v = lds32(kb[i] + 16 * 1152);
      qa[2 * i] = bf_lo(u); qa[2 * i + 1] = bf_hi(u);
      qb[2 * i] = bf_lo(v); qb[2 * i + 1] = bf_hi(v);
    }
    __syncwarp();
#pragma unroll U
    for (int t = 0; t < 9; t++) {
      const bool ok = rb - 2 * t >= 0;
      float a0 = 0.f, a1 = 0.f, b0 = 0.f, b1 = 0.f;
#pragma unroll
      for (int i = 0; i < 9; i++) {
        const uint32_t k = lds32(kb[i] - t * 2304);
        const float lo = bf_lo(k), hi = bf_hi(k);
        a0 = fmaf(qa[2 * i], lo, a0); a1 = fmaf(qa[2 * i + 1], hi, a1);
        b0 = fmaf(qb[2 * i], lo, b0); b1 = fmaf(qb[2 * i + 1], hi, b1);
      }
      a0 = (ok && t > 0) ? a0 + a1 : -INFINITY;
      b0 = (ok && t < 8) ? b0 + b1 : -INFINITY;
      ma = fmaxf(ma, a0);
      mb = fmaxf(mb, b0);
      asm volatile("st.shared.f32 [%0], %1;" ::"r"(sq - 2304 + t * 128 + lane * 4), "f"(a0) : "memory");
      asm volatile("st.shared.f32 [%0], %1;" ::"r"(sq + t * 128 + lane * 4), "f"(b0) : "memory");
    }
  }
  float oa[18], ob[18], sa = 0.f, sb = 0.f;
#pragma unroll
  for (int i = 0; i < 18; i++) { oa[i] = 0.f; ob[i] = 0.f; }
  mbar_wait(bL2, 0);
#pragma unroll U
  for (int t = 0; t < 9; t++) {
    const float wa = ex2((__uint_as_float(lds32(sq - 2304 + t * 128 + lane * 4)) - ma) * scale_l2);
    const float wb = ex2((__uint_as_float(lds32(sq + t * 128 + lane * 4)) - mb) * scale_l2);
    sa += wa;
    sb += wb;
#pragma unroll
    for (int i = 0; i < 9; i++) {
      const uint32_t v = lds32(kb[i] + 46 * 1152 - t * 2304);
      const float lo = bf_lo(v), hi = bf_hi(v);
      oa[2 * i] = fmaf(wa, lo, oa[2 * i]); oa[2 * i + 1] = fmaf(wa, hi, oa[2 * i + 1]);
      ob[2 * i] = fmaf(wb, lo, ob[2 * i]); ob[2 * i + 1] = fmaf(wb, hi, ob[2 * i + 1]);
    }
  }
  ga = __fdividef(ga, sa);
  gb = __fdividef(gb, sb);
  __syncwarp();
#pragma unroll
  for (int i = 0; i < 9; i++) {
    asm volatile("st.shared.u32 [%0], %1;" ::"r"(sq - 2304 + lane * 36 + 4 * i), "r"(pack_bf16(oa[2 * i] * ga, oa[2 * i + 1] * ga)) : "memory");
    asm volatile("st.shared.u32 [%0], %1;" ::"r"(sq + lane * 36 + 4 * i), "r"(pack_bf16(ob[2 * i] * gb, ob[2 * i + 1] * gb)) : "memory");
  }
  __syncwarp();
  uint32_t w[5][4];
#pragma unroll
  for (int t = 0; t < 5; t++) {
    const int c = min(t * 32 + lane, 143), r = c >= 72;
    asm volatile("ld.shared.v4.u32 {%0, %1, %2, %3}, [%4];" : "=r"(w[t][0]), "=r"(w[t][1]), "=r"(w[t][2]), "=r"(w[t][3])
                 : "r"(sq - 2304 + r * 2304 + (c - r * 72) * 16) : "memory");
  }
  asm volatile("fence.proxy.async.shared::cta;" ::: "memory");
  bar_arrive(4, 256 + 32);
#pragma unroll
  for (int t = 0; t < 5; t++) {
    const int c = min(t * 32 + lane, 143), r = c >= 72;
    st_v4(g_ctx + (size_t)(rb - 2 + 2 * r) * KCAT + HDIM + (c - r * 72) * 8, w[t][0], w[t][1], w[t][2], w[t][3]);
  }
}

#define K1_NST 6
constexpr int K1_BST = K1_NST;
#define MAXJ 11
constexpr int K1_MAXJOBS = MAXJ;
constexpr uint32_t K1_FLAG_TARGET = 7;
constexpr uint32_t RDY_TARGET = 48;
constexpr uint32_t GATE_TARGET = 128 * 3;
struct alignas(64) Params {
  CUtensorMap tmA[2];
  CUtensorMap tmW[4];
  CUtensorMap tmQ, tmK, tmV;
  CUtensorMap tmL[2];
  CUtensorMap tmC, tmO[2], tmOt[2];
  uint16_t jobs[NCLUSTER][K1_MAXJOBS + 1];
  uint8_t order[256];
  uint8_t unit[64][8];
};

struct K1State {
  uint32_t bs, bph, aph;
  bf16* pp;
  int pld8;
  int png;
  int tn;
  bool isq;
};
__device__ __forceinline__ void k1_flag(const K1State& st, int lane, uint32_t bS) {
  if (st.png) {
    __syncwarp();
    if (lane == 0) mbar_arrive(bS);
  }
}

__device__ __forceinline__ void scale_q4(uint32_t* v) {
#pragma unroll
  for (int i = 0; i < 4; i++)
    asm volatile("{\n.reg .b32 t;\nmul.rn.bf16x2 t, %0, %2;\nfma.rn.bf16x2 %0, %0, %1, t;\n}" : "+r"(v[i]) : "r"(0x3E033E03u), "r"(0xB9D8B9D8u));
}
__device__ __forceinline__ void k1_first(const K1State& st, uint32_t job, uint32_t bAf, uint32_t bBf) {
  if (job & 3) {
    if ((job >> 14) & 1) mbar_wait(bAf, st.aph);
    mbar_wait(bBf + st.bs * 8, st.bph);
  }
}
__device__ __forceinline__ void k1_tile(float (&acc)[128], uint32_t (&pk)[64], K1State& st, uint32_t job, uint32_t njob, uint32_t sA, uint32_t sB,
                                        uint32_t bAf, uint32_t bAe, uint32_t bBf, uint32_t bBe, uint32_t bS, int wg, int warp, int lane, uint32_t rank) {
  const int a_sel = (job >> 2) & 1, mpair = (job >> 3) & 7, w_sel = (job >> 6) & 3, chunk0 = (job >> 8) & 63;
  const bool newA = (job >> 14) & 1, lastA = (job >> 15) & 1;
  const bool sig = (lane == 0) && (warp < 2);
  const bool siga = lastA && (lane == 0) && (warp == 2);
  const int KC = 8 + a_sel;
  uint32_t prev_bs = 0, a8_bs = 0;
#pragma unroll
  for (int kc = 0; kc < 9; kc++) {
    if (kc >= KC) break;
    uint32_t abase = sA + ((kc + 2) & 7) * 16384;
    if (kc == 8) {
      mbar_wait(bBf + st.bs * 8, st.bph);
      a8_bs = st.bs;
      abase = sB + st.bs * 16384;
      if (++st.bs == K1_BST) { st.bs = 0; st.bph ^= 1; }
    } else if (newA && kc > 0) {
      mbar_wait(bAf + kc * 8, st.aph);
    }
    const uint64_t da = make_desc(abase + wg * 8192, 16, 1024, 1);
#pragma unroll
    for (int ks = 0; ks < 2; ks++) {
      if (ks > 0 || kc > 0) mbar_wait(bBf + st.bs * 8, st.bph);
      const uint64_t db = make_desc(sB + st.bs * 16384, 2048, 1024, 1);
      wg_fence();
      wgmma_ss_n256<1, 0>(acc, da + (uint64_t)(ks * 4), db, (ks > 0) ? 1 : (kc > 0));
      wgmma_ss_n256<1, 0>(acc, da + (uint64_t)(ks * 4 + 2), db + (uint64_t)512, 1);
      wg_commit();
      const int PO = (kc < 8 ? kc : 0) * 8;
      wg_wait<1>();
      if (ks > 0 || kc > 0) {
        if (sig) mbar_arrive_cluster(bBe + prev_bs * 8, warp);
        if (ks == 0 && siga) mbar_arrive(bAe + (kc - 1) * 8);
      }
      if (kc < 8 && st.isq) scale_q4(pk + PO + ks * 4);
      if (kc < st.png) st_v4a(st.pp + kc * 32 + ks * st.pld8, pk[PO + ks * 4], pk[PO + ks * 4 + 1], pk[PO + ks * 4 + 2], pk[PO + ks * 4 + 3]);
      prev_bs = st.bs;
      if (++st.bs == K1_BST) { st.bs = 0; st.bph ^= 1; }
    }
  }
  if (newA) st.aph ^= 1;
  k1_flag(st, lane, bS);
  const bool isA = (w_sel == 2);
  bf16* out = (w_sel == 0) ? g_K : (w_sel == 1) ? g_V : isA ? g_QKVA : g_Q;
  const int ld = isA ? NQKVA : HDIM;
  const int row = mpair * 256 + rank * 128 + wg * 64 + warp * 16 + (lane >> 2);
  st.pp = out + (size_t)row * ld + chunk0 * 64 + (lane & 3) * 8;
  st.pld8 = 8 * ld;
  st.png = ((job & 3) + 1) * 2;
  st.isq = (w_sel == 3);
  k1_first(st, njob, bAf, bBf);
  wg_wait<0>();
  fence_regs(acc);
  mbar_arrive_cluster_if(bBe + prev_bs * 8, warp & 1, sig);
  mbar_arrive_cluster_if(bBe + a8_bs * 8, warp & 1, sig && a_sel);
  mbar_arrive_if(bAe + 7 * 8, siga && !a_sel);
#pragma unroll
  for (int i = 0; i < 64; i++) {
    const int j = (i >> 3) * 16 + (i & 3) * 4 + ((i >> 2) & 1) * 2;
    pk[i] = pack_bf16(acc[j], acc[j + 1]);
  }
}

constexpr int K2_NST = 7;
constexpr uint32_t K2_END = 0x100;
#define PF_KC 7
#define FIRST_DRAW 3
#define PWAIT mbar_wait_ns<1000>
#define PVM 0x8A
#define W0 63
#define SPEC_HI 1.8446744073709552e19f
#define SPEC_LO 5.421010862427522e-20f
constexpr int K3_NST = 4;
__device__ __forceinline__ uint32_t k3_rot(uint32_t sv) { return (0x00E9u >> (2 * sv)) & 3; }
constexpr int K3_STAGE = 16384 + 32768 + 4096;
constexpr int SMEM_DATA = 7 * 32768;
constexpr int SMEM_BYTES = SMEM_DATA + 1024 + 768;

struct Cursor {
  uint32_t s, ph;
  __device__ __forceinline__ void next() {
    if (++s == K2_NST) { s = 0; ph ^= 1; }
  }
};

#define TURN_SYNC() bar_sync(mybar, 256)
#define TURN_ARRIVE() bar_arrive(otherbar, 256)
#define RELEASE_IF(cur, cond) mbar_arrive_cluster_if(bE + (cur).s * 8, warp & 1, sig && (cond))
#define RELEASE(cur) RELEASE_IF(cur, true)
#define ISSUE_PV(cur, first)                                                                                   \
  do {                                                                                                         \
    const uint64_t dv = make_desc(sbase + (cur).s * 32768, 16384, 1024, 1);                                    \
    _Pragma("unroll") for (int t = 0; t < 8; t++)                                                              \
        wgmma_rs_n128<1, 0>(O, P[4 * t], P[4 * t + 1], P[4 * t + 2], P[4 * t + 3], dv + (uint64_t)(t * 128), (t > 0) ? 1 : !(first)); \
  } while (0)
#define ISSUE_QK(cur)                                                                                          \
  do {                                                                                                         \
    const uint64_t dk = make_desc(sbase + (cur).s * 32768, 16, 1024, 1);                                       \
    _Pragma("unroll") for (int t = 0; t < 8; t++)                                                              \
        wgmma_rs_n128<0, 0>(S, Q[4 * t], Q[4 * t + 1], Q[4 * t + 2], Q[4 * t + 3], dk + (uint64_t)((t >> 2) * 1024 + (t & 3) * 2), t > 0); \
  } while (0)
#define EXPB(T)                                                                                                \
  do {                                                                                                         \
    _Pragma("unroll") for (int i = 4 * T; i < 4 * T + 4; i++) asm volatile("" : "+r"(P[i])::"memory");        \
    _Pragma("unroll") for (int jj = 2 * T; jj < 2 * T + 2; jj++) {                                             \
      const float e0 = ex2(S[jj * 4 + 0]), e1 = ex2(S[jj * 4 + 1]), e2 = ex2(S[jj * 4 + 2]), e3 = ex2(S[jj * 4 + 3]); \
      s0 += e0 + e1;                                                                                           \
      s1 += e2 + e3;                                                                                           \
      P[jj * 2 + 0] = pack_bf16(e0, e1);                                                                       \
      P[jj * 2 + 1] = pack_bf16(e2, e3);                                                                       \
    }                                                                                                          \
  } while (0)
#define EXPC(T)                                                                                                \
  do {                                                                                                         \
    if (T > 0 && ((PVM >> (T - 1)) & 1)) {                                                                     \
      anchor((T & 2) ? s0 : s1, never);                                                                        \
      wg_wait<__builtin_popcount(PVM >> T) - 1>();                                                             \
      if ((PVM >> T) == (128 >> T)) { fence_regs(O); RELEASE(cv); }                                            \
    }                                                                                                          \
    EXPB(T);                                                                                                   \
  } while (0)
#define MASK(G, g)                                                                                             \
  do {                                                                                                         \
    if ((g) * 8 > d) S[(G) * 4 + 0] = -INFINITY;                                                               \
    if ((g) * 8 + 1 > d) S[(G) * 4 + 1] = -INFINITY;                                                           \
    if ((g) * 8 - 8 > d) S[(G) * 4 + 2] = -INFINITY;                                                           \
    if ((g) * 8 - 7 > d) S[(G) * 4 + 3] = -INFINITY;                                                           \
  } while (0)
#define STORE_O(G)                                                                                             \
  do {                                                                                                         \
    st_v4(g_ctx + eoff + (G) * 32, pack_bf16(O[(G) * 16 + 0] * f0, O[(G) * 16 + 1] * f0), pack_bf16(O[(G) * 16 + 4] * f0, O[(G) * 16 + 5] * f0), \
          pack_bf16(O[(G) * 16 + 8] * f0, O[(G) * 16 + 9] * f0), pack_bf16(O[(G) * 16 + 12] * f0, O[(G) * 16 + 13] * f0)); \
    st_v4(g_ctx + eoff + 8 * KCAT + (G) * 32, pack_bf16(O[(G) * 16 + 2] * f1, O[(G) * 16 + 3] * f1), pack_bf16(O[(G) * 16 + 6] * f1, O[(G) * 16 + 7] * f1), \
          pack_bf16(O[(G) * 16 + 10] * f1, O[(G) * 16 + 11] * f1), pack_bf16(O[(G) * 16 + 14] * f1, O[(G) * 16 + 15] * f1)); \
  } while (0)

__global__ void __cluster_dims__(2, 1, 1) __launch_bounds__(384, 1)
fused_kernel(const __grid_constant__ Params p, const bf16* __restrict__ x, const bf16* __restrict__ gate_w, bf16* __restrict__ out) {
  extern __shared__ uint8_t smem_raw[];
  const uint32_t sbase = (smem_u32(smem_raw) + 1023) & ~1023u;
  const uint32_t sB = sbase, sA = sbase + K1_BST * 16384, sBar = sbase + SMEM_DATA;
  const uint32_t bAf = sBar, bAe = sBar + 64, bBf = sBar + 128, bBe = sBar + 176, bL = sBar + 224, bS = sBar + 232, bL2 = sBar + 240, sL = sA + 32768;
  const uint32_t bF = sBar + 256, bE = sBar + 320, bT = sBar + 384, sTick = sBar + 400, sItem = sBar + 416, bS2 = sBar + 448, bR = sBar + 456, bLast = sBar + 464, bH = sBar + 472, bT0 = sBar + 480;
  const uint32_t b3F = sBar + 512, b3E = sBar + 544, sGate = sBar + 576;
  const int tid = threadIdx.x, warp_g = __shfl_sync(0xffffffffu, tid >> 5, 0), lane = tid & 31;
  const uint32_t rank = cluster_rank();
  const int cl = blockIdx.x >> 1;
  TSM(0);
  if (tid == 0) {
    for (int i = 0; i < 8; i++) { mbar_init(bAf + i * 8, 1); mbar_init(bAe + i * 8, 2); }
    for (int i = 0; i < K1_BST; i++) { mbar_init(bBf + i * 8, 1); mbar_init(bBe + i * 8, 4); }
    mbar_init(bL, 1);
    mbar_init(bL2, 1);
    mbar_init(bR, 1);
    mbar_init(bLast, 1);
    mbar_init(bH, 4);
    mbar_init(bT0, 1);
    mbar_init(bS, 8);
    for (int i = 0; i < K2_NST; i++) { mbar_init(bF + i * 8, 1); mbar_init(bE + i * 8, 4); }
    mbar_init(bT, 1); mbar_init(bT + 8, 1);
    mbar_init(bS2, 8);
    for (int i = 0; i < K3_NST; i++) { mbar_init(b3F + i * 8, 1); mbar_init(b3E + i * 8, 4); }
    asm volatile("fence.mbarrier_init.release.cluster;" ::: "memory");
  }
  __syncwarp();
  if (warp_g != 8) cluster_sync();
  const int lr0 = blockIdx.x * 16;

  if (warp_g >= 8) {
    reg_dealloc<40>();
    if (warp_g == 8) {
      {
        const uint32_t job = p.jobs[cl][0];
        if (lane == 0) { prefetch_tmap(&p.tmA[(job >> 2) & 1]); prefetch_tmap(&p.tmW[(job >> 6) & 3]); }
        __syncwarp();
        cluster_sync();
      }
      if (elect_one()) {
        uint32_t bs = 0, bph = 1, aph = 1;
#pragma unroll 1
        for (int ji = 0; ji < K1_MAXJOBS; ji++) {
          const uint32_t job = p.jobs[cl][ji];
          if (!(job & 3)) break;
          const int a_sel = (job >> 2) & 1, mpair = (job >> 3) & 7, chunk0 = (job >> 8) & 63;
          const bool newA = (job >> 14) & 1;
          const int KC = a_sel ? 9 : 8;
          const uint32_t halfbytes = 8192;
          const bool lastjob = (ji + 1 == K1_MAXJOBS) || !(p.jobs[cl][ji + 1] & 3);
          const CUtensorMap* tw = &p.tmW[(job >> 6) & 3];
          {
            const uint32_t njob = (ji + 1 < K1_MAXJOBS) ? p.jobs[cl][ji + 1] : 0;
            if (!(njob & 3) && !newA) mbar_arrive(bLast);
          }
#pragma unroll 1
          for (int kc = 0; kc < KC; kc++) {
            if (kc == ((ji == 0) ? PF_KC : 0) && !lastjob) {
              const uint32_t njob = p.jobs[cl][ji + 1];
              const int nst = ((njob >> 2) & 1) ? 18 : 16;
#pragma unroll 1
              for (int t = (cl < 64) ? (cl & 7) : 0; t < nst; t += (cl < 64) ? 8 : 1)
                tma_pf3d(&p.tmW[(njob >> 6) & 3], 0, t * 32 + rank * 16, (njob >> 8) & 63);
            }
            if (kc == 8) {
              PWAIT(bBe + bs * 8, bph);
              mbar_expect(bBf + bs * 8, 16384);
              tma2d(sB + bs * 16384, &p.tmA[1], bBf + bs * 8, 512, mpair * 256 + rank * 128);
              if (++bs == K1_BST) { bs = 0; bph ^= 1; }
            } else if (newA) {
              PWAIT(bAe + kc * 8, aph);
              mbar_expect(bAf + kc * 8, 16384);
              tma2d(sA + ((kc + 2) & 7) * 16384, &p.tmA[a_sel], bAf + kc * 8, kc * 64, mpair * 256 + rank * 128);
              if (kc == 7 && lastjob) mbar_arrive(bLast);
            }
#pragma unroll 1
            for (int kk = 0; kk < 2; kk++) {
              PWAIT(bBe + bs * 8, bph);
              mbar_expect(bBf + bs * 8, 2 * halfbytes);
              tma3d_mc(sB + bs * 16384 + rank * halfbytes, tw, bBf + bs * 8, 0, kc * 64 + kk * 32 + rank * 16, chunk0, 3);
              if (++bs == K1_BST) { bs = 0; bph ^= 1; }
            }
          }
          if (newA) aph ^= 1;
        }
        Cursor c{0, 0};
        int pcol = 0;
        PWAIT(bR, 0);
        uint32_t tick = lds32(sTick + 8), seen = 1u << (p.order[tick] >> 4);
        asm volatile("fence.proxy.async.global;" ::: "memory");
#pragma unroll 1
        for (int it = 0;; it++) {
          const uint32_t item = (tick < 256) ? p.order[tick] : (K2_END | min(tick - 256, 255u));
          asm volatile("st.shared.u32 [%0], %1;" ::"r"(sItem + (it & 7) * 4), "r"(item) : "memory");
          if (item >= K2_END) break;
          const int h = item >> 3, j = item & 7;
          const int blk = 2 * j + (int)(rank ^ (it & 1));
          const int col = h * 128 + rank * 64;
          const int nb = 2 * j + 2;
          if (!((seen >> (h >> 1)) & 1)) {
            wait_flag(&g_sync[F_HP + (h >> 1)], RDY_TARGET);
            asm volatile("fence.proxy.async.global;" ::: "memory");
            seen |= 1u << (h >> 1);
          }
          PWAIT(bE + c.s * 8, c.ph);
          mbar_expect(bF + c.s * 8, 32768);
          tma2d(sbase + c.s * 32768, &p.tmQ, bF + c.s * 8, h * 128, blk * 128);
          tma2d(sbase + c.s * 32768 + 16384, &p.tmQ, bF + c.s * 8, h * 128 + 64, blk * 128);
          c.next();
#pragma unroll 1
          for (int n = nb - 1; n >= 0; n--) {
            if (n == 0 && rank == 0) tick = atomicAdd(&g_sync[F_TICK], 1u);
            PWAIT(bE + c.s * 8, c.ph);
            mbar_expect(bF + c.s * 8, 32768);
            tma2d_mc(sbase + c.s * 32768 + rank * 16384, &p.tmK, bF + c.s * 8, col, n * 128, 3);
            c.next();
            if (n < nb - 1 || it > 0) {
              PWAIT(bE + c.s * 8, c.ph);
              mbar_expect(bF + c.s * 8, 32768);
              tma2d_mc(sbase + c.s * 32768 + rank * 16384, &p.tmV, bF + c.s * 8, (n < nb - 1) ? col : pcol, (n < nb - 1) ? (n + 1) * 128 : 0, 3);
              c.next();
            }
          }
          pcol = col;
          if (rank == 0) {
            asm volatile(
                "{\n.reg .b32 a, b;\nmapa.shared::cluster.u32 a, %0, 1;\nmapa.shared::cluster.u32 b, %1, 1;\n"
                "st.async.shared::cluster.mbarrier::complete_tx::bytes.u32 [a], %2, [b];\n}" ::"r"(sTick + (it & 1) * 4),
                "r"(bT + (it & 1) * 8), "r"(tick) : "memory");
          } else {
            mbar_expect(bT + (it & 1) * 8, 4);
            PWAIT(bT + (it & 1) * 8, (it >> 1) & 1);
            tick = lds32(sTick + (it & 1) * 4);
          }
        }
        PWAIT(bE + c.s * 8, c.ph);
        mbar_expect(bF + c.s * 8, 32768);
        tma2d_mc(sbase + c.s * 32768 + rank * 16384, &p.tmV, bF + c.s * 8, pcol, 0, 3);
        const uint32_t unit = tick - 256;
        if (unit < 64) {
          const int mblk = (7 - (p.unit[unit][0] >> 1)) * 2 + rank, nhalf = p.unit[unit][0] & 1;
          const uint32_t rot = k3_rot(c.s), nfree = ((0x1Au >> c.s) & 1) ? 2 : 3;
#pragma unroll 1
          for (int i = 0; i < K2_NST - 1; i++) {
            c.next();
            PWAIT(bE + c.s * 8, c.ph);
          }
          uint32_t have = 0;
#pragma unroll 1
          for (uint32_t idx = 0; idx < p.unit[unit][2]; idx++) {
            const int kk = p.unit[unit][3] + idx + ((idx >= p.unit[unit][4]) ? p.unit[unit][5] : 0);
            const uint32_t s = (rot + idx) & 3;
            if (idx >= nfree) PWAIT((idx < 4) ? bH : b3E + s * 8, (idx < 4) ? 0 : (~idx >> 2) & 1);
            mbar_expect(b3F + s * 8, K3_STAGE);
            const uint32_t st = sbase + s * K3_STAGE;
            const int sel = (kk < 9), k = sel ? kk : kk - 9, kr = k * 64 + rank * 32;
            tma3d_mc(st + 16384 + rank * 16384, &p.tmO[sel], b3F + s * 8, 0, kr, nhalf * 4, 3);
            tma2d_mc(st + 49152 + rank * 2048, &p.tmOt[sel], b3F + s * 8, 512 + nhalf * 32, kr, 3);
            if (sel && idx == 0) {
              wait_flag(&g_sync[F_OA + mblk], 8);
              asm volatile("fence.proxy.async.global;" ::: "memory");
            }
            if (!sel && !((have >> (k >> 1)) & 1)) {
#pragma unroll 1
              for (uint32_t spins = 0; spins < (1u << 22); spins++) {
                asm volatile("ld.acquire.gpu.global.u32 %0, [%1];" : "=r"(have) : "l"(&g_sync[F_CTX + mblk]) : "memory");
                if ((have >> (k >> 1)) & 1) break;
                __nanosleep(100);
              }
              asm volatile("fence.proxy.async.global;" ::: "memory");
            }
            tma2d(st, &p.tmC, b3F + s * 8, (sel ? 64 + k : k) * 64, mblk * 128);
          }
        }
      }
    }
    __syncwarp();
    if (warp_g == 8) {
      uint32_t v = 0;
      if (lane == 0) {
        __threadfence();
        v = atomicAdd(&g_sync[F_DONE], 1u);
      }
      if (__shfl_sync(0xffffffffu, v, 0) == 2 * NCLUSTER - 1) {
        reinterpret_cast<uint4*>(g_sync)[lane] = make_uint4(0, 0, 0, 0);
        if (lane == 0) g_sync[F_EPOCH] = lds32(sGate + 64) + 1;
      }
    }
    asm volatile("" ::: "memory");
    if (__shfl_sync(0xffffffffu, warp_g, 0) != 8) {
      if (lr0 < S_LEN) {
#pragma unroll 1
        for (int i = warp_g - 9; i < 16; i += 3) {
          const float g = gate_row(lr0 + i, lane, x, gate_w);
          if (lane == 0) asm volatile("st.shared.f32 [%0], %1;" ::"r"(sGate + i * 4), "f"(g) : "memory");
        }
        bar_arrive(3, 256 + 96);
        if (lane == 0) {
          __threadfence();
          atomicAdd(&g_sync[F_GATE], 1u);
        }
      }
      uint32_t aph = 1;
#pragma unroll 1
      for (int ji = 0; ji < K1_MAXJOBS; ji++) aph ^= (p.jobs[cl][ji] >> 14) & 1;
      if (warp_g == 9 && lane == 0) {
#pragma unroll 1
        for (int ji = 0; ji < K1_MAXJOBS; ji++) {
          const uint32_t job = p.jobs[cl][ji];
          if (!(job & 3)) break;
          PWAIT(bS, ji & 1);
          __threadfence();
          atomicAdd(&g_sync[(((job >> 6) & 3) == 2) ? (F_QKVA + ((job >> 3) & 7) * 2 + rank) : (F_HP + ((job >> 10) & 15))], 1u);
        }
#pragma unroll 1
        for (int it = 0;; it++) {
          PWAIT(bS2, it & 1);
          const uint32_t item = lds32(sItem + (it & 7) * 4), nxt = lds32(sItem + ((it + 1) & 7) * 4);
          __threadfence();
          atomicOr(&g_sync[F_CTX + (item & 7) * 2 + (rank ^ (it & 1))], 1u << (item >> 3));
          if (nxt >= K2_END) break;
        }
      } else if (warp_g == 11) {
        if (lane == 0) {
          prefetch_tmap(&p.tmQ); prefetch_tmap(&p.tmK); prefetch_tmap(&p.tmV);
          asm volatile("st.shared.u32 [%0], %1;" ::"r"(sGate + 64), "r"(__ldcg(&g_sync[F_EPOCH])) : "memory");
          wait_flag(&g_sync[F_GATE], GATE_TARGET);
          uint32_t tick;
          if (rank == 0) {
            PWAIT(bLast, 0);
            PWAIT(bAe + FIRST_DRAW * 8, aph);
            tick = atomicAdd(&g_sync[F_TICK], 1u);
            asm volatile("st.shared.u32 [%0], %1;" ::"r"(sTick + 8), "r"(tick) : "memory");
            asm volatile(
                "{\n.reg .b32 a, b;\nmapa.shared::cluster.u32 a, %0, 1;\nmapa.shared::cluster.u32 b, %1, 1;\n"
                "st.async.shared::cluster.mbarrier::complete_tx::bytes.u32 [a], %2, [b];\n}" ::"r"(sTick + 8), "r"(bT0), "r"(tick) : "memory");
          } else {
            mbar_expect(bT0, 4);
            PWAIT(bT0, 0);
            tick = lds32(sTick + 8);
          }
          wait_flag(&g_sync[F_HP + (p.order[tick] >> 4)], RDY_TARGET);
          mbar_arrive(bR);
        }
        __syncwarp();
        bar_sync(4, 256 + 32);
        if (lane < 12) mbar_arrive_cluster(bE + (4 + lane % 3) * 8, (lane / 3) & 1);
      } else if (warp_g == 10 && lr0 < S_LEN) {
        if (elect_one()) {
          prefetch_tmap(&p.tmL[0]); prefetch_tmap(&p.tmL[1]);
          wait_flag(&g_sync[F_QKVA + (lr0 >> 7)], K1_FLAG_TARGET);
          wait_flag(&g_sync[F_QKVA + (max(lr0 - 14, 0) >> 7)], K1_FLAG_TARGET);
          asm volatile("fence.proxy.async.global;" ::: "memory");
          PWAIT(bLast, 0);
#pragma unroll 1
          for (int kc = 0; kc < 6; kc++) {
            PWAIT(bAe + kc * 8, aph);
            if (kc == 3) {
              mbar_expect(bL, 46 * 1152);
              tma3d(sL, &p.tmL[0], bL, 0, 9, lr0 - 14);
              tma3d(sL + 30 * 1152, &p.tmL[1], bL, 0, 0, lr0);
            }
          }
          mbar_expect(bL2, 30 * 1152);
          tma3d(sL + 46 * 1152, &p.tmL[0], bL2, 0, 18, lr0 - 14);
        }
        __syncwarp();
        bar_sync(5, 256 + 32);
        if (lane == 0) {
          __threadfence();
          atomicAdd(&g_sync[F_OA + (lr0 >> 7)], 1u);
        }
      }
    }
    __syncwarp();
    cluster_sync();
  } else {
    reg_alloc<232>();
    const int wg = warp_g >> 2, warp = warp_g & 3, q = lane & 3;
    const bool sig = (lane == 0) && (warp < 2);
    {
      K1State st{0, 0, 0, nullptr, 0, 0, 0, false};
      float acc[128];
      uint32_t pk[64];
      if (wg == 0) { TS(0, 0); TSC(0, 2); }
      uint32_t job = p.jobs[cl][0];
      k1_first(st, job, bAf, bBf);
#pragma unroll 1
      for (int ji = 0; job & 3; ji++) {
        const uint32_t njob = p.jobs[cl][ji + 1];
        k1_tile(acc, pk, st, job, njob, sA, sB, bAf, bAe, bBf, bBe, bS, wg, warp, lane, rank);
        job = njob;
      }
#pragma unroll
      for (int i = 0; i < 4; i++)
        mbar_arrive_cluster_if(bE + i * 8, warp & 1, sig);
      if (st.isq) {
#pragma unroll
        for (int G = 0; G < 16; G++) scale_q4(pk + G * 4);
      }
#pragma unroll
      for (int G = 0; G < 8; G++)
        if (G < st.png) {
          st_v4a(st.pp + G * 32, pk[G * 8], pk[G * 8 + 1], pk[G * 8 + 2], pk[G * 8 + 3]);
          st_v4a(st.pp + G * 32 + st.pld8, pk[G * 8 + 4], pk[G * 8 + 5], pk[G * 8 + 6], pk[G * 8 + 7]);
        }
      k1_flag(st, lane, bS);
      if (wg == 0) { TS(0, 1); TSC(0, 3); }
      if (lr0 < S_LEN) {
        const int ri = (warp_g >> 1) * 4 + (warp_g & 1) + 2, row = lr0 + ri;
        if (wg == 0) TS(1, 5);
        bar_sync(3, 256 + 96);
        const float gate0 = __uint_as_float(lds32(sGate + ri * 4 - 8)), gate1 = __uint_as_float(lds32(sGate + ri * 4));
        mbar_wait(bL, 0);
        if (wg == 0) TS(1, 6);
        local_rows2(row, ri, sL, bL2, lane, gate0, gate1);
        bar_arrive(5, 256 + 32);
      } else {
        bar_arrive(4, 256 + 32);
      }
    }
    __syncwarp();
    uint32_t item, rot;
    {
      const int mybar = 1 + wg, otherbar = 2 - wg;
      const uint32_t never = blockIdx.y;
      float S[64], O[64];
      uint32_t P[32], Q[32];
      float m0 = 0.f, m1 = 0.f, l0 = 1.f, l1 = 1.f, gf0 = 0.f, gf1 = 0.f;
      uint32_t eoff = 0, prev_single = 0;
      Cursor c{0, 0};
      if (wg == 1) bar_arrive(1, 256);
      if (wg == 0) { TS(1, 0); TSC(1, 2); }
#pragma unroll 1
      for (int it = 0;; it++) {
        TB(0);
        const int hi = (int)(rank ^ (it & 1));
        Cursor cq = c, ck, cv, cs0, cs1;
        rot = k3_rot(c.s);
        c.next();
        ck = c; c.next();
        cs0 = ck; cs1 = ck; cv = ck;
        if (it > 0) { cv = c; c.next(); }
        if (!hi) {
          ck = c; c.next();
          cs1 = c; c.next();
        }
        mbar_wait(bF + cq.s * 8, cq.ph);
        TB(1);
        item = lds32(sItem + (it & 7) * 4);
        {
          const uint32_t qa = sbase + cq.s * 32768 + (wg * 64 + warp * 16 + (lane & 15)) * 128;
#pragma unroll
          for (int t = 0; t < 8; t++)
            ldsm_x4(Q[4 * t], Q[4 * t + 1], Q[4 * t + 2], Q[4 * t + 3], qa + (t >> 2) * 16384 + ((((t & 3) * 2 + (lane >> 4)) ^ (lane & 7)) << 4));
        }
        const uint32_t rdy = mbar_test(bF + ck.s * 8, ck.ph) & mbar_test(bF + cv.s * 8, cv.ph);
        l0 += __shfl_xor_sync(0xffffffffu, l0, 1);
        l1 += __shfl_xor_sync(0xffffffffu, l1, 1);
        l0 += __shfl_xor_sync(0xffffffffu, l0, 2);
        l1 += __shfl_xor_sync(0xffffffffu, l1, 2);
        const bool last = item >= K2_END;
        if (last) {
          cv = cq; ck = cq;
        } else if (!rdy) {
          mbar_wait2(bF + ck.s * 8, ck.ph, bF + cv.s * 8, cv.ph);
        }
        TB(2);
        TURN_SYNC();
        TB(3);
        TRC(last ? 2 : 1);
        if (it > 0) {
          wg_fence();
          ISSUE_PV(cv, prev_single);
          wg_commit();
        } else {
          wg_fence();
          wg_commit();
        }
        wg_fence();
        ISSUE_QK(ck);
        wg_commit();
        if (!(last && wg == 1)) TURN_ARRIVE();
        RELEASE_IF(cq, !last);
        TB(4);
        asm volatile("" : "+f"(gf0), "+f"(gf1), "+f"(l0), "+f"(l1));
        const float f0 = __fdividef(1.f - gf0, l0), f1 = __fdividef(1.f - gf1, l1);
        wg_wait<1>();
        fence_regs(O);
        fence_regs(P);
        TB(5);
        if (it > 0) {
          RELEASE_IF(cv, !last);
          mbar_arrive_cluster_if(bH, warp & 1, sig && last);
          STORE_O(0); STORE_O(1); STORE_O(2); STORE_O(3);
          __syncwarp();
          mbar_arrive_if(bS2, lane == 0);
        }
        TB(6);
        if (!last) {
          const int row = (2 * (item & 7) + hi) * 128 + wg * 64 + warp * 16 + (lane >> 2);
          eoff = row * KCAT + (item >> 3) * 128 + q * 8;
          asm volatile("ld.global.f32 %0, [%1];" : "=f"(gf0) : "l"(g_gate + row));
          asm volatile("ld.global.f32 %0, [%1];" : "=f"(gf1) : "l"(g_gate + row + 8));
          if (!hi) {
            mbar_wait2(bF + cs0.s * 8, cs0.ph, bF + cs1.s * 8, cs1.ph);
            RELEASE(cs0);
            RELEASE(cs1);
          }
        }
        TB(7);
        wg_wait<0>();
        fence_regs(S);
        TB(8);
        if (last) break;
        RELEASE(ck);
        const int nblk = 2 * (item & 7) + 1 + hi;
        prev_single = (nblk == 1);
        float s0 = 0.f, s1 = 0.f;
        l0 = 0.f; l1 = 0.f;
        m0 = 0.f; m1 = 0.f;
        bool shifted = false;
        {
          const int d = warp * 16 + (lane >> 2) - 2 * q;
          if (wg == 0) {
#pragma unroll
            for (int jj = 0; jj < 8; jj++) MASK(jj, jj);
            EXPB(0); EXPB(1); EXPB(2); EXPB(3);
#pragma unroll
            for (int i = 32; i < 64; i++) S[i] = -INFINITY;
#pragma unroll
            for (int i = 16; i < 32; i++) P[i] = 0;
          } else {
#pragma unroll
            for (int jj = 0; jj < 8; jj++) MASK(jj + 8, jj);
            EXPB(0); EXPB(1); EXPB(2); EXPB(3); EXPB(4); EXPB(5); EXPB(6); EXPB(7);
          }
        }
        float chk = (q == 0 && !(fminf(s0, s1) >= SPEC_LO)) ? INFINITY : s0 + s1;
        fence_regs(P);
        TB(9);
#pragma unroll 1
        for (int n = 1;; n++) {
          if (__any_sync(0xffffffffu, !(chk <= SPEC_HI))) {
            float mx0 = fmaxf(S[0], S[1]), mx1 = fmaxf(S[2], S[3]);
#pragma unroll
            for (int jj = 1; jj < 16; jj++) {
              mx0 = fmaxf(mx0, fmaxf(S[jj * 4 + 0], S[jj * 4 + 1]));
              mx1 = fmaxf(mx1, fmaxf(S[jj * 4 + 2], S[jj * 4 + 3]));
            }
            mx0 = fmaxf(mx0, __shfl_xor_sync(0xffffffffu, mx0, 1));
            mx1 = fmaxf(mx1, __shfl_xor_sync(0xffffffffu, mx1, 1));
            mx0 = fmaxf(mx0, __shfl_xor_sync(0xffffffffu, mx0, 2));
            mx1 = fmaxf(mx1, __shfl_xor_sync(0xffffffffu, mx1, 2));
            const float lo = (n == 1) ? -INFINITY : 0.f;
            mx0 = fmaxf(mx0, lo);
            mx1 = fmaxf(mx1, lo);
            m0 += mx0; m1 += mx1;
            shifted = true;
            const float sc0 = ex2(-fmaxf(mx0, 0.f)), sc1 = ex2(-fmaxf(mx1, 0.f));
            l0 *= sc0; l1 *= sc1;
            s0 = 0.f; s1 = 0.f;
#pragma unroll
            for (int jj = 0; jj < 16; jj++) {
              const float e0 = ex2(S[jj * 4 + 0] - mx0), e1 = ex2(S[jj * 4 + 1] - mx0), e2 = ex2(S[jj * 4 + 2] - mx1), e3 = ex2(S[jj * 4 + 3] - mx1);
              s0 += e0 + e1;
              s1 += e2 + e3;
              P[jj * 2 + 0] = pack_bf16(e0, e1);
              P[jj * 2 + 1] = pack_bf16(e2, e3);
              O[jj * 4 + 0] *= sc0;
              O[jj * 4 + 1] *= sc0;
              O[jj * 4 + 2] *= sc1;
              O[jj * 4 + 3] *= sc1;
            }
          }
          l0 += s0;
          l1 += s1;
          if (n >= nblk) break;
          ck = c; c.next();
          cv = c; c.next();
          mbar_wait(bF + ck.s * 8, ck.ph);
          mbar_wait(bF + cv.s * 8, cv.ph);
          TURN_SYNC();
          TRC(0);
          wg_fence();
          ISSUE_QK(ck);
          wg_commit();
          {
            const uint64_t dv = make_desc(sbase + cv.s * 32768, 16384, 1024, 1);
#pragma unroll
            for (int t = 0; t < 8; t++) {
              wgmma_rs_n128<1, 0>(O, P[4 * t], P[4 * t + 1], P[4 * t + 2], P[4 * t + 3], dv + (uint64_t)(t * 128), (t > 0) ? 1 : (n != 1));
              if ((PVM >> t) & 1) wg_commit();
            }
          }
          TURN_ARRIVE();
          s0 = 0.f; s1 = 0.f;
          wg_wait<__builtin_popcount(PVM)>();
          fence_regs(S);
          RELEASE(ck);
          if (shifted) {
#pragma unroll
            for (int i = 0; i < 64; i++) S[i] -= (i & 2) ? m1 : m0;
          }
          wg_wait<__builtin_popcount(PVM) - 1>();
          EXPC(0); EXPC(1); EXPC(2); EXPC(3); EXPC(4); EXPC(5); EXPC(6); EXPC(7);
          chk = s0 + s1;
        }
      }
      TRC(3);
      if (wg == 1) { TS(1, 1); TSC(1, 3); }
    }
    __syncwarp();
    const uint32_t unit = item & 255;
    if (unit < 64) {
      const int mblk = (7 - (p.unit[unit][0] >> 1)) * 2 + rank, nhalf = p.unit[unit][0] & 1, ks = p.unit[unit][1];
      const int k0 = 0, k1 = p.unit[unit][2];
      float acc[144];
      uint32_t s = rot, ph = 0, prev = 0;
      if (wg == 0) { TS(2, 0); TSC(2, 2); }
#pragma unroll 1
      for (int k = k0; k < k1; k++) {
        mbar_wait(b3F + s * 8, ph);
        const uint32_t st = sbase + s * K3_STAGE;
        const uint64_t da = make_desc(st + wg * 8192, 16, 1024, 1);
        const uint64_t db = make_desc(st + 16384, 4096, 1024, 1);
        const uint64_t dt = make_desc(st + 49152, 16, 512, 2);
        wg_fence();
#pragma unroll
        for (int t = 0; t < 4; t++) {
          const int sd = (t > 0) || (k > k0);
          wgmma_ss_n256<1, 0>(acc, da + (uint64_t)(t * 2), db + (uint64_t)((t >> 1) * 1024 + (t & 1) * 128), sd);
          wgmma_ss_n32<1, 128>(acc, da + (uint64_t)(t * 2), dt + (uint64_t)(t * 64), sd);
        }
        wg_commit();
        if (k > k0) {
          wg_wait<1>();
          if (sig) mbar_arrive_cluster(b3E + prev * 8, warp);
        }
        prev = s;
        s = (s + 1) & 3;
        if (s == rot) ph ^= 1;
      }
      wg_wait<0>();
      fence_regs(acc);
      cluster_arrive();
      if (wg == 0) TS(2, 4);
      const int tile = mblk * 2 + nhalf;
      uint4* wp = g_part + (size_t)((tile * 4 + ks) * 4) * 5 * 256 + tid;
      const uint32_t sown = sbase + wg * 8192 + (tid & 127) * 16;
#pragma unroll
      for (int d = 0; d < 4; d++) {
        if (d != ks) {
#pragma unroll
          for (int i = 0; i < 4; i++)
            __stcg(wp + (d * 5 + i) * 256,
                   make_uint4(pack_bf16(acc[d * 32 + i * 8], acc[d * 32 + i * 8 + 1]), pack_bf16(acc[d * 32 + i * 8 + 2], acc[d * 32 + i * 8 + 3]),
                              pack_bf16(acc[d * 32 + i * 8 + 4], acc[d * 32 + i * 8 + 5]), pack_bf16(acc[d * 32 + i * 8 + 6], acc[d * 32 + i * 8 + 7])));
          __stcg(reinterpret_cast<uint2*>(wp - tid + (d * 5 + 4) * 256) + tid,
                 make_uint2(pack_bf16(acc[128 + d * 4], acc[128 + d * 4 + 1]), pack_bf16(acc[128 + d * 4 + 2], acc[128 + d * 4 + 3])));
        } else {
#pragma unroll
          for (int i = 0; i < 9; i++) {
            const int o = (i < 8) ? d * 32 + i * 4 : 128 + d * 4;
            asm volatile("st.shared.v4.f32 [%0], {%1, %2, %3, %4};" ::"r"(sown + (i >> 2) * K3_STAGE + (i & 3) * 2048), "f"(acc[o]), "f"(acc[o + 1]), "f"(acc[o + 2]), "f"(acc[o + 3]) : "memory");
          }
        }
      }
      __threadfence();
      __syncwarp();
      if (wg == 0) TS(2, 5);
      if (lane == 0) {
        unsigned int* cnt = &g_sync[F_XCH + tile * 8 + warp_g];
        const uint32_t xtarget = lds32(sGate + 64) * 4 + 4;
        atomicAdd(cnt, 1u);
        uint32_t v, spins = 0;
        do {
          asm volatile("ld.acquire.gpu.global.u32 %0, [%1];" : "=r"(v) : "l"(cnt) : "memory");
        } while ((int)(v - xtarget) < 0 && ++spins < (1u << 24));
      }
      __syncwarp();
      if (wg == 0) TS(2, 6);
      float r[36];
#pragma unroll
      for (int i = 0; i < 9; i++)
        asm volatile("ld.shared.v4.f32 {%0, %1, %2, %3}, [%4];" : "=f"(r[i * 4]), "=f"(r[i * 4 + 1]), "=f"(r[i * 4 + 2]), "=f"(r[i * 4 + 3])
                     : "r"(sown + (i >> 2) * K3_STAGE + (i & 3) * 2048) : "memory");
#pragma unroll
      for (int sI = 1; sI < 4; sI++) {
        const int src = (ks + sI) & 3;
        const uint4* rp = g_part + (size_t)(((tile * 4 + src) * 4) + ks) * 5 * 256;
#pragma unroll
        for (int i = 0; i < 4; i++) {
          const uint4 v = __ldcg(rp + i * 256 + tid);
          r[i * 8] += bf_lo(v.x); r[i * 8 + 1] += bf_hi(v.x); r[i * 8 + 2] += bf_lo(v.y); r[i * 8 + 3] += bf_hi(v.y);
          r[i * 8 + 4] += bf_lo(v.z); r[i * 8 + 5] += bf_hi(v.z); r[i * 8 + 6] += bf_lo(v.w); r[i * 8 + 7] += bf_hi(v.w);
        }
        const uint2 v = __ldcg(reinterpret_cast<const uint2*>(rp + 4 * 256) + tid);
        r[32] += bf_lo(v.x); r[33] += bf_hi(v.x); r[34] += bf_lo(v.y); r[35] += bf_hi(v.y);
      }
      const int row = mblk * 128 + wg * 64 + warp * 16 + (lane >> 2);
      bf16* o0 = out + (size_t)row * DM + nhalf * 256 + ks * 64 + 8 * q;
#pragma unroll
      for (int G = 0; G < 2; G++) {
        uint32_t a0 = pack_bf16(r[G * 16], r[G * 16 + 1]), a1 = pack_bf16(r[G * 16 + 4], r[G * 16 + 5]);
        uint32_t a2 = pack_bf16(r[G * 16 + 8], r[G * 16 + 9]), a3 = pack_bf16(r[G * 16 + 12], r[G * 16 + 13]);
        uint32_t b0 = pack_bf16(r[G * 16 + 2], r[G * 16 + 3]), b1 = pack_bf16(r[G * 16 + 6], r[G * 16 + 7]);
        uint32_t b2 = pack_bf16(r[G * 16 + 10], r[G * 16 + 11]), b3 = pack_bf16(r[G * 16 + 14], r[G * 16 + 15]);
        quad_transpose(a0, a1, a2, a3, q);
        quad_transpose(b0, b1, b2, b3, q);
        st_v4(o0 + G * 32, a0, a1, a2, a3);
        st_v4(o0 + 8 * DM + G * 32, b0, b1, b2, b3);
      }
      {
        uint32_t t0 = pack_bf16(r[32], r[33]), t1 = pack_bf16(r[34], r[35]), t2 = 0, t3 = 0;
        quad_transpose(t0, t1, t2, t3, q);
        if (q < 2) st_v4(out + (size_t)(row + q * 8) * DM + 512 + nhalf * 32 + ks * 8, t0, t1, t2, t3);
      }
    } else {
      cluster_arrive();
    }
    if (wg == 0) { TS(2, 1); TSC(2, 3); }
    cluster_wait();
  }
}

typedef CUresult (*EncFn)(CUtensorMap*, CUtensorMapDataType, cuuint32_t, void*, const cuuint64_t*, const cuuint64_t*, const cuuint32_t*,
                          const cuuint32_t*, CUtensorMapInterleave, CUtensorMapSwizzle, CUtensorMapL2promotion, CUtensorMapFloatOOBfill);

static void enc2d(EncFn enc, CUtensorMap* m, const void* ptr, uint64_t cols, uint64_t rows, uint32_t bc, uint32_t br,
                  CUtensorMapSwizzle sw = CU_TENSOR_MAP_SWIZZLE_128B) {
  cuuint64_t gd[2] = {cols, rows}, gs[1] = {cols * 2};
  cuuint32_t bx[2] = {bc, br}, es[2] = {1, 1};
  enc(m, CU_TENSOR_MAP_DATA_TYPE_BFLOAT16, 2, const_cast<void*>(ptr), gd, gs, bx, es, CU_TENSOR_MAP_INTERLEAVE_NONE, sw,
      CU_TENSOR_MAP_L2_PROMOTION_L2_256B, CU_TENSOR_MAP_FLOAT_OOB_FILL_NONE);
}
static void enc3d(EncFn enc, CUtensorMap* m, const void* ptr, uint64_t cols, uint64_t rows, uint32_t br, uint32_t bch) {
  cuuint64_t gd[3] = {64, rows, cols / 64}, gs[2] = {cols * 2, 128};
  cuuint32_t bx[3] = {64, br, bch}, es[3] = {1, 1, 1};
  enc(m, CU_TENSOR_MAP_DATA_TYPE_BFLOAT16, 3, const_cast<void*>(ptr), gd, gs, bx, es, CU_TENSOR_MAP_INTERLEAVE_NONE,
      CU_TENSOR_MAP_SWIZZLE_128B, CU_TENSOR_MAP_L2_PROMOTION_L2_256B, CU_TENSOR_MAP_FLOAT_OOB_FILL_NONE);
}

static int g_sched[10] = {11, 10, 7, 4, 4, 4, 6, 7, 6, 24};
static void build_k1_jobs(Params& p) {
  int cnt[NCLUSTER];
  for (int c = 0; c < NCLUSTER; c++) {
    cnt[c] = 0;
    for (int i = 0; i <= K1_MAXJOBS; i++) p.jobs[c][i] = 0;
  }
  auto add = [&](int c, int nch, int a_sel, int mp, int w_sel, int chunk0) {
    p.jobs[c][cnt[c]++] = (uint16_t)((nch - 1) | (a_sel << 2) | (mp << 3) | (w_sel << 6) | (chunk0 << 8));
  };
  const int *cg = g_sched, *xg = g_sched + 4;
  for (int mp = 0; mp < 8; mp++) {
    int k = 0;
    for (int i = 0; i < K1_MAXJOBS; i++)
      for (int g = 0; g < 4; g++)
        if (i < cg[g]) { add(g * 8 + mp, 4, 0, mp, k & 1, (k >> 1) * 4); k++; }
    k = 0;
    for (int i = 0; i < K1_MAXJOBS; i++)
      for (int g = 0; g < 4; g++)
        if (i < xg[g]) {
          if (k < 7) add((4 + g) * 8 + mp, k == 0 ? 3 : 4, 1, mp, 2, k == 0 ? 24 : (k - 1) * 4);
          else add((4 + g) * 8 + mp, 4, 1, mp, 3, (k - 7) * 4);
          k++;
        }
    add(64 + mp / 4, 4, 1, mp, 3, 14 * 4);
    add(64 + mp / 4, 4, 1, mp, 3, 15 * 4);
  }
  for (int cc = 0; cc < NCLUSTER; cc++)
    for (int i = 0; i < cnt[cc]; i++) {
      const int key = p.jobs[cc][i] & 0x3C;
      if (i == 0 || (p.jobs[cc][i - 1] & 0x3C) != key) p.jobs[cc][i] |= (1 << 14);
      if (i == cnt[cc] - 1 || (p.jobs[cc][i + 1] & 0x3C) != key) p.jobs[cc][i] |= (1 << 15);
    }
}

static void build_k2_items(Params& p) {
  int n = 0;
  const int SCHED_N1 = g_sched[8], SCHED_N2 = g_sched[9];
  for (int j = 7; j >= 0; j--)
    for (int h = 0; h < SCHED_N1; h++) p.order[n++] = (uint8_t)(h * 8 + j);
  for (int j = 7; j >= 4; j--)
    for (int h = SCHED_N1; h < SCHED_N2; h++) p.order[n++] = (uint8_t)(h * 8 + j);
  for (int j = 7; j >= 0; j--)
    for (int h = SCHED_N1; h < 32; h++)
      if (!(h < SCHED_N2 && j >= 4)) p.order[n++] = (uint8_t)(h * 8 + j);
}

static void build_k3_units(Params& p) {
  float slope = 0.045f;
  int NE = 25;
  for (int t = 0; t < 16; t++) {
    const int u[4] = {t, 31 - t, 32 + t, 63 - t};
    float acc = 0.f;
    int k0 = 0, l0 = NE;
    for (int i = 0; i < 4; i++) {
      acc += 18.25f + slope * (31.5f - u[i]);
      const int k1 = (i == 3) ? 73 : (int)(acc + 0.5f);
      const int e0 = NE * i / 4, e1 = NE * (i + 1) / 4;
      uint8_t* w = p.unit[u[i]];
      w[0] = (uint8_t)t; w[1] = (uint8_t)i; w[2] = (uint8_t)(k1 - k0); w[3] = (uint8_t)e0; w[4] = (uint8_t)(e1 - e0); w[5] = (uint8_t)(l0 - e1);
      l0 += (k1 - k0) - (e1 - e0);
      k0 = k1;
    }
  }
}

extern "C" void kernel_launch(void* const* d_in, const int* in_sizes, int n_in, void* d_out, int out_size) {
  const bf16* x = (const bf16*)d_in[0];
  const bf16* wqkv = (const bf16*)d_in[1];
  const bf16* wo = (const bf16*)d_in[2];
  const bf16* ckv = (const bf16*)d_in[4];
  const bf16* w_q = (const bf16*)d_in[5];
  const bf16* w_uk = (const bf16*)d_in[6];
  const bf16* w_uv = (const bf16*)d_in[7];
  const bf16* w_o = (const bf16*)d_in[8];
  const bf16* gate_w = (const bf16*)d_in[9];

  EncFn enc = nullptr;
  cudaDriverEntryPointQueryResult qr;
  cudaGetDriverEntryPoint("cuTensorMapEncodeTiled", (void**)&enc, cudaEnableDefault, &qr);
  void *pQ, *pK, *pV, *pCtx, *pQA;
  cudaGetSymbolAddress(&pQ, g_Q);
  cudaGetSymbolAddress(&pQA, g_QKVA);
  cudaGetSymbolAddress(&pK, g_K);
  cudaGetSymbolAddress(&pV, g_V);
  cudaGetSymbolAddress(&pCtx, g_ctx);

  static Params p;
  enc2d(enc, &p.tmA[0], ckv, DC, S_LEN, 64, 128);
  enc2d(enc, &p.tmA[1], x, DM, S_LEN, 64, 128);
  enc3d(enc, &p.tmW[0], w_uk, HDIM, DC, 16, 4);
  enc3d(enc, &p.tmW[1], w_uv, HDIM, DC, 16, 4);
  enc3d(enc, &p.tmW[2], wqkv, NQKVA, DM, 16, 4);
  enc3d(enc, &p.tmW[3], w_q, HDIM, DM, 16, 4);
  build_k1_jobs(p);
  enc2d(enc, &p.tmQ, pQ, HDIM, S_LEN, 64, 128);
  enc2d(enc, &p.tmK, pK, HDIM, S_LEN, 64, 128);
  enc2d(enc, &p.tmV, pV, HDIM, S_LEN, 64, 128);
  build_k2_items(p);
  build_k3_units(p);
  for (int i = 0; i < 2; i++) {
    cuuint64_t gd[3] = {64, 27, S_LEN}, gs[2] = {128, NQKVA * 2};
    cuuint32_t bx[3] = {64, 9, i ? 16u : 30u}, es[3] = {1, 1, 1};
    enc(&p.tmL[i], CU_TENSOR_MAP_DATA_TYPE_BFLOAT16, 3, pQA, gd, gs, bx, es, CU_TENSOR_MAP_INTERLEAVE_NONE, CU_TENSOR_MAP_SWIZZLE_NONE,
        CU_TENSOR_MAP_L2_PROMOTION_L2_256B, CU_TENSOR_MAP_FLOAT_OOB_FILL_NONE);
  }
  enc2d(enc, &p.tmC, pCtx, KCAT, S_LEN, 64, 128);
  enc3d(enc, &p.tmO[0], w_o, DM, HDIM, 32, 4);
  enc3d(enc, &p.tmO[1], wo, DM, DM, 32, 4);
  enc2d(enc, &p.tmOt[0], w_o, DM, HDIM, 32, 32, CU_TENSOR_MAP_SWIZZLE_64B);
  enc2d(enc, &p.tmOt[1], wo, DM, DM, 32, 32, CU_TENSOR_MAP_SWIZZLE_64B);

  cudaFuncSetAttribute(fused_kernel, cudaFuncAttributeMaxDynamicSharedMemorySize, SMEM_BYTES);
  fused_kernel<<<NCLUSTER * 2, 384, SMEM_BYTES>>>(p, x, gate_w, (bf16*)d_out);
}
```

```cpp
#include <cuda_runtime.h>
#include <cuda_bf16.h>
#include <cuda.h>
#include <stdint.h>

typedef __nv_bfloat16 bf16;

constexpr int S_LEN = 2048, DM = 576, DC = 512, HDIM = 4096, NQKVA = 1728, KCAT = 4672;
constexpr int NCLUSTER = 66;

__device__ __align__(1024) bf16 g_Q[S_LEN * HDIM];
__device__ __align__(1024) bf16 g_K[S_LEN * HDIM];
__device__ __align__(1024) bf16 g_V[S_LEN * HDIM];
__device__ __align__(1024) bf16 g_QKVA[S_LEN * NQKVA + 64];
__device__ __align__(1024) bf16 g_ctx[S_LEN * KCAT];
__device__ float g_gate[S_LEN];
__device__ __align__(1024) uint4 g_part[32 * 4 * 4 * 5 * 256];
__device__ __align__(16) unsigned int g_sync[400];
constexpr int F_QKVA = 0, F_HP = 16, F_CTX = 32, F_OA = 48, F_GATE = 96, F_TICK = 97, F_DONE = 98, F_XCH = 128, F_EPOCH = 384;

__device__ __forceinline__ uint32_t smem_u32(const void* p) { return (uint32_t)__cvta_generic_to_shared(p); }
__device__ __forceinline__ void mbar_init(uint32_t a, uint32_t c) {
  asm volatile("mbarrier.init.shared::cta.b64 [%0], %1;" ::"r"(a), "r"(c));
}
__device__ __forceinline__ void mbar_expect(uint32_t a, uint32_t b) {
  asm volatile("mbarrier.arrive.expect_tx.shared::cta.b64 _, [%0], %1;" ::"r"(a), "r"(b) : "memory");
}
#define TS(k, i)
#define TSC(k, i)
#define TSM(k)
#define BSEG(i)
#define TB(k)
#define TRC(fl)
#define SPIN_LIMIT "4194304"
__device__ __forceinline__ void mbar_wait(uint32_t a, uint32_t parity) {
  asm volatile(
      "{\n.reg .pred p;\n.reg .u32 n;\n"
      "mbarrier.try_wait.parity.shared::cta.b64 p, [%0], %1;\n"
      "@p bra DONE;\n"
      "mov.u32 n, 0;\n"
      "LOOP:\n"
      "mbarrier.try_wait.parity.shared::cta.b64 p, [%0], %1;\n"
      "@p bra DONE;\n"
      "add.u32 n, n, 1;\n"
      "setp.lt.u32 p, n, " SPIN_LIMIT ";\n"
      "@p bra LOOP;\n"
      "DONE:\n}" ::"r"(a), "r"(parity) : "memory");
}
template <int NS>
__device__ __forceinline__ void mbar_wait_ns(uint32_t a, uint32_t parity) {
  asm volatile(
      "{\n.reg .pred p;\n.reg .u32 n;\n"
      "mov.u32 n, 0;\n"
      "LOOP:\n"
      "mbarrier.try_wait.parity.shared::cta.b64 p, [%0], %1, %2;\n"
      "@p bra DONE;\n"
      "add.u32 n, n, 1;\n"
      "setp.lt.u32 p, n, " SPIN_LIMIT ";\n"
      "@p bra LOOP;\n"
      "DONE:\n}" ::"r"(a), "r"(parity), "n"(NS) : "memory");
}
__device__ __forceinline__ void mbar_wait2(uint32_t a, uint32_t pa, uint32_t b, uint32_t pb) {
  asm volatile(
      "{\n.reg .pred p, q;\n.reg .u32 n;\n"
      "mov.u32 n, 0;\n"
      "LOOP:\n"
      "mbarrier.try_wait.parity.shared::cta.b64 p, [%0], %1;\n"
      "mbarrier.try_wait.parity.shared::cta.b64 q, [%2], %3;\n"
      "add.u32 n, n, 1;\n"
      "and.pred p, p, q;\n"
      "setp.lt.and.u32 p, n, " SPIN_LIMIT ", !p;\n"
      "@p bra LOOP;\n"
      "}" ::"r"(a), "r"(pa), "r"(b), "r"(pb) : "memory");
}
__device__ __forceinline__ uint32_t mbar_test(uint32_t a, uint32_t parity) {
  uint32_t r;
  asm volatile("{\n.reg .pred p;\nmbarrier.test_wait.parity.shared::cta.b64 p, [%1], %2;\nselp.u32 %0, 1, 0, p;\n}" : "=r"(r) : "r"(a), "r"(parity) : "memory");
  return r;
}
__device__ __forceinline__ void mbar_arrive(uint32_t a) {
  asm volatile("mbarrier.arrive.shared::cta.b64 _, [%0];" ::"r"(a) : "memory");
}
__device__ __forceinline__ void mbar_arrive_cluster(uint32_t a, uint32_t cta) {
  asm volatile("{\n.reg .b32 r;\nmapa.shared::cluster.u32 r, %0, %1;\nmbarrier.arrive.shared::cluster.b64 _, [r];\n}" ::"r"(a),
               "r"(cta) : "memory");
}
__device__ __forceinline__ void mbar_arrive_cluster_if(uint32_t a, uint32_t cta, bool pred) {
  asm volatile("{\n.reg .b32 r;\n.reg .pred p;\nsetp.ne.u32 p, %2, 0;\nmapa.shared::cluster.u32 r, %0, %1;\n@p mbarrier.arrive.shared::cluster.b64 _, [r];\n}" ::"r"(a),
               "r"(cta), "r"((uint32_t)pred) : "memory");
}
__device__ __forceinline__ void anchor(float v, uint32_t pred) {
  asm volatile("{\n.reg .pred p;\nsetp.ne.u32 p, %1, 0;\n@p st.shared.f32 [%1], %0;\n}" ::"f"(v), "r"(pred) : "memory");
}
__device__ __forceinline__ void mbar_arrive_if(uint32_t a, bool pred) {
  asm volatile("{\n.reg .pred p;\nsetp.ne.u32 p, %1, 0;\n@p mbarrier.arrive.shared::cta.b64 _, [%0];\n}" ::"r"(a), "r"((uint32_t)pred) : "memory");
}
__device__ __forceinline__ void tma2d(uint32_t dst, const CUtensorMap* m, uint32_t bar, int c0, int c1) {
  asm volatile("cp.async.bulk.tensor.2d.shared::cluster.global.mbarrier::complete_tx::bytes [%0], [%1, {%3, %4}], [%2];" ::"r"(dst),
               "l"(m), "r"(bar), "r"(c0), "r"(c1) : "memory");
}
__device__ __forceinline__ void tma2d_mc(uint32_t dst, const CUtensorMap* m, uint32_t bar, int c0, int c1, uint16_t mask) {
  asm volatile(
      "cp.async.bulk.tensor.2d.shared::cluster.global.mbarrier::complete_tx::bytes.multicast::cluster [%0], [%1, {%3, %4}], [%2], %5;" ::"r"(dst),
      "l"(m), "r"(bar), "r"(c0), "r"(c1), "h"(mask) : "memory");
}
__device__ __forceinline__ void tma3d_mc(uint32_t dst, const CUtensorMap* m, uint32_t bar, int c0, int c1, int c2, uint16_t mask) {
  asm volatile(
      "cp.async.bulk.tensor.3d.shared::cluster.global.mbarrier::complete_tx::bytes.multicast::cluster [%0], [%1, {%3, %4, %5}], [%2], %6;" ::"r"(dst),
      "l"(m), "r"(bar), "r"(c0), "r"(c1), "r"(c2), "h"(mask) : "memory");
}
__device__ __forceinline__ void tma3d(uint32_t dst, const CUtensorMap* m, uint32_t bar, int c0, int c1, int c2) {
  asm volatile(
      "cp.async.bulk.tensor.3d.shared::cluster.global.mbarrier::complete_tx::bytes [%0], [%1, {%3, %4, %5}], [%2];" ::"r"(dst),
      "l"(m), "r"(bar), "r"(c0), "r"(c1), "r"(c2) : "memory");
}
__device__ __forceinline__ void tma_pf2d(const CUtensorMap* m, int c0, int c1) {
  asm volatile("cp.async.bulk.prefetch.tensor.2d.L2.global [%0, {%1, %2}];" ::"l"(m), "r"(c0), "r"(c1) : "memory");
}
__device__ __forceinline__ void tma_pf3d(const CUtensorMap* m, int c0, int c1, int c2) {
  asm volatile("cp.async.bulk.prefetch.tensor.3d.L2.global [%0, {%1, %2, %3}];" ::"l"(m), "r"(c0), "r"(c1), "r"(c2) : "memory");
}
__device__ __forceinline__ void prefetch_tmap(const CUtensorMap* m) {
  asm volatile("prefetch.tensormap [%0];" ::"l"(m) : "memory");
}
__device__ __forceinline__ void cluster_arrive() { asm volatile("barrier.cluster.arrive.relaxed.aligned;" ::: "memory"); }
__device__ __forceinline__ void cluster_wait() { asm volatile("barrier.cluster.wait.aligned;" ::: "memory"); }
__device__ __forceinline__ void cluster_sync() {
  cluster_arrive();
  cluster_wait();
}
__device__ __forceinline__ uint32_t cluster_rank() {
  uint32_t r;
  asm volatile("mov.u32 %0, %%cluster_ctarank;" : "=r"(r));
  return r;
}
__device__ __forceinline__ bool elect_one() {
  uint32_t p;
  asm volatile("{\n.reg .pred q;\nelect.sync _|q, 0xffffffff;\nselp.u32 %0, 1, 0, q;\n}" : "=r"(p));
  return p;
}
__device__ __forceinline__ void ldsm_x4(uint32_t& r0, uint32_t& r1, uint32_t& r2, uint32_t& r3, uint32_t addr) {
  asm volatile("ldmatrix.sync.aligned.m8n8.x4.shared.b16 {%0, %1, %2, %3}, [%4];" : "=r"(r0), "=r"(r1), "=r"(r2), "=r"(r3) : "r"(addr) : "memory");
}
__device__ __forceinline__ void wg_fence() { asm volatile("wgmma.fence.sync.aligned;" ::: "memory"); }
__device__ __forceinline__ void wg_commit() { asm volatile("wgmma.commit_group.sync.aligned;" ::: "memory"); }
template <int N>
__device__ __forceinline__ void wg_wait() { asm volatile("wgmma.wait_group.sync.aligned %0;" ::"n"(N) : "memory"); }
template <int N>
__device__ __forceinline__ void reg_alloc() { asm volatile("setmaxnreg.inc.sync.aligned.u32 %0;" ::"n"(N)); }
template <int N>
__device__ __forceinline__ void reg_dealloc() { asm volatile("setmaxnreg.dec.sync.aligned.u32 %0;" ::"n"(N)); }
__device__ __forceinline__ void bar_sync(int id, int n) { asm volatile("bar.sync %0, %1;" ::"r"(id), "r"(n) : "memory"); }
__device__ __forceinline__ void bar_arrive(int id, int n) { asm volatile("bar.arrive %0, %1;" ::"r"(id), "r"(n) : "memory"); }
template <int NT>
__device__ __forceinline__ void fence_regs(float (&d)[NT]) {
#pragma unroll
  for (int i = 0; i < NT; i++) asm volatile("" : "+f"(d[i])::"memory");
}
template <int NT>
__device__ __forceinline__ void fence_regs(uint32_t (&d)[NT]) {
#pragma unroll
  for (int i = 0; i < NT; i++) asm volatile("" : "+r"(d[i])::"memory");
}
__device__ __forceinline__ uint64_t make_desc(uint32_t saddr, uint32_t lbo, uint32_t sbo, uint32_t layout) {
  return (uint64_t)((saddr & 0x3FFFF) >> 4) | ((uint64_t)(lbo >> 4) << 16) | ((uint64_t)(sbo >> 4) << 32) | ((uint64_t)layout << 62);
}
__device__ __forceinline__ uint32_t pack_bf16(float lo, float hi) {
  uint32_t r;
  asm("cvt.rn.bf16x2.f32 %0, %1, %2;" : "=r"(r) : "f"(hi), "f"(lo));
  return r;
}
__device__ __forceinline__ float ex2(float x) {
  float r;
  asm("ex2.approx.ftz.f32 %0, %1;" : "=f"(r) : "f"(x));
  return r;
}
__device__ __forceinline__ void st_v4(void* p, uint32_t a, uint32_t b, uint32_t c, uint32_t d) {
#define ST_MOD ".cs"
  asm volatile("st.global" ST_MOD ".v4.b32 [%0], {%1, %2, %3, %4};" ::"l"(p), "r"(a), "r"(b), "r"(c), "r"(d) : "memory");
}
#define STA_MOD ".cs"
__device__ __forceinline__ void st_v4a(void* p, uint32_t a, uint32_t b, uint32_t c, uint32_t d) {
  asm volatile("st.global" STA_MOD ".v4.b32 [%0], {%1, %2, %3, %4};" ::"l"(p), "r"(a), "r"(b), "r"(c), "r"(d) : "memory");
}
__device__ __forceinline__ float bf_lo(uint32_t v) { return __uint_as_float(v << 16); }
__device__ __forceinline__ float bf_hi(uint32_t v) { return __uint_as_float(v & 0xFFFF0000u); }

__device__ __forceinline__ void quad_transpose(uint32_t& a0, uint32_t& a1, uint32_t& a2, uint32_t& a3, int q) {
  const bool o1 = q & 1, o2 = q & 2;
  uint32_t t0 = o1 ? a0 : a1, t1 = o1 ? a2 : a3;
  t0 = __shfl_xor_sync(0xffffffffu, t0, 1);
  t1 = __shfl_xor_sync(0xffffffffu, t1, 1);
  if (o1) { a0 = t0; a2 = t1; } else { a1 = t0; a3 = t1; }
  t0 = o2 ? a0 : a2;
  t1 = o2 ? a1 : a3;
  t0 = __shfl_xor_sync(0xffffffffu, t0, 2);
  t1 = __shfl_xor_sync(0xffffffffu, t1, 2);
  if (o2) { a0 = t0; a1 = t1; } else { a2 = t0; a3 = t1; }
}

template<int TB, int OFF, int NT>
__device__ __forceinline__ void wgmma_ss_n256(float (&d)[NT], uint64_t da, uint64_t db, int scale_d) {
  asm volatile("{\n.reg .pred p;\nsetp.ne.b32 p, %130, 0;\n"
    "wgmma.mma_async.sync.aligned.m64n256k16.f32.bf16.bf16 {%0, %1, %2, %3, %4, %5, %6, %7, %8, %9, %10, %11, %12, %13, %14, %15, %16, %17, %18, %19, %20, %21, %22, %23, %24, %25, %26, %27, %28, %29, %30, %31, %32, %33, %34, %35, %36, %37, %38, %39, %40, %41, %42, %43, %44, %45, %46, %47, %48, %49, %50, %51, %52, %53, %54, %55, %56, %57, %58, %59, %60, %61, %62, %63, %64, %65, %66, %67, %68, %69, %70, %71, %72, %73, %74, %75, %76, %77, %78, %79, %80, %81, %82, %83, %84, %85, %86, %87, %88, %89, %90, %91, %92, %93, %94, %95, %96, %97, %98, %99, %100, %101, %102, %103, %104, %105, %106, %107, %108, %109, %110, %111, %112, %113, %114, %115, %116, %117, %118, %119, %120, %121, %122, %123, %124, %125, %126, %127}, %128, %129, p, 1, 1, 0, %131;\n}\n"
    : "+f"(d[OFF+0]), "+f"(d[OFF+1]), "+f"(d[OFF+2]), "+f"(d[OFF+3]), "+f"(d[OFF+4]), "+f"(d[OFF+5]), "+f"(d[OFF+6]), "+f"(d[OFF+7]), "+f"(d[OFF+8]), "+f"(d[OFF+9]), "+f"(d[OFF+10]), "+f"(d[OFF+11]), "+f"(d[OFF+12]), "+f"(d[OFF+13]), "+f"(d[OFF+14]), "+f"(d[OFF+15]), "+f"(d[OFF+16]), "+f"(d[OFF+17]), "+f"(d[OFF+18]), "+f"(d[OFF+19]), "+f"(d[OFF+20]), "+f"(d[OFF+21]), "+f"(d[OFF+22]), "+f"(d[OFF+23]), "+f"(d[OFF+24]), "+f"(d[OFF+25]), "+f"(d[OFF+26]), "+f"(d[OFF+27]), "+f"(d[OFF+28]), "+f"(d[OFF+29]), "+f"(d[OFF+30]), "+f"(d[OFF+31]), "+f"(d[OFF+32]), "+f"(d[OFF+33]), "+f"(d[OFF+34]), "+f"(d[OFF+35]), "+f"(d[OFF+36]), "+f"(d[OFF+37]), "+f"(d[OFF+38]), "+f"(d[OFF+39]), "+f"(d[OFF+40]), "+f"(d[OFF+41]), "+f"(d[OFF+42]), "+f"(d[OFF+43]), "+f"(d[OFF+44]), "+f"(d[OFF+45]), "+f"(d[OFF+46]), "+f"(d[OFF+47]), "+f"(d[OFF+48]), "+f"(d[OFF+49]), "+f"(d[OFF+50]), "+f"(d[OFF+51]), "+f"(d[OFF+52]), "+f"(d[OFF+53]), "+f"(d[OFF+54]), "+f"(d[OFF+55]), "+f"(d[OFF+56]), "+f"(d[OFF+57]), "+f"(d[OFF+58]), "+f"(d[OFF+59]), "+f"(d[OFF+60]), "+f"(d[OFF+61]), "+f"(d[OFF+62]), "+f"(d[OFF+63]), "+f"(d[OFF+64]), "+f"(d[OFF+65]), "+f"(d[OFF+66]), "+f"(d[OFF+67]), "+f"(d[OFF+68]), "+f"(d[OFF+69]), "+f"(d[OFF+70]), "+f"(d[OFF+71]), "+f"(d[OFF+72]), "+f"(d[OFF+73]), "+f"(d[OFF+74]), "+f"(d[OFF+75]), "+f"(d[OFF+76]), "+f"(d[OFF+77]), "+f"(d[OFF+78]), "+f"(d[OFF+79]), "+f"(d[OFF+80]), "+f"(d[OFF+81]), "+f"(d[OFF+82]), "+f"(d[OFF+83]), "+f"(d[OFF+84]), "+f"(d[OFF+85]), "+f"(d[OFF+86]), "+f"(d[OFF+87]), "+f"(d[OFF+88]), "+f"(d[OFF+89]), "+f"(d[OFF+90]), "+f"(d[OFF+91]), "+f"(d[OFF+92]), "+f"(d[OFF+93]), "+f"(d[OFF+94]), "+f"(d[OFF+95]), "+f"(d[OFF+96]), "+f"(d[OFF+97]), "+f"(d[OFF+98]), "+f"(d[OFF+99]), "+f"(d[OFF+100]), "+f"(d[OFF+101]), "+f"(d[OFF+102]), "+f"(d[OFF+103]), "+f"(d[OFF+104]), "+f"(d[OFF+105]), "+f"(d[OFF+106]), "+f"(d[OFF+107]), "+f"(d[OFF+108]), "+f"(d[OFF+109]), "+f"(d[OFF+110]), "+f"(d[OFF+111]), "+f"(d[OFF+112]), "+f"(d[OFF+113]), "+f"(d[OFF+114]), "+f"(d[OFF+115]), "+f"(d[OFF+116]), "+f"(d[OFF+117]), "+f"(d[OFF+118]), "+f"(d[OFF+119]), "+f"(d[OFF+120]), "+f"(d[OFF+121]), "+f"(d[OFF+122]), "+f"(d[OFF+123]), "+f"(d[OFF+124]), "+f"(d[OFF+125]), "+f"(d[OFF+126]), "+f"(d[OFF+127])
    : "l"(da), "l"(db), "r"(scale_d), "n"(TB));
}
template<int TB, int OFF, int NT>
__device__ __forceinline__ void wgmma_ss_n32(float (&d)[NT], uint64_t da, uint64_t db, int scale_d) {
  asm volatile("{\n.reg .pred p;\nsetp.ne.b32 p, %18, 0;\n"
    "wgmma.mma_async.sync.aligned.m64n32k16.f32.bf16.bf16 {%0, %1, %2, %3, %4, %5, %6, %7, %8, %9, %10, %11, %12, %13, %14, %15}, %16, %17, p, 1, 1, 0, %19;\n}\n"
    : "+f"(d[OFF+0]), "+f"(d[OFF+1]), "+f"(d[OFF+2]), "+f"(d[OFF+3]), "+f"(d[OFF+4]), "+f"(d[OFF+5]), "+f"(d[OFF+6]), "+f"(d[OFF+7]), "+f"(d[OFF+8]), "+f"(d[OFF+9]), "+f"(d[OFF+10]), "+f"(d[OFF+11]), "+f"(d[OFF+12]), "+f"(d[OFF+13]), "+f"(d[OFF+14]), "+f"(d[OFF+15])
    : "l"(da), "l"(db), "r"(scale_d), "n"(TB));
}
template<int TB, int OFF, int NT>
__device__ __forceinline__ void wgmma_rs_n128(float (&d)[NT], uint32_t a0, uint32_t a1, uint32_t a2, uint32_t a3, uint64_t db, int scale_d) {
  asm volatile("{\n.reg .pred p;\nsetp.ne.b32 p, %69, 0;\n"
    "wgmma.mma_async.sync.aligned.m64n128k16.f32.bf16.bf16 {%0, %1, %2, %3, %4, %5, %6, %7, %8, %9, %10, %11, %12, %13, %14, %15, %16, %17, %18, %19, %20, %21, %22, %23, %24, %25, %26, %27, %28, %29, %30, %31, %32, %33, %34, %35, %36, %37, %38, %39, %40, %41, %42, %43, %44, %45, %46, %47, %48, %49, %50, %51, %52, %53, %54, %55, %56, %57, %58, %59, %60, %61, %62, %63}, {%64, %65, %66, %67}, %68, p, 1, 1, %70;\n}\n"
    : "+f"(d[OFF+0]), "+f"(d[OFF+1]), "+f"(d[OFF+2]), "+f"(d[OFF+3]), "+f"(d[OFF+4]), "+f"(d[OFF+5]), "+f"(d[OFF+6]), "+f"(d[OFF+7]), "+f"(d[OFF+8]), "+f"(d[OFF+9]), "+f"(d[OFF+10]), "+f"(d[OFF+11]), "+f"(d[OFF+12]), "+f"(d[OFF+13]), "+f"(d[OFF+14]), "+f"(d[OFF+15]), "+f"(d[OFF+16]), "+f"(d[OFF+17]), "+f"(d[OFF+18]), "+f"(d[OFF+19]), "+f"(d[OFF+20]), "+f"(d[OFF+21]), "+f"(d[OFF+22]), "+f"(d[OFF+23]), "+f"(d[OFF+24]), "+f"(d[OFF+25]), "+f"(d[OFF+26]), "+f"(d[OFF+27]), "+f"(d[OFF+28]), "+f"(d[OFF+29]), "+f"(d[OFF+30]), "+f"(d[OFF+31]), "+f"(d[OFF+32]), "+f"(d[OFF+33]), "+f"(d[OFF+34]), "+f"(d[OFF+35]), "+f"(d[OFF+36]), "+f"(d[OFF+37]), "+f"(d[OFF+38]), "+f"(d[OFF+39]), "+f"(d[OFF+40]), "+f"(d[OFF+41]), "+f"(d[OFF+42]), "+f"(d[OFF+43]), "+f"(d[OFF+44]), "+f"(d[OFF+45]), "+f"(d[OFF+46]), "+f"(d[OFF+47]), "+f"(d[OFF+48]), "+f"(d[OFF+49]), "+f"(d[OFF+50]), "+f"(d[OFF+51]), "+f"(d[OFF+52]), "+f"(d[OFF+53]), "+f"(d[OFF+54]), "+f"(d[OFF+55]), "+f"(d[OFF+56]), "+f"(d[OFF+57]), "+f"(d[OFF+58]), "+f"(d[OFF+59]), "+f"(d[OFF+60]), "+f"(d[OFF+61]), "+f"(d[OFF+62]), "+f"(d[OFF+63])
    : "r"(a0), "r"(a1), "r"(a2), "r"(a3), "l"(db), "r"(scale_d), "n"(TB));
}
template<int TB, int OFF, int NT>
__device__ __forceinline__ void wgmma_rs_n64(float (&d)[NT], uint32_t a0, uint32_t a1, uint32_t a2, uint32_t a3, uint64_t db, int scale_d) {
  asm volatile("{\n.reg .pred p;\nsetp.ne.b32 p, %37, 0;\n"
    "wgmma.mma_async.sync.aligned.m64n64k16.f32.bf16.bf16 {%0, %1, %2, %3, %4, %5, %6, %7, %8, %9, %10, %11, %12, %13, %14, %15, %16, %17, %18, %19, %20, %21, %22, %23, %24, %25, %26, %27, %28, %29, %30, %31}, {%32, %33, %34, %35}, %36, p, 1, 1, %38;\n}\n"
    : "+f"(d[OFF+0]), "+f"(d[OFF+1]), "+f"(d[OFF+2]), "+f"(d[OFF+3]), "+f"(d[OFF+4]), "+f"(d[OFF+5]), "+f"(d[OFF+6]), "+f"(d[OFF+7]), "+f"(d[OFF+8]), "+f"(d[OFF+9]), "+f"(d[OFF+10]), "+f"(d[OFF+11]), "+f"(d[OFF+12]), "+f"(d[OFF+13]), "+f"(d[OFF+14]), "+f"(d[OFF+15]), "+f"(d[OFF+16]), "+f"(d[OFF+17]), "+f"(d[OFF+18]), "+f"(d[OFF+19]), "+f"(d[OFF+20]), "+f"(d[OFF+21]), "+f"(d[OFF+22]), "+f"(d[OFF+23]), "+f"(d[OFF+24]), "+f"(d[OFF+25]), "+f"(d[OFF+26]), "+f"(d[OFF+27]), "+f"(d[OFF+28]), "+f"(d[OFF+29]), "+f"(d[OFF+30]), "+f"(d[OFF+31])
    : "r"(a0), "r"(a1), "r"(a2), "r"(a3), "l"(db), "r"(scale_d), "n"(TB));
}

__device__ __forceinline__ void wait_flag(const unsigned int* f, uint32_t target) {
  uint32_t v;
#pragma unroll 1
  for (uint32_t spins = 0; spins < (1u << 22); spins++) {
    asm volatile("ld.acquire.gpu.global.u32 %0, [%1];" : "=r"(v) : "l"(f) : "memory");
    if (v >= target) break;
    __nanosleep(100);
  }
}
__device__ __forceinline__ uint32_t lds32(uint32_t a) {
  uint32_t v;
  asm volatile("ld.shared.u32 %0, [%1];" : "=r"(v) : "r"(a) : "memory");
  return v;
}
__device__ __forceinline__ float gate_row(int row, int lane, const bf16* __restrict__ x, const bf16* __restrict__ gate_w) {
  const uint32_t* xr = reinterpret_cast<const uint32_t*>(x + (size_t)row * DM);
  const uint32_t* gw2 = reinterpret_cast<const uint32_t*>(gate_w);
  float gs = 0.f;
#pragma unroll
  for (int i = 0; i < 9; i++) {
    const uint32_t a = __ldg(xr + lane + 32 * i), b = __ldg(gw2 + lane + 32 * i);
    gs = fmaf(bf_lo(a), bf_lo(b), gs);
    gs = fmaf(bf_hi(a), bf_hi(b), gs);
  }
#pragma unroll
  for (int o = 16; o; o >>= 1) gs += __shfl_xor_sync(0xffffffffu, gs, o);
  const float g = 1.f / (1.f + __expf(-gs));
  if (lane == 0) g_gate[row] = g;
  return g;
}
constexpr uint32_t LQ = 36864, LV = 55296;
__device__ __forceinline__ void mma16(float (&c)[4], uint32_t a0, uint32_t a1, uint32_t a2, uint32_t a3, uint32_t b0, uint32_t b1) {
  asm("mma.sync.aligned.m16n8k16.row.col.f32.bf16.bf16.f32 {%0, %1, %2, %3}, {%4, %5, %6, %7}, {%8, %9}, {%0, %1, %2, %3};"
      : "+f"(c[0]), "+f"(c[1]), "+f"(c[2]), "+f"(c[3]) : "r"(a0), "r"(a1), "r"(a2), "r"(a3), "r"(b0), "r"(b1));
}
__device__ __forceinline__ void mma8(float (&c)[4], uint32_t a0, uint32_t a1, uint32_t b0) {
  asm("mma.sync.aligned.m16n8k8.row.col.f32.bf16.bf16.f32 {%0, %1, %2, %3}, {%4, %5}, {%6}, {%0, %1, %2, %3};"
      : "+f"(c[0]), "+f"(c[1]), "+f"(c[2]), "+f"(c[3]) : "r"(a0), "r"(a1), "r"(b0));
}
__device__ __forceinline__ void local_attn(int lr0, int warp_g, uint32_t sL, uint32_t bL, uint32_t bL2, int lane, float g0, float g1) {
  const float scale_l2 = 0.23570226039551584f * 1.4426950408889634f;
  const int g = lane >> 2, t = lane & 3;
  const bool lo0 = 2 * t > g, lo1 = 2 * t + 1 > g;
  const uint32_t mlo = (lo0 ? 0xFFFFu : 0u) | (lo1 ? 0xFFFF0000u : 0u);
  const bool ok0 = lr0 > 0 || !lo0, ok1 = lr0 > 0 || !lo1;
  uint32_t ad[9], k[9][4], qf[9][2], pe[4], po[4];
#pragma unroll
  for (int c = 0; c < 9; c++) {
    const uint32_t ch = warp_g * 9 + c;
    ad[c] = sL + (lane >> 4) * 18432 + (lane & 15) * 128 + ((ch >> 3) << 11) + (((ch ^ lane) & 7) << 4);
  }
  mbar_wait(bL, 0);
  if (warp_g == 0) TS(1, 6);
#pragma unroll
  for (int c = 0; c < 9; c++) {
    asm volatile("ldmatrix.sync.aligned.m8n8.x2.shared.b16 {%0, %1}, [%2];" : "=r"(qf[c][0]), "=r"(qf[c][1]) : "r"(ad[c] + LQ) : "memory");
    ldsm_x4(k[c][0], k[c][1], k[c][2], k[c][3], ad[c]);
  }
#pragma unroll
  for (int i = 0; i < 4; i++) {
    const uint32_t q0 = (t >= i) ? qf[2 * i][0] : 0u, q1 = (t >= i) ? qf[2 * i][1] : 0u;
    const uint32_t q4 = (t <= i) ? qf[2 * i + 2][0] : 0u, q5 = (t <= i) ? qf[2 * i + 2][1] : 0u;
    float c[4][4];
#pragma unroll
    for (int T = 0; T < 4; T++) {
#pragma unroll
      for (int j = 0; j < 4; j++) c[T][j] = 0.f;
      mma16(c[T], q0, q1, qf[2 * i + 1][0], qf[2 * i + 1][1], k[2 * i][T], k[2 * i + 1][T]);
      mma8(c[T], q4, q5, k[2 * i + 2][T]);
    }
    const float e0 = ok0 ? (lo0 ? c[0][0] : c[1][0]) : -INFINITY, e1 = ok1 ? (lo1 ? c[0][1] : c[1][1]) : -INFINITY;
    const float o0 = ok0 ? (lo0 ? c[2][2] : c[3][2]) : -INFINITY, o1 = ok1 ? (lo1 ? c[2][3] : c[3][3]) : -INFINITY;
    float me = fmaxf(e0, e1), mo = fmaxf(o0, o1);
    me = fmaxf(me, __shfl_xor_sync(0xffffffffu, me, 1));
    mo = fmaxf(mo, __shfl_xor_sync(0xffffffffu, mo, 1));
    me = fmaxf(me, __shfl_xor_sync(0xffffffffu, me, 2)) * scale_l2;
    mo = fmaxf(mo, __shfl_xor_sync(0xffffffffu, mo, 2)) * scale_l2;
    const float w0 = ex2(fmaf(e0, scale_l2, -me)), w1 = ex2(fmaf(e1, scale_l2, -me));
    const float w2 = ex2(fmaf(o0, scale_l2, -mo)), w3 = ex2(fmaf(o1, scale_l2, -mo));
    float se = w0 + w1, so = w2 + w3;
    se += __shfl_xor_sync(0xffffffffu, se, 1);
    so += __shfl_xor_sync(0xffffffffu, so, 1);
    se += __shfl_xor_sync(0xffffffffu, se, 2);
    so += __shfl_xor_sync(0xffffffffu, so, 2);
    asm("rcp.approx.ftz.f32 %0, %0;" : "+f"(se));
    asm("rcp.approx.ftz.f32 %0, %0;" : "+f"(so));
    se *= g0;
    so *= g1;
    pe[i] = pack_bf16(w0 * se, w1 * se);
    po[i] = pack_bf16(w2 * so, w3 * so);
  }
  if (warp_g == 0) TS(0, 4);
  mbar_wait(bL2, 0);
  if (warp_g == 0) TS(0, 5);
#pragma unroll
  for (int c = 0; c < 9; c++)
    asm volatile("ldmatrix.sync.aligned.m8n8.x4.trans.shared.b16 {%0, %1, %2, %3}, [%4];"
                 : "=r"(k[c][0]), "=r"(k[c][1]), "=r"(k[c][2]), "=r"(k[c][3]) : "r"(ad[c] + LV) : "memory");
#pragma unroll
  for (int i = 0; i < 4; i++) {
#pragma unroll
    for (int n = 0; n < 3; n++) {
      float c[4] = {0.f, 0.f, 0.f, 0.f};
      mma16(c, pe[i] & mlo, 0u, pe[i] & ~mlo, 0u, k[2 * i + n][0], k[2 * i + n][1]);
      mma16(c, 0u, po[i] & mlo, 0u, po[i] & ~mlo, k[2 * i + n][2], k[2 * i + n][3]);
      const uint32_t r0 = pack_bf16(c[0], c[1]), r1 = pack_bf16(c[2], c[3]);
      const bool keep = (n == 0) && (t < i);
      qf[2 * i + n][0] = keep ? qf[2 * i + n][0] : r0;
      qf[2 * i + n][1] = keep ? qf[2 * i + n][1] : r1;
    }
  }
#pragma unroll
  for (int c = 0; c < 9; c++)
    asm volatile("stmatrix.sync.aligned.m8n8.x2.shared.b16 [%0], {%1, %2};" ::"r"(ad[c] + LQ), "r"(qf[c][0]), "r"(qf[c][1]) : "memory");
  asm volatile("fence.proxy.async.shared::cta;" ::: "memory");
}
__device__ __forceinline__ void tma4d(uint32_t dst, const CUtensorMap* m, uint32_t bar, int c1, int c2, int c3) {
  asm volatile("cp.async.bulk.tensor.4d.shared::cluster.global.mbarrier::complete_tx::bytes [%0], [%1, {%3, %4, %5, %6}], [%2];" ::"r"(dst),
               "l"(m), "r"(bar), "r"(0), "r"(c1), "r"(c2), "r"(c3) : "memory");
}

#define K1_NST 6
constexpr int K1_BST = K1_NST;
#define MAXJ 11
constexpr int K1_MAXJOBS = MAXJ;
constexpr uint32_t K1_FLAG_TARGET = 7;
constexpr uint32_t RDY_TARGET = 48;
constexpr uint32_t GATE_TARGET = 128 * 3;
struct alignas(64) Params {
  CUtensorMap tmA[2];
  CUtensorMap tmW[4];
  CUtensorMap tmQ, tmK, tmV;
  CUtensorMap tmL[3];
  CUtensorMap tmC, tmO[2], tmOt[2];
  uint16_t jobs[NCLUSTER][K1_MAXJOBS + 1];
  uint8_t order[256];
  uint8_t unit[64][8];
};

struct K1State {
  uint32_t bs, bph, aph;
  bf16* pp;
  int pld8;
  int png;
  int tn;
  int wsel;
};
__device__ __forceinline__ void k1_flag(const K1State& st, int lane, uint32_t bS) {
  if (st.png) {
    __syncwarp();
    if (lane == 0) mbar_arrive(bS);
  }
}

__device__ __forceinline__ void scale_q4(uint32_t* v) {
#pragma unroll
  for (int i = 0; i < 4; i++)
    asm volatile("{\n.reg .b32 t;\nmul.rn.bf16x2 t, %0, %2;\nfma.rn.bf16x2 %0, %0, %1, t;\n}" : "+r"(v[i]) : "r"(0x3E033E03u), "r"(0xB9D8B9D8u));
}
__device__ __forceinline__ void k1_first(const K1State& st, uint32_t job, uint32_t bAf, uint32_t bBf) {
  if (job & 3) {
    if ((job >> 14) & 1) mbar_wait(bAf, st.aph);
    mbar_wait(bBf + st.bs * 8, st.bph);
  }
}
__device__ __forceinline__ void k1_tile(float (&acc)[128], uint32_t (&pk)[64], K1State& st, uint32_t job, uint32_t njob, uint32_t sA, uint32_t sB,
                                        uint32_t bAf, uint32_t bAe, uint32_t bBf, uint32_t bBe, uint32_t bS, int wg, int warp, int lane, uint32_t rank) {
  const int a_sel = (job >> 2) & 1, mpair = (job >> 3) & 7, w_sel = (job >> 6) & 3, chunk0 = (job >> 8) & 63;
  const bool newA = (job >> 14) & 1, lastA = (job >> 15) & 1;
  const bool sig = (lane == 0) && (warp < 2);
  const bool siga = lastA && (lane == 0) && (warp == 2);
  const int KC = 8 + a_sel;
  uint32_t prev_bs = 0, a8_bs = 0;
#pragma unroll
  for (int kc = 0; kc < 9; kc++) {
    if (kc >= KC) break;
    uint32_t abase = sA + ((kc + 2) & 7) * 16384;
    if (kc == 8) {
      mbar_wait(bBf + st.bs * 8, st.bph);
      a8_bs = st.bs;
      abase = sB + st.bs * 16384;
      if (++st.bs == K1_BST) { st.bs = 0; st.bph ^= 1; }
    } else if (newA && kc > 0) {
      mbar_wait(bAf + kc * 8, st.aph);
    }
    const uint64_t da = make_desc(abase + wg * 8192, 16, 1024, 1);
#pragma unroll
    for (int ks = 0; ks < 2; ks++) {
      if (ks > 0 || kc > 0) mbar_wait(bBf + st.bs * 8, st.bph);
      const uint64_t db = make_desc(sB + st.bs * 16384, 2048, 1024, 1);
      wg_fence();
      wgmma_ss_n256<1, 0>(acc, da + (uint64_t)(ks * 4), db, (ks > 0) ? 1 : (kc > 0));
      wgmma_ss_n256<1, 0>(acc, da + (uint64_t)(ks * 4 + 2), db + (uint64_t)512, 1);
      wg_commit();
      const int PO = (kc < 8 ? kc : 0) * 8;
      wg_wait<1>();
      if (ks > 0 || kc > 0) {
        if (sig) mbar_arrive_cluster(bBe + prev_bs * 8, warp);
        if (ks == 0 && siga) mbar_arrive(bAe + (kc - 1) * 8);
      }
      if (kc < 8 && st.wsel >= 2) {
        if (st.wsel == 3) scale_q4(pk + PO + ks * 4);
        else quad_transpose(pk[PO + ks * 4], pk[PO + ks * 4 + 1], pk[PO + ks * 4 + 2], pk[PO + ks * 4 + 3], lane & 3);
      }
      if (kc < st.png) st_v4a(st.pp + kc * 32 + ks * st.pld8, pk[PO + ks * 4], pk[PO + ks * 4 + 1], pk[PO + ks * 4 + 2], pk[PO + ks * 4 + 3]);
      prev_bs = st.bs;
      if (++st.bs == K1_BST) { st.bs = 0; st.bph ^= 1; }
    }
  }
  if (newA) st.aph ^= 1;
  k1_flag(st, lane, bS);
  const bool isA = (w_sel == 2);
  bf16* out = (w_sel == 0) ? g_K : (w_sel == 1) ? g_V : isA ? g_QKVA : g_Q;
  const int ld = isA ? NQKVA : HDIM;
  const int row = mpair * 256 + rank * 128 + wg * 64 + warp * 16 + (lane >> 2);
  st.pp = out + (size_t)row * ld + chunk0 * 64 + (lane & 3) * 8;
  st.pld8 = 8 * ld;
  st.png = ((job & 3) + 1) * 2;
  st.wsel = w_sel;
  k1_first(st, njob, bAf, bBf);
  wg_wait<0>();
  fence_regs(acc);
  mbar_arrive_cluster_if(bBe + prev_bs * 8, warp & 1, sig);
  mbar_arrive_cluster_if(bBe + a8_bs * 8, warp & 1, sig && a_sel);
  mbar_arrive_if(bAe + 7 * 8, siga && !a_sel);
#pragma unroll
  for (int i = 0; i < 64; i++) {
    const int j = (i >> 3) * 16 + (i & 3) * 4 + ((i >> 2) & 1) * 2;
    pk[i] = pack_bf16(acc[j], acc[j + 1]);
  }
}

constexpr int K2_NST = 7;
constexpr uint32_t K2_END = 0x100;
#define PF_KC 7
#define FIRST_DRAW 3
#define PWAIT mbar_wait_ns<1000>
#define PVM 0x8A
#define W0 63
#define SPEC_HI 1.8446744073709552e19f
#define SPEC_LO 5.421010862427522e-20f
constexpr int K3_NST = 4;
__device__ __forceinline__ uint32_t k3_rot(uint32_t sv) { return (0x00E9u >> (2 * sv)) & 3; }
constexpr int K3_STAGE = 16384 + 32768 + 4096;
constexpr int SMEM_DATA = 7 * 32768;
constexpr int SMEM_BYTES = SMEM_DATA + 1024 + 768;

struct Cursor {
  uint32_t s, ph;
  __device__ __forceinline__ void next() {
    if (++s == K2_NST) { s = 0; ph ^= 1; }
  }
};

#define TURN_SYNC() bar_sync(mybar, 256)
#define TURN_ARRIVE() bar_arrive(otherbar, 256)
#define RELEASE_IF(cur, cond) mbar_arrive_cluster_if(bE + (cur).s * 8, warp & 1, sig && (cond))
#define RELEASE(cur) RELEASE_IF(cur, true)
#define ISSUE_PV(cur, first)                                                                                   \
  do {                                                                                                         \
    const uint64_t dv = make_desc(sbase + (cur).s * 32768, 16384, 1024, 1);                                    \
    _Pragma("unroll") for (int t = 0; t < 8; t++)                                                              \
        wgmma_rs_n128<1, 0>(O, P[4 * t], P[4 * t + 1], P[4 * t + 2], P[4 * t + 3], dv + (uint64_t)(t * 128), (t > 0) ? 1 : !(first)); \
  } while (0)
#define ISSUE_QK(cur)                                                                                          \
  do {                                                                                                         \
    const uint64_t dk = make_desc(sbase + (cur).s * 32768, 16, 1024, 1);                                       \
    _Pragma("unroll") for (int t = 0; t < 8; t++)                                                              \
        wgmma_rs_n128<0, 0>(S, Q[4 * t], Q[4 * t + 1], Q[4 * t + 2], Q[4 * t + 3], dk + (uint64_t)((t >> 2) * 1024 + (t & 3) * 2), t > 0); \
  } while (0)
#define EXPB(T)                                                                                                \
  do {                                                                                                         \
    _Pragma("unroll") for (int i = 4 * T; i < 4 * T + 4; i++) asm volatile("" : "+r"(P[i])::"memory");        \
    _Pragma("unroll") for (int jj = 2 * T; jj < 2 * T + 2; jj++) {                                             \
      const float e0 = ex2(S[jj * 4 + 0]), e1 = ex2(S[jj * 4 + 1]), e2 = ex2(S[jj * 4 + 2]), e3 = ex2(S[jj * 4 + 3]); \
      s0 += e0 + e1;                                                                                           \
      s1 += e2 + e3;                                                                                           \
      P[jj * 2 + 0] = pack_bf16(e0, e1);                                                                       \
      P[jj * 2 + 1] = pack_bf16(e2, e3);                                                                       \
    }                                                                                                          \
  } while (0)
#define EXPC(T)                                                                                                \
  do {                                                                                                         \
    if (T > 0 && ((PVM >> (T - 1)) & 1)) {                                                                     \
      anchor((T & 2) ? s0 : s1, never);                                                                        \
      wg_wait<__builtin_popcount(PVM >> T) - 1>();                                                             \
      if ((PVM >> T) == (128 >> T)) { fence_regs(O); RELEASE(cv); }                                            \
    }                                                                                                          \
    EXPB(T);                                                                                                   \
  } while (0)
#define MASK(G, g)                                                                                             \
  do {                                                                                                         \
    if ((g) * 8 > d) S[(G) * 4 + 0] = -INFINITY;                                                               \
    if ((g) * 8 + 1 > d) S[(G) * 4 + 1] = -INFINITY;                                                           \
    if ((g) * 8 - 8 > d) S[(G) * 4 + 2] = -INFINITY;                                                           \
    if ((g) * 8 - 7 > d) S[(G) * 4 + 3] = -INFINITY;                                                           \
  } while (0)
#define STORE_O(G)                                                                                             \
  do {                                                                                                         \
    st_v4(g_ctx + eoff + (G) * 32, pack_bf16(O[(G) * 16 + 0] * f0, O[(G) * 16 + 1] * f0), pack_bf16(O[(G) * 16 + 4] * f0, O[(G) * 16 + 5] * f0), \
          pack_bf16(O[(G) * 16 + 8] * f0, O[(G) * 16 + 9] * f0), pack_bf16(O[(G) * 16 + 12] * f0, O[(G) * 16 + 13] * f0)); \
    st_v4(g_ctx + eoff + 8 * KCAT + (G) * 32, pack_bf16(O[(G) * 16 + 2] * f1, O[(G) * 16 + 3] * f1), pack_bf16(O[(G) * 16 + 6] * f1, O[(G) * 16 + 7] * f1), \
          pack_bf16(O[(G) * 16 + 10] * f1, O[(G) * 16 + 11] * f1), pack_bf16(O[(G) * 16 + 14] * f1, O[(G) * 16 + 15] * f1)); \
  } while (0)

#define FLUSH()                                                                                                \
  do {                                                                                                         \
    _Pragma("unroll") for (int G = 0; G < 8; G++) {                                                            \
      st_v4a(st.pp + G * 32, pk[G * 8], pk[G * 8 + 1], pk[G * 8 + 2], pk[G * 8 + 3]);                          \
      st_v4a(st.pp + G * 32 + 8 * HDIM, pk[G * 8 + 4], pk[G * 8 + 5], pk[G * 8 + 6], pk[G * 8 + 7]);           \
    }                                                                                                          \
    k1_flag(st, lane, bS);                                                                                     \
  } while (0)

__global__ void __cluster_dims__(2, 1, 1) __launch_bounds__(384, 1)
fused_kernel(const __grid_constant__ Params p, const bf16* __restrict__ x, const bf16* __restrict__ gate_w, bf16* __restrict__ out) {
  extern __shared__ uint8_t smem_raw[];
  const uint32_t sbase = (smem_u32(smem_raw) + 1023) & ~1023u;
  const uint32_t sB = sbase, sA = sbase + K1_BST * 16384, sBar = sbase + SMEM_DATA;
  const uint32_t bAf = sBar, bAe = sBar + 64, bBf = sBar + 128, bBe = sBar + 176, bL = sBar + 224, bS = sBar + 232, bL2 = sBar + 240, sL = sA + 32768;
  const uint32_t bF = sBar + 256, bE = sBar + 320, bT = sBar + 384, sTick = sBar + 400, sItem = sBar + 416, bS2 = sBar + 448, bR = sBar + 456, bLast = sBar + 464, bH = sBar + 472, bT0 = sBar + 480;
  const uint32_t b3F = sBar + 512, b3E = sBar + 544, sGate = sBar + 576;
  const int tid = threadIdx.x, warp_g = __shfl_sync(0xffffffffu, tid >> 5, 0), lane = tid & 31;
  const uint32_t rank = cluster_rank();
  const int cl = blockIdx.x >> 1;
  TSM(0);
  if (tid == 0) {
    for (int i = 0; i < 8; i++) { mbar_init(bAf + i * 8, 1); mbar_init(bAe + i * 8, 2); }
    for (int i = 0; i < K1_BST; i++) { mbar_init(bBf + i * 8, 1); mbar_init(bBe + i * 8, 4); }
    mbar_init(bL, 1);
    mbar_init(bL2, 1);
    mbar_init(bR, 1);
    mbar_init(bLast, 1);
    mbar_init(bH, 4);
    mbar_init(bT0, 1);
    mbar_init(bS, 8);
    for (int i = 0; i < K2_NST; i++) { mbar_init(bF + i * 8, 1); mbar_init(bE + i * 8, 4); }
    mbar_init(bT, 1); mbar_init(bT + 8, 1);
    mbar_init(bS2, 8);
    for (int i = 0; i < K3_NST; i++) { mbar_init(b3F + i * 8, 1); mbar_init(b3E + i * 8, 4); }
    asm volatile("fence.mbarrier_init.release.cluster;" ::: "memory");
  }
  __syncwarp();
  if (warp_g != 8) cluster_sync();
  const int lr0 = blockIdx.x * 16;

  if (warp_g >= 8) {
    reg_dealloc<40>();
    if (warp_g == 8) {
      {
        const uint32_t job = p.jobs[cl][0];
        if (lane == 0) { prefetch_tmap(&p.tmA[(job >> 2) & 1]); prefetch_tmap(&p.tmW[(job >> 6) & 3]); }
        __syncwarp();
        cluster_sync();
      }
      if (elect_one()) {
        uint32_t bs = 0, bph = 1, aph = 1;
#pragma unroll 1
        for (int ji = 0; ji < K1_MAXJOBS; ji++) {
          const uint32_t job = p.jobs[cl][ji];
          if (!(job & 3)) break;
          const int a_sel = (job >> 2) & 1, mpair = (job >> 3) & 7, chunk0 = (job >> 8) & 63;
          const bool newA = (job >> 14) & 1;
          const int KC = a_sel ? 9 : 8;
          const uint32_t halfbytes = 8192;
          const bool lastjob = (ji + 1 == K1_MAXJOBS) || !(p.jobs[cl][ji + 1] & 3);
          const CUtensorMap* tw = &p.tmW[(job >> 6) & 3];
          {
            const uint32_t njob = (ji + 1 < K1_MAXJOBS) ? p.jobs[cl][ji + 1] : 0;
            if (!(njob & 3) && !newA) mbar_arrive(bLast);
          }
#pragma unroll 1
          for (int kc = 0; kc < KC; kc++) {
            if (kc == ((ji == 0) ? PF_KC : 0) && !lastjob) {
              const uint32_t njob = p.jobs[cl][ji + 1];
              const int nst = ((njob >> 2) & 1) ? 18 : 16;
#pragma unroll 1
              for (int t = (cl < 64) ? (cl & 7) : 0; t < nst; t += (cl < 64) ? 8 : 1)
                tma_pf3d(&p.tmW[(njob >> 6) & 3], 0, t * 32 + rank * 16, (njob >> 8) & 63);
            }
            if (kc == 8) {
              PWAIT(bBe + bs * 8, bph);
              mbar_expect(bBf + bs * 8, 16384);
              tma2d(sB + bs * 16384, &p.tmA[1], bBf + bs * 8, 512, mpair * 256 + rank * 128);
              if (++bs == K1_BST) { bs = 0; bph ^= 1; }
            } else if (newA) {
              PWAIT(bAe + kc * 8, aph);
              mbar_expect(bAf + kc * 8, 16384);
              tma2d(sA + ((kc + 2) & 7) * 16384, &p.tmA[a_sel], bAf + kc * 8, kc * 64, mpair * 256 + rank * 128);
              if (kc == 7 && lastjob) mbar_arrive(bLast);
            }
#pragma unroll 1
            for (int kk = 0; kk < 2; kk++) {
              PWAIT(bBe + bs * 8, bph);
              mbar_expect(bBf + bs * 8, 2 * halfbytes);
              tma3d_mc(sB + bs * 16384 + rank * halfbytes, tw, bBf + bs * 8, 0, kc * 64 + kk * 32 + rank * 16, chunk0, 3);
              if (++bs == K1_BST) { bs = 0; bph ^= 1; }
            }
          }
          if (newA) aph ^= 1;
        }
        Cursor c{0, 0};
        int pcol = 0;
        PWAIT(bR, 0);
        uint32_t tick = lds32(sTick + 8), seen = 1u << (p.order[tick] >> 4);
        asm volatile("fence.proxy.async.global;" ::: "memory");
#pragma unroll 1
        for (int it = 0;; it++) {
          const uint32_t item = (tick < 256) ? p.order[tick] : (K2_END | min(tick - 256, 255u));
          asm volatile("st.shared.u32 [%0], %1;" ::"r"(sItem + (it & 7) * 4), "r"(item) : "memory");
          if (item >= K2_END) break;
          const int h = item >> 3, j = item & 7;
          const int blk = 2 * j + (int)(rank ^ (it & 1));
          const int col = h * 128 + rank * 64;
          const int nb = 2 * j + 2;
          if (!((seen >> (h >> 1)) & 1)) {
            wait_flag(&g_sync[F_HP + (h >> 1)], RDY_TARGET);
            asm volatile("fence.proxy.async.global;" ::: "memory");
            seen |= 1u << (h >> 1);
          }
          PWAIT(bE + c.s * 8, c.ph);
          mbar_expect(bF + c.s * 8, 32768);
          tma2d(sbase + c.s * 32768, &p.tmQ, bF + c.s * 8, h * 128, blk * 128);
          tma2d(sbase + c.s * 32768 + 16384, &p.tmQ, bF + c.s * 8, h * 128 + 64, blk * 128);
          c.next();
#pragma unroll 1
          for (int n = nb - 1; n >= 0; n--) {
            if (n == 0 && rank == 0) tick = atomicAdd(&g_sync[F_TICK], 1u);
            PWAIT(bE + c.s * 8, c.ph);
            mbar_expect(bF + c.s * 8, 32768);
            tma2d_mc(sbase + c.s * 32768 + rank * 16384, &p.tmK, bF + c.s * 8, col, n * 128, 3);
            c.next();
            if (n < nb - 1 || it > 0) {
              PWAIT(bE + c.s * 8, c.ph);
              mbar_expect(bF + c.s * 8, 32768);
              tma2d_mc(sbase + c.s * 32768 + rank * 16384, &p.tmV, bF + c.s * 8, (n < nb - 1) ? col : pcol, (n < nb - 1) ? (n + 1) * 128 : 0, 3);
              c.next();
            }
          }
          pcol = col;
          if (rank == 0) {
            asm volatile(
                "{\n.reg .b32 a, b;\nmapa.shared::cluster.u32 a, %0, 1;\nmapa.shared::cluster.u32 b, %1, 1;\n"
                "st.async.shared::cluster.mbarrier::complete_tx::bytes.u32 [a], %2, [b];\n}" ::"r"(sTick + (it & 1) * 4),
                "r"(bT + (it & 1) * 8), "r"(tick) : "memory");
          } else {
            mbar_expect(bT + (it & 1) * 8, 4);
            PWAIT(bT + (it & 1) * 8, (it >> 1) & 1);
            tick = lds32(sTick + (it & 1) * 4);
          }
        }
        PWAIT(bE + c.s * 8, c.ph);
        mbar_expect(bF + c.s * 8, 32768);
        tma2d_mc(sbase + c.s * 32768 + rank * 16384, &p.tmV, bF + c.s * 8, pcol, 0, 3);
        const uint32_t unit = tick - 256;
        if (unit < 64) {
          const int mblk = (7 - (p.unit[unit][0] >> 1)) * 2 + rank, nhalf = p.unit[unit][0] & 1;
          const uint32_t rot = k3_rot(c.s), nfree = ((0x1Au >> c.s) & 1) ? 2 : 3;
#pragma unroll 1
          for (int i = 0; i < K2_NST - 1; i++) {
            c.next();
            PWAIT(bE + c.s * 8, c.ph);
          }
          uint32_t have = 0;
#pragma unroll 1
          for (uint32_t idx = 0; idx < p.unit[unit][2]; idx++) {
            const int kk = p.unit[unit][3] + idx + ((idx >= p.unit[unit][4]) ? p.unit[unit][5] : 0);
            const uint32_t s = (rot + idx) & 3;
            if (idx >= nfree) PWAIT((idx < 4) ? bH : b3E + s * 8, (idx < 4) ? 0 : (~idx >> 2) & 1);
            mbar_expect(b3F + s * 8, K3_STAGE);
            const uint32_t st = sbase + s * K3_STAGE;
            const int sel = (kk < 9), k = sel ? kk : kk - 9, kr = k * 64 + rank * 32;
            tma3d_mc(st + 16384 + rank * 16384, &p.tmO[sel], b3F + s * 8, 0, kr, nhalf * 4, 3);
            tma2d_mc(st + 49152 + rank * 2048, &p.tmOt[sel], b3F + s * 8, 512 + nhalf * 32, kr, 3);
            if (sel && idx == 0) {
              wait_flag(&g_sync[F_OA + mblk], 8);
              asm volatile("fence.proxy.async.global;" ::: "memory");
            }
            if (!sel && !((have >> (k >> 1)) & 1)) {
#pragma unroll 1
              for (uint32_t spins = 0; spins < (1u << 22); spins++) {
                asm volatile("ld.acquire.gpu.global.u32 %0, [%1];" : "=r"(have) : "l"(&g_sync[F_CTX + mblk]) : "memory");
                if ((have >> (k >> 1)) & 1) break;
                __nanosleep(100);
              }
              asm volatile("fence.proxy.async.global;" ::: "memory");
            }
            tma2d(st, &p.tmC, b3F + s * 8, (sel ? 64 + k : k) * 64, mblk * 128);
          }
        }
      }
    }
    __syncwarp();
    if (warp_g == 8) {
      uint32_t v = 0;
      if (lane == 0) {
        __threadfence();
        v = atomicAdd(&g_sync[F_DONE], 1u);
      }
      if (__shfl_sync(0xffffffffu, v, 0) == 2 * NCLUSTER - 1) {
        reinterpret_cast<uint4*>(g_sync)[lane] = make_uint4(0, 0, 0, 0);
        if (lane == 0) g_sync[F_EPOCH] = lds32(sGate + 64) + 1;
      }
    }
    asm volatile("" ::: "memory");
    if (__shfl_sync(0xffffffffu, warp_g, 0) != 8) {
      if (lr0 < S_LEN) {
#pragma unroll 1
        for (int i = warp_g - 9; i < 16; i += 3) {
          const float g = gate_row(lr0 + i, lane, x, gate_w);
          if (lane == 0) asm volatile("st.shared.f32 [%0], %1;" ::"r"(sGate + i * 4), "f"(g) : "memory");
        }
        bar_arrive(3, 256 + 96);
        if (lane == 0) {
          __threadfence();
          atomicAdd(&g_sync[F_GATE], 1u);
        }
      }
      uint32_t aph = 1;
#pragma unroll 1
      for (int ji = 0; ji < K1_MAXJOBS; ji++) aph ^= (p.jobs[cl][ji] >> 14) & 1;
      if (warp_g == 9 && lane == 0) {
#pragma unroll 1
        for (int ji = 0; ji < K1_MAXJOBS; ji++) {
          const uint32_t job = p.jobs[cl][ji];
          if (!(job & 3)) break;
          PWAIT(bS, ji & 1);
          __threadfence();
          atomicAdd(&g_sync[(((job >> 6) & 3) == 2) ? (F_QKVA + ((job >> 3) & 7) * 2 + rank) : (F_HP + ((job >> 10) & 15))], 1u);
        }
#pragma unroll 1
        for (int it = 0;; it++) {
          PWAIT(bS2, it & 1);
          const uint32_t item = lds32(sItem + (it & 7) * 4), nxt = lds32(sItem + ((it + 1) & 7) * 4);
          __threadfence();
          atomicOr(&g_sync[F_CTX + (item & 7) * 2 + (rank ^ (it & 1))], 1u << (item >> 3));
          if (nxt >= K2_END) break;
        }
      } else if (warp_g == 11) {
        if (lane == 0) {
          prefetch_tmap(&p.tmQ); prefetch_tmap(&p.tmK); prefetch_tmap(&p.tmV);
          asm volatile("st.shared.u32 [%0], %1;" ::"r"(sGate + 64), "r"(__ldcg(&g_sync[F_EPOCH])) : "memory");
          wait_flag(&g_sync[F_GATE], GATE_TARGET);
          uint32_t tick;
          if (rank == 0) {
            PWAIT(bLast, 0);
            PWAIT(bAe + FIRST_DRAW * 8, aph);
            tick = atomicAdd(&g_sync[F_TICK], 1u);
            asm volatile("st.shared.u32 [%0], %1;" ::"r"(sTick + 8), "r"(tick) : "memory");
            asm volatile(
                "{\n.reg .b32 a, b;\nmapa.shared::cluster.u32 a, %0, 1;\nmapa.shared::cluster.u32 b, %1, 1;\n"
                "st.async.shared::cluster.mbarrier::complete_tx::bytes.u32 [a], %2, [b];\n}" ::"r"(sTick + 8), "r"(bT0), "r"(tick) : "memory");
          } else {
            mbar_expect(bT0, 4);
            PWAIT(bT0, 0);
            tick = lds32(sTick + 8);
          }
          wait_flag(&g_sync[F_HP + (p.order[tick] >> 4)], RDY_TARGET);
          mbar_arrive(bR);
        }
      } else if (warp_g == 10) {
        if (lr0 < S_LEN && lane == 0) {
          prefetch_tmap(&p.tmL[0]); prefetch_tmap(&p.tmL[1]); prefetch_tmap(&p.tmL[2]);
          wait_flag(&g_sync[F_QKVA + (lr0 >> 7)], K1_FLAG_TARGET);
          wait_flag(&g_sync[F_QKVA + (max(lr0 - 16, 0) >> 7)], K1_FLAG_TARGET);
          asm volatile("fence.proxy.async.global;" ::: "memory");
          PWAIT(bLast, 0);
#pragma unroll 1
          for (int kc = 0; kc < 6; kc++) {
            PWAIT(bAe + kc * 8, aph);
            if (kc == 3) {
              mbar_expect(bL, LV);
              tma4d(sL, &p.tmL[0], bL, lr0 / 2 - 8, 9, 0);
              tma4d(sL + LQ, &p.tmL[1], bL, lr0 / 2, 0, 0);
            }
          }
          mbar_expect(bL2, LQ);
          tma4d(sL + LV, &p.tmL[0], bL2, lr0 / 2 - 8, 18, 0);
        }
        __syncwarp();
        bar_sync(5, 256 + 32);
        if (lr0 < S_LEN && lane == 0) {
          asm volatile("cp.async.bulk.tensor.4d.global.shared::cta.bulk_group [%0, {%2, %3, %2, %2}], [%1];" ::"l"(&p.tmL[2]), "r"(sL + LQ), "r"(0), "r"(lr0 / 2) : "memory");
          asm volatile("cp.async.bulk.commit_group;" ::: "memory");
          asm volatile("cp.async.bulk.wait_group.read 0;" ::: "memory");
        }
        __syncwarp();
        if (lane < 12) mbar_arrive_cluster(bE + (4 + lane % 3) * 8, (lane / 3) & 1);
        if (lr0 < S_LEN && lane == 0) {
          asm volatile("cp.async.bulk.wait_group 0;" ::: "memory");
          asm volatile("fence.proxy.async.global;" ::: "memory");
          __threadfence();
          atomicAdd(&g_sync[F_OA + (lr0 >> 7)], 1u);
        }
      }
    }
    __syncwarp();
    cluster_sync();
  } else {
    reg_alloc<232>();
    const int wg = warp_g >> 2, warp = warp_g & 3, q = lane & 3;
    const bool sig = (lane == 0) && (warp < 2);
    {
      K1State st{0, 0, 0, nullptr, 0, 0, 0, 0};
      float acc[128];
      uint32_t pk[64];
      if (wg == 0) { TS(0, 0); TSC(0, 2); }
      uint32_t job = p.jobs[cl][0];
      k1_first(st, job, bAf, bBf);
      {
#pragma unroll 1
        for (int ji = 0; job & 3; ji++) {
          const uint32_t njob = p.jobs[cl][ji + 1];
          k1_tile(acc, pk, st, job, njob, sA, sB, bAf, bAe, bBf, bBe, bS, wg, warp, lane, rank);
          job = njob;
        }
      }
#pragma unroll
      for (int i = 0; i < 4; i++)
        mbar_arrive_cluster_if(bE + i * 8, warp & 1, sig);
      if (lr0 < S_LEN) bar_sync(3, 256 + 96);
      if (st.wsel == 3) {
#pragma unroll
        for (int G = 0; G < 16; G++) scale_q4(pk + G * 4);
      }
      FLUSH();
      if (wg == 0) { TS(0, 1); TSC(0, 3); }
      if (lr0 < S_LEN) {
        const float gate0 = __uint_as_float(lds32(sGate + (lane >> 2) * 8)), gate1 = __uint_as_float(lds32(sGate + (lane >> 2) * 8 + 4));
        local_attn(lr0, warp_g, sL, bL, bL2, lane, gate0, gate1);
      }
      bar_arrive(5, 256 + 32);
    }
    __syncwarp();
    uint32_t item, rot;
    {
      const int mybar = 1 + wg, otherbar = 2 - wg;
      const uint32_t never = blockIdx.y;
      float S[64], O[64];
      uint32_t P[32], Q[32];
      float m0 = 0.f, m1 = 0.f, l0 = 1.f, l1 = 1.f, gf0 = 0.f, gf1 = 0.f;
      uint32_t eoff = 0, prev_single = 0;
      Cursor c{0, 0};
      if (wg == 1) bar_arrive(1, 256);
      if (wg == 0) { TS(1, 0); TSC(1, 2); }
#pragma unroll 1
      for (int it = 0;; it++) {
        TB(0);
        const int hi = (int)(rank ^ (it & 1));
        Cursor cq = c, ck, cv, cs0, cs1;
        rot = k3_rot(c.s);
        c.next();
        ck = c; c.next();
        cs0 = ck; cs1 = ck; cv = ck;
        if (it > 0) { cv = c; c.next(); }
        if (!hi) {
          ck = c; c.next();
          cs1 = c; c.next();
        }
        mbar_wait(bF + cq.s * 8, cq.ph);
        TB(1);
        item = lds32(sItem + (it & 7) * 4);
        {
          const uint32_t qa = sbase + cq.s * 32768 + (wg * 64 + warp * 16 + (lane & 15)) * 128;
#pragma unroll
          for (int t = 0; t < 8; t++)
            ldsm_x4(Q[4 * t], Q[4 * t + 1], Q[4 * t + 2], Q[4 * t + 3], qa + (t >> 2) * 16384 + ((((t & 3) * 2 + (lane >> 4)) ^ (lane & 7)) << 4));
        }
        const uint32_t rdy = mbar_test(bF + ck.s * 8, ck.ph) & mbar_test(bF + cv.s * 8, cv.ph);
        l0 += __shfl_xor_sync(0xffffffffu, l0, 1);
        l1 += __shfl_xor_sync(0xffffffffu, l1, 1);
        l0 += __shfl_xor_sync(0xffffffffu, l0, 2);
        l1 += __shfl_xor_sync(0xffffffffu, l1, 2);
        const bool last = item >= K2_END;
        if (last) {
          cv = cq; ck = cq;
        } else if (!rdy) {
          mbar_wait2(bF + ck.s * 8, ck.ph, bF + cv.s * 8, cv.ph);
        }
        TB(2);
        TURN_SYNC();
        TB(3);
        TRC(last ? 2 : 1);
        if (it > 0) {
          wg_fence();
          ISSUE_PV(cv, prev_single);
          wg_commit();
        } else {
          wg_fence();
          wg_commit();
        }
        wg_fence();
        ISSUE_QK(ck);
        wg_commit();
        if (!(last && wg == 1)) TURN_ARRIVE();
        RELEASE_IF(cq, !last);
        TB(4);
        asm volatile("" : "+f"(gf0), "+f"(gf1), "+f"(l0), "+f"(l1));
        const float f0 = __fdividef(1.f - gf0, l0), f1 = __fdividef(1.f - gf1, l1);
        wg_wait<1>();
        fence_regs(O);
        fence_regs(P);
        TB(5);
        if (it > 0) {
          RELEASE_IF(cv, !last);
          mbar_arrive_cluster_if(bH, warp & 1, sig && last);
          STORE_O(0); STORE_O(1); STORE_O(2); STORE_O(3);
          __syncwarp();
          mbar_arrive_if(bS2, lane == 0);
        }
        TB(6);
        if (!last) {
          const int row = (2 * (item & 7) + hi) * 128 + wg * 64 + warp * 16 + (lane >> 2);
          eoff = row * KCAT + (item >> 3) * 128 + q * 8;
          asm volatile("ld.global.f32 %0, [%1];" : "=f"(gf0) : "l"(g_gate + row));
          asm volatile("ld.global.f32 %0, [%1];" : "=f"(gf1) : "l"(g_gate + row + 8));
          if (!hi) {
            mbar_wait2(bF + cs0.s * 8, cs0.ph, bF + cs1.s * 8, cs1.ph);
            RELEASE(cs0);
            RELEASE(cs1);
          }
        }
        TB(7);
        wg_wait<0>();
        fence_regs(S);
        TB(8);
        if (last) break;
        RELEASE(ck);
        const int nblk = 2 * (item & 7) + 1 + hi;
        prev_single = (nblk == 1);
        float s0 = 0.f, s1 = 0.f;
        l0 = 0.f; l1 = 0.f;
        m0 = 0.f; m1 = 0.f;
        bool shifted = false;
        {
          const int d = warp * 16 + (lane >> 2) - 2 * q;
          if (wg == 0) {
#pragma unroll
            for (int jj = 0; jj < 8; jj++) MASK(jj, jj);
            EXPB(0); EXPB(1); EXPB(2); EXPB(3);
#pragma unroll
            for (int i = 32; i < 64; i++) S[i] = -INFINITY;
#pragma unroll
            for (int i = 16; i < 32; i++) P[i] = 0;
          } else {
#pragma unroll
            for (int jj = 0; jj < 8; jj++) MASK(jj + 8, jj);
            EXPB(0); EXPB(1); EXPB(2); EXPB(3); EXPB(4); EXPB(5); EXPB(6); EXPB(7);
          }
        }
        float chk = (q == 0 && !(fminf(s0, s1) >= SPEC_LO)) ? INFINITY : s0 + s1;
        fence_regs(P);
        TB(9);
#pragma unroll 1
        for (int n = 1;; n++) {
          if (__any_sync(0xffffffffu, !(chk <= SPEC_HI))) {
            float mx0 = fmaxf(S[0], S[1]), mx1 = fmaxf(S[2], S[3]);
#pragma unroll
            for (int jj = 1; jj < 16; jj++) {
              mx0 = fmaxf(mx0, fmaxf(S[jj * 4 + 0], S[jj * 4 + 1]));
              mx1 = fmaxf(mx1, fmaxf(S[jj * 4 + 2], S[jj * 4 + 3]));
            }
            mx0 = fmaxf(mx0, __shfl_xor_sync(0xffffffffu, mx0, 1));
            mx1 = fmaxf(mx1, __shfl_xor_sync(0xffffffffu, mx1, 1));
            mx0 = fmaxf(mx0, __shfl_xor_sync(0xffffffffu, mx0, 2));
            mx1 = fmaxf(mx1, __shfl_xor_sync(0xffffffffu, mx1, 2));
            const float lo = (n == 1) ? -INFINITY : 0.f;
            mx0 = fmaxf(mx0, lo);
            mx1 = fmaxf(mx1, lo);
            m0 += mx0; m1 += mx1;
            shifted = true;
            const float sc0 = ex2(-fmaxf(mx0, 0.f)), sc1 = ex2(-fmaxf(mx1, 0.f));
            l0 *= sc0; l1 *= sc1;
            s0 = 0.f; s1 = 0.f;
#pragma unroll
            for (int jj = 0; jj < 16; jj++) {
              const float e0 = ex2(S[jj * 4 + 0] - mx0), e1 = ex2(S[jj * 4 + 1] - mx0), e2 = ex2(S[jj * 4 + 2] - mx1), e3 = ex2(S[jj * 4 + 3] - mx1);
              s0 += e0 + e1;
              s1 += e2 + e3;
              P[jj * 2 + 0] = pack_bf16(e0, e1);
              P[jj * 2 + 1] = pack_bf16(e2, e3);
              O[jj * 4 + 0] *= sc0;
              O[jj * 4 + 1] *= sc0;
              O[jj * 4 + 2] *= sc1;
              O[jj * 4 + 3] *= sc1;
            }
          }
          l0 += s0;
          l1 += s1;
          if (n >= nblk) break;
          ck = c; c.next();
          cv = c; c.next();
          mbar_wait(bF + ck.s * 8, ck.ph);
          mbar_wait(bF + cv.s * 8, cv.ph);
          TURN_SYNC();
          TRC(0);
          wg_fence();
          ISSUE_QK(ck);
          wg_commit();
          {
            const uint64_t dv = make_desc(sbase + cv.s * 32768, 16384, 1024, 1);
#pragma unroll
            for (int t = 0; t < 8; t++) {
              wgmma_rs_n128<1, 0>(O, P[4 * t], P[4 * t + 1], P[4 * t + 2], P[4 * t + 3], dv + (uint64_t)(t * 128), (t > 0) ? 1 : (n != 1));
              if ((PVM >> t) & 1) wg_commit();
            }
          }
          TURN_ARRIVE();
          s0 = 0.f; s1 = 0.f;
          wg_wait<__builtin_popcount(PVM)>();
          fence_regs(S);
          RELEASE(ck);
          if (shifted) {
#pragma unroll
            for (int i = 0; i < 64; i++) S[i] -= (i & 2) ? m1 : m0;
          }
          wg_wait<__builtin_popcount(PVM) - 1>();
          EXPC(0); EXPC(1); EXPC(2); EXPC(3); EXPC(4); EXPC(5); EXPC(6); EXPC(7);
          chk = s0 + s1;
        }
      }
      TRC(3);
      if (wg == 1) { TS(1, 1); TSC(1, 3); }
    }
    __syncwarp();
    const uint32_t unit = item & 255;
    if (unit < 64) {
      const int mblk = (7 - (p.unit[unit][0] >> 1)) * 2 + rank, nhalf = p.unit[unit][0] & 1, ks = p.unit[unit][1];
      const int k0 = 0, k1 = p.unit[unit][2];
      float acc[144];
      uint32_t s = rot, ph = 0, prev = 0;
      if (wg == 0) { TS(2, 0); TSC(2, 2); }
#pragma unroll 1
      for (int k = k0; k < k1; k++) {
        mbar_wait(b3F + s * 8, ph);
        const uint32_t st = sbase + s * K3_STAGE;
        const uint64_t da = make_desc(st + wg * 8192, 16, 1024, 1);
        const uint64_t db = make_desc(st + 16384, 4096, 1024, 1);
        const uint64_t dt = make_desc(st + 49152, 16, 512, 2);
        wg_fence();
#pragma unroll
        for (int t = 0; t < 4; t++) {
          const int sd = (t > 0) || (k > k0);
          wgmma_ss_n256<1, 0>(acc, da + (uint64_t)(t * 2), db + (uint64_t)((t >> 1) * 1024 + (t & 1) * 128), sd);
          wgmma_ss_n32<1, 128>(acc, da + (uint64_t)(t * 2), dt + (uint64_t)(t * 64), sd);
        }
        wg_commit();
        if (k > k0) {
          wg_wait<1>();
          if (sig) mbar_arrive_cluster(b3E + prev * 8, warp);
        }
        prev = s;
        s = (s + 1) & 3;
        if (s == rot) ph ^= 1;
      }
      wg_wait<0>();
      fence_regs(acc);
      cluster_arrive();
      if (wg == 0) TS(2, 4);
      const int tile = mblk * 2 + nhalf;
      uint4* wp = g_part + (size_t)((tile * 4 + ks) * 4) * 5 * 256 + tid;
      const uint32_t sown = sbase + wg * 8192 + (tid & 127) * 16;
#pragma unroll
      for (int d = 0; d < 4; d++) {
        if (d != ks) {
#pragma unroll
          for (int i = 0; i < 4; i++)
            __stcg(wp + (d * 5 + i) * 256,
                   make_uint4(pack_bf16(acc[d * 32 + i * 8], acc[d * 32 + i * 8 + 1]), pack_bf16(acc[d * 32 + i * 8 + 2], acc[d * 32 + i * 8 + 3]),
                              pack_bf16(acc[d * 32 + i * 8 + 4], acc[d * 32 + i * 8 + 5]), pack_bf16(acc[d * 32 + i * 8 + 6], acc[d * 32 + i * 8 + 7])));
          __stcg(reinterpret_cast<uint2*>(wp - tid + (d * 5 + 4) * 256) + tid,
                 make_uint2(pack_bf16(acc[128 + d * 4], acc[128 + d * 4 + 1]), pack_bf16(acc[128 + d * 4 + 2], acc[128 + d * 4 + 3])));
        } else {
#pragma unroll
          for (int i = 0; i < 9; i++) {
            const int o = (i < 8) ? d * 32 + i * 4 : 128 + d * 4;
            asm volatile("st.shared.v4.f32 [%0], {%1, %2, %3, %4};" ::"r"(sown + (i >> 2) * K3_STAGE + (i & 3) * 2048), "f"(acc[o]), "f"(acc[o + 1]), "f"(acc[o + 2]), "f"(acc[o + 3]) : "memory");
          }
        }
      }
      __threadfence();
      __syncwarp();
      if (wg == 0) TS(2, 5);
      if (lane == 0) {
        unsigned int* cnt = &g_sync[F_XCH + tile * 8 + warp_g];
        const uint32_t xtarget = lds32(sGate + 64) * 4 + 4;
        atomicAdd(cnt, 1u);
        uint32_t v, spins = 0;
        do {
          asm volatile("ld.acquire.gpu.global.u32 %0, [%1];" : "=r"(v) : "l"(cnt) : "memory");
        } while ((int)(v - xtarget) < 0 && ++spins < (1u << 24));
      }
      __syncwarp();
      if (wg == 0) TS(2, 6);
      float r[36];
#pragma unroll
      for (int i = 0; i < 9; i++)
        asm volatile("ld.shared.v4.f32 {%0, %1, %2, %3}, [%4];" : "=f"(r[i * 4]), "=f"(r[i * 4 + 1]), "=f"(r[i * 4 + 2]), "=f"(r[i * 4 + 3])
                     : "r"(sown + (i >> 2) * K3_STAGE + (i & 3) * 2048) : "memory");
#pragma unroll
      for (int sI = 1; sI < 4; sI++) {
        const int src = (ks + sI) & 3;
        const uint4* rp = g_part + (size_t)(((tile * 4 + src) * 4) + ks) * 5 * 256;
#pragma unroll
        for (int i = 0; i < 4; i++) {
          const uint4 v = __ldcg(rp + i * 256 + tid);
          r[i * 8] += bf_lo(v.x); r[i * 8 + 1] += bf_hi(v.x); r[i * 8 + 2] += bf_lo(v.y); r[i * 8 + 3] += bf_hi(v.y);
          r[i * 8 + 4] += bf_lo(v.z); r[i * 8 + 5] += bf_hi(v.z); r[i * 8 + 6] += bf_lo(v.w); r[i * 8 + 7] += bf_hi(v.w);
        }
        const uint2 v = __ldcg(reinterpret_cast<const uint2*>(rp + 4 * 256) + tid);
        r[32] += bf_lo(v.x); r[33] += bf_hi(v.x); r[34] += bf_lo(v.y); r[35] += bf_hi(v.y);
      }
      const int row = mblk * 128 + wg * 64 + warp * 16 + (lane >> 2);
      bf16* o0 = out + (size_t)row * DM + nhalf * 256 + ks * 64 + 8 * q;
#pragma unroll
      for (int G = 0; G < 2; G++) {
        uint32_t a0 = pack_bf16(r[G * 16], r[G * 16 + 1]), a1 = pack_bf16(r[G * 16 + 4], r[G * 16 + 5]);
        uint32_t a2 = pack_bf16(r[G * 16 + 8], r[G * 16 + 9]), a3 = pack_bf16(r[G * 16 + 12], r[G * 16 + 13]);
        uint32_t b0 = pack_bf16(r[G * 16 + 2], r[G * 16 + 3]), b1 = pack_bf16(r[G * 16 + 6], r[G * 16 + 7]);
        uint32_t b2 = pack_bf16(r[G * 16 + 10], r[G * 16 + 11]), b3 = pack_bf16(r[G * 16 + 14], r[G * 16 + 15]);
        quad_transpose(a0, a1, a2, a3, q);
        quad_transpose(b0, b1, b2, b3, q);
        st_v4(o0 + G * 32, a0, a1, a2, a3);
        st_v4(o0 + 8 * DM + G * 32, b0, b1, b2, b3);
      }
      {
        uint32_t t0 = pack_bf16(r[32], r[33]), t1 = pack_bf16(r[34], r[35]), t2 = 0, t3 = 0;
        quad_transpose(t0, t1, t2, t3, q);
        if (q < 2) st_v4(out + (size_t)(row + q * 8) * DM + 512 + nhalf * 32 + ks * 8, t0, t1, t2, t3);
      }
    } else {
      cluster_arrive();
    }
    if (wg == 0) { TS(2, 1); TSC(2, 3); }
    cluster_wait();
  }
}

typedef CUresult (*EncFn)(CUtensorMap*, CUtensorMapDataType, cuuint32_t, void*, const cuuint64_t*, const cuuint64_t*, const cuuint32_t*,
                          const cuuint32_t*, CUtensorMapInterleave, CUtensorMapSwizzle, CUtensorMapL2promotion, CUtensorMapFloatOOBfill);

static void enc2d(EncFn enc, CUtensorMap* m, const void* ptr, uint64_t cols, uint64_t rows, uint32_t bc, uint32_t br,
                  CUtensorMapSwizzle sw = CU_TENSOR_MAP_SWIZZLE_128B) {
  cuuint64_t gd[2] = {cols, rows}, gs[1] = {cols * 2};
  cuuint32_t bx[2] = {bc, br}, es[2] = {1, 1};
  enc(m, CU_TENSOR_MAP_DATA_TYPE_BFLOAT16, 2, const_cast<void*>(ptr), gd, gs, bx, es, CU_TENSOR_MAP_INTERLEAVE_NONE, sw,
      CU_TENSOR_MAP_L2_PROMOTION_L2_256B, CU_TENSOR_MAP_FLOAT_OOB_FILL_NONE);
}
static void enc3d(EncFn enc, CUtensorMap* m, const void* ptr, uint64_t cols, uint64_t rows, uint32_t br, uint32_t bch) {
  cuuint64_t gd[3] = {64, rows, cols / 64}, gs[2] = {cols * 2, 128};
  cuuint32_t bx[3] = {64, br, bch}, es[3] = {1, 1, 1};
  enc(m, CU_TENSOR_MAP_DATA_TYPE_BFLOAT16, 3, const_cast<void*>(ptr), gd, gs, bx, es, CU_TENSOR_MAP_INTERLEAVE_NONE,
      CU_TENSOR_MAP_SWIZZLE_128B, CU_TENSOR_MAP_L2_PROMOTION_L2_256B, CU_TENSOR_MAP_FLOAT_OOB_FILL_NONE);
}

static int g_sched[10] = {11, 10, 7, 4, 4, 4, 6, 7, 6, 24};
static void build_k1_jobs(Params& p) {
  int cnt[NCLUSTER];
  for (int c = 0; c < NCLUSTER; c++) {
    cnt[c] = 0;
    for (int i = 0; i <= K1_MAXJOBS; i++) p.jobs[c][i] = 0;
  }
  auto add = [&](int c, int nch, int a_sel, int mp, int w_sel, int chunk0) {
    p.jobs[c][cnt[c]++] = (uint16_t)((nch - 1) | (a_sel << 2) | (mp << 3) | (w_sel << 6) | (chunk0 << 8));
  };
  const int *cg = g_sched, *xg = g_sched + 4;
  for (int mp = 0; mp < 8; mp++) {
    int k = 0;
    for (int i = 0; i < K1_MAXJOBS; i++)
      for (int g = 0; g < 4; g++)
        if (i < cg[g]) { add(g * 8 + mp, 4, 0, mp, k & 1, (k >> 1) * 4); k++; }
    k = 0;
    for (int i = 0; i < K1_MAXJOBS; i++)
      for (int g = 0; g < 4; g++)
        if (i < xg[g]) {
          if (k < 7) add((4 + g) * 8 + mp, k == 0 ? 3 : 4, 1, mp, 2, k == 0 ? 24 : (k - 1) * 4);
          else add((4 + g) * 8 + mp, 4, 1, mp, 3, (k - 7) * 4);
          k++;
        }
    add(64 + mp / 4, 4, 1, mp, 3, 14 * 4);
    add(64 + mp / 4, 4, 1, mp, 3, 15 * 4);
  }
  for (int cc = 0; cc < NCLUSTER; cc++)
    for (int i = 0; i < cnt[cc]; i++) {
      const int key = p.jobs[cc][i] & 0x3C;
      if (i == 0 || (p.jobs[cc][i - 1] & 0x3C) != key) p.jobs[cc][i] |= (1 << 14);
      if (i == cnt[cc] - 1 || (p.jobs[cc][i + 1] & 0x3C) != key) p.jobs[cc][i] |= (1 << 15);
    }
}

static void build_k2_items(Params& p) {
  int n = 0;
  const int SCHED_N1 = g_sched[8], SCHED_N2 = g_sched[9];
  for (int j = 7; j >= 0; j--)
    for (int h = 0; h < SCHED_N1; h++) p.order[n++] = (uint8_t)(h * 8 + j);
  for (int j = 7; j >= 4; j--)
    for (int h = SCHED_N1; h < SCHED_N2; h++) p.order[n++] = (uint8_t)(h * 8 + j);
  for (int j = 7; j >= 0; j--)
    for (int h = SCHED_N1; h < 32; h++)
      if (!(h < SCHED_N2 && j >= 4)) p.order[n++] = (uint8_t)(h * 8 + j);
}

static void build_k3_units(Params& p) {
  float slope = 0.045f;
  int NE = 25;
  for (int t = 0; t < 16; t++) {
    const int u[4] = {t, 31 - t, 32 + t, 63 - t};
    float acc = 0.f;
    int k0 = 0, l0 = NE;
    for (int i = 0; i < 4; i++) {
      acc += 18.25f + slope * (31.5f - u[i]);
      const int k1 = (i == 3) ? 73 : (int)(acc + 0.5f);
      const int e0 = NE * i / 4, e1 = NE * (i + 1) / 4;
      uint8_t* w = p.unit[u[i]];
      w[0] = (uint8_t)t; w[1] = (uint8_t)i; w[2] = (uint8_t)(k1 - k0); w[3] = (uint8_t)e0; w[4] = (uint8_t)(e1 - e0); w[5] = (uint8_t)(l0 - e1);
      l0 += (k1 - k0) - (e1 - e0);
      k0 = k1;
    }
  }
}

extern "C" void kernel_launch(void* const* d_in, const int* in_sizes, int n_in, void* d_out, int out_size) {
  const bf16* x = (const bf16*)d_in[0];
  const bf16* wqkv = (const bf16*)d_in[1];
  const bf16* wo = (const bf16*)d_in[2];
  const bf16* ckv = (const bf16*)d_in[4];
  const bf16* w_q = (const bf16*)d_in[5];
  const bf16* w_uk = (const bf16*)d_in[6];
  const bf16* w_uv = (const bf16*)d_in[7];
  const bf16* w_o = (const bf16*)d_in[8];
  const bf16* gate_w = (const bf16*)d_in[9];

  EncFn enc = nullptr;
  cudaDriverEntryPointQueryResult qr;
  cudaGetDriverEntryPoint("cuTensorMapEncodeTiled", (void**)&enc, cudaEnableDefault, &qr);
  void *pQ, *pK, *pV, *pCtx, *pQA;
  cudaGetSymbolAddress(&pQA, g_QKVA);
  cudaGetSymbolAddress(&pQ, g_Q);
  cudaGetSymbolAddress(&pK, g_K);
  cudaGetSymbolAddress(&pV, g_V);
  cudaGetSymbolAddress(&pCtx, g_ctx);

  static Params p;
  enc2d(enc, &p.tmA[0], ckv, DC, S_LEN, 64, 128);
  enc2d(enc, &p.tmA[1], x, DM, S_LEN, 64, 128);
  enc3d(enc, &p.tmW[0], w_uk, HDIM, DC, 16, 4);
  enc3d(enc, &p.tmW[1], w_uv, HDIM, DC, 16, 4);
  enc3d(enc, &p.tmW[2], wqkv, NQKVA, DM, 16, 4);
  enc3d(enc, &p.tmW[3], w_q, HDIM, DM, 16, 4);
  build_k1_jobs(p);
  enc2d(enc, &p.tmQ, pQ, HDIM, S_LEN, 64, 128);
  enc2d(enc, &p.tmK, pK, HDIM, S_LEN, 64, 128);
  enc2d(enc, &p.tmV, pV, HDIM, S_LEN, 64, 128);
  build_k2_items(p);
  build_k3_units(p);
  for (int i = 0; i < 3; i++) {
    const cuuint64_t ld = (i < 2 ? NQKVA : KCAT) * 2, nch = (i < 2) ? 27 : 9;
    cuuint64_t gd[4] = {64, S_LEN / 2, i ? 2 : nch, i ? nch : 2}, gs[3] = {2 * ld, i ? ld : 128, i ? 128 : ld};
    cuuint32_t bx[4] = {64, i ? 8u : 16u, i ? 2u : 9u, i ? 9u : 2u}, es[4] = {1, 1, 1, 1};
    enc(&p.tmL[i], CU_TENSOR_MAP_DATA_TYPE_BFLOAT16, 4, (i < 2) ? pQA : (void*)((bf16*)pCtx + HDIM), gd, gs, bx, es, CU_TENSOR_MAP_INTERLEAVE_NONE,
        CU_TENSOR_MAP_SWIZZLE_128B, CU_TENSOR_MAP_L2_PROMOTION_L2_256B, CU_TENSOR_MAP_FLOAT_OOB_FILL_NONE);
  }
  enc2d(enc, &p.tmC, pCtx, KCAT, S_LEN, 64, 128);
  enc3d(enc, &p.tmO[0], w_o, DM, HDIM, 32, 4);
  enc3d(enc, &p.tmO[1], wo, DM, DM, 32, 4);
  enc2d(enc, &p.tmOt[0], w_o, DM, HDIM, 32, 32, CU_TENSOR_MAP_SWIZZLE_64B);
  enc2d(enc, &p.tmOt[1], wo, DM, DM, 32, 32, CU_TENSOR_MAP_SWIZZLE_64B);

  cudaFuncSetAttribute(fused_kernel, cudaFuncAttributeMaxDynamicSharedMemorySize, SMEM_BYTES);
  fused_kernel<<<NCLUSTER * 2, 384, SMEM_BYTES>>>(p, x, gate_w, (bf16*)d_out);
}
```

```cpp
#include <cuda_runtime.h>
#include <cuda_bf16.h>
#include <cuda.h>
#include <stdint.h>

typedef __nv_bfloat16 bf16;

constexpr int S_LEN = 2048, DM = 576, DC = 512, HDIM = 4096, NQKVA = 1728, KCAT = 4672;
constexpr int NCLUSTER = 66;

__device__ __align__(1024) bf16 g_Q[S_LEN * HDIM];
__device__ __align__(1024) bf16 g_K[S_LEN * HDIM];
__device__ __align__(1024) bf16 g_V[S_LEN * HDIM];
__device__ __align__(1024) bf16 g_QKVA[S_LEN * NQKVA + 64];
__device__ __align__(1024) bf16 g_ctx[S_LEN * KCAT];
__device__ float g_gate[S_LEN];
__device__ __align__(1024) uint4 g_part[32 * 4 * 4 * 5 * 256];
__device__ __align__(16) unsigned int g_sync[400];
constexpr int F_QKVA = 0, F_HP = 16, F_CTX = 32, F_OA = 48, F_GATE = 96, F_TICK = 97, F_DONE = 98, F_XCH = 128, F_EPOCH = 384;

__device__ __forceinline__ uint32_t smem_u32(const void* p) { return (uint32_t)__cvta_generic_to_shared(p); }
__device__ __forceinline__ void mbar_init(uint32_t a, uint32_t c) {
  asm volatile("mbarrier.init.shared::cta.b64 [%0], %1;" ::"r"(a), "r"(c));
}
__device__ __forceinline__ void mbar_expect(uint32_t a, uint32_t b) {
  asm volatile("mbarrier.arrive.expect_tx.shared::cta.b64 _, [%0], %1;" ::"r"(a), "r"(b) : "memory");
}
#define TS(k, i)
#define TSC(k, i)
#define TSM(k)
#define BSEG(i)
#define TB(k)
#define TRC(fl)
#define SPIN_LIMIT "4194304"
__device__ __forceinline__ void mbar_wait(uint32_t a, uint32_t parity) {
  asm volatile(
      "{\n.reg .pred p;\n.reg .u32 n;\n"
      "mbarrier.try_wait.parity.shared::cta.b64 p, [%0], %1;\n"
      "@p bra DONE;\n"
      "mov.u32 n, 0;\n"
      "LOOP:\n"
      "mbarrier.try_wait.parity.shared::cta.b64 p, [%0], %1;\n"
      "@p bra DONE;\n"
      "add.u32 n, n, 1;\n"
      "setp.lt.u32 p, n, " SPIN_LIMIT ";\n"
      "@p bra LOOP;\n"
      "DONE:\n}" ::"r"(a), "r"(parity) : "memory");
}
template <int NS>
__device__ __forceinline__ void mbar_wait_ns(uint32_t a, uint32_t parity) {
  asm volatile(
      "{\n.reg .pred p;\n.reg .u32 n;\n"
      "mov.u32 n, 0;\n"
      "LOOP:\n"
      "mbarrier.try_wait.parity.shared::cta.b64 p, [%0], %1, %2;\n"
      "@p bra DONE;\n"
      "add.u32 n, n, 1;\n"
      "setp.lt.u32 p, n, " SPIN_LIMIT ";\n"
      "@p bra LOOP;\n"
      "DONE:\n}" ::"r"(a), "r"(parity), "n"(NS) : "memory");
}
__device__ __forceinline__ void mbar_wait2(uint32_t a, uint32_t pa, uint32_t b, uint32_t pb) {
  asm volatile(
      "{\n.reg .pred p, q;\n.reg .u32 n;\n"
      "mov.u32 n, 0;\n"
      "LOOP:\n"
      "mbarrier.try_wait.parity.shared::cta.b64 p, [%0], %1;\n"
      "mbarrier.try_wait.parity.shared::cta.b64 q, [%2], %3;\n"
      "add.u32 n, n, 1;\n"
      "and.pred p, p, q;\n"
      "setp.lt.and.u32 p, n, " SPIN_LIMIT ", !p;\n"
      "@p bra LOOP;\n"
      "}" ::"r"(a), "r"(pa), "r"(b), "r"(pb) : "memory");
}
__device__ __forceinline__ uint32_t mbar_test(uint32_t a, uint32_t parity) {
  uint32_t r;
  asm volatile("{\n.reg .pred p;\nmbarrier.test_wait.parity.shared::cta.b64 p, [%1], %2;\nselp.u32 %0, 1, 0, p;\n}" : "=r"(r) : "r"(a), "r"(parity) : "memory");
  return r;
}
__device__ __forceinline__ void mbar_arrive(uint32_t a) {
  asm volatile("mbarrier.arrive.shared::cta.b64 _, [%0];" ::"r"(a) : "memory");
}
__device__ __forceinline__ void mbar_arrive_cluster(uint32_t a, uint32_t cta) {
  asm volatile("{\n.reg .b32 r;\nmapa.shared::cluster.u32 r, %0, %1;\nmbarrier.arrive.shared::cluster.b64 _, [r];\n}" ::"r"(a),
               "r"(cta) : "memory");
}
__device__ __forceinline__ void mbar_arrive_cluster_if(uint32_t a, uint32_t cta, bool pred) {
  asm volatile("{\n.reg .b32 r;\n.reg .pred p;\nsetp.ne.u32 p, %2, 0;\nmapa.shared::cluster.u32 r, %0, %1;\n@p mbarrier.arrive.shared::cluster.b64 _, [r];\n}" ::"r"(a),
               "r"(cta), "r"((uint32_t)pred) : "memory");
}
__device__ __forceinline__ void anchor(float v, uint32_t pred) {
  asm volatile("{\n.reg .pred p;\nsetp.ne.u32 p, %1, 0;\n@p st.shared.f32 [%1], %0;\n}" ::"f"(v), "r"(pred) : "memory");
}
__device__ __forceinline__ void mbar_arrive_if(uint32_t a, bool pred) {
  asm volatile("{\n.reg .pred p;\nsetp.ne.u32 p, %1, 0;\n@p mbarrier.arrive.shared::cta.b64 _, [%0];\n}" ::"r"(a), "r"((uint32_t)pred) : "memory");
}
__device__ __forceinline__ void tma2d(uint32_t dst, const CUtensorMap* m, uint32_t bar, int c0, int c1) {
  asm volatile("cp.async.bulk.tensor.2d.shared::cluster.global.mbarrier::complete_tx::bytes [%0], [%1, {%3, %4}], [%2];" ::"r"(dst),
               "l"(m), "r"(bar), "r"(c0), "r"(c1) : "memory");
}
__device__ __forceinline__ void tma2d_mc(uint32_t dst, const CUtensorMap* m, uint32_t bar, int c0, int c1, uint16_t mask) {
  asm volatile(
      "cp.async.bulk.tensor.2d.shared::cluster.global.mbarrier::complete_tx::bytes.multicast::cluster [%0], [%1, {%3, %4}], [%2], %5;" ::"r"(dst),
      "l"(m), "r"(bar), "r"(c0), "r"(c1), "h"(mask) : "memory");
}
__device__ __forceinline__ void tma3d_mc(uint32_t dst, const CUtensorMap* m, uint32_t bar, int c0, int c1, int c2, uint16_t mask) {
  asm volatile(
      "cp.async.bulk.tensor.3d.shared::cluster.global.mbarrier::complete_tx::bytes.multicast::cluster [%0], [%1, {%3, %4, %5}], [%2], %6;" ::"r"(dst),
      "l"(m), "r"(bar), "r"(c0), "r"(c1), "r"(c2), "h"(mask) : "memory");
}
__device__ __forceinline__ void tma3d(uint32_t dst, const CUtensorMap* m, uint32_t bar, int c0, int c1, int c2) {
  asm volatile(
      "cp.async.bulk.tensor.3d.shared::cluster.global.mbarrier::complete_tx::bytes [%0], [%1, {%3, %4, %5}], [%2];" ::"r"(dst),
      "l"(m), "r"(bar), "r"(c0), "r"(c1), "r"(c2) : "memory");
}
__device__ __forceinline__ void tma_pf2d(const CUtensorMap* m, int c0, int c1) {
  asm volatile("cp.async.bulk.prefetch.tensor.2d.L2.global [%0, {%1, %2}];" ::"l"(m), "r"(c0), "r"(c1) : "memory");
}
__device__ __forceinline__ void tma_pf3d(const CUtensorMap* m, int c0, int c1, int c2) {
  asm volatile("cp.async.bulk.prefetch.tensor.3d.L2.global [%0, {%1, %2, %3}];" ::"l"(m), "r"(c0), "r"(c1), "r"(c2) : "memory");
}
__device__ __forceinline__ void prefetch_tmap(const CUtensorMap* m) {
  asm volatile("prefetch.tensormap [%0];" ::"l"(m) : "memory");
}
__device__ __forceinline__ void cluster_arrive() { asm volatile("barrier.cluster.arrive.relaxed.aligned;" ::: "memory"); }
__device__ __forceinline__ void cluster_wait() { asm volatile("barrier.cluster.wait.aligned;" ::: "memory"); }
__device__ __forceinline__ void cluster_sync() {
  cluster_arrive();
  cluster_wait();
}
__device__ __forceinline__ uint32_t cluster_rank() {
  uint32_t r;
  asm volatile("mov.u32 %0, %%cluster_ctarank;" : "=r"(r));
  return r;
}
__device__ __forceinline__ bool elect_one() {
  uint32_t p;
  asm volatile("{\n.reg .pred q;\nelect.sync _|q, 0xffffffff;\nselp.u32 %0, 1, 0, q;\n}" : "=r"(p));
  return p;
}
__device__ __forceinline__ void ldsm_x4(uint32_t& r0, uint32_t& r1, uint32_t& r2, uint32_t& r3, uint32_t addr) {
  asm volatile("ldmatrix.sync.aligned.m8n8.x4.shared.b16 {%0, %1, %2, %3}, [%4];" : "=r"(r0), "=r"(r1), "=r"(r2), "=r"(r3) : "r"(addr) : "memory");
}
__device__ __forceinline__ void wg_fence() { asm volatile("wgmma.fence.sync.aligned;" ::: "memory"); }
__device__ __forceinline__ void wg_commit() { asm volatile("wgmma.commit_group.sync.aligned;" ::: "memory"); }
template <int N>
__device__ __forceinline__ void wg_wait() { asm volatile("wgmma.wait_group.sync.aligned %0;" ::"n"(N) : "memory"); }
template <int N>
__device__ __forceinline__ void reg_alloc() { asm volatile("setmaxnreg.inc.sync.aligned.u32 %0;" ::"n"(N)); }
template <int N>
__device__ __forceinline__ void reg_dealloc() { asm volatile("setmaxnreg.dec.sync.aligned.u32 %0;" ::"n"(N)); }
__device__ __forceinline__ void bar_sync(int id, int n) { asm volatile("bar.sync %0, %1;" ::"r"(id), "r"(n) : "memory"); }
__device__ __forceinline__ void bar_arrive(int id, int n) { asm volatile("bar.arrive %0, %1;" ::"r"(id), "r"(n) : "memory"); }
template <int NT>
__device__ __forceinline__ void fence_regs(float (&d)[NT]) {
#pragma unroll
  for (int i = 0; i < NT; i++) asm volatile("" : "+f"(d[i])::"memory");
}
template <int NT>
__device__ __forceinline__ void fence_regs(uint32_t (&d)[NT]) {
#pragma unroll
  for (int i = 0; i < NT; i++) asm volatile("" : "+r"(d[i])::"memory");
}
__device__ __forceinline__ uint64_t make_desc(uint32_t saddr, uint32_t lbo, uint32_t sbo, uint32_t layout) {
  return (uint64_t)((saddr & 0x3FFFF) >> 4) | ((uint64_t)(lbo >> 4) << 16) | ((uint64_t)(sbo >> 4) << 32) | ((uint64_t)layout << 62);
}
__device__ __forceinline__ uint32_t pack_bf16(float lo, float hi) {
  uint32_t r;
  asm("cvt.rn.bf16x2.f32 %0, %1, %2;" : "=r"(r) : "f"(hi), "f"(lo));
  return r;
}
__device__ __forceinline__ float ex2(float x) {
  float r;
  asm("ex2.approx.ftz.f32 %0, %1;" : "=f"(r) : "f"(x));
  return r;
}
__device__ __forceinline__ void st_v4(void* p, uint32_t a, uint32_t b, uint32_t c, uint32_t d) {
#define ST_MOD ".cs"
  asm volatile("st.global" ST_MOD ".v4.b32 [%0], {%1, %2, %3, %4};" ::"l"(p), "r"(a), "r"(b), "r"(c), "r"(d) : "memory");
}
#define STA_MOD ".cs"
__device__ __forceinline__ void st_v4a(void* p, uint32_t a, uint32_t b, uint32_t c, uint32_t d) {
  asm volatile("st.global" STA_MOD ".v4.b32 [%0], {%1, %2, %3, %4};" ::"l"(p), "r"(a), "r"(b), "r"(c), "r"(d) : "memory");
}
__device__ __forceinline__ float bf_lo(uint32_t v) { return __uint_as_float(v << 16); }
__device__ __forceinline__ float bf_hi(uint32_t v) { return __uint_as_float(v & 0xFFFF0000u); }

__device__ __forceinline__ void quad_transpose(uint32_t& a0, uint32_t& a1, uint32_t& a2, uint32_t& a3, int q) {
  const bool o1 = q & 1, o2 = q & 2;
  uint32_t t0 = o1 ? a0 : a1, t1 = o1 ? a2 : a3;
  t0 = __shfl_xor_sync(0xffffffffu, t0, 1);
  t1 = __shfl_xor_sync(0xffffffffu, t1, 1);
  if (o1) { a0 = t0; a2 = t1; } else { a1 = t0; a3 = t1; }
  t0 = o2 ? a0 : a2;
  t1 = o2 ? a1 : a3;
  t0 = __shfl_xor_sync(0xffffffffu, t0, 2);
  t1 = __shfl_xor_sync(0xffffffffu, t1, 2);
  if (o2) { a0 = t0; a1 = t1; } else { a2 = t0; a3 = t1; }
}

template<int TB, int OFF, int NT>
__device__ __forceinline__ void wgmma_ss_n256(float (&d)[NT], uint64_t da, uint64_t db, int scale_d) {
  asm volatile("{\n.reg .pred p;\nsetp.ne.b32 p, %130, 0;\n"
    "wgmma.mma_async.sync.aligned.m64n256k16.f32.bf16.bf16 {%0, %1, %2, %3, %4, %5, %6, %7, %8, %9, %10, %11, %12, %13, %14, %15, %16, %17, %18, %19, %20, %21, %22, %23, %24, %25, %26, %27, %28, %29, %30, %31, %32, %33, %34, %35, %36, %37, %38, %39, %40, %41, %42, %43, %44, %45, %46, %47, %48, %49, %50, %51, %52, %53, %54, %55, %56, %57, %58, %59, %60, %61, %62, %63, %64, %65, %66, %67, %68, %69, %70, %71, %72, %73, %74, %75, %76, %77, %78, %79, %80, %81, %82, %83, %84, %85, %86, %87, %88, %89, %90, %91, %92, %93, %94, %95, %96, %97, %98, %99, %100, %101, %102, %103, %104, %105, %106, %107, %108, %109, %110, %111, %112, %113, %114, %115, %116, %117, %118, %119, %120, %121, %122, %123, %124, %125, %126, %127}, %128, %129, p, 1, 1, 0, %131;\n}\n"
    : "+f"(d[OFF+0]), "+f"(d[OFF+1]), "+f"(d[OFF+2]), "+f"(d[OFF+3]), "+f"(d[OFF+4]), "+f"(d[OFF+5]), "+f"(d[OFF+6]), "+f"(d[OFF+7]), "+f"(d[OFF+8]), "+f"(d[OFF+9]), "+f"(d[OFF+10]), "+f"(d[OFF+11]), "+f"(d[OFF+12]), "+f"(d[OFF+13]), "+f"(d[OFF+14]), "+f"(d[OFF+15]), "+f"(d[OFF+16]), "+f"(d[OFF+17]), "+f"(d[OFF+18]), "+f"(d[OFF+19]), "+f"(d[OFF+20]), "+f"(d[OFF+21]), "+f"(d[OFF+22]), "+f"(d[OFF+23]), "+f"(d[OFF+24]), "+f"(d[OFF+25]), "+f"(d[OFF+26]), "+f"(d[OFF+27]), "+f"(d[OFF+28]), "+f"(d[OFF+29]), "+f"(d[OFF+30]), "+f"(d[OFF+31]), "+f"(d[OFF+32]), "+f"(d[OFF+33]), "+f"(d[OFF+34]), "+f"(d[OFF+35]), "+f"(d[OFF+36]), "+f"(d[OFF+37]), "+f"(d[OFF+38]), "+f"(d[OFF+39]), "+f"(d[OFF+40]), "+f"(d[OFF+41]), "+f"(d[OFF+42]), "+f"(d[OFF+43]), "+f"(d[OFF+44]), "+f"(d[OFF+45]), "+f"(d[OFF+46]), "+f"(d[OFF+47]), "+f"(d[OFF+48]), "+f"(d[OFF+49]), "+f"(d[OFF+50]), "+f"(d[OFF+51]), "+f"(d[OFF+52]), "+f"(d[OFF+53]), "+f"(d[OFF+54]), "+f"(d[OFF+55]), "+f"(d[OFF+56]), "+f"(d[OFF+57]), "+f"(d[OFF+58]), "+f"(d[OFF+59]), "+f"(d[OFF+60]), "+f"(d[OFF+61]), "+f"(d[OFF+62]), "+f"(d[OFF+63]), "+f"(d[OFF+64]), "+f"(d[OFF+65]), "+f"(d[OFF+66]), "+f"(d[OFF+67]), "+f"(d[OFF+68]), "+f"(d[OFF+69]), "+f"(d[OFF+70]), "+f"(d[OFF+71]), "+f"(d[OFF+72]), "+f"(d[OFF+73]), "+f"(d[OFF+74]), "+f"(d[OFF+75]), "+f"(d[OFF+76]), "+f"(d[OFF+77]), "+f"(d[OFF+78]), "+f"(d[OFF+79]), "+f"(d[OFF+80]), "+f"(d[OFF+81]), "+f"(d[OFF+82]), "+f"(d[OFF+83]), "+f"(d[OFF+84]), "+f"(d[OFF+85]), "+f"(d[OFF+86]), "+f"(d[OFF+87]), "+f"(d[OFF+88]), "+f"(d[OFF+89]), "+f"(d[OFF+90]), "+f"(d[OFF+91]), "+f"(d[OFF+92]), "+f"(d[OFF+93]), "+f"(d[OFF+94]), "+f"(d[OFF+95]), "+f"(d[OFF+96]), "+f"(d[OFF+97]), "+f"(d[OFF+98]), "+f"(d[OFF+99]), "+f"(d[OFF+100]), "+f"(d[OFF+101]), "+f"(d[OFF+102]), "+f"(d[OFF+103]), "+f"(d[OFF+104]), "+f"(d[OFF+105]), "+f"(d[OFF+106]), "+f"(d[OFF+107]), "+f"(d[OFF+108]), "+f"(d[OFF+109]), "+f"(d[OFF+110]), "+f"(d[OFF+111]), "+f"(d[OFF+112]), "+f"(d[OFF+113]), "+f"(d[OFF+114]), "+f"(d[OFF+115]), "+f"(d[OFF+116]), "+f"(d[OFF+117]), "+f"(d[OFF+118]), "+f"(d[OFF+119]), "+f"(d[OFF+120]), "+f"(d[OFF+121]), "+f"(d[OFF+122]), "+f"(d[OFF+123]), "+f"(d[OFF+124]), "+f"(d[OFF+125]), "+f"(d[OFF+126]), "+f"(d[OFF+127])
    : "l"(da), "l"(db), "r"(scale_d), "n"(TB));
}
template<int TB, int OFF, int NT>
__device__ __forceinline__ void wgmma_ss_n32(float (&d)[NT], uint64_t da, uint64_t db, int scale_d) {
  asm volatile("{\n.reg .pred p;\nsetp.ne.b32 p, %18, 0;\n"
    "wgmma.mma_async.sync.aligned.m64n32k16.f32.bf16.bf16 {%0, %1, %2, %3, %4, %5, %6, %7, %8, %9, %10, %11, %12, %13, %14, %15}, %16, %17, p, 1, 1, 0, %19;\n}\n"
    : "+f"(d[OFF+0]), "+f"(d[OFF+1]), "+f"(d[OFF+2]), "+f"(d[OFF+3]), "+f"(d[OFF+4]), "+f"(d[OFF+5]), "+f"(d[OFF+6]), "+f"(d[OFF+7]), "+f"(d[OFF+8]), "+f"(d[OFF+9]), "+f"(d[OFF+10]), "+f"(d[OFF+11]), "+f"(d[OFF+12]), "+f"(d[OFF+13]), "+f"(d[OFF+14]), "+f"(d[OFF+15])
    : "l"(da), "l"(db), "r"(scale_d), "n"(TB));
}
template<int TB, int OFF, int NT>
__device__ __forceinline__ void wgmma_rs_n128(float (&d)[NT], uint32_t a0, uint32_t a1, uint32_t a2, uint32_t a3, uint64_t db, int scale_d) {
  asm volatile("{\n.reg .pred p;\nsetp.ne.b32 p, %69, 0;\n"
    "wgmma.mma_async.sync.aligned.m64n128k16.f32.bf16.bf16 {%0, %1, %2, %3, %4, %5, %6, %7, %8, %9, %10, %11, %12, %13, %14, %15, %16, %17, %18, %19, %20, %21, %22, %23, %24, %25, %26, %27, %28, %29, %30, %31, %32, %33, %34, %35, %36, %37, %38, %39, %40, %41, %42, %43, %44, %45, %46, %47, %48, %49, %50, %51, %52, %53, %54, %55, %56, %57, %58, %59, %60, %61, %62, %63}, {%64, %65, %66, %67}, %68, p, 1, 1, %70;\n}\n"
    : "+f"(d[OFF+0]), "+f"(d[OFF+1]), "+f"(d[OFF+2]), "+f"(d[OFF+3]), "+f"(d[OFF+4]), "+f"(d[OFF+5]), "+f"(d[OFF+6]), "+f"(d[OFF+7]), "+f"(d[OFF+8]), "+f"(d[OFF+9]), "+f"(d[OFF+10]), "+f"(d[OFF+11]), "+f"(d[OFF+12]), "+f"(d[OFF+13]), "+f"(d[OFF+14]), "+f"(d[OFF+15]), "+f"(d[OFF+16]), "+f"(d[OFF+17]), "+f"(d[OFF+18]), "+f"(d[OFF+19]), "+f"(d[OFF+20]), "+f"(d[OFF+21]), "+f"(d[OFF+22]), "+f"(d[OFF+23]), "+f"(d[OFF+24]), "+f"(d[OFF+25]), "+f"(d[OFF+26]), "+f"(d[OFF+27]), "+f"(d[OFF+28]), "+f"(d[OFF+29]), "+f"(d[OFF+30]), "+f"(d[OFF+31]), "+f"(d[OFF+32]), "+f"(d[OFF+33]), "+f"(d[OFF+34]), "+f"(d[OFF+35]), "+f"(d[OFF+36]), "+f"(d[OFF+37]), "+f"(d[OFF+38]), "+f"(d[OFF+39]), "+f"(d[OFF+40]), "+f"(d[OFF+41]), "+f"(d[OFF+42]), "+f"(d[OFF+43]), "+f"(d[OFF+44]), "+f"(d[OFF+45]), "+f"(d[OFF+46]), "+f"(d[OFF+47]), "+f"(d[OFF+48]), "+f"(d[OFF+49]), "+f"(d[OFF+50]), "+f"(d[OFF+51]), "+f"(d[OFF+52]), "+f"(d[OFF+53]), "+f"(d[OFF+54]), "+f"(d[OFF+55]), "+f"(d[OFF+56]), "+f"(d[OFF+57]), "+f"(d[OFF+58]), "+f"(d[OFF+59]), "+f"(d[OFF+60]), "+f"(d[OFF+61]), "+f"(d[OFF+62]), "+f"(d[OFF+63])
    : "r"(a0), "r"(a1), "r"(a2), "r"(a3), "l"(db), "r"(scale_d), "n"(TB));
}
template<int TB, int OFF, int NT>
__device__ __forceinline__ void wgmma_rs_n64(float (&d)[NT], uint32_t a0, uint32_t a1, uint32_t a2, uint32_t a3, uint64_t db, int scale_d) {
  asm volatile("{\n.reg .pred p;\nsetp.ne.b32 p, %37, 0;\n"
    "wgmma.mma_async.sync.aligned.m64n64k16.f32.bf16.bf16 {%0, %1, %2, %3, %4, %5, %6, %7, %8, %9, %10, %11, %12, %13, %14, %15, %16, %17, %18, %19, %20, %21, %22, %23, %24, %25, %26, %27, %28, %29, %30, %31}, {%32, %33, %34, %35}, %36, p, 1, 1, %38;\n}\n"
    : "+f"(d[OFF+0]), "+f"(d[OFF+1]), "+f"(d[OFF+2]), "+f"(d[OFF+3]), "+f"(d[OFF+4]), "+f"(d[OFF+5]), "+f"(d[OFF+6]), "+f"(d[OFF+7]), "+f"(d[OFF+8]), "+f"(d[OFF+9]), "+f"(d[OFF+10]), "+f"(d[OFF+11]), "+f"(d[OFF+12]), "+f"(d[OFF+13]), "+f"(d[OFF+14]), "+f"(d[OFF+15]), "+f"(d[OFF+16]), "+f"(d[OFF+17]), "+f"(d[OFF+18]), "+f"(d[OFF+19]), "+f"(d[OFF+20]), "+f"(d[OFF+21]), "+f"(d[OFF+22]), "+f"(d[OFF+23]), "+f"(d[OFF+24]), "+f"(d[OFF+25]), "+f"(d[OFF+26]), "+f"(d[OFF+27]), "+f"(d[OFF+28]), "+f"(d[OFF+29]), "+f"(d[OFF+30]), "+f"(d[OFF+31])
    : "r"(a0), "r"(a1), "r"(a2), "r"(a3), "l"(db), "r"(scale_d), "n"(TB));
}

__device__ __forceinline__ void wait_flag(const unsigned int* f, uint32_t target) {
  uint32_t v;
#pragma unroll 1
  for (uint32_t spins = 0; spins < (1u << 22); spins++) {
    asm volatile("ld.acquire.gpu.global.u32 %0, [%1];" : "=r"(v) : "l"(f) : "memory");
    if (v >= target) break;
    __nanosleep(100);
  }
}
__device__ __forceinline__ uint32_t lds32(uint32_t a) {
  uint32_t v;
  asm volatile("ld.shared.u32 %0, [%1];" : "=r"(v) : "r"(a) : "memory");
  return v;
}
__device__ __forceinline__ float gate_row(int row, int lane, const bf16* __restrict__ x, const bf16* __restrict__ gate_w) {
  const uint32_t* xr = reinterpret_cast<const uint32_t*>(x + (size_t)row * DM);
  const uint32_t* gw2 = reinterpret_cast<const uint32_t*>(gate_w);
  float gs = 0.f;
#pragma unroll
  for (int i = 0; i < 9; i++) {
    const uint32_t a = __ldg(xr + lane + 32 * i), b = __ldg(gw2 + lane + 32 * i);
    gs = fmaf(bf_lo(a), bf_lo(b), gs);
    gs = fmaf(bf_hi(a), bf_hi(b), gs);
  }
#pragma unroll
  for (int o = 16; o; o >>= 1) gs += __shfl_xor_sync(0xffffffffu, gs, o);
  const float g = 1.f / (1.f + __expf(-gs));
  if (lane == 0) g_gate[row] = g;
  return g;
}
constexpr uint32_t LQ = 36864, LV = 55296;
__device__ __forceinline__ void mma16(float (&c)[4], uint32_t a0, uint32_t a1, uint32_t a2, uint32_t a3, uint32_t b0, uint32_t b1) {
  asm("mma.sync.aligned.m16n8k16.row.col.f32.bf16.bf16.f32 {%0, %1, %2, %3}, {%4, %5, %6, %7}, {%8, %9}, {%0, %1, %2, %3};"
      : "+f"(c[0]), "+f"(c[1]), "+f"(c[2]), "+f"(c[3]) : "r"(a0), "r"(a1), "r"(a2), "r"(a3), "r"(b0), "r"(b1));
}
__device__ __forceinline__ void mma8(float (&c)[4], uint32_t a0, uint32_t a1, uint32_t b0) {
  asm("mma.sync.aligned.m16n8k8.row.col.f32.bf16.bf16.f32 {%0, %1, %2, %3}, {%4, %5}, {%6}, {%0, %1, %2, %3};"
      : "+f"(c[0]), "+f"(c[1]), "+f"(c[2]), "+f"(c[3]) : "r"(a0), "r"(a1), "r"(b0));
}
__device__ __forceinline__ void local_attn(int lr0, int warp_g, uint32_t sL, uint32_t bL, uint32_t bL2, int lane, float g0, float g1) {
  const float scale_l2 = 0.23570226039551584f * 1.4426950408889634f;
  const int g = lane >> 2, t = lane & 3;
  const bool lo0 = 2 * t > g, lo1 = 2 * t + 1 > g;
  const uint32_t mlo = (lo0 ? 0xFFFFu : 0u) | (lo1 ? 0xFFFF0000u : 0u);
  const bool ok0 = lr0 > 0 || !lo0, ok1 = lr0 > 0 || !lo1;
  uint32_t ad[9], k[9][4], qf[9][2], pe[4], po[4];
#pragma unroll
  for (int c = 0; c < 9; c++) {
    const uint32_t ch = warp_g * 9 + c;
    ad[c] = sL + (lane >> 4) * 18432 + (lane & 15) * 128 + ((ch >> 3) << 11) + (((ch ^ lane) & 7) << 4);
  }
  mbar_wait(bL, 0);
  if (warp_g == 0) TS(1, 6);
#pragma unroll
  for (int c = 0; c < 9; c++) {
    asm volatile("ldmatrix.sync.aligned.m8n8.x2.shared.b16 {%0, %1}, [%2];" : "=r"(qf[c][0]), "=r"(qf[c][1]) : "r"(ad[c] + LQ) : "memory");
    ldsm_x4(k[c][0], k[c][1], k[c][2], k[c][3], ad[c]);
  }
#pragma unroll
  for (int i = 0; i < 4; i++) {
    const uint32_t q0 = (t >= i) ? qf[2 * i][0] : 0u, q1 = (t >= i) ? qf[2 * i][1] : 0u;
    const uint32_t q4 = (t <= i) ? qf[2 * i + 2][0] : 0u, q5 = (t <= i) ? qf[2 * i + 2][1] : 0u;
    float c[4][4];
#pragma unroll
    for (int T = 0; T < 4; T++) {
#pragma unroll
      for (int j = 0; j < 4; j++) c[T][j] = 0.f;
      mma16(c[T], q0, q1, qf[2 * i + 1][0], qf[2 * i + 1][1], k[2 * i][T], k[2 * i + 1][T]);
      mma8(c[T], q4, q5, k[2 * i + 2][T]);
    }
    const float e0 = ok0 ? (lo0 ? c[0][0] : c[1][0]) : -INFINITY, e1 = ok1 ? (lo1 ? c[0][1] : c[1][1]) : -INFINITY;
    const float o0 = ok0 ? (lo0 ? c[2][2] : c[3][2]) : -INFINITY, o1 = ok1 ? (lo1 ? c[2][3] : c[3][3]) : -INFINITY;
    float me = fmaxf(e0, e1), mo = fmaxf(o0, o1);
    me = fmaxf(me, __shfl_xor_sync(0xffffffffu, me, 1));
    mo = fmaxf(mo, __shfl_xor_sync(0xffffffffu, mo, 1));
    me = fmaxf(me, __shfl_xor_sync(0xffffffffu, me, 2)) * scale_l2;
    mo = fmaxf(mo, __shfl_xor_sync(0xffffffffu, mo, 2)) * scale_l2;
    const float w0 = ex2(fmaf(e0, scale_l2, -me)), w1 = ex2(fmaf(e1, scale_l2, -me));
    const float w2 = ex2(fmaf(o0, scale_l2, -mo)), w3 = ex2(fmaf(o1, scale_l2, -mo));
    float se = w0 + w1, so = w2 + w3;
    se += __shfl_xor_sync(0xffffffffu, se, 1);
    so += __shfl_xor_sync(0xffffffffu, so, 1);
    se += __shfl_xor_sync(0xffffffffu, se, 2);
    so += __shfl_xor_sync(0xffffffffu, so, 2);
    asm("rcp.approx.ftz.f32 %0, %0;" : "+f"(se));
    asm("rcp.approx.ftz.f32 %0, %0;" : "+f"(so));
    se *= g0;
    so *= g1;
    pe[i] = pack_bf16(w0 * se, w1 * se);
    po[i] = pack_bf16(w2 * so, w3 * so);
  }
  if (warp_g == 0) TS(0, 4);
  mbar_wait(bL2, 0);
  if (warp_g == 0) TS(0, 5);
#pragma unroll
  for (int c = 0; c < 9; c++)
    asm volatile("ldmatrix.sync.aligned.m8n8.x4.trans.shared.b16 {%0, %1, %2, %3}, [%4];"
                 : "=r"(k[c][0]), "=r"(k[c][1]), "=r"(k[c][2]), "=r"(k[c][3]) : "r"(ad[c] + LV) : "memory");
#pragma unroll
  for (int i = 0; i < 4; i++) {
#pragma unroll
    for (int n = 0; n < 3; n++) {
      float c[4] = {0.f, 0.f, 0.f, 0.f};
      mma16(c, pe[i] & mlo, 0u, pe[i] & ~mlo, 0u, k[2 * i + n][0], k[2 * i + n][1]);
      mma16(c, 0u, po[i] & mlo, 0u, po[i] & ~mlo, k[2 * i + n][2], k[2 * i + n][3]);
      const uint32_t r0 = pack_bf16(c[0], c[1]), r1 = pack_bf16(c[2], c[3]);
      const bool keep = (n == 0) && (t < i);
      qf[2 * i + n][0] = keep ? qf[2 * i + n][0] : r0;
      qf[2 * i + n][1] = keep ? qf[2 * i + n][1] : r1;
    }
  }
#pragma unroll
  for (int c = 0; c < 9; c++)
    asm volatile("stmatrix.sync.aligned.m8n8.x2.shared.b16 [%0], {%1, %2};" ::"r"(ad[c] + LQ), "r"(qf[c][0]), "r"(qf[c][1]) : "memory");
  asm volatile("fence.proxy.async.shared::cta;" ::: "memory");
}
__device__ __forceinline__ void tma4d(uint32_t dst, const CUtensorMap* m, uint32_t bar, int c1, int c2, int c3) {
  asm volatile("cp.async.bulk.tensor.4d.shared::cluster.global.mbarrier::complete_tx::bytes [%0], [%1, {%3, %4, %5, %6}], [%2];" ::"r"(dst),
               "l"(m), "r"(bar), "r"(0), "r"(c1), "r"(c2), "r"(c3) : "memory");
}

#define K1_NST 6
constexpr int K1_BST = K1_NST;
#define MAXJ 11
constexpr int K1_MAXJOBS = MAXJ;
constexpr uint32_t K1_FLAG_TARGET = 7;
constexpr uint32_t RDY_TARGET = 48;
constexpr uint32_t GATE_TARGET = 128 * 3;
struct alignas(64) Params {
  CUtensorMap tmA[2];
  CUtensorMap tmW[4];
  CUtensorMap tmQ, tmK, tmV;
  CUtensorMap tmL[3];
  CUtensorMap tmC, tmO[2], tmOt[2];
  uint16_t jobs[NCLUSTER][K1_MAXJOBS + 1];
  uint8_t order[256];
  uint8_t unit[64][8];
};

struct K1State {
  uint32_t bs, bph, aph;
  bf16* pp;
  int pld8;
  int png;
  int tn;
  int wsel;
};
__device__ __forceinline__ void k1_flag(const K1State& st, int lane, uint32_t bS) {
  if (st.png) {
    __syncwarp();
    if (lane == 0) mbar_arrive(bS);
  }
}

__device__ __forceinline__ void scale_q4(uint32_t* v) {
#pragma unroll
  for (int i = 0; i < 4; i++)
    asm volatile("{\n.reg .b32 t;\nmul.rn.bf16x2 t, %0, %2;\nfma.rn.bf16x2 %0, %0, %1, t;\n}" : "+r"(v[i]) : "r"(0x3E033E03u), "r"(0xB9D8B9D8u));
}
__device__ __forceinline__ void k1_first(const K1State& st, uint32_t job, uint32_t bAf, uint32_t bBf) {
  if (job & 3) {
    if ((job >> 14) & 1) mbar_wait(bAf, st.aph);
    mbar_wait(bBf + st.bs * 8, st.bph);
  }
}
__device__ __forceinline__ void k1_tile(float (&acc)[128], uint32_t (&pk)[64], K1State& st, uint32_t job, uint32_t njob, uint32_t sA, uint32_t sB,
                                        uint32_t bAf, uint32_t bAe, uint32_t bBf, uint32_t bBe, uint32_t bS, int wg, int warp, int lane, uint32_t rank) {
  const int a_sel = (job >> 2) & 1, mpair = (job >> 3) & 7, w_sel = (job >> 6) & 3, chunk0 = (job >> 8) & 63;
  const bool newA = (job >> 14) & 1, lastA = (job >> 15) & 1;
  const bool sig = (lane == 0) && (warp < 2);
  const bool siga = lastA && (lane == 0) && (warp == 2);
  const int KC = 8 + a_sel;
  uint32_t prev_bs = 0, a8_bs = 0;
#pragma unroll
  for (int kc = 0; kc < 9; kc++) {
    if (kc >= KC) break;
    uint32_t abase = sA + ((kc + 2) & 7) * 16384;
    if (kc == 8) {
      mbar_wait(bBf + st.bs * 8, st.bph);
      a8_bs = st.bs;
      abase = sB + st.bs * 16384;
      if (++st.bs == K1_BST) { st.bs = 0; st.bph ^= 1; }
    } else if (newA && kc > 0) {
      mbar_wait(bAf + kc * 8, st.aph);
    }
    const uint64_t da = make_desc(abase + wg * 8192, 16, 1024, 1);
#pragma unroll
    for (int ks = 0; ks < 2; ks++) {
      if (ks > 0 || kc > 0) mbar_wait(bBf + st.bs * 8, st.bph);
      const uint64_t db = make_desc(sB + st.bs * 16384, 2048, 1024, 1);
      wg_fence();
      wgmma_ss_n256<1, 0>(acc, da + (uint64_t)(ks * 4), db, (ks > 0) ? 1 : (kc > 0));
      wgmma_ss_n256<1, 0>(acc, da + (uint64_t)(ks * 4 + 2), db + (uint64_t)512, 1);
      wg_commit();
      const int PO = (kc < 8 ? kc : 0) * 8;
      wg_wait<1>();
      if (ks > 0 || kc > 0) {
        if (sig) mbar_arrive_cluster(bBe + prev_bs * 8, warp);
        if (ks == 0 && siga) mbar_arrive(bAe + (kc - 1) * 8);
      }
      if (kc < 8 && st.wsel >= 2) {
        if (st.wsel == 3) scale_q4(pk + PO + ks * 4);
        else quad_transpose(pk[PO + ks * 4], pk[PO + ks * 4 + 1], pk[PO + ks * 4 + 2], pk[PO + ks * 4 + 3], lane & 3);
      }
      if (kc < st.png) st_v4a(st.pp + kc * 32 + ks * st.pld8, pk[PO + ks * 4], pk[PO + ks * 4 + 1], pk[PO + ks * 4 + 2], pk[PO + ks * 4 + 3]);
      prev_bs = st.bs;
      if (++st.bs == K1_BST) { st.bs = 0; st.bph ^= 1; }
    }
  }
  if (newA) st.aph ^= 1;
  k1_flag(st, lane, bS);
  const bool isA = (w_sel == 2);
  bf16* out = (w_sel == 0) ? g_K : (w_sel == 1) ? g_V : isA ? g_QKVA : g_Q;
  const int ld = isA ? NQKVA : HDIM;
  const int row = mpair * 256 + rank * 128 + wg * 64 + warp * 16 + (lane >> 2);
  st.pp = out + (size_t)row * ld + chunk0 * 64 + (lane & 3) * 8;
  st.pld8 = 8 * ld;
  st.png = ((job & 3) + 1) * 2;
  st.wsel = w_sel;
  k1_first(st, njob, bAf, bBf);
  wg_wait<0>();
  fence_regs(acc);
  mbar_arrive_cluster_if(bBe + prev_bs * 8, warp & 1, sig);
  mbar_arrive_cluster_if(bBe + a8_bs * 8, warp & 1, sig && a_sel);
  mbar_arrive_if(bAe + 7 * 8, siga && !a_sel);
#pragma unroll
  for (int i = 0; i < 64; i++) {
    const int j = (i >> 3) * 16 + (i & 3) * 4 + ((i >> 2) & 1) * 2;
    pk[i] = pack_bf16(acc[j], acc[j + 1]);
  }
}

constexpr int K2_NST = 7;
constexpr uint32_t K2_END = 0x100;
#define PF_KC 4
#define FIRST_DRAW 3
#define PWAIT mbar_wait_ns<1000>
#define PVM 0x8A
#define W0 63
#define SPEC_HI 1.8446744073709552e19f
#define SPEC_LO 5.421010862427522e-20f
constexpr int K3_NST = 4;
__device__ __forceinline__ uint32_t k3_rot(uint32_t sv) { return (0x00E9u >> (2 * sv)) & 3; }
constexpr int K3_STAGE = 16384 + 32768 + 4096;
constexpr int SMEM_DATA = 7 * 32768;
constexpr int SMEM_BYTES = SMEM_DATA + 1024 + 768;

struct Cursor {
  uint32_t s, ph;
  __device__ __forceinline__ void next() {
    if (++s == K2_NST) { s = 0; ph ^= 1; }
  }
};

#define TURN_SYNC() bar_sync(mybar, 256)
#define TURN_ARRIVE() bar_arrive(otherbar, 256)
#define RELEASE_IF(cur, cond) mbar_arrive_cluster_if(bE + (cur).s * 8, warp & 1, sig && (cond))
#define RELEASE(cur) RELEASE_IF(cur, true)
#define ISSUE_PV(cur, first)                                                                                   \
  do {                                                                                                         \
    const uint64_t dv = make_desc(sbase + (cur).s * 32768, 16384, 1024, 1);                                    \
    _Pragma("unroll") for (int t = 0; t < 8; t++)                                                              \
        wgmma_rs_n128<1, 0>(O, P[4 * t], P[4 * t + 1], P[4 * t + 2], P[4 * t + 3], dv + (uint64_t)(t * 128), (t > 0) ? 1 : !(first)); \
  } while (0)
#define ISSUE_QK(cur)                                                                                          \
  do {                                                                                                         \
    const uint64_t dk = make_desc(sbase + (cur).s * 32768, 16, 1024, 1);                                       \
    _Pragma("unroll") for (int t = 0; t < 8; t++)                                                              \
        wgmma_rs_n128<0, 0>(S, Q[4 * t], Q[4 * t + 1], Q[4 * t + 2], Q[4 * t + 3], dk + (uint64_t)((t >> 2) * 1024 + (t & 3) * 2), t > 0); \
  } while (0)
#define EXPB(T)                                                                                                \
  do {                                                                                                         \
    _Pragma("unroll") for (int i = 4 * T; i < 4 * T + 4; i++) asm volatile("" : "+r"(P[i])::"memory");        \
    _Pragma("unroll") for (int jj = 2 * T; jj < 2 * T + 2; jj++) {                                             \
      const float e0 = ex2(S[jj * 4 + 0]), e1 = ex2(S[jj * 4 + 1]), e2 = ex2(S[jj * 4 + 2]), e3 = ex2(S[jj * 4 + 3]); \
      s0 += e0 + e1;                                                                                           \
      s1 += e2 + e3;                                                                                           \
      P[jj * 2 + 0] = pack_bf16(e0, e1);                                                                       \
      P[jj * 2 + 1] = pack_bf16(e2, e3);                                                                       \
    }                                                                                                          \
  } while (0)
#define EXPC(T)                                                                                                \
  do {                                                                                                         \
    if (T > 0 && ((PVM >> (T - 1)) & 1)) {                                                                     \
      anchor((T & 2) ? s0 : s1, never);                                                                        \
      wg_wait<__builtin_popcount(PVM >> T) - 1>();                                                             \
      if ((PVM >> T) == (128 >> T)) { fence_regs(O); RELEASE(cv); }                                            \
    }                                                                                                          \
    EXPB(T);                                                                                                   \
  } while (0)
#define MASK(G, g)                                                                                             \
  do {                                                                                                         \
    if ((g) * 8 > d) S[(G) * 4 + 0] = -INFINITY;                                                               \
    if ((g) * 8 + 1 > d) S[(G) * 4 + 1] = -INFINITY;                                                           \
    if ((g) * 8 - 8 > d) S[(G) * 4 + 2] = -INFINITY;                                                           \
    if ((g) * 8 - 7 > d) S[(G) * 4 + 3] = -INFINITY;                                                           \
  } while (0)
#define STORE_O(G)                                                                                             \
  do {                                                                                                         \
    st_v4(g_ctx + eoff + (G) * 32, pack_bf16(O[(G) * 16 + 0] * f0, O[(G) * 16 + 1] * f0), pack_bf16(O[(G) * 16 + 4] * f0, O[(G) * 16 + 5] * f0), \
          pack_bf16(O[(G) * 16 + 8] * f0, O[(G) * 16 + 9] * f0), pack_bf16(O[(G) * 16 + 12] * f0, O[(G) * 16 + 13] * f0)); \
    st_v4(g_ctx + eoff + 8 * KCAT + (G) * 32, pack_bf16(O[(G) * 16 + 2] * f1, O[(G) * 16 + 3] * f1), pack_bf16(O[(G) * 16 + 6] * f1, O[(G) * 16 + 7] * f1), \
          pack_bf16(O[(G) * 16 + 10] * f1, O[(G) * 16 + 11] * f1), pack_bf16(O[(G) * 16 + 14] * f1, O[(G) * 16 + 15] * f1)); \
  } while (0)

#define FLUSH()                                                                                                \
  do {                                                                                                         \
    _Pragma("unroll") for (int G = 0; G < 8; G++) {                                                            \
      st_v4a(st.pp + G * 32, pk[G * 8], pk[G * 8 + 1], pk[G * 8 + 2], pk[G * 8 + 3]);                          \
      st_v4a(st.pp + G * 32 + 8 * HDIM, pk[G * 8 + 4], pk[G * 8 + 5], pk[G * 8 + 6], pk[G * 8 + 7]);           \
    }                                                                                                          \
    k1_flag(st, lane, bS);                                                                                     \
  } while (0)

__global__ void __cluster_dims__(2, 1, 1) __launch_bounds__(384, 1)
fused_kernel(const __grid_constant__ Params p, const bf16* __restrict__ x, const bf16* __restrict__ gate_w, bf16* __restrict__ out) {
  extern __shared__ uint8_t smem_raw[];
  const uint32_t sbase = (smem_u32(smem_raw) + 1023) & ~1023u;
  const uint32_t sB = sbase, sA = sbase + K1_BST * 16384, sBar = sbase + SMEM_DATA;
  const uint32_t bAf = sBar, bAe = sBar + 64, bBf = sBar + 128, bBe = sBar + 176, bL = sBar + 224, bS = sBar + 232, bL2 = sBar + 240, sL = sA + 32768;
  const uint32_t bF = sBar + 256, bE = sBar + 320, bT = sBar + 384, sTick = sBar + 400, sItem = sBar + 416, bS2 = sBar + 448, bR = sBar + 456, bLast = sBar + 464, bH = sBar + 472, bT0 = sBar + 480;
  const uint32_t b3F = sBar + 512, b3E = sBar + 544, sGate = sBar + 576;
  const int tid = threadIdx.x, warp_g = __shfl_sync(0xffffffffu, tid >> 5, 0), lane = tid & 31;
  const uint32_t rank = cluster_rank();
  const int cl = blockIdx.x >> 1;
  TSM(0);
  if (tid == 0) {
    for (int i = 0; i < 8; i++) { mbar_init(bAf + i * 8, 1); mbar_init(bAe + i * 8, 2); }
    for (int i = 0; i < K1_BST; i++) { mbar_init(bBf + i * 8, 1); mbar_init(bBe + i * 8, 4); }
    mbar_init(bL, 1);
    mbar_init(bL2, 1);
    mbar_init(bR, 1);
    mbar_init(bLast, 1);
    mbar_init(bH, 4);
    mbar_init(bT0, 1);
    mbar_init(bS, 8);
    for (int i = 0; i < K2_NST; i++) { mbar_init(bF + i * 8, 1); mbar_init(bE + i * 8, 4); }
    mbar_init(bT, 1); mbar_init(bT + 8, 1);
    mbar_init(bS2, 8);
    for (int i = 0; i < K3_NST; i++) { mbar_init(b3F + i * 8, 1); mbar_init(b3E + i * 8, 4); }
    asm volatile("fence.mbarrier_init.release.cluster;" ::: "memory");
  }
  __syncwarp();
  if (warp_g != 8) cluster_sync();
  const int lr0 = blockIdx.x * 16;

  if (warp_g >= 8) {
    reg_dealloc<40>();
    if (warp_g == 8) {
      {
        const uint32_t job = p.jobs[cl][0];
        if (lane == 0) { prefetch_tmap(&p.tmA[(job >> 2) & 1]); prefetch_tmap(&p.tmW[(job >> 6) & 3]); }
        __syncwarp();
        cluster_sync();
      }
      if (elect_one()) {
        uint32_t bs = 0, bph = 1, aph = 1;
#pragma unroll 1
        for (int ji = 0; ji < K1_MAXJOBS; ji++) {
          const uint32_t job = p.jobs[cl][ji];
          if (!(job & 3)) break;
          const int a_sel = (job >> 2) & 1, mpair = (job >> 3) & 7, chunk0 = (job >> 8) & 63;
          const bool newA = (job >> 14) & 1;
          const int KC = a_sel ? 9 : 8;
          const uint32_t halfbytes = 8192;
          const bool lastjob = (ji + 1 == K1_MAXJOBS) || !(p.jobs[cl][ji + 1] & 3);
          const CUtensorMap* tw = &p.tmW[(job >> 6) & 3];
          {
            const uint32_t njob = (ji + 1 < K1_MAXJOBS) ? p.jobs[cl][ji + 1] : 0;
            if (!(njob & 3) && !newA) mbar_arrive(bLast);
          }
#pragma unroll 1
          for (int kc = 0; kc < KC; kc++) {
            if (kc == ((ji == 0) ? PF_KC : 0) && !lastjob) {
              const uint32_t njob = p.jobs[cl][ji + 1];
              const int nst = ((njob >> 2) & 1) ? 18 : 16;
#pragma unroll 1
              for (int t = (cl < 64) ? (cl & 7) : 0; t < nst; t += (cl < 64) ? 8 : 1)
                tma_pf3d(&p.tmW[(njob >> 6) & 3], 0, t * 32 + rank * 16, (njob >> 8) & 63);
            }
            if (kc == 8) {
              PWAIT(bBe + bs * 8, bph);
              mbar_expect(bBf + bs * 8, 16384);
              tma2d(sB + bs * 16384, &p.tmA[1], bBf + bs * 8, 512, mpair * 256 + rank * 128);
              if (++bs == K1_BST) { bs = 0; bph ^= 1; }
            } else if (newA) {
              PWAIT(bAe + kc * 8, aph);
              mbar_expect(bAf + kc * 8, 16384);
              tma2d(sA + ((kc + 2) & 7) * 16384, &p.tmA[a_sel], bAf + kc * 8, kc * 64, mpair * 256 + rank * 128);
              if (kc == 7 && lastjob) mbar_arrive(bLast);
            }
#pragma unroll 1
            for (int kk = 0; kk < 2; kk++) {
              PWAIT(bBe + bs * 8, bph);
              mbar_expect(bBf + bs * 8, 2 * halfbytes);
              tma3d_mc(sB + bs * 16384 + rank * halfbytes, tw, bBf + bs * 8, 0, kc * 64 + kk * 32 + rank * 16, chunk0, 3);
              if (++bs == K1_BST) { bs = 0; bph ^= 1; }
            }
          }
          if (newA) aph ^= 1;
        }
        Cursor c{0, 0};
        int pcol = 0;
        PWAIT(bR, 0);
        uint32_t tick = lds32(sTick + 8), seen = 1u << (p.order[tick] >> 4);
        asm volatile("fence.proxy.async.global;" ::: "memory");
#pragma unroll 1
        for (int it = 0;; it++) {
          const uint32_t item = (tick < 256) ? p.order[tick] : (K2_END | min(tick - 256, 255u));
          asm volatile("st.shared.u32 [%0], %1;" ::"r"(sItem + (it & 7) * 4), "r"(item) : "memory");
          if (item >= K2_END) break;
          const int h = item >> 3, j = item & 7;
          const int blk = 2 * j + (int)(rank ^ (it & 1));
          const int col = h * 128 + rank * 64;
          const int nb = 2 * j + 2;
          if (!((seen >> (h >> 1)) & 1)) {
            wait_flag(&g_sync[F_HP + (h >> 1)], RDY_TARGET);
            asm volatile("fence.proxy.async.global;" ::: "memory");
            seen |= 1u << (h >> 1);
          }
          PWAIT(bE + c.s * 8, c.ph);
          mbar_expect(bF + c.s * 8, 32768);
          tma2d(sbase + c.s * 32768, &p.tmQ, bF + c.s * 8, h * 128, blk * 128);
          tma2d(sbase + c.s * 32768 + 16384, &p.tmQ, bF + c.s * 8, h * 128 + 64, blk * 128);
          c.next();
#pragma unroll 1
          for (int n = nb - 1; n >= 0; n--) {
            if (n == 0 && rank == 0) tick = atomicAdd(&g_sync[F_TICK], 1u);
            PWAIT(bE + c.s * 8, c.ph);
            mbar_expect(bF + c.s * 8, 32768);
            tma2d_mc(sbase + c.s * 32768 + rank * 16384, &p.tmK, bF + c.s * 8, col, n * 128, 3);
            c.next();
            if (n < nb - 1 || it > 0) {
              PWAIT(bE + c.s * 8, c.ph);
              mbar_expect(bF + c.s * 8, 32768);
              tma2d_mc(sbase + c.s * 32768 + rank * 16384, &p.tmV, bF + c.s * 8, (n < nb - 1) ? col : pcol, (n < nb - 1) ? (n + 1) * 128 : 0, 3);
              c.next();
            }
          }
          pcol = col;
          if (rank == 0) {
            asm volatile(
                "{\n.reg .b32 a, b;\nmapa.shared::cluster.u32 a, %0, 1;\nmapa.shared::cluster.u32 b, %1, 1;\n"
                "st.async.shared::cluster.mbarrier::complete_tx::bytes.u32 [a], %2, [b];\n}" ::"r"(sTick + (it & 1) * 4),
                "r"(bT + (it & 1) * 8), "r"(tick) : "memory");
          } else {
            mbar_expect(bT + (it & 1) * 8, 4);
            PWAIT(bT + (it & 1) * 8, (it >> 1) & 1);
            tick = lds32(sTick + (it & 1) * 4);
          }
        }
        PWAIT(bE + c.s * 8, c.ph);
        mbar_expect(bF + c.s * 8, 32768);
        tma2d_mc(sbase + c.s * 32768 + rank * 16384, &p.tmV, bF + c.s * 8, pcol, 0, 3);
        const uint32_t unit = tick - 256;
        if (unit < 64) {
          const int mblk = (7 - (p.unit[unit][0] >> 1)) * 2 + rank, nhalf = p.unit[unit][0] & 1;
          const uint32_t rot = k3_rot(c.s), nfree = ((0x1Au >> c.s) & 1) ? 2 : 3;
#pragma unroll 1
          for (int i = 0; i < K2_NST - 1; i++) {
            c.next();
            PWAIT(bE + c.s * 8, c.ph);
          }
          uint32_t have = 0;
#pragma unroll 1
          for (uint32_t idx = 0; idx < p.unit[unit][2]; idx++) {
            const int kk = p.unit[unit][3] + idx + ((idx >= p.unit[unit][4]) ? p.unit[unit][5] : 0);
            const uint32_t s = (rot + idx) & 3;
            if (idx >= nfree) PWAIT((idx < 4) ? bH : b3E + s * 8, (idx < 4) ? 0 : (~idx >> 2) & 1);
            mbar_expect(b3F + s * 8, K3_STAGE);
            const uint32_t st = sbase + s * K3_STAGE;
            const int sel = (kk < 9), k = sel ? kk : kk - 9, kr = k * 64 + rank * 32;
            tma3d_mc(st + 16384 + rank * 16384, &p.tmO[sel], b3F + s * 8, 0, kr, nhalf * 4, 3);
            tma2d_mc(st + 49152 + rank * 2048, &p.tmOt[sel], b3F + s * 8, 512 + nhalf * 32, kr, 3);
            if (sel && idx == 0) {
              wait_flag(&g_sync[F_OA + mblk], 8);
              asm volatile("fence.proxy.async.global;" ::: "memory");
            }
            if (!sel && !((have >> (k >> 1)) & 1)) {
#pragma unroll 1
              for (uint32_t spins = 0; spins < (1u << 22); spins++) {
                asm volatile("ld.acquire.gpu.global.u32 %0, [%1];" : "=r"(have) : "l"(&g_sync[F_CTX + mblk]) : "memory");
                if ((have >> (k >> 1)) & 1) break;
                __nanosleep(100);
              }
              asm volatile("fence.proxy.async.global;" ::: "memory");
            }
            tma2d(st, &p.tmC, b3F + s * 8, (sel ? 64 + k : k) * 64, mblk * 128);
          }
        }
      }
    }
    __syncwarp();
    if (warp_g == 8) {
      uint32_t v = 0;
      if (lane == 0) {
        __threadfence();
        v = atomicAdd(&g_sync[F_DONE], 1u);
      }
      if (__shfl_sync(0xffffffffu, v, 0) == 2 * NCLUSTER - 1) {
        reinterpret_cast<uint4*>(g_sync)[lane] = make_uint4(0, 0, 0, 0);
        if (lane == 0) g_sync[F_EPOCH] = lds32(sGate + 64) + 1;
      }
    }
    asm volatile("" ::: "memory");
    if (__shfl_sync(0xffffffffu, warp_g, 0) != 8) {
      if (lr0 < S_LEN) {
#pragma unroll 1
        for (int i = warp_g - 9; i < 16; i += 3) {
          const float g = gate_row(lr0 + i, lane, x, gate_w);
          if (lane == 0) asm volatile("st.shared.f32 [%0], %1;" ::"r"(sGate + i * 4), "f"(g) : "memory");
        }
        bar_arrive(3, 256 + 96);
        if (lane == 0) {
          __threadfence();
          atomicAdd(&g_sync[F_GATE], 1u);
        }
      }
      uint32_t aph = 1;
#pragma unroll 1
      for (int ji = 0; ji < K1_MAXJOBS; ji++) aph ^= (p.jobs[cl][ji] >> 14) & 1;
      if (warp_g == 9 && lane == 0) {
#pragma unroll 1
        for (int ji = 0; ji < K1_MAXJOBS; ji++) {
          const uint32_t job = p.jobs[cl][ji];
          if (!(job & 3)) break;
          PWAIT(bS, ji & 1);
          __threadfence();
          atomicAdd(&g_sync[(((job >> 6) & 3) == 2) ? (F_QKVA + ((job >> 3) & 7) * 2 + rank) : (F_HP + ((job >> 10) & 15))], 1u);
        }
#pragma unroll 1
        for (int it = 0;; it++) {
          PWAIT(bS2, it & 1);
          const uint32_t item = lds32(sItem + (it & 7) * 4), nxt = lds32(sItem + ((it + 1) & 7) * 4);
          __threadfence();
          atomicOr(&g_sync[F_CTX + (item & 7) * 2 + (rank ^ (it & 1))], 1u << (item >> 3));
          if (nxt >= K2_END) break;
        }
      } else if (warp_g == 11) {
        if (lane == 0) {
          prefetch_tmap(&p.tmQ); prefetch_tmap(&p.tmK); prefetch_tmap(&p.tmV);
          asm volatile("st.shared.u32 [%0], %1;" ::"r"(sGate + 64), "r"(__ldcg(&g_sync[F_EPOCH])) : "memory");
          wait_flag(&g_sync[F_GATE], GATE_TARGET);
          uint32_t tick;
          if (rank == 0) {
            PWAIT(bLast, 0);
            PWAIT(bAe + FIRST_DRAW * 8, aph);
            tick = atomicAdd(&g_sync[F_TICK], 1u);
            asm volatile("st.shared.u32 [%0], %1;" ::"r"(sTick + 8), "r"(tick) : "memory");
            asm volatile(
                "{\n.reg .b32 a, b;\nmapa.shared::cluster.u32 a, %0, 1;\nmapa.shared::cluster.u32 b, %1, 1;\n"
                "st.async.shared::cluster.mbarrier::complete_tx::bytes.u32 [a], %2, [b];\n}" ::"r"(sTick + 8), "r"(bT0), "r"(tick) : "memory");
          } else {
            mbar_expect(bT0, 4);
            PWAIT(bT0, 0);
            tick = lds32(sTick + 8);
          }
          wait_flag(&g_sync[F_HP + (p.order[tick] >> 4)], RDY_TARGET);
          mbar_arrive(bR);
        }
      } else if (warp_g == 10) {
        if (lr0 < S_LEN && lane == 0) {
          prefetch_tmap(&p.tmL[0]); prefetch_tmap(&p.tmL[1]); prefetch_tmap(&p.tmL[2]);
          wait_flag(&g_sync[F_QKVA + (lr0 >> 7)], K1_FLAG_TARGET);
          wait_flag(&g_sync[F_QKVA + (max(lr0 - 16, 0) >> 7)], K1_FLAG_TARGET);
          asm volatile("fence.proxy.async.global;" ::: "memory");
          PWAIT(bLast, 0);
#pragma unroll 1
          for (int kc = 0; kc < 6; kc++) {
            PWAIT(bAe + kc * 8, aph);
            if (kc == 3) {
              mbar_expect(bL, LV);
              tma4d(sL, &p.tmL[0], bL, lr0 / 2 - 8, 9, 0);
              tma4d(sL + LQ, &p.tmL[1], bL, lr0 / 2, 0, 0);
            }
          }
          mbar_expect(bL2, LQ);
          tma4d(sL + LV, &p.tmL[0], bL2, lr0 / 2 - 8, 18, 0);
        }
        __syncwarp();
        bar_sync(5, 256 + 32);
        if (lr0 < S_LEN && lane == 0) {
          asm volatile("cp.async.bulk.tensor.4d.global.shared::cta.bulk_group [%0, {%2, %3, %2, %2}], [%1];" ::"l"(&p.tmL[2]), "r"(sL + LQ), "r"(0), "r"(lr0 / 2) : "memory");
          asm volatile("cp.async.bulk.commit_group;" ::: "memory");
          asm volatile("cp.async.bulk.wait_group.read 0;" ::: "memory");
        }
        __syncwarp();
        if (lane < 12) mbar_arrive_cluster(bE + (4 + lane % 3) * 8, (lane / 3) & 1);
        if (lr0 < S_LEN && lane == 0) {
          asm volatile("cp.async.bulk.wait_group 0;" ::: "memory");
          asm volatile("fence.proxy.async.global;" ::: "memory");
          __threadfence();
          atomicAdd(&g_sync[F_OA + (lr0 >> 7)], 1u);
        }
      }
    }
    __syncwarp();
    cluster_sync();
  } else {
    reg_alloc<232>();
    const int wg = warp_g >> 2, warp = warp_g & 3, q = lane & 3;
    const bool sig = (lane == 0) && (warp < 2);
    {
      K1State st{0, 0, 0, nullptr, 0, 0, 0, 0};
      float acc[128];
      uint32_t pk[64];
      if (wg == 0) { TS(0, 0); TSC(0, 2); }
      uint32_t job = p.jobs[cl][0];
      k1_first(st, job, bAf, bBf);
      {
#pragma unroll 1
        for (int ji = 0; job & 3; ji++) {
          const uint32_t njob = p.jobs[cl][ji + 1];
          k1_tile(acc, pk, st, job, njob, sA, sB, bAf, bAe, bBf, bBe, bS, wg, warp, lane, rank);
          job = njob;
        }
      }
#pragma unroll
      for (int i = 0; i < 4; i++)
        mbar_arrive_cluster_if(bE + i * 8, warp & 1, sig);
      if (lr0 < S_LEN) bar_sync(3, 256 + 96);
      if (st.wsel == 3) {
#pragma unroll
        for (int G = 0; G < 16; G++) scale_q4(pk + G * 4);
      }
      FLUSH();
      if (wg == 0) { TS(0, 1); TSC(0, 3); }
      if (lr0 < S_LEN) {
        const float gate0 = __uint_as_float(lds32(sGate + (lane >> 2) * 8)), gate1 = __uint_as_float(lds32(sGate + (lane >> 2) * 8 + 4));
        local_attn(lr0, warp_g, sL, bL, bL2, lane, gate0, gate1);
      }
      bar_arrive(5, 256 + 32);
    }
    __syncwarp();
    uint32_t item, rot;
    {
      const int mybar = 1 + wg, otherbar = 2 - wg;
      const uint32_t never = blockIdx.y;
      float S[64], O[64];
      uint32_t P[32], Q[32];
      float m0 = 0.f, m1 = 0.f, l0 = 1.f, l1 = 1.f, gf0 = 0.f, gf1 = 0.f;
      uint32_t eoff = 0, prev_single = 0;
      Cursor c{0, 0};
      if (wg == 1) bar_arrive(1, 256);
      if (wg == 0) { TS(1, 0); TSC(1, 2); }
#pragma unroll 1
      for (int it = 0;; it++) {
        TB(0);
        const int hi = (int)(rank ^ (it & 1));
        Cursor cq = c, ck, cv, cs0, cs1;
        rot = k3_rot(c.s);
        c.next();
        ck = c; c.next();
        cs0 = ck; cs1 = ck; cv = ck;
        if (it > 0) { cv = c; c.next(); }
        if (!hi) {
          ck = c; c.next();
          cs1 = c; c.next();
        }
        mbar_wait(bF + cq.s * 8, cq.ph);
        TB(1);
        item = lds32(sItem + (it & 7) * 4);
        {
          const uint32_t qa = sbase + cq.s * 32768 + (wg * 64 + warp * 16 + (lane & 15)) * 128;
#pragma unroll
          for (int t = 0; t < 8; t++)
            ldsm_x4(Q[4 * t], Q[4 * t + 1], Q[4 * t + 2], Q[4 * t + 3], qa + (t >> 2) * 16384 + ((((t & 3) * 2 + (lane >> 4)) ^ (lane & 7)) << 4));
        }
        const uint32_t rdy = mbar_test(bF + ck.s * 8, ck.ph) & mbar_test(bF + cv.s * 8, cv.ph);
        l0 += __shfl_xor_sync(0xffffffffu, l0, 1);
        l1 += __shfl_xor_sync(0xffffffffu, l1, 1);
        l0 += __shfl_xor_sync(0xffffffffu, l0, 2);
        l1 += __shfl_xor_sync(0xffffffffu, l1, 2);
        const bool last = item >= K2_END;
        if (last) {
          cv = cq; ck = cq;
        } else if (!rdy) {
          mbar_wait2(bF + ck.s * 8, ck.ph, bF + cv.s * 8, cv.ph);
        }
        TB(2);
        TURN_SYNC();
        TB(3);
        TRC(last ? 2 : 1);
        if (it > 0) {
          wg_fence();
          ISSUE_PV(cv, prev_single);
          wg_commit();
        } else {
          wg_fence();
          wg_commit();
        }
        wg_fence();
        ISSUE_QK(ck);
        wg_commit();
        if (!(last && wg == 1)) TURN_ARRIVE();
        RELEASE_IF(cq, !last);
        TB(4);
        asm volatile("" : "+f"(gf0), "+f"(gf1), "+f"(l0), "+f"(l1));
        const float f0 = __fdividef(1.f - gf0, l0), f1 = __fdividef(1.f - gf1, l1);
        wg_wait<1>();
        fence_regs(O);
        fence_regs(P);
        TB(5);
        if (it > 0) {
          RELEASE_IF(cv, !last);
          mbar_arrive_cluster_if(bH, warp & 1, sig && last);
          STORE_O(0); STORE_O(1); STORE_O(2); STORE_O(3);
          __syncwarp();
          mbar_arrive_if(bS2, lane == 0);
        }
        TB(6);
        if (!last) {
          const int row = (2 * (item & 7) + hi) * 128 + wg * 64 + warp * 16 + (lane >> 2);
          eoff = row * KCAT + (item >> 3) * 128 + q * 8;
          asm volatile("ld.global.f32 %0, [%1];" : "=f"(gf0) : "l"(g_gate + row));
          asm volatile("ld.global.f32 %0, [%1];" : "=f"(gf1) : "l"(g_gate + row + 8));
          if (!hi) {
            mbar_wait2(bF + cs0.s * 8, cs0.ph, bF + cs1.s * 8, cs1.ph);
            RELEASE(cs0);
            RELEASE(cs1);
          }
        }
        TB(7);
        wg_wait<0>();
        fence_regs(S);
        TB(8);
        if (last) break;
        RELEASE(ck);
        const int nblk = 2 * (item & 7) + 1 + hi;
        prev_single = (nblk == 1);
        float s0 = 0.f, s1 = 0.f;
        l0 = 0.f; l1 = 0.f;
        m0 = 0.f; m1 = 0.f;
        bool shifted = false;
        {
          const int d = warp * 16 + (lane >> 2) - 2 * q;
          if (wg == 0) {
#pragma unroll
            for (int jj = 0; jj < 8; jj++) MASK(jj, jj);
            EXPB(0); EXPB(1); EXPB(2); EXPB(3);
#pragma unroll
            for (int i = 32; i < 64; i++) S[i] = -INFINITY;
#pragma unroll
            for (int i = 16; i < 32; i++) P[i] = 0;
          } else {
#pragma unroll
            for (int jj = 0; jj < 8; jj++) MASK(jj + 8, jj);
            EXPB(0); EXPB(1); EXPB(2); EXPB(3); EXPB(4); EXPB(5); EXPB(6); EXPB(7);
          }
        }
        float chk = (q == 0 && !(fminf(s0, s1) >= SPEC_LO)) ? INFINITY : s0 + s1;
        fence_regs(P);
        TB(9);
#pragma unroll 1
        for (int n = 1;; n++) {
          if (__any_sync(0xffffffffu, !(chk <= SPEC_HI))) {
            float mx0 = fmaxf(S[0], S[1]), mx1 = fmaxf(S[2], S[3]);
#pragma unroll
            for (int jj = 1; jj < 16; jj++) {
              mx0 = fmaxf(mx0, fmaxf(S[jj * 4 + 0], S[jj * 4 + 1]));
              mx1 = fmaxf(mx1, fmaxf(S[jj * 4 + 2], S[jj * 4 + 3]));
            }
            mx0 = fmaxf(mx0, __shfl_xor_sync(0xffffffffu, mx0, 1));
            mx1 = fmaxf(mx1, __shfl_xor_sync(0xffffffffu, mx1, 1));
            mx0 = fmaxf(mx0, __shfl_xor_sync(0xffffffffu, mx0, 2));
            mx1 = fmaxf(mx1, __shfl_xor_sync(0xffffffffu, mx1, 2));
            const float lo = (n == 1) ? -INFINITY : 0.f;
            mx0 = fmaxf(mx0, lo);
            mx1 = fmaxf(mx1, lo);
            m0 += mx0; m1 += mx1;
            shifted = true;
            const float sc0 = ex2(-fmaxf(mx0, 0.f)), sc1 = ex2(-fmaxf(mx1, 0.f));
            l0 *= sc0; l1 *= sc1;
            s0 = 0.f; s1 = 0.f;
#pragma unroll
            for (int jj = 0; jj < 16; jj++) {
              const float e0 = ex2(S[jj * 4 + 0] - mx0), e1 = ex2(S[jj * 4 + 1] - mx0), e2 = ex2(S[jj * 4 + 2] - mx1), e3 = ex2(S[jj * 4 + 3] - mx1);
              s0 += e0 + e1;
              s1 += e2 + e3;
              P[jj * 2 + 0] = pack_bf16(e0, e1);
              P[jj * 2 + 1] = pack_bf16(e2, e3);
              O[jj * 4 + 0] *= sc0;
              O[jj * 4 + 1] *= sc0;
              O[jj * 4 + 2] *= sc1;
              O[jj * 4 + 3] *= sc1;
            }
          }
          l0 += s0;
          l1 += s1;
          if (n >= nblk) break;
          ck = c; c.next();
          cv = c; c.next();
          mbar_wait(bF + ck.s * 8, ck.ph);
          mbar_wait(bF + cv.s * 8, cv.ph);
          TURN_SYNC();
          TRC(0);
          wg_fence();
          ISSUE_QK(ck);
          wg_commit();
          {
            const uint64_t dv = make_desc(sbase + cv.s * 32768, 16384, 1024, 1);
#pragma unroll
            for (int t = 0; t < 8; t++) {
              wgmma_rs_n128<1, 0>(O, P[4 * t], P[4 * t + 1], P[4 * t + 2], P[4 * t + 3], dv + (uint64_t)(t * 128), (t > 0) ? 1 : (n != 1));
              if ((PVM >> t) & 1) wg_commit();
            }
          }
          TURN_ARRIVE();
          s0 = 0.f; s1 = 0.f;
          wg_wait<__builtin_popcount(PVM)>();
          fence_regs(S);
          RELEASE(ck);
          if (shifted) {
#pragma unroll
            for (int i = 0; i < 64; i++) S[i] -= (i & 2) ? m1 : m0;
          }
          wg_wait<__builtin_popcount(PVM) - 1>();
          EXPC(0); EXPC(1); EXPC(2); EXPC(3); EXPC(4); EXPC(5); EXPC(6); EXPC(7);
          chk = s0 + s1;
        }
      }
      TRC(3);
      if (wg == 1) { TS(1, 1); TSC(1, 3); }
    }
    __syncwarp();
    const uint32_t unit = item & 255;
    if (unit < 64) {
      const int mblk = (7 - (p.unit[unit][0] >> 1)) * 2 + rank, nhalf = p.unit[unit][0] & 1, ks = p.unit[unit][1];
      const int k0 = 0, k1 = p.unit[unit][2];
      float acc[144];
      uint32_t s = rot, ph = 0, prev = 0;
      if (wg == 0) { TS(2, 0); TSC(2, 2); }
#pragma unroll 1
      for (int k = k0; k < k1; k++) {
        mbar_wait(b3F + s * 8, ph);
        const uint32_t st = sbase + s * K3_STAGE;
        const uint64_t da = make_desc(st + wg * 8192, 16, 1024, 1);
        const uint64_t db = make_desc(st + 16384, 4096, 1024, 1);
        const uint64_t dt = make_desc(st + 49152, 16, 512, 2);
        wg_fence();
#pragma unroll
        for (int t = 0; t < 4; t++) {
          const int sd = (t > 0) || (k > k0);
          wgmma_ss_n256<1, 0>(acc, da + (uint64_t)(t * 2), db + (uint64_t)((t >> 1) * 1024 + (t & 1) * 128), sd);
          wgmma_ss_n32<1, 128>(acc, da + (uint64_t)(t * 2), dt + (uint64_t)(t * 64), sd);
        }
        wg_commit();
        if (k > k0) {
          wg_wait<1>();
          if (sig) mbar_arrive_cluster(b3E + prev * 8, warp);
        }
        prev = s;
        s = (s + 1) & 3;
        if (s == rot) ph ^= 1;
      }
      wg_wait<0>();
      fence_regs(acc);
      cluster_arrive();
      if (wg == 0) TS(2, 4);
      const int tile = mblk * 2 + nhalf;
      uint4* wp = g_part + (size_t)((tile * 4 + ks) * 4) * 5 * 256 + tid;
      const uint32_t sown = sbase + wg * 8192 + (tid & 127) * 16;
#pragma unroll
      for (int d = 0; d < 4; d++) {
        if (d != ks) {
#pragma unroll
          for (int i = 0; i < 4; i++)
            __stcg(wp + (d * 5 + i) * 256,
                   make_uint4(pack_bf16(acc[d * 32 + i * 8], acc[d * 32 + i * 8 + 1]), pack_bf16(acc[d * 32 + i * 8 + 2], acc[d * 32 + i * 8 + 3]),
                              pack_bf16(acc[d * 32 + i * 8 + 4], acc[d * 32 + i * 8 + 5]), pack_bf16(acc[d * 32 + i * 8 + 6], acc[d * 32 + i * 8 + 7])));
          __stcg(reinterpret_cast<uint2*>(wp - tid + (d * 5 + 4) * 256) + tid,
                 make_uint2(pack_bf16(acc[128 + d * 4], acc[128 + d * 4 + 1]), pack_bf16(acc[128 + d * 4 + 2], acc[128 + d * 4 + 3])));
        } else {
#pragma unroll
          for (int i = 0; i < 9; i++) {
            const int o = (i < 8) ? d * 32 + i * 4 : 128 + d * 4;
            asm volatile("st.shared.v4.f32 [%0], {%1, %2, %3, %4};" ::"r"(sown + (i >> 2) * K3_STAGE + (i & 3) * 2048), "f"(acc[o]), "f"(acc[o + 1]), "f"(acc[o + 2]), "f"(acc[o + 3]) : "memory");
          }
        }
      }
      __threadfence();
      __syncwarp();
      if (wg == 0) TS(2, 5);
      if (lane == 0) {
        unsigned int* cnt = &g_sync[F_XCH + tile * 8 + warp_g];
        const uint32_t xtarget = lds32(sGate + 64) * 4 + 4;
        atomicAdd(cnt, 1u);
        uint32_t v, spins = 0;
        do {
          asm volatile("ld.acquire.gpu.global.u32 %0, [%1];" : "=r"(v) : "l"(cnt) : "memory");
        } while ((int)(v - xtarget) < 0 && ++spins < (1u << 24));
      }
      __syncwarp();
      if (wg == 0) TS(2, 6);
      float r[36];
#pragma unroll
      for (int i = 0; i < 9; i++)
        asm volatile("ld.shared.v4.f32 {%0, %1, %2, %3}, [%4];" : "=f"(r[i * 4]), "=f"(r[i * 4 + 1]), "=f"(r[i * 4 + 2]), "=f"(r[i * 4 + 3])
                     : "r"(sown + (i >> 2) * K3_STAGE + (i & 3) * 2048) : "memory");
#pragma unroll
      for (int sI = 1; sI < 4; sI++) {
        const int src = (ks + sI) & 3;
        const uint4* rp = g_part + (size_t)(((tile * 4 + src) * 4) + ks) * 5 * 256;
#pragma unroll
        for (int i = 0; i < 4; i++) {
          const uint4 v = __ldcg(rp + i * 256 + tid);
          r[i * 8] += bf_lo(v.x); r[i * 8 + 1] += bf_hi(v.x); r[i * 8 + 2] += bf_lo(v.y); r[i * 8 + 3] += bf_hi(v.y);
          r[i * 8 + 4] += bf_lo(v.z); r[i * 8 + 5] += bf_hi(v.z); r[i * 8 + 6] += bf_lo(v.w); r[i * 8 + 7] += bf_hi(v.w);
        }
        const uint2 v = __ldcg(reinterpret_cast<const uint2*>(rp + 4 * 256) + tid);
        r[32] += bf_lo(v.x); r[33] += bf_hi(v.x); r[34] += bf_lo(v.y); r[35] += bf_hi(v.y);
      }
      const int row = mblk * 128 + wg * 64 + warp * 16 + (lane >> 2);
      bf16* o0 = out + (size_t)row * DM + nhalf * 256 + ks * 64 + 8 * q;
#pragma unroll
      for (int G = 0; G < 2; G++) {
        uint32_t a0 = pack_bf16(r[G * 16], r[G * 16 + 1]), a1 = pack_bf16(r[G * 16 + 4], r[G * 16 + 5]);
        uint32_t a2 = pack_bf16(r[G * 16 + 8], r[G * 16 + 9]), a3 = pack_bf16(r[G * 16 + 12], r[G * 16 + 13]);
        uint32_t b0 = pack_bf16(r[G * 16 + 2], r[G * 16 + 3]), b1 = pack_bf16(r[G * 16 + 6], r[G * 16 + 7]);
        uint32_t b2 = pack_bf16(r[G * 16 + 10], r[G * 16 + 11]), b3 = pack_bf16(r[G * 16 + 14], r[G * 16 + 15]);
        quad_transpose(a0, a1, a2, a3, q);
        quad_transpose(b0, b1, b2, b3, q);
        st_v4(o0 + G * 32, a0, a1, a2, a3);
        st_v4(o0 + 8 * DM + G * 32, b0, b1, b2, b3);
      }
      {
        uint32_t t0 = pack_bf16(r[32], r[33]), t1 = pack_bf16(r[34], r[35]), t2 = 0, t3 = 0;
        quad_transpose(t0, t1, t2, t3, q);
        if (q < 2) st_v4(out + (size_t)(row + q * 8) * DM + 512 + nhalf * 32 + ks * 8, t0, t1, t2, t3);
      }
    } else {
      cluster_arrive();
    }
    if (wg == 0) { TS(2, 1); TSC(2, 3); }
    cluster_wait();
  }
}

typedef CUresult (*EncFn)(CUtensorMap*, CUtensorMapDataType, cuuint32_t, void*, const cuuint64_t*, const cuuint64_t*, const cuuint32_t*,
                          const cuuint32_t*, CUtensorMapInterleave, CUtensorMapSwizzle, CUtensorMapL2promotion, CUtensorMapFloatOOBfill);

static void enc2d(EncFn enc, CUtensorMap* m, const void* ptr, uint64_t cols, uint64_t rows, uint32_t bc, uint32_t br,
                  CUtensorMapSwizzle sw = CU_TENSOR_MAP_SWIZZLE_128B) {
  cuuint64_t gd[2] = {cols, rows}, gs[1] = {cols * 2};
  cuuint32_t bx[2] = {bc, br}, es[2] = {1, 1};
  enc(m, CU_TENSOR_MAP_DATA_TYPE_BFLOAT16, 2, const_cast<void*>(ptr), gd, gs, bx, es, CU_TENSOR_MAP_INTERLEAVE_NONE, sw,
      CU_TENSOR_MAP_L2_PROMOTION_L2_256B, CU_TENSOR_MAP_FLOAT_OOB_FILL_NONE);
}
static void enc3d(EncFn enc, CUtensorMap* m, const void* ptr, uint64_t cols, uint64_t rows, uint32_t br, uint32_t bch) {
  cuuint64_t gd[3] = {64, rows, cols / 64}, gs[2] = {cols * 2, 128};
  cuuint32_t bx[3] = {64, br, bch}, es[3] = {1, 1, 1};
  enc(m, CU_TENSOR_MAP_DATA_TYPE_BFLOAT16, 3, const_cast<void*>(ptr), gd, gs, bx, es, CU_TENSOR_MAP_INTERLEAVE_NONE,
      CU_TENSOR_MAP_SWIZZLE_128B, CU_TENSOR_MAP_L2_PROMOTION_L2_256B, CU_TENSOR_MAP_FLOAT_OOB_FILL_NONE);
}

static int g_sched[10] = {11, 10, 7, 4, 4, 4, 6, 7, 6, 24};
static void build_k1_jobs(Params& p) {
  int cnt[NCLUSTER];
  for (int c = 0; c < NCLUSTER; c++) {
    cnt[c] = 0;
    for (int i = 0; i <= K1_MAXJOBS; i++) p.jobs[c][i] = 0;
  }
  auto add = [&](int c, int nch, int a_sel, int mp, int w_sel, int chunk0) {
    p.jobs[c][cnt[c]++] = (uint16_t)((nch - 1) | (a_sel << 2) | (mp << 3) | (w_sel << 6) | (chunk0 << 8));
  };
  const int *cg = g_sched, *xg = g_sched + 4;
  for (int mp = 0; mp < 8; mp++) {
    int k = 0;
    for (int i = 0; i < K1_MAXJOBS; i++)
      for (int g = 0; g < 4; g++)
        if (i < cg[g]) { add(g * 8 + mp, 4, 0, mp, k & 1, (k >> 1) * 4); k++; }
    k = 0;
    for (int i = 0; i < K1_MAXJOBS; i++)
      for (int g = 0; g < 4; g++)
        if (i < xg[g]) {
          if (k < 7) add((4 + g) * 8 + mp, k == 0 ? 3 : 4, 1, mp, 2, k == 0 ? 24 : (k - 1) * 4);
          else add((4 + g) * 8 + mp, 4, 1, mp, 3, (k - 7) * 4);
          k++;
        }
    add(64 + mp / 4, 4, 1, mp, 3, 14 * 4);
    add(64 + mp / 4, 4, 1, mp, 3, 15 * 4);
  }
  for (int cc = 0; cc < NCLUSTER; cc++)
    for (int i = 0; i < cnt[cc]; i++) {
      const int key = p.jobs[cc][i] & 0x3C;
      if (i == 0 || (p.jobs[cc][i - 1] & 0x3C) != key) p.jobs[cc][i] |= (1 << 14);
      if (i == cnt[cc] - 1 || (p.jobs[cc][i + 1] & 0x3C) != key) p.jobs[cc][i] |= (1 << 15);
    }
}

static void build_k2_items(Params& p) {
  int n = 0;
  const int SCHED_N1 = g_sched[8], SCHED_N2 = g_sched[9];
  int N0 = 2, J0 = 2;
  for (int j = 7; j >= J0; j--)
    for (int h = 0; h < N0; h++) p.order[n++] = (uint8_t)(h * 8 + j);
  for (int j = 7; j >= 0; j--)
    for (int h = 0; h < SCHED_N1; h++)
      if (!(h < N0 && j >= J0)) p.order[n++] = (uint8_t)(h * 8 + j);
  for (int j = 7; j >= 4; j--)
    for (int h = SCHED_N1; h < SCHED_N2; h++) p.order[n++] = (uint8_t)(h * 8 + j);
  for (int j = 7; j >= 0; j--)
    for (int h = SCHED_N1; h < 32; h++)
      if (!(h < SCHED_N2 && j >= 4)) p.order[n++] = (uint8_t)(h * 8 + j);
}

static void build_k3_units(Params& p) {
  float slope = 0.045f;
  int NE = 25;
  for (int t = 0; t < 16; t++) {
    const int u[4] = {t, 31 - t, 32 + t, 63 - t};
    float acc = 0.f;
    int k0 = 0, l0 = NE;
    for (int i = 0; i < 4; i++) {
      acc += 18.25f + slope * (31.5f - u[i]);
      const int k1 = (i == 3) ? 73 : (int)(acc + 0.5f);
      const int e0 = NE * i / 4, e1 = NE * (i + 1) / 4;
      uint8_t* w = p.unit[u[i]];
      w[0] = (uint8_t)t; w[1] = (uint8_t)i; w[2] = (uint8_t)(k1 - k0); w[3] = (uint8_t)e0; w[4] = (uint8_t)(e1 - e0); w[5] = (uint8_t)(l0 - e1);
      l0 += (k1 - k0) - (e1 - e0);
      k0 = k1;
    }
  }
}

extern "C" void kernel_launch(void* const* d_in, const int* in_sizes, int n_in, void* d_out, int out_size) {
  const bf16* x = (const bf16*)d_in[0];
  const bf16* wqkv = (const bf16*)d_in[1];
  const bf16* wo = (const bf16*)d_in[2];
  const bf16* ckv = (const bf16*)d_in[4];
  const bf16* w_q = (const bf16*)d_in[5];
  const bf16* w_uk = (const bf16*)d_in[6];
  const bf16* w_uv = (const bf16*)d_in[7];
  const bf16* w_o = (const bf16*)d_in[8];
  const bf16* gate_w = (const bf16*)d_in[9];

  EncFn enc = nullptr;
  cudaDriverEntryPointQueryResult qr;
  cudaGetDriverEntryPoint("cuTensorMapEncodeTiled", (void**)&enc, cudaEnableDefault, &qr);
  void *pQ, *pK, *pV, *pCtx, *pQA;
  cudaGetSymbolAddress(&pQA, g_QKVA);
  cudaGetSymbolAddress(&pQ, g_Q);
  cudaGetSymbolAddress(&pK, g_K);
  cudaGetSymbolAddress(&pV, g_V);
  cudaGetSymbolAddress(&pCtx, g_ctx);

  static Params p;
  enc2d(enc, &p.tmA[0], ckv, DC, S_LEN, 64, 128);
  enc2d(enc, &p.tmA[1], x, DM, S_LEN, 64, 128);
  enc3d(enc, &p.tmW[0], w_uk, HDIM, DC, 16, 4);
  enc3d(enc, &p.tmW[1], w_uv, HDIM, DC, 16, 4);
  enc3d(enc, &p.tmW[2], wqkv, NQKVA, DM, 16, 4);
  enc3d(enc, &p.tmW[3], w_q, HDIM, DM, 16, 4);
  build_k1_jobs(p);
  enc2d(enc, &p.tmQ, pQ, HDIM, S_LEN, 64, 128);
  enc2d(enc, &p.tmK, pK, HDIM, S_LEN, 64, 128);
  enc2d(enc, &p.tmV, pV, HDIM, S_LEN, 64, 128);
  build_k2_items(p);
  build_k3_units(p);
  for (int i = 0; i < 3; i++) {
    const cuuint64_t ld = (i < 2 ? NQKVA : KCAT) * 2, nch = (i < 2) ? 27 : 9;
    cuuint64_t gd[4] = {64, S_LEN / 2, i ? 2 : nch, i ? nch : 2}, gs[3] = {2 * ld, i ? ld : 128, i ? 128 : ld};
    cuuint32_t bx[4] = {64, i ? 8u : 16u, i ? 2u : 9u, i ? 9u : 2u}, es[4] = {1, 1, 1, 1};
    enc(&p.tmL[i], CU_TENSOR_MAP_DATA_TYPE_BFLOAT16, 4, (i < 2) ? pQA : (void*)((bf16*)pCtx + HDIM), gd, gs, bx, es, CU_TENSOR_MAP_INTERLEAVE_NONE,
        CU_TENSOR_MAP_SWIZZLE_128B, CU_TENSOR_MAP_L2_PROMOTION_L2_256B, CU_TENSOR_MAP_FLOAT_OOB_FILL_NONE);
  }
  enc2d(enc, &p.tmC, pCtx, KCAT, S_LEN, 64, 128);
  enc3d(enc, &p.tmO[0], w_o, DM, HDIM, 32, 4);
  enc3d(enc, &p.tmO[1], wo, DM, DM, 32, 4);
  enc2d(enc, &p.tmOt[0], w_o, DM, HDIM, 32, 32, CU_TENSOR_MAP_SWIZZLE_64B);
  enc2d(enc, &p.tmOt[1], wo, DM, DM, 32, 32, CU_TENSOR_MAP_SWIZZLE_64B);

  cudaFuncSetAttribute(fused_kernel, cudaFuncAttributeMaxDynamicSharedMemorySize, SMEM_BYTES);
  fused_kernel<<<NCLUSTER * 2, 384, SMEM_BYTES>>>(p, x, gate_w, (bf16*)d_out);
}
```

```cpp
#include <cuda_runtime.h>
#include <cuda_bf16.h>
#include <cuda.h>
#include <stdint.h>

typedef __nv_bfloat16 bf16;

constexpr int S_LEN = 2048, DM = 576, DC = 512, HDIM = 4096, NQKVA = 1728, KCAT = 4672;
constexpr int NCLUSTER = 66;

__device__ __align__(1024) bf16 g_Q[S_LEN * HDIM];
__device__ __align__(1024) bf16 g_K[S_LEN * HDIM];
__device__ __align__(1024) bf16 g_V[S_LEN * HDIM];
__device__ __align__(1024) bf16 g_QKVA[S_LEN * NQKVA + 64];
__device__ __align__(1024) bf16 g_ctx[S_LEN * KCAT];
__device__ float g_gate[S_LEN];
__device__ __align__(1024) uint4 g_part[32 * 4 * 4 * 5 * 256];
__device__ __align__(16) unsigned int g_sync[400];
constexpr int F_QKVA = 0, F_HP = 16, F_CTX = 32, F_OA = 48, F_GATE = 96, F_TICK = 97, F_DONE = 98, F_XCH = 128, F_EPOCH = 384;

__device__ __forceinline__ uint32_t smem_u32(const void* p) { return (uint32_t)__cvta_generic_to_shared(p); }
__device__ __forceinline__ void mbar_init(uint32_t a, uint32_t c) {
  asm volatile("mbarrier.init.shared::cta.b64 [%0], %1;" ::"r"(a), "r"(c));
}
__device__ __forceinline__ void mbar_expect(uint32_t a, uint32_t b) {
  asm volatile("mbarrier.arrive.expect_tx.shared::cta.b64 _, [%0], %1;" ::"r"(a), "r"(b) : "memory");
}
#define TS(k, i)
#define TSC(k, i)
#define TSM(k)
#define BSEG(i)
#define TB(k)
#define TRC(fl)
#define SPIN_LIMIT "4194304"
__device__ __forceinline__ void mbar_wait(uint32_t a, uint32_t parity) {
  asm volatile(
      "{\n.reg .pred p;\n.reg .u32 n;\n"
      "mbarrier.try_wait.parity.shared::cta.b64 p, [%0], %1;\n"
      "@p bra DONE;\n"
      "mov.u32 n, 0;\n"
      "LOOP:\n"
      "mbarrier.try_wait.parity.shared::cta.b64 p, [%0], %1;\n"
      "@p bra DONE;\n"
      "add.u32 n, n, 1;\n"
      "setp.lt.u32 p, n, " SPIN_LIMIT ";\n"
      "@p bra LOOP;\n"
      "DONE:\n}" ::"r"(a), "r"(parity) : "memory");
}
template <int NS>
__device__ __forceinline__ void mbar_wait_ns(uint32_t a, uint32_t parity) {
  asm volatile(
      "{\n.reg .pred p;\n.reg .u32 n;\n"
      "mov.u32 n, 0;\n"
      "LOOP:\n"
      "mbarrier.try_wait.parity.shared::cta.b64 p, [%0], %1, %2;\n"
      "@p bra DONE;\n"
      "add.u32 n, n, 1;\n"
      "setp.lt.u32 p, n, " SPIN_LIMIT ";\n"
      "@p bra LOOP;\n"
      "DONE:\n}" ::"r"(a), "r"(parity), "n"(NS) : "memory");
}
__device__ __forceinline__ void mbar_wait2(uint32_t a, uint32_t pa, uint32_t b, uint32_t pb) {
  asm volatile(
      "{\n.reg .pred p, q;\n.reg .u32 n;\n"
      "mov.u32 n, 0;\n"
      "LOOP:\n"
      "mbarrier.try_wait.parity.shared::cta.b64 p, [%0], %1;\n"
      "mbarrier.try_wait.parity.shared::cta.b64 q, [%2], %3;\n"
      "add.u32 n, n, 1;\n"
      "and.pred p, p, q;\n"
      "setp.lt.and.u32 p, n, " SPIN_LIMIT ", !p;\n"
      "@p bra LOOP;\n"
      "}" ::"r"(a), "r"(pa), "r"(b), "r"(pb) : "memory");
}
__device__ __forceinline__ uint32_t mbar_test(uint32_t a, uint32_t parity) {
  uint32_t r;
  asm volatile("{\n.reg .pred p;\nmbarrier.test_wait.parity.shared::cta.b64 p, [%1], %2;\nselp.u32 %0, 1, 0, p;\n}" : "=r"(r) : "r"(a), "r"(parity) : "memory");
  return r;
}
__device__ __forceinline__ void mbar_arrive(uint32_t a) {
  asm volatile("mbarrier.arrive.shared::cta.b64 _, [%0];" ::"r"(a) : "memory");
}
__device__ __forceinline__ void mbar_arrive_cluster(uint32_t a, uint32_t cta) {
  asm volatile("{\n.reg .b32 r;\nmapa.shared::cluster.u32 r, %0, %1;\nmbarrier.arrive.shared::cluster.b64 _, [r];\n}" ::"r"(a),
               "r"(cta) : "memory");
}
__device__ __forceinline__ void mbar_arrive_cluster_if(uint32_t a, uint32_t cta, bool pred) {
  asm volatile("{\n.reg .b32 r;\n.reg .pred p;\nsetp.ne.u32 p, %2, 0;\nmapa.shared::cluster.u32 r, %0, %1;\n@p mbarrier.arrive.shared::cluster.b64 _, [r];\n}" ::"r"(a),
               "r"(cta), "r"((uint32_t)pred) : "memory");
}
__device__ __forceinline__ void anchor(float v, uint32_t pred) {
  asm volatile("{\n.reg .pred p;\nsetp.ne.u32 p, %1, 0;\n@p st.shared.f32 [%1], %0;\n}" ::"f"(v), "r"(pred) : "memory");
}
__device__ __forceinline__ void mbar_arrive_if(uint32_t a, bool pred) {
  asm volatile("{\n.reg .pred p;\nsetp.ne.u32 p, %1, 0;\n@p mbarrier.arrive.shared::cta.b64 _, [%0];\n}" ::"r"(a), "r"((uint32_t)pred) : "memory");
}
__device__ __forceinline__ void tma2d(uint32_t dst, const CUtensorMap* m, uint32_t bar, int c0, int c1) {
  asm volatile("cp.async.bulk.tensor.2d.shared::cluster.global.mbarrier::complete_tx::bytes [%0], [%1, {%3, %4}], [%2];" ::"r"(dst),
               "l"(m), "r"(bar), "r"(c0), "r"(c1) : "memory");
}
__device__ __forceinline__ void tma2d_mc(uint32_t dst, const CUtensorMap* m, uint32_t bar, int c0, int c1, uint16_t mask) {
  asm volatile(
      "cp.async.bulk.tensor.2d.shared::cluster.global.mbarrier::complete_tx::bytes.multicast::cluster [%0], [%1, {%3, %4}], [%2], %5;" ::"r"(dst),
      "l"(m), "r"(bar), "r"(c0), "r"(c1), "h"(mask) : "memory");
}
__device__ __forceinline__ void tma3d_mc(uint32_t dst, const CUtensorMap* m, uint32_t bar, int c0, int c1, int c2, uint16_t mask) {
  asm volatile(
      "cp.async.bulk.tensor.3d.shared::cluster.global.mbarrier::complete_tx::bytes.multicast::cluster [%0], [%1, {%3, %4, %5}], [%2], %6;" ::"r"(dst),
      "l"(m), "r"(bar), "r"(c0), "r"(c1), "r"(c2), "h"(mask) : "memory");
}
__device__ __forceinline__ void tma3d(uint32_t dst, const CUtensorMap* m, uint32_t bar, int c0, int c1, int c2) {
  asm volatile(
      "cp.async.bulk.tensor.3d.shared::cluster.global.mbarrier::complete_tx::bytes [%0], [%1, {%3, %4, %5}], [%2];" ::"r"(dst),
      "l"(m), "r"(bar), "r"(c0), "r"(c1), "r"(c2) : "memory");
}
__device__ __forceinline__ void tma_pf2d(const CUtensorMap* m, int c0, int c1) {
  asm volatile("cp.async.bulk.prefetch.tensor.2d.L2.global [%0, {%1, %2}];" ::"l"(m), "r"(c0), "r"(c1) : "memory");
}
__device__ __forceinline__ void tma_pf3d(const CUtensorMap* m, int c0, int c1, int c2) {
  asm volatile("cp.async.bulk.prefetch.tensor.3d.L2.global [%0, {%1, %2, %3}];" ::"l"(m), "r"(c0), "r"(c1), "r"(c2) : "memory");
}
__device__ __forceinline__ void prefetch_tmap(const CUtensorMap* m) {
  asm volatile("prefetch.tensormap [%0];" ::"l"(m) : "memory");
}
__device__ __forceinline__ void cluster_arrive() { asm volatile("barrier.cluster.arrive.relaxed.aligned;" ::: "memory"); }
__device__ __forceinline__ void cluster_wait() { asm volatile("barrier.cluster.wait.aligned;" ::: "memory"); }
__device__ __forceinline__ void cluster_sync() {
  cluster_arrive();
  cluster_wait();
}
__device__ __forceinline__ uint32_t cluster_rank() {
  uint32_t r;
  asm volatile("mov.u32 %0, %%cluster_ctarank;" : "=r"(r));
  return r;
}
__device__ __forceinline__ bool elect_one() {
  uint32_t p;
  asm volatile("{\n.reg .pred q;\nelect.sync _|q, 0xffffffff;\nselp.u32 %0, 1, 0, q;\n}" : "=r"(p));
  return p;
}
__device__ __forceinline__ void ldsm_x4(uint32_t& r0, uint32_t& r1, uint32_t& r2, uint32_t& r3, uint32_t addr) {
  asm volatile("ldmatrix.sync.aligned.m8n8.x4.shared.b16 {%0, %1, %2, %3}, [%4];" : "=r"(r0), "=r"(r1), "=r"(r2), "=r"(r3) : "r"(addr) : "memory");
}
__device__ __forceinline__ void wg_fence() { asm volatile("wgmma.fence.sync.aligned;" ::: "memory"); }
__device__ __forceinline__ void wg_commit() { asm volatile("wgmma.commit_group.sync.aligned;" ::: "memory"); }
template <int N>
__device__ __forceinline__ void wg_wait() { asm volatile("wgmma.wait_group.sync.aligned %0;" ::"n"(N) : "memory"); }
template <int N>
__device__ __forceinline__ void reg_alloc() { asm volatile("setmaxnreg.inc.sync.aligned.u32 %0;" ::"n"(N)); }
template <int N>
__device__ __forceinline__ void reg_dealloc() { asm volatile("setmaxnreg.dec.sync.aligned.u32 %0;" ::"n"(N)); }
__device__ __forceinline__ void bar_sync(int id, int n) { asm volatile("bar.sync %0, %1;" ::"r"(id), "r"(n) : "memory"); }
__device__ __forceinline__ void bar_arrive(int id, int n) { asm volatile("bar.arrive %0, %1;" ::"r"(id), "r"(n) : "memory"); }
template <int NT>
__device__ __forceinline__ void fence_regs(float (&d)[NT]) {
#pragma unroll
  for (int i = 0; i < NT; i++) asm volatile("" : "+f"(d[i])::"memory");
}
template <int NT>
__device__ __forceinline__ void fence_regs(uint32_t (&d)[NT]) {
#pragma unroll
  for (int i = 0; i < NT; i++) asm volatile("" : "+r"(d[i])::"memory");
}
__device__ __forceinline__ uint64_t make_desc(uint32_t saddr, uint32_t lbo, uint32_t sbo, uint32_t layout) {
  return (uint64_t)((saddr & 0x3FFFF) >> 4) | ((uint64_t)(lbo >> 4) << 16) | ((uint64_t)(sbo >> 4) << 32) | ((uint64_t)layout << 62);
}
__device__ __forceinline__ uint32_t pack_bf16(float lo, float hi) {
  uint32_t r;
  asm("cvt.rn.bf16x2.f32 %0, %1, %2;" : "=r"(r) : "f"(hi), "f"(lo));
  return r;
}
__device__ __forceinline__ float ex2(float x) {
  float r;
  asm("ex2.approx.ftz.f32 %0, %1;" : "=f"(r) : "f"(x));
  return r;
}
__device__ __forceinline__ void st_v4(void* p, uint32_t a, uint32_t b, uint32_t c, uint32_t d) {
#define ST_MOD ".cs"
  asm volatile("st.global" ST_MOD ".v4.b32 [%0], {%1, %2, %3, %4};" ::"l"(p), "r"(a), "r"(b), "r"(c), "r"(d) : "memory");
}
#define STA_MOD ".cs"
__device__ __forceinline__ void st_v4a(void* p, uint32_t a, uint32_t b, uint32_t c, uint32_t d) {
  asm volatile("st.global" STA_MOD ".v4.b32 [%0], {%1, %2, %3, %4};" ::"l"(p), "r"(a), "r"(b), "r"(c), "r"(d) : "memory");
}
__device__ __forceinline__ float bf_lo(uint32_t v) { return __uint_as_float(v << 16); }
__device__ __forceinline__ float bf_hi(uint32_t v) { return __uint_as_float(v & 0xFFFF0000u); }

__device__ __forceinline__ void quad_transpose(uint32_t& a0, uint32_t& a1, uint32_t& a2, uint32_t& a3, int q) {
  const bool o1 = q & 1, o2 = q & 2;
  uint32_t t0 = o1 ? a0 : a1, t1 = o1 ? a2 : a3;
  t0 = __shfl_xor_sync(0xffffffffu, t0, 1);
  t1 = __shfl_xor_sync(0xffffffffu, t1, 1);
  if (o1) { a0 = t0; a2 = t1; } else { a1 = t0; a3 = t1; }
  t0 = o2 ? a0 : a2;
  t1 = o2 ? a1 : a3;
  t0 = __shfl_xor_sync(0xffffffffu, t0, 2);
  t1 = __shfl_xor_sync(0xffffffffu, t1, 2);
  if (o2) { a0 = t0; a1 = t1; } else { a2 = t0; a3 = t1; }
}

template<int TB, int OFF, int NT>
__device__ __forceinline__ void wgmma_ss_n256(float (&d)[NT], uint64_t da, uint64_t db, int scale_d) {
  asm volatile("{\n.reg .pred p;\nsetp.ne.b32 p, %130, 0;\n"
    "wgmma.mma_async.sync.aligned.m64n256k16.f32.bf16.bf16 {%0, %1, %2, %3, %4, %5, %6, %7, %8, %9, %10, %11, %12, %13, %14, %15, %16, %17, %18, %19, %20, %21, %22, %23, %24, %25, %26, %27, %28, %29, %30, %31, %32, %33, %34, %35, %36, %37, %38, %39, %40, %41, %42, %43, %44, %45, %46, %47, %48, %49, %50, %51, %52, %53, %54, %55, %56, %57, %58, %59, %60, %61, %62, %63, %64, %65, %66, %67, %68, %69, %70, %71, %72, %73, %74, %75, %76, %77, %78, %79, %80, %81, %82, %83, %84, %85, %86, %87, %88, %89, %90, %91, %92, %93, %94, %95, %96, %97, %98, %99, %100, %101, %102, %103, %104, %105, %106, %107, %108, %109, %110, %111, %112, %113, %114, %115, %116, %117, %118, %119, %120, %121, %122, %123, %124, %125, %126, %127}, %128, %129, p, 1, 1, 0, %131;\n}\n"
    : "+f"(d[OFF+0]), "+f"(d[OFF+1]), "+f"(d[OFF+2]), "+f"(d[OFF+3]), "+f"(d[OFF+4]), "+f"(d[OFF+5]), "+f"(d[OFF+6]), "+f"(d[OFF+7]), "+f"(d[OFF+8]), "+f"(d[OFF+9]), "+f"(d[OFF+10]), "+f"(d[OFF+11]), "+f"(d[OFF+12]), "+f"(d[OFF+13]), "+f"(d[OFF+14]), "+f"(d[OFF+15]), "+f"(d[OFF+16]), "+f"(d[OFF+17]), "+f"(d[OFF+18]), "+f"(d[OFF+19]), "+f"(d[OFF+20]), "+f"(d[OFF+21]), "+f"(d[OFF+22]), "+f"(d[OFF+23]), "+f"(d[OFF+24]), "+f"(d[OFF+25]), "+f"(d[OFF+26]), "+f"(d[OFF+27]), "+f"(d[OFF+28]), "+f"(d[OFF+29]), "+f"(d[OFF+30]), "+f"(d[OFF+31]), "+f"(d[OFF+32]), "+f"(d[OFF+33]), "+f"(d[OFF+34]), "+f"(d[OFF+35]), "+f"(d[OFF+36]), "+f"(d[OFF+37]), "+f"(d[OFF+38]), "+f"(d[OFF+39]), "+f"(d[OFF+40]), "+f"(d[OFF+41]), "+f"(d[OFF+42]), "+f"(d[OFF+43]), "+f"(d[OFF+44]), "+f"(d[OFF+45]), "+f"(d[OFF+46]), "+f"(d[OFF+47]), "+f"(d[OFF+48]), "+f"(d[OFF+49]), "+f"(d[OFF+50]), "+f"(d[OFF+51]), "+f"(d[OFF+52]), "+f"(d[OFF+53]), "+f"(d[OFF+54]), "+f"(d[OFF+55]), "+f"(d[OFF+56]), "+f"(d[OFF+57]), "+f"(d[OFF+58]), "+f"(d[OFF+59]), "+f"(d[OFF+60]), "+f"(d[OFF+61]), "+f"(d[OFF+62]), "+f"(d[OFF+63]), "+f"(d[OFF+64]), "+f"(d[OFF+65]), "+f"(d[OFF+66]), "+f"(d[OFF+67]), "+f"(d[OFF+68]), "+f"(d[OFF+69]), "+f"(d[OFF+70]), "+f"(d[OFF+71]), "+f"(d[OFF+72]), "+f"(d[OFF+73]), "+f"(d[OFF+74]), "+f"(d[OFF+75]), "+f"(d[OFF+76]), "+f"(d[OFF+77]), "+f"(d[OFF+78]), "+f"(d[OFF+79]), "+f"(d[OFF+80]), "+f"(d[OFF+81]), "+f"(d[OFF+82]), "+f"(d[OFF+83]), "+f"(d[OFF+84]), "+f"(d[OFF+85]), "+f"(d[OFF+86]), "+f"(d[OFF+87]), "+f"(d[OFF+88]), "+f"(d[OFF+89]), "+f"(d[OFF+90]), "+f"(d[OFF+91]), "+f"(d[OFF+92]), "+f"(d[OFF+93]), "+f"(d[OFF+94]), "+f"(d[OFF+95]), "+f"(d[OFF+96]), "+f"(d[OFF+97]), "+f"(d[OFF+98]), "+f"(d[OFF+99]), "+f"(d[OFF+100]), "+f"(d[OFF+101]), "+f"(d[OFF+102]), "+f"(d[OFF+103]), "+f"(d[OFF+104]), "+f"(d[OFF+105]), "+f"(d[OFF+106]), "+f"(d[OFF+107]), "+f"(d[OFF+108]), "+f"(d[OFF+109]), "+f"(d[OFF+110]), "+f"(d[OFF+111]), "+f"(d[OFF+112]), "+f"(d[OFF+113]), "+f"(d[OFF+114]), "+f"(d[OFF+115]), "+f"(d[OFF+116]), "+f"(d[OFF+117]), "+f"(d[OFF+118]), "+f"(d[OFF+119]), "+f"(d[OFF+120]), "+f"(d[OFF+121]), "+f"(d[OFF+122]), "+f"(d[OFF+123]), "+f"(d[OFF+124]), "+f"(d[OFF+125]), "+f"(d[OFF+126]), "+f"(d[OFF+127])
    : "l"(da), "l"(db), "r"(scale_d), "n"(TB));
}
template<int TB, int OFF, int NT>
__device__ __forceinline__ void wgmma_ss_n32(float (&d)[NT], uint64_t da, uint64_t db, int scale_d) {
  asm volatile("{\n.reg .pred p;\nsetp.ne.b32 p, %18, 0;\n"
    "wgmma.mma_async.sync.aligned.m64n32k16.f32.bf16.bf16 {%0, %1, %2, %3, %4, %5, %6, %7, %8, %9, %10, %11, %12, %13, %14, %15}, %16, %17, p, 1, 1, 0, %19;\n}\n"
    : "+f"(d[OFF+0]), "+f"(d[OFF+1]), "+f"(d[OFF+2]), "+f"(d[OFF+3]), "+f"(d[OFF+4]), "+f"(d[OFF+5]), "+f"(d[OFF+6]), "+f"(d[OFF+7]), "+f"(d[OFF+8]), "+f"(d[OFF+9]), "+f"(d[OFF+10]), "+f"(d[OFF+11]), "+f"(d[OFF+12]), "+f"(d[OFF+13]), "+f"(d[OFF+14]), "+f"(d[OFF+15])
    : "l"(da), "l"(db), "r"(scale_d), "n"(TB));
}
template<int TB, int OFF, int NT>
__device__ __forceinline__ void wgmma_rs_n128(float (&d)[NT], uint32_t a0, uint32_t a1, uint32_t a2, uint32_t a3, uint64_t db, int scale_d) {
  asm volatile("{\n.reg .pred p;\nsetp.ne.b32 p, %69, 0;\n"
    "wgmma.mma_async.sync.aligned.m64n128k16.f32.bf16.bf16 {%0, %1, %2, %3, %4, %5, %6, %7, %8, %9, %10, %11, %12, %13, %14, %15, %16, %17, %18, %19, %20, %21, %22, %23, %24, %25, %26, %27, %28, %29, %30, %31, %32, %33, %34, %35, %36, %37, %38, %39, %40, %41, %42, %43, %44, %45, %46, %47, %48, %49, %50, %51, %52, %53, %54, %55, %56, %57, %58, %59, %60, %61, %62, %63}, {%64, %65, %66, %67}, %68, p, 1, 1, %70;\n}\n"
    : "+f"(d[OFF+0]), "+f"(d[OFF+1]), "+f"(d[OFF+2]), "+f"(d[OFF+3]), "+f"(d[OFF+4]), "+f"(d[OFF+5]), "+f"(d[OFF+6]), "+f"(d[OFF+7]), "+f"(d[OFF+8]), "+f"(d[OFF+9]), "+f"(d[OFF+10]), "+f"(d[OFF+11]), "+f"(d[OFF+12]), "+f"(d[OFF+13]), "+f"(d[OFF+14]), "+f"(d[OFF+15]), "+f"(d[OFF+16]), "+f"(d[OFF+17]), "+f"(d[OFF+18]), "+f"(d[OFF+19]), "+f"(d[OFF+20]), "+f"(d[OFF+21]), "+f"(d[OFF+22]), "+f"(d[OFF+23]), "+f"(d[OFF+24]), "+f"(d[OFF+25]), "+f"(d[OFF+26]), "+f"(d[OFF+27]), "+f"(d[OFF+28]), "+f"(d[OFF+29]), "+f"(d[OFF+30]), "+f"(d[OFF+31]), "+f"(d[OFF+32]), "+f"(d[OFF+33]), "+f"(d[OFF+34]), "+f"(d[OFF+35]), "+f"(d[OFF+36]), "+f"(d[OFF+37]), "+f"(d[OFF+38]), "+f"(d[OFF+39]), "+f"(d[OFF+40]), "+f"(d[OFF+41]), "+f"(d[OFF+42]), "+f"(d[OFF+43]), "+f"(d[OFF+44]), "+f"(d[OFF+45]), "+f"(d[OFF+46]), "+f"(d[OFF+47]), "+f"(d[OFF+48]), "+f"(d[OFF+49]), "+f"(d[OFF+50]), "+f"(d[OFF+51]), "+f"(d[OFF+52]), "+f"(d[OFF+53]), "+f"(d[OFF+54]), "+f"(d[OFF+55]), "+f"(d[OFF+56]), "+f"(d[OFF+57]), "+f"(d[OFF+58]), "+f"(d[OFF+59]), "+f"(d[OFF+60]), "+f"(d[OFF+61]), "+f"(d[OFF+62]), "+f"(d[OFF+63])
    : "r"(a0), "r"(a1), "r"(a2), "r"(a3), "l"(db), "r"(scale_d), "n"(TB));
}
template<int TB, int OFF, int NT>
__device__ __forceinline__ void wgmma_rs_n256(float (&d)[NT], uint32_t a0, uint32_t a1, uint32_t a2, uint32_t a3, uint64_t db, int scale_d) {
  asm volatile("{\n.reg .pred p;\nsetp.ne.b32 p, %133, 0;\n"
    "wgmma.mma_async.sync.aligned.m64n256k16.f32.bf16.bf16 {%0, %1, %2, %3, %4, %5, %6, %7, %8, %9, %10, %11, %12, %13, %14, %15, %16, %17, %18, %19, %20, %21, %22, %23, %24, %25, %26, %27, %28, %29, %30, %31, %32, %33, %34, %35, %36, %37, %38, %39, %40, %41, %42, %43, %44, %45, %46, %47, %48, %49, %50, %51, %52, %53, %54, %55, %56, %57, %58, %59, %60, %61, %62, %63, %64, %65, %66, %67, %68, %69, %70, %71, %72, %73, %74, %75, %76, %77, %78, %79, %80, %81, %82, %83, %84, %85, %86, %87, %88, %89, %90, %91, %92, %93, %94, %95, %96, %97, %98, %99, %100, %101, %102, %103, %104, %105, %106, %107, %108, %109, %110, %111, %112, %113, %114, %115, %116, %117, %118, %119, %120, %121, %122, %123, %124, %125, %126, %127}, {%128, %129, %130, %131}, %132, p, 1, 1, %134;\n}\n"
    : "+f"(d[OFF+0]), "+f"(d[OFF+1]), "+f"(d[OFF+2]), "+f"(d[OFF+3]), "+f"(d[OFF+4]), "+f"(d[OFF+5]), "+f"(d[OFF+6]), "+f"(d[OFF+7]), "+f"(d[OFF+8]), "+f"(d[OFF+9]), "+f"(d[OFF+10]), "+f"(d[OFF+11]), "+f"(d[OFF+12]), "+f"(d[OFF+13]), "+f"(d[OFF+14]), "+f"(d[OFF+15]), "+f"(d[OFF+16]), "+f"(d[OFF+17]), "+f"(d[OFF+18]), "+f"(d[OFF+19]), "+f"(d[OFF+20]), "+f"(d[OFF+21]), "+f"(d[OFF+22]), "+f"(d[OFF+23]), "+f"(d[OFF+24]), "+f"(d[OFF+25]), "+f"(d[OFF+26]), "+f"(d[OFF+27]), "+f"(d[OFF+28]), "+f"(d[OFF+29]), "+f"(d[OFF+30]), "+f"(d[OFF+31]), "+f"(d[OFF+32]), "+f"(d[OFF+33]), "+f"(d[OFF+34]), "+f"(d[OFF+35]), "+f"(d[OFF+36]), "+f"(d[OFF+37]), "+f"(d[OFF+38]), "+f"(d[OFF+39]), "+f"(d[OFF+40]), "+f"(d[OFF+41]), "+f"(d[OFF+42]), "+f"(d[OFF+43]), "+f"(d[OFF+44]), "+f"(d[OFF+45]), "+f"(d[OFF+46]), "+f"(d[OFF+47]), "+f"(d[OFF+48]), "+f"(d[OFF+49]), "+f"(d[OFF+50]), "+f"(d[OFF+51]), "+f"(d[OFF+52]), "+f"(d[OFF+53]), "+f"(d[OFF+54]), "+f"(d[OFF+55]), "+f"(d[OFF+56]), "+f"(d[OFF+57]), "+f"(d[OFF+58]), "+f"(d[OFF+59]), "+f"(d[OFF+60]), "+f"(d[OFF+61]), "+f"(d[OFF+62]), "+f"(d[OFF+63]), "+f"(d[OFF+64]), "+f"(d[OFF+65]), "+f"(d[OFF+66]), "+f"(d[OFF+67]), "+f"(d[OFF+68]), "+f"(d[OFF+69]), "+f"(d[OFF+70]), "+f"(d[OFF+71]), "+f"(d[OFF+72]), "+f"(d[OFF+73]), "+f"(d[OFF+74]), "+f"(d[OFF+75]), "+f"(d[OFF+76]), "+f"(d[OFF+77]), "+f"(d[OFF+78]), "+f"(d[OFF+79]), "+f"(d[OFF+80]), "+f"(d[OFF+81]), "+f"(d[OFF+82]), "+f"(d[OFF+83]), "+f"(d[OFF+84]), "+f"(d[OFF+85]), "+f"(d[OFF+86]), "+f"(d[OFF+87]), "+f"(d[OFF+88]), "+f"(d[OFF+89]), "+f"(d[OFF+90]), "+f"(d[OFF+91]), "+f"(d[OFF+92]), "+f"(d[OFF+93]), "+f"(d[OFF+94]), "+f"(d[OFF+95]), "+f"(d[OFF+96]), "+f"(d[OFF+97]), "+f"(d[OFF+98]), "+f"(d[OFF+99]), "+f"(d[OFF+100]), "+f"(d[OFF+101]), "+f"(d[OFF+102]), "+f"(d[OFF+103]), "+f"(d[OFF+104]), "+f"(d[OFF+105]), "+f"(d[OFF+106]), "+f"(d[OFF+107]), "+f"(d[OFF+108]), "+f"(d[OFF+109]), "+f"(d[OFF+110]), "+f"(d[OFF+111]), "+f"(d[OFF+112]), "+f"(d[OFF+113]), "+f"(d[OFF+114]), "+f"(d[OFF+115]), "+f"(d[OFF+116]), "+f"(d[OFF+117]), "+f"(d[OFF+118]), "+f"(d[OFF+119]), "+f"(d[OFF+120]), "+f"(d[OFF+121]), "+f"(d[OFF+122]), "+f"(d[OFF+123]), "+f"(d[OFF+124]), "+f"(d[OFF+125]), "+f"(d[OFF+126]), "+f"(d[OFF+127])
    : "r"(a0), "r"(a1), "r"(a2), "r"(a3), "l"(db), "r"(scale_d), "n"(TB));
}
template<int TB, int OFF, int NT>
__device__ __forceinline__ void wgmma_rs_n32(float (&d)[NT], uint32_t a0, uint32_t a1, uint32_t a2, uint32_t a3, uint64_t db, int scale_d) {
  asm volatile("{\n.reg .pred p;\nsetp.ne.b32 p, %21, 0;\n"
    "wgmma.mma_async.sync.aligned.m64n32k16.f32.bf16.bf16 {%0, %1, %2, %3, %4, %5, %6, %7, %8, %9, %10, %11, %12, %13, %14, %15}, {%16, %17, %18, %19}, %20, p, 1, 1, %22;\n}\n"
    : "+f"(d[OFF+0]), "+f"(d[OFF+1]), "+f"(d[OFF+2]), "+f"(d[OFF+3]), "+f"(d[OFF+4]), "+f"(d[OFF+5]), "+f"(d[OFF+6]), "+f"(d[OFF+7]), "+f"(d[OFF+8]), "+f"(d[OFF+9]), "+f"(d[OFF+10]), "+f"(d[OFF+11]), "+f"(d[OFF+12]), "+f"(d[OFF+13]), "+f"(d[OFF+14]), "+f"(d[OFF+15])
    : "r"(a0), "r"(a1), "r"(a2), "r"(a3), "l"(db), "r"(scale_d), "n"(TB));
}

__device__ __forceinline__ void wait_flag(const unsigned int* f, uint32_t target) {
  uint32_t v;
#pragma unroll 1
  for (uint32_t spins = 0; spins < (1u << 22); spins++) {
    asm volatile("ld.acquire.gpu.global.u32 %0, [%1];" : "=r"(v) : "l"(f) : "memory");
    if (v >= target) break;
    __nanosleep(100);
  }
}
__device__ __forceinline__ uint32_t lds32(uint32_t a) {
  uint32_t v;
  asm volatile("ld.shared.u32 %0, [%1];" : "=r"(v) : "r"(a) : "memory");
  return v;
}
__device__ __forceinline__ float gate_row(int row, int lane, const bf16* __restrict__ x, const bf16* __restrict__ gate_w) {
  const uint32_t* xr = reinterpret_cast<const uint32_t*>(x + (size_t)row * DM);
  const uint32_t* gw2 = reinterpret_cast<const uint32_t*>(gate_w);
  float gs = 0.f;
#pragma unroll
  for (int i = 0; i < 9; i++) {
    const uint32_t a = __ldg(xr + lane + 32 * i), b = __ldg(gw2 + lane + 32 * i);
    gs = fmaf(bf_lo(a), bf_lo(b), gs);
    gs = fmaf(bf_hi(a), bf_hi(b), gs);
  }
#pragma unroll
  for (int o = 16; o; o >>= 1) gs += __shfl_xor_sync(0xffffffffu, gs, o);
  const float g = 1.f / (1.f + __expf(-gs));
  if (lane == 0) g_gate[row] = g;
  return g;
}
constexpr uint32_t LQ = 36864, LV = 55296;
__device__ __forceinline__ void mma16(float (&c)[4], uint32_t a0, uint32_t a1, uint32_t a2, uint32_t a3, uint32_t b0, uint32_t b1) {
  asm("mma.sync.aligned.m16n8k16.row.col.f32.bf16.bf16.f32 {%0, %1, %2, %3}, {%4, %5, %6, %7}, {%8, %9}, {%0, %1, %2, %3};"
      : "+f"(c[0]), "+f"(c[1]), "+f"(c[2]), "+f"(c[3]) : "r"(a0), "r"(a1), "r"(a2), "r"(a3), "r"(b0), "r"(b1));
}
__device__ __forceinline__ void mma8(float (&c)[4], uint32_t a0, uint32_t a1, uint32_t b0) {
  asm("mma.sync.aligned.m16n8k8.row.col.f32.bf16.bf16.f32 {%0, %1, %2, %3}, {%4, %5}, {%6}, {%0, %1, %2, %3};"
      : "+f"(c[0]), "+f"(c[1]), "+f"(c[2]), "+f"(c[3]) : "r"(a0), "r"(a1), "r"(b0));
}
__device__ __forceinline__ void local_attn(int lr0, int warp_g, uint32_t sL, uint32_t bL, uint32_t bL2, int lane, float g0, float g1) {
  const float scale_l2 = 0.23570226039551584f * 1.4426950408889634f;
  const int g = lane >> 2, t = lane & 3;
  const bool lo0 = 2 * t > g, lo1 = 2 * t + 1 > g;
  const uint32_t mlo = (lo0 ? 0xFFFFu : 0u) | (lo1 ? 0xFFFF0000u : 0u);
  const bool ok0 = lr0 > 0 || !lo0, ok1 = lr0 > 0 || !lo1;
  uint32_t ad[9], k[9][4], qf[9][2], pe[4], po[4];
#pragma unroll
  for (int c = 0; c < 9; c++) {
    const uint32_t ch = warp_g * 9 + c;
    ad[c] = sL + (lane >> 4) * 18432 + (lane & 15) * 128 + ((ch >> 3) << 11) + (((ch ^ lane) & 7) << 4);
  }
  mbar_wait(bL, 0);
  if (warp_g == 0) TS(1, 6);
#pragma unroll
  for (int c = 0; c < 9; c++) {
    asm volatile("ldmatrix.sync.aligned.m8n8.x2.shared.b16 {%0, %1}, [%2];" : "=r"(qf[c][0]), "=r"(qf[c][1]) : "r"(ad[c] + LQ) : "memory");
    ldsm_x4(k[c][0], k[c][1], k[c][2], k[c][3], ad[c]);
  }
#pragma unroll
  for (int i = 0; i < 4; i++) {
    const uint32_t q0 = (t >= i) ? qf[2 * i][0] : 0u, q1 = (t >= i) ? qf[2 * i][1] : 0u;
    const uint32_t q4 = (t <= i) ? qf[2 * i + 2][0] : 0u, q5 = (t <= i) ? qf[2 * i + 2][1] : 0u;
    float c[4][4];
#pragma unroll
    for (int T = 0; T < 4; T++) {
#pragma unroll
      for (int j = 0; j < 4; j++) c[T][j] = 0.f;
      mma16(c[T], q0, q1, qf[2 * i + 1][0], qf[2 * i + 1][1], k[2 * i][T], k[2 * i + 1][T]);
      mma8(c[T], q4, q5, k[2 * i + 2][T]);
    }
    const float e0 = ok0 ? (lo0 ? c[0][0] : c[1][0]) : -INFINITY, e1 = ok1 ? (lo1 ? c[0][1] : c[1][1]) : -INFINITY;
    const float o0 = ok0 ? (lo0 ? c[2][2] : c[3][2]) : -INFINITY, o1 = ok1 ? (lo1 ? c[2][3] : c[3][3]) : -INFINITY;
    float me = fmaxf(e0, e1), mo = fmaxf(o0, o1);
    me = fmaxf(me, __shfl_xor_sync(0xffffffffu, me, 1));
    mo = fmaxf(mo, __shfl_xor_sync(0xffffffffu, mo, 1));
    me = fmaxf(me, __shfl_xor_sync(0xffffffffu, me, 2)) * scale_l2;
    mo = fmaxf(mo, __shfl_xor_sync(0xffffffffu, mo, 2)) * scale_l2;
    const float w0 = ex2(fmaf(e0, scale_l2, -me)), w1 = ex2(fmaf(e1, scale_l2, -me));
    const float w2 = ex2(fmaf(o0, scale_l2, -mo)), w3 = ex2(fmaf(o1, scale_l2, -mo));
    float se = w0 + w1, so = w2 + w3;
    se += __shfl_xor_sync(0xffffffffu, se, 1);
    so += __shfl_xor_sync(0xffffffffu, so, 1);
    se += __shfl_xor_sync(0xffffffffu, se, 2);
    so += __shfl_xor_sync(0xffffffffu, so, 2);
    asm("rcp.approx.ftz.f32 %0, %0;" : "+f"(se));
    asm("rcp.approx.ftz.f32 %0, %0;" : "+f"(so));
    se *= g0;
    so *= g1;
    pe[i] = pack_bf16(w0 * se, w1 * se);
    po[i] = pack_bf16(w2 * so, w3 * so);
  }
  if (warp_g == 0) TS(0, 4);
  mbar_wait(bL2, 0);
  if (warp_g == 0) TS(0, 5);
#pragma unroll
  for (int c = 0; c < 9; c++)
    asm volatile("ldmatrix.sync.aligned.m8n8.x4.trans.shared.b16 {%0, %1, %2, %3}, [%4];"
                 : "=r"(k[c][0]), "=r"(k[c][1]), "=r"(k[c][2]), "=r"(k[c][3]) : "r"(ad[c] + LV) : "memory");
#pragma unroll
  for (int i = 0; i < 4; i++) {
#pragma unroll
    for (int n = 0; n < 3; n++) {
      float c[4] = {0.f, 0.f, 0.f, 0.f};
      mma16(c, pe[i] & mlo, 0u, pe[i] & ~mlo, 0u, k[2 * i + n][0], k[2 * i + n][1]);
      mma16(c, 0u, po[i] & mlo, 0u, po[i] & ~mlo, k[2 * i + n][2], k[2 * i + n][3]);
      const uint32_t r0 = pack_bf16(c[0], c[1]), r1 = pack_bf16(c[2], c[3]);
      const bool keep = (n == 0) && (t < i);
      qf[2 * i + n][0] = keep ? qf[2 * i + n][0] : r0;
      qf[2 * i + n][1] = keep ? qf[2 * i + n][1] : r1;
    }
  }
#pragma unroll
  for (int c = 0; c < 9; c++)
    asm volatile("stmatrix.sync.aligned.m8n8.x2.shared.b16 [%0], {%1, %2};" ::"r"(ad[c] + LQ), "r"(qf[c][0]), "r"(qf[c][1]) : "memory");
  asm volatile("fence.proxy.async.shared::cta;" ::: "memory");
}
__device__ __forceinline__ void tma4d(uint32_t dst, const CUtensorMap* m, uint32_t bar, int c1, int c2, int c3) {
  asm volatile("cp.async.bulk.tensor.4d.shared::cluster.global.mbarrier::complete_tx::bytes [%0], [%1, {%3, %4, %5, %6}], [%2];" ::"r"(dst),
               "l"(m), "r"(bar), "r"(0), "r"(c1), "r"(c2), "r"(c3) : "memory");
}

#define K1_NST 6
constexpr int K1_BST = K1_NST;
#define MAXJ 11
constexpr int K1_MAXJOBS = MAXJ;
constexpr uint32_t K1_FLAG_TARGET = 7;
constexpr uint32_t RDY_TARGET = 48;
constexpr uint32_t GATE_TARGET = 128 * 3;
struct alignas(64) Params {
  CUtensorMap tmA[2];
  CUtensorMap tmW[4];
  CUtensorMap tmQ, tmK, tmV;
  CUtensorMap tmL[3];
  CUtensorMap tmC, tmO[2], tmOt[2];
  uint16_t jobs[NCLUSTER][K1_MAXJOBS + 1];
  uint8_t order[256];
  uint8_t unit[64][8];
};

struct K1State {
  uint32_t bs, bph, aph;
  bf16* pp;
  int pld8;
  int png;
  int tn;
  int wsel;
};
__device__ __forceinline__ void k1_flag(const K1State& st, int lane, uint32_t bS) {
  if (st.png) {
    __syncwarp();
    if (lane == 0) mbar_arrive(bS);
  }
}

__device__ __forceinline__ void scale_q4(uint32_t* v) {
#pragma unroll
  for (int i = 0; i < 4; i++)
    asm volatile("{\n.reg .b32 t;\nmul.rn.bf16x2 t, %0, %2;\nfma.rn.bf16x2 %0, %0, %1, t;\n}" : "+r"(v[i]) : "r"(0x3E033E03u), "r"(0xB9D8B9D8u));
}
__device__ __forceinline__ void k1_first(const K1State& st, uint32_t job, uint32_t bAf, uint32_t bBf) {
  if (job & 3) {
    if ((job >> 14) & 1) mbar_wait(bAf, st.aph);
    mbar_wait(bBf + st.bs * 8, st.bph);
  }
}
__device__ __forceinline__ void k1_tile(float (&acc)[128], uint32_t (&pk)[64], K1State& st, uint32_t job, uint32_t njob, uint32_t sA, uint32_t sB,
                                        uint32_t bAf, uint32_t bAe, uint32_t bBf, uint32_t bBe, uint32_t bS, int wg, int warp, int lane, uint32_t rank) {
  const int a_sel = (job >> 2) & 1, mpair = (job >> 3) & 7, w_sel = (job >> 6) & 3, chunk0 = (job >> 8) & 63;
  const bool newA = (job >> 14) & 1, lastA = (job >> 15) & 1;
  const bool sig = (lane == 0) && (warp < 2);
  const bool siga = lastA && (lane == 0) && (warp == 2);
  const int KC = 8 + a_sel;
  uint32_t prev_bs = 0, a8_bs = 0;
#pragma unroll
  for (int kc = 0; kc < 9; kc++) {
    if (kc >= KC) break;
    uint32_t abase = sA + ((kc + 2) & 7) * 16384;
    if (kc == 8) {
      mbar_wait(bBf + st.bs * 8, st.bph);
      a8_bs = st.bs;
      abase = sB + st.bs * 16384;
      if (++st.bs == K1_BST) { st.bs = 0; st.bph ^= 1; }
    } else if (newA && kc > 0) {
      mbar_wait(bAf + kc * 8, st.aph);
    }
    const uint64_t da = make_desc(abase + wg * 8192, 16, 1024, 1);
#pragma unroll
    for (int ks = 0; ks < 2; ks++) {
      if (ks > 0 || kc > 0) mbar_wait(bBf + st.bs * 8, st.bph);
      const uint64_t db = make_desc(sB + st.bs * 16384, 2048, 1024, 1);
      wg_fence();
      wgmma_ss_n256<1, 0>(acc, da + (uint64_t)(ks * 4), db, (ks > 0) ? 1 : (kc > 0));
      wgmma_ss_n256<1, 0>(acc, da + (uint64_t)(ks * 4 + 2), db + (uint64_t)512, 1);
      wg_commit();
      const int PO = (kc < 8 ? kc : 0) * 8;
      wg_wait<1>();
      if (ks > 0 || kc > 0) {
        if (sig) mbar_arrive_cluster(bBe + prev_bs * 8, warp);
        if (ks == 0 && siga) mbar_arrive(bAe + (kc - 1) * 8);
      }
      if (kc < 8 && st.wsel >= 2) {
        if (st.wsel == 3) scale_q4(pk + PO + ks * 4);
        else quad_transpose(pk[PO + ks * 4], pk[PO + ks * 4 + 1], pk[PO + ks * 4 + 2], pk[PO + ks * 4 + 3], lane & 3);
      }
      if (kc < st.png) st_v4a(st.pp + kc * 32 + ks * st.pld8, pk[PO + ks * 4], pk[PO + ks * 4 + 1], pk[PO + ks * 4 + 2], pk[PO + ks * 4 + 3]);
      prev_bs = st.bs;
      if (++st.bs == K1_BST) { st.bs = 0; st.bph ^= 1; }
    }
  }
  if (newA) st.aph ^= 1;
  k1_flag(st, lane, bS);
  const bool isA = (w_sel == 2);
  bf16* out = (w_sel == 0) ? g_K : (w_sel == 1) ? g_V : isA ? g_QKVA : g_Q;
  const int ld = isA ? NQKVA : HDIM;
  const int row = mpair * 256 + rank * 128 + wg * 64 + warp * 16 + (lane >> 2);
  st.pp = out + (size_t)row * ld + chunk0 * 64 + (lane & 3) * 8;
  st.pld8 = 8 * ld;
  st.png = ((job & 3) + 1) * 2;
  st.wsel = w_sel;
  k1_first(st, njob, bAf, bBf);
  wg_wait<0>();
  fence_regs(acc);
  mbar_arrive_cluster_if(bBe + prev_bs * 8, warp & 1, sig);
  mbar_arrive_cluster_if(bBe + a8_bs * 8, warp & 1, sig && a_sel);
  mbar_arrive_if(bAe + 7 * 8, siga && !a_sel);
#pragma unroll
  for (int i = 0; i < 64; i++) {
    const int j = (i >> 3) * 16 + (i & 3) * 4 + ((i >> 2) & 1) * 2;
    pk[i] = pack_bf16(acc[j], acc[j + 1]);
  }
}

constexpr int K2_NST = 7;
constexpr uint32_t K2_END = 0x100;
#define PF_KC 4
#define FIRST_DRAW 3
#define PWAIT mbar_wait_ns<1000>
#define PVM 0x8A
#define W0 63
#define SPEC_HI 1.8446744073709552e19f
#define SPEC_LO 5.421010862427522e-20f
constexpr int K3_NST = 4;
__device__ __forceinline__ uint32_t k3_rot(uint32_t sv) { return (0x00E9u >> (2 * sv)) & 3; }
constexpr int K3_STAGE = 16384 + 32768 + 4096;
constexpr int SMEM_DATA = 7 * 32768;
constexpr int SMEM_BYTES = SMEM_DATA + 1024 + 768;

struct Cursor {
  uint32_t s, ph;
  __device__ __forceinline__ void next() {
    if (++s == K2_NST) { s = 0; ph ^= 1; }
  }
};

#define TURN_SYNC() bar_sync(mybar, 256)
#define TURN_ARRIVE() bar_arrive(otherbar, 256)
#define RELEASE_IF(cur, cond) mbar_arrive_cluster_if(bE + (cur).s * 8, warp & 1, sig && (cond))
#define RELEASE(cur) RELEASE_IF(cur, true)
#define ISSUE_PV(cur, first)                                                                                   \
  do {                                                                                                         \
    const uint64_t dv = make_desc(sbase + (cur).s * 32768, 16384, 1024, 1);                                    \
    _Pragma("unroll") for (int t = 0; t < 8; t++)                                                              \
        wgmma_rs_n128<1, 0>(O, P[4 * t], P[4 * t + 1], P[4 * t + 2], P[4 * t + 3], dv + (uint64_t)(t * 128), (t > 0) ? 1 : !(first)); \
  } while (0)
#define ISSUE_QK(cur)                                                                                          \
  do {                                                                                                         \
    const uint64_t dk = make_desc(sbase + (cur).s * 32768, 16, 1024, 1);                                       \
    _Pragma("unroll") for (int t = 0; t < 8; t++)                                                              \
        wgmma_rs_n128<0, 0>(S, Q[4 * t], Q[4 * t + 1], Q[4 * t + 2], Q[4 * t + 3], dk + (uint64_t)((t >> 2) * 1024 + (t & 3) * 2), t > 0); \
  } while (0)
#define EXPB(T)                                                                                                \
  do {                                                                                                         \
    _Pragma("unroll") for (int i = 4 * T; i < 4 * T + 4; i++) asm volatile("" : "+r"(P[i])::"memory");        \
    _Pragma("unroll") for (int jj = 2 * T; jj < 2 * T + 2; jj++) {                                             \
      const float e0 = ex2(S[jj * 4 + 0]), e1 = ex2(S[jj * 4 + 1]), e2 = ex2(S[jj * 4 + 2]), e3 = ex2(S[jj * 4 + 3]); \
      s0 += e0 + e1;                                                                                           \
      s1 += e2 + e3;                                                                                           \
      P[jj * 2 + 0] = pack_bf16(e0, e1);                                                                       \
      P[jj * 2 + 1] = pack_bf16(e2, e3);                                                                       \
    }                                                                                                          \
  } while (0)
#define EXPC(T)                                                                                                \
  do {                                                                                                         \
    if (T > 0 && ((PVM >> (T - 1)) & 1)) {                                                                     \
      anchor((T & 2) ? s0 : s1, never);                                                                        \
      wg_wait<__builtin_popcount(PVM >> T) - 1>();                                                             \
      if ((PVM >> T) == (128 >> T)) { fence_regs(O); RELEASE(cv); }                                            \
    }                                                                                                          \
    EXPB(T);                                                                                                   \
  } while (0)
#define MASK(G, g)                                                                                             \
  do {                                                                                                         \
    if ((g) * 8 > d) S[(G) * 4 + 0] = -INFINITY;                                                               \
    if ((g) * 8 + 1 > d) S[(G) * 4 + 1] = -INFINITY;                                                           \
    if ((g) * 8 - 8 > d) S[(G) * 4 + 2] = -INFINITY;                                                           \
    if ((g) * 8 - 7 > d) S[(G) * 4 + 3] = -INFINITY;                                                           \
  } while (0)
#define STORE_O(G)                                                                                             \
  do {                                                                                                         \
    st_v4(g_ctx + eoff + (G) * 32, pack_bf16(O[(G) * 16 + 0] * f0, O[(G) * 16 + 1] * f0), pack_bf16(O[(G) * 16 + 4] * f0, O[(G) * 16 + 5] * f0), \
          pack_bf16(O[(G) * 16 + 8] * f0, O[(G) * 16 + 9] * f0), pack_bf16(O[(G) * 16 + 12] * f0, O[(G) * 16 + 13] * f0)); \
    st_v4(g_ctx + eoff + 8 * KCAT + (G) * 32, pack_bf16(O[(G) * 16 + 2] * f1, O[(G) * 16 + 3] * f1), pack_bf16(O[(G) * 16 + 6] * f1, O[(G) * 16 + 7] * f1), \
          pack_bf16(O[(G) * 16 + 10] * f1, O[(G) * 16 + 11] * f1), pack_bf16(O[(G) * 16 + 14] * f1, O[(G) * 16 + 15] * f1)); \
  } while (0)

#define FLUSH()                                                                                                \
  do {                                                                                                         \
    _Pragma("unroll") for (int G = 0; G < 8; G++) {                                                            \
      st_v4a(st.pp + G * 32, pk[G * 8], pk[G * 8 + 1], pk[G * 8 + 2], pk[G * 8 + 3]);                          \
      st_v4a(st.pp + G * 32 + 8 * HDIM, pk[G * 8 + 4], pk[G * 8 + 5], pk[G * 8 + 6], pk[G * 8 + 7]);           \
    }                                                                                                          \
    k1_flag(st, lane, bS);                                                                                     \
  } while (0)

__global__ void __cluster_dims__(2, 1, 1) __launch_bounds__(384, 1)
fused_kernel(const __grid_constant__ Params p, const bf16* __restrict__ x, const bf16* __restrict__ gate_w, bf16* __restrict__ out) {
  extern __shared__ uint8_t smem_raw[];
  const uint32_t sbase = (smem_u32(smem_raw) + 1023) & ~1023u;
  const uint32_t sB = sbase, sA = sbase + K1_BST * 16384, sBar = sbase + SMEM_DATA;
  const uint32_t bAf = sBar, bAe = sBar + 64, bBf = sBar + 128, bBe = sBar + 176, bL = sBar + 224, bS = sBar + 232, bL2 = sBar + 240, sL = sA + 32768;
  const uint32_t bF = sBar + 256, bE = sBar + 320, bT = sBar + 384, sTick = sBar + 400, sItem = sBar + 416, bS2 = sBar + 448, bR = sBar + 456, bLast = sBar + 464, bH = sBar + 472, bT0 = sBar + 480;
  const uint32_t b3F = sBar + 512, b3E = sBar + 544, sGate = sBar + 576;
  const int tid = threadIdx.x, warp_g = __shfl_sync(0xffffffffu, tid >> 5, 0), lane = tid & 31;
  const uint32_t rank = cluster_rank();
  const int cl = blockIdx.x >> 1;
  TSM(0);
  if (tid == 0) {
    for (int i = 0; i < 8; i++) { mbar_init(bAf + i * 8, 1); mbar_init(bAe + i * 8, 2); }
    for (int i = 0; i < K1_BST; i++) { mbar_init(bBf + i * 8, 1); mbar_init(bBe + i * 8, 4); }
    mbar_init(bL, 1);
    mbar_init(bL2, 1);
    mbar_init(bR, 1);
    mbar_init(bLast, 1);
    mbar_init(bH, 4);
    mbar_init(bT0, 1);
    mbar_init(bS, 8);
    for (int i = 0; i < K2_NST; i++) { mbar_init(bF + i * 8, 1); mbar_init(bE + i * 8, 4); }
    mbar_init(bT, 1); mbar_init(bT + 8, 1);
    mbar_init(bS2, 8);
    for (int i = 0; i < K3_NST; i++) { mbar_init(b3F + i * 8, 1); mbar_init(b3E + i * 8, 4); }
    asm volatile("fence.mbarrier_init.release.cluster;" ::: "memory");
  }
  __syncwarp();
  if (warp_g != 8) cluster_sync();
  const int lr0 = blockIdx.x * 16;

  if (warp_g >= 8) {
    reg_dealloc<40>();
    if (warp_g == 8) {
      {
        const uint32_t job = p.jobs[cl][0];
        if (lane == 0) { prefetch_tmap(&p.tmA[(job >> 2) & 1]); prefetch_tmap(&p.tmW[(job >> 6) & 3]); }
        __syncwarp();
        cluster_sync();
      }
      if (elect_one()) {
        uint32_t bs = 0, bph = 1, aph = 1;
#pragma unroll 1
        for (int ji = 0; ji < K1_MAXJOBS; ji++) {
          const uint32_t job = p.jobs[cl][ji];
          if (!(job & 3)) break;
          const int a_sel = (job >> 2) & 1, mpair = (job >> 3) & 7, chunk0 = (job >> 8) & 63;
          const bool newA = (job >> 14) & 1;
          const int KC = a_sel ? 9 : 8;
          const uint32_t halfbytes = 8192;
          const bool lastjob = (ji + 1 == K1_MAXJOBS) || !(p.jobs[cl][ji + 1] & 3);
          const CUtensorMap* tw = &p.tmW[(job >> 6) & 3];
          {
            const uint32_t njob = (ji + 1 < K1_MAXJOBS) ? p.jobs[cl][ji + 1] : 0;
            if (!(njob & 3) && !newA) mbar_arrive(bLast);
          }
#pragma unroll 1
          for (int kc = 0; kc < KC; kc++) {
            if (kc == ((ji == 0) ? PF_KC : 0) && !lastjob) {
              const uint32_t njob = p.jobs[cl][ji + 1];
              const int nst = ((njob >> 2) & 1) ? 18 : 16;
#pragma unroll 1
              for (int t = (cl < 64) ? (cl & 7) : 0; t < nst; t += (cl < 64) ? 8 : 1)
                tma_pf3d(&p.tmW[(njob >> 6) & 3], 0, t * 32 + rank * 16, (njob >> 8) & 63);
            }
            if (kc == 8) {
              PWAIT(bBe + bs * 8, bph);
              mbar_expect(bBf + bs * 8, 16384);
              tma2d(sB + bs * 16384, &p.tmA[1], bBf + bs * 8, 512, mpair * 256 + rank * 128);
              if (++bs == K1_BST) { bs = 0; bph ^= 1; }
            } else if (newA) {
              PWAIT(bAe + kc * 8, aph);
              mbar_expect(bAf + kc * 8, 16384);
              tma2d(sA + ((kc + 2) & 7) * 16384, &p.tmA[a_sel], bAf + kc * 8, kc * 64, mpair * 256 + rank * 128);
              if (kc == 7 && lastjob) mbar_arrive(bLast);
            }
#pragma unroll 1
            for (int kk = 0; kk < 2; kk++) {
              PWAIT(bBe + bs * 8, bph);
              mbar_expect(bBf + bs * 8, 2 * halfbytes);
              tma3d_mc(sB + bs * 16384 + rank * halfbytes, tw, bBf + bs * 8, 0, kc * 64 + kk * 32 + rank * 16, chunk0, 3);
              if (++bs == K1_BST) { bs = 0; bph ^= 1; }
            }
          }
          if (newA) aph ^= 1;
        }
        Cursor c{0, 0};
        int pcol = 0;
        PWAIT(bR, 0);
        uint32_t tick = lds32(sTick + 8), seen = 1u << (p.order[tick] >> 4);
        asm volatile("fence.proxy.async.global;" ::: "memory");
#pragma unroll 1
        for (int it = 0;; it++) {
          const uint32_t item = (tick < 256) ? p.order[tick] : (K2_END | min(tick - 256, 255u));
          asm volatile("st.shared.u32 [%0], %1;" ::"r"(sItem + (it & 7) * 4), "r"(item) : "memory");
          if (item >= K2_END) break;
          const int h = item >> 3, j = item & 7;
          const int blk = 2 * j + (int)(rank ^ (it & 1));
          const int col = h * 128 + rank * 64;
          const int nb = 2 * j + 2;
          if (!((seen >> (h >> 1)) & 1)) {
            wait_flag(&g_sync[F_HP + (h >> 1)], RDY_TARGET);
            asm volatile("fence.proxy.async.global;" ::: "memory");
            seen |= 1u << (h >> 1);
          }
          PWAIT(bE + c.s * 8, c.ph);
          mbar_expect(bF + c.s * 8, 32768);
          tma2d(sbase + c.s * 32768, &p.tmQ, bF + c.s * 8, h * 128, blk * 128);
          tma2d(sbase + c.s * 32768 + 16384, &p.tmQ, bF + c.s * 8, h * 128 + 64, blk * 128);
          c.next();
#pragma unroll 1
          for (int n = nb - 1; n >= 0; n--) {
            if (n == 0 && rank == 0) tick = atomicAdd(&g_sync[F_TICK], 1u);
            PWAIT(bE + c.s * 8, c.ph);
            mbar_expect(bF + c.s * 8, 32768);
            tma2d_mc(sbase + c.s * 32768 + rank * 16384, &p.tmK, bF + c.s * 8, col, n * 128, 3);
            c.next();
            if (n < nb - 1 || it > 0) {
              PWAIT(bE + c.s * 8, c.ph);
              mbar_expect(bF + c.s * 8, 32768);
              tma2d_mc(sbase + c.s * 32768 + rank * 16384, &p.tmV, bF + c.s * 8, (n < nb - 1) ? col : pcol, (n < nb - 1) ? (n + 1) * 128 : 0, 3);
              c.next();
            }
          }
          pcol = col;
          if (rank == 0) {
            asm volatile(
                "{\n.reg .b32 a, b;\nmapa.shared::cluster.u32 a, %0, 1;\nmapa.shared::cluster.u32 b, %1, 1;\n"
                "st.async.shared::cluster.mbarrier::complete_tx::bytes.u32 [a], %2, [b];\n}" ::"r"(sTick + (it & 1) * 4),
                "r"(bT + (it & 1) * 8), "r"(tick) : "memory");
          } else {
            mbar_expect(bT + (it & 1) * 8, 4);
            PWAIT(bT + (it & 1) * 8, (it >> 1) & 1);
            tick = lds32(sTick + (it & 1) * 4);
          }
        }
        PWAIT(bE + c.s * 8, c.ph);
        mbar_expect(bF + c.s * 8, 32768);
        tma2d_mc(sbase + c.s * 32768 + rank * 16384, &p.tmV, bF + c.s * 8, pcol, 0, 3);
        const uint32_t unit = tick - 256;
        if (unit < 64) {
          const int mblk = (7 - (p.unit[unit][0] >> 1)) * 2 + rank, nhalf = p.unit[unit][0] & 1;
          const uint32_t rot = k3_rot(c.s), nfree = ((0x1Au >> c.s) & 1) ? 2 : 3;
#pragma unroll 1
          for (int i = 0; i < K2_NST - 1; i++) {
            c.next();
            PWAIT(bE + c.s * 8, c.ph);
          }
          uint32_t have = 0;
#pragma unroll 1
          for (uint32_t idx = 0; idx < p.unit[unit][2]; idx++) {
            const int kk = p.unit[unit][3] + idx + ((idx >= p.unit[unit][4]) ? p.unit[unit][5] : 0);
            const uint32_t s = (rot + idx) & 3;
            if (idx >= nfree) PWAIT((idx < 4) ? bH : b3E + s * 8, (idx < 4) ? 0 : (~idx >> 2) & 1);
            mbar_expect(b3F + s * 8, K3_STAGE);
            const uint32_t st = sbase + s * K3_STAGE;
            const int sel = (kk < 9), k = sel ? kk : kk - 9, kr = k * 64 + rank * 32;
            tma3d_mc(st + 16384 + rank * 16384, &p.tmO[sel], b3F + s * 8, 0, kr, nhalf * 4, 3);
            tma2d_mc(st + 49152 + rank * 2048, &p.tmOt[sel], b3F + s * 8, 512 + nhalf * 32, kr, 3);
            if (sel && idx == 0) {
              wait_flag(&g_sync[F_OA + mblk], 8);
              asm volatile("fence.proxy.async.global;" ::: "memory");
            }
            if (!sel && !((have >> (k >> 1)) & 1)) {
#pragma unroll 1
              for (uint32_t spins = 0; spins < (1u << 22); spins++) {
                asm volatile("ld.acquire.gpu.global.u32 %0, [%1];" : "=r"(have) : "l"(&g_sync[F_CTX + mblk]) : "memory");
                if ((have >> (k >> 1)) & 1) break;
                __nanosleep(100);
              }
              asm volatile("fence.proxy.async.global;" ::: "memory");
            }
            tma2d(st, &p.tmC, b3F + s * 8, (sel ? 64 + k : k) * 64, mblk * 128);
          }
        }
      }
    }
    __syncwarp();
    if (warp_g == 8) {
      uint32_t v = 0;
      if (lane == 0) {
        __threadfence();
        v = atomicAdd(&g_sync[F_DONE], 1u);
      }
      if (__shfl_sync(0xffffffffu, v, 0) == 2 * NCLUSTER - 1) {
        reinterpret_cast<uint4*>(g_sync)[lane] = make_uint4(0, 0, 0, 0);
        if (lane == 0) g_sync[F_EPOCH] = lds32(sGate + 64) + 1;
      }
    }
    asm volatile("" ::: "memory");
    if (__shfl_sync(0xffffffffu, warp_g, 0) != 8) {
      if (lr0 < S_LEN) {
#pragma unroll 1
        for (int i = warp_g - 9; i < 16; i += 3) {
          const float g = gate_row(lr0 + i, lane, x, gate_w);
          if (lane == 0) asm volatile("st.shared.f32 [%0], %1;" ::"r"(sGate + i * 4), "f"(g) : "memory");
        }
        bar_arrive(3, 256 + 96);
        if (lane == 0) {
          __threadfence();
          atomicAdd(&g_sync[F_GATE], 1u);
        }
      }
      uint32_t aph = 1;
#pragma unroll 1
      for (int ji = 0; ji < K1_MAXJOBS; ji++) aph ^= (p.jobs[cl][ji] >> 14) & 1;
      if (warp_g == 9 && lane == 0) {
#pragma unroll 1
        for (int ji = 0; ji < K1_MAXJOBS; ji++) {
          const uint32_t job = p.jobs[cl][ji];
          if (!(job & 3)) break;
          PWAIT(bS, ji & 1);
          __threadfence();
          atomicAdd(&g_sync[(((job >> 6) & 3) == 2) ? (F_QKVA + ((job >> 3) & 7) * 2 + rank) : (F_HP + ((job >> 10) & 15))], 1u);
        }
#pragma unroll 1
        for (int it = 0;; it++) {
          PWAIT(bS2, it & 1);
          const uint32_t item = lds32(sItem + (it & 7) * 4), nxt = lds32(sItem + ((it + 1) & 7) * 4);
          __threadfence();
          atomicOr(&g_sync[F_CTX + (item & 7) * 2 + (rank ^ (it & 1))], 1u << (item >> 3));
          if (nxt >= K2_END) break;
        }
      } else if (warp_g == 11) {
        if (lane == 0) {
          prefetch_tmap(&p.tmQ); prefetch_tmap(&p.tmK); prefetch_tmap(&p.tmV);
          asm volatile("st.shared.u32 [%0], %1;" ::"r"(sGate + 64), "r"(__ldcg(&g_sync[F_EPOCH])) : "memory");
          wait_flag(&g_sync[F_GATE], GATE_TARGET);
          uint32_t tick;
          if (rank == 0) {
            PWAIT(bLast, 0);
            PWAIT(bAe + FIRST_DRAW * 8, aph);
            tick = atomicAdd(&g_sync[F_TICK], 1u);
            asm volatile("st.shared.u32 [%0], %1;" ::"r"(sTick + 8), "r"(tick) : "memory");
            asm volatile(
                "{\n.reg .b32 a, b;\nmapa.shared::cluster.u32 a, %0, 1;\nmapa.shared::cluster.u32 b, %1, 1;\n"
                "st.async.shared::cluster.mbarrier::complete_tx::bytes.u32 [a], %2, [b];\n}" ::"r"(sTick + 8), "r"(bT0), "r"(tick) : "memory");
          } else {
            mbar_expect(bT0, 4);
            PWAIT(bT0, 0);
            tick = lds32(sTick + 8);
          }
          wait_flag(&g_sync[F_HP + (p.order[tick] >> 4)], RDY_TARGET);
          mbar_arrive(bR);
        }
      } else if (warp_g == 10) {
        if (lr0 < S_LEN && lane == 0) {
          prefetch_tmap(&p.tmL[0]); prefetch_tmap(&p.tmL[1]); prefetch_tmap(&p.tmL[2]);
          wait_flag(&g_sync[F_QKVA + (lr0 >> 7)], K1_FLAG_TARGET);
          wait_flag(&g_sync[F_QKVA + (max(lr0 - 16, 0) >> 7)], K1_FLAG_TARGET);
          asm volatile("fence.proxy.async.global;" ::: "memory");
          PWAIT(bLast, 0);
#pragma unroll 1
          for (int kc = 0; kc < 6; kc++) {
            PWAIT(bAe + kc * 8, aph);
            if (kc == 3) {
              mbar_expect(bL, LV);
              tma4d(sL, &p.tmL[0], bL, lr0 / 2 - 8, 9, 0);
              tma4d(sL + LQ, &p.tmL[1], bL, lr0 / 2, 0, 0);
            }
          }
          mbar_expect(bL2, LQ);
          tma4d(sL + LV, &p.tmL[0], bL2, lr0 / 2 - 8, 18, 0);
        }
        __syncwarp();
        bar_sync(5, 256 + 32);
        if (lr0 < S_LEN && lane == 0) {
          asm volatile("cp.async.bulk.tensor.4d.global.shared::cta.bulk_group [%0, {%2, %3, %2, %2}], [%1];" ::"l"(&p.tmL[2]), "r"(sL + LQ), "r"(0), "r"(lr0 / 2) : "memory");
          asm volatile("cp.async.bulk.commit_group;" ::: "memory");
          asm volatile("cp.async.bulk.wait_group.read 0;" ::: "memory");
        }
        __syncwarp();
        if (lane < 12) mbar_arrive_cluster(bE + (4 + lane % 3) * 8, (lane / 3) & 1);
        if (lr0 < S_LEN && lane == 0) {
          asm volatile("cp.async.bulk.wait_group 0;" ::: "memory");
          asm volatile("fence.proxy.async.global;" ::: "memory");
          __threadfence();
          atomicAdd(&g_sync[F_OA + (lr0 >> 7)], 1u);
        }
      }
    }
    __syncwarp();
    cluster_sync();
  } else {
    reg_alloc<232>();
    const int wg = warp_g >> 2, warp = warp_g & 3, q = lane & 3;
    const bool sig = (lane == 0) && (warp < 2);
    {
      K1State st{0, 0, 0, nullptr, 0, 0, 0, 0};
      float acc[128];
      uint32_t pk[64];
      if (wg == 0) { TS(0, 0); TSC(0, 2); }
      uint32_t job = p.jobs[cl][0];
      k1_first(st, job, bAf, bBf);
      {
#pragma unroll 1
        for (int ji = 0; job & 3; ji++) {
          const uint32_t njob = p.jobs[cl][ji + 1];
          k1_tile(acc, pk, st, job, njob, sA, sB, bAf, bAe, bBf, bBe, bS, wg, warp, lane, rank);
          job = njob;
        }
      }
#pragma unroll
      for (int i = 0; i < 4; i++)
        mbar_arrive_cluster_if(bE + i * 8, warp & 1, sig);
      if (lr0 < S_LEN) bar_sync(3, 256 + 96);
      if (st.wsel == 3) {
#pragma unroll
        for (int G = 0; G < 16; G++) scale_q4(pk + G * 4);
      }
      FLUSH();
      if (wg == 0) { TS(0, 1); TSC(0, 3); }
      if (lr0 < S_LEN) {
        const float gate0 = __uint_as_float(lds32(sGate + (lane >> 2) * 8)), gate1 = __uint_as_float(lds32(sGate + (lane >> 2) * 8 + 4));
        local_attn(lr0, warp_g, sL, bL, bL2, lane, gate0, gate1);
      }
      bar_arrive(5, 256 + 32);
    }
    __syncwarp();
    uint32_t item, rot;
    {
      const int mybar = 1 + wg, otherbar = 2 - wg;
      const uint32_t never = blockIdx.y;
      float S[64], O[64];
      uint32_t P[32], Q[32];
      float m0 = 0.f, m1 = 0.f, l0 = 1.f, l1 = 1.f, gf0 = 0.f, gf1 = 0.f;
      uint32_t eoff = 0, prev_single = 0;
      Cursor c{0, 0};
      if (wg == 1) bar_arrive(1, 256);
      if (wg == 0) { TS(1, 0); TSC(1, 2); }
#pragma unroll 1
      for (int it = 0;; it++) {
        TB(0);
        const int hi = (int)(rank ^ (it & 1));
        Cursor cq = c, ck, cv, cs0, cs1;
        rot = k3_rot(c.s);
        c.next();
        ck = c; c.next();
        cs0 = ck; cs1 = ck; cv = ck;
        if (it > 0) { cv = c; c.next(); }
        if (!hi) {
          ck = c; c.next();
          cs1 = c; c.next();
        }
        mbar_wait(bF + cq.s * 8, cq.ph);
        TB(1);
        item = lds32(sItem + (it & 7) * 4);
        {
          const uint32_t qa = sbase + cq.s * 32768 + (wg * 64 + warp * 16 + (lane & 15)) * 128;
#pragma unroll
          for (int t = 0; t < 8; t++)
            ldsm_x4(Q[4 * t], Q[4 * t + 1], Q[4 * t + 2], Q[4 * t + 3], qa + (t >> 2) * 16384 + ((((t & 3) * 2 + (lane >> 4)) ^ (lane & 7)) << 4));
        }
        const uint32_t rdy = mbar_test(bF + ck.s * 8, ck.ph) & mbar_test(bF + cv.s * 8, cv.ph);
        l0 += __shfl_xor_sync(0xffffffffu, l0, 1);
        l1 += __shfl_xor_sync(0xffffffffu, l1, 1);
        l0 += __shfl_xor_sync(0xffffffffu, l0, 2);
        l1 += __shfl_xor_sync(0xffffffffu, l1, 2);
        const bool last = item >= K2_END;
        if (last) {
          cv = cq; ck = cq;
        } else if (!rdy) {
          mbar_wait2(bF + ck.s * 8, ck.ph, bF + cv.s * 8, cv.ph);
        }
        TB(2);
        TURN_SYNC();
        TB(3);
        TRC(last ? 2 : 1);
        if (it > 0) {
          wg_fence();
          ISSUE_PV(cv, prev_single);
          wg_commit();
        } else {
          wg_fence();
          wg_commit();
        }
        wg_fence();
        ISSUE_QK(ck);
        wg_commit();
        if (!(last && wg == 1)) TURN_ARRIVE();
        RELEASE_IF(cq, !last);
        TB(4);
        asm volatile("" : "+f"(gf0), "+f"(gf1), "+f"(l0), "+f"(l1));
        const float f0 = __fdividef(1.f - gf0, l0), f1 = __fdividef(1.f - gf1, l1);
        wg_wait<1>();
        fence_regs(O);
        fence_regs(P);
        TB(5);
        if (it > 0) {
          RELEASE_IF(cv, !last);
          mbar_arrive_cluster_if(bH, warp & 1, sig && last);
          STORE_O(0); STORE_O(1); STORE_O(2); STORE_O(3);
          __syncwarp();
          mbar_arrive_if(bS2, lane == 0);
        }
        TB(6);
        if (!last) {
          const int row = (2 * (item & 7) + hi) * 128 + wg * 64 + warp * 16 + (lane >> 2);
          eoff = row * KCAT + (item >> 3) * 128 + q * 8;
          asm volatile("ld.global.f32 %0, [%1];" : "=f"(gf0) : "l"(g_gate + row));
          asm volatile("ld.global.f32 %0, [%1];" : "=f"(gf1) : "l"(g_gate + row + 8));
          if (!hi) {
            mbar_wait2(bF + cs0.s * 8, cs0.ph, bF + cs1.s * 8, cs1.ph);
            RELEASE(cs0);
            RELEASE(cs1);
          }
        }
        TB(7);
        wg_wait<0>();
        fence_regs(S);
        TB(8);
        if (last) break;
        RELEASE(ck);
        const int nblk = 2 * (item & 7) + 1 + hi;
        prev_single = (nblk == 1);
        float s0 = 0.f, s1 = 0.f;
        l0 = 0.f; l1 = 0.f;
        m0 = 0.f; m1 = 0.f;
        bool shifted = false;
        {
          const int d = warp * 16 + (lane >> 2) - 2 * q;
          if (wg == 0) {
#pragma unroll
            for (int jj = 0; jj < 8; jj++) MASK(jj, jj);
            EXPB(0); EXPB(1); EXPB(2); EXPB(3);
#pragma unroll
            for (int i = 32; i < 64; i++) S[i] = -INFINITY;
#pragma unroll
            for (int i = 16; i < 32; i++) P[i] = 0;
          } else {
#pragma unroll
            for (int jj = 0; jj < 8; jj++) MASK(jj + 8, jj);
            EXPB(0); EXPB(1); EXPB(2); EXPB(3); EXPB(4); EXPB(5); EXPB(6); EXPB(7);
          }
        }
        float chk = (q == 0 && !(fminf(s0, s1) >= SPEC_LO)) ? INFINITY : s0 + s1;
        fence_regs(P);
        TB(9);
#pragma unroll 1
        for (int n = 1;; n++) {
          if (__any_sync(0xffffffffu, !(chk <= SPEC_HI))) {
            float mx0 = fmaxf(S[0], S[1]), mx1 = fmaxf(S[2], S[3]);
#pragma unroll
            for (int jj = 1; jj < 16; jj++) {
              mx0 = fmaxf(mx0, fmaxf(S[jj * 4 + 0], S[jj * 4 + 1]));
              mx1 = fmaxf(mx1, fmaxf(S[jj * 4 + 2], S[jj * 4 + 3]));
            }
            mx0 = fmaxf(mx0, __shfl_xor_sync(0xffffffffu, mx0, 1));
            mx1 = fmaxf(mx1, __shfl_xor_sync(0xffffffffu, mx1, 1));
            mx0 = fmaxf(mx0, __shfl_xor_sync(0xffffffffu, mx0, 2));
            mx1 = fmaxf(mx1, __shfl_xor_sync(0xffffffffu, mx1, 2));
            const float lo = (n == 1) ? -INFINITY : 0.f;
            mx0 = fmaxf(mx0, lo);
            mx1 = fmaxf(mx1, lo);
            m0 += mx0; m1 += mx1;
            shifted = true;
            const float sc0 = ex2(-fmaxf(mx0, 0.f)), sc1 = ex2(-fmaxf(mx1, 0.f));
            l0 *= sc0; l1 *= sc1;
            s0 = 0.f; s1 = 0.f;
#pragma unroll
            for (int jj = 0; jj < 16; jj++) {
              const float e0 = ex2(S[jj * 4 + 0] - mx0), e1 = ex2(S[jj * 4 + 1] - mx0), e2 = ex2(S[jj * 4 + 2] - mx1), e3 = ex2(S[jj * 4 + 3] - mx1);
              s0 += e0 + e1;
              s1 += e2 + e3;
              P[jj * 2 + 0] = pack_bf16(e0, e1);
              P[jj * 2 + 1] = pack_bf16(e2, e3);
              O[jj * 4 + 0] *= sc0;
              O[jj * 4 + 1] *= sc0;
              O[jj * 4 + 2] *= sc1;
              O[jj * 4 + 3] *= sc1;
            }
          }
          l0 += s0;
          l1 += s1;
          if (n >= nblk) break;
          ck = c; c.next();
          cv = c; c.next();
          mbar_wait(bF + ck.s * 8, ck.ph);
          mbar_wait(bF + cv.s * 8, cv.ph);
          TURN_SYNC();
          TRC(0);
          wg_fence();
          ISSUE_QK(ck);
          wg_commit();
          {
            const uint64_t dv = make_desc(sbase + cv.s * 32768, 16384, 1024, 1);
#pragma unroll
            for (int t = 0; t < 8; t++) {
              wgmma_rs_n128<1, 0>(O, P[4 * t], P[4 * t + 1], P[4 * t + 2], P[4 * t + 3], dv + (uint64_t)(t * 128), (t > 0) ? 1 : (n != 1));
              if ((PVM >> t) & 1) wg_commit();
            }
          }
          TURN_ARRIVE();
          s0 = 0.f; s1 = 0.f;
          wg_wait<__builtin_popcount(PVM)>();
          fence_regs(S);
          RELEASE(ck);
          if (shifted) {
#pragma unroll
            for (int i = 0; i < 64; i++) S[i] -= (i & 2) ? m1 : m0;
          }
          wg_wait<__builtin_popcount(PVM) - 1>();
          EXPC(0); EXPC(1); EXPC(2); EXPC(3); EXPC(4); EXPC(5); EXPC(6); EXPC(7);
          chk = s0 + s1;
        }
      }
      TRC(3);
      if (wg == 1) { TS(1, 1); TSC(1, 3); }
    }
    __syncwarp();
    const uint32_t unit = item & 255;
    if (unit < 64) {
      const int mblk = (7 - (p.unit[unit][0] >> 1)) * 2 + rank, nhalf = p.unit[unit][0] & 1, ks = p.unit[unit][1];
      const int k0 = 0, k1 = p.unit[unit][2];
      float acc[144];
      uint32_t s = rot, ph = 0, prev = 0;
      if (wg == 0) { TS(2, 0); TSC(2, 2); }
      uint32_t fa[16], fb[16];
      const uint32_t aoff = (wg * 64 + warp * 16 + (lane & 15)) * 128 + (((lane >> 4) ^ (lane & 7)) << 4);
#define C_LOAD(F)                                                                                              \
  do {                                                                                                         \
    mbar_wait(b3F + s * 8, ph);                                                                                \
    _Pragma("unroll") for (int t = 0; t < 4; t++)                                                              \
        ldsm_x4(F[4 * t], F[4 * t + 1], F[4 * t + 2], F[4 * t + 3], sbase + s * K3_STAGE + (aoff ^ (t * 32))); \
  } while (0)
#define C_STEP(F, G)                                                                                           \
  {                                                                                                            \
    const uint32_t st = sbase + s * K3_STAGE;                                                                  \
    const uint64_t db = make_desc(st + 16384, 4096, 1024, 1), dt = make_desc(st + 49152, 16, 512, 2);          \
    wg_fence();                                                                                                \
    _Pragma("unroll") for (int t = 0; t < 4; t++) {                                                            \
      const int sd = (t > 0) || (k > k0);                                                                      \
      wgmma_rs_n256<1, 0>(acc, F[4 * t], F[4 * t + 1], F[4 * t + 2], F[4 * t + 3], db + (uint64_t)((t >> 1) * 1024 + (t & 1) * 128), sd); \
      wgmma_rs_n32<1, 128>(acc, F[4 * t], F[4 * t + 1], F[4 * t + 2], F[4 * t + 3], dt + (uint64_t)(t * 64), sd); \
    }                                                                                                          \
    wg_commit();                                                                                               \
    wg_wait<1>();                                                                                              \
    fence_regs(G);                                                                                             \
    mbar_arrive_cluster_if(b3E + prev * 8, warp & 1, sig && k > k0);                                           \
    prev = s;                                                                                                  \
    s = (s + 1) & 3;                                                                                           \
    if (s == rot) ph ^= 1;                                                                                     \
    if (++k == k1) break;                                                                                      \
    C_LOAD(G);                                                                                                 \
  }
      C_LOAD(fa);
#pragma unroll
      for (int i = 0; i < 16; i++) fb[i] = 0;
#pragma unroll 1
      for (int k = k0;;) {
        C_STEP(fa, fb)
        C_STEP(fb, fa)
      }
      wg_wait<0>();
      fence_regs(acc);
      cluster_arrive();
      if (wg == 0) TS(2, 4);
      const int tile = mblk * 2 + nhalf;
      uint4* wp = g_part + (size_t)((tile * 4 + ks) * 4) * 5 * 256 + tid;
      const uint32_t sown = sbase + wg * 8192 + (tid & 127) * 16;
#pragma unroll
      for (int d = 0; d < 4; d++) {
        if (d != ks) {
#pragma unroll
          for (int i = 0; i < 4; i++)
            __stcg(wp + (d * 5 + i) * 256,
                   make_uint4(pack_bf16(acc[d * 32 + i * 8], acc[d * 32 + i * 8 + 1]), pack_bf16(acc[d * 32 + i * 8 + 2], acc[d * 32 + i * 8 + 3]),
                              pack_bf16(acc[d * 32 + i * 8 + 4], acc[d * 32 + i * 8 + 5]), pack_bf16(acc[d * 32 + i * 8 + 6], acc[d * 32 + i * 8 + 7])));
          __stcg(reinterpret_cast<uint2*>(wp - tid + (d * 5 + 4) * 256) + tid,
                 make_uint2(pack_bf16(acc[128 + d * 4], acc[128 + d * 4 + 1]), pack_bf16(acc[128 + d * 4 + 2], acc[128 + d * 4 + 3])));
        } else {
#pragma unroll
          for (int i = 0; i < 9; i++) {
            const int o = (i < 8) ? d * 32 + i * 4 : 128 + d * 4;
            asm volatile("st.shared.v4.f32 [%0], {%1, %2, %3, %4};" ::"r"(sown + (i >> 2) * K3_STAGE + (i & 3) * 2048), "f"(acc[o]), "f"(acc[o + 1]), "f"(acc[o + 2]), "f"(acc[o + 3]) : "memory");
          }
        }
      }
      __threadfence();
      __syncwarp();
      if (wg == 0) TS(2, 5);
      if (lane == 0) {
        unsigned int* cnt = &g_sync[F_XCH + tile * 8 + warp_g];
        const uint32_t xtarget = lds32(sGate + 64) * 4 + 4;
        atomicAdd(cnt, 1u);
        uint32_t v, spins = 0;
        do {
          asm volatile("ld.acquire.gpu.global.u32 %0, [%1];" : "=r"(v) : "l"(cnt) : "memory");
        } while ((int)(v - xtarget) < 0 && ++spins < (1u << 24));
      }
      __syncwarp();
      if (wg == 0) TS(2, 6);
      float r[36];
#pragma unroll
      for (int i = 0; i < 9; i++)
        asm volatile("ld.shared.v4.f32 {%0, %1, %2, %3}, [%4];" : "=f"(r[i * 4]), "=f"(r[i * 4 + 1]), "=f"(r[i * 4 + 2]), "=f"(r[i * 4 + 3])
                     : "r"(sown + (i >> 2) * K3_STAGE + (i & 3) * 2048) : "memory");
#pragma unroll
      for (int sI = 1; sI < 4; sI++) {
        const int src = (ks + sI) & 3;
        const uint4* rp = g_part + (size_t)(((tile * 4 + src) * 4) + ks) * 5 * 256;
#pragma unroll
        for (int i = 0; i < 4; i++) {
          const uint4 v = __ldcg(rp + i * 256 + tid);
          r[i * 8] += bf_lo(v.x); r[i * 8 + 1] += bf_hi(v.x); r[i * 8 + 2] += bf_lo(v.y); r[i * 8 + 3] += bf_hi(v.y);
          r[i * 8 + 4] += bf_lo(v.z); r[i * 8 + 5] += bf_hi(v.z); r[i * 8 + 6] += bf_lo(v.w); r[i * 8 + 7] += bf_hi(v.w);
        }
        const uint2 v = __ldcg(reinterpret_cast<const uint2*>(rp + 4 * 256) + tid);
        r[32] += bf_lo(v.x); r[33] += bf_hi(v.x); r[34] += bf_lo(v.y); r[35] += bf_hi(v.y);
      }
      const int row = mblk * 128 + wg * 64 + warp * 16 + (lane >> 2);
      bf16* o0 = out + (size_t)row * DM + nhalf * 256 + ks * 64 + 8 * q;
#pragma unroll
      for (int G = 0; G < 2; G++) {
        uint32_t a0 = pack_bf16(r[G * 16], r[G * 16 + 1]), a1 = pack_bf16(r[G * 16 + 4], r[G * 16 + 5]);
        uint32_t a2 = pack_bf16(r[G * 16 + 8], r[G * 16 + 9]), a3 = pack_bf16(r[G * 16 + 12], r[G * 16 + 13]);
        uint32_t b0 = pack_bf16(r[G * 16 + 2], r[G * 16 + 3]), b1 = pack_bf16(r[G * 16 + 6], r[G * 16 + 7]);
        uint32_t b2 = pack_bf16(r[G * 16 + 10], r[G * 16 + 11]), b3 = pack_bf16(r[G * 16 + 14], r[G * 16 + 15]);
        quad_transpose(a0, a1, a2, a3, q);
        quad_transpose(b0, b1, b2, b3, q);
        st_v4(o0 + G * 32, a0, a1, a2, a3);
        st_v4(o0 + 8 * DM + G * 32, b0, b1, b2, b3);
      }
      {
        uint32_t t0 = pack_bf16(r[32], r[33]), t1 = pack_bf16(r[34], r[35]), t2 = 0, t3 = 0;
        quad_transpose(t0, t1, t2, t3, q);
        if (q < 2) st_v4(out + (size_t)(row + q * 8) * DM + 512 + nhalf * 32 + ks * 8, t0, t1, t2, t3);
      }
    } else {
      cluster_arrive();
    }
    if (wg == 0) { TS(2, 1); TSC(2, 3); }
    cluster_wait();
  }
}

typedef CUresult (*EncFn)(CUtensorMap*, CUtensorMapDataType, cuuint32_t, void*, const cuuint64_t*, const cuuint64_t*, const cuuint32_t*,
                          const cuuint32_t*, CUtensorMapInterleave, CUtensorMapSwizzle, CUtensorMapL2promotion, CUtensorMapFloatOOBfill);

static void enc2d(EncFn enc, CUtensorMap* m, const void* ptr, uint64_t cols, uint64_t rows, uint32_t bc, uint32_t br,
                  CUtensorMapSwizzle sw = CU_TENSOR_MAP_SWIZZLE_128B) {
  cuuint64_t gd[2] = {cols, rows}, gs[1] = {cols * 2};
  cuuint32_t bx[2] = {bc, br}, es[2] = {1, 1};
  enc(m, CU_TENSOR_MAP_DATA_TYPE_BFLOAT16, 2, const_cast<void*>(ptr), gd, gs, bx, es, CU_TENSOR_MAP_INTERLEAVE_NONE, sw,
      CU_TENSOR_MAP_L2_PROMOTION_L2_256B, CU_TENSOR_MAP_FLOAT_OOB_FILL_NONE);
}
static void enc3d(EncFn enc, CUtensorMap* m, const void* ptr, uint64_t cols, uint64_t rows, uint32_t br, uint32_t bch) {
  cuuint64_t gd[3] = {64, rows, cols / 64}, gs[2] = {cols * 2, 128};
  cuuint32_t bx[3] = {64, br, bch}, es[3] = {1, 1, 1};
  enc(m, CU_TENSOR_MAP_DATA_TYPE_BFLOAT16, 3, const_cast<void*>(ptr), gd, gs, bx, es, CU_TENSOR_MAP_INTERLEAVE_NONE,
      CU_TENSOR_MAP_SWIZZLE_128B, CU_TENSOR_MAP_L2_PROMOTION_L2_256B, CU_TENSOR_MAP_FLOAT_OOB_FILL_NONE);
}

static int g_sched[10] = {11, 10, 7, 4, 4, 4, 6, 7, 6, 24};
static void build_k1_jobs(Params& p) {
  int cnt[NCLUSTER];
  for (int c = 0; c < NCLUSTER; c++) {
    cnt[c] = 0;
    for (int i = 0; i <= K1_MAXJOBS; i++) p.jobs[c][i] = 0;
  }
  auto add = [&](int c, int nch, int a_sel, int mp, int w_sel, int chunk0) {
    p.jobs[c][cnt[c]++] = (uint16_t)((nch - 1) | (a_sel << 2) | (mp << 3) | (w_sel << 6) | (chunk0 << 8));
  };
  const int *cg = g_sched, *xg = g_sched + 4;
  for (int mp = 0; mp < 8; mp++) {
    int k = 0;
    for (int i = 0; i < K1_MAXJOBS; i++)
      for (int g = 0; g < 4; g++)
        if (i < cg[g]) { add(g * 8 + mp, 4, 0, mp, k & 1, (k >> 1) * 4); k++; }
    k = 0;
    for (int i = 0; i < K1_MAXJOBS; i++)
      for (int g = 0; g < 4; g++)
        if (i < xg[g]) {
          if (k < 7) add((4 + g) * 8 + mp, k == 0 ? 3 : 4, 1, mp, 2, k == 0 ? 24 : (k - 1) * 4);
          else add((4 + g) * 8 + mp, 4, 1, mp, 3, (k - 7) * 4);
          k++;
        }
    add(64 + mp / 4, 4, 1, mp, 3, 14 * 4);
    add(64 + mp / 4, 4, 1, mp, 3, 15 * 4);
  }
  for (int cc = 0; cc < NCLUSTER; cc++)
    for (int i = 0; i < cnt[cc]; i++) {
      const int key = p.jobs[cc][i] & 0x3C;
      if (i == 0 || (p.jobs[cc][i - 1] & 0x3C) != key) p.jobs[cc][i] |= (1 << 14);
      if (i == cnt[cc] - 1 || (p.jobs[cc][i + 1] & 0x3C) != key) p.jobs[cc][i] |= (1 << 15);
    }
}

static void build_k2_items(Params& p) {
  int n = 0;
  const int SCHED_N1 = g_sched[8], SCHED_N2 = g_sched[9];
  int N0 = 2, J0 = 2;
  for (int j = 7; j >= J0; j--)
    for (int h = 0; h < N0; h++) p.order[n++] = (uint8_t)(h * 8 + j);
  for (int j = 7; j >= 0; j--)
    for (int h = 0; h < SCHED_N1; h++)
      if (!(h < N0 && j >= J0)) p.order[n++] = (uint8_t)(h * 8 + j);
  for (int j = 7; j >= 4; j--)
    for (int h = SCHED_N1; h < SCHED_N2; h++) p.order[n++] = (uint8_t)(h * 8 + j);
  for (int j = 7; j >= 0; j--)
    for (int h = SCHED_N1; h < 32; h++)
      if (!(h < SCHED_N2 && j >= 4)) p.order[n++] = (uint8_t)(h * 8 + j);
}

static void build_k3_units(Params& p) {
  float slope = 0.045f;
  int NE = 25;
  for (int t = 0; t < 16; t++) {
    const int u[4] = {t, 31 - t, 32 + t, 63 - t};
    float acc = 0.f;
    int k0 = 0, l0 = NE;
    for (int i = 0; i < 4; i++) {
      acc += 18.25f + slope * (31.5f - u[i]);
      const int k1 = (i == 3) ? 73 : (int)(acc + 0.5f);
      const int e0 = NE * i / 4, e1 = NE * (i + 1) / 4;
      uint8_t* w = p.unit[u[i]];
      w[0] = (uint8_t)t; w[1] = (uint8_t)i; w[2] = (uint8_t)(k1 - k0); w[3] = (uint8_t)e0; w[4] = (uint8_t)(e1 - e0); w[5] = (uint8_t)(l0 - e1);
      l0 += (k1 - k0) - (e1 - e0);
      k0 = k1;
    }
  }
}

extern "C" void kernel_launch(void* const* d_in, const int* in_sizes, int n_in, void* d_out, int out_size) {
  const bf16* x = (const bf16*)d_in[0];
  const bf16* wqkv = (const bf16*)d_in[1];
  const bf16* wo = (const bf16*)d_in[2];
  const bf16* ckv = (const bf16*)d_in[4];
  const bf16* w_q = (const bf16*)d_in[5];
  const bf16* w_uk = (const bf16*)d_in[6];
  const bf16* w_uv = (const bf16*)d_in[7];
  const bf16* w_o = (const bf16*)d_in[8];
  const bf16* gate_w = (const bf16*)d_in[9];

  EncFn enc = nullptr;
  cudaDriverEntryPointQueryResult qr;
  cudaGetDriverEntryPoint("cuTensorMapEncodeTiled", (void**)&enc, cudaEnableDefault, &qr);
  void *pQ, *pK, *pV, *pCtx, *pQA;
  cudaGetSymbolAddress(&pQA, g_QKVA);
  cudaGetSymbolAddress(&pQ, g_Q);
  cudaGetSymbolAddress(&pK, g_K);
  cudaGetSymbolAddress(&pV, g_V);
  cudaGetSymbolAddress(&pCtx, g_ctx);

  static Params p;
  enc2d(enc, &p.tmA[0], ckv, DC, S_LEN, 64, 128);
  enc2d(enc, &p.tmA[1], x, DM, S_LEN, 64, 128);
  enc3d(enc, &p.tmW[0], w_uk, HDIM, DC, 16, 4);
  enc3d(enc, &p.tmW[1], w_uv, HDIM, DC, 16, 4);
  enc3d(enc, &p.tmW[2], wqkv, NQKVA, DM, 16, 4);
  enc3d(enc, &p.tmW[3], w_q, HDIM, DM, 16, 4);
  build_k1_jobs(p);
  enc2d(enc, &p.tmQ, pQ, HDIM, S_LEN, 64, 128);
  enc2d(enc, &p.tmK, pK, HDIM, S_LEN, 64, 128);
  enc2d(enc, &p.tmV, pV, HDIM, S_LEN, 64, 128);
  build_k2_items(p);
  build_k3_units(p);
  for (int i = 0; i < 3; i++) {
    const cuuint64_t ld = (i < 2 ? NQKVA : KCAT) * 2, nch = (i < 2) ? 27 : 9;
    cuuint64_t gd[4] = {64, S_LEN / 2, i ? 2 : nch, i ? nch : 2}, gs[3] = {2 * ld, i ? ld : 128, i ? 128 : ld};
    cuuint32_t bx[4] = {64, i ? 8u : 16u, i ? 2u : 9u, i ? 9u : 2u}, es[4] = {1, 1, 1, 1};
    enc(&p.tmL[i], CU_TENSOR_MAP_DATA_TYPE_BFLOAT16, 4, (i < 2) ? pQA : (void*)((bf16*)pCtx + HDIM), gd, gs, bx, es, CU_TENSOR_MAP_INTERLEAVE_NONE,
        CU_TENSOR_MAP_SWIZZLE_128B, CU_TENSOR_MAP_L2_PROMOTION_L2_256B, CU_TENSOR_MAP_FLOAT_OOB_FILL_NONE);
  }
  enc2d(enc, &p.tmC, pCtx, KCAT, S_LEN, 64, 128);
  enc3d(enc, &p.tmO[0], w_o, DM, HDIM, 32, 4);
  enc3d(enc, &p.tmO[1], wo, DM, DM, 32, 4);
  enc2d(enc, &p.tmOt[0], w_o, DM, HDIM, 32, 32, CU_TENSOR_MAP_SWIZZLE_64B);
  enc2d(enc, &p.tmOt[1], wo, DM, DM, 32, 32, CU_TENSOR_MAP_SWIZZLE_64B);

  cudaFuncSetAttribute(fused_kernel, cudaFuncAttributeMaxDynamicSharedMemorySize, SMEM_BYTES);
  fused_kernel<<<NCLUSTER * 2, 384, SMEM_BYTES>>>(p, x, gate_w, (bf16*)d_out);
}
```

```cpp
#include <cuda_runtime.h>
#include <cuda_bf16.h>
#include <cuda.h>
#include <stdint.h>

typedef __nv_bfloat16 bf16;

constexpr int S_LEN = 2048, DM = 576, DC = 512, HDIM = 4096, NQKVA = 1728, KCAT = 4672;
constexpr int NCLUSTER = 66;

__device__ __align__(1024) bf16 g_Q[S_LEN * HDIM];
__device__ __align__(1024) bf16 g_K[S_LEN * HDIM];
__device__ __align__(1024) bf16 g_V[S_LEN * HDIM];
__device__ __align__(1024) bf16 g_QKVA[S_LEN * NQKVA + 64];
__device__ __align__(1024) bf16 g_ctx[S_LEN * KCAT];
__device__ float g_gate[S_LEN];
__device__ __align__(1024) uint4 g_part[32 * 4 * 4 * 5 * 256];
__device__ __align__(16) unsigned int g_sync[400];
constexpr int F_QKVA = 0, F_HP = 16, F_CTX = 32, F_OA = 48, F_GATE = 96, F_TICK = 97, F_DONE = 98, F_XCH = 128, F_EPOCH = 384;

__device__ __forceinline__ uint32_t smem_u32(const void* p) { return (uint32_t)__cvta_generic_to_shared(p); }
__device__ __forceinline__ void mbar_init(uint32_t a, uint32_t c) {
  asm volatile("mbarrier.init.shared::cta.b64 [%0], %1;" ::"r"(a), "r"(c));
}
__device__ __forceinline__ void mbar_expect(uint32_t a, uint32_t b) {
  asm volatile("mbarrier.arrive.expect_tx.shared::cta.b64 _, [%0], %1;" ::"r"(a), "r"(b) : "memory");
}
#define TS(k, i)
#define TSC(k, i)
#define TSM(k)
#define BSEG(i)
#define TB(k)
#define TRC(fl)
#define SPIN_LIMIT "4194304"
__device__ __forceinline__ void mbar_wait(uint32_t a, uint32_t parity) {
  asm volatile(
      "{\n.reg .pred p;\n.reg .u32 n;\n"
      "mbarrier.try_wait.parity.shared::cta.b64 p, [%0], %1;\n"
      "@p bra DONE;\n"
      "mov.u32 n, 0;\n"
      "LOOP:\n"
      "mbarrier.try_wait.parity.shared::cta.b64 p, [%0], %1;\n"
      "@p bra DONE;\n"
      "add.u32 n, n, 1;\n"
      "setp.lt.u32 p, n, " SPIN_LIMIT ";\n"
      "@p bra LOOP;\n"
      "DONE:\n}" ::"r"(a), "r"(parity) : "memory");
}
template <int NS>
__device__ __forceinline__ void mbar_wait_ns(uint32_t a, uint32_t parity) {
  asm volatile(
      "{\n.reg .pred p;\n.reg .u32 n;\n"
      "mov.u32 n, 0;\n"
      "LOOP:\n"
      "mbarrier.try_wait.parity.shared::cta.b64 p, [%0], %1, %2;\n"
      "@p bra DONE;\n"
      "add.u32 n, n, 1;\n"
      "setp.lt.u32 p, n, " SPIN_LIMIT ";\n"
      "@p bra LOOP;\n"
      "DONE:\n}" ::"r"(a), "r"(parity), "n"(NS) : "memory");
}
__device__ __forceinline__ void mbar_wait2(uint32_t a, uint32_t pa, uint32_t b, uint32_t pb) {
  asm volatile(
      "{\n.reg .pred p, q;\n.reg .u32 n;\n"
      "mov.u32 n, 0;\n"
      "LOOP:\n"
      "mbarrier.try_wait.parity.shared::cta.b64 p, [%0], %1;\n"
      "mbarrier.try_wait.parity.shared::cta.b64 q, [%2], %3;\n"
      "add.u32 n, n, 1;\n"
      "and.pred p, p, q;\n"
      "setp.lt.and.u32 p, n, " SPIN_LIMIT ", !p;\n"
      "@p bra LOOP;\n"
      "}" ::"r"(a), "r"(pa), "r"(b), "r"(pb) : "memory");
}
__device__ __forceinline__ uint32_t mbar_test(uint32_t a, uint32_t parity) {
  uint32_t r;
  asm volatile("{\n.reg .pred p;\nmbarrier.test_wait.parity.shared::cta.b64 p, [%1], %2;\nselp.u32 %0, 1, 0, p;\n}" : "=r"(r) : "r"(a), "r"(parity) : "memory");
  return r;
}
__device__ __forceinline__ void mbar_arrive(uint32_t a) {
  asm volatile("mbarrier.arrive.shared::cta.b64 _, [%0];" ::"r"(a) : "memory");
}
__device__ __forceinline__ void mbar_arrive_cluster(uint32_t a, uint32_t cta) {
  asm volatile("{\n.reg .b32 r;\nmapa.shared::cluster.u32 r, %0, %1;\nmbarrier.arrive.shared::cluster.b64 _, [r];\n}" ::"r"(a),
               "r"(cta) : "memory");
}
__device__ __forceinline__ void mbar_arrive_cluster_if(uint32_t a, uint32_t cta, bool pred) {
  asm volatile("{\n.reg .b32 r;\n.reg .pred p;\nsetp.ne.u32 p, %2, 0;\nmapa.shared::cluster.u32 r, %0, %1;\n@p mbarrier.arrive.shared::cluster.b64 _, [r];\n}" ::"r"(a),
               "r"(cta), "r"((uint32_t)pred) : "memory");
}
__device__ __forceinline__ void anchor(float v, uint32_t pred) {
  asm volatile("{\n.reg .pred p;\nsetp.ne.u32 p, %1, 0;\n@p st.shared.f32 [%1], %0;\n}" ::"f"(v), "r"(pred) : "memory");
}
__device__ __forceinline__ void mbar_arrive_if(uint32_t a, bool pred) {
  asm volatile("{\n.reg .pred p;\nsetp.ne.u32 p, %1, 0;\n@p mbarrier.arrive.shared::cta.b64 _, [%0];\n}" ::"r"(a), "r"((uint32_t)pred) : "memory");
}
__device__ __forceinline__ void tma2d(uint32_t dst, const CUtensorMap* m, uint32_t bar, int c0, int c1) {
  asm volatile("cp.async.bulk.tensor.2d.shared::cluster.global.mbarrier::complete_tx::bytes [%0], [%1, {%3, %4}], [%2];" ::"r"(dst),
               "l"(m), "r"(bar), "r"(c0), "r"(c1) : "memory");
}
__device__ __forceinline__ void tma2d_mc(uint32_t dst, const CUtensorMap* m, uint32_t bar, int c0, int c1, uint16_t mask) {
  asm volatile(
      "cp.async.bulk.tensor.2d.shared::cluster.global.mbarrier::complete_tx::bytes.multicast::cluster [%0], [%1, {%3, %4}], [%2], %5;" ::"r"(dst),
      "l"(m), "r"(bar), "r"(c0), "r"(c1), "h"(mask) : "memory");
}
__device__ __forceinline__ void tma3d_mc(uint32_t dst, const CUtensorMap* m, uint32_t bar, int c0, int c1, int c2, uint16_t mask) {
  asm volatile(
      "cp.async.bulk.tensor.3d.shared::cluster.global.mbarrier::complete_tx::bytes.multicast::cluster [%0], [%1, {%3, %4, %5}], [%2], %6;" ::"r"(dst),
      "l"(m), "r"(bar), "r"(c0), "r"(c1), "r"(c2), "h"(mask) : "memory");
}
__device__ __forceinline__ void tma3d(uint32_t dst, const CUtensorMap* m, uint32_t bar, int c0, int c1, int c2) {
  asm volatile(
      "cp.async.bulk.tensor.3d.shared::cluster.global.mbarrier::complete_tx::bytes [%0], [%1, {%3, %4, %5}], [%2];" ::"r"(dst),
      "l"(m), "r"(bar), "r"(c0), "r"(c1), "r"(c2) : "memory");
}
__device__ __forceinline__ void tma_pf2d(const CUtensorMap* m, int c0, int c1) {
  asm volatile("cp.async.bulk.prefetch.tensor.2d.L2.global [%0, {%1, %2}];" ::"l"(m), "r"(c0), "r"(c1) : "memory");
}
__device__ __forceinline__ void tma_pf3d(const CUtensorMap* m, int c0, int c1, int c2) {
  asm volatile("cp.async.bulk.prefetch.tensor.3d.L2.global [%0, {%1, %2, %3}];" ::"l"(m), "r"(c0), "r"(c1), "r"(c2) : "memory");
}
__device__ __forceinline__ void prefetch_tmap(const CUtensorMap* m) {
  asm volatile("prefetch.tensormap [%0];" ::"l"(m) : "memory");
}
__device__ __forceinline__ void cluster_arrive() { asm volatile("barrier.cluster.arrive.relaxed.aligned;" ::: "memory"); }
__device__ __forceinline__ void cluster_wait() { asm volatile("barrier.cluster.wait.aligned;" ::: "memory"); }
__device__ __forceinline__ void cluster_sync() {
  cluster_arrive();
  cluster_wait();
}
__device__ __forceinline__ uint32_t cluster_rank() {
  uint32_t r;
  asm volatile("mov.u32 %0, %%cluster_ctarank;" : "=r"(r));
  return r;
}
__device__ __forceinline__ bool elect_one() {
  uint32_t p;
  asm volatile("{\n.reg .pred q;\nelect.sync _|q, 0xffffffff;\nselp.u32 %0, 1, 0, q;\n}" : "=r"(p));
  return p;
}
__device__ __forceinline__ void ldsm_x4(uint32_t& r0, uint32_t& r1, uint32_t& r2, uint32_t& r3, uint32_t addr) {
  asm volatile("ldmatrix.sync.aligned.m8n8.x4.shared.b16 {%0, %1, %2, %3}, [%4];" : "=r"(r0), "=r"(r1), "=r"(r2), "=r"(r3) : "r"(addr) : "memory");
}
__device__ __forceinline__ void wg_fence() { asm volatile("wgmma.fence.sync.aligned;" ::: "memory"); }
__device__ __forceinline__ void wg_commit() { asm volatile("wgmma.commit_group.sync.aligned;" ::: "memory"); }
template <int N>
__device__ __forceinline__ void wg_wait() { asm volatile("wgmma.wait_group.sync.aligned %0;" ::"n"(N) : "memory"); }
template <int N>
__device__ __forceinline__ void reg_alloc() { asm volatile("setmaxnreg.inc.sync.aligned.u32 %0;" ::"n"(N)); }
template <int N>
__device__ __forceinline__ void reg_dealloc() { asm volatile("setmaxnreg.dec.sync.aligned.u32 %0;" ::"n"(N)); }
__device__ __forceinline__ void bar_sync(int id, int n) { asm volatile("bar.sync %0, %1;" ::"r"(id), "r"(n) : "memory"); }
__device__ __forceinline__ void bar_arrive(int id, int n) { asm volatile("bar.arrive %0, %1;" ::"r"(id), "r"(n) : "memory"); }
template <int NT>
__device__ __forceinline__ void fence_regs(float (&d)[NT]) {
#pragma unroll
  for (int i = 0; i < NT; i++) asm volatile("" : "+f"(d[i])::"memory");
}
template <int NT>
__device__ __forceinline__ void fence_regs(uint32_t (&d)[NT]) {
#pragma unroll
  for (int i = 0; i < NT; i++) asm volatile("" : "+r"(d[i])::"memory");
}
__device__ __forceinline__ uint64_t make_desc(uint32_t saddr, uint32_t lbo, uint32_t sbo, uint32_t layout) {
  return (uint64_t)((saddr & 0x3FFFF) >> 4) | ((uint64_t)(lbo >> 4) << 16) | ((uint64_t)(sbo >> 4) << 32) | ((uint64_t)layout << 62);
}
__device__ __forceinline__ uint32_t pack_bf16(float lo, float hi) {
  uint32_t r;
  asm("cvt.rn.bf16x2.f32 %0, %1, %2;" : "=r"(r) : "f"(hi), "f"(lo));
  return r;
}
__device__ __forceinline__ float ex2(float x) {
  float r;
  asm("ex2.approx.ftz.f32 %0, %1;" : "=f"(r) : "f"(x));
  return r;
}
__device__ __forceinline__ void st_v4(void* p, uint32_t a, uint32_t b, uint32_t c, uint32_t d) {
#define ST_MOD ".cs"
  asm volatile("st.global" ST_MOD ".v4.b32 [%0], {%1, %2, %3, %4};" ::"l"(p), "r"(a), "r"(b), "r"(c), "r"(d) : "memory");
}
#define STA_MOD ".cs"
__device__ __forceinline__ void st_v4a(void* p, uint32_t a, uint32_t b, uint32_t c, uint32_t d) {
  asm volatile("st.global" STA_MOD ".v4.b32 [%0], {%1, %2, %3, %4};" ::"l"(p), "r"(a), "r"(b), "r"(c), "r"(d) : "memory");
}
template <typename T>
__device__ __forceinline__ T* ptr_add(T* base, uint32_t bytes) {
  uint64_t r;
  asm volatile("{\n.reg .u32 l, h;\nmov.b64 {l, h}, %1;\nadd.cc.u32 l, l, %2;\naddc.u32 h, h, 0;\nmov.b64 %0, {l, h};\n}" : "=l"(r) : "l"(base), "r"(bytes));
  return reinterpret_cast<T*>(r);
}
__device__ __forceinline__ float bf_lo(uint32_t v) { return __uint_as_float(v << 16); }
__device__ __forceinline__ float bf_hi(uint32_t v) { return __uint_as_float(v & 0xFFFF0000u); }

__device__ __forceinline__ void quad_transpose(uint32_t& a0, uint32_t& a1, uint32_t& a2, uint32_t& a3, int q) {
  const bool o1 = q & 1, o2 = q & 2;
  uint32_t t0 = o1 ? a0 : a1, t1 = o1 ? a2 : a3;
  t0 = __shfl_xor_sync(0xffffffffu, t0, 1);
  t1 = __shfl_xor_sync(0xffffffffu, t1, 1);
  if (o1) { a0 = t0; a2 = t1; } else { a1 = t0; a3 = t1; }
  t0 = o2 ? a0 : a2;
  t1 = o2 ? a1 : a3;
  t0 = __shfl_xor_sync(0xffffffffu, t0, 2);
  t1 = __shfl_xor_sync(0xffffffffu, t1, 2);
  if (o2) { a0 = t0; a1 = t1; } else { a2 = t0; a3 = t1; }
}

template<int TB, int OFF, int NT>
__device__ __forceinline__ void wgmma_ss_n256(float (&d)[NT], uint64_t da, uint64_t db, int scale_d) {
  asm volatile("{\n.reg .pred p;\nsetp.ne.b32 p, %130, 0;\n"
    "wgmma.mma_async.sync.aligned.m64n256k16.f32.bf16.bf16 {%0, %1, %2, %3, %4, %5, %6, %7, %8, %9, %10, %11, %12, %13, %14, %15, %16, %17, %18, %19, %20, %21, %22, %23, %24, %25, %26, %27, %28, %29, %30, %31, %32, %33, %34, %35, %36, %37, %38, %39, %40, %41, %42, %43, %44, %45, %46, %47, %48, %49, %50, %51, %52, %53, %54, %55, %56, %57, %58, %59, %60, %61, %62, %63, %64, %65, %66, %67, %68, %69, %70, %71, %72, %73, %74, %75, %76, %77, %78, %79, %80, %81, %82, %83, %84, %85, %86, %87, %88, %89, %90, %91, %92, %93, %94, %95, %96, %97, %98, %99, %100, %101, %102, %103, %104, %105, %106, %107, %108, %109, %110, %111, %112, %113, %114, %115, %116, %117, %118, %119, %120, %121, %122, %123, %124, %125, %126, %127}, %128, %129, p, 1, 1, 0, %131;\n}\n"
    : "+f"(d[OFF+0]), "+f"(d[OFF+1]), "+f"(d[OFF+2]), "+f"(d[OFF+3]), "+f"(d[OFF+4]), "+f"(d[OFF+5]), "+f"(d[OFF+6]), "+f"(d[OFF+7]), "+f"(d[OFF+8]), "+f"(d[OFF+9]), "+f"(d[OFF+10]), "+f"(d[OFF+11]), "+f"(d[OFF+12]), "+f"(d[OFF+13]), "+f"(d[OFF+14]), "+f"(d[OFF+15]), "+f"(d[OFF+16]), "+f"(d[OFF+17]), "+f"(d[OFF+18]), "+f"(d[OFF+19]), "+f"(d[OFF+20]), "+f"(d[OFF+21]), "+f"(d[OFF+22]), "+f"(d[OFF+23]), "+f"(d[OFF+24]), "+f"(d[OFF+25]), "+f"(d[OFF+26]), "+f"(d[OFF+27]), "+f"(d[OFF+28]), "+f"(d[OFF+29]), "+f"(d[OFF+30]), "+f"(d[OFF+31]), "+f"(d[OFF+32]), "+f"(d[OFF+33]), "+f"(d[OFF+34]), "+f"(d[OFF+35]), "+f"(d[OFF+36]), "+f"(d[OFF+37]), "+f"(d[OFF+38]), "+f"(d[OFF+39]), "+f"(d[OFF+40]), "+f"(d[OFF+41]), "+f"(d[OFF+42]), "+f"(d[OFF+43]), "+f"(d[OFF+44]), "+f"(d[OFF+45]), "+f"(d[OFF+46]), "+f"(d[OFF+47]), "+f"(d[OFF+48]), "+f"(d[OFF+49]), "+f"(d[OFF+50]), "+f"(d[OFF+51]), "+f"(d[OFF+52]), "+f"(d[OFF+53]), "+f"(d[OFF+54]), "+f"(d[OFF+55]), "+f"(d[OFF+56]), "+f"(d[OFF+57]), "+f"(d[OFF+58]), "+f"(d[OFF+59]), "+f"(d[OFF+60]), "+f"(d[OFF+61]), "+f"(d[OFF+62]), "+f"(d[OFF+63]), "+f"(d[OFF+64]), "+f"(d[OFF+65]), "+f"(d[OFF+66]), "+f"(d[OFF+67]), "+f"(d[OFF+68]), "+f"(d[OFF+69]), "+f"(d[OFF+70]), "+f"(d[OFF+71]), "+f"(d[OFF+72]), "+f"(d[OFF+73]), "+f"(d[OFF+74]), "+f"(d[OFF+75]), "+f"(d[OFF+76]), "+f"(d[OFF+77]), "+f"(d[OFF+78]), "+f"(d[OFF+79]), "+f"(d[OFF+80]), "+f"(d[OFF+81]), "+f"(d[OFF+82]), "+f"(d[OFF+83]), "+f"(d[OFF+84]), "+f"(d[OFF+85]), "+f"(d[OFF+86]), "+f"(d[OFF+87]), "+f"(d[OFF+88]), "+f"(d[OFF+89]), "+f"(d[OFF+90]), "+f"(d[OFF+91]), "+f"(d[OFF+92]), "+f"(d[OFF+93]), "+f"(d[OFF+94]), "+f"(d[OFF+95]), "+f"(d[OFF+96]), "+f"(d[OFF+97]), "+f"(d[OFF+98]), "+f"(d[OFF+99]), "+f"(d[OFF+100]), "+f"(d[OFF+101]), "+f"(d[OFF+102]), "+f"(d[OFF+103]), "+f"(d[OFF+104]), "+f"(d[OFF+105]), "+f"(d[OFF+106]), "+f"(d[OFF+107]), "+f"(d[OFF+108]), "+f"(d[OFF+109]), "+f"(d[OFF+110]), "+f"(d[OFF+111]), "+f"(d[OFF+112]), "+f"(d[OFF+113]), "+f"(d[OFF+114]), "+f"(d[OFF+115]), "+f"(d[OFF+116]), "+f"(d[OFF+117]), "+f"(d[OFF+118]), "+f"(d[OFF+119]), "+f"(d[OFF+120]), "+f"(d[OFF+121]), "+f"(d[OFF+122]), "+f"(d[OFF+123]), "+f"(d[OFF+124]), "+f"(d[OFF+125]), "+f"(d[OFF+126]), "+f"(d[OFF+127])
    : "l"(da), "l"(db), "r"(scale_d), "n"(TB));
}
template<int TB, int OFF, int NT>
__device__ __forceinline__ void wgmma_ss_n32(float (&d)[NT], uint64_t da, uint64_t db, int scale_d) {
  asm volatile("{\n.reg .pred p;\nsetp.ne.b32 p, %18, 0;\n"
    "wgmma.mma_async.sync.aligned.m64n32k16.f32.bf16.bf16 {%0, %1, %2, %3, %4, %5, %6, %7, %8, %9, %10, %11, %12, %13, %14, %15}, %16, %17, p, 1, 1, 0, %19;\n}\n"
    : "+f"(d[OFF+0]), "+f"(d[OFF+1]), "+f"(d[OFF+2]), "+f"(d[OFF+3]), "+f"(d[OFF+4]), "+f"(d[OFF+5]), "+f"(d[OFF+6]), "+f"(d[OFF+7]), "+f"(d[OFF+8]), "+f"(d[OFF+9]), "+f"(d[OFF+10]), "+f"(d[OFF+11]), "+f"(d[OFF+12]), "+f"(d[OFF+13]), "+f"(d[OFF+14]), "+f"(d[OFF+15])
    : "l"(da), "l"(db), "r"(scale_d), "n"(TB));
}
template<int TB, int OFF, int NT>
__device__ __forceinline__ void wgmma_rs_n128(float (&d)[NT], uint32_t a0, uint32_t a1, uint32_t a2, uint32_t a3, uint64_t db, int scale_d) {
  asm volatile("{\n.reg .pred p;\nsetp.ne.b32 p, %69, 0;\n"
    "wgmma.mma_async.sync.aligned.m64n128k16.f32.bf16.bf16 {%0, %1, %2, %3, %4, %5, %6, %7, %8, %9, %10, %11, %12, %13, %14, %15, %16, %17, %18, %19, %20, %21, %22, %23, %24, %25, %26, %27, %28, %29, %30, %31, %32, %33, %34, %35, %36, %37, %38, %39, %40, %41, %42, %43, %44, %45, %46, %47, %48, %49, %50, %51, %52, %53, %54, %55, %56, %57, %58, %59, %60, %61, %62, %63}, {%64, %65, %66, %67}, %68, p, 1, 1, %70;\n}\n"
    : "+f"(d[OFF+0]), "+f"(d[OFF+1]), "+f"(d[OFF+2]), "+f"(d[OFF+3]), "+f"(d[OFF+4]), "+f"(d[OFF+5]), "+f"(d[OFF+6]), "+f"(d[OFF+7]), "+f"(d[OFF+8]), "+f"(d[OFF+9]), "+f"(d[OFF+10]), "+f"(d[OFF+11]), "+f"(d[OFF+12]), "+f"(d[OFF+13]), "+f"(d[OFF+14]), "+f"(d[OFF+15]), "+f"(d[OFF+16]), "+f"(d[OFF+17]), "+f"(d[OFF+18]), "+f"(d[OFF+19]), "+f"(d[OFF+20]), "+f"(d[OFF+21]), "+f"(d[OFF+22]), "+f"(d[OFF+23]), "+f"(d[OFF+24]), "+f"(d[OFF+25]), "+f"(d[OFF+26]), "+f"(d[OFF+27]), "+f"(d[OFF+28]), "+f"(d[OFF+29]), "+f"(d[OFF+30]), "+f"(d[OFF+31]), "+f"(d[OFF+32]), "+f"(d[OFF+33]), "+f"(d[OFF+34]), "+f"(d[OFF+35]), "+f"(d[OFF+36]), "+f"(d[OFF+37]), "+f"(d[OFF+38]), "+f"(d[OFF+39]), "+f"(d[OFF+40]), "+f"(d[OFF+41]), "+f"(d[OFF+42]), "+f"(d[OFF+43]), "+f"(d[OFF+44]), "+f"(d[OFF+45]), "+f"(d[OFF+46]), "+f"(d[OFF+47]), "+f"(d[OFF+48]), "+f"(d[OFF+49]), "+f"(d[OFF+50]), "+f"(d[OFF+51]), "+f"(d[OFF+52]), "+f"(d[OFF+53]), "+f"(d[OFF+54]), "+f"(d[OFF+55]), "+f"(d[OFF+56]), "+f"(d[OFF+57]), "+f"(d[OFF+58]), "+f"(d[OFF+59]), "+f"(d[OFF+60]), "+f"(d[OFF+61]), "+f"(d[OFF+62]), "+f"(d[OFF+63])
    : "r"(a0), "r"(a1), "r"(a2), "r"(a3), "l"(db), "r"(scale_d), "n"(TB));
}
template<int TB, int OFF, int NT>
__device__ __forceinline__ void wgmma_rs_n256(float (&d)[NT], uint32_t a0, uint32_t a1, uint32_t a2, uint32_t a3, uint64_t db, int scale_d) {
  asm volatile("{\n.reg .pred p;\nsetp.ne.b32 p, %133, 0;\n"
    "wgmma.mma_async.sync.aligned.m64n256k16.f32.bf16.bf16 {%0, %1, %2, %3, %4, %5, %6, %7, %8, %9, %10, %11, %12, %13, %14, %15, %16, %17, %18, %19, %20, %21, %22, %23, %24, %25, %26, %27, %28, %29, %30, %31, %32, %33, %34, %35, %36, %37, %38, %39, %40, %41, %42, %43, %44, %45, %46, %47, %48, %49, %50, %51, %52, %53, %54, %55, %56, %57, %58, %59, %60, %61, %62, %63, %64, %65, %66, %67, %68, %69, %70, %71, %72, %73, %74, %75, %76, %77, %78, %79, %80, %81, %82, %83, %84, %85, %86, %87, %88, %89, %90, %91, %92, %93, %94, %95, %96, %97, %98, %99, %100, %101, %102, %103, %104, %105, %106, %107, %108, %109, %110, %111, %112, %113, %114, %115, %116, %117, %118, %119, %120, %121, %122, %123, %124, %125, %126, %127}, {%128, %129, %130, %131}, %132, p, 1, 1, %134;\n}\n"
    : "+f"(d[OFF+0]), "+f"(d[OFF+1]), "+f"(d[OFF+2]), "+f"(d[OFF+3]), "+f"(d[OFF+4]), "+f"(d[OFF+5]), "+f"(d[OFF+6]), "+f"(d[OFF+7]), "+f"(d[OFF+8]), "+f"(d[OFF+9]), "+f"(d[OFF+10]), "+f"(d[OFF+11]), "+f"(d[OFF+12]), "+f"(d[OFF+13]), "+f"(d[OFF+14]), "+f"(d[OFF+15]), "+f"(d[OFF+16]), "+f"(d[OFF+17]), "+f"(d[OFF+18]), "+f"(d[OFF+19]), "+f"(d[OFF+20]), "+f"(d[OFF+21]), "+f"(d[OFF+22]), "+f"(d[OFF+23]), "+f"(d[OFF+24]), "+f"(d[OFF+25]), "+f"(d[OFF+26]), "+f"(d[OFF+27]), "+f"(d[OFF+28]), "+f"(d[OFF+29]), "+f"(d[OFF+30]), "+f"(d[OFF+31]), "+f"(d[OFF+32]), "+f"(d[OFF+33]), "+f"(d[OFF+34]), "+f"(d[OFF+35]), "+f"(d[OFF+36]), "+f"(d[OFF+37]), "+f"(d[OFF+38]), "+f"(d[OFF+39]), "+f"(d[OFF+40]), "+f"(d[OFF+41]), "+f"(d[OFF+42]), "+f"(d[OFF+43]), "+f"(d[OFF+44]), "+f"(d[OFF+45]), "+f"(d[OFF+46]), "+f"(d[OFF+47]), "+f"(d[OFF+48]), "+f"(d[OFF+49]), "+f"(d[OFF+50]), "+f"(d[OFF+51]), "+f"(d[OFF+52]), "+f"(d[OFF+53]), "+f"(d[OFF+54]), "+f"(d[OFF+55]), "+f"(d[OFF+56]), "+f"(d[OFF+57]), "+f"(d[OFF+58]), "+f"(d[OFF+59]), "+f"(d[OFF+60]), "+f"(d[OFF+61]), "+f"(d[OFF+62]), "+f"(d[OFF+63]), "+f"(d[OFF+64]), "+f"(d[OFF+65]), "+f"(d[OFF+66]), "+f"(d[OFF+67]), "+f"(d[OFF+68]), "+f"(d[OFF+69]), "+f"(d[OFF+70]), "+f"(d[OFF+71]), "+f"(d[OFF+72]), "+f"(d[OFF+73]), "+f"(d[OFF+74]), "+f"(d[OFF+75]), "+f"(d[OFF+76]), "+f"(d[OFF+77]), "+f"(d[OFF+78]), "+f"(d[OFF+79]), "+f"(d[OFF+80]), "+f"(d[OFF+81]), "+f"(d[OFF+82]), "+f"(d[OFF+83]), "+f"(d[OFF+84]), "+f"(d[OFF+85]), "+f"(d[OFF+86]), "+f"(d[OFF+87]), "+f"(d[OFF+88]), "+f"(d[OFF+89]), "+f"(d[OFF+90]), "+f"(d[OFF+91]), "+f"(d[OFF+92]), "+f"(d[OFF+93]), "+f"(d[OFF+94]), "+f"(d[OFF+95]), "+f"(d[OFF+96]), "+f"(d[OFF+97]), "+f"(d[OFF+98]), "+f"(d[OFF+99]), "+f"(d[OFF+100]), "+f"(d[OFF+101]), "+f"(d[OFF+102]), "+f"(d[OFF+103]), "+f"(d[OFF+104]), "+f"(d[OFF+105]), "+f"(d[OFF+106]), "+f"(d[OFF+107]), "+f"(d[OFF+108]), "+f"(d[OFF+109]), "+f"(d[OFF+110]), "+f"(d[OFF+111]), "+f"(d[OFF+112]), "+f"(d[OFF+113]), "+f"(d[OFF+114]), "+f"(d[OFF+115]), "+f"(d[OFF+116]), "+f"(d[OFF+117]), "+f"(d[OFF+118]), "+f"(d[OFF+119]), "+f"(d[OFF+120]), "+f"(d[OFF+121]), "+f"(d[OFF+122]), "+f"(d[OFF+123]), "+f"(d[OFF+124]), "+f"(d[OFF+125]), "+f"(d[OFF+126]), "+f"(d[OFF+127])
    : "r"(a0), "r"(a1), "r"(a2), "r"(a3), "l"(db), "r"(scale_d), "n"(TB));
}
template<int TB, int OFF, int NT>
__device__ __forceinline__ void wgmma_rs_n32(float (&d)[NT], uint32_t a0, uint32_t a1, uint32_t a2, uint32_t a3, uint64_t db, int scale_d) {
  asm volatile("{\n.reg .pred p;\nsetp.ne.b32 p, %21, 0;\n"
    "wgmma.mma_async.sync.aligned.m64n32k16.f32.bf16.bf16 {%0, %1, %2, %3, %4, %5, %6, %7, %8, %9, %10, %11, %12, %13, %14, %15}, {%16, %17, %18, %19}, %20, p, 1, 1, %22;\n}\n"
    : "+f"(d[OFF+0]), "+f"(d[OFF+1]), "+f"(d[OFF+2]), "+f"(d[OFF+3]), "+f"(d[OFF+4]), "+f"(d[OFF+5]), "+f"(d[OFF+6]), "+f"(d[OFF+7]), "+f"(d[OFF+8]), "+f"(d[OFF+9]), "+f"(d[OFF+10]), "+f"(d[OFF+11]), "+f"(d[OFF+12]), "+f"(d[OFF+13]), "+f"(d[OFF+14]), "+f"(d[OFF+15])
    : "r"(a0), "r"(a1), "r"(a2), "r"(a3), "l"(db), "r"(scale_d), "n"(TB));
}

__device__ __forceinline__ void wait_flag(const unsigned int* f, uint32_t target) {
  uint32_t v;
#pragma unroll 1
  for (uint32_t spins = 0; spins < (1u << 22); spins++) {
    asm volatile("ld.acquire.gpu.global.u32 %0, [%1];" : "=r"(v) : "l"(f) : "memory");
    if (v >= target) break;
    __nanosleep(100);
  }
}
__device__ __forceinline__ uint32_t lds32(uint32_t a) {
  uint32_t v;
  asm volatile("ld.shared.u32 %0, [%1];" : "=r"(v) : "r"(a) : "memory");
  return v;
}
__device__ __forceinline__ float gate_row(int row, int lane, const bf16* __restrict__ x, const bf16* __restrict__ gate_w) {
  const uint32_t* xr = reinterpret_cast<const uint32_t*>(x + (size_t)row * DM);
  const uint32_t* gw2 = reinterpret_cast<const uint32_t*>(gate_w);
  float gs = 0.f;
#pragma unroll
  for (int i = 0; i < 9; i++) {
    const uint32_t a = __ldg(xr + lane + 32 * i), b = __ldg(gw2 + lane + 32 * i);
    gs = fmaf(bf_lo(a), bf_lo(b), gs);
    gs = fmaf(bf_hi(a), bf_hi(b), gs);
  }
#pragma unroll
  for (int o = 16; o; o >>= 1) gs += __shfl_xor_sync(0xffffffffu, gs, o);
  const float g = 1.f / (1.f + __expf(-gs));
  if (lane == 0) g_gate[row] = g;
  return g;
}
constexpr uint32_t LQ = 36864, LV = 55296;
__device__ __forceinline__ void mma16(float (&c)[4], uint32_t a0, uint32_t a1, uint32_t a2, uint32_t a3, uint32_t b0, uint32_t b1) {
  asm("mma.sync.aligned.m16n8k16.row.col.f32.bf16.bf16.f32 {%0, %1, %2, %3}, {%4, %5, %6, %7}, {%8, %9}, {%0, %1, %2, %3};"
      : "+f"(c[0]), "+f"(c[1]), "+f"(c[2]), "+f"(c[3]) : "r"(a0), "r"(a1), "r"(a2), "r"(a3), "r"(b0), "r"(b1));
}
__device__ __forceinline__ void mma8(float (&c)[4], uint32_t a0, uint32_t a1, uint32_t b0) {
  asm("mma.sync.aligned.m16n8k8.row.col.f32.bf16.bf16.f32 {%0, %1, %2, %3}, {%4, %5}, {%6}, {%0, %1, %2, %3};"
      : "+f"(c[0]), "+f"(c[1]), "+f"(c[2]), "+f"(c[3]) : "r"(a0), "r"(a1), "r"(b0));
}
__device__ __forceinline__ void local_attn(int lr0, int warp_g, uint32_t sL, uint32_t bL, uint32_t bL2, int lane, float g0, float g1) {
  const float scale_l2 = 0.23570226039551584f * 1.4426950408889634f;
  const int g = lane >> 2, t = lane & 3;
  const bool lo0 = 2 * t > g, lo1 = 2 * t + 1 > g;
  const uint32_t mlo = (lo0 ? 0xFFFFu : 0u) | (lo1 ? 0xFFFF0000u : 0u);
  const bool ok0 = lr0 > 0 || !lo0, ok1 = lr0 > 0 || !lo1;
  uint32_t ad[9], k[9][4], qf[9][2], pe[4], po[4];
#pragma unroll
  for (int c = 0; c < 9; c++) {
    const uint32_t ch = warp_g * 9 + c;
    ad[c] = sL + (lane >> 4) * 18432 + (lane & 15) * 128 + ((ch >> 3) << 11) + (((ch ^ lane) & 7) << 4);
  }
  mbar_wait(bL, 0);
  if (warp_g == 0) TS(1, 6);
#pragma unroll
  for (int c = 0; c < 9; c++) {
    asm volatile("ldmatrix.sync.aligned.m8n8.x2.shared.b16 {%0, %1}, [%2];" : "=r"(qf[c][0]), "=r"(qf[c][1]) : "r"(ad[c] + LQ) : "memory");
    ldsm_x4(k[c][0], k[c][1], k[c][2], k[c][3], ad[c]);
  }
#pragma unroll
  for (int i = 0; i < 4; i++) {
    const uint32_t q0 = (t >= i) ? qf[2 * i][0] : 0u, q1 = (t >= i) ? qf[2 * i][1] : 0u;
    const uint32_t q4 = (t <= i) ? qf[2 * i + 2][0] : 0u, q5 = (t <= i) ? qf[2 * i + 2][1] : 0u;
    float c[4][4];
#pragma unroll
    for (int T = 0; T < 4; T++) {
#pragma unroll
      for (int j = 0; j < 4; j++) c[T][j] = 0.f;
      mma16(c[T], q0, q1, qf[2 * i + 1][0], qf[2 * i + 1][1], k[2 * i][T], k[2 * i + 1][T]);
      mma8(c[T], q4, q5, k[2 * i + 2][T]);
    }
    const float e0 = ok0 ? (lo0 ? c[0][0] : c[1][0]) : -INFINITY, e1 = ok1 ? (lo1 ? c[0][1] : c[1][1]) : -INFINITY;
    const float o0 = ok0 ? (lo0 ? c[2][2] : c[3][2]) : -INFINITY, o1 = ok1 ? (lo1 ? c[2][3] : c[3][3]) : -INFINITY;
    float me = fmaxf(e0, e1), mo = fmaxf(o0, o1);
    me = fmaxf(me, __shfl_xor_sync(0xffffffffu, me, 1));
    mo = fmaxf(mo, __shfl_xor_sync(0xffffffffu, mo, 1));
    me = fmaxf(me, __shfl_xor_sync(0xffffffffu, me, 2)) * scale_l2;
    mo = fmaxf(mo, __shfl_xor_sync(0xffffffffu, mo, 2)) * scale_l2;
    const float w0 = ex2(fmaf(e0, scale_l2, -me)), w1 = ex2(fmaf(e1, scale_l2, -me));
    const float w2 = ex2(fmaf(o0, scale_l2, -mo)), w3 = ex2(fmaf(o1, scale_l2, -mo));
    float se = w0 + w1, so = w2 + w3;
    se += __shfl_xor_sync(0xffffffffu, se, 1);
    so += __shfl_xor_sync(0xffffffffu, so, 1);
    se += __shfl_xor_sync(0xffffffffu, se, 2);
    so += __shfl_xor_sync(0xffffffffu, so, 2);
    asm("rcp.approx.ftz.f32 %0, %0;" : "+f"(se));
    asm("rcp.approx.ftz.f32 %0, %0;" : "+f"(so));
    se *= g0;
    so *= g1;
    pe[i] = pack_bf16(w0 * se, w1 * se);
    po[i] = pack_bf16(w2 * so, w3 * so);
  }
  if (warp_g == 0) TS(0, 4);
  mbar_wait(bL2, 0);
  if (warp_g == 0) TS(0, 5);
#pragma unroll
  for (int c = 0; c < 9; c++)
    asm volatile("ldmatrix.sync.aligned.m8n8.x4.trans.shared.b16 {%0, %1, %2, %3}, [%4];"
                 : "=r"(k[c][0]), "=r"(k[c][1]), "=r"(k[c][2]), "=r"(k[c][3]) : "r"(ad[c] + LV) : "memory");
#pragma unroll
  for (int i = 0; i < 4; i++) {
#pragma unroll
    for (int n = 0; n < 3; n++) {
      float c[4] = {0.f, 0.f, 0.f, 0.f};
      mma16(c, pe[i] & mlo, 0u, pe[i] & ~mlo, 0u, k[2 * i + n][0], k[2 * i + n][1]);
      mma16(c, 0u, po[i] & mlo, 0u, po[i] & ~mlo, k[2 * i + n][2], k[2 * i + n][3]);
      const uint32_t r0 = pack_bf16(c[0], c[1]), r1 = pack_bf16(c[2], c[3]);
      const bool keep = (n == 0) && (t < i);
      qf[2 * i + n][0] = keep ? qf[2 * i + n][0] : r0;
      qf[2 * i + n][1] = keep ? qf[2 * i + n][1] : r1;
    }
  }
#pragma unroll
  for (int c = 0; c < 9; c++)
    asm volatile("stmatrix.sync.aligned.m8n8.x2.shared.b16 [%0], {%1, %2};" ::"r"(ad[c] + LQ), "r"(qf[c][0]), "r"(qf[c][1]) : "memory");
  asm volatile("fence.proxy.async.shared::cta;" ::: "memory");
}
__device__ __forceinline__ void tma4d(uint32_t dst, const CUtensorMap* m, uint32_t bar, int c1, int c2, int c3) {
  asm volatile("cp.async.bulk.tensor.4d.shared::cluster.global.mbarrier::complete_tx::bytes [%0], [%1, {%3, %4, %5, %6}], [%2];" ::"r"(dst),
               "l"(m), "r"(bar), "r"(0), "r"(c1), "r"(c2), "r"(c3) : "memory");
}

#define K1_NST 6
constexpr int K1_BST = K1_NST;
#define MAXJ 11
constexpr int K1_MAXJOBS = MAXJ;
constexpr uint32_t K1_FLAG_TARGET = 7;
constexpr uint32_t RDY_TARGET = 48;
constexpr uint32_t GATE_TARGET = 128 * 3;
struct alignas(64) Params {
  CUtensorMap tmA[2];
  CUtensorMap tmW[4];
  CUtensorMap tmQ, tmK, tmV;
  CUtensorMap tmL[3];
  CUtensorMap tmC, tmO[2], tmOt[2];
  uint16_t jobs[NCLUSTER][K1_MAXJOBS + 1];
  uint8_t order[256];
  uint8_t unit[64][8];
};

struct K1State {
  uint32_t bs, bph, aph;
  bf16 *pp, *pp8;
  int png;
  int tn;
  int wsel;
};
__device__ __forceinline__ void k1_flag(const K1State& st, int lane, uint32_t bS) {
  if (st.png) {
    __syncwarp();
    if (lane == 0) mbar_arrive(bS);
  }
}

__device__ __forceinline__ void scale_q4(uint32_t* v) {
#pragma unroll
  for (int i = 0; i < 4; i++)
    asm volatile("{\n.reg .b32 t;\nmul.rn.bf16x2 t, %0, %2;\nfma.rn.bf16x2 %0, %0, %1, t;\n}" : "+r"(v[i]) : "r"(0x3E033E03u), "r"(0xB9D8B9D8u));
}
__device__ __forceinline__ void k1_first(const K1State& st, uint32_t job, uint32_t bAf, uint32_t bBf) {
  if (job & 3) {
    if ((job >> 14) & 1) mbar_wait(bAf, st.aph);
    mbar_wait(bBf + st.bs * 8, st.bph);
  }
}
__device__ __forceinline__ void k1_tile(float (&acc)[128], uint32_t (&pk)[64], K1State& st, uint32_t job, uint32_t njob, uint32_t sA, uint32_t sB,
                                        uint32_t bAf, uint32_t bAe, uint32_t bBf, uint32_t bBe, uint32_t bS, int wg, int warp, int lane, uint32_t rank) {
  const int a_sel = (job >> 2) & 1, mpair = (job >> 3) & 7, w_sel = (job >> 6) & 3, chunk0 = (job >> 8) & 63;
  const bool newA = (job >> 14) & 1, lastA = (job >> 15) & 1;
  const bool sig = (lane == 0) && (warp < 2);
  const bool siga = lastA && (lane == 0) && (warp == 2);
  const int KC = 8 + a_sel;
  uint32_t prev_bs = 0, a8_bs = 0;
#pragma unroll
  for (int kc = 0; kc < 9; kc++) {
    if (kc >= KC) break;
    uint32_t abase = sA + ((kc + 2) & 7) * 16384;
    if (kc == 8) {
      mbar_wait(bBf + st.bs * 8, st.bph);
      a8_bs = st.bs;
      abase = sB + st.bs * 16384;
      if (++st.bs == K1_BST) { st.bs = 0; st.bph ^= 1; }
    } else if (newA && kc > 0) {
      mbar_wait(bAf + kc * 8, st.aph);
    }
    const uint64_t da = make_desc(abase + wg * 8192, 16, 1024, 1);
#pragma unroll
    for (int ks = 0; ks < 2; ks++) {
      if (ks > 0 || kc > 0) mbar_wait(bBf + st.bs * 8, st.bph);
      const uint64_t db = make_desc(sB + st.bs * 16384, 2048, 1024, 1);
      wg_fence();
      wgmma_ss_n256<1, 0>(acc, da + (uint64_t)(ks * 4), db, (ks > 0) ? 1 : (kc > 0));
      wgmma_ss_n256<1, 0>(acc, da + (uint64_t)(ks * 4 + 2), db + (uint64_t)512, 1);
      wg_commit();
      const int PO = (kc < 8 ? kc : 0) * 8;
      wg_wait<1>();
      if (ks > 0 || kc > 0) {
        if (sig) mbar_arrive_cluster(bBe + prev_bs * 8, warp);
        if (ks == 0 && siga) mbar_arrive(bAe + (kc - 1) * 8);
      }
      if (kc < 8 && st.wsel >= 2) {
        if (st.wsel == 3) scale_q4(pk + PO + ks * 4);
        else quad_transpose(pk[PO + ks * 4], pk[PO + ks * 4 + 1], pk[PO + ks * 4 + 2], pk[PO + ks * 4 + 3], lane & 3);
      }
      if (kc < st.png) st_v4a((ks ? st.pp8 : st.pp) + kc * 32, pk[PO + ks * 4], pk[PO + ks * 4 + 1], pk[PO + ks * 4 + 2], pk[PO + ks * 4 + 3]);
      prev_bs = st.bs;
      if (++st.bs == K1_BST) { st.bs = 0; st.bph ^= 1; }
    }
  }
  if (newA) st.aph ^= 1;
  k1_flag(st, lane, bS);
  const bool isA = (w_sel == 2);
  bf16* out = (w_sel == 0) ? g_K : (w_sel == 1) ? g_V : isA ? g_QKVA : g_Q;
  const int ld = isA ? NQKVA : HDIM;
  const int row = mpair * 256 + rank * 128 + wg * 64 + warp * 16 + (lane >> 2);
  st.pp = ptr_add(out, (row * ld + chunk0 * 64 + (lane & 3) * 8) * 2);
  st.pp8 = ptr_add(st.pp, 16 * ld);
  st.png = ((job & 3) + 1) * 2;
  st.wsel = w_sel;
  k1_first(st, njob, bAf, bBf);
  wg_wait<0>();
  fence_regs(acc);
  mbar_arrive_cluster_if(bBe + prev_bs * 8, warp & 1, sig);
  mbar_arrive_cluster_if(bBe + a8_bs * 8, warp & 1, sig && a_sel);
  mbar_arrive_if(bAe + 7 * 8, siga && !a_sel);
#pragma unroll
  for (int i = 0; i < 64; i++) {
    const int j = (i >> 3) * 16 + (i & 3) * 4 + ((i >> 2) & 1) * 2;
    pk[i] = pack_bf16(acc[j], acc[j + 1]);
  }
}

constexpr int K2_NST = 7;
constexpr uint32_t K2_END = 0x100;
#define PF_KC 4
#define FIRST_DRAW 3
#define PWAIT mbar_wait_ns<1000>
#define PVM 0x8A
#define W0 63
#define SPEC_HI 1.8446744073709552e19f
#define SPEC_LO 5.421010862427522e-20f
constexpr int K3_NST = 4;
__device__ __forceinline__ uint32_t k3_rot(uint32_t sv) { return (0x00E9u >> (2 * sv)) & 3; }
constexpr int K3_STAGE = 16384 + 32768 + 4096;
constexpr int SMEM_DATA = 7 * 32768;
constexpr int SMEM_BYTES = SMEM_DATA + 1024 + 768;

struct Cursor {
  uint32_t s, ph;
  __device__ __forceinline__ void next() {
    if (++s == K2_NST) { s = 0; ph ^= 1; }
  }
};

#define TURN_SYNC() bar_sync(mybar, 256)
#define TURN_ARRIVE() bar_arrive(otherbar, 256)
#define RELEASE_IF(cur, cond) mbar_arrive_cluster_if(bE + (cur).s * 8, warp & 1, sig && (cond))
#define RELEASE(cur) RELEASE_IF(cur, true)
#define ISSUE_PV(cur, first)                                                                                   \
  do {                                                                                                         \
    const uint64_t dv = make_desc(sbase + (cur).s * 32768, 16384, 1024, 1);                                    \
    _Pragma("unroll") for (int t = 0; t < 8; t++)                                                              \
        wgmma_rs_n128<1, 0>(O, P[4 * t], P[4 * t + 1], P[4 * t + 2], P[4 * t + 3], dv + (uint64_t)(t * 128), (t > 0) ? 1 : !(first)); \
  } while (0)
#define ISSUE_QK(cur)                                                                                          \
  do {                                                                                                         \
    const uint64_t dk = make_desc(sbase + (cur).s * 32768, 16, 1024, 1);                                       \
    _Pragma("unroll") for (int t = 0; t < 8; t++)                                                              \
        wgmma_rs_n128<0, 0>(S, Q[4 * t], Q[4 * t + 1], Q[4 * t + 2], Q[4 * t + 3], dk + (uint64_t)((t >> 2) * 1024 + (t & 3) * 2), t > 0); \
  } while (0)
#define EXPB(T)                                                                                                \
  do {                                                                                                         \
    _Pragma("unroll") for (int i = 4 * T; i < 4 * T + 4; i++) asm volatile("" : "+r"(P[i])::"memory");        \
    _Pragma("unroll") for (int jj = 2 * T; jj < 2 * T + 2; jj++) {                                             \
      const float e0 = ex2(S[jj * 4 + 0]), e1 = ex2(S[jj * 4 + 1]), e2 = ex2(S[jj * 4 + 2]), e3 = ex2(S[jj * 4 + 3]); \
      s0 += e0 + e1;                                                                                           \
      s1 += e2 + e3;                                                                                           \
      P[jj * 2 + 0] = pack_bf16(e0, e1);                                                                       \
      P[jj * 2 + 1] = pack_bf16(e2, e3);                                                                       \
    }                                                                                                          \
  } while (0)
#define EXPC(T)                                                                                                \
  do {                                                                                                         \
    if (T > 0 && ((PVM >> (T - 1)) & 1)) {                                                                     \
      anchor((T & 2) ? s0 : s1, never);                                                                        \
      wg_wait<__builtin_popcount(PVM >> T) - 1>();                                                             \
      if ((PVM >> T) == (128 >> T)) { fence_regs(O); RELEASE(cv); }                                            \
    }                                                                                                          \
    EXPB(T);                                                                                                   \
  } while (0)
#define MASK(G, g)                                                                                             \
  do {                                                                                                         \
    if ((g) * 8 > d) S[(G) * 4 + 0] = -INFINITY;                                                               \
    if ((g) * 8 + 1 > d) S[(G) * 4 + 1] = -INFINITY;                                                           \
    if ((g) * 8 - 8 > d) S[(G) * 4 + 2] = -INFINITY;                                                           \
    if ((g) * 8 - 7 > d) S[(G) * 4 + 3] = -INFINITY;                                                           \
  } while (0)
#define STORE_O(G)                                                                                             \
  do {                                                                                                         \
    st_v4(optr + (G) * 32, pack_bf16(O[(G) * 16 + 0] * f0, O[(G) * 16 + 1] * f0), pack_bf16(O[(G) * 16 + 4] * f0, O[(G) * 16 + 5] * f0), \
          pack_bf16(O[(G) * 16 + 8] * f0, O[(G) * 16 + 9] * f0), pack_bf16(O[(G) * 16 + 12] * f0, O[(G) * 16 + 13] * f0)); \
    st_v4(optr + 8 * KCAT + (G) * 32, pack_bf16(O[(G) * 16 + 2] * f1, O[(G) * 16 + 3] * f1), pack_bf16(O[(G) * 16 + 6] * f1, O[(G) * 16 + 7] * f1), \
          pack_bf16(O[(G) * 16 + 10] * f1, O[(G) * 16 + 11] * f1), pack_bf16(O[(G) * 16 + 14] * f1, O[(G) * 16 + 15] * f1)); \
  } while (0)

#define FLUSH()                                                                                                \
  do {                                                                                                         \
    _Pragma("unroll") for (int G = 0; G < 8; G++) {                                                            \
      st_v4a(st.pp + G * 32, pk[G * 8], pk[G * 8 + 1], pk[G * 8 + 2], pk[G * 8 + 3]);                          \
      st_v4a(st.pp + G * 32 + 8 * HDIM, pk[G * 8 + 4], pk[G * 8 + 5], pk[G * 8 + 6], pk[G * 8 + 7]);           \
    }                                                                                                          \
    k1_flag(st, lane, bS);                                                                                     \
  } while (0)

__global__ void __cluster_dims__(2, 1, 1) __launch_bounds__(384, 1)
fused_kernel(const __grid_constant__ Params p, const bf16* __restrict__ x, const bf16* __restrict__ gate_w, bf16* __restrict__ out) {
  extern __shared__ uint8_t smem_raw[];
  const uint32_t sbase = (smem_u32(smem_raw) + 1023) & ~1023u;
  const uint32_t sB = sbase, sA = sbase + K1_BST * 16384, sBar = sbase + SMEM_DATA;
  const uint32_t bAf = sBar, bAe = sBar + 64, bBf = sBar + 128, bBe = sBar + 176, bL = sBar + 224, bS = sBar + 232, bL2 = sBar + 240, sL = sA + 32768;
  const uint32_t bF = sBar + 256, bE = sBar + 320, bT = sBar + 384, sTick = sBar + 400, sItem = sBar + 416, bS2 = sBar + 448, bR = sBar + 456, bLast = sBar + 464, bH = sBar + 472, bT0 = sBar + 480;
  const uint32_t b3F = sBar + 512, b3E = sBar + 544, sGate = sBar + 576;
  const int tid = threadIdx.x, warp_g = __shfl_sync(0xffffffffu, tid >> 5, 0), lane = tid & 31;
  const uint32_t rank = cluster_rank();
  const int cl = blockIdx.x >> 1;
  TSM(0);
  if (tid == 0) {
    for (int i = 0; i < 8; i++) { mbar_init(bAf + i * 8, 1); mbar_init(bAe + i * 8, 2); }
    for (int i = 0; i < K1_BST; i++) { mbar_init(bBf + i * 8, 1); mbar_init(bBe + i * 8, 4); }
    mbar_init(bL, 1);
    mbar_init(bL2, 1);
    mbar_init(bR, 1);
    mbar_init(bLast, 1);
    mbar_init(bH, 4);
    mbar_init(bT0, 1);
    mbar_init(bS, 8);
    for (int i = 0; i < K2_NST; i++) { mbar_init(bF + i * 8, 1); mbar_init(bE + i * 8, 4); }
    mbar_init(bT, 1); mbar_init(bT + 8, 1);
    mbar_init(bS2, 8);
    for (int i = 0; i < K3_NST; i++) { mbar_init(b3F + i * 8, 1); mbar_init(b3E + i * 8, 4); }
    asm volatile("fence.mbarrier_init.release.cluster;" ::: "memory");
  }
  __syncwarp();
  if (warp_g != 8) cluster_sync();
  const int lr0 = blockIdx.x * 16;

  if (warp_g >= 8) {
    reg_dealloc<40>();
    if (warp_g == 8) {
      {
        const uint32_t job = p.jobs[cl][0];
        if (lane == 0) { prefetch_tmap(&p.tmA[(job >> 2) & 1]); prefetch_tmap(&p.tmW[(job >> 6) & 3]); }
        __syncwarp();
        cluster_sync();
      }
      if (elect_one()) {
        uint32_t bs = 0, bph = 1, aph = 1;
#pragma unroll 1
        for (int ji = 0; ji < K1_MAXJOBS; ji++) {
          const uint32_t job = p.jobs[cl][ji];
          if (!(job & 3)) break;
          const int a_sel = (job >> 2) & 1, mpair = (job >> 3) & 7, chunk0 = (job >> 8) & 63;
          const bool newA = (job >> 14) & 1;
          const int KC = a_sel ? 9 : 8;
          const uint32_t halfbytes = 8192;
          const bool lastjob = (ji + 1 == K1_MAXJOBS) || !(p.jobs[cl][ji + 1] & 3);
          const CUtensorMap* tw = &p.tmW[(job >> 6) & 3];
          {
            const uint32_t njob = (ji + 1 < K1_MAXJOBS) ? p.jobs[cl][ji + 1] : 0;
            if (!(njob & 3) && !newA) mbar_arrive(bLast);
          }
#pragma unroll 1
          for (int kc = 0; kc < KC; kc++) {
            if (kc == ((ji == 0) ? PF_KC : 0) && !lastjob) {
              const uint32_t njob = p.jobs[cl][ji + 1];
              const int nst = ((njob >> 2) & 1) ? 18 : 16;
#pragma unroll 1
              for (int t = (cl < 64) ? (cl & 7) : 0; t < nst; t += (cl < 64) ? 8 : 1)
                tma_pf3d(&p.tmW[(njob >> 6) & 3], 0, t * 32 + rank * 16, (njob >> 8) & 63);
            }
            if (kc == 8) {
              PWAIT(bBe + bs * 8, bph);
              mbar_expect(bBf + bs * 8, 16384);
              tma2d(sB + bs * 16384, &p.tmA[1], bBf + bs * 8, 512, mpair * 256 + rank * 128);
              if (++bs == K1_BST) { bs = 0; bph ^= 1; }
            } else if (newA) {
              PWAIT(bAe + kc * 8, aph);
              mbar_expect(bAf + kc * 8, 16384);
              tma2d(sA + ((kc + 2) & 7) * 16384, &p.tmA[a_sel], bAf + kc * 8, kc * 64, mpair * 256 + rank * 128);
              if (kc == 7 && lastjob) mbar_arrive(bLast);
            }
#pragma unroll 1
            for (int kk = 0; kk < 2; kk++) {
              PWAIT(bBe + bs * 8, bph);
              mbar_expect(bBf + bs * 8, 2 * halfbytes);
              tma3d_mc(sB + bs * 16384 + rank * halfbytes, tw, bBf + bs * 8, 0, kc * 64 + kk * 32 + rank * 16, chunk0, 3);
              if (++bs == K1_BST) { bs = 0; bph ^= 1; }
            }
          }
          if (newA) aph ^= 1;
        }
        Cursor c{0, 0};
        int pcol = 0;
        PWAIT(bR, 0);
        uint32_t tick = lds32(sTick + 8), seen = 1u << (p.order[tick] >> 4);
        asm volatile("fence.proxy.async.global;" ::: "memory");
#pragma unroll 1
        for (int it = 0;; it++) {
          const uint32_t item = (tick < 256) ? p.order[tick] : (K2_END | min(tick - 256, 255u));
          asm volatile("st.shared.u32 [%0], %1;" ::"r"(sItem + (it & 7) * 4), "r"(item) : "memory");
          if (item >= K2_END) break;
          const int h = item >> 3, j = item & 7;
          const int blk = 2 * j + (int)(rank ^ (it & 1));
          const int col = h * 128 + rank * 64;
          const int nb = 2 * j + 2;
          if (!((seen >> (h >> 1)) & 1)) {
            wait_flag(&g_sync[F_HP + (h >> 1)], RDY_TARGET);
            asm volatile("fence.proxy.async.global;" ::: "memory");
            seen |= 1u << (h >> 1);
          }
          PWAIT(bE + c.s * 8, c.ph);
          mbar_expect(bF + c.s * 8, 32768);
          tma2d(sbase + c.s * 32768, &p.tmQ, bF + c.s * 8, h * 128, blk * 128);
          tma2d(sbase + c.s * 32768 + 16384, &p.tmQ, bF + c.s * 8, h * 128 + 64, blk * 128);
          c.next();
#pragma unroll 1
          for (int n = nb - 1; n >= 0; n--) {
            if (n == 0 && rank == 0) tick = atomicAdd(&g_sync[F_TICK], 1u);
            PWAIT(bE + c.s * 8, c.ph);
            mbar_expect(bF + c.s * 8, 32768);
            tma2d_mc(sbase + c.s * 32768 + rank * 16384, &p.tmK, bF + c.s * 8, col, n * 128, 3);
            c.next();
            if (n < nb - 1 || it > 0) {
              PWAIT(bE + c.s * 8, c.ph);
              mbar_expect(bF + c.s * 8, 32768);
              tma2d_mc(sbase + c.s * 32768 + rank * 16384, &p.tmV, bF + c.s * 8, (n < nb - 1) ? col : pcol, (n < nb - 1) ? (n + 1) * 128 : 0, 3);
              c.next();
            }
          }
          pcol = col;
          if (rank == 0) {
            asm volatile(
                "{\n.reg .b32 a, b;\nmapa.shared::cluster.u32 a, %0, 1;\nmapa.shared::cluster.u32 b, %1, 1;\n"
                "st.async.shared::cluster.mbarrier::complete_tx::bytes.u32 [a], %2, [b];\n}" ::"r"(sTick + (it & 1) * 4),
                "r"(bT + (it & 1) * 8), "r"(tick) : "memory");
          } else {
            mbar_expect(bT + (it & 1) * 8, 4);
            PWAIT(bT + (it & 1) * 8, (it >> 1) & 1);
            tick = lds32(sTick + (it & 1) * 4);
          }
        }
        PWAIT(bE + c.s * 8, c.ph);
        mbar_expect(bF + c.s * 8, 32768);
        tma2d_mc(sbase + c.s * 32768 + rank * 16384, &p.tmV, bF + c.s * 8, pcol, 0, 3);
        const uint32_t unit = tick - 256;
        if (unit < 64) {
          const int mblk = (7 - (p.unit[unit][0] >> 1)) * 2 + rank, nhalf = p.unit[unit][0] & 1;
          const uint32_t rot = k3_rot(c.s), nfree = ((0x1Au >> c.s) & 1) ? 2 : 3;
#pragma unroll 1
          for (int i = 0; i < K2_NST - 1; i++) {
            c.next();
            PWAIT(bE + c.s * 8, c.ph);
          }
          uint32_t have = 0;
#pragma unroll 1
          for (uint32_t idx = 0; idx < p.unit[unit][2]; idx++) {
            const int kk = p.unit[unit][3] + idx + ((idx >= p.unit[unit][4]) ? p.unit[unit][5] : 0);
            const uint32_t s = (rot + idx) & 3;
            if (idx >= nfree) PWAIT((idx < 4) ? bH : b3E + s * 8, (idx < 4) ? 0 : (~idx >> 2) & 1);
            mbar_expect(b3F + s * 8, K3_STAGE);
            const uint32_t st = sbase + s * K3_STAGE;
            const int sel = (kk < 9), k = sel ? kk : kk - 9, kr = k * 64 + rank * 32;
            tma3d_mc(st + 16384 + rank * 16384, &p.tmO[sel], b3F + s * 8, 0, kr, nhalf * 4, 3);
            tma2d_mc(st + 49152 + rank * 2048, &p.tmOt[sel], b3F + s * 8, 512 + nhalf * 32, kr, 3);
            if (sel && idx == 0) {
              wait_flag(&g_sync[F_OA + mblk], 8);
              asm volatile("fence.proxy.async.global;" ::: "memory");
            }
            if (!sel && !((have >> (k >> 1)) & 1)) {
#pragma unroll 1
              for (uint32_t spins = 0; spins < (1u << 22); spins++) {
                asm volatile("ld.acquire.gpu.global.u32 %0, [%1];" : "=r"(have) : "l"(&g_sync[F_CTX + mblk]) : "memory");
                if ((have >> (k >> 1)) & 1) break;
                __nanosleep(100);
              }
              asm volatile("fence.proxy.async.global;" ::: "memory");
            }
            tma2d(st, &p.tmC, b3F + s * 8, (sel ? 64 + k : k) * 64, mblk * 128);
          }
        }
      }
    }
    __syncwarp();
    if (warp_g == 8) {
      uint32_t v = 0;
      if (lane == 0) {
        __threadfence();
        v = atomicAdd(&g_sync[F_DONE], 1u);
      }
      if (__shfl_sync(0xffffffffu, v, 0) == 2 * NCLUSTER - 1) {
        reinterpret_cast<uint4*>(g_sync)[lane] = make_uint4(0, 0, 0, 0);
        if (lane == 0) g_sync[F_EPOCH] = lds32(sGate + 64) + 1;
      }
    }
    asm volatile("" ::: "memory");
    if (__shfl_sync(0xffffffffu, warp_g, 0) != 8) {
      if (lr0 < S_LEN) {
#pragma unroll 1
        for (int i = warp_g - 9; i < 16; i += 3) {
          const float g = gate_row(lr0 + i, lane, x, gate_w);
          if (lane == 0) asm volatile("st.shared.f32 [%0], %1;" ::"r"(sGate + i * 4), "f"(g) : "memory");
        }
        bar_arrive(3, 256 + 96);
        if (lane == 0) {
          __threadfence();
          atomicAdd(&g_sync[F_GATE], 1u);
        }
      }
      uint32_t aph = 1;
#pragma unroll 1
      for (int ji = 0; ji < K1_MAXJOBS; ji++) aph ^= (p.jobs[cl][ji] >> 14) & 1;
      if (warp_g == 9 && lane == 0) {
#pragma unroll 1
        for (int ji = 0; ji < K1_MAXJOBS; ji++) {
          const uint32_t job = p.jobs[cl][ji];
          if (!(job & 3)) break;
          PWAIT(bS, ji & 1);
          __threadfence();
          atomicAdd(&g_sync[(((job >> 6) & 3) == 2) ? (F_QKVA + ((job >> 3) & 7) * 2 + rank) : (F_HP + ((job >> 10) & 15))], 1u);
        }
#pragma unroll 1
        for (int it = 0;; it++) {
          PWAIT(bS2, it & 1);
          const uint32_t item = lds32(sItem + (it & 7) * 4), nxt = lds32(sItem + ((it + 1) & 7) * 4);
          __threadfence();
          atomicOr(&g_sync[F_CTX + (item & 7) * 2 + (rank ^ (it & 1))], 1u << (item >> 3));
          if (nxt >= K2_END) break;
        }
      } else if (warp_g == 11) {
        if (lane == 0) {
          prefetch_tmap(&p.tmQ); prefetch_tmap(&p.tmK); prefetch_tmap(&p.tmV);
          asm volatile("st.shared.u32 [%0], %1;" ::"r"(sGate + 64), "r"(__ldcg(&g_sync[F_EPOCH])) : "memory");
          wait_flag(&g_sync[F_GATE], GATE_TARGET);
          uint32_t tick;
          if (rank == 0) {
            PWAIT(bLast, 0);
            PWAIT(bAe + FIRST_DRAW * 8, aph);
            tick = atomicAdd(&g_sync[F_TICK], 1u);
            asm volatile("st.shared.u32 [%0], %1;" ::"r"(sTick + 8), "r"(tick) : "memory");
            asm volatile(
                "{\n.reg .b32 a, b;\nmapa.shared::cluster.u32 a, %0, 1;\nmapa.shared::cluster.u32 b, %1, 1;\n"
                "st.async.shared::cluster.mbarrier::complete_tx::bytes.u32 [a], %2, [b];\n}" ::"r"(sTick + 8), "r"(bT0), "r"(tick) : "memory");
          } else {
            mbar_expect(bT0, 4);
            PWAIT(bT0, 0);
            tick = lds32(sTick + 8);
          }
          wait_flag(&g_sync[F_HP + (p.order[tick] >> 4)], RDY_TARGET);
          mbar_arrive(bR);
        }
      } else if (warp_g == 10) {
        if (lr0 < S_LEN && lane == 0) {
          prefetch_tmap(&p.tmL[0]); prefetch_tmap(&p.tmL[1]); prefetch_tmap(&p.tmL[2]);
          wait_flag(&g_sync[F_QKVA + (lr0 >> 7)], K1_FLAG_TARGET);
          wait_flag(&g_sync[F_QKVA + (max(lr0 - 16, 0) >> 7)], K1_FLAG_TARGET);
          asm volatile("fence.proxy.async.global;" ::: "memory");
          PWAIT(bLast, 0);
#pragma unroll 1
          for (int kc = 0; kc < 6; kc++) {
            PWAIT(bAe + kc * 8, aph);
            if (kc == 3) {
              mbar_expect(bL, LV);
              tma4d(sL, &p.tmL[0], bL, lr0 / 2 - 8, 9, 0);
              tma4d(sL + LQ, &p.tmL[1], bL, lr0 / 2, 0, 0);
            }
          }
          mbar_expect(bL2, LQ);
          tma4d(sL + LV, &p.tmL[0], bL2, lr0 / 2 - 8, 18, 0);
        }
        __syncwarp();
        bar_sync(5, 256 + 32);
        if (lr0 < S_LEN && lane == 0) {
          asm volatile("cp.async.bulk.tensor.4d.global.shared::cta.bulk_group [%0, {%2, %3, %2, %2}], [%1];" ::"l"(&p.tmL[2]), "r"(sL + LQ), "r"(0), "r"(lr0 / 2) : "memory");
          asm volatile("cp.async.bulk.commit_group;" ::: "memory");
          asm volatile("cp.async.bulk.wait_group.read 0;" ::: "memory");
        }
        __syncwarp();
        if (lane < 12) mbar_arrive_cluster(bE + (4 + lane % 3) * 8, (lane / 3) & 1);
        if (lr0 < S_LEN && lane == 0) {
          asm volatile("cp.async.bulk.wait_group 0;" ::: "memory");
          asm volatile("fence.proxy.async.global;" ::: "memory");
          __threadfence();
          atomicAdd(&g_sync[F_OA + (lr0 >> 7)], 1u);
        }
      }
    }
    __syncwarp();
    cluster_sync();
  } else {
    reg_alloc<232>();
    const int wg = warp_g >> 2, warp = warp_g & 3, q = lane & 3;
    const bool sig = (lane == 0) && (warp < 2);
    {
      K1State st{0, 0, 0, nullptr, nullptr, 0, 0, 0};
      float acc[128];
      uint32_t pk[64];
      if (wg == 0) { TS(0, 0); TSC(0, 2); }
      uint32_t job = p.jobs[cl][0];
      k1_first(st, job, bAf, bBf);
      {
#pragma unroll 1
        for (int ji = 0; job & 3; ji++) {
          const uint32_t njob = p.jobs[cl][ji + 1];
          k1_tile(acc, pk, st, job, njob, sA, sB, bAf, bAe, bBf, bBe, bS, wg, warp, lane, rank);
          job = njob;
        }
      }
#pragma unroll
      for (int i = 0; i < 4; i++)
        mbar_arrive_cluster_if(bE + i * 8, warp & 1, sig);
      if (lr0 < S_LEN) bar_sync(3, 256 + 96);
      if (st.wsel == 3) {
#pragma unroll
        for (int G = 0; G < 16; G++) scale_q4(pk + G * 4);
      }
      FLUSH();
      if (wg == 0) { TS(0, 1); TSC(0, 3); }
      if (lr0 < S_LEN) {
        const float gate0 = __uint_as_float(lds32(sGate + (lane >> 2) * 8)), gate1 = __uint_as_float(lds32(sGate + (lane >> 2) * 8 + 4));
        local_attn(lr0, warp_g, sL, bL, bL2, lane, gate0, gate1);
      }
      bar_arrive(5, 256 + 32);
    }
    __syncwarp();
    uint32_t item, rot;
    {
      const int mybar = 1 + wg, otherbar = 2 - wg;
      const uint32_t never = blockIdx.y;
      float S[64], O[64];
      uint32_t P[32], Q[32];
      float m0 = 0.f, m1 = 0.f, l0 = 1.f, l1 = 1.f, gf0 = 0.f, gf1 = 0.f;
      uint32_t eoff = 0, prev_single = 0;
      Cursor c{0, 0};
      if (wg == 1) bar_arrive(1, 256);
      if (wg == 0) { TS(1, 0); TSC(1, 2); }
#pragma unroll 1
      for (int it = 0;; it++) {
        TB(0);
        const int hi = (int)(rank ^ (it & 1));
        Cursor cq = c, ck, cv, cs0, cs1;
        rot = k3_rot(c.s);
        c.next();
        ck = c; c.next();
        cs0 = ck; cs1 = ck; cv = ck;
        if (it > 0) { cv = c; c.next(); }
        if (!hi) {
          ck = c; c.next();
          cs1 = c; c.next();
        }
        mbar_wait(bF + cq.s * 8, cq.ph);
        TB(1);
        item = lds32(sItem + (it & 7) * 4);
        {
          const uint32_t qa = sbase + cq.s * 32768 + (wg * 64 + warp * 16 + (lane & 15)) * 128;
#pragma unroll
          for (int t = 0; t < 8; t++)
            ldsm_x4(Q[4 * t], Q[4 * t + 1], Q[4 * t + 2], Q[4 * t + 3], qa + (t >> 2) * 16384 + ((((t & 3) * 2 + (lane >> 4)) ^ (lane & 7)) << 4));
        }
        const uint32_t rdy = mbar_test(bF + ck.s * 8, ck.ph) & mbar_test(bF + cv.s * 8, cv.ph);
        l0 += __shfl_xor_sync(0xffffffffu, l0, 1);
        l1 += __shfl_xor_sync(0xffffffffu, l1, 1);
        l0 += __shfl_xor_sync(0xffffffffu, l0, 2);
        l1 += __shfl_xor_sync(0xffffffffu, l1, 2);
        const bool last = item >= K2_END;
        if (last) {
          cv = cq; ck = cq;
        } else if (!rdy) {
          mbar_wait2(bF + ck.s * 8, ck.ph, bF + cv.s * 8, cv.ph);
        }
        TB(2);
        TURN_SYNC();
        TB(3);
        TRC(last ? 2 : 1);
        if (it > 0) {
          wg_fence();
          ISSUE_PV(cv, prev_single);
          wg_commit();
        } else {
          wg_fence();
          wg_commit();
        }
        wg_fence();
        ISSUE_QK(ck);
        wg_commit();
        if (!(last && wg == 1)) TURN_ARRIVE();
        RELEASE_IF(cq, !last);
        TB(4);
        asm volatile("" : "+f"(gf0), "+f"(gf1), "+f"(l0), "+f"(l1));
        const float f0 = __fdividef(1.f - gf0, l0), f1 = __fdividef(1.f - gf1, l1);
        wg_wait<1>();
        fence_regs(O);
        fence_regs(P);
        TB(5);
        if (it > 0) {
          RELEASE_IF(cv, !last);
          mbar_arrive_cluster_if(bH, warp & 1, sig && last);
          bf16* optr = ptr_add(g_ctx, eoff);
          STORE_O(0); STORE_O(1); STORE_O(2); STORE_O(3);
          __syncwarp();
          mbar_arrive_if(bS2, lane == 0);
        }
        TB(6);
        if (!last) {
          const int row = (2 * (item & 7) + hi) * 128 + wg * 64 + warp * 16 + (lane >> 2);
          eoff = (row * KCAT + (item >> 3) * 128 + q * 8) * 2;
          const float* gp = ptr_add(g_gate, row * 4);
          asm volatile("ld.global.f32 %0, [%1];" : "=f"(gf0) : "l"(gp));
          asm volatile("ld.global.f32 %0, [%1];" : "=f"(gf1) : "l"(gp + 8));
          if (!hi) {
            mbar_wait2(bF + cs0.s * 8, cs0.ph, bF + cs1.s * 8, cs1.ph);
            RELEASE(cs0);
            RELEASE(cs1);
          }
        }
        TB(7);
        wg_wait<0>();
        fence_regs(S);
        TB(8);
        if (last) break;
        RELEASE(ck);
        const int nblk = 2 * (item & 7) + 1 + hi;
        prev_single = (nblk == 1);
        float s0 = 0.f, s1 = 0.f;
        l0 = 0.f; l1 = 0.f;
        m0 = 0.f; m1 = 0.f;
        bool shifted = false;
        {
          const int d = warp * 16 + (lane >> 2) - 2 * q;
          if (wg == 0) {
#pragma unroll
            for (int jj = 0; jj < 8; jj++) MASK(jj, jj);
            EXPB(0); EXPB(1); EXPB(2); EXPB(3);
#pragma unroll
            for (int i = 32; i < 64; i++) S[i] = -INFINITY;
#pragma unroll
            for (int i = 16; i < 32; i++) P[i] = 0;
          } else {
#pragma unroll
            for (int jj = 0; jj < 8; jj++) MASK(jj + 8, jj);
            EXPB(0); EXPB(1); EXPB(2); EXPB(3); EXPB(4); EXPB(5); EXPB(6); EXPB(7);
          }
        }
        float chk = (q == 0 && !(fminf(s0, s1) >= SPEC_LO)) ? INFINITY : s0 + s1;
        fence_regs(P);
        TB(9);
#pragma unroll 1
        for (int n = 1;; n++) {
          if (__any_sync(0xffffffffu, !(chk <= SPEC_HI))) {
            float mx0 = fmaxf(S[0], S[1]), mx1 = fmaxf(S[2], S[3]);
#pragma unroll
            for (int jj = 1; jj < 16; jj++) {
              mx0 = fmaxf(mx0, fmaxf(S[jj * 4 + 0], S[jj * 4 + 1]));
              mx1 = fmaxf(mx1, fmaxf(S[jj * 4 + 2], S[jj * 4 + 3]));
            }
            mx0 = fmaxf(mx0, __shfl_xor_sync(0xffffffffu, mx0, 1));
            mx1 = fmaxf(mx1, __shfl_xor_sync(0xffffffffu, mx1, 1));
            mx0 = fmaxf(mx0, __shfl_xor_sync(0xffffffffu, mx0, 2));
            mx1 = fmaxf(mx1, __shfl_xor_sync(0xffffffffu, mx1, 2));
            const float lo = (n == 1) ? -INFINITY : 0.f;
            mx0 = fmaxf(mx0, lo);
            mx1 = fmaxf(mx1, lo);
            m0 += mx0; m1 += mx1;
            shifted = true;
            const float sc0 = ex2(-fmaxf(mx0, 0.f)), sc1 = ex2(-fmaxf(mx1, 0.f));
            l0 *= sc0; l1 *= sc1;
            s0 = 0.f; s1 = 0.f;
#pragma unroll
            for (int jj = 0; jj < 16; jj++) {
              const float e0 = ex2(S[jj * 4 + 0] - mx0), e1 = ex2(S[jj * 4 + 1] - mx0), e2 = ex2(S[jj * 4 + 2] - mx1), e3 = ex2(S[jj * 4 + 3] - mx1);
              s0 += e0 + e1;
              s1 += e2 + e3;
              P[jj * 2 + 0] = pack_bf16(e0, e1);
              P[jj * 2 + 1] = pack_bf16(e2, e3);
              O[jj * 4 + 0] *= sc0;
              O[jj * 4 + 1] *= sc0;
              O[jj * 4 + 2] *= sc1;
              O[jj * 4 + 3] *= sc1;
            }
          }
          l0 += s0;
          l1 += s1;
          if (n >= nblk) break;
          ck = c; c.next();
          cv = c; c.next();
          mbar_wait(bF + ck.s * 8, ck.ph);
          mbar_wait(bF + cv.s * 8, cv.ph);
          TURN_SYNC();
          TRC(0);
          wg_fence();
          ISSUE_QK(ck);
          wg_commit();
          {
            const uint64_t dv = make_desc(sbase + cv.s * 32768, 16384, 1024, 1);
#pragma unroll
            for (int t = 0; t < 8; t++) {
              wgmma_rs_n128<1, 0>(O, P[4 * t], P[4 * t + 1], P[4 * t + 2], P[4 * t + 3], dv + (uint64_t)(t * 128), (t > 0) ? 1 : (n != 1));
              if ((PVM >> t) & 1) wg_commit();
            }
          }
          TURN_ARRIVE();
          s0 = 0.f; s1 = 0.f;
          wg_wait<__builtin_popcount(PVM)>();
          fence_regs(S);
          RELEASE(ck);
          if (shifted) {
#pragma unroll
            for (int i = 0; i < 64; i++) S[i] -= (i & 2) ? m1 : m0;
          }
          wg_wait<__builtin_popcount(PVM) - 1>();
          EXPC(0); EXPC(1); EXPC(2); EXPC(3); EXPC(4); EXPC(5); EXPC(6); EXPC(7);
          chk = s0 + s1;
        }
      }
      TRC(3);
      if (wg == 1) { TS(1, 1); TSC(1, 3); }
    }
    __syncwarp();
    const uint32_t unit = item & 255;
    if (unit < 64) {
      const int mblk = (7 - (p.unit[unit][0] >> 1)) * 2 + rank, nhalf = p.unit[unit][0] & 1, ks = p.unit[unit][1];
      const int k0 = 0, k1 = p.unit[unit][2];
      float acc[144];
      uint32_t s = rot, ph = 0, prev = 0;
      if (wg == 0) { TS(2, 0); TSC(2, 2); }
      uint32_t fa[16], fb[16];
      const uint32_t aoff = (wg * 64 + warp * 16 + (lane & 15)) * 128 + (((lane >> 4) ^ (lane & 7)) << 4);
#define C_LOAD(F)                                                                                              \
  do {                                                                                                         \
    mbar_wait(b3F + s * 8, ph);                                                                                \
    _Pragma("unroll") for (int t = 0; t < 4; t++)                                                              \
        ldsm_x4(F[4 * t], F[4 * t + 1], F[4 * t + 2], F[4 * t + 3], sbase + s * K3_STAGE + (aoff ^ (t * 32))); \
  } while (0)
#define C_STEP(F, G)                                                                                           \
  {                                                                                                            \
    const uint32_t st = sbase + s * K3_STAGE;                                                                  \
    const uint64_t db = make_desc(st + 16384, 4096, 1024, 1), dt = make_desc(st + 49152, 16, 512, 2);          \
    wg_fence();                                                                                                \
    _Pragma("unroll") for (int t = 0; t < 4; t++) {                                                            \
      const int sd = (t > 0) || (k > k0);                                                                      \
      wgmma_rs_n256<1, 0>(acc, F[4 * t], F[4 * t + 1], F[4 * t + 2], F[4 * t + 3], db + (uint64_t)((t >> 1) * 1024 + (t & 1) * 128), sd); \
      wgmma_rs_n32<1, 128>(acc, F[4 * t], F[4 * t + 1], F[4 * t + 2], F[4 * t + 3], dt + (uint64_t)(t * 64), sd); \
    }                                                                                                          \
    wg_commit();                                                                                               \
    wg_wait<1>();                                                                                              \
    fence_regs(G);                                                                                             \
    mbar_arrive_cluster_if(b3E + prev * 8, warp & 1, sig && k > k0);                                           \
    prev = s;                                                                                                  \
    s = (s + 1) & 3;                                                                                           \
    if (s == rot) ph ^= 1;                                                                                     \
    if (++k == k1) break;                                                                                      \
    C_LOAD(G);                                                                                                 \
  }
      C_LOAD(fa);
#pragma unroll
      for (int i = 0; i < 16; i++) fb[i] = 0;
#pragma unroll 1
      for (int k = k0;;) {
        C_STEP(fa, fb)
        C_STEP(fb, fa)
      }
      wg_wait<0>();
      fence_regs(acc);
      cluster_arrive();
      if (wg == 0) TS(2, 4);
      const int tile = mblk * 2 + nhalf;
      uint4* wp = g_part + (size_t)((tile * 4 + ks) * 4) * 5 * 256 + tid;
      const uint32_t sown = sbase + wg * 8192 + (tid & 127) * 16;
#pragma unroll
      for (int d = 0; d < 4; d++) {
        if (d != ks) {
#pragma unroll
          for (int i = 0; i < 4; i++)
            __stcg(wp + (d * 5 + i) * 256,
                   make_uint4(pack_bf16(acc[d * 32 + i * 8], acc[d * 32 + i * 8 + 1]), pack_bf16(acc[d * 32 + i * 8 + 2], acc[d * 32 + i * 8 + 3]),
                              pack_bf16(acc[d * 32 + i * 8 + 4], acc[d * 32 + i * 8 + 5]), pack_bf16(acc[d * 32 + i * 8 + 6], acc[d * 32 + i * 8 + 7])));
          __stcg(reinterpret_cast<uint2*>(wp - tid + (d * 5 + 4) * 256) + tid,
                 make_uint2(pack_bf16(acc[128 + d * 4], acc[128 + d * 4 + 1]), pack_bf16(acc[128 + d * 4 + 2], acc[128 + d * 4 + 3])));
        } else {
#pragma unroll
          for (int i = 0; i < 9; i++) {
            const int o = (i < 8) ? d * 32 + i * 4 : 128 + d * 4;
            asm volatile("st.shared.v4.f32 [%0], {%1, %2, %3, %4};" ::"r"(sown + (i >> 2) * K3_STAGE + (i & 3) * 2048), "f"(acc[o]), "f"(acc[o + 1]), "f"(acc[o + 2]), "f"(acc[o + 3]) : "memory");
          }
        }
      }
      __threadfence();
      __syncwarp();
      if (wg == 0) TS(2, 5);
      if (lane == 0) {
        unsigned int* cnt = &g_sync[F_XCH + tile * 8 + warp_g];
        const uint32_t xtarget = lds32(sGate + 64) * 4 + 4;
        atomicAdd(cnt, 1u);
        uint32_t v, spins = 0;
        do {
          asm volatile("ld.acquire.gpu.global.u32 %0, [%1];" : "=r"(v) : "l"(cnt) : "memory");
        } while ((int)(v - xtarget) < 0 && ++spins < (1u << 24));
      }
      __syncwarp();
      if (wg == 0) TS(2, 6);
      float r[36];
#pragma unroll
      for (int i = 0; i < 9; i++)
        asm volatile("ld.shared.v4.f32 {%0, %1, %2, %3}, [%4];" : "=f"(r[i * 4]), "=f"(r[i * 4 + 1]), "=f"(r[i * 4 + 2]), "=f"(r[i * 4 + 3])
                     : "r"(sown + (i >> 2) * K3_STAGE + (i & 3) * 2048) : "memory");
#pragma unroll
      for (int sI = 1; sI < 4; sI++) {
        const int src = (ks + sI) & 3;
        const uint4* rp = g_part + (size_t)(((tile * 4 + src) * 4) + ks) * 5 * 256;
#pragma unroll
        for (int i = 0; i < 4; i++) {
          const uint4 v = __ldcg(rp + i * 256 + tid);
          r[i * 8] += bf_lo(v.x); r[i * 8 + 1] += bf_hi(v.x); r[i * 8 + 2] += bf_lo(v.y); r[i * 8 + 3] += bf_hi(v.y);
          r[i * 8 + 4] += bf_lo(v.z); r[i * 8 + 5] += bf_hi(v.z); r[i * 8 + 6] += bf_lo(v.w); r[i * 8 + 7] += bf_hi(v.w);
        }
        const uint2 v = __ldcg(reinterpret_cast<const uint2*>(rp + 4 * 256) + tid);
        r[32] += bf_lo(v.x); r[33] += bf_hi(v.x); r[34] += bf_lo(v.y); r[35] += bf_hi(v.y);
      }
      const int row = mblk * 128 + wg * 64 + warp * 16 + (lane >> 2);
      bf16* o0 = out + (size_t)row * DM + nhalf * 256 + ks * 64 + 8 * q;
#pragma unroll
      for (int G = 0; G < 2; G++) {
        uint32_t a0 = pack_bf16(r[G * 16], r[G * 16 + 1]), a1 = pack_bf16(r[G * 16 + 4], r[G * 16 + 5]);
        uint32_t a2 = pack_bf16(r[G * 16 + 8], r[G * 16 + 9]), a3 = pack_bf16(r[G * 16 + 12], r[G * 16 + 13]);
        uint32_t b0 = pack_bf16(r[G * 16 + 2], r[G * 16 + 3]), b1 = pack_bf16(r[G * 16 + 6], r[G * 16 + 7]);
        uint32_t b2 = pack_bf16(r[G * 16 + 10], r[G * 16 + 11]), b3 = pack_bf16(r[G * 16 + 14], r[G * 16 + 15]);
        quad_transpose(a0, a1, a2, a3, q);
        quad_transpose(b0, b1, b2, b3, q);
        st_v4(o0 + G * 32, a0, a1, a2, a3);
        st_v4(o0 + 8 * DM + G * 32, b0, b1, b2, b3);
      }
      {
        uint32_t t0 = pack_bf16(r[32], r[33]), t1 = pack_bf16(r[34], r[35]), t2 = 0, t3 = 0;
        quad_transpose(t0, t1, t2, t3, q);
        if (q < 2) st_v4(out + (size_t)(row + q * 8) * DM + 512 + nhalf * 32 + ks * 8, t0, t1, t2, t3);
      }
    } else {
      cluster_arrive();
    }
    if (wg == 0) { TS(2, 1); TSC(2, 3); }
    cluster_wait();
  }
}

typedef CUresult (*EncFn)(CUtensorMap*, CUtensorMapDataType, cuuint32_t, void*, const cuuint64_t*, const cuuint64_t*, const cuuint32_t*,
                          const cuuint32_t*, CUtensorMapInterleave, CUtensorMapSwizzle, CUtensorMapL2promotion, CUtensorMapFloatOOBfill);

static void enc2d(EncFn enc, CUtensorMap* m, const void* ptr, uint64_t cols, uint64_t rows, uint32_t bc, uint32_t br,
                  CUtensorMapSwizzle sw = CU_TENSOR_MAP_SWIZZLE_128B) {
  cuuint64_t gd[2] = {cols, rows}, gs[1] = {cols * 2};
  cuuint32_t bx[2] = {bc, br}, es[2] = {1, 1};
  enc(m, CU_TENSOR_MAP_DATA_TYPE_BFLOAT16, 2, const_cast<void*>(ptr), gd, gs, bx, es, CU_TENSOR_MAP_INTERLEAVE_NONE, sw,
      CU_TENSOR_MAP_L2_PROMOTION_L2_256B, CU_TENSOR_MAP_FLOAT_OOB_FILL_NONE);
}
static void enc3d(EncFn enc, CUtensorMap* m, const void* ptr, uint64_t cols, uint64_t rows, uint32_t br, uint32_t bch) {
  cuuint64_t gd[3] = {64, rows, cols / 64}, gs[2] = {cols * 2, 128};
  cuuint32_t bx[3] = {64, br, bch}, es[3] = {1, 1, 1};
  enc(m, CU_TENSOR_MAP_DATA_TYPE_BFLOAT16, 3, const_cast<void*>(ptr), gd, gs, bx, es, CU_TENSOR_MAP_INTERLEAVE_NONE,
      CU_TENSOR_MAP_SWIZZLE_128B, CU_TENSOR_MAP_L2_PROMOTION_L2_256B, CU_TENSOR_MAP_FLOAT_OOB_FILL_NONE);
}

static int g_sched[10] = {11, 10, 7, 4, 4, 4, 6, 7, 6, 24};
static void build_k1_jobs(Params& p) {
  int cnt[NCLUSTER];
  for (int c = 0; c < NCLUSTER; c++) {
    cnt[c] = 0;
    for (int i = 0; i <= K1_MAXJOBS; i++) p.jobs[c][i] = 0;
  }
  auto add = [&](int c, int nch, int a_sel, int mp, int w_sel, int chunk0) {
    p.jobs[c][cnt[c]++] = (uint16_t)((nch - 1) | (a_sel << 2) | (mp << 3) | (w_sel << 6) | (chunk0 << 8));
  };
  const int *cg = g_sched, *xg = g_sched + 4;
  for (int mp = 0; mp < 8; mp++) {
    int k = 0;
    for (int i = 0; i < K1_MAXJOBS; i++)
      for (int g = 0; g < 4; g++)
        if (i < cg[g]) { add(g * 8 + mp, 4, 0, mp, k & 1, (k >> 1) * 4); k++; }
    k = 0;
    for (int i = 0; i < K1_MAXJOBS; i++)
      for (int g = 0; g < 4; g++)
        if (i < xg[g]) {
          if (k < 7) add((4 + g) * 8 + mp, k == 0 ? 3 : 4, 1, mp, 2, k == 0 ? 24 : (k - 1) * 4);
          else add((4 + g) * 8 + mp, 4, 1, mp, 3, (k - 7) * 4);
          k++;
        }
    add(64 + mp / 4, 4, 1, mp, 3, 14 * 4);
    add(64 + mp / 4, 4, 1, mp, 3, 15 * 4);
  }
  for (int cc = 0; cc < NCLUSTER; cc++)
    for (int i = 0; i < cnt[cc]; i++) {
      const int key = p.jobs[cc][i] & 0x3C;
      if (i == 0 || (p.jobs[cc][i - 1] & 0x3C) != key) p.jobs[cc][i] |= (1 << 14);
      if (i == cnt[cc] - 1 || (p.jobs[cc][i + 1] & 0x3C) != key) p.jobs[cc][i] |= (1 << 15);
    }
}

static void build_k2_items(Params& p) {
  int n = 0;
  const int SCHED_N1 = g_sched[8], SCHED_N2 = g_sched[9];
  int N0 = 2, J0 = 2;
  for (int j = 7; j >= J0; j--)
    for (int h = 0; h < N0; h++) p.order[n++] = (uint8_t)(h * 8 + j);
  for (int j = 7; j >= 0; j--)
    for (int h = 0; h < SCHED_N1; h++)
      if (!(h < N0 && j >= J0)) p.order[n++] = (uint8_t)(h * 8 + j);
  for (int j = 7; j >= 4; j--)
    for (int h = SCHED_N1; h < SCHED_N2; h++) p.order[n++] = (uint8_t)(h * 8 + j);
  for (int j = 7; j >= 0; j--)
    for (int h = SCHED_N1; h < 32; h++)
      if (!(h < SCHED_N2 && j >= 4)) p.order[n++] = (uint8_t)(h * 8 + j);
}

static void build_k3_units(Params& p) {
  float slope = 0.045f;
  int NE = 25;
  for (int t = 0; t < 16; t++) {
    const int u[4] = {t, 31 - t, 32 + t, 63 - t};
    float acc = 0.f;
    int k0 = 0, l0 = NE;
    for (int i = 0; i < 4; i++) {
      acc += 18.25f + slope * (31.5f - u[i]);
      const int k1 = (i == 3) ? 73 : (int)(acc + 0.5f);
      const int e0 = NE * i / 4, e1 = NE * (i + 1) / 4;
      uint8_t* w = p.unit[u[i]];
      w[0] = (uint8_t)t; w[1] = (uint8_t)i; w[2] = (uint8_t)(k1 - k0); w[3] = (uint8_t)e0; w[4] = (uint8_t)(e1 - e0); w[5] = (uint8_t)(l0 - e1);
      l0 += (k1 - k0) - (e1 - e0);
      k0 = k1;
    }
  }
}

extern "C" void kernel_launch(void* const* d_in, const int* in_sizes, int n_in, void* d_out, int out_size) {
  const bf16* x = (const bf16*)d_in[0];
  const bf16* wqkv = (const bf16*)d_in[1];
  const bf16* wo = (const bf16*)d_in[2];
  const bf16* ckv = (const bf16*)d_in[4];
  const bf16* w_q = (const bf16*)d_in[5];
  const bf16* w_uk = (const bf16*)d_in[6];
  const bf16* w_uv = (const bf16*)d_in[7];
  const bf16* w_o = (const bf16*)d_in[8];
  const bf16* gate_w = (const bf16*)d_in[9];

  EncFn enc = nullptr;
  cudaDriverEntryPointQueryResult qr;
  cudaGetDriverEntryPoint("cuTensorMapEncodeTiled", (void**)&enc, cudaEnableDefault, &qr);
  void *pQ, *pK, *pV, *pCtx, *pQA;
  cudaGetSymbolAddress(&pQA, g_QKVA);
  cudaGetSymbolAddress(&pQ, g_Q);
  cudaGetSymbolAddress(&pK, g_K);
  cudaGetSymbolAddress(&pV, g_V);
  cudaGetSymbolAddress(&pCtx, g_ctx);

  static Params p;
  enc2d(enc, &p.tmA[0], ckv, DC, S_LEN, 64, 128);
  enc2d(enc, &p.tmA[1], x, DM, S_LEN, 64, 128);
  enc3d(enc, &p.tmW[0], w_uk, HDIM, DC, 16, 4);
  enc3d(enc, &p.tmW[1], w_uv, HDIM, DC, 16, 4);
  enc3d(enc, &p.tmW[2], wqkv, NQKVA, DM, 16, 4);
  enc3d(enc, &p.tmW[3], w_q, HDIM, DM, 16, 4);
  build_k1_jobs(p);
  enc2d(enc, &p.tmQ, pQ, HDIM, S_LEN, 64, 128);
  enc2d(enc, &p.tmK, pK, HDIM, S_LEN, 64, 128);
  enc2d(enc, &p.tmV, pV, HDIM, S_LEN, 64, 128);
  build_k2_items(p);
  build_k3_units(p);
  for (int i = 0; i < 3; i++) {
    const cuuint64_t ld = (i < 2 ? NQKVA : KCAT) * 2, nch = (i < 2) ? 27 : 9;
    cuuint64_t gd[4] = {64, S_LEN / 2, i ? 2 : nch, i ? nch : 2}, gs[3] = {2 * ld, i ? ld : 128, i ? 128 : ld};
    cuuint32_t bx[4] = {64, i ? 8u : 16u, i ? 2u : 9u, i ? 9u : 2u}, es[4] = {1, 1, 1, 1};
    enc(&p.tmL[i], CU_TENSOR_MAP_DATA_TYPE_BFLOAT16, 4, (i < 2) ? pQA : (void*)((bf16*)pCtx + HDIM), gd, gs, bx, es, CU_TENSOR_MAP_INTERLEAVE_NONE,
        CU_TENSOR_MAP_SWIZZLE_128B, CU_TENSOR_MAP_L2_PROMOTION_L2_256B, CU_TENSOR_MAP_FLOAT_OOB_FILL_NONE);
  }
  enc2d(enc, &p.tmC, pCtx, KCAT, S_LEN, 64, 128);
  enc3d(enc, &p.tmO[0], w_o, DM, HDIM, 32, 4);
  enc3d(enc, &p.tmO[1], wo, DM, DM, 32, 4);
  enc2d(enc, &p.tmOt[0], w_o, DM, HDIM, 32, 32, CU_TENSOR_MAP_SWIZZLE_64B);
  enc2d(enc, &p.tmOt[1], wo, DM, DM, 32, 32, CU_TENSOR_MAP_SWIZZLE_64B);

  cudaFuncSetAttribute(fused_kernel, cudaFuncAttributeMaxDynamicSharedMemorySize, SMEM_BYTES);
  fused_kernel<<<NCLUSTER * 2, 384, SMEM_BYTES>>>(p, x, gate_w, (bf16*)d_out);
}
```

```cpp
#include <cuda_runtime.h>
#include <cuda_bf16.h>
#include <cuda.h>
#include <stdint.h>

typedef __nv_bfloat16 bf16;

constexpr int S_LEN = 2048, DM = 576, DC = 512, HDIM = 4096, NQKVA = 1728, KCAT = 4672;
constexpr int NCLUSTER = 66;

__device__ __align__(1024) bf16 g_K[S_LEN * HDIM];
__device__ __align__(1024) bf16 g_V[S_LEN * HDIM];
__device__ __align__(1024) bf16 g_QKVA[S_LEN * NQKVA + 64];
__device__ __align__(1024) bf16 g_ctx[S_LEN * KCAT];
__device__ float g_gate[S_LEN];
__device__ __align__(1024) uint4 g_part[32 * 4 * 4 * 5 * 256];
__device__ __align__(16) unsigned int g_sync[400];
constexpr int F_QKVA = 0, F_HP = 16, F_CTX = 32, F_OA = 48, F_GATE = 96, F_TICK = 97, F_DONE = 98, F_XCH = 128, F_EPOCH = 384;

__device__ __forceinline__ uint32_t smem_u32(const void* p) { return (uint32_t)__cvta_generic_to_shared(p); }
__device__ __forceinline__ void mbar_init(uint32_t a, uint32_t c) {
  asm volatile("mbarrier.init.shared::cta.b64 [%0], %1;" ::"r"(a), "r"(c));
}
__device__ __forceinline__ void mbar_expect(uint32_t a, uint32_t b) {
  asm volatile("mbarrier.arrive.expect_tx.shared::cta.b64 _, [%0], %1;" ::"r"(a), "r"(b) : "memory");
}
#define TS(k, i)
#define TSC(k, i)
#define TSM(k)
#define BSEG(i)
#define TB(k)
#define TRC(fl)
#define SPIN_LIMIT "4194304"
__device__ __forceinline__ void mbar_wait(uint32_t a, uint32_t parity) {
  asm volatile(
      "{\n.reg .pred p;\n.reg .u32 n;\n"
      "mbarrier.try_wait.parity.shared::cta.b64 p, [%0], %1;\n"
      "@p bra DONE;\n"
      "mov.u32 n, 0;\n"
      "LOOP:\n"
      "mbarrier.try_wait.parity.shared::cta.b64 p, [%0], %1;\n"
      "@p bra DONE;\n"
      "add.u32 n, n, 1;\n"
      "setp.lt.u32 p, n, " SPIN_LIMIT ";\n"
      "@p bra LOOP;\n"
      "DONE:\n}" ::"r"(a), "r"(parity) : "memory");
}
template <int NS>
__device__ __forceinline__ void mbar_wait_ns(uint32_t a, uint32_t parity) {
  asm volatile(
      "{\n.reg .pred p;\n.reg .u32 n;\n"
      "mov.u32 n, 0;\n"
      "LOOP:\n"
      "mbarrier.try_wait.parity.shared::cta.b64 p, [%0], %1, %2;\n"
      "@p bra DONE;\n"
      "add.u32 n, n, 1;\n"
      "setp.lt.u32 p, n, " SPIN_LIMIT ";\n"
      "@p bra LOOP;\n"
      "DONE:\n}" ::"r"(a), "r"(parity), "n"(NS) : "memory");
}
__device__ __forceinline__ void mbar_wait2(uint32_t a, uint32_t pa, uint32_t b, uint32_t pb) {
  asm volatile(
      "{\n.reg .pred p, q;\n.reg .u32 n;\n"
      "mov.u32 n, 0;\n"
      "LOOP:\n"
      "mbarrier.try_wait.parity.shared::cta.b64 p, [%0], %1;\n"
      "mbarrier.try_wait.parity.shared::cta.b64 q, [%2], %3;\n"
      "add.u32 n, n, 1;\n"
      "and.pred p, p, q;\n"
      "setp.lt.and.u32 p, n, " SPIN_LIMIT ", !p;\n"
      "@p bra LOOP;\n"
      "}" ::"r"(a), "r"(pa), "r"(b), "r"(pb) : "memory");
}
__device__ __forceinline__ uint32_t mbar_test(uint32_t a, uint32_t parity) {
  uint32_t r;
  asm volatile("{\n.reg .pred p;\nmbarrier.test_wait.parity.shared::cta.b64 p, [%1], %2;\nselp.u32 %0, 1, 0, p;\n}" : "=r"(r) : "r"(a), "r"(parity) : "memory");
  return r;
}
__device__ __forceinline__ void mbar_arrive(uint32_t a) {
  asm volatile("mbarrier.arrive.shared::cta.b64 _, [%0];" ::"r"(a) : "memory");
}
__device__ __forceinline__ void mbar_arrive_cluster(uint32_t a, uint32_t cta) {
  asm volatile("{\n.reg .b32 r;\nmapa.shared::cluster.u32 r, %0, %1;\nmbarrier.arrive.shared::cluster.b64 _, [r];\n}" ::"r"(a),
               "r"(cta) : "memory");
}
__device__ __forceinline__ void mbar_arrive_cluster_if(uint32_t a, uint32_t cta, bool pred) {
  asm volatile("{\n.reg .b32 r;\n.reg .pred p;\nsetp.ne.u32 p, %2, 0;\nmapa.shared::cluster.u32 r, %0, %1;\n@p mbarrier.arrive.shared::cluster.b64 _, [r];\n}" ::"r"(a),
               "r"(cta), "r"((uint32_t)pred) : "memory");
}
__device__ __forceinline__ void anchor(float v, uint32_t pred) {
  asm volatile("{\n.reg .pred p;\nsetp.ne.u32 p, %1, 0;\n@p st.shared.f32 [%1], %0;\n}" ::"f"(v), "r"(pred) : "memory");
}
__device__ __forceinline__ void mbar_arrive_if(uint32_t a, bool pred) {
  asm volatile("{\n.reg .pred p;\nsetp.ne.u32 p, %1, 0;\n@p mbarrier.arrive.shared::cta.b64 _, [%0];\n}" ::"r"(a), "r"((uint32_t)pred) : "memory");
}
__device__ __forceinline__ void tma2d(uint32_t dst, const CUtensorMap* m, uint32_t bar, int c0, int c1) {
  asm volatile("cp.async.bulk.tensor.2d.shared::cluster.global.mbarrier::complete_tx::bytes [%0], [%1, {%3, %4}], [%2];" ::"r"(dst),
               "l"(m), "r"(bar), "r"(c0), "r"(c1) : "memory");
}
__device__ __forceinline__ void tma2d_mc(uint32_t dst, const CUtensorMap* m, uint32_t bar, int c0, int c1, uint16_t mask) {
  asm volatile(
      "cp.async.bulk.tensor.2d.shared::cluster.global.mbarrier::complete_tx::bytes.multicast::cluster [%0], [%1, {%3, %4}], [%2], %5;" ::"r"(dst),
      "l"(m), "r"(bar), "r"(c0), "r"(c1), "h"(mask) : "memory");
}
__device__ __forceinline__ void tma3d_mc(uint32_t dst, const CUtensorMap* m, uint32_t bar, int c0, int c1, int c2, uint16_t mask) {
  asm volatile(
      "cp.async.bulk.tensor.3d.shared::cluster.global.mbarrier::complete_tx::bytes.multicast::cluster [%0], [%1, {%3, %4, %5}], [%2], %6;" ::"r"(dst),
      "l"(m), "r"(bar), "r"(c0), "r"(c1), "r"(c2), "h"(mask) : "memory");
}
__device__ __forceinline__ void tma3d(uint32_t dst, const CUtensorMap* m, uint32_t bar, int c0, int c1, int c2) {
  asm volatile(
      "cp.async.bulk.tensor.3d.shared::cluster.global.mbarrier::complete_tx::bytes [%0], [%1, {%3, %4, %5}], [%2];" ::"r"(dst),
      "l"(m), "r"(bar), "r"(c0), "r"(c1), "r"(c2) : "memory");
}
__device__ __forceinline__ void tma_pf2d(const CUtensorMap* m, int c0, int c1) {
  asm volatile("cp.async.bulk.prefetch.tensor.2d.L2.global [%0, {%1, %2}];" ::"l"(m), "r"(c0), "r"(c1) : "memory");
}
__device__ __forceinline__ void tma_pf3d(const CUtensorMap* m, int c0, int c1, int c2) {
  asm volatile("cp.async.bulk.prefetch.tensor.3d.L2.global [%0, {%1, %2, %3}];" ::"l"(m), "r"(c0), "r"(c1), "r"(c2) : "memory");
}
__device__ __forceinline__ void prefetch_tmap(const CUtensorMap* m) {
  asm volatile("prefetch.tensormap [%0];" ::"l"(m) : "memory");
}
__device__ __forceinline__ void cluster_arrive() { asm volatile("barrier.cluster.arrive.relaxed.aligned;" ::: "memory"); }
__device__ __forceinline__ void cluster_wait() { asm volatile("barrier.cluster.wait.aligned;" ::: "memory"); }
__device__ __forceinline__ void cluster_sync() {
  cluster_arrive();
  cluster_wait();
}
__device__ __forceinline__ uint32_t cluster_rank() {
  uint32_t r;
  asm volatile("mov.u32 %0, %%cluster_ctarank;" : "=r"(r));
  return r;
}
__device__ __forceinline__ bool elect_one() {
  uint32_t p;
  asm volatile("{\n.reg .pred q;\nelect.sync _|q, 0xffffffff;\nselp.u32 %0, 1, 0, q;\n}" : "=r"(p));
  return p;
}
__device__ __forceinline__ void ldsm_x4(uint32_t& r0, uint32_t& r1, uint32_t& r2, uint32_t& r3, uint32_t addr) {
  asm volatile("ldmatrix.sync.aligned.m8n8.x4.shared.b16 {%0, %1, %2, %3}, [%4];" : "=r"(r0), "=r"(r1), "=r"(r2), "=r"(r3) : "r"(addr) : "memory");
}
__device__ __forceinline__ void wg_fence() { asm volatile("wgmma.fence.sync.aligned;" ::: "memory"); }
__device__ __forceinline__ void wg_commit() { asm volatile("wgmma.commit_group.sync.aligned;" ::: "memory"); }
template <int N>
__device__ __forceinline__ void wg_wait() { asm volatile("wgmma.wait_group.sync.aligned %0;" ::"n"(N) : "memory"); }
template <int N>
__device__ __forceinline__ void reg_alloc() { asm volatile("setmaxnreg.inc.sync.aligned.u32 %0;" ::"n"(N)); }
template <int N>
__device__ __forceinline__ void reg_dealloc() { asm volatile("setmaxnreg.dec.sync.aligned.u32 %0;" ::"n"(N)); }
__device__ __forceinline__ void bar_sync(int id, int n) { asm volatile("bar.sync %0, %1;" ::"r"(id), "r"(n) : "memory"); }
__device__ __forceinline__ void bar_arrive(int id, int n) { asm volatile("bar.arrive %0, %1;" ::"r"(id), "r"(n) : "memory"); }
template <int NT>
__device__ __forceinline__ void fence_regs(float (&d)[NT]) {
#pragma unroll
  for (int i = 0; i < NT; i++) asm volatile("" : "+f"(d[i])::"memory");
}
template <int NT>
__device__ __forceinline__ void fence_regs(uint32_t (&d)[NT]) {
#pragma unroll
  for (int i = 0; i < NT; i++) asm volatile("" : "+r"(d[i])::"memory");
}
__device__ __forceinline__ uint64_t make_desc(uint32_t saddr, uint32_t lbo, uint32_t sbo, uint32_t layout) {
  return (uint64_t)((saddr & 0x3FFFF) >> 4) | ((uint64_t)(lbo >> 4) << 16) | ((uint64_t)(sbo >> 4) << 32) | ((uint64_t)layout << 62);
}
__device__ __forceinline__ uint32_t pack_bf16(float lo, float hi) {
  uint32_t r;
  asm("cvt.rn.bf16x2.f32 %0, %1, %2;" : "=r"(r) : "f"(hi), "f"(lo));
  return r;
}
__device__ __forceinline__ float ex2(float x) {
  float r;
  asm("ex2.approx.ftz.f32 %0, %1;" : "=f"(r) : "f"(x));
  return r;
}
__device__ __forceinline__ void st_v4(void* p, uint32_t a, uint32_t b, uint32_t c, uint32_t d) {
#define ST_MOD ".cs"
  asm volatile("st.global" ST_MOD ".v4.b32 [%0], {%1, %2, %3, %4};" ::"l"(p), "r"(a), "r"(b), "r"(c), "r"(d) : "memory");
}
#define STA_MOD ".cs"
__device__ __forceinline__ void st_v4a(void* p, uint32_t a, uint32_t b, uint32_t c, uint32_t d) {
  asm volatile("st.global" STA_MOD ".v4.b32 [%0], {%1, %2, %3, %4};" ::"l"(p), "r"(a), "r"(b), "r"(c), "r"(d) : "memory");
}
template <typename T>
__device__ __forceinline__ T* ptr_add(T* base, uint32_t bytes) {
  uint64_t r;
  asm volatile("{\n.reg .u32 l, h;\nmov.b64 {l, h}, %1;\nadd.cc.u32 l, l, %2;\naddc.u32 h, h, 0;\nmov.b64 %0, {l, h};\n}" : "=l"(r) : "l"(base), "r"(bytes));
  return reinterpret_cast<T*>(r);
}
__device__ __forceinline__ float bf_lo(uint32_t v) { return __uint_as_float(v << 16); }
__device__ __forceinline__ float bf_hi(uint32_t v) { return __uint_as_float(v & 0xFFFF0000u); }

__device__ __forceinline__ void quad_transpose(uint32_t& a0, uint32_t& a1, uint32_t& a2, uint32_t& a3, int q) {
  const bool o1 = q & 1, o2 = q & 2;
  uint32_t t0 = o1 ? a0 : a1, t1 = o1 ? a2 : a3;
  t0 = __shfl_xor_sync(0xffffffffu, t0, 1);
  t1 = __shfl_xor_sync(0xffffffffu, t1, 1);
  if (o1) { a0 = t0; a2 = t1; } else { a1 = t0; a3 = t1; }
  t0 = o2 ? a0 : a2;
  t1 = o2 ? a1 : a3;
  t0 = __shfl_xor_sync(0xffffffffu, t0, 2);
  t1 = __shfl_xor_sync(0xffffffffu, t1, 2);
  if (o2) { a0 = t0; a1 = t1; } else { a2 = t0; a3 = t1; }
}

template<int TB, int OFF, int NT>
__device__ __forceinline__ void wgmma_ss_n256(float (&d)[NT], uint64_t da, uint64_t db, int scale_d) {
  asm volatile("{\n.reg .pred p;\nsetp.ne.b32 p, %130, 0;\n"
    "wgmma.mma_async.sync.aligned.m64n256k16.f32.bf16.bf16 {%0, %1, %2, %3, %4, %5, %6, %7, %8, %9, %10, %11, %12, %13, %14, %15, %16, %17, %18, %19, %20, %21, %22, %23, %24, %25, %26, %27, %28, %29, %30, %31, %32, %33, %34, %35, %36, %37, %38, %39, %40, %41, %42, %43, %44, %45, %46, %47, %48, %49, %50, %51, %52, %53, %54, %55, %56, %57, %58, %59, %60, %61, %62, %63, %64, %65, %66, %67, %68, %69, %70, %71, %72, %73, %74, %75, %76, %77, %78, %79, %80, %81, %82, %83, %84, %85, %86, %87, %88, %89, %90, %91, %92, %93, %94, %95, %96, %97, %98, %99, %100, %101, %102, %103, %104, %105, %106, %107, %108, %109, %110, %111, %112, %113, %114, %115, %116, %117, %118, %119, %120, %121, %122, %123, %124, %125, %126, %127}, %128, %129, p, 1, 1, 0, %131;\n}\n"
    : "+f"(d[OFF+0]), "+f"(d[OFF+1]), "+f"(d[OFF+2]), "+f"(d[OFF+3]), "+f"(d[OFF+4]), "+f"(d[OFF+5]), "+f"(d[OFF+6]), "+f"(d[OFF+7]), "+f"(d[OFF+8]), "+f"(d[OFF+9]), "+f"(d[OFF+10]), "+f"(d[OFF+11]), "+f"(d[OFF+12]), "+f"(d[OFF+13]), "+f"(d[OFF+14]), "+f"(d[OFF+15]), "+f"(d[OFF+16]), "+f"(d[OFF+17]), "+f"(d[OFF+18]), "+f"(d[OFF+19]), "+f"(d[OFF+20]), "+f"(d[OFF+21]), "+f"(d[OFF+22]), "+f"(d[OFF+23]), "+f"(d[OFF+24]), "+f"(d[OFF+25]), "+f"(d[OFF+26]), "+f"(d[OFF+27]), "+f"(d[OFF+28]), "+f"(d[OFF+29]), "+f"(d[OFF+30]), "+f"(d[OFF+31]), "+f"(d[OFF+32]), "+f"(d[OFF+33]), "+f"(d[OFF+34]), "+f"(d[OFF+35]), "+f"(d[OFF+36]), "+f"(d[OFF+37]), "+f"(d[OFF+38]), "+f"(d[OFF+39]), "+f"(d[OFF+40]), "+f"(d[OFF+41]), "+f"(d[OFF+42]), "+f"(d[OFF+43]), "+f"(d[OFF+44]), "+f"(d[OFF+45]), "+f"(d[OFF+46]), "+f"(d[OFF+47]), "+f"(d[OFF+48]), "+f"(d[OFF+49]), "+f"(d[OFF+50]), "+f"(d[OFF+51]), "+f"(d[OFF+52]), "+f"(d[OFF+53]), "+f"(d[OFF+54]), "+f"(d[OFF+55]), "+f"(d[OFF+56]), "+f"(d[OFF+57]), "+f"(d[OFF+58]), "+f"(d[OFF+59]), "+f"(d[OFF+60]), "+f"(d[OFF+61]), "+f"(d[OFF+62]), "+f"(d[OFF+63]), "+f"(d[OFF+64]), "+f"(d[OFF+65]), "+f"(d[OFF+66]), "+f"(d[OFF+67]), "+f"(d[OFF+68]), "+f"(d[OFF+69]), "+f"(d[OFF+70]), "+f"(d[OFF+71]), "+f"(d[OFF+72]), "+f"(d[OFF+73]), "+f"(d[OFF+74]), "+f"(d[OFF+75]), "+f"(d[OFF+76]), "+f"(d[OFF+77]), "+f"(d[OFF+78]), "+f"(d[OFF+79]), "+f"(d[OFF+80]), "+f"(d[OFF+81]), "+f"(d[OFF+82]), "+f"(d[OFF+83]), "+f"(d[OFF+84]), "+f"(d[OFF+85]), "+f"(d[OFF+86]), "+f"(d[OFF+87]), "+f"(d[OFF+88]), "+f"(d[OFF+89]), "+f"(d[OFF+90]), "+f"(d[OFF+91]), "+f"(d[OFF+92]), "+f"(d[OFF+93]), "+f"(d[OFF+94]), "+f"(d[OFF+95]), "+f"(d[OFF+96]), "+f"(d[OFF+97]), "+f"(d[OFF+98]), "+f"(d[OFF+99]), "+f"(d[OFF+100]), "+f"(d[OFF+101]), "+f"(d[OFF+102]), "+f"(d[OFF+103]), "+f"(d[OFF+104]), "+f"(d[OFF+105]), "+f"(d[OFF+106]), "+f"(d[OFF+107]), "+f"(d[OFF+108]), "+f"(d[OFF+109]), "+f"(d[OFF+110]), "+f"(d[OFF+111]), "+f"(d[OFF+112]), "+f"(d[OFF+113]), "+f"(d[OFF+114]), "+f"(d[OFF+115]), "+f"(d[OFF+116]), "+f"(d[OFF+117]), "+f"(d[OFF+118]), "+f"(d[OFF+119]), "+f"(d[OFF+120]), "+f"(d[OFF+121]), "+f"(d[OFF+122]), "+f"(d[OFF+123]), "+f"(d[OFF+124]), "+f"(d[OFF+125]), "+f"(d[OFF+126]), "+f"(d[OFF+127])
    : "l"(da), "l"(db), "r"(scale_d), "n"(TB));
}
template<int TB, int OFF, int NT>
__device__ __forceinline__ void wgmma_ss_n32(float (&d)[NT], uint64_t da, uint64_t db, int scale_d) {
  asm volatile("{\n.reg .pred p;\nsetp.ne.b32 p, %18, 0;\n"
    "wgmma.mma_async.sync.aligned.m64n32k16.f32.bf16.bf16 {%0, %1, %2, %3, %4, %5, %6, %7, %8, %9, %10, %11, %12, %13, %14, %15}, %16, %17, p, 1, 1, 0, %19;\n}\n"
    : "+f"(d[OFF+0]), "+f"(d[OFF+1]), "+f"(d[OFF+2]), "+f"(d[OFF+3]), "+f"(d[OFF+4]), "+f"(d[OFF+5]), "+f"(d[OFF+6]), "+f"(d[OFF+7]), "+f"(d[OFF+8]), "+f"(d[OFF+9]), "+f"(d[OFF+10]), "+f"(d[OFF+11]), "+f"(d[OFF+12]), "+f"(d[OFF+13]), "+f"(d[OFF+14]), "+f"(d[OFF+15])
    : "l"(da), "l"(db), "r"(scale_d), "n"(TB));
}
template<int TB, int OFF, int NT>
__device__ __forceinline__ void wgmma_rs_n128(float (&d)[NT], uint32_t a0, uint32_t a1, uint32_t a2, uint32_t a3, uint64_t db, int scale_d) {
  asm volatile("{\n.reg .pred p;\nsetp.ne.b32 p, %69, 0;\n"
    "wgmma.mma_async.sync.aligned.m64n128k16.f32.bf16.bf16 {%0, %1, %2, %3, %4, %5, %6, %7, %8, %9, %10, %11, %12, %13, %14, %15, %16, %17, %18, %19, %20, %21, %22, %23, %24, %25, %26, %27, %28, %29, %30, %31, %32, %33, %34, %35, %36, %37, %38, %39, %40, %41, %42, %43, %44, %45, %46, %47, %48, %49, %50, %51, %52, %53, %54, %55, %56, %57, %58, %59, %60, %61, %62, %63}, {%64, %65, %66, %67}, %68, p, 1, 1, %70;\n}\n"
    : "+f"(d[OFF+0]), "+f"(d[OFF+1]), "+f"(d[OFF+2]), "+f"(d[OFF+3]), "+f"(d[OFF+4]), "+f"(d[OFF+5]), "+f"(d[OFF+6]), "+f"(d[OFF+7]), "+f"(d[OFF+8]), "+f"(d[OFF+9]), "+f"(d[OFF+10]), "+f"(d[OFF+11]), "+f"(d[OFF+12]), "+f"(d[OFF+13]), "+f"(d[OFF+14]), "+f"(d[OFF+15]), "+f"(d[OFF+16]), "+f"(d[OFF+17]), "+f"(d[OFF+18]), "+f"(d[OFF+19]), "+f"(d[OFF+20]), "+f"(d[OFF+21]), "+f"(d[OFF+22]), "+f"(d[OFF+23]), "+f"(d[OFF+24]), "+f"(d[OFF+25]), "+f"(d[OFF+26]), "+f"(d[OFF+27]), "+f"(d[OFF+28]), "+f"(d[OFF+29]), "+f"(d[OFF+30]), "+f"(d[OFF+31]), "+f"(d[OFF+32]), "+f"(d[OFF+33]), "+f"(d[OFF+34]), "+f"(d[OFF+35]), "+f"(d[OFF+36]), "+f"(d[OFF+37]), "+f"(d[OFF+38]), "+f"(d[OFF+39]), "+f"(d[OFF+40]), "+f"(d[OFF+41]), "+f"(d[OFF+42]), "+f"(d[OFF+43]), "+f"(d[OFF+44]), "+f"(d[OFF+45]), "+f"(d[OFF+46]), "+f"(d[OFF+47]), "+f"(d[OFF+48]), "+f"(d[OFF+49]), "+f"(d[OFF+50]), "+f"(d[OFF+51]), "+f"(d[OFF+52]), "+f"(d[OFF+53]), "+f"(d[OFF+54]), "+f"(d[OFF+55]), "+f"(d[OFF+56]), "+f"(d[OFF+57]), "+f"(d[OFF+58]), "+f"(d[OFF+59]), "+f"(d[OFF+60]), "+f"(d[OFF+61]), "+f"(d[OFF+62]), "+f"(d[OFF+63])
    : "r"(a0), "r"(a1), "r"(a2), "r"(a3), "l"(db), "r"(scale_d), "n"(TB));
}
template<int TB, int OFF, int NT>
__device__ __forceinline__ void wgmma_rs_n256(float (&d)[NT], uint32_t a0, uint32_t a1, uint32_t a2, uint32_t a3, uint64_t db, int scale_d) {
  asm volatile("{\n.reg .pred p;\nsetp.ne.b32 p, %133, 0;\n"
    "wgmma.mma_async.sync.aligned.m64n256k16.f32.bf16.bf16 {%0, %1, %2, %3, %4, %5, %6, %7, %8, %9, %10, %11, %12, %13, %14, %15, %16, %17, %18, %19, %20, %21, %22, %23, %24, %25, %26, %27, %28, %29, %30, %31, %32, %33, %34, %35, %36, %37, %38, %39, %40, %41, %42, %43, %44, %45, %46, %47, %48, %49, %50, %51, %52, %53, %54, %55, %56, %57, %58, %59, %60, %61, %62, %63, %64, %65, %66, %67, %68, %69, %70, %71, %72, %73, %74, %75, %76, %77, %78, %79, %80, %81, %82, %83, %84, %85, %86, %87, %88, %89, %90, %91, %92, %93, %94, %95, %96, %97, %98, %99, %100, %101, %102, %103, %104, %105, %106, %107, %108, %109, %110, %111, %112, %113, %114, %115, %116, %117, %118, %119, %120, %121, %122, %123, %124, %125, %126, %127}, {%128, %129, %130, %131}, %132, p, 1, 1, %134;\n}\n"
    : "+f"(d[OFF+0]), "+f"(d[OFF+1]), "+f"(d[OFF+2]), "+f"(d[OFF+3]), "+f"(d[OFF+4]), "+f"(d[OFF+5]), "+f"(d[OFF+6]), "+f"(d[OFF+7]), "+f"(d[OFF+8]), "+f"(d[OFF+9]), "+f"(d[OFF+10]), "+f"(d[OFF+11]), "+f"(d[OFF+12]), "+f"(d[OFF+13]), "+f"(d[OFF+14]), "+f"(d[OFF+15]), "+f"(d[OFF+16]), "+f"(d[OFF+17]), "+f"(d[OFF+18]), "+f"(d[OFF+19]), "+f"(d[OFF+20]), "+f"(d[OFF+21]), "+f"(d[OFF+22]), "+f"(d[OFF+23]), "+f"(d[OFF+24]), "+f"(d[OFF+25]), "+f"(d[OFF+26]), "+f"(d[OFF+27]), "+f"(d[OFF+28]), "+f"(d[OFF+29]), "+f"(d[OFF+30]), "+f"(d[OFF+31]), "+f"(d[OFF+32]), "+f"(d[OFF+33]), "+f"(d[OFF+34]), "+f"(d[OFF+35]), "+f"(d[OFF+36]), "+f"(d[OFF+37]), "+f"(d[OFF+38]), "+f"(d[OFF+39]), "+f"(d[OFF+40]), "+f"(d[OFF+41]), "+f"(d[OFF+42]), "+f"(d[OFF+43]), "+f"(d[OFF+44]), "+f"(d[OFF+45]), "+f"(d[OFF+46]), "+f"(d[OFF+47]), "+f"(d[OFF+48]), "+f"(d[OFF+49]), "+f"(d[OFF+50]), "+f"(d[OFF+51]), "+f"(d[OFF+52]), "+f"(d[OFF+53]), "+f"(d[OFF+54]), "+f"(d[OFF+55]), "+f"(d[OFF+56]), "+f"(d[OFF+57]), "+f"(d[OFF+58]), "+f"(d[OFF+59]), "+f"(d[OFF+60]), "+f"(d[OFF+61]), "+f"(d[OFF+62]), "+f"(d[OFF+63]), "+f"(d[OFF+64]), "+f"(d[OFF+65]), "+f"(d[OFF+66]), "+f"(d[OFF+67]), "+f"(d[OFF+68]), "+f"(d[OFF+69]), "+f"(d[OFF+70]), "+f"(d[OFF+71]), "+f"(d[OFF+72]), "+f"(d[OFF+73]), "+f"(d[OFF+74]), "+f"(d[OFF+75]), "+f"(d[OFF+76]), "+f"(d[OFF+77]), "+f"(d[OFF+78]), "+f"(d[OFF+79]), "+f"(d[OFF+80]), "+f"(d[OFF+81]), "+f"(d[OFF+82]), "+f"(d[OFF+83]), "+f"(d[OFF+84]), "+f"(d[OFF+85]), "+f"(d[OFF+86]), "+f"(d[OFF+87]), "+f"(d[OFF+88]), "+f"(d[OFF+89]), "+f"(d[OFF+90]), "+f"(d[OFF+91]), "+f"(d[OFF+92]), "+f"(d[OFF+93]), "+f"(d[OFF+94]), "+f"(d[OFF+95]), "+f"(d[OFF+96]), "+f"(d[OFF+97]), "+f"(d[OFF+98]), "+f"(d[OFF+99]), "+f"(d[OFF+100]), "+f"(d[OFF+101]), "+f"(d[OFF+102]), "+f"(d[OFF+103]), "+f"(d[OFF+104]), "+f"(d[OFF+105]), "+f"(d[OFF+106]), "+f"(d[OFF+107]), "+f"(d[OFF+108]), "+f"(d[OFF+109]), "+f"(d[OFF+110]), "+f"(d[OFF+111]), "+f"(d[OFF+112]), "+f"(d[OFF+113]), "+f"(d[OFF+114]), "+f"(d[OFF+115]), "+f"(d[OFF+116]), "+f"(d[OFF+117]), "+f"(d[OFF+118]), "+f"(d[OFF+119]), "+f"(d[OFF+120]), "+f"(d[OFF+121]), "+f"(d[OFF+122]), "+f"(d[OFF+123]), "+f"(d[OFF+124]), "+f"(d[OFF+125]), "+f"(d[OFF+126]), "+f"(d[OFF+127])
    : "r"(a0), "r"(a1), "r"(a2), "r"(a3), "l"(db), "r"(scale_d), "n"(TB));
}
template<int TB, int OFF, int NT>
__device__ __forceinline__ void wgmma_rs_n32(float (&d)[NT], uint32_t a0, uint32_t a1, uint32_t a2, uint32_t a3, uint64_t db, int scale_d) {
  asm volatile("{\n.reg .pred p;\nsetp.ne.b32 p, %21, 0;\n"
    "wgmma.mma_async.sync.aligned.m64n32k16.f32.bf16.bf16 {%0, %1, %2, %3, %4, %5, %6, %7, %8, %9, %10, %11, %12, %13, %14, %15}, {%16, %17, %18, %19}, %20, p, 1, 1, %22;\n}\n"
    : "+f"(d[OFF+0]), "+f"(d[OFF+1]), "+f"(d[OFF+2]), "+f"(d[OFF+3]), "+f"(d[OFF+4]), "+f"(d[OFF+5]), "+f"(d[OFF+6]), "+f"(d[OFF+7]), "+f"(d[OFF+8]), "+f"(d[OFF+9]), "+f"(d[OFF+10]), "+f"(d[OFF+11]), "+f"(d[OFF+12]), "+f"(d[OFF+13]), "+f"(d[OFF+14]), "+f"(d[OFF+15])
    : "r"(a0), "r"(a1), "r"(a2), "r"(a3), "l"(db), "r"(scale_d), "n"(TB));
}

__device__ __forceinline__ void wait_flag(const unsigned int* f, uint32_t target) {
  uint32_t v;
#pragma unroll 1
  for (uint32_t spins = 0; spins < (1u << 22); spins++) {
    asm volatile("ld.acquire.gpu.global.u32 %0, [%1];" : "=r"(v) : "l"(f) : "memory");
    if (v >= target) break;
    __nanosleep(100);
  }
}
__device__ __forceinline__ uint32_t lds32(uint32_t a) {
  uint32_t v;
  asm volatile("ld.shared.u32 %0, [%1];" : "=r"(v) : "r"(a) : "memory");
  return v;
}
__device__ __forceinline__ float gate_row(int row, int lane, const bf16* __restrict__ x, const bf16* __restrict__ gate_w) {
  const uint32_t* xr = reinterpret_cast<const uint32_t*>(x + (size_t)row * DM);
  const uint32_t* gw2 = reinterpret_cast<const uint32_t*>(gate_w);
  float gs = 0.f;
#pragma unroll
  for (int i = 0; i < 9; i++) {
    const uint32_t a = __ldg(xr + lane + 32 * i), b = __ldg(gw2 + lane + 32 * i);
    gs = fmaf(bf_lo(a), bf_lo(b), gs);
    gs = fmaf(bf_hi(a), bf_hi(b), gs);
  }
#pragma unroll
  for (int o = 16; o; o >>= 1) gs += __shfl_xor_sync(0xffffffffu, gs, o);
  const float g = 1.f / (1.f + __expf(-gs));
  if (lane == 0) g_gate[row] = g;
  return g;
}
constexpr uint32_t LQ = 36864, LV = 55296;
__device__ __forceinline__ void mma16(float (&c)[4], uint32_t a0, uint32_t a1, uint32_t a2, uint32_t a3, uint32_t b0, uint32_t b1) {
  asm("mma.sync.aligned.m16n8k16.row.col.f32.bf16.bf16.f32 {%0, %1, %2, %3}, {%4, %5, %6, %7}, {%8, %9}, {%0, %1, %2, %3};"
      : "+f"(c[0]), "+f"(c[1]), "+f"(c[2]), "+f"(c[3]) : "r"(a0), "r"(a1), "r"(a2), "r"(a3), "r"(b0), "r"(b1));
}
__device__ __forceinline__ void mma8(float (&c)[4], uint32_t a0, uint32_t a1, uint32_t b0) {
  asm("mma.sync.aligned.m16n8k8.row.col.f32.bf16.bf16.f32 {%0, %1, %2, %3}, {%4, %5}, {%6}, {%0, %1, %2, %3};"
      : "+f"(c[0]), "+f"(c[1]), "+f"(c[2]), "+f"(c[3]) : "r"(a0), "r"(a1), "r"(b0));
}
__device__ __forceinline__ void local_attn(int lr0, int warp_g, uint32_t sL, uint32_t bL, uint32_t bL2, int lane, float g0, float g1) {
  const float scale_l2 = 0.23570226039551584f * 1.4426950408889634f;
  const int g = lane >> 2, t = lane & 3;
  const bool lo0 = 2 * t > g, lo1 = 2 * t + 1 > g;
  const uint32_t mlo = (lo0 ? 0xFFFFu : 0u) | (lo1 ? 0xFFFF0000u : 0u);
  const bool ok0 = lr0 > 0 || !lo0, ok1 = lr0 > 0 || !lo1;
  uint32_t ad[9], k[9][4], qf[9][2], pe[4], po[4];
#pragma unroll
  for (int c = 0; c < 9; c++) {
    const uint32_t ch = warp_g * 9 + c;
    ad[c] = sL + (lane >> 4) * 18432 + (lane & 15) * 128 + ((ch >> 3) << 11) + (((ch ^ lane) & 7) << 4);
  }
  mbar_wait(bL, 0);
  if (warp_g == 0) TS(1, 6);
#pragma unroll
  for (int c = 0; c < 9; c++) {
    asm volatile("ldmatrix.sync.aligned.m8n8.x2.shared.b16 {%0, %1}, [%2];" : "=r"(qf[c][0]), "=r"(qf[c][1]) : "r"(ad[c] + LQ) : "memory");
    ldsm_x4(k[c][0], k[c][1], k[c][2], k[c][3], ad[c]);
  }
#pragma unroll
  for (int i = 0; i < 4; i++) {
    const uint32_t q0 = (t >= i) ? qf[2 * i][0] : 0u, q1 = (t >= i) ? qf[2 * i][1] : 0u;
    const uint32_t q4 = (t <= i) ? qf[2 * i + 2][0] : 0u, q5 = (t <= i) ? qf[2 * i + 2][1] : 0u;
    float c[4][4];
#pragma unroll
    for (int T = 0; T < 4; T++) {
#pragma unroll
      for (int j = 0; j < 4; j++) c[T][j] = 0.f;
      mma16(c[T], q0, q1, qf[2 * i + 1][0], qf[2 * i + 1][1], k[2 * i][T], k[2 * i + 1][T]);
      mma8(c[T], q4, q5, k[2 * i + 2][T]);
    }
    const float e0 = ok0 ? (lo0 ? c[0][0] : c[1][0]) : -INFINITY, e1 = ok1 ? (lo1 ? c[0][1] : c[1][1]) : -INFINITY;
    const float o0 = ok0 ? (lo0 ? c[2][2] : c[3][2]) : -INFINITY, o1 = ok1 ? (lo1 ? c[2][3] : c[3][3]) : -INFINITY;
    float me = fmaxf(e0, e1), mo = fmaxf(o0, o1);
    me = fmaxf(me, __shfl_xor_sync(0xffffffffu, me, 1));
    mo = fmaxf(mo, __shfl_xor_sync(0xffffffffu, mo, 1));
    me = fmaxf(me, __shfl_xor_sync(0xffffffffu, me, 2)) * scale_l2;
    mo = fmaxf(mo, __shfl_xor_sync(0xffffffffu, mo, 2)) * scale_l2;
    const float w0 = ex2(fmaf(e0, scale_l2, -me)), w1 = ex2(fmaf(e1, scale_l2, -me));
    const float w2 = ex2(fmaf(o0, scale_l2, -mo)), w3 = ex2(fmaf(o1, scale_l2, -mo));
    float se = w0 + w1, so = w2 + w3;
    se += __shfl_xor_sync(0xffffffffu, se, 1);
    so += __shfl_xor_sync(0xffffffffu, so, 1);
    se += __shfl_xor_sync(0xffffffffu, se, 2);
    so += __shfl_xor_sync(0xffffffffu, so, 2);
    asm("rcp.approx.ftz.f32 %0, %0;" : "+f"(se));
    asm("rcp.approx.ftz.f32 %0, %0;" : "+f"(so));
    se *= g0;
    so *= g1;
    pe[i] = pack_bf16(w0 * se, w1 * se);
    po[i] = pack_bf16(w2 * so, w3 * so);
  }
  if (warp_g == 0) TS(0, 4);
  mbar_wait(bL2, 0);
  if (warp_g == 0) TS(0, 5);
#pragma unroll
  for (int c = 0; c < 9; c++)
    asm volatile("ldmatrix.sync.aligned.m8n8.x4.trans.shared.b16 {%0, %1, %2, %3}, [%4];"
                 : "=r"(k[c][0]), "=r"(k[c][1]), "=r"(k[c][2]), "=r"(k[c][3]) : "r"(ad[c] + LV) : "memory");
#pragma unroll
  for (int i = 0; i < 4; i++) {
#pragma unroll
    for (int n = 0; n < 3; n++) {
      float c[4] = {0.f, 0.f, 0.f, 0.f};
      mma16(c, pe[i] & mlo, 0u, pe[i] & ~mlo, 0u, k[2 * i + n][0], k[2 * i + n][1]);
      mma16(c, 0u, po[i] & mlo, 0u, po[i] & ~mlo, k[2 * i + n][2], k[2 * i + n][3]);
      const uint32_t r0 = pack_bf16(c[0], c[1]), r1 = pack_bf16(c[2], c[3]);
      const bool keep = (n == 0) && (t < i);
      qf[2 * i + n][0] = keep ? qf[2 * i + n][0] : r0;
      qf[2 * i + n][1] = keep ? qf[2 * i + n][1] : r1;
    }
  }
#pragma unroll
  for (int c = 0; c < 9; c++)
    asm volatile("stmatrix.sync.aligned.m8n8.x2.shared.b16 [%0], {%1, %2};" ::"r"(ad[c] + LQ), "r"(qf[c][0]), "r"(qf[c][1]) : "memory");
  asm volatile("fence.proxy.async.shared::cta;" ::: "memory");
}
__device__ __forceinline__ void tma4d(uint32_t dst, const CUtensorMap* m, uint32_t bar, int c1, int c2, int c3) {
  asm volatile("cp.async.bulk.tensor.4d.shared::cluster.global.mbarrier::complete_tx::bytes [%0], [%1, {%3, %4, %5, %6}], [%2];" ::"r"(dst),
               "l"(m), "r"(bar), "r"(0), "r"(c1), "r"(c2), "r"(c3) : "memory");
}

#define K1_NST 6
constexpr int K1_BST = K1_NST;
#define MAXJ 11
constexpr int K1_MAXJOBS = MAXJ;
constexpr uint32_t K1_FLAG_TARGET = 7;
constexpr uint32_t RDY_TARGET = 48;
constexpr uint32_t GATE_TARGET = 128 * 3;
struct alignas(64) Params {
  CUtensorMap tmA[2];
  CUtensorMap tmW[4];
  CUtensorMap tmK, tmV;
  CUtensorMap tmL[3];
  CUtensorMap tmC, tmO[2], tmOt[2];
  uint16_t jobs[NCLUSTER][K1_MAXJOBS + 1];
  uint8_t order[256];
  uint8_t unit[64][8];
};

struct K1State {
  uint32_t bs, bph, aph;
  bf16 *pp, *pp8;
  int png;
  int tn;
  int wsel;
};
__device__ __forceinline__ void k1_flag(const K1State& st, int lane, uint32_t bS) {
  if (st.png) {
    __syncwarp();
    if (lane == 0) mbar_arrive(bS);
  }
}

__device__ __forceinline__ void scale_q4(uint32_t* v) {
#pragma unroll
  for (int i = 0; i < 4; i++)
    asm volatile("{\n.reg .b32 t;\nmul.rn.bf16x2 t, %0, %2;\nfma.rn.bf16x2 %0, %0, %1, t;\n}" : "+r"(v[i]) : "r"(0x3E033E03u), "r"(0xB9D8B9D8u));
}
__device__ __forceinline__ void k1_first(const K1State& st, uint32_t job, uint32_t bAf, uint32_t bBf) {
  if (job & 3) {
    if ((job >> 14) & 1) mbar_wait(bAf, st.aph);
    mbar_wait(bBf + st.bs * 8, st.bph);
  }
}
__device__ __forceinline__ void k1_tile(float (&acc)[128], uint32_t (&pk)[64], K1State& st, uint32_t job, uint32_t njob, uint32_t sA, uint32_t sB,
                                        uint32_t bAf, uint32_t bAe, uint32_t bBf, uint32_t bBe, uint32_t bS, int wg, int warp, int lane, uint32_t rank) {
  const int a_sel = (job >> 2) & 1, mpair = (job >> 3) & 7, w_sel = (job >> 6) & 3, chunk0 = (job >> 8) & 63;
  const bool newA = (job >> 14) & 1, lastA = (job >> 15) & 1;
  const bool sig = (lane == 0) && (warp < 2);
  const bool siga = lastA && (lane == 0) && (warp == 2);
  const int KC = 8 + a_sel;
  uint32_t prev_bs = 0, a8_bs = 0;
#pragma unroll
  for (int kc = 0; kc < 9; kc++) {
    if (kc >= KC) break;
    uint32_t abase = sA + ((kc + 2) & 7) * 16384;
    if (kc == 8) {
      mbar_wait(bBf + st.bs * 8, st.bph);
      a8_bs = st.bs;
      abase = sB + st.bs * 16384;
      if (++st.bs == K1_BST) { st.bs = 0; st.bph ^= 1; }
    } else if (newA && kc > 0) {
      mbar_wait(bAf + kc * 8, st.aph);
    }
    const uint64_t da = make_desc(abase + wg * 8192, 16, 1024, 1);
#pragma unroll
    for (int ks = 0; ks < 2; ks++) {
      if (ks > 0 || kc > 0) mbar_wait(bBf + st.bs * 8, st.bph);
      const uint64_t db = make_desc(sB + st.bs * 16384, 2048, 1024, 1);
      wg_fence();
      wgmma_ss_n256<1, 0>(acc, da + (uint64_t)(ks * 4), db, (ks > 0) ? 1 : (kc > 0));
      wgmma_ss_n256<1, 0>(acc, da + (uint64_t)(ks * 4 + 2), db + (uint64_t)512, 1);
      wg_commit();
      const int PO = (kc < 8 ? kc : 0) * 8;
      wg_wait<1>();
      if (ks > 0 || kc > 0) {
        if (sig) mbar_arrive_cluster(bBe + prev_bs * 8, warp);
        if (ks == 0 && siga) mbar_arrive(bAe + (kc - 1) * 8);
      }
      if (kc < 8 && st.wsel >= 2) {
        if (st.wsel == 3) scale_q4(pk + PO + ks * 4);
        else quad_transpose(pk[PO + ks * 4], pk[PO + ks * 4 + 1], pk[PO + ks * 4 + 2], pk[PO + ks * 4 + 3], lane & 3);
      }
      if (kc < st.png) st_v4a((ks ? st.pp8 : st.pp) + kc * 32, pk[PO + ks * 4], pk[PO + ks * 4 + 1], pk[PO + ks * 4 + 2], pk[PO + ks * 4 + 3]);
      prev_bs = st.bs;
      if (++st.bs == K1_BST) { st.bs = 0; st.bph ^= 1; }
    }
  }
  if (newA) st.aph ^= 1;
  k1_flag(st, lane, bS);
  const bool isA = (w_sel == 2);
  bf16* out = (w_sel == 0) ? g_K : (w_sel == 1) ? g_V : isA ? g_QKVA : g_ctx;
  const int ld = isA ? NQKVA : (w_sel == 3) ? KCAT : HDIM;
  const int row = mpair * 256 + rank * 128 + wg * 64 + warp * 16 + (lane >> 2);
  st.pp = ptr_add(out, (row * ld + chunk0 * 64 + (lane & 3) * 8) * 2);
  st.pp8 = ptr_add(st.pp, 16 * ld);
  st.png = ((job & 3) + 1) * 2;
  st.wsel = w_sel;
  k1_first(st, njob, bAf, bBf);
  wg_wait<0>();
  fence_regs(acc);
  mbar_arrive_cluster_if(bBe + prev_bs * 8, warp & 1, sig);
  mbar_arrive_cluster_if(bBe + a8_bs * 8, warp & 1, sig && a_sel);
  mbar_arrive_if(bAe + 7 * 8, siga && !a_sel);
#pragma unroll
  for (int i = 0; i < 64; i++) {
    const int j = (i >> 3) * 16 + (i & 3) * 4 + ((i >> 2) & 1) * 2;
    pk[i] = pack_bf16(acc[j], acc[j + 1]);
  }
}

constexpr int K2_NST = 7;
constexpr uint32_t K2_END = 0x100;
#define PF_KC 4
#define FIRST_DRAW 3
#define PWAIT mbar_wait_ns<1000>
#define PVM 0x8A
#define W0 63
#define SPEC_HI 1.8446744073709552e19f
#define SPEC_LO 5.421010862427522e-20f
constexpr int K3_NST = 4;
__device__ __forceinline__ uint32_t k3_rot(uint32_t sv) { return (0x00E9u >> (2 * sv)) & 3; }
constexpr int K3_STAGE = 16384 + 32768 + 4096;
constexpr int SMEM_DATA = 7 * 32768;
constexpr int SMEM_BYTES = SMEM_DATA + 1024 + 768;

struct Cursor {
  uint32_t s, ph;
  __device__ __forceinline__ void next() {
    if (++s == K2_NST) { s = 0; ph ^= 1; }
  }
};

#define TURN_SYNC() bar_sync(mybar, 256)
#define TURN_ARRIVE() bar_arrive(otherbar, 256)
#define RELEASE_IF(cur, cond) mbar_arrive_cluster_if(bE + (cur).s * 8, warp & 1, sig && (cond))
#define RELEASE(cur) RELEASE_IF(cur, true)
#define ISSUE_PV(cur, first)                                                                                   \
  do {                                                                                                         \
    const uint64_t dv = make_desc(sbase + (cur).s * 32768, 16384, 1024, 1);                                    \
    _Pragma("unroll") for (int t = 0; t < 8; t++)                                                              \
        wgmma_rs_n128<1, 0>(O, P[4 * t], P[4 * t + 1], P[4 * t + 2], P[4 * t + 3], dv + (uint64_t)(t * 128), (t > 0) ? 1 : !(first)); \
  } while (0)
#define ISSUE_QK(cur)                                                                                          \
  do {                                                                                                         \
    const uint64_t dk = make_desc(sbase + (cur).s * 32768, 16, 1024, 1);                                       \
    _Pragma("unroll") for (int t = 0; t < 8; t++)                                                              \
        wgmma_rs_n128<0, 0>(S, Q[4 * t], Q[4 * t + 1], Q[4 * t + 2], Q[4 * t + 3], dk + (uint64_t)((t >> 2) * 1024 + (t & 3) * 2), t > 0); \
  } while (0)
#define EXPB(T)                                                                                                \
  do {                                                                                                         \
    _Pragma("unroll") for (int i = 4 * T; i < 4 * T + 4; i++) asm volatile("" : "+r"(P[i])::"memory");        \
    _Pragma("unroll") for (int jj = 2 * T; jj < 2 * T + 2; jj++) {                                             \
      const float e0 = ex2(S[jj * 4 + 0]), e1 = ex2(S[jj * 4 + 1]), e2 = ex2(S[jj * 4 + 2]), e3 = ex2(S[jj * 4 + 3]); \
      s0 += e0 + e1;                                                                                           \
      s1 += e2 + e3;                                                                                           \
      P[jj * 2 + 0] = pack_bf16(e0, e1);                                                                       \
      P[jj * 2 + 1] = pack_bf16(e2, e3);                                                                       \
    }                                                                                                          \
  } while (0)
#define EXPC(T)                                                                                                \
  do {                                                                                                         \
    if (T > 0 && ((PVM >> (T - 1)) & 1)) {                                                                     \
      anchor((T & 2) ? s0 : s1, never);                                                                        \
      wg_wait<__builtin_popcount(PVM >> T) - 1>();                                                             \
      if ((PVM >> T) == (128 >> T)) { fence_regs(O); RELEASE(cv); }                                            \
    }                                                                                                          \
    EXPB(T);                                                                                                   \
  } while (0)
#define MASK(G, g)                                                                                             \
  do {                                                                                                         \
    if ((g) * 8 > d) S[(G) * 4 + 0] = -INFINITY;                                                               \
    if ((g) * 8 + 1 > d) S[(G) * 4 + 1] = -INFINITY;                                                           \
    if ((g) * 8 - 8 > d) S[(G) * 4 + 2] = -INFINITY;                                                           \
    if ((g) * 8 - 7 > d) S[(G) * 4 + 3] = -INFINITY;                                                           \
  } while (0)
#define STORE_O(G)                                                                                             \
  do {                                                                                                         \
    st_v4(optr + (G) * 32, pack_bf16(O[(G) * 16 + 0] * f0, O[(G) * 16 + 1] * f0), pack_bf16(O[(G) * 16 + 4] * f0, O[(G) * 16 + 5] * f0), \
          pack_bf16(O[(G) * 16 + 8] * f0, O[(G) * 16 + 9] * f0), pack_bf16(O[(G) * 16 + 12] * f0, O[(G) * 16 + 13] * f0)); \
    st_v4(optr + 8 * KCAT + (G) * 32, pack_bf16(O[(G) * 16 + 2] * f1, O[(G) * 16 + 3] * f1), pack_bf16(O[(G) * 16 + 6] * f1, O[(G) * 16 + 7] * f1), \
          pack_bf16(O[(G) * 16 + 10] * f1, O[(G) * 16 + 11] * f1), pack_bf16(O[(G) * 16 + 14] * f1, O[(G) * 16 + 15] * f1)); \
  } while (0)

#define FLUSH()                                                                                                \
  do {                                                                                                         \
    _Pragma("unroll") for (int G = 0; G < 8; G++) {                                                            \
      st_v4a(st.pp + G * 32, pk[G * 8], pk[G * 8 + 1], pk[G * 8 + 2], pk[G * 8 + 3]);                          \
      st_v4a(st.pp8 + G * 32, pk[G * 8 + 4], pk[G * 8 + 5], pk[G * 8 + 6], pk[G * 8 + 7]);                     \
    }                                                                                                          \
    k1_flag(st, lane, bS);                                                                                     \
  } while (0)

__global__ void __cluster_dims__(2, 1, 1) __launch_bounds__(384, 1)
fused_kernel(const __grid_constant__ Params p, const bf16* __restrict__ x, const bf16* __restrict__ gate_w, bf16* __restrict__ out) {
  extern __shared__ uint8_t smem_raw[];
  const uint32_t sbase = (smem_u32(smem_raw) + 1023) & ~1023u;
  const uint32_t sB = sbase, sA = sbase + K1_BST * 16384, sBar = sbase + SMEM_DATA;
  const uint32_t bAf = sBar, bAe = sBar + 64, bBf = sBar + 128, bBe = sBar + 176, bL = sBar + 224, bS = sBar + 232, bL2 = sBar + 240, sL = sA + 32768;
  const uint32_t bF = sBar + 256, bE = sBar + 320, bT = sBar + 384, sTick = sBar + 400, sItem = sBar + 416, bS2 = sBar + 448, bR = sBar + 456, bLast = sBar + 464, bH = sBar + 472, bT0 = sBar + 480;
  const uint32_t b3F = sBar + 512, b3E = sBar + 544, sGate = sBar + 576;
  const int tid = threadIdx.x, warp_g = __shfl_sync(0xffffffffu, tid >> 5, 0), lane = tid & 31;
  const uint32_t rank = cluster_rank();
  const int cl = blockIdx.x >> 1;
  TSM(0);
  if (tid == 0) {
    for (int i = 0; i < 8; i++) { mbar_init(bAf + i * 8, 1); mbar_init(bAe + i * 8, 2); }
    for (int i = 0; i < K1_BST; i++) { mbar_init(bBf + i * 8, 1); mbar_init(bBe + i * 8, 4); }
    mbar_init(bL, 1);
    mbar_init(bL2, 1);
    mbar_init(bR, 1);
    mbar_init(bLast, 1);
    mbar_init(bH, 4);
    mbar_init(bT0, 1);
    mbar_init(bS, 8);
    for (int i = 0; i < K2_NST; i++) { mbar_init(bF + i * 8, 1); mbar_init(bE + i * 8, 4); }
    mbar_init(bT, 1); mbar_init(bT + 8, 1);
    mbar_init(bS2, 8);
    for (int i = 0; i < K3_NST; i++) { mbar_init(b3F + i * 8, 1); mbar_init(b3E + i * 8, 4); }
    asm volatile("fence.mbarrier_init.release.cluster;" ::: "memory");
  }
  __syncwarp();
  if (warp_g != 8) cluster_sync();
  const int lr0 = blockIdx.x * 16;

  if (warp_g >= 8) {
    reg_dealloc<40>();
    if (warp_g == 8) {
      {
        const uint32_t job = p.jobs[cl][0];
        if (lane == 0) { prefetch_tmap(&p.tmA[(job >> 2) & 1]); prefetch_tmap(&p.tmW[(job >> 6) & 3]); }
        __syncwarp();
        cluster_sync();
      }
      if (elect_one()) {
        uint32_t bs = 0, bph = 1, aph = 1;
#pragma unroll 1
        for (int ji = 0; ji < K1_MAXJOBS; ji++) {
          const uint32_t job = p.jobs[cl][ji];
          if (!(job & 3)) break;
          const int a_sel = (job >> 2) & 1, mpair = (job >> 3) & 7, chunk0 = (job >> 8) & 63;
          const bool newA = (job >> 14) & 1;
          const int KC = a_sel ? 9 : 8;
          const uint32_t halfbytes = 8192;
          const bool lastjob = (ji + 1 == K1_MAXJOBS) || !(p.jobs[cl][ji + 1] & 3);
          const CUtensorMap* tw = &p.tmW[(job >> 6) & 3];
          {
            const uint32_t njob = (ji + 1 < K1_MAXJOBS) ? p.jobs[cl][ji + 1] : 0;
            if (!(njob & 3) && !newA) mbar_arrive(bLast);
          }
#pragma unroll 1
          for (int kc = 0; kc < KC; kc++) {
            if (kc == ((ji == 0) ? PF_KC : 0) && !lastjob) {
              const uint32_t njob = p.jobs[cl][ji + 1];
              const int nst = ((njob >> 2) & 1) ? 18 : 16;
#pragma unroll 1
              for (int t = (cl < 64) ? (cl & 7) : 0; t < nst; t += (cl < 64) ? 8 : 1)
                tma_pf3d(&p.tmW[(njob >> 6) & 3], 0, t * 32 + rank * 16, (njob >> 8) & 63);
            }
            if (kc == 8) {
              PWAIT(bBe + bs * 8, bph);
              mbar_expect(bBf + bs * 8, 16384);
              tma2d(sB + bs * 16384, &p.tmA[1], bBf + bs * 8, 512, mpair * 256 + rank * 128);
              if (++bs == K1_BST) { bs = 0; bph ^= 1; }
            } else if (newA) {
              PWAIT(bAe + kc * 8, aph);
              mbar_expect(bAf + kc * 8, 16384);
              tma2d(sA + ((kc + 2) & 7) * 16384, &p.tmA[a_sel], bAf + kc * 8, kc * 64, mpair * 256 + rank * 128);
              if (kc == 7 && lastjob) mbar_arrive(bLast);
            }
#pragma unroll 1
            for (int kk = 0; kk < 2; kk++) {
              PWAIT(bBe + bs * 8, bph);
              mbar_expect(bBf + bs * 8, 2 * halfbytes);
              tma3d_mc(sB + bs * 16384 + rank * halfbytes, tw, bBf + bs * 8, 0, kc * 64 + kk * 32 + rank * 16, chunk0, 3);
              if (++bs == K1_BST) { bs = 0; bph ^= 1; }
            }
          }
          if (newA) aph ^= 1;
        }
        Cursor c{0, 0};
        int pcol = 0;
        PWAIT(bR, 0);
        uint32_t tick = lds32(sTick + 8), seen = 1u << (p.order[tick] >> 4);
        asm volatile("fence.proxy.async.global;" ::: "memory");
#pragma unroll 1
        for (int it = 0;; it++) {
          const uint32_t item = (tick < 256) ? p.order[tick] : (K2_END | min(tick - 256, 255u));
          asm volatile("st.shared.u32 [%0], %1;" ::"r"(sItem + (it & 7) * 4), "r"(item) : "memory");
          if (item >= K2_END) break;
          const int h = item >> 3, j = item & 7;
          const int blk = 2 * j + (int)(rank ^ (it & 1));
          const int col = h * 128 + rank * 64;
          const int nb = 2 * j + 2;
          if (!((seen >> (h >> 1)) & 1)) {
            wait_flag(&g_sync[F_HP + (h >> 1)], RDY_TARGET);
            asm volatile("fence.proxy.async.global;" ::: "memory");
            seen |= 1u << (h >> 1);
          }
          PWAIT(bE + c.s * 8, c.ph);
          mbar_expect(bF + c.s * 8, 32768);
          tma2d(sbase + c.s * 32768, &p.tmC, bF + c.s * 8, h * 128, blk * 128);
          tma2d(sbase + c.s * 32768 + 16384, &p.tmC, bF + c.s * 8, h * 128 + 64, blk * 128);
          c.next();
#pragma unroll 1
          for (int n = nb - 1; n >= 0; n--) {
            if (n == 0 && rank == 0) tick = atomicAdd(&g_sync[F_TICK], 1u);
            PWAIT(bE + c.s * 8, c.ph);
            mbar_expect(bF + c.s * 8, 32768);
            tma2d_mc(sbase + c.s * 32768 + rank * 16384, &p.tmK, bF + c.s * 8, col, n * 128, 3);
            c.next();
            if (n < nb - 1 || it > 0) {
              PWAIT(bE + c.s * 8, c.ph);
              mbar_expect(bF + c.s * 8, 32768);
              tma2d_mc(sbase + c.s * 32768 + rank * 16384, &p.tmV, bF + c.s * 8, (n < nb - 1) ? col : pcol, (n < nb - 1) ? (n + 1) * 128 : 0, 3);
              c.next();
            }
          }
          pcol = col;
          if (rank == 0) {
            asm volatile(
                "{\n.reg .b32 a, b;\nmapa.shared::cluster.u32 a, %0, 1;\nmapa.shared::cluster.u32 b, %1, 1;\n"
                "st.async.shared::cluster.mbarrier::complete_tx::bytes.u32 [a], %2, [b];\n}" ::"r"(sTick + (it & 1) * 4),
                "r"(bT + (it & 1) * 8), "r"(tick) : "memory");
          } else {
            mbar_expect(bT + (it & 1) * 8, 4);
            PWAIT(bT + (it & 1) * 8, (it >> 1) & 1);
            tick = lds32(sTick + (it & 1) * 4);
          }
        }
        PWAIT(bE + c.s * 8, c.ph);
        mbar_expect(bF + c.s * 8, 32768);
        tma2d_mc(sbase + c.s * 32768 + rank * 16384, &p.tmV, bF + c.s * 8, pcol, 0, 3);
        const uint32_t unit = tick - 256;
        if (unit < 64) {
          const int mblk = (7 - (p.unit[unit][0] >> 1)) * 2 + rank, nhalf = p.unit[unit][0] & 1;
          const uint32_t rot = k3_rot(c.s), nfree = ((0x1Au >> c.s) & 1) ? 2 : 3;
#pragma unroll 1
          for (int i = 0; i < K2_NST - 1; i++) {
            c.next();
            PWAIT(bE + c.s * 8, c.ph);
          }
          uint32_t have = 0;
#pragma unroll 1
          for (uint32_t idx = 0; idx < p.unit[unit][2]; idx++) {
            const int kk = p.unit[unit][3] + idx + ((idx >= p.unit[unit][4]) ? p.unit[unit][5] : 0);
            const uint32_t s = (rot + idx) & 3;
            if (idx >= nfree) PWAIT((idx < 4) ? bH : b3E + s * 8, (idx < 4) ? 0 : (~idx >> 2) & 1);
            mbar_expect(b3F + s * 8, K3_STAGE);
            const uint32_t st = sbase + s * K3_STAGE;
            const int sel = (kk < 9), k = sel ? kk : kk - 9, kr = k * 64 + rank * 32;
            tma3d_mc(st + 16384 + rank * 16384, &p.tmO[sel], b3F + s * 8, 0, kr, nhalf * 4, 3);
            tma2d_mc(st + 49152 + rank * 2048, &p.tmOt[sel], b3F + s * 8, 512 + nhalf * 32, kr, 3);
            if (sel && idx == 0) {
              wait_flag(&g_sync[F_OA + mblk], 8);
              asm volatile("fence.proxy.async.global;" ::: "memory");
            }
            if (!sel && !((have >> (k >> 1)) & 1)) {
#pragma unroll 1
              for (uint32_t spins = 0; spins < (1u << 22); spins++) {
                asm volatile("ld.acquire.gpu.global.u32 %0, [%1];" : "=r"(have) : "l"(&g_sync[F_CTX + mblk]) : "memory");
                if ((have >> (k >> 1)) & 1) break;
                __nanosleep(100);
              }
              asm volatile("fence.proxy.async.global;" ::: "memory");
            }
            tma2d(st, &p.tmC, b3F + s * 8, (sel ? 64 + k : k) * 64, mblk * 128);
          }
        }
      }
    }
    __syncwarp();
    if (warp_g == 8) {
      uint32_t v = 0;
      if (lane == 0) {
        __threadfence();
        v = atomicAdd(&g_sync[F_DONE], 1u);
      }
      if (__shfl_sync(0xffffffffu, v, 0) == 2 * NCLUSTER - 1) {
        reinterpret_cast<uint4*>(g_sync)[lane] = make_uint4(0, 0, 0, 0);
        if (lane == 0) g_sync[F_EPOCH] = lds32(sGate + 64) + 1;
      }
    }
    asm volatile("" ::: "memory");
    if (__shfl_sync(0xffffffffu, warp_g, 0) != 8) {
      if (lr0 < S_LEN) {
#pragma unroll 1
        for (int i = warp_g - 9; i < 16; i += 3) {
          const float g = gate_row(lr0 + i, lane, x, gate_w);
          if (lane == 0) asm volatile("st.shared.f32 [%0], %1;" ::"r"(sGate + i * 4), "f"(g) : "memory");
        }
        bar_arrive(3, 256 + 96);
        if (lane == 0) {
          __threadfence();
          atomicAdd(&g_sync[F_GATE], 1u);
        }
      }
      uint32_t aph = 1;
#pragma unroll 1
      for (int ji = 0; ji < K1_MAXJOBS; ji++) aph ^= (p.jobs[cl][ji] >> 14) & 1;
      if (warp_g == 9 && lane == 0) {
#pragma unroll 1
        for (int ji = 0; ji < K1_MAXJOBS; ji++) {
          const uint32_t job = p.jobs[cl][ji];
          if (!(job & 3)) break;
          PWAIT(bS, ji & 1);
          __threadfence();
          atomicAdd(&g_sync[(((job >> 6) & 3) == 2) ? (F_QKVA + ((job >> 3) & 7) * 2 + rank) : (F_HP + ((job >> 10) & 15))], 1u);
        }
#pragma unroll 1
        for (int it = 0;; it++) {
          PWAIT(bS2, it & 1);
          const uint32_t item = lds32(sItem + (it & 7) * 4), nxt = lds32(sItem + ((it + 1) & 7) * 4);
          __threadfence();
          atomicOr(&g_sync[F_CTX + (item & 7) * 2 + (rank ^ (it & 1))], 1u << (item >> 3));
          if (nxt >= K2_END) break;
        }
      } else if (warp_g == 11) {
        if (lane == 0) {
          prefetch_tmap(&p.tmC); prefetch_tmap(&p.tmK); prefetch_tmap(&p.tmV);
          asm volatile("st.shared.u32 [%0], %1;" ::"r"(sGate + 64), "r"(__ldcg(&g_sync[F_EPOCH])) : "memory");
          wait_flag(&g_sync[F_GATE], GATE_TARGET);
          uint32_t tick;
          if (rank == 0) {
            PWAIT(bLast, 0);
            PWAIT(bAe + FIRST_DRAW * 8, aph);
            tick = atomicAdd(&g_sync[F_TICK], 1u);
            asm volatile("st.shared.u32 [%0], %1;" ::"r"(sTick + 8), "r"(tick) : "memory");
            asm volatile(
                "{\n.reg .b32 a, b;\nmapa.shared::cluster.u32 a, %0, 1;\nmapa.shared::cluster.u32 b, %1, 1;\n"
                "st.async.shared::cluster.mbarrier::complete_tx::bytes.u32 [a], %2, [b];\n}" ::"r"(sTick + 8), "r"(bT0), "r"(tick) : "memory");
          } else {
            mbar_expect(bT0, 4);
            PWAIT(bT0, 0);
            tick = lds32(sTick + 8);
          }
          wait_flag(&g_sync[F_HP + (p.order[tick] >> 4)], RDY_TARGET);
          mbar_arrive(bR);
        }
      } else if (warp_g == 10) {
        if (lr0 < S_LEN && lane == 0) {
          prefetch_tmap(&p.tmL[0]); prefetch_tmap(&p.tmL[1]); prefetch_tmap(&p.tmL[2]);
          wait_flag(&g_sync[F_QKVA + (lr0 >> 7)], K1_FLAG_TARGET);
          wait_flag(&g_sync[F_QKVA + (max(lr0 - 16, 0) >> 7)], K1_FLAG_TARGET);
          asm volatile("fence.proxy.async.global;" ::: "memory");
          PWAIT(bLast, 0);
#pragma unroll 1
          for (int kc = 0; kc < 6; kc++) {
            PWAIT(bAe + kc * 8, aph);
            if (kc == 3) {
              mbar_expect(bL, LV);
              tma4d(sL, &p.tmL[0], bL, lr0 / 2 - 8, 9, 0);
              tma4d(sL + LQ, &p.tmL[1], bL, lr0 / 2, 0, 0);
            }
          }
          mbar_expect(bL2, LQ);
          tma4d(sL + LV, &p.tmL[0], bL2, lr0 / 2 - 8, 18, 0);
        }
        __syncwarp();
        bar_sync(5, 256 + 32);
        if (lr0 < S_LEN && lane == 0) {
          asm volatile("cp.async.bulk.tensor.4d.global.shared::cta.bulk_group [%0, {%2, %3, %2, %2}], [%1];" ::"l"(&p.tmL[2]), "r"(sL + LQ), "r"(0), "r"(lr0 / 2) : "memory");
          asm volatile("cp.async.bulk.commit_group;" ::: "memory");
          asm volatile("cp.async.bulk.wait_group.read 0;" ::: "memory");
        }
        __syncwarp();
        if (lane < 12) mbar_arrive_cluster(bE + (4 + lane % 3) * 8, (lane / 3) & 1);
        if (lr0 < S_LEN && lane == 0) {
          asm volatile("cp.async.bulk.wait_group 0;" ::: "memory");
          asm volatile("fence.proxy.async.global;" ::: "memory");
          __threadfence();
          atomicAdd(&g_sync[F_OA + (lr0 >> 7)], 1u);
        }
      }
    }
    __syncwarp();
    cluster_sync();
  } else {
    reg_alloc<232>();
    const int wg = warp_g >> 2, warp = warp_g & 3, q = lane & 3;
    const bool sig = (lane == 0) && (warp < 2);
    {
      K1State st{0, 0, 0, nullptr, nullptr, 0, 0, 0};
      float acc[128];
      uint32_t pk[64];
      if (wg == 0) { TS(0, 0); TSC(0, 2); }
      uint32_t job = p.jobs[cl][0];
      k1_first(st, job, bAf, bBf);
      {
#pragma unroll 1
        for (int ji = 0; job & 3; ji++) {
          const uint32_t njob = p.jobs[cl][ji + 1];
          k1_tile(acc, pk, st, job, njob, sA, sB, bAf, bAe, bBf, bBe, bS, wg, warp, lane, rank);
          job = njob;
        }
      }
#pragma unroll
      for (int i = 0; i < 4; i++)
        mbar_arrive_cluster_if(bE + i * 8, warp & 1, sig);
      if (lr0 < S_LEN) bar_sync(3, 256 + 96);
      if (st.wsel == 3) {
#pragma unroll
        for (int G = 0; G < 16; G++) scale_q4(pk + G * 4);
      }
      FLUSH();
      if (wg == 0) { TS(0, 1); TSC(0, 3); }
      if (lr0 < S_LEN) {
        const float gate0 = __uint_as_float(lds32(sGate + (lane >> 2) * 8)), gate1 = __uint_as_float(lds32(sGate + (lane >> 2) * 8 + 4));
        local_attn(lr0, warp_g, sL, bL, bL2, lane, gate0, gate1);
      }
      bar_arrive(5, 256 + 32);
    }
    __syncwarp();
    uint32_t item, rot;
    {
      const int mybar = 1 + wg, otherbar = 2 - wg;
      const uint32_t never = blockIdx.y;
      float S[64], O[64];
      uint32_t P[32], Q[32];
      float m0 = 0.f, m1 = 0.f, l0 = 1.f, l1 = 1.f, gf0 = 0.f, gf1 = 0.f;
      uint32_t eoff = 0, prev_single = 0;
      Cursor c{0, 0};
      if (wg == 1) bar_arrive(1, 256);
      if (wg == 0) { TS(1, 0); TSC(1, 2); }
#pragma unroll 1
      for (int it = 0;; it++) {
        TB(0);
        const int hi = (int)(rank ^ (it & 1));
        Cursor cq = c, ck, cv, cs0, cs1;
        rot = k3_rot(c.s);
        c.next();
        ck = c; c.next();
        cs0 = ck; cs1 = ck; cv = ck;
        if (it > 0) { cv = c; c.next(); }
        if (!hi) {
          ck = c; c.next();
          cs1 = c; c.next();
        }
        mbar_wait(bF + cq.s * 8, cq.ph);
        TB(1);
        item = lds32(sItem + (it & 7) * 4);
        {
          const uint32_t qa = sbase + cq.s * 32768 + (wg * 64 + warp * 16 + (lane & 15)) * 128;
#pragma unroll
          for (int t = 0; t < 8; t++)
            ldsm_x4(Q[4 * t], Q[4 * t + 1], Q[4 * t + 2], Q[4 * t + 3], qa + (t >> 2) * 16384 + ((((t & 3) * 2 + (lane >> 4)) ^ (lane & 7)) << 4));
        }
        const uint32_t rdy = mbar_test(bF + ck.s * 8, ck.ph) & mbar_test(bF + cv.s * 8, cv.ph);
        l0 += __shfl_xor_sync(0xffffffffu, l0, 1);
        l1 += __shfl_xor_sync(0xffffffffu, l1, 1);
        l0 += __shfl_xor_sync(0xffffffffu, l0, 2);
        l1 += __shfl_xor_sync(0xffffffffu, l1, 2);
        const bool last = item >= K2_END;
        if (last) {
          cv = cq; ck = cq;
        } else if (!rdy) {
          mbar_wait2(bF + ck.s * 8, ck.ph, bF + cv.s * 8, cv.ph);
        }
        TB(2);
        TURN_SYNC();
        TB(3);
        TRC(last ? 2 : 1);
        if (it > 0) {
          wg_fence();
          ISSUE_PV(cv, prev_single);
          wg_commit();
        } else {
          wg_fence();
          wg_commit();
        }
        wg_fence();
        ISSUE_QK(ck);
        wg_commit();
        if (!(last && wg == 1)) TURN_ARRIVE();
        RELEASE_IF(cq, !last);
        TB(4);
        asm volatile("" : "+f"(gf0), "+f"(gf1), "+f"(l0), "+f"(l1));
        const float f0 = __fdividef(1.f - gf0, l0), f1 = __fdividef(1.f - gf1, l1);
        wg_wait<1>();
        fence_regs(O);
        fence_regs(P);
        TB(5);
        if (it > 0) {
          RELEASE_IF(cv, !last);
          mbar_arrive_cluster_if(bH, warp & 1, sig && last);
          bf16* optr = ptr_add(g_ctx, eoff);
          STORE_O(0); STORE_O(1); STORE_O(2); STORE_O(3);
          __syncwarp();
          mbar_arrive_if(bS2, lane == 0);
        }
        TB(6);
        if (!last) {
          const int row = (2 * (item & 7) + hi) * 128 + wg * 64 + warp * 16 + (lane >> 2);
          eoff = (row * KCAT + (item >> 3) * 128 + q * 8) * 2;
          const float* gp = ptr_add(g_gate, row * 4);
          asm volatile("ld.global.f32 %0, [%1];" : "=f"(gf0) : "l"(gp));
          asm volatile("ld.global.f32 %0, [%1];" : "=f"(gf1) : "l"(gp + 8));
          if (!hi) {
            mbar_wait2(bF + cs0.s * 8, cs0.ph, bF + cs1.s * 8, cs1.ph);
            RELEASE(cs0);
            RELEASE(cs1);
          }
        }
        TB(7);
        wg_wait<0>();
        fence_regs(S);
        TB(8);
        if (last) break;
        RELEASE(ck);
        const int nblk = 2 * (item & 7) + 1 + hi;
        prev_single = (nblk == 1);
        float s0 = 0.f, s1 = 0.f;
        l0 = 0.f; l1 = 0.f;
        m0 = 0.f; m1 = 0.f;
        bool shifted = false;
        {
          const int d = warp * 16 + (lane >> 2) - 2 * q;
          if (wg == 0) {
#pragma unroll
            for (int jj = 0; jj < 8; jj++) MASK(jj, jj);
            EXPB(0); EXPB(1); EXPB(2); EXPB(3);
#pragma unroll
            for (int i = 32; i < 64; i++) S[i] = -INFINITY;
#pragma unroll
            for (int i = 16; i < 32; i++) P[i] = 0;
          } else {
#pragma unroll
            for (int jj = 0; jj < 8; jj++) MASK(jj + 8, jj);
            EXPB(0); EXPB(1); EXPB(2); EXPB(3); EXPB(4); EXPB(5); EXPB(6); EXPB(7);
          }
        }
        float chk = (q == 0 && !(fminf(s0, s1) >= SPEC_LO)) ? INFINITY : s0 + s1;
        fence_regs(P);
        TB(9);
#pragma unroll 1
        for (int n = 1;; n++) {
          if (__any_sync(0xffffffffu, !(chk <= SPEC_HI))) {
            float mx0 = fmaxf(S[0], S[1]), mx1 = fmaxf(S[2], S[3]);
#pragma unroll
            for (int jj = 1; jj < 16; jj++) {
              mx0 = fmaxf(mx0, fmaxf(S[jj * 4 + 0], S[jj * 4 + 1]));
              mx1 = fmaxf(mx1, fmaxf(S[jj * 4 + 2], S[jj * 4 + 3]));
            }
            mx0 = fmaxf(mx0, __shfl_xor_sync(0xffffffffu, mx0, 1));
            mx1 = fmaxf(mx1, __shfl_xor_sync(0xffffffffu, mx1, 1));
            mx0 = fmaxf(mx0, __shfl_xor_sync(0xffffffffu, mx0, 2));
            mx1 = fmaxf(mx1, __shfl_xor_sync(0xffffffffu, mx1, 2));
            const float lo = (n == 1) ? -INFINITY : 0.f;
            mx0 = fmaxf(mx0, lo);
            mx1 = fmaxf(mx1, lo);
            m0 += mx0; m1 += mx1;
            shifted = true;
            const float sc0 = ex2(-fmaxf(mx0, 0.f)), sc1 = ex2(-fmaxf(mx1, 0.f));
            l0 *= sc0; l1 *= sc1;
            s0 = 0.f; s1 = 0.f;
#pragma unroll
            for (int jj = 0; jj < 16; jj++) {
              const float e0 = ex2(S[jj * 4 + 0] - mx0), e1 = ex2(S[jj * 4 + 1] - mx0), e2 = ex2(S[jj * 4 + 2] - mx1), e3 = ex2(S[jj * 4 + 3] - mx1);
              s0 += e0 + e1;
              s1 += e2 + e3;
              P[jj * 2 + 0] = pack_bf16(e0, e1);
              P[jj * 2 + 1] = pack_bf16(e2, e3);
              O[jj * 4 + 0] *= sc0;
              O[jj * 4 + 1] *= sc0;
              O[jj * 4 + 2] *= sc1;
              O[jj * 4 + 3] *= sc1;
            }
          }
          l0 += s0;
          l1 += s1;
          if (n >= nblk) break;
          ck = c; c.next();
          cv = c; c.next();
          mbar_wait(bF + ck.s * 8, ck.ph);
          mbar_wait(bF + cv.s * 8, cv.ph);
          TURN_SYNC();
          TRC(0);
          wg_fence();
          ISSUE_QK(ck);
          wg_commit();
          {
            const uint64_t dv = make_desc(sbase + cv.s * 32768, 16384, 1024, 1);
#pragma unroll
            for (int t = 0; t < 8; t++) {
              wgmma_rs_n128<1, 0>(O, P[4 * t], P[4 * t + 1], P[4 * t + 2], P[4 * t + 3], dv + (uint64_t)(t * 128), (t > 0) ? 1 : (n != 1));
              if ((PVM >> t) & 1) wg_commit();
            }
          }
          TURN_ARRIVE();
          s0 = 0.f; s1 = 0.f;
          wg_wait<__builtin_popcount(PVM)>();
          fence_regs(S);
          RELEASE(ck);
          if (shifted) {
#pragma unroll
            for (int i = 0; i < 64; i++) S[i] -= (i & 2) ? m1 : m0;
          }
          wg_wait<__builtin_popcount(PVM) - 1>();
          EXPC(0); EXPC(1); EXPC(2); EXPC(3); EXPC(4); EXPC(5); EXPC(6); EXPC(7);
          chk = s0 + s1;
        }
      }
      TRC(3);
      if (wg == 1) { TS(1, 1); TSC(1, 3); }
    }
    __syncwarp();
    const uint32_t unit = item & 255;
    if (unit < 64) {
      const int mblk = (7 - (p.unit[unit][0] >> 1)) * 2 + rank, nhalf = p.unit[unit][0] & 1, ks = p.unit[unit][1];
      const int k0 = 0, k1 = p.unit[unit][2];
      float acc[144];
      uint32_t s = rot, ph = 0, prev = 0;
      if (wg == 0) { TS(2, 0); TSC(2, 2); }
      uint32_t fa[16], fb[16];
      const uint32_t aoff = (wg * 64 + warp * 16 + (lane & 15)) * 128 + (((lane >> 4) ^ (lane & 7)) << 4);
#define C_LOAD(F)                                                                                              \
  do {                                                                                                         \
    mbar_wait(b3F + s * 8, ph);                                                                                \
    _Pragma("unroll") for (int t = 0; t < 4; t++)                                                              \
        ldsm_x4(F[4 * t], F[4 * t + 1], F[4 * t + 2], F[4 * t + 3], sbase + s * K3_STAGE + (aoff ^ (t * 32))); \
  } while (0)
#define C_STEP(F, G)                                                                                           \
  {                                                                                                            \
    const uint32_t st = sbase + s * K3_STAGE;                                                                  \
    const uint64_t db = make_desc(st + 16384, 4096, 1024, 1), dt = make_desc(st + 49152, 16, 512, 2);          \
    wg_fence();                                                                                                \
    _Pragma("unroll") for (int t = 0; t < 4; t++) {                                                            \
      const int sd = (t > 0) || (k > k0);                                                                      \
      wgmma_rs_n256<1, 0>(acc, F[4 * t], F[4 * t + 1], F[4 * t + 2], F[4 * t + 3], db + (uint64_t)((t >> 1) * 1024 + (t & 1) * 128), sd); \
      wgmma_rs_n32<1, 128>(acc, F[4 * t], F[4 * t + 1], F[4 * t + 2], F[4 * t + 3], dt + (uint64_t)(t * 64), sd); \
    }                                                                                                          \
    wg_commit();                                                                                               \
    wg_wait<1>();                                                                                              \
    fence_regs(G);                                                                                             \
    mbar_arrive_cluster_if(b3E + prev * 8, warp & 1, sig && k > k0);                                           \
    prev = s;                                                                                                  \
    s = (s + 1) & 3;                                                                                           \
    if (s == rot) ph ^= 1;                                                                                     \
    if (++k == k1) break;                                                                                      \
    C_LOAD(G);                                                                                                 \
  }
      C_LOAD(fa);
#pragma unroll
      for (int i = 0; i < 16; i++) fb[i] = 0;
#pragma unroll 1
      for (int k = k0;;) {
        C_STEP(fa, fb)
        C_STEP(fb, fa)
      }
      wg_wait<0>();
      fence_regs(acc);
      cluster_arrive();
      if (wg == 0) TS(2, 4);
      const int tile = mblk * 2 + nhalf;
      uint4* wp = g_part + (size_t)((tile * 4 + ks) * 4) * 5 * 256 + tid;
      const uint32_t sown = sbase + wg * 8192 + (tid & 127) * 16;
#pragma unroll
      for (int d = 0; d < 4; d++) {
        if (d != ks) {
#pragma unroll
          for (int i = 0; i < 4; i++)
            __stcg(wp + (d * 5 + i) * 256,
                   make_uint4(pack_bf16(acc[d * 32 + i * 8], acc[d * 32 + i * 8 + 1]), pack_bf16(acc[d * 32 + i * 8 + 2], acc[d * 32 + i * 8 + 3]),
                              pack_bf16(acc[d * 32 + i * 8 + 4], acc[d * 32 + i * 8 + 5]), pack_bf16(acc[d * 32 + i * 8 + 6], acc[d * 32 + i * 8 + 7])));
          __stcg(reinterpret_cast<uint2*>(wp - tid + (d * 5 + 4) * 256) + tid,
                 make_uint2(pack_bf16(acc[128 + d * 4], acc[128 + d * 4 + 1]), pack_bf16(acc[128 + d * 4 + 2], acc[128 + d * 4 + 3])));
        } else {
#pragma unroll
          for (int i = 0; i < 9; i++) {
            const int o = (i < 8) ? d * 32 + i * 4 : 128 + d * 4;
            asm volatile("st.shared.v4.f32 [%0], {%1, %2, %3, %4};" ::"r"(sown + (i >> 2) * K3_STAGE + (i & 3) * 2048), "f"(acc[o]), "f"(acc[o + 1]), "f"(acc[o + 2]), "f"(acc[o + 3]) : "memory");
          }
        }
      }
      __threadfence();
      __syncwarp();
      if (wg == 0) TS(2, 5);
      if (lane == 0) {
        unsigned int* cnt = &g_sync[F_XCH + tile * 8 + warp_g];
        const uint32_t xtarget = lds32(sGate + 64) * 4 + 4;
        atomicAdd(cnt, 1u);
        uint32_t v, spins = 0;
        do {
          asm volatile("ld.acquire.gpu.global.u32 %0, [%1];" : "=r"(v) : "l"(cnt) : "memory");
        } while ((int)(v - xtarget) < 0 && ++spins < (1u << 24));
      }
      __syncwarp();
      if (wg == 0) TS(2, 6);
      float r[36];
#pragma unroll
      for (int i = 0; i < 9; i++)
        asm volatile("ld.shared.v4.f32 {%0, %1, %2, %3}, [%4];" : "=f"(r[i * 4]), "=f"(r[i * 4 + 1]), "=f"(r[i * 4 + 2]), "=f"(r[i * 4 + 3])
                     : "r"(sown + (i >> 2) * K3_STAGE + (i & 3) * 2048) : "memory");
#pragma unroll
      for (int sI = 1; sI < 4; sI++) {
        const int src = (ks + sI) & 3;
        const uint4* rp = g_part + (size_t)(((tile * 4 + src) * 4) + ks) * 5 * 256;
#pragma unroll
        for (int i = 0; i < 4; i++) {
          const uint4 v = __ldcg(rp + i * 256 + tid);
          r[i * 8] += bf_lo(v.x); r[i * 8 + 1] += bf_hi(v.x); r[i * 8 + 2] += bf_lo(v.y); r[i * 8 + 3] += bf_hi(v.y);
          r[i * 8 + 4] += bf_lo(v.z); r[i * 8 + 5] += bf_hi(v.z); r[i * 8 + 6] += bf_lo(v.w); r[i * 8 + 7] += bf_hi(v.w);
        }
        const uint2 v = __ldcg(reinterpret_cast<const uint2*>(rp + 4 * 256) + tid);
        r[32] += bf_lo(v.x); r[33] += bf_hi(v.x); r[34] += bf_lo(v.y); r[35] += bf_hi(v.y);
      }
      const int row = mblk * 128 + wg * 64 + warp * 16 + (lane >> 2);
      bf16* o0 = out + (size_t)row * DM + nhalf * 256 + ks * 64 + 8 * q;
#pragma unroll
      for (int G = 0; G < 2; G++) {
        uint32_t a0 = pack_bf16(r[G * 16], r[G * 16 + 1]), a1 = pack_bf16(r[G * 16 + 4], r[G * 16 + 5]);
        uint32_t a2 = pack_bf16(r[G * 16 + 8], r[G * 16 + 9]), a3 = pack_bf16(r[G * 16 + 12], r[G * 16 + 13]);
        uint32_t b0 = pack_bf16(r[G * 16 + 2], r[G * 16 + 3]), b1 = pack_bf16(r[G * 16 + 6], r[G * 16 + 7]);
        uint32_t b2 = pack_bf16(r[G * 16 + 10], r[G * 16 + 11]), b3 = pack_bf16(r[G * 16 + 14], r[G * 16 + 15]);
        quad_transpose(a0, a1, a2, a3, q);
        quad_transpose(b0, b1, b2, b3, q);
        st_v4(o0 + G * 32, a0, a1, a2, a3);
        st_v4(o0 + 8 * DM + G * 32, b0, b1, b2, b3);
      }
      {
        uint32_t t0 = pack_bf16(r[32], r[33]), t1 = pack_bf16(r[34], r[35]), t2 = 0, t3 = 0;
        quad_transpose(t0, t1, t2, t3, q);
        if (q < 2) st_v4(out + (size_t)(row + q * 8) * DM + 512 + nhalf * 32 + ks * 8, t0, t1, t2, t3);
      }
    } else {
      cluster_arrive();
    }
    if (wg == 0) { TS(2, 1); TSC(2, 3); }
    cluster_wait();
  }
}

typedef CUresult (*EncFn)(CUtensorMap*, CUtensorMapDataType, cuuint32_t, void*, const cuuint64_t*, const cuuint64_t*, const cuuint32_t*,
                          const cuuint32_t*, CUtensorMapInterleave, CUtensorMapSwizzle, CUtensorMapL2promotion, CUtensorMapFloatOOBfill);

static void enc2d(EncFn enc, CUtensorMap* m, const void* ptr, uint64_t cols, uint64_t rows, uint32_t bc, uint32_t br,
                  CUtensorMapSwizzle sw = CU_TENSOR_MAP_SWIZZLE_128B) {
  cuuint64_t gd[2] = {cols, rows}, gs[1] = {cols * 2};
  cuuint32_t bx[2] = {bc, br}, es[2] = {1, 1};
  enc(m, CU_TENSOR_MAP_DATA_TYPE_BFLOAT16, 2, const_cast<void*>(ptr), gd, gs, bx, es, CU_TENSOR_MAP_INTERLEAVE_NONE, sw,
      CU_TENSOR_MAP_L2_PROMOTION_L2_256B, CU_TENSOR_MAP_FLOAT_OOB_FILL_NONE);
}
static void enc3d(EncFn enc, CUtensorMap* m, const void* ptr, uint64_t cols, uint64_t rows, uint32_t br, uint32_t bch) {
  cuuint64_t gd[3] = {64, rows, cols / 64}, gs[2] = {cols * 2, 128};
  cuuint32_t bx[3] = {64, br, bch}, es[3] = {1, 1, 1};
  enc(m, CU_TENSOR_MAP_DATA_TYPE_BFLOAT16, 3, const_cast<void*>(ptr), gd, gs, bx, es, CU_TENSOR_MAP_INTERLEAVE_NONE,
      CU_TENSOR_MAP_SWIZZLE_128B, CU_TENSOR_MAP_L2_PROMOTION_L2_256B, CU_TENSOR_MAP_FLOAT_OOB_FILL_NONE);
}

static int g_sched[10] = {11, 10, 7, 4, 4, 4, 6, 7, 6, 24};
static void build_k1_jobs(Params& p) {
  int cnt[NCLUSTER];
  for (int c = 0; c < NCLUSTER; c++) {
    cnt[c] = 0;
    for (int i = 0; i <= K1_MAXJOBS; i++) p.jobs[c][i] = 0;
  }
  auto add = [&](int c, int nch, int a_sel, int mp, int w_sel, int chunk0) {
    p.jobs[c][cnt[c]++] = (uint16_t)((nch - 1) | (a_sel << 2) | (mp << 3) | (w_sel << 6) | (chunk0 << 8));
  };
  const int *cg = g_sched, *xg = g_sched + 4;
  for (int mp = 0; mp < 8; mp++) {
    int k = 0;
    for (int i = 0; i < K1_MAXJOBS; i++)
      for (int g = 0; g < 4; g++)
        if (i < cg[g]) { add(g * 8 + mp, 4, 0, mp, k & 1, (k >> 1) * 4); k++; }
    k = 0;
    for (int i = 0; i < K1_MAXJOBS; i++)
      for (int g = 0; g < 4; g++)
        if (i < xg[g]) {
          if (k < 7) add((4 + g) * 8 + mp, k == 0 ? 3 : 4, 1, mp, 2, k == 0 ? 24 : (k - 1) * 4);
          else add((4 + g) * 8 + mp, 4, 1, mp, 3, (k - 7) * 4);
          k++;
        }
    add(64 + mp / 4, 4, 1, mp, 3, 14 * 4);
    add(64 + mp / 4, 4, 1, mp, 3, 15 * 4);
  }
  for (int cc = 0; cc < NCLUSTER; cc++)
    for (int i = 0; i < cnt[cc]; i++) {
      const int key = p.jobs[cc][i] & 0x3C;
      if (i == 0 || (p.jobs[cc][i - 1] & 0x3C) != key) p.jobs[cc][i] |= (1 << 14);
      if (i == cnt[cc] - 1 || (p.jobs[cc][i + 1] & 0x3C) != key) p.jobs[cc][i] |= (1 << 15);
    }
}

static void build_k2_items(Params& p) {
  int n = 0;
  const int SCHED_N1 = g_sched[8], SCHED_N2 = g_sched[9];
  int N0 = 2, J0 = 2;
  for (int j = 7; j >= J0; j--)
    for (int h = 0; h < N0; h++) p.order[n++] = (uint8_t)(h * 8 + j);
  for (int j = 7; j >= 0; j--)
    for (int h = 0; h < SCHED_N1; h++)
      if (!(h < N0 && j >= J0)) p.order[n++] = (uint8_t)(h * 8 + j);
  for (int j = 7; j >= 4; j--)
    for (int h = SCHED_N1; h < SCHED_N2; h++) p.order[n++] = (uint8_t)(h * 8 + j);
  for (int j = 7; j >= 0; j--)
    for (int h = SCHED_N1; h < 32; h++)
      if (!(h < SCHED_N2 && j >= 4)) p.order[n++] = (uint8_t)(h * 8 + j);
}

static void build_k3_units(Params& p) {
  float slope = 0.045f;
  int NE = 25;
  for (int t = 0; t < 16; t++) {
    const int u[4] = {t, 31 - t, 32 + t, 63 - t};
    float acc = 0.f;
    int k0 = 0, l0 = NE;
    for (int i = 0; i < 4; i++) {
      acc += 18.25f + slope * (31.5f - u[i]);
      const int k1 = (i == 3) ? 73 : (int)(acc + 0.5f);
      const int e0 = NE * i / 4, e1 = NE * (i + 1) / 4;
      uint8_t* w = p.unit[u[i]];
      w[0] = (uint8_t)t; w[1] = (uint8_t)i; w[2] = (uint8_t)(k1 - k0); w[3] = (uint8_t)e0; w[4] = (uint8_t)(e1 - e0); w[5] = (uint8_t)(l0 - e1);
      l0 += (k1 - k0) - (e1 - e0);
      k0 = k1;
    }
  }
}

extern "C" void kernel_launch(void* const* d_in, const int* in_sizes, int n_in, void* d_out, int out_size) {
  const bf16* x = (const bf16*)d_in[0];
  const bf16* wqkv = (const bf16*)d_in[1];
  const bf16* wo = (const bf16*)d_in[2];
  const bf16* ckv = (const bf16*)d_in[4];
  const bf16* w_q = (const bf16*)d_in[5];
  const bf16* w_uk = (const bf16*)d_in[6];
  const bf16* w_uv = (const bf16*)d_in[7];
  const bf16* w_o = (const bf16*)d_in[8];
  const bf16* gate_w = (const bf16*)d_in[9];

  EncFn enc = nullptr;
  cudaDriverEntryPointQueryResult qr;
  cudaGetDriverEntryPoint("cuTensorMapEncodeTiled", (void**)&enc, cudaEnableDefault, &qr);
  void *pK, *pV, *pCtx, *pQA;
  cudaGetSymbolAddress(&pQA, g_QKVA);
  cudaGetSymbolAddress(&pK, g_K);
  cudaGetSymbolAddress(&pV, g_V);
  cudaGetSymbolAddress(&pCtx, g_ctx);

  static Params p;
  enc2d(enc, &p.tmA[0], ckv, DC, S_LEN, 64, 128);
  enc2d(enc, &p.tmA[1], x, DM, S_LEN, 64, 128);
  enc3d(enc, &p.tmW[0], w_uk, HDIM, DC, 16, 4);
  enc3d(enc, &p.tmW[1], w_uv, HDIM, DC, 16, 4);
  enc3d(enc, &p.tmW[2], wqkv, NQKVA, DM, 16, 4);
  enc3d(enc, &p.tmW[3], w_q, HDIM, DM, 16, 4);
  build_k1_jobs(p);
  enc2d(enc, &p.tmK, pK, HDIM, S_LEN, 64, 128);
  enc2d(enc, &p.tmV, pV, HDIM, S_LEN, 64, 128);
  build_k2_items(p);
  build_k3_units(p);
  for (int i = 0; i < 3; i++) {
    const cuuint64_t ld = (i < 2 ? NQKVA : KCAT) * 2, nch = (i < 2) ? 27 : 9;
    cuuint64_t gd[4] = {64, S_LEN / 2, i ? 2 : nch, i ? nch : 2}, gs[3] = {2 * ld, i ? ld : 128, i ? 128 : ld};
    cuuint32_t bx[4] = {64, i ? 8u : 16u, i ? 2u : 9u, i ? 9u : 2u}, es[4] = {1, 1, 1, 1};
    enc(&p.tmL[i], CU_TENSOR_MAP_DATA_TYPE_BFLOAT16, 4, (i < 2) ? pQA : (void*)((bf16*)pCtx + HDIM), gd, gs, bx, es, CU_TENSOR_MAP_INTERLEAVE_NONE,
        CU_TENSOR_MAP_SWIZZLE_128B, CU_TENSOR_MAP_L2_PROMOTION_L2_256B, CU_TENSOR_MAP_FLOAT_OOB_FILL_NONE);
  }
  enc2d(enc, &p.tmC, pCtx, KCAT, S_LEN, 64, 128);
  enc3d(enc, &p.tmO[0], w_o, DM, HDIM, 32, 4);
  enc3d(enc, &p.tmO[1], wo, DM, DM, 32, 4);
  enc2d(enc, &p.tmOt[0], w_o, DM, HDIM, 32, 32, CU_TENSOR_MAP_SWIZZLE_64B);
  enc2d(enc, &p.tmOt[1], wo, DM, DM, 32, 32, CU_TENSOR_MAP_SWIZZLE_64B);

  cudaFuncSetAttribute(fused_kernel, cudaFuncAttributeMaxDynamicSharedMemorySize, SMEM_BYTES);
  fused_kernel<<<NCLUSTER * 2, 384, SMEM_BYTES>>>(p, x, gate_w, (bf16*)d_out);
}
```

```cpp
#include <cuda_runtime.h>
#include <cuda_bf16.h>
#include <cuda.h>
#include <stdint.h>

typedef __nv_bfloat16 bf16;

constexpr int S_LEN = 2048, DM = 576, DC = 512, HDIM = 4096, NQKVA = 1728, KCAT = 4672;
constexpr int NCLUSTER = 66;

__device__ __align__(1024) bf16 g_K[S_LEN * HDIM];
__device__ __align__(1024) bf16 g_V[S_LEN * HDIM];
__device__ __align__(1024) bf16 g_QKVA[S_LEN * NQKVA + 64];
__device__ __align__(1024) bf16 g_ctx[S_LEN * KCAT];
__device__ float g_gate[S_LEN];
__device__ __align__(1024) uint4 g_part[32 * 4 * 4 * 5 * 256];
__device__ __align__(16) unsigned int g_sync[400];
constexpr int F_QKVA = 0, F_HP = 16, F_CTX = 32, F_OA = 48, F_GATE = 96, F_TICK = 97, F_DONE = 98, F_XCH = 128, F_EPOCH = 384;

__device__ __forceinline__ uint32_t smem_u32(const void* p) { return (uint32_t)__cvta_generic_to_shared(p); }
__device__ __forceinline__ void mbar_init(uint32_t a, uint32_t c) {
  asm volatile("mbarrier.init.shared::cta.b64 [%0], %1;" ::"r"(a), "r"(c));
}
__device__ __forceinline__ void mbar_expect(uint32_t a, uint32_t b) {
  asm volatile("mbarrier.arrive.expect_tx.shared::cta.b64 _, [%0], %1;" ::"r"(a), "r"(b) : "memory");
}
#define TS(k, i)
#define TSC(k, i)
#define TSM(k)
#define BSEG(i)
#define TB(k)
#define TRC(fl)
#define SPIN_LIMIT "4194304"
__device__ __forceinline__ void mbar_wait(uint32_t a, uint32_t parity) {
  asm volatile(
      "{\n.reg .pred p;\n.reg .u32 n;\n"
      "mbarrier.try_wait.parity.shared::cta.b64 p, [%0], %1;\n"
      "@p bra DONE;\n"
      "mov.u32 n, 0;\n"
      "LOOP:\n"
      "mbarrier.try_wait.parity.shared::cta.b64 p, [%0], %1;\n"
      "@p bra DONE;\n"
      "add.u32 n, n, 1;\n"
      "setp.lt.u32 p, n, " SPIN_LIMIT ";\n"
      "@p bra LOOP;\n"
      "DONE:\n}" ::"r"(a), "r"(parity) : "memory");
}
template <int NS>
__device__ __forceinline__ void mbar_wait_ns(uint32_t a, uint32_t parity) {
  asm volatile(
      "{\n.reg .pred p;\n.reg .u32 n;\n"
      "mov.u32 n, 0;\n"
      "LOOP:\n"
      "mbarrier.try_wait.parity.shared::cta.b64 p, [%0], %1, %2;\n"
      "@p bra DONE;\n"
      "add.u32 n, n, 1;\n"
      "setp.lt.u32 p, n, " SPIN_LIMIT ";\n"
      "@p bra LOOP;\n"
      "DONE:\n}" ::"r"(a), "r"(parity), "n"(NS) : "memory");
}
__device__ __forceinline__ void mbar_wait2(uint32_t a, uint32_t pa, uint32_t b, uint32_t pb) {
  asm volatile(
      "{\n.reg .pred p, q;\n.reg .u32 n;\n"
      "mov.u32 n, 0;\n"
      "LOOP:\n"
      "mbarrier.try_wait.parity.shared::cta.b64 p, [%0], %1;\n"
      "mbarrier.try_wait.parity.shared::cta.b64 q, [%2], %3;\n"
      "add.u32 n, n, 1;\n"
      "and.pred p, p, q;\n"
      "setp.lt.and.u32 p, n, " SPIN_LIMIT ", !p;\n"
      "@p bra LOOP;\n"
      "}" ::"r"(a), "r"(pa), "r"(b), "r"(pb) : "memory");
}
__device__ __forceinline__ uint32_t mbar_test(uint32_t a, uint32_t parity) {
  uint32_t r;
  asm volatile("{\n.reg .pred p;\nmbarrier.test_wait.parity.shared::cta.b64 p, [%1], %2;\nselp.u32 %0, 1, 0, p;\n}" : "=r"(r) : "r"(a), "r"(parity) : "memory");
  return r;
}
__device__ __forceinline__ void mbar_arrive(uint32_t a) {
  asm volatile("mbarrier.arrive.shared::cta.b64 _, [%0];" ::"r"(a) : "memory");
}
__device__ __forceinline__ void mbar_arrive_cluster(uint32_t a, uint32_t cta) {
  asm volatile("{\n.reg .b32 r;\nmapa.shared::cluster.u32 r, %0, %1;\nmbarrier.arrive.shared::cluster.b64 _, [r];\n}" ::"r"(a),
               "r"(cta) : "memory");
}
__device__ __forceinline__ void mbar_arrive_cluster_if(uint32_t a, uint32_t cta, bool pred) {
  asm volatile("{\n.reg .b32 r;\n.reg .pred p;\nsetp.ne.u32 p, %2, 0;\nmapa.shared::cluster.u32 r, %0, %1;\n@p mbarrier.arrive.shared::cluster.b64 _, [r];\n}" ::"r"(a),
               "r"(cta), "r"((uint32_t)pred) : "memory");
}
__device__ __forceinline__ void anchor(float v, uint32_t pred) {
  asm volatile("{\n.reg .pred p;\nsetp.ne.u32 p, %1, 0;\n@p st.shared.f32 [%1], %0;\n}" ::"f"(v), "r"(pred) : "memory");
}
__device__ __forceinline__ void mbar_arrive_if(uint32_t a, bool pred) {
  asm volatile("{\n.reg .pred p;\nsetp.ne.u32 p, %1, 0;\n@p mbarrier.arrive.shared::cta.b64 _, [%0];\n}" ::"r"(a), "r"((uint32_t)pred) : "memory");
}
__device__ __forceinline__ void tma2d(uint32_t dst, const CUtensorMap* m, uint32_t bar, int c0, int c1) {
  asm volatile("cp.async.bulk.tensor.2d.shared::cluster.global.mbarrier::complete_tx::bytes [%0], [%1, {%3, %4}], [%2];" ::"r"(dst),
               "l"(m), "r"(bar), "r"(c0), "r"(c1) : "memory");
}
__device__ __forceinline__ void tma2d_mc(uint32_t dst, const CUtensorMap* m, uint32_t bar, int c0, int c1, uint16_t mask) {
  asm volatile(
      "cp.async.bulk.tensor.2d.shared::cluster.global.mbarrier::complete_tx::bytes.multicast::cluster [%0], [%1, {%3, %4}], [%2], %5;" ::"r"(dst),
      "l"(m), "r"(bar), "r"(c0), "r"(c1), "h"(mask) : "memory");
}
__device__ __forceinline__ void tma3d_mc(uint32_t dst, const CUtensorMap* m, uint32_t bar, int c0, int c1, int c2, uint16_t mask) {
  asm volatile(
      "cp.async.bulk.tensor.3d.shared::cluster.global.mbarrier::complete_tx::bytes.multicast::cluster [%0], [%1, {%3, %4, %5}], [%2], %6;" ::"r"(dst),
      "l"(m), "r"(bar), "r"(c0), "r"(c1), "r"(c2), "h"(mask) : "memory");
}
__device__ __forceinline__ void tma3d(uint32_t dst, const CUtensorMap* m, uint32_t bar, int c0, int c1, int c2) {
  asm volatile(
      "cp.async.bulk.tensor.3d.shared::cluster.global.mbarrier::complete_tx::bytes [%0], [%1, {%3, %4, %5}], [%2];" ::"r"(dst),
      "l"(m), "r"(bar), "r"(c0), "r"(c1), "r"(c2) : "memory");
}
__device__ __forceinline__ void tma_pf2d(const CUtensorMap* m, int c0, int c1) {
  asm volatile("cp.async.bulk.prefetch.tensor.2d.L2.global [%0, {%1, %2}];" ::"l"(m), "r"(c0), "r"(c1) : "memory");
}
__device__ __forceinline__ void tma_pf3d(const CUtensorMap* m, int c0, int c1, int c2) {
  asm volatile("cp.async.bulk.prefetch.tensor.3d.L2.global [%0, {%1, %2, %3}];" ::"l"(m), "r"(c0), "r"(c1), "r"(c2) : "memory");
}
__device__ __forceinline__ void prefetch_tmap(const CUtensorMap* m) {
  asm volatile("prefetch.tensormap [%0];" ::"l"(m) : "memory");
}
__device__ __forceinline__ void cluster_arrive() { asm volatile("barrier.cluster.arrive.relaxed.aligned;" ::: "memory"); }
__device__ __forceinline__ void cluster_wait() { asm volatile("barrier.cluster.wait.aligned;" ::: "memory"); }
__device__ __forceinline__ void cluster_sync() {
  cluster_arrive();
  cluster_wait();
}
__device__ __forceinline__ uint32_t cluster_rank() {
  uint32_t r;
  asm volatile("mov.u32 %0, %%cluster_ctarank;" : "=r"(r));
  return r;
}
__device__ __forceinline__ bool elect_one() {
  uint32_t p;
  asm volatile("{\n.reg .pred q;\nelect.sync _|q, 0xffffffff;\nselp.u32 %0, 1, 0, q;\n}" : "=r"(p));
  return p;
}
__device__ __forceinline__ void ldsm_x4(uint32_t& r0, uint32_t& r1, uint32_t& r2, uint32_t& r3, uint32_t addr) {
  asm volatile("ldmatrix.sync.aligned.m8n8.x4.shared.b16 {%0, %1, %2, %3}, [%4];" : "=r"(r0), "=r"(r1), "=r"(r2), "=r"(r3) : "r"(addr) : "memory");
}
__device__ __forceinline__ void wg_fence() { asm volatile("wgmma.fence.sync.aligned;" ::: "memory"); }
__device__ __forceinline__ void wg_commit() { asm volatile("wgmma.commit_group.sync.aligned;" ::: "memory"); }
template <int N>
__device__ __forceinline__ void wg_wait() { asm volatile("wgmma.wait_group.sync.aligned %0;" ::"n"(N) : "memory"); }
template <int N>
__device__ __forceinline__ void reg_alloc() { asm volatile("setmaxnreg.inc.sync.aligned.u32 %0;" ::"n"(N)); }
template <int N>
__device__ __forceinline__ void reg_dealloc() { asm volatile("setmaxnreg.dec.sync.aligned.u32 %0;" ::"n"(N)); }
__device__ __forceinline__ void bar_sync(int id, int n) { asm volatile("bar.sync %0, %1;" ::"r"(id), "r"(n) : "memory"); }
__device__ __forceinline__ void bar_arrive(int id, int n) { asm volatile("bar.arrive %0, %1;" ::"r"(id), "r"(n) : "memory"); }
template <int NT>
__device__ __forceinline__ void fence_regs(float (&d)[NT]) {
#pragma unroll
  for (int i = 0; i < NT; i++) asm volatile("" : "+f"(d[i])::"memory");
}
template <int NT>
__device__ __forceinline__ void fence_regs(uint32_t (&d)[NT]) {
#pragma unroll
  for (int i = 0; i < NT; i++) asm volatile("" : "+r"(d[i])::"memory");
}
__device__ __forceinline__ uint64_t make_desc(uint32_t saddr, uint32_t lbo, uint32_t sbo, uint32_t layout) {
  return (uint64_t)((saddr & 0x3FFFF) >> 4) | ((uint64_t)(lbo >> 4) << 16) | ((uint64_t)(sbo >> 4) << 32) | ((uint64_t)layout << 62);
}
__device__ __forceinline__ uint32_t pack_bf16(float lo, float hi) {
  uint32_t r;
  asm("cvt.rn.bf16x2.f32 %0, %1, %2;" : "=r"(r) : "f"(hi), "f"(lo));
  return r;
}
__device__ __forceinline__ float ex2(float x) {
  float r;
  asm("ex2.approx.ftz.f32 %0, %1;" : "=f"(r) : "f"(x));
  return r;
}
__device__ __forceinline__ void st_v4(void* p, uint32_t a, uint32_t b, uint32_t c, uint32_t d) {
#define ST_MOD ".cs"
  asm volatile("st.global" ST_MOD ".v4.b32 [%0], {%1, %2, %3, %4};" ::"l"(p), "r"(a), "r"(b), "r"(c), "r"(d) : "memory");
}
#define STA_MOD ".cs"
__device__ __forceinline__ void st_v4a(void* p, uint32_t a, uint32_t b, uint32_t c, uint32_t d) {
  asm volatile("st.global" STA_MOD ".v4.b32 [%0], {%1, %2, %3, %4};" ::"l"(p), "r"(a), "r"(b), "r"(c), "r"(d) : "memory");
}
template <typename T>
__device__ __forceinline__ T* ptr_add(T* base, uint32_t bytes) {
  uint64_t r;
  asm volatile("{\n.reg .u32 l, h;\nmov.b64 {l, h}, %1;\nadd.cc.u32 l, l, %2;\naddc.u32 h, h, 0;\nmov.b64 %0, {l, h};\n}" : "=l"(r) : "l"(base), "r"(bytes));
  return reinterpret_cast<T*>(r);
}
__device__ __forceinline__ float bf_lo(uint32_t v) { return __uint_as_float(v << 16); }
__device__ __forceinline__ float bf_hi(uint32_t v) { return __uint_as_float(v & 0xFFFF0000u); }

__device__ __forceinline__ void quad_transpose(uint32_t& a0, uint32_t& a1, uint32_t& a2, uint32_t& a3, int q) {
  const bool o1 = q & 1, o2 = q & 2;
  uint32_t t0 = o1 ? a0 : a1, t1 = o1 ? a2 : a3;
  t0 = __shfl_xor_sync(0xffffffffu, t0, 1);
  t1 = __shfl_xor_sync(0xffffffffu, t1, 1);
  if (o1) { a0 = t0; a2 = t1; } else { a1 = t0; a3 = t1; }
  t0 = o2 ? a0 : a2;
  t1 = o2 ? a1 : a3;
  t0 = __shfl_xor_sync(0xffffffffu, t0, 2);
  t1 = __shfl_xor_sync(0xffffffffu, t1, 2);
  if (o2) { a0 = t0; a1 = t1; } else { a2 = t0; a3 = t1; }
}

template<int TB, int OFF, int NT>
__device__ __forceinline__ void wgmma_ss_n256(float (&d)[NT], uint64_t da, uint64_t db, int scale_d) {
  asm volatile("{\n.reg .pred p;\nsetp.ne.b32 p, %130, 0;\n"
    "wgmma.mma_async.sync.aligned.m64n256k16.f32.bf16.bf16 {%0, %1, %2, %3, %4, %5, %6, %7, %8, %9, %10, %11, %12, %13, %14, %15, %16, %17, %18, %19, %20, %21, %22, %23, %24, %25, %26, %27, %28, %29, %30, %31, %32, %33, %34, %35, %36, %37, %38, %39, %40, %41, %42, %43, %44, %45, %46, %47, %48, %49, %50, %51, %52, %53, %54, %55, %56, %57, %58, %59, %60, %61, %62, %63, %64, %65, %66, %67, %68, %69, %70, %71, %72, %73, %74, %75, %76, %77, %78, %79, %80, %81, %82, %83, %84, %85, %86, %87, %88, %89, %90, %91, %92, %93, %94, %95, %96, %97, %98, %99, %100, %101, %102, %103, %104, %105, %106, %107, %108, %109, %110, %111, %112, %113, %114, %115, %116, %117, %118, %119, %120, %121, %122, %123, %124, %125, %126, %127}, %128, %129, p, 1, 1, 0, %131;\n}\n"
    : "+f"(d[OFF+0]), "+f"(d[OFF+1]), "+f"(d[OFF+2]), "+f"(d[OFF+3]), "+f"(d[OFF+4]), "+f"(d[OFF+5]), "+f"(d[OFF+6]), "+f"(d[OFF+7]), "+f"(d[OFF+8]), "+f"(d[OFF+9]), "+f"(d[OFF+10]), "+f"(d[OFF+11]), "+f"(d[OFF+12]), "+f"(d[OFF+13]), "+f"(d[OFF+14]), "+f"(d[OFF+15]), "+f"(d[OFF+16]), "+f"(d[OFF+17]), "+f"(d[OFF+18]), "+f"(d[OFF+19]), "+f"(d[OFF+20]), "+f"(d[OFF+21]), "+f"(d[OFF+22]), "+f"(d[OFF+23]), "+f"(d[OFF+24]), "+f"(d[OFF+25]), "+f"(d[OFF+26]), "+f"(d[OFF+27]), "+f"(d[OFF+28]), "+f"(d[OFF+29]), "+f"(d[OFF+30]), "+f"(d[OFF+31]), "+f"(d[OFF+32]), "+f"(d[OFF+33]), "+f"(d[OFF+34]), "+f"(d[OFF+35]), "+f"(d[OFF+36]), "+f"(d[OFF+37]), "+f"(d[OFF+38]), "+f"(d[OFF+39]), "+f"(d[OFF+40]), "+f"(d[OFF+41]), "+f"(d[OFF+42]), "+f"(d[OFF+43]), "+f"(d[OFF+44]), "+f"(d[OFF+45]), "+f"(d[OFF+46]), "+f"(d[OFF+47]), "+f"(d[OFF+48]), "+f"(d[OFF+49]), "+f"(d[OFF+50]), "+f"(d[OFF+51]), "+f"(d[OFF+52]), "+f"(d[OFF+53]), "+f"(d[OFF+54]), "+f"(d[OFF+55]), "+f"(d[OFF+56]), "+f"(d[OFF+57]), "+f"(d[OFF+58]), "+f"(d[OFF+59]), "+f"(d[OFF+60]), "+f"(d[OFF+61]), "+f"(d[OFF+62]), "+f"(d[OFF+63]), "+f"(d[OFF+64]), "+f"(d[OFF+65]), "+f"(d[OFF+66]), "+f"(d[OFF+67]), "+f"(d[OFF+68]), "+f"(d[OFF+69]), "+f"(d[OFF+70]), "+f"(d[OFF+71]), "+f"(d[OFF+72]), "+f"(d[OFF+73]), "+f"(d[OFF+74]), "+f"(d[OFF+75]), "+f"(d[OFF+76]), "+f"(d[OFF+77]), "+f"(d[OFF+78]), "+f"(d[OFF+79]), "+f"(d[OFF+80]), "+f"(d[OFF+81]), "+f"(d[OFF+82]), "+f"(d[OFF+83]), "+f"(d[OFF+84]), "+f"(d[OFF+85]), "+f"(d[OFF+86]), "+f"(d[OFF+87]), "+f"(d[OFF+88]), "+f"(d[OFF+89]), "+f"(d[OFF+90]), "+f"(d[OFF+91]), "+f"(d[OFF+92]), "+f"(d[OFF+93]), "+f"(d[OFF+94]), "+f"(d[OFF+95]), "+f"(d[OFF+96]), "+f"(d[OFF+97]), "+f"(d[OFF+98]), "+f"(d[OFF+99]), "+f"(d[OFF+100]), "+f"(d[OFF+101]), "+f"(d[OFF+102]), "+f"(d[OFF+103]), "+f"(d[OFF+104]), "+f"(d[OFF+105]), "+f"(d[OFF+106]), "+f"(d[OFF+107]), "+f"(d[OFF+108]), "+f"(d[OFF+109]), "+f"(d[OFF+110]), "+f"(d[OFF+111]), "+f"(d[OFF+112]), "+f"(d[OFF+113]), "+f"(d[OFF+114]), "+f"(d[OFF+115]), "+f"(d[OFF+116]), "+f"(d[OFF+117]), "+f"(d[OFF+118]), "+f"(d[OFF+119]), "+f"(d[OFF+120]), "+f"(d[OFF+121]), "+f"(d[OFF+122]), "+f"(d[OFF+123]), "+f"(d[OFF+124]), "+f"(d[OFF+125]), "+f"(d[OFF+126]), "+f"(d[OFF+127])
    : "l"(da), "l"(db), "r"(scale_d), "n"(TB));
}
template<int TB, int OFF, int NT>
__device__ __forceinline__ void wgmma_ss_n32(float (&d)[NT], uint64_t da, uint64_t db, int scale_d) {
  asm volatile("{\n.reg .pred p;\nsetp.ne.b32 p, %18, 0;\n"
    "wgmma.mma_async.sync.aligned.m64n32k16.f32.bf16.bf16 {%0, %1, %2, %3, %4, %5, %6, %7, %8, %9, %10, %11, %12, %13, %14, %15}, %16, %17, p, 1, 1, 0, %19;\n}\n"
    : "+f"(d[OFF+0]), "+f"(d[OFF+1]), "+f"(d[OFF+2]), "+f"(d[OFF+3]), "+f"(d[OFF+4]), "+f"(d[OFF+5]), "+f"(d[OFF+6]), "+f"(d[OFF+7]), "+f"(d[OFF+8]), "+f"(d[OFF+9]), "+f"(d[OFF+10]), "+f"(d[OFF+11]), "+f"(d[OFF+12]), "+f"(d[OFF+13]), "+f"(d[OFF+14]), "+f"(d[OFF+15])
    : "l"(da), "l"(db), "r"(scale_d), "n"(TB));
}
template<int TB, int OFF, int NT>
__device__ __forceinline__ void wgmma_rs_n128(float (&d)[NT], uint32_t a0, uint32_t a1, uint32_t a2, uint32_t a3, uint64_t db, int scale_d) {
  asm volatile("{\n.reg .pred p;\nsetp.ne.b32 p, %69, 0;\n"
    "wgmma.mma_async.sync.aligned.m64n128k16.f32.bf16.bf16 {%0, %1, %2, %3, %4, %5, %6, %7, %8, %9, %10, %11, %12, %13, %14, %15, %16, %17, %18, %19, %20, %21, %22, %23, %24, %25, %26, %27, %28, %29, %30, %31, %32, %33, %34, %35, %36, %37, %38, %39, %40, %41, %42, %43, %44, %45, %46, %47, %48, %49, %50, %51, %52, %53, %54, %55, %56, %57, %58, %59, %60, %61, %62, %63}, {%64, %65, %66, %67}, %68, p, 1, 1, %70;\n}\n"
    : "+f"(d[OFF+0]), "+f"(d[OFF+1]), "+f"(d[OFF+2]), "+f"(d[OFF+3]), "+f"(d[OFF+4]), "+f"(d[OFF+5]), "+f"(d[OFF+6]), "+f"(d[OFF+7]), "+f"(d[OFF+8]), "+f"(d[OFF+9]), "+f"(d[OFF+10]), "+f"(d[OFF+11]), "+f"(d[OFF+12]), "+f"(d[OFF+13]), "+f"(d[OFF+14]), "+f"(d[OFF+15]), "+f"(d[OFF+16]), "+f"(d[OFF+17]), "+f"(d[OFF+18]), "+f"(d[OFF+19]), "+f"(d[OFF+20]), "+f"(d[OFF+21]), "+f"(d[OFF+22]), "+f"(d[OFF+23]), "+f"(d[OFF+24]), "+f"(d[OFF+25]), "+f"(d[OFF+26]), "+f"(d[OFF+27]), "+f"(d[OFF+28]), "+f"(d[OFF+29]), "+f"(d[OFF+30]), "+f"(d[OFF+31]), "+f"(d[OFF+32]), "+f"(d[OFF+33]), "+f"(d[OFF+34]), "+f"(d[OFF+35]), "+f"(d[OFF+36]), "+f"(d[OFF+37]), "+f"(d[OFF+38]), "+f"(d[OFF+39]), "+f"(d[OFF+40]), "+f"(d[OFF+41]), "+f"(d[OFF+42]), "+f"(d[OFF+43]), "+f"(d[OFF+44]), "+f"(d[OFF+45]), "+f"(d[OFF+46]), "+f"(d[OFF+47]), "+f"(d[OFF+48]), "+f"(d[OFF+49]), "+f"(d[OFF+50]), "+f"(d[OFF+51]), "+f"(d[OFF+52]), "+f"(d[OFF+53]), "+f"(d[OFF+54]), "+f"(d[OFF+55]), "+f"(d[OFF+56]), "+f"(d[OFF+57]), "+f"(d[OFF+58]), "+f"(d[OFF+59]), "+f"(d[OFF+60]), "+f"(d[OFF+61]), "+f"(d[OFF+62]), "+f"(d[OFF+63])
    : "r"(a0), "r"(a1), "r"(a2), "r"(a3), "l"(db), "r"(scale_d), "n"(TB));
}
template<int TB, int OFF, int NT>
__device__ __forceinline__ void wgmma_rs_n256(float (&d)[NT], uint32_t a0, uint32_t a1, uint32_t a2, uint32_t a3, uint64_t db, int scale_d) {
  asm volatile("{\n.reg .pred p;\nsetp.ne.b32 p, %133, 0;\n"
    "wgmma.mma_async.sync.aligned.m64n256k16.f32.bf16.bf16 {%0, %1, %2, %3, %4, %5, %6, %7, %8, %9, %10, %11, %12, %13, %14, %15, %16, %17, %18, %19, %20, %21, %22, %23, %24, %25, %26, %27, %28, %29, %30, %31, %32, %33, %34, %35, %36, %37, %38, %39, %40, %41, %42, %43, %44, %45, %46, %47, %48, %49, %50, %51, %52, %53, %54, %55, %56, %57, %58, %59, %60, %61, %62, %63, %64, %65, %66, %67, %68, %69, %70, %71, %72, %73, %74, %75, %76, %77, %78, %79, %80, %81, %82, %83, %84, %85, %86, %87, %88, %89, %90, %91, %92, %93, %94, %95, %96, %97, %98, %99, %100, %101, %102, %103, %104, %105, %106, %107, %108, %109, %110, %111, %112, %113, %114, %115, %116, %117, %118, %119, %120, %121, %122, %123, %124, %125, %126, %127}, {%128, %129, %130, %131}, %132, p, 1, 1, %134;\n}\n"
    : "+f"(d[OFF+0]), "+f"(d[OFF+1]), "+f"(d[OFF+2]), "+f"(d[OFF+3]), "+f"(d[OFF+4]), "+f"(d[OFF+5]), "+f"(d[OFF+6]), "+f"(d[OFF+7]), "+f"(d[OFF+8]), "+f"(d[OFF+9]), "+f"(d[OFF+10]), "+f"(d[OFF+11]), "+f"(d[OFF+12]), "+f"(d[OFF+13]), "+f"(d[OFF+14]), "+f"(d[OFF+15]), "+f"(d[OFF+16]), "+f"(d[OFF+17]), "+f"(d[OFF+18]), "+f"(d[OFF+19]), "+f"(d[OFF+20]), "+f"(d[OFF+21]), "+f"(d[OFF+22]), "+f"(d[OFF+23]), "+f"(d[OFF+24]), "+f"(d[OFF+25]), "+f"(d[OFF+26]), "+f"(d[OFF+27]), "+f"(d[OFF+28]), "+f"(d[OFF+29]), "+f"(d[OFF+30]), "+f"(d[OFF+31]), "+f"(d[OFF+32]), "+f"(d[OFF+33]), "+f"(d[OFF+34]), "+f"(d[OFF+35]), "+f"(d[OFF+36]), "+f"(d[OFF+37]), "+f"(d[OFF+38]), "+f"(d[OFF+39]), "+f"(d[OFF+40]), "+f"(d[OFF+41]), "+f"(d[OFF+42]), "+f"(d[OFF+43]), "+f"(d[OFF+44]), "+f"(d[OFF+45]), "+f"(d[OFF+46]), "+f"(d[OFF+47]), "+f"(d[OFF+48]), "+f"(d[OFF+49]), "+f"(d[OFF+50]), "+f"(d[OFF+51]), "+f"(d[OFF+52]), "+f"(d[OFF+53]), "+f"(d[OFF+54]), "+f"(d[OFF+55]), "+f"(d[OFF+56]), "+f"(d[OFF+57]), "+f"(d[OFF+58]), "+f"(d[OFF+59]), "+f"(d[OFF+60]), "+f"(d[OFF+61]), "+f"(d[OFF+62]), "+f"(d[OFF+63]), "+f"(d[OFF+64]), "+f"(d[OFF+65]), "+f"(d[OFF+66]), "+f"(d[OFF+67]), "+f"(d[OFF+68]), "+f"(d[OFF+69]), "+f"(d[OFF+70]), "+f"(d[OFF+71]), "+f"(d[OFF+72]), "+f"(d[OFF+73]), "+f"(d[OFF+74]), "+f"(d[OFF+75]), "+f"(d[OFF+76]), "+f"(d[OFF+77]), "+f"(d[OFF+78]), "+f"(d[OFF+79]), "+f"(d[OFF+80]), "+f"(d[OFF+81]), "+f"(d[OFF+82]), "+f"(d[OFF+83]), "+f"(d[OFF+84]), "+f"(d[OFF+85]), "+f"(d[OFF+86]), "+f"(d[OFF+87]), "+f"(d[OFF+88]), "+f"(d[OFF+89]), "+f"(d[OFF+90]), "+f"(d[OFF+91]), "+f"(d[OFF+92]), "+f"(d[OFF+93]), "+f"(d[OFF+94]), "+f"(d[OFF+95]), "+f"(d[OFF+96]), "+f"(d[OFF+97]), "+f"(d[OFF+98]), "+f"(d[OFF+99]), "+f"(d[OFF+100]), "+f"(d[OFF+101]), "+f"(d[OFF+102]), "+f"(d[OFF+103]), "+f"(d[OFF+104]), "+f"(d[OFF+105]), "+f"(d[OFF+106]), "+f"(d[OFF+107]), "+f"(d[OFF+108]), "+f"(d[OFF+109]), "+f"(d[OFF+110]), "+f"(d[OFF+111]), "+f"(d[OFF+112]), "+f"(d[OFF+113]), "+f"(d[OFF+114]), "+f"(d[OFF+115]), "+f"(d[OFF+116]), "+f"(d[OFF+117]), "+f"(d[OFF+118]), "+f"(d[OFF+119]), "+f"(d[OFF+120]), "+f"(d[OFF+121]), "+f"(d[OFF+122]), "+f"(d[OFF+123]), "+f"(d[OFF+124]), "+f"(d[OFF+125]), "+f"(d[OFF+126]), "+f"(d[OFF+127])
    : "r"(a0), "r"(a1), "r"(a2), "r"(a3), "l"(db), "r"(scale_d), "n"(TB));
}
template<int TB, int OFF, int NT>
__device__ __forceinline__ void wgmma_rs_n32(float (&d)[NT], uint32_t a0, uint32_t a1, uint32_t a2, uint32_t a3, uint64_t db, int scale_d) {
  asm volatile("{\n.reg .pred p;\nsetp.ne.b32 p, %21, 0;\n"
    "wgmma.mma_async.sync.aligned.m64n32k16.f32.bf16.bf16 {%0, %1, %2, %3, %4, %5, %6, %7, %8, %9, %10, %11, %12, %13, %14, %15}, {%16, %17, %18, %19}, %20, p, 1, 1, %22;\n}\n"
    : "+f"(d[OFF+0]), "+f"(d[OFF+1]), "+f"(d[OFF+2]), "+f"(d[OFF+3]), "+f"(d[OFF+4]), "+f"(d[OFF+5]), "+f"(d[OFF+6]), "+f"(d[OFF+7]), "+f"(d[OFF+8]), "+f"(d[OFF+9]), "+f"(d[OFF+10]), "+f"(d[OFF+11]), "+f"(d[OFF+12]), "+f"(d[OFF+13]), "+f"(d[OFF+14]), "+f"(d[OFF+15])
    : "r"(a0), "r"(a1), "r"(a2), "r"(a3), "l"(db), "r"(scale_d), "n"(TB));
}

__device__ __forceinline__ void wait_flag(const unsigned int* f, uint32_t target) {
  uint32_t v;
#pragma unroll 1
  for (uint32_t spins = 0; spins < (1u << 22); spins++) {
    asm volatile("ld.acquire.gpu.global.u32 %0, [%1];" : "=r"(v) : "l"(f) : "memory");
    if (v >= target) break;
    __nanosleep(100);
  }
}
__device__ __forceinline__ uint32_t lds32(uint32_t a) {
  uint32_t v;
  asm volatile("ld.shared.u32 %0, [%1];" : "=r"(v) : "r"(a) : "memory");
  return v;
}
__device__ __forceinline__ float gate_row(int row, int lane, const bf16* __restrict__ x, const bf16* __restrict__ gate_w) {
  const uint32_t* xr = reinterpret_cast<const uint32_t*>(x + (size_t)row * DM);
  const uint32_t* gw2 = reinterpret_cast<const uint32_t*>(gate_w);
  float gs = 0.f;
#pragma unroll
  for (int i = 0; i < 9; i++) {
    const uint32_t a = __ldg(xr + lane + 32 * i), b = __ldg(gw2 + lane + 32 * i);
    gs = fmaf(bf_lo(a), bf_lo(b), gs);
    gs = fmaf(bf_hi(a), bf_hi(b), gs);
  }
#pragma unroll
  for (int o = 16; o; o >>= 1) gs += __shfl_xor_sync(0xffffffffu, gs, o);
  const float g = 1.f / (1.f + __expf(-gs));
  if (lane == 0) g_gate[row] = g;
  return g;
}
constexpr uint32_t LQ = 36864, LV = 55296;
__device__ __forceinline__ void mma16(float (&c)[4], uint32_t a0, uint32_t a1, uint32_t a2, uint32_t a3, uint32_t b0, uint32_t b1) {
  asm("mma.sync.aligned.m16n8k16.row.col.f32.bf16.bf16.f32 {%0, %1, %2, %3}, {%4, %5, %6, %7}, {%8, %9}, {%0, %1, %2, %3};"
      : "+f"(c[0]), "+f"(c[1]), "+f"(c[2]), "+f"(c[3]) : "r"(a0), "r"(a1), "r"(a2), "r"(a3), "r"(b0), "r"(b1));
}
__device__ __forceinline__ void mma8(float (&c)[4], uint32_t a0, uint32_t a1, uint32_t b0) {
  asm("mma.sync.aligned.m16n8k8.row.col.f32.bf16.bf16.f32 {%0, %1, %2, %3}, {%4, %5}, {%6}, {%0, %1, %2, %3};"
      : "+f"(c[0]), "+f"(c[1]), "+f"(c[2]), "+f"(c[3]) : "r"(a0), "r"(a1), "r"(b0));
}
__device__ __forceinline__ void local_attn(int lr0, int warp_g, uint32_t sL, uint32_t bL, uint32_t bL2, int lane, float g0, float g1) {
  const float scale_l2 = 0.23570226039551584f * 1.4426950408889634f;
  const int g = lane >> 2, t = lane & 3;
  const bool lo0 = 2 * t > g, lo1 = 2 * t + 1 > g;
  const uint32_t mlo = (lo0 ? 0xFFFFu : 0u) | (lo1 ? 0xFFFF0000u : 0u);
  const bool ok0 = lr0 > 0 || !lo0, ok1 = lr0 > 0 || !lo1;
  uint32_t ad[9], k[9][4], qf[9][2], pe[4], po[4];
#pragma unroll
  for (int c = 0; c < 9; c++) {
    const uint32_t ch = warp_g * 9 + c;
    ad[c] = sL + (lane >> 4) * 18432 + (lane & 15) * 128 + ((ch >> 3) << 11) + (((ch ^ lane) & 7) << 4);
  }
  mbar_wait(bL, 0);
  if (warp_g == 0) TS(1, 6);
#pragma unroll
  for (int c = 0; c < 9; c++) {
    asm volatile("ldmatrix.sync.aligned.m8n8.x2.shared.b16 {%0, %1}, [%2];" : "=r"(qf[c][0]), "=r"(qf[c][1]) : "r"(ad[c] + LQ) : "memory");
    ldsm_x4(k[c][0], k[c][1], k[c][2], k[c][3], ad[c]);
  }
#pragma unroll
  for (int i = 0; i < 4; i++) {
    const uint32_t q0 = (t >= i) ? qf[2 * i][0] : 0u, q1 = (t >= i) ? qf[2 * i][1] : 0u;
    const uint32_t q4 = (t <= i) ? qf[2 * i + 2][0] : 0u, q5 = (t <= i) ? qf[2 * i + 2][1] : 0u;
    float c[4][4];
#pragma unroll
    for (int T = 0; T < 4; T++) {
#pragma unroll
      for (int j = 0; j < 4; j++) c[T][j] = 0.f;
      mma16(c[T], q0, q1, qf[2 * i + 1][0], qf[2 * i + 1][1], k[2 * i][T], k[2 * i + 1][T]);
      mma8(c[T], q4, q5, k[2 * i + 2][T]);
    }
    const float e0 = ok0 ? (lo0 ? c[0][0] : c[1][0]) : -INFINITY, e1 = ok1 ? (lo1 ? c[0][1] : c[1][1]) : -INFINITY;
    const float o0 = ok0 ? (lo0 ? c[2][2] : c[3][2]) : -INFINITY, o1 = ok1 ? (lo1 ? c[2][3] : c[3][3]) : -INFINITY;
    float me = fmaxf(e0, e1), mo = fmaxf(o0, o1);
    me = fmaxf(me, __shfl_xor_sync(0xffffffffu, me, 1));
    mo = fmaxf(mo, __shfl_xor_sync(0xffffffffu, mo, 1));
    me = fmaxf(me, __shfl_xor_sync(0xffffffffu, me, 2)) * scale_l2;
    mo = fmaxf(mo, __shfl_xor_sync(0xffffffffu, mo, 2)) * scale_l2;
    const float w0 = ex2(fmaf(e0, scale_l2, -me)), w1 = ex2(fmaf(e1, scale_l2, -me));
    const float w2 = ex2(fmaf(o0, scale_l2, -mo)), w3 = ex2(fmaf(o1, scale_l2, -mo));
    float se = w0 + w1, so = w2 + w3;
    se += __shfl_xor_sync(0xffffffffu, se, 1);
    so += __shfl_xor_sync(0xffffffffu, so, 1);
    se += __shfl_xor_sync(0xffffffffu, se, 2);
    so += __shfl_xor_sync(0xffffffffu, so, 2);
    asm("rcp.approx.ftz.f32 %0, %0;" : "+f"(se));
    asm("rcp.approx.ftz.f32 %0, %0;" : "+f"(so));
    se *= g0;
    so *= g1;
    pe[i] = pack_bf16(w0 * se, w1 * se);
    po[i] = pack_bf16(w2 * so, w3 * so);
  }
  if (warp_g == 0) TS(0, 4);
  mbar_wait(bL2, 0);
  if (warp_g == 0) TS(0, 5);
#pragma unroll
  for (int c = 0; c < 9; c++)
    asm volatile("ldmatrix.sync.aligned.m8n8.x4.trans.shared.b16 {%0, %1, %2, %3}, [%4];"
                 : "=r"(k[c][0]), "=r"(k[c][1]), "=r"(k[c][2]), "=r"(k[c][3]) : "r"(ad[c] + LV) : "memory");
#pragma unroll
  for (int i = 0; i < 4; i++) {
#pragma unroll
    for (int n = 0; n < 3; n++) {
      float c[4] = {0.f, 0.f, 0.f, 0.f};
      mma16(c, pe[i] & mlo, 0u, pe[i] & ~mlo, 0u, k[2 * i + n][0], k[2 * i + n][1]);
      mma16(c, 0u, po[i] & mlo, 0u, po[i] & ~mlo, k[2 * i + n][2], k[2 * i + n][3]);
      const uint32_t r0 = pack_bf16(c[0], c[1]), r1 = pack_bf16(c[2], c[3]);
      const bool keep = (n == 0) && (t < i);
      qf[2 * i + n][0] = keep ? qf[2 * i + n][0] : r0;
      qf[2 * i + n][1] = keep ? qf[2 * i + n][1] : r1;
    }
  }
#pragma unroll
  for (int c = 0; c < 9; c++)
    asm volatile("stmatrix.sync.aligned.m8n8.x2.shared.b16 [%0], {%1, %2};" ::"r"(ad[c] + LQ), "r"(qf[c][0]), "r"(qf[c][1]) : "memory");
  asm volatile("fence.proxy.async.shared::cta;" ::: "memory");
}
__device__ __forceinline__ void tma4d(uint32_t dst, const CUtensorMap* m, uint32_t bar, int c1, int c2, int c3) {
  asm volatile("cp.async.bulk.tensor.4d.shared::cluster.global.mbarrier::complete_tx::bytes [%0], [%1, {%3, %4, %5, %6}], [%2];" ::"r"(dst),
               "l"(m), "r"(bar), "r"(0), "r"(c1), "r"(c2), "r"(c3) : "memory");
}

#define K1_NST 6
constexpr int K1_BST = K1_NST;
#define MAXJ 11
constexpr int K1_MAXJOBS = MAXJ;
constexpr uint32_t K1_FLAG_TARGET = 7;
constexpr uint32_t RDY_TARGET = 48;
constexpr uint32_t GATE_TARGET = 128 * 3;
struct alignas(64) Params {
  CUtensorMap tmA[2];
  CUtensorMap tmW[4];
  CUtensorMap tmK, tmV;
  CUtensorMap tmL[3];
  CUtensorMap tmC, tmO[2], tmOt[2];
  uint16_t jobs[NCLUSTER][K1_MAXJOBS + 1];
  uint8_t order[256];
  uint8_t unit[64][8];
};

struct K1State {
  uint32_t bs, bph, aph;
  bf16 *pp, *pp8;
  int png;
  int tn;
  int wsel;
};
__device__ __forceinline__ void k1_flag(const K1State& st, int lane, uint32_t bS) {
  if (st.png) {
    __syncwarp();
    if (lane == 0) mbar_arrive(bS);
  }
}

__device__ __forceinline__ void scale_q4(uint32_t* v) {
#pragma unroll
  for (int i = 0; i < 4; i++)
    asm volatile("{\n.reg .b32 t;\nmul.rn.bf16x2 t, %0, %2;\nfma.rn.bf16x2 %0, %0, %1, t;\n}" : "+r"(v[i]) : "r"(0x3E033E03u), "r"(0xB9D8B9D8u));
}
__device__ __forceinline__ void k1_first(const K1State& st, uint32_t job, uint32_t bAf, uint32_t bBf) {
  if (job & 3) {
    if ((job >> 14) & 1) mbar_wait(bAf, st.aph);
    mbar_wait(bBf + st.bs * 8, st.bph);
  }
}
__device__ __forceinline__ void k1_tile(float (&acc)[128], uint32_t (&pk)[64], K1State& st, uint32_t job, uint32_t njob, uint32_t sA, uint32_t sB,
                                        uint32_t bAf, uint32_t bAe, uint32_t bBf, uint32_t bBe, uint32_t bS, int wg, int warp, int lane, uint32_t rank) {
  const int a_sel = (job >> 2) & 1, mpair = (job >> 3) & 7, w_sel = (job >> 6) & 3, chunk0 = (job >> 8) & 63;
  const bool newA = (job >> 14) & 1, lastA = (job >> 15) & 1;
  const bool sig = (lane == 0) && (warp < 2);
  const bool siga = lastA && (lane == 0) && (warp == 2);
  const int KC = 8 + a_sel;
  uint32_t prev_bs = 0, a8_bs = 0;
#pragma unroll
  for (int kc = 0; kc < 9; kc++) {
    if (kc >= KC) break;
    uint32_t abase = sA + ((kc + 2) & 7) * 16384;
    if (kc == 8) {
      mbar_wait(bBf + st.bs * 8, st.bph);
      a8_bs = st.bs;
      abase = sB + st.bs * 16384;
      if (++st.bs == K1_BST) { st.bs = 0; st.bph ^= 1; }
    } else if (newA && kc > 0) {
      mbar_wait(bAf + kc * 8, st.aph);
    }
    const uint64_t da = make_desc(abase + wg * 8192, 16, 1024, 1);
#pragma unroll
    for (int ks = 0; ks < 2; ks++) {
      if (ks > 0 || kc > 0) mbar_wait(bBf + st.bs * 8, st.bph);
      const uint64_t db = make_desc(sB + st.bs * 16384, 2048, 1024, 1);
      wg_fence();
      wgmma_ss_n256<1, 0>(acc, da + (uint64_t)(ks * 4), db, (ks > 0) ? 1 : (kc > 0));
      wgmma_ss_n256<1, 0>(acc, da + (uint64_t)(ks * 4 + 2), db + (uint64_t)512, 1);
      wg_commit();
      const int PO = (kc < 8 ? kc : 0) * 8;
      wg_wait<1>();
      if (ks > 0 || kc > 0) {
        if (sig) mbar_arrive_cluster(bBe + prev_bs * 8, warp);
        if (ks == 0 && siga) mbar_arrive(bAe + (kc - 1) * 8);
      }
      if (kc < 8 && st.wsel >= 2) {
        if (st.wsel == 3) scale_q4(pk + PO + ks * 4);
        else quad_transpose(pk[PO + ks * 4], pk[PO + ks * 4 + 1], pk[PO + ks * 4 + 2], pk[PO + ks * 4 + 3], lane & 3);
      }
      if (kc < st.png) st_v4a((ks ? st.pp8 : st.pp) + kc * 32, pk[PO + ks * 4], pk[PO + ks * 4 + 1], pk[PO + ks * 4 + 2], pk[PO + ks * 4 + 3]);
      prev_bs = st.bs;
      if (++st.bs == K1_BST) { st.bs = 0; st.bph ^= 1; }
    }
  }
  if (newA) st.aph ^= 1;
  k1_flag(st, lane, bS);
  const bool isA = (w_sel == 2);
  bf16* out = (w_sel == 0) ? g_K : (w_sel == 1) ? g_V : isA ? g_QKVA : g_ctx;
  const int ld = isA ? NQKVA : (w_sel == 3) ? KCAT : HDIM;
  const int row = mpair * 256 + rank * 128 + wg * 64 + warp * 16 + (lane >> 2);
  st.pp = ptr_add(out, (row * ld + chunk0 * 64 + (lane & 3) * 8) * 2);
  st.pp8 = ptr_add(st.pp, 16 * ld);
  st.png = ((job & 3) + 1) * 2;
  st.wsel = w_sel;
  k1_first(st, njob, bAf, bBf);
  wg_wait<0>();
  fence_regs(acc);
  mbar_arrive_cluster_if(bBe + prev_bs * 8, warp & 1, sig);
  mbar_arrive_cluster_if(bBe + a8_bs * 8, warp & 1, sig && a_sel);
  mbar_arrive_if(bAe + 7 * 8, siga && !a_sel);
#pragma unroll
  for (int i = 0; i < 64; i++) {
    const int j = (i >> 3) * 16 + (i & 3) * 4 + ((i >> 2) & 1) * 2;
    pk[i] = pack_bf16(acc[j], acc[j + 1]);
  }
}

constexpr int K2_NST = 7;
constexpr uint32_t K2_END = 0x100;
#define PFD 4
#define FIRST_DRAW 3
#define PWAIT mbar_wait_ns<1000>
#define PVM 0x8A
#define W0 63
#define SPEC_HI 1.8446744073709552e19f
#define SPEC_LO 5.421010862427522e-20f
constexpr int K3_NST = 4;
__device__ __forceinline__ uint32_t k3_rot(uint32_t sv) { return (0x00E9u >> (2 * sv)) & 3; }
constexpr int K3_STAGE = 16384 + 32768 + 4096;
constexpr int SMEM_DATA = 7 * 32768;
constexpr int SMEM_BYTES = SMEM_DATA + 1024 + 768;

struct Cursor {
  uint32_t s, ph;
  __device__ __forceinline__ void next() {
    if (++s == K2_NST) { s = 0; ph ^= 1; }
  }
};

#define TURN_SYNC() bar_sync(mybar, 256)
#define TURN_ARRIVE() bar_arrive(otherbar, 256)
#define RELEASE_IF(cur, cond) mbar_arrive_cluster_if(bE + (cur).s * 8, warp & 1, sig && (cond))
#define RELEASE(cur) RELEASE_IF(cur, true)
#define ISSUE_PV(cur, first)                                                                                   \
  do {                                                                                                         \
    const uint64_t dv = make_desc(sbase + (cur).s * 32768, 16384, 1024, 1);                                    \
    _Pragma("unroll") for (int t = 0; t < 8; t++)                                                              \
        wgmma_rs_n128<1, 0>(O, P[4 * t], P[4 * t + 1], P[4 * t + 2], P[4 * t + 3], dv + (uint64_t)(t * 128), (t > 0) ? 1 : !(first)); \
  } while (0)
#define ISSUE_QK(cur)                                                                                          \
  do {                                                                                                         \
    const uint64_t dk = make_desc(sbase + (cur).s * 32768, 16, 1024, 1);                                       \
    _Pragma("unroll") for (int t = 0; t < 8; t++)                                                              \
        wgmma_rs_n128<0, 0>(S, Q[4 * t], Q[4 * t + 1], Q[4 * t + 2], Q[4 * t + 3], dk + (uint64_t)((t >> 2) * 1024 + (t & 3) * 2), t > 0); \
  } while (0)
#define EXPB(T)                                                                                                \
  do {                                                                                                         \
    _Pragma("unroll") for (int i = 4 * T; i < 4 * T + 4; i++) asm volatile("" : "+r"(P[i])::"memory");        \
    _Pragma("unroll") for (int jj = 2 * T; jj < 2 * T + 2; jj++) {                                             \
      const float e0 = ex2(S[jj * 4 + 0]), e1 = ex2(S[jj * 4 + 1]), e2 = ex2(S[jj * 4 + 2]), e3 = ex2(S[jj * 4 + 3]); \
      s0 += e0 + e1;                                                                                           \
      s1 += e2 + e3;                                                                                           \
      P[jj * 2 + 0] = pack_bf16(e0, e1);                                                                       \
      P[jj * 2 + 1] = pack_bf16(e2, e3);                                                                       \
    }                                                                                                          \
  } while (0)
#define EXPC(T)                                                                                                \
  do {                                                                                                         \
    if (T > 0 && ((PVM >> (T - 1)) & 1)) {                                                                     \
      anchor((T & 2) ? s0 : s1, never);                                                                        \
      wg_wait<__builtin_popcount(PVM >> T) - 1>();                                                             \
      if ((PVM >> T) == (128 >> T)) { fence_regs(O); RELEASE(cv); }                                            \
    }                                                                                                          \
    EXPB(T);                                                                                                   \
  } while (0)
#define MASK(G, g)                                                                                             \
  do {                                                                                                         \
    if ((g) * 8 > d) S[(G) * 4 + 0] = -INFINITY;                                                               \
    if ((g) * 8 + 1 > d) S[(G) * 4 + 1] = -INFINITY;                                                           \
    if ((g) * 8 - 8 > d) S[(G) * 4 + 2] = -INFINITY;                                                           \
    if ((g) * 8 - 7 > d) S[(G) * 4 + 3] = -INFINITY;                                                           \
  } while (0)
#define STORE_O(G)                                                                                             \
  do {                                                                                                         \
    st_v4(optr + (G) * 32, pack_bf16(O[(G) * 16 + 0] * f0, O[(G) * 16 + 1] * f0), pack_bf16(O[(G) * 16 + 4] * f0, O[(G) * 16 + 5] * f0), \
          pack_bf16(O[(G) * 16 + 8] * f0, O[(G) * 16 + 9] * f0), pack_bf16(O[(G) * 16 + 12] * f0, O[(G) * 16 + 13] * f0)); \
    st_v4(optr + 8 * KCAT + (G) * 32, pack_bf16(O[(G) * 16 + 2] * f1, O[(G) * 16 + 3] * f1), pack_bf16(O[(G) * 16 + 6] * f1, O[(G) * 16 + 7] * f1), \
          pack_bf16(O[(G) * 16 + 10] * f1, O[(G) * 16 + 11] * f1), pack_bf16(O[(G) * 16 + 14] * f1, O[(G) * 16 + 15] * f1)); \
  } while (0)

#define FLUSH()                                                                                                \
  do {                                                                                                         \
    _Pragma("unroll") for (int G = 0; G < 8; G++) {                                                            \
      st_v4a(st.pp + G * 32, pk[G * 8], pk[G * 8 + 1], pk[G * 8 + 2], pk[G * 8 + 3]);                          \
      st_v4a(st.pp8 + G * 32, pk[G * 8 + 4], pk[G * 8 + 5], pk[G * 8 + 6], pk[G * 8 + 7]);                     \
    }                                                                                                          \
    k1_flag(st, lane, bS);                                                                                     \
  } while (0)

__global__ void __cluster_dims__(2, 1, 1) __launch_bounds__(384, 1)
fused_kernel(const __grid_constant__ Params p, const bf16* __restrict__ x, const bf16* __restrict__ gate_w, bf16* __restrict__ out) {
  extern __shared__ uint8_t smem_raw[];
  const uint32_t sbase = (smem_u32(smem_raw) + 1023) & ~1023u;
  const uint32_t sB = sbase, sA = sbase + K1_BST * 16384, sBar = sbase + SMEM_DATA;
  const uint32_t bAf = sBar, bAe = sBar + 64, bBf = sBar + 128, bBe = sBar + 176, bL = sBar + 224, bS = sBar + 232, bL2 = sBar + 240, sL = sA + 32768;
  const uint32_t bF = sBar + 256, bE = sBar + 320, bT = sBar + 384, sTick = sBar + 400, sItem = sBar + 416, bS2 = sBar + 448, bR = sBar + 456, bLast = sBar + 464, bH = sBar + 472, bT0 = sBar + 480;
  const uint32_t b3F = sBar + 512, b3E = sBar + 544, sGate = sBar + 576;
  const int tid = threadIdx.x, warp_g = __shfl_sync(0xffffffffu, tid >> 5, 0), lane = tid & 31;
  const uint32_t rank = cluster_rank();
  const int cl = blockIdx.x >> 1;
  TSM(0);
  if (tid == 0) {
    for (int i = 0; i < 8; i++) { mbar_init(bAf + i * 8, 1); mbar_init(bAe + i * 8, 2); }
    for (int i = 0; i < K1_BST; i++) { mbar_init(bBf + i * 8, 1); mbar_init(bBe + i * 8, 4); }
    mbar_init(bL, 1);
    mbar_init(bL2, 1);
    mbar_init(bR, 1);
    mbar_init(bLast, 1);
    mbar_init(bH, 4);
    mbar_init(bT0, 1);
    mbar_init(bS, 8);
    for (int i = 0; i < K2_NST; i++) { mbar_init(bF + i * 8, 1); mbar_init(bE + i * 8, 4); }
    mbar_init(bT, 1); mbar_init(bT + 8, 1);
    mbar_init(bS2, 8);
    for (int i = 0; i < K3_NST; i++) { mbar_init(b3F + i * 8, 1); mbar_init(b3E + i * 8, 4); }
    asm volatile("fence.mbarrier_init.release.cluster;" ::: "memory");
  }
  __syncwarp();
  if (warp_g != 8) cluster_sync();
  const int lr0 = blockIdx.x * 16;

  if (warp_g >= 8) {
    reg_dealloc<40>();
    if (warp_g == 8) {
      {
        const uint32_t job = p.jobs[cl][0];
        if (lane == 0) { prefetch_tmap(&p.tmA[(job >> 2) & 1]); prefetch_tmap(&p.tmW[(job >> 6) & 3]); }
        __syncwarp();
        cluster_sync();
      }
      if (elect_one()) {
        uint32_t bs = 0, bph = 1, aph = 1;
#pragma unroll 1
        for (int ji = 0; ji < K1_MAXJOBS; ji++) {
          const uint32_t job = p.jobs[cl][ji];
          if (!(job & 3)) break;
          const int a_sel = (job >> 2) & 1, mpair = (job >> 3) & 7, chunk0 = (job >> 8) & 63;
          const bool newA = (job >> 14) & 1;
          const int KC = a_sel ? 9 : 8;
          const uint32_t halfbytes = 8192;
          const bool lastjob = (ji + 1 == K1_MAXJOBS) || !(p.jobs[cl][ji + 1] & 3);
          const CUtensorMap* tw = &p.tmW[(job >> 6) & 3];
          {
            const uint32_t njob = (ji + 1 < K1_MAXJOBS) ? p.jobs[cl][ji + 1] : 0;
            if (!(njob & 3) && !newA) mbar_arrive(bLast);
          }
#pragma unroll 1
          for (int kc = 0; kc < KC; kc++) {
            {
              const bool nx = kc + PFD >= KC;
              const uint32_t njob = nx ? p.jobs[cl][ji + 1] : job;
              const int pk = nx ? kc + PFD - KC : kc + PFD;
              if ((njob & 3) && (nx || ji > 0)) {
                if (cl >= 64 || ((pk ^ (cl >> 1)) & 3) == 0)
                  tma_pf3d(&p.tmW[(njob >> 6) & 3], 0, pk * 64 + (cl & 1) * 32 + rank * 16, (njob >> 8) & 63);
                if (((njob >> 14) & 1) || pk == 8) tma_pf2d(&p.tmA[a_sel], pk * 64, ((njob >> 3) & 7) * 256 + rank * 128);
              }
            }
            if (kc == 8) {
              PWAIT(bBe + bs * 8, bph);
              mbar_expect(bBf + bs * 8, 16384);
              tma2d(sB + bs * 16384, &p.tmA[1], bBf + bs * 8, 512, mpair * 256 + rank * 128);
              if (++bs == K1_BST) { bs = 0; bph ^= 1; }
            } else if (newA) {
              PWAIT(bAe + kc * 8, aph);
              mbar_expect(bAf + kc * 8, 16384);
              tma2d(sA + ((kc + 2) & 7) * 16384, &p.tmA[a_sel], bAf + kc * 8, kc * 64, mpair * 256 + rank * 128);
              if (kc == 7 && lastjob) mbar_arrive(bLast);
            }
#pragma unroll 1
            for (int kk = 0; kk < 2; kk++) {
              PWAIT(bBe + bs * 8, bph);
              mbar_expect(bBf + bs * 8, 2 * halfbytes);
              tma3d_mc(sB + bs * 16384 + rank * halfbytes, tw, bBf + bs * 8, 0, kc * 64 + kk * 32 + rank * 16, chunk0, 3);
              if (++bs == K1_BST) { bs = 0; bph ^= 1; }
            }
          }
          if (newA) aph ^= 1;
        }
        Cursor c{0, 0};
        int pcol = 0;
        PWAIT(bR, 0);
        uint32_t tick = lds32(sTick + 8), seen = 1u << (p.order[tick] >> 4);
        asm volatile("fence.proxy.async.global;" ::: "memory");
#pragma unroll 1
        for (int it = 0;; it++) {
          const uint32_t item = (tick < 256) ? p.order[tick] : (K2_END | min(tick - 256, 255u));
          asm volatile("st.shared.u32 [%0], %1;" ::"r"(sItem + (it & 7) * 4), "r"(item) : "memory");
          if (item >= K2_END) break;
          const int h = item >> 3, j = item & 7;
          const int blk = 2 * j + (int)(rank ^ (it & 1));
          const int col = h * 128 + rank * 64;
          const int nb = 2 * j + 2;
          if (!((seen >> (h >> 1)) & 1)) {
            wait_flag(&g_sync[F_HP + (h >> 1)], RDY_TARGET);
            asm volatile("fence.proxy.async.global;" ::: "memory");
            seen |= 1u << (h >> 1);
          }
          PWAIT(bE + c.s * 8, c.ph);
          mbar_expect(bF + c.s * 8, 32768);
          tma2d(sbase + c.s * 32768, &p.tmC, bF + c.s * 8, h * 128, blk * 128);
          tma2d(sbase + c.s * 32768 + 16384, &p.tmC, bF + c.s * 8, h * 128 + 64, blk * 128);
          c.next();
#pragma unroll 1
          for (int n = nb - 1; n >= 0; n--) {
            if (n == 0 && rank == 0) tick = atomicAdd(&g_sync[F_TICK], 1u);
            PWAIT(bE + c.s * 8, c.ph);
            mbar_expect(bF + c.s * 8, 32768);
            tma2d_mc(sbase + c.s * 32768 + rank * 16384, &p.tmK, bF + c.s * 8, col, n * 128, 3);
            c.next();
            if (n < nb - 1 || it > 0) {
              PWAIT(bE + c.s * 8, c.ph);
              mbar_expect(bF + c.s * 8, 32768);
              tma2d_mc(sbase + c.s * 32768 + rank * 16384, &p.tmV, bF + c.s * 8, (n < nb - 1) ? col : pcol, (n < nb - 1) ? (n + 1) * 128 : 0, 3);
              c.next();
            }
          }
          pcol = col;
          if (rank == 0) {
            asm volatile(
                "{\n.reg .b32 a, b;\nmapa.shared::cluster.u32 a, %0, 1;\nmapa.shared::cluster.u32 b, %1, 1;\n"
                "st.async.shared::cluster.mbarrier::complete_tx::bytes.u32 [a], %2, [b];\n}" ::"r"(sTick + (it & 1) * 4),
                "r"(bT + (it & 1) * 8), "r"(tick) : "memory");
          } else {
            mbar_expect(bT + (it & 1) * 8, 4);
            PWAIT(bT + (it & 1) * 8, (it >> 1) & 1);
            tick = lds32(sTick + (it & 1) * 4);
          }
        }
        PWAIT(bE + c.s * 8, c.ph);
        mbar_expect(bF + c.s * 8, 32768);
        tma2d_mc(sbase + c.s * 32768 + rank * 16384, &p.tmV, bF + c.s * 8, pcol, 0, 3);
        const uint32_t unit = tick - 256;
        if (unit < 64) {
          const int mblk = (7 - (p.unit[unit][0] >> 1)) * 2 + rank, nhalf = p.unit[unit][0] & 1;
          const uint32_t rot = k3_rot(c.s), nfree = ((0x1Au >> c.s) & 1) ? 2 : 3;
#pragma unroll 1
          for (int i = 0; i < K2_NST - 1; i++) {
            c.next();
            PWAIT(bE + c.s * 8, c.ph);
          }
          uint32_t have = 0;
#pragma unroll 1
          for (uint32_t idx = 0; idx < p.unit[unit][2]; idx++) {
            const int kk = p.unit[unit][3] + idx + ((idx >= p.unit[unit][4]) ? p.unit[unit][5] : 0);
            const uint32_t s = (rot + idx) & 3;
            if (idx >= nfree) PWAIT((idx < 4) ? bH : b3E + s * 8, (idx < 4) ? 0 : (~idx >> 2) & 1);
            mbar_expect(b3F + s * 8, K3_STAGE);
            const uint32_t st = sbase + s * K3_STAGE;
            const int sel = (kk < 9), k = sel ? kk : kk - 9, kr = k * 64 + rank * 32;
            tma3d_mc(st + 16384 + rank * 16384, &p.tmO[sel], b3F + s * 8, 0, kr, nhalf * 4, 3);
            tma2d_mc(st + 49152 + rank * 2048, &p.tmOt[sel], b3F + s * 8, 512 + nhalf * 32, kr, 3);
            if (sel && idx == 0) {
              wait_flag(&g_sync[F_OA + mblk], 8);
              asm volatile("fence.proxy.async.global;" ::: "memory");
            }
            if (!sel && !((have >> (k >> 1)) & 1)) {
#pragma unroll 1
              for (uint32_t spins = 0; spins < (1u << 22); spins++) {
                asm volatile("ld.acquire.gpu.global.u32 %0, [%1];" : "=r"(have) : "l"(&g_sync[F_CTX + mblk]) : "memory");
                if ((have >> (k >> 1)) & 1) break;
                __nanosleep(100);
              }
              asm volatile("fence.proxy.async.global;" ::: "memory");
            }
            tma2d(st, &p.tmC, b3F + s * 8, (sel ? 64 + k : k) * 64, mblk * 128);
          }
        }
      }
    }
    __syncwarp();
    if (warp_g == 8) {
      uint32_t v = 0;
      if (lane == 0) {
        __threadfence();
        v = atomicAdd(&g_sync[F_DONE], 1u);
      }
      if (__shfl_sync(0xffffffffu, v, 0) == 2 * NCLUSTER - 1) {
        reinterpret_cast<uint4*>(g_sync)[lane] = make_uint4(0, 0, 0, 0);
        if (lane == 0) g_sync[F_EPOCH] = lds32(sGate + 64) + 1;
      }
    }
    asm volatile("" ::: "memory");
    if (__shfl_sync(0xffffffffu, warp_g, 0) != 8) {
      if (lr0 < S_LEN) {
#pragma unroll 1
        for (int i = warp_g - 9; i < 16; i += 3) {
          const float g = gate_row(lr0 + i, lane, x, gate_w);
          if (lane == 0) asm volatile("st.shared.f32 [%0], %1;" ::"r"(sGate + i * 4), "f"(g) : "memory");
        }
        bar_arrive(3, 256 + 96);
        if (lane == 0) {
          __threadfence();
          atomicAdd(&g_sync[F_GATE], 1u);
        }
      }
      uint32_t aph = 1;
#pragma unroll 1
      for (int ji = 0; ji < K1_MAXJOBS; ji++) aph ^= (p.jobs[cl][ji] >> 14) & 1;
      if (warp_g == 9 && lane == 0) {
#pragma unroll 1
        for (int ji = 0; ji < K1_MAXJOBS; ji++) {
          const uint32_t job = p.jobs[cl][ji];
          if (!(job & 3)) break;
          PWAIT(bS, ji & 1);
          __threadfence();
          atomicAdd(&g_sync[(((job >> 6) & 3) == 2) ? (F_QKVA + ((job >> 3) & 7) * 2 + rank) : (F_HP + ((job >> 10) & 15))], 1u);
        }
#pragma unroll 1
        for (int it = 0;; it++) {
          PWAIT(bS2, it & 1);
          const uint32_t item = lds32(sItem + (it & 7) * 4), nxt = lds32(sItem + ((it + 1) & 7) * 4);
          __threadfence();
          atomicOr(&g_sync[F_CTX + (item & 7) * 2 + (rank ^ (it & 1))], 1u << (item >> 3));
          if (nxt >= K2_END) break;
        }
      } else if (warp_g == 11) {
        if (lane == 0) {
          prefetch_tmap(&p.tmC); prefetch_tmap(&p.tmK); prefetch_tmap(&p.tmV);
          asm volatile("st.shared.u32 [%0], %1;" ::"r"(sGate + 64), "r"(__ldcg(&g_sync[F_EPOCH])) : "memory");
          wait_flag(&g_sync[F_GATE], GATE_TARGET);
          uint32_t tick;
          if (rank == 0) {
            PWAIT(bLast, 0);
            PWAIT(bAe + FIRST_DRAW * 8, aph);
            tick = atomicAdd(&g_sync[F_TICK], 1u);
            asm volatile("st.shared.u32 [%0], %1;" ::"r"(sTick + 8), "r"(tick) : "memory");
            asm volatile(
                "{\n.reg .b32 a, b;\nmapa.shared::cluster.u32 a, %0, 1;\nmapa.shared::cluster.u32 b, %1, 1;\n"
                "st.async.shared::cluster.mbarrier::complete_tx::bytes.u32 [a], %2, [b];\n}" ::"r"(sTick + 8), "r"(bT0), "r"(tick) : "memory");
          } else {
            mbar_expect(bT0, 4);
            PWAIT(bT0, 0);
            tick = lds32(sTick + 8);
          }
          wait_flag(&g_sync[F_HP + (p.order[tick] >> 4)], RDY_TARGET);
          mbar_arrive(bR);
        }
      } else if (warp_g == 10) {
        if (lr0 < S_LEN && lane == 0) {
          prefetch_tmap(&p.tmL[0]); prefetch_tmap(&p.tmL[1]); prefetch_tmap(&p.tmL[2]);
          wait_flag(&g_sync[F_QKVA + (lr0 >> 7)], K1_FLAG_TARGET);
          wait_flag(&g_sync[F_QKVA + (max(lr0 - 16, 0) >> 7)], K1_FLAG_TARGET);
          asm volatile("fence.proxy.async.global;" ::: "memory");
          PWAIT(bLast, 0);
#pragma unroll 1
          for (int kc = 0; kc < 6; kc++) {
            PWAIT(bAe + kc * 8, aph);
            if (kc == 3) {
              mbar_expect(bL, LV);
              tma4d(sL, &p.tmL[0], bL, lr0 / 2 - 8, 9, 0);
              tma4d(sL + LQ, &p.tmL[1], bL, lr0 / 2, 0, 0);
            }
          }
          mbar_expect(bL2, LQ);
          tma4d(sL + LV, &p.tmL[0], bL2, lr0 / 2 - 8, 18, 0);
        }
        __syncwarp();
        bar_sync(5, 256 + 32);
        if (lr0 < S_LEN && lane == 0) {
          asm volatile("cp.async.bulk.tensor.4d.global.shared::cta.bulk_group [%0, {%2, %3, %2, %2}], [%1];" ::"l"(&p.tmL[2]), "r"(sL + LQ), "r"(0), "r"(lr0 / 2) : "memory");
          asm volatile("cp.async.bulk.commit_group;" ::: "memory");
          asm volatile("cp.async.bulk.wait_group.read 0;" ::: "memory");
        }
        __syncwarp();
        if (lane < 12) mbar_arrive_cluster(bE + (4 + lane % 3) * 8, (lane / 3) & 1);
        if (lr0 < S_LEN && lane == 0) {
          asm volatile("cp.async.bulk.wait_group 0;" ::: "memory");
          asm volatile("fence.proxy.async.global;" ::: "memory");
          __threadfence();
          atomicAdd(&g_sync[F_OA + (lr0 >> 7)], 1u);
        }
      }
    }
    __syncwarp();
    cluster_sync();
  } else {
    reg_alloc<232>();
    const int wg = warp_g >> 2, warp = warp_g & 3, q = lane & 3;
    const bool sig = (lane == 0) && (warp < 2);
    {
      K1State st{0, 0, 0, nullptr, nullptr, 0, 0, 0};
      float acc[128];
      uint32_t pk[64];
      if (wg == 0) { TS(0, 0); TSC(0, 2); }
      uint32_t job = p.jobs[cl][0];
      k1_first(st, job, bAf, bBf);
      {
#pragma unroll 1
        for (int ji = 0; job & 3; ji++) {
          const uint32_t njob = p.jobs[cl][ji + 1];
          k1_tile(acc, pk, st, job, njob, sA, sB, bAf, bAe, bBf, bBe, bS, wg, warp, lane, rank);
          job = njob;
        }
      }
#pragma unroll
      for (int i = 0; i < 4; i++)
        mbar_arrive_cluster_if(bE + i * 8, warp & 1, sig);
      if (lr0 < S_LEN) bar_sync(3, 256 + 96);
      if (st.wsel == 3) {
#pragma unroll
        for (int G = 0; G < 16; G++) scale_q4(pk + G * 4);
      }
      FLUSH();
      if (wg == 0) { TS(0, 1); TSC(0, 3); }
      if (lr0 < S_LEN) {
        const float gate0 = __uint_as_float(lds32(sGate + (lane >> 2) * 8)), gate1 = __uint_as_float(lds32(sGate + (lane >> 2) * 8 + 4));
        local_attn(lr0, warp_g, sL, bL, bL2, lane, gate0, gate1);
      }
      bar_arrive(5, 256 + 32);
    }
    __syncwarp();
    uint32_t item, rot;
    {
      const int mybar = 1 + wg, otherbar = 2 - wg;
      const uint32_t never = blockIdx.y;
      float S[64], O[64];
      uint32_t P[32], Q[32];
      float m0 = 0.f, m1 = 0.f, l0 = 1.f, l1 = 1.f, gf0 = 0.f, gf1 = 0.f;
      uint32_t eoff = 0, prev_single = 0;
      Cursor c{0, 0};
      if (wg == 1) bar_arrive(1, 256);
      if (wg == 0) { TS(1, 0); TSC(1, 2); }
#pragma unroll 1
      for (int it = 0;; it++) {
        TB(0);
        const int hi = (int)(rank ^ (it & 1));
        Cursor cq = c, ck, cv, cs0, cs1;
        rot = k3_rot(c.s);
        c.next();
        ck = c; c.next();
        cs0 = ck; cs1 = ck; cv = ck;
        if (it > 0) { cv = c; c.next(); }
        if (!hi) {
          ck = c; c.next();
          cs1 = c; c.next();
        }
        mbar_wait(bF + cq.s * 8, cq.ph);
        TB(1);
        item = lds32(sItem + (it & 7) * 4);
        {
          const uint32_t qa = sbase + cq.s * 32768 + (wg * 64 + warp * 16 + (lane & 15)) * 128;
#pragma unroll
          for (int t = 0; t < 8; t++)
            ldsm_x4(Q[4 * t], Q[4 * t + 1], Q[4 * t + 2], Q[4 * t + 3], qa + (t >> 2) * 16384 + ((((t & 3) * 2 + (lane >> 4)) ^ (lane & 7)) << 4));
        }
        const uint32_t rdy = mbar_test(bF + ck.s * 8, ck.ph) & mbar_test(bF + cv.s * 8, cv.ph);
        l0 += __shfl_xor_sync(0xffffffffu, l0, 1);
        l1 += __shfl_xor_sync(0xffffffffu, l1, 1);
        l0 += __shfl_xor_sync(0xffffffffu, l0, 2);
        l1 += __shfl_xor_sync(0xffffffffu, l1, 2);
        const bool last = item >= K2_END;
        if (last) {
          cv = cq; ck = cq;
        } else if (!rdy) {
          mbar_wait2(bF + ck.s * 8, ck.ph, bF + cv.s * 8, cv.ph);
        }
        TB(2);
        TURN_SYNC();
        TB(3);
        TRC(last ? 2 : 1);
        if (it > 0) {
          wg_fence();
          ISSUE_PV(cv, prev_single);
          wg_commit();
        } else {
          wg_fence();
          wg_commit();
        }
        wg_fence();
        ISSUE_QK(ck);
        wg_commit();
        if (!(last && wg == 1)) TURN_ARRIVE();
        RELEASE_IF(cq, !last);
        TB(4);
        asm volatile("" : "+f"(gf0), "+f"(gf1), "+f"(l0), "+f"(l1));
        const float f0 = __fdividef(1.f - gf0, l0), f1 = __fdividef(1.f - gf1, l1);
        wg_wait<1>();
        fence_regs(O);
        fence_regs(P);
        TB(5);
        if (it > 0) {
          RELEASE_IF(cv, !last);
          mbar_arrive_cluster_if(bH, warp & 1, sig && last);
          bf16* optr = ptr_add(g_ctx, eoff);
          STORE_O(0); STORE_O(1); STORE_O(2); STORE_O(3);
          __syncwarp();
          mbar_arrive_if(bS2, lane == 0);
        }
        TB(6);
        if (!last) {
          const int row = (2 * (item & 7) + hi) * 128 + wg * 64 + warp * 16 + (lane >> 2);
          eoff = (row * KCAT + (item >> 3) * 128 + q * 8) * 2;
          const float* gp = ptr_add(g_gate, row * 4);
          asm volatile("ld.global.f32 %0, [%1];" : "=f"(gf0) : "l"(gp));
          asm volatile("ld.global.f32 %0, [%1];" : "=f"(gf1) : "l"(gp + 8));
          if (!hi) {
            mbar_wait2(bF + cs0.s * 8, cs0.ph, bF + cs1.s * 8, cs1.ph);
            RELEASE(cs0);
            RELEASE(cs1);
          }
        }
        TB(7);
        wg_wait<0>();
        fence_regs(S);
        TB(8);
        if (last) break;
        RELEASE(ck);
        const int nblk = 2 * (item & 7) + 1 + hi;
        prev_single = (nblk == 1);
        float s0 = 0.f, s1 = 0.f;
        l0 = 0.f; l1 = 0.f;
        m0 = 0.f; m1 = 0.f;
        bool shifted = false;
        {
          const int d = warp * 16 + (lane >> 2) - 2 * q;
          if (wg == 0) {
#pragma unroll
            for (int jj = 0; jj < 8; jj++) MASK(jj, jj);
            EXPB(0); EXPB(1); EXPB(2); EXPB(3);
#pragma unroll
            for (int i = 32; i < 64; i++) S[i] = -INFINITY;
#pragma unroll
            for (int i = 16; i < 32; i++) P[i] = 0;
          } else {
#pragma unroll
            for (int jj = 0; jj < 8; jj++) MASK(jj + 8, jj);
            EXPB(0); EXPB(1); EXPB(2); EXPB(3); EXPB(4); EXPB(5); EXPB(6); EXPB(7);
          }
        }
        float chk = (q == 0 && !(fminf(s0, s1) >= SPEC_LO)) ? INFINITY : s0 + s1;
        fence_regs(P);
        TB(9);
#pragma unroll 1
        for (int n = 1;; n++) {
          if (__any_sync(0xffffffffu, !(chk <= SPEC_HI))) {
            float mx0 = fmaxf(S[0], S[1]), mx1 = fmaxf(S[2], S[3]);
#pragma unroll
            for (int jj = 1; jj < 16; jj++) {
              mx0 = fmaxf(mx0, fmaxf(S[jj * 4 + 0], S[jj * 4 + 1]));
              mx1 = fmaxf(mx1, fmaxf(S[jj * 4 + 2], S[jj * 4 + 3]));
            }
            mx0 = fmaxf(mx0, __shfl_xor_sync(0xffffffffu, mx0, 1));
            mx1 = fmaxf(mx1, __shfl_xor_sync(0xffffffffu, mx1, 1));
            mx0 = fmaxf(mx0, __shfl_xor_sync(0xffffffffu, mx0, 2));
            mx1 = fmaxf(mx1, __shfl_xor_sync(0xffffffffu, mx1, 2));
            const float lo = (n == 1) ? -INFINITY : 0.f;
            mx0 = fmaxf(mx0, lo);
            mx1 = fmaxf(mx1, lo);
            m0 += mx0; m1 += mx1;
            shifted = true;
            const float sc0 = ex2(-fmaxf(mx0, 0.f)), sc1 = ex2(-fmaxf(mx1, 0.f));
            l0 *= sc0; l1 *= sc1;
            s0 = 0.f; s1 = 0.f;
#pragma unroll
            for (int jj = 0; jj < 16; jj++) {
              const float e0 = ex2(S[jj * 4 + 0] - mx0), e1 = ex2(S[jj * 4 + 1] - mx0), e2 = ex2(S[jj * 4 + 2] - mx1), e3 = ex2(S[jj * 4 + 3] - mx1);
              s0 += e0 + e1;
              s1 += e2 + e3;
              P[jj * 2 + 0] = pack_bf16(e0, e1);
              P[jj * 2 + 1] = pack_bf16(e2, e3);
              O[jj * 4 + 0] *= sc0;
              O[jj * 4 + 1] *= sc0;
              O[jj * 4 + 2] *= sc1;
              O[jj * 4 + 3] *= sc1;
            }
          }
          l0 += s0;
          l1 += s1;
          if (n >= nblk) break;
          ck = c; c.next();
          cv = c; c.next();
          mbar_wait(bF + ck.s * 8, ck.ph);
          mbar_wait(bF + cv.s * 8, cv.ph);
          TURN_SYNC();
          TRC(0);
          wg_fence();
          ISSUE_QK(ck);
          wg_commit();
          {
            const uint64_t dv = make_desc(sbase + cv.s * 32768, 16384, 1024, 1);
#pragma unroll
            for (int t = 0; t < 8; t++) {
              wgmma_rs_n128<1, 0>(O, P[4 * t], P[4 * t + 1], P[4 * t + 2], P[4 * t + 3], dv + (uint64_t)(t * 128), (t > 0) ? 1 : (n != 1));
              if ((PVM >> t) & 1) wg_commit();
            }
          }
          TURN_ARRIVE();
          s0 = 0.f; s1 = 0.f;
          wg_wait<__builtin_popcount(PVM)>();
          fence_regs(S);
          RELEASE(ck);
          if (shifted) {
#pragma unroll
            for (int i = 0; i < 64; i++) S[i] -= (i & 2) ? m1 : m0;
          }
          wg_wait<__builtin_popcount(PVM) - 1>();
          EXPC(0); EXPC(1); EXPC(2); EXPC(3); EXPC(4); EXPC(5); EXPC(6); EXPC(7);
          chk = s0 + s1;
        }
      }
      TRC(3);
      if (wg == 1) { TS(1, 1); TSC(1, 3); }
    }
    __syncwarp();
    const uint32_t unit = item & 255;
    if (unit < 64) {
      const int mblk = (7 - (p.unit[unit][0] >> 1)) * 2 + rank, nhalf = p.unit[unit][0] & 1, ks = p.unit[unit][1];
      const int k0 = 0, k1 = p.unit[unit][2];
      float acc[144];
      uint32_t s = rot, ph = 0, prev = 0;
      if (wg == 0) { TS(2, 0); TSC(2, 2); }
      uint32_t fa[16], fb[16];
      const uint32_t aoff = (wg * 64 + warp * 16 + (lane & 15)) * 128 + (((lane >> 4) ^ (lane & 7)) << 4);
#define C_LOAD(F)                                                                                              \
  do {                                                                                                         \
    mbar_wait(b3F + s * 8, ph);                                                                                \
    _Pragma("unroll") for (int t = 0; t < 4; t++)                                                              \
        ldsm_x4(F[4 * t], F[4 * t + 1], F[4 * t + 2], F[4 * t + 3], sbase + s * K3_STAGE + (aoff ^ (t * 32))); \
  } while (0)
#define C_STEP(F, G)                                                                                           \
  {                                                                                                            \
    const uint32_t st = sbase + s * K3_STAGE;                                                                  \
    const uint64_t db = make_desc(st + 16384, 4096, 1024, 1), dt = make_desc(st + 49152, 16, 512, 2);          \
    wg_fence();                                                                                                \
    _Pragma("unroll") for (int t = 0; t < 4; t++) {                                                            \
      const int sd = (t > 0) || (k > k0);                                                                      \
      wgmma_rs_n256<1, 0>(acc, F[4 * t], F[4 * t + 1], F[4 * t + 2], F[4 * t + 3], db + (uint64_t)((t >> 1) * 1024 + (t & 1) * 128), sd); \
      wgmma_rs_n32<1, 128>(acc, F[4 * t], F[4 * t + 1], F[4 * t + 2], F[4 * t + 3], dt + (uint64_t)(t * 64), sd); \
    }                                                                                                          \
    wg_commit();                                                                                               \
    wg_wait<1>();                                                                                              \
    fence_regs(G);                                                                                             \
    mbar_arrive_cluster_if(b3E + prev * 8, warp & 1, sig && k > k0);                                           \
    prev = s;                                                                                                  \
    s = (s + 1) & 3;                                                                                           \
    if (s == rot) ph ^= 1;                                                                                     \
    if (++k == k1) break;                                                                                      \
    C_LOAD(G);                                                                                                 \
  }
      C_LOAD(fa);
#pragma unroll
      for (int i = 0; i < 16; i++) fb[i] = 0;
#pragma unroll 1
      for (int k = k0;;) {
        C_STEP(fa, fb)
        C_STEP(fb, fa)
      }
      wg_wait<0>();
      fence_regs(acc);
      cluster_arrive();
      if (wg == 0) TS(2, 4);
      const int tile = mblk * 2 + nhalf;
      uint4* wp = g_part + (size_t)((tile * 4 + ks) * 4) * 5 * 256 + tid;
      const uint32_t sown = sbase + wg * 8192 + (tid & 127) * 16;
#pragma unroll
      for (int d = 0; d < 4; d++) {
        if (d != ks) {
#pragma unroll
          for (int i = 0; i < 4; i++)
            __stcg(wp + (d * 5 + i) * 256,
                   make_uint4(pack_bf16(acc[d * 32 + i * 8], acc[d * 32 + i * 8 + 1]), pack_bf16(acc[d * 32 + i * 8 + 2], acc[d * 32 + i * 8 + 3]),
                              pack_bf16(acc[d * 32 + i * 8 + 4], acc[d * 32 + i * 8 + 5]), pack_bf16(acc[d * 32 + i * 8 + 6], acc[d * 32 + i * 8 + 7])));
          __stcg(reinterpret_cast<uint2*>(wp - tid + (d * 5 + 4) * 256) + tid,
                 make_uint2(pack_bf16(acc[128 + d * 4], acc[128 + d * 4 + 1]), pack_bf16(acc[128 + d * 4 + 2], acc[128 + d * 4 + 3])));
        } else {
#pragma unroll
          for (int i = 0; i < 9; i++) {
            const int o = (i < 8) ? d * 32 + i * 4 : 128 + d * 4;
            asm volatile("st.shared.v4.f32 [%0], {%1, %2, %3, %4};" ::"r"(sown + (i >> 2) * K3_STAGE + (i & 3) * 2048), "f"(acc[o]), "f"(acc[o + 1]), "f"(acc[o + 2]), "f"(acc[o + 3]) : "memory");
          }
        }
      }
      __threadfence();
      __syncwarp();
      if (wg == 0) TS(2, 5);
      if (lane == 0) {
        unsigned int* cnt = &g_sync[F_XCH + tile * 8 + warp_g];
        const uint32_t xtarget = lds32(sGate + 64) * 4 + 4;
        atomicAdd(cnt, 1u);
        uint32_t v, spins = 0;
        do {
          asm volatile("ld.acquire.gpu.global.u32 %0, [%1];" : "=r"(v) : "l"(cnt) : "memory");
        } while ((int)(v - xtarget) < 0 && ++spins < (1u << 24));
      }
      __syncwarp();
      if (wg == 0) TS(2, 6);
      float r[36];
#pragma unroll
      for (int i = 0; i < 9; i++)
        asm volatile("ld.shared.v4.f32 {%0, %1, %2, %3}, [%4];" : "=f"(r[i * 4]), "=f"(r[i * 4 + 1]), "=f"(r[i * 4 + 2]), "=f"(r[i * 4 + 3])
                     : "r"(sown + (i >> 2) * K3_STAGE + (i & 3) * 2048) : "memory");
#pragma unroll
      for (int sI = 1; sI < 4; sI++) {
        const int src = (ks + sI) & 3;
        const uint4* rp = g_part + (size_t)(((tile * 4 + src) * 4) + ks) * 5 * 256;
#pragma unroll
        for (int i = 0; i < 4; i++) {
          const uint4 v = __ldcg(rp + i * 256 + tid);
          r[i * 8] += bf_lo(v.x); r[i * 8 + 1] += bf_hi(v.x); r[i * 8 + 2] += bf_lo(v.y); r[i * 8 + 3] += bf_hi(v.y);
          r[i * 8 + 4] += bf_lo(v.z); r[i * 8 + 5] += bf_hi(v.z); r[i * 8 + 6] += bf_lo(v.w); r[i * 8 + 7] += bf_hi(v.w);
        }
        const uint2 v = __ldcg(reinterpret_cast<const uint2*>(rp + 4 * 256) + tid);
        r[32] += bf_lo(v.x); r[33] += bf_hi(v.x); r[34] += bf_lo(v.y); r[35] += bf_hi(v.y);
      }
      const int row = mblk * 128 + wg * 64 + warp * 16 + (lane >> 2);
      bf16* o0 = out + (size_t)row * DM + nhalf * 256 + ks * 64 + 8 * q;
#pragma unroll
      for (int G = 0; G < 2; G++) {
        uint32_t a0 = pack_bf16(r[G * 16], r[G * 16 + 1]), a1 = pack_bf16(r[G * 16 + 4], r[G * 16 + 5]);
        uint32_t a2 = pack_bf16(r[G * 16 + 8], r[G * 16 + 9]), a3 = pack_bf16(r[G * 16 + 12], r[G * 16 + 13]);
        uint32_t b0 = pack_bf16(r[G * 16 + 2], r[G * 16 + 3]), b1 = pack_bf16(r[G * 16 + 6], r[G * 16 + 7]);
        uint32_t b2 = pack_bf16(r[G * 16 + 10], r[G * 16 + 11]), b3 = pack_bf16(r[G * 16 + 14], r[G * 16 + 15]);
        quad_transpose(a0, a1, a2, a3, q);
        quad_transpose(b0, b1, b2, b3, q);
        st_v4(o0 + G * 32, a0, a1, a2, a3);
        st_v4(o0 + 8 * DM + G * 32, b0, b1, b2, b3);
      }
      {
        uint32_t t0 = pack_bf16(r[32], r[33]), t1 = pack_bf16(r[34], r[35]), t2 = 0, t3 = 0;
        quad_transpose(t0, t1, t2, t3, q);
        if (q < 2) st_v4(out + (size_t)(row + q * 8) * DM + 512 + nhalf * 32 + ks * 8, t0, t1, t2, t3);
      }
    } else {
      cluster_arrive();
    }
    if (wg == 0) { TS(2, 1); TSC(2, 3); }
    cluster_wait();
  }
}

typedef CUresult (*EncFn)(CUtensorMap*, CUtensorMapDataType, cuuint32_t, void*, const cuuint64_t*, const cuuint64_t*, const cuuint32_t*,
                          const cuuint32_t*, CUtensorMapInterleave, CUtensorMapSwizzle, CUtensorMapL2promotion, CUtensorMapFloatOOBfill);

static void enc2d(EncFn enc, CUtensorMap* m, const void* ptr, uint64_t cols, uint64_t rows, uint32_t bc, uint32_t br,
                  CUtensorMapSwizzle sw = CU_TENSOR_MAP_SWIZZLE_128B) {
  cuuint64_t gd[2] = {cols, rows}, gs[1] = {cols * 2};
  cuuint32_t bx[2] = {bc, br}, es[2] = {1, 1};
  enc(m, CU_TENSOR_MAP_DATA_TYPE_BFLOAT16, 2, const_cast<void*>(ptr), gd, gs, bx, es, CU_TENSOR_MAP_INTERLEAVE_NONE, sw,
      CU_TENSOR_MAP_L2_PROMOTION_L2_256B, CU_TENSOR_MAP_FLOAT_OOB_FILL_NONE);
}
static void enc3d(EncFn enc, CUtensorMap* m, const void* ptr, uint64_t cols, uint64_t rows, uint32_t br, uint32_t bch) {
  cuuint64_t gd[3] = {64, rows, cols / 64}, gs[2] = {cols * 2, 128};
  cuuint32_t bx[3] = {64, br, bch}, es[3] = {1, 1, 1};
  enc(m, CU_TENSOR_MAP_DATA_TYPE_BFLOAT16, 3, const_cast<void*>(ptr), gd, gs, bx, es, CU_TENSOR_MAP_INTERLEAVE_NONE,
      CU_TENSOR_MAP_SWIZZLE_128B, CU_TENSOR_MAP_L2_PROMOTION_L2_256B, CU_TENSOR_MAP_FLOAT_OOB_FILL_NONE);
}

static int g_sched[10] = {11, 10, 7, 4, 4, 4, 6, 8, 6, 24};
static void build_k1_jobs(Params& p) {
  int cnt[NCLUSTER];
  for (int c = 0; c < NCLUSTER; c++) {
    cnt[c] = 0;
    for (int i = 0; i <= K1_MAXJOBS; i++) p.jobs[c][i] = 0;
  }
  auto add = [&](int c, int nch, int a_sel, int mp, int w_sel, int chunk0) {
    p.jobs[c][cnt[c]++] = (uint16_t)((nch - 1) | (a_sel << 2) | (mp << 3) | (w_sel << 6) | (chunk0 << 8));
  };
  const int *cg = g_sched, *xg = g_sched + 4;
  for (int mp = 0; mp < 8; mp++) {
    int k = 0;
    for (int i = 0; i < K1_MAXJOBS; i++)
      for (int g = 0; g < 4; g++)
        if (i < cg[g]) { add(g * 8 + mp, 4, 0, mp, k & 1, (k >> 1) * 4); k++; }
    k = 0;
    for (int i = 0; i < K1_MAXJOBS; i++)
      for (int g = 0; g < 4; g++)
        if (i < xg[g]) {
          if (k < 7) add((4 + g) * 8 + mp, k == 0 ? 3 : 4, 1, mp, 2, k == 0 ? 24 : (k - 1) * 4);
          else add((4 + g) * 8 + mp, 4, 1, mp, 3, (k - 7) * 4);
          k++;
        }
    if (k < 22) add(64 + mp / 4, 4, 1, mp, 3, 14 * 4);
    add(64 + mp / 4, 4, 1, mp, 3, 15 * 4);
  }
  for (int cc = 0; cc < NCLUSTER; cc++)
    for (int i = 0; i < cnt[cc]; i++) {
      const int key = p.jobs[cc][i] & 0x3C;
      if (i == 0 || (p.jobs[cc][i - 1] & 0x3C) != key) p.jobs[cc][i] |= (1 << 14);
      if (i == cnt[cc] - 1 || (p.jobs[cc][i + 1] & 0x3C) != key) p.jobs[cc][i] |= (1 << 15);
    }
}

static void build_k2_items(Params& p) {
  int n = 0;
  const int SCHED_N1 = g_sched[8], SCHED_N2 = g_sched[9];
  int N0 = 2, J0 = 2;
  for (int j = 7; j >= J0; j--)
    for (int h = 0; h < N0; h++) p.order[n++] = (uint8_t)(h * 8 + j);
  for (int j = 7; j >= 0; j--)
    for (int h = 0; h < SCHED_N1; h++)
      if (!(h < N0 && j >= J0)) p.order[n++] = (uint8_t)(h * 8 + j);
  for (int j = 7; j >= 4; j--)
    for (int h = SCHED_N1; h < SCHED_N2; h++) p.order[n++] = (uint8_t)(h * 8 + j);
  for (int j = 7; j >= 0; j--)
    for (int h = SCHED_N1; h < 32; h++)
      if (!(h < SCHED_N2 && j >= 4)) p.order[n++] = (uint8_t)(h * 8 + j);
}

static void build_k3_units(Params& p) {
  float slope = 0.045f;
  int NE = 25;
  for (int t = 0; t < 16; t++) {
    const int u[4] = {t, 31 - t, 32 + t, 63 - t};
    float acc = 0.f;
    int k0 = 0, l0 = NE;
    for (int i = 0; i < 4; i++) {
      acc += 18.25f + slope * (31.5f - u[i]);
      const int k1 = (i == 3) ? 73 : (int)(acc + 0.5f);
      const int e0 = NE * i / 4, e1 = NE * (i + 1) / 4;
      uint8_t* w = p.unit[u[i]];
      w[0] = (uint8_t)t; w[1] = (uint8_t)i; w[2] = (uint8_t)(k1 - k0); w[3] = (uint8_t)e0; w[4] = (uint8_t)(e1 - e0); w[5] = (uint8_t)(l0 - e1);
      l0 += (k1 - k0) - (e1 - e0);
      k0 = k1;
    }
  }
}

extern "C" void kernel_launch(void* const* d_in, const int* in_sizes, int n_in, void* d_out, int out_size) {
  const bf16* x = (const bf16*)d_in[0];
  const bf16* wqkv = (const bf16*)d_in[1];
  const bf16* wo = (const bf16*)d_in[2];
  const bf16* ckv = (const bf16*)d_in[4];
  const bf16* w_q = (const bf16*)d_in[5];
  const bf16* w_uk = (const bf16*)d_in[6];
  const bf16* w_uv = (const bf16*)d_in[7];
  const bf16* w_o = (const bf16*)d_in[8];
  const bf16* gate_w = (const bf16*)d_in[9];

  EncFn enc = nullptr;
  cudaDriverEntryPointQueryResult qr;
  cudaGetDriverEntryPoint("cuTensorMapEncodeTiled", (void**)&enc, cudaEnableDefault, &qr);
  void *pK, *pV, *pCtx, *pQA;
  cudaGetSymbolAddress(&pQA, g_QKVA);
  cudaGetSymbolAddress(&pK, g_K);
  cudaGetSymbolAddress(&pV, g_V);
  cudaGetSymbolAddress(&pCtx, g_ctx);

  static Params p;
  enc2d(enc, &p.tmA[0], ckv, DC, S_LEN, 64, 128);
  enc2d(enc, &p.tmA[1], x, DM, S_LEN, 64, 128);
  enc3d(enc, &p.tmW[0], w_uk, HDIM, DC, 16, 4);
  enc3d(enc, &p.tmW[1], w_uv, HDIM, DC, 16, 4);
  enc3d(enc, &p.tmW[2], wqkv, NQKVA, DM, 16, 4);
  enc3d(enc, &p.tmW[3], w_q, HDIM, DM, 16, 4);
  build_k1_jobs(p);
  enc2d(enc, &p.tmK, pK, HDIM, S_LEN, 64, 128);
  enc2d(enc, &p.tmV, pV, HDIM, S_LEN, 64, 128);
  build_k2_items(p);
  build_k3_units(p);
  for (int i = 0; i < 3; i++) {
    const cuuint64_t ld = (i < 2 ? NQKVA : KCAT) * 2, nch = (i < 2) ? 27 : 9;
    cuuint64_t gd[4] = {64, S_LEN / 2, i ? 2 : nch, i ? nch : 2}, gs[3] = {2 * ld, i ? ld : 128, i ? 128 : ld};
    cuuint32_t bx[4] = {64, i ? 8u : 16u, i ? 2u : 9u, i ? 9u : 2u}, es[4] = {1, 1, 1, 1};
    enc(&p.tmL[i], CU_TENSOR_MAP_DATA_TYPE_BFLOAT16, 4, (i < 2) ? pQA : (void*)((bf16*)pCtx + HDIM), gd, gs, bx, es, CU_TENSOR_MAP_INTERLEAVE_NONE,
        CU_TENSOR_MAP_SWIZZLE_128B, CU_TENSOR_MAP_L2_PROMOTION_L2_256B, CU_TENSOR_MAP_FLOAT_OOB_FILL_NONE);
  }
  enc2d(enc, &p.tmC, pCtx, KCAT, S_LEN, 64, 128);
  enc3d(enc, &p.tmO[0], w_o, DM, HDIM, 32, 4);
  enc3d(enc, &p.tmO[1], wo, DM, DM, 32, 4);
  enc2d(enc, &p.tmOt[0], w_o, DM, HDIM, 32, 32, CU_TENSOR_MAP_SWIZZLE_64B);
  enc2d(enc, &p.tmOt[1], wo, DM, DM, 32, 32, CU_TENSOR_MAP_SWIZZLE_64B);

  cudaFuncSetAttribute(fused_kernel, cudaFuncAttributeMaxDynamicSharedMemorySize, SMEM_BYTES);
  fused_kernel<<<NCLUSTER * 2, 384, SMEM_BYTES>>>(p, x, gate_w, (bf16*)d_out);
}
```

```cpp
#include <cuda_runtime.h>
#include <cuda_bf16.h>
#include <cuda.h>
#include <stdint.h>

typedef __nv_bfloat16 bf16;

constexpr int S_LEN = 2048, DM = 576, DC = 512, HDIM = 4096, NQKVA = 1728, KCAT = 4672;
constexpr int NCLUSTER = 66;

__device__ __align__(1024) bf16 g_K[S_LEN * HDIM];
__device__ __align__(1024) bf16 g_V[S_LEN * HDIM];
__device__ __align__(1024) bf16 g_QKVA[S_LEN * NQKVA + 64];
__device__ __align__(1024) bf16 g_ctx[S_LEN * KCAT];
__device__ float g_gate[S_LEN];
__device__ __align__(1024) uint4 g_part[32 * 4 * 4 * 5 * 256];
__device__ __align__(16) unsigned int g_sync[400];
constexpr int F_QKVA = 0, F_HP = 16, F_CTX = 32, F_OA = 48, F_GATE = 96, F_TICK = 97, F_DONE = 98, F_XCH = 128, F_EPOCH = 384;

__device__ __forceinline__ uint32_t smem_u32(const void* p) { return (uint32_t)__cvta_generic_to_shared(p); }
__device__ __forceinline__ void mbar_init(uint32_t a, uint32_t c) {
  asm volatile("mbarrier.init.shared::cta.b64 [%0], %1;" ::"r"(a), "r"(c));
}
__device__ __forceinline__ void mbar_expect(uint32_t a, uint32_t b) {
  asm volatile("mbarrier.arrive.expect_tx.shared::cta.b64 _, [%0], %1;" ::"r"(a), "r"(b) : "memory");
}
#define TS(k, i)
#define TSC(k, i)
#define TSM(k)
#define BSEG(i)
#define TB(k)
#define TRC(fl)
#define SPIN_LIMIT "4194304"
__device__ __forceinline__ void mbar_wait(uint32_t a, uint32_t parity) {
  asm volatile(
      "{\n.reg .pred p;\n.reg .u32 n;\n"
      "mbarrier.try_wait.parity.shared::cta.b64 p, [%0], %1;\n"
      "@p bra DONE;\n"
      "mov.u32 n, 0;\n"
      "LOOP:\n"
      "mbarrier.try_wait.parity.shared::cta.b64 p, [%0], %1;\n"
      "@p bra DONE;\n"
      "add.u32 n, n, 1;\n"
      "setp.lt.u32 p, n, " SPIN_LIMIT ";\n"
      "@p bra LOOP;\n"
      "DONE:\n}" ::"r"(a), "r"(parity) : "memory");
}
template <int NS>
__device__ __forceinline__ void mbar_wait_ns(uint32_t a, uint32_t parity) {
  asm volatile(
      "{\n.reg .pred p;\n.reg .u32 n;\n"
      "mov.u32 n, 0;\n"
      "LOOP:\n"
      "mbarrier.try_wait.parity.shared::cta.b64 p, [%0], %1, %2;\n"
      "@p bra DONE;\n"
      "add.u32 n, n, 1;\n"
      "setp.lt.u32 p, n, " SPIN_LIMIT ";\n"
      "@p bra LOOP;\n"
      "DONE:\n}" ::"r"(a), "r"(parity), "n"(NS) : "memory");
}
__device__ __forceinline__ void mbar_wait2(uint32_t a, uint32_t pa, uint32_t b, uint32_t pb) {
  asm volatile(
      "{\n.reg .pred p, q;\n.reg .u32 n;\n"
      "mov.u32 n, 0;\n"
      "LOOP:\n"
      "mbarrier.try_wait.parity.shared::cta.b64 p, [%0], %1;\n"
      "mbarrier.try_wait.parity.shared::cta.b64 q, [%2], %3;\n"
      "add.u32 n, n, 1;\n"
      "and.pred p, p, q;\n"
      "setp.lt.and.u32 p, n, " SPIN_LIMIT ", !p;\n"
      "@p bra LOOP;\n"
      "}" ::"r"(a), "r"(pa), "r"(b), "r"(pb) : "memory");
}
__device__ __forceinline__ uint32_t mbar_test(uint32_t a, uint32_t parity) {
  uint32_t r;
  asm volatile("{\n.reg .pred p;\nmbarrier.test_wait.parity.shared::cta.b64 p, [%1], %2;\nselp.u32 %0, 1, 0, p;\n}" : "=r"(r) : "r"(a), "r"(parity) : "memory");
  return r;
}
__device__ __forceinline__ void mbar_arrive(uint32_t a) {
  asm volatile("mbarrier.arrive.shared::cta.b64 _, [%0];" ::"r"(a) : "memory");
}
__device__ __forceinline__ void mbar_arrive_cluster(uint32_t a, uint32_t cta) {
  asm volatile("{\n.reg .b32 r;\nmapa.shared::cluster.u32 r, %0, %1;\nmbarrier.arrive.shared::cluster.b64 _, [r];\n}" ::"r"(a),
               "r"(cta) : "memory");
}
__device__ __forceinline__ void mbar_arrive_cluster_if(uint32_t a, uint32_t cta, bool pred) {
  asm volatile("{\n.reg .b32 r;\n.reg .pred p;\nsetp.ne.u32 p, %2, 0;\nmapa.shared::cluster.u32 r, %0, %1;\n@p mbarrier.arrive.shared::cluster.b64 _, [r];\n}" ::"r"(a),
               "r"(cta), "r"((uint32_t)pred) : "memory");
}
__device__ __forceinline__ void anchor(float v, uint32_t pred) {
  asm volatile("{\n.reg .pred p;\nsetp.ne.u32 p, %1, 0;\n@p st.shared.f32 [%1], %0;\n}" ::"f"(v), "r"(pred) : "memory");
}
__device__ __forceinline__ void mbar_arrive_if(uint32_t a, bool pred) {
  asm volatile("{\n.reg .pred p;\nsetp.ne.u32 p, %1, 0;\n@p mbarrier.arrive.shared::cta.b64 _, [%0];\n}" ::"r"(a), "r"((uint32_t)pred) : "memory");
}
__device__ __forceinline__ void tma2d(uint32_t dst, const CUtensorMap* m, uint32_t bar, int c0, int c1) {
  asm volatile("cp.async.bulk.tensor.2d.shared::cluster.global.mbarrier::complete_tx::bytes [%0], [%1, {%3, %4}], [%2];" ::"r"(dst),
               "l"(m), "r"(bar), "r"(c0), "r"(c1) : "memory");
}
__device__ __forceinline__ void tma2d_mc(uint32_t dst, const CUtensorMap* m, uint32_t bar, int c0, int c1, uint16_t mask) {
  asm volatile(
      "cp.async.bulk.tensor.2d.shared::cluster.global.mbarrier::complete_tx::bytes.multicast::cluster [%0], [%1, {%3, %4}], [%2], %5;" ::"r"(dst),
      "l"(m), "r"(bar), "r"(c0), "r"(c1), "h"(mask) : "memory");
}
__device__ __forceinline__ void tma3d_mc(uint32_t dst, const CUtensorMap* m, uint32_t bar, int c0, int c1, int c2, uint16_t mask) {
  asm volatile(
      "cp.async.bulk.tensor.3d.shared::cluster.global.mbarrier::complete_tx::bytes.multicast::cluster [%0], [%1, {%3, %4, %5}], [%2], %6;" ::"r"(dst),
      "l"(m), "r"(bar), "r"(c0), "r"(c1), "r"(c2), "h"(mask) : "memory");
}
__device__ __forceinline__ void tma3d(uint32_t dst, const CUtensorMap* m, uint32_t bar, int c0, int c1, int c2) {
  asm volatile(
      "cp.async.bulk.tensor.3d.shared::cluster.global.mbarrier::complete_tx::bytes [%0], [%1, {%3, %4, %5}], [%2];" ::"r"(dst),
      "l"(m), "r"(bar), "r"(c0), "r"(c1), "r"(c2) : "memory");
}
__device__ __forceinline__ void tma_pf2d(const CUtensorMap* m, int c0, int c1) {
  asm volatile("cp.async.bulk.prefetch.tensor.2d.L2.global [%0, {%1, %2}];" ::"l"(m), "r"(c0), "r"(c1) : "memory");
}
__device__ __forceinline__ void tma_pf3d(const CUtensorMap* m, int c0, int c1, int c2) {
  asm volatile("cp.async.bulk.prefetch.tensor.3d.L2.global [%0, {%1, %2, %3}];" ::"l"(m), "r"(c0), "r"(c1), "r"(c2) : "memory");
}
__device__ __forceinline__ void prefetch_tmap(const CUtensorMap* m) {
  asm volatile("prefetch.tensormap [%0];" ::"l"(m) : "memory");
}
__device__ __forceinline__ void cluster_arrive() { asm volatile("barrier.cluster.arrive.relaxed.aligned;" ::: "memory"); }
__device__ __forceinline__ void cluster_wait() { asm volatile("barrier.cluster.wait.aligned;" ::: "memory"); }
__device__ __forceinline__ void cluster_sync() {
  cluster_arrive();
  cluster_wait();
}
__device__ __forceinline__ uint32_t cluster_rank() {
  uint32_t r;
  asm volatile("mov.u32 %0, %%cluster_ctarank;" : "=r"(r));
  return r;
}
__device__ __forceinline__ bool elect_one() {
  uint32_t p;
  asm volatile("{\n.reg .pred q;\nelect.sync _|q, 0xffffffff;\nselp.u32 %0, 1, 0, q;\n}" : "=r"(p));
  return p;
}
__device__ __forceinline__ void ldsm_x4(uint32_t& r0, uint32_t& r1, uint32_t& r2, uint32_t& r3, uint32_t addr) {
  asm volatile("ldmatrix.sync.aligned.m8n8.x4.shared.b16 {%0, %1, %2, %3}, [%4];" : "=r"(r0), "=r"(r1), "=r"(r2), "=r"(r3) : "r"(addr) : "memory");
}
__device__ __forceinline__ void wg_fence() { asm volatile("wgmma.fence.sync.aligned;" ::: "memory"); }
__device__ __forceinline__ void wg_commit() { asm volatile("wgmma.commit_group.sync.aligned;" ::: "memory"); }
template <int N>
__device__ __forceinline__ void wg_wait() { asm volatile("wgmma.wait_group.sync.aligned %0;" ::"n"(N) : "memory"); }
template <int N>
__device__ __forceinline__ void reg_alloc() { asm volatile("setmaxnreg.inc.sync.aligned.u32 %0;" ::"n"(N)); }
template <int N>
__device__ __forceinline__ void reg_dealloc() { asm volatile("setmaxnreg.dec.sync.aligned.u32 %0;" ::"n"(N)); }
__device__ __forceinline__ void bar_sync(int id, int n) { asm volatile("bar.sync %0, %1;" ::"r"(id), "r"(n) : "memory"); }
__device__ __forceinline__ void bar_arrive(int id, int n) { asm volatile("bar.arrive %0, %1;" ::"r"(id), "r"(n) : "memory"); }
template <int NT>
__device__ __forceinline__ void fence_regs(float (&d)[NT]) {
#pragma unroll
  for (int i = 0; i < NT; i++) asm volatile("" : "+f"(d[i])::"memory");
}
template <int NT>
__device__ __forceinline__ void fence_regs(uint32_t (&d)[NT]) {
#pragma unroll
  for (int i = 0; i < NT; i++) asm volatile("" : "+r"(d[i])::"memory");
}
__device__ __forceinline__ uint64_t make_desc(uint32_t saddr, uint32_t lbo, uint32_t sbo, uint32_t layout) {
  return (uint64_t)((saddr & 0x3FFFF) >> 4) | ((uint64_t)(lbo >> 4) << 16) | ((uint64_t)(sbo >> 4) << 32) | ((uint64_t)layout << 62);
}
__device__ __forceinline__ uint32_t pack_bf16(float lo, float hi) {
  uint32_t r;
  asm("cvt.rn.bf16x2.f32 %0, %1, %2;" : "=r"(r) : "f"(hi), "f"(lo));
  return r;
}
__device__ __forceinline__ float ex2(float x) {
  float r;
  asm("ex2.approx.ftz.f32 %0, %1;" : "=f"(r) : "f"(x));
  return r;
}
__device__ __forceinline__ void st_v4(void* p, uint32_t a, uint32_t b, uint32_t c, uint32_t d) {
#define ST_MOD ".cs"
  asm volatile("st.global" ST_MOD ".v4.b32 [%0], {%1, %2, %3, %4};" ::"l"(p), "r"(a), "r"(b), "r"(c), "r"(d) : "memory");
}
#define STA_MOD ".cs"
__device__ __forceinline__ void st_v4a(void* p, uint32_t a, uint32_t b, uint32_t c, uint32_t d) {
  asm volatile("st.global" STA_MOD ".v4.b32 [%0], {%1, %2, %3, %4};" ::"l"(p), "r"(a), "r"(b), "r"(c), "r"(d) : "memory");
}
template <typename T>
__device__ __forceinline__ T* ptr_add(T* base, uint32_t bytes) {
  uint64_t r;
  asm volatile("{\n.reg .u32 l, h;\nmov.b64 {l, h}, %1;\nadd.cc.u32 l, l, %2;\naddc.u32 h, h, 0;\nmov.b64 %0, {l, h};\n}" : "=l"(r) : "l"(base), "r"(bytes));
  return reinterpret_cast<T*>(r);
}
__device__ __forceinline__ float bf_lo(uint32_t v) { return __uint_as_float(v << 16); }
__device__ __forceinline__ float bf_hi(uint32_t v) { return __uint_as_float(v & 0xFFFF0000u); }

__device__ __forceinline__ void quad_transpose(uint32_t& a0, uint32_t& a1, uint32_t& a2, uint32_t& a3, int q) {
  const bool o1 = q & 1, o2 = q & 2;
  uint32_t t0 = o1 ? a0 : a1, t1 = o1 ? a2 : a3;
  t0 = __shfl_xor_sync(0xffffffffu, t0, 1);
  t1 = __shfl_xor_sync(0xffffffffu, t1, 1);
  if (o1) { a0 = t0; a2 = t1; } else { a1 = t0; a3 = t1; }
  t0 = o2 ? a0 : a2;
  t1 = o2 ? a1 : a3;
  t0 = __shfl_xor_sync(0xffffffffu, t0, 2);
  t1 = __shfl_xor_sync(0xffffffffu, t1, 2);
  if (o2) { a0 = t0; a1 = t1; } else { a2 = t0; a3 = t1; }
}

template<int TB, int OFF, int NT>
__device__ __forceinline__ void wgmma_ss_n256(float (&d)[NT], uint64_t da, uint64_t db, int scale_d) {
  asm volatile("{\n.reg .pred p;\nsetp.ne.b32 p, %130, 0;\n"
    "wgmma.mma_async.sync.aligned.m64n256k16.f32.bf16.bf16 {%0, %1, %2, %3, %4, %5, %6, %7, %8, %9, %10, %11, %12, %13, %14, %15, %16, %17, %18, %19, %20, %21, %22, %23, %24, %25, %26, %27, %28, %29, %30, %31, %32, %33, %34, %35, %36, %37, %38, %39, %40, %41, %42, %43, %44, %45, %46, %47, %48, %49, %50, %51, %52, %53, %54, %55, %56, %57, %58, %59, %60, %61, %62, %63, %64, %65, %66, %67, %68, %69, %70, %71, %72, %73, %74, %75, %76, %77, %78, %79, %80, %81, %82, %83, %84, %85, %86, %87, %88, %89, %90, %91, %92, %93, %94, %95, %96, %97, %98, %99, %100, %101, %102, %103, %104, %105, %106, %107, %108, %109, %110, %111, %112, %113, %114, %115, %116, %117, %118, %119, %120, %121, %122, %123, %124, %125, %126, %127}, %128, %129, p, 1, 1, 0, %131;\n}\n"
    : "+f"(d[OFF+0]), "+f"(d[OFF+1]), "+f"(d[OFF+2]), "+f"(d[OFF+3]), "+f"(d[OFF+4]), "+f"(d[OFF+5]), "+f"(d[OFF+6]), "+f"(d[OFF+7]), "+f"(d[OFF+8]), "+f"(d[OFF+9]), "+f"(d[OFF+10]), "+f"(d[OFF+11]), "+f"(d[OFF+12]), "+f"(d[OFF+13]), "+f"(d[OFF+14]), "+f"(d[OFF+15]), "+f"(d[OFF+16]), "+f"(d[OFF+17]), "+f"(d[OFF+18]), "+f"(d[OFF+19]), "+f"(d[OFF+20]), "+f"(d[OFF+21]), "+f"(d[OFF+22]), "+f"(d[OFF+23]), "+f"(d[OFF+24]), "+f"(d[OFF+25]), "+f"(d[OFF+26]), "+f"(d[OFF+27]), "+f"(d[OFF+28]), "+f"(d[OFF+29]), "+f"(d[OFF+30]), "+f"(d[OFF+31]), "+f"(d[OFF+32]), "+f"(d[OFF+33]), "+f"(d[OFF+34]), "+f"(d[OFF+35]), "+f"(d[OFF+36]), "+f"(d[OFF+37]), "+f"(d[OFF+38]), "+f"(d[OFF+39]), "+f"(d[OFF+40]), "+f"(d[OFF+41]), "+f"(d[OFF+42]), "+f"(d[OFF+43]), "+f"(d[OFF+44]), "+f"(d[OFF+45]), "+f"(d[OFF+46]), "+f"(d[OFF+47]), "+f"(d[OFF+48]), "+f"(d[OFF+49]), "+f"(d[OFF+50]), "+f"(d[OFF+51]), "+f"(d[OFF+52]), "+f"(d[OFF+53]), "+f"(d[OFF+54]), "+f"(d[OFF+55]), "+f"(d[OFF+56]), "+f"(d[OFF+57]), "+f"(d[OFF+58]), "+f"(d[OFF+59]), "+f"(d[OFF+60]), "+f"(d[OFF+61]), "+f"(d[OFF+62]), "+f"(d[OFF+63]), "+f"(d[OFF+64]), "+f"(d[OFF+65]), "+f"(d[OFF+66]), "+f"(d[OFF+67]), "+f"(d[OFF+68]), "+f"(d[OFF+69]), "+f"(d[OFF+70]), "+f"(d[OFF+71]), "+f"(d[OFF+72]), "+f"(d[OFF+73]), "+f"(d[OFF+74]), "+f"(d[OFF+75]), "+f"(d[OFF+76]), "+f"(d[OFF+77]), "+f"(d[OFF+78]), "+f"(d[OFF+79]), "+f"(d[OFF+80]), "+f"(d[OFF+81]), "+f"(d[OFF+82]), "+f"(d[OFF+83]), "+f"(d[OFF+84]), "+f"(d[OFF+85]), "+f"(d[OFF+86]), "+f"(d[OFF+87]), "+f"(d[OFF+88]), "+f"(d[OFF+89]), "+f"(d[OFF+90]), "+f"(d[OFF+91]), "+f"(d[OFF+92]), "+f"(d[OFF+93]), "+f"(d[OFF+94]), "+f"(d[OFF+95]), "+f"(d[OFF+96]), "+f"(d[OFF+97]), "+f"(d[OFF+98]), "+f"(d[OFF+99]), "+f"(d[OFF+100]), "+f"(d[OFF+101]), "+f"(d[OFF+102]), "+f"(d[OFF+103]), "+f"(d[OFF+104]), "+f"(d[OFF+105]), "+f"(d[OFF+106]), "+f"(d[OFF+107]), "+f"(d[OFF+108]), "+f"(d[OFF+109]), "+f"(d[OFF+110]), "+f"(d[OFF+111]), "+f"(d[OFF+112]), "+f"(d[OFF+113]), "+f"(d[OFF+114]), "+f"(d[OFF+115]), "+f"(d[OFF+116]), "+f"(d[OFF+117]), "+f"(d[OFF+118]), "+f"(d[OFF+119]), "+f"(d[OFF+120]), "+f"(d[OFF+121]), "+f"(d[OFF+122]), "+f"(d[OFF+123]), "+f"(d[OFF+124]), "+f"(d[OFF+125]), "+f"(d[OFF+126]), "+f"(d[OFF+127])
    : "l"(da), "l"(db), "r"(scale_d), "n"(TB));
}
template<int TB, int OFF, int NT>
__device__ __forceinline__ void wgmma_ss_n32(float (&d)[NT], uint64_t da, uint64_t db, int scale_d) {
  asm volatile("{\n.reg .pred p;\nsetp.ne.b32 p, %18, 0;\n"
    "wgmma.mma_async.sync.aligned.m64n32k16.f32.bf16.bf16 {%0, %1, %2, %3, %4, %5, %6, %7, %8, %9, %10, %11, %12, %13, %14, %15}, %16, %17, p, 1, 1, 0, %19;\n}\n"
    : "+f"(d[OFF+0]), "+f"(d[OFF+1]), "+f"(d[OFF+2]), "+f"(d[OFF+3]), "+f"(d[OFF+4]), "+f"(d[OFF+5]), "+f"(d[OFF+6]), "+f"(d[OFF+7]), "+f"(d[OFF+8]), "+f"(d[OFF+9]), "+f"(d[OFF+10]), "+f"(d[OFF+11]), "+f"(d[OFF+12]), "+f"(d[OFF+13]), "+f"(d[OFF+14]), "+f"(d[OFF+15])
    : "l"(da), "l"(db), "r"(scale_d), "n"(TB));
}
template<int TB, int OFF, int NT>
__device__ __forceinline__ void wgmma_rs_n128(float (&d)[NT], uint32_t a0, uint32_t a1, uint32_t a2, uint32_t a3, uint64_t db, int scale_d) {
  asm volatile("{\n.reg .pred p;\nsetp.ne.b32 p, %69, 0;\n"
    "wgmma.mma_async.sync.aligned.m64n128k16.f32.bf16.bf16 {%0, %1, %2, %3, %4, %5, %6, %7, %8, %9, %10, %11, %12, %13, %14, %15, %16, %17, %18, %19, %20, %21, %22, %23, %24, %25, %26, %27, %28, %29, %30, %31, %32, %33, %34, %35, %36, %37, %38, %39, %40, %41, %42, %43, %44, %45, %46, %47, %48, %49, %50, %51, %52, %53, %54, %55, %56, %57, %58, %59, %60, %61, %62, %63}, {%64, %65, %66, %67}, %68, p, 1, 1, %70;\n}\n"
    : "+f"(d[OFF+0]), "+f"(d[OFF+1]), "+f"(d[OFF+2]), "+f"(d[OFF+3]), "+f"(d[OFF+4]), "+f"(d[OFF+5]), "+f"(d[OFF+6]), "+f"(d[OFF+7]), "+f"(d[OFF+8]), "+f"(d[OFF+9]), "+f"(d[OFF+10]), "+f"(d[OFF+11]), "+f"(d[OFF+12]), "+f"(d[OFF+13]), "+f"(d[OFF+14]), "+f"(d[OFF+15]), "+f"(d[OFF+16]), "+f"(d[OFF+17]), "+f"(d[OFF+18]), "+f"(d[OFF+19]), "+f"(d[OFF+20]), "+f"(d[OFF+21]), "+f"(d[OFF+22]), "+f"(d[OFF+23]), "+f"(d[OFF+24]), "+f"(d[OFF+25]), "+f"(d[OFF+26]), "+f"(d[OFF+27]), "+f"(d[OFF+28]), "+f"(d[OFF+29]), "+f"(d[OFF+30]), "+f"(d[OFF+31]), "+f"(d[OFF+32]), "+f"(d[OFF+33]), "+f"(d[OFF+34]), "+f"(d[OFF+35]), "+f"(d[OFF+36]), "+f"(d[OFF+37]), "+f"(d[OFF+38]), "+f"(d[OFF+39]), "+f"(d[OFF+40]), "+f"(d[OFF+41]), "+f"(d[OFF+42]), "+f"(d[OFF+43]), "+f"(d[OFF+44]), "+f"(d[OFF+45]), "+f"(d[OFF+46]), "+f"(d[OFF+47]), "+f"(d[OFF+48]), "+f"(d[OFF+49]), "+f"(d[OFF+50]), "+f"(d[OFF+51]), "+f"(d[OFF+52]), "+f"(d[OFF+53]), "+f"(d[OFF+54]), "+f"(d[OFF+55]), "+f"(d[OFF+56]), "+f"(d[OFF+57]), "+f"(d[OFF+58]), "+f"(d[OFF+59]), "+f"(d[OFF+60]), "+f"(d[OFF+61]), "+f"(d[OFF+62]), "+f"(d[OFF+63])
    : "r"(a0), "r"(a1), "r"(a2), "r"(a3), "l"(db), "r"(scale_d), "n"(TB));
}
template<int TB, int OFF, int NT>
__device__ __forceinline__ void wgmma_rs_n256(float (&d)[NT], uint32_t a0, uint32_t a1, uint32_t a2, uint32_t a3, uint64_t db, int scale_d) {
  asm volatile("{\n.reg .pred p;\nsetp.ne.b32 p, %133, 0;\n"
    "wgmma.mma_async.sync.aligned.m64n256k16.f32.bf16.bf16 {%0, %1, %2, %3, %4, %5, %6, %7, %8, %9, %10, %11, %12, %13, %14, %15, %16, %17, %18, %19, %20, %21, %22, %23, %24, %25, %26, %27, %28, %29, %30, %31, %32, %33, %34, %35, %36, %37, %38, %39, %40, %41, %42, %43, %44, %45, %46, %47, %48, %49, %50, %51, %52, %53, %54, %55, %56, %57, %58, %59, %60, %61, %62, %63, %64, %65, %66, %67, %68, %69, %70, %71, %72, %73, %74, %75, %76, %77, %78, %79, %80, %81, %82, %83, %84, %85, %86, %87, %88, %89, %90, %91, %92, %93, %94, %95, %96, %97, %98, %99, %100, %101, %102, %103, %104, %105, %106, %107, %108, %109, %110, %111, %112, %113, %114, %115, %116, %117, %118, %119, %120, %121, %122, %123, %124, %125, %126, %127}, {%128, %129, %130, %131}, %132, p, 1, 1, %134;\n}\n"
    : "+f"(d[OFF+0]), "+f"(d[OFF+1]), "+f"(d[OFF+2]), "+f"(d[OFF+3]), "+f"(d[OFF+4]), "+f"(d[OFF+5]), "+f"(d[OFF+6]), "+f"(d[OFF+7]), "+f"(d[OFF+8]), "+f"(d[OFF+9]), "+f"(d[OFF+10]), "+f"(d[OFF+11]), "+f"(d[OFF+12]), "+f"(d[OFF+13]), "+f"(d[OFF+14]), "+f"(d[OFF+15]), "+f"(d[OFF+16]), "+f"(d[OFF+17]), "+f"(d[OFF+18]), "+f"(d[OFF+19]), "+f"(d[OFF+20]), "+f"(d[OFF+21]), "+f"(d[OFF+22]), "+f"(d[OFF+23]), "+f"(d[OFF+24]), "+f"(d[OFF+25]), "+f"(d[OFF+26]), "+f"(d[OFF+27]), "+f"(d[OFF+28]), "+f"(d[OFF+29]), "+f"(d[OFF+30]), "+f"(d[OFF+31]), "+f"(d[OFF+32]), "+f"(d[OFF+33]), "+f"(d[OFF+34]), "+f"(d[OFF+35]), "+f"(d[OFF+36]), "+f"(d[OFF+37]), "+f"(d[OFF+38]), "+f"(d[OFF+39]), "+f"(d[OFF+40]), "+f"(d[OFF+41]), "+f"(d[OFF+42]), "+f"(d[OFF+43]), "+f"(d[OFF+44]), "+f"(d[OFF+45]), "+f"(d[OFF+46]), "+f"(d[OFF+47]), "+f"(d[OFF+48]), "+f"(d[OFF+49]), "+f"(d[OFF+50]), "+f"(d[OFF+51]), "+f"(d[OFF+52]), "+f"(d[OFF+53]), "+f"(d[OFF+54]), "+f"(d[OFF+55]), "+f"(d[OFF+56]), "+f"(d[OFF+57]), "+f"(d[OFF+58]), "+f"(d[OFF+59]), "+f"(d[OFF+60]), "+f"(d[OFF+61]), "+f"(d[OFF+62]), "+f"(d[OFF+63]), "+f"(d[OFF+64]), "+f"(d[OFF+65]), "+f"(d[OFF+66]), "+f"(d[OFF+67]), "+f"(d[OFF+68]), "+f"(d[OFF+69]), "+f"(d[OFF+70]), "+f"(d[OFF+71]), "+f"(d[OFF+72]), "+f"(d[OFF+73]), "+f"(d[OFF+74]), "+f"(d[OFF+75]), "+f"(d[OFF+76]), "+f"(d[OFF+77]), "+f"(d[OFF+78]), "+f"(d[OFF+79]), "+f"(d[OFF+80]), "+f"(d[OFF+81]), "+f"(d[OFF+82]), "+f"(d[OFF+83]), "+f"(d[OFF+84]), "+f"(d[OFF+85]), "+f"(d[OFF+86]), "+f"(d[OFF+87]), "+f"(d[OFF+88]), "+f"(d[OFF+89]), "+f"(d[OFF+90]), "+f"(d[OFF+91]), "+f"(d[OFF+92]), "+f"(d[OFF+93]), "+f"(d[OFF+94]), "+f"(d[OFF+95]), "+f"(d[OFF+96]), "+f"(d[OFF+97]), "+f"(d[OFF+98]), "+f"(d[OFF+99]), "+f"(d[OFF+100]), "+f"(d[OFF+101]), "+f"(d[OFF+102]), "+f"(d[OFF+103]), "+f"(d[OFF+104]), "+f"(d[OFF+105]), "+f"(d[OFF+106]), "+f"(d[OFF+107]), "+f"(d[OFF+108]), "+f"(d[OFF+109]), "+f"(d[OFF+110]), "+f"(d[OFF+111]), "+f"(d[OFF+112]), "+f"(d[OFF+113]), "+f"(d[OFF+114]), "+f"(d[OFF+115]), "+f"(d[OFF+116]), "+f"(d[OFF+117]), "+f"(d[OFF+118]), "+f"(d[OFF+119]), "+f"(d[OFF+120]), "+f"(d[OFF+121]), "+f"(d[OFF+122]), "+f"(d[OFF+123]), "+f"(d[OFF+124]), "+f"(d[OFF+125]), "+f"(d[OFF+126]), "+f"(d[OFF+127])
    : "r"(a0), "r"(a1), "r"(a2), "r"(a3), "l"(db), "r"(scale_d), "n"(TB));
}
template<int TB, int OFF, int NT>
__device__ __forceinline__ void wgmma_rs_n32(float (&d)[NT], uint32_t a0, uint32_t a1, uint32_t a2, uint32_t a3, uint64_t db, int scale_d) {
  asm volatile("{\n.reg .pred p;\nsetp.ne.b32 p, %21, 0;\n"
    "wgmma.mma_async.sync.aligned.m64n32k16.f32.bf16.bf16 {%0, %1, %2, %3, %4, %5, %6, %7, %8, %9, %10, %11, %12, %13, %14, %15}, {%16, %17, %18, %19}, %20, p, 1, 1, %22;\n}\n"
    : "+f"(d[OFF+0]), "+f"(d[OFF+1]), "+f"(d[OFF+2]), "+f"(d[OFF+3]), "+f"(d[OFF+4]), "+f"(d[OFF+5]), "+f"(d[OFF+6]), "+f"(d[OFF+7]), "+f"(d[OFF+8]), "+f"(d[OFF+9]), "+f"(d[OFF+10]), "+f"(d[OFF+11]), "+f"(d[OFF+12]), "+f"(d[OFF+13]), "+f"(d[OFF+14]), "+f"(d[OFF+15])
    : "r"(a0), "r"(a1), "r"(a2), "r"(a3), "l"(db), "r"(scale_d), "n"(TB));
}

__device__ __forceinline__ void wait_flag(const unsigned int* f, uint32_t target) {
  uint32_t v;
#pragma unroll 1
  for (uint32_t spins = 0; spins < (1u << 22); spins++) {
    asm volatile("ld.acquire.gpu.global.u32 %0, [%1];" : "=r"(v) : "l"(f) : "memory");
    if (v >= target) break;
    __nanosleep(100);
  }
}
__device__ __forceinline__ uint32_t lds32(uint32_t a) {
  uint32_t v;
  asm volatile("ld.shared.u32 %0, [%1];" : "=r"(v) : "r"(a) : "memory");
  return v;
}
__device__ __forceinline__ float gate_row(int row, int lane, const bf16* __restrict__ x, const bf16* __restrict__ gate_w) {
  const uint32_t* xr = reinterpret_cast<const uint32_t*>(x + (size_t)row * DM);
  const uint32_t* gw2 = reinterpret_cast<const uint32_t*>(gate_w);
  float gs = 0.f;
#pragma unroll
  for (int i = 0; i < 9; i++) {
    const uint32_t a = __ldg(xr + lane + 32 * i), b = __ldg(gw2 + lane + 32 * i);
    gs = fmaf(bf_lo(a), bf_lo(b), gs);
    gs = fmaf(bf_hi(a), bf_hi(b), gs);
  }
#pragma unroll
  for (int o = 16; o; o >>= 1) gs += __shfl_xor_sync(0xffffffffu, gs, o);
  const float g = 1.f / (1.f + __expf(-gs));
  if (lane == 0) g_gate[row] = g;
  return g;
}
constexpr uint32_t LQ = 36864, LV = 55296;
__device__ __forceinline__ void mma16(float (&c)[4], uint32_t a0, uint32_t a1, uint32_t a2, uint32_t a3, uint32_t b0, uint32_t b1) {
  asm("mma.sync.aligned.m16n8k16.row.col.f32.bf16.bf16.f32 {%0, %1, %2, %3}, {%4, %5, %6, %7}, {%8, %9}, {%0, %1, %2, %3};"
      : "+f"(c[0]), "+f"(c[1]), "+f"(c[2]), "+f"(c[3]) : "r"(a0), "r"(a1), "r"(a2), "r"(a3), "r"(b0), "r"(b1));
}
__device__ __forceinline__ void mma8(float (&c)[4], uint32_t a0, uint32_t a1, uint32_t b0) {
  asm("mma.sync.aligned.m16n8k8.row.col.f32.bf16.bf16.f32 {%0, %1, %2, %3}, {%4, %5}, {%6}, {%0, %1, %2, %3};"
      : "+f"(c[0]), "+f"(c[1]), "+f"(c[2]), "+f"(c[3]) : "r"(a0), "r"(a1), "r"(b0));
}
template <typename F>
__device__ __forceinline__ void local_attn(int lr0, int warp_g, uint32_t sL, uint32_t bL, uint32_t bL2, int lane, float g0, float g1, F st) {
  const float scale_l2 = 0.23570226039551584f * 1.4426950408889634f;
  const int g = lane >> 2, t = lane & 3;
  const bool lo0 = 2 * t > g, lo1 = 2 * t + 1 > g;
  const uint32_t mlo = (lo0 ? 0xFFFFu : 0u) | (lo1 ? 0xFFFF0000u : 0u);
  const bool ok0 = lr0 > 0 || !lo0, ok1 = lr0 > 0 || !lo1;
  uint32_t ad[9], k[9][4], qf[9][2], pe[4], po[4];
#pragma unroll
  for (int c = 0; c < 9; c++) {
    const uint32_t ch = warp_g * 9 + c;
    ad[c] = sL + (lane >> 4) * 18432 + (lane & 15) * 128 + ((ch >> 3) << 11) + (((ch ^ lane) & 7) << 4);
  }
  st(0, 0u); st(1, 0u);
  mbar_wait(bL, 0);
  if (warp_g == 0) TS(1, 6);
#pragma unroll
  for (int c = 0; c < 9; c++) {
    asm volatile("ldmatrix.sync.aligned.m8n8.x2.shared.b16 {%0, %1}, [%2];" : "=r"(qf[c][0]), "=r"(qf[c][1]) : "r"(ad[c] + LQ) : "memory");
    ldsm_x4(k[c][0], k[c][1], k[c][2], k[c][3], ad[c]);
  }
  st(2, k[0][0]); st(3, k[8][0]);
#pragma unroll
  for (int i = 0; i < 4; i++) {
    const uint32_t q0 = (t >= i) ? qf[2 * i][0] : 0u, q1 = (t >= i) ? qf[2 * i][1] : 0u;
    const uint32_t q4 = (t <= i) ? qf[2 * i + 2][0] : 0u, q5 = (t <= i) ? qf[2 * i + 2][1] : 0u;
    float c[4][4];
#pragma unroll
    for (int T = 0; T < 4; T++) {
#pragma unroll
      for (int j = 0; j < 4; j++) c[T][j] = 0.f;
      mma16(c[T], q0, q1, qf[2 * i + 1][0], qf[2 * i + 1][1], k[2 * i][T], k[2 * i + 1][T]);
      mma8(c[T], q4, q5, k[2 * i + 2][T]);
    }
    const float e0 = ok0 ? (lo0 ? c[0][0] : c[1][0]) : -INFINITY, e1 = ok1 ? (lo1 ? c[0][1] : c[1][1]) : -INFINITY;
    const float o0 = ok0 ? (lo0 ? c[2][2] : c[3][2]) : -INFINITY, o1 = ok1 ? (lo1 ? c[2][3] : c[3][3]) : -INFINITY;
    float me = fmaxf(e0, e1), mo = fmaxf(o0, o1);
    me = fmaxf(me, __shfl_xor_sync(0xffffffffu, me, 1));
    mo = fmaxf(mo, __shfl_xor_sync(0xffffffffu, mo, 1));
    me = fmaxf(me, __shfl_xor_sync(0xffffffffu, me, 2)) * scale_l2;
    mo = fmaxf(mo, __shfl_xor_sync(0xffffffffu, mo, 2)) * scale_l2;
    const float w0 = ex2(fmaf(e0, scale_l2, -me)), w1 = ex2(fmaf(e1, scale_l2, -me));
    const float w2 = ex2(fmaf(o0, scale_l2, -mo)), w3 = ex2(fmaf(o1, scale_l2, -mo));
    float se = w0 + w1, so = w2 + w3;
    st(4 + 2 * i, __float_as_uint(i == 1 ? me : i == 2 ? se : e0));
    se += __shfl_xor_sync(0xffffffffu, se, 1);
    so += __shfl_xor_sync(0xffffffffu, so, 1);
    se += __shfl_xor_sync(0xffffffffu, se, 2);
    so += __shfl_xor_sync(0xffffffffu, so, 2);
    asm("rcp.approx.ftz.f32 %0, %0;" : "+f"(se));
    asm("rcp.approx.ftz.f32 %0, %0;" : "+f"(so));
    se *= g0;
    so *= g1;
    pe[i] = pack_bf16(w0 * se, w1 * se);
    po[i] = pack_bf16(w2 * so, w3 * so);
    st(5 + 2 * i, i == 0 ? __float_as_uint(w0) : i == 2 ? __float_as_uint(mo) : po[i]);
  }
  if (warp_g == 0) TS(0, 4);
  mbar_wait(bL2, 0);
  if (warp_g == 0) TS(0, 5);
#pragma unroll
  for (int c = 0; c < 9; c++)
    asm volatile("ldmatrix.sync.aligned.m8n8.x4.trans.shared.b16 {%0, %1, %2, %3}, [%4];"
                 : "=r"(k[c][0]), "=r"(k[c][1]), "=r"(k[c][2]), "=r"(k[c][3]) : "r"(ad[c] + LV) : "memory");
#pragma unroll
  for (int i = 0; i < 4; i++) {
#pragma unroll
    for (int n = 0; n < 3; n++) {
      float c[4] = {0.f, 0.f, 0.f, 0.f};
      mma16(c, pe[i] & mlo, 0u, pe[i] & ~mlo, 0u, k[2 * i + n][0], k[2 * i + n][1]);
      mma16(c, 0u, po[i] & mlo, 0u, po[i] & ~mlo, k[2 * i + n][2], k[2 * i + n][3]);
      const uint32_t r0 = pack_bf16(c[0], c[1]), r1 = pack_bf16(c[2], c[3]);
      const bool keep = (n == 0) && (t < i);
      qf[2 * i + n][0] = keep ? qf[2 * i + n][0] : r0;
      qf[2 * i + n][1] = keep ? qf[2 * i + n][1] : r1;
    }
    st(12 + i, qf[2 * i + 1][0]);
  }
#pragma unroll
  for (int c = 0; c < 9; c++)
    asm volatile("stmatrix.sync.aligned.m8n8.x2.shared.b16 [%0], {%1, %2};" ::"r"(ad[c] + LQ), "r"(qf[c][0]), "r"(qf[c][1]) : "memory");
  asm volatile("fence.proxy.async.shared::cta;" ::: "memory");
}
__device__ __forceinline__ void tma4d(uint32_t dst, const CUtensorMap* m, uint32_t bar, int c1, int c2, int c3) {
  asm volatile("cp.async.bulk.tensor.4d.shared::cluster.global.mbarrier::complete_tx::bytes [%0], [%1, {%3, %4, %5, %6}], [%2];" ::"r"(dst),
               "l"(m), "r"(bar), "r"(0), "r"(c1), "r"(c2), "r"(c3) : "memory");
}

#define ST_NUM 1
#define ST_DEN 2
#define K1_NST 6
constexpr int K1_BST = K1_NST;
#define MAXJ 11
constexpr int K1_MAXJOBS = MAXJ;
constexpr uint32_t K1_FLAG_TARGET = 7;
constexpr uint32_t RDY_TARGET = 48;
constexpr uint32_t GATE_TARGET = 128 * 3;
struct alignas(64) Params {
  CUtensorMap tmA[2];
  CUtensorMap tmW[4];
  CUtensorMap tmK, tmV;
  CUtensorMap tmL[3];
  CUtensorMap tmC, tmO[2], tmOt[2];
  uint16_t jobs[NCLUSTER][K1_MAXJOBS + 1];
  uint8_t order[256];
  uint8_t unit[64][8];
};

struct K1State {
  uint32_t bs, bph, aph;
  bf16 *pp, *pp8;
  int png;
  int tn;
  int wsel;
};
__device__ __forceinline__ void k1_flag(const K1State& st, int lane, uint32_t bS) {
  if (st.png) {
    __syncwarp();
    if (lane == 0) mbar_arrive(bS);
  }
}

__device__ __forceinline__ void scale_q4(uint32_t* v) {
#pragma unroll
  for (int i = 0; i < 4; i++)
    asm volatile("{\n.reg .b32 t;\nmul.rn.bf16x2 t, %0, %2;\nfma.rn.bf16x2 %0, %0, %1, t;\n}" : "+r"(v[i]) : "r"(0x3E033E03u), "r"(0xB9D8B9D8u));
}
__device__ __forceinline__ void k1_first(const K1State& st, uint32_t job, uint32_t bAf, uint32_t bBf) {
  if (job & 3) {
    if ((job >> 14) & 1) mbar_wait(bAf, st.aph);
    mbar_wait(bBf + st.bs * 8, st.bph);
  }
}
__device__ __forceinline__ void k1_tile(float (&acc)[128], uint32_t (&pk)[64], K1State& st, uint32_t job, uint32_t njob, uint32_t sA, uint32_t sB,
                                        uint32_t bAf, uint32_t bAe, uint32_t bBf, uint32_t bBe, uint32_t bS, int wg, int warp, int lane, uint32_t rank) {
  const int a_sel = (job >> 2) & 1, mpair = (job >> 3) & 7, w_sel = (job >> 6) & 3, chunk0 = (job >> 8) & 63;
  const bool newA = (job >> 14) & 1, lastA = (job >> 15) & 1;
  const bool sig = (lane == 0) && (warp < 2);
  const bool siga = lastA && (lane == 0) && (warp == 2);
  const int KC = 8 + a_sel;
  uint32_t prev_bs = 0, a8_bs = 0;
#pragma unroll
  for (int kc = 0; kc < 9; kc++) {
    if (kc >= KC) break;
    uint32_t abase = sA + ((kc + 2) & 7) * 16384;
    if (kc == 8) {
      mbar_wait(bBf + st.bs * 8, st.bph);
      a8_bs = st.bs;
      abase = sB + st.bs * 16384;
      if (++st.bs == K1_BST) { st.bs = 0; st.bph ^= 1; }
    } else if (newA && kc > 0) {
      mbar_wait(bAf + kc * 8, st.aph);
    }
    const uint64_t da = make_desc(abase + wg * 8192, 16, 1024, 1);
#pragma unroll
    for (int ks = 0; ks < 2; ks++) {
      if (ks > 0 || kc > 0) mbar_wait(bBf + st.bs * 8, st.bph);
      const uint64_t db = make_desc(sB + st.bs * 16384, 2048, 1024, 1);
      wg_fence();
      wgmma_ss_n256<1, 0>(acc, da + (uint64_t)(ks * 4), db, (ks > 0) ? 1 : (kc > 0));
      wgmma_ss_n256<1, 0>(acc, da + (uint64_t)(ks * 4 + 2), db + (uint64_t)512, 1);
      wg_commit();
      wg_wait<1>();
      if (ks > 0 || kc > 0) {
        if (sig) mbar_arrive_cluster(bBe + prev_bs * 8, warp);
        if (ks == 0 && siga) mbar_arrive(bAe + (kc - 1) * 8);
      }
      if (st.wsel == 2) {
        const int i = (kc & 7) * 2 + ks;
        if (kc < st.png) {
          quad_transpose(pk[i * 4], pk[i * 4 + 1], pk[i * 4 + 2], pk[i * 4 + 3], lane & 3);
          st_v4a((ks ? st.pp8 : st.pp) + kc * 32, pk[i * 4], pk[i * 4 + 1], pk[i * 4 + 2], pk[i * 4 + 3]);
        }
        if (i == 15) k1_flag(st, lane, bS);
      } else if (st.png) {
#pragma unroll
        for (int i = 0; i < 16; i++) {
          if (i * ST_NUM / ST_DEN != kc * 2 + ks) continue;
          if (st.wsel == 3) scale_q4(pk + i * 4);
          st_v4a(((i & 1) ? st.pp8 : st.pp) + (i / 2) * 32, pk[i * 4], pk[i * 4 + 1], pk[i * 4 + 2], pk[i * 4 + 3]);
          if (i == 15) k1_flag(st, lane, bS);
        }
      }
      prev_bs = st.bs;
      if (++st.bs == K1_BST) { st.bs = 0; st.bph ^= 1; }
    }
  }
  if (newA) st.aph ^= 1;
  const bool isA = (w_sel == 2);
  bf16* out = (w_sel == 0) ? g_K : (w_sel == 1) ? g_V : isA ? g_QKVA : g_ctx;
  const int ld = isA ? NQKVA : (w_sel == 3) ? KCAT : HDIM;
  const int row = mpair * 256 + rank * 128 + wg * 64 + warp * 16 + (lane >> 2);
  st.pp = ptr_add(out, (row * ld + chunk0 * 64 + (lane & 3) * 8) * 2);
  st.pp8 = ptr_add(st.pp, 16 * ld);
  st.png = ((job & 3) + 1) * 2;
  st.wsel = w_sel;
  k1_first(st, njob, bAf, bBf);
  wg_wait<0>();
  fence_regs(acc);
  mbar_arrive_cluster_if(bBe + prev_bs * 8, warp & 1, sig);
  mbar_arrive_cluster_if(bBe + a8_bs * 8, warp & 1, sig && a_sel);
  mbar_arrive_if(bAe + 7 * 8, siga && !a_sel);
#pragma unroll
  for (int i = 0; i < 64; i++) {
    const int j = (i >> 3) * 16 + (i & 3) * 4 + ((i >> 2) & 1) * 2;
    pk[i] = pack_bf16(acc[j], acc[j + 1]);
  }
}

constexpr int K2_NST = 7;
constexpr uint32_t K2_END = 0x100;
#define PFD 4
#define FIRST_DRAW 3
#define PWAIT mbar_wait_ns<1000>
#define PVM 0x8A
#define W0 63
#define SPEC_HI 1.8446744073709552e19f
#define SPEC_LO 5.421010862427522e-20f
constexpr int K3_NST = 4;
__device__ __forceinline__ uint32_t k3_rot(uint32_t sv) { return (0x00E9u >> (2 * sv)) & 3; }
constexpr int K3_STAGE = 16384 + 32768 + 4096;
constexpr int SMEM_DATA = 7 * 32768;
constexpr int SMEM_BYTES = SMEM_DATA + 1024 + 768;

struct Cursor {
  uint32_t s, ph;
  __device__ __forceinline__ void next() {
    if (++s == K2_NST) { s = 0; ph ^= 1; }
  }
};

#define TURN_SYNC() bar_sync(mybar, 256)
#define TURN_ARRIVE() bar_arrive(otherbar, 256)
#define RELEASE_IF(cur, cond) mbar_arrive_cluster_if(bE + (cur).s * 8, warp & 1, sig && (cond))
#define RELEASE(cur) RELEASE_IF(cur, true)
#define ISSUE_PV(cur, first)                                                                                   \
  do {                                                                                                         \
    const uint64_t dv = make_desc(sbase + (cur).s * 32768, 16384, 1024, 1);                                    \
    _Pragma("unroll") for (int t = 0; t < 8; t++)                                                              \
        wgmma_rs_n128<1, 0>(O, P[4 * t], P[4 * t + 1], P[4 * t + 2], P[4 * t + 3], dv + (uint64_t)(t * 128), (t > 0) ? 1 : !(first)); \
  } while (0)
#define ISSUE_QK(cur)                                                                                          \
  do {                                                                                                         \
    const uint64_t dk = make_desc(sbase + (cur).s * 32768, 16, 1024, 1);                                       \
    _Pragma("unroll") for (int t = 0; t < 8; t++)                                                              \
        wgmma_rs_n128<0, 0>(S, Q[4 * t], Q[4 * t + 1], Q[4 * t + 2], Q[4 * t + 3], dk + (uint64_t)((t >> 2) * 1024 + (t & 3) * 2), t > 0); \
  } while (0)
#define EXPB(T)                                                                                                \
  do {                                                                                                         \
    _Pragma("unroll") for (int i = 4 * T; i < 4 * T + 4; i++) asm volatile("" : "+r"(P[i])::"memory");        \
    _Pragma("unroll") for (int jj = 2 * T; jj < 2 * T + 2; jj++) {                                             \
      const float e0 = ex2(S[jj * 4 + 0]), e1 = ex2(S[jj * 4 + 1]), e2 = ex2(S[jj * 4 + 2]), e3 = ex2(S[jj * 4 + 3]); \
      s0 += e0 + e1;                                                                                           \
      s1 += e2 + e3;                                                                                           \
      P[jj * 2 + 0] = pack_bf16(e0, e1);                                                                       \
      P[jj * 2 + 1] = pack_bf16(e2, e3);                                                                       \
    }                                                                                                          \
  } while (0)
#define EXPC(T)                                                                                                \
  do {                                                                                                         \
    if (T > 0 && ((PVM >> (T - 1)) & 1)) {                                                                     \
      anchor((T & 2) ? s0 : s1, never);                                                                        \
      wg_wait<__builtin_popcount(PVM >> T) - 1>();                                                             \
      if ((PVM >> T) == (128 >> T)) { fence_regs(O); RELEASE(cv); }                                            \
    }                                                                                                          \
    EXPB(T);                                                                                                   \
  } while (0)
#define MASK(G, g)                                                                                             \
  do {                                                                                                         \
    if ((g) * 8 > d) S[(G) * 4 + 0] = -INFINITY;                                                               \
    if ((g) * 8 + 1 > d) S[(G) * 4 + 1] = -INFINITY;                                                           \
    if ((g) * 8 - 8 > d) S[(G) * 4 + 2] = -INFINITY;                                                           \
    if ((g) * 8 - 7 > d) S[(G) * 4 + 3] = -INFINITY;                                                           \
  } while (0)
#define STORE_O(G)                                                                                             \
  do {                                                                                                         \
    st_v4(optr + (G) * 32, pack_bf16(O[(G) * 16 + 0] * f0, O[(G) * 16 + 1] * f0), pack_bf16(O[(G) * 16 + 4] * f0, O[(G) * 16 + 5] * f0), \
          pack_bf16(O[(G) * 16 + 8] * f0, O[(G) * 16 + 9] * f0), pack_bf16(O[(G) * 16 + 12] * f0, O[(G) * 16 + 13] * f0)); \
    st_v4(optr + 8 * KCAT + (G) * 32, pack_bf16(O[(G) * 16 + 2] * f1, O[(G) * 16 + 3] * f1), pack_bf16(O[(G) * 16 + 6] * f1, O[(G) * 16 + 7] * f1), \
          pack_bf16(O[(G) * 16 + 10] * f1, O[(G) * 16 + 11] * f1), pack_bf16(O[(G) * 16 + 14] * f1, O[(G) * 16 + 15] * f1)); \
  } while (0)

#define FLUSH()                                                                                                \
  do {                                                                                                         \
    _Pragma("unroll") for (int G = 0; G < 8; G++) {                                                            \
      st_v4a(st.pp + G * 32, pk[G * 8], pk[G * 8 + 1], pk[G * 8 + 2], pk[G * 8 + 3]);                          \
      st_v4a(st.pp8 + G * 32, pk[G * 8 + 4], pk[G * 8 + 5], pk[G * 8 + 6], pk[G * 8 + 7]);                     \
    }                                                                                                          \
    k1_flag(st, lane, bS);                                                                                     \
  } while (0)

__global__ void __cluster_dims__(2, 1, 1) __launch_bounds__(384, 1)
fused_kernel(const __grid_constant__ Params p, const bf16* __restrict__ x, const bf16* __restrict__ gate_w, bf16* __restrict__ out) {
  extern __shared__ uint8_t smem_raw[];
  const uint32_t sbase = (smem_u32(smem_raw) + 1023) & ~1023u;
  const uint32_t sB = sbase, sA = sbase + K1_BST * 16384, sBar = sbase + SMEM_DATA;
  const uint32_t bAf = sBar, bAe = sBar + 64, bBf = sBar + 128, bBe = sBar + 176, bL = sBar + 224, bS = sBar + 232, bL2 = sBar + 240, sL = sA + 32768;
  const uint32_t bF = sBar + 256, bE = sBar + 320, bT = sBar + 384, sTick = sBar + 400, sItem = sBar + 416, bS2 = sBar + 448, bR = sBar + 456, bLast = sBar + 464, bH = sBar + 472, bT0 = sBar + 480;
  const uint32_t b3F = sBar + 512, b3E = sBar + 544, sGate = sBar + 576;
  const int tid = threadIdx.x, warp_g = __shfl_sync(0xffffffffu, tid >> 5, 0), lane = tid & 31;
  const uint32_t rank = cluster_rank();
  const int cl = blockIdx.x >> 1;
  TSM(0);
  if (tid == 0) {
    for (int i = 0; i < 8; i++) { mbar_init(bAf + i * 8, 1); mbar_init(bAe + i * 8, 2); }
    for (int i = 0; i < K1_BST; i++) { mbar_init(bBf + i * 8, 1); mbar_init(bBe + i * 8, 4); }
    mbar_init(bL, 1);
    mbar_init(bL2, 1);
    mbar_init(bR, 1);
    mbar_init(bLast, 1);
    mbar_init(bH, 4);
    mbar_init(bT0, 1);
    mbar_init(bS, 8);
    for (int i = 0; i < K2_NST; i++) { mbar_init(bF + i * 8, 1); mbar_init(bE + i * 8, 4); }
    mbar_init(bT, 1); mbar_init(bT + 8, 1);
    mbar_init(bS2, 8);
    for (int i = 0; i < K3_NST; i++) { mbar_init(b3F + i * 8, 1); mbar_init(b3E + i * 8, 4); }
    asm volatile("fence.mbarrier_init.release.cluster;" ::: "memory");
  }
  __syncwarp();
  if (warp_g != 8) cluster_sync();
  const int lr0 = blockIdx.x * 16;

  if (warp_g >= 8) {
    reg_dealloc<40>();
    if (warp_g == 8) {
      {
        const uint32_t job = p.jobs[cl][0];
        if (lane == 0) { prefetch_tmap(&p.tmA[(job >> 2) & 1]); prefetch_tmap(&p.tmW[(job >> 6) & 3]); }
        __syncwarp();
        cluster_sync();
      }
      if (elect_one()) {
        uint32_t bs = 0, bph = 1, aph = 1;
#pragma unroll 1
        for (int ji = 0; ji < K1_MAXJOBS; ji++) {
          const uint32_t job = p.jobs[cl][ji];
          if (!(job & 3)) break;
          const int a_sel = (job >> 2) & 1, mpair = (job >> 3) & 7, chunk0 = (job >> 8) & 63;
          const bool newA = (job >> 14) & 1;
          const int KC = a_sel ? 9 : 8;
          const uint32_t halfbytes = 8192;
          const bool lastjob = (ji + 1 == K1_MAXJOBS) || !(p.jobs[cl][ji + 1] & 3);
          const CUtensorMap* tw = &p.tmW[(job >> 6) & 3];
          {
            const uint32_t njob = (ji + 1 < K1_MAXJOBS) ? p.jobs[cl][ji + 1] : 0;
            if (!(njob & 3) && !newA) mbar_arrive(bLast);
          }
#pragma unroll 1
          for (int kc = 0; kc < KC; kc++) {
            {
              const bool nx = kc + PFD >= KC;
              const uint32_t njob = nx ? p.jobs[cl][ji + 1] : job;
              const int pk = nx ? kc + PFD - KC : kc + PFD;
              if ((njob & 3) && (nx || ji > 0)) {
                if (cl >= 64 || ((pk ^ (cl >> 1)) & 3) == 0)
                  tma_pf3d(&p.tmW[(njob >> 6) & 3], 0, pk * 64 + (cl & 1) * 32 + rank * 16, (njob >> 8) & 63);
                if (((njob >> 14) & 1) || pk == 8) tma_pf2d(&p.tmA[(njob >> 2) & 1], pk * 64, ((njob >> 3) & 7) * 256 + rank * 128);
              }
            }
            if (kc == 8) {
              PWAIT(bBe + bs * 8, bph);
              mbar_expect(bBf + bs * 8, 16384);
              tma2d(sB + bs * 16384, &p.tmA[1], bBf + bs * 8, 512, mpair * 256 + rank * 128);
              if (++bs == K1_BST) { bs = 0; bph ^= 1; }
            } else if (newA) {
              PWAIT(bAe + kc * 8, aph);
              mbar_expect(bAf + kc * 8, 16384);
              tma2d(sA + ((kc + 2) & 7) * 16384, &p.tmA[a_sel], bAf + kc * 8, kc * 64, mpair * 256 + rank * 128);
              if (kc == 7 && lastjob) mbar_arrive(bLast);
            }
#pragma unroll 1
            for (int kk = 0; kk < 2; kk++) {
              PWAIT(bBe + bs * 8, bph);
              mbar_expect(bBf + bs * 8, 2 * halfbytes);
              tma3d_mc(sB + bs * 16384 + rank * halfbytes, tw, bBf + bs * 8, 0, kc * 64 + kk * 32 + rank * 16, chunk0, 3);
              if (++bs == K1_BST) { bs = 0; bph ^= 1; }
            }
          }
          if (newA) aph ^= 1;
        }
        Cursor c{0, 0};
        int pcol = 0;
        PWAIT(bR, 0);
        uint32_t tick = lds32(sTick + 8), seen = 1u << (p.order[tick] >> 4);
        asm volatile("fence.proxy.async.global;" ::: "memory");
#pragma unroll 1
        for (int it = 0;; it++) {
          const uint32_t item = (tick < 256) ? p.order[tick] : (K2_END | min(tick - 256, 255u));
          asm volatile("st.shared.u32 [%0], %1;" ::"r"(sItem + (it & 7) * 4), "r"(item) : "memory");
          if (item >= K2_END) break;
          const int h = item >> 3, j = item & 7;
          const int blk = 2 * j + (int)(rank ^ (it & 1));
          const int col = h * 128 + rank * 64;
          const int nb = 2 * j + 2;
          if (!((seen >> (h >> 1)) & 1)) {
            wait_flag(&g_sync[F_HP + (h >> 1)], RDY_TARGET);
            asm volatile("fence.proxy.async.global;" ::: "memory");
            seen |= 1u << (h >> 1);
          }
          PWAIT(bE + c.s * 8, c.ph);
          mbar_expect(bF + c.s * 8, 32768);
          tma2d(sbase + c.s * 32768, &p.tmC, bF + c.s * 8, h * 128, blk * 128);
          tma2d(sbase + c.s * 32768 + 16384, &p.tmC, bF + c.s * 8, h * 128 + 64, blk * 128);
          c.next();
#pragma unroll 1
          for (int n = nb - 1; n >= 0; n--) {
            if (n == 0 && rank == 0) tick = atomicAdd(&g_sync[F_TICK], 1u);
            PWAIT(bE + c.s * 8, c.ph);
            mbar_expect(bF + c.s * 8, 32768);
            tma2d_mc(sbase + c.s * 32768 + rank * 16384, &p.tmK, bF + c.s * 8, col, n * 128, 3);
            c.next();
            if (n < nb - 1 || it > 0) {
              PWAIT(bE + c.s * 8, c.ph);
              mbar_expect(bF + c.s * 8, 32768);
              tma2d_mc(sbase + c.s * 32768 + rank * 16384, &p.tmV, bF + c.s * 8, (n < nb - 1) ? col : pcol, (n < nb - 1) ? (n + 1) * 128 : 0, 3);
              c.next();
            }
          }
          pcol = col;
          if (rank == 0) {
            asm volatile(
                "{\n.reg .b32 a, b;\nmapa.shared::cluster.u32 a, %0, 1;\nmapa.shared::cluster.u32 b, %1, 1;\n"
                "st.async.shared::cluster.mbarrier::complete_tx::bytes.u32 [a], %2, [b];\n}" ::"r"(sTick + (it & 1) * 4),
                "r"(bT + (it & 1) * 8), "r"(tick) : "memory");
          } else {
            mbar_expect(bT + (it & 1) * 8, 4);
            PWAIT(bT + (it & 1) * 8, (it >> 1) & 1);
            tick = lds32(sTick + (it & 1) * 4);
          }
        }
        PWAIT(bE + c.s * 8, c.ph);
        mbar_expect(bF + c.s * 8, 32768);
        tma2d_mc(sbase + c.s * 32768 + rank * 16384, &p.tmV, bF + c.s * 8, pcol, 0, 3);
        const uint32_t unit = tick - 256;
        if (unit < 64) {
          const int mblk = (7 - (p.unit[unit][0] >> 1)) * 2 + rank, nhalf = p.unit[unit][0] & 1;
          const uint32_t rot = k3_rot(c.s), nfree = ((0x1Au >> c.s) & 1) ? 2 : 3;
#pragma unroll 1
          for (int i = 0; i < K2_NST - 1; i++) {
            c.next();
            PWAIT(bE + c.s * 8, c.ph);
          }
          uint32_t have = 0;
#pragma unroll 1
          for (uint32_t idx = 0; idx < p.unit[unit][2]; idx++) {
            const int kk = p.unit[unit][3] + idx + ((idx >= p.unit[unit][4]) ? p.unit[unit][5] : 0);
            const uint32_t s = (rot + idx) & 3;
            if (idx >= nfree) PWAIT((idx < 4) ? bH : b3E + s * 8, (idx < 4) ? 0 : (~idx >> 2) & 1);
            mbar_expect(b3F + s * 8, K3_STAGE);
            const uint32_t st = sbase + s * K3_STAGE;
            const int sel = (kk < 9), k = sel ? kk : kk - 9, kr = k * 64 + rank * 32;
            tma3d_mc(st + 16384 + rank * 16384, &p.tmO[sel], b3F + s * 8, 0, kr, nhalf * 4, 3);
            tma2d_mc(st + 49152 + rank * 2048, &p.tmOt[sel], b3F + s * 8, 512 + nhalf * 32, kr, 3);
            if (sel && idx == 0) {
              wait_flag(&g_sync[F_OA + mblk], 8);
              asm volatile("fence.proxy.async.global;" ::: "memory");
            }
            if (!sel && !((have >> (k >> 1)) & 1)) {
#pragma unroll 1
              for (uint32_t spins = 0; spins < (1u << 22); spins++) {
                asm volatile("ld.acquire.gpu.global.u32 %0, [%1];" : "=r"(have) : "l"(&g_sync[F_CTX + mblk]) : "memory");
                if ((have >> (k >> 1)) & 1) break;
                __nanosleep(100);
              }
              asm volatile("fence.proxy.async.global;" ::: "memory");
            }
            tma2d(st, &p.tmC, b3F + s * 8, (sel ? 64 + k : k) * 64, mblk * 128);
          }
        }
      }
    }
    __syncwarp();
    if (warp_g == 8) {
      uint32_t v = 0;
      if (lane == 0) {
        __threadfence();
        v = atomicAdd(&g_sync[F_DONE], 1u);
      }
      if (__shfl_sync(0xffffffffu, v, 0) == 2 * NCLUSTER - 1) {
        reinterpret_cast<uint4*>(g_sync)[lane] = make_uint4(0, 0, 0, 0);
        if (lane == 0) g_sync[F_EPOCH] = lds32(sGate + 64) + 1;
      }
    }
    asm volatile("" ::: "memory");
    if (__shfl_sync(0xffffffffu, warp_g, 0) != 8) {
      if (lr0 < S_LEN) {
#pragma unroll 1
        for (int i = warp_g - 9; i < 16; i += 3) {
          const float g = gate_row(lr0 + i, lane, x, gate_w);
          if (lane == 0) asm volatile("st.shared.f32 [%0], %1;" ::"r"(sGate + i * 4), "f"(g) : "memory");
        }
        bar_arrive(3, 256 + 96);
        if (lane == 0) {
          __threadfence();
          atomicAdd(&g_sync[F_GATE], 1u);
        }
      }
      uint32_t aph = 1;
#pragma unroll 1
      for (int ji = 0; ji < K1_MAXJOBS; ji++) aph ^= (p.jobs[cl][ji] >> 14) & 1;
      if (warp_g == 9 && lane == 0) {
#pragma unroll 1
        for (int ji = 0; ji < K1_MAXJOBS; ji++) {
          const uint32_t job = p.jobs[cl][ji];
          if (!(job & 3)) break;
          PWAIT(bS, ji & 1);
          __threadfence();
          atomicAdd(&g_sync[(((job >> 6) & 3) == 2) ? (F_QKVA + ((job >> 3) & 7) * 2 + rank) : (F_HP + ((job >> 10) & 15))], 1u);
        }
#pragma unroll 1
        for (int it = 0;; it++) {
          PWAIT(bS2, it & 1);
          const uint32_t item = lds32(sItem + (it & 7) * 4), nxt = lds32(sItem + ((it + 1) & 7) * 4);
          __threadfence();
          atomicOr(&g_sync[F_CTX + (item & 7) * 2 + (rank ^ (it & 1))], 1u << (item >> 3));
          if (nxt >= K2_END) break;
        }
      } else if (warp_g == 11) {
        if (lane == 0) {
          prefetch_tmap(&p.tmC); prefetch_tmap(&p.tmK); prefetch_tmap(&p.tmV);
          asm volatile("st.shared.u32 [%0], %1;" ::"r"(sGate + 64), "r"(__ldcg(&g_sync[F_EPOCH])) : "memory");
          wait_flag(&g_sync[F_GATE], GATE_TARGET);
          uint32_t tick;
          if (rank == 0) {
            PWAIT(bLast, 0);
            PWAIT(bAe + FIRST_DRAW * 8, aph);
            tick = atomicAdd(&g_sync[F_TICK], 1u);
            asm volatile("st.shared.u32 [%0], %1;" ::"r"(sTick + 8), "r"(tick) : "memory");
            asm volatile(
                "{\n.reg .b32 a, b;\nmapa.shared::cluster.u32 a, %0, 1;\nmapa.shared::cluster.u32 b, %1, 1;\n"
                "st.async.shared::cluster.mbarrier::complete_tx::bytes.u32 [a], %2, [b];\n}" ::"r"(sTick + 8), "r"(bT0), "r"(tick) : "memory");
          } else {
            mbar_expect(bT0, 4);
            PWAIT(bT0, 0);
            tick = lds32(sTick + 8);
          }
          wait_flag(&g_sync[F_HP + (p.order[tick] >> 4)], RDY_TARGET);
          mbar_arrive(bR);
        }
      } else if (warp_g == 10) {
        if (lr0 < S_LEN && lane == 0) {
          prefetch_tmap(&p.tmL[0]); prefetch_tmap(&p.tmL[1]); prefetch_tmap(&p.tmL[2]);
          wait_flag(&g_sync[F_QKVA + (lr0 >> 7)], K1_FLAG_TARGET);
          wait_flag(&g_sync[F_QKVA + (max(lr0 - 16, 0) >> 7)], K1_FLAG_TARGET);
          asm volatile("fence.proxy.async.global;" ::: "memory");
          PWAIT(bLast, 0);
#pragma unroll 1
          for (int kc = 0; kc < 6; kc++) {
            PWAIT(bAe + kc * 8, aph);
            if (kc == 3) {
              mbar_expect(bL, LV);
              tma4d(sL, &p.tmL[0], bL, lr0 / 2 - 8, 9, 0);
              tma4d(sL + LQ, &p.tmL[1], bL, lr0 / 2, 0, 0);
            }
          }
          mbar_expect(bL2, LQ);
          tma4d(sL + LV, &p.tmL[0], bL2, lr0 / 2 - 8, 18, 0);
        }
        __syncwarp();
        bar_sync(5, 256 + 32);
        if (lr0 < S_LEN && lane == 0) {
          asm volatile("cp.async.bulk.tensor.4d.global.shared::cta.bulk_group [%0, {%2, %3, %2, %2}], [%1];" ::"l"(&p.tmL[2]), "r"(sL + LQ), "r"(0), "r"(lr0 / 2) : "memory");
          asm volatile("cp.async.bulk.commit_group;" ::: "memory");
          asm volatile("cp.async.bulk.wait_group.read 0;" ::: "memory");
        }
        __syncwarp();
        if (lane < 12) mbar_arrive_cluster(bE + (4 + lane % 3) * 8, (lane / 3) & 1);
        if (lr0 < S_LEN && lane == 0) {
          asm volatile("cp.async.bulk.wait_group 0;" ::: "memory");
          asm volatile("fence.proxy.async.global;" ::: "memory");
          __threadfence();
          atomicAdd(&g_sync[F_OA + (lr0 >> 7)], 1u);
        }
      }
    }
    __syncwarp();
    cluster_sync();
  } else {
    reg_alloc<232>();
    const int wg = warp_g >> 2, warp = warp_g & 3, q = lane & 3;
    const bool sig = (lane == 0) && (warp < 2);
    {
      K1State st{0, 0, 0, nullptr, nullptr, 0, 0, 0};
      float acc[128];
      uint32_t pk[64];
      if (wg == 0) { TS(0, 0); TSC(0, 2); }
      uint32_t job = p.jobs[cl][0];
      k1_first(st, job, bAf, bBf);
      {
#pragma unroll 1
        for (int ji = 0; job & 3; ji++) {
          const uint32_t njob = p.jobs[cl][ji + 1];
          k1_tile(acc, pk, st, job, njob, sA, sB, bAf, bAe, bBf, bBe, bS, wg, warp, lane, rank);
          job = njob;
        }
      }
#pragma unroll
      for (int i = 0; i < 4; i++)
        mbar_arrive_cluster_if(bE + i * 8, warp & 1, sig);
      if (lr0 < S_LEN) bar_sync(3, 256 + 96);
      if (st.wsel == 3) {
#pragma unroll
        for (int G = 0; G < 16; G++) scale_q4(pk + G * 4);
      }
      auto flush = [&](int i, uint32_t dep) {
        asm volatile("{\n.reg .pred p;\nsetp.eq.u32 p, %5, 0;\n@p st.global.cs.v4.b32 [%0], {%1, %2, %3, %4};\n}" ::"l"(((i & 1) ? st.pp8 : st.pp) + (i / 2) * 32),
                     "r"(pk[i * 4]), "r"(pk[i * 4 + 1]), "r"(pk[i * 4 + 2]), "r"(pk[i * 4 + 3]), "r"(dep & blockIdx.y) : "memory");
      };
      if (wg == 0) { TS(0, 1); TSC(0, 3); }
      if (lr0 < S_LEN) {
        const float gate0 = __uint_as_float(lds32(sGate + (lane >> 2) * 8)), gate1 = __uint_as_float(lds32(sGate + (lane >> 2) * 8 + 4));
        local_attn(lr0, warp_g, sL, bL, bL2, lane, gate0, gate1, flush);
        k1_flag(st, lane, bS);
      } else {
        FLUSH();
      }
      bar_arrive(5, 256 + 32);
    }
    __syncwarp();
    uint32_t item, rot;
    {
      const int mybar = 1 + wg, otherbar = 2 - wg;
      const uint32_t never = blockIdx.y;
      float S[64], O[64];
      uint32_t P[32], Q[32];
      float m0 = 0.f, m1 = 0.f, l0 = 1.f, l1 = 1.f, gf0 = 0.f, gf1 = 0.f;
      uint32_t eoff = 0, prev_single = 0;
      Cursor c{0, 0};
      if (wg == 1) bar_arrive(1, 256);
      if (wg == 0) { TS(1, 0); TSC(1, 2); }
#pragma unroll 1
      for (int it = 0;; it++) {
        TB(0);
        const int hi = (int)(rank ^ (it & 1));
        Cursor cq = c, ck, cv, cs0, cs1;
        rot = k3_rot(c.s);
        c.next();
        ck = c; c.next();
        cs0 = ck; cs1 = ck; cv = ck;
        if (it > 0) { cv = c; c.next(); }
        if (!hi) {
          ck = c; c.next();
          cs1 = c; c.next();
        }
        mbar_wait(bF + cq.s * 8, cq.ph);
        TB(1);
        item = lds32(sItem + (it & 7) * 4);
        {
          const uint32_t qa = sbase + cq.s * 32768 + (wg * 64 + warp * 16 + (lane & 15)) * 128;
#pragma unroll
          for (int t = 0; t < 8; t++)
            ldsm_x4(Q[4 * t], Q[4 * t + 1], Q[4 * t + 2], Q[4 * t + 3], qa + (t >> 2) * 16384 + ((((t & 3) * 2 + (lane >> 4)) ^ (lane & 7)) << 4));
        }
        const uint32_t rdy = mbar_test(bF + ck.s * 8, ck.ph) & mbar_test(bF + cv.s * 8, cv.ph);
        l0 += __shfl_xor_sync(0xffffffffu, l0, 1);
        l1 += __shfl_xor_sync(0xffffffffu, l1, 1);
        l0 += __shfl_xor_sync(0xffffffffu, l0, 2);
        l1 += __shfl_xor_sync(0xffffffffu, l1, 2);
        const bool last = item >= K2_END;
        if (last) {
          cv = cq; ck = cq;
        } else if (!rdy) {
          mbar_wait2(bF + ck.s * 8, ck.ph, bF + cv.s * 8, cv.ph);
        }
        TB(2);
        TURN_SYNC();
        TB(3);
        TRC(last ? 2 : 1);
        if (it > 0) {
          wg_fence();
          ISSUE_PV(cv, prev_single);
          wg_commit();
        } else {
          wg_fence();
          wg_commit();
        }
        wg_fence();
        ISSUE_QK(ck);
        wg_commit();
        if (!(last && wg == 1)) TURN_ARRIVE();
        RELEASE_IF(cq, !last);
        TB(4);
        asm volatile("" : "+f"(gf0), "+f"(gf1), "+f"(l0), "+f"(l1));
        const float f0 = __fdividef(1.f - gf0, l0), f1 = __fdividef(1.f - gf1, l1);
        wg_wait<1>();
        fence_regs(O);
        fence_regs(P);
        TB(5);
        if (it > 0) {
          RELEASE_IF(cv, !last);
          mbar_arrive_cluster_if(bH, warp & 1, sig && last);
          bf16* optr = ptr_add(g_ctx, eoff);
          STORE_O(0); STORE_O(1); STORE_O(2); STORE_O(3);
          __syncwarp();
          mbar_arrive_if(bS2, lane == 0);
        }
        TB(6);
        if (!last) {
          const int row = (2 * (item & 7) + hi) * 128 + wg * 64 + warp * 16 + (lane >> 2);
          eoff = (row * KCAT + (item >> 3) * 128 + q * 8) * 2;
          const float* gp = ptr_add(g_gate, row * 4);
          asm volatile("ld.global.f32 %0, [%1];" : "=f"(gf0) : "l"(gp));
          asm volatile("ld.global.f32 %0, [%1];" : "=f"(gf1) : "l"(gp + 8));
          if (!hi) {
            mbar_wait2(bF + cs0.s * 8, cs0.ph, bF + cs1.s * 8, cs1.ph);
            RELEASE(cs0);
            RELEASE(cs1);
          }
        }
        TB(7);
        wg_wait<0>();
        fence_regs(S);
        TB(8);
        if (last) break;
        RELEASE(ck);
        const int nblk = 2 * (item & 7) + 1 + hi;
        prev_single = (nblk == 1);
        float s0 = 0.f, s1 = 0.f;
        l0 = 0.f; l1 = 0.f;
        m0 = 0.f; m1 = 0.f;
        bool shifted = false;
        {
          const int d = warp * 16 + (lane >> 2) - 2 * q;
          if (wg == 0) {
#pragma unroll
            for (int jj = 0; jj < 8; jj++) MASK(jj, jj);
            EXPB(0); EXPB(1); EXPB(2); EXPB(3);
#pragma unroll
            for (int i = 32; i < 64; i++) S[i] = -INFINITY;
#pragma unroll
            for (int i = 16; i < 32; i++) P[i] = 0;
          } else {
#pragma unroll
            for (int jj = 0; jj < 8; jj++) MASK(jj + 8, jj);
            EXPB(0); EXPB(1); EXPB(2); EXPB(3); EXPB(4); EXPB(5); EXPB(6); EXPB(7);
          }
        }
        float chk = (q == 0 && !(fminf(s0, s1) >= SPEC_LO)) ? INFINITY : s0 + s1;
        fence_regs(P);
        TB(9);
#pragma unroll 1
        for (int n = 1;; n++) {
          if (__any_sync(0xffffffffu, !(chk <= SPEC_HI))) {
            float mx0 = fmaxf(S[0], S[1]), mx1 = fmaxf(S[2], S[3]);
#pragma unroll
            for (int jj = 1; jj < 16; jj++) {
              mx0 = fmaxf(mx0, fmaxf(S[jj * 4 + 0], S[jj * 4 + 1]));
              mx1 = fmaxf(mx1, fmaxf(S[jj * 4 + 2], S[jj * 4 + 3]));
            }
            mx0 = fmaxf(mx0, __shfl_xor_sync(0xffffffffu, mx0, 1));
            mx1 = fmaxf(mx1, __shfl_xor_sync(0xffffffffu, mx1, 1));
            mx0 = fmaxf(mx0, __shfl_xor_sync(0xffffffffu, mx0, 2));
            mx1 = fmaxf(mx1, __shfl_xor_sync(0xffffffffu, mx1, 2));
            const float lo = (n == 1) ? -INFINITY : 0.f;
            mx0 = fmaxf(mx0, lo);
            mx1 = fmaxf(mx1, lo);
            m0 += mx0; m1 += mx1;
            shifted = true;
            const float sc0 = ex2(-fmaxf(mx0, 0.f)), sc1 = ex2(-fmaxf(mx1, 0.f));
            l0 *= sc0; l1 *= sc1;
            s0 = 0.f; s1 = 0.f;
#pragma unroll
            for (int jj = 0; jj < 16; jj++) {
              const float e0 = ex2(S[jj * 4 + 0] - mx0), e1 = ex2(S[jj * 4 + 1] - mx0), e2 = ex2(S[jj * 4 + 2] - mx1), e3 = ex2(S[jj * 4 + 3] - mx1);
              s0 += e0 + e1;
              s1 += e2 + e3;
              P[jj * 2 + 0] = pack_bf16(e0, e1);
              P[jj * 2 + 1] = pack_bf16(e2, e3);
              O[jj * 4 + 0] *= sc0;
              O[jj * 4 + 1] *= sc0;
              O[jj * 4 + 2] *= sc1;
              O[jj * 4 + 3] *= sc1;
            }
          }
          l0 += s0;
          l1 += s1;
          if (n >= nblk) break;
          ck = c; c.next();
          cv = c; c.next();
          mbar_wait(bF + ck.s * 8, ck.ph);
          mbar_wait(bF + cv.s * 8, cv.ph);
          TURN_SYNC();
          TRC(0);
          wg_fence();
          ISSUE_QK(ck);
          wg_commit();
          {
            const uint64_t dv = make_desc(sbase + cv.s * 32768, 16384, 1024, 1);
#pragma unroll
            for (int t = 0; t < 8; t++) {
              wgmma_rs_n128<1, 0>(O, P[4 * t], P[4 * t + 1], P[4 * t + 2], P[4 * t + 3], dv + (uint64_t)(t * 128), (t > 0) ? 1 : (n != 1));
              if ((PVM >> t) & 1) wg_commit();
            }
          }
          TURN_ARRIVE();
          s0 = 0.f; s1 = 0.f;
          wg_wait<__builtin_popcount(PVM)>();
          fence_regs(S);
          RELEASE(ck);
          if (shifted) {
#pragma unroll
            for (int i = 0; i < 64; i++) S[i] -= (i & 2) ? m1 : m0;
          }
          wg_wait<__builtin_popcount(PVM) - 1>();
          EXPC(0); EXPC(1); EXPC(2); EXPC(3); EXPC(4); EXPC(5); EXPC(6); EXPC(7);
          chk = s0 + s1;
        }
      }
      TRC(3);
      if (wg == 1) { TS(1, 1); TSC(1, 3); }
    }
    __syncwarp();
    const uint32_t unit = item & 255;
    if (unit < 64) {
      const int mblk = (7 - (p.unit[unit][0] >> 1)) * 2 + rank, nhalf = p.unit[unit][0] & 1, ks = p.unit[unit][1];
      const int k0 = 0, k1 = p.unit[unit][2];
      float acc[144];
      uint32_t s = rot, ph = 0, prev = 0;
      if (wg == 0) { TS(2, 0); TSC(2, 2); }
      uint32_t fa[16], fb[16];
      const uint32_t aoff = (wg * 64 + warp * 16 + (lane & 15)) * 128 + (((lane >> 4) ^ (lane & 7)) << 4);
#define C_LOAD(F)                                                                                              \
  do {                                                                                                         \
    mbar_wait(b3F + s * 8, ph);                                                                                \
    _Pragma("unroll") for (int t = 0; t < 4; t++)                                                              \
        ldsm_x4(F[4 * t], F[4 * t + 1], F[4 * t + 2], F[4 * t + 3], sbase + s * K3_STAGE + (aoff ^ (t * 32))); \
  } while (0)
#define C_STEP(F, G)                                                                                           \
  {                                                                                                            \
    const uint32_t st = sbase + s * K3_STAGE;                                                                  \
    const uint64_t db = make_desc(st + 16384, 4096, 1024, 1), dt = make_desc(st + 49152, 16, 512, 2);          \
    wg_fence();                                                                                                \
    _Pragma("unroll") for (int t = 0; t < 4; t++) {                                                            \
      const int sd = (t > 0) || (k > k0);                                                                      \
      wgmma_rs_n256<1, 0>(acc, F[4 * t], F[4 * t + 1], F[4 * t + 2], F[4 * t + 3], db + (uint64_t)((t >> 1) * 1024 + (t & 1) * 128), sd); \
      wgmma_rs_n32<1, 128>(acc, F[4 * t], F[4 * t + 1], F[4 * t + 2], F[4 * t + 3], dt + (uint64_t)(t * 64), sd); \
    }                                                                                                          \
    wg_commit();                                                                                               \
    wg_wait<1>();                                                                                              \
    fence_regs(G);                                                                                             \
    mbar_arrive_cluster_if(b3E + prev * 8, warp & 1, sig && k > k0);                                           \
    prev = s;                                                                                                  \
    s = (s + 1) & 3;                                                                                           \
    if (s == rot) ph ^= 1;                                                                                     \
    if (++k == k1) break;                                                                                      \
    C_LOAD(G);                                                                                                 \
  }
      C_LOAD(fa);
#pragma unroll
      for (int i = 0; i < 16; i++) fb[i] = 0;
#pragma unroll 1
      for (int k = k0;;) {
        C_STEP(fa, fb)
        C_STEP(fb, fa)
      }
      wg_wait<0>();
      fence_regs(acc);
      cluster_arrive();
      if (wg == 0) TS(2, 4);
      const int tile = mblk * 2 + nhalf;
      uint4* wp = g_part + (size_t)((tile * 4 + ks) * 4) * 5 * 256 + tid;
      const uint32_t sown = sbase + wg * 8192 + (tid & 127) * 16;
#pragma unroll
      for (int d = 0; d < 4; d++) {
        if (d != ks) {
#pragma unroll
          for (int i = 0; i < 4; i++)
            __stcg(wp + (d * 5 + i) * 256,
                   make_uint4(pack_bf16(acc[d * 32 + i * 8], acc[d * 32 + i * 8 + 1]), pack_bf16(acc[d * 32 + i * 8 + 2], acc[d * 32 + i * 8 + 3]),
                              pack_bf16(acc[d * 32 + i * 8 + 4], acc[d * 32 + i * 8 + 5]), pack_bf16(acc[d * 32 + i * 8 + 6], acc[d * 32 + i * 8 + 7])));
          __stcg(reinterpret_cast<uint2*>(wp - tid + (d * 5 + 4) * 256) + tid,
                 make_uint2(pack_bf16(acc[128 + d * 4], acc[128 + d * 4 + 1]), pack_bf16(acc[128 + d * 4 + 2], acc[128 + d * 4 + 3])));
        } else {
#pragma unroll
          for (int i = 0; i < 9; i++) {
            const int o = (i < 8) ? d * 32 + i * 4 : 128 + d * 4;
            asm volatile("st.shared.v4.f32 [%0], {%1, %2, %3, %4};" ::"r"(sown + (i >> 2) * K3_STAGE + (i & 3) * 2048), "f"(acc[o]), "f"(acc[o + 1]), "f"(acc[o + 2]), "f"(acc[o + 3]) : "memory");
          }
        }
      }
      __threadfence();
      __syncwarp();
      if (wg == 0) TS(2, 5);
      if (lane == 0) {
        unsigned int* cnt = &g_sync[F_XCH + tile * 8 + warp_g];
        const uint32_t xtarget = lds32(sGate + 64) * 4 + 4;
        atomicAdd(cnt, 1u);
        uint32_t v, spins = 0;
        do {
          asm volatile("ld.acquire.gpu.global.u32 %0, [%1];" : "=r"(v) : "l"(cnt) : "memory");
        } while ((int)(v - xtarget) < 0 && ++spins < (1u << 24));
      }
      __syncwarp();
      if (wg == 0) TS(2, 6);
      float r[36];
#pragma unroll
      for (int i = 0; i < 9; i++)
        asm volatile("ld.shared.v4.f32 {%0, %1, %2, %3}, [%4];" : "=f"(r[i * 4]), "=f"(r[i * 4 + 1]), "=f"(r[i * 4 + 2]), "=f"(r[i * 4 + 3])
                     : "r"(sown + (i >> 2) * K3_STAGE + (i & 3) * 2048) : "memory");
#pragma unroll
      for (int sI = 1; sI < 4; sI++) {
        const int src = (ks + sI) & 3;
        const uint4* rp = g_part + (size_t)(((tile * 4 + src) * 4) + ks) * 5 * 256;
#pragma unroll
        for (int i = 0; i < 4; i++) {
          const uint4 v = __ldcg(rp + i * 256 + tid);
          r[i * 8] += bf_lo(v.x); r[i * 8 + 1] += bf_hi(v.x); r[i * 8 + 2] += bf_lo(v.y); r[i * 8 + 3] += bf_hi(v.y);
          r[i * 8 + 4] += bf_lo(v.z); r[i * 8 + 5] += bf_hi(v.z); r[i * 8 + 6] += bf_lo(v.w); r[i * 8 + 7] += bf_hi(v.w);
        }
        const uint2 v = __ldcg(reinterpret_cast<const uint2*>(rp + 4 * 256) + tid);
        r[32] += bf_lo(v.x); r[33] += bf_hi(v.x); r[34] += bf_lo(v.y); r[35] += bf_hi(v.y);
      }
      const int row = mblk * 128 + wg * 64 + warp * 16 + (lane >> 2);
      bf16* o0 = out + (size_t)row * DM + nhalf * 256 + ks * 64 + 8 * q;
#pragma unroll
      for (int G = 0; G < 2; G++) {
        uint32_t a0 = pack_bf16(r[G * 16], r[G * 16 + 1]), a1 = pack_bf16(r[G * 16 + 4], r[G * 16 + 5]);
        uint32_t a2 = pack_bf16(r[G * 16 + 8], r[G * 16 + 9]), a3 = pack_bf16(r[G * 16 + 12], r[G * 16 + 13]);
        uint32_t b0 = pack_bf16(r[G * 16 + 2], r[G * 16 + 3]), b1 = pack_bf16(r[G * 16 + 6], r[G * 16 + 7]);
        uint32_t b2 = pack_bf16(r[G * 16 + 10], r[G * 16 + 11]), b3 = pack_bf16(r[G * 16 + 14], r[G * 16 + 15]);
        quad_transpose(a0, a1, a2, a3, q);
        quad_transpose(b0, b1, b2, b3, q);
        st_v4(o0 + G * 32, a0, a1, a2, a3);
        st_v4(o0 + 8 * DM + G * 32, b0, b1, b2, b3);
      }
      {
        uint32_t t0 = pack_bf16(r[32], r[33]), t1 = pack_bf16(r[34], r[35]), t2 = 0, t3 = 0;
        quad_transpose(t0, t1, t2, t3, q);
        if (q < 2) st_v4(out + (size_t)(row + q * 8) * DM + 512 + nhalf * 32 + ks * 8, t0, t1, t2, t3);
      }
    } else {
      cluster_arrive();
    }
    if (wg == 0) { TS(2, 1); TSC(2, 3); }
    cluster_wait();
  }
}

typedef CUresult (*EncFn)(CUtensorMap*, CUtensorMapDataType, cuuint32_t, void*, const cuuint64_t*, const cuuint64_t*, const cuuint32_t*,
                          const cuuint32_t*, CUtensorMapInterleave, CUtensorMapSwizzle, CUtensorMapL2promotion, CUtensorMapFloatOOBfill);

static void enc2d(EncFn enc, CUtensorMap* m, const void* ptr, uint64_t cols, uint64_t rows, uint32_t bc, uint32_t br,
                  CUtensorMapSwizzle sw = CU_TENSOR_MAP_SWIZZLE_128B) {
  cuuint64_t gd[2] = {cols, rows}, gs[1] = {cols * 2};
  cuuint32_t bx[2] = {bc, br}, es[2] = {1, 1};
  enc(m, CU_TENSOR_MAP_DATA_TYPE_BFLOAT16, 2, const_cast<void*>(ptr), gd, gs, bx, es, CU_TENSOR_MAP_INTERLEAVE_NONE, sw,
      CU_TENSOR_MAP_L2_PROMOTION_L2_256B, CU_TENSOR_MAP_FLOAT_OOB_FILL_NONE);
}
static void enc3d(EncFn enc, CUtensorMap* m, const void* ptr, uint64_t cols, uint64_t rows, uint32_t br, uint32_t bch) {
  cuuint64_t gd[3] = {64, rows, cols / 64}, gs[2] = {cols * 2, 128};
  cuuint32_t bx[3] = {64, br, bch}, es[3] = {1, 1, 1};
  enc(m, CU_TENSOR_MAP_DATA_TYPE_BFLOAT16, 3, const_cast<void*>(ptr), gd, gs, bx, es, CU_TENSOR_MAP_INTERLEAVE_NONE,
      CU_TENSOR_MAP_SWIZZLE_128B, CU_TENSOR_MAP_L2_PROMOTION_L2_256B, CU_TENSOR_MAP_FLOAT_OOB_FILL_NONE);
}

static int g_sched[10] = {11, 10, 7, 4, 4, 4, 6, 8, 6, 24};
static void build_k1_jobs(Params& p) {
  int cnt[NCLUSTER];
  for (int c = 0; c < NCLUSTER; c++) {
    cnt[c] = 0;
    for (int i = 0; i <= K1_MAXJOBS; i++) p.jobs[c][i] = 0;
  }
  auto add = [&](int c, int nch, int a_sel, int mp, int w_sel, int chunk0) {
    p.jobs[c][cnt[c]++] = (uint16_t)((nch - 1) | (a_sel << 2) | (mp << 3) | (w_sel << 6) | (chunk0 << 8));
  };
  const char* plan = "ccccccccccc cccccccccc ccccccc cccc xxxx xxxx xxxxxx xxxxxxxx";
  int TIE = 0;
  int XA = 0;
  const char* cur[8];
  int tend[8] = {};
  for (int g = 0; g < 8; g++) {
    cur[g] = plan;
    while (*plan == 'c' || *plan == 'x') plan++;
    if (*plan) plan++;
  }
  int kc = 0, kx = 0;
  for (;;) {
    int b = -1, bt = 0;
    for (int g = 0; g < 8; g++) {
      const int t = tend[g] + (*cur[g] == 'x' ? 94 : 85);
      if ((*cur[g] == 'c' || *cur[g] == 'x') && (b < 0 || t < bt || (TIE && t == bt))) { b = g; bt = t; }
    }
    if (b < 0) break;
    const int a = kx - XA;
    for (int mp = 0; mp < 8; mp++) {
      if (*cur[b] == 'c') add(b * 8 + mp, 4, 0, mp, kc & 1, (kc >> 1) * 4);
      else if (a >= 0 && a < 7) add(b * 8 + mp, a == 0 ? 3 : 4, 1, mp, 2, a == 0 ? 24 : (a - 1) * 4);
      else add(b * 8 + mp, 4, 1, mp, 3, (a < 0 ? kx : kx - 7) * 4);
    }
    if (*cur[b] == 'c') kc++; else kx++;
    cur[b]++;
    tend[b] = bt;
  }
  for (int mp = 0; mp < 8; mp++) add(64 + mp / 4, 4, 1, mp, 3, 15 * 4);
  for (int cc = 0; cc < NCLUSTER; cc++)
    for (int i = 0; i < cnt[cc]; i++) {
      const int key = p.jobs[cc][i] & 0x3C;
      if (i == 0 || (p.jobs[cc][i - 1] & 0x3C) != key) p.jobs[cc][i] |= (1 << 14);
      if (i == cnt[cc] - 1 || (p.jobs[cc][i + 1] & 0x3C) != key) p.jobs[cc][i] |= (1 << 15);
    }
}

static void build_k2_items(Params& p) {
  int n = 0;
  const int SCHED_N1 = g_sched[8], SCHED_N2 = g_sched[9];
  int N0 = 2, J0 = 2;
  for (int j = 7; j >= J0; j--)
    for (int h = 0; h < N0; h++) p.order[n++] = (uint8_t)(h * 8 + j);
  for (int j = 7; j >= 0; j--)
    for (int h = 0; h < SCHED_N1; h++)
      if (!(h < N0 && j >= J0)) p.order[n++] = (uint8_t)(h * 8 + j);
  for (int j = 7; j >= 4; j--)
    for (int h = SCHED_N1; h < SCHED_N2; h++) p.order[n++] = (uint8_t)(h * 8 + j);
  for (int j = 7; j >= 0; j--)
    for (int h = SCHED_N1; h < 32; h++)
      if (!(h < SCHED_N2 && j >= 4)) p.order[n++] = (uint8_t)(h * 8 + j);
}

static void build_k3_units(Params& p) {
  float slope = 0.045f;
  int NE = 25;
  for (int t = 0; t < 16; t++) {
    const int u[4] = {t, 31 - t, 32 + t, 63 - t};
    float acc = 0.f;
    int k0 = 0, l0 = NE;
    for (int i = 0; i < 4; i++) {
      acc += 18.25f + slope * (31.5f - u[i]);
      const int k1 = (i == 3) ? 73 : (int)(acc + 0.5f);
      const int e0 = NE * i / 4, e1 = NE * (i + 1) / 4;
      uint8_t* w = p.unit[u[i]];
      w[0] = (uint8_t)t; w[1] = (uint8_t)i; w[2] = (uint8_t)(k1 - k0); w[3] = (uint8_t)e0; w[4] = (uint8_t)(e1 - e0); w[5] = (uint8_t)(l0 - e1);
      l0 += (k1 - k0) - (e1 - e0);
      k0 = k1;
    }
  }
}

extern "C" void kernel_launch(void* const* d_in, const int* in_sizes, int n_in, void* d_out, int out_size) {
  const bf16* x = (const bf16*)d_in[0];
  const bf16* wqkv = (const bf16*)d_in[1];
  const bf16* wo = (const bf16*)d_in[2];
  const bf16* ckv = (const bf16*)d_in[4];
  const bf16* w_q = (const bf16*)d_in[5];
  const bf16* w_uk = (const bf16*)d_in[6];
  const bf16* w_uv = (const bf16*)d_in[7];
  const bf16* w_o = (const bf16*)d_in[8];
  const bf16* gate_w = (const bf16*)d_in[9];

  EncFn enc = nullptr;
  cudaDriverEntryPointQueryResult qr;
  cudaGetDriverEntryPoint("cuTensorMapEncodeTiled", (void**)&enc, cudaEnableDefault, &qr);
  void *pK, *pV, *pCtx, *pQA;
  cudaGetSymbolAddress(&pQA, g_QKVA);
  cudaGetSymbolAddress(&pK, g_K);
  cudaGetSymbolAddress(&pV, g_V);
  cudaGetSymbolAddress(&pCtx, g_ctx);

  static Params p;
  enc2d(enc, &p.tmA[0], ckv, DC, S_LEN, 64, 128);
  enc2d(enc, &p.tmA[1], x, DM, S_LEN, 64, 128);
  enc3d(enc, &p.tmW[0], w_uk, HDIM, DC, 16, 4);
  enc3d(enc, &p.tmW[1], w_uv, HDIM, DC, 16, 4);
  enc3d(enc, &p.tmW[2], wqkv, NQKVA, DM, 16, 4);
  enc3d(enc, &p.tmW[3], w_q, HDIM, DM, 16, 4);
  build_k1_jobs(p);
  enc2d(enc, &p.tmK, pK, HDIM, S_LEN, 64, 128);
  enc2d(enc, &p.tmV, pV, HDIM, S_LEN, 64, 128);
  build_k2_items(p);
  build_k3_units(p);
  for (int i = 0; i < 3; i++) {
    const cuuint64_t ld = (i < 2 ? NQKVA : KCAT) * 2, nch = (i < 2) ? 27 : 9;
    cuuint64_t gd[4] = {64, S_LEN / 2, i ? 2 : nch, i ? nch : 2}, gs[3] = {2 * ld, i ? ld : 128, i ? 128 : ld};
    cuuint32_t bx[4] = {64, i ? 8u : 16u, i ? 2u : 9u, i ? 9u : 2u}, es[4] = {1, 1, 1, 1};
    enc(&p.tmL[i], CU_TENSOR_MAP_DATA_TYPE_BFLOAT16, 4, (i < 2) ? pQA : (void*)((bf16*)pCtx + HDIM), gd, gs, bx, es, CU_TENSOR_MAP_INTERLEAVE_NONE,
        CU_TENSOR_MAP_SWIZZLE_128B, CU_TENSOR_MAP_L2_PROMOTION_L2_256B, CU_TENSOR_MAP_FLOAT_OOB_FILL_NONE);
  }
  enc2d(enc, &p.tmC, pCtx, KCAT, S_LEN, 64, 128);
  enc3d(enc, &p.tmO[0], w_o, DM, HDIM, 32, 4);
  enc3d(enc, &p.tmO[1], wo, DM, DM, 32, 4);
  enc2d(enc, &p.tmOt[0], w_o, DM, HDIM, 32, 32, CU_TENSOR_MAP_SWIZZLE_64B);
  enc2d(enc, &p.tmOt[1], wo, DM, DM, 32, 32, CU_TENSOR_MAP_SWIZZLE_64B);

  cudaFuncSetAttribute(fused_kernel, cudaFuncAttributeMaxDynamicSharedMemorySize, SMEM_BYTES);
  fused_kernel<<<NCLUSTER * 2, 384, SMEM_BYTES>>>(p, x, gate_w, (bf16*)d_out);
}
```

```cpp
#include <cuda_runtime.h>
#include <cuda_bf16.h>
#include <cuda.h>
#include <stdint.h>

typedef __nv_bfloat16 bf16;

constexpr int S_LEN = 2048, DM = 576, DC = 512, HDIM = 4096, NQKVA = 1728, KCAT = 4672;
constexpr int NCLUSTER = 66;

__device__ __align__(1024) bf16 g_K[S_LEN * HDIM];
__device__ __align__(1024) bf16 g_V[S_LEN * HDIM];
__device__ __align__(1024) bf16 g_QKVA[S_LEN * NQKVA + 64];
__device__ __align__(1024) bf16 g_ctx[S_LEN * KCAT];
__device__ float g_gate[S_LEN];
__device__ __align__(1024) uint4 g_part[32 * 4 * 4 * 5 * 256];
__device__ __align__(16) unsigned int g_sync[400];
constexpr int F_QKVA = 0, F_HP = 16, F_CTX = 32, F_OA = 48, F_GATE = 96, F_TICK = 97, F_DONE = 98, F_XCH = 128, F_EPOCH = 384;

__device__ __forceinline__ uint32_t smem_u32(const void* p) { return (uint32_t)__cvta_generic_to_shared(p); }
__device__ __forceinline__ void mbar_init(uint32_t a, uint32_t c) {
  asm volatile("mbarrier.init.shared::cta.b64 [%0], %1;" ::"r"(a), "r"(c));
}
__device__ __forceinline__ void mbar_expect(uint32_t a, uint32_t b) {
  asm volatile("mbarrier.arrive.expect_tx.shared::cta.b64 _, [%0], %1;" ::"r"(a), "r"(b) : "memory");
}
#define TS(k, i)
#define TSC(k, i)
#define TSM(k)
#define BSEG(i)
#define TB(k)
#define TRC(fl)
#define TCK(i)
#define SPIN_LIMIT "4194304"
__device__ __forceinline__ void mbar_wait(uint32_t a, uint32_t parity) {
  asm volatile(
      "{\n.reg .pred p;\n.reg .u32 n;\n"
      "mbarrier.try_wait.parity.shared::cta.b64 p, [%0], %1;\n"
      "@p bra DONE;\n"
      "mov.u32 n, 0;\n"
      "LOOP:\n"
      "mbarrier.try_wait.parity.shared::cta.b64 p, [%0], %1;\n"
      "@p bra DONE;\n"
      "add.u32 n, n, 1;\n"
      "setp.lt.u32 p, n, " SPIN_LIMIT ";\n"
      "@p bra LOOP;\n"
      "DONE:\n}" ::"r"(a), "r"(parity) : "memory");
}
template <int NS>
__device__ __forceinline__ void mbar_wait_ns(uint32_t a, uint32_t parity) {
  asm volatile(
      "{\n.reg .pred p;\n.reg .u32 n;\n"
      "mov.u32 n, 0;\n"
      "LOOP:\n"
      "mbarrier.try_wait.parity.shared::cta.b64 p, [%0], %1, %2;\n"
      "@p bra DONE;\n"
      "add.u32 n, n, 1;\n"
      "setp.lt.u32 p, n, " SPIN_LIMIT ";\n"
      "@p bra LOOP;\n"
      "DONE:\n}" ::"r"(a), "r"(parity), "n"(NS) : "memory");
}
__device__ __forceinline__ void mbar_wait2(uint32_t a, uint32_t pa, uint32_t b, uint32_t pb) {
  asm volatile(
      "{\n.reg .pred p, q;\n.reg .u32 n;\n"
      "mov.u32 n, 0;\n"
      "LOOP:\n"
      "mbarrier.try_wait.parity.shared::cta.b64 p, [%0], %1;\n"
      "mbarrier.try_wait.parity.shared::cta.b64 q, [%2], %3;\n"
      "add.u32 n, n, 1;\n"
      "and.pred p, p, q;\n"
      "setp.lt.and.u32 p, n, " SPIN_LIMIT ", !p;\n"
      "@p bra LOOP;\n"
      "}" ::"r"(a), "r"(pa), "r"(b), "r"(pb) : "memory");
}
__device__ __forceinline__ uint32_t mbar_test(uint32_t a, uint32_t parity) {
  uint32_t r;
  asm volatile("{\n.reg .pred p;\nmbarrier.test_wait.parity.shared::cta.b64 p, [%1], %2;\nselp.u32 %0, 1, 0, p;\n}" : "=r"(r) : "r"(a), "r"(parity) : "memory");
  return r;
}
__device__ __forceinline__ void mbar_arrive(uint32_t a) {
  asm volatile("mbarrier.arrive.shared::cta.b64 _, [%0];" ::"r"(a) : "memory");
}
__device__ __forceinline__ void mbar_arrive_cluster(uint32_t a, uint32_t cta) {
  asm volatile("{\n.reg .b32 r;\nmapa.shared::cluster.u32 r, %0, %1;\nmbarrier.arrive.shared::cluster.b64 _, [r];\n}" ::"r"(a),
               "r"(cta) : "memory");
}
__device__ __forceinline__ void mbar_arrive_cluster_if(uint32_t a, uint32_t cta, bool pred) {
  asm volatile("{\n.reg .b32 r;\n.reg .pred p;\nsetp.ne.u32 p, %2, 0;\nmapa.shared::cluster.u32 r, %0, %1;\n@p mbarrier.arrive.shared::cluster.b64 _, [r];\n}" ::"r"(a),
               "r"(cta), "r"((uint32_t)pred) : "memory");
}
__device__ __forceinline__ void anchor(float v, uint32_t pred) {
  asm volatile("{\n.reg .pred p;\nsetp.ne.u32 p, %1, 0;\n@p st.shared.f32 [%1], %0;\n}" ::"f"(v), "r"(pred) : "memory");
}
__device__ __forceinline__ void mbar_arrive_if(uint32_t a, bool pred) {
  asm volatile("{\n.reg .pred p;\nsetp.ne.u32 p, %1, 0;\n@p mbarrier.arrive.shared::cta.b64 _, [%0];\n}" ::"r"(a), "r"((uint32_t)pred) : "memory");
}
__device__ __forceinline__ void tma2d(uint32_t dst, const CUtensorMap* m, uint32_t bar, int c0, int c1) {
  asm volatile("cp.async.bulk.tensor.2d.shared::cluster.global.mbarrier::complete_tx::bytes [%0], [%1, {%3, %4}], [%2];" ::"r"(dst),
               "l"(m), "r"(bar), "r"(c0), "r"(c1) : "memory");
}
__device__ __forceinline__ void tma2d_mc(uint32_t dst, const CUtensorMap* m, uint32_t bar, int c0, int c1, uint16_t mask) {
  asm volatile(
      "cp.async.bulk.tensor.2d.shared::cluster.global.mbarrier::complete_tx::bytes.multicast::cluster [%0], [%1, {%3, %4}], [%2], %5;" ::"r"(dst),
      "l"(m), "r"(bar), "r"(c0), "r"(c1), "h"(mask) : "memory");
}
__device__ __forceinline__ void tma3d_mc(uint32_t dst, const CUtensorMap* m, uint32_t bar, int c0, int c1, int c2, uint16_t mask) {
  asm volatile(
      "cp.async.bulk.tensor.3d.shared::cluster.global.mbarrier::complete_tx::bytes.multicast::cluster [%0], [%1, {%3, %4, %5}], [%2], %6;" ::"r"(dst),
      "l"(m), "r"(bar), "r"(c0), "r"(c1), "r"(c2), "h"(mask) : "memory");
}
__device__ __forceinline__ void tma3d(uint32_t dst, const CUtensorMap* m, uint32_t bar, int c0, int c1, int c2) {
  asm volatile(
      "cp.async.bulk.tensor.3d.shared::cluster.global.mbarrier::complete_tx::bytes [%0], [%1, {%3, %4, %5}], [%2];" ::"r"(dst),
      "l"(m), "r"(bar), "r"(c0), "r"(c1), "r"(c2) : "memory");
}
__device__ __forceinline__ void tma_pf2d(const CUtensorMap* m, int c0, int c1) {
  asm volatile("cp.async.bulk.prefetch.tensor.2d.L2.global [%0, {%1, %2}];" ::"l"(m), "r"(c0), "r"(c1) : "memory");
}
__device__ __forceinline__ void tma_pf3d(const CUtensorMap* m, int c0, int c1, int c2) {
  asm volatile("cp.async.bulk.prefetch.tensor.3d.L2.global [%0, {%1, %2, %3}];" ::"l"(m), "r"(c0), "r"(c1), "r"(c2) : "memory");
}
__device__ __forceinline__ void prefetch_tmap(const CUtensorMap* m) {
  asm volatile("prefetch.tensormap [%0];" ::"l"(m) : "memory");
}
__device__ __forceinline__ void cluster_arrive() { asm volatile("barrier.cluster.arrive.relaxed.aligned;" ::: "memory"); }
__device__ __forceinline__ void cluster_wait() { asm volatile("barrier.cluster.wait.aligned;" ::: "memory"); }
__device__ __forceinline__ void cluster_sync() {
  cluster_arrive();
  cluster_wait();
}
__device__ __forceinline__ uint32_t cluster_rank() {
  uint32_t r;
  asm volatile("mov.u32 %0, %%cluster_ctarank;" : "=r"(r));
  return r;
}
__device__ __forceinline__ bool elect_one() {
  uint32_t p;
  asm volatile("{\n.reg .pred q;\nelect.sync _|q, 0xffffffff;\nselp.u32 %0, 1, 0, q;\n}" : "=r"(p));
  return p;
}
__device__ __forceinline__ void ldsm_x4(uint32_t& r0, uint32_t& r1, uint32_t& r2, uint32_t& r3, uint32_t addr) {
  asm volatile("ldmatrix.sync.aligned.m8n8.x4.shared.b16 {%0, %1, %2, %3}, [%4];" : "=r"(r0), "=r"(r1), "=r"(r2), "=r"(r3) : "r"(addr) : "memory");
}
__device__ __forceinline__ void wg_fence() { asm volatile("wgmma.fence.sync.aligned;" ::: "memory"); }
__device__ __forceinline__ void wg_commit() { asm volatile("wgmma.commit_group.sync.aligned;" ::: "memory"); }
template <int N>
__device__ __forceinline__ void wg_wait() { asm volatile("wgmma.wait_group.sync.aligned %0;" ::"n"(N) : "memory"); }
template <int N>
__device__ __forceinline__ void reg_alloc() { asm volatile("setmaxnreg.inc.sync.aligned.u32 %0;" ::"n"(N)); }
template <int N>
__device__ __forceinline__ void reg_dealloc() { asm volatile("setmaxnreg.dec.sync.aligned.u32 %0;" ::"n"(N)); }
__device__ __forceinline__ void bar_sync(int id, int n) { asm volatile("bar.sync %0, %1;" ::"r"(id), "r"(n) : "memory"); }
__device__ __forceinline__ void bar_arrive(int id, int n) { asm volatile("bar.arrive %0, %1;" ::"r"(id), "r"(n) : "memory"); }
template <int NT>
__device__ __forceinline__ void fence_regs(float (&d)[NT]) {
#pragma unroll
  for (int i = 0; i < NT; i++) asm volatile("" : "+f"(d[i])::"memory");
}
template <int NT>
__device__ __forceinline__ void fence_regs(uint32_t (&d)[NT]) {
#pragma unroll
  for (int i = 0; i < NT; i++) asm volatile("" : "+r"(d[i])::"memory");
}
__device__ __forceinline__ uint64_t make_desc(uint32_t saddr, uint32_t lbo, uint32_t sbo, uint32_t layout) {
  return (uint64_t)((saddr & 0x3FFFF) >> 4) | ((uint64_t)(lbo >> 4) << 16) | ((uint64_t)(sbo >> 4) << 32) | ((uint64_t)layout << 62);
}
__device__ __forceinline__ uint32_t pack_bf16(float lo, float hi) {
  uint32_t r;
  asm("cvt.rn.bf16x2.f32 %0, %1, %2;" : "=r"(r) : "f"(hi), "f"(lo));
  return r;
}
__device__ __forceinline__ float ex2(float x) {
  float r;
  asm("ex2.approx.ftz.f32 %0, %1;" : "=f"(r) : "f"(x));
  return r;
}
__device__ __forceinline__ void st_v4(void* p, uint32_t a, uint32_t b, uint32_t c, uint32_t d) {
#define ST_MOD ".cs"
  asm volatile("st.global" ST_MOD ".v4.b32 [%0], {%1, %2, %3, %4};" ::"l"(p), "r"(a), "r"(b), "r"(c), "r"(d) : "memory");
}
#define STA_MOD ".cs"
__device__ __forceinline__ void st_v4a(void* p, uint32_t a, uint32_t b, uint32_t c, uint32_t d) {
  asm volatile("st.global" STA_MOD ".v4.b32 [%0], {%1, %2, %3, %4};" ::"l"(p), "r"(a), "r"(b), "r"(c), "r"(d) : "memory");
}
template <typename T>
__device__ __forceinline__ T* ptr_add(T* base, uint32_t bytes) {
  uint64_t r;
  asm volatile("{\n.reg .u32 l, h;\nmov.b64 {l, h}, %1;\nadd.cc.u32 l, l, %2;\naddc.u32 h, h, 0;\nmov.b64 %0, {l, h};\n}" : "=l"(r) : "l"(base), "r"(bytes));
  return reinterpret_cast<T*>(r);
}
__device__ __forceinline__ float bf_lo(uint32_t v) { return __uint_as_float(v << 16); }
__device__ __forceinline__ float bf_hi(uint32_t v) { return __uint_as_float(v & 0xFFFF0000u); }

__device__ __forceinline__ void quad_transpose(uint32_t& a0, uint32_t& a1, uint32_t& a2, uint32_t& a3, int q) {
  const bool o1 = q & 1, o2 = q & 2;
  uint32_t t0 = o1 ? a0 : a1, t1 = o1 ? a2 : a3;
  t0 = __shfl_xor_sync(0xffffffffu, t0, 1);
  t1 = __shfl_xor_sync(0xffffffffu, t1, 1);
  if (o1) { a0 = t0; a2 = t1; } else { a1 = t0; a3 = t1; }
  t0 = o2 ? a0 : a2;
  t1 = o2 ? a1 : a3;
  t0 = __shfl_xor_sync(0xffffffffu, t0, 2);
  t1 = __shfl_xor_sync(0xffffffffu, t1, 2);
  if (o2) { a0 = t0; a1 = t1; } else { a2 = t0; a3 = t1; }
}

template<int TB, int OFF, int NT>
__device__ __forceinline__ void wgmma_ss_n256(float (&d)[NT], uint64_t da, uint64_t db, int scale_d) {
  asm volatile("{\n.reg .pred p;\nsetp.ne.b32 p, %130, 0;\n"
    "wgmma.mma_async.sync.aligned.m64n256k16.f32.bf16.bf16 {%0, %1, %2, %3, %4, %5, %6, %7, %8, %9, %10, %11, %12, %13, %14, %15, %16, %17, %18, %19, %20, %21, %22, %23, %24, %25, %26, %27, %28, %29, %30, %31, %32, %33, %34, %35, %36, %37, %38, %39, %40, %41, %42, %43, %44, %45, %46, %47, %48, %49, %50, %51, %52, %53, %54, %55, %56, %57, %58, %59, %60, %61, %62, %63, %64, %65, %66, %67, %68, %69, %70, %71, %72, %73, %74, %75, %76, %77, %78, %79, %80, %81, %82, %83, %84, %85, %86, %87, %88, %89, %90, %91, %92, %93, %94, %95, %96, %97, %98, %99, %100, %101, %102, %103, %104, %105, %106, %107, %108, %109, %110, %111, %112, %113, %114, %115, %116, %117, %118, %119, %120, %121, %122, %123, %124, %125, %126, %127}, %128, %129, p, 1, 1, 0, %131;\n}\n"
    : "+f"(d[OFF+0]), "+f"(d[OFF+1]), "+f"(d[OFF+2]), "+f"(d[OFF+3]), "+f"(d[OFF+4]), "+f"(d[OFF+5]), "+f"(d[OFF+6]), "+f"(d[OFF+7]), "+f"(d[OFF+8]), "+f"(d[OFF+9]), "+f"(d[OFF+10]), "+f"(d[OFF+11]), "+f"(d[OFF+12]), "+f"(d[OFF+13]), "+f"(d[OFF+14]), "+f"(d[OFF+15]), "+f"(d[OFF+16]), "+f"(d[OFF+17]), "+f"(d[OFF+18]), "+f"(d[OFF+19]), "+f"(d[OFF+20]), "+f"(d[OFF+21]), "+f"(d[OFF+22]), "+f"(d[OFF+23]), "+f"(d[OFF+24]), "+f"(d[OFF+25]), "+f"(d[OFF+26]), "+f"(d[OFF+27]), "+f"(d[OFF+28]), "+f"(d[OFF+29]), "+f"(d[OFF+30]), "+f"(d[OFF+31]), "+f"(d[OFF+32]), "+f"(d[OFF+33]), "+f"(d[OFF+34]), "+f"(d[OFF+35]), "+f"(d[OFF+36]), "+f"(d[OFF+37]), "+f"(d[OFF+38]), "+f"(d[OFF+39]), "+f"(d[OFF+40]), "+f"(d[OFF+41]), "+f"(d[OFF+42]), "+f"(d[OFF+43]), "+f"(d[OFF+44]), "+f"(d[OFF+45]), "+f"(d[OFF+46]), "+f"(d[OFF+47]), "+f"(d[OFF+48]), "+f"(d[OFF+49]), "+f"(d[OFF+50]), "+f"(d[OFF+51]), "+f"(d[OFF+52]), "+f"(d[OFF+53]), "+f"(d[OFF+54]), "+f"(d[OFF+55]), "+f"(d[OFF+56]), "+f"(d[OFF+57]), "+f"(d[OFF+58]), "+f"(d[OFF+59]), "+f"(d[OFF+60]), "+f"(d[OFF+61]), "+f"(d[OFF+62]), "+f"(d[OFF+63]), "+f"(d[OFF+64]), "+f"(d[OFF+65]), "+f"(d[OFF+66]), "+f"(d[OFF+67]), "+f"(d[OFF+68]), "+f"(d[OFF+69]), "+f"(d[OFF+70]), "+f"(d[OFF+71]), "+f"(d[OFF+72]), "+f"(d[OFF+73]), "+f"(d[OFF+74]), "+f"(d[OFF+75]), "+f"(d[OFF+76]), "+f"(d[OFF+77]), "+f"(d[OFF+78]), "+f"(d[OFF+79]), "+f"(d[OFF+80]), "+f"(d[OFF+81]), "+f"(d[OFF+82]), "+f"(d[OFF+83]), "+f"(d[OFF+84]), "+f"(d[OFF+85]), "+f"(d[OFF+86]), "+f"(d[OFF+87]), "+f"(d[OFF+88]), "+f"(d[OFF+89]), "+f"(d[OFF+90]), "+f"(d[OFF+91]), "+f"(d[OFF+92]), "+f"(d[OFF+93]), "+f"(d[OFF+94]), "+f"(d[OFF+95]), "+f"(d[OFF+96]), "+f"(d[OFF+97]), "+f"(d[OFF+98]), "+f"(d[OFF+99]), "+f"(d[OFF+100]), "+f"(d[OFF+101]), "+f"(d[OFF+102]), "+f"(d[OFF+103]), "+f"(d[OFF+104]), "+f"(d[OFF+105]), "+f"(d[OFF+106]), "+f"(d[OFF+107]), "+f"(d[OFF+108]), "+f"(d[OFF+109]), "+f"(d[OFF+110]), "+f"(d[OFF+111]), "+f"(d[OFF+112]), "+f"(d[OFF+113]), "+f"(d[OFF+114]), "+f"(d[OFF+115]), "+f"(d[OFF+116]), "+f"(d[OFF+117]), "+f"(d[OFF+118]), "+f"(d[OFF+119]), "+f"(d[OFF+120]), "+f"(d[OFF+121]), "+f"(d[OFF+122]), "+f"(d[OFF+123]), "+f"(d[OFF+124]), "+f"(d[OFF+125]), "+f"(d[OFF+126]), "+f"(d[OFF+127])
    : "l"(da), "l"(db), "r"(scale_d), "n"(TB));
}
template<int TB, int OFF, int NT>
__device__ __forceinline__ void wgmma_ss_n32(float (&d)[NT], uint64_t da, uint64_t db, int scale_d) {
  asm volatile("{\n.reg .pred p;\nsetp.ne.b32 p, %18, 0;\n"
    "wgmma.mma_async.sync.aligned.m64n32k16.f32.bf16.bf16 {%0, %1, %2, %3, %4, %5, %6, %7, %8, %9, %10, %11, %12, %13, %14, %15}, %16, %17, p, 1, 1, 0, %19;\n}\n"
    : "+f"(d[OFF+0]), "+f"(d[OFF+1]), "+f"(d[OFF+2]), "+f"(d[OFF+3]), "+f"(d[OFF+4]), "+f"(d[OFF+5]), "+f"(d[OFF+6]), "+f"(d[OFF+7]), "+f"(d[OFF+8]), "+f"(d[OFF+9]), "+f"(d[OFF+10]), "+f"(d[OFF+11]), "+f"(d[OFF+12]), "+f"(d[OFF+13]), "+f"(d[OFF+14]), "+f"(d[OFF+15])
    : "l"(da), "l"(db), "r"(scale_d), "n"(TB));
}
template<int TB, int OFF, int NT>
__device__ __forceinline__ void wgmma_rs_n128(float (&d)[NT], uint32_t a0, uint32_t a1, uint32_t a2, uint32_t a3, uint64_t db, int scale_d) {
  asm volatile("{\n.reg .pred p;\nsetp.ne.b32 p, %69, 0;\n"
    "wgmma.mma_async.sync.aligned.m64n128k16.f32.bf16.bf16 {%0, %1, %2, %3, %4, %5, %6, %7, %8, %9, %10, %11, %12, %13, %14, %15, %16, %17, %18, %19, %20, %21, %22, %23, %24, %25, %26, %27, %28, %29, %30, %31, %32, %33, %34, %35, %36, %37, %38, %39, %40, %41, %42, %43, %44, %45, %46, %47, %48, %49, %50, %51, %52, %53, %54, %55, %56, %57, %58, %59, %60, %61, %62, %63}, {%64, %65, %66, %67}, %68, p, 1, 1, %70;\n}\n"
    : "+f"(d[OFF+0]), "+f"(d[OFF+1]), "+f"(d[OFF+2]), "+f"(d[OFF+3]), "+f"(d[OFF+4]), "+f"(d[OFF+5]), "+f"(d[OFF+6]), "+f"(d[OFF+7]), "+f"(d[OFF+8]), "+f"(d[OFF+9]), "+f"(d[OFF+10]), "+f"(d[OFF+11]), "+f"(d[OFF+12]), "+f"(d[OFF+13]), "+f"(d[OFF+14]), "+f"(d[OFF+15]), "+f"(d[OFF+16]), "+f"(d[OFF+17]), "+f"(d[OFF+18]), "+f"(d[OFF+19]), "+f"(d[OFF+20]), "+f"(d[OFF+21]), "+f"(d[OFF+22]), "+f"(d[OFF+23]), "+f"(d[OFF+24]), "+f"(d[OFF+25]), "+f"(d[OFF+26]), "+f"(d[OFF+27]), "+f"(d[OFF+28]), "+f"(d[OFF+29]), "+f"(d[OFF+30]), "+f"(d[OFF+31]), "+f"(d[OFF+32]), "+f"(d[OFF+33]), "+f"(d[OFF+34]), "+f"(d[OFF+35]), "+f"(d[OFF+36]), "+f"(d[OFF+37]), "+f"(d[OFF+38]), "+f"(d[OFF+39]), "+f"(d[OFF+40]), "+f"(d[OFF+41]), "+f"(d[OFF+42]), "+f"(d[OFF+43]), "+f"(d[OFF+44]), "+f"(d[OFF+45]), "+f"(d[OFF+46]), "+f"(d[OFF+47]), "+f"(d[OFF+48]), "+f"(d[OFF+49]), "+f"(d[OFF+50]), "+f"(d[OFF+51]), "+f"(d[OFF+52]), "+f"(d[OFF+53]), "+f"(d[OFF+54]), "+f"(d[OFF+55]), "+f"(d[OFF+56]), "+f"(d[OFF+57]), "+f"(d[OFF+58]), "+f"(d[OFF+59]), "+f"(d[OFF+60]), "+f"(d[OFF+61]), "+f"(d[OFF+62]), "+f"(d[OFF+63])
    : "r"(a0), "r"(a1), "r"(a2), "r"(a3), "l"(db), "r"(scale_d), "n"(TB));
}
template<int TB, int OFF, int NT>
__device__ __forceinline__ void wgmma_rs_n256(float (&d)[NT], uint32_t a0, uint32_t a1, uint32_t a2, uint32_t a3, uint64_t db, int scale_d) {
  asm volatile("{\n.reg .pred p;\nsetp.ne.b32 p, %133, 0;\n"
    "wgmma.mma_async.sync.aligned.m64n256k16.f32.bf16.bf16 {%0, %1, %2, %3, %4, %5, %6, %7, %8, %9, %10, %11, %12, %13, %14, %15, %16, %17, %18, %19, %20, %21, %22, %23, %24, %25, %26, %27, %28, %29, %30, %31, %32, %33, %34, %35, %36, %37, %38, %39, %40, %41, %42, %43, %44, %45, %46, %47, %48, %49, %50, %51, %52, %53, %54, %55, %56, %57, %58, %59, %60, %61, %62, %63, %64, %65, %66, %67, %68, %69, %70, %71, %72, %73, %74, %75, %76, %77, %78, %79, %80, %81, %82, %83, %84, %85, %86, %87, %88, %89, %90, %91, %92, %93, %94, %95, %96, %97, %98, %99, %100, %101, %102, %103, %104, %105, %106, %107, %108, %109, %110, %111, %112, %113, %114, %115, %116, %117, %118, %119, %120, %121, %122, %123, %124, %125, %126, %127}, {%128, %129, %130, %131}, %132, p, 1, 1, %134;\n}\n"
    : "+f"(d[OFF+0]), "+f"(d[OFF+1]), "+f"(d[OFF+2]), "+f"(d[OFF+3]), "+f"(d[OFF+4]), "+f"(d[OFF+5]), "+f"(d[OFF+6]), "+f"(d[OFF+7]), "+f"(d[OFF+8]), "+f"(d[OFF+9]), "+f"(d[OFF+10]), "+f"(d[OFF+11]), "+f"(d[OFF+12]), "+f"(d[OFF+13]), "+f"(d[OFF+14]), "+f"(d[OFF+15]), "+f"(d[OFF+16]), "+f"(d[OFF+17]), "+f"(d[OFF+18]), "+f"(d[OFF+19]), "+f"(d[OFF+20]), "+f"(d[OFF+21]), "+f"(d[OFF+22]), "+f"(d[OFF+23]), "+f"(d[OFF+24]), "+f"(d[OFF+25]), "+f"(d[OFF+26]), "+f"(d[OFF+27]), "+f"(d[OFF+28]), "+f"(d[OFF+29]), "+f"(d[OFF+30]), "+f"(d[OFF+31]), "+f"(d[OFF+32]), "+f"(d[OFF+33]), "+f"(d[OFF+34]), "+f"(d[OFF+35]), "+f"(d[OFF+36]), "+f"(d[OFF+37]), "+f"(d[OFF+38]), "+f"(d[OFF+39]), "+f"(d[OFF+40]), "+f"(d[OFF+41]), "+f"(d[OFF+42]), "+f"(d[OFF+43]), "+f"(d[OFF+44]), "+f"(d[OFF+45]), "+f"(d[OFF+46]), "+f"(d[OFF+47]), "+f"(d[OFF+48]), "+f"(d[OFF+49]), "+f"(d[OFF+50]), "+f"(d[OFF+51]), "+f"(d[OFF+52]), "+f"(d[OFF+53]), "+f"(d[OFF+54]), "+f"(d[OFF+55]), "+f"(d[OFF+56]), "+f"(d[OFF+57]), "+f"(d[OFF+58]), "+f"(d[OFF+59]), "+f"(d[OFF+60]), "+f"(d[OFF+61]), "+f"(d[OFF+62]), "+f"(d[OFF+63]), "+f"(d[OFF+64]), "+f"(d[OFF+65]), "+f"(d[OFF+66]), "+f"(d[OFF+67]), "+f"(d[OFF+68]), "+f"(d[OFF+69]), "+f"(d[OFF+70]), "+f"(d[OFF+71]), "+f"(d[OFF+72]), "+f"(d[OFF+73]), "+f"(d[OFF+74]), "+f"(d[OFF+75]), "+f"(d[OFF+76]), "+f"(d[OFF+77]), "+f"(d[OFF+78]), "+f"(d[OFF+79]), "+f"(d[OFF+80]), "+f"(d[OFF+81]), "+f"(d[OFF+82]), "+f"(d[OFF+83]), "+f"(d[OFF+84]), "+f"(d[OFF+85]), "+f"(d[OFF+86]), "+f"(d[OFF+87]), "+f"(d[OFF+88]), "+f"(d[OFF+89]), "+f"(d[OFF+90]), "+f"(d[OFF+91]), "+f"(d[OFF+92]), "+f"(d[OFF+93]), "+f"(d[OFF+94]), "+f"(d[OFF+95]), "+f"(d[OFF+96]), "+f"(d[OFF+97]), "+f"(d[OFF+98]), "+f"(d[OFF+99]), "+f"(d[OFF+100]), "+f"(d[OFF+101]), "+f"(d[OFF+102]), "+f"(d[OFF+103]), "+f"(d[OFF+104]), "+f"(d[OFF+105]), "+f"(d[OFF+106]), "+f"(d[OFF+107]), "+f"(d[OFF+108]), "+f"(d[OFF+109]), "+f"(d[OFF+110]), "+f"(d[OFF+111]), "+f"(d[OFF+112]), "+f"(d[OFF+113]), "+f"(d[OFF+114]), "+f"(d[OFF+115]), "+f"(d[OFF+116]), "+f"(d[OFF+117]), "+f"(d[OFF+118]), "+f"(d[OFF+119]), "+f"(d[OFF+120]), "+f"(d[OFF+121]), "+f"(d[OFF+122]), "+f"(d[OFF+123]), "+f"(d[OFF+124]), "+f"(d[OFF+125]), "+f"(d[OFF+126]), "+f"(d[OFF+127])
    : "r"(a0), "r"(a1), "r"(a2), "r"(a3), "l"(db), "r"(scale_d), "n"(TB));
}
template<int TB, int OFF, int NT>
__device__ __forceinline__ void wgmma_rs_n32(float (&d)[NT], uint32_t a0, uint32_t a1, uint32_t a2, uint32_t a3, uint64_t db, int scale_d) {
  asm volatile("{\n.reg .pred p;\nsetp.ne.b32 p, %21, 0;\n"
    "wgmma.mma_async.sync.aligned.m64n32k16.f32.bf16.bf16 {%0, %1, %2, %3, %4, %5, %6, %7, %8, %9, %10, %11, %12, %13, %14, %15}, {%16, %17, %18, %19}, %20, p, 1, 1, %22;\n}\n"
    : "+f"(d[OFF+0]), "+f"(d[OFF+1]), "+f"(d[OFF+2]), "+f"(d[OFF+3]), "+f"(d[OFF+4]), "+f"(d[OFF+5]), "+f"(d[OFF+6]), "+f"(d[OFF+7]), "+f"(d[OFF+8]), "+f"(d[OFF+9]), "+f"(d[OFF+10]), "+f"(d[OFF+11]), "+f"(d[OFF+12]), "+f"(d[OFF+13]), "+f"(d[OFF+14]), "+f"(d[OFF+15])
    : "r"(a0), "r"(a1), "r"(a2), "r"(a3), "l"(db), "r"(scale_d), "n"(TB));
}

__device__ __forceinline__ void wait_flag(const unsigned int* f, uint32_t target) {
  uint32_t v;
#pragma unroll 1
  for (uint32_t spins = 0; spins < (1u << 22); spins++) {
    asm volatile("ld.acquire.gpu.global.u32 %0, [%1];" : "=r"(v) : "l"(f) : "memory");
    if (v >= target) break;
    __nanosleep(100);
  }
}
__device__ __forceinline__ uint32_t lds32(uint32_t a) {
  uint32_t v;
  asm volatile("ld.shared.u32 %0, [%1];" : "=r"(v) : "r"(a) : "memory");
  return v;
}
__device__ __forceinline__ float gate_row(int row, int lane, const bf16* __restrict__ x, const bf16* __restrict__ gate_w) {
  const uint32_t* xr = reinterpret_cast<const uint32_t*>(x + (size_t)row * DM);
  const uint32_t* gw2 = reinterpret_cast<const uint32_t*>(gate_w);
  float gs = 0.f;
#pragma unroll
  for (int i = 0; i < 9; i++) {
    const uint32_t a = __ldg(xr + lane + 32 * i), b = __ldg(gw2 + lane + 32 * i);
    gs = fmaf(bf_lo(a), bf_lo(b), gs);
    gs = fmaf(bf_hi(a), bf_hi(b), gs);
  }
#pragma unroll
  for (int o = 16; o; o >>= 1) gs += __shfl_xor_sync(0xffffffffu, gs, o);
  const float g = 1.f / (1.f + __expf(-gs));
  if (lane == 0) g_gate[row] = g;
  return g;
}
constexpr uint32_t LQ = 36864, LV = 55296;
__device__ __forceinline__ void mma16(float (&c)[4], uint32_t a0, uint32_t a1, uint32_t a2, uint32_t a3, uint32_t b0, uint32_t b1) {
  asm("mma.sync.aligned.m16n8k16.row.col.f32.bf16.bf16.f32 {%0, %1, %2, %3}, {%4, %5, %6, %7}, {%8, %9}, {%0, %1, %2, %3};"
      : "+f"(c[0]), "+f"(c[1]), "+f"(c[2]), "+f"(c[3]) : "r"(a0), "r"(a1), "r"(a2), "r"(a3), "r"(b0), "r"(b1));
}
__device__ __forceinline__ void mma8(float (&c)[4], uint32_t a0, uint32_t a1, uint32_t b0) {
  asm("mma.sync.aligned.m16n8k8.row.col.f32.bf16.bf16.f32 {%0, %1, %2, %3}, {%4, %5}, {%6}, {%0, %1, %2, %3};"
      : "+f"(c[0]), "+f"(c[1]), "+f"(c[2]), "+f"(c[3]) : "r"(a0), "r"(a1), "r"(b0));
}
template <typename F>
__device__ __forceinline__ void local_attn(int lr0, int warp_g, uint32_t sL, uint32_t bL, uint32_t bL2, int lane, float g0, float g1, F st) {
  const float scale_l2 = 0.23570226039551584f * 1.4426950408889634f;
  const int g = lane >> 2, t = lane & 3;
  const bool lo0 = 2 * t > g, lo1 = 2 * t + 1 > g;
  const uint32_t mlo = (lo0 ? 0xFFFFu : 0u) | (lo1 ? 0xFFFF0000u : 0u);
  const bool ok0 = lr0 > 0 || !lo0, ok1 = lr0 > 0 || !lo1;
  uint32_t ad[9], k[9][4], qf[9][2], pe[4], po[4];
#pragma unroll
  for (int c = 0; c < 9; c++) {
    const uint32_t ch = warp_g * 9 + c;
    ad[c] = sL + (lane >> 4) * 18432 + (lane & 15) * 128 + ((ch >> 3) << 11) + (((ch ^ lane) & 7) << 4);
  }
  st(0, 0u); st(1, 0u);
  mbar_wait(bL, 0);
  if (warp_g == 0) TS(1, 6);
#pragma unroll
  for (int c = 0; c < 9; c++) {
    asm volatile("ldmatrix.sync.aligned.m8n8.x2.shared.b16 {%0, %1}, [%2];" : "=r"(qf[c][0]), "=r"(qf[c][1]) : "r"(ad[c] + LQ) : "memory");
    ldsm_x4(k[c][0], k[c][1], k[c][2], k[c][3], ad[c]);
  }
  st(2, k[0][0]); st(3, k[8][0]);
#pragma unroll
  for (int i = 0; i < 4; i++) {
    const uint32_t q0 = (t >= i) ? qf[2 * i][0] : 0u, q1 = (t >= i) ? qf[2 * i][1] : 0u;
    const uint32_t q4 = (t <= i) ? qf[2 * i + 2][0] : 0u, q5 = (t <= i) ? qf[2 * i + 2][1] : 0u;
    float c[4][4];
#pragma unroll
    for (int T = 0; T < 4; T++) {
#pragma unroll
      for (int j = 0; j < 4; j++) c[T][j] = 0.f;
      mma16(c[T], q0, q1, qf[2 * i + 1][0], qf[2 * i + 1][1], k[2 * i][T], k[2 * i + 1][T]);
      mma8(c[T], q4, q5, k[2 * i + 2][T]);
    }
    const float e0 = ok0 ? (lo0 ? c[0][0] : c[1][0]) : -INFINITY, e1 = ok1 ? (lo1 ? c[0][1] : c[1][1]) : -INFINITY;
    const float o0 = ok0 ? (lo0 ? c[2][2] : c[3][2]) : -INFINITY, o1 = ok1 ? (lo1 ? c[2][3] : c[3][3]) : -INFINITY;
    float me = fmaxf(e0, e1), mo = fmaxf(o0, o1);
    me = fmaxf(me, __shfl_xor_sync(0xffffffffu, me, 1));
    mo = fmaxf(mo, __shfl_xor_sync(0xffffffffu, mo, 1));
    me = fmaxf(me, __shfl_xor_sync(0xffffffffu, me, 2)) * scale_l2;
    mo = fmaxf(mo, __shfl_xor_sync(0xffffffffu, mo, 2)) * scale_l2;
    const float w0 = ex2(fmaf(e0, scale_l2, -me)), w1 = ex2(fmaf(e1, scale_l2, -me));
    const float w2 = ex2(fmaf(o0, scale_l2, -mo)), w3 = ex2(fmaf(o1, scale_l2, -mo));
    float se = w0 + w1, so = w2 + w3;
    st(4 + 2 * i, __float_as_uint(i == 1 ? me : i == 2 ? se : e0));
    se += __shfl_xor_sync(0xffffffffu, se, 1);
    so += __shfl_xor_sync(0xffffffffu, so, 1);
    se += __shfl_xor_sync(0xffffffffu, se, 2);
    so += __shfl_xor_sync(0xffffffffu, so, 2);
    asm("rcp.approx.ftz.f32 %0, %0;" : "+f"(se));
    asm("rcp.approx.ftz.f32 %0, %0;" : "+f"(so));
    se *= g0;
    so *= g1;
    pe[i] = pack_bf16(w0 * se, w1 * se);
    po[i] = pack_bf16(w2 * so, w3 * so);
    st(5 + 2 * i, i == 0 ? __float_as_uint(w0) : i == 2 ? __float_as_uint(mo) : po[i]);
  }
  if (warp_g == 0) TS(0, 4);
  mbar_wait(bL2, 0);
  if (warp_g == 0) TS(0, 5);
#pragma unroll
  for (int c = 0; c < 9; c++)
    asm volatile("ldmatrix.sync.aligned.m8n8.x4.trans.shared.b16 {%0, %1, %2, %3}, [%4];"
                 : "=r"(k[c][0]), "=r"(k[c][1]), "=r"(k[c][2]), "=r"(k[c][3]) : "r"(ad[c] + LV) : "memory");
#pragma unroll
  for (int i = 0; i < 4; i++) {
#pragma unroll
    for (int n = 0; n < 3; n++) {
      float c[4] = {0.f, 0.f, 0.f, 0.f};
      mma16(c, pe[i] & mlo, 0u, pe[i] & ~mlo, 0u, k[2 * i + n][0], k[2 * i + n][1]);
      mma16(c, 0u, po[i] & mlo, 0u, po[i] & ~mlo, k[2 * i + n][2], k[2 * i + n][3]);
      const uint32_t r0 = pack_bf16(c[0], c[1]), r1 = pack_bf16(c[2], c[3]);
      const bool keep = (n == 0) && (t < i);
      qf[2 * i + n][0] = keep ? qf[2 * i + n][0] : r0;
      qf[2 * i + n][1] = keep ? qf[2 * i + n][1] : r1;
    }
    st(12 + i, qf[2 * i + 1][0]);
  }
#pragma unroll
  for (int c = 0; c < 9; c++)
    asm volatile("stmatrix.sync.aligned.m8n8.x2.shared.b16 [%0], {%1, %2};" ::"r"(ad[c] + LQ), "r"(qf[c][0]), "r"(qf[c][1]) : "memory");
  asm volatile("fence.proxy.async.shared::cta;" ::: "memory");
}
__device__ __forceinline__ void tma4d(uint32_t dst, const CUtensorMap* m, uint32_t bar, int c1, int c2, int c3) {
  asm volatile("cp.async.bulk.tensor.4d.shared::cluster.global.mbarrier::complete_tx::bytes [%0], [%1, {%3, %4, %5, %6}], [%2];" ::"r"(dst),
               "l"(m), "r"(bar), "r"(0), "r"(c1), "r"(c2), "r"(c3) : "memory");
}

#define ST_NUM 1
#define ST_DEN 2
#define K1_NST 6
constexpr int K1_BST = K1_NST;
#define MAXJ 11
constexpr int K1_MAXJOBS = MAXJ;
constexpr uint32_t K1_FLAG_TARGET = 7;
constexpr uint32_t RDY_TARGET = 48;
constexpr uint32_t GATE_TARGET = 128 * 3;
struct alignas(64) Params {
  CUtensorMap tmA[2];
  CUtensorMap tmW[4];
  CUtensorMap tmK, tmV;
  CUtensorMap tmL[3];
  CUtensorMap tmC, tmO[2], tmOt[2];
  uint16_t jobs[NCLUSTER][K1_MAXJOBS + 1];
  uint8_t order[256];
  uint8_t unit[65][8];
};

struct K1State {
  uint32_t bs, bph, aph;
  bf16 *pp, *pp8;
  int png;
  int tn;
  int wsel;
};
__device__ __forceinline__ void k1_flag(const K1State& st, int lane, uint32_t bS) {
  if (st.png) {
    __syncwarp();
    if (lane == 0) mbar_arrive(bS);
  }
}

__device__ __forceinline__ void scale_q4(uint32_t* v) {
#pragma unroll
  for (int i = 0; i < 4; i++)
    asm volatile("{\n.reg .b32 t;\nmul.rn.bf16x2 t, %0, %2;\nfma.rn.bf16x2 %0, %0, %1, t;\n}" : "+r"(v[i]) : "r"(0x3E033E03u), "r"(0xB9D8B9D8u));
}
__device__ __forceinline__ void k1_first(const K1State& st, uint32_t job, uint32_t bAf, uint32_t bBf) {
  if (job & 3) {
    if ((job >> 14) & 1) mbar_wait(bAf, st.aph);
    mbar_wait(bBf + st.bs * 8, st.bph);
  }
}
__device__ __forceinline__ void k1_tile(float (&acc)[128], uint32_t (&pk)[64], K1State& st, uint32_t job, uint32_t njob, uint32_t sA, uint32_t sB,
                                        uint32_t bAf, uint32_t bAe, uint32_t bBf, uint32_t bBe, uint32_t bS, int wg, int warp, int lane, uint32_t rank) {
  const int a_sel = (job >> 2) & 1, mpair = (job >> 3) & 7, w_sel = (job >> 6) & 3, chunk0 = (job >> 8) & 63;
  const bool newA = (job >> 14) & 1, lastA = (job >> 15) & 1;
  const bool sig = (lane == 0) && (warp < 2);
  const bool siga = lastA && (lane == 0) && (warp == 2);
  const int KC = 8 + a_sel;
  uint32_t prev_bs = 0, a8_bs = 0;
#pragma unroll
  for (int kc = 0; kc < 9; kc++) {
    if (kc >= KC) break;
    uint32_t abase = sA + ((kc + 2) & 7) * 16384;
    if (kc == 8) {
      mbar_wait(bBf + st.bs * 8, st.bph);
      a8_bs = st.bs;
      abase = sB + st.bs * 16384;
      if (++st.bs == K1_BST) { st.bs = 0; st.bph ^= 1; }
    } else if (newA && kc > 0) {
      mbar_wait(bAf + kc * 8, st.aph);
    }
    const uint64_t da = make_desc(abase + wg * 8192, 16, 1024, 1);
#pragma unroll
    for (int ks = 0; ks < 2; ks++) {
      if (ks > 0 || kc > 0) mbar_wait(bBf + st.bs * 8, st.bph);
      const uint64_t db = make_desc(sB + st.bs * 16384, 2048, 1024, 1);
      wg_fence();
      wgmma_ss_n256<1, 0>(acc, da + (uint64_t)(ks * 4), db, (ks > 0) ? 1 : (kc > 0));
      wgmma_ss_n256<1, 0>(acc, da + (uint64_t)(ks * 4 + 2), db + (uint64_t)512, 1);
      wg_commit();
      wg_wait<1>();
      if (ks > 0 || kc > 0) {
        if (sig) mbar_arrive_cluster(bBe + prev_bs * 8, warp);
        if (ks == 0 && siga) mbar_arrive(bAe + (kc - 1) * 8);
      }
      if (st.wsel == 2) {
        const int i = (kc & 7) * 2 + ks;
        if (kc < st.png) {
          quad_transpose(pk[i * 4], pk[i * 4 + 1], pk[i * 4 + 2], pk[i * 4 + 3], lane & 3);
          st_v4a((ks ? st.pp8 : st.pp) + kc * 32, pk[i * 4], pk[i * 4 + 1], pk[i * 4 + 2], pk[i * 4 + 3]);
        }
        if (i == 15) k1_flag(st, lane, bS);
      } else if (st.png) {
#pragma unroll
        for (int i = 0; i < 16; i++) {
          if (i * ST_NUM / ST_DEN != kc * 2 + ks) continue;
          if (st.wsel == 3) scale_q4(pk + i * 4);
          st_v4a(((i & 1) ? st.pp8 : st.pp) + (i / 2) * 32, pk[i * 4], pk[i * 4 + 1], pk[i * 4 + 2], pk[i * 4 + 3]);
          if (i == 15) k1_flag(st, lane, bS);
        }
      }
      prev_bs = st.bs;
      if (++st.bs == K1_BST) { st.bs = 0; st.bph ^= 1; }
    }
  }
  if (newA) st.aph ^= 1;
  const bool isA = (w_sel == 2);
  bf16* out = (w_sel == 0) ? g_K : (w_sel == 1) ? g_V : isA ? g_QKVA : g_ctx;
  const int ld = isA ? NQKVA : (w_sel == 3) ? KCAT : HDIM;
  const int row = mpair * 256 + rank * 128 + wg * 64 + warp * 16 + (lane >> 2);
  st.pp = ptr_add(out, (row * ld + chunk0 * 64 + (lane & 3) * 8) * 2);
  st.pp8 = ptr_add(st.pp, 16 * ld);
  st.png = ((job & 3) + 1) * 2;
  st.wsel = w_sel;
  k1_first(st, njob, bAf, bBf);
  wg_wait<0>();
  fence_regs(acc);
  mbar_arrive_cluster_if(bBe + prev_bs * 8, warp & 1, sig);
  mbar_arrive_cluster_if(bBe + a8_bs * 8, warp & 1, sig && a_sel);
  mbar_arrive_if(bAe + 7 * 8, siga && !a_sel);
#pragma unroll
  for (int i = 0; i < 64; i++) {
    const int j = (i >> 3) * 16 + (i & 3) * 4 + ((i >> 2) & 1) * 2;
    pk[i] = pack_bf16(acc[j], acc[j + 1]);
  }
}

constexpr int K2_NST = 7;
constexpr uint32_t K2_END = 0x100;
#define PFD 4
#define PF3 3
#define FIRST_DRAW 3
#define PWAIT mbar_wait_ns<1000>
#define PVM 0x8A
#define W0 63
#define SPEC_HI 1.8446744073709552e19f
#define SPEC_LO 5.421010862427522e-20f
constexpr int K3_NST = 4;
__device__ __forceinline__ uint32_t k3_rot(uint32_t sv) { return (0x00E9u >> (2 * sv)) & 3; }
constexpr int K3_STAGE = 16384 + 32768 + 4096;
constexpr int SMEM_DATA = 7 * 32768;
constexpr int SMEM_BYTES = SMEM_DATA + 1024 + 768;

struct Cursor {
  uint32_t s, ph;
  __device__ __forceinline__ void next() {
    if (++s == K2_NST) { s = 0; ph ^= 1; }
  }
};

#define TURN_SYNC() bar_sync(mybar, 256)
#define TURN_ARRIVE() bar_arrive(otherbar, 256)
#define RELEASE_IF(cur, cond) mbar_arrive_cluster_if(bE + (cur).s * 8, warp & 1, sig && (cond))
#define RELEASE(cur) RELEASE_IF(cur, true)
#define ISSUE_PV(cur, first)                                                                                   \
  do {                                                                                                         \
    const uint64_t dv = make_desc(sbase + (cur).s * 32768, 16384, 1024, 1);                                    \
    _Pragma("unroll") for (int t = 0; t < 8; t++)                                                              \
        wgmma_rs_n128<1, 0>(O, P[4 * t], P[4 * t + 1], P[4 * t + 2], P[4 * t + 3], dv + (uint64_t)(t * 128), (t > 0) ? 1 : !(first)); \
  } while (0)
#define ISSUE_QK(cur)                                                                                          \
  do {                                                                                                         \
    const uint64_t dk = make_desc(sbase + (cur).s * 32768, 16, 1024, 1);                                       \
    _Pragma("unroll") for (int t = 0; t < 8; t++)                                                              \
        wgmma_rs_n128<0, 0>(S, Q[4 * t], Q[4 * t + 1], Q[4 * t + 2], Q[4 * t + 3], dk + (uint64_t)((t >> 2) * 1024 + (t & 3) * 2), t > 0); \
  } while (0)
#define EXPB(T)                                                                                                \
  do {                                                                                                         \
    _Pragma("unroll") for (int i = 4 * T; i < 4 * T + 4; i++) asm volatile("" : "+r"(P[i])::"memory");        \
    _Pragma("unroll") for (int jj = 2 * T; jj < 2 * T + 2; jj++) {                                             \
      const float e0 = ex2(S[jj * 4 + 0]), e1 = ex2(S[jj * 4 + 1]), e2 = ex2(S[jj * 4 + 2]), e3 = ex2(S[jj * 4 + 3]); \
      s0 += e0 + e1;                                                                                           \
      s1 += e2 + e3;                                                                                           \
      P[jj * 2 + 0] = pack_bf16(e0, e1);                                                                       \
      P[jj * 2 + 1] = pack_bf16(e2, e3);                                                                       \
    }                                                                                                          \
  } while (0)
#define EXPC(T)                                                                                                \
  do {                                                                                                         \
    if (T > 0 && ((PVM >> (T - 1)) & 1)) {                                                                     \
      anchor((T & 2) ? s0 : s1, never);                                                                        \
      wg_wait<__builtin_popcount(PVM >> T) - 1>();                                                             \
      if ((PVM >> T) == (128 >> T)) { fence_regs(O); RELEASE(cv); }                                            \
    }                                                                                                          \
    EXPB(T);                                                                                                   \
  } while (0)
#define MASK(G, g)                                                                                             \
  do {                                                                                                         \
    if ((g) * 8 > d) S[(G) * 4 + 0] = -INFINITY;                                                               \
    if ((g) * 8 + 1 > d) S[(G) * 4 + 1] = -INFINITY;                                                           \
    if ((g) * 8 - 8 > d) S[(G) * 4 + 2] = -INFINITY;                                                           \
    if ((g) * 8 - 7 > d) S[(G) * 4 + 3] = -INFINITY;                                                           \
  } while (0)
#define STORE_O(G)                                                                                             \
  do {                                                                                                         \
    st_v4(optr + (G) * 32, pack_bf16(O[(G) * 16 + 0] * f0, O[(G) * 16 + 1] * f0), pack_bf16(O[(G) * 16 + 4] * f0, O[(G) * 16 + 5] * f0), \
          pack_bf16(O[(G) * 16 + 8] * f0, O[(G) * 16 + 9] * f0), pack_bf16(O[(G) * 16 + 12] * f0, O[(G) * 16 + 13] * f0)); \
    st_v4(optr + 8 * KCAT + (G) * 32, pack_bf16(O[(G) * 16 + 2] * f1, O[(G) * 16 + 3] * f1), pack_bf16(O[(G) * 16 + 6] * f1, O[(G) * 16 + 7] * f1), \
          pack_bf16(O[(G) * 16 + 10] * f1, O[(G) * 16 + 11] * f1), pack_bf16(O[(G) * 16 + 14] * f1, O[(G) * 16 + 15] * f1)); \
  } while (0)

#define FLUSH()                                                                                                \
  do {                                                                                                         \
    _Pragma("unroll") for (int G = 0; G < 8; G++) {                                                            \
      st_v4a(st.pp + G * 32, pk[G * 8], pk[G * 8 + 1], pk[G * 8 + 2], pk[G * 8 + 3]);                          \
      st_v4a(st.pp8 + G * 32, pk[G * 8 + 4], pk[G * 8 + 5], pk[G * 8 + 6], pk[G * 8 + 7]);                     \
    }                                                                                                          \
    k1_flag(st, lane, bS);                                                                                     \
  } while (0)

__global__ void __cluster_dims__(2, 1, 1) __launch_bounds__(384, 1)
fused_kernel(const __grid_constant__ Params p, const bf16* __restrict__ x, const bf16* __restrict__ gate_w, bf16* __restrict__ out) {
  extern __shared__ uint8_t smem_raw[];
  const uint32_t sbase = (smem_u32(smem_raw) + 1023) & ~1023u;
  const uint32_t sB = sbase, sA = sbase + K1_BST * 16384, sBar = sbase + SMEM_DATA;
  const uint32_t bAf = sBar, bAe = sBar + 64, bBf = sBar + 128, bBe = sBar + 176, bL = sBar + 224, bS = sBar + 232, bL2 = sBar + 240, sL = sA + 32768;
  const uint32_t bF = sBar + 256, bE = sBar + 320, bT = sBar + 384, sTick = sBar + 400, sItem = sBar + 416, bS2 = sBar + 448, bR = sBar + 456, bLast = sBar + 464, bH = sBar + 472, bT0 = sBar + 480;
  const uint32_t b3F = sBar + 512, b3E = sBar + 544, sGate = sBar + 576;
  const int tid = threadIdx.x, warp_g = __shfl_sync(0xffffffffu, tid >> 5, 0), lane = tid & 31;
  const uint32_t rank = cluster_rank();
  const int cl = blockIdx.x >> 1;
  TSM(0);
  if (tid == 0) {
    for (int i = 0; i < 8; i++) { mbar_init(bAf + i * 8, 1); mbar_init(bAe + i * 8, 2); }
    for (int i = 0; i < K1_BST; i++) { mbar_init(bBf + i * 8, 1); mbar_init(bBe + i * 8, 4); }
    mbar_init(bL, 1);
    mbar_init(bL2, 1);
    mbar_init(bR, 1);
    mbar_init(bLast, 1);
    mbar_init(bH, 4);
    mbar_init(bT0, 1);
    mbar_init(bS, 8);
    for (int i = 0; i < K2_NST; i++) { mbar_init(bF + i * 8, 1); mbar_init(bE + i * 8, 4); }
    mbar_init(bT, 1); mbar_init(bT + 8, 1);
    mbar_init(bS2, 8);
    for (int i = 0; i < K3_NST; i++) { mbar_init(b3F + i * 8, 1); mbar_init(b3E + i * 8, 4); }
    asm volatile("fence.mbarrier_init.release.cluster;" ::: "memory");
  }
  __syncwarp();
  if (warp_g != 8) cluster_sync();
  const int lr0 = blockIdx.x * 16;

  if (warp_g >= 8) {
    reg_dealloc<40>();
    if (warp_g == 8) {
      {
        const uint32_t job = p.jobs[cl][0];
        if (lane == 0) { prefetch_tmap(&p.tmA[(job >> 2) & 1]); prefetch_tmap(&p.tmW[(job >> 6) & 3]); }
        __syncwarp();
        cluster_sync();
      }
      if (elect_one()) {
        uint32_t bs = 0, bph = 1, aph = 1;
#pragma unroll 1
        for (int ji = 0; ji < K1_MAXJOBS; ji++) {
          const uint32_t job = p.jobs[cl][ji];
          if (!(job & 3)) break;
          const int a_sel = (job >> 2) & 1, mpair = (job >> 3) & 7, chunk0 = (job >> 8) & 63;
          const bool newA = (job >> 14) & 1;
          const int KC = a_sel ? 9 : 8;
          const uint32_t halfbytes = 8192;
          const bool lastjob = (ji + 1 == K1_MAXJOBS) || !(p.jobs[cl][ji + 1] & 3);
          const CUtensorMap* tw = &p.tmW[(job >> 6) & 3];
          {
            const uint32_t njob = (ji + 1 < K1_MAXJOBS) ? p.jobs[cl][ji + 1] : 0;
            if (!(njob & 3) && !newA) mbar_arrive(bLast);
          }
#pragma unroll 1
          for (int kc = 0; kc < KC; kc++) {
            {
              const bool nx = kc + PFD >= KC;
              const uint32_t njob = nx ? p.jobs[cl][ji + 1] : job;
              const int pk = nx ? kc + PFD - KC : kc + PFD;
              if ((njob & 3) && (nx || ji > 0)) {
                if (cl >= 64 || ((pk ^ (cl >> 1)) & 3) == 0)
                  tma_pf3d(&p.tmW[(njob >> 6) & 3], 0, pk * 64 + (cl & 1) * 32 + rank * 16, (njob >> 8) & 63);
                if (((njob >> 14) & 1) || pk == 8) tma_pf2d(&p.tmA[(njob >> 2) & 1], pk * 64, ((njob >> 3) & 7) * 256 + rank * 128);
              }
            }
            if (kc == 8) {
              PWAIT(bBe + bs * 8, bph);
              mbar_expect(bBf + bs * 8, 16384);
              tma2d(sB + bs * 16384, &p.tmA[1], bBf + bs * 8, 512, mpair * 256 + rank * 128);
              if (++bs == K1_BST) { bs = 0; bph ^= 1; }
            } else if (newA) {
              PWAIT(bAe + kc * 8, aph);
              mbar_expect(bAf + kc * 8, 16384);
              tma2d(sA + ((kc + 2) & 7) * 16384, &p.tmA[a_sel], bAf + kc * 8, kc * 64, mpair * 256 + rank * 128);
              if (kc == 7 && lastjob) mbar_arrive(bLast);
            }
#pragma unroll 1
            for (int kk = 0; kk < 2; kk++) {
              PWAIT(bBe + bs * 8, bph);
              mbar_expect(bBf + bs * 8, 2 * halfbytes);
              tma3d_mc(sB + bs * 16384 + rank * halfbytes, tw, bBf + bs * 8, 0, kc * 64 + kk * 32 + rank * 16, chunk0, 3);
              if (++bs == K1_BST) { bs = 0; bph ^= 1; }
            }
          }
          if (newA) aph ^= 1;
        }
        Cursor c{0, 0};
        int pcol = 0;
        PWAIT(bR, 0);
        uint32_t tick = lds32(sTick + 8), seen = 1u << (p.order[tick] >> 4);
        asm volatile("fence.proxy.async.global;" ::: "memory");
#pragma unroll 1
        for (int it = 0;; it++) {
          const uint32_t item = (tick < 256) ? p.order[tick] : (K2_END | min(tick - 256, 255u));
          asm volatile("st.shared.u32 [%0], %1;" ::"r"(sItem + (it & 7) * 4), "r"(item) : "memory");
          if (item >= K2_END) break;
          const int h = item >> 3, j = item & 7;
          const int blk = 2 * j + (int)(rank ^ (it & 1));
          const int col = h * 128 + rank * 64;
          const int nb = 2 * j + 2;
          if (!((seen >> (h >> 1)) & 1)) {
            wait_flag(&g_sync[F_HP + (h >> 1)], RDY_TARGET);
            asm volatile("fence.proxy.async.global;" ::: "memory");
            seen |= 1u << (h >> 1);
          }
          PWAIT(bE + c.s * 8, c.ph);
          mbar_expect(bF + c.s * 8, 32768);
          tma2d(sbase + c.s * 32768, &p.tmC, bF + c.s * 8, h * 128, blk * 128);
          tma2d(sbase + c.s * 32768 + 16384, &p.tmC, bF + c.s * 8, h * 128 + 64, blk * 128);
          c.next();
          if (tick >= 256 - 73) {
            const int kk = tick - (256 - 73), sel = (kk < 9), kr = (sel ? kk : kk - 9) * 64 + rank * 32;
#pragma unroll 1
            for (int i = 0; i < 2; i++) {
              tma_pf3d(&p.tmO[sel], 0, kr, i * 4);
              tma_pf2d(&p.tmOt[sel], 512 + i * 32, kr);
            }
          }
#pragma unroll 1
          for (int n = nb - 1; n >= 0; n--) {
            if (n == 0 && rank == 0) tick = atomicAdd(&g_sync[F_TICK], 1u);
            PWAIT(bE + c.s * 8, c.ph);
            mbar_expect(bF + c.s * 8, 32768);
            tma2d_mc(sbase + c.s * 32768 + rank * 16384, &p.tmK, bF + c.s * 8, col, n * 128, 3);
            c.next();
            if (n < nb - 1 || it > 0) {
              PWAIT(bE + c.s * 8, c.ph);
              mbar_expect(bF + c.s * 8, 32768);
              tma2d_mc(sbase + c.s * 32768 + rank * 16384, &p.tmV, bF + c.s * 8, (n < nb - 1) ? col : pcol, (n < nb - 1) ? (n + 1) * 128 : 0, 3);
              c.next();
            }
          }
          pcol = col;
          if (rank == 0) {
            asm volatile(
                "{\n.reg .b32 a, b;\nmapa.shared::cluster.u32 a, %0, 1;\nmapa.shared::cluster.u32 b, %1, 1;\n"
                "st.async.shared::cluster.mbarrier::complete_tx::bytes.u32 [a], %2, [b];\n}" ::"r"(sTick + (it & 1) * 4),
                "r"(bT + (it & 1) * 8), "r"(tick) : "memory");
          } else {
            mbar_expect(bT + (it & 1) * 8, 4);
            PWAIT(bT + (it & 1) * 8, (it >> 1) & 1);
            tick = lds32(sTick + (it & 1) * 4);
          }
        }
        PWAIT(bE + c.s * 8, c.ph);
        mbar_expect(bF + c.s * 8, 32768);
        tma2d_mc(sbase + c.s * 32768 + rank * 16384, &p.tmV, bF + c.s * 8, pcol, 0, 3);
        const uint32_t unit = min(tick - 256, 64u);
        const int mblk = (7 - (p.unit[unit][0] >> 1)) * 2 + rank, nhalf = p.unit[unit][0] & 1;
        uint32_t have, hoa;
        asm volatile("ld.acquire.gpu.global.u32 %0, [%1];" : "=r"(have) : "l"(&g_sync[F_CTX + mblk]) : "memory");
        asm volatile("ld.acquire.gpu.global.u32 %0, [%1];" : "=r"(hoa) : "l"(&g_sync[F_OA + mblk]) : "memory");
        asm volatile("fence.proxy.async.global;" ::: "memory");
#pragma unroll 1
        for (uint32_t idx = 0; idx < PF3 && unit < 64; idx++) {
          const int kk = p.unit[unit][3] + idx;
          if ((kk < 9) ? (hoa >= 8) : ((have >> ((kk - 9) >> 1)) & 1)) tma_pf2d(&p.tmC, ((kk < 9) ? 64 + kk : kk - 9) * 64, mblk * 128);
        }
        if (unit < 64) {
          const uint32_t rot = k3_rot(c.s), nfree = ((0x1Au >> c.s) & 1) ? 2 : 3;
#pragma unroll 1
          for (int i = 0; i < K2_NST - 1; i++) {
            c.next();
            PWAIT(bE + c.s * 8, c.ph);
          }
#pragma unroll 1
          for (uint32_t idx = 0; idx < p.unit[unit][2]; idx++) {
            const int kk = p.unit[unit][3] + idx + ((idx >= p.unit[unit][4]) ? p.unit[unit][5] : 0);
            const uint32_t s = (rot + idx) & 3;
            if (idx >= nfree) PWAIT((idx < 4) ? bH : b3E + s * 8, (idx < 4) ? 0 : (~idx >> 2) & 1);
            mbar_expect(b3F + s * 8, K3_STAGE);
            const uint32_t st = sbase + s * K3_STAGE;
            const int sel = (kk < 9), k = sel ? kk : kk - 9, kr = k * 64 + rank * 32;
            tma3d_mc(st + 16384 + rank * 16384, &p.tmO[sel], b3F + s * 8, 0, kr, nhalf * 4, 3);
            tma2d_mc(st + 49152 + rank * 2048, &p.tmOt[sel], b3F + s * 8, 512 + nhalf * 32, kr, 3);
            if (sel && hoa < 8) {
              wait_flag(&g_sync[F_OA + mblk], 8);
              hoa = 8;
              asm volatile("fence.proxy.async.global;" ::: "memory");
            }
            if (!sel && !((have >> (k >> 1)) & 1)) {
#pragma unroll 1
              for (uint32_t spins = 0; spins < (1u << 22); spins++) {
                asm volatile("ld.acquire.gpu.global.u32 %0, [%1];" : "=r"(have) : "l"(&g_sync[F_CTX + mblk]) : "memory");
                if ((have >> (k >> 1)) & 1) break;
                __nanosleep(100);
              }
              asm volatile("fence.proxy.async.global;" ::: "memory");
            }
            tma2d(st, &p.tmC, b3F + s * 8, (sel ? 64 + k : k) * 64, mblk * 128);
          }
        }
      }
    }
    __syncwarp();
    if (warp_g == 8) {
      uint32_t v = 0;
      if (lane == 0) {
        __threadfence();
        v = atomicAdd(&g_sync[F_DONE], 1u);
      }
      if (__shfl_sync(0xffffffffu, v, 0) == 2 * NCLUSTER - 1) {
        reinterpret_cast<uint4*>(g_sync)[lane] = make_uint4(0, 0, 0, 0);
        if (lane == 0) g_sync[F_EPOCH] = lds32(sGate + 64) + 1;
      }
    }
    asm volatile("" ::: "memory");
    if (__shfl_sync(0xffffffffu, warp_g, 0) != 8) {
      if (lr0 < S_LEN) {
#pragma unroll 1
        for (int i = warp_g - 9; i < 16; i += 3) {
          const float g = gate_row(lr0 + i, lane, x, gate_w);
          if (lane == 0) asm volatile("st.shared.f32 [%0], %1;" ::"r"(sGate + i * 4), "f"(g) : "memory");
        }
        bar_arrive(3, 256 + 96);
        if (lane == 0) {
          __threadfence();
          atomicAdd(&g_sync[F_GATE], 1u);
        }
      }
      uint32_t aph = 1;
#pragma unroll 1
      for (int ji = 0; ji < K1_MAXJOBS; ji++) aph ^= (p.jobs[cl][ji] >> 14) & 1;
      if (warp_g == 9 && lane == 0) {
#pragma unroll 1
        for (int ji = 0; ji < K1_MAXJOBS; ji++) {
          const uint32_t job = p.jobs[cl][ji];
          if (!(job & 3)) break;
          PWAIT(bS, ji & 1);
          __threadfence();
          atomicAdd(&g_sync[(((job >> 6) & 3) == 2) ? (F_QKVA + ((job >> 3) & 7) * 2 + rank) : (F_HP + ((job >> 10) & 15))], 1u);
        }
#pragma unroll 1
        for (int it = 0;; it++) {
          PWAIT(bS2, it & 1);
          const uint32_t item = lds32(sItem + (it & 7) * 4), nxt = lds32(sItem + ((it + 1) & 7) * 4);
          __threadfence();
          atomicOr(&g_sync[F_CTX + (item & 7) * 2 + (rank ^ (it & 1))], 1u << (item >> 3));
          if (nxt >= K2_END) break;
        }
      } else if (warp_g == 11) {
        if (lane == 0) {
          prefetch_tmap(&p.tmC); prefetch_tmap(&p.tmK); prefetch_tmap(&p.tmV);
          asm volatile("st.shared.u32 [%0], %1;" ::"r"(sGate + 64), "r"(__ldcg(&g_sync[F_EPOCH])) : "memory");
          wait_flag(&g_sync[F_GATE], GATE_TARGET);
          uint32_t tick;
          if (rank == 0) {
            PWAIT(bLast, 0);
            PWAIT(bAe + FIRST_DRAW * 8, aph);
            tick = atomicAdd(&g_sync[F_TICK], 1u);
            asm volatile("st.shared.u32 [%0], %1;" ::"r"(sTick + 8), "r"(tick) : "memory");
            asm volatile(
                "{\n.reg .b32 a, b;\nmapa.shared::cluster.u32 a, %0, 1;\nmapa.shared::cluster.u32 b, %1, 1;\n"
                "st.async.shared::cluster.mbarrier::complete_tx::bytes.u32 [a], %2, [b];\n}" ::"r"(sTick + 8), "r"(bT0), "r"(tick) : "memory");
          } else {
            mbar_expect(bT0, 4);
            PWAIT(bT0, 0);
            tick = lds32(sTick + 8);
          }
          wait_flag(&g_sync[F_HP + (p.order[tick] >> 4)], RDY_TARGET);
          mbar_arrive(bR);
        }
      } else if (warp_g == 10) {
        if (lr0 < S_LEN && lane == 0) {
          prefetch_tmap(&p.tmL[0]); prefetch_tmap(&p.tmL[1]); prefetch_tmap(&p.tmL[2]);
          wait_flag(&g_sync[F_QKVA + (lr0 >> 7)], K1_FLAG_TARGET);
          wait_flag(&g_sync[F_QKVA + (max(lr0 - 16, 0) >> 7)], K1_FLAG_TARGET);
          asm volatile("fence.proxy.async.global;" ::: "memory");
          PWAIT(bLast, 0);
#pragma unroll 1
          for (int kc = 0; kc < 6; kc++) {
            PWAIT(bAe + kc * 8, aph);
            if (kc == 3) {
              mbar_expect(bL, LV);
              tma4d(sL, &p.tmL[0], bL, lr0 / 2 - 8, 9, 0);
              tma4d(sL + LQ, &p.tmL[1], bL, lr0 / 2, 0, 0);
            }
          }
          mbar_expect(bL2, LQ);
          tma4d(sL + LV, &p.tmL[0], bL2, lr0 / 2 - 8, 18, 0);
        }
        __syncwarp();
        bar_sync(5, 256 + 32);
        if (lr0 < S_LEN && lane == 0) {
          asm volatile("cp.async.bulk.tensor.4d.global.shared::cta.bulk_group [%0, {%2, %3, %2, %2}], [%1];" ::"l"(&p.tmL[2]), "r"(sL + LQ), "r"(0), "r"(lr0 / 2) : "memory");
          asm volatile("cp.async.bulk.commit_group;" ::: "memory");
          asm volatile("cp.async.bulk.wait_group.read 0;" ::: "memory");
        }
        __syncwarp();
        if (lane < 12) mbar_arrive_cluster(bE + (4 + lane % 3) * 8, (lane / 3) & 1);
        if (lr0 < S_LEN && lane == 0) {
          asm volatile("cp.async.bulk.wait_group 0;" ::: "memory");
          asm volatile("fence.proxy.async.global;" ::: "memory");
          __threadfence();
          atomicAdd(&g_sync[F_OA + (lr0 >> 7)], 1u);
        }
      }
    }
    __syncwarp();
    cluster_sync();
  } else {
    reg_alloc<232>();
    const int wg = warp_g >> 2, warp = warp_g & 3, q = lane & 3;
    const bool sig = (lane == 0) && (warp < 2);
    {
      K1State st{0, 0, 0, nullptr, nullptr, 0, 0, 0};
      float acc[128];
      uint32_t pk[64];
      if (wg == 0) { TS(0, 0); TSC(0, 2); }
      uint32_t job = p.jobs[cl][0];
      k1_first(st, job, bAf, bBf);
      {
#pragma unroll 1
        for (int ji = 0; job & 3; ji++) {
          const uint32_t njob = p.jobs[cl][ji + 1];
          k1_tile(acc, pk, st, job, njob, sA, sB, bAf, bAe, bBf, bBe, bS, wg, warp, lane, rank);
          job = njob;
        }
      }
#pragma unroll
      for (int i = 0; i < 4; i++)
        mbar_arrive_cluster_if(bE + i * 8, warp & 1, sig);
      if (lr0 < S_LEN) bar_sync(3, 256 + 96);
      if (st.wsel == 3) {
#pragma unroll
        for (int G = 0; G < 16; G++) scale_q4(pk + G * 4);
      }
      auto flush = [&](int i, uint32_t dep) {
        asm volatile("{\n.reg .pred p;\nsetp.eq.u32 p, %5, 0;\n@p st.global.cs.v4.b32 [%0], {%1, %2, %3, %4};\n}" ::"l"(((i & 1) ? st.pp8 : st.pp) + (i / 2) * 32),
                     "r"(pk[i * 4]), "r"(pk[i * 4 + 1]), "r"(pk[i * 4 + 2]), "r"(pk[i * 4 + 3]), "r"(dep & blockIdx.y) : "memory");
      };
      if (wg == 0) { TS(0, 1); TSC(0, 3); }
      if (lr0 < S_LEN) {
        const float gate0 = __uint_as_float(lds32(sGate + (lane >> 2) * 8)), gate1 = __uint_as_float(lds32(sGate + (lane >> 2) * 8 + 4));
        local_attn(lr0, warp_g, sL, bL, bL2, lane, gate0, gate1, flush);
        k1_flag(st, lane, bS);
      } else {
        FLUSH();
      }
      bar_arrive(5, 256 + 32);
    }
    __syncwarp();
    uint32_t item, rot;
    {
      const int mybar = 1 + wg, otherbar = 2 - wg;
      const uint32_t never = blockIdx.y;
      float S[64], O[64];
      uint32_t P[32], Q[32];
      float m0 = 0.f, m1 = 0.f, l0 = 1.f, l1 = 1.f, gf0 = 0.f, gf1 = 0.f;
      uint32_t eoff = 0, prev_single = 0;
      Cursor c{0, 0};
      if (wg == 1) bar_arrive(1, 256);
      if (wg == 0) { TS(1, 0); TSC(1, 2); }
#pragma unroll 1
      for (int it = 0;; it++) {
        TB(0);
        const int hi = (int)(rank ^ (it & 1));
        Cursor cq = c, ck, cv, cs0, cs1;
        rot = k3_rot(c.s);
        c.next();
        ck = c; c.next();
        cs0 = ck; cs1 = ck; cv = ck;
        if (it > 0) { cv = c; c.next(); }
        if (!hi) {
          ck = c; c.next();
          cs1 = c; c.next();
        }
        mbar_wait(bF + cq.s * 8, cq.ph);
        TB(1);
        item = lds32(sItem + (it & 7) * 4);
        {
          const uint32_t qa = sbase + cq.s * 32768 + (wg * 64 + warp * 16 + (lane & 15)) * 128;
#pragma unroll
          for (int t = 0; t < 8; t++)
            ldsm_x4(Q[4 * t], Q[4 * t + 1], Q[4 * t + 2], Q[4 * t + 3], qa + (t >> 2) * 16384 + ((((t & 3) * 2 + (lane >> 4)) ^ (lane & 7)) << 4));
        }
        const uint32_t rdy = mbar_test(bF + ck.s * 8, ck.ph) & mbar_test(bF + cv.s * 8, cv.ph);
        l0 += __shfl_xor_sync(0xffffffffu, l0, 1);
        l1 += __shfl_xor_sync(0xffffffffu, l1, 1);
        l0 += __shfl_xor_sync(0xffffffffu, l0, 2);
        l1 += __shfl_xor_sync(0xffffffffu, l1, 2);
        const bool last = item >= K2_END;
        if (last) {
          cv = cq; ck = cq;
        } else if (!rdy) {
          mbar_wait2(bF + ck.s * 8, ck.ph, bF + cv.s * 8, cv.ph);
        }
        TB(2);
        TURN_SYNC();
        TB(3);
        TRC(last ? 2 : 1);
        if (it > 0) {
          wg_fence();
          ISSUE_PV(cv, prev_single);
          wg_commit();
        } else {
          wg_fence();
          wg_commit();
        }
        wg_fence();
        ISSUE_QK(ck);
        wg_commit();
        if (!(last && wg == 1)) TURN_ARRIVE();
        RELEASE_IF(cq, !last);
        TB(4);
        asm volatile("" : "+f"(gf0), "+f"(gf1), "+f"(l0), "+f"(l1));
        const float f0 = __fdividef(1.f - gf0, l0), f1 = __fdividef(1.f - gf1, l1);
        wg_wait<1>();
        fence_regs(O);
        fence_regs(P);
        TB(5);
        if (it > 0) {
          RELEASE_IF(cv, !last);
          mbar_arrive_cluster_if(bH, warp & 1, sig && last);
          bf16* optr = ptr_add(g_ctx, eoff);
          STORE_O(0); STORE_O(1); STORE_O(2); STORE_O(3);
          __syncwarp();
          mbar_arrive_if(bS2, lane == 0);
        }
        TB(6);
        if (!last) {
          const int row = (2 * (item & 7) + hi) * 128 + wg * 64 + warp * 16 + (lane >> 2);
          eoff = (row * KCAT + (item >> 3) * 128 + q * 8) * 2;
          const float* gp = ptr_add(g_gate, row * 4);
          asm volatile("ld.global.f32 %0, [%1];" : "=f"(gf0) : "l"(gp));
          asm volatile("ld.global.f32 %0, [%1];" : "=f"(gf1) : "l"(gp + 8));
          if (!hi) {
            mbar_wait2(bF + cs0.s * 8, cs0.ph, bF + cs1.s * 8, cs1.ph);
            RELEASE(cs0);
            RELEASE(cs1);
          }
        }
        TB(7);
        wg_wait<0>();
        fence_regs(S);
        TB(8);
        if (last) break;
        RELEASE(ck);
        const int nblk = 2 * (item & 7) + 1 + hi;
        prev_single = (nblk == 1);
        float s0 = 0.f, s1 = 0.f;
        l0 = 0.f; l1 = 0.f;
        m0 = 0.f; m1 = 0.f;
        bool shifted = false;
        {
          const int d = warp * 16 + (lane >> 2) - 2 * q;
          if (wg == 0) {
#pragma unroll
            for (int jj = 0; jj < 8; jj++) MASK(jj, jj);
            EXPB(0); EXPB(1); EXPB(2); EXPB(3);
#pragma unroll
            for (int i = 32; i < 64; i++) S[i] = -INFINITY;
#pragma unroll
            for (int i = 16; i < 32; i++) P[i] = 0;
          } else {
#pragma unroll
            for (int jj = 0; jj < 8; jj++) MASK(jj + 8, jj);
            EXPB(0); EXPB(1); EXPB(2); EXPB(3); EXPB(4); EXPB(5); EXPB(6); EXPB(7);
          }
        }
        float chk = (q == 0 && !(fminf(s0, s1) >= SPEC_LO)) ? INFINITY : s0 + s1;
        fence_regs(P);
        TB(9);
#pragma unroll 1
        for (int n = 1;; n++) {
          if (__any_sync(0xffffffffu, !(chk <= SPEC_HI))) {
            float mx0 = fmaxf(S[0], S[1]), mx1 = fmaxf(S[2], S[3]);
#pragma unroll
            for (int jj = 1; jj < 16; jj++) {
              mx0 = fmaxf(mx0, fmaxf(S[jj * 4 + 0], S[jj * 4 + 1]));
              mx1 = fmaxf(mx1, fmaxf(S[jj * 4 + 2], S[jj * 4 + 3]));
            }
            mx0 = fmaxf(mx0, __shfl_xor_sync(0xffffffffu, mx0, 1));
            mx1 = fmaxf(mx1, __shfl_xor_sync(0xffffffffu, mx1, 1));
            mx0 = fmaxf(mx0, __shfl_xor_sync(0xffffffffu, mx0, 2));
            mx1 = fmaxf(mx1, __shfl_xor_sync(0xffffffffu, mx1, 2));
            const float lo = (n == 1) ? -INFINITY : 0.f;
            mx0 = fmaxf(mx0, lo);
            mx1 = fmaxf(mx1, lo);
            m0 += mx0; m1 += mx1;
            shifted = true;
            const float sc0 = ex2(-fmaxf(mx0, 0.f)), sc1 = ex2(-fmaxf(mx1, 0.f));
            l0 *= sc0; l1 *= sc1;
            s0 = 0.f; s1 = 0.f;
#pragma unroll
            for (int jj = 0; jj < 16; jj++) {
              const float e0 = ex2(S[jj * 4 + 0] - mx0), e1 = ex2(S[jj * 4 + 1] - mx0), e2 = ex2(S[jj * 4 + 2] - mx1), e3 = ex2(S[jj * 4 + 3] - mx1);
              s0 += e0 + e1;
              s1 += e2 + e3;
              P[jj * 2 + 0] = pack_bf16(e0, e1);
              P[jj * 2 + 1] = pack_bf16(e2, e3);
              O[jj * 4 + 0] *= sc0;
              O[jj * 4 + 1] *= sc0;
              O[jj * 4 + 2] *= sc1;
              O[jj * 4 + 3] *= sc1;
            }
          }
          l0 += s0;
          l1 += s1;
          if (n >= nblk) break;
          ck = c; c.next();
          cv = c; c.next();
          mbar_wait(bF + ck.s * 8, ck.ph);
          mbar_wait(bF + cv.s * 8, cv.ph);
          TURN_SYNC();
          TRC(0);
          wg_fence();
          ISSUE_QK(ck);
          wg_commit();
          {
            const uint64_t dv = make_desc(sbase + cv.s * 32768, 16384, 1024, 1);
#pragma unroll
            for (int t = 0; t < 8; t++) {
              wgmma_rs_n128<1, 0>(O, P[4 * t], P[4 * t + 1], P[4 * t + 2], P[4 * t + 3], dv + (uint64_t)(t * 128), (t > 0) ? 1 : (n != 1));
              if ((PVM >> t) & 1) wg_commit();
            }
          }
          TURN_ARRIVE();
          s0 = 0.f; s1 = 0.f;
          wg_wait<__builtin_popcount(PVM)>();
          fence_regs(S);
          RELEASE(ck);
          if (shifted) {
#pragma unroll
            for (int i = 0; i < 64; i++) S[i] -= (i & 2) ? m1 : m0;
          }
          wg_wait<__builtin_popcount(PVM) - 1>();
          EXPC(0); EXPC(1); EXPC(2); EXPC(3); EXPC(4); EXPC(5); EXPC(6); EXPC(7);
          chk = s0 + s1;
        }
      }
      TRC(3);
      if (wg == 1) { TS(1, 1); TSC(1, 3); }
    }
    __syncwarp();
    const uint32_t unit = item & 255;
    if (unit < 64) {
      const int mblk = (7 - (p.unit[unit][0] >> 1)) * 2 + rank, nhalf = p.unit[unit][0] & 1, ks = p.unit[unit][1];
      const int k0 = 0, k1 = p.unit[unit][2];
      float acc[144];
      uint32_t s = rot, ph = 0, prev = 0;
      if (wg == 0) { TS(2, 0); TSC(2, 2); }
      uint32_t fa[16], fb[16];
      const uint32_t aoff = (wg * 64 + warp * 16 + (lane & 15)) * 128 + (((lane >> 4) ^ (lane & 7)) << 4);
#define C_LOAD(F)                                                                                              \
  do {                                                                                                         \
    mbar_wait(b3F + s * 8, ph);                                                                                \
    _Pragma("unroll") for (int t = 0; t < 4; t++)                                                              \
        ldsm_x4(F[4 * t], F[4 * t + 1], F[4 * t + 2], F[4 * t + 3], sbase + s * K3_STAGE + (aoff ^ (t * 32))); \
  } while (0)
#define C_STEP(F, G)                                                                                           \
  {                                                                                                            \
    const uint32_t st = sbase + s * K3_STAGE;                                                                  \
    const uint64_t db = make_desc(st + 16384, 4096, 1024, 1), dt = make_desc(st + 49152, 16, 512, 2);          \
    wg_fence();                                                                                                \
    _Pragma("unroll") for (int t = 0; t < 4; t++) {                                                            \
      const int sd = (t > 0) || (k > k0);                                                                      \
      wgmma_rs_n256<1, 0>(acc, F[4 * t], F[4 * t + 1], F[4 * t + 2], F[4 * t + 3], db + (uint64_t)((t >> 1) * 1024 + (t & 1) * 128), sd); \
      wgmma_rs_n32<1, 128>(acc, F[4 * t], F[4 * t + 1], F[4 * t + 2], F[4 * t + 3], dt + (uint64_t)(t * 64), sd); \
    }                                                                                                          \
    wg_commit();                                                                                               \
    wg_wait<1>();                                                                                              \
    fence_regs(G);                                                                                             \
    mbar_arrive_cluster_if(b3E + prev * 8, warp & 1, sig && k > k0);                                           \
    prev = s;                                                                                                  \
    s = (s + 1) & 3;                                                                                           \
    if (s == rot) ph ^= 1;                                                                                     \
    TCK(k + 1);                                                                                                \
    if (++k == k1) break;                                                                                      \
    C_LOAD(G);                                                                                                 \
  }
      TCK(0);
      C_LOAD(fa);
#pragma unroll
      for (int i = 0; i < 16; i++) fb[i] = 0;
#pragma unroll 1
      for (int k = k0;;) {
        C_STEP(fa, fb)
        C_STEP(fb, fa)
      }
      wg_wait<0>();
      fence_regs(acc);
      cluster_arrive();
      if (wg == 0) TS(2, 4);
      const int tile = mblk * 2 + nhalf;
      uint4* wp = g_part + (size_t)((tile * 4 + ks) * 4) * 5 * 256 + tid;
      const uint32_t sown = sbase + wg * 8192 + (tid & 127) * 16;
#pragma unroll
      for (int d = 0; d < 4; d++) {
        if (d != ks) {
#pragma unroll
          for (int i = 0; i < 4; i++)
            __stcg(wp + (d * 5 + i) * 256,
                   make_uint4(pack_bf16(acc[d * 32 + i * 8], acc[d * 32 + i * 8 + 1]), pack_bf16(acc[d * 32 + i * 8 + 2], acc[d * 32 + i * 8 + 3]),
                              pack_bf16(acc[d * 32 + i * 8 + 4], acc[d * 32 + i * 8 + 5]), pack_bf16(acc[d * 32 + i * 8 + 6], acc[d * 32 + i * 8 + 7])));
          __stcg(reinterpret_cast<uint2*>(wp - tid + (d * 5 + 4) * 256) + tid,
                 make_uint2(pack_bf16(acc[128 + d * 4], acc[128 + d * 4 + 1]), pack_bf16(acc[128 + d * 4 + 2], acc[128 + d * 4 + 3])));
        } else {
#pragma unroll
          for (int i = 0; i < 9; i++) {
            const int o = (i < 8) ? d * 32 + i * 4 : 128 + d * 4;
            asm volatile("st.shared.v4.f32 [%0], {%1, %2, %3, %4};" ::"r"(sown + (i >> 2) * K3_STAGE + (i & 3) * 2048), "f"(acc[o]), "f"(acc[o + 1]), "f"(acc[o + 2]), "f"(acc[o + 3]) : "memory");
          }
        }
      }
      __threadfence();
      __syncwarp();
      if (wg == 0) TS(2, 5);
      if (lane == 0) {
        unsigned int* cnt = &g_sync[F_XCH + tile * 8 + warp_g];
        const uint32_t xtarget = lds32(sGate + 64) * 4 + 4;
        atomicAdd(cnt, 1u);
        uint32_t v, spins = 0;
        do {
          asm volatile("ld.acquire.gpu.global.u32 %0, [%1];" : "=r"(v) : "l"(cnt) : "memory");
        } while ((int)(v - xtarget) < 0 && ++spins < (1u << 24));
      }
      __syncwarp();
      if (wg == 0) TS(2, 6);
      float r[36];
#pragma unroll
      for (int i = 0; i < 9; i++)
        asm volatile("ld.shared.v4.f32 {%0, %1, %2, %3}, [%4];" : "=f"(r[i * 4]), "=f"(r[i * 4 + 1]), "=f"(r[i * 4 + 2]), "=f"(r[i * 4 + 3])
                     : "r"(sown + (i >> 2) * K3_STAGE + (i & 3) * 2048) : "memory");
#pragma unroll
      for (int sI = 1; sI < 4; sI++) {
        const int src = (ks + sI) & 3;
        const uint4* rp = g_part + (size_t)(((tile * 4 + src) * 4) + ks) * 5 * 256;
#pragma unroll
        for (int i = 0; i < 4; i++) {
          const uint4 v = __ldcg(rp + i * 256 + tid);
          r[i * 8] += bf_lo(v.x); r[i * 8 + 1] += bf_hi(v.x); r[i * 8 + 2] += bf_lo(v.y); r[i * 8 + 3] += bf_hi(v.y);
          r[i * 8 + 4] += bf_lo(v.z); r[i * 8 + 5] += bf_hi(v.z); r[i * 8 + 6] += bf_lo(v.w); r[i * 8 + 7] += bf_hi(v.w);
        }
        const uint2 v = __ldcg(reinterpret_cast<const uint2*>(rp + 4 * 256) + tid);
        r[32] += bf_lo(v.x); r[33] += bf_hi(v.x); r[34] += bf_lo(v.y); r[35] += bf_hi(v.y);
      }
      const int row = mblk * 128 + wg * 64 + warp * 16 + (lane >> 2);
      bf16* o0 = out + (size_t)row * DM + nhalf * 256 + ks * 64 + 8 * q;
#pragma unroll
      for (int G = 0; G < 2; G++) {
        uint32_t a0 = pack_bf16(r[G * 16], r[G * 16 + 1]), a1 = pack_bf16(r[G * 16 + 4], r[G * 16 + 5]);
        uint32_t a2 = pack_bf16(r[G * 16 + 8], r[G * 16 + 9]), a3 = pack_bf16(r[G * 16 + 12], r[G * 16 + 13]);
        uint32_t b0 = pack_bf16(r[G * 16 + 2], r[G * 16 + 3]), b1 = pack_bf16(r[G * 16 + 6], r[G * 16 + 7]);
        uint32_t b2 = pack_bf16(r[G * 16 + 10], r[G * 16 + 11]), b3 = pack_bf16(r[G * 16 + 14], r[G * 16 + 15]);
        quad_transpose(a0, a1, a2, a3, q);
        quad_transpose(b0, b1, b2, b3, q);
        st_v4(o0 + G * 32, a0, a1, a2, a3);
        st_v4(o0 + 8 * DM + G * 32, b0, b1, b2, b3);
      }
      {
        uint32_t t0 = pack_bf16(r[32], r[33]), t1 = pack_bf16(r[34], r[35]), t2 = 0, t3 = 0;
        quad_transpose(t0, t1, t2, t3, q);
        if (q < 2) st_v4(out + (size_t)(row + q * 8) * DM + 512 + nhalf * 32 + ks * 8, t0, t1, t2, t3);
      }
    } else {
      cluster_arrive();
    }
    if (wg == 0) { TS(2, 1); TSC(2, 3); }
    cluster_wait();
  }
}

typedef CUresult (*EncFn)(CUtensorMap*, CUtensorMapDataType, cuuint32_t, void*, const cuuint64_t*, const cuuint64_t*, const cuuint32_t*,
                          const cuuint32_t*, CUtensorMapInterleave, CUtensorMapSwizzle, CUtensorMapL2promotion, CUtensorMapFloatOOBfill);

static void enc2d(EncFn enc, CUtensorMap* m, const void* ptr, uint64_t cols, uint64_t rows, uint32_t bc, uint32_t br,
                  CUtensorMapSwizzle sw = CU_TENSOR_MAP_SWIZZLE_128B) {
  cuuint64_t gd[2] = {cols, rows}, gs[1] = {cols * 2};
  cuuint32_t bx[2] = {bc, br}, es[2] = {1, 1};
  enc(m, CU_TENSOR_MAP_DATA_TYPE_BFLOAT16, 2, const_cast<void*>(ptr), gd, gs, bx, es, CU_TENSOR_MAP_INTERLEAVE_NONE, sw,
      CU_TENSOR_MAP_L2_PROMOTION_L2_256B, CU_TENSOR_MAP_FLOAT_OOB_FILL_NONE);
}
static void enc3d(EncFn enc, CUtensorMap* m, const void* ptr, uint64_t cols, uint64_t rows, uint32_t br, uint32_t bch) {
  cuuint64_t gd[3] = {64, rows, cols / 64}, gs[2] = {cols * 2, 128};
  cuuint32_t bx[3] = {64, br, bch}, es[3] = {1, 1, 1};
  enc(m, CU_TENSOR_MAP_DATA_TYPE_BFLOAT16, 3, const_cast<void*>(ptr), gd, gs, bx, es, CU_TENSOR_MAP_INTERLEAVE_NONE,
      CU_TENSOR_MAP_SWIZZLE_128B, CU_TENSOR_MAP_L2_PROMOTION_L2_256B, CU_TENSOR_MAP_FLOAT_OOB_FILL_NONE);
}

static int g_sched[10] = {11, 10, 7, 4, 4, 4, 6, 8, 6, 24};
static void build_k1_jobs(Params& p) {
  int cnt[NCLUSTER];
  for (int c = 0; c < NCLUSTER; c++) {
    cnt[c] = 0;
    for (int i = 0; i <= K1_MAXJOBS; i++) p.jobs[c][i] = 0;
  }
  auto add = [&](int c, int nch, int a_sel, int mp, int w_sel, int chunk0) {
    p.jobs[c][cnt[c]++] = (uint16_t)((nch - 1) | (a_sel << 2) | (mp << 3) | (w_sel << 6) | (chunk0 << 8));
  };
  const char* plan = "ccccccccccc cccccccccc ccccccc cccc xxxx xxxx xxxxxx xxxxxxxx";
  int TIE = 0;
  int XA = 0;
  const char* cur[8];
  int tend[8] = {};
  for (int g = 0; g < 8; g++) {
    cur[g] = plan;
    while (*plan == 'c' || *plan == 'x') plan++;
    if (*plan) plan++;
  }
  int kc = 0, kx = 0;
  for (;;) {
    int b = -1, bt = 0;
    for (int g = 0; g < 8; g++) {
      const int t = tend[g] + (*cur[g] == 'x' ? 94 : 85);
      if ((*cur[g] == 'c' || *cur[g] == 'x') && (b < 0 || t < bt || (TIE && t == bt))) { b = g; bt = t; }
    }
    if (b < 0) break;
    const int a = kx - XA;
    for (int mp = 0; mp < 8; mp++) {
      if (*cur[b] == 'c') add(b * 8 + mp, 4, 0, mp, kc & 1, (kc >> 1) * 4);
      else if (a >= 0 && a < 7) add(b * 8 + mp, a == 0 ? 3 : 4, 1, mp, 2, a == 0 ? 24 : (a - 1) * 4);
      else add(b * 8 + mp, 4, 1, mp, 3, (a < 0 ? kx : kx - 7) * 4);
    }
    if (*cur[b] == 'c') kc++; else kx++;
    cur[b]++;
    tend[b] = bt;
  }
  for (int mp = 0; mp < 8; mp++) add(64 + mp / 4, 4, 1, mp, 3, 15 * 4);
  for (int cc = 0; cc < NCLUSTER; cc++)
    for (int i = 0; i < cnt[cc]; i++) {
      const int key = p.jobs[cc][i] & 0x3C;
      if (i == 0 || (p.jobs[cc][i - 1] & 0x3C) != key) p.jobs[cc][i] |= (1 << 14);
      if (i == cnt[cc] - 1 || (p.jobs[cc][i + 1] & 0x3C) != key) p.jobs[cc][i] |= (1 << 15);
    }
}

static void build_k2_items(Params& p) {
  int n = 0;
  const int SCHED_N1 = g_sched[8], SCHED_N2 = g_sched[9];
  int N0 = 2, J0 = 2;
  for (int j = 7; j >= J0; j--)
    for (int h = 0; h < N0; h++) p.order[n++] = (uint8_t)(h * 8 + j);
  for (int j = 7; j >= 0; j--)
    for (int h = 0; h < SCHED_N1; h++)
      if (!(h < N0 && j >= J0)) p.order[n++] = (uint8_t)(h * 8 + j);
  for (int j = 7; j >= 4; j--)
    for (int h = SCHED_N1; h < SCHED_N2; h++) p.order[n++] = (uint8_t)(h * 8 + j);
  for (int j = 7; j >= 0; j--)
    for (int h = SCHED_N1; h < 32; h++)
      if (!(h < SCHED_N2 && j >= 4)) p.order[n++] = (uint8_t)(h * 8 + j);
}

static void build_k3_units(Params& p) {
  float slope = 0.045f;
  int NE = 25;
  for (int t = 0; t < 16; t++) {
    const int u[4] = {t, 31 - t, 32 + t, 63 - t};
    float acc = 0.f;
    int k0 = 0, l0 = NE;
    for (int i = 0; i < 4; i++) {
      acc += 18.25f + slope * (31.5f - u[i]);
      const int k1 = (i == 3) ? 73 : (int)(acc + 0.5f);
      const int e0 = NE * i / 4, e1 = NE * (i + 1) / 4;
      uint8_t* w = p.unit[u[i]];
      w[0] = (uint8_t)t; w[1] = (uint8_t)i; w[2] = (uint8_t)(k1 - k0); w[3] = (uint8_t)e0; w[4] = (uint8_t)(e1 - e0); w[5] = (uint8_t)(l0 - e1);
      l0 += (k1 - k0) - (e1 - e0);
      k0 = k1;
    }
  }
}

extern "C" void kernel_launch(void* const* d_in, const int* in_sizes, int n_in, void* d_out, int out_size) {
  const bf16* x = (const bf16*)d_in[0];
  const bf16* wqkv = (const bf16*)d_in[1];
  const bf16* wo = (const bf16*)d_in[2];
  const bf16* ckv = (const bf16*)d_in[4];
  const bf16* w_q = (const bf16*)d_in[5];
  const bf16* w_uk = (const bf16*)d_in[6];
  const bf16* w_uv = (const bf16*)d_in[7];
  const bf16* w_o = (const bf16*)d_in[8];
  const bf16* gate_w = (const bf16*)d_in[9];

  EncFn enc = nullptr;
  cudaDriverEntryPointQueryResult qr;
  cudaGetDriverEntryPoint("cuTensorMapEncodeTiled", (void**)&enc, cudaEnableDefault, &qr);
  void *pK, *pV, *pCtx, *pQA;
  cudaGetSymbolAddress(&pQA, g_QKVA);
  cudaGetSymbolAddress(&pK, g_K);
  cudaGetSymbolAddress(&pV, g_V);
  cudaGetSymbolAddress(&pCtx, g_ctx);

  static Params p;
  enc2d(enc, &p.tmA[0], ckv, DC, S_LEN, 64, 128);
  enc2d(enc, &p.tmA[1], x, DM, S_LEN, 64, 128);
  enc3d(enc, &p.tmW[0], w_uk, HDIM, DC, 16, 4);
  enc3d(enc, &p.tmW[1], w_uv, HDIM, DC, 16, 4);
  enc3d(enc, &p.tmW[2], wqkv, NQKVA, DM, 16, 4);
  enc3d(enc, &p.tmW[3], w_q, HDIM, DM, 16, 4);
  build_k1_jobs(p);
  enc2d(enc, &p.tmK, pK, HDIM, S_LEN, 64, 128);
  enc2d(enc, &p.tmV, pV, HDIM, S_LEN, 64, 128);
  build_k2_items(p);
  build_k3_units(p);
  for (int i = 0; i < 3; i++) {
    const cuuint64_t ld = (i < 2 ? NQKVA : KCAT) * 2, nch = (i < 2) ? 27 : 9;
    cuuint64_t gd[4] = {64, S_LEN / 2, i ? 2 : nch, i ? nch : 2}, gs[3] = {2 * ld, i ? ld : 128, i ? 128 : ld};
    cuuint32_t bx[4] = {64, i ? 8u : 16u, i ? 2u : 9u, i ? 9u : 2u}, es[4] = {1, 1, 1, 1};
    enc(&p.tmL[i], CU_TENSOR_MAP_DATA_TYPE_BFLOAT16, 4, (i < 2) ? pQA : (void*)((bf16*)pCtx + HDIM), gd, gs, bx, es, CU_TENSOR_MAP_INTERLEAVE_NONE,
        CU_TENSOR_MAP_SWIZZLE_128B, CU_TENSOR_MAP_L2_PROMOTION_L2_256B, CU_TENSOR_MAP_FLOAT_OOB_FILL_NONE);
  }
  enc2d(enc, &p.tmC, pCtx, KCAT, S_LEN, 64, 128);
  enc3d(enc, &p.tmO[0], w_o, DM, HDIM, 32, 4);
  enc3d(enc, &p.tmO[1], wo, DM, DM, 32, 4);
  enc2d(enc, &p.tmOt[0], w_o, DM, HDIM, 32, 32, CU_TENSOR_MAP_SWIZZLE_64B);
  enc2d(enc, &p.tmOt[1], wo, DM, DM, 32, 32, CU_TENSOR_MAP_SWIZZLE_64B);

  cudaFuncSetAttribute(fused_kernel, cudaFuncAttributeMaxDynamicSharedMemorySize, SMEM_BYTES);
  fused_kernel<<<NCLUSTER * 2, 384, SMEM_BYTES>>>(p, x, gate_w, (bf16*)d_out);
}
```

```cpp
#include <cuda_runtime.h>
#include <cuda_bf16.h>
#include <cuda.h>
#include <stdint.h>

typedef __nv_bfloat16 bf16;

constexpr int S_LEN = 2048, DM = 576, DC = 512, HDIM = 4096, NQKVA = 1728, KCAT = 4672;
constexpr int NCLUSTER = 66;

__device__ __align__(1024) bf16 g_K[S_LEN * HDIM];
__device__ __align__(1024) bf16 g_V[S_LEN * HDIM];
__device__ __align__(1024) bf16 g_QKVA[S_LEN * NQKVA + 64];
__device__ __align__(1024) bf16 g_ctx[S_LEN * KCAT];
__device__ float g_gate[S_LEN];
__device__ __align__(1024) uint4 g_part[32 * 4 * 4 * 5 * 256];
__device__ __align__(16) unsigned int g_sync[400];
constexpr int F_QKVA = 0, F_HP = 16, F_CTX = 32, F_OA = 48, F_GATE = 96, F_TICK = 97, F_DONE = 98, F_XCH = 128, F_EPOCH = 384;

__device__ __forceinline__ uint32_t smem_u32(const void* p) { return (uint32_t)__cvta_generic_to_shared(p); }
__device__ __forceinline__ void mbar_init(uint32_t a, uint32_t c) {
  asm volatile("mbarrier.init.shared::cta.b64 [%0], %1;" ::"r"(a), "r"(c));
}
__device__ __forceinline__ void mbar_expect(uint32_t a, uint32_t b) {
  asm volatile("mbarrier.arrive.expect_tx.shared::cta.b64 _, [%0], %1;" ::"r"(a), "r"(b) : "memory");
}
#define TS(k, i)
#define TSC(k, i)
#define TSM(k)
#define BSEG(i)
#define TB(k)
#define TRC(fl)
#define TCK(i)
#define SPIN_LIMIT "4194304"
__device__ __forceinline__ void mbar_wait(uint32_t a, uint32_t parity) {
  asm volatile(
      "{\n.reg .pred p;\n.reg .u32 n;\n"
      "mbarrier.try_wait.parity.shared::cta.b64 p, [%0], %1;\n"
      "@p bra DONE;\n"
      "mov.u32 n, 0;\n"
      "LOOP:\n"
      "mbarrier.try_wait.parity.shared::cta.b64 p, [%0], %1;\n"
      "@p bra DONE;\n"
      "add.u32 n, n, 1;\n"
      "setp.lt.u32 p, n, " SPIN_LIMIT ";\n"
      "@p bra LOOP;\n"
      "DONE:\n}" ::"r"(a), "r"(parity) : "memory");
}
template <int NS>
__device__ __forceinline__ void mbar_wait_ns(uint32_t a, uint32_t parity) {
  asm volatile(
      "{\n.reg .pred p;\n.reg .u32 n;\n"
      "mov.u32 n, 0;\n"
      "LOOP:\n"
      "mbarrier.try_wait.parity.shared::cta.b64 p, [%0], %1, %2;\n"
      "@p bra DONE;\n"
      "add.u32 n, n, 1;\n"
      "setp.lt.u32 p, n, " SPIN_LIMIT ";\n"
      "@p bra LOOP;\n"
      "DONE:\n}" ::"r"(a), "r"(parity), "n"(NS) : "memory");
}
__device__ __forceinline__ void mbar_wait2(uint32_t a, uint32_t pa, uint32_t b, uint32_t pb) {
  asm volatile(
      "{\n.reg .pred p, q;\n.reg .u32 n;\n"
      "mov.u32 n, 0;\n"
      "LOOP:\n"
      "mbarrier.try_wait.parity.shared::cta.b64 p, [%0], %1;\n"
      "mbarrier.try_wait.parity.shared::cta.b64 q, [%2], %3;\n"
      "add.u32 n, n, 1;\n"
      "and.pred p, p, q;\n"
      "setp.lt.and.u32 p, n, " SPIN_LIMIT ", !p;\n"
      "@p bra LOOP;\n"
      "}" ::"r"(a), "r"(pa), "r"(b), "r"(pb) : "memory");
}
__device__ __forceinline__ uint32_t mbar_test(uint32_t a, uint32_t parity) {
  uint32_t r;
  asm volatile("{\n.reg .pred p;\nmbarrier.test_wait.parity.shared::cta.b64 p, [%1], %2;\nselp.u32 %0, 1, 0, p;\n}" : "=r"(r) : "r"(a), "r"(parity) : "memory");
  return r;
}
__device__ __forceinline__ void mbar_arrive(uint32_t a) {
  asm volatile("mbarrier.arrive.shared::cta.b64 _, [%0];" ::"r"(a) : "memory");
}
__device__ __forceinline__ void mbar_arrive_cluster(uint32_t a, uint32_t cta) {
  asm volatile("{\n.reg .b32 r;\nmapa.shared::cluster.u32 r, %0, %1;\nmbarrier.arrive.shared::cluster.b64 _, [r];\n}" ::"r"(a),
               "r"(cta) : "memory");
}
__device__ __forceinline__ void mbar_arrive_cluster_if(uint32_t a, uint32_t cta, bool pred) {
  asm volatile("{\n.reg .b32 r;\n.reg .pred p;\nsetp.ne.u32 p, %2, 0;\nmapa.shared::cluster.u32 r, %0, %1;\n@p mbarrier.arrive.shared::cluster.b64 _, [r];\n}" ::"r"(a),
               "r"(cta), "r"((uint32_t)pred) : "memory");
}
__device__ __forceinline__ void anchor(float v, uint32_t pred) {
  asm volatile("{\n.reg .pred p;\nsetp.ne.u32 p, %1, 0;\n@p st.shared.f32 [%1], %0;\n}" ::"f"(v), "r"(pred) : "memory");
}
__device__ __forceinline__ void mbar_arrive_if(uint32_t a, bool pred) {
  asm volatile("{\n.reg .pred p;\nsetp.ne.u32 p, %1, 0;\n@p mbarrier.arrive.shared::cta.b64 _, [%0];\n}" ::"r"(a), "r"((uint32_t)pred) : "memory");
}
__device__ __forceinline__ void tma2d(uint32_t dst, const CUtensorMap* m, uint32_t bar, int c0, int c1) {
  asm volatile("cp.async.bulk.tensor.2d.shared::cluster.global.mbarrier::complete_tx::bytes [%0], [%1, {%3, %4}], [%2];" ::"r"(dst),
               "l"(m), "r"(bar), "r"(c0), "r"(c1) : "memory");
}
__device__ __forceinline__ void tma2d_mc(uint32_t dst, const CUtensorMap* m, uint32_t bar, int c0, int c1, uint16_t mask) {
  asm volatile(
      "cp.async.bulk.tensor.2d.shared::cluster.global.mbarrier::complete_tx::bytes.multicast::cluster [%0], [%1, {%3, %4}], [%2], %5;" ::"r"(dst),
      "l"(m), "r"(bar), "r"(c0), "r"(c1), "h"(mask) : "memory");
}
__device__ __forceinline__ void tma3d_mc(uint32_t dst, const CUtensorMap* m, uint32_t bar, int c0, int c1, int c2, uint16_t mask) {
  asm volatile(
      "cp.async.bulk.tensor.3d.shared::cluster.global.mbarrier::complete_tx::bytes.multicast::cluster [%0], [%1, {%3, %4, %5}], [%2], %6;" ::"r"(dst),
      "l"(m), "r"(bar), "r"(c0), "r"(c1), "r"(c2), "h"(mask) : "memory");
}
__device__ __forceinline__ void tma3d(uint32_t dst, const CUtensorMap* m, uint32_t bar, int c0, int c1, int c2) {
  asm volatile(
      "cp.async.bulk.tensor.3d.shared::cluster.global.mbarrier::complete_tx::bytes [%0], [%1, {%3, %4, %5}], [%2];" ::"r"(dst),
      "l"(m), "r"(bar), "r"(c0), "r"(c1), "r"(c2) : "memory");
}
__device__ __forceinline__ void tma_pf2d(const CUtensorMap* m, int c0, int c1) {
  asm volatile("cp.async.bulk.prefetch.tensor.2d.L2.global [%0, {%1, %2}];" ::"l"(m), "r"(c0), "r"(c1) : "memory");
}
__device__ __forceinline__ void tma_pf3d(const CUtensorMap* m, int c0, int c1, int c2) {
  asm volatile("cp.async.bulk.prefetch.tensor.3d.L2.global [%0, {%1, %2, %3}];" ::"l"(m), "r"(c0), "r"(c1), "r"(c2) : "memory");
}
__device__ __forceinline__ void prefetch_tmap(const CUtensorMap* m) {
  asm volatile("prefetch.tensormap [%0];" ::"l"(m) : "memory");
}
__device__ __forceinline__ void cluster_arrive() { asm volatile("barrier.cluster.arrive.relaxed.aligned;" ::: "memory"); }
__device__ __forceinline__ void cluster_wait() { asm volatile("barrier.cluster.wait.aligned;" ::: "memory"); }
__device__ __forceinline__ void cluster_sync() {
  cluster_arrive();
  cluster_wait();
}
__device__ __forceinline__ uint32_t cluster_rank() {
  uint32_t r;
  asm volatile("mov.u32 %0, %%cluster_ctarank;" : "=r"(r));
  return r;
}
__device__ __forceinline__ bool elect_one() {
  uint32_t p;
  asm volatile("{\n.reg .pred q;\nelect.sync _|q, 0xffffffff;\nselp.u32 %0, 1, 0, q;\n}" : "=r"(p));
  return p;
}
__device__ __forceinline__ void ldsm_x4(uint32_t& r0, uint32_t& r1, uint32_t& r2, uint32_t& r3, uint32_t addr) {
  asm volatile("ldmatrix.sync.aligned.m8n8.x4.shared.b16 {%0, %1, %2, %3}, [%4];" : "=r"(r0), "=r"(r1), "=r"(r2), "=r"(r3) : "r"(addr) : "memory");
}
__device__ __forceinline__ void wg_fence() { asm volatile("wgmma.fence.sync.aligned;" ::: "memory"); }
__device__ __forceinline__ void wg_commit() { asm volatile("wgmma.commit_group.sync.aligned;" ::: "memory"); }
template <int N>
__device__ __forceinline__ void wg_wait() { asm volatile("wgmma.wait_group.sync.aligned %0;" ::"n"(N) : "memory"); }
template <int N>
__device__ __forceinline__ void reg_alloc() { asm volatile("setmaxnreg.inc.sync.aligned.u32 %0;" ::"n"(N)); }
template <int N>
__device__ __forceinline__ void reg_dealloc() { asm volatile("setmaxnreg.dec.sync.aligned.u32 %0;" ::"n"(N)); }
__device__ __forceinline__ void bar_sync(int id, int n) { asm volatile("bar.sync %0, %1;" ::"r"(id), "r"(n) : "memory"); }
__device__ __forceinline__ void bar_arrive(int id, int n) { asm volatile("bar.arrive %0, %1;" ::"r"(id), "r"(n) : "memory"); }
template <int NT>
__device__ __forceinline__ void fence_regs(float (&d)[NT]) {
#pragma unroll
  for (int i = 0; i < NT; i++) asm volatile("" : "+f"(d[i])::"memory");
}
template <int NT>
__device__ __forceinline__ void fence_regs(uint32_t (&d)[NT]) {
#pragma unroll
  for (int i = 0; i < NT; i++) asm volatile("" : "+r"(d[i])::"memory");
}
__device__ __forceinline__ uint64_t make_desc(uint32_t saddr, uint32_t lbo, uint32_t sbo, uint32_t layout) {
  return (uint64_t)((saddr & 0x3FFFF) >> 4) | ((uint64_t)(lbo >> 4) << 16) | ((uint64_t)(sbo >> 4) << 32) | ((uint64_t)layout << 62);
}
__device__ __forceinline__ uint32_t pack_bf16(float lo, float hi) {
  uint32_t r;
  asm("cvt.rn.bf16x2.f32 %0, %1, %2;" : "=r"(r) : "f"(hi), "f"(lo));
  return r;
}
__device__ __forceinline__ float ex2(float x) {
  float r;
  asm("ex2.approx.ftz.f32 %0, %1;" : "=f"(r) : "f"(x));
  return r;
}
__device__ __forceinline__ void st_v4(void* p, uint32_t a, uint32_t b, uint32_t c, uint32_t d) {
#define ST_MOD ".cs"
  asm volatile("st.global" ST_MOD ".v4.b32 [%0], {%1, %2, %3, %4};" ::"l"(p), "r"(a), "r"(b), "r"(c), "r"(d) : "memory");
}
#define STA_MOD ".cs"
__device__ __forceinline__ void st_v4a(void* p, uint32_t a, uint32_t b, uint32_t c, uint32_t d) {
  asm volatile("st.global" STA_MOD ".v4.b32 [%0], {%1, %2, %3, %4};" ::"l"(p), "r"(a), "r"(b), "r"(c), "r"(d) : "memory");
}
template <typename T>
__device__ __forceinline__ T* ptr_add(T* base, uint32_t bytes) {
  uint64_t r;
  asm volatile("{\n.reg .u32 l, h;\nmov.b64 {l, h}, %1;\nadd.cc.u32 l, l, %2;\naddc.u32 h, h, 0;\nmov.b64 %0, {l, h};\n}" : "=l"(r) : "l"(base), "r"(bytes));
  return reinterpret_cast<T*>(r);
}
__device__ __forceinline__ float bf_lo(uint32_t v) { return __uint_as_float(v << 16); }
__device__ __forceinline__ float bf_hi(uint32_t v) { return __uint_as_float(v & 0xFFFF0000u); }

__device__ __forceinline__ void quad_transpose(uint32_t& a0, uint32_t& a1, uint32_t& a2, uint32_t& a3, int q) {
  const bool o1 = q & 1, o2 = q & 2;
  uint32_t t0 = o1 ? a0 : a1, t1 = o1 ? a2 : a3;
  t0 = __shfl_xor_sync(0xffffffffu, t0, 1);
  t1 = __shfl_xor_sync(0xffffffffu, t1, 1);
  if (o1) { a0 = t0; a2 = t1; } else { a1 = t0; a3 = t1; }
  t0 = o2 ? a0 : a2;
  t1 = o2 ? a1 : a3;
  t0 = __shfl_xor_sync(0xffffffffu, t0, 2);
  t1 = __shfl_xor_sync(0xffffffffu, t1, 2);
  if (o2) { a0 = t0; a1 = t1; } else { a2 = t0; a3 = t1; }
}

template<int TB, int OFF, int NT>
__device__ __forceinline__ void wgmma_ss_n256(float (&d)[NT], uint64_t da, uint64_t db, int scale_d) {
  asm volatile("{\n.reg .pred p;\nsetp.ne.b32 p, %130, 0;\n"
    "wgmma.mma_async.sync.aligned.m64n256k16.f32.bf16.bf16 {%0, %1, %2, %3, %4, %5, %6, %7, %8, %9, %10, %11, %12, %13, %14, %15, %16, %17, %18, %19, %20, %21, %22, %23, %24, %25, %26, %27, %28, %29, %30, %31, %32, %33, %34, %35, %36, %37, %38, %39, %40, %41, %42, %43, %44, %45, %46, %47, %48, %49, %50, %51, %52, %53, %54, %55, %56, %57, %58, %59, %60, %61, %62, %63, %64, %65, %66, %67, %68, %69, %70, %71, %72, %73, %74, %75, %76, %77, %78, %79, %80, %81, %82, %83, %84, %85, %86, %87, %88, %89, %90, %91, %92, %93, %94, %95, %96, %97, %98, %99, %100, %101, %102, %103, %104, %105, %106, %107, %108, %109, %110, %111, %112, %113, %114, %115, %116, %117, %118, %119, %120, %121, %122, %123, %124, %125, %126, %127}, %128, %129, p, 1, 1, 0, %131;\n}\n"
    : "+f"(d[OFF+0]), "+f"(d[OFF+1]), "+f"(d[OFF+2]), "+f"(d[OFF+3]), "+f"(d[OFF+4]), "+f"(d[OFF+5]), "+f"(d[OFF+6]), "+f"(d[OFF+7]), "+f"(d[OFF+8]), "+f"(d[OFF+9]), "+f"(d[OFF+10]), "+f"(d[OFF+11]), "+f"(d[OFF+12]), "+f"(d[OFF+13]), "+f"(d[OFF+14]), "+f"(d[OFF+15]), "+f"(d[OFF+16]), "+f"(d[OFF+17]), "+f"(d[OFF+18]), "+f"(d[OFF+19]), "+f"(d[OFF+20]), "+f"(d[OFF+21]), "+f"(d[OFF+22]), "+f"(d[OFF+23]), "+f"(d[OFF+24]), "+f"(d[OFF+25]), "+f"(d[OFF+26]), "+f"(d[OFF+27]), "+f"(d[OFF+28]), "+f"(d[OFF+29]), "+f"(d[OFF+30]), "+f"(d[OFF+31]), "+f"(d[OFF+32]), "+f"(d[OFF+33]), "+f"(d[OFF+34]), "+f"(d[OFF+35]), "+f"(d[OFF+36]), "+f"(d[OFF+37]), "+f"(d[OFF+38]), "+f"(d[OFF+39]), "+f"(d[OFF+40]), "+f"(d[OFF+41]), "+f"(d[OFF+42]), "+f"(d[OFF+43]), "+f"(d[OFF+44]), "+f"(d[OFF+45]), "+f"(d[OFF+46]), "+f"(d[OFF+47]), "+f"(d[OFF+48]), "+f"(d[OFF+49]), "+f"(d[OFF+50]), "+f"(d[OFF+51]), "+f"(d[OFF+52]), "+f"(d[OFF+53]), "+f"(d[OFF+54]), "+f"(d[OFF+55]), "+f"(d[OFF+56]), "+f"(d[OFF+57]), "+f"(d[OFF+58]), "+f"(d[OFF+59]), "+f"(d[OFF+60]), "+f"(d[OFF+61]), "+f"(d[OFF+62]), "+f"(d[OFF+63]), "+f"(d[OFF+64]), "+f"(d[OFF+65]), "+f"(d[OFF+66]), "+f"(d[OFF+67]), "+f"(d[OFF+68]), "+f"(d[OFF+69]), "+f"(d[OFF+70]), "+f"(d[OFF+71]), "+f"(d[OFF+72]), "+f"(d[OFF+73]), "+f"(d[OFF+74]), "+f"(d[OFF+75]), "+f"(d[OFF+76]), "+f"(d[OFF+77]), "+f"(d[OFF+78]), "+f"(d[OFF+79]), "+f"(d[OFF+80]), "+f"(d[OFF+81]), "+f"(d[OFF+82]), "+f"(d[OFF+83]), "+f"(d[OFF+84]), "+f"(d[OFF+85]), "+f"(d[OFF+86]), "+f"(d[OFF+87]), "+f"(d[OFF+88]), "+f"(d[OFF+89]), "+f"(d[OFF+90]), "+f"(d[OFF+91]), "+f"(d[OFF+92]), "+f"(d[OFF+93]), "+f"(d[OFF+94]), "+f"(d[OFF+95]), "+f"(d[OFF+96]), "+f"(d[OFF+97]), "+f"(d[OFF+98]), "+f"(d[OFF+99]), "+f"(d[OFF+100]), "+f"(d[OFF+101]), "+f"(d[OFF+102]), "+f"(d[OFF+103]), "+f"(d[OFF+104]), "+f"(d[OFF+105]), "+f"(d[OFF+106]), "+f"(d[OFF+107]), "+f"(d[OFF+108]), "+f"(d[OFF+109]), "+f"(d[OFF+110]), "+f"(d[OFF+111]), "+f"(d[OFF+112]), "+f"(d[OFF+113]), "+f"(d[OFF+114]), "+f"(d[OFF+115]), "+f"(d[OFF+116]), "+f"(d[OFF+117]), "+f"(d[OFF+118]), "+f"(d[OFF+119]), "+f"(d[OFF+120]), "+f"(d[OFF+121]), "+f"(d[OFF+122]), "+f"(d[OFF+123]), "+f"(d[OFF+124]), "+f"(d[OFF+125]), "+f"(d[OFF+126]), "+f"(d[OFF+127])
    : "l"(da), "l"(db), "r"(scale_d), "n"(TB));
}
template<int TB, int OFF, int NT>
__device__ __forceinline__ void wgmma_ss_n32(float (&d)[NT], uint64_t da, uint64_t db, int scale_d) {
  asm volatile("{\n.reg .pred p;\nsetp.ne.b32 p, %18, 0;\n"
    "wgmma.mma_async.sync.aligned.m64n32k16.f32.bf16.bf16 {%0, %1, %2, %3, %4, %5, %6, %7, %8, %9, %10, %11, %12, %13, %14, %15}, %16, %17, p, 1, 1, 0, %19;\n}\n"
    : "+f"(d[OFF+0]), "+f"(d[OFF+1]), "+f"(d[OFF+2]), "+f"(d[OFF+3]), "+f"(d[OFF+4]), "+f"(d[OFF+5]), "+f"(d[OFF+6]), "+f"(d[OFF+7]), "+f"(d[OFF+8]), "+f"(d[OFF+9]), "+f"(d[OFF+10]), "+f"(d[OFF+11]), "+f"(d[OFF+12]), "+f"(d[OFF+13]), "+f"(d[OFF+14]), "+f"(d[OFF+15])
    : "l"(da), "l"(db), "r"(scale_d), "n"(TB));
}
template<int TB, int OFF, int NT>
__device__ __forceinline__ void wgmma_rs_n128(float (&d)[NT], uint32_t a0, uint32_t a1, uint32_t a2, uint32_t a3, uint64_t db, int scale_d) {
  asm volatile("{\n.reg .pred p;\nsetp.ne.b32 p, %69, 0;\n"
    "wgmma.mma_async.sync.aligned.m64n128k16.f32.bf16.bf16 {%0, %1, %2, %3, %4, %5, %6, %7, %8, %9, %10, %11, %12, %13, %14, %15, %16, %17, %18, %19, %20, %21, %22, %23, %24, %25, %26, %27, %28, %29, %30, %31, %32, %33, %34, %35, %36, %37, %38, %39, %40, %41, %42, %43, %44, %45, %46, %47, %48, %49, %50, %51, %52, %53, %54, %55, %56, %57, %58, %59, %60, %61, %62, %63}, {%64, %65, %66, %67}, %68, p, 1, 1, %70;\n}\n"
    : "+f"(d[OFF+0]), "+f"(d[OFF+1]), "+f"(d[OFF+2]), "+f"(d[OFF+3]), "+f"(d[OFF+4]), "+f"(d[OFF+5]), "+f"(d[OFF+6]), "+f"(d[OFF+7]), "+f"(d[OFF+8]), "+f"(d[OFF+9]), "+f"(d[OFF+10]), "+f"(d[OFF+11]), "+f"(d[OFF+12]), "+f"(d[OFF+13]), "+f"(d[OFF+14]), "+f"(d[OFF+15]), "+f"(d[OFF+16]), "+f"(d[OFF+17]), "+f"(d[OFF+18]), "+f"(d[OFF+19]), "+f"(d[OFF+20]), "+f"(d[OFF+21]), "+f"(d[OFF+22]), "+f"(d[OFF+23]), "+f"(d[OFF+24]), "+f"(d[OFF+25]), "+f"(d[OFF+26]), "+f"(d[OFF+27]), "+f"(d[OFF+28]), "+f"(d[OFF+29]), "+f"(d[OFF+30]), "+f"(d[OFF+31]), "+f"(d[OFF+32]), "+f"(d[OFF+33]), "+f"(d[OFF+34]), "+f"(d[OFF+35]), "+f"(d[OFF+36]), "+f"(d[OFF+37]), "+f"(d[OFF+38]), "+f"(d[OFF+39]), "+f"(d[OFF+40]), "+f"(d[OFF+41]), "+f"(d[OFF+42]), "+f"(d[OFF+43]), "+f"(d[OFF+44]), "+f"(d[OFF+45]), "+f"(d[OFF+46]), "+f"(d[OFF+47]), "+f"(d[OFF+48]), "+f"(d[OFF+49]), "+f"(d[OFF+50]), "+f"(d[OFF+51]), "+f"(d[OFF+52]), "+f"(d[OFF+53]), "+f"(d[OFF+54]), "+f"(d[OFF+55]), "+f"(d[OFF+56]), "+f"(d[OFF+57]), "+f"(d[OFF+58]), "+f"(d[OFF+59]), "+f"(d[OFF+60]), "+f"(d[OFF+61]), "+f"(d[OFF+62]), "+f"(d[OFF+63])
    : "r"(a0), "r"(a1), "r"(a2), "r"(a3), "l"(db), "r"(scale_d), "n"(TB));
}
template<int TB, int OFF, int NT>
__device__ __forceinline__ void wgmma_rs_n256(float (&d)[NT], uint32_t a0, uint32_t a1, uint32_t a2, uint32_t a3, uint64_t db, int scale_d) {
  asm volatile("{\n.reg .pred p;\nsetp.ne.b32 p, %133, 0;\n"
    "wgmma.mma_async.sync.aligned.m64n256k16.f32.bf16.bf16 {%0, %1, %2, %3, %4, %5, %6, %7, %8, %9, %10, %11, %12, %13, %14, %15, %16, %17, %18, %19, %20, %21, %22, %23, %24, %25, %26, %27, %28, %29, %30, %31, %32, %33, %34, %35, %36, %37, %38, %39, %40, %41, %42, %43, %44, %45, %46, %47, %48, %49, %50, %51, %52, %53, %54, %55, %56, %57, %58, %59, %60, %61, %62, %63, %64, %65, %66, %67, %68, %69, %70, %71, %72, %73, %74, %75, %76, %77, %78, %79, %80, %81, %82, %83, %84, %85, %86, %87, %88, %89, %90, %91, %92, %93, %94, %95, %96, %97, %98, %99, %100, %101, %102, %103, %104, %105, %106, %107, %108, %109, %110, %111, %112, %113, %114, %115, %116, %117, %118, %119, %120, %121, %122, %123, %124, %125, %126, %127}, {%128, %129, %130, %131}, %132, p, 1, 1, %134;\n}\n"
    : "+f"(d[OFF+0]), "+f"(d[OFF+1]), "+f"(d[OFF+2]), "+f"(d[OFF+3]), "+f"(d[OFF+4]), "+f"(d[OFF+5]), "+f"(d[OFF+6]), "+f"(d[OFF+7]), "+f"(d[OFF+8]), "+f"(d[OFF+9]), "+f"(d[OFF+10]), "+f"(d[OFF+11]), "+f"(d[OFF+12]), "+f"(d[OFF+13]), "+f"(d[OFF+14]), "+f"(d[OFF+15]), "+f"(d[OFF+16]), "+f"(d[OFF+17]), "+f"(d[OFF+18]), "+f"(d[OFF+19]), "+f"(d[OFF+20]), "+f"(d[OFF+21]), "+f"(d[OFF+22]), "+f"(d[OFF+23]), "+f"(d[OFF+24]), "+f"(d[OFF+25]), "+f"(d[OFF+26]), "+f"(d[OFF+27]), "+f"(d[OFF+28]), "+f"(d[OFF+29]), "+f"(d[OFF+30]), "+f"(d[OFF+31]), "+f"(d[OFF+32]), "+f"(d[OFF+33]), "+f"(d[OFF+34]), "+f"(d[OFF+35]), "+f"(d[OFF+36]), "+f"(d[OFF+37]), "+f"(d[OFF+38]), "+f"(d[OFF+39]), "+f"(d[OFF+40]), "+f"(d[OFF+41]), "+f"(d[OFF+42]), "+f"(d[OFF+43]), "+f"(d[OFF+44]), "+f"(d[OFF+45]), "+f"(d[OFF+46]), "+f"(d[OFF+47]), "+f"(d[OFF+48]), "+f"(d[OFF+49]), "+f"(d[OFF+50]), "+f"(d[OFF+51]), "+f"(d[OFF+52]), "+f"(d[OFF+53]), "+f"(d[OFF+54]), "+f"(d[OFF+55]), "+f"(d[OFF+56]), "+f"(d[OFF+57]), "+f"(d[OFF+58]), "+f"(d[OFF+59]), "+f"(d[OFF+60]), "+f"(d[OFF+61]), "+f"(d[OFF+62]), "+f"(d[OFF+63]), "+f"(d[OFF+64]), "+f"(d[OFF+65]), "+f"(d[OFF+66]), "+f"(d[OFF+67]), "+f"(d[OFF+68]), "+f"(d[OFF+69]), "+f"(d[OFF+70]), "+f"(d[OFF+71]), "+f"(d[OFF+72]), "+f"(d[OFF+73]), "+f"(d[OFF+74]), "+f"(d[OFF+75]), "+f"(d[OFF+76]), "+f"(d[OFF+77]), "+f"(d[OFF+78]), "+f"(d[OFF+79]), "+f"(d[OFF+80]), "+f"(d[OFF+81]), "+f"(d[OFF+82]), "+f"(d[OFF+83]), "+f"(d[OFF+84]), "+f"(d[OFF+85]), "+f"(d[OFF+86]), "+f"(d[OFF+87]), "+f"(d[OFF+88]), "+f"(d[OFF+89]), "+f"(d[OFF+90]), "+f"(d[OFF+91]), "+f"(d[OFF+92]), "+f"(d[OFF+93]), "+f"(d[OFF+94]), "+f"(d[OFF+95]), "+f"(d[OFF+96]), "+f"(d[OFF+97]), "+f"(d[OFF+98]), "+f"(d[OFF+99]), "+f"(d[OFF+100]), "+f"(d[OFF+101]), "+f"(d[OFF+102]), "+f"(d[OFF+103]), "+f"(d[OFF+104]), "+f"(d[OFF+105]), "+f"(d[OFF+106]), "+f"(d[OFF+107]), "+f"(d[OFF+108]), "+f"(d[OFF+109]), "+f"(d[OFF+110]), "+f"(d[OFF+111]), "+f"(d[OFF+112]), "+f"(d[OFF+113]), "+f"(d[OFF+114]), "+f"(d[OFF+115]), "+f"(d[OFF+116]), "+f"(d[OFF+117]), "+f"(d[OFF+118]), "+f"(d[OFF+119]), "+f"(d[OFF+120]), "+f"(d[OFF+121]), "+f"(d[OFF+122]), "+f"(d[OFF+123]), "+f"(d[OFF+124]), "+f"(d[OFF+125]), "+f"(d[OFF+126]), "+f"(d[OFF+127])
    : "r"(a0), "r"(a1), "r"(a2), "r"(a3), "l"(db), "r"(scale_d), "n"(TB));
}
template<int TB, int OFF, int NT>
__device__ __forceinline__ void wgmma_rs_n32(float (&d)[NT], uint32_t a0, uint32_t a1, uint32_t a2, uint32_t a3, uint64_t db, int scale_d) {
  asm volatile("{\n.reg .pred p;\nsetp.ne.b32 p, %21, 0;\n"
    "wgmma.mma_async.sync.aligned.m64n32k16.f32.bf16.bf16 {%0, %1, %2, %3, %4, %5, %6, %7, %8, %9, %10, %11, %12, %13, %14, %15}, {%16, %17, %18, %19}, %20, p, 1, 1, %22;\n}\n"
    : "+f"(d[OFF+0]), "+f"(d[OFF+1]), "+f"(d[OFF+2]), "+f"(d[OFF+3]), "+f"(d[OFF+4]), "+f"(d[OFF+5]), "+f"(d[OFF+6]), "+f"(d[OFF+7]), "+f"(d[OFF+8]), "+f"(d[OFF+9]), "+f"(d[OFF+10]), "+f"(d[OFF+11]), "+f"(d[OFF+12]), "+f"(d[OFF+13]), "+f"(d[OFF+14]), "+f"(d[OFF+15])
    : "r"(a0), "r"(a1), "r"(a2), "r"(a3), "l"(db), "r"(scale_d), "n"(TB));
}

__device__ __forceinline__ void wait_flag(const unsigned int* f, uint32_t target) {
  uint32_t v;
#pragma unroll 1
  for (uint32_t spins = 0; spins < (1u << 22); spins++) {
    asm volatile("ld.acquire.gpu.global.u32 %0, [%1];" : "=r"(v) : "l"(f) : "memory");
    if (v >= target) break;
    __nanosleep(100);
  }
}
__device__ __forceinline__ uint32_t lds32(uint32_t a) {
  uint32_t v;
  asm volatile("ld.shared.u32 %0, [%1];" : "=r"(v) : "r"(a) : "memory");
  return v;
}
__device__ __forceinline__ float gate_row(int row, int lane, const bf16* __restrict__ x, const bf16* __restrict__ gate_w) {
  const uint32_t* xr = reinterpret_cast<const uint32_t*>(x + (size_t)row * DM);
  const uint32_t* gw2 = reinterpret_cast<const uint32_t*>(gate_w);
  float gs = 0.f;
#pragma unroll
  for (int i = 0; i < 9; i++) {
    const uint32_t a = __ldg(xr + lane + 32 * i), b = __ldg(gw2 + lane + 32 * i);
    gs = fmaf(bf_lo(a), bf_lo(b), gs);
    gs = fmaf(bf_hi(a), bf_hi(b), gs);
  }
#pragma unroll
  for (int o = 16; o; o >>= 1) gs += __shfl_xor_sync(0xffffffffu, gs, o);
  const float g = 1.f / (1.f + __expf(-gs));
  if (lane == 0) g_gate[row] = g;
  return g;
}
constexpr uint32_t LQ = 36864, LV = 55296;
__device__ __forceinline__ void mma16(float (&c)[4], uint32_t a0, uint32_t a1, uint32_t a2, uint32_t a3, uint32_t b0, uint32_t b1) {
  asm("mma.sync.aligned.m16n8k16.row.col.f32.bf16.bf16.f32 {%0, %1, %2, %3}, {%4, %5, %6, %7}, {%8, %9}, {%0, %1, %2, %3};"
      : "+f"(c[0]), "+f"(c[1]), "+f"(c[2]), "+f"(c[3]) : "r"(a0), "r"(a1), "r"(a2), "r"(a3), "r"(b0), "r"(b1));
}
__device__ __forceinline__ void mma8(float (&c)[4], uint32_t a0, uint32_t a1, uint32_t b0) {
  asm("mma.sync.aligned.m16n8k8.row.col.f32.bf16.bf16.f32 {%0, %1, %2, %3}, {%4, %5}, {%6}, {%0, %1, %2, %3};"
      : "+f"(c[0]), "+f"(c[1]), "+f"(c[2]), "+f"(c[3]) : "r"(a0), "r"(a1), "r"(b0));
}
template <typename F>
__device__ __forceinline__ void local_attn(int lr0, int warp_g, uint32_t sL, uint32_t bL, uint32_t bL2, int lane, float g0, float g1, F st) {
  const float scale_l2 = 0.23570226039551584f * 1.4426950408889634f;
  const int g = lane >> 2, t = lane & 3;
  const bool lo0 = 2 * t > g, lo1 = 2 * t + 1 > g;
  const uint32_t mlo = (lo0 ? 0xFFFFu : 0u) | (lo1 ? 0xFFFF0000u : 0u);
  const bool ok0 = lr0 > 0 || !lo0, ok1 = lr0 > 0 || !lo1;
  uint32_t ad[9], k[9][4], qf[9][2], pe[4], po[4];
#pragma unroll
  for (int c = 0; c < 9; c++) {
    const uint32_t ch = warp_g * 9 + c;
    ad[c] = sL + (lane >> 4) * 18432 + (lane & 15) * 128 + ((ch >> 3) << 11) + (((ch ^ lane) & 7) << 4);
  }
  st(0, 0u); st(1, 0u);
  mbar_wait(bL, 0);
  if (warp_g == 0) TS(1, 6);
#pragma unroll
  for (int c = 0; c < 9; c++) {
    asm volatile("ldmatrix.sync.aligned.m8n8.x2.shared.b16 {%0, %1}, [%2];" : "=r"(qf[c][0]), "=r"(qf[c][1]) : "r"(ad[c] + LQ) : "memory");
    ldsm_x4(k[c][0], k[c][1], k[c][2], k[c][3], ad[c]);
  }
  st(2, k[0][0]); st(3, k[8][0]);
#pragma unroll
  for (int i = 0; i < 4; i++) {
    const uint32_t q0 = (t >= i) ? qf[2 * i][0] : 0u, q1 = (t >= i) ? qf[2 * i][1] : 0u;
    const uint32_t q4 = (t <= i) ? qf[2 * i + 2][0] : 0u, q5 = (t <= i) ? qf[2 * i + 2][1] : 0u;
    float c[4][4];
#pragma unroll
    for (int T = 0; T < 4; T++) {
#pragma unroll
      for (int j = 0; j < 4; j++) c[T][j] = 0.f;
      mma16(c[T], q0, q1, qf[2 * i + 1][0], qf[2 * i + 1][1], k[2 * i][T], k[2 * i + 1][T]);
      mma8(c[T], q4, q5, k[2 * i + 2][T]);
    }
    const float e0 = ok0 ? (lo0 ? c[0][0] : c[1][0]) : -INFINITY, e1 = ok1 ? (lo1 ? c[0][1] : c[1][1]) : -INFINITY;
    const float o0 = ok0 ? (lo0 ? c[2][2] : c[3][2]) : -INFINITY, o1 = ok1 ? (lo1 ? c[2][3] : c[3][3]) : -INFINITY;
    float me = fmaxf(e0, e1), mo = fmaxf(o0, o1);
    me = fmaxf(me, __shfl_xor_sync(0xffffffffu, me, 1));
    mo = fmaxf(mo, __shfl_xor_sync(0xffffffffu, mo, 1));
    me = fmaxf(me, __shfl_xor_sync(0xffffffffu, me, 2)) * scale_l2;
    mo = fmaxf(mo, __shfl_xor_sync(0xffffffffu, mo, 2)) * scale_l2;
    const float w0 = ex2(fmaf(e0, scale_l2, -me)), w1 = ex2(fmaf(e1, scale_l2, -me));
    const float w2 = ex2(fmaf(o0, scale_l2, -mo)), w3 = ex2(fmaf(o1, scale_l2, -mo));
    float se = w0 + w1, so = w2 + w3;
    st(4 + 2 * i, __float_as_uint(i == 1 ? me : i == 2 ? se : e0));
    se += __shfl_xor_sync(0xffffffffu, se, 1);
    so += __shfl_xor_sync(0xffffffffu, so, 1);
    se += __shfl_xor_sync(0xffffffffu, se, 2);
    so += __shfl_xor_sync(0xffffffffu, so, 2);
    asm("rcp.approx.ftz.f32 %0, %0;" : "+f"(se));
    asm("rcp.approx.ftz.f32 %0, %0;" : "+f"(so));
    se *= g0;
    so *= g1;
    pe[i] = pack_bf16(w0 * se, w1 * se);
    po[i] = pack_bf16(w2 * so, w3 * so);
    st(5 + 2 * i, i == 0 ? __float_as_uint(w0) : i == 2 ? __float_as_uint(mo) : po[i]);
  }
  if (warp_g == 0) TS(0, 4);
  mbar_wait(bL2, 0);
  if (warp_g == 0) TS(0, 5);
#pragma unroll
  for (int c = 0; c < 9; c++)
    asm volatile("ldmatrix.sync.aligned.m8n8.x4.trans.shared.b16 {%0, %1, %2, %3}, [%4];"
                 : "=r"(k[c][0]), "=r"(k[c][1]), "=r"(k[c][2]), "=r"(k[c][3]) : "r"(ad[c] + LV) : "memory");
#pragma unroll
  for (int i = 0; i < 4; i++) {
#pragma unroll
    for (int n = 0; n < 3; n++) {
      float c[4] = {0.f, 0.f, 0.f, 0.f};
      mma16(c, pe[i] & mlo, 0u, pe[i] & ~mlo, 0u, k[2 * i + n][0], k[2 * i + n][1]);
      mma16(c, 0u, po[i] & mlo, 0u, po[i] & ~mlo, k[2 * i + n][2], k[2 * i + n][3]);
      const uint32_t r0 = pack_bf16(c[0], c[1]), r1 = pack_bf16(c[2], c[3]);
      const bool keep = (n == 0) && (t < i);
      qf[2 * i + n][0] = keep ? qf[2 * i + n][0] : r0;
      qf[2 * i + n][1] = keep ? qf[2 * i + n][1] : r1;
    }
    st(12 + i, qf[2 * i + 1][0]);
  }
#pragma unroll
  for (int c = 0; c < 9; c++)
    asm volatile("stmatrix.sync.aligned.m8n8.x2.shared.b16 [%0], {%1, %2};" ::"r"(ad[c] + LQ), "r"(qf[c][0]), "r"(qf[c][1]) : "memory");
  asm volatile("fence.proxy.async.shared::cta;" ::: "memory");
}
__device__ __forceinline__ void tma4d(uint32_t dst, const CUtensorMap* m, uint32_t bar, int c1, int c2, int c3) {
  asm volatile("cp.async.bulk.tensor.4d.shared::cluster.global.mbarrier::complete_tx::bytes [%0], [%1, {%3, %4, %5, %6}], [%2];" ::"r"(dst),
               "l"(m), "r"(bar), "r"(0), "r"(c1), "r"(c2), "r"(c3) : "memory");
}

#define ST_NUM 1
#define ST_DEN 2
#define K1_NST 6
constexpr int K1_BST = K1_NST;
#define MAXJ 11
constexpr int K1_MAXJOBS = MAXJ;
constexpr uint32_t K1_FLAG_TARGET = 7;
constexpr uint32_t RDY_TARGET = 48;
constexpr uint32_t GATE_TARGET = 128 * 3;
struct alignas(64) Params {
  CUtensorMap tmA[2];
  CUtensorMap tmW[4];
  CUtensorMap tmK, tmV;
  CUtensorMap tmL[3];
  CUtensorMap tmC, tmO[2], tmOt[2];
  uint16_t jobs[NCLUSTER][K1_MAXJOBS + 1];
  uint8_t order[256];
  uint8_t unit[65][8];
};

struct K1State {
  uint32_t bs, bph, aph;
  bf16 *pp, *pp8;
  int png;
  int tn;
  int wsel;
};
__device__ __forceinline__ void k1_flag(const K1State& st, int lane, uint32_t bS) {
  if (st.png) {
    __syncwarp();
    if (lane == 0) mbar_arrive(bS);
  }
}

__device__ __forceinline__ void scale_q4(uint32_t* v) {
#pragma unroll
  for (int i = 0; i < 4; i++)
    asm volatile("{\n.reg .b32 t;\nmul.rn.bf16x2 t, %0, %2;\nfma.rn.bf16x2 %0, %0, %1, t;\n}" : "+r"(v[i]) : "r"(0x3E033E03u), "r"(0xB9D8B9D8u));
}
__device__ __forceinline__ void k1_first(const K1State& st, uint32_t job, uint32_t bAf, uint32_t bBf) {
  if (job & 3) {
    if ((job >> 14) & 1) mbar_wait(bAf, st.aph);
    mbar_wait(bBf + st.bs * 8, st.bph);
  }
}
__device__ __forceinline__ void k1_tile(float (&acc)[128], uint32_t (&pk)[64], K1State& st, uint32_t job, uint32_t njob, uint32_t sA, uint32_t sB,
                                        uint32_t bAf, uint32_t bAe, uint32_t bBf, uint32_t bBe, uint32_t bS, int wg, int warp, int lane, uint32_t rank) {
  const int a_sel = (job >> 2) & 1, mpair = (job >> 3) & 7, w_sel = (job >> 6) & 3, chunk0 = (job >> 8) & 63;
  const bool newA = (job >> 14) & 1, lastA = (job >> 15) & 1;
  const bool sig = (lane == 0) && (warp < 2);
  const bool siga = lastA && (lane == 0) && (warp == 2);
  const int KC = 8 + a_sel;
  uint32_t prev_bs = 0, a8_bs = 0;
#pragma unroll
  for (int kc = 0; kc < 9; kc++) {
    if (kc >= KC) break;
    uint32_t abase = sA + ((kc + 2) & 7) * 16384;
    if (kc == 8) {
      mbar_wait(bBf + st.bs * 8, st.bph);
      a8_bs = st.bs;
      abase = sB + st.bs * 16384;
      if (++st.bs == K1_BST) { st.bs = 0; st.bph ^= 1; }
    } else if (newA && kc > 0) {
      mbar_wait(bAf + kc * 8, st.aph);
    }
    const uint64_t da = make_desc(abase + wg * 8192, 16, 1024, 1);
#pragma unroll
    for (int ks = 0; ks < 2; ks++) {
      if (ks > 0 || kc > 0) mbar_wait(bBf + st.bs * 8, st.bph);
      const uint64_t db = make_desc(sB + st.bs * 16384, 2048, 1024, 1);
      wg_fence();
      wgmma_ss_n256<1, 0>(acc, da + (uint64_t)(ks * 4), db, (ks > 0) ? 1 : (kc > 0));
      wgmma_ss_n256<1, 0>(acc, da + (uint64_t)(ks * 4 + 2), db + (uint64_t)512, 1);
      wg_commit();
      wg_wait<1>();
      if (ks > 0 || kc > 0) {
        if (sig) mbar_arrive_cluster(bBe + prev_bs * 8, warp);
        if (ks == 0 && siga) mbar_arrive(bAe + (kc - 1) * 8);
      }
      if (st.wsel == 2) {
        const int i = (kc & 7) * 2 + ks;
        if (kc < st.png) {
          quad_transpose(pk[i * 4], pk[i * 4 + 1], pk[i * 4 + 2], pk[i * 4 + 3], lane & 3);
          st_v4a((ks ? st.pp8 : st.pp) + kc * 32, pk[i * 4], pk[i * 4 + 1], pk[i * 4 + 2], pk[i * 4 + 3]);
        }
        if (i == 15) k1_flag(st, lane, bS);
      } else if (st.png) {
#pragma unroll
        for (int i = 0; i < 16; i++) {
          if (i * ST_NUM / ST_DEN != kc * 2 + ks) continue;
          if (st.wsel == 3) scale_q4(pk + i * 4);
          st_v4a(((i & 1) ? st.pp8 : st.pp) + (i / 2) * 32, pk[i * 4], pk[i * 4 + 1], pk[i * 4 + 2], pk[i * 4 + 3]);
          if (i == 15) k1_flag(st, lane, bS);
        }
      }
      prev_bs = st.bs;
      if (++st.bs == K1_BST) { st.bs = 0; st.bph ^= 1; }
    }
  }
  if (newA) st.aph ^= 1;
  const bool isA = (w_sel == 2);
  bf16* out = (w_sel == 0) ? g_K : (w_sel == 1) ? g_V : isA ? g_QKVA : g_ctx;
  const int ld = isA ? NQKVA : (w_sel == 3) ? KCAT : HDIM;
  const int row = mpair * 256 + rank * 128 + wg * 64 + warp * 16 + (lane >> 2);
  st.pp = ptr_add(out, (row * ld + chunk0 * 64 + (lane & 3) * 8) * 2);
  st.pp8 = ptr_add(st.pp, 16 * ld);
  st.png = ((job & 3) + 1) * 2;
  st.wsel = w_sel;
  k1_first(st, njob, bAf, bBf);
  wg_wait<0>();
  fence_regs(acc);
  mbar_arrive_cluster_if(bBe + prev_bs * 8, warp & 1, sig);
  mbar_arrive_cluster_if(bBe + a8_bs * 8, warp & 1, sig && a_sel);
  mbar_arrive_if(bAe + 7 * 8, siga && !a_sel);
#pragma unroll
  for (int i = 0; i < 64; i++) {
    const int j = (i >> 3) * 16 + (i & 3) * 4 + ((i >> 2) & 1) * 2;
    pk[i] = pack_bf16(acc[j], acc[j + 1]);
  }
}

constexpr int K2_NST = 7;
constexpr uint32_t K2_END = 0x100;
#define PFD 4
#define PF3A 2
#define PF3 6
#define FIRST_DRAW 3
#define PWAIT mbar_wait_ns<1000>
#define PVM 0x8A
#define W0 63
#define SPEC_HI 1.8446744073709552e19f
#define SPEC_LO 5.421010862427522e-20f
constexpr int K3_NST = 4;
__device__ __forceinline__ uint32_t k3_rot(uint32_t sv) { return (0x00E9u >> (2 * sv)) & 3; }
constexpr int K3_STAGE = 16384 + 32768 + 4096;
constexpr int SMEM_DATA = 7 * 32768;
constexpr int SMEM_BYTES = SMEM_DATA + 1024 + 768;

struct Cursor {
  uint32_t s, ph;
  __device__ __forceinline__ void next() {
    if (++s == K2_NST) { s = 0; ph ^= 1; }
  }
};

#define TURN_SYNC() bar_sync(mybar, 256)
#define TURN_ARRIVE() bar_arrive(otherbar, 256)
#define RELEASE_IF(cur, cond) mbar_arrive_cluster_if(bE + (cur).s * 8, warp & 1, sig && (cond))
#define RELEASE(cur) RELEASE_IF(cur, true)
#define ISSUE_PV(cur, first)                                                                                   \
  do {                                                                                                         \
    const uint64_t dv = make_desc(sbase + (cur).s * 32768, 16384, 1024, 1);                                    \
    _Pragma("unroll") for (int t = 0; t < 8; t++)                                                              \
        wgmma_rs_n128<1, 0>(O, P[4 * t], P[4 * t + 1], P[4 * t + 2], P[4 * t + 3], dv + (uint64_t)(t * 128), (t > 0) ? 1 : !(first)); \
  } while (0)
#define ISSUE_QK(cur)                                                                                          \
  do {                                                                                                         \
    const uint64_t dk = make_desc(sbase + (cur).s * 32768, 16, 1024, 1);                                       \
    _Pragma("unroll") for (int t = 0; t < 8; t++)                                                              \
        wgmma_rs_n128<0, 0>(S, Q[4 * t], Q[4 * t + 1], Q[4 * t + 2], Q[4 * t + 3], dk + (uint64_t)((t >> 2) * 1024 + (t & 3) * 2), t > 0); \
  } while (0)
#define EXPB(T)                                                                                                \
  do {                                                                                                         \
    _Pragma("unroll") for (int i = 4 * T; i < 4 * T + 4; i++) asm volatile("" : "+r"(P[i])::"memory");        \
    _Pragma("unroll") for (int jj = 2 * T; jj < 2 * T + 2; jj++) {                                             \
      const float e0 = ex2(S[jj * 4 + 0]), e1 = ex2(S[jj * 4 + 1]), e2 = ex2(S[jj * 4 + 2]), e3 = ex2(S[jj * 4 + 3]); \
      s0 += e0 + e1;                                                                                           \
      s1 += e2 + e3;                                                                                           \
      P[jj * 2 + 0] = pack_bf16(e0, e1);                                                                       \
      P[jj * 2 + 1] = pack_bf16(e2, e3);                                                                       \
    }                                                                                                          \
  } while (0)
#define EXPC(T)                                                                                                \
  do {                                                                                                         \
    if (T > 0 && ((PVM >> (T - 1)) & 1)) {                                                                     \
      anchor((T & 2) ? s0 : s1, never);                                                                        \
      wg_wait<__builtin_popcount(PVM >> T) - 1>();                                                             \
      if ((PVM >> T) == (128 >> T)) { fence_regs(O); RELEASE(cv); }                                            \
    }                                                                                                          \
    EXPB(T);                                                                                                   \
  } while (0)
#define MASK(G, g)                                                                                             \
  do {                                                                                                         \
    if ((g) * 8 > d) S[(G) * 4 + 0] = -INFINITY;                                                               \
    if ((g) * 8 + 1 > d) S[(G) * 4 + 1] = -INFINITY;                                                           \
    if ((g) * 8 - 8 > d) S[(G) * 4 + 2] = -INFINITY;                                                           \
    if ((g) * 8 - 7 > d) S[(G) * 4 + 3] = -INFINITY;                                                           \
  } while (0)
#define STORE_O(G)                                                                                             \
  do {                                                                                                         \
    st_v4(optr + (G) * 32, pack_bf16(O[(G) * 16 + 0] * f0, O[(G) * 16 + 1] * f0), pack_bf16(O[(G) * 16 + 4] * f0, O[(G) * 16 + 5] * f0), \
          pack_bf16(O[(G) * 16 + 8] * f0, O[(G) * 16 + 9] * f0), pack_bf16(O[(G) * 16 + 12] * f0, O[(G) * 16 + 13] * f0)); \
    st_v4(optr + 8 * KCAT + (G) * 32, pack_bf16(O[(G) * 16 + 2] * f1, O[(G) * 16 + 3] * f1), pack_bf16(O[(G) * 16 + 6] * f1, O[(G) * 16 + 7] * f1), \
          pack_bf16(O[(G) * 16 + 10] * f1, O[(G) * 16 + 11] * f1), pack_bf16(O[(G) * 16 + 14] * f1, O[(G) * 16 + 15] * f1)); \
  } while (0)

#define FLUSH()                                                                                                \
  do {                                                                                                         \
    _Pragma("unroll") for (int G = 0; G < 8; G++) {                                                            \
      st_v4a(st.pp + G * 32, pk[G * 8], pk[G * 8 + 1], pk[G * 8 + 2], pk[G * 8 + 3]);                          \
      st_v4a(st.pp8 + G * 32, pk[G * 8 + 4], pk[G * 8 + 5], pk[G * 8 + 6], pk[G * 8 + 7]);                     \
    }                                                                                                          \
    k1_flag(st, lane, bS);                                                                                     \
  } while (0)

__global__ void __cluster_dims__(2, 1, 1) __launch_bounds__(384, 1)
fused_kernel(const __grid_constant__ Params p, const bf16* __restrict__ x, const bf16* __restrict__ gate_w, bf16* __restrict__ out) {
  extern __shared__ uint8_t smem_raw[];
  const uint32_t sbase = (smem_u32(smem_raw) + 1023) & ~1023u;
  const uint32_t sB = sbase, sA = sbase + K1_BST * 16384, sBar = sbase + SMEM_DATA;
  const uint32_t bAf = sBar, bAe = sBar + 64, bBf = sBar + 128, bBe = sBar + 176, bL = sBar + 224, bS = sBar + 232, bL2 = sBar + 240, sL = sA + 32768;
  const uint32_t bF = sBar + 256, bE = sBar + 320, bT = sBar + 384, sTick = sBar + 400, sItem = sBar + 416, bS2 = sBar + 448, bR = sBar + 456, bLast = sBar + 464, bH = sBar + 472, bT0 = sBar + 480;
  const uint32_t b3F = sBar + 512, b3E = sBar + 544, sGate = sBar + 576;
  const int tid = threadIdx.x, warp_g = __shfl_sync(0xffffffffu, tid >> 5, 0), lane = tid & 31;
  const uint32_t rank = cluster_rank();
  const int cl = blockIdx.x >> 1;
  TSM(0);
  if (tid == 0) {
    for (int i = 0; i < 8; i++) { mbar_init(bAf + i * 8, 1); mbar_init(bAe + i * 8, 2); }
    for (int i = 0; i < K1_BST; i++) { mbar_init(bBf + i * 8, 1); mbar_init(bBe + i * 8, 4); }
    mbar_init(bL, 1);
    mbar_init(bL2, 1);
    mbar_init(bR, 1);
    mbar_init(bLast, 1);
    mbar_init(bH, 4);
    mbar_init(bT0, 1);
    mbar_init(bS, 8);
    for (int i = 0; i < K2_NST; i++) { mbar_init(bF + i * 8, 1); mbar_init(bE + i * 8, 4); }
    mbar_init(bT, 1); mbar_init(bT + 8, 1);
    mbar_init(bS2, 8);
    for (int i = 0; i < K3_NST; i++) { mbar_init(b3F + i * 8, 1); mbar_init(b3E + i * 8, 4); }
    asm volatile("fence.mbarrier_init.release.cluster;" ::: "memory");
  }
  __syncwarp();
  if (warp_g != 8) cluster_sync();
  const int lr0 = blockIdx.x * 16;

  if (warp_g >= 8) {
    reg_dealloc<40>();
    if (warp_g == 8) {
      {
        const uint32_t job = p.jobs[cl][0];
        if (lane == 0) { prefetch_tmap(&p.tmA[(job >> 2) & 1]); prefetch_tmap(&p.tmW[(job >> 6) & 3]); }
        __syncwarp();
        cluster_sync();
      }
      if (elect_one()) {
        uint32_t bs = 0, bph = 1, aph = 1;
#pragma unroll 1
        for (int ji = 0; ji < K1_MAXJOBS; ji++) {
          const uint32_t job = p.jobs[cl][ji];
          if (!(job & 3)) break;
          const int a_sel = (job >> 2) & 1, mpair = (job >> 3) & 7, chunk0 = (job >> 8) & 63;
          const bool newA = (job >> 14) & 1;
          const int KC = a_sel ? 9 : 8;
          const uint32_t halfbytes = 8192;
          const bool lastjob = (ji + 1 == K1_MAXJOBS) || !(p.jobs[cl][ji + 1] & 3);
          const CUtensorMap* tw = &p.tmW[(job >> 6) & 3];
          {
            const uint32_t njob = (ji + 1 < K1_MAXJOBS) ? p.jobs[cl][ji + 1] : 0;
            if (!(njob & 3) && !newA) mbar_arrive(bLast);
          }
#pragma unroll 1
          for (int kc = 0; kc < KC; kc++) {
            {
              const bool nx = kc + PFD >= KC;
              const uint32_t njob = nx ? p.jobs[cl][ji + 1] : job;
              const int pk = nx ? kc + PFD - KC : kc + PFD;
              if ((njob & 3) && (nx || ji > 0)) {
                if (cl >= 64 || ((pk ^ (cl >> 1)) & 3) == 0)
                  tma_pf3d(&p.tmW[(njob >> 6) & 3], 0, pk * 64 + (cl & 1) * 32 + rank * 16, (njob >> 8) & 63);
                if (((njob >> 14) & 1) || pk == 8) tma_pf2d(&p.tmA[(njob >> 2) & 1], pk * 64, ((njob >> 3) & 7) * 256 + rank * 128);
              }
            }
            if (kc == 8) {
              PWAIT(bBe + bs * 8, bph);
              mbar_expect(bBf + bs * 8, 16384);
              tma2d(sB + bs * 16384, &p.tmA[1], bBf + bs * 8, 512, mpair * 256 + rank * 128);
              if (++bs == K1_BST) { bs = 0; bph ^= 1; }
            } else if (newA) {
              PWAIT(bAe + kc * 8, aph);
              mbar_expect(bAf + kc * 8, 16384);
              tma2d(sA + ((kc + 2) & 7) * 16384, &p.tmA[a_sel], bAf + kc * 8, kc * 64, mpair * 256 + rank * 128);
              if (kc == 7 && lastjob) mbar_arrive(bLast);
            }
#pragma unroll 1
            for (int kk = 0; kk < 2; kk++) {
              PWAIT(bBe + bs * 8, bph);
              mbar_expect(bBf + bs * 8, 2 * halfbytes);
              tma3d_mc(sB + bs * 16384 + rank * halfbytes, tw, bBf + bs * 8, 0, kc * 64 + kk * 32 + rank * 16, chunk0, 3);
              if (++bs == K1_BST) { bs = 0; bph ^= 1; }
            }
          }
          if (newA) aph ^= 1;
        }
        Cursor c{0, 0};
        int pcol = 0;
        PWAIT(bR, 0);
        uint32_t tick = lds32(sTick + 8), seen = 1u << (p.order[tick] >> 4);
        asm volatile("fence.proxy.async.global;" ::: "memory");
#pragma unroll 1
        for (int it = 0;; it++) {
          const uint32_t item = (tick < 256) ? p.order[tick] : (K2_END | min(tick - 256, 255u));
          asm volatile("st.shared.u32 [%0], %1;" ::"r"(sItem + (it & 7) * 4), "r"(item) : "memory");
          if (item >= K2_END) break;
          const int h = item >> 3, j = item & 7;
          const int blk = 2 * j + (int)(rank ^ (it & 1));
          const int col = h * 128 + rank * 64;
          const int nb = 2 * j + 2;
          if (!((seen >> (h >> 1)) & 1)) {
            wait_flag(&g_sync[F_HP + (h >> 1)], RDY_TARGET);
            asm volatile("fence.proxy.async.global;" ::: "memory");
            seen |= 1u << (h >> 1);
          }
          PWAIT(bE + c.s * 8, c.ph);
          mbar_expect(bF + c.s * 8, 32768);
          tma2d(sbase + c.s * 32768, &p.tmC, bF + c.s * 8, h * 128, blk * 128);
          tma2d(sbase + c.s * 32768 + 16384, &p.tmC, bF + c.s * 8, h * 128 + 64, blk * 128);
          c.next();
          if (tick >= 256 - 73) {
            const int kk = tick - (256 - 73), sel = (kk < 9), kr = (sel ? kk : kk - 9) * 64 + rank * 32;
#pragma unroll 1
            for (int i = 0; i < 2; i++) {
              tma_pf3d(&p.tmO[sel], 0, kr, i * 4);
              tma_pf2d(&p.tmOt[sel], 512 + i * 32, kr);
            }
          }
#pragma unroll 1
          for (int n = nb - 1; n >= 0; n--) {
            if (n == 0 && rank == 0) tick = atomicAdd(&g_sync[F_TICK], 1u);
            PWAIT(bE + c.s * 8, c.ph);
            mbar_expect(bF + c.s * 8, 32768);
            tma2d_mc(sbase + c.s * 32768 + rank * 16384, &p.tmK, bF + c.s * 8, col, n * 128, 3);
            c.next();
            if (n < nb - 1 || it > 0) {
              PWAIT(bE + c.s * 8, c.ph);
              mbar_expect(bF + c.s * 8, 32768);
              tma2d_mc(sbase + c.s * 32768 + rank * 16384, &p.tmV, bF + c.s * 8, (n < nb - 1) ? col : pcol, (n < nb - 1) ? (n + 1) * 128 : 0, 3);
              c.next();
            }
          }
          pcol = col;
          if (rank == 0) {
            asm volatile(
                "{\n.reg .b32 a, b;\nmapa.shared::cluster.u32 a, %0, 1;\nmapa.shared::cluster.u32 b, %1, 1;\n"
                "st.async.shared::cluster.mbarrier::complete_tx::bytes.u32 [a], %2, [b];\n}" ::"r"(sTick + (it & 1) * 4),
                "r"(bT + (it & 1) * 8), "r"(tick) : "memory");
          } else {
            mbar_expect(bT + (it & 1) * 8, 4);
            PWAIT(bT + (it & 1) * 8, (it >> 1) & 1);
            tick = lds32(sTick + (it & 1) * 4);
          }
        }
        PWAIT(bE + c.s * 8, c.ph);
        mbar_expect(bF + c.s * 8, 32768);
        tma2d_mc(sbase + c.s * 32768 + rank * 16384, &p.tmV, bF + c.s * 8, pcol, 0, 3);
        const uint32_t unit = min(tick - 256, 64u);
        const int mblk = (7 - (p.unit[unit][0] >> 1)) * 2 + rank, nhalf = p.unit[unit][0] & 1;
        uint32_t have, hoa;
        asm volatile("ld.acquire.gpu.global.u32 %0, [%1];" : "=r"(have) : "l"(&g_sync[F_CTX + mblk]) : "memory");
        asm volatile("ld.acquire.gpu.global.u32 %0, [%1];" : "=r"(hoa) : "l"(&g_sync[F_OA + mblk]) : "memory");
        asm volatile("fence.proxy.async.global;" ::: "memory");
#pragma unroll 1
        for (uint32_t idx = PF3A; idx < PF3 && unit < 64; idx++) {
          const int kk = p.unit[unit][3] + idx;
          if ((kk < 9) ? (hoa >= 8) : ((have >> ((kk - 9) >> 1)) & 1)) tma_pf2d(&p.tmC, ((kk < 9) ? 64 + kk : kk - 9) * 64, mblk * 128);
        }
        if (unit < 64) {
          const uint32_t rot = k3_rot(c.s), nfree = ((0x1Au >> c.s) & 1) ? 2 : 3;
#pragma unroll 1
          for (uint32_t idx = 0; idx < p.unit[unit][2]; idx++) {
            const int kk = p.unit[unit][3] + idx + ((idx >= p.unit[unit][4]) ? p.unit[unit][5] : 0);
            const uint32_t s = (rot + idx) & 3;
            if (idx >= nfree) PWAIT((idx < 4) ? bH : b3E + s * 8, (idx < 4) ? 0 : (~idx >> 2) & 1);
#pragma unroll 1
            while (idx < nfree && c.s != ((0x6431u >> (4 * s)) & 15)) {
              c.next();
              PWAIT(bE + c.s * 8, c.ph);
            }
            mbar_expect(b3F + s * 8, K3_STAGE);
            const uint32_t st = sbase + s * K3_STAGE;
            const int sel = (kk < 9), k = sel ? kk : kk - 9, kr = k * 64 + rank * 32;
            tma3d_mc(st + 16384 + rank * 16384, &p.tmO[sel], b3F + s * 8, 0, kr, nhalf * 4, 3);
            tma2d_mc(st + 49152 + rank * 2048, &p.tmOt[sel], b3F + s * 8, 512 + nhalf * 32, kr, 3);
            if (sel && hoa < 8) {
              wait_flag(&g_sync[F_OA + mblk], 8);
              hoa = 8;
              asm volatile("fence.proxy.async.global;" ::: "memory");
            }
            if (!sel && !((have >> (k >> 1)) & 1)) {
#pragma unroll 1
              for (uint32_t spins = 0; spins < (1u << 22); spins++) {
                asm volatile("ld.acquire.gpu.global.u32 %0, [%1];" : "=r"(have) : "l"(&g_sync[F_CTX + mblk]) : "memory");
                if ((have >> (k >> 1)) & 1) break;
                __nanosleep(100);
              }
              asm volatile("fence.proxy.async.global;" ::: "memory");
            }
            tma2d(st, &p.tmC, b3F + s * 8, (sel ? 64 + k : k) * 64, mblk * 128);
          }
        }
      }
    }
    __syncwarp();
    if (warp_g == 8) {
      uint32_t v = 0;
      if (lane == 0) {
        __threadfence();
        v = atomicAdd(&g_sync[F_DONE], 1u);
      }
      if (__shfl_sync(0xffffffffu, v, 0) == 2 * NCLUSTER - 1) {
        reinterpret_cast<uint4*>(g_sync)[lane] = make_uint4(0, 0, 0, 0);
        if (lane == 0) g_sync[F_EPOCH] = lds32(sGate + 64) + 1;
      }
    }
    asm volatile("" ::: "memory");
    if (__shfl_sync(0xffffffffu, warp_g, 0) != 8) {
      if (lr0 < S_LEN) {
#pragma unroll 1
        for (int i = warp_g - 9; i < 16; i += 3) {
          const float g = gate_row(lr0 + i, lane, x, gate_w);
          if (lane == 0) asm volatile("st.shared.f32 [%0], %1;" ::"r"(sGate + i * 4), "f"(g) : "memory");
        }
        bar_arrive(3, 256 + 96);
        if (lane == 0) {
          __threadfence();
          atomicAdd(&g_sync[F_GATE], 1u);
        }
      }
      uint32_t aph = 1;
#pragma unroll 1
      for (int ji = 0; ji < K1_MAXJOBS; ji++) aph ^= (p.jobs[cl][ji] >> 14) & 1;
      if (warp_g == 9 && lane == 0) {
#pragma unroll 1
        for (int ji = 0; ji < K1_MAXJOBS; ji++) {
          const uint32_t job = p.jobs[cl][ji];
          if (!(job & 3)) break;
          PWAIT(bS, ji & 1);
          __threadfence();
          atomicAdd(&g_sync[(((job >> 6) & 3) == 2) ? (F_QKVA + ((job >> 3) & 7) * 2 + rank) : (F_HP + ((job >> 10) & 15))], 1u);
        }
#pragma unroll 1
        for (int it = 0;; it++) {
          PWAIT(bS2, it & 1);
          const uint32_t item = lds32(sItem + (it & 7) * 4), nxt = lds32(sItem + ((it + 1) & 7) * 4);
          __threadfence();
          atomicOr(&g_sync[F_CTX + (item & 7) * 2 + (rank ^ (it & 1))], 1u << (item >> 3));
          if (nxt >= K2_END) break;
        }
      } else if (warp_g == 11) {
        if (lane == 0) {
          prefetch_tmap(&p.tmC); prefetch_tmap(&p.tmK); prefetch_tmap(&p.tmV);
          asm volatile("st.shared.u32 [%0], %1;" ::"r"(sGate + 64), "r"(__ldcg(&g_sync[F_EPOCH])) : "memory");
          wait_flag(&g_sync[F_GATE], GATE_TARGET);
          uint32_t tick;
          if (rank == 0) {
            PWAIT(bLast, 0);
            PWAIT(bAe + FIRST_DRAW * 8, aph);
            tick = atomicAdd(&g_sync[F_TICK], 1u);
            asm volatile("st.shared.u32 [%0], %1;" ::"r"(sTick + 8), "r"(tick) : "memory");
            asm volatile(
                "{\n.reg .b32 a, b;\nmapa.shared::cluster.u32 a, %0, 1;\nmapa.shared::cluster.u32 b, %1, 1;\n"
                "st.async.shared::cluster.mbarrier::complete_tx::bytes.u32 [a], %2, [b];\n}" ::"r"(sTick + 8), "r"(bT0), "r"(tick) : "memory");
          } else {
            mbar_expect(bT0, 4);
            PWAIT(bT0, 0);
            tick = lds32(sTick + 8);
          }
          wait_flag(&g_sync[F_HP + (p.order[tick] >> 4)], RDY_TARGET);
          mbar_arrive(bR);
        }
      } else if (warp_g == 10) {
        if (lr0 < S_LEN && lane == 0) {
          prefetch_tmap(&p.tmL[0]); prefetch_tmap(&p.tmL[1]); prefetch_tmap(&p.tmL[2]);
          wait_flag(&g_sync[F_QKVA + (lr0 >> 7)], K1_FLAG_TARGET);
          wait_flag(&g_sync[F_QKVA + (max(lr0 - 16, 0) >> 7)], K1_FLAG_TARGET);
          asm volatile("fence.proxy.async.global;" ::: "memory");
          PWAIT(bLast, 0);
#pragma unroll 1
          for (int kc = 0; kc < 6; kc++) {
            PWAIT(bAe + kc * 8, aph);
            if (kc == 3) {
              mbar_expect(bL, LV);
              tma4d(sL, &p.tmL[0], bL, lr0 / 2 - 8, 9, 0);
              tma4d(sL + LQ, &p.tmL[1], bL, lr0 / 2, 0, 0);
            }
          }
          mbar_expect(bL2, LQ);
          tma4d(sL + LV, &p.tmL[0], bL2, lr0 / 2 - 8, 18, 0);
        }
        __syncwarp();
        bar_sync(5, 256 + 32);
        if (lr0 < S_LEN && lane == 0) {
          asm volatile("cp.async.bulk.tensor.4d.global.shared::cta.bulk_group [%0, {%2, %3, %2, %2}], [%1];" ::"l"(&p.tmL[2]), "r"(sL + LQ), "r"(0), "r"(lr0 / 2) : "memory");
          asm volatile("cp.async.bulk.commit_group;" ::: "memory");
          asm volatile("cp.async.bulk.wait_group.read 0;" ::: "memory");
        }
        __syncwarp();
        if (lane < 12) mbar_arrive_cluster(bE + (4 + lane % 3) * 8, (lane / 3) & 1);
        if (lr0 < S_LEN && lane == 0) {
          asm volatile("cp.async.bulk.wait_group 0;" ::: "memory");
          asm volatile("fence.proxy.async.global;" ::: "memory");
          __threadfence();
          atomicAdd(&g_sync[F_OA + (lr0 >> 7)], 1u);
        }
      }
    }
    __syncwarp();
    cluster_sync();
  } else {
    reg_alloc<232>();
    const int wg = warp_g >> 2, warp = warp_g & 3, q = lane & 3;
    const bool sig = (lane == 0) && (warp < 2);
    {
      K1State st{0, 0, 0, nullptr, nullptr, 0, 0, 0};
      float acc[128];
      uint32_t pk[64];
      if (wg == 0) { TS(0, 0); TSC(0, 2); }
      uint32_t job = p.jobs[cl][0];
      k1_first(st, job, bAf, bBf);
      {
#pragma unroll 1
        for (int ji = 0; job & 3; ji++) {
          const uint32_t njob = p.jobs[cl][ji + 1];
          k1_tile(acc, pk, st, job, njob, sA, sB, bAf, bAe, bBf, bBe, bS, wg, warp, lane, rank);
          job = njob;
        }
      }
#pragma unroll
      for (int i = 0; i < 4; i++)
        mbar_arrive_cluster_if(bE + i * 8, warp & 1, sig);
      if (lr0 < S_LEN) bar_sync(3, 256 + 96);
      if (st.wsel == 3) {
#pragma unroll
        for (int G = 0; G < 16; G++) scale_q4(pk + G * 4);
      }
      auto flush = [&](int i, uint32_t dep) {
        asm volatile("{\n.reg .pred p;\nsetp.eq.u32 p, %5, 0;\n@p st.global.cs.v4.b32 [%0], {%1, %2, %3, %4};\n}" ::"l"(((i & 1) ? st.pp8 : st.pp) + (i / 2) * 32),
                     "r"(pk[i * 4]), "r"(pk[i * 4 + 1]), "r"(pk[i * 4 + 2]), "r"(pk[i * 4 + 3]), "r"(dep & blockIdx.y) : "memory");
      };
      if (wg == 0) { TS(0, 1); TSC(0, 3); }
      if (lr0 < S_LEN) {
        const float gate0 = __uint_as_float(lds32(sGate + (lane >> 2) * 8)), gate1 = __uint_as_float(lds32(sGate + (lane >> 2) * 8 + 4));
        local_attn(lr0, warp_g, sL, bL, bL2, lane, gate0, gate1, flush);
        k1_flag(st, lane, bS);
      } else {
        FLUSH();
      }
      bar_arrive(5, 256 + 32);
    }
    __syncwarp();
    uint32_t item, rot;
    {
      const int mybar = 1 + wg, otherbar = 2 - wg;
      const uint32_t never = blockIdx.y;
      float S[64], O[64];
      uint32_t P[32], Q[32];
      float m0 = 0.f, m1 = 0.f, l0 = 1.f, l1 = 1.f, gf0 = 0.f, gf1 = 0.f;
      uint32_t eoff = 0, prev_single = 0;
      Cursor c{0, 0};
      if (wg == 1) bar_arrive(1, 256);
      if (wg == 0) { TS(1, 0); TSC(1, 2); }
#pragma unroll 1
      for (int it = 0;; it++) {
        TB(0);
        const int hi = (int)(rank ^ (it & 1));
        Cursor cq = c, ck, cv, cs0, cs1;
        rot = k3_rot(c.s);
        c.next();
        ck = c; c.next();
        cs0 = ck; cs1 = ck; cv = ck;
        if (it > 0) { cv = c; c.next(); }
        if (!hi) {
          ck = c; c.next();
          cs1 = c; c.next();
        }
        mbar_wait(bF + cq.s * 8, cq.ph);
        TB(1);
        item = lds32(sItem + (it & 7) * 4);
        {
          const uint32_t qa = sbase + cq.s * 32768 + (wg * 64 + warp * 16 + (lane & 15)) * 128;
#pragma unroll
          for (int t = 0; t < 8; t++)
            ldsm_x4(Q[4 * t], Q[4 * t + 1], Q[4 * t + 2], Q[4 * t + 3], qa + (t >> 2) * 16384 + ((((t & 3) * 2 + (lane >> 4)) ^ (lane & 7)) << 4));
        }
        const uint32_t rdy = mbar_test(bF + ck.s * 8, ck.ph) & mbar_test(bF + cv.s * 8, cv.ph);
        l0 += __shfl_xor_sync(0xffffffffu, l0, 1);
        l1 += __shfl_xor_sync(0xffffffffu, l1, 1);
        l0 += __shfl_xor_sync(0xffffffffu, l0, 2);
        l1 += __shfl_xor_sync(0xffffffffu, l1, 2);
        if (item >= K2_END) {
          TURN_SYNC();
          TRC(2);
          wg_fence();
          ISSUE_PV(cq, prev_single);
          wg_commit();
          if (wg == 0) TURN_ARRIVE();
          asm volatile("" : "+f"(gf0), "+f"(gf1), "+f"(l0), "+f"(l1));
          const float f0 = __fdividef(1.f - gf0, l0), f1 = __fdividef(1.f - gf1, l1);
          bf16* optr = ptr_add(g_ctx, eoff);
          wg_wait<0>();
          fence_regs(O);
          mbar_arrive_cluster_if(bH, warp & 1, sig);
          STORE_O(0); STORE_O(1); STORE_O(2); STORE_O(3);
          __syncwarp();
          mbar_arrive_if(bS2, lane == 0);
          break;
        }
        if (!rdy) mbar_wait2(bF + ck.s * 8, ck.ph, bF + cv.s * 8, cv.ph);
        TB(2);
        TURN_SYNC();
        TB(3);
        TRC(1);
        if (it > 0) {
          wg_fence();
          ISSUE_PV(cv, prev_single);
          wg_commit();
        } else {
          wg_fence();
          wg_commit();
        }
        wg_fence();
        ISSUE_QK(ck);
        wg_commit();
        TURN_ARRIVE();
        RELEASE(cq);
        TB(4);
        asm volatile("" : "+f"(gf0), "+f"(gf1), "+f"(l0), "+f"(l1));
        const float f0 = __fdividef(1.f - gf0, l0), f1 = __fdividef(1.f - gf1, l1);
        wg_wait<1>();
        fence_regs(O);
        fence_regs(P);
        TB(5);
        if (it > 0) {
          RELEASE(cv);
          bf16* optr = ptr_add(g_ctx, eoff);
          STORE_O(0); STORE_O(1); STORE_O(2); STORE_O(3);
          __syncwarp();
          mbar_arrive_if(bS2, lane == 0);
        }
        TB(6);
        {
          const int row = (2 * (item & 7) + hi) * 128 + wg * 64 + warp * 16 + (lane >> 2);
          eoff = (row * KCAT + (item >> 3) * 128 + q * 8) * 2;
          const float* gp = ptr_add(g_gate, row * 4);
          asm volatile("ld.global.f32 %0, [%1];" : "=f"(gf0) : "l"(gp));
          asm volatile("ld.global.f32 %0, [%1];" : "=f"(gf1) : "l"(gp + 8));
          if (!hi) {
            mbar_wait2(bF + cs0.s * 8, cs0.ph, bF + cs1.s * 8, cs1.ph);
            RELEASE(cs0);
            RELEASE(cs1);
          }
        }
        TB(7);
        wg_wait<0>();
        fence_regs(S);
        TB(8);
        RELEASE(ck);
        const int nblk = 2 * (item & 7) + 1 + hi;
        prev_single = (nblk == 1);
        float s0 = 0.f, s1 = 0.f;
        l0 = 0.f; l1 = 0.f;
        m0 = 0.f; m1 = 0.f;
        bool shifted = false;
        {
          const int d = warp * 16 + (lane >> 2) - 2 * q;
          if (wg == 0) {
#pragma unroll
            for (int jj = 0; jj < 8; jj++) MASK(jj, jj);
            EXPB(0); EXPB(1); EXPB(2); EXPB(3);
#pragma unroll
            for (int i = 32; i < 64; i++) S[i] = -INFINITY;
#pragma unroll
            for (int i = 16; i < 32; i++) P[i] = 0;
          } else {
#pragma unroll
            for (int jj = 0; jj < 8; jj++) MASK(jj + 8, jj);
            EXPB(0); EXPB(1); EXPB(2); EXPB(3); EXPB(4); EXPB(5); EXPB(6); EXPB(7);
          }
        }
        float chk = (q == 0 && !(fminf(s0, s1) >= SPEC_LO)) ? INFINITY : s0 + s1;
        fence_regs(P);
        TB(9);
#pragma unroll 1
        for (int n = 1;; n++) {
          if (__any_sync(0xffffffffu, !(chk <= SPEC_HI))) {
            float mx0 = fmaxf(S[0], S[1]), mx1 = fmaxf(S[2], S[3]);
#pragma unroll
            for (int jj = 1; jj < 16; jj++) {
              mx0 = fmaxf(mx0, fmaxf(S[jj * 4 + 0], S[jj * 4 + 1]));
              mx1 = fmaxf(mx1, fmaxf(S[jj * 4 + 2], S[jj * 4 + 3]));
            }
            mx0 = fmaxf(mx0, __shfl_xor_sync(0xffffffffu, mx0, 1));
            mx1 = fmaxf(mx1, __shfl_xor_sync(0xffffffffu, mx1, 1));
            mx0 = fmaxf(mx0, __shfl_xor_sync(0xffffffffu, mx0, 2));
            mx1 = fmaxf(mx1, __shfl_xor_sync(0xffffffffu, mx1, 2));
            const float lo = (n == 1) ? -INFINITY : 0.f;
            mx0 = fmaxf(mx0, lo);
            mx1 = fmaxf(mx1, lo);
            m0 += mx0; m1 += mx1;
            shifted = true;
            const float sc0 = ex2(-fmaxf(mx0, 0.f)), sc1 = ex2(-fmaxf(mx1, 0.f));
            l0 *= sc0; l1 *= sc1;
            s0 = 0.f; s1 = 0.f;
#pragma unroll
            for (int jj = 0; jj < 16; jj++) {
              const float e0 = ex2(S[jj * 4 + 0] - mx0), e1 = ex2(S[jj * 4 + 1] - mx0), e2 = ex2(S[jj * 4 + 2] - mx1), e3 = ex2(S[jj * 4 + 3] - mx1);
              s0 += e0 + e1;
              s1 += e2 + e3;
              P[jj * 2 + 0] = pack_bf16(e0, e1);
              P[jj * 2 + 1] = pack_bf16(e2, e3);
              O[jj * 4 + 0] *= sc0;
              O[jj * 4 + 1] *= sc0;
              O[jj * 4 + 2] *= sc1;
              O[jj * 4 + 3] *= sc1;
            }
          }
          l0 += s0;
          l1 += s1;
          if (n >= nblk) break;
          ck = c; c.next();
          cv = c; c.next();
          mbar_wait(bF + ck.s * 8, ck.ph);
          mbar_wait(bF + cv.s * 8, cv.ph);
          TURN_SYNC();
          TRC(0);
          wg_fence();
          ISSUE_QK(ck);
          wg_commit();
          {
            const uint64_t dv = make_desc(sbase + cv.s * 32768, 16384, 1024, 1);
#pragma unroll
            for (int t = 0; t < 8; t++) {
              wgmma_rs_n128<1, 0>(O, P[4 * t], P[4 * t + 1], P[4 * t + 2], P[4 * t + 3], dv + (uint64_t)(t * 128), (t > 0) ? 1 : (n != 1));
              if ((PVM >> t) & 1) wg_commit();
            }
          }
          TURN_ARRIVE();
          s0 = 0.f; s1 = 0.f;
          wg_wait<__builtin_popcount(PVM)>();
          fence_regs(S);
          RELEASE(ck);
          if (shifted) {
#pragma unroll
            for (int i = 0; i < 64; i++) S[i] -= (i & 2) ? m1 : m0;
          }
          wg_wait<__builtin_popcount(PVM) - 1>();
          EXPC(0); EXPC(1); EXPC(2); EXPC(3); EXPC(4); EXPC(5); EXPC(6); EXPC(7);
          chk = s0 + s1;
        }
      }
      TRC(3);
      if (wg == 1) { TS(1, 1); TSC(1, 3); }
    }
    __syncwarp();
    const uint32_t unit = item & 255;
    if (unit < 64) {
      const int mblk = (7 - (p.unit[unit][0] >> 1)) * 2 + rank, nhalf = p.unit[unit][0] & 1, ks = p.unit[unit][1];
      const int k0 = 0, k1 = p.unit[unit][2];
      float acc[144];
      uint32_t s = rot, ph = 0, prev = 0;
      if (wg == 0) { TS(2, 0); TSC(2, 2); }
      uint32_t fa[16], fb[16];
      const uint32_t aoff = (wg * 64 + warp * 16 + (lane & 15)) * 128 + (((lane >> 4) ^ (lane & 7)) << 4);
#define C_LOAD(F)                                                                                              \
  do {                                                                                                         \
    mbar_wait(b3F + s * 8, ph);                                                                                \
    _Pragma("unroll") for (int t = 0; t < 4; t++)                                                              \
        ldsm_x4(F[4 * t], F[4 * t + 1], F[4 * t + 2], F[4 * t + 3], sbase + s * K3_STAGE + (aoff ^ (t * 32))); \
  } while (0)
#define C_STEP(F, G)                                                                                           \
  {                                                                                                            \
    const uint32_t st = sbase + s * K3_STAGE;                                                                  \
    const uint64_t db = make_desc(st + 16384, 4096, 1024, 1), dt = make_desc(st + 49152, 16, 512, 2);          \
    wg_fence();                                                                                                \
    _Pragma("unroll") for (int t = 0; t < 4; t++) {                                                            \
      const int sd = (t > 0) || (k > k0);                                                                      \
      wgmma_rs_n256<1, 0>(acc, F[4 * t], F[4 * t + 1], F[4 * t + 2], F[4 * t + 3], db + (uint64_t)((t >> 1) * 1024 + (t & 1) * 128), sd); \
      wgmma_rs_n32<1, 128>(acc, F[4 * t], F[4 * t + 1], F[4 * t + 2], F[4 * t + 3], dt + (uint64_t)(t * 64), sd); \
    }                                                                                                          \
    wg_commit();                                                                                               \
    wg_wait<1>();                                                                                              \
    fence_regs(G);                                                                                             \
    mbar_arrive_cluster_if(b3E + prev * 8, warp & 1, sig && k > k0);                                           \
    prev = s;                                                                                                  \
    s = (s + 1) & 3;                                                                                           \
    if (s == rot) ph ^= 1;                                                                                     \
    TCK(k + 1);                                                                                                \
    if (++k == k1) break;                                                                                      \
    C_LOAD(G);                                                                                                 \
  }
      TCK(0);
      C_LOAD(fa);
#pragma unroll
      for (int i = 0; i < 16; i++) fb[i] = 0;
#pragma unroll 1
      for (int k = k0;;) {
        C_STEP(fa, fb)
        C_STEP(fb, fa)
      }
      wg_wait<0>();
      fence_regs(acc);
      cluster_arrive();
      if (wg == 0) TS(2, 4);
      const int tile = mblk * 2 + nhalf;
      uint4* wp = g_part + (size_t)((tile * 4 + ks) * 4) * 5 * 256 + tid;
      const uint32_t sown = sbase + wg * 8192 + (tid & 127) * 16;
#pragma unroll
      for (int d = 0; d < 4; d++) {
        if (d != ks) {
#pragma unroll
          for (int i = 0; i < 4; i++)
            __stcg(wp + (d * 5 + i) * 256,
                   make_uint4(pack_bf16(acc[d * 32 + i * 8], acc[d * 32 + i * 8 + 1]), pack_bf16(acc[d * 32 + i * 8 + 2], acc[d * 32 + i * 8 + 3]),
                              pack_bf16(acc[d * 32 + i * 8 + 4], acc[d * 32 + i * 8 + 5]), pack_bf16(acc[d * 32 + i * 8 + 6], acc[d * 32 + i * 8 + 7])));
          __stcg(reinterpret_cast<uint2*>(wp - tid + (d * 5 + 4) * 256) + tid,
                 make_uint2(pack_bf16(acc[128 + d * 4], acc[128 + d * 4 + 1]), pack_bf16(acc[128 + d * 4 + 2], acc[128 + d * 4 + 3])));
        } else {
#pragma unroll
          for (int i = 0; i < 9; i++) {
            const int o = (i < 8) ? d * 32 + i * 4 : 128 + d * 4;
            asm volatile("st.shared.v4.f32 [%0], {%1, %2, %3, %4};" ::"r"(sown + (i >> 2) * K3_STAGE + (i & 3) * 2048), "f"(acc[o]), "f"(acc[o + 1]), "f"(acc[o + 2]), "f"(acc[o + 3]) : "memory");
          }
        }
      }
      __threadfence();
      __syncwarp();
      if (wg == 0) TS(2, 5);
      if (lane == 0) {
        unsigned int* cnt = &g_sync[F_XCH + tile * 8 + warp_g];
        const uint32_t xtarget = lds32(sGate + 64) * 4 + 4;
        atomicAdd(cnt, 1u);
        uint32_t v, spins = 0;
        do {
          asm volatile("ld.acquire.gpu.global.u32 %0, [%1];" : "=r"(v) : "l"(cnt) : "memory");
        } while ((int)(v - xtarget) < 0 && ++spins < (1u << 24));
      }
      __syncwarp();
      if (wg == 0) TS(2, 6);
      float r[36];
#pragma unroll
      for (int i = 0; i < 9; i++)
        asm volatile("ld.shared.v4.f32 {%0, %1, %2, %3}, [%4];" : "=f"(r[i * 4]), "=f"(r[i * 4 + 1]), "=f"(r[i * 4 + 2]), "=f"(r[i * 4 + 3])
                     : "r"(sown + (i >> 2) * K3_STAGE + (i & 3) * 2048) : "memory");
#pragma unroll
      for (int sI = 1; sI < 4; sI++) {
        const int src = (ks + sI) & 3;
        const uint4* rp = g_part + (size_t)(((tile * 4 + src) * 4) + ks) * 5 * 256;
#pragma unroll
        for (int i = 0; i < 4; i++) {
          const uint4 v = __ldcg(rp + i * 256 + tid);
          r[i * 8] += bf_lo(v.x); r[i * 8 + 1] += bf_hi(v.x); r[i * 8 + 2] += bf_lo(v.y); r[i * 8 + 3] += bf_hi(v.y);
          r[i * 8 + 4] += bf_lo(v.z); r[i * 8 + 5] += bf_hi(v.z); r[i * 8 + 6] += bf_lo(v.w); r[i * 8 + 7] += bf_hi(v.w);
        }
        const uint2 v = __ldcg(reinterpret_cast<const uint2*>(rp + 4 * 256) + tid);
        r[32] += bf_lo(v.x); r[33] += bf_hi(v.x); r[34] += bf_lo(v.y); r[35] += bf_hi(v.y);
      }
      const int row = mblk * 128 + wg * 64 + warp * 16 + (lane >> 2);
      bf16* o0 = out + (size_t)row * DM + nhalf * 256 + ks * 64 + 8 * q;
#pragma unroll
      for (int G = 0; G < 2; G++) {
        uint32_t a0 = pack_bf16(r[G * 16], r[G * 16 + 1]), a1 = pack_bf16(r[G * 16 + 4], r[G * 16 + 5]);
        uint32_t a2 = pack_bf16(r[G * 16 + 8], r[G * 16 + 9]), a3 = pack_bf16(r[G * 16 + 12], r[G * 16 + 13]);
        uint32_t b0 = pack_bf16(r[G * 16 + 2], r[G * 16 + 3]), b1 = pack_bf16(r[G * 16 + 6], r[G * 16 + 7]);
        uint32_t b2 = pack_bf16(r[G * 16 + 10], r[G * 16 + 11]), b3 = pack_bf16(r[G * 16 + 14], r[G * 16 + 15]);
        quad_transpose(a0, a1, a2, a3, q);
        quad_transpose(b0, b1, b2, b3, q);
        st_v4(o0 + G * 32, a0, a1, a2, a3);
        st_v4(o0 + 8 * DM + G * 32, b0, b1, b2, b3);
      }
      {
        uint32_t t0 = pack_bf16(r[32], r[33]), t1 = pack_bf16(r[34], r[35]), t2 = 0, t3 = 0;
        quad_transpose(t0, t1, t2, t3, q);
        if (q < 2) st_v4(out + (size_t)(row + q * 8) * DM + 512 + nhalf * 32 + ks * 8, t0, t1, t2, t3);
      }
    } else {
      cluster_arrive();
    }
    if (wg == 0) { TS(2, 1); TSC(2, 3); }
    cluster_wait();
  }
}

typedef CUresult (*EncFn)(CUtensorMap*, CUtensorMapDataType, cuuint32_t, void*, const cuuint64_t*, const cuuint64_t*, const cuuint32_t*,
                          const cuuint32_t*, CUtensorMapInterleave, CUtensorMapSwizzle, CUtensorMapL2promotion, CUtensorMapFloatOOBfill);

static void enc2d(EncFn enc, CUtensorMap* m, const void* ptr, uint64_t cols, uint64_t rows, uint32_t bc, uint32_t br,
                  CUtensorMapSwizzle sw = CU_TENSOR_MAP_SWIZZLE_128B) {
  cuuint64_t gd[2] = {cols, rows}, gs[1] = {cols * 2};
  cuuint32_t bx[2] = {bc, br}, es[2] = {1, 1};
  enc(m, CU_TENSOR_MAP_DATA_TYPE_BFLOAT16, 2, const_cast<void*>(ptr), gd, gs, bx, es, CU_TENSOR_MAP_INTERLEAVE_NONE, sw,
      CU_TENSOR_MAP_L2_PROMOTION_L2_256B, CU_TENSOR_MAP_FLOAT_OOB_FILL_NONE);
}
static void enc3d(EncFn enc, CUtensorMap* m, const void* ptr, uint64_t cols, uint64_t rows, uint32_t br, uint32_t bch) {
  cuuint64_t gd[3] = {64, rows, cols / 64}, gs[2] = {cols * 2, 128};
  cuuint32_t bx[3] = {64, br, bch}, es[3] = {1, 1, 1};
  enc(m, CU_TENSOR_MAP_DATA_TYPE_BFLOAT16, 3, const_cast<void*>(ptr), gd, gs, bx, es, CU_TENSOR_MAP_INTERLEAVE_NONE,
      CU_TENSOR_MAP_SWIZZLE_128B, CU_TENSOR_MAP_L2_PROMOTION_L2_256B, CU_TENSOR_MAP_FLOAT_OOB_FILL_NONE);
}

static int g_sched[10] = {11, 10, 7, 4, 4, 4, 6, 8, 6, 24};
static void build_k1_jobs(Params& p) {
  int cnt[NCLUSTER];
  for (int c = 0; c < NCLUSTER; c++) {
    cnt[c] = 0;
    for (int i = 0; i <= K1_MAXJOBS; i++) p.jobs[c][i] = 0;
  }
  auto add = [&](int c, int nch, int a_sel, int mp, int w_sel, int chunk0) {
    p.jobs[c][cnt[c]++] = (uint16_t)((nch - 1) | (a_sel << 2) | (mp << 3) | (w_sel << 6) | (chunk0 << 8));
  };
  const char* plan = "ccccccccccc cccccccccc ccccccc cccc xxxx xxxx xxxxxx xxxxxxxx";
  int TIE = 0;
  int XA = 0;
  const char* cur[8];
  int tend[8] = {};
  for (int g = 0; g < 8; g++) {
    cur[g] = plan;
    while (*plan == 'c' || *plan == 'x') plan++;
    if (*plan) plan++;
  }
  int kc = 0, kx = 0;
  for (;;) {
    int b = -1, bt = 0;
    for (int g = 0; g < 8; g++) {
      const int t = tend[g] + (*cur[g] == 'x' ? 94 : 85);
      if ((*cur[g] == 'c' || *cur[g] == 'x') && (b < 0 || t < bt || (TIE && t == bt))) { b = g; bt = t; }
    }
    if (b < 0) break;
    const int a = kx - XA;
    for (int mp = 0; mp < 8; mp++) {
      if (*cur[b] == 'c') add(b * 8 + mp, 4, 0, mp, kc & 1, (kc >> 1) * 4);
      else if (a >= 0 && a < 7) add(b * 8 + mp, a == 0 ? 3 : 4, 1, mp, 2, a == 0 ? 24 : (a - 1) * 4);
      else add(b * 8 + mp, 4, 1, mp, 3, (a < 0 ? kx : kx - 7) * 4);
    }
    if (*cur[b] == 'c') kc++; else kx++;
    cur[b]++;
    tend[b] = bt;
  }
  for (int mp = 0; mp < 8; mp++) add(64 + mp / 4, 4, 1, mp, 3, 15 * 4);
  for (int cc = 0; cc < NCLUSTER; cc++)
    for (int i = 0; i < cnt[cc]; i++) {
      const int key = p.jobs[cc][i] & 0x3C;
      if (i == 0 || (p.jobs[cc][i - 1] & 0x3C) != key) p.jobs[cc][i] |= (1 << 14);
      if (i == cnt[cc] - 1 || (p.jobs[cc][i + 1] & 0x3C) != key) p.jobs[cc][i] |= (1 << 15);
    }
}

static void build_k2_items(Params& p) {
  int n = 0;
  const int SCHED_N1 = g_sched[8], SCHED_N2 = g_sched[9];
  int N0 = 2, J0 = 2;
  for (int j = 7; j >= J0; j--)
    for (int h = 0; h < N0; h++) p.order[n++] = (uint8_t)(h * 8 + j);
  for (int j = 7; j >= 0; j--)
    for (int h = 0; h < SCHED_N1; h++)
      if (!(h < N0 && j >= J0)) p.order[n++] = (uint8_t)(h * 8 + j);
  for (int j = 7; j >= 4; j--)
    for (int h = SCHED_N1; h < SCHED_N2; h++) p.order[n++] = (uint8_t)(h * 8 + j);
  for (int j = 7; j >= 0; j--)
    for (int h = SCHED_N1; h < 32; h++)
      if (!(h < SCHED_N2 && j >= 4)) p.order[n++] = (uint8_t)(h * 8 + j);
}

static void build_k3_units(Params& p) {
  float slope = 0.045f;
  int NE = 25;
  for (int t = 0; t < 16; t++) {
    const int u[4] = {t, 31 - t, 32 + t, 63 - t};
    float acc = 0.f;
    int k0 = 0, l0 = NE;
    for (int i = 0; i < 4; i++) {
      acc += 18.25f + slope * (31.5f - u[i]);
      const int k1 = (i == 3) ? 73 : (int)(acc + 0.5f);
      const int e0 = NE * i / 4, e1 = NE * (i + 1) / 4;
      uint8_t* w = p.unit[u[i]];
      w[0] = (uint8_t)t; w[1] = (uint8_t)i; w[2] = (uint8_t)(k1 - k0); w[3] = (uint8_t)e0; w[4] = (uint8_t)(e1 - e0); w[5] = (uint8_t)(l0 - e1);
      l0 += (k1 - k0) - (e1 - e0);
      k0 = k1;
    }
  }
}

extern "C" void kernel_launch(void* const* d_in, const int* in_sizes, int n_in, void* d_out, int out_size) {
  const bf16* x = (const bf16*)d_in[0];
  const bf16* wqkv = (const bf16*)d_in[1];
  const bf16* wo = (const bf16*)d_in[2];
  const bf16* ckv = (const bf16*)d_in[4];
  const bf16* w_q = (const bf16*)d_in[5];
  const bf16* w_uk = (const bf16*)d_in[6];
  const bf16* w_uv = (const bf16*)d_in[7];
  const bf16* w_o = (const bf16*)d_in[8];
  const bf16* gate_w = (const bf16*)d_in[9];

  EncFn enc = nullptr;
  cudaDriverEntryPointQueryResult qr;
  cudaGetDriverEntryPoint("cuTensorMapEncodeTiled", (void**)&enc, cudaEnableDefault, &qr);
  void *pK, *pV, *pCtx, *pQA;
  cudaGetSymbolAddress(&pQA, g_QKVA);
  cudaGetSymbolAddress(&pK, g_K);
  cudaGetSymbolAddress(&pV, g_V);
  cudaGetSymbolAddress(&pCtx, g_ctx);

  static Params p;
  enc2d(enc, &p.tmA[0], ckv, DC, S_LEN, 64, 128);
  enc2d(enc, &p.tmA[1], x, DM, S_LEN, 64, 128);
  enc3d(enc, &p.tmW[0], w_uk, HDIM, DC, 16, 4);
  enc3d(enc, &p.tmW[1], w_uv, HDIM, DC, 16, 4);
  enc3d(enc, &p.tmW[2], wqkv, NQKVA, DM, 16, 4);
  enc3d(enc, &p.tmW[3], w_q, HDIM, DM, 16, 4);
  build_k1_jobs(p);
  enc2d(enc, &p.tmK, pK, HDIM, S_LEN, 64, 128);
  enc2d(enc, &p.tmV, pV, HDIM, S_LEN, 64, 128);
  build_k2_items(p);
  build_k3_units(p);
  for (int i = 0; i < 3; i++) {
    const cuuint64_t ld = (i < 2 ? NQKVA : KCAT) * 2, nch = (i < 2) ? 27 : 9;
    cuuint64_t gd[4] = {64, S_LEN / 2, i ? 2 : nch, i ? nch : 2}, gs[3] = {2 * ld, i ? ld : 128, i ? 128 : ld};
    cuuint32_t bx[4] = {64, i ? 8u : 16u, i ? 2u : 9u, i ? 9u : 2u}, es[4] = {1, 1, 1, 1};
    enc(&p.tmL[i], CU_TENSOR_MAP_DATA_TYPE_BFLOAT16, 4, (i < 2) ? pQA : (void*)((bf16*)pCtx + HDIM), gd, gs, bx, es, CU_TENSOR_MAP_INTERLEAVE_NONE,
        CU_TENSOR_MAP_SWIZZLE_128B, CU_TENSOR_MAP_L2_PROMOTION_L2_256B, CU_TENSOR_MAP_FLOAT_OOB_FILL_NONE);
  }
  enc2d(enc, &p.tmC, pCtx, KCAT, S_LEN, 64, 128);
  enc3d(enc, &p.tmO[0], w_o, DM, HDIM, 32, 4);
  enc3d(enc, &p.tmO[1], wo, DM, DM, 32, 4);
  enc2d(enc, &p.tmOt[0], w_o, DM, HDIM, 32, 32, CU_TENSOR_MAP_SWIZZLE_64B);
  enc2d(enc, &p.tmOt[1], wo, DM, DM, 32, 32, CU_TENSOR_MAP_SWIZZLE_64B);

  cudaFuncSetAttribute(fused_kernel, cudaFuncAttributeMaxDynamicSharedMemorySize, SMEM_BYTES);
  fused_kernel<<<NCLUSTER * 2, 384, SMEM_BYTES>>>(p, x, gate_w, (bf16*)d_out);
}
```

```cpp
#include <cuda_runtime.h>
#include <cuda_bf16.h>
#include <cuda.h>
#include <stdint.h>

typedef __nv_bfloat16 bf16;

constexpr int S_LEN = 2048, DM = 576, DC = 512, HDIM = 4096, NQKVA = 1728, KCAT = 4672;
constexpr int NCLUSTER = 66;

__device__ __align__(1024) bf16 g_K[S_LEN * HDIM];
__device__ __align__(1024) bf16 g_V[S_LEN * HDIM];
__device__ __align__(1024) bf16 g_QKVA[S_LEN * NQKVA + 64];
__device__ __align__(1024) bf16 g_ctx[S_LEN * KCAT];
__device__ float g_gate[S_LEN];
__device__ __align__(1024) uint4 g_part[32 * 4 * 4 * 5 * 256];
__device__ __align__(16) unsigned int g_sync[400];
constexpr int F_QKVA = 0, F_HP = 16, F_CTX = 32, F_OA = 48, F_GATE = 96, F_TICK = 97, F_DONE = 98, F_XCH = 128, F_EPOCH = 384;

__device__ __forceinline__ uint32_t smem_u32(const void* p) { return (uint32_t)__cvta_generic_to_shared(p); }
__device__ __forceinline__ void mbar_init(uint32_t a, uint32_t c) {
  asm volatile("mbarrier.init.shared::cta.b64 [%0], %1;" ::"r"(a), "r"(c));
}
__device__ __forceinline__ void mbar_expect(uint32_t a, uint32_t b) {
  asm volatile("mbarrier.arrive.expect_tx.shared::cta.b64 _, [%0], %1;" ::"r"(a), "r"(b) : "memory");
}
#define TS(k, i)
#define TSC(k, i)
#define TSM(k)
#define BSEG(i)
#define TB(k)
#define TRC(fl)
#define TCK(i)
#define SPIN_LIMIT "4194304"
__device__ __forceinline__ void mbar_wait(uint32_t a, uint32_t parity) {
  asm volatile(
      "{\n.reg .pred p;\n.reg .u32 n;\n"
      "mbarrier.try_wait.parity.shared::cta.b64 p, [%0], %1;\n"
      "@p bra DONE;\n"
      "mov.u32 n, 0;\n"
      "LOOP:\n"
      "mbarrier.try_wait.parity.shared::cta.b64 p, [%0], %1;\n"
      "@p bra DONE;\n"
      "add.u32 n, n, 1;\n"
      "setp.lt.u32 p, n, " SPIN_LIMIT ";\n"
      "@p bra LOOP;\n"
      "DONE:\n}" ::"r"(a), "r"(parity) : "memory");
}
template <int NS>
__device__ __forceinline__ void mbar_wait_ns(uint32_t a, uint32_t parity) {
  asm volatile(
      "{\n.reg .pred p;\n.reg .u32 n;\n"
      "mov.u32 n, 0;\n"
      "LOOP:\n"
      "mbarrier.try_wait.parity.shared::cta.b64 p, [%0], %1, %2;\n"
      "@p bra DONE;\n"
      "add.u32 n, n, 1;\n"
      "setp.lt.u32 p, n, " SPIN_LIMIT ";\n"
      "@p bra LOOP;\n"
      "DONE:\n}" ::"r"(a), "r"(parity), "n"(NS) : "memory");
}
__device__ __forceinline__ void mbar_wait2(uint32_t a, uint32_t pa, uint32_t b, uint32_t pb) {
  asm volatile(
      "{\n.reg .pred p, q;\n.reg .u32 n;\n"
      "mov.u32 n, 0;\n"
      "LOOP:\n"
      "mbarrier.try_wait.parity.shared::cta.b64 p, [%0], %1;\n"
      "mbarrier.try_wait.parity.shared::cta.b64 q, [%2], %3;\n"
      "add.u32 n, n, 1;\n"
      "and.pred p, p, q;\n"
      "setp.lt.and.u32 p, n, " SPIN_LIMIT ", !p;\n"
      "@p bra LOOP;\n"
      "}" ::"r"(a), "r"(pa), "r"(b), "r"(pb) : "memory");
}
__device__ __forceinline__ uint32_t mbar_test(uint32_t a, uint32_t parity) {
  uint32_t r;
  asm volatile("{\n.reg .pred p;\nmbarrier.test_wait.parity.shared::cta.b64 p, [%1], %2;\nselp.u32 %0, 1, 0, p;\n}" : "=r"(r) : "r"(a), "r"(parity) : "memory");
  return r;
}
__device__ __forceinline__ void mbar_arrive(uint32_t a) {
  asm volatile("mbarrier.arrive.shared::cta.b64 _, [%0];" ::"r"(a) : "memory");
}
__device__ __forceinline__ void mbar_arrive_cluster(uint32_t a, uint32_t cta) {
  asm volatile("{\n.reg .b32 r;\nmapa.shared::cluster.u32 r, %0, %1;\nmbarrier.arrive.shared::cluster.b64 _, [r];\n}" ::"r"(a),
               "r"(cta) : "memory");
}
__device__ __forceinline__ void mbar_arrive_cluster_if(uint32_t a, uint32_t cta, bool pred) {
  asm volatile("{\n.reg .b32 r;\n.reg .pred p;\nsetp.ne.u32 p, %2, 0;\nmapa.shared::cluster.u32 r, %0, %1;\n@p mbarrier.arrive.shared::cluster.b64 _, [r];\n}" ::"r"(a),
               "r"(cta), "r"((uint32_t)pred) : "memory");
}
__device__ __forceinline__ void anchor(float v, uint32_t pred) {
  asm volatile("{\n.reg .pred p;\nsetp.ne.u32 p, %1, 0;\n@p st.shared.f32 [%1], %0;\n}" ::"f"(v), "r"(pred) : "memory");
}
__device__ __forceinline__ void mbar_arrive_if(uint32_t a, bool pred) {
  asm volatile("{\n.reg .pred p;\nsetp.ne.u32 p, %1, 0;\n@p mbarrier.arrive.shared::cta.b64 _, [%0];\n}" ::"r"(a), "r"((uint32_t)pred) : "memory");
}
__device__ __forceinline__ void tma2d(uint32_t dst, const CUtensorMap* m, uint32_t bar, int c0, int c1) {
  asm volatile("cp.async.bulk.tensor.2d.shared::cluster.global.mbarrier::complete_tx::bytes [%0], [%1, {%3, %4}], [%2];" ::"r"(dst),
               "l"(m), "r"(bar), "r"(c0), "r"(c1) : "memory");
}
__device__ __forceinline__ void tma2d_mc(uint32_t dst, const CUtensorMap* m, uint32_t bar, int c0, int c1, uint16_t mask) {
  asm volatile(
      "cp.async.bulk.tensor.2d.shared::cluster.global.mbarrier::complete_tx::bytes.multicast::cluster [%0], [%1, {%3, %4}], [%2], %5;" ::"r"(dst),
      "l"(m), "r"(bar), "r"(c0), "r"(c1), "h"(mask) : "memory");
}
__device__ __forceinline__ void tma3d_mc(uint32_t dst, const CUtensorMap* m, uint32_t bar, int c0, int c1, int c2, uint16_t mask) {
  asm volatile(
      "cp.async.bulk.tensor.3d.shared::cluster.global.mbarrier::complete_tx::bytes.multicast::cluster [%0], [%1, {%3, %4, %5}], [%2], %6;" ::"r"(dst),
      "l"(m), "r"(bar), "r"(c0), "r"(c1), "r"(c2), "h"(mask) : "memory");
}
__device__ __forceinline__ void tma3d(uint32_t dst, const CUtensorMap* m, uint32_t bar, int c0, int c1, int c2) {
  asm volatile(
      "cp.async.bulk.tensor.3d.shared::cluster.global.mbarrier::complete_tx::bytes [%0], [%1, {%3, %4, %5}], [%2];" ::"r"(dst),
      "l"(m), "r"(bar), "r"(c0), "r"(c1), "r"(c2) : "memory");
}
__device__ __forceinline__ void tma_pf2d(const CUtensorMap* m, int c0, int c1) {
  asm volatile("cp.async.bulk.prefetch.tensor.2d.L2.global [%0, {%1, %2}];" ::"l"(m), "r"(c0), "r"(c1) : "memory");
}
__device__ __forceinline__ void tma_pf3d(const CUtensorMap* m, int c0, int c1, int c2) {
  asm volatile("cp.async.bulk.prefetch.tensor.3d.L2.global [%0, {%1, %2, %3}];" ::"l"(m), "r"(c0), "r"(c1), "r"(c2) : "memory");
}
__device__ __forceinline__ void prefetch_tmap(const CUtensorMap* m) {
  asm volatile("prefetch.tensormap [%0];" ::"l"(m) : "memory");
}
__device__ __forceinline__ void cluster_arrive() { asm volatile("barrier.cluster.arrive.relaxed.aligned;" ::: "memory"); }
__device__ __forceinline__ void cluster_wait() { asm volatile("barrier.cluster.wait.aligned;" ::: "memory"); }
__device__ __forceinline__ void cluster_sync() {
  cluster_arrive();
  cluster_wait();
}
__device__ __forceinline__ uint32_t cluster_rank() {
  uint32_t r;
  asm volatile("mov.u32 %0, %%cluster_ctarank;" : "=r"(r));
  return r;
}
__device__ __forceinline__ bool elect_one() {
  uint32_t p;
  asm volatile("{\n.reg .pred q;\nelect.sync _|q, 0xffffffff;\nselp.u32 %0, 1, 0, q;\n}" : "=r"(p));
  return p;
}
__device__ __forceinline__ void ldsm_x4(uint32_t& r0, uint32_t& r1, uint32_t& r2, uint32_t& r3, uint32_t addr) {
  asm volatile("ldmatrix.sync.aligned.m8n8.x4.shared.b16 {%0, %1, %2, %3}, [%4];" : "=r"(r0), "=r"(r1), "=r"(r2), "=r"(r3) : "r"(addr) : "memory");
}
__device__ __forceinline__ void wg_fence() { asm volatile("wgmma.fence.sync.aligned;" ::: "memory"); }
__device__ __forceinline__ void wg_commit() { asm volatile("wgmma.commit_group.sync.aligned;" ::: "memory"); }
template <int N>
__device__ __forceinline__ void wg_wait() { asm volatile("wgmma.wait_group.sync.aligned %0;" ::"n"(N) : "memory"); }
template <int N>
__device__ __forceinline__ void reg_alloc() { asm volatile("setmaxnreg.inc.sync.aligned.u32 %0;" ::"n"(N)); }
template <int N>
__device__ __forceinline__ void reg_dealloc() { asm volatile("setmaxnreg.dec.sync.aligned.u32 %0;" ::"n"(N)); }
__device__ __forceinline__ void bar_sync(int id, int n) { asm volatile("bar.sync %0, %1;" ::"r"(id), "r"(n) : "memory"); }
__device__ __forceinline__ void bar_arrive(int id, int n) { asm volatile("bar.arrive %0, %1;" ::"r"(id), "r"(n) : "memory"); }
template <int NT>
__device__ __forceinline__ void fence_regs(float (&d)[NT]) {
#pragma unroll
  for (int i = 0; i < NT; i++) asm volatile("" : "+f"(d[i])::"memory");
}
template <int NT>
__device__ __forceinline__ void fence_regs(uint32_t (&d)[NT]) {
#pragma unroll
  for (int i = 0; i < NT; i++) asm volatile("" : "+r"(d[i])::"memory");
}
__device__ __forceinline__ uint64_t make_desc(uint32_t saddr, uint32_t lbo, uint32_t sbo, uint32_t layout) {
  return (uint64_t)((saddr & 0x3FFFF) >> 4) | ((uint64_t)(lbo >> 4) << 16) | ((uint64_t)(sbo >> 4) << 32) | ((uint64_t)layout << 62);
}
__device__ __forceinline__ uint32_t pack_bf16(float lo, float hi) {
  uint32_t r;
  asm("cvt.rn.bf16x2.f32 %0, %1, %2;" : "=r"(r) : "f"(hi), "f"(lo));
  return r;
}
__device__ __forceinline__ float ex2(float x) {
  float r;
  asm("ex2.approx.ftz.f32 %0, %1;" : "=f"(r) : "f"(x));
  return r;
}
__device__ __forceinline__ void st_v4(void* p, uint32_t a, uint32_t b, uint32_t c, uint32_t d) {
#define ST_MOD ".cs"
  asm volatile("st.global" ST_MOD ".v4.b32 [%0], {%1, %2, %3, %4};" ::"l"(p), "r"(a), "r"(b), "r"(c), "r"(d) : "memory");
}
#define STA_MOD ".cs"
__device__ __forceinline__ void st_v4a(void* p, uint32_t a, uint32_t b, uint32_t c, uint32_t d) {
  asm volatile("st.global" STA_MOD ".v4.b32 [%0], {%1, %2, %3, %4};" ::"l"(p), "r"(a), "r"(b), "r"(c), "r"(d) : "memory");
}
template <typename T>
__device__ __forceinline__ T* ptr_add(T* base, uint32_t bytes) {
  uint64_t r;
  asm volatile("{\n.reg .u32 l, h;\nmov.b64 {l, h}, %1;\nadd.cc.u32 l, l, %2;\naddc.u32 h, h, 0;\nmov.b64 %0, {l, h};\n}" : "=l"(r) : "l"(base), "r"(bytes));
  return reinterpret_cast<T*>(r);
}
__device__ __forceinline__ float bf_lo(uint32_t v) { return __uint_as_float(v << 16); }
__device__ __forceinline__ float bf_hi(uint32_t v) { return __uint_as_float(v & 0xFFFF0000u); }

__device__ __forceinline__ void quad_transpose(uint32_t& a0, uint32_t& a1, uint32_t& a2, uint32_t& a3, int q) {
  const bool o1 = q & 1, o2 = q & 2;
  uint32_t t0 = o1 ? a0 : a1, t1 = o1 ? a2 : a3;
  t0 = __shfl_xor_sync(0xffffffffu, t0, 1);
  t1 = __shfl_xor_sync(0xffffffffu, t1, 1);
  if (o1) { a0 = t0; a2 = t1; } else { a1 = t0; a3 = t1; }
  t0 = o2 ? a0 : a2;
  t1 = o2 ? a1 : a3;
  t0 = __shfl_xor_sync(0xffffffffu, t0, 2);
  t1 = __shfl_xor_sync(0xffffffffu, t1, 2);
  if (o2) { a0 = t0; a1 = t1; } else { a2 = t0; a3 = t1; }
}

template<int TB, int OFF, int NT>
__device__ __forceinline__ void wgmma_ss_n256(float (&d)[NT], uint64_t da, uint64_t db, int scale_d) {
  asm volatile("{\n.reg .pred p;\nsetp.ne.b32 p, %130, 0;\n"
    "wgmma.mma_async.sync.aligned.m64n256k16.f32.bf16.bf16 {%0, %1, %2, %3, %4, %5, %6, %7, %8, %9, %10, %11, %12, %13, %14, %15, %16, %17, %18, %19, %20, %21, %22, %23, %24, %25, %26, %27, %28, %29, %30, %31, %32, %33, %34, %35, %36, %37, %38, %39, %40, %41, %42, %43, %44, %45, %46, %47, %48, %49, %50, %51, %52, %53, %54, %55, %56, %57, %58, %59, %60, %61, %62, %63, %64, %65, %66, %67, %68, %69, %70, %71, %72, %73, %74, %75, %76, %77, %78, %79, %80, %81, %82, %83, %84, %85, %86, %87, %88, %89, %90, %91, %92, %93, %94, %95, %96, %97, %98, %99, %100, %101, %102, %103, %104, %105, %106, %107, %108, %109, %110, %111, %112, %113, %114, %115, %116, %117, %118, %119, %120, %121, %122, %123, %124, %125, %126, %127}, %128, %129, p, 1, 1, 0, %131;\n}\n"
    : "+f"(d[OFF+0]), "+f"(d[OFF+1]), "+f"(d[OFF+2]), "+f"(d[OFF+3]), "+f"(d[OFF+4]), "+f"(d[OFF+5]), "+f"(d[OFF+6]), "+f"(d[OFF+7]), "+f"(d[OFF+8]), "+f"(d[OFF+9]), "+f"(d[OFF+10]), "+f"(d[OFF+11]), "+f"(d[OFF+12]), "+f"(d[OFF+13]), "+f"(d[OFF+14]), "+f"(d[OFF+15]), "+f"(d[OFF+16]), "+f"(d[OFF+17]), "+f"(d[OFF+18]), "+f"(d[OFF+19]), "+f"(d[OFF+20]), "+f"(d[OFF+21]), "+f"(d[OFF+22]), "+f"(d[OFF+23]), "+f"(d[OFF+24]), "+f"(d[OFF+25]), "+f"(d[OFF+26]), "+f"(d[OFF+27]), "+f"(d[OFF+28]), "+f"(d[OFF+29]), "+f"(d[OFF+30]), "+f"(d[OFF+31]), "+f"(d[OFF+32]), "+f"(d[OFF+33]), "+f"(d[OFF+34]), "+f"(d[OFF+35]), "+f"(d[OFF+36]), "+f"(d[OFF+37]), "+f"(d[OFF+38]), "+f"(d[OFF+39]), "+f"(d[OFF+40]), "+f"(d[OFF+41]), "+f"(d[OFF+42]), "+f"(d[OFF+43]), "+f"(d[OFF+44]), "+f"(d[OFF+45]), "+f"(d[OFF+46]), "+f"(d[OFF+47]), "+f"(d[OFF+48]), "+f"(d[OFF+49]), "+f"(d[OFF+50]), "+f"(d[OFF+51]), "+f"(d[OFF+52]), "+f"(d[OFF+53]), "+f"(d[OFF+54]), "+f"(d[OFF+55]), "+f"(d[OFF+56]), "+f"(d[OFF+57]), "+f"(d[OFF+58]), "+f"(d[OFF+59]), "+f"(d[OFF+60]), "+f"(d[OFF+61]), "+f"(d[OFF+62]), "+f"(d[OFF+63]), "+f"(d[OFF+64]), "+f"(d[OFF+65]), "+f"(d[OFF+66]), "+f"(d[OFF+67]), "+f"(d[OFF+68]), "+f"(d[OFF+69]), "+f"(d[OFF+70]), "+f"(d[OFF+71]), "+f"(d[OFF+72]), "+f"(d[OFF+73]), "+f"(d[OFF+74]), "+f"(d[OFF+75]), "+f"(d[OFF+76]), "+f"(d[OFF+77]), "+f"(d[OFF+78]), "+f"(d[OFF+79]), "+f"(d[OFF+80]), "+f"(d[OFF+81]), "+f"(d[OFF+82]), "+f"(d[OFF+83]), "+f"(d[OFF+84]), "+f"(d[OFF+85]), "+f"(d[OFF+86]), "+f"(d[OFF+87]), "+f"(d[OFF+88]), "+f"(d[OFF+89]), "+f"(d[OFF+90]), "+f"(d[OFF+91]), "+f"(d[OFF+92]), "+f"(d[OFF+93]), "+f"(d[OFF+94]), "+f"(d[OFF+95]), "+f"(d[OFF+96]), "+f"(d[OFF+97]), "+f"(d[OFF+98]), "+f"(d[OFF+99]), "+f"(d[OFF+100]), "+f"(d[OFF+101]), "+f"(d[OFF+102]), "+f"(d[OFF+103]), "+f"(d[OFF+104]), "+f"(d[OFF+105]), "+f"(d[OFF+106]), "+f"(d[OFF+107]), "+f"(d[OFF+108]), "+f"(d[OFF+109]), "+f"(d[OFF+110]), "+f"(d[OFF+111]), "+f"(d[OFF+112]), "+f"(d[OFF+113]), "+f"(d[OFF+114]), "+f"(d[OFF+115]), "+f"(d[OFF+116]), "+f"(d[OFF+117]), "+f"(d[OFF+118]), "+f"(d[OFF+119]), "+f"(d[OFF+120]), "+f"(d[OFF+121]), "+f"(d[OFF+122]), "+f"(d[OFF+123]), "+f"(d[OFF+124]), "+f"(d[OFF+125]), "+f"(d[OFF+126]), "+f"(d[OFF+127])
    : "l"(da), "l"(db), "r"(scale_d), "n"(TB));
}
template<int TB, int OFF, int NT>
__device__ __forceinline__ void wgmma_ss_n32(float (&d)[NT], uint64_t da, uint64_t db, int scale_d) {
  asm volatile("{\n.reg .pred p;\nsetp.ne.b32 p, %18, 0;\n"
    "wgmma.mma_async.sync.aligned.m64n32k16.f32.bf16.bf16 {%0, %1, %2, %3, %4, %5, %6, %7, %8, %9, %10, %11, %12, %13, %14, %15}, %16, %17, p, 1, 1, 0, %19;\n}\n"
    : "+f"(d[OFF+0]), "+f"(d[OFF+1]), "+f"(d[OFF+2]), "+f"(d[OFF+3]), "+f"(d[OFF+4]), "+f"(d[OFF+5]), "+f"(d[OFF+6]), "+f"(d[OFF+7]), "+f"(d[OFF+8]), "+f"(d[OFF+9]), "+f"(d[OFF+10]), "+f"(d[OFF+11]), "+f"(d[OFF+12]), "+f"(d[OFF+13]), "+f"(d[OFF+14]), "+f"(d[OFF+15])
    : "l"(da), "l"(db), "r"(scale_d), "n"(TB));
}
template<int TB, int OFF, int NT>
__device__ __forceinline__ void wgmma_rs_n128(float (&d)[NT], uint32_t a0, uint32_t a1, uint32_t a2, uint32_t a3, uint64_t db, int scale_d) {
  asm volatile("{\n.reg .pred p;\nsetp.ne.b32 p, %69, 0;\n"
    "wgmma.mma_async.sync.aligned.m64n128k16.f32.bf16.bf16 {%0, %1, %2, %3, %4, %5, %6, %7, %8, %9, %10, %11, %12, %13, %14, %15, %16, %17, %18, %19, %20, %21, %22, %23, %24, %25, %26, %27, %28, %29, %30, %31, %32, %33, %34, %35, %36, %37, %38, %39, %40, %41, %42, %43, %44, %45, %46, %47, %48, %49, %50, %51, %52, %53, %54, %55, %56, %57, %58, %59, %60, %61, %62, %63}, {%64, %65, %66, %67}, %68, p, 1, 1, %70;\n}\n"
    : "+f"(d[OFF+0]), "+f"(d[OFF+1]), "+f"(d[OFF+2]), "+f"(d[OFF+3]), "+f"(d[OFF+4]), "+f"(d[OFF+5]), "+f"(d[OFF+6]), "+f"(d[OFF+7]), "+f"(d[OFF+8]), "+f"(d[OFF+9]), "+f"(d[OFF+10]), "+f"(d[OFF+11]), "+f"(d[OFF+12]), "+f"(d[OFF+13]), "+f"(d[OFF+14]), "+f"(d[OFF+15]), "+f"(d[OFF+16]), "+f"(d[OFF+17]), "+f"(d[OFF+18]), "+f"(d[OFF+19]), "+f"(d[OFF+20]), "+f"(d[OFF+21]), "+f"(d[OFF+22]), "+f"(d[OFF+23]), "+f"(d[OFF+24]), "+f"(d[OFF+25]), "+f"(d[OFF+26]), "+f"(d[OFF+27]), "+f"(d[OFF+28]), "+f"(d[OFF+29]), "+f"(d[OFF+30]), "+f"(d[OFF+31]), "+f"(d[OFF+32]), "+f"(d[OFF+33]), "+f"(d[OFF+34]), "+f"(d[OFF+35]), "+f"(d[OFF+36]), "+f"(d[OFF+37]), "+f"(d[OFF+38]), "+f"(d[OFF+39]), "+f"(d[OFF+40]), "+f"(d[OFF+41]), "+f"(d[OFF+42]), "+f"(d[OFF+43]), "+f"(d[OFF+44]), "+f"(d[OFF+45]), "+f"(d[OFF+46]), "+f"(d[OFF+47]), "+f"(d[OFF+48]), "+f"(d[OFF+49]), "+f"(d[OFF+50]), "+f"(d[OFF+51]), "+f"(d[OFF+52]), "+f"(d[OFF+53]), "+f"(d[OFF+54]), "+f"(d[OFF+55]), "+f"(d[OFF+56]), "+f"(d[OFF+57]), "+f"(d[OFF+58]), "+f"(d[OFF+59]), "+f"(d[OFF+60]), "+f"(d[OFF+61]), "+f"(d[OFF+62]), "+f"(d[OFF+63])
    : "r"(a0), "r"(a1), "r"(a2), "r"(a3), "l"(db), "r"(scale_d), "n"(TB));
}
template<int TB, int OFF, int NT>
__device__ __forceinline__ void wgmma_rs_n256(float (&d)[NT], uint32_t a0, uint32_t a1, uint32_t a2, uint32_t a3, uint64_t db, int scale_d) {
  asm volatile("{\n.reg .pred p;\nsetp.ne.b32 p, %133, 0;\n"
    "wgmma.mma_async.sync.aligned.m64n256k16.f32.bf16.bf16 {%0, %1, %2, %3, %4, %5, %6, %7, %8, %9, %10, %11, %12, %13, %14, %15, %16, %17, %18, %19, %20, %21, %22, %23, %24, %25, %26, %27, %28, %29, %30, %31, %32, %33, %34, %35, %36, %37, %38, %39, %40, %41, %42, %43, %44, %45, %46, %47, %48, %49, %50, %51, %52, %53, %54, %55, %56, %57, %58, %59, %60, %61, %62, %63, %64, %65, %66, %67, %68, %69, %70, %71, %72, %73, %74, %75, %76, %77, %78, %79, %80, %81, %82, %83, %84, %85, %86, %87, %88, %89, %90, %91, %92, %93, %94, %95, %96, %97, %98, %99, %100, %101, %102, %103, %104, %105, %106, %107, %108, %109, %110, %111, %112, %113, %114, %115, %116, %117, %118, %119, %120, %121, %122, %123, %124, %125, %126, %127}, {%128, %129, %130, %131}, %132, p, 1, 1, %134;\n}\n"
    : "+f"(d[OFF+0]), "+f"(d[OFF+1]), "+f"(d[OFF+2]), "+f"(d[OFF+3]), "+f"(d[OFF+4]), "+f"(d[OFF+5]), "+f"(d[OFF+6]), "+f"(d[OFF+7]), "+f"(d[OFF+8]), "+f"(d[OFF+9]), "+f"(d[OFF+10]), "+f"(d[OFF+11]), "+f"(d[OFF+12]), "+f"(d[OFF+13]), "+f"(d[OFF+14]), "+f"(d[OFF+15]), "+f"(d[OFF+16]), "+f"(d[OFF+17]), "+f"(d[OFF+18]), "+f"(d[OFF+19]), "+f"(d[OFF+20]), "+f"(d[OFF+21]), "+f"(d[OFF+22]), "+f"(d[OFF+23]), "+f"(d[OFF+24]), "+f"(d[OFF+25]), "+f"(d[OFF+26]), "+f"(d[OFF+27]), "+f"(d[OFF+28]), "+f"(d[OFF+29]), "+f"(d[OFF+30]), "+f"(d[OFF+31]), "+f"(d[OFF+32]), "+f"(d[OFF+33]), "+f"(d[OFF+34]), "+f"(d[OFF+35]), "+f"(d[OFF+36]), "+f"(d[OFF+37]), "+f"(d[OFF+38]), "+f"(d[OFF+39]), "+f"(d[OFF+40]), "+f"(d[OFF+41]), "+f"(d[OFF+42]), "+f"(d[OFF+43]), "+f"(d[OFF+44]), "+f"(d[OFF+45]), "+f"(d[OFF+46]), "+f"(d[OFF+47]), "+f"(d[OFF+48]), "+f"(d[OFF+49]), "+f"(d[OFF+50]), "+f"(d[OFF+51]), "+f"(d[OFF+52]), "+f"(d[OFF+53]), "+f"(d[OFF+54]), "+f"(d[OFF+55]), "+f"(d[OFF+56]), "+f"(d[OFF+57]), "+f"(d[OFF+58]), "+f"(d[OFF+59]), "+f"(d[OFF+60]), "+f"(d[OFF+61]), "+f"(d[OFF+62]), "+f"(d[OFF+63]), "+f"(d[OFF+64]), "+f"(d[OFF+65]), "+f"(d[OFF+66]), "+f"(d[OFF+67]), "+f"(d[OFF+68]), "+f"(d[OFF+69]), "+f"(d[OFF+70]), "+f"(d[OFF+71]), "+f"(d[OFF+72]), "+f"(d[OFF+73]), "+f"(d[OFF+74]), "+f"(d[OFF+75]), "+f"(d[OFF+76]), "+f"(d[OFF+77]), "+f"(d[OFF+78]), "+f"(d[OFF+79]), "+f"(d[OFF+80]), "+f"(d[OFF+81]), "+f"(d[OFF+82]), "+f"(d[OFF+83]), "+f"(d[OFF+84]), "+f"(d[OFF+85]), "+f"(d[OFF+86]), "+f"(d[OFF+87]), "+f"(d[OFF+88]), "+f"(d[OFF+89]), "+f"(d[OFF+90]), "+f"(d[OFF+91]), "+f"(d[OFF+92]), "+f"(d[OFF+93]), "+f"(d[OFF+94]), "+f"(d[OFF+95]), "+f"(d[OFF+96]), "+f"(d[OFF+97]), "+f"(d[OFF+98]), "+f"(d[OFF+99]), "+f"(d[OFF+100]), "+f"(d[OFF+101]), "+f"(d[OFF+102]), "+f"(d[OFF+103]), "+f"(d[OFF+104]), "+f"(d[OFF+105]), "+f"(d[OFF+106]), "+f"(d[OFF+107]), "+f"(d[OFF+108]), "+f"(d[OFF+109]), "+f"(d[OFF+110]), "+f"(d[OFF+111]), "+f"(d[OFF+112]), "+f"(d[OFF+113]), "+f"(d[OFF+114]), "+f"(d[OFF+115]), "+f"(d[OFF+116]), "+f"(d[OFF+117]), "+f"(d[OFF+118]), "+f"(d[OFF+119]), "+f"(d[OFF+120]), "+f"(d[OFF+121]), "+f"(d[OFF+122]), "+f"(d[OFF+123]), "+f"(d[OFF+124]), "+f"(d[OFF+125]), "+f"(d[OFF+126]), "+f"(d[OFF+127])
    : "r"(a0), "r"(a1), "r"(a2), "r"(a3), "l"(db), "r"(scale_d), "n"(TB));
}
template<int TB, int OFF, int NT>
__device__ __forceinline__ void wgmma_rs_n32(float (&d)[NT], uint32_t a0, uint32_t a1, uint32_t a2, uint32_t a3, uint64_t db, int scale_d) {
  asm volatile("{\n.reg .pred p;\nsetp.ne.b32 p, %21, 0;\n"
    "wgmma.mma_async.sync.aligned.m64n32k16.f32.bf16.bf16 {%0, %1, %2, %3, %4, %5, %6, %7, %8, %9, %10, %11, %12, %13, %14, %15}, {%16, %17, %18, %19}, %20, p, 1, 1, %22;\n}\n"
    : "+f"(d[OFF+0]), "+f"(d[OFF+1]), "+f"(d[OFF+2]), "+f"(d[OFF+3]), "+f"(d[OFF+4]), "+f"(d[OFF+5]), "+f"(d[OFF+6]), "+f"(d[OFF+7]), "+f"(d[OFF+8]), "+f"(d[OFF+9]), "+f"(d[OFF+10]), "+f"(d[OFF+11]), "+f"(d[OFF+12]), "+f"(d[OFF+13]), "+f"(d[OFF+14]), "+f"(d[OFF+15])
    : "r"(a0), "r"(a1), "r"(a2), "r"(a3), "l"(db), "r"(scale_d), "n"(TB));
}

__device__ __forceinline__ void wait_flag(const unsigned int* f, uint32_t target) {
  uint32_t v;
#pragma unroll 1
  for (uint32_t spins = 0; spins < (1u << 22); spins++) {
    asm volatile("ld.acquire.gpu.global.u32 %0, [%1];" : "=r"(v) : "l"(f) : "memory");
    if (v >= target) break;
    __nanosleep(100);
  }
}
__device__ __forceinline__ uint32_t lds32(uint32_t a) {
  uint32_t v;
  asm volatile("ld.shared.u32 %0, [%1];" : "=r"(v) : "r"(a) : "memory");
  return v;
}
__device__ __forceinline__ float gate_row(int row, int lane, const bf16* __restrict__ x, const bf16* __restrict__ gate_w) {
  const uint32_t* xr = reinterpret_cast<const uint32_t*>(x + (size_t)row * DM);
  const uint32_t* gw2 = reinterpret_cast<const uint32_t*>(gate_w);
  float gs = 0.f;
#pragma unroll
  for (int i = 0; i < 9; i++) {
    const uint32_t a = __ldg(xr + lane + 32 * i), b = __ldg(gw2 + lane + 32 * i);
    gs = fmaf(bf_lo(a), bf_lo(b), gs);
    gs = fmaf(bf_hi(a), bf_hi(b), gs);
  }
#pragma unroll
  for (int o = 16; o; o >>= 1) gs += __shfl_xor_sync(0xffffffffu, gs, o);
  const float g = 1.f / (1.f + __expf(-gs));
  if (lane == 0) g_gate[row] = g;
  return g;
}
constexpr uint32_t LQ = 36864, LV = 55296;
__device__ __forceinline__ void mma16(float (&c)[4], uint32_t a0, uint32_t a1, uint32_t a2, uint32_t a3, uint32_t b0, uint32_t b1) {
  asm("mma.sync.aligned.m16n8k16.row.col.f32.bf16.bf16.f32 {%0, %1, %2, %3}, {%4, %5, %6, %7}, {%8, %9}, {%0, %1, %2, %3};"
      : "+f"(c[0]), "+f"(c[1]), "+f"(c[2]), "+f"(c[3]) : "r"(a0), "r"(a1), "r"(a2), "r"(a3), "r"(b0), "r"(b1));
}
__device__ __forceinline__ void mma8(float (&c)[4], uint32_t a0, uint32_t a1, uint32_t b0) {
  asm("mma.sync.aligned.m16n8k8.row.col.f32.bf16.bf16.f32 {%0, %1, %2, %3}, {%4, %5}, {%6}, {%0, %1, %2, %3};"
      : "+f"(c[0]), "+f"(c[1]), "+f"(c[2]), "+f"(c[3]) : "r"(a0), "r"(a1), "r"(b0));
}
template <typename F>
__device__ __forceinline__ void local_attn(int lr0, int warp_g, uint32_t sL, uint32_t bL, uint32_t bL2, int lane, float g0, float g1, F st) {
  const float scale_l2 = 0.23570226039551584f * 1.4426950408889634f;
  const int g = lane >> 2, t = lane & 3;
  const bool lo0 = 2 * t > g, lo1 = 2 * t + 1 > g;
  const uint32_t mlo = (lo0 ? 0xFFFFu : 0u) | (lo1 ? 0xFFFF0000u : 0u);
  const bool ok0 = lr0 > 0 || !lo0, ok1 = lr0 > 0 || !lo1;
  uint32_t ad[9], k[9][4], qf[9][2], pe[4], po[4];
#pragma unroll
  for (int c = 0; c < 9; c++) {
    const uint32_t ch = warp_g * 9 + c;
    ad[c] = sL + (lane >> 4) * 18432 + (lane & 15) * 128 + ((ch >> 3) << 11) + (((ch ^ lane) & 7) << 4);
  }
  st(0, 0u); st(1, 0u);
  mbar_wait(bL, 0);
  if (warp_g == 0) TS(1, 6);
#pragma unroll
  for (int c = 0; c < 9; c++) {
    asm volatile("ldmatrix.sync.aligned.m8n8.x2.shared.b16 {%0, %1}, [%2];" : "=r"(qf[c][0]), "=r"(qf[c][1]) : "r"(ad[c] + LQ) : "memory");
    ldsm_x4(k[c][0], k[c][1], k[c][2], k[c][3], ad[c]);
  }
  st(2, k[0][0]); st(3, k[8][0]);
#pragma unroll
  for (int i = 0; i < 4; i++) {
    const uint32_t q0 = (t >= i) ? qf[2 * i][0] : 0u, q1 = (t >= i) ? qf[2 * i][1] : 0u;
    const uint32_t q4 = (t <= i) ? qf[2 * i + 2][0] : 0u, q5 = (t <= i) ? qf[2 * i + 2][1] : 0u;
    float c[4][4];
#pragma unroll
    for (int T = 0; T < 4; T++) {
#pragma unroll
      for (int j = 0; j < 4; j++) c[T][j] = 0.f;
      mma16(c[T], q0, q1, qf[2 * i + 1][0], qf[2 * i + 1][1], k[2 * i][T], k[2 * i + 1][T]);
      mma8(c[T], q4, q5, k[2 * i + 2][T]);
    }
    const float e0 = ok0 ? (lo0 ? c[0][0] : c[1][0]) : -INFINITY, e1 = ok1 ? (lo1 ? c[0][1] : c[1][1]) : -INFINITY;
    const float o0 = ok0 ? (lo0 ? c[2][2] : c[3][2]) : -INFINITY, o1 = ok1 ? (lo1 ? c[2][3] : c[3][3]) : -INFINITY;
    float me = fmaxf(e0, e1), mo = fmaxf(o0, o1);
    me = fmaxf(me, __shfl_xor_sync(0xffffffffu, me, 1));
    mo = fmaxf(mo, __shfl_xor_sync(0xffffffffu, mo, 1));
    me = fmaxf(me, __shfl_xor_sync(0xffffffffu, me, 2)) * scale_l2;
    mo = fmaxf(mo, __shfl_xor_sync(0xffffffffu, mo, 2)) * scale_l2;
    const float w0 = ex2(fmaf(e0, scale_l2, -me)), w1 = ex2(fmaf(e1, scale_l2, -me));
    const float w2 = ex2(fmaf(o0, scale_l2, -mo)), w3 = ex2(fmaf(o1, scale_l2, -mo));
    float se = w0 + w1, so = w2 + w3;
    st(4 + 2 * i, __float_as_uint(i == 1 ? me : i == 2 ? se : e0));
    se += __shfl_xor_sync(0xffffffffu, se, 1);
    so += __shfl_xor_sync(0xffffffffu, so, 1);
    se += __shfl_xor_sync(0xffffffffu, se, 2);
    so += __shfl_xor_sync(0xffffffffu, so, 2);
    asm("rcp.approx.ftz.f32 %0, %0;" : "+f"(se));
    asm("rcp.approx.ftz.f32 %0, %0;" : "+f"(so));
    se *= g0;
    so *= g1;
    pe[i] = pack_bf16(w0 * se, w1 * se);
    po[i] = pack_bf16(w2 * so, w3 * so);
    st(5 + 2 * i, i == 0 ? __float_as_uint(w0) : i == 2 ? __float_as_uint(mo) : po[i]);
  }
  if (warp_g == 0) TS(0, 4);
  mbar_wait(bL2, 0);
  if (warp_g == 0) TS(0, 5);
#pragma unroll
  for (int c = 0; c < 9; c++)
    asm volatile("ldmatrix.sync.aligned.m8n8.x4.trans.shared.b16 {%0, %1, %2, %3}, [%4];"
                 : "=r"(k[c][0]), "=r"(k[c][1]), "=r"(k[c][2]), "=r"(k[c][3]) : "r"(ad[c] + LV) : "memory");
#pragma unroll
  for (int i = 0; i < 4; i++) {
#pragma unroll
    for (int n = 0; n < 3; n++) {
      float c[4] = {0.f, 0.f, 0.f, 0.f};
      mma16(c, pe[i] & mlo, 0u, pe[i] & ~mlo, 0u, k[2 * i + n][0], k[2 * i + n][1]);
      mma16(c, 0u, po[i] & mlo, 0u, po[i] & ~mlo, k[2 * i + n][2], k[2 * i + n][3]);
      const uint32_t r0 = pack_bf16(c[0], c[1]), r1 = pack_bf16(c[2], c[3]);
      const bool keep = (n == 0) && (t < i);
      qf[2 * i + n][0] = keep ? qf[2 * i + n][0] : r0;
      qf[2 * i + n][1] = keep ? qf[2 * i + n][1] : r1;
    }
    st(12 + i, qf[2 * i + 1][0]);
  }
#pragma unroll
  for (int c = 0; c < 9; c++)
    asm volatile("stmatrix.sync.aligned.m8n8.x2.shared.b16 [%0], {%1, %2};" ::"r"(ad[c] + LQ), "r"(qf[c][0]), "r"(qf[c][1]) : "memory");
  asm volatile("fence.proxy.async.shared::cta;" ::: "memory");
}
__device__ __forceinline__ void tma4d(uint32_t dst, const CUtensorMap* m, uint32_t bar, int c1, int c2, int c3) {
  asm volatile("cp.async.bulk.tensor.4d.shared::cluster.global.mbarrier::complete_tx::bytes [%0], [%1, {%3, %4, %5, %6}], [%2];" ::"r"(dst),
               "l"(m), "r"(bar), "r"(0), "r"(c1), "r"(c2), "r"(c3) : "memory");
}

#define ST_NUM 1
#define ST_DEN 2
#define K1_NST 6
constexpr int K1_BST = K1_NST;
#define MAXJ 11
constexpr int K1_MAXJOBS = MAXJ;
constexpr uint32_t K1_FLAG_TARGET = 7;
constexpr uint32_t RDY_TARGET = 48;
constexpr uint32_t GATE_TARGET = 128 * 3;
struct alignas(64) Params {
  CUtensorMap tmA[2];
  CUtensorMap tmW[4];
  CUtensorMap tmK, tmV;
  CUtensorMap tmL[3];
  CUtensorMap tmC, tmO[2], tmOt[2];
  uint16_t jobs[NCLUSTER][K1_MAXJOBS + 1];
  uint8_t order[256];
  uint8_t unit[65][8];
};

struct K1State {
  uint32_t bs, bph, aph;
  bf16 *pp, *pp8;
  int png;
  int tn;
  int wsel;
  uint32_t fo;
};
__device__ __forceinline__ void k1_flag(const K1State& st, int lane, uint32_t bS) {
  if (st.png) {
    __syncwarp();
    if (lane == 0) mbar_arrive(bS + st.fo);
  }
}

__device__ __forceinline__ void scale_q4(uint32_t* v) {
#pragma unroll
  for (int i = 0; i < 4; i++)
    asm volatile("{\n.reg .b32 t;\nmul.rn.bf16x2 t, %0, %2;\nfma.rn.bf16x2 %0, %0, %1, t;\n}" : "+r"(v[i]) : "r"(0x3E033E03u), "r"(0xB9D8B9D8u));
}
__device__ __forceinline__ void k1_first(const K1State& st, uint32_t job, uint32_t bAf, uint32_t bBf) {
  if (job & 3) {
    if ((job >> 14) & 1) mbar_wait(bAf, st.aph);
    mbar_wait(bBf + st.bs * 8, st.bph);
  }
}
__device__ __forceinline__ void k1_tile(float (&acc)[128], uint32_t (&pk)[64], K1State& st, uint32_t job, uint32_t njob, uint32_t sA, uint32_t sB,
                                        uint32_t bAf, uint32_t bAe, uint32_t bBf, uint32_t bBe, uint32_t bS, int wg, int warp, int lane, uint32_t rank) {
  const int a_sel = (job >> 2) & 1, mpair = (job >> 3) & 7, w_sel = (job >> 6) & 3, chunk0 = (job >> 8) & 63;
  const bool newA = (job >> 14) & 1, lastA = (job >> 15) & 1;
  const bool sig = (lane == 0) && (warp < 2);
  const bool siga = lastA && (lane == 0) && (warp == 2);
  const int KC = 8 + a_sel;
  uint32_t prev_bs = 0, a8_bs = 0;
#pragma unroll
  for (int kc = 0; kc < 9; kc++) {
    if (kc >= KC) break;
    uint32_t abase = sA + ((kc + 2) & 7) * 16384;
    if (kc == 8) {
      mbar_wait(bBf + st.bs * 8, st.bph);
      a8_bs = st.bs;
      abase = sB + st.bs * 16384;
      if (++st.bs == K1_BST) { st.bs = 0; st.bph ^= 1; }
    } else if (newA && kc > 0) {
      mbar_wait(bAf + kc * 8, st.aph);
    }
    const uint64_t da = make_desc(abase + wg * 8192, 16, 1024, 1);
#pragma unroll
    for (int ks = 0; ks < 2; ks++) {
      if (ks > 0 || kc > 0) mbar_wait(bBf + st.bs * 8, st.bph);
      const uint64_t db = make_desc(sB + st.bs * 16384, 2048, 1024, 1);
      wg_fence();
      wgmma_ss_n256<1, 0>(acc, da + (uint64_t)(ks * 4), db, (ks > 0) ? 1 : (kc > 0));
      wgmma_ss_n256<1, 0>(acc, da + (uint64_t)(ks * 4 + 2), db + (uint64_t)512, 1);
      wg_commit();
      wg_wait<1>();
      if (ks > 0 || kc > 0) {
        if (sig) mbar_arrive_cluster(bBe + prev_bs * 8, warp);
        if (ks == 0 && siga) mbar_arrive(bAe + (kc - 1) * 8);
      }
      if (st.wsel == 2) {
        const int i = (kc & 7) * 2 + ks;
        if (kc < st.png) {
          quad_transpose(pk[i * 4], pk[i * 4 + 1], pk[i * 4 + 2], pk[i * 4 + 3], lane & 3);
          st_v4a((ks ? st.pp8 : st.pp) + kc * 32, pk[i * 4], pk[i * 4 + 1], pk[i * 4 + 2], pk[i * 4 + 3]);
        }
        if (i == 15) k1_flag(st, lane, bS);
      } else if (st.png) {
#pragma unroll
        for (int i = 0; i < 16; i++) {
          if (i * ST_NUM / ST_DEN != kc * 2 + ks) continue;
          if (st.wsel == 3) scale_q4(pk + i * 4);
          st_v4a(((i & 1) ? st.pp8 : st.pp) + (i / 2) * 32, pk[i * 4], pk[i * 4 + 1], pk[i * 4 + 2], pk[i * 4 + 3]);
          if (i == 15) k1_flag(st, lane, bS);
        }
      }
      prev_bs = st.bs;
      if (++st.bs == K1_BST) { st.bs = 0; st.bph ^= 1; }
    }
  }
  if (newA) st.aph ^= 1;
  const bool isA = (w_sel == 2);
  bf16* out = (w_sel == 0) ? g_K : (w_sel == 1) ? g_V : isA ? g_QKVA : g_ctx;
  const int ld = isA ? NQKVA : (w_sel == 3) ? KCAT : HDIM;
  const int row = mpair * 256 + rank * 128 + wg * 64 + warp * 16 + (lane >> 2);
  st.pp = ptr_add(out, (row * ld + chunk0 * 64 + (lane & 3) * 8) * 2);
  st.pp8 = ptr_add(st.pp, 16 * ld);
  st.png = ((job & 3) + 1) * 2;
  st.wsel = w_sel;
  st.fo = (st.fo + 8) & 24;
  k1_first(st, njob, bAf, bBf);
  wg_wait<0>();
  fence_regs(acc);
  mbar_arrive_cluster_if(bBe + prev_bs * 8, warp & 1, sig);
  mbar_arrive_cluster_if(bBe + a8_bs * 8, warp & 1, sig && a_sel);
  mbar_arrive_if(bAe + 7 * 8, siga && !a_sel);
#pragma unroll
  for (int i = 0; i < 64; i++) {
    const int j = (i >> 3) * 16 + (i & 3) * 4 + ((i >> 2) & 1) * 2;
    pk[i] = pack_bf16(acc[j], acc[j + 1]);
  }
}

constexpr int K2_NST = 7;
constexpr uint32_t K2_END = 0x100;
#define PFD 4
#define PF3A 2
#define PF3 6
#define KC0 1
#define FIRST_DRAW 3
#define PWAIT mbar_wait_ns<1000>
#define PVM 0x8A
#define W0 63
#define SPEC_HI 1.8446744073709552e19f
#define SPEC_LO 5.421010862427522e-20f
constexpr int K3_NST = 4;
__device__ __forceinline__ uint32_t k3_rot(uint32_t sv) { return (0x00E9u >> (2 * sv)) & 3; }
constexpr int K3_STAGE = 16384 + 32768 + 4096;
constexpr int SMEM_DATA = 7 * 32768;
constexpr int SMEM_BYTES = SMEM_DATA + 1024 + 768;

struct Cursor {
  uint32_t s, ph;
  __device__ __forceinline__ void next() {
    if (++s == K2_NST) { s = 0; ph ^= 1; }
  }
};

#define TURN_SYNC() bar_sync(mybar, 256)
#define TURN_ARRIVE() bar_arrive(otherbar, 256)
#define RELEASE_IF(cur, cond) mbar_arrive_cluster_if(bE + (cur).s * 8, warp & 1, sig && (cond))
#define RELEASE(cur) RELEASE_IF(cur, true)
#define ISSUE_PV(cur, first)                                                                                   \
  do {                                                                                                         \
    const uint64_t dv = make_desc(sbase + (cur).s * 32768, 16384, 1024, 1);                                    \
    _Pragma("unroll") for (int t = 0; t < 8; t++)                                                              \
        wgmma_rs_n128<1, 0>(O, P[4 * t], P[4 * t + 1], P[4 * t + 2], P[4 * t + 3], dv + (uint64_t)(t * 128), (t > 0) ? 1 : !(first)); \
  } while (0)
#define ISSUE_QK(cur)                                                                                          \
  do {                                                                                                         \
    const uint64_t dk = make_desc(sbase + (cur).s * 32768, 16, 1024, 1);                                       \
    _Pragma("unroll") for (int t = 0; t < 8; t++)                                                              \
        wgmma_rs_n128<0, 0>(S, Q[4 * t], Q[4 * t + 1], Q[4 * t + 2], Q[4 * t + 3], dk + (uint64_t)((t >> 2) * 1024 + (t & 3) * 2), t > 0); \
  } while (0)
#define EXPB(T)                                                                                                \
  do {                                                                                                         \
    _Pragma("unroll") for (int i = 4 * T; i < 4 * T + 4; i++) asm volatile("" : "+r"(P[i])::"memory");        \
    _Pragma("unroll") for (int jj = 2 * T; jj < 2 * T + 2; jj++) {                                             \
      const float e0 = ex2(S[jj * 4 + 0]), e1 = ex2(S[jj * 4 + 1]), e2 = ex2(S[jj * 4 + 2]), e3 = ex2(S[jj * 4 + 3]); \
      s0 += e0 + e1;                                                                                           \
      s1 += e2 + e3;                                                                                           \
      P[jj * 2 + 0] = pack_bf16(e0, e1);                                                                       \
      P[jj * 2 + 1] = pack_bf16(e2, e3);                                                                       \
    }                                                                                                          \
  } while (0)
#define EXPC(T)                                                                                                \
  do {                                                                                                         \
    if (T > 0 && ((PVM >> (T - 1)) & 1)) {                                                                     \
      anchor((T & 2) ? s0 : s1, never);                                                                        \
      wg_wait<__builtin_popcount(PVM >> T) - 1>();                                                             \
      if ((PVM >> T) == (128 >> T)) { fence_regs(O); RELEASE(cv); }                                            \
    }                                                                                                          \
    EXPB(T);                                                                                                   \
  } while (0)
#define MASK(G, g)                                                                                             \
  do {                                                                                                         \
    if ((g) * 8 > d) S[(G) * 4 + 0] = -INFINITY;                                                               \
    if ((g) * 8 + 1 > d) S[(G) * 4 + 1] = -INFINITY;                                                           \
    if ((g) * 8 - 8 > d) S[(G) * 4 + 2] = -INFINITY;                                                           \
    if ((g) * 8 - 7 > d) S[(G) * 4 + 3] = -INFINITY;                                                           \
  } while (0)
#define STORE_O(G)                                                                                             \
  do {                                                                                                         \
    st_v4(optr + (G) * 32, pack_bf16(O[(G) * 16 + 0] * f0, O[(G) * 16 + 1] * f0), pack_bf16(O[(G) * 16 + 4] * f0, O[(G) * 16 + 5] * f0), \
          pack_bf16(O[(G) * 16 + 8] * f0, O[(G) * 16 + 9] * f0), pack_bf16(O[(G) * 16 + 12] * f0, O[(G) * 16 + 13] * f0)); \
    st_v4(optr + 8 * KCAT + (G) * 32, pack_bf16(O[(G) * 16 + 2] * f1, O[(G) * 16 + 3] * f1), pack_bf16(O[(G) * 16 + 6] * f1, O[(G) * 16 + 7] * f1), \
          pack_bf16(O[(G) * 16 + 10] * f1, O[(G) * 16 + 11] * f1), pack_bf16(O[(G) * 16 + 14] * f1, O[(G) * 16 + 15] * f1)); \
  } while (0)

#define FLUSH()                                                                                                \
  do {                                                                                                         \
    _Pragma("unroll") for (int G = 0; G < 8; G++) {                                                            \
      st_v4a(st.pp + G * 32, pk[G * 8], pk[G * 8 + 1], pk[G * 8 + 2], pk[G * 8 + 3]);                          \
      st_v4a(st.pp8 + G * 32, pk[G * 8 + 4], pk[G * 8 + 5], pk[G * 8 + 6], pk[G * 8 + 7]);                     \
    }                                                                                                          \
    k1_flag(st, lane, bS);                                                                                     \
  } while (0)

__global__ void __cluster_dims__(2, 1, 1) __launch_bounds__(384, 1)
fused_kernel(const __grid_constant__ Params p, const bf16* __restrict__ x, const bf16* __restrict__ gate_w, bf16* __restrict__ out) {
  extern __shared__ uint8_t smem_raw[];
  const uint32_t sbase = (smem_u32(smem_raw) + 1023) & ~1023u;
  const uint32_t sB = sbase, sA = sbase + K1_BST * 16384, sBar = sbase + SMEM_DATA;
  const uint32_t bAf = sBar, bAe = sBar + 64, bBf = sBar + 128, bBe = sBar + 176, bL = sBar + 224, bS = sBar + 656, bL2 = sBar + 240, sL = sA + 32768;
  const uint32_t bF = sBar + 256, bE = sBar + 320, bT = sBar + 384, sTick = sBar + 400, sItem = sBar + 416, bS2 = sBar + 688, bR = sBar + 456, bLast = sBar + 464, bH = sBar + 472, bT0 = sBar + 480;
  const uint32_t b3F = sBar + 512, b3E = sBar + 544, sGate = sBar + 576;
  const int tid = threadIdx.x, warp_g = __shfl_sync(0xffffffffu, tid >> 5, 0), lane = tid & 31;
  const uint32_t rank = cluster_rank();
  const int cl = blockIdx.x >> 1;
  TSM(0);
  if (tid == 256) {
    const uint32_t job = p.jobs[cl][0];
#pragma unroll
    for (int i = 0; i < KC0; i++) { mbar_init(bAf + i * 8, 1); mbar_init(bBf + i * 16, 1); mbar_init(bBf + i * 16 + 8, 1); }
    asm volatile("fence.mbarrier_init.release.cluster;" ::: "memory");
#pragma unroll 1
    for (int i = 0; i < 4 * KC0; i++) {
      if (!(i & 3)) {
        mbar_expect(bAf + i * 2, 16384);
        tma2d(sA + (i / 4 + 2) * 16384, &p.tmA[(job >> 2) & 1], bAf + i * 2, i * 16, ((job >> 3) & 7) * 256 + rank * 128);
      }
      if (!(i & 1)) mbar_expect(bBf + i * 4, 16384);
      tma3d(sB + i * 8192, &p.tmW[(job >> 6) & 3], bBf + (i >> 1) * 8, 0, i * 16, (job >> 8) & 63);
    }
  }
  if (tid == 0) {
    for (int i = 0; i < 8; i++) { if (i >= KC0) mbar_init(bAf + i * 8, 1); mbar_init(bAe + i * 8, 2); }
    for (int i = 0; i < K1_BST; i++) { if (i >= 2 * KC0) mbar_init(bBf + i * 8, 1); mbar_init(bBe + i * 8, 4); }
    mbar_init(bL, 1);
    mbar_init(bL2, 1);
    mbar_init(bR, 1);
    mbar_init(bLast, 1);
    mbar_init(bH, 4);
    mbar_init(bT0, 1);
    for (int i = 0; i < 8; i++) mbar_init(bS + i * 8, 8);
    for (int i = 0; i < K2_NST; i++) { mbar_init(bF + i * 8, 1); mbar_init(bE + i * 8, 4); }
    mbar_init(bT, 1); mbar_init(bT + 8, 1);
    for (int i = 0; i < K3_NST; i++) { mbar_init(b3F + i * 8, 1); mbar_init(b3E + i * 8, 4); }
    asm volatile("fence.mbarrier_init.release.cluster;" ::: "memory");
  }
  __syncwarp();
  if (warp_g != 8) cluster_sync();
  const int lr0 = blockIdx.x * 16;

  if (warp_g >= 8) {
    reg_dealloc<40>();
    if (warp_g == 8) {
      {
        __syncwarp();
        cluster_sync();
      }
      if (elect_one()) {
        uint32_t bs = (2 * KC0) % K1_BST, bph = (2 * KC0 < K1_BST), aph = 1;
#pragma unroll 1
        for (int ji = 0; ji < K1_MAXJOBS; ji++) {
          const uint32_t job = p.jobs[cl][ji];
          if (!(job & 3)) break;
          const int a_sel = (job >> 2) & 1, mpair = (job >> 3) & 7, chunk0 = (job >> 8) & 63;
          const bool newA = (job >> 14) & 1;
          const int KC = a_sel ? 9 : 8;
          const uint32_t halfbytes = 8192;
          const bool lastjob = (ji + 1 == K1_MAXJOBS) || !(p.jobs[cl][ji + 1] & 3);
          const CUtensorMap* tw = &p.tmW[(job >> 6) & 3];
          {
            const uint32_t njob = (ji + 1 < K1_MAXJOBS) ? p.jobs[cl][ji + 1] : 0;
            if (!(njob & 3) && !newA) mbar_arrive(bLast);
          }
#pragma unroll 1
          for (int kc = ji ? 0 : KC0; kc < KC; kc++) {
            {
              const bool nx = kc + PFD >= KC;
              const uint32_t njob = nx ? p.jobs[cl][ji + 1] : job;
              const int pk = nx ? kc + PFD - KC : kc + PFD;
              if ((njob & 3) && (nx || ji > 0)) {
                if (cl >= 64 || ((pk ^ (cl >> 1)) & 3) == 0)
                  tma_pf3d(&p.tmW[(njob >> 6) & 3], 0, pk * 64 + (cl & 1) * 32 + rank * 16, (njob >> 8) & 63);
                if (((njob >> 14) & 1) || pk == 8) tma_pf2d(&p.tmA[(njob >> 2) & 1], pk * 64, ((njob >> 3) & 7) * 256 + rank * 128);
              }
            }
            if (kc == 8) {
              PWAIT(bBe + bs * 8, bph);
              mbar_expect(bBf + bs * 8, 16384);
              tma2d(sB + bs * 16384, &p.tmA[1], bBf + bs * 8, 512, mpair * 256 + rank * 128);
              if (++bs == K1_BST) { bs = 0; bph ^= 1; }
            } else if (newA) {
              PWAIT(bAe + kc * 8, aph);
              mbar_expect(bAf + kc * 8, 16384);
              tma2d(sA + ((kc + 2) & 7) * 16384, &p.tmA[a_sel], bAf + kc * 8, kc * 64, mpair * 256 + rank * 128);
              if (kc == 7 && lastjob) mbar_arrive(bLast);
            }
#pragma unroll 1
            for (int kk = 0; kk < 2; kk++) {
              PWAIT(bBe + bs * 8, bph);
              mbar_expect(bBf + bs * 8, 2 * halfbytes);
              tma3d_mc(sB + bs * 16384 + rank * halfbytes, tw, bBf + bs * 8, 0, kc * 64 + kk * 32 + rank * 16, chunk0, 3);
              if (++bs == K1_BST) { bs = 0; bph ^= 1; }
            }
          }
          if (newA) aph ^= 1;
        }
        Cursor c{0, 0};
        int pcol = 0;
        PWAIT(bR, 0);
        uint32_t tick = lds32(sTick + 8), seen = 1u << (p.order[tick] >> 4);
        asm volatile("fence.proxy.async.global;" ::: "memory");
#pragma unroll 1
        for (int it = 0;; it++) {
          const uint32_t item = (tick < 256) ? p.order[tick] : (K2_END | min(tick - 256, 255u));
          asm volatile("st.shared.u32 [%0], %1;" ::"r"(sItem + (it & 7) * 4), "r"(item) : "memory");
          if (item >= K2_END) break;
          const int h = item >> 3, j = item & 7;
          const int blk = 2 * j + (int)(rank ^ (it & 1));
          const int col = h * 128 + rank * 64;
          const int nb = 2 * j + 2;
          if (!((seen >> (h >> 1)) & 1)) {
            wait_flag(&g_sync[F_HP + (h >> 1)], RDY_TARGET);
            asm volatile("fence.proxy.async.global;" ::: "memory");
            seen |= 1u << (h >> 1);
          }
          PWAIT(bE + c.s * 8, c.ph);
          mbar_expect(bF + c.s * 8, 32768);
          tma2d(sbase + c.s * 32768, &p.tmC, bF + c.s * 8, h * 128, blk * 128);
          tma2d(sbase + c.s * 32768 + 16384, &p.tmC, bF + c.s * 8, h * 128 + 64, blk * 128);
          c.next();
          if (tick >= 256 - 73) {
            const int kk = tick - (256 - 73), sel = (kk < 9), kr = (sel ? kk : kk - 9) * 64 + rank * 32;
#pragma unroll 1
            for (int i = 0; i < 2; i++) {
              tma_pf3d(&p.tmO[sel], 0, kr, i * 4);
              tma_pf2d(&p.tmOt[sel], 512 + i * 32, kr);
            }
          }
#pragma unroll 1
          for (int n = nb - 1; n >= 0; n--) {
            if (n == 0 && rank == 0) tick = atomicAdd(&g_sync[F_TICK], 1u);
            PWAIT(bE + c.s * 8, c.ph);
            mbar_expect(bF + c.s * 8, 32768);
            tma2d_mc(sbase + c.s * 32768 + rank * 16384, &p.tmK, bF + c.s * 8, col, n * 128, 3);
            c.next();
            if (n < nb - 1 || it > 0) {
              PWAIT(bE + c.s * 8, c.ph);
              mbar_expect(bF + c.s * 8, 32768);
              tma2d_mc(sbase + c.s * 32768 + rank * 16384, &p.tmV, bF + c.s * 8, (n < nb - 1) ? col : pcol, (n < nb - 1) ? (n + 1) * 128 : 0, 3);
              c.next();
            }
          }
          pcol = col;
          if (rank == 0) {
            asm volatile(
                "{\n.reg .b32 a, b;\nmapa.shared::cluster.u32 a, %0, 1;\nmapa.shared::cluster.u32 b, %1, 1;\n"
                "st.async.shared::cluster.mbarrier::complete_tx::bytes.u32 [a], %2, [b];\n}" ::"r"(sTick + (it & 1) * 4),
                "r"(bT + (it & 1) * 8), "r"(tick) : "memory");
          } else {
            mbar_expect(bT + (it & 1) * 8, 4);
            PWAIT(bT + (it & 1) * 8, (it >> 1) & 1);
            tick = lds32(sTick + (it & 1) * 4);
          }
        }
        PWAIT(bE + c.s * 8, c.ph);
        mbar_expect(bF + c.s * 8, 32768);
        tma2d_mc(sbase + c.s * 32768 + rank * 16384, &p.tmV, bF + c.s * 8, pcol, 0, 3);
        const uint32_t unit = min(tick - 256, 64u);
        const int mblk = (7 - (p.unit[unit][0] >> 1)) * 2 + rank, nhalf = p.unit[unit][0] & 1;
        uint32_t have, hoa;
        asm volatile("ld.acquire.gpu.global.u32 %0, [%1];" : "=r"(have) : "l"(&g_sync[F_CTX + mblk]) : "memory");
        asm volatile("ld.acquire.gpu.global.u32 %0, [%1];" : "=r"(hoa) : "l"(&g_sync[F_OA + mblk]) : "memory");
        asm volatile("fence.proxy.async.global;" ::: "memory");
#pragma unroll 1
        for (uint32_t idx = PF3A; idx < PF3 && unit < 64; idx++) {
          const int kk = p.unit[unit][3] + idx;
          if ((kk < 9) ? (hoa >= 8) : ((have >> ((kk - 9) >> 1)) & 1)) tma_pf2d(&p.tmC, ((kk < 9) ? 64 + kk : kk - 9) * 64, mblk * 128);
        }
        if (unit < 64) {
          const uint32_t rot = k3_rot(c.s), nfree = ((0x1Au >> c.s) & 1) ? 2 : 3;
#pragma unroll 1
          for (uint32_t idx = 0; idx < p.unit[unit][2]; idx++) {
            const int kk = p.unit[unit][3] + idx + ((idx >= p.unit[unit][4]) ? p.unit[unit][5] : 0);
            const uint32_t s = (rot + idx) & 3;
            if (idx >= nfree) PWAIT((idx < 4) ? bH : b3E + s * 8, (idx < 4) ? 0 : (~idx >> 2) & 1);
#pragma unroll 1
            while (idx < nfree && c.s != ((0x6431u >> (4 * s)) & 15)) {
              c.next();
              PWAIT(bE + c.s * 8, c.ph);
            }
            mbar_expect(b3F + s * 8, K3_STAGE);
            const uint32_t st = sbase + s * K3_STAGE;
            const int sel = (kk < 9), k = sel ? kk : kk - 9, kr = k * 64 + rank * 32;
            tma3d_mc(st + 16384 + rank * 16384, &p.tmO[sel], b3F + s * 8, 0, kr, nhalf * 4, 3);
            tma2d_mc(st + 49152 + rank * 2048, &p.tmOt[sel], b3F + s * 8, 512 + nhalf * 32, kr, 3);
            if (sel && hoa < 8) {
              wait_flag(&g_sync[F_OA + mblk], 8);
              hoa = 8;
              asm volatile("fence.proxy.async.global;" ::: "memory");
            }
            if (!sel && !((have >> (k >> 1)) & 1)) {
#pragma unroll 1
              for (uint32_t spins = 0; spins < (1u << 22); spins++) {
                asm volatile("ld.acquire.gpu.global.u32 %0, [%1];" : "=r"(have) : "l"(&g_sync[F_CTX + mblk]) : "memory");
                if ((have >> (k >> 1)) & 1) break;
                __nanosleep(100);
              }
              asm volatile("fence.proxy.async.global;" ::: "memory");
            }
            tma2d(st, &p.tmC, b3F + s * 8, (sel ? 64 + k : k) * 64, mblk * 128);
          }
        }
      }
    }
    __syncwarp();
    if (warp_g == 8) {
      uint32_t v = 0;
      if (lane == 0) {
        __threadfence();
        v = atomicAdd(&g_sync[F_DONE], 1u);
      }
      if (__shfl_sync(0xffffffffu, v, 0) == 2 * NCLUSTER - 1) {
        reinterpret_cast<uint4*>(g_sync)[lane] = make_uint4(0, 0, 0, 0);
        if (lane == 0) g_sync[F_EPOCH] = lds32(sGate + 64) + 1;
      }
    }
    asm volatile("" ::: "memory");
    if (__shfl_sync(0xffffffffu, warp_g, 0) != 8) {
      if (lr0 < S_LEN) {
#pragma unroll 1
        for (int i = warp_g - 9; i < 16; i += 3) {
          const float g = gate_row(lr0 + i, lane, x, gate_w);
          if (lane == 0) asm volatile("st.shared.f32 [%0], %1;" ::"r"(sGate + i * 4), "f"(g) : "memory");
        }
        bar_arrive(3, 256 + 96);
        if (lane == 0) {
          __threadfence();
          atomicAdd(&g_sync[F_GATE], 1u);
        }
      }
      uint32_t aph = 1;
#pragma unroll 1
      for (int ji = 0; ji < K1_MAXJOBS; ji++) aph ^= (p.jobs[cl][ji] >> 14) & 1;
      if (warp_g == 9 && lane == 0) {
#pragma unroll 1
        for (int ji = 0; ji < K1_MAXJOBS; ji++) {
          const uint32_t job = p.jobs[cl][ji];
          if (!(job & 3)) break;
          PWAIT(bS + (ji & 3) * 8, (ji >> 2) & 1);
          __threadfence();
          atomicAdd(&g_sync[(((job >> 6) & 3) == 2) ? (F_QKVA + ((job >> 3) & 7) * 2 + rank) : (F_HP + ((job >> 10) & 15))], 1u);
        }
#pragma unroll 1
        for (int it = 0;; it++) {
          PWAIT(bS2 + (it & 3) * 8, (it >> 2) & 1);
          const uint32_t item = lds32(sItem + (it & 7) * 4), nxt = lds32(sItem + ((it + 1) & 7) * 4);
          __threadfence();
          atomicOr(&g_sync[F_CTX + (item & 7) * 2 + (rank ^ (it & 1))], 1u << (item >> 3));
          if (nxt >= K2_END) break;
        }
      } else if (warp_g == 11) {
        if (lane == 0) {
          prefetch_tmap(&p.tmC); prefetch_tmap(&p.tmK); prefetch_tmap(&p.tmV);
          asm volatile("st.shared.u32 [%0], %1;" ::"r"(sGate + 64), "r"(__ldcg(&g_sync[F_EPOCH])) : "memory");
          wait_flag(&g_sync[F_GATE], GATE_TARGET);
          uint32_t tick;
          if (rank == 0) {
            PWAIT(bLast, 0);
            PWAIT(bAe + FIRST_DRAW * 8, aph);
            tick = atomicAdd(&g_sync[F_TICK], 1u);
            asm volatile("st.shared.u32 [%0], %1;" ::"r"(sTick + 8), "r"(tick) : "memory");
            asm volatile(
                "{\n.reg .b32 a, b;\nmapa.shared::cluster.u32 a, %0, 1;\nmapa.shared::cluster.u32 b, %1, 1;\n"
                "st.async.shared::cluster.mbarrier::complete_tx::bytes.u32 [a], %2, [b];\n}" ::"r"(sTick + 8), "r"(bT0), "r"(tick) : "memory");
          } else {
            mbar_expect(bT0, 4);
            PWAIT(bT0, 0);
            tick = lds32(sTick + 8);
          }
          wait_flag(&g_sync[F_HP + (p.order[tick] >> 4)], RDY_TARGET);
          mbar_arrive(bR);
        }
      } else if (warp_g == 10) {
        if (lr0 < S_LEN && lane == 0) {
          prefetch_tmap(&p.tmL[0]); prefetch_tmap(&p.tmL[1]); prefetch_tmap(&p.tmL[2]);
          wait_flag(&g_sync[F_QKVA + (lr0 >> 7)], K1_FLAG_TARGET);
          wait_flag(&g_sync[F_QKVA + (max(lr0 - 16, 0) >> 7)], K1_FLAG_TARGET);
          asm volatile("fence.proxy.async.global;" ::: "memory");
          PWAIT(bLast, 0);
#pragma unroll 1
          for (int kc = 0; kc < 6; kc++) {
            PWAIT(bAe + kc * 8, aph);
            if (kc == 3) {
              mbar_expect(bL, LV);
              tma4d(sL, &p.tmL[0], bL, lr0 / 2 - 8, 9, 0);
              tma4d(sL + LQ, &p.tmL[1], bL, lr0 / 2, 0, 0);
            }
          }
          mbar_expect(bL2, LQ);
          tma4d(sL + LV, &p.tmL[0], bL2, lr0 / 2 - 8, 18, 0);
        }
        __syncwarp();
        bar_sync(5, 256 + 32);
        if (lr0 < S_LEN && lane == 0) {
          asm volatile("cp.async.bulk.tensor.4d.global.shared::cta.bulk_group [%0, {%2, %3, %2, %2}], [%1];" ::"l"(&p.tmL[2]), "r"(sL + LQ), "r"(0), "r"(lr0 / 2) : "memory");
          asm volatile("cp.async.bulk.commit_group;" ::: "memory");
          asm volatile("cp.async.bulk.wait_group.read 0;" ::: "memory");
        }
        __syncwarp();
        if (lane < 12) mbar_arrive_cluster(bE + (4 + lane % 3) * 8, (lane / 3) & 1);
        if (lr0 < S_LEN && lane == 0) {
          asm volatile("cp.async.bulk.wait_group 0;" ::: "memory");
          asm volatile("fence.proxy.async.global;" ::: "memory");
          __threadfence();
          atomicAdd(&g_sync[F_OA + (lr0 >> 7)], 1u);
        }
      }
    }
    __syncwarp();
    cluster_sync();
  } else {
    reg_alloc<232>();
    const int wg = warp_g >> 2, warp = warp_g & 3, q = lane & 3;
    const bool sig = (lane == 0) && (warp < 2);
    {
      K1State st{0, 0, 0, nullptr, nullptr, 0, 0, 0, 24};
      float acc[128];
      uint32_t pk[64];
      if (wg == 0) { TS(0, 0); TSC(0, 2); }
      uint32_t job = p.jobs[cl][0];
      k1_first(st, job, bAf, bBf);
      {
#pragma unroll 1
        for (int ji = 0; job & 3; ji++) {
          const uint32_t njob = p.jobs[cl][ji + 1];
          k1_tile(acc, pk, st, job, njob, sA, sB, bAf, bAe, bBf, bBe, bS, wg, warp, lane, rank);
          job = njob;
        }
      }
#pragma unroll
      for (int i = 0; i < 4; i++)
        mbar_arrive_cluster_if(bE + i * 8, warp & 1, sig);
      if (lr0 < S_LEN) bar_sync(3, 256 + 96);
      if (st.wsel == 3) {
#pragma unroll
        for (int G = 0; G < 16; G++) scale_q4(pk + G * 4);
      }
      auto flush = [&](int i, uint32_t dep) {
        asm volatile("{\n.reg .pred p;\nsetp.eq.u32 p, %5, 0;\n@p st.global.cs.v4.b32 [%0], {%1, %2, %3, %4};\n}" ::"l"(((i & 1) ? st.pp8 : st.pp) + (i / 2) * 32),
                     "r"(pk[i * 4]), "r"(pk[i * 4 + 1]), "r"(pk[i * 4 + 2]), "r"(pk[i * 4 + 3]), "r"(dep & blockIdx.y) : "memory");
      };
      if (wg == 0) { TS(0, 1); TSC(0, 3); }
      if (lr0 < S_LEN) {
        const float gate0 = __uint_as_float(lds32(sGate + (lane >> 2) * 8)), gate1 = __uint_as_float(lds32(sGate + (lane >> 2) * 8 + 4));
        local_attn(lr0, warp_g, sL, bL, bL2, lane, gate0, gate1, flush);
        k1_flag(st, lane, bS);
      } else {
        FLUSH();
      }
      bar_arrive(5, 256 + 32);
    }
    __syncwarp();
    uint32_t item, rot;
    {
      const int mybar = 1 + wg, otherbar = 2 - wg;
      const uint32_t never = blockIdx.y;
      float S[64], O[64];
      uint32_t P[32], Q[32];
      float m0 = 0.f, m1 = 0.f, l0 = 1.f, l1 = 1.f, gf0 = 0.f, gf1 = 0.f;
      uint32_t eoff = 0, prev_single = 0;
      Cursor c{0, 0};
      if (wg == 1) bar_arrive(1, 256);
      if (wg == 0) { TS(1, 0); TSC(1, 2); }
#pragma unroll 1
      for (int it = 0;; it++) {
        TB(0);
        const int hi = (int)(rank ^ (it & 1));
        Cursor cq = c, ck, cv, cs0, cs1;
        rot = k3_rot(c.s);
        c.next();
        ck = c; c.next();
        cs0 = ck; cs1 = ck; cv = ck;
        if (it > 0) { cv = c; c.next(); }
        if (!hi) {
          ck = c; c.next();
          cs1 = c; c.next();
        }
        mbar_wait(bF + cq.s * 8, cq.ph);
        TB(1);
        item = lds32(sItem + (it & 7) * 4);
        {
          const uint32_t qa = sbase + cq.s * 32768 + (wg * 64 + warp * 16 + (lane & 15)) * 128;
#pragma unroll
          for (int t = 0; t < 8; t++)
            ldsm_x4(Q[4 * t], Q[4 * t + 1], Q[4 * t + 2], Q[4 * t + 3], qa + (t >> 2) * 16384 + ((((t & 3) * 2 + (lane >> 4)) ^ (lane & 7)) << 4));
        }
        const uint32_t rdy = mbar_test(bF + ck.s * 8, ck.ph) & mbar_test(bF + cv.s * 8, cv.ph);
        l0 += __shfl_xor_sync(0xffffffffu, l0, 1);
        l1 += __shfl_xor_sync(0xffffffffu, l1, 1);
        l0 += __shfl_xor_sync(0xffffffffu, l0, 2);
        l1 += __shfl_xor_sync(0xffffffffu, l1, 2);
        if (item >= K2_END) {
          TURN_SYNC();
          TRC(2);
          wg_fence();
          ISSUE_PV(cq, prev_single);
          wg_commit();
          if (wg == 0) TURN_ARRIVE();
          asm volatile("" : "+f"(gf0), "+f"(gf1), "+f"(l0), "+f"(l1));
          const float f0 = __fdividef(1.f - gf0, l0), f1 = __fdividef(1.f - gf1, l1);
          bf16* optr = ptr_add(g_ctx, eoff);
          wg_wait<0>();
          fence_regs(O);
          mbar_arrive_cluster_if(bH, warp & 1, sig);
          STORE_O(0); STORE_O(1); STORE_O(2); STORE_O(3);
          __syncwarp();
          mbar_arrive_if(bS2 + ((it - 1) & 3) * 8, lane == 0);
          break;
        }
        if (!rdy) mbar_wait2(bF + ck.s * 8, ck.ph, bF + cv.s * 8, cv.ph);
        TB(2);
        TURN_SYNC();
        TB(3);
        TRC(1);
        if (it > 0) {
          wg_fence();
          ISSUE_PV(cv, prev_single);
          wg_commit();
        } else {
          wg_fence();
          wg_commit();
        }
        wg_fence();
        ISSUE_QK(ck);
        wg_commit();
        TURN_ARRIVE();
        RELEASE(cq);
        TB(4);
        asm volatile("" : "+f"(gf0), "+f"(gf1), "+f"(l0), "+f"(l1));
        const float f0 = __fdividef(1.f - gf0, l0), f1 = __fdividef(1.f - gf1, l1);
        wg_wait<1>();
        fence_regs(O);
        fence_regs(P);
        TB(5);
        if (it > 0) {
          RELEASE(cv);
          bf16* optr = ptr_add(g_ctx, eoff);
          STORE_O(0); STORE_O(1); STORE_O(2); STORE_O(3);
          __syncwarp();
          mbar_arrive_if(bS2 + ((it - 1) & 3) * 8, lane == 0);
        }
        TB(6);
        {
          const int row = (2 * (item & 7) + hi) * 128 + wg * 64 + warp * 16 + (lane >> 2);
          eoff = (row * KCAT + (item >> 3) * 128 + q * 8) * 2;
          const float* gp = ptr_add(g_gate, row * 4);
          asm volatile("ld.global.f32 %0, [%1];" : "=f"(gf0) : "l"(gp));
          asm volatile("ld.global.f32 %0, [%1];" : "=f"(gf1) : "l"(gp + 8));
          if (!hi) {
            mbar_wait2(bF + cs0.s * 8, cs0.ph, bF + cs1.s * 8, cs1.ph);
            RELEASE(cs0);
            RELEASE(cs1);
          }
        }
        TB(7);
        wg_wait<0>();
        fence_regs(S);
        TB(8);
        RELEASE(ck);
        const int nblk = 2 * (item & 7) + 1 + hi;
        prev_single = (nblk == 1);
        float s0 = 0.f, s1 = 0.f;
        l0 = 0.f; l1 = 0.f;
        m0 = 0.f; m1 = 0.f;
        bool shifted = false;
        {
          const int d = warp * 16 + (lane >> 2) - 2 * q;
          if (wg == 0) {
#pragma unroll
            for (int jj = 0; jj < 8; jj++) MASK(jj, jj);
            EXPB(0); EXPB(1); EXPB(2); EXPB(3);
#pragma unroll
            for (int i = 32; i < 64; i++) S[i] = -INFINITY;
#pragma unroll
            for (int i = 16; i < 32; i++) P[i] = 0;
          } else {
#pragma unroll
            for (int jj = 0; jj < 8; jj++) MASK(jj + 8, jj);
            EXPB(0); EXPB(1); EXPB(2); EXPB(3); EXPB(4); EXPB(5); EXPB(6); EXPB(7);
          }
        }
        float chk = (q == 0 && !(fminf(s0, s1) >= SPEC_LO)) ? INFINITY : s0 + s1;
        fence_regs(P);
        TB(9);
#pragma unroll 1
        for (int n = 1;; n++) {
          if (__any_sync(0xffffffffu, !(chk <= SPEC_HI))) {
            float mx0 = fmaxf(S[0], S[1]), mx1 = fmaxf(S[2], S[3]);
#pragma unroll
            for (int jj = 1; jj < 16; jj++) {
              mx0 = fmaxf(mx0, fmaxf(S[jj * 4 + 0], S[jj * 4 + 1]));
              mx1 = fmaxf(mx1, fmaxf(S[jj * 4 + 2], S[jj * 4 + 3]));
            }
            mx0 = fmaxf(mx0, __shfl_xor_sync(0xffffffffu, mx0, 1));
            mx1 = fmaxf(mx1, __shfl_xor_sync(0xffffffffu, mx1, 1));
            mx0 = fmaxf(mx0, __shfl_xor_sync(0xffffffffu, mx0, 2));
            mx1 = fmaxf(mx1, __shfl_xor_sync(0xffffffffu, mx1, 2));
            const float lo = (n == 1) ? -INFINITY : 0.f;
            mx0 = fmaxf(mx0, lo);
            mx1 = fmaxf(mx1, lo);
            m0 += mx0; m1 += mx1;
            shifted = true;
            const float sc0 = ex2(-fmaxf(mx0, 0.f)), sc1 = ex2(-fmaxf(mx1, 0.f));
            l0 *= sc0; l1 *= sc1;
            s0 = 0.f; s1 = 0.f;
#pragma unroll
            for (int jj = 0; jj < 16; jj++) {
              const float e0 = ex2(S[jj * 4 + 0] - mx0), e1 = ex2(S[jj * 4 + 1] - mx0), e2 = ex2(S[jj * 4 + 2] - mx1), e3 = ex2(S[jj * 4 + 3] - mx1);
              s0 += e0 + e1;
              s1 += e2 + e3;
              P[jj * 2 + 0] = pack_bf16(e0, e1);
              P[jj * 2 + 1] = pack_bf16(e2, e3);
              O[jj * 4 + 0] *= sc0;
              O[jj * 4 + 1] *= sc0;
              O[jj * 4 + 2] *= sc1;
              O[jj * 4 + 3] *= sc1;
            }
          }
          l0 += s0;
          l1 += s1;
          if (n >= nblk) break;
          ck = c; c.next();
          cv = c; c.next();
          mbar_wait(bF + ck.s * 8, ck.ph);
          mbar_wait(bF + cv.s * 8, cv.ph);
          TURN_SYNC();
          TRC(0);
          wg_fence();
          ISSUE_QK(ck);
          wg_commit();
          {
            const uint64_t dv = make_desc(sbase + cv.s * 32768, 16384, 1024, 1);
#pragma unroll
            for (int t = 0; t < 8; t++) {
              wgmma_rs_n128<1, 0>(O, P[4 * t], P[4 * t + 1], P[4 * t + 2], P[4 * t + 3], dv + (uint64_t)(t * 128), (t > 0) ? 1 : (n != 1));
              if ((PVM >> t) & 1) wg_commit();
            }
          }
          TURN_ARRIVE();
          s0 = 0.f; s1 = 0.f;
          wg_wait<__builtin_popcount(PVM)>();
          fence_regs(S);
          RELEASE(ck);
          if (shifted) {
#pragma unroll
            for (int i = 0; i < 64; i++) S[i] -= (i & 2) ? m1 : m0;
          }
          wg_wait<__builtin_popcount(PVM) - 1>();
          EXPC(0); EXPC(1); EXPC(2); EXPC(3); EXPC(4); EXPC(5); EXPC(6); EXPC(7);
          chk = s0 + s1;
        }
      }
      TRC(3);
      if (wg == 1) { TS(1, 1); TSC(1, 3); }
    }
    __syncwarp();
    const uint32_t unit = item & 255;
    if (unit < 64) {
      const int mblk = (7 - (p.unit[unit][0] >> 1)) * 2 + rank, nhalf = p.unit[unit][0] & 1, ks = p.unit[unit][1];
      const int k0 = 0, k1 = p.unit[unit][2];
      float acc[144];
      uint32_t s = rot, ph = 0, prev = 0;
      if (wg == 0) { TS(2, 0); TSC(2, 2); }
      uint32_t fa[16], fb[16];
      const uint32_t aoff = (wg * 64 + warp * 16 + (lane & 15)) * 128 + (((lane >> 4) ^ (lane & 7)) << 4);
#define C_LOAD(F)                                                                                              \
  do {                                                                                                         \
    mbar_wait(b3F + s * 8, ph);                                                                                \
    _Pragma("unroll") for (int t = 0; t < 4; t++)                                                              \
        ldsm_x4(F[4 * t], F[4 * t + 1], F[4 * t + 2], F[4 * t + 3], sbase + s * K3_STAGE + (aoff ^ (t * 32))); \
  } while (0)
#define C_STEP(F, G)                                                                                           \
  {                                                                                                            \
    const uint32_t st = sbase + s * K3_STAGE;                                                                  \
    const uint64_t db = make_desc(st + 16384, 4096, 1024, 1), dt = make_desc(st + 49152, 16, 512, 2);          \
    wg_fence();                                                                                                \
    _Pragma("unroll") for (int t = 0; t < 4; t++) {                                                            \
      const int sd = (t > 0) || (k > k0);                                                                      \
      wgmma_rs_n256<1, 0>(acc, F[4 * t], F[4 * t + 1], F[4 * t + 2], F[4 * t + 3], db + (uint64_t)((t >> 1) * 1024 + (t & 1) * 128), sd); \
      wgmma_rs_n32<1, 128>(acc, F[4 * t], F[4 * t + 1], F[4 * t + 2], F[4 * t + 3], dt + (uint64_t)(t * 64), sd); \
    }                                                                                                          \
    wg_commit();                                                                                               \
    wg_wait<1>();                                                                                              \
    fence_regs(G);                                                                                             \
    mbar_arrive_cluster_if(b3E + prev * 8, warp & 1, sig && k > k0);                                           \
    prev = s;                                                                                                  \
    s = (s + 1) & 3;                                                                                           \
    if (s == rot) ph ^= 1;                                                                                     \
    TCK(k + 1);                                                                                                \
    if (++k == k1) break;                                                                                      \
    C_LOAD(G);                                                                                                 \
  }
      TCK(0);
      C_LOAD(fa);
#pragma unroll
      for (int i = 0; i < 16; i++) fb[i] = 0;
#pragma unroll 1
      for (int k = k0;;) {
        C_STEP(fa, fb)
        C_STEP(fb, fa)
      }
      wg_wait<0>();
      fence_regs(acc);
      cluster_arrive();
      if (wg == 0) TS(2, 4);
      const int tile = mblk * 2 + nhalf;
      uint4* wp = g_part + (size_t)((tile * 4 + ks) * 4) * 5 * 256 + tid;
      const uint32_t sown = sbase + wg * 8192 + (tid & 127) * 16;
#pragma unroll
      for (int d = 0; d < 4; d++) {
        if (d != ks) {
#pragma unroll
          for (int i = 0; i < 4; i++)
            __stcg(wp + (d * 5 + i) * 256,
                   make_uint4(pack_bf16(acc[d * 32 + i * 8], acc[d * 32 + i * 8 + 1]), pack_bf16(acc[d * 32 + i * 8 + 2], acc[d * 32 + i * 8 + 3]),
                              pack_bf16(acc[d * 32 + i * 8 + 4], acc[d * 32 + i * 8 + 5]), pack_bf16(acc[d * 32 + i * 8 + 6], acc[d * 32 + i * 8 + 7])));
          __stcg(reinterpret_cast<uint2*>(wp - tid + (d * 5 + 4) * 256) + tid,
                 make_uint2(pack_bf16(acc[128 + d * 4], acc[128 + d * 4 + 1]), pack_bf16(acc[128 + d * 4 + 2], acc[128 + d * 4 + 3])));
        } else {
#pragma unroll
          for (int i = 0; i < 9; i++) {
            const int o = (i < 8) ? d * 32 + i * 4 : 128 + d * 4;
            asm volatile("st.shared.v4.f32 [%0], {%1, %2, %3, %4};" ::"r"(sown + (i >> 2) * K3_STAGE + (i & 3) * 2048), "f"(acc[o]), "f"(acc[o + 1]), "f"(acc[o + 2]), "f"(acc[o + 3]) : "memory");
          }
        }
      }
      __threadfence();
      __syncwarp();
      if (wg == 0) TS(2, 5);
      if (lane == 0) {
        unsigned int* cnt = &g_sync[F_XCH + tile * 8 + warp_g];
        const uint32_t xtarget = lds32(sGate + 64) * 4 + 4;
        atomicAdd(cnt, 1u);
        uint32_t v, spins = 0;
        do {
          asm volatile("ld.acquire.gpu.global.u32 %0, [%1];" : "=r"(v) : "l"(cnt) : "memory");
        } while ((int)(v - xtarget) < 0 && ++spins < (1u << 24));
      }
      __syncwarp();
      if (wg == 0) TS(2, 6);
      float r[36];
#pragma unroll
      for (int i = 0; i < 9; i++)
        asm volatile("ld.shared.v4.f32 {%0, %1, %2, %3}, [%4];" : "=f"(r[i * 4]), "=f"(r[i * 4 + 1]), "=f"(r[i * 4 + 2]), "=f"(r[i * 4 + 3])
                     : "r"(sown + (i >> 2) * K3_STAGE + (i & 3) * 2048) : "memory");
#pragma unroll
      for (int sI = 1; sI < 4; sI++) {
        const int src = (ks + sI) & 3;
        const uint4* rp = g_part + (size_t)(((tile * 4 + src) * 4) + ks) * 5 * 256;
#pragma unroll
        for (int i = 0; i < 4; i++) {
          const uint4 v = __ldcg(rp + i * 256 + tid);
          r[i * 8] += bf_lo(v.x); r[i * 8 + 1] += bf_hi(v.x); r[i * 8 + 2] += bf_lo(v.y); r[i * 8 + 3] += bf_hi(v.y);
          r[i * 8 + 4] += bf_lo(v.z); r[i * 8 + 5] += bf_hi(v.z); r[i * 8 + 6] += bf_lo(v.w); r[i * 8 + 7] += bf_hi(v.w);
        }
        const uint2 v = __ldcg(reinterpret_cast<const uint2*>(rp + 4 * 256) + tid);
        r[32] += bf_lo(v.x); r[33] += bf_hi(v.x); r[34] += bf_lo(v.y); r[35] += bf_hi(v.y);
      }
      const int row = mblk * 128 + wg * 64 + warp * 16 + (lane >> 2);
      bf16* o0 = out + (size_t)row * DM + nhalf * 256 + ks * 64 + 8 * q;
#pragma unroll
      for (int G = 0; G < 2; G++) {
        uint32_t a0 = pack_bf16(r[G * 16], r[G * 16 + 1]), a1 = pack_bf16(r[G * 16 + 4], r[G * 16 + 5]);
        uint32_t a2 = pack_bf16(r[G * 16 + 8], r[G * 16 + 9]), a3 = pack_bf16(r[G * 16 + 12], r[G * 16 + 13]);
        uint32_t b0 = pack_bf16(r[G * 16 + 2], r[G * 16 + 3]), b1 = pack_bf16(r[G * 16 + 6], r[G * 16 + 7]);
        uint32_t b2 = pack_bf16(r[G * 16 + 10], r[G * 16 + 11]), b3 = pack_bf16(r[G * 16 + 14], r[G * 16 + 15]);
        quad_transpose(a0, a1, a2, a3, q);
        quad_transpose(b0, b1, b2, b3, q);
        st_v4(o0 + G * 32, a0, a1, a2, a3);
        st_v4(o0 + 8 * DM + G * 32, b0, b1, b2, b3);
      }
      {
        uint32_t t0 = pack_bf16(r[32], r[33]), t1 = pack_bf16(r[34], r[35]), t2 = 0, t3 = 0;
        quad_transpose(t0, t1, t2, t3, q);
        if (q < 2) st_v4(out + (size_t)(row + q * 8) * DM + 512 + nhalf * 32 + ks * 8, t0, t1, t2, t3);
      }
    } else {
      cluster_arrive();
    }
    if (wg == 0) { TS(2, 1); TSC(2, 3); }
    cluster_wait();
  }
}

typedef CUresult (*EncFn)(CUtensorMap*, CUtensorMapDataType, cuuint32_t, void*, const cuuint64_t*, const cuuint64_t*, const cuuint32_t*,
                          const cuuint32_t*, CUtensorMapInterleave, CUtensorMapSwizzle, CUtensorMapL2promotion, CUtensorMapFloatOOBfill);

static void enc2d(EncFn enc, CUtensorMap* m, const void* ptr, uint64_t cols, uint64_t rows, uint32_t bc, uint32_t br,
                  CUtensorMapSwizzle sw = CU_TENSOR_MAP_SWIZZLE_128B) {
  cuuint64_t gd[2] = {cols, rows}, gs[1] = {cols * 2};
  cuuint32_t bx[2] = {bc, br}, es[2] = {1, 1};
  enc(m, CU_TENSOR_MAP_DATA_TYPE_BFLOAT16, 2, const_cast<void*>(ptr), gd, gs, bx, es, CU_TENSOR_MAP_INTERLEAVE_NONE, sw,
      CU_TENSOR_MAP_L2_PROMOTION_L2_256B, CU_TENSOR_MAP_FLOAT_OOB_FILL_NONE);
}
static void enc3d(EncFn enc, CUtensorMap* m, const void* ptr, uint64_t cols, uint64_t rows, uint32_t br, uint32_t bch) {
  cuuint64_t gd[3] = {64, rows, cols / 64}, gs[2] = {cols * 2, 128};
  cuuint32_t bx[3] = {64, br, bch}, es[3] = {1, 1, 1};
  enc(m, CU_TENSOR_MAP_DATA_TYPE_BFLOAT16, 3, const_cast<void*>(ptr), gd, gs, bx, es, CU_TENSOR_MAP_INTERLEAVE_NONE,
      CU_TENSOR_MAP_SWIZZLE_128B, CU_TENSOR_MAP_L2_PROMOTION_L2_256B, CU_TENSOR_MAP_FLOAT_OOB_FILL_NONE);
}

static int g_sched[10] = {11, 10, 7, 4, 4, 4, 6, 8, 6, 24};
static void build_k1_jobs(Params& p) {
  int cnt[NCLUSTER];
  for (int c = 0; c < NCLUSTER; c++) {
    cnt[c] = 0;
    for (int i = 0; i <= K1_MAXJOBS; i++) p.jobs[c][i] = 0;
  }
  auto add = [&](int c, int nch, int a_sel, int mp, int w_sel, int chunk0) {
    p.jobs[c][cnt[c]++] = (uint16_t)((nch - 1) | (a_sel << 2) | (mp << 3) | (w_sel << 6) | (chunk0 << 8));
  };
  const char* plan = "ccccccccccc cccccccccc ccccccc cccc xxxx xxxx xxxxxx xxxxxxxx";
  int TIE = 0;
  int XA = 0;
  const char* cur[8];
  int tend[8] = {};
  for (int g = 0; g < 8; g++) {
    cur[g] = plan;
    while (*plan == 'c' || *plan == 'x') plan++;
    if (*plan) plan++;
  }
  int kc = 0, kx = 0;
  for (;;) {
    int b = -1, bt = 0;
    for (int g = 0; g < 8; g++) {
      const int t = tend[g] + (*cur[g] == 'x' ? 94 : 85);
      if ((*cur[g] == 'c' || *cur[g] == 'x') && (b < 0 || t < bt || (TIE && t == bt))) { b = g; bt = t; }
    }
    if (b < 0) break;
    const int a = kx - XA;
    for (int mp = 0; mp < 8; mp++) {
      if (*cur[b] == 'c') add(b * 8 + mp, 4, 0, mp, kc & 1, (kc >> 1) * 4);
      else if (a >= 0 && a < 7) add(b * 8 + mp, a == 0 ? 3 : 4, 1, mp, 2, a == 0 ? 24 : (a - 1) * 4);
      else add(b * 8 + mp, 4, 1, mp, 3, (a < 0 ? kx : kx - 7) * 4);
    }
    if (*cur[b] == 'c') kc++; else kx++;
    cur[b]++;
    tend[b] = bt;
  }
  for (int mp = 0; mp < 8; mp++) add(64 + mp / 4, 4, 1, mp, 3, 15 * 4);
  for (int cc = 0; cc < NCLUSTER; cc++)
    for (int i = 0; i < cnt[cc]; i++) {
      const int key = p.jobs[cc][i] & 0x3C;
      if (i == 0 || (p.jobs[cc][i - 1] & 0x3C) != key) p.jobs[cc][i] |= (1 << 14);
      if (i == cnt[cc] - 1 || (p.jobs[cc][i + 1] & 0x3C) != key) p.jobs[cc][i] |= (1 << 15);
    }
}

static void build_k2_items(Params& p) {
  int n = 0;
  const int SCHED_N1 = g_sched[8], SCHED_N2 = g_sched[9];
  int N0 = 2, J0 = 2;
  for (int j = 7; j >= J0; j--)
    for (int h = 0; h < N0; h++) p.order[n++] = (uint8_t)(h * 8 + j);
  for (int j = 7; j >= 0; j--)
    for (int h = 0; h < SCHED_N1; h++)
      if (!(h < N0 && j >= J0)) p.order[n++] = (uint8_t)(h * 8 + j);
  for (int j = 7; j >= 4; j--)
    for (int h = SCHED_N1; h < SCHED_N2; h++) p.order[n++] = (uint8_t)(h * 8 + j);
  for (int j = 7; j >= 0; j--)
    for (int h = SCHED_N1; h < 32; h++)
      if (!(h < SCHED_N2 && j >= 4)) p.order[n++] = (uint8_t)(h * 8 + j);
}

static void build_k3_units(Params& p) {
  float slope = 0.045f;
  int NE = 25;
  for (int t = 0; t < 16; t++) {
    const int u[4] = {t, 31 - t, 32 + t, 63 - t};
    float acc = 0.f;
    int k0 = 0, l0 = NE;
    for (int i = 0; i < 4; i++) {
      acc += 18.25f + slope * (31.5f - u[i]);
      const int k1 = (i == 3) ? 73 : (int)(acc + 0.5f);
      const int e0 = NE * i / 4, e1 = NE * (i + 1) / 4;
      uint8_t* w = p.unit[u[i]];
      w[0] = (uint8_t)t; w[1] = (uint8_t)i; w[2] = (uint8_t)(k1 - k0); w[3] = (uint8_t)e0; w[4] = (uint8_t)(e1 - e0); w[5] = (uint8_t)(l0 - e1);
      l0 += (k1 - k0) - (e1 - e0);
      k0 = k1;
    }
  }
}

extern "C" void kernel_launch(void* const* d_in, const int* in_sizes, int n_in, void* d_out, int out_size) {
  const bf16* x = (const bf16*)d_in[0];
  const bf16* wqkv = (const bf16*)d_in[1];
  const bf16* wo = (const bf16*)d_in[2];
  const bf16* ckv = (const bf16*)d_in[4];
  const bf16* w_q = (const bf16*)d_in[5];
  const bf16* w_uk = (const bf16*)d_in[6];
  const bf16* w_uv = (const bf16*)d_in[7];
  const bf16* w_o = (const bf16*)d_in[8];
  const bf16* gate_w = (const bf16*)d_in[9];

  EncFn enc = nullptr;
  cudaDriverEntryPointQueryResult qr;
  cudaGetDriverEntryPoint("cuTensorMapEncodeTiled", (void**)&enc, cudaEnableDefault, &qr);
  void *pK, *pV, *pCtx, *pQA;
  cudaGetSymbolAddress(&pQA, g_QKVA);
  cudaGetSymbolAddress(&pK, g_K);
  cudaGetSymbolAddress(&pV, g_V);
  cudaGetSymbolAddress(&pCtx, g_ctx);

  static Params p;
  enc2d(enc, &p.tmA[0], ckv, DC, S_LEN, 64, 128);
  enc2d(enc, &p.tmA[1], x, DM, S_LEN, 64, 128);
  enc3d(enc, &p.tmW[0], w_uk, HDIM, DC, 16, 4);
  enc3d(enc, &p.tmW[1], w_uv, HDIM, DC, 16, 4);
  enc3d(enc, &p.tmW[2], wqkv, NQKVA, DM, 16, 4);
  enc3d(enc, &p.tmW[3], w_q, HDIM, DM, 16, 4);
  build_k1_jobs(p);
  enc2d(enc, &p.tmK, pK, HDIM, S_LEN, 64, 128);
  enc2d(enc, &p.tmV, pV, HDIM, S_LEN, 64, 128);
  build_k2_items(p);
  build_k3_units(p);
  for (int i = 0; i < 3; i++) {
    const cuuint64_t ld = (i < 2 ? NQKVA : KCAT) * 2, nch = (i < 2) ? 27 : 9;
    cuuint64_t gd[4] = {64, S_LEN / 2, i ? 2 : nch, i ? nch : 2}, gs[3] = {2 * ld, i ? ld : 128, i ? 128 : ld};
    cuuint32_t bx[4] = {64, i ? 8u : 16u, i ? 2u : 9u, i ? 9u : 2u}, es[4] = {1, 1, 1, 1};
    enc(&p.tmL[i], CU_TENSOR_MAP_DATA_TYPE_BFLOAT16, 4, (i < 2) ? pQA : (void*)((bf16*)pCtx + HDIM), gd, gs, bx, es, CU_TENSOR_MAP_INTERLEAVE_NONE,
        CU_TENSOR_MAP_SWIZZLE_128B, CU_TENSOR_MAP_L2_PROMOTION_L2_256B, CU_TENSOR_MAP_FLOAT_OOB_FILL_NONE);
  }
  enc2d(enc, &p.tmC, pCtx, KCAT, S_LEN, 64, 128);
  enc3d(enc, &p.tmO[0], w_o, DM, HDIM, 32, 4);
  enc3d(enc, &p.tmO[1], wo, DM, DM, 32, 4);
  enc2d(enc, &p.tmOt[0], w_o, DM, HDIM, 32, 32, CU_TENSOR_MAP_SWIZZLE_64B);
  enc2d(enc, &p.tmOt[1], wo, DM, DM, 32, 32, CU_TENSOR_MAP_SWIZZLE_64B);

  cudaFuncSetAttribute(fused_kernel, cudaFuncAttributeMaxDynamicSharedMemorySize, SMEM_BYTES);
  fused_kernel<<<NCLUSTER * 2, 384, SMEM_BYTES>>>(p, x, gate_w, (bf16*)d_out);
}
```

```cpp
#include <cuda_runtime.h>
#include <cuda_bf16.h>
#include <cuda.h>
#include <stdint.h>

typedef __nv_bfloat16 bf16;

constexpr int S_LEN = 2048, DM = 576, DC = 512, HDIM = 4096, NQKVA = 1728, KCAT = 4672;
constexpr int NCLUSTER = 66;

__device__ __align__(1024) bf16 g_K[S_LEN * HDIM];
__device__ __align__(1024) bf16 g_V[S_LEN * HDIM];
__device__ __align__(1024) bf16 g_QKVA[S_LEN * NQKVA + 64];
__device__ __align__(1024) bf16 g_ctx[S_LEN * KCAT];
__device__ float g_gate[S_LEN];
__device__ __align__(1024) uint4 g_part[32 * 4 * 4 * 5 * 256];
__device__ __align__(16) unsigned int g_sync[400];
constexpr int F_QKVA = 0, F_HP = 16, F_CTX = 32, F_OA = 48, F_GATE = 96, F_TICK = 97, F_DONE = 98, F_XCH = 128, F_EPOCH = 384;

__device__ __forceinline__ uint32_t smem_u32(const void* p) { return (uint32_t)__cvta_generic_to_shared(p); }
__device__ __forceinline__ void mbar_init(uint32_t a, uint32_t c) {
  asm volatile("mbarrier.init.shared::cta.b64 [%0], %1;" ::"r"(a), "r"(c));
}
__device__ __forceinline__ void mbar_expect(uint32_t a, uint32_t b) {
  asm volatile("mbarrier.arrive.expect_tx.shared::cta.b64 _, [%0], %1;" ::"r"(a), "r"(b) : "memory");
}
#define TS(k, i)
#define TSC(k, i)
#define TSM(k)
#define BSEG(i)
#define TB(k)
#define TRC(fl)
#define TCK(i)
#define SPIN_LIMIT "4194304"
__device__ __forceinline__ void mbar_wait(uint32_t a, uint32_t parity) {
  asm volatile(
      "{\n.reg .pred p;\n.reg .u32 n;\n"
      "mbarrier.try_wait.parity.shared::cta.b64 p, [%0], %1;\n"
      "@p bra DONE;\n"
      "mov.u32 n, 0;\n"
      "LOOP:\n"
      "mbarrier.try_wait.parity.shared::cta.b64 p, [%0], %1;\n"
      "@p bra DONE;\n"
      "add.u32 n, n, 1;\n"
      "setp.lt.u32 p, n, " SPIN_LIMIT ";\n"
      "@p bra LOOP;\n"
      "DONE:\n}" ::"r"(a), "r"(parity) : "memory");
}
template <int NS>
__device__ __forceinline__ void mbar_wait_ns(uint32_t a, uint32_t parity) {
  asm volatile(
      "{\n.reg .pred p;\n.reg .u32 n;\n"
      "mov.u32 n, 0;\n"
      "LOOP:\n"
      "mbarrier.try_wait.parity.shared::cta.b64 p, [%0], %1, %2;\n"
      "@p bra DONE;\n"
      "add.u32 n, n, 1;\n"
      "setp.lt.u32 p, n, " SPIN_LIMIT ";\n"
      "@p bra LOOP;\n"
      "DONE:\n}" ::"r"(a), "r"(parity), "n"(NS) : "memory");
}
__device__ __forceinline__ void mbar_wait2(uint32_t a, uint32_t pa, uint32_t b, uint32_t pb) {
  asm volatile(
      "{\n.reg .pred p, q;\n.reg .u32 n;\n"
      "mov.u32 n, 0;\n"
      "LOOP:\n"
      "mbarrier.try_wait.parity.shared::cta.b64 p, [%0], %1;\n"
      "mbarrier.try_wait.parity.shared::cta.b64 q, [%2], %3;\n"
      "add.u32 n, n, 1;\n"
      "and.pred p, p, q;\n"
      "setp.lt.and.u32 p, n, " SPIN_LIMIT ", !p;\n"
      "@p bra LOOP;\n"
      "}" ::"r"(a), "r"(pa), "r"(b), "r"(pb) : "memory");
}
__device__ __forceinline__ uint32_t mbar_test(uint32_t a, uint32_t parity) {
  uint32_t r;
  asm volatile("{\n.reg .pred p;\nmbarrier.test_wait.parity.shared::cta.b64 p, [%1], %2;\nselp.u32 %0, 1, 0, p;\n}" : "=r"(r) : "r"(a), "r"(parity) : "memory");
  return r;
}
__device__ __forceinline__ void mbar_arrive(uint32_t a) {
  asm volatile("mbarrier.arrive.shared::cta.b64 _, [%0];" ::"r"(a) : "memory");
}
__device__ __forceinline__ void mbar_arrive_cluster(uint32_t a, uint32_t cta) {
  asm volatile("{\n.reg .b32 r;\nmapa.shared::cluster.u32 r, %0, %1;\nmbarrier.arrive.shared::cluster.b64 _, [r];\n}" ::"r"(a),
               "r"(cta) : "memory");
}
__device__ __forceinline__ void mbar_arrive_cluster_if(uint32_t a, uint32_t cta, bool pred) {
  asm volatile("{\n.reg .b32 r;\n.reg .pred p;\nsetp.ne.u32 p, %2, 0;\nmapa.shared::cluster.u32 r, %0, %1;\n@p mbarrier.arrive.shared::cluster.b64 _, [r];\n}" ::"r"(a),
               "r"(cta), "r"((uint32_t)pred) : "memory");
}
__device__ __forceinline__ void anchor(float v, uint32_t pred) {
  asm volatile("{\n.reg .pred p;\nsetp.ne.u32 p, %1, 0;\n@p st.shared.f32 [%1], %0;\n}" ::"f"(v), "r"(pred) : "memory");
}
__device__ __forceinline__ void mbar_arrive_if(uint32_t a, bool pred) {
  asm volatile("{\n.reg .pred p;\nsetp.ne.u32 p, %1, 0;\n@p mbarrier.arrive.shared::cta.b64 _, [%0];\n}" ::"r"(a), "r"((uint32_t)pred) : "memory");
}
__device__ __forceinline__ void tma2d(uint32_t dst, const CUtensorMap* m, uint32_t bar, int c0, int c1) {
  asm volatile("cp.async.bulk.tensor.2d.shared::cluster.global.mbarrier::complete_tx::bytes [%0], [%1, {%3, %4}], [%2];" ::"r"(dst),
               "l"(m), "r"(bar), "r"(c0), "r"(c1) : "memory");
}
__device__ __forceinline__ void tma2d_mc(uint32_t dst, const CUtensorMap* m, uint32_t bar, int c0, int c1, uint16_t mask) {
  asm volatile(
      "cp.async.bulk.tensor.2d.shared::cluster.global.mbarrier::complete_tx::bytes.multicast::cluster [%0], [%1, {%3, %4}], [%2], %5;" ::"r"(dst),
      "l"(m), "r"(bar), "r"(c0), "r"(c1), "h"(mask) : "memory");
}
__device__ __forceinline__ void tma3d_mc(uint32_t dst, const CUtensorMap* m, uint32_t bar, int c0, int c1, int c2, uint16_t mask) {
  asm volatile(
      "cp.async.bulk.tensor.3d.shared::cluster.global.mbarrier::complete_tx::bytes.multicast::cluster [%0], [%1, {%3, %4, %5}], [%2], %6;" ::"r"(dst),
      "l"(m), "r"(bar), "r"(c0), "r"(c1), "r"(c2), "h"(mask) : "memory");
}
__device__ __forceinline__ void tma3d(uint32_t dst, const CUtensorMap* m, uint32_t bar, int c0, int c1, int c2) {
  asm volatile(
      "cp.async.bulk.tensor.3d.shared::cluster.global.mbarrier::complete_tx::bytes [%0], [%1, {%3, %4, %5}], [%2];" ::"r"(dst),
      "l"(m), "r"(bar), "r"(c0), "r"(c1), "r"(c2) : "memory");
}
__device__ __forceinline__ void tma_pf2d(const CUtensorMap* m, int c0, int c1) {
  asm volatile("cp.async.bulk.prefetch.tensor.2d.L2.global [%0, {%1, %2}];" ::"l"(m), "r"(c0), "r"(c1) : "memory");
}
__device__ __forceinline__ void tma_pf3d(const CUtensorMap* m, int c0, int c1, int c2) {
  asm volatile("cp.async.bulk.prefetch.tensor.3d.L2.global [%0, {%1, %2, %3}];" ::"l"(m), "r"(c0), "r"(c1), "r"(c2) : "memory");
}
__device__ __forceinline__ void prefetch_tmap(const CUtensorMap* m) {
  asm volatile("prefetch.tensormap [%0];" ::"l"(m) : "memory");
}
__device__ __forceinline__ void cluster_arrive() { asm volatile("barrier.cluster.arrive.relaxed.aligned;" ::: "memory"); }
__device__ __forceinline__ void cluster_wait() { asm volatile("barrier.cluster.wait.aligned;" ::: "memory"); }
__device__ __forceinline__ void cluster_sync() {
  cluster_arrive();
  cluster_wait();
}
__device__ __forceinline__ uint32_t cluster_rank() {
  uint32_t r;
  asm volatile("mov.u32 %0, %%cluster_ctarank;" : "=r"(r));
  return r;
}
__device__ __forceinline__ bool elect_one() {
  uint32_t p;
  asm volatile("{\n.reg .pred q;\nelect.sync _|q, 0xffffffff;\nselp.u32 %0, 1, 0, q;\n}" : "=r"(p));
  return p;
}
__device__ __forceinline__ void ldsm_x4(uint32_t& r0, uint32_t& r1, uint32_t& r2, uint32_t& r3, uint32_t addr) {
  asm volatile("ldmatrix.sync.aligned.m8n8.x4.shared.b16 {%0, %1, %2, %3}, [%4];" : "=r"(r0), "=r"(r1), "=r"(r2), "=r"(r3) : "r"(addr) : "memory");
}
__device__ __forceinline__ void wg_fence() { asm volatile("wgmma.fence.sync.aligned;" ::: "memory"); }
__device__ __forceinline__ void wg_commit() { asm volatile("wgmma.commit_group.sync.aligned;" ::: "memory"); }
template <int N>
__device__ __forceinline__ void wg_wait() { asm volatile("wgmma.wait_group.sync.aligned %0;" ::"n"(N) : "memory"); }
template <int N>
__device__ __forceinline__ void reg_alloc() { asm volatile("setmaxnreg.inc.sync.aligned.u32 %0;" ::"n"(N)); }
template <int N>
__device__ __forceinline__ void reg_dealloc() { asm volatile("setmaxnreg.dec.sync.aligned.u32 %0;" ::"n"(N)); }
__device__ __forceinline__ void bar_sync(int id, int n) { asm volatile("bar.sync %0, %1;" ::"r"(id), "r"(n) : "memory"); }
__device__ __forceinline__ void bar_arrive(int id, int n) { asm volatile("bar.arrive %0, %1;" ::"r"(id), "r"(n) : "memory"); }
template <int NT>
__device__ __forceinline__ void fence_regs(float (&d)[NT]) {
#pragma unroll
  for (int i = 0; i < NT; i++) asm volatile("" : "+f"(d[i])::"memory");
}
template <int NT>
__device__ __forceinline__ void fence_regs(uint32_t (&d)[NT]) {
#pragma unroll
  for (int i = 0; i < NT; i++) asm volatile("" : "+r"(d[i])::"memory");
}
__device__ __forceinline__ uint64_t make_desc(uint32_t saddr, uint32_t lbo, uint32_t sbo, uint32_t layout) {
  return (uint64_t)((saddr & 0x3FFFF) >> 4) | ((uint64_t)(lbo >> 4) << 16) | ((uint64_t)(sbo >> 4) << 32) | ((uint64_t)layout << 62);
}
__device__ __forceinline__ uint32_t pack_bf16(float lo, float hi) {
  uint32_t r;
  asm("cvt.rn.bf16x2.f32 %0, %1, %2;" : "=r"(r) : "f"(hi), "f"(lo));
  return r;
}
__device__ __forceinline__ float ex2(float x) {
  float r;
  asm("ex2.approx.ftz.f32 %0, %1;" : "=f"(r) : "f"(x));
  return r;
}
__device__ __forceinline__ void st_v4(void* p, uint32_t a, uint32_t b, uint32_t c, uint32_t d) {
#define ST_MOD ".cs"
  asm volatile("st.global" ST_MOD ".v4.b32 [%0], {%1, %2, %3, %4};" ::"l"(p), "r"(a), "r"(b), "r"(c), "r"(d) : "memory");
}
#define STA_MOD ".cs"
__device__ __forceinline__ void st_v4a(void* p, uint32_t a, uint32_t b, uint32_t c, uint32_t d) {
  asm volatile("st.global" STA_MOD ".v4.b32 [%0], {%1, %2, %3, %4};" ::"l"(p), "r"(a), "r"(b), "r"(c), "r"(d) : "memory");
}
template <typename T>
__device__ __forceinline__ T* ptr_add(T* base, uint32_t bytes) {
  uint64_t r;
  asm volatile("{\n.reg .u32 l, h;\nmov.b64 {l, h}, %1;\nadd.cc.u32 l, l, %2;\naddc.u32 h, h, 0;\nmov.b64 %0, {l, h};\n}" : "=l"(r) : "l"(base), "r"(bytes));
  return reinterpret_cast<T*>(r);
}
__device__ __forceinline__ float bf_lo(uint32_t v) { return __uint_as_float(v << 16); }
__device__ __forceinline__ float bf_hi(uint32_t v) { return __uint_as_float(v & 0xFFFF0000u); }

__device__ __forceinline__ void quad_transpose(uint32_t& a0, uint32_t& a1, uint32_t& a2, uint32_t& a3, int q) {
  const bool o1 = q & 1, o2 = q & 2;
  uint32_t t0 = o1 ? a0 : a1, t1 = o1 ? a2 : a3;
  t0 = __shfl_xor_sync(0xffffffffu, t0, 1);
  t1 = __shfl_xor_sync(0xffffffffu, t1, 1);
  if (o1) { a0 = t0; a2 = t1; } else { a1 = t0; a3 = t1; }
  t0 = o2 ? a0 : a2;
  t1 = o2 ? a1 : a3;
  t0 = __shfl_xor_sync(0xffffffffu, t0, 2);
  t1 = __shfl_xor_sync(0xffffffffu, t1, 2);
  if (o2) { a0 = t0; a1 = t1; } else { a2 = t0; a3 = t1; }
}

template<int TB, int OFF, int NT>
__device__ __forceinline__ void wgmma_ss_n256(float (&d)[NT], uint64_t da, uint64_t db, int scale_d) {
  asm volatile("{\n.reg .pred p;\nsetp.ne.b32 p, %130, 0;\n"
    "wgmma.mma_async.sync.aligned.m64n256k16.f32.bf16.bf16 {%0, %1, %2, %3, %4, %5, %6, %7, %8, %9, %10, %11, %12, %13, %14, %15, %16, %17, %18, %19, %20, %21, %22, %23, %24, %25, %26, %27, %28, %29, %30, %31, %32, %33, %34, %35, %36, %37, %38, %39, %40, %41, %42, %43, %44, %45, %46, %47, %48, %49, %50, %51, %52, %53, %54, %55, %56, %57, %58, %59, %60, %61, %62, %63, %64, %65, %66, %67, %68, %69, %70, %71, %72, %73, %74, %75, %76, %77, %78, %79, %80, %81, %82, %83, %84, %85, %86, %87, %88, %89, %90, %91, %92, %93, %94, %95, %96, %97, %98, %99, %100, %101, %102, %103, %104, %105, %106, %107, %108, %109, %110, %111, %112, %113, %114, %115, %116, %117, %118, %119, %120, %121, %122, %123, %124, %125, %126, %127}, %128, %129, p, 1, 1, 0, %131;\n}\n"
    : "+f"(d[OFF+0]), "+f"(d[OFF+1]), "+f"(d[OFF+2]), "+f"(d[OFF+3]), "+f"(d[OFF+4]), "+f"(d[OFF+5]), "+f"(d[OFF+6]), "+f"(d[OFF+7]), "+f"(d[OFF+8]), "+f"(d[OFF+9]), "+f"(d[OFF+10]), "+f"(d[OFF+11]), "+f"(d[OFF+12]), "+f"(d[OFF+13]), "+f"(d[OFF+14]), "+f"(d[OFF+15]), "+f"(d[OFF+16]), "+f"(d[OFF+17]), "+f"(d[OFF+18]), "+f"(d[OFF+19]), "+f"(d[OFF+20]), "+f"(d[OFF+21]), "+f"(d[OFF+22]), "+f"(d[OFF+23]), "+f"(d[OFF+24]), "+f"(d[OFF+25]), "+f"(d[OFF+26]), "+f"(d[OFF+27]), "+f"(d[OFF+28]), "+f"(d[OFF+29]), "+f"(d[OFF+30]), "+f"(d[OFF+31]), "+f"(d[OFF+32]), "+f"(d[OFF+33]), "+f"(d[OFF+34]), "+f"(d[OFF+35]), "+f"(d[OFF+36]), "+f"(d[OFF+37]), "+f"(d[OFF+38]), "+f"(d[OFF+39]), "+f"(d[OFF+40]), "+f"(d[OFF+41]), "+f"(d[OFF+42]), "+f"(d[OFF+43]), "+f"(d[OFF+44]), "+f"(d[OFF+45]), "+f"(d[OFF+46]), "+f"(d[OFF+47]), "+f"(d[OFF+48]), "+f"(d[OFF+49]), "+f"(d[OFF+50]), "+f"(d[OFF+51]), "+f"(d[OFF+52]), "+f"(d[OFF+53]), "+f"(d[OFF+54]), "+f"(d[OFF+55]), "+f"(d[OFF+56]), "+f"(d[OFF+57]), "+f"(d[OFF+58]), "+f"(d[OFF+59]), "+f"(d[OFF+60]), "+f"(d[OFF+61]), "+f"(d[OFF+62]), "+f"(d[OFF+63]), "+f"(d[OFF+64]), "+f"(d[OFF+65]), "+f"(d[OFF+66]), "+f"(d[OFF+67]), "+f"(d[OFF+68]), "+f"(d[OFF+69]), "+f"(d[OFF+70]), "+f"(d[OFF+71]), "+f"(d[OFF+72]), "+f"(d[OFF+73]), "+f"(d[OFF+74]), "+f"(d[OFF+75]), "+f"(d[OFF+76]), "+f"(d[OFF+77]), "+f"(d[OFF+78]), "+f"(d[OFF+79]), "+f"(d[OFF+80]), "+f"(d[OFF+81]), "+f"(d[OFF+82]), "+f"(d[OFF+83]), "+f"(d[OFF+84]), "+f"(d[OFF+85]), "+f"(d[OFF+86]), "+f"(d[OFF+87]), "+f"(d[OFF+88]), "+f"(d[OFF+89]), "+f"(d[OFF+90]), "+f"(d[OFF+91]), "+f"(d[OFF+92]), "+f"(d[OFF+93]), "+f"(d[OFF+94]), "+f"(d[OFF+95]), "+f"(d[OFF+96]), "+f"(d[OFF+97]), "+f"(d[OFF+98]), "+f"(d[OFF+99]), "+f"(d[OFF+100]), "+f"(d[OFF+101]), "+f"(d[OFF+102]), "+f"(d[OFF+103]), "+f"(d[OFF+104]), "+f"(d[OFF+105]), "+f"(d[OFF+106]), "+f"(d[OFF+107]), "+f"(d[OFF+108]), "+f"(d[OFF+109]), "+f"(d[OFF+110]), "+f"(d[OFF+111]), "+f"(d[OFF+112]), "+f"(d[OFF+113]), "+f"(d[OFF+114]), "+f"(d[OFF+115]), "+f"(d[OFF+116]), "+f"(d[OFF+117]), "+f"(d[OFF+118]), "+f"(d[OFF+119]), "+f"(d[OFF+120]), "+f"(d[OFF+121]), "+f"(d[OFF+122]), "+f"(d[OFF+123]), "+f"(d[OFF+124]), "+f"(d[OFF+125]), "+f"(d[OFF+126]), "+f"(d[OFF+127])
    : "l"(da), "l"(db), "r"(scale_d), "n"(TB));
}
template<int TB, int OFF, int NT>
__device__ __forceinline__ void wgmma_ss_n32(float (&d)[NT], uint64_t da, uint64_t db, int scale_d) {
  asm volatile("{\n.reg .pred p;\nsetp.ne.b32 p, %18, 0;\n"
    "wgmma.mma_async.sync.aligned.m64n32k16.f32.bf16.bf16 {%0, %1, %2, %3, %4, %5, %6, %7, %8, %9, %10, %11, %12, %13, %14, %15}, %16, %17, p, 1, 1, 0, %19;\n}\n"
    : "+f"(d[OFF+0]), "+f"(d[OFF+1]), "+f"(d[OFF+2]), "+f"(d[OFF+3]), "+f"(d[OFF+4]), "+f"(d[OFF+5]), "+f"(d[OFF+6]), "+f"(d[OFF+7]), "+f"(d[OFF+8]), "+f"(d[OFF+9]), "+f"(d[OFF+10]), "+f"(d[OFF+11]), "+f"(d[OFF+12]), "+f"(d[OFF+13]), "+f"(d[OFF+14]), "+f"(d[OFF+15])
    : "l"(da), "l"(db), "r"(scale_d), "n"(TB));
}
template<int TB, int OFF, int NT>
__device__ __forceinline__ void wgmma_rs_n128(float (&d)[NT], uint32_t a0, uint32_t a1, uint32_t a2, uint32_t a3, uint64_t db, int scale_d) {
  asm volatile("{\n.reg .pred p;\nsetp.ne.b32 p, %69, 0;\n"
    "wgmma.mma_async.sync.aligned.m64n128k16.f32.bf16.bf16 {%0, %1, %2, %3, %4, %5, %6, %7, %8, %9, %10, %11, %12, %13, %14, %15, %16, %17, %18, %19, %20, %21, %22, %23, %24, %25, %26, %27, %28, %29, %30, %31, %32, %33, %34, %35, %36, %37, %38, %39, %40, %41, %42, %43, %44, %45, %46, %47, %48, %49, %50, %51, %52, %53, %54, %55, %56, %57, %58, %59, %60, %61, %62, %63}, {%64, %65, %66, %67}, %68, p, 1, 1, %70;\n}\n"
    : "+f"(d[OFF+0]), "+f"(d[OFF+1]), "+f"(d[OFF+2]), "+f"(d[OFF+3]), "+f"(d[OFF+4]), "+f"(d[OFF+5]), "+f"(d[OFF+6]), "+f"(d[OFF+7]), "+f"(d[OFF+8]), "+f"(d[OFF+9]), "+f"(d[OFF+10]), "+f"(d[OFF+11]), "+f"(d[OFF+12]), "+f"(d[OFF+13]), "+f"(d[OFF+14]), "+f"(d[OFF+15]), "+f"(d[OFF+16]), "+f"(d[OFF+17]), "+f"(d[OFF+18]), "+f"(d[OFF+19]), "+f"(d[OFF+20]), "+f"(d[OFF+21]), "+f"(d[OFF+22]), "+f"(d[OFF+23]), "+f"(d[OFF+24]), "+f"(d[OFF+25]), "+f"(d[OFF+26]), "+f"(d[OFF+27]), "+f"(d[OFF+28]), "+f"(d[OFF+29]), "+f"(d[OFF+30]), "+f"(d[OFF+31]), "+f"(d[OFF+32]), "+f"(d[OFF+33]), "+f"(d[OFF+34]), "+f"(d[OFF+35]), "+f"(d[OFF+36]), "+f"(d[OFF+37]), "+f"(d[OFF+38]), "+f"(d[OFF+39]), "+f"(d[OFF+40]), "+f"(d[OFF+41]), "+f"(d[OFF+42]), "+f"(d[OFF+43]), "+f"(d[OFF+44]), "+f"(d[OFF+45]), "+f"(d[OFF+46]), "+f"(d[OFF+47]), "+f"(d[OFF+48]), "+f"(d[OFF+49]), "+f"(d[OFF+50]), "+f"(d[OFF+51]), "+f"(d[OFF+52]), "+f"(d[OFF+53]), "+f"(d[OFF+54]), "+f"(d[OFF+55]), "+f"(d[OFF+56]), "+f"(d[OFF+57]), "+f"(d[OFF+58]), "+f"(d[OFF+59]), "+f"(d[OFF+60]), "+f"(d[OFF+61]), "+f"(d[OFF+62]), "+f"(d[OFF+63])
    : "r"(a0), "r"(a1), "r"(a2), "r"(a3), "l"(db), "r"(scale_d), "n"(TB));
}
template<int TB, int OFF, int NT>
__device__ __forceinline__ void wgmma_rs_n256(float (&d)[NT], uint32_t a0, uint32_t a1, uint32_t a2, uint32_t a3, uint64_t db, int scale_d) {
  asm volatile("{\n.reg .pred p;\nsetp.ne.b32 p, %133, 0;\n"
    "wgmma.mma_async.sync.aligned.m64n256k16.f32.bf16.bf16 {%0, %1, %2, %3, %4, %5, %6, %7, %8, %9, %10, %11, %12, %13, %14, %15, %16, %17, %18, %19, %20, %21, %22, %23, %24, %25, %26, %27, %28, %29, %30, %31, %32, %33, %34, %35, %36, %37, %38, %39, %40, %41, %42, %43, %44, %45, %46, %47, %48, %49, %50, %51, %52, %53, %54, %55, %56, %57, %58, %59, %60, %61, %62, %63, %64, %65, %66, %67, %68, %69, %70, %71, %72, %73, %74, %75, %76, %77, %78, %79, %80, %81, %82, %83, %84, %85, %86, %87, %88, %89, %90, %91, %92, %93, %94, %95, %96, %97, %98, %99, %100, %101, %102, %103, %104, %105, %106, %107, %108, %109, %110, %111, %112, %113, %114, %115, %116, %117, %118, %119, %120, %121, %122, %123, %124, %125, %126, %127}, {%128, %129, %130, %131}, %132, p, 1, 1, %134;\n}\n"
    : "+f"(d[OFF+0]), "+f"(d[OFF+1]), "+f"(d[OFF+2]), "+f"(d[OFF+3]), "+f"(d[OFF+4]), "+f"(d[OFF+5]), "+f"(d[OFF+6]), "+f"(d[OFF+7]), "+f"(d[OFF+8]), "+f"(d[OFF+9]), "+f"(d[OFF+10]), "+f"(d[OFF+11]), "+f"(d[OFF+12]), "+f"(d[OFF+13]), "+f"(d[OFF+14]), "+f"(d[OFF+15]), "+f"(d[OFF+16]), "+f"(d[OFF+17]), "+f"(d[OFF+18]), "+f"(d[OFF+19]), "+f"(d[OFF+20]), "+f"(d[OFF+21]), "+f"(d[OFF+22]), "+f"(d[OFF+23]), "+f"(d[OFF+24]), "+f"(d[OFF+25]), "+f"(d[OFF+26]), "+f"(d[OFF+27]), "+f"(d[OFF+28]), "+f"(d[OFF+29]), "+f"(d[OFF+30]), "+f"(d[OFF+31]), "+f"(d[OFF+32]), "+f"(d[OFF+33]), "+f"(d[OFF+34]), "+f"(d[OFF+35]), "+f"(d[OFF+36]), "+f"(d[OFF+37]), "+f"(d[OFF+38]), "+f"(d[OFF+39]), "+f"(d[OFF+40]), "+f"(d[OFF+41]), "+f"(d[OFF+42]), "+f"(d[OFF+43]), "+f"(d[OFF+44]), "+f"(d[OFF+45]), "+f"(d[OFF+46]), "+f"(d[OFF+47]), "+f"(d[OFF+48]), "+f"(d[OFF+49]), "+f"(d[OFF+50]), "+f"(d[OFF+51]), "+f"(d[OFF+52]), "+f"(d[OFF+53]), "+f"(d[OFF+54]), "+f"(d[OFF+55]), "+f"(d[OFF+56]), "+f"(d[OFF+57]), "+f"(d[OFF+58]), "+f"(d[OFF+59]), "+f"(d[OFF+60]), "+f"(d[OFF+61]), "+f"(d[OFF+62]), "+f"(d[OFF+63]), "+f"(d[OFF+64]), "+f"(d[OFF+65]), "+f"(d[OFF+66]), "+f"(d[OFF+67]), "+f"(d[OFF+68]), "+f"(d[OFF+69]), "+f"(d[OFF+70]), "+f"(d[OFF+71]), "+f"(d[OFF+72]), "+f"(d[OFF+73]), "+f"(d[OFF+74]), "+f"(d[OFF+75]), "+f"(d[OFF+76]), "+f"(d[OFF+77]), "+f"(d[OFF+78]), "+f"(d[OFF+79]), "+f"(d[OFF+80]), "+f"(d[OFF+81]), "+f"(d[OFF+82]), "+f"(d[OFF+83]), "+f"(d[OFF+84]), "+f"(d[OFF+85]), "+f"(d[OFF+86]), "+f"(d[OFF+87]), "+f"(d[OFF+88]), "+f"(d[OFF+89]), "+f"(d[OFF+90]), "+f"(d[OFF+91]), "+f"(d[OFF+92]), "+f"(d[OFF+93]), "+f"(d[OFF+94]), "+f"(d[OFF+95]), "+f"(d[OFF+96]), "+f"(d[OFF+97]), "+f"(d[OFF+98]), "+f"(d[OFF+99]), "+f"(d[OFF+100]), "+f"(d[OFF+101]), "+f"(d[OFF+102]), "+f"(d[OFF+103]), "+f"(d[OFF+104]), "+f"(d[OFF+105]), "+f"(d[OFF+106]), "+f"(d[OFF+107]), "+f"(d[OFF+108]), "+f"(d[OFF+109]), "+f"(d[OFF+110]), "+f"(d[OFF+111]), "+f"(d[OFF+112]), "+f"(d[OFF+113]), "+f"(d[OFF+114]), "+f"(d[OFF+115]), "+f"(d[OFF+116]), "+f"(d[OFF+117]), "+f"(d[OFF+118]), "+f"(d[OFF+119]), "+f"(d[OFF+120]), "+f"(d[OFF+121]), "+f"(d[OFF+122]), "+f"(d[OFF+123]), "+f"(d[OFF+124]), "+f"(d[OFF+125]), "+f"(d[OFF+126]), "+f"(d[OFF+127])
    : "r"(a0), "r"(a1), "r"(a2), "r"(a3), "l"(db), "r"(scale_d), "n"(TB));
}
template<int TB, int OFF, int NT>
__device__ __forceinline__ void wgmma_rs_n32(float (&d)[NT], uint32_t a0, uint32_t a1, uint32_t a2, uint32_t a3, uint64_t db, int scale_d) {
  asm volatile("{\n.reg .pred p;\nsetp.ne.b32 p, %21, 0;\n"
    "wgmma.mma_async.sync.aligned.m64n32k16.f32.bf16.bf16 {%0, %1, %2, %3, %4, %5, %6, %7, %8, %9, %10, %11, %12, %13, %14, %15}, {%16, %17, %18, %19}, %20, p, 1, 1, %22;\n}\n"
    : "+f"(d[OFF+0]), "+f"(d[OFF+1]), "+f"(d[OFF+2]), "+f"(d[OFF+3]), "+f"(d[OFF+4]), "+f"(d[OFF+5]), "+f"(d[OFF+6]), "+f"(d[OFF+7]), "+f"(d[OFF+8]), "+f"(d[OFF+9]), "+f"(d[OFF+10]), "+f"(d[OFF+11]), "+f"(d[OFF+12]), "+f"(d[OFF+13]), "+f"(d[OFF+14]), "+f"(d[OFF+15])
    : "r"(a0), "r"(a1), "r"(a2), "r"(a3), "l"(db), "r"(scale_d), "n"(TB));
}

__device__ __forceinline__ void wait_flag(const unsigned int* f, uint32_t target) {
  uint32_t v;
#pragma unroll 1
  for (uint32_t spins = 0; spins < (1u << 22); spins++) {
    asm volatile("ld.acquire.gpu.global.u32 %0, [%1];" : "=r"(v) : "l"(f) : "memory");
    if (v >= target) break;
    __nanosleep(100);
  }
}
__device__ __forceinline__ uint32_t lds32(uint32_t a) {
  uint32_t v;
  asm volatile("ld.shared.u32 %0, [%1];" : "=r"(v) : "r"(a) : "memory");
  return v;
}
__device__ __forceinline__ float gate_row(int row, int lane, const bf16* __restrict__ x, const bf16* __restrict__ gate_w) {
  const uint32_t* xr = reinterpret_cast<const uint32_t*>(x + (size_t)row * DM);
  const uint32_t* gw2 = reinterpret_cast<const uint32_t*>(gate_w);
  float gs = 0.f;
#pragma unroll
  for (int i = 0; i < 9; i++) {
    const uint32_t a = __ldg(xr + lane + 32 * i), b = __ldg(gw2 + lane + 32 * i);
    gs = fmaf(bf_lo(a), bf_lo(b), gs);
    gs = fmaf(bf_hi(a), bf_hi(b), gs);
  }
#pragma unroll
  for (int o = 16; o; o >>= 1) gs += __shfl_xor_sync(0xffffffffu, gs, o);
  const float g = 1.f / (1.f + __expf(-gs));
  if (lane == 0) g_gate[row] = g;
  return g;
}
constexpr uint32_t LQ = 36864, LV = 55296;
__device__ __forceinline__ void mma16(float (&c)[4], uint32_t a0, uint32_t a1, uint32_t a2, uint32_t a3, uint32_t b0, uint32_t b1) {
  asm("mma.sync.aligned.m16n8k16.row.col.f32.bf16.bf16.f32 {%0, %1, %2, %3}, {%4, %5, %6, %7}, {%8, %9}, {%0, %1, %2, %3};"
      : "+f"(c[0]), "+f"(c[1]), "+f"(c[2]), "+f"(c[3]) : "r"(a0), "r"(a1), "r"(a2), "r"(a3), "r"(b0), "r"(b1));
}
__device__ __forceinline__ void mma8(float (&c)[4], uint32_t a0, uint32_t a1, uint32_t b0) {
  asm("mma.sync.aligned.m16n8k8.row.col.f32.bf16.bf16.f32 {%0, %1, %2, %3}, {%4, %5}, {%6}, {%0, %1, %2, %3};"
      : "+f"(c[0]), "+f"(c[1]), "+f"(c[2]), "+f"(c[3]) : "r"(a0), "r"(a1), "r"(b0));
}
template <typename F>
__device__ __forceinline__ void local_attn1(int lr0, int warp_g, uint32_t sL, uint32_t bL, int lane, float g0, float g1, F st,
                                            uint32_t (&ad)[9], uint32_t (&pe)[4], uint32_t (&po)[4]) {
  const float scale_l2 = 0.23570226039551584f * 1.4426950408889634f;
  const int g = lane >> 2, t = lane & 3;
  const bool lo0 = 2 * t > g, lo1 = 2 * t + 1 > g;
  const bool ok0 = lr0 > 0 || !lo0, ok1 = lr0 > 0 || !lo1;
  uint32_t k[9][4], qf[9][2];
#pragma unroll
  for (int c = 0; c < 9; c++) {
    const uint32_t ch = warp_g * 9 + c;
    ad[c] = sL + (lane >> 4) * 18432 + (lane & 15) * 128 + ((ch >> 3) << 11) + (((ch ^ lane) & 7) << 4);
  }
  st(0, 0u); st(1, 0u);
  mbar_wait(bL, 0);
  if (warp_g == 0) TS(1, 6);
#pragma unroll
  for (int c = 0; c < 9; c++) {
    asm volatile("ldmatrix.sync.aligned.m8n8.x2.shared.b16 {%0, %1}, [%2];" : "=r"(qf[c][0]), "=r"(qf[c][1]) : "r"(ad[c] + LQ) : "memory");
    ldsm_x4(k[c][0], k[c][1], k[c][2], k[c][3], ad[c]);
  }
  st(2, k[0][0]); st(3, k[8][0]);
#pragma unroll
  for (int i = 0; i < 4; i++) {
    const uint32_t q0 = (t >= i) ? qf[2 * i][0] : 0u, q1 = (t >= i) ? qf[2 * i][1] : 0u;
    const uint32_t q4 = (t <= i) ? qf[2 * i + 2][0] : 0u, q5 = (t <= i) ? qf[2 * i + 2][1] : 0u;
    float c[4][4];
#pragma unroll
    for (int T = 0; T < 4; T++) {
#pragma unroll
      for (int j = 0; j < 4; j++) c[T][j] = 0.f;
      mma16(c[T], q0, q1, qf[2 * i + 1][0], qf[2 * i + 1][1], k[2 * i][T], k[2 * i + 1][T]);
      mma8(c[T], q4, q5, k[2 * i + 2][T]);
    }
    const float e0 = ok0 ? (lo0 ? c[0][0] : c[1][0]) : -INFINITY, e1 = ok1 ? (lo1 ? c[0][1] : c[1][1]) : -INFINITY;
    const float o0 = ok0 ? (lo0 ? c[2][2] : c[3][2]) : -INFINITY, o1 = ok1 ? (lo1 ? c[2][3] : c[3][3]) : -INFINITY;
    float me = fmaxf(e0, e1), mo = fmaxf(o0, o1);
    me = fmaxf(me, __shfl_xor_sync(0xffffffffu, me, 1));
    mo = fmaxf(mo, __shfl_xor_sync(0xffffffffu, mo, 1));
    me = fmaxf(me, __shfl_xor_sync(0xffffffffu, me, 2)) * scale_l2;
    mo = fmaxf(mo, __shfl_xor_sync(0xffffffffu, mo, 2)) * scale_l2;
    const float w0 = ex2(fmaf(e0, scale_l2, -me)), w1 = ex2(fmaf(e1, scale_l2, -me));
    const float w2 = ex2(fmaf(o0, scale_l2, -mo)), w3 = ex2(fmaf(o1, scale_l2, -mo));
    float se = w0 + w1, so = w2 + w3;
    st(4 + 2 * i, __float_as_uint(i == 1 ? me : i == 2 ? se : e0));
    se += __shfl_xor_sync(0xffffffffu, se, 1);
    so += __shfl_xor_sync(0xffffffffu, so, 1);
    se += __shfl_xor_sync(0xffffffffu, se, 2);
    so += __shfl_xor_sync(0xffffffffu, so, 2);
    asm("rcp.approx.ftz.f32 %0, %0;" : "+f"(se));
    asm("rcp.approx.ftz.f32 %0, %0;" : "+f"(so));
    se *= g0;
    so *= g1;
    pe[i] = pack_bf16(w0 * se, w1 * se);
    po[i] = pack_bf16(w2 * so, w3 * so);
    st(5 + 2 * i, i == 0 ? __float_as_uint(w0) : i == 2 ? __float_as_uint(mo) : po[i]);
  }
  if (warp_g == 0) TS(0, 4);
}
template <typename F>
__device__ __forceinline__ void local_attn2(int warp_g, uint32_t bL2, int lane, const uint32_t (&ad)[9], const uint32_t (&pe)[4], const uint32_t (&po)[4], F st) {
  const int g = lane >> 2, t = lane & 3;
  const uint32_t mlo = (2 * t > g ? 0xFFFFu : 0u) | (2 * t + 1 > g ? 0xFFFF0000u : 0u);
  uint32_t k[9][4], qf[9][2];
  mbar_wait(bL2, 0);
  if (warp_g == 0) TS(0, 5);
#pragma unroll
  for (int c = 0; c < 9; c++)
    asm volatile("ldmatrix.sync.aligned.m8n8.x4.trans.shared.b16 {%0, %1, %2, %3}, [%4];"
                 : "=r"(k[c][0]), "=r"(k[c][1]), "=r"(k[c][2]), "=r"(k[c][3]) : "r"(ad[c] + LV) : "memory");
#pragma unroll
  for (int i = 0; i < 4; i++) {
#pragma unroll
    for (int n = 0; n < 3; n++) {
      float c[4] = {0.f, 0.f, 0.f, 0.f};
      mma16(c, pe[i] & mlo, 0u, pe[i] & ~mlo, 0u, k[2 * i + n][0], k[2 * i + n][1]);
      mma16(c, 0u, po[i] & mlo, 0u, po[i] & ~mlo, k[2 * i + n][2], k[2 * i + n][3]);
      const uint32_t r0 = pack_bf16(c[0], c[1]), r1 = pack_bf16(c[2], c[3]);
      const bool keep = (n == 0) && (i > 0) && (t < i);
      qf[2 * i + n][0] = keep ? qf[2 * i + n][0] : r0;
      qf[2 * i + n][1] = keep ? qf[2 * i + n][1] : r1;
    }
    st(i, qf[2 * i + 1][0]);
  }
#pragma unroll
  for (int c = 0; c < 9; c++)
    asm volatile("stmatrix.sync.aligned.m8n8.x2.shared.b16 [%0], {%1, %2};" ::"r"(ad[c] + LQ), "r"(qf[c][0]), "r"(qf[c][1]) : "memory");
  asm volatile("fence.proxy.async.shared::cta;" ::: "memory");
}
__device__ __forceinline__ void tma4d(uint32_t dst, const CUtensorMap* m, uint32_t bar, int c1, int c2, int c3) {
  asm volatile("cp.async.bulk.tensor.4d.shared::cluster.global.mbarrier::complete_tx::bytes [%0], [%1, {%3, %4, %5, %6}], [%2];" ::"r"(dst),
               "l"(m), "r"(bar), "r"(0), "r"(c1), "r"(c2), "r"(c3) : "memory");
}

#define ST_NUM 1
#define ST_DEN 2
#define K1_NST 6
constexpr int K1_BST = K1_NST;
#define MAXJ 11
constexpr int K1_MAXJOBS = MAXJ;
constexpr uint32_t K1_FLAG_TARGET = 7;
constexpr uint32_t RDY_TARGET = 48;
constexpr uint32_t GATE_TARGET = 128 * 3;
struct alignas(64) Params {
  CUtensorMap tmA[2];
  CUtensorMap tmW[4];
  CUtensorMap tmK, tmV;
  CUtensorMap tmL[3];
  CUtensorMap tmC, tmO[2], tmOt[2];
  uint16_t jobs[NCLUSTER][K1_MAXJOBS + 1];
  uint8_t order[256];
  uint8_t unit[65][8];
};

struct K1State {
  uint32_t bs, bph, aph;
  bf16 *pp, *pp8;
  int png;
  int tn;
  int wsel;
  uint32_t fo;
};
__device__ __forceinline__ void k1_flag(const K1State& st, int lane, uint32_t bS) {
  if (st.png) {
    __syncwarp();
    if (lane == 0) mbar_arrive(bS + st.fo);
  }
}

__device__ __forceinline__ void scale_q4(uint32_t* v) {
#pragma unroll
  for (int i = 0; i < 4; i++)
    asm volatile("{\n.reg .b32 t;\nmul.rn.bf16x2 t, %0, %2;\nfma.rn.bf16x2 %0, %0, %1, t;\n}" : "+r"(v[i]) : "r"(0x3E033E03u), "r"(0xB9D8B9D8u));
}
__device__ __forceinline__ void k1_first(const K1State& st, uint32_t job, uint32_t bAf, uint32_t bBf) {
  if (job & 3) {
    if ((job >> 14) & 1) mbar_wait(bAf, st.aph);
    mbar_wait(bBf + st.bs * 8, st.bph);
  }
}
__device__ __forceinline__ void k1_tile(float (&acc)[128], uint32_t (&pk)[64], K1State& st, uint32_t job, uint32_t njob, uint32_t sA, uint32_t sB,
                                        uint32_t bAf, uint32_t bAe, uint32_t bBf, uint32_t bBe, uint32_t bS, int wg, int warp, int lane, uint32_t rank) {
  const int a_sel = (job >> 2) & 1, mpair = (job >> 3) & 7, w_sel = (job >> 6) & 3, chunk0 = (job >> 8) & 63;
  const bool newA = (job >> 14) & 1, lastA = (job >> 15) & 1;
  const bool sig = (lane == 0) && (warp < 2);
  const bool siga = lastA && (lane == 0) && (warp == 2);
  const int KC = 8 + a_sel;
  uint32_t prev_bs = 0, a8_bs = 0;
#pragma unroll
  for (int kc = 0; kc < 9; kc++) {
    if (kc >= KC) break;
    uint32_t abase = sA + ((kc + 2) & 7) * 16384;
    if (kc == 8) {
      mbar_wait(bBf + st.bs * 8, st.bph);
      a8_bs = st.bs;
      abase = sB + st.bs * 16384;
      if (++st.bs == K1_BST) { st.bs = 0; st.bph ^= 1; }
    } else if (newA && kc > 0) {
      mbar_wait(bAf + kc * 8, st.aph);
    }
    const uint64_t da = make_desc(abase + wg * 8192, 16, 1024, 1);
#pragma unroll
    for (int ks = 0; ks < 2; ks++) {
      if (ks > 0 || kc > 0) mbar_wait(bBf + st.bs * 8, st.bph);
      const uint64_t db = make_desc(sB + st.bs * 16384, 2048, 1024, 1);
      wg_fence();
      wgmma_ss_n256<1, 0>(acc, da + (uint64_t)(ks * 4), db, (ks > 0) ? 1 : (kc > 0));
      wgmma_ss_n256<1, 0>(acc, da + (uint64_t)(ks * 4 + 2), db + (uint64_t)512, 1);
      wg_commit();
      wg_wait<1>();
      if (ks > 0 || kc > 0) {
        if (sig) mbar_arrive_cluster(bBe + prev_bs * 8, warp);
        if (ks == 0 && siga) mbar_arrive(bAe + (kc - 1) * 8);
      }
      if (st.wsel == 2) {
        const int i = (kc & 7) * 2 + ks;
        if (kc < st.png) {
          quad_transpose(pk[i * 4], pk[i * 4 + 1], pk[i * 4 + 2], pk[i * 4 + 3], lane & 3);
          st_v4a((ks ? st.pp8 : st.pp) + kc * 32, pk[i * 4], pk[i * 4 + 1], pk[i * 4 + 2], pk[i * 4 + 3]);
        }
        if (i == 15) k1_flag(st, lane, bS);
      } else if (st.png) {
#pragma unroll
        for (int i = 0; i < 16; i++) {
          if (i * ST_NUM / ST_DEN != kc * 2 + ks) continue;
          if (st.wsel == 3) scale_q4(pk + i * 4);
          st_v4a(((i & 1) ? st.pp8 : st.pp) + (i / 2) * 32, pk[i * 4], pk[i * 4 + 1], pk[i * 4 + 2], pk[i * 4 + 3]);
          if (i == 15) k1_flag(st, lane, bS);
        }
      }
      prev_bs = st.bs;
      if (++st.bs == K1_BST) { st.bs = 0; st.bph ^= 1; }
    }
  }
  if (newA) st.aph ^= 1;
  const bool isA = (w_sel == 2);
  bf16* out = (w_sel == 0) ? g_K : (w_sel == 1) ? g_V : isA ? g_QKVA : g_ctx;
  const int ld = isA ? NQKVA : (w_sel == 3) ? KCAT : HDIM;
  const int row = mpair * 256 + rank * 128 + wg * 64 + warp * 16 + (lane >> 2);
  st.pp = ptr_add(out, (row * ld + chunk0 * 64 + (lane & 3) * 8) * 2);
  st.pp8 = ptr_add(st.pp, 16 * ld);
  st.png = ((job & 3) + 1) * 2;
  st.wsel = w_sel;
  st.fo = (st.fo + 8) & 24;
  k1_first(st, njob, bAf, bBf);
  wg_wait<0>();
  fence_regs(acc);
  mbar_arrive_cluster_if(bBe + prev_bs * 8, warp & 1, sig);
  mbar_arrive_cluster_if(bBe + a8_bs * 8, warp & 1, sig && a_sel);
  mbar_arrive_if(bAe + 7 * 8, siga && !a_sel);
#pragma unroll
  for (int i = 0; i < 64; i++) {
    const int j = (i >> 3) * 16 + (i & 3) * 4 + ((i >> 2) & 1) * 2;
    pk[i] = pack_bf16(acc[j], acc[j + 1]);
  }
}

constexpr int K2_NST = 7;
constexpr uint32_t K2_END = 0x100;
#define PFD 4
#define PF3A 2
#define PF3 6
#define KC0 1
#define FIRST_DRAW 3
#define PWAIT mbar_wait_ns<1000>
#define PVM 0x8A
#define W0 63
#define SPEC_HI 1.8446744073709552e19f
#define SPEC_LO 5.421010862427522e-20f
constexpr int K3_NST = 4;
__device__ __forceinline__ uint32_t k3_rot(uint32_t sv) { return (0x00E9u >> (2 * sv)) & 3; }
constexpr int K3_STAGE = 16384 + 32768 + 4096;
constexpr int SMEM_DATA = 7 * 32768;
constexpr int SMEM_BYTES = SMEM_DATA + 1024 + 768;

struct Cursor {
  uint32_t s, ph;
  __device__ __forceinline__ void next() {
    if (++s == K2_NST) { s = 0; ph ^= 1; }
  }
};

#define TURN_SYNC() bar_sync(mybar, 256)
#define TURN_ARRIVE() bar_arrive(otherbar, 256)
#define RELEASE_IF(cur, cond) mbar_arrive_cluster_if(bE + (cur).s * 8, warp & 1, sig && (cond))
#define RELEASE(cur) RELEASE_IF(cur, true)
#define ISSUE_PV(cur, first)                                                                                   \
  do {                                                                                                         \
    const uint64_t dv = make_desc(sbase + (cur).s * 32768, 16384, 1024, 1);                                    \
    _Pragma("unroll") for (int t = 0; t < 8; t++)                                                              \
        wgmma_rs_n128<1, 0>(O, P[4 * t], P[4 * t + 1], P[4 * t + 2], P[4 * t + 3], dv + (uint64_t)(t * 128), (t > 0) ? 1 : !(first)); \
  } while (0)
#define ISSUE_QK(cur)                                                                                          \
  do {                                                                                                         \
    const uint64_t dk = make_desc(sbase + (cur).s * 32768, 16, 1024, 1);                                       \
    _Pragma("unroll") for (int t = 0; t < 8; t++)                                                              \
        wgmma_rs_n128<0, 0>(S, Q[4 * t], Q[4 * t + 1], Q[4 * t + 2], Q[4 * t + 3], dk + (uint64_t)((t >> 2) * 1024 + (t & 3) * 2), t > 0); \
  } while (0)
#define LOAD_Q()                                                                                               \
  do {                                                                                                         \
    item = lds32(sItem + (it & 7) * 4);                                                                        \
    const uint32_t qa = sbase + cq.s * 32768 + (wg * 64 + warp * 16 + (lane & 15)) * 128;                      \
    _Pragma("unroll") for (int t = 0; t < 8; t++)                                                              \
        ldsm_x4(Q[4 * t], Q[4 * t + 1], Q[4 * t + 2], Q[4 * t + 3], qa + (t >> 2) * 16384 + ((((t & 3) * 2 + (lane >> 4)) ^ (lane & 7)) << 4)); \
  } while (0)
#define NEW_ITEM()                                                                                             \
  do {                                                                                                         \
    const int row = (2 * (item & 7) + hi) * 128 + wg * 64 + warp * 16 + (lane >> 2);                           \
    eoff = (row * KCAT + (item >> 3) * 128 + q * 8) * 2;                                                       \
    const float* gp = ptr_add(g_gate, row * 4);                                                                \
    asm volatile("ld.global.f32 %0, [%1];" : "=f"(gf0) : "l"(gp));                                             \
    asm volatile("ld.global.f32 %0, [%1];" : "=f"(gf1) : "l"(gp + 8));                                         \
    if (!hi) {                                                                                                 \
      mbar_wait2(bF + cs0.s * 8, cs0.ph, bF + cs1.s * 8, cs1.ph);                                              \
      RELEASE(cs0);                                                                                            \
      RELEASE(cs1);                                                                                            \
    }                                                                                                          \
  } while (0)
#define EXPB(T)                                                                                                \
  do {                                                                                                         \
    _Pragma("unroll") for (int i = 4 * T; i < 4 * T + 4; i++) asm volatile("" : "+r"(P[i])::"memory");        \
    _Pragma("unroll") for (int jj = 2 * T; jj < 2 * T + 2; jj++) {                                             \
      const float e0 = ex2(S[jj * 4 + 0]), e1 = ex2(S[jj * 4 + 1]), e2 = ex2(S[jj * 4 + 2]), e3 = ex2(S[jj * 4 + 3]); \
      s0 += e0 + e1;                                                                                           \
      s1 += e2 + e3;                                                                                           \
      P[jj * 2 + 0] = pack_bf16(e0, e1);                                                                       \
      P[jj * 2 + 1] = pack_bf16(e2, e3);                                                                       \
    }                                                                                                          \
  } while (0)
#define EXPC(T)                                                                                                \
  do {                                                                                                         \
    if (T > 0 && ((PVM >> (T - 1)) & 1)) {                                                                     \
      anchor((T & 2) ? s0 : s1, never);                                                                        \
      wg_wait<__builtin_popcount(PVM >> T) - 1>();                                                             \
      if ((PVM >> T) == (128 >> T)) { fence_regs(O); RELEASE(cv); }                                            \
    }                                                                                                          \
    EXPB(T);                                                                                                   \
  } while (0)
#define MASK(G, g)                                                                                             \
  do {                                                                                                         \
    if ((g) * 8 > d) S[(G) * 4 + 0] = -INFINITY;                                                               \
    if ((g) * 8 + 1 > d) S[(G) * 4 + 1] = -INFINITY;                                                           \
    if ((g) * 8 - 8 > d) S[(G) * 4 + 2] = -INFINITY;                                                           \
    if ((g) * 8 - 7 > d) S[(G) * 4 + 3] = -INFINITY;                                                           \
  } while (0)
#define STORE_O(G)                                                                                             \
  do {                                                                                                         \
    st_v4(optr + (G) * 32, pack_bf16(O[(G) * 16 + 0] * f0, O[(G) * 16 + 1] * f0), pack_bf16(O[(G) * 16 + 4] * f0, O[(G) * 16 + 5] * f0), \
          pack_bf16(O[(G) * 16 + 8] * f0, O[(G) * 16 + 9] * f0), pack_bf16(O[(G) * 16 + 12] * f0, O[(G) * 16 + 13] * f0)); \
    st_v4(optr + 8 * KCAT + (G) * 32, pack_bf16(O[(G) * 16 + 2] * f1, O[(G) * 16 + 3] * f1), pack_bf16(O[(G) * 16 + 6] * f1, O[(G) * 16 + 7] * f1), \
          pack_bf16(O[(G) * 16 + 10] * f1, O[(G) * 16 + 11] * f1), pack_bf16(O[(G) * 16 + 14] * f1, O[(G) * 16 + 15] * f1)); \
  } while (0)

#define FLUSH()                                                                                                \
  do {                                                                                                         \
    _Pragma("unroll") for (int G = 0; G < 8; G++) {                                                            \
      st_v4a(st.pp + G * 32, pk[G * 8], pk[G * 8 + 1], pk[G * 8 + 2], pk[G * 8 + 3]);                          \
      st_v4a(st.pp8 + G * 32, pk[G * 8 + 4], pk[G * 8 + 5], pk[G * 8 + 6], pk[G * 8 + 7]);                     \
    }                                                                                                          \
    k1_flag(st, lane, bS);                                                                                     \
  } while (0)

__global__ void __cluster_dims__(2, 1, 1) __launch_bounds__(384, 1)
fused_kernel(const __grid_constant__ Params p, const bf16* __restrict__ x, const bf16* __restrict__ gate_w, bf16* __restrict__ out) {
  extern __shared__ uint8_t smem_raw[];
  const uint32_t sbase = (smem_u32(smem_raw) + 1023) & ~1023u;
  const uint32_t sB = sbase, sA = sbase + K1_BST * 16384, sBar = sbase + SMEM_DATA;
  const uint32_t bAf = sBar, bAe = sBar + 64, bBf = sBar + 128, bBe = sBar + 176, bL = sBar + 224, bS = sBar + 656, bL2 = sBar + 240, sL = sA + 32768;
  const uint32_t bF = sBar + 256, bE = sBar + 320, bT = sBar + 384, sTick = sBar + 400, sItem = sBar + 416, bS2 = sBar + 688, bR = sBar + 456, bLast = sBar + 464, bH = sBar + 472, bT0 = sBar + 480;
  const uint32_t b3F = sBar + 512, b3E = sBar + 544, sGate = sBar + 576;
  const int tid = threadIdx.x, warp_g = __shfl_sync(0xffffffffu, tid >> 5, 0), lane = tid & 31;
  const uint32_t rank = cluster_rank();
  const int cl = blockIdx.x >> 1;
  TSM(0);
  if (tid == 256) {
    const uint32_t job = p.jobs[cl][0];
#pragma unroll
    for (int i = 0; i < KC0; i++) { mbar_init(bAf + i * 8, 1); mbar_init(bBf + i * 16, 1); mbar_init(bBf + i * 16 + 8, 1); }
    asm volatile("fence.mbarrier_init.release.cluster;" ::: "memory");
#pragma unroll 1
    for (int i = 0; i < 4 * KC0; i++) {
      if (!(i & 3)) {
        mbar_expect(bAf + i * 2, 16384);
        tma2d(sA + (i / 4 + 2) * 16384, &p.tmA[(job >> 2) & 1], bAf + i * 2, i * 16, ((job >> 3) & 7) * 256 + rank * 128);
      }
      if (!(i & 1)) mbar_expect(bBf + i * 4, 16384);
      tma3d(sB + i * 8192, &p.tmW[(job >> 6) & 3], bBf + (i >> 1) * 8, 0, i * 16, (job >> 8) & 63);
    }
  }
  if (tid == 0) {
    for (int i = 0; i < 8; i++) { if (i >= KC0) mbar_init(bAf + i * 8, 1); mbar_init(bAe + i * 8, 2); }
    for (int i = 0; i < K1_BST; i++) { if (i >= 2 * KC0) mbar_init(bBf + i * 8, 1); mbar_init(bBe + i * 8, 4); }
    mbar_init(bL, 1);
    mbar_init(bL2, 1);
    mbar_init(bR, 1);
    mbar_init(bLast, 1);
    mbar_init(bH, 4);
    mbar_init(bT0, 1);
    for (int i = 0; i < 8; i++) mbar_init(bS + i * 8, 8);
    for (int i = 0; i < K2_NST; i++) { mbar_init(bF + i * 8, 1); mbar_init(bE + i * 8, 4); }
    mbar_init(bT, 1); mbar_init(bT + 8, 1);
    for (int i = 0; i < K3_NST; i++) { mbar_init(b3F + i * 8, 1); mbar_init(b3E + i * 8, 4); }
    asm volatile("fence.mbarrier_init.release.cluster;" ::: "memory");
  }
  __syncwarp();
  if (warp_g != 8) cluster_sync();
  const int lr0 = blockIdx.x * 16;

  if (warp_g >= 8) {
    reg_dealloc<40>();
    if (warp_g == 8) {
      {
        __syncwarp();
        cluster_sync();
      }
      if (elect_one()) {
        uint32_t bs = (2 * KC0) % K1_BST, bph = (2 * KC0 < K1_BST), aph = 1;
#pragma unroll 1
        for (int ji = 0; ji < K1_MAXJOBS; ji++) {
          const uint32_t job = p.jobs[cl][ji];
          if (!(job & 3)) break;
          const int a_sel = (job >> 2) & 1, mpair = (job >> 3) & 7, chunk0 = (job >> 8) & 63;
          const bool newA = (job >> 14) & 1;
          const int KC = a_sel ? 9 : 8;
          const uint32_t halfbytes = 8192;
          const bool lastjob = (ji + 1 == K1_MAXJOBS) || !(p.jobs[cl][ji + 1] & 3);
          const CUtensorMap* tw = &p.tmW[(job >> 6) & 3];
          {
            const uint32_t njob = (ji + 1 < K1_MAXJOBS) ? p.jobs[cl][ji + 1] : 0;
            if (!(njob & 3) && !newA) mbar_arrive(bLast);
          }
#pragma unroll 1
          for (int kc = ji ? 0 : KC0; kc < KC; kc++) {
            {
              const bool nx = kc + PFD >= KC;
              const uint32_t njob = nx ? p.jobs[cl][ji + 1] : job;
              const int pk = nx ? kc + PFD - KC : kc + PFD;
              if ((njob & 3) && (nx || ji > 0)) {
                if (cl >= 64 || ((pk ^ (cl >> 1)) & 3) == 0)
                  tma_pf3d(&p.tmW[(njob >> 6) & 3], 0, pk * 64 + (cl & 1) * 32 + rank * 16, (njob >> 8) & 63);
                if (((njob >> 14) & 1) || pk == 8) tma_pf2d(&p.tmA[(njob >> 2) & 1], pk * 64, ((njob >> 3) & 7) * 256 + rank * 128);
              }
            }
            if (kc == 8) {
              PWAIT(bBe + bs * 8, bph);
              mbar_expect(bBf + bs * 8, 16384);
              tma2d(sB + bs * 16384, &p.tmA[1], bBf + bs * 8, 512, mpair * 256 + rank * 128);
              if (++bs == K1_BST) { bs = 0; bph ^= 1; }
            } else if (newA) {
              PWAIT(bAe + kc * 8, aph);
              mbar_expect(bAf + kc * 8, 16384);
              tma2d(sA + ((kc + 2) & 7) * 16384, &p.tmA[a_sel], bAf + kc * 8, kc * 64, mpair * 256 + rank * 128);
              if (kc == 7 && lastjob) mbar_arrive(bLast);
            }
#pragma unroll 1
            for (int kk = 0; kk < 2; kk++) {
              PWAIT(bBe + bs * 8, bph);
              mbar_expect(bBf + bs * 8, 2 * halfbytes);
              tma3d_mc(sB + bs * 16384 + rank * halfbytes, tw, bBf + bs * 8, 0, kc * 64 + kk * 32 + rank * 16, chunk0, 3);
              if (++bs == K1_BST) { bs = 0; bph ^= 1; }
            }
          }
          if (newA) aph ^= 1;
        }
        Cursor c{0, 0};
        int pcol = 0;
        PWAIT(bR, 0);
        uint32_t tick = lds32(sTick + 8), seen = 1u << (p.order[tick] >> 4);
        asm volatile("fence.proxy.async.global;" ::: "memory");
#pragma unroll 1
        for (int it = 0;; it++) {
          const uint32_t item = (tick < 256) ? p.order[tick] : (K2_END | min(tick - 256, 255u));
          asm volatile("st.shared.u32 [%0], %1;" ::"r"(sItem + (it & 7) * 4), "r"(item) : "memory");
          if (item >= K2_END) break;
          const int h = item >> 3, j = item & 7;
          const int blk = 2 * j + (int)(rank ^ (it & 1));
          const int col = h * 128 + rank * 64;
          const int nb = 2 * j + 2;
          if (!((seen >> (h >> 1)) & 1)) {
            wait_flag(&g_sync[F_HP + (h >> 1)], RDY_TARGET);
            asm volatile("fence.proxy.async.global;" ::: "memory");
            seen |= 1u << (h >> 1);
          }
          PWAIT(bE + c.s * 8, c.ph);
          mbar_expect(bF + c.s * 8, 32768);
          tma2d(sbase + c.s * 32768, &p.tmC, bF + c.s * 8, h * 128, blk * 128);
          tma2d(sbase + c.s * 32768 + 16384, &p.tmC, bF + c.s * 8, h * 128 + 64, blk * 128);
          c.next();
          if (tick >= 256 - 73) {
            const int kk = tick - (256 - 73), sel = (kk < 9), kr = (sel ? kk : kk - 9) * 64 + rank * 32;
#pragma unroll 1
            for (int i = 0; i < 2; i++) {
              tma_pf3d(&p.tmO[sel], 0, kr, i * 4);
              tma_pf2d(&p.tmOt[sel], 512 + i * 32, kr);
            }
          }
#pragma unroll 1
          for (int n = nb - 1; n >= 0; n--) {
            if (n == 0 && rank == 0) tick = atomicAdd(&g_sync[F_TICK], 1u);
            PWAIT(bE + c.s * 8, c.ph);
            mbar_expect(bF + c.s * 8, 32768);
            tma2d_mc(sbase + c.s * 32768 + rank * 16384, &p.tmK, bF + c.s * 8, col, n * 128, 3);
            c.next();
            if (n < nb - 1 || it > 0) {
              PWAIT(bE + c.s * 8, c.ph);
              mbar_expect(bF + c.s * 8, 32768);
              tma2d_mc(sbase + c.s * 32768 + rank * 16384, &p.tmV, bF + c.s * 8, (n < nb - 1) ? col : pcol, (n < nb - 1) ? (n + 1) * 128 : 0, 3);
              c.next();
            }
          }
          pcol = col;
          if (rank == 0) {
            asm volatile(
                "{\n.reg .b32 a, b;\nmapa.shared::cluster.u32 a, %0, 1;\nmapa.shared::cluster.u32 b, %1, 1;\n"
                "st.async.shared::cluster.mbarrier::complete_tx::bytes.u32 [a], %2, [b];\n}" ::"r"(sTick + (it & 1) * 4),
                "r"(bT + (it & 1) * 8), "r"(tick) : "memory");
          } else {
            mbar_expect(bT + (it & 1) * 8, 4);
            PWAIT(bT + (it & 1) * 8, (it >> 1) & 1);
            tick = lds32(sTick + (it & 1) * 4);
          }
        }
        PWAIT(bE + c.s * 8, c.ph);
        mbar_expect(bF + c.s * 8, 32768);
        tma2d_mc(sbase + c.s * 32768 + rank * 16384, &p.tmV, bF + c.s * 8, pcol, 0, 3);
        const uint32_t unit = min(tick - 256, 64u);
        const int mblk = (7 - (p.unit[unit][0] >> 1)) * 2 + rank, nhalf = p.unit[unit][0] & 1;
        uint32_t have, hoa;
        asm volatile("ld.acquire.gpu.global.u32 %0, [%1];" : "=r"(have) : "l"(&g_sync[F_CTX + mblk]) : "memory");
        asm volatile("ld.acquire.gpu.global.u32 %0, [%1];" : "=r"(hoa) : "l"(&g_sync[F_OA + mblk]) : "memory");
        asm volatile("fence.proxy.async.global;" ::: "memory");
#pragma unroll 1
        for (uint32_t idx = PF3A; idx < PF3 && unit < 64; idx++) {
          const int kk = p.unit[unit][3] + idx;
          if ((kk < 9) ? (hoa >= 8) : ((have >> ((kk - 9) >> 1)) & 1)) tma_pf2d(&p.tmC, ((kk < 9) ? 64 + kk : kk - 9) * 64, mblk * 128);
        }
        if (unit < 64) {
          const uint32_t rot = k3_rot(c.s), nfree = ((0x1Au >> c.s) & 1) ? 2 : 3;
#pragma unroll 1
          for (uint32_t idx = 0; idx < p.unit[unit][2]; idx++) {
            const int kk = p.unit[unit][3] + idx + ((idx >= p.unit[unit][4]) ? p.unit[unit][5] : 0);
            const uint32_t s = (rot + idx) & 3;
            if (idx >= nfree) PWAIT((idx < 4) ? bH : b3E + s * 8, (idx < 4) ? 0 : (~idx >> 2) & 1);
#pragma unroll 1
            while (idx < nfree && c.s != ((0x6431u >> (4 * s)) & 15)) {
              c.next();
              PWAIT(bE + c.s * 8, c.ph);
            }
            mbar_expect(b3F + s * 8, K3_STAGE);
            const uint32_t st = sbase + s * K3_STAGE;
            const int sel = (kk < 9), k = sel ? kk : kk - 9, kr = k * 64 + rank * 32;
            tma3d_mc(st + 16384 + rank * 16384, &p.tmO[sel], b3F + s * 8, 0, kr, nhalf * 4, 3);
            tma2d_mc(st + 49152 + rank * 2048, &p.tmOt[sel], b3F + s * 8, 512 + nhalf * 32, kr, 3);
            if (sel && hoa < 8) {
              wait_flag(&g_sync[F_OA + mblk], 8);
              hoa = 8;
              asm volatile("fence.proxy.async.global;" ::: "memory");
            }
            if (!sel && !((have >> (k >> 1)) & 1)) {
#pragma unroll 1
              for (uint32_t spins = 0; spins < (1u << 22); spins++) {
                asm volatile("ld.acquire.gpu.global.u32 %0, [%1];" : "=r"(have) : "l"(&g_sync[F_CTX + mblk]) : "memory");
                if ((have >> (k >> 1)) & 1) break;
                __nanosleep(100);
              }
              asm volatile("fence.proxy.async.global;" ::: "memory");
            }
            tma2d(st, &p.tmC, b3F + s * 8, (sel ? 64 + k : k) * 64, mblk * 128);
          }
        }
      }
    }
    __syncwarp();
    if (warp_g == 8) {
      uint32_t v = 0;
      if (lane == 0) {
        __threadfence();
        v = atomicAdd(&g_sync[F_DONE], 1u);
      }
      if (__shfl_sync(0xffffffffu, v, 0) == 2 * NCLUSTER - 1) {
        reinterpret_cast<uint4*>(g_sync)[lane] = make_uint4(0, 0, 0, 0);
        if (lane == 0) g_sync[F_EPOCH] = lds32(sGate + 64) + 1;
      }
    }
    asm volatile("" ::: "memory");
    if (__shfl_sync(0xffffffffu, warp_g, 0) != 8) {
      if (lr0 < S_LEN) {
#pragma unroll 1
        for (int i = warp_g - 9; i < 16; i += 3) {
          const float g = gate_row(lr0 + i, lane, x, gate_w);
          if (lane == 0) asm volatile("st.shared.f32 [%0], %1;" ::"r"(sGate + i * 4), "f"(g) : "memory");
        }
        bar_arrive(3, 256 + 96);
        if (lane == 0) {
          __threadfence();
          atomicAdd(&g_sync[F_GATE], 1u);
        }
      }
      uint32_t aph = 1;
#pragma unroll 1
      for (int ji = 0; ji < K1_MAXJOBS; ji++) aph ^= (p.jobs[cl][ji] >> 14) & 1;
      if (warp_g == 9 && lane == 0) {
#pragma unroll 1
        for (int ji = 0; ji < K1_MAXJOBS; ji++) {
          const uint32_t job = p.jobs[cl][ji];
          if (!(job & 3)) break;
          PWAIT(bS + (ji & 3) * 8, (ji >> 2) & 1);
          __threadfence();
          atomicAdd(&g_sync[(((job >> 6) & 3) == 2) ? (F_QKVA + ((job >> 3) & 7) * 2 + rank) : (F_HP + ((job >> 10) & 15))], 1u);
        }
#pragma unroll 1
        for (int it = 0;; it++) {
          PWAIT(bS2 + (it & 3) * 8, (it >> 2) & 1);
          const uint32_t item = lds32(sItem + (it & 7) * 4), nxt = lds32(sItem + ((it + 1) & 7) * 4);
          __threadfence();
          atomicOr(&g_sync[F_CTX + (item & 7) * 2 + (rank ^ (it & 1))], 1u << (item >> 3));
          if (nxt >= K2_END) break;
        }
      } else if (warp_g == 11) {
        if (lane == 0) {
          prefetch_tmap(&p.tmC); prefetch_tmap(&p.tmK); prefetch_tmap(&p.tmV);
          asm volatile("st.shared.u32 [%0], %1;" ::"r"(sGate + 64), "r"(__ldcg(&g_sync[F_EPOCH])) : "memory");
          wait_flag(&g_sync[F_GATE], GATE_TARGET);
          uint32_t tick;
          if (rank == 0) {
            PWAIT(bLast, 0);
            PWAIT(bAe + FIRST_DRAW * 8, aph);
            tick = atomicAdd(&g_sync[F_TICK], 1u);
            asm volatile("st.shared.u32 [%0], %1;" ::"r"(sTick + 8), "r"(tick) : "memory");
            asm volatile(
                "{\n.reg .b32 a, b;\nmapa.shared::cluster.u32 a, %0, 1;\nmapa.shared::cluster.u32 b, %1, 1;\n"
                "st.async.shared::cluster.mbarrier::complete_tx::bytes.u32 [a], %2, [b];\n}" ::"r"(sTick + 8), "r"(bT0), "r"(tick) : "memory");
          } else {
            mbar_expect(bT0, 4);
            PWAIT(bT0, 0);
            tick = lds32(sTick + 8);
          }
          wait_flag(&g_sync[F_HP + (p.order[tick] >> 4)], RDY_TARGET);
          mbar_arrive(bR);
        }
      } else if (warp_g == 10) {
        if (lr0 < S_LEN && lane == 0) {
          prefetch_tmap(&p.tmL[0]); prefetch_tmap(&p.tmL[1]); prefetch_tmap(&p.tmL[2]);
          wait_flag(&g_sync[F_QKVA + (lr0 >> 7)], K1_FLAG_TARGET);
          wait_flag(&g_sync[F_QKVA + (max(lr0 - 16, 0) >> 7)], K1_FLAG_TARGET);
          asm volatile("fence.proxy.async.global;" ::: "memory");
          PWAIT(bLast, 0);
#pragma unroll 1
          for (int kc = 0; kc < 6; kc++) {
            PWAIT(bAe + kc * 8, aph);
            if (kc == 3) {
              mbar_expect(bL, LV);
              tma4d(sL, &p.tmL[0], bL, lr0 / 2 - 8, 9, 0);
              tma4d(sL + LQ, &p.tmL[1], bL, lr0 / 2, 0, 0);
            }
          }
          mbar_expect(bL2, LQ);
          tma4d(sL + LV, &p.tmL[0], bL2, lr0 / 2 - 8, 18, 0);
        }
        __syncwarp();
        bar_sync(5, 256 + 32);
        if (lr0 < S_LEN && lane == 0) {
          asm volatile("cp.async.bulk.tensor.4d.global.shared::cta.bulk_group [%0, {%2, %3, %2, %2}], [%1];" ::"l"(&p.tmL[2]), "r"(sL + LQ), "r"(0), "r"(lr0 / 2) : "memory");
          asm volatile("cp.async.bulk.commit_group;" ::: "memory");
          asm volatile("cp.async.bulk.wait_group.read 0;" ::: "memory");
        }
        __syncwarp();
        if (lane < 12) mbar_arrive_cluster(bE + (4 + lane % 3) * 8, (lane / 3) & 1);
        if (lr0 < S_LEN && lane == 0) {
          asm volatile("cp.async.bulk.wait_group 0;" ::: "memory");
          asm volatile("fence.proxy.async.global;" ::: "memory");
          __threadfence();
          atomicAdd(&g_sync[F_OA + (lr0 >> 7)], 1u);
        }
      }
    }
    __syncwarp();
    cluster_sync();
  } else {
    reg_alloc<232>();
    const int wg = warp_g >> 2, warp = warp_g & 3, q = lane & 3;
    const bool sig = (lane == 0) && (warp < 2);
    uint32_t lad[9], lpe[4], lpo[4], lpk[16], late = 1, lfo;
    bf16 *lp, *lp8;
    {
      K1State st{0, 0, 0, nullptr, nullptr, 0, 0, 0, 24};
      float acc[128];
      uint32_t pk[64];
      if (wg == 0) { TS(0, 0); TSC(0, 2); }
      uint32_t job = p.jobs[cl][0];
      k1_first(st, job, bAf, bBf);
      {
#pragma unroll 1
        for (int ji = 0; job & 3; ji++) {
          const uint32_t njob = p.jobs[cl][ji + 1];
          k1_tile(acc, pk, st, job, njob, sA, sB, bAf, bAe, bBf, bBe, bS, wg, warp, lane, rank);
          job = njob;
        }
      }
#pragma unroll
      for (int i = 0; i < 4; i++)
        mbar_arrive_cluster_if(bE + i * 8, warp & 1, sig);
      if (lr0 < S_LEN) bar_sync(3, 256 + 96);
      if (st.wsel == 3) {
#pragma unroll
        for (int G = 0; G < 16; G++) scale_q4(pk + G * 4);
      }
      auto flush = [&](int i, uint32_t dep) {
        asm volatile("{\n.reg .pred p;\nsetp.eq.u32 p, %5, 0;\n@p st.global.cs.v4.b32 [%0], {%1, %2, %3, %4};\n}" ::"l"(((i & 1) ? st.pp8 : st.pp) + (i / 2) * 32),
                     "r"(pk[i * 4]), "r"(pk[i * 4 + 1]), "r"(pk[i * 4 + 2]), "r"(pk[i * 4 + 3]), "r"(dep & blockIdx.y) : "memory");
      };
      if (wg == 0) { TS(0, 1); TSC(0, 3); }
      if (lr0 < S_LEN) {
        const float gate0 = __uint_as_float(lds32(sGate + (lane >> 2) * 8)), gate1 = __uint_as_float(lds32(sGate + (lane >> 2) * 8 + 4));
        local_attn1(lr0, warp_g, sL, bL, lane, gate0, gate1, flush, lad, lpe, lpo);
        late = __any_sync(0xffffffffu, !mbar_test(bR, 0));
        if (late) {
          flush(12, 0u); flush(13, 0u); flush(14, 0u); flush(15, 0u);
          k1_flag(st, lane, bS);
        }
      } else {
        FLUSH();
      }
#pragma unroll
      for (int i = 0; i < 16; i++) lpk[i] = pk[48 + i];
      lp = st.pp; lp8 = st.pp8; lfo = st.fo;
    }
    __syncwarp();
    uint32_t item, rot;
    {
      const int mybar = 1 + wg, otherbar = 2 - wg;
      const uint32_t never = blockIdx.y;
      float S[64], O[64];
      uint32_t P[32], Q[32];
      float m0, m1, l0, l1, gf0, gf1;
      uint32_t eoff;
      Cursor c{4 - 2 * rank, 0}, ck{2 - rank, 0};
      if (wg == 1) bar_arrive(1, 256);
      {
        const Cursor cq{0, 0}, cs0{1, 0}, cs1{3, 0};
        const int it = 0, hi = rank;
        mbar_wait2(bF, 0, bF + ck.s * 8, 0);
        LOAD_Q();
        wg_fence();
        ISSUE_QK(ck);
        wg_commit();
        RELEASE(cq);
        if (lr0 < S_LEN) {
          local_attn2(warp_g, bL2, lane, lad, lpe, lpo, [&](int i, uint32_t dep) {
            asm volatile("{\n.reg .pred p;\nsetp.eq.u32 p, %5, 0;\n@p st.global.cs.v4.b32 [%0], {%1, %2, %3, %4};\n}" ::"l"(((i & 1) ? lp8 : lp) + (6 + i / 2) * 32),
                         "r"(lpk[i * 4]), "r"(lpk[i * 4 + 1]), "r"(lpk[i * 4 + 2]), "r"(lpk[i * 4 + 3]), "r"((dep & never) | late) : "memory");
          });
          __syncwarp();
          mbar_arrive_if(bS + lfo, lane == 0 && !late);
        }
        bar_arrive(5, 256 + 32);
        if (wg == 0) { TS(1, 0); TSC(1, 2); }
        NEW_ITEM();
        wg_wait<0>();
        fence_regs(S);
      }
#pragma unroll 1
      for (int it = 0;;) {
        int hi = (int)(rank ^ (it & 1));
        RELEASE(ck);
        const int nblk = 2 * (item & 7) + 1 + hi;
        Cursor cv;
        float s0 = 0.f, s1 = 0.f;
        l0 = 0.f; l1 = 0.f;
        m0 = 0.f; m1 = 0.f;
        bool shifted = false;
        {
          const int d = warp * 16 + (lane >> 2) - 2 * q;
          if (wg == 0) {
#pragma unroll
            for (int jj = 0; jj < 8; jj++) MASK(jj, jj);
            EXPB(0); EXPB(1); EXPB(2); EXPB(3);
#pragma unroll
            for (int i = 32; i < 64; i++) S[i] = -INFINITY;
#pragma unroll
            for (int i = 16; i < 32; i++) P[i] = 0;
          } else {
#pragma unroll
            for (int jj = 0; jj < 8; jj++) MASK(jj + 8, jj);
            EXPB(0); EXPB(1); EXPB(2); EXPB(3); EXPB(4); EXPB(5); EXPB(6); EXPB(7);
          }
        }
        float chk = (q == 0 && !(fminf(s0, s1) >= SPEC_LO)) ? INFINITY : s0 + s1;
        fence_regs(P);
        TB(9);
#pragma unroll 1
        for (int n = 1;; n++) {
          if (__any_sync(0xffffffffu, !(chk <= SPEC_HI))) {
            float mx0 = fmaxf(S[0], S[1]), mx1 = fmaxf(S[2], S[3]);
#pragma unroll
            for (int jj = 1; jj < 16; jj++) {
              mx0 = fmaxf(mx0, fmaxf(S[jj * 4 + 0], S[jj * 4 + 1]));
              mx1 = fmaxf(mx1, fmaxf(S[jj * 4 + 2], S[jj * 4 + 3]));
            }
            mx0 = fmaxf(mx0, __shfl_xor_sync(0xffffffffu, mx0, 1));
            mx1 = fmaxf(mx1, __shfl_xor_sync(0xffffffffu, mx1, 1));
            mx0 = fmaxf(mx0, __shfl_xor_sync(0xffffffffu, mx0, 2));
            mx1 = fmaxf(mx1, __shfl_xor_sync(0xffffffffu, mx1, 2));
            const float lo = (n == 1) ? -INFINITY : 0.f;
            mx0 = fmaxf(mx0, lo);
            mx1 = fmaxf(mx1, lo);
            m0 += mx0; m1 += mx1;
            shifted = true;
            const float sc0 = ex2(-fmaxf(mx0, 0.f)), sc1 = ex2(-fmaxf(mx1, 0.f));
            l0 *= sc0; l1 *= sc1;
            s0 = 0.f; s1 = 0.f;
#pragma unroll
            for (int jj = 0; jj < 16; jj++) {
              const float e0 = ex2(S[jj * 4 + 0] - mx0), e1 = ex2(S[jj * 4 + 1] - mx0), e2 = ex2(S[jj * 4 + 2] - mx1), e3 = ex2(S[jj * 4 + 3] - mx1);
              s0 += e0 + e1;
              s1 += e2 + e3;
              P[jj * 2 + 0] = pack_bf16(e0, e1);
              P[jj * 2 + 1] = pack_bf16(e2, e3);
              O[jj * 4 + 0] *= sc0;
              O[jj * 4 + 1] *= sc0;
              O[jj * 4 + 2] *= sc1;
              O[jj * 4 + 3] *= sc1;
            }
          }
          l0 += s0;
          l1 += s1;
          if (n >= nblk) break;
          ck = c; c.next();
          cv = c; c.next();
          mbar_wait(bF + ck.s * 8, ck.ph);
          mbar_wait(bF + cv.s * 8, cv.ph);
          TURN_SYNC();
          TRC(0);
          wg_fence();
          ISSUE_QK(ck);
          wg_commit();
          {
            const uint64_t dv = make_desc(sbase + cv.s * 32768, 16384, 1024, 1);
#pragma unroll
            for (int t = 0; t < 8; t++) {
              wgmma_rs_n128<1, 0>(O, P[4 * t], P[4 * t + 1], P[4 * t + 2], P[4 * t + 3], dv + (uint64_t)(t * 128), (t > 0) ? 1 : (n != 1));
              if ((PVM >> t) & 1) wg_commit();
            }
          }
          TURN_ARRIVE();
          s0 = 0.f; s1 = 0.f;
          wg_wait<__builtin_popcount(PVM)>();
          fence_regs(S);
          RELEASE(ck);
          if (shifted) {
#pragma unroll
            for (int i = 0; i < 64; i++) S[i] -= (i & 2) ? m1 : m0;
          }
          wg_wait<__builtin_popcount(PVM) - 1>();
          EXPC(0); EXPC(1); EXPC(2); EXPC(3); EXPC(4); EXPC(5); EXPC(6); EXPC(7);
          chk = s0 + s1;
        }
        it++;
        hi ^= 1;
        TB(0);
        Cursor cq = c, cs0, cs1;
        rot = k3_rot(c.s);
        c.next();
        ck = c; c.next();
        cs0 = ck; cs1 = ck;
        cv = c; c.next();
        if (!hi) {
          ck = c; c.next();
          cs1 = c; c.next();
        }
        mbar_wait(bF + cq.s * 8, cq.ph);
        TB(1);
        LOAD_Q();
        const uint32_t rdy = mbar_test(bF + ck.s * 8, ck.ph) & mbar_test(bF + cv.s * 8, cv.ph);
        l0 += __shfl_xor_sync(0xffffffffu, l0, 1);
        l1 += __shfl_xor_sync(0xffffffffu, l1, 1);
        l0 += __shfl_xor_sync(0xffffffffu, l0, 2);
        l1 += __shfl_xor_sync(0xffffffffu, l1, 2);
        if (item >= K2_END) {
          TURN_SYNC();
          TRC(2);
          wg_fence();
          ISSUE_PV(cq, nblk == 1);
          wg_commit();
          if (wg == 0) TURN_ARRIVE();
          asm volatile("" : "+f"(gf0), "+f"(gf1), "+f"(l0), "+f"(l1));
          const float f0 = __fdividef(1.f - gf0, l0), f1 = __fdividef(1.f - gf1, l1);
          bf16* optr = ptr_add(g_ctx, eoff);
          wg_wait<0>();
          fence_regs(O);
          mbar_arrive_cluster_if(bH, warp & 1, sig);
          STORE_O(0); STORE_O(1); STORE_O(2); STORE_O(3);
          __syncwarp();
          mbar_arrive_if(bS2 + ((it - 1) & 3) * 8, lane == 0);
          break;
        }
        if (!rdy) mbar_wait2(bF + ck.s * 8, ck.ph, bF + cv.s * 8, cv.ph);
        TB(2);
        TURN_SYNC();
        TB(3);
        TRC(1);
        wg_fence();
        ISSUE_PV(cv, nblk == 1);
        wg_commit();
        ISSUE_QK(ck);
        wg_commit();
        TURN_ARRIVE();
        RELEASE(cq);
        TB(4);
        asm volatile("" : "+f"(gf0), "+f"(gf1), "+f"(l0), "+f"(l1));
        const float f0 = __fdividef(1.f - gf0, l0), f1 = __fdividef(1.f - gf1, l1);
        wg_wait<1>();
        fence_regs(O);
        fence_regs(P);
        TB(5);
        RELEASE(cv);
        {
          bf16* optr = ptr_add(g_ctx, eoff);
          STORE_O(0); STORE_O(1); STORE_O(2); STORE_O(3);
          __syncwarp();
          mbar_arrive_if(bS2 + ((it - 1) & 3) * 8, lane == 0);
        }
        TB(6);
        NEW_ITEM();
        TB(7);
        wg_wait<0>();
        fence_regs(S);
        TB(8);
      }
      TRC(3);
      if (wg == 1) { TS(1, 1); TSC(1, 3); }
    }
    __syncwarp();
    const uint32_t unit = item & 255;
    if (unit < 64) {
      const int mblk = (7 - (p.unit[unit][0] >> 1)) * 2 + rank, nhalf = p.unit[unit][0] & 1, ks = p.unit[unit][1];
      const int k0 = 0, k1 = p.unit[unit][2];
      float acc[144];
      uint32_t s = rot, ph = 0, prev = 0;
      if (wg == 0) { TS(2, 0); TSC(2, 2); }
      uint32_t fa[16], fb[16];
      const uint32_t aoff = (wg * 64 + warp * 16 + (lane & 15)) * 128 + (((lane >> 4) ^ (lane & 7)) << 4);
#define C_LOAD(F)                                                                                              \
  do {                                                                                                         \
    mbar_wait(b3F + s * 8, ph);                                                                                \
    _Pragma("unroll") for (int t = 0; t < 4; t++)                                                              \
        ldsm_x4(F[4 * t], F[4 * t + 1], F[4 * t + 2], F[4 * t + 3], sbase + s * K3_STAGE + (aoff ^ (t * 32))); \
  } while (0)
#define C_STEP(F, G)                                                                                           \
  {                                                                                                            \
    const uint32_t st = sbase + s * K3_STAGE;                                                                  \
    const uint64_t db = make_desc(st + 16384, 4096, 1024, 1), dt = make_desc(st + 49152, 16, 512, 2);          \
    wg_fence();                                                                                                \
    _Pragma("unroll") for (int t = 0; t < 4; t++) {                                                            \
      const int sd = (t > 0) || (k > k0);                                                                      \
      wgmma_rs_n256<1, 0>(acc, F[4 * t], F[4 * t + 1], F[4 * t + 2], F[4 * t + 3], db + (uint64_t)((t >> 1) * 1024 + (t & 1) * 128), sd); \
      wgmma_rs_n32<1, 128>(acc, F[4 * t], F[4 * t + 1], F[4 * t + 2], F[4 * t + 3], dt + (uint64_t)(t * 64), sd); \
    }                                                                                                          \
    wg_commit();                                                                                               \
    wg_wait<1>();                                                                                              \
    fence_regs(G);                                                                                             \
    mbar_arrive_cluster_if(b3E + prev * 8, warp & 1, sig && k > k0);                                           \
    prev = s;                                                                                                  \
    s = (s + 1) & 3;                                                                                           \
    if (s == rot) ph ^= 1;                                                                                     \
    TCK(k + 1);                                                                                                \
    if (++k == k1) break;                                                                                      \
    C_LOAD(G);                                                                                                 \
  }
      TCK(0);
      C_LOAD(fa);
#pragma unroll
      for (int i = 0; i < 16; i++) fb[i] = 0;
#pragma unroll 1
      for (int k = k0;;) {
        C_STEP(fa, fb)
        C_STEP(fb, fa)
      }
      wg_wait<0>();
      fence_regs(acc);
      cluster_arrive();
      if (wg == 0) TS(2, 4);
      const int tile = mblk * 2 + nhalf;
      uint4* wp = g_part + (size_t)((tile * 4 + ks) * 4) * 5 * 256 + tid;
      const uint32_t sown = sbase + wg * 8192 + (tid & 127) * 16;
#pragma unroll
      for (int d = 0; d < 4; d++) {
        if (d != ks) {
#pragma unroll
          for (int i = 0; i < 4; i++)
            __stcg(wp + (d * 5 + i) * 256,
                   make_uint4(pack_bf16(acc[d * 32 + i * 8], acc[d * 32 + i * 8 + 1]), pack_bf16(acc[d * 32 + i * 8 + 2], acc[d * 32 + i * 8 + 3]),
                              pack_bf16(acc[d * 32 + i * 8 + 4], acc[d * 32 + i * 8 + 5]), pack_bf16(acc[d * 32 + i * 8 + 6], acc[d * 32 + i * 8 + 7])));
          __stcg(reinterpret_cast<uint2*>(wp - tid + (d * 5 + 4) * 256) + tid,
                 make_uint2(pack_bf16(acc[128 + d * 4], acc[128 + d * 4 + 1]), pack_bf16(acc[128 + d * 4 + 2], acc[128 + d * 4 + 3])));
        } else {
#pragma unroll
          for (int i = 0; i < 9; i++) {
            const int o = (i < 8) ? d * 32 + i * 4 : 128 + d * 4;
            asm volatile("st.shared.v4.f32 [%0], {%1, %2, %3, %4};" ::"r"(sown + (i >> 2) * K3_STAGE + (i & 3) * 2048), "f"(acc[o]), "f"(acc[o + 1]), "f"(acc[o + 2]), "f"(acc[o + 3]) : "memory");
          }
        }
      }
      __threadfence();
      __syncwarp();
      if (wg == 0) TS(2, 5);
      if (lane == 0) {
        unsigned int* cnt = &g_sync[F_XCH + tile * 8 + warp_g];
        const uint32_t xtarget = lds32(sGate + 64) * 4 + 4;
        atomicAdd(cnt, 1u);
        uint32_t v, spins = 0;
        do {
          asm volatile("ld.acquire.gpu.global.u32 %0, [%1];" : "=r"(v) : "l"(cnt) : "memory");
        } while ((int)(v - xtarget) < 0 && ++spins < (1u << 24));
      }
      __syncwarp();
      if (wg == 0) TS(2, 6);
      float r[36];
#pragma unroll
      for (int i = 0; i < 9; i++)
        asm volatile("ld.shared.v4.f32 {%0, %1, %2, %3}, [%4];" : "=f"(r[i * 4]), "=f"(r[i * 4 + 1]), "=f"(r[i * 4 + 2]), "=f"(r[i * 4 + 3])
                     : "r"(sown + (i >> 2) * K3_STAGE + (i & 3) * 2048) : "memory");
#pragma unroll
      for (int sI = 1; sI < 4; sI++) {
        const int src = (ks + sI) & 3;
        const uint4* rp = g_part + (size_t)(((tile * 4 + src) * 4) + ks) * 5 * 256;
#pragma unroll
        for (int i = 0; i < 4; i++) {
          const uint4 v = __ldcg(rp + i * 256 + tid);
          r[i * 8] += bf_lo(v.x); r[i * 8 + 1] += bf_hi(v.x); r[i * 8 + 2] += bf_lo(v.y); r[i * 8 + 3] += bf_hi(v.y);
          r[i * 8 + 4] += bf_lo(v.z); r[i * 8 + 5] += bf_hi(v.z); r[i * 8 + 6] += bf_lo(v.w); r[i * 8 + 7] += bf_hi(v.w);
        }
        const uint2 v = __ldcg(reinterpret_cast<const uint2*>(rp + 4 * 256) + tid);
        r[32] += bf_lo(v.x); r[33] += bf_hi(v.x); r[34] += bf_lo(v.y); r[35] += bf_hi(v.y);
      }
      const int row = mblk * 128 + wg * 64 + warp * 16 + (lane >> 2);
      bf16* o0 = out + (size_t)row * DM + nhalf * 256 + ks * 64 + 8 * q;
#pragma unroll
      for (int G = 0; G < 2; G++) {
        uint32_t a0 = pack_bf16(r[G * 16], r[G * 16 + 1]), a1 = pack_bf16(r[G * 16 + 4], r[G * 16 + 5]);
        uint32_t a2 = pack_bf16(r[G * 16 + 8], r[G * 16 + 9]), a3 = pack_bf16(r[G * 16 + 12], r[G * 16 + 13]);
        uint32_t b0 = pack_bf16(r[G * 16 + 2], r[G * 16 + 3]), b1 = pack_bf16(r[G * 16 + 6], r[G * 16 + 7]);
        uint32_t b2 = pack_bf16(r[G * 16 + 10], r[G * 16 + 11]), b3 = pack_bf16(r[G * 16 + 14], r[G * 16 + 15]);
        quad_transpose(a0, a1, a2, a3, q);
        quad_transpose(b0, b1, b2, b3, q);
        st_v4(o0 + G * 32, a0, a1, a2, a3);
        st_v4(o0 + 8 * DM + G * 32, b0, b1, b2, b3);
      }
      {
        uint32_t t0 = pack_bf16(r[32], r[33]), t1 = pack_bf16(r[34], r[35]), t2 = 0, t3 = 0;
        quad_transpose(t0, t1, t2, t3, q);
        if (q < 2) st_v4(out + (size_t)(row + q * 8) * DM + 512 + nhalf * 32 + ks * 8, t0, t1, t2, t3);
      }
    } else {
      cluster_arrive();
    }
    if (wg == 0) { TS(2, 1); TSC(2, 3); }
    cluster_wait();
  }
}

typedef CUresult (*EncFn)(CUtensorMap*, CUtensorMapDataType, cuuint32_t, void*, const cuuint64_t*, const cuuint64_t*, const cuuint32_t*,
                          const cuuint32_t*, CUtensorMapInterleave, CUtensorMapSwizzle, CUtensorMapL2promotion, CUtensorMapFloatOOBfill);

static void enc2d(EncFn enc, CUtensorMap* m, const void* ptr, uint64_t cols, uint64_t rows, uint32_t bc, uint32_t br,
                  CUtensorMapSwizzle sw = CU_TENSOR_MAP_SWIZZLE_128B) {
  cuuint64_t gd[2] = {cols, rows}, gs[1] = {cols * 2};
  cuuint32_t bx[2] = {bc, br}, es[2] = {1, 1};
  enc(m, CU_TENSOR_MAP_DATA_TYPE_BFLOAT16, 2, const_cast<void*>(ptr), gd, gs, bx, es, CU_TENSOR_MAP_INTERLEAVE_NONE, sw,
      CU_TENSOR_MAP_L2_PROMOTION_L2_256B, CU_TENSOR_MAP_FLOAT_OOB_FILL_NONE);
}
static void enc3d(EncFn enc, CUtensorMap* m, const void* ptr, uint64_t cols, uint64_t rows, uint32_t br, uint32_t bch) {
  cuuint64_t gd[3] = {64, rows, cols / 64}, gs[2] = {cols * 2, 128};
  cuuint32_t bx[3] = {64, br, bch}, es[3] = {1, 1, 1};
  enc(m, CU_TENSOR_MAP_DATA_TYPE_BFLOAT16, 3, const_cast<void*>(ptr), gd, gs, bx, es, CU_TENSOR_MAP_INTERLEAVE_NONE,
      CU_TENSOR_MAP_SWIZZLE_128B, CU_TENSOR_MAP_L2_PROMOTION_L2_256B, CU_TENSOR_MAP_FLOAT_OOB_FILL_NONE);
}

static int g_sched[10] = {11, 10, 7, 4, 4, 4, 6, 8, 6, 24};
static void build_k1_jobs(Params& p) {
  int cnt[NCLUSTER];
  for (int c = 0; c < NCLUSTER; c++) {
    cnt[c] = 0;
    for (int i = 0; i <= K1_MAXJOBS; i++) p.jobs[c][i] = 0;
  }
  auto add = [&](int c, int nch, int a_sel, int mp, int w_sel, int chunk0) {
    p.jobs[c][cnt[c]++] = (uint16_t)((nch - 1) | (a_sel << 2) | (mp << 3) | (w_sel << 6) | (chunk0 << 8));
  };
  const char* plan = "ccccccccccc cccccccccc ccccccc cccc xxxx xxxx xxxxxx xxxxxxxx";
  int TIE = 0;
  int XA = 0;
  const char* cur[8];
  int tend[8] = {};
  for (int g = 0; g < 8; g++) {
    cur[g] = plan;
    while (*plan == 'c' || *plan == 'x') plan++;
    if (*plan) plan++;
  }
  int kc = 0, kx = 0;
  for (;;) {
    int b = -1, bt = 0;
    for (int g = 0; g < 8; g++) {
      const int t = tend[g] + (*cur[g] == 'x' ? 94 : 85);
      if ((*cur[g] == 'c' || *cur[g] == 'x') && (b < 0 || t < bt || (TIE && t == bt))) { b = g; bt = t; }
    }
    if (b < 0) break;
    const int a = kx - XA;
    for (int mp = 0; mp < 8; mp++) {
      if (*cur[b] == 'c') add(b * 8 + mp, 4, 0, mp, kc & 1, (kc >> 1) * 4);
      else if (a >= 0 && a < 7) add(b * 8 + mp, a == 0 ? 3 : 4, 1, mp, 2, a == 0 ? 24 : (a - 1) * 4);
      else add(b * 8 + mp, 4, 1, mp, 3, (a < 0 ? kx : kx - 7) * 4);
    }
    if (*cur[b] == 'c') kc++; else kx++;
    cur[b]++;
    tend[b] = bt;
  }
  for (int mp = 0; mp < 8; mp++) add(64 + mp / 4, 4, 1, mp, 3, 15 * 4);
  for (int cc = 0; cc < NCLUSTER; cc++)
    for (int i = 0; i < cnt[cc]; i++) {
      const int key = p.jobs[cc][i] & 0x3C;
      if (i == 0 || (p.jobs[cc][i - 1] & 0x3C) != key) p.jobs[cc][i] |= (1 << 14);
      if (i == cnt[cc] - 1 || (p.jobs[cc][i + 1] & 0x3C) != key) p.jobs[cc][i] |= (1 << 15);
    }
}

static void build_k2_items(Params& p) {
  int n = 0;
  const int SCHED_N1 = g_sched[8], SCHED_N2 = g_sched[9];
  int N0 = 2, J0 = 2;
  for (int j = 7; j >= J0; j--)
    for (int h = 0; h < N0; h++) p.order[n++] = (uint8_t)(h * 8 + j);
  for (int j = 7; j >= 0; j--)
    for (int h = 0; h < SCHED_N1; h++)
      if (!(h < N0 && j >= J0)) p.order[n++] = (uint8_t)(h * 8 + j);
  for (int j = 7; j >= 4; j--)
    for (int h = SCHED_N1; h < SCHED_N2; h++) p.order[n++] = (uint8_t)(h * 8 + j);
  for (int j = 7; j >= 0; j--)
    for (int h = SCHED_N1; h < 32; h++)
      if (!(h < SCHED_N2 && j >= 4)) p.order[n++] = (uint8_t)(h * 8 + j);
  int TJ[2] = {0, 0}, TP = 0;
  for (int t = 0; t < 2; t++) {
    if (!TJ[t]) continue;
    int i = 0;
    while (p.order[i] != 31 * 8 + TJ[t]) i++;
    for (; i < 255 - TP; i++) p.order[i] = p.order[i + 1];
    p.order[i] = (uint8_t)(31 * 8 + TJ[t]);
  }
}

static void build_k3_units(Params& p) {
  float slope = 0.045f;
  int NE = 25;
  for (int t = 0; t < 16; t++) {
    const int u[4] = {t, 31 - t, 32 + t, 63 - t};
    float acc = 0.f;
    int k0 = 0, l0 = NE;
    for (int i = 0; i < 4; i++) {
      acc += 18.25f + slope * (31.5f - u[i]);
      const int k1 = (i == 3) ? 73 : (int)(acc + 0.5f);
      const int e0 = NE * i / 4, e1 = NE * (i + 1) / 4;
      uint8_t* w = p.unit[u[i]];
      w[0] = (uint8_t)t; w[1] = (uint8_t)i; w[2] = (uint8_t)(k1 - k0); w[3] = (uint8_t)e0; w[4] = (uint8_t)(e1 - e0); w[5] = (uint8_t)(l0 - e1);
      l0 += (k1 - k0) - (e1 - e0);
      k0 = k1;
    }
  }
}

extern "C" void kernel_launch(void* const* d_in, const int* in_sizes, int n_in, void* d_out, int out_size) {
  const bf16* x = (const bf16*)d_in[0];
  const bf16* wqkv = (const bf16*)d_in[1];
  const bf16* wo = (const bf16*)d_in[2];
  const bf16* ckv = (const bf16*)d_in[4];
  const bf16* w_q = (const bf16*)d_in[5];
  const bf16* w_uk = (const bf16*)d_in[6];
  const bf16* w_uv = (const bf16*)d_in[7];
  const bf16* w_o = (const bf16*)d_in[8];
  const bf16* gate_w = (const bf16*)d_in[9];

  EncFn enc = nullptr;
  cudaDriverEntryPointQueryResult qr;
  cudaGetDriverEntryPoint("cuTensorMapEncodeTiled", (void**)&enc, cudaEnableDefault, &qr);
  void *pK, *pV, *pCtx, *pQA;
  cudaGetSymbolAddress(&pQA, g_QKVA);
  cudaGetSymbolAddress(&pK, g_K);
  cudaGetSymbolAddress(&pV, g_V);
  cudaGetSymbolAddress(&pCtx, g_ctx);

  static Params p;
  enc2d(enc, &p.tmA[0], ckv, DC, S_LEN, 64, 128);
  enc2d(enc, &p.tmA[1], x, DM, S_LEN, 64, 128);
  enc3d(enc, &p.tmW[0], w_uk, HDIM, DC, 16, 4);
  enc3d(enc, &p.tmW[1], w_uv, HDIM, DC, 16, 4);
  enc3d(enc, &p.tmW[2], wqkv, NQKVA, DM, 16, 4);
  enc3d(enc, &p.tmW[3], w_q, HDIM, DM, 16, 4);
  build_k1_jobs(p);
  enc2d(enc, &p.tmK, pK, HDIM, S_LEN, 64, 128);
  enc2d(enc, &p.tmV, pV, HDIM, S_LEN, 64, 128);
  build_k2_items(p);
  build_k3_units(p);
  for (int i = 0; i < 3; i++) {
    const cuuint64_t ld = (i < 2 ? NQKVA : KCAT) * 2, nch = (i < 2) ? 27 : 9;
    cuuint64_t gd[4] = {64, S_LEN / 2, i ? 2 : nch, i ? nch : 2}, gs[3] = {2 * ld, i ? ld : 128, i ? 128 : ld};
    cuuint32_t bx[4] = {64, i ? 8u : 16u, i ? 2u : 9u, i ? 9u : 2u}, es[4] = {1, 1, 1, 1};
    enc(&p.tmL[i], CU_TENSOR_MAP_DATA_TYPE_BFLOAT16, 4, (i < 2) ? pQA : (void*)((bf16*)pCtx + HDIM), gd, gs, bx, es, CU_TENSOR_MAP_INTERLEAVE_NONE,
        CU_TENSOR_MAP_SWIZZLE_128B, CU_TENSOR_MAP_L2_PROMOTION_L2_256B, CU_TENSOR_MAP_FLOAT_OOB_FILL_NONE);
  }
  enc2d(enc, &p.tmC, pCtx, KCAT, S_LEN, 64, 128);
  enc3d(enc, &p.tmO[0], w_o, DM, HDIM, 32, 4);
  enc3d(enc, &p.tmO[1], wo, DM, DM, 32, 4);
  enc2d(enc, &p.tmOt[0], w_o, DM, HDIM, 32, 32, CU_TENSOR_MAP_SWIZZLE_64B);
  enc2d(enc, &p.tmOt[1], wo, DM, DM, 32, 32, CU_TENSOR_MAP_SWIZZLE_64B);

  cudaFuncSetAttribute(fused_kernel, cudaFuncAttributeMaxDynamicSharedMemorySize, SMEM_BYTES);
  fused_kernel<<<NCLUSTER * 2, 384, SMEM_BYTES>>>(p, x, gate_w, (bf16*)d_out);
}
```

```cpp
#include <cuda_runtime.h>
#include <cuda_bf16.h>
#include <cuda.h>
#include <stdint.h>

typedef __nv_bfloat16 bf16;

constexpr int S_LEN = 2048, DM = 576, DC = 512, HDIM = 4096, NQKVA = 1728, KCAT = 4672;
constexpr int NCLUSTER = 66;

__device__ __align__(1024) bf16 g_K[S_LEN * HDIM];
__device__ __align__(1024) bf16 g_V[S_LEN * HDIM];
__device__ __align__(1024) bf16 g_QKVA[S_LEN * NQKVA + 64];
__device__ __align__(1024) bf16 g_ctx[S_LEN * KCAT];
__device__ float g_gate[S_LEN];
__device__ __align__(1024) uint4 g_part[32 * 4 * 4 * 5 * 256];
__device__ __align__(16) unsigned int g_sync[400];
constexpr int F_QKVA = 0, F_HP = 16, F_CTX = 32, F_OA = 48, F_GATE = 96, F_TICK = 97, F_DONE = 98, F_XCH = 128, F_EPOCH = 384;

__device__ __forceinline__ uint32_t smem_u32(const void* p) { return (uint32_t)__cvta_generic_to_shared(p); }
__device__ __forceinline__ void mbar_init(uint32_t a, uint32_t c) {
  asm volatile("mbarrier.init.shared::cta.b64 [%0], %1;" ::"r"(a), "r"(c));
}
__device__ __forceinline__ void mbar_expect(uint32_t a, uint32_t b) {
  asm volatile("mbarrier.arrive.expect_tx.shared::cta.b64 _, [%0], %1;" ::"r"(a), "r"(b) : "memory");
}
#define TS(k, i)
#define TSC(k, i)
#define TSM(k)
#define BSEG(i)
#define TB(k)
#define TRC(fl)
#define TCK(i)
#define SPIN_LIMIT "4194304"
__device__ __forceinline__ void mbar_wait(uint32_t a, uint32_t parity) {
  asm volatile(
      "{\n.reg .pred p;\n.reg .u32 n;\n"
      "mbarrier.try_wait.parity.shared::cta.b64 p, [%0], %1;\n"
      "@p bra DONE;\n"
      "mov.u32 n, 0;\n"
      "LOOP:\n"
      "mbarrier.try_wait.parity.shared::cta.b64 p, [%0], %1;\n"
      "@p bra DONE;\n"
      "add.u32 n, n, 1;\n"
      "setp.lt.u32 p, n, " SPIN_LIMIT ";\n"
      "@p bra LOOP;\n"
      "DONE:\n}" ::"r"(a), "r"(parity) : "memory");
}
template <int NS>
__device__ __forceinline__ void mbar_wait_ns(uint32_t a, uint32_t parity) {
  asm volatile(
      "{\n.reg .pred p;\n.reg .u32 n;\n"
      "mov.u32 n, 0;\n"
      "LOOP:\n"
      "mbarrier.try_wait.parity.shared::cta.b64 p, [%0], %1, %2;\n"
      "@p bra DONE;\n"
      "add.u32 n, n, 1;\n"
      "setp.lt.u32 p, n, " SPIN_LIMIT ";\n"
      "@p bra LOOP;\n"
      "DONE:\n}" ::"r"(a), "r"(parity), "n"(NS) : "memory");
}
__device__ __forceinline__ void mbar_wait2(uint32_t a, uint32_t pa, uint32_t b, uint32_t pb) {
  asm volatile(
      "{\n.reg .pred p, q;\n.reg .u32 n;\n"
      "mov.u32 n, 0;\n"
      "LOOP:\n"
      "mbarrier.try_wait.parity.shared::cta.b64 p, [%0], %1;\n"
      "mbarrier.try_wait.parity.shared::cta.b64 q, [%2], %3;\n"
      "add.u32 n, n, 1;\n"
      "and.pred p, p, q;\n"
      "setp.lt.and.u32 p, n, " SPIN_LIMIT ", !p;\n"
      "@p bra LOOP;\n"
      "}" ::"r"(a), "r"(pa), "r"(b), "r"(pb) : "memory");
}
__device__ __forceinline__ uint32_t mbar_test(uint32_t a, uint32_t parity) {
  uint32_t r;
  asm volatile("{\n.reg .pred p;\nmbarrier.test_wait.parity.shared::cta.b64 p, [%1], %2;\nselp.u32 %0, 1, 0, p;\n}" : "=r"(r) : "r"(a), "r"(parity) : "memory");
  return r;
}
__device__ __forceinline__ void mbar_arrive(uint32_t a) {
  asm volatile("mbarrier.arrive.shared::cta.b64 _, [%0];" ::"r"(a) : "memory");
}
__device__ __forceinline__ void mbar_arrive_cluster(uint32_t a, uint32_t cta) {
  asm volatile("{\n.reg .b32 r;\nmapa.shared::cluster.u32 r, %0, %1;\nmbarrier.arrive.shared::cluster.b64 _, [r];\n}" ::"r"(a),
               "r"(cta) : "memory");
}
__device__ __forceinline__ void mbar_arrive_cluster_if(uint32_t a, uint32_t cta, bool pred) {
  asm volatile("{\n.reg .b32 r;\n.reg .pred p;\nsetp.ne.u32 p, %2, 0;\nmapa.shared::cluster.u32 r, %0, %1;\n@p mbarrier.arrive.shared::cluster.b64 _, [r];\n}" ::"r"(a),
               "r"(cta), "r"((uint32_t)pred) : "memory");
}
__device__ __forceinline__ void anchor(float v, uint32_t pred) {
  asm volatile("{\n.reg .pred p;\nsetp.ne.u32 p, %1, 0;\n@p st.shared.f32 [%1], %0;\n}" ::"f"(v), "r"(pred) : "memory");
}
__device__ __forceinline__ void mbar_arrive_if(uint32_t a, bool pred) {
  asm volatile("{\n.reg .pred p;\nsetp.ne.u32 p, %1, 0;\n@p mbarrier.arrive.shared::cta.b64 _, [%0];\n}" ::"r"(a), "r"((uint32_t)pred) : "memory");
}
__device__ __forceinline__ void tma2d(uint32_t dst, const CUtensorMap* m, uint32_t bar, int c0, int c1) {
  asm volatile("cp.async.bulk.tensor.2d.shared::cluster.global.mbarrier::complete_tx::bytes [%0], [%1, {%3, %4}], [%2];" ::"r"(dst),
               "l"(m), "r"(bar), "r"(c0), "r"(c1) : "memory");
}
__device__ __forceinline__ void tma2d_mc(uint32_t dst, const CUtensorMap* m, uint32_t bar, int c0, int c1, uint16_t mask) {
  asm volatile(
      "cp.async.bulk.tensor.2d.shared::cluster.global.mbarrier::complete_tx::bytes.multicast::cluster [%0], [%1, {%3, %4}], [%2], %5;" ::"r"(dst),
      "l"(m), "r"(bar), "r"(c0), "r"(c1), "h"(mask) : "memory");
}
__device__ __forceinline__ void tma3d_mc(uint32_t dst, const CUtensorMap* m, uint32_t bar, int c0, int c1, int c2, uint16_t mask) {
  asm volatile(
      "cp.async.bulk.tensor.3d.shared::cluster.global.mbarrier::complete_tx::bytes.multicast::cluster [%0], [%1, {%3, %4, %5}], [%2], %6;" ::"r"(dst),
      "l"(m), "r"(bar), "r"(c0), "r"(c1), "r"(c2), "h"(mask) : "memory");
}
__device__ __forceinline__ void tma3d(uint32_t dst, const CUtensorMap* m, uint32_t bar, int c0, int c1, int c2) {
  asm volatile(
      "cp.async.bulk.tensor.3d.shared::cluster.global.mbarrier::complete_tx::bytes [%0], [%1, {%3, %4, %5}], [%2];" ::"r"(dst),
      "l"(m), "r"(bar), "r"(c0), "r"(c1), "r"(c2) : "memory");
}
__device__ __forceinline__ void tma_pf2d(const CUtensorMap* m, int c0, int c1) {
  asm volatile("cp.async.bulk.prefetch.tensor.2d.L2.global [%0, {%1, %2}];" ::"l"(m), "r"(c0), "r"(c1) : "memory");
}
__device__ __forceinline__ void tma_pf3d(const CUtensorMap* m, int c0, int c1, int c2) {
  asm volatile("cp.async.bulk.prefetch.tensor.3d.L2.global [%0, {%1, %2, %3}];" ::"l"(m), "r"(c0), "r"(c1), "r"(c2) : "memory");
}
__device__ __forceinline__ void prefetch_tmap(const CUtensorMap* m) {
  asm volatile("prefetch.tensormap [%0];" ::"l"(m) : "memory");
}
__device__ __forceinline__ void cluster_arrive() { asm volatile("barrier.cluster.arrive.relaxed.aligned;" ::: "memory"); }
__device__ __forceinline__ void cluster_wait() { asm volatile("barrier.cluster.wait.aligned;" ::: "memory"); }
__device__ __forceinline__ void cluster_sync() {
  cluster_arrive();
  cluster_wait();
}
__device__ __forceinline__ uint32_t cluster_rank() {
  uint32_t r;
  asm volatile("mov.u32 %0, %%cluster_ctarank;" : "=r"(r));
  return r;
}
__device__ __forceinline__ bool elect_one() {
  uint32_t p;
  asm volatile("{\n.reg .pred q;\nelect.sync _|q, 0xffffffff;\nselp.u32 %0, 1, 0, q;\n}" : "=r"(p));
  return p;
}
__device__ __forceinline__ void ldsm_x4(uint32_t& r0, uint32_t& r1, uint32_t& r2, uint32_t& r3, uint32_t addr) {
  asm volatile("ldmatrix.sync.aligned.m8n8.x4.shared.b16 {%0, %1, %2, %3}, [%4];" : "=r"(r0), "=r"(r1), "=r"(r2), "=r"(r3) : "r"(addr) : "memory");
}
__device__ __forceinline__ void wg_fence() { asm volatile("wgmma.fence.sync.aligned;" ::: "memory"); }
__device__ __forceinline__ void wg_commit() { asm volatile("wgmma.commit_group.sync.aligned;" ::: "memory"); }
template <int N>
__device__ __forceinline__ void wg_wait() { asm volatile("wgmma.wait_group.sync.aligned %0;" ::"n"(N) : "memory"); }
template <int N>
__device__ __forceinline__ void reg_alloc() { asm volatile("setmaxnreg.inc.sync.aligned.u32 %0;" ::"n"(N)); }
template <int N>
__device__ __forceinline__ void reg_dealloc() { asm volatile("setmaxnreg.dec.sync.aligned.u32 %0;" ::"n"(N)); }
__device__ __forceinline__ void bar_sync(int id, int n) { asm volatile("bar.sync %0, %1;" ::"r"(id), "r"(n) : "memory"); }
__device__ __forceinline__ void bar_arrive(int id, int n) { asm volatile("bar.arrive %0, %1;" ::"r"(id), "r"(n) : "memory"); }
template <int NT>
__device__ __forceinline__ void fence_regs(float (&d)[NT]) {
#pragma unroll
  for (int i = 0; i < NT; i++) asm volatile("" : "+f"(d[i])::"memory");
}
template <int NT>
__device__ __forceinline__ void fence_regs(uint32_t (&d)[NT]) {
#pragma unroll
  for (int i = 0; i < NT; i++) asm volatile("" : "+r"(d[i])::"memory");
}
__device__ __forceinline__ uint64_t make_desc(uint32_t saddr, uint32_t lbo, uint32_t sbo, uint32_t layout) {
  return (uint64_t)((saddr & 0x3FFFF) >> 4) | ((uint64_t)(lbo >> 4) << 16) | ((uint64_t)(sbo >> 4) << 32) | ((uint64_t)layout << 62);
}
__device__ __forceinline__ uint32_t pack_bf16(float lo, float hi) {
  uint32_t r;
  asm("cvt.rn.bf16x2.f32 %0, %1, %2;" : "=r"(r) : "f"(hi), "f"(lo));
  return r;
}
__device__ __forceinline__ float ex2(float x) {
  float r;
  asm("ex2.approx.ftz.f32 %0, %1;" : "=f"(r) : "f"(x));
  return r;
}
__device__ __forceinline__ void st_v4(void* p, uint32_t a, uint32_t b, uint32_t c, uint32_t d) {
#define ST_MOD ".cs"
  asm volatile("st.global" ST_MOD ".v4.b32 [%0], {%1, %2, %3, %4};" ::"l"(p), "r"(a), "r"(b), "r"(c), "r"(d) : "memory");
}
#define STA_MOD ".cs"
__device__ __forceinline__ void st_v4a(void* p, uint32_t a, uint32_t b, uint32_t c, uint32_t d) {
  asm volatile("st.global" STA_MOD ".v4.b32 [%0], {%1, %2, %3, %4};" ::"l"(p), "r"(a), "r"(b), "r"(c), "r"(d) : "memory");
}
template <typename T>
__device__ __forceinline__ T* ptr_add(T* base, uint32_t bytes) {
  uint64_t r;
  asm volatile("{\n.reg .u32 l, h;\nmov.b64 {l, h}, %1;\nadd.cc.u32 l, l, %2;\naddc.u32 h, h, 0;\nmov.b64 %0, {l, h};\n}" : "=l"(r) : "l"(base), "r"(bytes));
  return reinterpret_cast<T*>(r);
}
__device__ __forceinline__ float bf_lo(uint32_t v) { return __uint_as_float(v << 16); }
__device__ __forceinline__ float bf_hi(uint32_t v) { return __uint_as_float(v & 0xFFFF0000u); }

__device__ __forceinline__ void quad_transpose(uint32_t& a0, uint32_t& a1, uint32_t& a2, uint32_t& a3, int q) {
  const bool o1 = q & 1, o2 = q & 2;
  uint32_t t0 = o1 ? a0 : a1, t1 = o1 ? a2 : a3;
  t0 = __shfl_xor_sync(0xffffffffu, t0, 1);
  t1 = __shfl_xor_sync(0xffffffffu, t1, 1);
  if (o1) { a0 = t0; a2 = t1; } else { a1 = t0; a3 = t1; }
  t0 = o2 ? a0 : a2;
  t1 = o2 ? a1 : a3;
  t0 = __shfl_xor_sync(0xffffffffu, t0, 2);
  t1 = __shfl_xor_sync(0xffffffffu, t1, 2);
  if (o2) { a0 = t0; a1 = t1; } else { a2 = t0; a3 = t1; }
}

template<int TB, int OFF, int NT>
__device__ __forceinline__ void wgmma_ss_n256(float (&d)[NT], uint64_t da, uint64_t db, int scale_d) {
  asm volatile("{\n.reg .pred p;\nsetp.ne.b32 p, %130, 0;\n"
    "wgmma.mma_async.sync.aligned.m64n256k16.f32.bf16.bf16 {%0, %1, %2, %3, %4, %5, %6, %7, %8, %9, %10, %11, %12, %13, %14, %15, %16, %17, %18, %19, %20, %21, %22, %23, %24, %25, %26, %27, %28, %29, %30, %31, %32, %33, %34, %35, %36, %37, %38, %39, %40, %41, %42, %43, %44, %45, %46, %47, %48, %49, %50, %51, %52, %53, %54, %55, %56, %57, %58, %59, %60, %61, %62, %63, %64, %65, %66, %67, %68, %69, %70, %71, %72, %73, %74, %75, %76, %77, %78, %79, %80, %81, %82, %83, %84, %85, %86, %87, %88, %89, %90, %91, %92, %93, %94, %95, %96, %97, %98, %99, %100, %101, %102, %103, %104, %105, %106, %107, %108, %109, %110, %111, %112, %113, %114, %115, %116, %117, %118, %119, %120, %121, %122, %123, %124, %125, %126, %127}, %128, %129, p, 1, 1, 0, %131;\n}\n"
    : "+f"(d[OFF+0]), "+f"(d[OFF+1]), "+f"(d[OFF+2]), "+f"(d[OFF+3]), "+f"(d[OFF+4]), "+f"(d[OFF+5]), "+f"(d[OFF+6]), "+f"(d[OFF+7]), "+f"(d[OFF+8]), "+f"(d[OFF+9]), "+f"(d[OFF+10]), "+f"(d[OFF+11]), "+f"(d[OFF+12]), "+f"(d[OFF+13]), "+f"(d[OFF+14]), "+f"(d[OFF+15]), "+f"(d[OFF+16]), "+f"(d[OFF+17]), "+f"(d[OFF+18]), "+f"(d[OFF+19]), "+f"(d[OFF+20]), "+f"(d[OFF+21]), "+f"(d[OFF+22]), "+f"(d[OFF+23]), "+f"(d[OFF+24]), "+f"(d[OFF+25]), "+f"(d[OFF+26]), "+f"(d[OFF+27]), "+f"(d[OFF+28]), "+f"(d[OFF+29]), "+f"(d[OFF+30]), "+f"(d[OFF+31]), "+f"(d[OFF+32]), "+f"(d[OFF+33]), "+f"(d[OFF+34]), "+f"(d[OFF+35]), "+f"(d[OFF+36]), "+f"(d[OFF+37]), "+f"(d[OFF+38]), "+f"(d[OFF+39]), "+f"(d[OFF+40]), "+f"(d[OFF+41]), "+f"(d[OFF+42]), "+f"(d[OFF+43]), "+f"(d[OFF+44]), "+f"(d[OFF+45]), "+f"(d[OFF+46]), "+f"(d[OFF+47]), "+f"(d[OFF+48]), "+f"(d[OFF+49]), "+f"(d[OFF+50]), "+f"(d[OFF+51]), "+f"(d[OFF+52]), "+f"(d[OFF+53]), "+f"(d[OFF+54]), "+f"(d[OFF+55]), "+f"(d[OFF+56]), "+f"(d[OFF+57]), "+f"(d[OFF+58]), "+f"(d[OFF+59]), "+f"(d[OFF+60]), "+f"(d[OFF+61]), "+f"(d[OFF+62]), "+f"(d[OFF+63]), "+f"(d[OFF+64]), "+f"(d[OFF+65]), "+f"(d[OFF+66]), "+f"(d[OFF+67]), "+f"(d[OFF+68]), "+f"(d[OFF+69]), "+f"(d[OFF+70]), "+f"(d[OFF+71]), "+f"(d[OFF+72]), "+f"(d[OFF+73]), "+f"(d[OFF+74]), "+f"(d[OFF+75]), "+f"(d[OFF+76]), "+f"(d[OFF+77]), "+f"(d[OFF+78]), "+f"(d[OFF+79]), "+f"(d[OFF+80]), "+f"(d[OFF+81]), "+f"(d[OFF+82]), "+f"(d[OFF+83]), "+f"(d[OFF+84]), "+f"(d[OFF+85]), "+f"(d[OFF+86]), "+f"(d[OFF+87]), "+f"(d[OFF+88]), "+f"(d[OFF+89]), "+f"(d[OFF+90]), "+f"(d[OFF+91]), "+f"(d[OFF+92]), "+f"(d[OFF+93]), "+f"(d[OFF+94]), "+f"(d[OFF+95]), "+f"(d[OFF+96]), "+f"(d[OFF+97]), "+f"(d[OFF+98]), "+f"(d[OFF+99]), "+f"(d[OFF+100]), "+f"(d[OFF+101]), "+f"(d[OFF+102]), "+f"(d[OFF+103]), "+f"(d[OFF+104]), "+f"(d[OFF+105]), "+f"(d[OFF+106]), "+f"(d[OFF+107]), "+f"(d[OFF+108]), "+f"(d[OFF+109]), "+f"(d[OFF+110]), "+f"(d[OFF+111]), "+f"(d[OFF+112]), "+f"(d[OFF+113]), "+f"(d[OFF+114]), "+f"(d[OFF+115]), "+f"(d[OFF+116]), "+f"(d[OFF+117]), "+f"(d[OFF+118]), "+f"(d[OFF+119]), "+f"(d[OFF+120]), "+f"(d[OFF+121]), "+f"(d[OFF+122]), "+f"(d[OFF+123]), "+f"(d[OFF+124]), "+f"(d[OFF+125]), "+f"(d[OFF+126]), "+f"(d[OFF+127])
    : "l"(da), "l"(db), "r"(scale_d), "n"(TB));
}
template<int TB, int OFF, int NT>
__device__ __forceinline__ void wgmma_ss_n32(float (&d)[NT], uint64_t da, uint64_t db, int scale_d) {
  asm volatile("{\n.reg .pred p;\nsetp.ne.b32 p, %18, 0;\n"
    "wgmma.mma_async.sync.aligned.m64n32k16.f32.bf16.bf16 {%0, %1, %2, %3, %4, %5, %6, %7, %8, %9, %10, %11, %12, %13, %14, %15}, %16, %17, p, 1, 1, 0, %19;\n}\n"
    : "+f"(d[OFF+0]), "+f"(d[OFF+1]), "+f"(d[OFF+2]), "+f"(d[OFF+3]), "+f"(d[OFF+4]), "+f"(d[OFF+5]), "+f"(d[OFF+6]), "+f"(d[OFF+7]), "+f"(d[OFF+8]), "+f"(d[OFF+9]), "+f"(d[OFF+10]), "+f"(d[OFF+11]), "+f"(d[OFF+12]), "+f"(d[OFF+13]), "+f"(d[OFF+14]), "+f"(d[OFF+15])
    : "l"(da), "l"(db), "r"(scale_d), "n"(TB));
}
template<int TB, int OFF, int NT>
__device__ __forceinline__ void wgmma_rs_n128(float (&d)[NT], uint32_t a0, uint32_t a1, uint32_t a2, uint32_t a3, uint64_t db, int scale_d) {
  asm volatile("{\n.reg .pred p;\nsetp.ne.b32 p, %69, 0;\n"
    "wgmma.mma_async.sync.aligned.m64n128k16.f32.bf16.bf16 {%0, %1, %2, %3, %4, %5, %6, %7, %8, %9, %10, %11, %12, %13, %14, %15, %16, %17, %18, %19, %20, %21, %22, %23, %24, %25, %26, %27, %28, %29, %30, %31, %32, %33, %34, %35, %36, %37, %38, %39, %40, %41, %42, %43, %44, %45, %46, %47, %48, %49, %50, %51, %52, %53, %54, %55, %56, %57, %58, %59, %60, %61, %62, %63}, {%64, %65, %66, %67}, %68, p, 1, 1, %70;\n}\n"
    : "+f"(d[OFF+0]), "+f"(d[OFF+1]), "+f"(d[OFF+2]), "+f"(d[OFF+3]), "+f"(d[OFF+4]), "+f"(d[OFF+5]), "+f"(d[OFF+6]), "+f"(d[OFF+7]), "+f"(d[OFF+8]), "+f"(d[OFF+9]), "+f"(d[OFF+10]), "+f"(d[OFF+11]), "+f"(d[OFF+12]), "+f"(d[OFF+13]), "+f"(d[OFF+14]), "+f"(d[OFF+15]), "+f"(d[OFF+16]), "+f"(d[OFF+17]), "+f"(d[OFF+18]), "+f"(d[OFF+19]), "+f"(d[OFF+20]), "+f"(d[OFF+21]), "+f"(d[OFF+22]), "+f"(d[OFF+23]), "+f"(d[OFF+24]), "+f"(d[OFF+25]), "+f"(d[OFF+26]), "+f"(d[OFF+27]), "+f"(d[OFF+28]), "+f"(d[OFF+29]), "+f"(d[OFF+30]), "+f"(d[OFF+31]), "+f"(d[OFF+32]), "+f"(d[OFF+33]), "+f"(d[OFF+34]), "+f"(d[OFF+35]), "+f"(d[OFF+36]), "+f"(d[OFF+37]), "+f"(d[OFF+38]), "+f"(d[OFF+39]), "+f"(d[OFF+40]), "+f"(d[OFF+41]), "+f"(d[OFF+42]), "+f"(d[OFF+43]), "+f"(d[OFF+44]), "+f"(d[OFF+45]), "+f"(d[OFF+46]), "+f"(d[OFF+47]), "+f"(d[OFF+48]), "+f"(d[OFF+49]), "+f"(d[OFF+50]), "+f"(d[OFF+51]), "+f"(d[OFF+52]), "+f"(d[OFF+53]), "+f"(d[OFF+54]), "+f"(d[OFF+55]), "+f"(d[OFF+56]), "+f"(d[OFF+57]), "+f"(d[OFF+58]), "+f"(d[OFF+59]), "+f"(d[OFF+60]), "+f"(d[OFF+61]), "+f"(d[OFF+62]), "+f"(d[OFF+63])
    : "r"(a0), "r"(a1), "r"(a2), "r"(a3), "l"(db), "r"(scale_d), "n"(TB));
}
template<int TB, int OFF, int NT>
__device__ __forceinline__ void wgmma_rs_n256(float (&d)[NT], uint32_t a0, uint32_t a1, uint32_t a2, uint32_t a3, uint64_t db, int scale_d) {
  asm volatile("{\n.reg .pred p;\nsetp.ne.b32 p, %133, 0;\n"
    "wgmma.mma_async.sync.aligned.m64n256k16.f32.bf16.bf16 {%0, %1, %2, %3, %4, %5, %6, %7, %8, %9, %10, %11, %12, %13, %14, %15, %16, %17, %18, %19, %20, %21, %22, %23, %24, %25, %26, %27, %28, %29, %30, %31, %32, %33, %34, %35, %36, %37, %38, %39, %40, %41, %42, %43, %44, %45, %46, %47, %48, %49, %50, %51, %52, %53, %54, %55, %56, %57, %58, %59, %60, %61, %62, %63, %64, %65, %66, %67, %68, %69, %70, %71, %72, %73, %74, %75, %76, %77, %78, %79, %80, %81, %82, %83, %84, %85, %86, %87, %88, %89, %90, %91, %92, %93, %94, %95, %96, %97, %98, %99, %100, %101, %102, %103, %104, %105, %106, %107, %108, %109, %110, %111, %112, %113, %114, %115, %116, %117, %118, %119, %120, %121, %122, %123, %124, %125, %126, %127}, {%128, %129, %130, %131}, %132, p, 1, 1, %134;\n}\n"
    : "+f"(d[OFF+0]), "+f"(d[OFF+1]), "+f"(d[OFF+2]), "+f"(d[OFF+3]), "+f"(d[OFF+4]), "+f"(d[OFF+5]), "+f"(d[OFF+6]), "+f"(d[OFF+7]), "+f"(d[OFF+8]), "+f"(d[OFF+9]), "+f"(d[OFF+10]), "+f"(d[OFF+11]), "+f"(d[OFF+12]), "+f"(d[OFF+13]), "+f"(d[OFF+14]), "+f"(d[OFF+15]), "+f"(d[OFF+16]), "+f"(d[OFF+17]), "+f"(d[OFF+18]), "+f"(d[OFF+19]), "+f"(d[OFF+20]), "+f"(d[OFF+21]), "+f"(d[OFF+22]), "+f"(d[OFF+23]), "+f"(d[OFF+24]), "+f"(d[OFF+25]), "+f"(d[OFF+26]), "+f"(d[OFF+27]), "+f"(d[OFF+28]), "+f"(d[OFF+29]), "+f"(d[OFF+30]), "+f"(d[OFF+31]), "+f"(d[OFF+32]), "+f"(d[OFF+33]), "+f"(d[OFF+34]), "+f"(d[OFF+35]), "+f"(d[OFF+36]), "+f"(d[OFF+37]), "+f"(d[OFF+38]), "+f"(d[OFF+39]), "+f"(d[OFF+40]), "+f"(d[OFF+41]), "+f"(d[OFF+42]), "+f"(d[OFF+43]), "+f"(d[OFF+44]), "+f"(d[OFF+45]), "+f"(d[OFF+46]), "+f"(d[OFF+47]), "+f"(d[OFF+48]), "+f"(d[OFF+49]), "+f"(d[OFF+50]), "+f"(d[OFF+51]), "+f"(d[OFF+52]), "+f"(d[OFF+53]), "+f"(d[OFF+54]), "+f"(d[OFF+55]), "+f"(d[OFF+56]), "+f"(d[OFF+57]), "+f"(d[OFF+58]), "+f"(d[OFF+59]), "+f"(d[OFF+60]), "+f"(d[OFF+61]), "+f"(d[OFF+62]), "+f"(d[OFF+63]), "+f"(d[OFF+64]), "+f"(d[OFF+65]), "+f"(d[OFF+66]), "+f"(d[OFF+67]), "+f"(d[OFF+68]), "+f"(d[OFF+69]), "+f"(d[OFF+70]), "+f"(d[OFF+71]), "+f"(d[OFF+72]), "+f"(d[OFF+73]), "+f"(d[OFF+74]), "+f"(d[OFF+75]), "+f"(d[OFF+76]), "+f"(d[OFF+77]), "+f"(d[OFF+78]), "+f"(d[OFF+79]), "+f"(d[OFF+80]), "+f"(d[OFF+81]), "+f"(d[OFF+82]), "+f"(d[OFF+83]), "+f"(d[OFF+84]), "+f"(d[OFF+85]), "+f"(d[OFF+86]), "+f"(d[OFF+87]), "+f"(d[OFF+88]), "+f"(d[OFF+89]), "+f"(d[OFF+90]), "+f"(d[OFF+91]), "+f"(d[OFF+92]), "+f"(d[OFF+93]), "+f"(d[OFF+94]), "+f"(d[OFF+95]), "+f"(d[OFF+96]), "+f"(d[OFF+97]), "+f"(d[OFF+98]), "+f"(d[OFF+99]), "+f"(d[OFF+100]), "+f"(d[OFF+101]), "+f"(d[OFF+102]), "+f"(d[OFF+103]), "+f"(d[OFF+104]), "+f"(d[OFF+105]), "+f"(d[OFF+106]), "+f"(d[OFF+107]), "+f"(d[OFF+108]), "+f"(d[OFF+109]), "+f"(d[OFF+110]), "+f"(d[OFF+111]), "+f"(d[OFF+112]), "+f"(d[OFF+113]), "+f"(d[OFF+114]), "+f"(d[OFF+115]), "+f"(d[OFF+116]), "+f"(d[OFF+117]), "+f"(d[OFF+118]), "+f"(d[OFF+119]), "+f"(d[OFF+120]), "+f"(d[OFF+121]), "+f"(d[OFF+122]), "+f"(d[OFF+123]), "+f"(d[OFF+124]), "+f"(d[OFF+125]), "+f"(d[OFF+126]), "+f"(d[OFF+127])
    : "r"(a0), "r"(a1), "r"(a2), "r"(a3), "l"(db), "r"(scale_d), "n"(TB));
}
template<int TB, int OFF, int NT>
__device__ __forceinline__ void wgmma_rs_n32(float (&d)[NT], uint32_t a0, uint32_t a1, uint32_t a2, uint32_t a3, uint64_t db, int scale_d) {
  asm volatile("{\n.reg .pred p;\nsetp.ne.b32 p, %21, 0;\n"
    "wgmma.mma_async.sync.aligned.m64n32k16.f32.bf16.bf16 {%0, %1, %2, %3, %4, %5, %6, %7, %8, %9, %10, %11, %12, %13, %14, %15}, {%16, %17, %18, %19}, %20, p, 1, 1, %22;\n}\n"
    : "+f"(d[OFF+0]), "+f"(d[OFF+1]), "+f"(d[OFF+2]), "+f"(d[OFF+3]), "+f"(d[OFF+4]), "+f"(d[OFF+5]), "+f"(d[OFF+6]), "+f"(d[OFF+7]), "+f"(d[OFF+8]), "+f"(d[OFF+9]), "+f"(d[OFF+10]), "+f"(d[OFF+11]), "+f"(d[OFF+12]), "+f"(d[OFF+13]), "+f"(d[OFF+14]), "+f"(d[OFF+15])
    : "r"(a0), "r"(a1), "r"(a2), "r"(a3), "l"(db), "r"(scale_d), "n"(TB));
}

__device__ __forceinline__ void wait_flag(const unsigned int* f, uint32_t target) {
  uint32_t v;
#pragma unroll 1
  for (uint32_t spins = 0; spins < (1u << 22); spins++) {
    asm volatile("ld.acquire.gpu.global.u32 %0, [%1];" : "=r"(v) : "l"(f) : "memory");
    if (v >= target) break;
    __nanosleep(100);
  }
}
__device__ __forceinline__ uint32_t lds32(uint32_t a) {
  uint32_t v;
  asm volatile("ld.shared.u32 %0, [%1];" : "=r"(v) : "r"(a) : "memory");
  return v;
}
__device__ __forceinline__ float gate_row(int row, int lane, const bf16* __restrict__ x, const bf16* __restrict__ gate_w) {
  const uint32_t* xr = reinterpret_cast<const uint32_t*>(x + (size_t)row * DM);
  const uint32_t* gw2 = reinterpret_cast<const uint32_t*>(gate_w);
  float gs = 0.f;
#pragma unroll
  for (int i = 0; i < 9; i++) {
    const uint32_t a = __ldg(xr + lane + 32 * i), b = __ldg(gw2 + lane + 32 * i);
    gs = fmaf(bf_lo(a), bf_lo(b), gs);
    gs = fmaf(bf_hi(a), bf_hi(b), gs);
  }
#pragma unroll
  for (int o = 16; o; o >>= 1) gs += __shfl_xor_sync(0xffffffffu, gs, o);
  const float g = 1.f / (1.f + __expf(-gs));
  if (lane == 0) g_gate[row] = g;
  return g;
}
constexpr uint32_t LQ = 36864, LV = 55296;
__device__ __forceinline__ void mma16(float (&c)[4], uint32_t a0, uint32_t a1, uint32_t a2, uint32_t a3, uint32_t b0, uint32_t b1) {
  asm("mma.sync.aligned.m16n8k16.row.col.f32.bf16.bf16.f32 {%0, %1, %2, %3}, {%4, %5, %6, %7}, {%8, %9}, {%0, %1, %2, %3};"
      : "+f"(c[0]), "+f"(c[1]), "+f"(c[2]), "+f"(c[3]) : "r"(a0), "r"(a1), "r"(a2), "r"(a3), "r"(b0), "r"(b1));
}
__device__ __forceinline__ void mma8(float (&c)[4], uint32_t a0, uint32_t a1, uint32_t b0) {
  asm("mma.sync.aligned.m16n8k8.row.col.f32.bf16.bf16.f32 {%0, %1, %2, %3}, {%4, %5}, {%6}, {%0, %1, %2, %3};"
      : "+f"(c[0]), "+f"(c[1]), "+f"(c[2]), "+f"(c[3]) : "r"(a0), "r"(a1), "r"(b0));
}
template <typename F>
__device__ __forceinline__ void local_attn(int lr0, int warp_g, uint32_t sL, uint32_t bL, uint32_t bL2, int lane, float g0, float g1, F st) {
  const float scale_l2 = 0.23570226039551584f * 1.4426950408889634f;
  const int g = lane >> 2, t = lane & 3;
  const bool lo0 = 2 * t > g, lo1 = 2 * t + 1 > g;
  const bool ok0 = lr0 > 0 || !lo0, ok1 = lr0 > 0 || !lo1;
  const uint32_t mlo = (lo0 ? 0xFFFFu : 0u) | (lo1 ? 0xFFFF0000u : 0u);
  uint32_t ad[9], k[9][4], qf[9][2], pe[4], po[4];
#pragma unroll
  for (int c = 0; c < 9; c++) {
    const uint32_t ch = warp_g * 9 + c;
    ad[c] = sL + (lane >> 4) * 18432 + (lane & 15) * 128 + ((ch >> 3) << 11) + (((ch ^ lane) & 7) << 4);
  }
  st(0, 0u); st(1, 0u);
  mbar_wait(bL, 0);
  if (warp_g == 0) TS(1, 6);
#pragma unroll
  for (int c = 0; c < 9; c++) {
    asm volatile("ldmatrix.sync.aligned.m8n8.x2.shared.b16 {%0, %1}, [%2];" : "=r"(qf[c][0]), "=r"(qf[c][1]) : "r"(ad[c] + LQ) : "memory");
    ldsm_x4(k[c][0], k[c][1], k[c][2], k[c][3], ad[c]);
  }
  st(2, k[0][0]); st(3, k[8][0]);
#pragma unroll
  for (int i = 0; i < 4; i++) {
    const uint32_t q0 = (t >= i) ? qf[2 * i][0] : 0u, q1 = (t >= i) ? qf[2 * i][1] : 0u;
    const uint32_t q4 = (t <= i) ? qf[2 * i + 2][0] : 0u, q5 = (t <= i) ? qf[2 * i + 2][1] : 0u;
    float c[4][4];
#pragma unroll
    for (int T = 0; T < 4; T++) {
#pragma unroll
      for (int j = 0; j < 4; j++) c[T][j] = 0.f;
      mma16(c[T], q0, q1, qf[2 * i + 1][0], qf[2 * i + 1][1], k[2 * i][T], k[2 * i + 1][T]);
      mma8(c[T], q4, q5, k[2 * i + 2][T]);
    }
    const float e0 = ok0 ? (lo0 ? c[0][0] : c[1][0]) : -INFINITY, e1 = ok1 ? (lo1 ? c[0][1] : c[1][1]) : -INFINITY;
    const float o0 = ok0 ? (lo0 ? c[2][2] : c[3][2]) : -INFINITY, o1 = ok1 ? (lo1 ? c[2][3] : c[3][3]) : -INFINITY;
    float me = fmaxf(e0, e1), mo = fmaxf(o0, o1);
    me = fmaxf(me, __shfl_xor_sync(0xffffffffu, me, 1));
    mo = fmaxf(mo, __shfl_xor_sync(0xffffffffu, mo, 1));
    me = fmaxf(me, __shfl_xor_sync(0xffffffffu, me, 2)) * scale_l2;
    mo = fmaxf(mo, __shfl_xor_sync(0xffffffffu, mo, 2)) * scale_l2;
    const float w0 = ex2(fmaf(e0, scale_l2, -me)), w1 = ex2(fmaf(e1, scale_l2, -me));
    const float w2 = ex2(fmaf(o0, scale_l2, -mo)), w3 = ex2(fmaf(o1, scale_l2, -mo));
    float se = w0 + w1, so = w2 + w3;
    st(4 + 2 * i, __float_as_uint(i == 1 ? me : i == 2 ? se : e0));
    se += __shfl_xor_sync(0xffffffffu, se, 1);
    so += __shfl_xor_sync(0xffffffffu, so, 1);
    se += __shfl_xor_sync(0xffffffffu, se, 2);
    so += __shfl_xor_sync(0xffffffffu, so, 2);
    asm("rcp.approx.ftz.f32 %0, %0;" : "+f"(se));
    asm("rcp.approx.ftz.f32 %0, %0;" : "+f"(so));
    se *= g0;
    so *= g1;
    pe[i] = pack_bf16(w0 * se, w1 * se);
    po[i] = pack_bf16(w2 * so, w3 * so);
    st(5 + 2 * i, i == 0 ? __float_as_uint(w0) : i == 2 ? __float_as_uint(mo) : po[i]);
  }
  if (warp_g == 0) TS(0, 4);
  mbar_wait(bL2, 0);
  if (warp_g == 0) TS(0, 5);
#pragma unroll
  for (int c = 0; c < 9; c++)
    asm volatile("ldmatrix.sync.aligned.m8n8.x4.trans.shared.b16 {%0, %1, %2, %3}, [%4];"
                 : "=r"(k[c][0]), "=r"(k[c][1]), "=r"(k[c][2]), "=r"(k[c][3]) : "r"(ad[c] + LV) : "memory");
#pragma unroll
  for (int i = 0; i < 4; i++) {
#pragma unroll
    for (int n = 0; n < 3; n++) {
      float c[4] = {0.f, 0.f, 0.f, 0.f};
      mma16(c, pe[i] & mlo, 0u, pe[i] & ~mlo, 0u, k[2 * i + n][0], k[2 * i + n][1]);
      mma16(c, 0u, po[i] & mlo, 0u, po[i] & ~mlo, k[2 * i + n][2], k[2 * i + n][3]);
      const uint32_t r0 = pack_bf16(c[0], c[1]), r1 = pack_bf16(c[2], c[3]);
      const bool keep = (n == 0) && (i > 0) && (t < i);
      qf[2 * i + n][0] = keep ? qf[2 * i + n][0] : r0;
      qf[2 * i + n][1] = keep ? qf[2 * i + n][1] : r1;
    }
    st(12 + i, qf[2 * i + 1][0]);
  }
#pragma unroll
  for (int c = 0; c < 9; c++)
    asm volatile("stmatrix.sync.aligned.m8n8.x2.shared.b16 [%0], {%1, %2};" ::"r"(ad[c] + LQ), "r"(qf[c][0]), "r"(qf[c][1]) : "memory");
  asm volatile("fence.proxy.async.shared::cta;" ::: "memory");
}
__device__ __forceinline__ void tma4d(uint32_t dst, const CUtensorMap* m, uint32_t bar, int c1, int c2, int c3) {
  asm volatile("cp.async.bulk.tensor.4d.shared::cluster.global.mbarrier::complete_tx::bytes [%0], [%1, {%3, %4, %5, %6}], [%2];" ::"r"(dst),
               "l"(m), "r"(bar), "r"(0), "r"(c1), "r"(c2), "r"(c3) : "memory");
}

#define ST_NUM 1
#define ST_DEN 2
#define K1_NST 6
constexpr int K1_BST = K1_NST;
#define MAXJ 11
constexpr int K1_MAXJOBS = MAXJ;
constexpr uint32_t K1_FLAG_TARGET = 7;
constexpr uint32_t RDY_TARGET = 48;
constexpr uint32_t GATE_TARGET = 128 * 3;
struct alignas(64) Params {
  CUtensorMap tmA[2];
  CUtensorMap tmW[4];
  CUtensorMap tmK, tmV;
  CUtensorMap tmL[3];
  CUtensorMap tmC, tmO[2], tmOt[2];
  uint16_t jobs[NCLUSTER][K1_MAXJOBS + 1];
  uint8_t order[256];
  uint8_t unit[65][8];
};

struct K1State {
  uint32_t bs, bph, aph;
  bf16 *pp, *pp8;
  int png;
  int tn;
  int wsel;
  uint32_t fo;
};
__device__ __forceinline__ void k1_flag(const K1State& st, int lane, uint32_t bS) {
  if (st.png) {
    __syncwarp();
    if (lane == 0) mbar_arrive(bS + st.fo);
  }
}

__device__ __forceinline__ void scale_q4(uint32_t* v) {
#pragma unroll
  for (int i = 0; i < 4; i++)
    asm volatile("{\n.reg .b32 t;\nmul.rn.bf16x2 t, %0, %2;\nfma.rn.bf16x2 %0, %0, %1, t;\n}" : "+r"(v[i]) : "r"(0x3E033E03u), "r"(0xB9D8B9D8u));
}
__device__ __forceinline__ void k1_first(const K1State& st, uint32_t job, uint32_t bAf, uint32_t bBf) {
  if (job & 3) {
    if ((job >> 14) & 1) mbar_wait(bAf, st.aph);
    mbar_wait(bBf + st.bs * 8, st.bph);
  }
}
__device__ __forceinline__ void k1_tile(float (&acc)[128], uint32_t (&pk)[64], K1State& st, uint32_t job, uint32_t njob, uint32_t sA, uint32_t sB,
                                        uint32_t bAf, uint32_t bAe, uint32_t bBf, uint32_t bBe, uint32_t bS, int wg, int warp, int lane, uint32_t rank) {
  const int a_sel = (job >> 2) & 1, mpair = (job >> 3) & 7, w_sel = (job >> 6) & 3, chunk0 = (job >> 8) & 63;
  const bool newA = (job >> 14) & 1, lastA = (job >> 15) & 1;
  const bool sig = (lane == 0) && (warp < 2);
  const bool siga = lastA && (lane == 0) && (warp == 2);
  const int KC = 8 + a_sel;
  uint32_t prev_bs = 0, a8_bs = 0;
#pragma unroll
  for (int kc = 0; kc < 9; kc++) {
    if (kc >= KC) break;
    uint32_t abase = sA + ((kc + 2) & 7) * 16384;
    if (kc == 8) {
      mbar_wait(bBf + st.bs * 8, st.bph);
      a8_bs = st.bs;
      abase = sB + st.bs * 16384;
      if (++st.bs == K1_BST) { st.bs = 0; st.bph ^= 1; }
    } else if (newA && kc > 0) {
      mbar_wait(bAf + kc * 8, st.aph);
    }
    const uint64_t da = make_desc(abase + wg * 8192, 16, 1024, 1);
#pragma unroll
    for (int ks = 0; ks < 2; ks++) {
      if (ks > 0 || kc > 0) mbar_wait(bBf + st.bs * 8, st.bph);
      const uint64_t db = make_desc(sB + st.bs * 16384, 2048, 1024, 1);
      wg_fence();
      wgmma_ss_n256<1, 0>(acc, da + (uint64_t)(ks * 4), db, (ks > 0) ? 1 : (kc > 0));
      wgmma_ss_n256<1, 0>(acc, da + (uint64_t)(ks * 4 + 2), db + (uint64_t)512, 1);
      wg_commit();
      wg_wait<1>();
      if (ks > 0 || kc > 0) {
        if (sig) mbar_arrive_cluster(bBe + prev_bs * 8, warp);
        if (ks == 0 && siga) mbar_arrive(bAe + (kc - 1) * 8);
      }
      if (st.wsel == 2) {
        const int i = (kc & 7) * 2 + ks;
        if (kc < st.png) {
          quad_transpose(pk[i * 4], pk[i * 4 + 1], pk[i * 4 + 2], pk[i * 4 + 3], lane & 3);
          st_v4a((ks ? st.pp8 : st.pp) + kc * 32, pk[i * 4], pk[i * 4 + 1], pk[i * 4 + 2], pk[i * 4 + 3]);
        }
        if (i == 15) k1_flag(st, lane, bS);
      } else if (st.png) {
#pragma unroll
        for (int i = 0; i < 16; i++) {
          if (i * ST_NUM / ST_DEN != kc * 2 + ks) continue;
          if (st.wsel == 3) scale_q4(pk + i * 4);
          st_v4a(((i & 1) ? st.pp8 : st.pp) + (i / 2) * 32, pk[i * 4], pk[i * 4 + 1], pk[i * 4 + 2], pk[i * 4 + 3]);
          if (i == 15) k1_flag(st, lane, bS);
        }
      }
      prev_bs = st.bs;
      if (++st.bs == K1_BST) { st.bs = 0; st.bph ^= 1; }
    }
  }
  if (newA) st.aph ^= 1;
  const bool isA = (w_sel == 2);
  bf16* out = (w_sel == 0) ? g_K : (w_sel == 1) ? g_V : isA ? g_QKVA : g_ctx;
  const int ld = isA ? NQKVA : (w_sel == 3) ? KCAT : HDIM;
  const int row = mpair * 256 + rank * 128 + wg * 64 + warp * 16 + (lane >> 2);
  st.pp = ptr_add(out, (row * ld + chunk0 * 64 + (lane & 3) * 8) * 2);
  st.pp8 = ptr_add(st.pp, 16 * ld);
  st.png = ((job & 3) + 1) * 2;
  st.wsel = w_sel;
  st.fo = (st.fo + 8) & 24;
  k1_first(st, njob, bAf, bBf);
  wg_wait<0>();
  fence_regs(acc);
  mbar_arrive_cluster_if(bBe + prev_bs * 8, warp & 1, sig);
  mbar_arrive_cluster_if(bBe + a8_bs * 8, warp & 1, sig && a_sel);
  mbar_arrive_if(bAe + 7 * 8, siga && !a_sel);
#pragma unroll
  for (int i = 0; i < 64; i++) {
    const int j = (i >> 3) * 16 + (i & 3) * 4 + ((i >> 2) & 1) * 2;
    pk[i] = pack_bf16(acc[j], acc[j + 1]);
  }
}

constexpr int K2_NST = 7;
constexpr uint32_t K2_END = 0x100;
#define PFD 4
#define PF3A 2
#define PF3 6
#define KC0 1
#define CLEAD 2
#define FIRST_DRAW 3
#define PWAIT mbar_wait_ns<1000>
#define PVM 0x8A
#define W0 63
#define SPEC_HI 1.8446744073709552e19f
#define SPEC_LO 5.421010862427522e-20f
constexpr int K3_NST = 4;
__device__ __forceinline__ uint32_t k3_rot(uint32_t sv) { return (0x00E9u >> (2 * sv)) & 3; }
constexpr int K3_STAGE = 16384 + 32768 + 4096;
constexpr int SMEM_DATA = 7 * 32768;
constexpr int SMEM_BYTES = SMEM_DATA + 1024 + 768;

struct Cursor {
  uint32_t s, ph;
  __device__ __forceinline__ void next() {
    if (++s == K2_NST) { s = 0; ph ^= 1; }
  }
};

#define TURN_SYNC() bar_sync(mybar, 256)
#define TURN_ARRIVE() bar_arrive(otherbar, 256)
#define RELEASE_IF(cur, cond) mbar_arrive_cluster_if(bE + (cur).s * 8, warp & 1, sig && (cond))
#define RELEASE(cur) RELEASE_IF(cur, true)
#define ISSUE_PV(cur, first)                                                                                   \
  do {                                                                                                         \
    const uint64_t dv = make_desc(sbase + (cur).s * 32768, 16384, 1024, 1);                                    \
    _Pragma("unroll") for (int t = 0; t < 8; t++)                                                              \
        wgmma_rs_n128<1, 0>(O, P[4 * t], P[4 * t + 1], P[4 * t + 2], P[4 * t + 3], dv + (uint64_t)(t * 128), (t > 0) ? 1 : !(first)); \
  } while (0)
#define ISSUE_QK(cur)                                                                                          \
  do {                                                                                                         \
    const uint64_t dk = make_desc(sbase + (cur).s * 32768, 16, 1024, 1);                                       \
    _Pragma("unroll") for (int t = 0; t < 8; t++)                                                              \
        wgmma_rs_n128<0, 0>(S, Q[4 * t], Q[4 * t + 1], Q[4 * t + 2], Q[4 * t + 3], dk + (uint64_t)((t >> 2) * 1024 + (t & 3) * 2), t > 0); \
  } while (0)
#define LOAD_Q()                                                                                               \
  do {                                                                                                         \
    item = lds32(sItem + (it & 7) * 4);                                                                        \
    const uint32_t qa = sbase + cq.s * 32768 + (wg * 64 + warp * 16 + (lane & 15)) * 128;                      \
    _Pragma("unroll") for (int t = 0; t < 8; t++)                                                              \
        ldsm_x4(Q[4 * t], Q[4 * t + 1], Q[4 * t + 2], Q[4 * t + 3], qa + (t >> 2) * 16384 + ((((t & 3) * 2 + (lane >> 4)) ^ (lane & 7)) << 4)); \
  } while (0)
#define NEW_ITEM()                                                                                             \
  do {                                                                                                         \
    const int row = (2 * (item & 7) + hi) * 128 + wg * 64 + warp * 16 + (lane >> 2);                           \
    eoff = (row * KCAT + (item >> 3) * 128 + q * 8) * 2;                                                       \
    const float* gp = ptr_add(g_gate, row * 4);                                                                \
    asm volatile("ld.global.f32 %0, [%1];" : "=f"(gf0) : "l"(gp));                                             \
    asm volatile("ld.global.f32 %0, [%1];" : "=f"(gf1) : "l"(gp + 8));                                         \
    if (!hi) {                                                                                                 \
      mbar_wait2(bF + cs0.s * 8, cs0.ph, bF + cs1.s * 8, cs1.ph);                                              \
      RELEASE(cs0);                                                                                            \
      RELEASE(cs1);                                                                                            \
    }                                                                                                          \
  } while (0)
#define EXPB(T)                                                                                                \
  do {                                                                                                         \
    _Pragma("unroll") for (int i = 4 * T; i < 4 * T + 4; i++) asm volatile("" : "+r"(P[i])::"memory");        \
    _Pragma("unroll") for (int jj = 2 * T; jj < 2 * T + 2; jj++) {                                             \
      const float e0 = ex2(S[jj * 4 + 0]), e1 = ex2(S[jj * 4 + 1]), e2 = ex2(S[jj * 4 + 2]), e3 = ex2(S[jj * 4 + 3]); \
      s0 += e0 + e1;                                                                                           \
      s1 += e2 + e3;                                                                                           \
      P[jj * 2 + 0] = pack_bf16(e0, e1);                                                                       \
      P[jj * 2 + 1] = pack_bf16(e2, e3);                                                                       \
    }                                                                                                          \
  } while (0)
#define EXPC(T)                                                                                                \
  do {                                                                                                         \
    if (T > 0 && ((PVM >> (T - 1)) & 1)) {                                                                     \
      anchor((T & 2) ? s0 : s1, never);                                                                        \
      wg_wait<__builtin_popcount(PVM >> T) - 1>();                                                             \
      if ((PVM >> T) == (128 >> T)) { fence_regs(O); RELEASE(cv); }                                            \
    }                                                                                                          \
    EXPB(T);                                                                                                   \
  } while (0)
#define MASK(G, g)                                                                                             \
  do {                                                                                                         \
    if ((g) * 8 > d) S[(G) * 4 + 0] = -INFINITY;                                                               \
    if ((g) * 8 + 1 > d) S[(G) * 4 + 1] = -INFINITY;                                                           \
    if ((g) * 8 - 8 > d) S[(G) * 4 + 2] = -INFINITY;                                                           \
    if ((g) * 8 - 7 > d) S[(G) * 4 + 3] = -INFINITY;                                                           \
  } while (0)
#define STORE_O(G)                                                                                             \
  do {                                                                                                         \
    st_v4(optr + (G) * 32, pack_bf16(O[(G) * 16 + 0] * f0, O[(G) * 16 + 1] * f0), pack_bf16(O[(G) * 16 + 4] * f0, O[(G) * 16 + 5] * f0), \
          pack_bf16(O[(G) * 16 + 8] * f0, O[(G) * 16 + 9] * f0), pack_bf16(O[(G) * 16 + 12] * f0, O[(G) * 16 + 13] * f0)); \
    st_v4(optr + 8 * KCAT + (G) * 32, pack_bf16(O[(G) * 16 + 2] * f1, O[(G) * 16 + 3] * f1), pack_bf16(O[(G) * 16 + 6] * f1, O[(G) * 16 + 7] * f1), \
          pack_bf16(O[(G) * 16 + 10] * f1, O[(G) * 16 + 11] * f1), pack_bf16(O[(G) * 16 + 14] * f1, O[(G) * 16 + 15] * f1)); \
  } while (0)

#define FLUSH()                                                                                                \
  do {                                                                                                         \
    _Pragma("unroll") for (int G = 0; G < 8; G++) {                                                            \
      st_v4a(st.pp + G * 32, pk[G * 8], pk[G * 8 + 1], pk[G * 8 + 2], pk[G * 8 + 3]);                          \
      st_v4a(st.pp8 + G * 32, pk[G * 8 + 4], pk[G * 8 + 5], pk[G * 8 + 6], pk[G * 8 + 7]);                     \
    }                                                                                                          \
    k1_flag(st, lane, bS);                                                                                     \
  } while (0)

__global__ void __cluster_dims__(2, 1, 1) __launch_bounds__(384, 1)
fused_kernel(const __grid_constant__ Params p, const bf16* __restrict__ x, const bf16* __restrict__ gate_w, bf16* __restrict__ out) {
  extern __shared__ uint8_t smem_raw[];
  const uint32_t sbase = (smem_u32(smem_raw) + 1023) & ~1023u;
  const uint32_t sB = sbase, sA = sbase + K1_BST * 16384, sBar = sbase + SMEM_DATA;
  const uint32_t bAf = sBar, bAe = sBar + 64, bBf = sBar + 128, bBe = sBar + 176, bL = sBar + 224, bS = sBar + 656, bL2 = sBar + 240, sL = sA + 32768;
  const uint32_t bF = sBar + 256, bE = sBar + 320, bT = sBar + 384, sTick = sBar + 400, sItem = sBar + 416, bS2 = sBar + 688, bR = sBar + 456, bLast = sBar + 464, bH = sBar + 472, bT0 = sBar + 480;
  const uint32_t b3F = sBar + 512, b3E = sBar + 544, sGate = sBar + 576;
  const int tid = threadIdx.x, warp_g = __shfl_sync(0xffffffffu, tid >> 5, 0), lane = tid & 31;
  const uint32_t rank = cluster_rank();
  const int cl = blockIdx.x >> 1;
  TSM(0);
  if (tid == 256) {
    const uint32_t job = p.jobs[cl][0];
#pragma unroll
    for (int i = 0; i < KC0; i++) { mbar_init(bAf + i * 8, 1); mbar_init(bBf + i * 16, 1); mbar_init(bBf + i * 16 + 8, 1); }
    asm volatile("fence.mbarrier_init.release.cluster;" ::: "memory");
#pragma unroll 1
    for (int i = 0; i < 4 * KC0; i++) {
      if (!(i & 3)) {
        mbar_expect(bAf + i * 2, 16384);
        tma2d(sA + (i / 4 + 2) * 16384, &p.tmA[(job >> 2) & 1], bAf + i * 2, i * 16, ((job >> 3) & 7) * 256 + rank * 128);
      }
      if (!(i & 1)) mbar_expect(bBf + i * 4, 16384);
      tma3d(sB + i * 8192, &p.tmW[(job >> 6) & 3], bBf + (i >> 1) * 8, 0, i * 16, (job >> 8) & 63);
    }
  }
  if (tid == 0) {
    for (int i = 0; i < 8; i++) { if (i >= KC0) mbar_init(bAf + i * 8, 1); mbar_init(bAe + i * 8, 2); }
    for (int i = 0; i < K1_BST; i++) { if (i >= 2 * KC0) mbar_init(bBf + i * 8, 1); mbar_init(bBe + i * 8, 4); }
    mbar_init(bL, 1);
    mbar_init(bL2, 1);
    mbar_init(bR, 1);
    mbar_init(bLast, 1);
    mbar_init(bH, 4);
    mbar_init(bT0, 1);
    for (int i = 0; i < 8; i++) mbar_init(bS + i * 8, 8);
    for (int i = 0; i < K2_NST; i++) { mbar_init(bF + i * 8, 1); mbar_init(bE + i * 8, 4); }
    mbar_init(bT, 1); mbar_init(bT + 8, 1);
    for (int i = 0; i < K3_NST; i++) { mbar_init(b3F + i * 8, 1); mbar_init(b3E + i * 8, 4); }
    asm volatile("fence.mbarrier_init.release.cluster;" ::: "memory");
  }
  __syncwarp();
  if (warp_g != 8) cluster_sync();
  const int lr0 = blockIdx.x * 16;

  if (warp_g >= 8) {
    reg_dealloc<40>();
    if (warp_g == 8) {
      {
        __syncwarp();
        cluster_sync();
      }
      if (elect_one()) {
        uint32_t bs = (2 * KC0) % K1_BST, bph = (2 * KC0 < K1_BST), aph = 1;
#pragma unroll 1
        for (int ji = 0; ji < K1_MAXJOBS; ji++) {
          const uint32_t job = p.jobs[cl][ji];
          if (!(job & 3)) break;
          const int a_sel = (job >> 2) & 1, mpair = (job >> 3) & 7, chunk0 = (job >> 8) & 63;
          const bool newA = (job >> 14) & 1;
          const int KC = a_sel ? 9 : 8;
          const uint32_t halfbytes = 8192;
          const bool lastjob = (ji + 1 == K1_MAXJOBS) || !(p.jobs[cl][ji + 1] & 3);
          const CUtensorMap* tw = &p.tmW[(job >> 6) & 3];
          {
            const uint32_t njob = (ji + 1 < K1_MAXJOBS) ? p.jobs[cl][ji + 1] : 0;
            if (!(njob & 3) && !newA) mbar_arrive(bLast);
          }
#pragma unroll 1
          for (int kc = ji ? 0 : KC0; kc < KC; kc++) {
            {
              const bool nx = kc + PFD >= KC;
              const uint32_t njob = nx ? p.jobs[cl][ji + 1] : job;
              const int pk = nx ? kc + PFD - KC : kc + PFD;
              if ((njob & 3) && (nx || ji > 0)) {
                if (cl >= 64 || ((pk ^ (cl >> 1)) & 3) == 0)
                  tma_pf3d(&p.tmW[(njob >> 6) & 3], 0, pk * 64 + (cl & 1) * 32 + rank * 16, (njob >> 8) & 63);
                if (((njob >> 14) & 1) || pk == 8) tma_pf2d(&p.tmA[(njob >> 2) & 1], pk * 64, ((njob >> 3) & 7) * 256 + rank * 128);
              }
            }
            if (kc == 8) {
              PWAIT(bBe + bs * 8, bph);
              mbar_expect(bBf + bs * 8, 16384);
              tma2d(sB + bs * 16384, &p.tmA[1], bBf + bs * 8, 512, mpair * 256 + rank * 128);
              if (++bs == K1_BST) { bs = 0; bph ^= 1; }
            } else if (newA) {
              PWAIT(bAe + kc * 8, aph);
              mbar_expect(bAf + kc * 8, 16384);
              tma2d(sA + ((kc + 2) & 7) * 16384, &p.tmA[a_sel], bAf + kc * 8, kc * 64, mpair * 256 + rank * 128);
              if (kc == 7 && lastjob) mbar_arrive(bLast);
            }
#pragma unroll 1
            for (int kk = 0; kk < 2; kk++) {
              PWAIT(bBe + bs * 8, bph);
              mbar_expect(bBf + bs * 8, 2 * halfbytes);
              tma3d_mc(sB + bs * 16384 + rank * halfbytes, tw, bBf + bs * 8, 0, kc * 64 + kk * 32 + rank * 16, chunk0, 3);
              if (++bs == K1_BST) { bs = 0; bph ^= 1; }
            }
          }
          if (newA) aph ^= 1;
        }
        Cursor c{0, 0};
        int pcol = 0;
        PWAIT(bR, 0);
        uint32_t tick = lds32(sTick + 8), seen = 1u << (p.order[tick] >> 4);
        asm volatile("fence.proxy.async.global;" ::: "memory");
#pragma unroll 1
        for (int it = 0;; it++) {
          const uint32_t item = (tick < 256) ? p.order[tick] : (K2_END | min(tick - 256, 255u));
          asm volatile("st.shared.u32 [%0], %1;" ::"r"(sItem + (it & 7) * 4), "r"(item) : "memory");
          if (item >= K2_END) break;
          const int h = item >> 3, j = item & 7;
          const int blk = 2 * j + (int)(rank ^ (it & 1));
          const int col = h * 128 + rank * 64;
          const int nb = 2 * j + 2;
          if (!((seen >> (h >> 1)) & 1)) {
            wait_flag(&g_sync[F_HP + (h >> 1)], RDY_TARGET);
            asm volatile("fence.proxy.async.global;" ::: "memory");
            seen |= 1u << (h >> 1);
          }
          PWAIT(bE + c.s * 8, c.ph);
          mbar_expect(bF + c.s * 8, 32768);
          tma2d(sbase + c.s * 32768, &p.tmC, bF + c.s * 8, h * 128, blk * 128);
          tma2d(sbase + c.s * 32768 + 16384, &p.tmC, bF + c.s * 8, h * 128 + 64, blk * 128);
          c.next();
          if (tick >= 256 - 73) {
            const int kk = tick - (256 - 73), sel = (kk < 9), kr = (sel ? kk : kk - 9) * 64 + rank * 32;
#pragma unroll 1
            for (int i = 0; i < 2; i++) {
              tma_pf3d(&p.tmO[sel], 0, kr, i * 4);
              tma_pf2d(&p.tmOt[sel], 512 + i * 32, kr);
            }
          }
#pragma unroll 1
          for (int n = nb - 1; n >= 0; n--) {
            if (n == 0 && rank == 0) tick = atomicAdd(&g_sync[F_TICK], 1u);
            PWAIT(bE + c.s * 8, c.ph);
            mbar_expect(bF + c.s * 8, 32768);
            tma2d_mc(sbase + c.s * 32768 + rank * 16384, &p.tmK, bF + c.s * 8, col, n * 128, 3);
            c.next();
            if (n < nb - 1 || it > 0) {
              PWAIT(bE + c.s * 8, c.ph);
              mbar_expect(bF + c.s * 8, 32768);
              tma2d_mc(sbase + c.s * 32768 + rank * 16384, &p.tmV, bF + c.s * 8, (n < nb - 1) ? col : pcol, (n < nb - 1) ? (n + 1) * 128 : 0, 3);
              c.next();
            }
          }
          pcol = col;
          if (rank == 0) {
            asm volatile(
                "{\n.reg .b32 a, b;\nmapa.shared::cluster.u32 a, %0, 1;\nmapa.shared::cluster.u32 b, %1, 1;\n"
                "st.async.shared::cluster.mbarrier::complete_tx::bytes.u32 [a], %2, [b];\n}" ::"r"(sTick + (it & 1) * 4),
                "r"(bT + (it & 1) * 8), "r"(tick) : "memory");
          } else {
            mbar_expect(bT + (it & 1) * 8, 4);
            PWAIT(bT + (it & 1) * 8, (it >> 1) & 1);
            tick = lds32(sTick + (it & 1) * 4);
          }
        }
        PWAIT(bE + c.s * 8, c.ph);
        mbar_expect(bF + c.s * 8, 32768);
        tma2d_mc(sbase + c.s * 32768 + rank * 16384, &p.tmV, bF + c.s * 8, pcol, 0, 3);
        const uint32_t unit = min(tick - 256, 64u);
        const int mblk = (7 - (p.unit[unit][0] >> 1)) * 2 + rank, nhalf = p.unit[unit][0] & 1;
        uint32_t have, hoa;
        asm volatile("ld.acquire.gpu.global.u32 %0, [%1];" : "=r"(have) : "l"(&g_sync[F_CTX + mblk]) : "memory");
        asm volatile("ld.acquire.gpu.global.u32 %0, [%1];" : "=r"(hoa) : "l"(&g_sync[F_OA + mblk]) : "memory");
        asm volatile("fence.proxy.async.global;" ::: "memory");
#pragma unroll 1
        for (uint32_t idx = PF3A; idx < PF3 && unit < 64; idx++) {
          const int kk = p.unit[unit][3] + idx;
          if ((kk < 9) ? (hoa >= 8) : ((have >> ((kk - 9) >> 1)) & 1)) tma_pf2d(&p.tmC, ((kk < 9) ? 64 + kk : kk - 9) * 64, mblk * 128);
        }
        if (unit < 64) {
          const uint32_t rot = k3_rot(c.s), nfree = ((0x1Au >> c.s) & 1) ? 2 : 3;
#pragma unroll 1
          for (uint32_t idx = 0; idx < p.unit[unit][2]; idx++) {
            const int kk = p.unit[unit][3] + idx + ((idx >= p.unit[unit][4]) ? p.unit[unit][5] : 0);
            const uint32_t s = (rot + idx) & 3;
            if (idx >= nfree) PWAIT((idx < 4) ? bH : b3E + s * 8, (idx < 4) ? 0 : (~idx >> 2) & 1);
#pragma unroll 1
            while (idx < nfree && c.s != ((0x6431u >> (4 * s)) & 15)) {
              c.next();
              PWAIT(bE + c.s * 8, c.ph);
            }
            mbar_expect(b3F + s * 8, K3_STAGE);
            const uint32_t st = sbase + s * K3_STAGE;
            const int sel = (kk < 9), k = sel ? kk : kk - 9, kr = k * 64 + rank * 32;
            tma3d_mc(st + 16384 + rank * 16384, &p.tmO[sel], b3F + s * 8, 0, kr, nhalf * 4, 3);
            tma2d_mc(st + 49152 + rank * 2048, &p.tmOt[sel], b3F + s * 8, 512 + nhalf * 32, kr, 3);
            if (sel && hoa < 8) {
              wait_flag(&g_sync[F_OA + mblk], 8);
              hoa = 8;
              asm volatile("fence.proxy.async.global;" ::: "memory");
            }
            if (!sel && !((have >> (k >> 1)) & 1)) {
#pragma unroll 1
              for (uint32_t spins = 0; spins < (1u << 22); spins++) {
                asm volatile("ld.acquire.gpu.global.u32 %0, [%1];" : "=r"(have) : "l"(&g_sync[F_CTX + mblk]) : "memory");
                if ((have >> (k >> 1)) & 1) break;
                __nanosleep(100);
              }
              asm volatile("fence.proxy.async.global;" ::: "memory");
            }
            tma2d(st, &p.tmC, b3F + s * 8, (sel ? 64 + k : k) * 64, mblk * 128);
          }
        }
      }
    }
    __syncwarp();
    if (warp_g == 8) {
      uint32_t v = 0;
      if (lane == 0) {
        __threadfence();
        v = atomicAdd(&g_sync[F_DONE], 1u);
      }
      if (__shfl_sync(0xffffffffu, v, 0) == 2 * NCLUSTER - 1) {
        reinterpret_cast<uint4*>(g_sync)[lane] = make_uint4(0, 0, 0, 0);
        if (lane == 0) g_sync[F_EPOCH] = lds32(sGate + 64) + 1;
      }
    }
    asm volatile("" ::: "memory");
    if (__shfl_sync(0xffffffffu, warp_g, 0) != 8) {
      if (lr0 < S_LEN) {
#pragma unroll 1
        for (int i = warp_g - 9; i < 16; i += 3) {
          const float g = gate_row(lr0 + i, lane, x, gate_w);
          if (lane == 0) asm volatile("st.shared.f32 [%0], %1;" ::"r"(sGate + i * 4), "f"(g) : "memory");
        }
        bar_arrive(3, 256 + 96);
        if (lane == 0) {
          __threadfence();
          atomicAdd(&g_sync[F_GATE], 1u);
        }
      }
      uint32_t aph = 1;
#pragma unroll 1
      for (int ji = 0; ji < K1_MAXJOBS; ji++) aph ^= (p.jobs[cl][ji] >> 14) & 1;
      if (warp_g == 9 && lane == 0) {
#pragma unroll 1
        for (int ji = 0; ji < K1_MAXJOBS; ji++) {
          const uint32_t job = p.jobs[cl][ji];
          if (!(job & 3)) break;
          PWAIT(bS + (ji & 3) * 8, (ji >> 2) & 1);
          __threadfence();
          atomicAdd(&g_sync[(((job >> 6) & 3) == 2) ? (F_QKVA + ((job >> 3) & 7) * 2 + rank) : (F_HP + ((job >> 10) & 15))], 1u);
        }
#pragma unroll 1
        for (int it = 0;; it++) {
          PWAIT(bS2 + (it & 3) * 8, (it >> 2) & 1);
          const uint32_t item = lds32(sItem + (it & 7) * 4), nxt = lds32(sItem + ((it + 1) & 7) * 4);
          __threadfence();
          atomicOr(&g_sync[F_CTX + (item & 7) * 2 + (rank ^ (it & 1))], 1u << (item >> 3));
          if (nxt >= K2_END) break;
        }
      } else if (warp_g == 11) {
        if (lane == 0) {
          prefetch_tmap(&p.tmC); prefetch_tmap(&p.tmK); prefetch_tmap(&p.tmV);
          asm volatile("st.shared.u32 [%0], %1;" ::"r"(sGate + 64), "r"(__ldcg(&g_sync[F_EPOCH])) : "memory");
          wait_flag(&g_sync[F_GATE], GATE_TARGET);
          uint32_t tick;
          if (rank == 0) {
            PWAIT(bLast, 0);
            PWAIT(bAe + FIRST_DRAW * 8, aph);
            tick = atomicAdd(&g_sync[F_TICK], 1u);
            asm volatile("st.shared.u32 [%0], %1;" ::"r"(sTick + 8), "r"(tick) : "memory");
            asm volatile(
                "{\n.reg .b32 a, b;\nmapa.shared::cluster.u32 a, %0, 1;\nmapa.shared::cluster.u32 b, %1, 1;\n"
                "st.async.shared::cluster.mbarrier::complete_tx::bytes.u32 [a], %2, [b];\n}" ::"r"(sTick + 8), "r"(bT0), "r"(tick) : "memory");
          } else {
            mbar_expect(bT0, 4);
            PWAIT(bT0, 0);
            tick = lds32(sTick + 8);
          }
          wait_flag(&g_sync[F_HP + (p.order[tick] >> 4)], RDY_TARGET);
          mbar_arrive(bR);
        }
      } else if (warp_g == 10) {
        if (lr0 < S_LEN && lane == 0) {
          prefetch_tmap(&p.tmL[0]); prefetch_tmap(&p.tmL[1]); prefetch_tmap(&p.tmL[2]);
          wait_flag(&g_sync[F_QKVA + (lr0 >> 7)], K1_FLAG_TARGET);
          wait_flag(&g_sync[F_QKVA + (max(lr0 - 16, 0) >> 7)], K1_FLAG_TARGET);
          asm volatile("fence.proxy.async.global;" ::: "memory");
          PWAIT(bLast, 0);
#pragma unroll 1
          for (int kc = 0; kc < 6; kc++) {
            PWAIT(bAe + kc * 8, aph);
            if (kc == 3) {
              mbar_expect(bL, LV);
              tma4d(sL, &p.tmL[0], bL, lr0 / 2 - 8, 9, 0);
              tma4d(sL + LQ, &p.tmL[1], bL, lr0 / 2, 0, 0);
            }
          }
          mbar_expect(bL2, LQ);
          tma4d(sL + LV, &p.tmL[0], bL2, lr0 / 2 - 8, 18, 0);
        }
        __syncwarp();
        bar_sync(5, 256 + 32);
        if (lr0 < S_LEN && lane == 0) {
          asm volatile("cp.async.bulk.tensor.4d.global.shared::cta.bulk_group [%0, {%2, %3, %2, %2}], [%1];" ::"l"(&p.tmL[2]), "r"(sL + LQ), "r"(0), "r"(lr0 / 2) : "memory");
          asm volatile("cp.async.bulk.commit_group;" ::: "memory");
          asm volatile("cp.async.bulk.wait_group.read 0;" ::: "memory");
        }
        __syncwarp();
        if (lane < 12) mbar_arrive_cluster(bE + (4 + lane % 3) * 8, (lane / 3) & 1);
        if (lr0 < S_LEN && lane == 0) {
          asm volatile("cp.async.bulk.wait_group 0;" ::: "memory");
          asm volatile("fence.proxy.async.global;" ::: "memory");
          __threadfence();
          atomicAdd(&g_sync[F_OA + (lr0 >> 7)], 1u);
        }
      }
    }
    __syncwarp();
    cluster_sync();
  } else {
    reg_alloc<232>();
    const int wg = warp_g >> 2, warp = warp_g & 3, q = lane & 3;
    const bool sig = (lane == 0) && (warp < 2);
    {
      K1State st{0, 0, 0, nullptr, nullptr, 0, 0, 0, 24};
      float acc[128];
      uint32_t pk[64];
      if (wg == 0) { TS(0, 0); TSC(0, 2); }
      uint32_t job = p.jobs[cl][0];
      k1_first(st, job, bAf, bBf);
      {
#pragma unroll 1
        for (int ji = 0; job & 3; ji++) {
          const uint32_t njob = p.jobs[cl][ji + 1];
          k1_tile(acc, pk, st, job, njob, sA, sB, bAf, bAe, bBf, bBe, bS, wg, warp, lane, rank);
          job = njob;
        }
      }
#pragma unroll
      for (int i = 0; i < 4; i++)
        mbar_arrive_cluster_if(bE + i * 8, warp & 1, sig);
      if (lr0 < S_LEN) bar_sync(3, 256 + 96);
      if (st.wsel == 3) {
#pragma unroll
        for (int G = 0; G < 16; G++) scale_q4(pk + G * 4);
      }
      auto flush = [&](int i, uint32_t dep) {
        asm volatile("{\n.reg .pred p;\nsetp.eq.u32 p, %5, 0;\n@p st.global.cs.v4.b32 [%0], {%1, %2, %3, %4};\n}" ::"l"(((i & 1) ? st.pp8 : st.pp) + (i / 2) * 32),
                     "r"(pk[i * 4]), "r"(pk[i * 4 + 1]), "r"(pk[i * 4 + 2]), "r"(pk[i * 4 + 3]), "r"(dep & blockIdx.y) : "memory");
      };
      if (wg == 0) { TS(0, 1); TSC(0, 3); }
      if (lr0 < S_LEN) {
        const float gate0 = __uint_as_float(lds32(sGate + (lane >> 2) * 8)), gate1 = __uint_as_float(lds32(sGate + (lane >> 2) * 8 + 4));
        local_attn(lr0, warp_g, sL, bL, bL2, lane, gate0, gate1, flush);
        k1_flag(st, lane, bS);
      } else {
        FLUSH();
      }
      bar_arrive(5, 256 + 32);
    }
    __syncwarp();
    uint32_t item, rot;
    {
      const int mybar = 1 + wg, otherbar = 2 - wg;
      const uint32_t never = blockIdx.y;
      float S[64], O[64];
      uint32_t P[32], Q[32];
      float m0, m1, l0, l1, gf0, gf1;
      uint32_t eoff;
      Cursor c{4 - 2 * rank, 0}, ck{2 - rank, 0};
      if (wg == 1) bar_arrive(1, 256);
      if (wg == 0) { TS(1, 0); TSC(1, 2); }
      {
        const Cursor cq{0, 0}, cs0{1, 0}, cs1{3, 0};
        const int it = 0, hi = rank;
        mbar_wait2(bF, 0, bF + ck.s * 8, 0);
        LOAD_Q();
        wg_fence();
        ISSUE_QK(ck);
        wg_commit();
        RELEASE(cq);
        NEW_ITEM();
        wg_wait<0>();
        fence_regs(S);
      }
#pragma unroll 1
      for (int it = 0;;) {
        int hi = (int)(rank ^ (it & 1));
        RELEASE(ck);
        const int nblk = 2 * (item & 7) + 1 + hi;
        Cursor cv;
        float s0 = 0.f, s1 = 0.f;
        l0 = 0.f; l1 = 0.f;
        m0 = 0.f; m1 = 0.f;
        bool shifted = false;
        {
          const int d = warp * 16 + (lane >> 2) - 2 * q;
          if (wg == 0) {
#pragma unroll
            for (int jj = 0; jj < 8; jj++) MASK(jj, jj);
            EXPB(0); EXPB(1); EXPB(2); EXPB(3);
#pragma unroll
            for (int i = 32; i < 64; i++) S[i] = -INFINITY;
#pragma unroll
            for (int i = 16; i < 32; i++) P[i] = 0;
          } else {
#pragma unroll
            for (int jj = 0; jj < 8; jj++) MASK(jj + 8, jj);
            EXPB(0); EXPB(1); EXPB(2); EXPB(3); EXPB(4); EXPB(5); EXPB(6); EXPB(7);
          }
        }
        float chk = (q == 0 && !(fminf(s0, s1) >= SPEC_LO)) ? INFINITY : s0 + s1;
        fence_regs(P);
        TB(9);
#pragma unroll 1
        for (int n = 1;; n++) {
          if (__any_sync(0xffffffffu, !(chk <= SPEC_HI))) {
            float mx0 = fmaxf(S[0], S[1]), mx1 = fmaxf(S[2], S[3]);
#pragma unroll
            for (int jj = 1; jj < 16; jj++) {
              mx0 = fmaxf(mx0, fmaxf(S[jj * 4 + 0], S[jj * 4 + 1]));
              mx1 = fmaxf(mx1, fmaxf(S[jj * 4 + 2], S[jj * 4 + 3]));
            }
            mx0 = fmaxf(mx0, __shfl_xor_sync(0xffffffffu, mx0, 1));
            mx1 = fmaxf(mx1, __shfl_xor_sync(0xffffffffu, mx1, 1));
            mx0 = fmaxf(mx0, __shfl_xor_sync(0xffffffffu, mx0, 2));
            mx1 = fmaxf(mx1, __shfl_xor_sync(0xffffffffu, mx1, 2));
            const float lo = (n == 1) ? -INFINITY : 0.f;
            mx0 = fmaxf(mx0, lo);
            mx1 = fmaxf(mx1, lo);
            m0 += mx0; m1 += mx1;
            shifted = true;
            const float sc0 = ex2(-fmaxf(mx0, 0.f)), sc1 = ex2(-fmaxf(mx1, 0.f));
            l0 *= sc0; l1 *= sc1;
            s0 = 0.f; s1 = 0.f;
#pragma unroll
            for (int jj = 0; jj < 16; jj++) {
              const float e0 = ex2(S[jj * 4 + 0] - mx0), e1 = ex2(S[jj * 4 + 1] - mx0), e2 = ex2(S[jj * 4 + 2] - mx1), e3 = ex2(S[jj * 4 + 3] - mx1);
              s0 += e0 + e1;
              s1 += e2 + e3;
              P[jj * 2 + 0] = pack_bf16(e0, e1);
              P[jj * 2 + 1] = pack_bf16(e2, e3);
              O[jj * 4 + 0] *= sc0;
              O[jj * 4 + 1] *= sc0;
              O[jj * 4 + 2] *= sc1;
              O[jj * 4 + 3] *= sc1;
            }
          }
          l0 += s0;
          l1 += s1;
          if (n >= nblk) break;
          ck = c; c.next();
          cv = c; c.next();
          mbar_wait(bF + ck.s * 8, ck.ph);
          mbar_wait(bF + cv.s * 8, cv.ph);
          TURN_SYNC();
          TRC(0);
          wg_fence();
          ISSUE_QK(ck);
          wg_commit();
          {
            const uint64_t dv = make_desc(sbase + cv.s * 32768, 16384, 1024, 1);
#pragma unroll
            for (int t = 0; t < 8; t++) {
              wgmma_rs_n128<1, 0>(O, P[4 * t], P[4 * t + 1], P[4 * t + 2], P[4 * t + 3], dv + (uint64_t)(t * 128), (t > 0) ? 1 : (n != 1));
              if ((PVM >> t) & 1) wg_commit();
            }
          }
          TURN_ARRIVE();
          s0 = 0.f; s1 = 0.f;
          wg_wait<__builtin_popcount(PVM)>();
          fence_regs(S);
          RELEASE(ck);
          if (shifted) {
#pragma unroll
            for (int i = 0; i < 64; i++) S[i] -= (i & 2) ? m1 : m0;
          }
          wg_wait<__builtin_popcount(PVM) - 1>();
          EXPC(0); EXPC(1); EXPC(2); EXPC(3); EXPC(4); EXPC(5); EXPC(6); EXPC(7);
          chk = s0 + s1;
        }
        it++;
        hi ^= 1;
        TB(0);
        Cursor cq = c, cs0, cs1;
        rot = k3_rot(c.s);
        c.next();
        ck = c; c.next();
        cs0 = ck; cs1 = ck;
        cv = c; c.next();
        if (!hi) {
          ck = c; c.next();
          cs1 = c; c.next();
        }
        mbar_wait(bF + cq.s * 8, cq.ph);
        TB(1);
        LOAD_Q();
        const uint32_t rdy = mbar_test(bF + ck.s * 8, ck.ph) & mbar_test(bF + cv.s * 8, cv.ph);
        l0 += __shfl_xor_sync(0xffffffffu, l0, 1);
        l1 += __shfl_xor_sync(0xffffffffu, l1, 1);
        l0 += __shfl_xor_sync(0xffffffffu, l0, 2);
        l1 += __shfl_xor_sync(0xffffffffu, l1, 2);
        if (item >= K2_END) {
          TURN_SYNC();
          TRC(2);
          wg_fence();
          ISSUE_PV(cq, nblk == 1);
          wg_commit();
          if (wg == 0) TURN_ARRIVE();
          asm volatile("" : "+f"(gf0), "+f"(gf1), "+f"(l0), "+f"(l1));
          const float f0 = __fdividef(1.f - gf0, l0), f1 = __fdividef(1.f - gf1, l1);
          bf16* optr = ptr_add(g_ctx, eoff);
          wg_wait<0>();
          fence_regs(O);
          mbar_arrive_cluster_if(bH, warp & 1, sig);
          STORE_O(0); STORE_O(1); STORE_O(2); STORE_O(3);
          __syncwarp();
          mbar_arrive_if(bS2 + ((it - 1) & 3) * 8, lane == 0);
          break;
        }
        if (!rdy) mbar_wait2(bF + ck.s * 8, ck.ph, bF + cv.s * 8, cv.ph);
        TB(2);
        TURN_SYNC();
        TB(3);
        TRC(1);
        wg_fence();
        ISSUE_PV(cv, nblk == 1);
        wg_commit();
        ISSUE_QK(ck);
        wg_commit();
        TURN_ARRIVE();
        RELEASE(cq);
        TB(4);
        asm volatile("" : "+f"(gf0), "+f"(gf1), "+f"(l0), "+f"(l1));
        const float f0 = __fdividef(1.f - gf0, l0), f1 = __fdividef(1.f - gf1, l1);
        wg_wait<1>();
        fence_regs(O);
        fence_regs(P);
        TB(5);
        RELEASE(cv);
        {
          bf16* optr = ptr_add(g_ctx, eoff);
          STORE_O(0); STORE_O(1); STORE_O(2); STORE_O(3);
          __syncwarp();
          mbar_arrive_if(bS2 + ((it - 1) & 3) * 8, lane == 0);
        }
        TB(6);
        NEW_ITEM();
        TB(7);
        wg_wait<0>();
        fence_regs(S);
        TB(8);
      }
      TRC(3);
      if (wg == 1) { TS(1, 1); TSC(1, 3); }
    }
    __syncwarp();
    const uint32_t unit = item & 255;
    if (unit < 64) {
      const int mblk = (7 - (p.unit[unit][0] >> 1)) * 2 + rank, nhalf = p.unit[unit][0] & 1, ks = p.unit[unit][1];
      const int k0 = 0, k1 = p.unit[unit][2];
      float acc[144];
      uint32_t s = rot, ph = 0, prev = 0;
      if (wg == 0) { TS(2, 0); TSC(2, 2); }
      uint32_t fa[16], fb[16];
      const uint32_t aoff = (wg * 64 + warp * 16 + (lane & 15)) * 128 + (((lane >> 4) ^ (lane & 7)) << 4);
#define C_LOAD(F)                                                                                              \
  do {                                                                                                         \
    mbar_wait(b3F + s * 8, ph);                                                                                \
    _Pragma("unroll") for (int t = 0; t < 4; t++)                                                              \
        ldsm_x4(F[4 * t], F[4 * t + 1], F[4 * t + 2], F[4 * t + 3], sbase + s * K3_STAGE + (aoff ^ (t * 32))); \
  } while (0)
#define C_STEP(F, G)                                                                                           \
  {                                                                                                            \
    const uint32_t st = sbase + s * K3_STAGE;                                                                  \
    const uint64_t db = make_desc(st + 16384, 4096, 1024, 1), dt = make_desc(st + 49152, 16, 512, 2);          \
    if (CLEAD && wg == 1 && k == k1 - CLEAD) bar_sync(4, 256);                                                 \
    wg_fence();                                                                                                \
    _Pragma("unroll") for (int t = 0; t < 4; t++) {                                                            \
      const int sd = (t > 0) || (k > k0);                                                                      \
      wgmma_rs_n256<1, 0>(acc, F[4 * t], F[4 * t + 1], F[4 * t + 2], F[4 * t + 3], db + (uint64_t)((t >> 1) * 1024 + (t & 1) * 128), sd); \
      wgmma_rs_n32<1, 128>(acc, F[4 * t], F[4 * t + 1], F[4 * t + 2], F[4 * t + 3], dt + (uint64_t)(t * 64), sd); \
    }                                                                                                          \
    wg_commit();                                                                                               \
    if (CLEAD && wg == 0 && k == k1 - 1) bar_arrive(4, 256);                                                   \
    wg_wait<1>();                                                                                              \
    fence_regs(G);                                                                                             \
    mbar_arrive_cluster_if(b3E + prev * 8, warp & 1, sig && k > k0);                                           \
    prev = s;                                                                                                  \
    s = (s + 1) & 3;                                                                                           \
    if (s == rot) ph ^= 1;                                                                                     \
    TCK(k + 1);                                                                                                \
    if (++k == k1) break;                                                                                      \
    C_LOAD(G);                                                                                                 \
  }
      TCK(0);
      C_LOAD(fa);
#pragma unroll
      for (int i = 0; i < 16; i++) fb[i] = 0;
#pragma unroll 1
      for (int k = k0;;) {
        C_STEP(fa, fb)
        C_STEP(fb, fa)
      }
      wg_wait<0>();
      fence_regs(acc);
      cluster_arrive();
      if (wg == 0) TS(2, 4);
      const int tile = mblk * 2 + nhalf;
      uint4* wp = g_part + (size_t)((tile * 4 + ks) * 4) * 5 * 256 + tid;
      const uint32_t sown = sbase + wg * 8192 + (tid & 127) * 16;
#pragma unroll
      for (int d = 0; d < 4; d++) {
        if (d != ks) {
#pragma unroll
          for (int i = 0; i < 4; i++)
            __stcg(wp + (d * 5 + i) * 256,
                   make_uint4(pack_bf16(acc[d * 32 + i * 8], acc[d * 32 + i * 8 + 1]), pack_bf16(acc[d * 32 + i * 8 + 2], acc[d * 32 + i * 8 + 3]),
                              pack_bf16(acc[d * 32 + i * 8 + 4], acc[d * 32 + i * 8 + 5]), pack_bf16(acc[d * 32 + i * 8 + 6], acc[d * 32 + i * 8 + 7])));
          __stcg(reinterpret_cast<uint2*>(wp - tid + (d * 5 + 4) * 256) + tid,
                 make_uint2(pack_bf16(acc[128 + d * 4], acc[128 + d * 4 + 1]), pack_bf16(acc[128 + d * 4 + 2], acc[128 + d * 4 + 3])));
        } else {
#pragma unroll
          for (int i = 0; i < 9; i++) {
            const int o = (i < 8) ? d * 32 + i * 4 : 128 + d * 4;
            asm volatile("st.shared.v4.f32 [%0], {%1, %2, %3, %4};" ::"r"(sown + (i >> 2) * K3_STAGE + (i & 3) * 2048), "f"(acc[o]), "f"(acc[o + 1]), "f"(acc[o + 2]), "f"(acc[o + 3]) : "memory");
          }
        }
      }
      __threadfence();
      __syncwarp();
      if (wg == 0) TS(2, 5);
      if (lane == 0) {
        unsigned int* cnt = &g_sync[F_XCH + tile * 8 + warp_g];
        const uint32_t xtarget = lds32(sGate + 64) * 4 + 4;
        atomicAdd(cnt, 1u);
        uint32_t v, spins = 0;
        do {
          asm volatile("ld.acquire.gpu.global.u32 %0, [%1];" : "=r"(v) : "l"(cnt) : "memory");
        } while ((int)(v - xtarget) < 0 && ++spins < (1u << 24));
      }
      __syncwarp();
      if (wg == 0) TS(2, 6);
      float r[36];
#pragma unroll
      for (int i = 0; i < 9; i++)
        asm volatile("ld.shared.v4.f32 {%0, %1, %2, %3}, [%4];" : "=f"(r[i * 4]), "=f"(r[i * 4 + 1]), "=f"(r[i * 4 + 2]), "=f"(r[i * 4 + 3])
                     : "r"(sown + (i >> 2) * K3_STAGE + (i & 3) * 2048) : "memory");
#pragma unroll
      for (int sI = 1; sI < 4; sI++) {
        const int src = (ks + sI) & 3;
        const uint4* rp = g_part + (size_t)(((tile * 4 + src) * 4) + ks) * 5 * 256;
#pragma unroll
        for (int i = 0; i < 4; i++) {
          const uint4 v = __ldcg(rp + i * 256 + tid);
          r[i * 8] += bf_lo(v.x); r[i * 8 + 1] += bf_hi(v.x); r[i * 8 + 2] += bf_lo(v.y); r[i * 8 + 3] += bf_hi(v.y);
          r[i * 8 + 4] += bf_lo(v.z); r[i * 8 + 5] += bf_hi(v.z); r[i * 8 + 6] += bf_lo(v.w); r[i * 8 + 7] += bf_hi(v.w);
        }
        const uint2 v = __ldcg(reinterpret_cast<const uint2*>(rp + 4 * 256) + tid);
        r[32] += bf_lo(v.x); r[33] += bf_hi(v.x); r[34] += bf_lo(v.y); r[35] += bf_hi(v.y);
      }
      const int row = mblk * 128 + wg * 64 + warp * 16 + (lane >> 2);
      bf16* o0 = out + (size_t)row * DM + nhalf * 256 + ks * 64 + 8 * q;
#pragma unroll
      for (int G = 0; G < 2; G++) {
        uint32_t a0 = pack_bf16(r[G * 16], r[G * 16 + 1]), a1 = pack_bf16(r[G * 16 + 4], r[G * 16 + 5]);
        uint32_t a2 = pack_bf16(r[G * 16 + 8], r[G * 16 + 9]), a3 = pack_bf16(r[G * 16 + 12], r[G * 16 + 13]);
        uint32_t b0 = pack_bf16(r[G * 16 + 2], r[G * 16 + 3]), b1 = pack_bf16(r[G * 16 + 6], r[G * 16 + 7]);
        uint32_t b2 = pack_bf16(r[G * 16 + 10], r[G * 16 + 11]), b3 = pack_bf16(r[G * 16 + 14], r[G * 16 + 15]);
        quad_transpose(a0, a1, a2, a3, q);
        quad_transpose(b0, b1, b2, b3, q);
        st_v4(o0 + G * 32, a0, a1, a2, a3);
        st_v4(o0 + 8 * DM + G * 32, b0, b1, b2, b3);
      }
      {
        uint32_t t0 = pack_bf16(r[32], r[33]), t1 = pack_bf16(r[34], r[35]), t2 = 0, t3 = 0;
        quad_transpose(t0, t1, t2, t3, q);
        if (q < 2) st_v4(out + (size_t)(row + q * 8) * DM + 512 + nhalf * 32 + ks * 8, t0, t1, t2, t3);
      }
    } else {
      cluster_arrive();
    }
    if (wg == 0) { TS(2, 1); TSC(2, 3); }
    cluster_wait();
  }
}

typedef CUresult (*EncFn)(CUtensorMap*, CUtensorMapDataType, cuuint32_t, void*, const cuuint64_t*, const cuuint64_t*, const cuuint32_t*,
                          const cuuint32_t*, CUtensorMapInterleave, CUtensorMapSwizzle, CUtensorMapL2promotion, CUtensorMapFloatOOBfill);

static void enc2d(EncFn enc, CUtensorMap* m, const void* ptr, uint64_t cols, uint64_t rows, uint32_t bc, uint32_t br,
                  CUtensorMapSwizzle sw = CU_TENSOR_MAP_SWIZZLE_128B) {
  cuuint64_t gd[2] = {cols, rows}, gs[1] = {cols * 2};
  cuuint32_t bx[2] = {bc, br}, es[2] = {1, 1};
  enc(m, CU_TENSOR_MAP_DATA_TYPE_BFLOAT16, 2, const_cast<void*>(ptr), gd, gs, bx, es, CU_TENSOR_MAP_INTERLEAVE_NONE, sw,
      CU_TENSOR_MAP_L2_PROMOTION_L2_256B, CU_TENSOR_MAP_FLOAT_OOB_FILL_NONE);
}
static void enc3d(EncFn enc, CUtensorMap* m, const void* ptr, uint64_t cols, uint64_t rows, uint32_t br, uint32_t bch) {
  cuuint64_t gd[3] = {64, rows, cols / 64}, gs[2] = {cols * 2, 128};
  cuuint32_t bx[3] = {64, br, bch}, es[3] = {1, 1, 1};
  enc(m, CU_TENSOR_MAP_DATA_TYPE_BFLOAT16, 3, const_cast<void*>(ptr), gd, gs, bx, es, CU_TENSOR_MAP_INTERLEAVE_NONE,
      CU_TENSOR_MAP_SWIZZLE_128B, CU_TENSOR_MAP_L2_PROMOTION_L2_256B, CU_TENSOR_MAP_FLOAT_OOB_FILL_NONE);
}

static int g_sched[10] = {11, 10, 7, 4, 4, 4, 6, 8, 6, 24};
static void build_k1_jobs(Params& p) {
  int cnt[NCLUSTER];
  for (int c = 0; c < NCLUSTER; c++) {
    cnt[c] = 0;
    for (int i = 0; i <= K1_MAXJOBS; i++) p.jobs[c][i] = 0;
  }
  auto add = [&](int c, int nch, int a_sel, int mp, int w_sel, int chunk0) {
    p.jobs[c][cnt[c]++] = (uint16_t)((nch - 1) | (a_sel << 2) | (mp << 3) | (w_sel << 6) | (chunk0 << 8));
  };
  const char* plan = "ccccccccccc cccccccccc ccccccc cccc xxxx xxxx xxxxxx xxxxxxxx";
  int TIE = 0;
  int XA = 0;
  const char* cur[8];
  int tend[8] = {};
  for (int g = 0; g < 8; g++) {
    cur[g] = plan;
    while (*plan == 'c' || *plan == 'x') plan++;
    if (*plan) plan++;
  }
  int kc = 0, kx = 0;
  for (;;) {
    int b = -1, bt = 0;
    for (int g = 0; g < 8; g++) {
      const int t = tend[g] + (*cur[g] == 'x' ? 94 : 85);
      if ((*cur[g] == 'c' || *cur[g] == 'x') && (b < 0 || t < bt || (TIE && t == bt))) { b = g; bt = t; }
    }
    if (b < 0) break;
    const int a = kx - XA;
    for (int mp = 0; mp < 8; mp++) {
      if (*cur[b] == 'c') add(b * 8 + mp, 4, 0, mp, kc & 1, (kc >> 1) * 4);
      else if (a >= 0 && a < 7) add(b * 8 + mp, a == 0 ? 3 : 4, 1, mp, 2, a == 0 ? 24 : (a - 1) * 4);
      else add(b * 8 + mp, 4, 1, mp, 3, (a < 0 ? kx : kx - 7) * 4);
    }
    if (*cur[b] == 'c') kc++; else kx++;
    cur[b]++;
    tend[b] = bt;
  }
  for (int mp = 0; mp < 8; mp++) add(64 + mp / 4, 4, 1, mp, 3, 15 * 4);
  for (int cc = 0; cc < NCLUSTER; cc++)
    for (int i = 0; i < cnt[cc]; i++) {
      const int key = p.jobs[cc][i] & 0x3C;
      if (i == 0 || (p.jobs[cc][i - 1] & 0x3C) != key) p.jobs[cc][i] |= (1 << 14);
      if (i == cnt[cc] - 1 || (p.jobs[cc][i + 1] & 0x3C) != key) p.jobs[cc][i] |= (1 << 15);
    }
}

static void build_k2_items(Params& p) {
  int n = 0;
  const int SCHED_N1 = g_sched[8], SCHED_N2 = g_sched[9];
  int N0 = 2, J0 = 2;
  for (int j = 7; j >= J0; j--)
    for (int h = 0; h < N0; h++) p.order[n++] = (uint8_t)(h * 8 + j);
  for (int j = 7; j >= 0; j--)
    for (int h = 0; h < SCHED_N1; h++)
      if (!(h < N0 && j >= J0)) p.order[n++] = (uint8_t)(h * 8 + j);
  for (int j = 7; j >= 4; j--)
    for (int h = SCHED_N1; h < SCHED_N2; h++) p.order[n++] = (uint8_t)(h * 8 + j);
  for (int j = 7; j >= 0; j--)
    for (int h = SCHED_N1; h < 32; h++)
      if (!(h < SCHED_N2 && j >= 4)) p.order[n++] = (uint8_t)(h * 8 + j);
  int TJ[2] = {0, 0}, TP = 0;
  for (int t = 0; t < 2; t++) {
    if (!TJ[t]) continue;
    int i = 0;
    while (p.order[i] != 31 * 8 + TJ[t]) i++;
    for (; i < 255 - TP; i++) p.order[i] = p.order[i + 1];
    p.order[i] = (uint8_t)(31 * 8 + TJ[t]);
  }
}

static void build_k3_units(Params& p) {
  float slope = 0.045f;
  int NE = 25;
  for (int t = 0; t < 16; t++) {
    const int u[4] = {t, 31 - t, 32 + t, 63 - t};
    float acc = 0.f;
    int k0 = 0, l0 = NE;
    for (int i = 0; i < 4; i++) {
      acc += 18.25f + slope * (31.5f - u[i]);
      const int k1 = (i == 3) ? 73 : (int)(acc + 0.5f);
      const int e0 = NE * i / 4, e1 = NE * (i + 1) / 4;
      uint8_t* w = p.unit[u[i]];
      w[0] = (uint8_t)t; w[1] = (uint8_t)i; w[2] = (uint8_t)(k1 - k0); w[3] = (uint8_t)e0; w[4] = (uint8_t)(e1 - e0); w[5] = (uint8_t)(l0 - e1);
      l0 += (k1 - k0) - (e1 - e0);
      k0 = k1;
    }
  }
}

extern "C" void kernel_launch(void* const* d_in, const int* in_sizes, int n_in, void* d_out, int out_size) {
  const bf16* x = (const bf16*)d_in[0];
  const bf16* wqkv = (const bf16*)d_in[1];
  const bf16* wo = (const bf16*)d_in[2];
  const bf16* ckv = (const bf16*)d_in[4];
  const bf16* w_q = (const bf16*)d_in[5];
  const bf16* w_uk = (const bf16*)d_in[6];
  const bf16* w_uv = (const bf16*)d_in[7];
  const bf16* w_o = (const bf16*)d_in[8];
  const bf16* gate_w = (const bf16*)d_in[9];

  EncFn enc = nullptr;
  cudaDriverEntryPointQueryResult qr;
  cudaGetDriverEntryPoint("cuTensorMapEncodeTiled", (void**)&enc, cudaEnableDefault, &qr);
  void *pK, *pV, *pCtx, *pQA;
  cudaGetSymbolAddress(&pQA, g_QKVA);
  cudaGetSymbolAddress(&pK, g_K);
  cudaGetSymbolAddress(&pV, g_V);
  cudaGetSymbolAddress(&pCtx, g_ctx);

  static Params p;
  enc2d(enc, &p.tmA[0], ckv, DC, S_LEN, 64, 128);
  enc2d(enc, &p.tmA[1], x, DM, S_LEN, 64, 128);
  enc3d(enc, &p.tmW[0], w_uk, HDIM, DC, 16, 4);
  enc3d(enc, &p.tmW[1], w_uv, HDIM, DC, 16, 4);
  enc3d(enc, &p.tmW[2], wqkv, NQKVA, DM, 16, 4);
  enc3d(enc, &p.tmW[3], w_q, HDIM, DM, 16, 4);
  build_k1_jobs(p);
  enc2d(enc, &p.tmK, pK, HDIM, S_LEN, 64, 128);
  enc2d(enc, &p.tmV, pV, HDIM, S_LEN, 64, 128);
  build_k2_items(p);
  build_k3_units(p);
  for (int i = 0; i < 3; i++) {
    const cuuint64_t ld = (i < 2 ? NQKVA : KCAT) * 2, nch = (i < 2) ? 27 : 9;
    cuuint64_t gd[4] = {64, S_LEN / 2, i ? 2 : nch, i ? nch : 2}, gs[3] = {2 * ld, i ? ld : 128, i ? 128 : ld};
    cuuint32_t bx[4] = {64, i ? 8u : 16u, i ? 2u : 9u, i ? 9u : 2u}, es[4] = {1, 1, 1, 1};
    enc(&p.tmL[i], CU_TENSOR_MAP_DATA_TYPE_BFLOAT16, 4, (i < 2) ? pQA : (void*)((bf16*)pCtx + HDIM), gd, gs, bx, es, CU_TENSOR_MAP_INTERLEAVE_NONE,
        CU_TENSOR_MAP_SWIZZLE_128B, CU_TENSOR_MAP_L2_PROMOTION_L2_256B, CU_TENSOR_MAP_FLOAT_OOB_FILL_NONE);
  }
  enc2d(enc, &p.tmC, pCtx, KCAT, S_LEN, 64, 128);
  enc3d(enc, &p.tmO[0], w_o, DM, HDIM, 32, 4);
  enc3d(enc, &p.tmO[1], wo, DM, DM, 32, 4);
  enc2d(enc, &p.tmOt[0], w_o, DM, HDIM, 32, 32, CU_TENSOR_MAP_SWIZZLE_64B);
  enc2d(enc, &p.tmOt[1], wo, DM, DM, 32, 32, CU_TENSOR_MAP_SWIZZLE_64B);

  cudaFuncSetAttribute(fused_kernel, cudaFuncAttributeMaxDynamicSharedMemorySize, SMEM_BYTES);
  fused_kernel<<<NCLUSTER * 2, 384, SMEM_BYTES>>>(p, x, gate_w, (bf16*)d_out);
}
```

```cpp
#include <cuda_runtime.h>
#include <cuda_bf16.h>
#include <cuda.h>
#include <stdint.h>

typedef __nv_bfloat16 bf16;

constexpr int S_LEN = 2048, DM = 576, DC = 512, HDIM = 4096, NQKVA = 1728, KCAT = 4672;
constexpr int NCLUSTER = 66;

__device__ __align__(1024) bf16 g_K[S_LEN * HDIM];
__device__ __align__(1024) bf16 g_V[S_LEN * HDIM];
__device__ __align__(1024) bf16 g_QKVA[S_LEN * NQKVA + 64];
__device__ __align__(1024) bf16 g_ctx[S_LEN * KCAT];
__device__ float g_gate[S_LEN];
__device__ __align__(16) unsigned int g_sync[400];
constexpr int F_QKVA = 0, F_HP = 16, F_CTX = 32, F_OA = 48, F_CLM = 64, F_GATE = 96, F_TICK = 97, F_DONE = 98, F_XCH = 128, F_EPOCH = 384;

__device__ __forceinline__ uint32_t smem_u32(const void* p) { return (uint32_t)__cvta_generic_to_shared(p); }
__device__ __forceinline__ void mbar_init(uint32_t a, uint32_t c) {
  asm volatile("mbarrier.init.shared::cta.b64 [%0], %1;" ::"r"(a), "r"(c));
}
__device__ __forceinline__ void mbar_expect(uint32_t a, uint32_t b) {
  asm volatile("mbarrier.arrive.expect_tx.shared::cta.b64 _, [%0], %1;" ::"r"(a), "r"(b) : "memory");
}
#define TS(k, i)
#define TSC(k, i)
#define TSM(k)
#define BSEG(i)
#define TB(k)
#define TRC(fl)
#define TCK(i)
#define SPIN_LIMIT "4194304"
__device__ __forceinline__ void mbar_wait(uint32_t a, uint32_t parity) {
  asm volatile(
      "{\n.reg .pred p;\n.reg .u32 n;\n"
      "mbarrier.try_wait.parity.shared::cta.b64 p, [%0], %1;\n"
      "@p bra DONE;\n"
      "mov.u32 n, 0;\n"
      "LOOP:\n"
      "mbarrier.try_wait.parity.shared::cta.b64 p, [%0], %1;\n"
      "@p bra DONE;\n"
      "add.u32 n, n, 1;\n"
      "setp.lt.u32 p, n, " SPIN_LIMIT ";\n"
      "@p bra LOOP;\n"
      "DONE:\n}" ::"r"(a), "r"(parity) : "memory");
}
template <int NS>
__device__ __forceinline__ void mbar_wait_ns(uint32_t a, uint32_t parity) {
  asm volatile(
      "{\n.reg .pred p;\n.reg .u32 n;\n"
      "mov.u32 n, 0;\n"
      "LOOP:\n"
      "mbarrier.try_wait.parity.shared::cta.b64 p, [%0], %1, %2;\n"
      "@p bra DONE;\n"
      "add.u32 n, n, 1;\n"
      "setp.lt.u32 p, n, " SPIN_LIMIT ";\n"
      "@p bra LOOP;\n"
      "DONE:\n}" ::"r"(a), "r"(parity), "n"(NS) : "memory");
}
__device__ __forceinline__ void mbar_wait2(uint32_t a, uint32_t pa, uint32_t b, uint32_t pb) {
  asm volatile(
      "{\n.reg .pred p, q;\n.reg .u32 n;\n"
      "mov.u32 n, 0;\n"
      "LOOP:\n"
      "mbarrier.try_wait.parity.shared::cta.b64 p, [%0], %1;\n"
      "mbarrier.try_wait.parity.shared::cta.b64 q, [%2], %3;\n"
      "add.u32 n, n, 1;\n"
      "and.pred p, p, q;\n"
      "setp.lt.and.u32 p, n, " SPIN_LIMIT ", !p;\n"
      "@p bra LOOP;\n"
      "}" ::"r"(a), "r"(pa), "r"(b), "r"(pb) : "memory");
}
__device__ __forceinline__ uint32_t mbar_test(uint32_t a, uint32_t parity) {
  uint32_t r;
  asm volatile("{\n.reg .pred p;\nmbarrier.test_wait.parity.shared::cta.b64 p, [%1], %2;\nselp.u32 %0, 1, 0, p;\n}" : "=r"(r) : "r"(a), "r"(parity) : "memory");
  return r;
}
__device__ __forceinline__ void mbar_arrive(uint32_t a) {
  asm volatile("mbarrier.arrive.shared::cta.b64 _, [%0];" ::"r"(a) : "memory");
}
__device__ __forceinline__ void mbar_arrive_cluster(uint32_t a, uint32_t cta) {
  asm volatile("{\n.reg .b32 r;\nmapa.shared::cluster.u32 r, %0, %1;\nmbarrier.arrive.shared::cluster.b64 _, [r];\n}" ::"r"(a),
               "r"(cta) : "memory");
}
__device__ __forceinline__ void mbar_arrive_cluster_if(uint32_t a, uint32_t cta, bool pred) {
  asm volatile("{\n.reg .b32 r;\n.reg .pred p;\nsetp.ne.u32 p, %2, 0;\nmapa.shared::cluster.u32 r, %0, %1;\n@p mbarrier.arrive.shared::cluster.b64 _, [r];\n}" ::"r"(a),
               "r"(cta), "r"((uint32_t)pred) : "memory");
}
__device__ __forceinline__ void anchor(float v, uint32_t pred) {
  asm volatile("{\n.reg .pred p;\nsetp.ne.u32 p, %1, 0;\n@p st.shared.f32 [%1], %0;\n}" ::"f"(v), "r"(pred) : "memory");
}
__device__ __forceinline__ void mbar_arrive_if(uint32_t a, bool pred) {
  asm volatile("{\n.reg .pred p;\nsetp.ne.u32 p, %1, 0;\n@p mbarrier.arrive.shared::cta.b64 _, [%0];\n}" ::"r"(a), "r"((uint32_t)pred) : "memory");
}
__device__ __forceinline__ void tma2d(uint32_t dst, const CUtensorMap* m, uint32_t bar, int c0, int c1) {
  asm volatile("cp.async.bulk.tensor.2d.shared::cluster.global.mbarrier::complete_tx::bytes [%0], [%1, {%3, %4}], [%2];" ::"r"(dst),
               "l"(m), "r"(bar), "r"(c0), "r"(c1) : "memory");
}
__device__ __forceinline__ void tma2d_mc(uint32_t dst, const CUtensorMap* m, uint32_t bar, int c0, int c1, uint16_t mask) {
  asm volatile(
      "cp.async.bulk.tensor.2d.shared::cluster.global.mbarrier::complete_tx::bytes.multicast::cluster [%0], [%1, {%3, %4}], [%2], %5;" ::"r"(dst),
      "l"(m), "r"(bar), "r"(c0), "r"(c1), "h"(mask) : "memory");
}
__device__ __forceinline__ void tma3d_mc(uint32_t dst, const CUtensorMap* m, uint32_t bar, int c0, int c1, int c2, uint16_t mask) {
  asm volatile(
      "cp.async.bulk.tensor.3d.shared::cluster.global.mbarrier::complete_tx::bytes.multicast::cluster [%0], [%1, {%3, %4, %5}], [%2], %6;" ::"r"(dst),
      "l"(m), "r"(bar), "r"(c0), "r"(c1), "r"(c2), "h"(mask) : "memory");
}
__device__ __forceinline__ void tma3d(uint32_t dst, const CUtensorMap* m, uint32_t bar, int c0, int c1, int c2) {
  asm volatile(
      "cp.async.bulk.tensor.3d.shared::cluster.global.mbarrier::complete_tx::bytes [%0], [%1, {%3, %4, %5}], [%2];" ::"r"(dst),
      "l"(m), "r"(bar), "r"(c0), "r"(c1), "r"(c2) : "memory");
}
__device__ __forceinline__ void tma_pf2d(const CUtensorMap* m, int c0, int c1) {
  asm volatile("cp.async.bulk.prefetch.tensor.2d.L2.global [%0, {%1, %2}];" ::"l"(m), "r"(c0), "r"(c1) : "memory");
}
__device__ __forceinline__ void tma_pf3d(const CUtensorMap* m, int c0, int c1, int c2) {
  asm volatile("cp.async.bulk.prefetch.tensor.3d.L2.global [%0, {%1, %2, %3}];" ::"l"(m), "r"(c0), "r"(c1), "r"(c2) : "memory");
}
__device__ __forceinline__ void prefetch_tmap(const CUtensorMap* m) {
  asm volatile("prefetch.tensormap [%0];" ::"l"(m) : "memory");
}
__device__ __forceinline__ void cluster_arrive() { asm volatile("barrier.cluster.arrive.relaxed.aligned;" ::: "memory"); }
__device__ __forceinline__ void cluster_wait() { asm volatile("barrier.cluster.wait.aligned;" ::: "memory"); }
__device__ __forceinline__ void cluster_sync() {
  cluster_arrive();
  cluster_wait();
}
__device__ __forceinline__ uint32_t cluster_rank() {
  uint32_t r;
  asm volatile("mov.u32 %0, %%cluster_ctarank;" : "=r"(r));
  return r;
}
__device__ __forceinline__ bool elect_one() {
  uint32_t p;
  asm volatile("{\n.reg .pred q;\nelect.sync _|q, 0xffffffff;\nselp.u32 %0, 1, 0, q;\n}" : "=r"(p));
  return p;
}
__device__ __forceinline__ void ldsm_x4(uint32_t& r0, uint32_t& r1, uint32_t& r2, uint32_t& r3, uint32_t addr) {
  asm volatile("ldmatrix.sync.aligned.m8n8.x4.shared.b16 {%0, %1, %2, %3}, [%4];" : "=r"(r0), "=r"(r1), "=r"(r2), "=r"(r3) : "r"(addr) : "memory");
}
__device__ __forceinline__ void wg_fence() { asm volatile("wgmma.fence.sync.aligned;" ::: "memory"); }
__device__ __forceinline__ void wg_commit() { asm volatile("wgmma.commit_group.sync.aligned;" ::: "memory"); }
template <int N>
__device__ __forceinline__ void wg_wait() { asm volatile("wgmma.wait_group.sync.aligned %0;" ::"n"(N) : "memory"); }
template <int N>
__device__ __forceinline__ void reg_alloc() { asm volatile("setmaxnreg.inc.sync.aligned.u32 %0;" ::"n"(N)); }
template <int N>
__device__ __forceinline__ void reg_dealloc() { asm volatile("setmaxnreg.dec.sync.aligned.u32 %0;" ::"n"(N)); }
__device__ __forceinline__ void bar_sync(int id, int n) { asm volatile("bar.sync %0, %1;" ::"r"(id), "r"(n) : "memory"); }
__device__ __forceinline__ void bar_arrive(int id, int n) { asm volatile("bar.arrive %0, %1;" ::"r"(id), "r"(n) : "memory"); }
template <int NT>
__device__ __forceinline__ void fence_regs(float (&d)[NT]) {
#pragma unroll
  for (int i = 0; i < NT; i++) asm volatile("" : "+f"(d[i])::"memory");
}
template <int NT>
__device__ __forceinline__ void fence_regs(uint32_t (&d)[NT]) {
#pragma unroll
  for (int i = 0; i < NT; i++) asm volatile("" : "+r"(d[i])::"memory");
}
__device__ __forceinline__ uint64_t make_desc(uint32_t saddr, uint32_t lbo, uint32_t sbo, uint32_t layout) {
  return (uint64_t)((saddr & 0x3FFFF) >> 4) | ((uint64_t)(lbo >> 4) << 16) | ((uint64_t)(sbo >> 4) << 32) | ((uint64_t)layout << 62);
}
__device__ __forceinline__ uint32_t pack_bf16(float lo, float hi) {
  uint32_t r;
  asm("cvt.rn.bf16x2.f32 %0, %1, %2;" : "=r"(r) : "f"(hi), "f"(lo));
  return r;
}
__device__ __forceinline__ float ex2(float x) {
  float r;
  asm("ex2.approx.ftz.f32 %0, %1;" : "=f"(r) : "f"(x));
  return r;
}
__device__ __forceinline__ void st_v4(void* p, uint32_t a, uint32_t b, uint32_t c, uint32_t d) {
#define ST_MOD ".cs"
  asm volatile("st.global" ST_MOD ".v4.b32 [%0], {%1, %2, %3, %4};" ::"l"(p), "r"(a), "r"(b), "r"(c), "r"(d) : "memory");
}
#define STA_MOD ".cs"
__device__ __forceinline__ void st_v4a(void* p, uint32_t a, uint32_t b, uint32_t c, uint32_t d) {
  asm volatile("st.global" STA_MOD ".v4.b32 [%0], {%1, %2, %3, %4};" ::"l"(p), "r"(a), "r"(b), "r"(c), "r"(d) : "memory");
}
template <typename T>
__device__ __forceinline__ T* ptr_add(T* base, uint32_t bytes) {
  uint64_t r;
  asm volatile("{\n.reg .u32 l, h;\nmov.b64 {l, h}, %1;\nadd.cc.u32 l, l, %2;\naddc.u32 h, h, 0;\nmov.b64 %0, {l, h};\n}" : "=l"(r) : "l"(base), "r"(bytes));
  return reinterpret_cast<T*>(r);
}
__device__ __forceinline__ float bf_lo(uint32_t v) { return __uint_as_float(v << 16); }
__device__ __forceinline__ float bf_hi(uint32_t v) { return __uint_as_float(v & 0xFFFF0000u); }

__device__ __forceinline__ void quad_transpose(uint32_t& a0, uint32_t& a1, uint32_t& a2, uint32_t& a3, int q) {
  const bool o1 = q & 1, o2 = q & 2;
  uint32_t t0 = o1 ? a0 : a1, t1 = o1 ? a2 : a3;
  t0 = __shfl_xor_sync(0xffffffffu, t0, 1);
  t1 = __shfl_xor_sync(0xffffffffu, t1, 1);
  if (o1) { a0 = t0; a2 = t1; } else { a1 = t0; a3 = t1; }
  t0 = o2 ? a0 : a2;
  t1 = o2 ? a1 : a3;
  t0 = __shfl_xor_sync(0xffffffffu, t0, 2);
  t1 = __shfl_xor_sync(0xffffffffu, t1, 2);
  if (o2) { a0 = t0; a1 = t1; } else { a2 = t0; a3 = t1; }
}

template<int TB, int OFF, int NT>
__device__ __forceinline__ void wgmma_ss_n256(float (&d)[NT], uint64_t da, uint64_t db, int scale_d) {
  asm volatile("{\n.reg .pred p;\nsetp.ne.b32 p, %130, 0;\n"
    "wgmma.mma_async.sync.aligned.m64n256k16.f32.bf16.bf16 {%0, %1, %2, %3, %4, %5, %6, %7, %8, %9, %10, %11, %12, %13, %14, %15, %16, %17, %18, %19, %20, %21, %22, %23, %24, %25, %26, %27, %28, %29, %30, %31, %32, %33, %34, %35, %36, %37, %38, %39, %40, %41, %42, %43, %44, %45, %46, %47, %48, %49, %50, %51, %52, %53, %54, %55, %56, %57, %58, %59, %60, %61, %62, %63, %64, %65, %66, %67, %68, %69, %70, %71, %72, %73, %74, %75, %76, %77, %78, %79, %80, %81, %82, %83, %84, %85, %86, %87, %88, %89, %90, %91, %92, %93, %94, %95, %96, %97, %98, %99, %100, %101, %102, %103, %104, %105, %106, %107, %108, %109, %110, %111, %112, %113, %114, %115, %116, %117, %118, %119, %120, %121, %122, %123, %124, %125, %126, %127}, %128, %129, p, 1, 1, 0, %131;\n}\n"
    : "+f"(d[OFF+0]), "+f"(d[OFF+1]), "+f"(d[OFF+2]), "+f"(d[OFF+3]), "+f"(d[OFF+4]), "+f"(d[OFF+5]), "+f"(d[OFF+6]), "+f"(d[OFF+7]), "+f"(d[OFF+8]), "+f"(d[OFF+9]), "+f"(d[OFF+10]), "+f"(d[OFF+11]), "+f"(d[OFF+12]), "+f"(d[OFF+13]), "+f"(d[OFF+14]), "+f"(d[OFF+15]), "+f"(d[OFF+16]), "+f"(d[OFF+17]), "+f"(d[OFF+18]), "+f"(d[OFF+19]), "+f"(d[OFF+20]), "+f"(d[OFF+21]), "+f"(d[OFF+22]), "+f"(d[OFF+23]), "+f"(d[OFF+24]), "+f"(d[OFF+25]), "+f"(d[OFF+26]), "+f"(d[OFF+27]), "+f"(d[OFF+28]), "+f"(d[OFF+29]), "+f"(d[OFF+30]), "+f"(d[OFF+31]), "+f"(d[OFF+32]), "+f"(d[OFF+33]), "+f"(d[OFF+34]), "+f"(d[OFF+35]), "+f"(d[OFF+36]), "+f"(d[OFF+37]), "+f"(d[OFF+38]), "+f"(d[OFF+39]), "+f"(d[OFF+40]), "+f"(d[OFF+41]), "+f"(d[OFF+42]), "+f"(d[OFF+43]), "+f"(d[OFF+44]), "+f"(d[OFF+45]), "+f"(d[OFF+46]), "+f"(d[OFF+47]), "+f"(d[OFF+48]), "+f"(d[OFF+49]), "+f"(d[OFF+50]), "+f"(d[OFF+51]), "+f"(d[OFF+52]), "+f"(d[OFF+53]), "+f"(d[OFF+54]), "+f"(d[OFF+55]), "+f"(d[OFF+56]), "+f"(d[OFF+57]), "+f"(d[OFF+58]), "+f"(d[OFF+59]), "+f"(d[OFF+60]), "+f"(d[OFF+61]), "+f"(d[OFF+62]), "+f"(d[OFF+63]), "+f"(d[OFF+64]), "+f"(d[OFF+65]), "+f"(d[OFF+66]), "+f"(d[OFF+67]), "+f"(d[OFF+68]), "+f"(d[OFF+69]), "+f"(d[OFF+70]), "+f"(d[OFF+71]), "+f"(d[OFF+72]), "+f"(d[OFF+73]), "+f"(d[OFF+74]), "+f"(d[OFF+75]), "+f"(d[OFF+76]), "+f"(d[OFF+77]), "+f"(d[OFF+78]), "+f"(d[OFF+79]), "+f"(d[OFF+80]), "+f"(d[OFF+81]), "+f"(d[OFF+82]), "+f"(d[OFF+83]), "+f"(d[OFF+84]), "+f"(d[OFF+85]), "+f"(d[OFF+86]), "+f"(d[OFF+87]), "+f"(d[OFF+88]), "+f"(d[OFF+89]), "+f"(d[OFF+90]), "+f"(d[OFF+91]), "+f"(d[OFF+92]), "+f"(d[OFF+93]), "+f"(d[OFF+94]), "+f"(d[OFF+95]), "+f"(d[OFF+96]), "+f"(d[OFF+97]), "+f"(d[OFF+98]), "+f"(d[OFF+99]), "+f"(d[OFF+100]), "+f"(d[OFF+101]), "+f"(d[OFF+102]), "+f"(d[OFF+103]), "+f"(d[OFF+104]), "+f"(d[OFF+105]), "+f"(d[OFF+106]), "+f"(d[OFF+107]), "+f"(d[OFF+108]), "+f"(d[OFF+109]), "+f"(d[OFF+110]), "+f"(d[OFF+111]), "+f"(d[OFF+112]), "+f"(d[OFF+113]), "+f"(d[OFF+114]), "+f"(d[OFF+115]), "+f"(d[OFF+116]), "+f"(d[OFF+117]), "+f"(d[OFF+118]), "+f"(d[OFF+119]), "+f"(d[OFF+120]), "+f"(d[OFF+121]), "+f"(d[OFF+122]), "+f"(d[OFF+123]), "+f"(d[OFF+124]), "+f"(d[OFF+125]), "+f"(d[OFF+126]), "+f"(d[OFF+127])
    : "l"(da), "l"(db), "r"(scale_d), "n"(TB));
}
template<int TB, int OFF, int NT>
__device__ __forceinline__ void wgmma_ss_n32(float (&d)[NT], uint64_t da, uint64_t db, int scale_d) {
  asm volatile("{\n.reg .pred p;\nsetp.ne.b32 p, %18, 0;\n"
    "wgmma.mma_async.sync.aligned.m64n32k16.f32.bf16.bf16 {%0, %1, %2, %3, %4, %5, %6, %7, %8, %9, %10, %11, %12, %13, %14, %15}, %16, %17, p, 1, 1, 0, %19;\n}\n"
    : "+f"(d[OFF+0]), "+f"(d[OFF+1]), "+f"(d[OFF+2]), "+f"(d[OFF+3]), "+f"(d[OFF+4]), "+f"(d[OFF+5]), "+f"(d[OFF+6]), "+f"(d[OFF+7]), "+f"(d[OFF+8]), "+f"(d[OFF+9]), "+f"(d[OFF+10]), "+f"(d[OFF+11]), "+f"(d[OFF+12]), "+f"(d[OFF+13]), "+f"(d[OFF+14]), "+f"(d[OFF+15])
    : "l"(da), "l"(db), "r"(scale_d), "n"(TB));
}
template<int TB, int OFF, int NT>
__device__ __forceinline__ void wgmma_rs_n128(float (&d)[NT], uint32_t a0, uint32_t a1, uint32_t a2, uint32_t a3, uint64_t db, int scale_d) {
  asm volatile("{\n.reg .pred p;\nsetp.ne.b32 p, %69, 0;\n"
    "wgmma.mma_async.sync.aligned.m64n128k16.f32.bf16.bf16 {%0, %1, %2, %3, %4, %5, %6, %7, %8, %9, %10, %11, %12, %13, %14, %15, %16, %17, %18, %19, %20, %21, %22, %23, %24, %25, %26, %27, %28, %29, %30, %31, %32, %33, %34, %35, %36, %37, %38, %39, %40, %41, %42, %43, %44, %45, %46, %47, %48, %49, %50, %51, %52, %53, %54, %55, %56, %57, %58, %59, %60, %61, %62, %63}, {%64, %65, %66, %67}, %68, p, 1, 1, %70;\n}\n"
    : "+f"(d[OFF+0]), "+f"(d[OFF+1]), "+f"(d[OFF+2]), "+f"(d[OFF+3]), "+f"(d[OFF+4]), "+f"(d[OFF+5]), "+f"(d[OFF+6]), "+f"(d[OFF+7]), "+f"(d[OFF+8]), "+f"(d[OFF+9]), "+f"(d[OFF+10]), "+f"(d[OFF+11]), "+f"(d[OFF+12]), "+f"(d[OFF+13]), "+f"(d[OFF+14]), "+f"(d[OFF+15]), "+f"(d[OFF+16]), "+f"(d[OFF+17]), "+f"(d[OFF+18]), "+f"(d[OFF+19]), "+f"(d[OFF+20]), "+f"(d[OFF+21]), "+f"(d[OFF+22]), "+f"(d[OFF+23]), "+f"(d[OFF+24]), "+f"(d[OFF+25]), "+f"(d[OFF+26]), "+f"(d[OFF+27]), "+f"(d[OFF+28]), "+f"(d[OFF+29]), "+f"(d[OFF+30]), "+f"(d[OFF+31]), "+f"(d[OFF+32]), "+f"(d[OFF+33]), "+f"(d[OFF+34]), "+f"(d[OFF+35]), "+f"(d[OFF+36]), "+f"(d[OFF+37]), "+f"(d[OFF+38]), "+f"(d[OFF+39]), "+f"(d[OFF+40]), "+f"(d[OFF+41]), "+f"(d[OFF+42]), "+f"(d[OFF+43]), "+f"(d[OFF+44]), "+f"(d[OFF+45]), "+f"(d[OFF+46]), "+f"(d[OFF+47]), "+f"(d[OFF+48]), "+f"(d[OFF+49]), "+f"(d[OFF+50]), "+f"(d[OFF+51]), "+f"(d[OFF+52]), "+f"(d[OFF+53]), "+f"(d[OFF+54]), "+f"(d[OFF+55]), "+f"(d[OFF+56]), "+f"(d[OFF+57]), "+f"(d[OFF+58]), "+f"(d[OFF+59]), "+f"(d[OFF+60]), "+f"(d[OFF+61]), "+f"(d[OFF+62]), "+f"(d[OFF+63])
    : "r"(a0), "r"(a1), "r"(a2), "r"(a3), "l"(db), "r"(scale_d), "n"(TB));
}
template<int TB, int OFF, int NT>
__device__ __forceinline__ void wgmma_rs_n256(float (&d)[NT], uint32_t a0, uint32_t a1, uint32_t a2, uint32_t a3, uint64_t db, int scale_d) {
  asm volatile("{\n.reg .pred p;\nsetp.ne.b32 p, %133, 0;\n"
    "wgmma.mma_async.sync.aligned.m64n256k16.f32.bf16.bf16 {%0, %1, %2, %3, %4, %5, %6, %7, %8, %9, %10, %11, %12, %13, %14, %15, %16, %17, %18, %19, %20, %21, %22, %23, %24, %25, %26, %27, %28, %29, %30, %31, %32, %33, %34, %35, %36, %37, %38, %39, %40, %41, %42, %43, %44, %45, %46, %47, %48, %49, %50, %51, %52, %53, %54, %55, %56, %57, %58, %59, %60, %61, %62, %63, %64, %65, %66, %67, %68, %69, %70, %71, %72, %73, %74, %75, %76, %77, %78, %79, %80, %81, %82, %83, %84, %85, %86, %87, %88, %89, %90, %91, %92, %93, %94, %95, %96, %97, %98, %99, %100, %101, %102, %103, %104, %105, %106, %107, %108, %109, %110, %111, %112, %113, %114, %115, %116, %117, %118, %119, %120, %121, %122, %123, %124, %125, %126, %127}, {%128, %129, %130, %131}, %132, p, 1, 1, %134;\n}\n"
    : "+f"(d[OFF+0]), "+f"(d[OFF+1]), "+f"(d[OFF+2]), "+f"(d[OFF+3]), "+f"(d[OFF+4]), "+f"(d[OFF+5]), "+f"(d[OFF+6]), "+f"(d[OFF+7]), "+f"(d[OFF+8]), "+f"(d[OFF+9]), "+f"(d[OFF+10]), "+f"(d[OFF+11]), "+f"(d[OFF+12]), "+f"(d[OFF+13]), "+f"(d[OFF+14]), "+f"(d[OFF+15]), "+f"(d[OFF+16]), "+f"(d[OFF+17]), "+f"(d[OFF+18]), "+f"(d[OFF+19]), "+f"(d[OFF+20]), "+f"(d[OFF+21]), "+f"(d[OFF+22]), "+f"(d[OFF+23]), "+f"(d[OFF+24]), "+f"(d[OFF+25]), "+f"(d[OFF+26]), "+f"(d[OFF+27]), "+f"(d[OFF+28]), "+f"(d[OFF+29]), "+f"(d[OFF+30]), "+f"(d[OFF+31]), "+f"(d[OFF+32]), "+f"(d[OFF+33]), "+f"(d[OFF+34]), "+f"(d[OFF+35]), "+f"(d[OFF+36]), "+f"(d[OFF+37]), "+f"(d[OFF+38]), "+f"(d[OFF+39]), "+f"(d[OFF+40]), "+f"(d[OFF+41]), "+f"(d[OFF+42]), "+f"(d[OFF+43]), "+f"(d[OFF+44]), "+f"(d[OFF+45]), "+f"(d[OFF+46]), "+f"(d[OFF+47]), "+f"(d[OFF+48]), "+f"(d[OFF+49]), "+f"(d[OFF+50]), "+f"(d[OFF+51]), "+f"(d[OFF+52]), "+f"(d[OFF+53]), "+f"(d[OFF+54]), "+f"(d[OFF+55]), "+f"(d[OFF+56]), "+f"(d[OFF+57]), "+f"(d[OFF+58]), "+f"(d[OFF+59]), "+f"(d[OFF+60]), "+f"(d[OFF+61]), "+f"(d[OFF+62]), "+f"(d[OFF+63]), "+f"(d[OFF+64]), "+f"(d[OFF+65]), "+f"(d[OFF+66]), "+f"(d[OFF+67]), "+f"(d[OFF+68]), "+f"(d[OFF+69]), "+f"(d[OFF+70]), "+f"(d[OFF+71]), "+f"(d[OFF+72]), "+f"(d[OFF+73]), "+f"(d[OFF+74]), "+f"(d[OFF+75]), "+f"(d[OFF+76]), "+f"(d[OFF+77]), "+f"(d[OFF+78]), "+f"(d[OFF+79]), "+f"(d[OFF+80]), "+f"(d[OFF+81]), "+f"(d[OFF+82]), "+f"(d[OFF+83]), "+f"(d[OFF+84]), "+f"(d[OFF+85]), "+f"(d[OFF+86]), "+f"(d[OFF+87]), "+f"(d[OFF+88]), "+f"(d[OFF+89]), "+f"(d[OFF+90]), "+f"(d[OFF+91]), "+f"(d[OFF+92]), "+f"(d[OFF+93]), "+f"(d[OFF+94]), "+f"(d[OFF+95]), "+f"(d[OFF+96]), "+f"(d[OFF+97]), "+f"(d[OFF+98]), "+f"(d[OFF+99]), "+f"(d[OFF+100]), "+f"(d[OFF+101]), "+f"(d[OFF+102]), "+f"(d[OFF+103]), "+f"(d[OFF+104]), "+f"(d[OFF+105]), "+f"(d[OFF+106]), "+f"(d[OFF+107]), "+f"(d[OFF+108]), "+f"(d[OFF+109]), "+f"(d[OFF+110]), "+f"(d[OFF+111]), "+f"(d[OFF+112]), "+f"(d[OFF+113]), "+f"(d[OFF+114]), "+f"(d[OFF+115]), "+f"(d[OFF+116]), "+f"(d[OFF+117]), "+f"(d[OFF+118]), "+f"(d[OFF+119]), "+f"(d[OFF+120]), "+f"(d[OFF+121]), "+f"(d[OFF+122]), "+f"(d[OFF+123]), "+f"(d[OFF+124]), "+f"(d[OFF+125]), "+f"(d[OFF+126]), "+f"(d[OFF+127])
    : "r"(a0), "r"(a1), "r"(a2), "r"(a3), "l"(db), "r"(scale_d), "n"(TB));
}
template<int TB, int OFF, int NT>
__device__ __forceinline__ void wgmma_rs_n32(float (&d)[NT], uint32_t a0, uint32_t a1, uint32_t a2, uint32_t a3, uint64_t db, int scale_d) {
  asm volatile("{\n.reg .pred p;\nsetp.ne.b32 p, %21, 0;\n"
    "wgmma.mma_async.sync.aligned.m64n32k16.f32.bf16.bf16 {%0, %1, %2, %3, %4, %5, %6, %7, %8, %9, %10, %11, %12, %13, %14, %15}, {%16, %17, %18, %19}, %20, p, 1, 1, %22;\n}\n"
    : "+f"(d[OFF+0]), "+f"(d[OFF+1]), "+f"(d[OFF+2]), "+f"(d[OFF+3]), "+f"(d[OFF+4]), "+f"(d[OFF+5]), "+f"(d[OFF+6]), "+f"(d[OFF+7]), "+f"(d[OFF+8]), "+f"(d[OFF+9]), "+f"(d[OFF+10]), "+f"(d[OFF+11]), "+f"(d[OFF+12]), "+f"(d[OFF+13]), "+f"(d[OFF+14]), "+f"(d[OFF+15])
    : "r"(a0), "r"(a1), "r"(a2), "r"(a3), "l"(db), "r"(scale_d), "n"(TB));
}

__device__ __forceinline__ void wait_flag(const unsigned int* f, uint32_t target) {
  uint32_t v;
#pragma unroll 1
  for (uint32_t spins = 0; spins < (1u << 22); spins++) {
    asm volatile("ld.acquire.gpu.global.u32 %0, [%1];" : "=r"(v) : "l"(f) : "memory");
    if (v >= target) break;
    __nanosleep(100);
  }
}
__device__ __forceinline__ uint32_t lds32(uint32_t a) {
  uint32_t v;
  asm volatile("ld.shared.u32 %0, [%1];" : "=r"(v) : "r"(a) : "memory");
  return v;
}
__device__ __forceinline__ float gate_row(int row, int lane, const bf16* __restrict__ x, const bf16* __restrict__ gate_w) {
  const uint32_t* xr = reinterpret_cast<const uint32_t*>(x + (size_t)row * DM);
  const uint32_t* gw2 = reinterpret_cast<const uint32_t*>(gate_w);
  float gs = 0.f;
#pragma unroll
  for (int i = 0; i < 9; i++) {
    const uint32_t a = __ldg(xr + lane + 32 * i), b = __ldg(gw2 + lane + 32 * i);
    gs = fmaf(bf_lo(a), bf_lo(b), gs);
    gs = fmaf(bf_hi(a), bf_hi(b), gs);
  }
#pragma unroll
  for (int o = 16; o; o >>= 1) gs += __shfl_xor_sync(0xffffffffu, gs, o);
  const float g = 1.f / (1.f + __expf(-gs));
  if (lane == 0) g_gate[row] = g;
  return g;
}
constexpr uint32_t LQ = 36864, LV = 55296;
__device__ __forceinline__ void mma16(float (&c)[4], uint32_t a0, uint32_t a1, uint32_t a2, uint32_t a3, uint32_t b0, uint32_t b1) {
  asm("mma.sync.aligned.m16n8k16.row.col.f32.bf16.bf16.f32 {%0, %1, %2, %3}, {%4, %5, %6, %7}, {%8, %9}, {%0, %1, %2, %3};"
      : "+f"(c[0]), "+f"(c[1]), "+f"(c[2]), "+f"(c[3]) : "r"(a0), "r"(a1), "r"(a2), "r"(a3), "r"(b0), "r"(b1));
}
__device__ __forceinline__ void mma8(float (&c)[4], uint32_t a0, uint32_t a1, uint32_t b0) {
  asm("mma.sync.aligned.m16n8k8.row.col.f32.bf16.bf16.f32 {%0, %1, %2, %3}, {%4, %5}, {%6}, {%0, %1, %2, %3};"
      : "+f"(c[0]), "+f"(c[1]), "+f"(c[2]), "+f"(c[3]) : "r"(a0), "r"(a1), "r"(b0));
}
template <typename F>
__device__ __forceinline__ void local_attn(int lr0, int warp_g, uint32_t sL, uint32_t bL, uint32_t bL2, int lane, float g0, float g1, F st) {
  const float scale_l2 = 0.23570226039551584f * 1.4426950408889634f;
  const int g = lane >> 2, t = lane & 3;
  const bool lo0 = 2 * t > g, lo1 = 2 * t + 1 > g;
  const bool ok0 = lr0 > 0 || !lo0, ok1 = lr0 > 0 || !lo1;
  const uint32_t mlo = (lo0 ? 0xFFFFu : 0u) | (lo1 ? 0xFFFF0000u : 0u);
  uint32_t ad[9], k[9][4], qf[9][2], pe[4], po[4];
#pragma unroll
  for (int c = 0; c < 9; c++) {
    const uint32_t ch = warp_g * 9 + c;
    ad[c] = sL + (lane >> 4) * 18432 + (lane & 15) * 128 + ((ch >> 3) << 11) + (((ch ^ lane) & 7) << 4);
  }
  st(0, 0u); st(1, 0u);
  mbar_wait(bL, 0);
  if (warp_g == 0) TS(1, 6);
#pragma unroll
  for (int c = 0; c < 9; c++) {
    asm volatile("ldmatrix.sync.aligned.m8n8.x2.shared.b16 {%0, %1}, [%2];" : "=r"(qf[c][0]), "=r"(qf[c][1]) : "r"(ad[c] + LQ) : "memory");
    ldsm_x4(k[c][0], k[c][1], k[c][2], k[c][3], ad[c]);
  }
  st(2, k[0][0]); st(3, k[8][0]);
#pragma unroll
  for (int i = 0; i < 4; i++) {
    const uint32_t q0 = (t >= i) ? qf[2 * i][0] : 0u, q1 = (t >= i) ? qf[2 * i][1] : 0u;
    const uint32_t q4 = (t <= i) ? qf[2 * i + 2][0] : 0u, q5 = (t <= i) ? qf[2 * i + 2][1] : 0u;
    float c[4][4];
#pragma unroll
    for (int T = 0; T < 4; T++) {
#pragma unroll
      for (int j = 0; j < 4; j++) c[T][j] = 0.f;
      mma16(c[T], q0, q1, qf[2 * i + 1][0], qf[2 * i + 1][1], k[2 * i][T], k[2 * i + 1][T]);
      mma8(c[T], q4, q5, k[2 * i + 2][T]);
    }
    const float e0 = ok0 ? (lo0 ? c[0][0] : c[1][0]) : -INFINITY, e1 = ok1 ? (lo1 ? c[0][1] : c[1][1]) : -INFINITY;
    const float o0 = ok0 ? (lo0 ? c[2][2] : c[3][2]) : -INFINITY, o1 = ok1 ? (lo1 ? c[2][3] : c[3][3]) : -INFINITY;
    float me = fmaxf(e0, e1), mo = fmaxf(o0, o1);
    me = fmaxf(me, __shfl_xor_sync(0xffffffffu, me, 1));
    mo = fmaxf(mo, __shfl_xor_sync(0xffffffffu, mo, 1));
    me = fmaxf(me, __shfl_xor_sync(0xffffffffu, me, 2)) * scale_l2;
    mo = fmaxf(mo, __shfl_xor_sync(0xffffffffu, mo, 2)) * scale_l2;
    const float w0 = ex2(fmaf(e0, scale_l2, -me)), w1 = ex2(fmaf(e1, scale_l2, -me));
    const float w2 = ex2(fmaf(o0, scale_l2, -mo)), w3 = ex2(fmaf(o1, scale_l2, -mo));
    float se = w0 + w1, so = w2 + w3;
    st(4 + 2 * i, __float_as_uint(i == 1 ? me : i == 2 ? se : e0));
    se += __shfl_xor_sync(0xffffffffu, se, 1);
    so += __shfl_xor_sync(0xffffffffu, so, 1);
    se += __shfl_xor_sync(0xffffffffu, se, 2);
    so += __shfl_xor_sync(0xffffffffu, so, 2);
    asm("rcp.approx.ftz.f32 %0, %0;" : "+f"(se));
    asm("rcp.approx.ftz.f32 %0, %0;" : "+f"(so));
    se *= g0;
    so *= g1;
    pe[i] = pack_bf16(w0 * se, w1 * se);
    po[i] = pack_bf16(w2 * so, w3 * so);
    st(5 + 2 * i, i == 0 ? __float_as_uint(w0) : i == 2 ? __float_as_uint(mo) : po[i]);
  }
  if (warp_g == 0) TS(0, 4);
  mbar_wait(bL2, 0);
  if (warp_g == 0) TS(0, 5);
#pragma unroll
  for (int c = 0; c < 9; c++)
    asm volatile("ldmatrix.sync.aligned.m8n8.x4.trans.shared.b16 {%0, %1, %2, %3}, [%4];"
                 : "=r"(k[c][0]), "=r"(k[c][1]), "=r"(k[c][2]), "=r"(k[c][3]) : "r"(ad[c] + LV) : "memory");
#pragma unroll
  for (int i = 0; i < 4; i++) {
#pragma unroll
    for (int n = 0; n < 3; n++) {
      float c[4] = {0.f, 0.f, 0.f, 0.f};
      mma16(c, pe[i] & mlo, 0u, pe[i] & ~mlo, 0u, k[2 * i + n][0], k[2 * i + n][1]);
      mma16(c, 0u, po[i] & mlo, 0u, po[i] & ~mlo, k[2 * i + n][2], k[2 * i + n][3]);
      const uint32_t r0 = pack_bf16(c[0], c[1]), r1 = pack_bf16(c[2], c[3]);
      const bool keep = (n == 0) && (i > 0) && (t < i);
      qf[2 * i + n][0] = keep ? qf[2 * i + n][0] : r0;
      qf[2 * i + n][1] = keep ? qf[2 * i + n][1] : r1;
    }
    st(12 + i, qf[2 * i + 1][0]);
  }
#pragma unroll
  for (int c = 0; c < 9; c++)
    asm volatile("stmatrix.sync.aligned.m8n8.x2.shared.b16 [%0], {%1, %2};" ::"r"(ad[c] + LQ), "r"(qf[c][0]), "r"(qf[c][1]) : "memory");
  asm volatile("fence.proxy.async.shared::cta;" ::: "memory");
}
__device__ __forceinline__ void tma4d(uint32_t dst, const CUtensorMap* m, uint32_t bar, int c1, int c2, int c3) {
  asm volatile("cp.async.bulk.tensor.4d.shared::cluster.global.mbarrier::complete_tx::bytes [%0], [%1, {%3, %4, %5, %6}], [%2];" ::"r"(dst),
               "l"(m), "r"(bar), "r"(0), "r"(c1), "r"(c2), "r"(c3) : "memory");
}

#define ST_NUM 1
#define ST_DEN 2
#define K1_NST 6
constexpr int K1_BST = K1_NST;
#define MAXJ 11
constexpr int K1_MAXJOBS = MAXJ;
constexpr uint32_t K1_FLAG_TARGET = 7;
constexpr uint32_t RDY_TARGET = 48;
constexpr uint32_t GATE_TARGET = 128 * 3;
struct alignas(64) Params {
  CUtensorMap tmA[2];
  CUtensorMap tmW[4];
  CUtensorMap tmK, tmV;
  CUtensorMap tmL[3];
  CUtensorMap tmC, tmO[2], tmOt[2];
  CUtensorMap tmR[2];
  uint16_t jobs[NCLUSTER][K1_MAXJOBS + 1];
  uint8_t order[256];
  uint8_t unit[66][4];
};

struct K1State {
  uint32_t bs, bph, aph;
  bf16 *pp, *pp8;
  int png;
  int tn;
  int wsel;
  uint32_t fo;
};
__device__ __forceinline__ void k1_flag(const K1State& st, int lane, uint32_t bS) {
  if (st.png) {
    __syncwarp();
    if (lane == 0) mbar_arrive(bS + st.fo);
  }
}

__device__ __forceinline__ void scale_q4(uint32_t* v) {
#pragma unroll
  for (int i = 0; i < 4; i++)
    asm volatile("{\n.reg .b32 t;\nmul.rn.bf16x2 t, %0, %2;\nfma.rn.bf16x2 %0, %0, %1, t;\n}" : "+r"(v[i]) : "r"(0x3E033E03u), "r"(0xB9D8B9D8u));
}
__device__ __forceinline__ void k1_first(const K1State& st, uint32_t job, uint32_t bAf, uint32_t bBf) {
  if (job & 3) {
    if ((job >> 14) & 1) mbar_wait(bAf, st.aph);
    mbar_wait(bBf + st.bs * 8, st.bph);
  }
}
__device__ __forceinline__ void k1_tile(float (&acc)[128], uint32_t (&pk)[64], K1State& st, uint32_t job, uint32_t njob, uint32_t sA, uint32_t sB,
                                        uint32_t bAf, uint32_t bAe, uint32_t bBf, uint32_t bBe, uint32_t bS, int wg, int warp, int lane, uint32_t rank) {
  const int a_sel = (job >> 2) & 1, mpair = (job >> 3) & 7, w_sel = (job >> 6) & 3, chunk0 = (job >> 8) & 63;
  const bool newA = (job >> 14) & 1, lastA = (job >> 15) & 1;
  const bool sig = (lane == 0) && (warp < 2);
  const bool siga = lastA && (lane == 0) && (warp == 2);
  const int KC = 8 + a_sel;
  uint32_t prev_bs = 0, a8_bs = 0;
#pragma unroll
  for (int kc = 0; kc < 9; kc++) {
    if (kc >= KC) break;
    uint32_t abase = sA + ((kc + 2) & 7) * 16384;
    if (kc == 8) {
      mbar_wait(bBf + st.bs * 8, st.bph);
      a8_bs = st.bs;
      abase = sB + st.bs * 16384;
      if (++st.bs == K1_BST) { st.bs = 0; st.bph ^= 1; }
    } else if (newA && kc > 0) {
      mbar_wait(bAf + kc * 8, st.aph);
    }
    const uint64_t da = make_desc(abase + wg * 8192, 16, 1024, 1);
#pragma unroll
    for (int ks = 0; ks < 2; ks++) {
      if (ks > 0 || kc > 0) mbar_wait(bBf + st.bs * 8, st.bph);
      const uint64_t db = make_desc(sB + st.bs * 16384, 2048, 1024, 1);
      wg_fence();
      wgmma_ss_n256<1, 0>(acc, da + (uint64_t)(ks * 4), db, (ks > 0) ? 1 : (kc > 0));
      wgmma_ss_n256<1, 0>(acc, da + (uint64_t)(ks * 4 + 2), db + (uint64_t)512, 1);
      wg_commit();
      wg_wait<1>();
      if (ks > 0 || kc > 0) {
        if (sig) mbar_arrive_cluster(bBe + prev_bs * 8, warp);
        if (ks == 0 && siga) mbar_arrive(bAe + (kc - 1) * 8);
      }
      if (st.wsel == 2) {
        const int i = (kc & 7) * 2 + ks;
        if (kc < st.png) {
          quad_transpose(pk[i * 4], pk[i * 4 + 1], pk[i * 4 + 2], pk[i * 4 + 3], lane & 3);
          st_v4a((ks ? st.pp8 : st.pp) + kc * 32, pk[i * 4], pk[i * 4 + 1], pk[i * 4 + 2], pk[i * 4 + 3]);
        }
        if (i == 15) k1_flag(st, lane, bS);
      } else if (st.png) {
#pragma unroll
        for (int i = 0; i < 16; i++) {
          if (i * ST_NUM / ST_DEN != kc * 2 + ks) continue;
          if (st.wsel == 3) scale_q4(pk + i * 4);
          st_v4a(((i & 1) ? st.pp8 : st.pp) + (i / 2) * 32, pk[i * 4], pk[i * 4 + 1], pk[i * 4 + 2], pk[i * 4 + 3]);
          if (i == 15) k1_flag(st, lane, bS);
        }
      }
      prev_bs = st.bs;
      if (++st.bs == K1_BST) { st.bs = 0; st.bph ^= 1; }
    }
  }
  if (newA) st.aph ^= 1;
  const bool isA = (w_sel == 2);
  bf16* out = (w_sel == 0) ? g_K : (w_sel == 1) ? g_V : isA ? g_QKVA : g_ctx;
  const int ld = isA ? NQKVA : (w_sel == 3) ? KCAT : HDIM;
  const int row = mpair * 256 + rank * 128 + wg * 64 + warp * 16 + (lane >> 2);
  st.pp = ptr_add(out, (row * ld + chunk0 * 64 + (lane & 3) * 8) * 2);
  st.pp8 = ptr_add(st.pp, 16 * ld);
  st.png = ((job & 3) + 1) * 2;
  st.wsel = w_sel;
  st.fo = (st.fo + 8) & 24;
  k1_first(st, njob, bAf, bBf);
  wg_wait<0>();
  fence_regs(acc);
  mbar_arrive_cluster_if(bBe + prev_bs * 8, warp & 1, sig);
  mbar_arrive_cluster_if(bBe + a8_bs * 8, warp & 1, sig && a_sel);
  mbar_arrive_if(bAe + 7 * 8, siga && !a_sel);
#pragma unroll
  for (int i = 0; i < 64; i++) {
    const int j = (i >> 3) * 16 + (i & 3) * 4 + ((i >> 2) & 1) * 2;
    pk[i] = pack_bf16(acc[j], acc[j + 1]);
  }
}

constexpr int K2_NST = 7;
constexpr uint32_t K2_END = 0x100;
#define PFD 4
#define PF3A 2
#define PF3 6
#define KC0 1
#define CLEAD 2
#define RSPLIT 0x20000
#define RWAIT ""
#define FIRST_DRAW 3
#define PWAIT mbar_wait_ns<1000>
#define PVM 0x8A
#define W0 63
#define SPEC_HI 1.8446744073709552e19f
#define SPEC_LO 5.421010862427522e-20f
constexpr int K3_NST = 4;
#define K3_NS 6
__device__ __forceinline__ uint32_t k3_rot(uint32_t sv) { return (0x00E9u >> (2 * sv)) & 3; }
constexpr int K3_STAGE = 16384 + 32768 + 4096;
constexpr int SMEM_DATA = 7 * 32768;
constexpr int SMEM_BYTES = SMEM_DATA + 1024 + 896;

struct Cursor {
  uint32_t s, ph;
  __device__ __forceinline__ void next() {
    if (++s == K2_NST) { s = 0; ph ^= 1; }
  }
};

#define TURN_SYNC() bar_sync(mybar, 256)
#define TURN_ARRIVE() bar_arrive(otherbar, 256)
#define RELEASE_IF(cur, cond) mbar_arrive_cluster_if(bE + (cur).s * 8, warp & 1, sig && (cond))
#define RELEASE(cur) RELEASE_IF(cur, true)
#define ISSUE_PV(cur, first)                                                                                   \
  do {                                                                                                         \
    const uint64_t dv = make_desc(sbase + (cur).s * 32768, 16384, 1024, 1);                                    \
    _Pragma("unroll") for (int t = 0; t < 8; t++)                                                              \
        wgmma_rs_n128<1, 0>(O, P[4 * t], P[4 * t + 1], P[4 * t + 2], P[4 * t + 3], dv + (uint64_t)(t * 128), (t > 0) ? 1 : !(first)); \
  } while (0)
#define ISSUE_QK(cur)                                                                                          \
  do {                                                                                                         \
    const uint64_t dk = make_desc(sbase + (cur).s * 32768, 16, 1024, 1);                                       \
    _Pragma("unroll") for (int t = 0; t < 8; t++)                                                              \
        wgmma_rs_n128<0, 0>(S, Q[4 * t], Q[4 * t + 1], Q[4 * t + 2], Q[4 * t + 3], dk + (uint64_t)((t >> 2) * 1024 + (t & 3) * 2), t > 0); \
  } while (0)
#define LOAD_Q()                                                                                               \
  do {                                                                                                         \
    item = lds32(sItem + (it & 7) * 4);                                                                        \
    const uint32_t qa = sbase + cq.s * 32768 + (wg * 64 + warp * 16 + (lane & 15)) * 128;                      \
    _Pragma("unroll") for (int t = 0; t < 8; t++)                                                              \
        ldsm_x4(Q[4 * t], Q[4 * t + 1], Q[4 * t + 2], Q[4 * t + 3], qa + (t >> 2) * 16384 + ((((t & 3) * 2 + (lane >> 4)) ^ (lane & 7)) << 4)); \
  } while (0)
#define NEW_ITEM()                                                                                             \
  do {                                                                                                         \
    const int row = (2 * (item & 7) + hi) * 128 + wg * 64 + warp * 16 + (lane >> 2);                           \
    eoff = (row * KCAT + (item >> 3) * 128 + q * 8) * 2;                                                       \
    const float* gp = ptr_add(g_gate, row * 4);                                                                \
    asm volatile("ld.global.f32 %0, [%1];" : "=f"(gf0) : "l"(gp));                                             \
    asm volatile("ld.global.f32 %0, [%1];" : "=f"(gf1) : "l"(gp + 8));                                         \
    if (!hi) {                                                                                                 \
      mbar_wait2(bF + cs0.s * 8, cs0.ph, bF + cs1.s * 8, cs1.ph);                                              \
      RELEASE(cs0);                                                                                            \
      RELEASE(cs1);                                                                                            \
    }                                                                                                          \
  } while (0)
#define EXPB(T)                                                                                                \
  do {                                                                                                         \
    _Pragma("unroll") for (int i = 4 * T; i < 4 * T + 4; i++) asm volatile("" : "+r"(P[i])::"memory");        \
    _Pragma("unroll") for (int jj = 2 * T; jj < 2 * T + 2; jj++) {                                             \
      const float e0 = ex2(S[jj * 4 + 0]), e1 = ex2(S[jj * 4 + 1]), e2 = ex2(S[jj * 4 + 2]), e3 = ex2(S[jj * 4 + 3]); \
      s0 += e0 + e1;                                                                                           \
      s1 += e2 + e3;                                                                                           \
      P[jj * 2 + 0] = pack_bf16(e0, e1);                                                                       \
      P[jj * 2 + 1] = pack_bf16(e2, e3);                                                                       \
    }                                                                                                          \
  } while (0)
#define EXPC(T)                                                                                                \
  do {                                                                                                         \
    if (T > 0 && ((PVM >> (T - 1)) & 1)) {                                                                     \
      anchor((T & 2) ? s0 : s1, never);                                                                        \
      wg_wait<__builtin_popcount(PVM >> T) - 1>();                                                             \
      if ((PVM >> T) == (128 >> T)) { fence_regs(O); RELEASE(cv); }                                            \
    }                                                                                                          \
    EXPB(T);                                                                                                   \
  } while (0)
#define MASK(G, g)                                                                                             \
  do {                                                                                                         \
    if ((g) * 8 > d) S[(G) * 4 + 0] = -INFINITY;                                                               \
    if ((g) * 8 + 1 > d) S[(G) * 4 + 1] = -INFINITY;                                                           \
    if ((g) * 8 - 8 > d) S[(G) * 4 + 2] = -INFINITY;                                                           \
    if ((g) * 8 - 7 > d) S[(G) * 4 + 3] = -INFINITY;                                                           \
  } while (0)
#define STORE_O(G)                                                                                             \
  do {                                                                                                         \
    st_v4(optr + (G) * 32, pack_bf16(O[(G) * 16 + 0] * f0, O[(G) * 16 + 1] * f0), pack_bf16(O[(G) * 16 + 4] * f0, O[(G) * 16 + 5] * f0), \
          pack_bf16(O[(G) * 16 + 8] * f0, O[(G) * 16 + 9] * f0), pack_bf16(O[(G) * 16 + 12] * f0, O[(G) * 16 + 13] * f0)); \
    st_v4(optr + 8 * KCAT + (G) * 32, pack_bf16(O[(G) * 16 + 2] * f1, O[(G) * 16 + 3] * f1), pack_bf16(O[(G) * 16 + 6] * f1, O[(G) * 16 + 7] * f1), \
          pack_bf16(O[(G) * 16 + 10] * f1, O[(G) * 16 + 11] * f1), pack_bf16(O[(G) * 16 + 14] * f1, O[(G) * 16 + 15] * f1)); \
  } while (0)

#define FLUSH()                                                                                                \
  do {                                                                                                         \
    _Pragma("unroll") for (int G = 0; G < 8; G++) {                                                            \
      st_v4a(st.pp + G * 32, pk[G * 8], pk[G * 8 + 1], pk[G * 8 + 2], pk[G * 8 + 3]);                          \
      st_v4a(st.pp8 + G * 32, pk[G * 8 + 4], pk[G * 8 + 5], pk[G * 8 + 6], pk[G * 8 + 7]);                     \
    }                                                                                                          \
    k1_flag(st, lane, bS);                                                                                     \
  } while (0)

__global__ void __cluster_dims__(2, 1, 1) __launch_bounds__(384, 1)
fused_kernel(const __grid_constant__ Params p, const bf16* __restrict__ x, const bf16* __restrict__ gate_w, bf16* __restrict__ out) {
  extern __shared__ uint8_t smem_raw[];
  const uint32_t sbase = (smem_u32(smem_raw) + 1023) & ~1023u;
  const uint32_t sB = sbase, sA = sbase + K1_BST * 16384, sBar = sbase + SMEM_DATA;
  const uint32_t bAf = sBar, bAe = sBar + 64, bBf = sBar + 128, bBe = sBar + 176, bL = sBar + 224, bS = sBar + 656, bL2 = sBar + 240, sL = sA + 32768;
  const uint32_t bF = sBar + 256, bE = sBar + 320, bT = sBar + 384, sTick = sBar + 400, sItem = sBar + 416, bS2 = sBar + 688, bR = sBar + 456, bLast = sBar + 464, bH = sBar + 472, bT0 = sBar + 480, bZ = sBar + 488, bLd = sBar + 496;
  const uint32_t b3F = sBar + 512, b3E = sBar + 544, sGate = sBar + 576, sK1 = sBar + 720, sClm = sBar + 768;
  const int tid = threadIdx.x, warp_g = __shfl_sync(0xffffffffu, tid >> 5, 0), lane = tid & 31;
  const uint32_t rank = cluster_rank();
  const int cl = blockIdx.x >> 1;
  TSM(0);
  if (tid == 256) {
    const uint32_t job = p.jobs[cl][0];
#pragma unroll
    for (int i = 0; i < KC0; i++) { mbar_init(bAf + i * 8, 1); mbar_init(bBf + i * 16, 1); mbar_init(bBf + i * 16 + 8, 1); }
    asm volatile("fence.mbarrier_init.release.cluster;" ::: "memory");
#pragma unroll 1
    for (int i = 0; i < 4 * KC0; i++) {
      if (!(i & 3)) {
        mbar_expect(bAf + i * 2, 16384);
        tma2d(sA + (i / 4 + 2) * 16384, &p.tmA[(job >> 2) & 1], bAf + i * 2, i * 16, ((job >> 3) & 7) * 256 + rank * 128);
      }
      if (!(i & 1)) mbar_expect(bBf + i * 4, 16384);
      tma3d(sB + i * 8192, &p.tmW[(job >> 6) & 3], bBf + (i >> 1) * 8, 0, i * 16, (job >> 8) & 63);
    }
  }
  if (warp_g == 1) asm volatile("st.shared.u32 [%0], %1;" ::"r"(lane ? sClm + lane * 4 : sK1), "r"(lane ? 0xFFFFFFFFu : 80u) : "memory");
  if (tid == 0) {
    for (int i = 0; i < 8; i++) { if (i >= KC0) mbar_init(bAf + i * 8, 1); mbar_init(bAe + i * 8, 2); }
    for (int i = 0; i < K1_BST; i++) { if (i >= 2 * KC0) mbar_init(bBf + i * 8, 1); mbar_init(bBe + i * 8, 4); }
    mbar_init(bL, 1);
    mbar_init(bL2, 1);
    mbar_init(bR, 1);
    mbar_init(bLast, 1);
    mbar_init(bH, 4);
    mbar_init(bT0, 1);
    mbar_init(bZ, 1);
    mbar_init(bLd, 4);
    for (int i = 0; i < 8; i++) mbar_init(bS + i * 8, 8);
    for (int i = 0; i < K2_NST; i++) { mbar_init(bF + i * 8, 1); mbar_init(bE + i * 8, 4); }
    mbar_init(bT, 1); mbar_init(bT + 8, 1);
    for (int i = 0; i < K3_NST; i++) { mbar_init(b3F + i * 8, 1); mbar_init(b3E + i * 8, 4); }
    asm volatile("fence.mbarrier_init.release.cluster;" ::: "memory");
  }
  __syncwarp();
  if (warp_g != 8) cluster_sync();
  const int lr0 = blockIdx.x * 16;

  if (warp_g >= 8) {
    reg_dealloc<40>();
    if (warp_g == 8) {
      {
        __syncwarp();
        cluster_sync();
      }
      if (elect_one()) {
        uint32_t bs = (2 * KC0) % K1_BST, bph = (2 * KC0 < K1_BST), aph = 1;
#pragma unroll 1
        for (int ji = 0; ji < K1_MAXJOBS; ji++) {
          const uint32_t job = p.jobs[cl][ji];
          if (!(job & 3)) break;
          const int a_sel = (job >> 2) & 1, mpair = (job >> 3) & 7, chunk0 = (job >> 8) & 63;
          const bool newA = (job >> 14) & 1;
          const int KC = a_sel ? 9 : 8;
          const uint32_t halfbytes = 8192;
          const bool lastjob = (ji + 1 == K1_MAXJOBS) || !(p.jobs[cl][ji + 1] & 3);
          const CUtensorMap* tw = &p.tmW[(job >> 6) & 3];
          {
            const uint32_t njob = (ji + 1 < K1_MAXJOBS) ? p.jobs[cl][ji + 1] : 0;
            if (!(njob & 3) && !newA) mbar_arrive(bLast);
          }
#pragma unroll 1
          for (int kc = ji ? 0 : KC0; kc < KC; kc++) {
            {
              const bool nx = kc + PFD >= KC;
              const uint32_t njob = nx ? p.jobs[cl][ji + 1] : job;
              const int pk = nx ? kc + PFD - KC : kc + PFD;
              if ((njob & 3) && (nx || ji > 0)) {
                if (cl >= 64 || ((pk ^ (cl >> 1)) & 3) == 0)
                  tma_pf3d(&p.tmW[(njob >> 6) & 3], 0, pk * 64 + (cl & 1) * 32 + rank * 16, (njob >> 8) & 63);
                if (((njob >> 14) & 1) || pk == 8) tma_pf2d(&p.tmA[(njob >> 2) & 1], pk * 64, ((njob >> 3) & 7) * 256 + rank * 128);
              }
            }
            if (kc == 8) {
              PWAIT(bBe + bs * 8, bph);
              mbar_expect(bBf + bs * 8, 16384);
              tma2d(sB + bs * 16384, &p.tmA[1], bBf + bs * 8, 512, mpair * 256 + rank * 128);
              if (++bs == K1_BST) { bs = 0; bph ^= 1; }
            } else if (newA) {
              PWAIT(bAe + kc * 8, aph);
              mbar_expect(bAf + kc * 8, 16384);
              tma2d(sA + ((kc + 2) & 7) * 16384, &p.tmA[a_sel], bAf + kc * 8, kc * 64, mpair * 256 + rank * 128);
              if (kc == 7 && lastjob) mbar_arrive(bLast);
            }
#pragma unroll 1
            for (int kk = 0; kk < 2; kk++) {
              PWAIT(bBe + bs * 8, bph);
              mbar_expect(bBf + bs * 8, 2 * halfbytes);
              tma3d_mc(sB + bs * 16384 + rank * halfbytes, tw, bBf + bs * 8, 0, kc * 64 + kk * 32 + rank * 16, chunk0, 3);
              if (++bs == K1_BST) { bs = 0; bph ^= 1; }
            }
          }
          if (newA) aph ^= 1;
        }
        Cursor c{0, 0};
        int pcol = 0;
        PWAIT(bR, 0);
        uint32_t tick = lds32(sTick + 8), seen = 1u << (p.order[tick] >> 4);
        asm volatile("fence.proxy.async.global;" ::: "memory");
#pragma unroll 1
        for (int it = 0;; it++) {
          const uint32_t item = (tick < 256) ? p.order[tick] : (K2_END | min(tick - 256, 255u));
          asm volatile("st.shared.u32 [%0], %1;" ::"r"(sItem + (it & 7) * 4), "r"(item) : "memory");
          if (item >= K2_END) break;
          const int h = item >> 3, j = item & 7;
          const int blk = 2 * j + (int)(rank ^ (it & 1));
          const int col = h * 128 + rank * 64;
          const int nb = 2 * j + 2;
          if (!((seen >> (h >> 1)) & 1)) {
            wait_flag(&g_sync[F_HP + (h >> 1)], RDY_TARGET);
            asm volatile("fence.proxy.async.global;" ::: "memory");
            seen |= 1u << (h >> 1);
          }
          PWAIT(bE + c.s * 8, c.ph);
          mbar_expect(bF + c.s * 8, 32768);
          tma2d(sbase + c.s * 32768, &p.tmC, bF + c.s * 8, h * 128, blk * 128);
          tma2d(sbase + c.s * 32768 + 16384, &p.tmC, bF + c.s * 8, h * 128 + 64, blk * 128);
          c.next();
          if (tick >= 256 - 73) {
            const int kk = tick - (256 - 73), sel = (kk < 9), kr = (sel ? kk : kk - 9) * 64 + rank * 32;
#pragma unroll 1
            for (int i = 0; i < 2; i++) {
              tma_pf3d(&p.tmO[sel], 0, kr, i * 4);
              tma_pf2d(&p.tmOt[sel], 512 + i * 32, kr);
            }
          }
#pragma unroll 1
          for (int n = nb - 1; n >= 0; n--) {
            if (n == 0 && rank == 0) tick = atomicAdd(&g_sync[F_TICK], 1u);
            PWAIT(bE + c.s * 8, c.ph);
            mbar_expect(bF + c.s * 8, 32768);
            tma2d_mc(sbase + c.s * 32768 + rank * 16384, &p.tmK, bF + c.s * 8, col, n * 128, 3);
            c.next();
            if (n < nb - 1 || it > 0) {
              PWAIT(bE + c.s * 8, c.ph);
              mbar_expect(bF + c.s * 8, 32768);
              tma2d_mc(sbase + c.s * 32768 + rank * 16384, &p.tmV, bF + c.s * 8, (n < nb - 1) ? col : pcol, (n < nb - 1) ? (n + 1) * 128 : 0, 3);
              c.next();
            }
          }
          pcol = col;
          if (rank == 0) {
            asm volatile(
                "{\n.reg .b32 a, b;\nmapa.shared::cluster.u32 a, %0, 1;\nmapa.shared::cluster.u32 b, %1, 1;\n"
                "st.async.shared::cluster.mbarrier::complete_tx::bytes.u32 [a], %2, [b];\n}" ::"r"(sTick + (it & 1) * 4),
                "r"(bT + (it & 1) * 8), "r"(tick) : "memory");
          } else {
            mbar_expect(bT + (it & 1) * 8, 4);
            PWAIT(bT + (it & 1) * 8, (it >> 1) & 1);
            tick = lds32(sTick + (it & 1) * 4);
          }
        }
        PWAIT(bE + c.s * 8, c.ph);
        mbar_expect(bF + c.s * 8, 32768);
        tma2d_mc(sbase + c.s * 32768 + rank * 16384, &p.tmV, bF + c.s * 8, pcol, 0, 3);
        const uint32_t unit = tick - 256;
        const int mblk = (7 - (p.unit[unit][0] >> 1)) * 2 + rank, nhalf = p.unit[unit][0] & 1;
        uint32_t have, hoa;
        asm volatile("ld.acquire.gpu.global.u32 %0, [%1];" : "=r"(have) : "l"(&g_sync[F_CTX + mblk]) : "memory");
        asm volatile("ld.acquire.gpu.global.u32 %0, [%1];" : "=r"(hoa) : "l"(&g_sync[F_OA + mblk]) : "memory");
        asm volatile("fence.proxy.async.global;" ::: "memory");
#pragma unroll 1
        for (uint32_t idx = PF3A; idx < PF3; idx++) {
          const int kk = p.unit[unit][2] + idx;
          if ((kk < 9) ? (hoa >= 8) : ((have >> ((kk - 9) >> 1)) & 1)) tma_pf2d(&p.tmC, ((kk < 9) ? 64 + kk : kk - 9) * 64, mblk * 128);
        }
        {
          const uint32_t rot = k3_rot(c.s), nfree = ((0x1Au >> c.s) & 1) ? 2 : 3;
          uint32_t kk = p.unit[unit][2], idx = 0, pa = 0, pb = 0;
          auto step = [&](uint32_t& pend) {
            uint32_t nxt = kk + 1;
            if (idx + 1 >= K3_NS) {
              if (rank == 0) {
                nxt = min(pend + p.unit[unit][3], 73u);
                asm volatile("{\n.reg .b32 a;\nmapa.shared::cluster.u32 a, %0, 1;\nst.volatile.shared::cluster.u8 [a], %1;\n}" ::"r"(sClm + idx), "r"(nxt) : "memory");
              } else {
#pragma unroll 1
                for (uint32_t spins = 0; spins < (1u << 22); spins++) {
                  asm volatile("ld.volatile.shared.u8 %0, [%1];" : "=r"(nxt) : "r"(sClm + idx) : "memory");
                  if (nxt != 255) break;
                  __nanosleep(20);
                }
              }
              if (nxt >= 73) asm volatile("st.shared.u32 [%0], %1;" ::"r"(sK1), "r"(idx + 1) : "memory");
            }
            const uint32_t s = (rot + idx) & 3;
            if (idx >= nfree) PWAIT((idx < 4) ? bH : b3E + s * 8, (idx < 4) ? 0 : (~idx >> 2) & 1);
#pragma unroll 1
            while (idx < nfree && c.s != ((0x6431u >> (4 * s)) & 15)) {
              c.next();
              PWAIT(bE + c.s * 8, c.ph);
            }
            mbar_expect(b3F + s * 8, K3_STAGE);
            const uint32_t st = sbase + s * K3_STAGE;
            const int sel = (kk < 9), k = sel ? kk : kk - 9, kr = k * 64 + rank * 32;
            tma3d_mc(st + 16384 + rank * 16384, &p.tmO[sel], b3F + s * 8, 0, kr, nhalf * 4, 3);
            tma2d_mc(st + 49152 + rank * 2048, &p.tmOt[sel], b3F + s * 8, 512 + nhalf * 32, kr, 3);
            if (rank == 0 && idx + 3 >= K3_NS) pend = atomicAdd(&g_sync[F_CLM + p.unit[unit][0]], 1u);
            if (sel && hoa < 8) {
              wait_flag(&g_sync[F_OA + mblk], 8);
              hoa = 8;
              asm volatile("fence.proxy.async.global;" ::: "memory");
            }
            if (!sel && !((have >> (k >> 1)) & 1)) {
#pragma unroll 1
              for (uint32_t spins = 0; spins < (1u << 22); spins++) {
                asm volatile("ld.acquire.gpu.global.u32 %0, [%1];" : "=r"(have) : "l"(&g_sync[F_CTX + mblk]) : "memory");
                if ((have >> (k >> 1)) & 1) break;
                __nanosleep(100);
              }
              asm volatile("fence.proxy.async.global;" ::: "memory");
            }
            tma2d(st, &p.tmC, b3F + s * 8, (sel ? 64 + k : k) * 64, mblk * 128);
            kk = nxt;
            idx++;
            return nxt >= 73;
          };
#pragma unroll 1
          for (;;) {
            if (step(pa)) break;
            if (step(pb)) break;
          }
          asm volatile("" ::"r"(pa), "r"(pb) : "memory");
        }
      }
    }
    __syncwarp();
    if (warp_g == 8) {
      uint32_t v = 0;
      if (lane == 0) {
        __threadfence();
        v = atomicAdd(&g_sync[F_DONE], 1u);
      }
      if (__shfl_sync(0xffffffffu, v, 0) == 2 * NCLUSTER - 1) {
        reinterpret_cast<uint4*>(g_sync)[lane] = make_uint4(0, 0, 0, 0);
        if (lane == 0) g_sync[F_EPOCH] = lds32(sGate + 64) + 1;
      }
    }
    asm volatile("" ::: "memory");
    if (__shfl_sync(0xffffffffu, warp_g, 0) != 8) {
      if (lr0 < S_LEN) {
#pragma unroll 1
        for (int i = warp_g - 9; i < 16; i += 3) {
          const float g = gate_row(lr0 + i, lane, x, gate_w);
          if (lane == 0) asm volatile("st.shared.f32 [%0], %1;" ::"r"(sGate + i * 4), "f"(g) : "memory");
        }
        bar_arrive(3, 256 + 96);
        if (lane == 0) {
          __threadfence();
          atomicAdd(&g_sync[F_GATE], 1u);
        }
      }
      uint32_t aph = 1;
#pragma unroll 1
      for (int ji = 0; ji < K1_MAXJOBS; ji++) aph ^= (p.jobs[cl][ji] >> 14) & 1;
      if (warp_g == 9) {
        uint32_t nxt = 0;
        if (lane == 0) {
#pragma unroll 1
        for (int ji = 0; ji < K1_MAXJOBS; ji++) {
          const uint32_t job = p.jobs[cl][ji];
          if (!(job & 3)) break;
          PWAIT(bS + (ji & 3) * 8, (ji >> 2) & 1);
          __threadfence();
          atomicAdd(&g_sync[(((job >> 6) & 3) == 2) ? (F_QKVA + ((job >> 3) & 7) * 2 + rank) : (F_HP + ((job >> 10) & 15))], 1u);
        }
#pragma unroll 1
        for (int it = 0;; it++) {
          PWAIT(bS2 + (it & 3) * 8, (it >> 2) & 1);
          const uint32_t item = lds32(sItem + (it & 7) * 4);
          nxt = lds32(sItem + ((it + 1) & 7) * 4);
          __threadfence();
          atomicOr(&g_sync[F_CTX + (item & 7) * 2 + (rank ^ (it & 1))], 1u << (item >> 3));
          if (nxt >= K2_END) break;
        }
        }
        const uint32_t unit = __shfl_sync(0xffffffffu, nxt, 0) & 255;
        {
          const int mblk = (7 - (p.unit[unit][0] >> 1)) * 2 + rank, nhalf = p.unit[unit][0] & 1;
          bf16* o = ptr_add(out, (mblk * 128 + p.unit[unit][1] * 32) * DM * 2);
          const bool mine = p.unit[unit][1] < 4;
#pragma unroll 4
          for (int i = 0; i < 32 && mine; i++) __stcg(reinterpret_cast<uint4*>(ptr_add(o, i * DM * 2 + nhalf * 512 + lane * 16)), make_uint4(0, 0, 0, 0));
#pragma unroll
          for (int i = 0; i < 4 && mine; i++) __stcg(reinterpret_cast<uint4*>(ptr_add(o, (i * 8 + (lane >> 2)) * DM * 2 + 1024 + nhalf * 64 + (lane & 3) * 16)), make_uint4(0, 0, 0, 0));
          asm volatile("fence.proxy.async.global;" ::: "memory");
          __threadfence();
          __syncwarp();
          if (lane == 0) {
            prefetch_tmap(&p.tmR[0]); prefetch_tmap(&p.tmR[1]);
            unsigned int* cnt = &g_sync[F_XCH + mblk * 2 + nhalf];
            const uint32_t xtarget = lds32(sGate + 64) * 4 + 4;
            if (mine) atomicAdd(cnt, 1u);
            uint32_t v;
#pragma unroll 1
            for (uint32_t spins = 0; spins < (1u << 22); spins++) {
              asm volatile("ld.acquire.gpu.global.u32 %0, [%1];" : "=r"(v) : "l"(cnt) : "memory");
              if ((int)(v - xtarget) >= 0) break;
              __nanosleep(200);
            }
            asm volatile("fence.proxy.async.global;" ::: "memory");
            mbar_arrive(bZ);
          }
        }
      } else if (warp_g == 11) {
        if (lane == 0) {
          prefetch_tmap(&p.tmC); prefetch_tmap(&p.tmK); prefetch_tmap(&p.tmV);
          asm volatile("st.shared.u32 [%0], %1;" ::"r"(sGate + 64), "r"(__ldcg(&g_sync[F_EPOCH])) : "memory");
          wait_flag(&g_sync[F_GATE], GATE_TARGET);
          uint32_t tick;
          if (rank == 0) {
            PWAIT(bLast, 0);
            PWAIT(bAe + FIRST_DRAW * 8, aph);
            tick = atomicAdd(&g_sync[F_TICK], 1u);
            asm volatile("st.shared.u32 [%0], %1;" ::"r"(sTick + 8), "r"(tick) : "memory");
            asm volatile(
                "{\n.reg .b32 a, b;\nmapa.shared::cluster.u32 a, %0, 1;\nmapa.shared::cluster.u32 b, %1, 1;\n"
                "st.async.shared::cluster.mbarrier::complete_tx::bytes.u32 [a], %2, [b];\n}" ::"r"(sTick + 8), "r"(bT0), "r"(tick) : "memory");
          } else {
            mbar_expect(bT0, 4);
            PWAIT(bT0, 0);
            tick = lds32(sTick + 8);
          }
          wait_flag(&g_sync[F_HP + (p.order[tick] >> 4)], RDY_TARGET);
          mbar_arrive(bR);
        }
      } else if (warp_g == 10) {
        if (lr0 < S_LEN && lane == 0) {
          prefetch_tmap(&p.tmL[0]); prefetch_tmap(&p.tmL[1]); prefetch_tmap(&p.tmL[2]);
          wait_flag(&g_sync[F_QKVA + (lr0 >> 7)], K1_FLAG_TARGET);
          wait_flag(&g_sync[F_QKVA + (max(lr0 - 16, 0) >> 7)], K1_FLAG_TARGET);
          asm volatile("fence.proxy.async.global;" ::: "memory");
          PWAIT(bLast, 0);
#pragma unroll 1
          for (int kc = 0; kc < 6; kc++) {
            PWAIT(bAe + kc * 8, aph);
            if (kc == 3) {
              mbar_expect(bL, LV);
              tma4d(sL, &p.tmL[0], bL, lr0 / 2 - 8, 9, 0);
              tma4d(sL + LQ, &p.tmL[1], bL, lr0 / 2, 0, 0);
            }
          }
          mbar_expect(bL2, LQ);
          tma4d(sL + LV, &p.tmL[0], bL2, lr0 / 2 - 8, 18, 0);
        }
        __syncwarp();
        bar_sync(5, 256 + 32);
        if (lr0 < S_LEN && lane == 0) {
          asm volatile("cp.async.bulk.tensor.4d.global.shared::cta.bulk_group [%0, {%2, %3, %2, %2}], [%1];" ::"l"(&p.tmL[2]), "r"(sL + LQ), "r"(0), "r"(lr0 / 2) : "memory");
          asm volatile("cp.async.bulk.commit_group;" ::: "memory");
          asm volatile("cp.async.bulk.wait_group.read 0;" ::: "memory");
        }
        __syncwarp();
        if (lane < 12) mbar_arrive_cluster(bE + (4 + lane % 3) * 8, (lane / 3) & 1);
        if (lr0 < S_LEN && lane == 0) {
          asm volatile("cp.async.bulk.wait_group 0;" ::: "memory");
          asm volatile("fence.proxy.async.global;" ::: "memory");
          __threadfence();
          atomicAdd(&g_sync[F_OA + (lr0 >> 7)], 1u);
        }
      }
    }
    __syncwarp();
    cluster_sync();
  } else {
    reg_alloc<232>();
    const int wg = warp_g >> 2, warp = warp_g & 3, q = lane & 3;
    const bool sig = (lane == 0) && (warp < 2);
    {
      K1State st{0, 0, 0, nullptr, nullptr, 0, 0, 0, 24};
      float acc[128];
      uint32_t pk[64];
      if (wg == 0) { TS(0, 0); TSC(0, 2); }
      uint32_t job = p.jobs[cl][0];
      k1_first(st, job, bAf, bBf);
      {
#pragma unroll 1
        for (int ji = 0; job & 3; ji++) {
          const uint32_t njob = p.jobs[cl][ji + 1];
          k1_tile(acc, pk, st, job, njob, sA, sB, bAf, bAe, bBf, bBe, bS, wg, warp, lane, rank);
          job = njob;
        }
      }
#pragma unroll
      for (int i = 0; i < 4; i++)
        mbar_arrive_cluster_if(bE + i * 8, warp & 1, sig);
      if (lr0 < S_LEN) bar_sync(3, 256 + 96);
      if (st.wsel == 3) {
#pragma unroll
        for (int G = 0; G < 16; G++) scale_q4(pk + G * 4);
      }
      auto flush = [&](int i, uint32_t dep) {
        asm volatile("{\n.reg .pred p;\nsetp.eq.u32 p, %5, 0;\n@p st.global.cs.v4.b32 [%0], {%1, %2, %3, %4};\n}" ::"l"(((i & 1) ? st.pp8 : st.pp) + (i / 2) * 32),
                     "r"(pk[i * 4]), "r"(pk[i * 4 + 1]), "r"(pk[i * 4 + 2]), "r"(pk[i * 4 + 3]), "r"(dep & blockIdx.y) : "memory");
      };
      if (wg == 0) { TS(0, 1); TSC(0, 3); }
      if (lr0 < S_LEN) {
        const float gate0 = __uint_as_float(lds32(sGate + (lane >> 2) * 8)), gate1 = __uint_as_float(lds32(sGate + (lane >> 2) * 8 + 4));
        local_attn(lr0, warp_g, sL, bL, bL2, lane, gate0, gate1, flush);
        k1_flag(st, lane, bS);
      } else {
        FLUSH();
      }
      bar_arrive(5, 256 + 32);
    }
    __syncwarp();
    uint32_t item, rot;
    {
      const int mybar = 1 + wg, otherbar = 2 - wg;
      const uint32_t never = blockIdx.y;
      float S[64], O[64];
      uint32_t P[32], Q[32];
      float m0, m1, l0, l1, gf0, gf1;
      uint32_t eoff;
      Cursor c{4 - 2 * rank, 0}, ck{2 - rank, 0};
      if (wg == 1) bar_arrive(1, 256);
      if (wg == 0) { TS(1, 0); TSC(1, 2); }
      {
        const Cursor cq{0, 0}, cs0{1, 0}, cs1{3, 0};
        const int it = 0, hi = rank;
        mbar_wait2(bF, 0, bF + ck.s * 8, 0);
        LOAD_Q();
        wg_fence();
        ISSUE_QK(ck);
        wg_commit();
        RELEASE(cq);
        NEW_ITEM();
        wg_wait<0>();
        fence_regs(S);
      }
#pragma unroll 1
      for (int it = 0;;) {
        int hi = (int)(rank ^ (it & 1));
        RELEASE(ck);
        const int nblk = 2 * (item & 7) + 1 + hi;
        Cursor cv;
        float s0 = 0.f, s1 = 0.f;
        l0 = 0.f; l1 = 0.f;
        m0 = 0.f; m1 = 0.f;
        bool shifted = false;
        {
          const int d = warp * 16 + (lane >> 2) - 2 * q;
          if (wg == 0) {
#pragma unroll
            for (int jj = 0; jj < 8; jj++) MASK(jj, jj);
            EXPB(0); EXPB(1); EXPB(2); EXPB(3);
#pragma unroll
            for (int i = 32; i < 64; i++) S[i] = -INFINITY;
#pragma unroll
            for (int i = 16; i < 32; i++) P[i] = 0;
          } else {
#pragma unroll
            for (int jj = 0; jj < 8; jj++) MASK(jj + 8, jj);
            EXPB(0); EXPB(1); EXPB(2); EXPB(3); EXPB(4); EXPB(5); EXPB(6); EXPB(7);
          }
        }
        float chk = (q == 0 && !(fminf(s0, s1) >= SPEC_LO)) ? INFINITY : s0 + s1;
        fence_regs(P);
        TB(9);
#pragma unroll 1
        for (int n = 1;; n++) {
          if (__any_sync(0xffffffffu, !(chk <= SPEC_HI))) {
            float mx0 = fmaxf(S[0], S[1]), mx1 = fmaxf(S[2], S[3]);
#pragma unroll
            for (int jj = 1; jj < 16; jj++) {
              mx0 = fmaxf(mx0, fmaxf(S[jj * 4 + 0], S[jj * 4 + 1]));
              mx1 = fmaxf(mx1, fmaxf(S[jj * 4 + 2], S[jj * 4 + 3]));
            }
            mx0 = fmaxf(mx0, __shfl_xor_sync(0xffffffffu, mx0, 1));
            mx1 = fmaxf(mx1, __shfl_xor_sync(0xffffffffu, mx1, 1));
            mx0 = fmaxf(mx0, __shfl_xor_sync(0xffffffffu, mx0, 2));
            mx1 = fmaxf(mx1, __shfl_xor_sync(0xffffffffu, mx1, 2));
            const float lo = (n == 1) ? -INFINITY : 0.f;
            mx0 = fmaxf(mx0, lo);
            mx1 = fmaxf(mx1, lo);
            m0 += mx0; m1 += mx1;
            shifted = true;
            const float sc0 = ex2(-fmaxf(mx0, 0.f)), sc1 = ex2(-fmaxf(mx1, 0.f));
            l0 *= sc0; l1 *= sc1;
            s0 = 0.f; s1 = 0.f;
#pragma unroll
            for (int jj = 0; jj < 16; jj++) {
              const float e0 = ex2(S[jj * 4 + 0] - mx0), e1 = ex2(S[jj * 4 + 1] - mx0), e2 = ex2(S[jj * 4 + 2] - mx1), e3 = ex2(S[jj * 4 + 3] - mx1);
              s0 += e0 + e1;
              s1 += e2 + e3;
              P[jj * 2 + 0] = pack_bf16(e0, e1);
              P[jj * 2 + 1] = pack_bf16(e2, e3);
              O[jj * 4 + 0] *= sc0;
              O[jj * 4 + 1] *= sc0;
              O[jj * 4 + 2] *= sc1;
              O[jj * 4 + 3] *= sc1;
            }
          }
          l0 += s0;
          l1 += s1;
          if (n >= nblk) break;
          ck = c; c.next();
          cv = c; c.next();
          mbar_wait(bF + ck.s * 8, ck.ph);
          mbar_wait(bF + cv.s * 8, cv.ph);
          TURN_SYNC();
          TRC(0);
          wg_fence();
          ISSUE_QK(ck);
          wg_commit();
          {
            const uint64_t dv = make_desc(sbase + cv.s * 32768, 16384, 1024, 1);
#pragma unroll
            for (int t = 0; t < 8; t++) {
              wgmma_rs_n128<1, 0>(O, P[4 * t], P[4 * t + 1], P[4 * t + 2], P[4 * t + 3], dv + (uint64_t)(t * 128), (t > 0) ? 1 : (n != 1));
              if ((PVM >> t) & 1) wg_commit();
            }
          }
          TURN_ARRIVE();
          s0 = 0.f; s1 = 0.f;
          wg_wait<__builtin_popcount(PVM)>();
          fence_regs(S);
          RELEASE(ck);
          if (shifted) {
#pragma unroll
            for (int i = 0; i < 64; i++) S[i] -= (i & 2) ? m1 : m0;
          }
          wg_wait<__builtin_popcount(PVM) - 1>();
          EXPC(0); EXPC(1); EXPC(2); EXPC(3); EXPC(4); EXPC(5); EXPC(6); EXPC(7);
          chk = s0 + s1;
        }
        it++;
        hi ^= 1;
        TB(0);
        Cursor cq = c, cs0, cs1;
        rot = k3_rot(c.s);
        c.next();
        ck = c; c.next();
        cs0 = ck; cs1 = ck;
        cv = c; c.next();
        if (!hi) {
          ck = c; c.next();
          cs1 = c; c.next();
        }
        mbar_wait(bF + cq.s * 8, cq.ph);
        TB(1);
        LOAD_Q();
        const uint32_t rdy = mbar_test(bF + ck.s * 8, ck.ph) & mbar_test(bF + cv.s * 8, cv.ph);
        l0 += __shfl_xor_sync(0xffffffffu, l0, 1);
        l1 += __shfl_xor_sync(0xffffffffu, l1, 1);
        l0 += __shfl_xor_sync(0xffffffffu, l0, 2);
        l1 += __shfl_xor_sync(0xffffffffu, l1, 2);
        if (item >= K2_END) {
          TURN_SYNC();
          TRC(2);
          wg_fence();
          ISSUE_PV(cq, nblk == 1);
          wg_commit();
          if (wg == 0) TURN_ARRIVE();
          asm volatile("" : "+f"(gf0), "+f"(gf1), "+f"(l0), "+f"(l1));
          const float f0 = __fdividef(1.f - gf0, l0), f1 = __fdividef(1.f - gf1, l1);
          bf16* optr = ptr_add(g_ctx, eoff);
          wg_wait<0>();
          fence_regs(O);
          mbar_arrive_cluster_if(bH, warp & 1, sig);
          STORE_O(0); STORE_O(1); STORE_O(2); STORE_O(3);
          __syncwarp();
          mbar_arrive_if(bS2 + ((it - 1) & 3) * 8, lane == 0);
          break;
        }
        if (!rdy) mbar_wait2(bF + ck.s * 8, ck.ph, bF + cv.s * 8, cv.ph);
        TB(2);
        TURN_SYNC();
        TB(3);
        TRC(1);
        wg_fence();
        ISSUE_PV(cv, nblk == 1);
        wg_commit();
        ISSUE_QK(ck);
        wg_commit();
        TURN_ARRIVE();
        RELEASE(cq);
        TB(4);
        asm volatile("" : "+f"(gf0), "+f"(gf1), "+f"(l0), "+f"(l1));
        const float f0 = __fdividef(1.f - gf0, l0), f1 = __fdividef(1.f - gf1, l1);
        wg_wait<1>();
        fence_regs(O);
        fence_regs(P);
        TB(5);
        RELEASE(cv);
        {
          bf16* optr = ptr_add(g_ctx, eoff);
          STORE_O(0); STORE_O(1); STORE_O(2); STORE_O(3);
          __syncwarp();
          mbar_arrive_if(bS2 + ((it - 1) & 3) * 8, lane == 0);
        }
        TB(6);
        NEW_ITEM();
        TB(7);
        wg_wait<0>();
        fence_regs(S);
        TB(8);
      }
      TRC(3);
      if (wg == 1) { TS(1, 1); TSC(1, 3); }
    }
    __syncwarp();
    const uint32_t unit = item & 255;
    {
      const int mblk = (7 - (p.unit[unit][0] >> 1)) * 2 + rank, nhalf = p.unit[unit][0] & 1;
      const uint32_t k0 = 0;
      uint32_t k1;
      float acc[144];
      uint32_t s = rot, ph = 0, prev = 0;
      if (wg == 0) { TS(2, 0); TSC(2, 2); }
      uint32_t fa[16], fb[16];
      const uint32_t aoff = (wg * 64 + warp * 16 + (lane & 15)) * 128 + (((lane >> 4) ^ (lane & 7)) << 4);
#define C_LOAD(F)                                                                                              \
  do {                                                                                                         \
    mbar_wait(b3F + s * 8, ph);                                                                                \
    k1 = lds32(sK1);                                                                                           \
    _Pragma("unroll") for (int t = 0; t < 4; t++)                                                              \
        ldsm_x4(F[4 * t], F[4 * t + 1], F[4 * t + 2], F[4 * t + 3], sbase + s * K3_STAGE + (aoff ^ (t * 32))); \
  } while (0)
#define C_STEP(F, G)                                                                                           \
  {                                                                                                            \
    const uint32_t st = sbase + s * K3_STAGE;                                                                  \
    const uint64_t db = make_desc(st + 16384, 4096, 1024, 1), dt = make_desc(st + 49152, 16, 512, 2);          \
    if (CLEAD && wg == 1 && k + CLEAD >= k1) mbar_wait(bLd, 0);                                                \
    wg_fence();                                                                                                \
    _Pragma("unroll") for (int t = 0; t < 4; t++) {                                                            \
      const int sd = (t > 0) || (k > k0);                                                                      \
      wgmma_rs_n256<1, 0>(acc, F[4 * t], F[4 * t + 1], F[4 * t + 2], F[4 * t + 3], db + (uint64_t)((t >> 1) * 1024 + (t & 1) * 128), sd); \
      wgmma_rs_n32<1, 128>(acc, F[4 * t], F[4 * t + 1], F[4 * t + 2], F[4 * t + 3], dt + (uint64_t)(t * 64), sd); \
    }                                                                                                          \
    wg_commit();                                                                                               \
    mbar_arrive_if(bLd, CLEAD && tid < 128 && lane == 0 && k + 1 == k1);                                       \
    wg_wait<1>();                                                                                              \
    fence_regs(G);                                                                                             \
    mbar_arrive_cluster_if(b3E + prev * 8, warp & 1, sig && k > k0);                                           \
    prev = s;                                                                                                  \
    s = (s + 1) & 3;                                                                                           \
    if (s == rot) ph ^= 1;                                                                                     \
    TCK(k + 1);                                                                                                \
    if (++k >= k1) break;                                                                                      \
    C_LOAD(G);                                                                                                 \
  }
      TCK(0);
      C_LOAD(fa);
#pragma unroll
      for (int i = 0; i < 16; i++) fb[i] = 0;
#pragma unroll 1
      for (uint32_t k = k0;;) {
        C_STEP(fa, fb)
        C_STEP(fb, fa)
      }
      wg_wait<0>();
      fence_regs(acc);
      cluster_arrive();
      if (wg == 0) TS(2, 4);
      const uint32_t stail = sbase + K3_NST * K3_STAGE + warp_g * 1024;
      const int row = mblk * 128 + warp_g * 16;
      mbar_wait(bZ, 0);
#pragma unroll
      for (int i = 0; i < 18; i++) {
        const uint32_t ad = (i < 16) ? sbase + (i >> 2) * K3_STAGE + (aoff ^ ((i & 3) * 32))
                                     : stail + (lane & 15) * 64 + ((((i & 1) * 2 + (lane >> 4)) ^ ((lane >> 1) & 3)) << 4);
        asm volatile("stmatrix.sync.aligned.m8n8.x4.shared.b16 [%0], {%1, %2, %3, %4};" ::"r"(ad), "r"(pack_bf16(acc[i * 8], acc[i * 8 + 1])),
                     "r"(pack_bf16(acc[i * 8 + 2], acc[i * 8 + 3])), "r"(pack_bf16(acc[i * 8 + 4], acc[i * 8 + 5])), "r"(pack_bf16(acc[i * 8 + 6], acc[i * 8 + 7])) : "memory");
        if ((RSPLIT >> i) & 1) {
          asm volatile("fence.proxy.async.shared::cta;" ::: "memory");
          __syncwarp();
          if (i == 17 && wg == 0) TS(2, 5);
          if (lane == 0) {
#pragma unroll
            for (int c = 0; c < 5; c++)
              if (c * 4 <= i && (RSPLIT & ((1 << i) - 1)) < (1 << (c * 4))
              )
                asm volatile("cp.reduce.async.bulk.tensor.2d.global.shared::cta.add.tile.bulk_group [%0, {%2, %3}], [%1];" ::"l"(&p.tmR[c >> 2]),
                             "r"((c < 4) ? sbase + c * K3_STAGE + warp_g * 2048 : stail), "r"((c < 4) ? nhalf * 256 + c * 64 : 512 + nhalf * 32), "r"(row) : "memory");
          }
        }
      }
      if (lane == 0) {
        asm volatile("cp.async.bulk.commit_group;" ::: "memory");
        if (wg == 0) TS(2, 6);
        asm volatile("cp.async.bulk.wait_group" RWAIT " 0;" ::: "memory");
      }
      __syncwarp();
    }
    if (wg == 0) { TS(2, 1); TSC(2, 3); }
    cluster_wait();
  }
}

typedef CUresult (*EncFn)(CUtensorMap*, CUtensorMapDataType, cuuint32_t, void*, const cuuint64_t*, const cuuint64_t*, const cuuint32_t*,
                          const cuuint32_t*, CUtensorMapInterleave, CUtensorMapSwizzle, CUtensorMapL2promotion, CUtensorMapFloatOOBfill);

static void enc2d(EncFn enc, CUtensorMap* m, const void* ptr, uint64_t cols, uint64_t rows, uint32_t bc, uint32_t br,
                  CUtensorMapSwizzle sw = CU_TENSOR_MAP_SWIZZLE_128B) {
  cuuint64_t gd[2] = {cols, rows}, gs[1] = {cols * 2};
  cuuint32_t bx[2] = {bc, br}, es[2] = {1, 1};
  enc(m, CU_TENSOR_MAP_DATA_TYPE_BFLOAT16, 2, const_cast<void*>(ptr), gd, gs, bx, es, CU_TENSOR_MAP_INTERLEAVE_NONE, sw,
      CU_TENSOR_MAP_L2_PROMOTION_L2_256B, CU_TENSOR_MAP_FLOAT_OOB_FILL_NONE);
}
static void enc3d(EncFn enc, CUtensorMap* m, const void* ptr, uint64_t cols, uint64_t rows, uint32_t br, uint32_t bch) {
  cuuint64_t gd[3] = {64, rows, cols / 64}, gs[2] = {cols * 2, 128};
  cuuint32_t bx[3] = {64, br, bch}, es[3] = {1, 1, 1};
  enc(m, CU_TENSOR_MAP_DATA_TYPE_BFLOAT16, 3, const_cast<void*>(ptr), gd, gs, bx, es, CU_TENSOR_MAP_INTERLEAVE_NONE,
      CU_TENSOR_MAP_SWIZZLE_128B, CU_TENSOR_MAP_L2_PROMOTION_L2_256B, CU_TENSOR_MAP_FLOAT_OOB_FILL_NONE);
}

static int g_sched[10] = {11, 10, 7, 4, 4, 4, 6, 8, 6, 24};
static void build_k1_jobs(Params& p) {
  int cnt[NCLUSTER];
  for (int c = 0; c < NCLUSTER; c++) {
    cnt[c] = 0;
    for (int i = 0; i <= K1_MAXJOBS; i++) p.jobs[c][i] = 0;
  }
  auto add = [&](int c, int nch, int a_sel, int mp, int w_sel, int chunk0) {
    p.jobs[c][cnt[c]++] = (uint16_t)((nch - 1) | (a_sel << 2) | (mp << 3) | (w_sel << 6) | (chunk0 << 8));
  };
  const char* plan = "ccccccccccc cccccccccc ccccccc cccc xxxx xxxx xxxxxx xxxxxxxx";
  int TIE = 0;
  int XA = 0;
  const char* cur[8];
  int tend[8] = {};
  for (int g = 0; g < 8; g++) {
    cur[g] = plan;
    while (*plan == 'c' || *plan == 'x') plan++;
    if (*plan) plan++;
  }
  int kc = 0, kx = 0;
  for (;;) {
    int b = -1, bt = 0;
    for (int g = 0; g < 8; g++) {
      const int t = tend[g] + (*cur[g] == 'x' ? 94 : 85);
      if ((*cur[g] == 'c' || *cur[g] == 'x') && (b < 0 || t < bt || (TIE && t == bt))) { b = g; bt = t; }
    }
    if (b < 0) break;
    const int a = kx - XA;
    for (int mp = 0; mp < 8; mp++) {
      if (*cur[b] == 'c') add(b * 8 + mp, 4, 0, mp, kc & 1, (kc >> 1) * 4);
      else if (a >= 0 && a < 7) add(b * 8 + mp, a == 0 ? 3 : 4, 1, mp, 2, a == 0 ? 24 : (a - 1) * 4);
      else add(b * 8 + mp, 4, 1, mp, 3, (a < 0 ? kx : kx - 7) * 4);
    }
    if (*cur[b] == 'c') kc++; else kx++;
    cur[b]++;
    tend[b] = bt;
  }
  for (int mp = 0; mp < 8; mp++) add(64 + mp / 4, 4, 1, mp, 3, 15 * 4);
  for (int cc = 0; cc < NCLUSTER; cc++)
    for (int i = 0; i < cnt[cc]; i++) {
      const int key = p.jobs[cc][i] & 0x3C;
      if (i == 0 || (p.jobs[cc][i - 1] & 0x3C) != key) p.jobs[cc][i] |= (1 << 14);
      if (i == cnt[cc] - 1 || (p.jobs[cc][i + 1] & 0x3C) != key) p.jobs[cc][i] |= (1 << 15);
    }
}

static void build_k2_items(Params& p) {
  int n = 0;
  const int SCHED_N1 = g_sched[8], SCHED_N2 = g_sched[9];
  int N0 = 2, J0 = 2;
  for (int j = 7; j >= J0; j--)
    for (int h = 0; h < N0; h++) p.order[n++] = (uint8_t)(h * 8 + j);
  for (int j = 7; j >= 0; j--)
    for (int h = 0; h < SCHED_N1; h++)
      if (!(h < N0 && j >= J0)) p.order[n++] = (uint8_t)(h * 8 + j);
  for (int j = 7; j >= 4; j--)
    for (int h = SCHED_N1; h < SCHED_N2; h++) p.order[n++] = (uint8_t)(h * 8 + j);
  for (int j = 7; j >= 0; j--)
    for (int h = SCHED_N1; h < 32; h++)
      if (!(h < SCHED_N2 && j >= 4)) p.order[n++] = (uint8_t)(h * 8 + j);
  int TJ[2] = {0, 0}, TP = 0;
  for (int t = 0; t < 2; t++) {
    if (!TJ[t]) continue;
    int i = 0;
    while (p.order[i] != 31 * 8 + TJ[t]) i++;
    for (; i < 255 - TP; i++) p.order[i] = p.order[i + 1];
    p.order[i] = (uint8_t)(31 * 8 + TJ[t]);
  }
}

static void build_k3_units(Params& p) {
  int um = 0;
  for (int u = 0; u < 66; u++) {
    int t = (u % 28 < 14) ? u % 28 : 27 - u % 28, i = u / 14;
    if (um == 1) t = u % 14;
    if (um == 2) { t = (u % 28) / 2; i = (u / 28) * 2 + (u & 1); }
    if (um == 3) { t = u / 4; i = u & 3; }
    if (um == 4) { t = (u < 42) ? u / 3 : u - 42; i = (u < 42) ? u % 3 : 3; }
    if (u >= 56) { t = 14 + ((0x199 >> (u - 56)) & 1); i = (u - 56) / 2; }
    uint8_t* w = p.unit[u];
    w[0] = (uint8_t)t; w[1] = (uint8_t)i; w[2] = (uint8_t)(i * K3_NS); w[3] = (uint8_t)(((u >= 56) ? 5 : 4) * K3_NS);
  }
}

extern "C" void kernel_launch(void* const* d_in, const int* in_sizes, int n_in, void* d_out, int out_size) {
  const bf16* x = (const bf16*)d_in[0];
  const bf16* wqkv = (const bf16*)d_in[1];
  const bf16* wo = (const bf16*)d_in[2];
  const bf16* ckv = (const bf16*)d_in[4];
  const bf16* w_q = (const bf16*)d_in[5];
  const bf16* w_uk = (const bf16*)d_in[6];
  const bf16* w_uv = (const bf16*)d_in[7];
  const bf16* w_o = (const bf16*)d_in[8];
  const bf16* gate_w = (const bf16*)d_in[9];

  EncFn enc = nullptr;
  cudaDriverEntryPointQueryResult qr;
  cudaGetDriverEntryPoint("cuTensorMapEncodeTiled", (void**)&enc, cudaEnableDefault, &qr);
  void *pK, *pV, *pCtx, *pQA;
  cudaGetSymbolAddress(&pQA, g_QKVA);
  cudaGetSymbolAddress(&pK, g_K);
  cudaGetSymbolAddress(&pV, g_V);
  cudaGetSymbolAddress(&pCtx, g_ctx);

  static Params p;
  enc2d(enc, &p.tmA[0], ckv, DC, S_LEN, 64, 128);
  enc2d(enc, &p.tmA[1], x, DM, S_LEN, 64, 128);
  enc3d(enc, &p.tmW[0], w_uk, HDIM, DC, 16, 4);
  enc3d(enc, &p.tmW[1], w_uv, HDIM, DC, 16, 4);
  enc3d(enc, &p.tmW[2], wqkv, NQKVA, DM, 16, 4);
  enc3d(enc, &p.tmW[3], w_q, HDIM, DM, 16, 4);
  build_k1_jobs(p);
  enc2d(enc, &p.tmK, pK, HDIM, S_LEN, 64, 128);
  enc2d(enc, &p.tmV, pV, HDIM, S_LEN, 64, 128);
  build_k2_items(p);
  build_k3_units(p);
  for (int i = 0; i < 3; i++) {
    const cuuint64_t ld = (i < 2 ? NQKVA : KCAT) * 2, nch = (i < 2) ? 27 : 9;
    cuuint64_t gd[4] = {64, S_LEN / 2, i ? 2 : nch, i ? nch : 2}, gs[3] = {2 * ld, i ? ld : 128, i ? 128 : ld};
    cuuint32_t bx[4] = {64, i ? 8u : 16u, i ? 2u : 9u, i ? 9u : 2u}, es[4] = {1, 1, 1, 1};
    enc(&p.tmL[i], CU_TENSOR_MAP_DATA_TYPE_BFLOAT16, 4, (i < 2) ? pQA : (void*)((bf16*)pCtx + HDIM), gd, gs, bx, es, CU_TENSOR_MAP_INTERLEAVE_NONE,
        CU_TENSOR_MAP_SWIZZLE_128B, CU_TENSOR_MAP_L2_PROMOTION_L2_256B, CU_TENSOR_MAP_FLOAT_OOB_FILL_NONE);
  }
  enc2d(enc, &p.tmC, pCtx, KCAT, S_LEN, 64, 128);
  enc3d(enc, &p.tmO[0], w_o, DM, HDIM, 32, 4);
  enc3d(enc, &p.tmO[1], wo, DM, DM, 32, 4);
  enc2d(enc, &p.tmOt[0], w_o, DM, HDIM, 32, 32, CU_TENSOR_MAP_SWIZZLE_64B);
  enc2d(enc, &p.tmOt[1], wo, DM, DM, 32, 32, CU_TENSOR_MAP_SWIZZLE_64B);
  enc2d(enc, &p.tmR[0], d_out, DM, S_LEN, 64, 16);
  enc2d(enc, &p.tmR[1], d_out, DM, S_LEN, 32, 16, CU_TENSOR_MAP_SWIZZLE_64B);

  cudaFuncSetAttribute(fused_kernel, cudaFuncAttributeMaxDynamicSharedMemorySize, SMEM_BYTES);
  fused_kernel<<<NCLUSTER * 2, 384, SMEM_BYTES>>>(p, x, gate_w, (bf16*)d_out);
}
```

```cpp
#include <cuda_runtime.h>
#include <cuda_bf16.h>
#include <cuda.h>
#include <stdint.h>

typedef __nv_bfloat16 bf16;

constexpr int S_LEN = 2048, DM = 576, DC = 512, HDIM = 4096, NQKVA = 1728, KCAT = 4672;
constexpr int NCLUSTER = 66;

__device__ __align__(1024) bf16 g_K[S_LEN * HDIM];
__device__ __align__(1024) bf16 g_V[S_LEN * HDIM];
__device__ __align__(1024) bf16 g_QKVA[S_LEN * NQKVA + 64];
__device__ __align__(1024) bf16 g_ctx[S_LEN * KCAT];
__device__ float g_gate[S_LEN];
__device__ __align__(16) unsigned int g_sync[400];
constexpr int F_QKVA = 0, F_HP = 16, F_CTX = 32, F_OA = 48, F_CLM = 64, F_GATE = 96, F_TICK = 97, F_DONE = 98, F_XCH = 128, F_EPOCH = 384;

__device__ __forceinline__ uint32_t smem_u32(const void* p) { return (uint32_t)__cvta_generic_to_shared(p); }
__device__ __forceinline__ void mbar_init(uint32_t a, uint32_t c) {
  asm volatile("mbarrier.init.shared::cta.b64 [%0], %1;" ::"r"(a), "r"(c));
}
__device__ __forceinline__ void mbar_expect(uint32_t a, uint32_t b) {
  asm volatile("mbarrier.arrive.expect_tx.shared::cta.b64 _, [%0], %1;" ::"r"(a), "r"(b) : "memory");
}
#define TS(k, i)
#define TSC(k, i)
#define TSM(k)
#define BSEG(i)
#define TB(k)
#define TRC(fl)
#define TCK(i)
#define SPIN_LIMIT "4194304"
__device__ __forceinline__ void mbar_wait(uint32_t a, uint32_t parity) {
  asm volatile(
      "{\n.reg .pred p;\n.reg .u32 n;\n"
      "mbarrier.try_wait.parity.shared::cta.b64 p, [%0], %1;\n"
      "@p bra DONE;\n"
      "mov.u32 n, 0;\n"
      "LOOP:\n"
      "mbarrier.try_wait.parity.shared::cta.b64 p, [%0], %1;\n"
      "@p bra DONE;\n"
      "add.u32 n, n, 1;\n"
      "setp.lt.u32 p, n, " SPIN_LIMIT ";\n"
      "@p bra LOOP;\n"
      "DONE:\n}" ::"r"(a), "r"(parity) : "memory");
}
template <int NS>
__device__ __forceinline__ void mbar_wait_ns(uint32_t a, uint32_t parity) {
  asm volatile(
      "{\n.reg .pred p;\n.reg .u32 n;\n"
      "mov.u32 n, 0;\n"
      "LOOP:\n"
      "mbarrier.try_wait.parity.shared::cta.b64 p, [%0], %1, %2;\n"
      "@p bra DONE;\n"
      "add.u32 n, n, 1;\n"
      "setp.lt.u32 p, n, " SPIN_LIMIT ";\n"
      "@p bra LOOP;\n"
      "DONE:\n}" ::"r"(a), "r"(parity), "n"(NS) : "memory");
}
__device__ __forceinline__ void mbar_wait2(uint32_t a, uint32_t pa, uint32_t b, uint32_t pb) {
  asm volatile(
      "{\n.reg .pred p, q;\n.reg .u32 n;\n"
      "mov.u32 n, 0;\n"
      "LOOP:\n"
      "mbarrier.try_wait.parity.shared::cta.b64 p, [%0], %1;\n"
      "mbarrier.try_wait.parity.shared::cta.b64 q, [%2], %3;\n"
      "add.u32 n, n, 1;\n"
      "and.pred p, p, q;\n"
      "setp.lt.and.u32 p, n, " SPIN_LIMIT ", !p;\n"
      "@p bra LOOP;\n"
      "}" ::"r"(a), "r"(pa), "r"(b), "r"(pb) : "memory");
}
__device__ __forceinline__ uint32_t mbar_test(uint32_t a, uint32_t parity) {
  uint32_t r;
  asm volatile("{\n.reg .pred p;\nmbarrier.test_wait.parity.shared::cta.b64 p, [%1], %2;\nselp.u32 %0, 1, 0, p;\n}" : "=r"(r) : "r"(a), "r"(parity) : "memory");
  return r;
}
__device__ __forceinline__ void mbar_arrive(uint32_t a) {
  asm volatile("mbarrier.arrive.shared::cta.b64 _, [%0];" ::"r"(a) : "memory");
}
__device__ __forceinline__ void mbar_arrive_cluster(uint32_t a, uint32_t cta) {
  asm volatile("{\n.reg .b32 r;\nmapa.shared::cluster.u32 r, %0, %1;\nmbarrier.arrive.shared::cluster.b64 _, [r];\n}" ::"r"(a),
               "r"(cta) : "memory");
}
__device__ __forceinline__ void mbar_arrive_cluster_if(uint32_t a, uint32_t cta, bool pred) {
  asm volatile("{\n.reg .b32 r;\n.reg .pred p;\nsetp.ne.u32 p, %2, 0;\nmapa.shared::cluster.u32 r, %0, %1;\n@p mbarrier.arrive.shared::cluster.b64 _, [r];\n}" ::"r"(a),
               "r"(cta), "r"((uint32_t)pred) : "memory");
}
__device__ __forceinline__ void anchor(float v, uint32_t pred) {
  asm volatile("{\n.reg .pred p;\nsetp.ne.u32 p, %1, 0;\n@p st.shared.f32 [%1], %0;\n}" ::"f"(v), "r"(pred) : "memory");
}
__device__ __forceinline__ void mbar_arrive_if(uint32_t a, bool pred) {
  asm volatile("{\n.reg .pred p;\nsetp.ne.u32 p, %1, 0;\n@p mbarrier.arrive.shared::cta.b64 _, [%0];\n}" ::"r"(a), "r"((uint32_t)pred) : "memory");
}
__device__ __forceinline__ void tma2d(uint32_t dst, const CUtensorMap* m, uint32_t bar, int c0, int c1) {
  asm volatile("cp.async.bulk.tensor.2d.shared::cluster.global.mbarrier::complete_tx::bytes [%0], [%1, {%3, %4}], [%2];" ::"r"(dst),
               "l"(m), "r"(bar), "r"(c0), "r"(c1) : "memory");
}
__device__ __forceinline__ void tma2d_mc(uint32_t dst, const CUtensorMap* m, uint32_t bar, int c0, int c1, uint16_t mask) {
  asm volatile(
      "cp.async.bulk.tensor.2d.shared::cluster.global.mbarrier::complete_tx::bytes.multicast::cluster [%0], [%1, {%3, %4}], [%2], %5;" ::"r"(dst),
      "l"(m), "r"(bar), "r"(c0), "r"(c1), "h"(mask) : "memory");
}
__device__ __forceinline__ void tma3d_mc(uint32_t dst, const CUtensorMap* m, uint32_t bar, int c0, int c1, int c2, uint16_t mask) {
  asm volatile(
      "cp.async.bulk.tensor.3d.shared::cluster.global.mbarrier::complete_tx::bytes.multicast::cluster [%0], [%1, {%3, %4, %5}], [%2], %6;" ::"r"(dst),
      "l"(m), "r"(bar), "r"(c0), "r"(c1), "r"(c2), "h"(mask) : "memory");
}
__device__ __forceinline__ void tma3d(uint32_t dst, const CUtensorMap* m, uint32_t bar, int c0, int c1, int c2) {
  asm volatile(
      "cp.async.bulk.tensor.3d.shared::cluster.global.mbarrier::complete_tx::bytes [%0], [%1, {%3, %4, %5}], [%2];" ::"r"(dst),
      "l"(m), "r"(bar), "r"(c0), "r"(c1), "r"(c2) : "memory");
}
__device__ __forceinline__ void tma_pf2d(const CUtensorMap* m, int c0, int c1) {
  asm volatile("cp.async.bulk.prefetch.tensor.2d.L2.global [%0, {%1, %2}];" ::"l"(m), "r"(c0), "r"(c1) : "memory");
}
__device__ __forceinline__ void tma_pf3d(const CUtensorMap* m, int c0, int c1, int c2) {
  asm volatile("cp.async.bulk.prefetch.tensor.3d.L2.global [%0, {%1, %2, %3}];" ::"l"(m), "r"(c0), "r"(c1), "r"(c2) : "memory");
}
__device__ __forceinline__ void prefetch_tmap(const CUtensorMap* m) {
  asm volatile("prefetch.tensormap [%0];" ::"l"(m) : "memory");
}
__device__ __forceinline__ void cluster_arrive() { asm volatile("barrier.cluster.arrive.relaxed.aligned;" ::: "memory"); }
__device__ __forceinline__ void cluster_wait() { asm volatile("barrier.cluster.wait.aligned;" ::: "memory"); }
__device__ __forceinline__ void cluster_sync() {
  cluster_arrive();
  cluster_wait();
}
__device__ __forceinline__ uint32_t cluster_rank() {
  uint32_t r;
  asm volatile("mov.u32 %0, %%cluster_ctarank;" : "=r"(r));
  return r;
}
__device__ __forceinline__ bool elect_one() {
  uint32_t p;
  asm volatile("{\n.reg .pred q;\nelect.sync _|q, 0xffffffff;\nselp.u32 %0, 1, 0, q;\n}" : "=r"(p));
  return p;
}
__device__ __forceinline__ void ldsm_x4(uint32_t& r0, uint32_t& r1, uint32_t& r2, uint32_t& r3, uint32_t addr) {
  asm volatile("ldmatrix.sync.aligned.m8n8.x4.shared.b16 {%0, %1, %2, %3}, [%4];" : "=r"(r0), "=r"(r1), "=r"(r2), "=r"(r3) : "r"(addr) : "memory");
}
__device__ __forceinline__ void wg_fence() { asm volatile("wgmma.fence.sync.aligned;" ::: "memory"); }
__device__ __forceinline__ void wg_commit() { asm volatile("wgmma.commit_group.sync.aligned;" ::: "memory"); }
template <int N>
__device__ __forceinline__ void wg_wait() { asm volatile("wgmma.wait_group.sync.aligned %0;" ::"n"(N) : "memory"); }
template <int N>
__device__ __forceinline__ void reg_alloc() { asm volatile("setmaxnreg.inc.sync.aligned.u32 %0;" ::"n"(N)); }
template <int N>
__device__ __forceinline__ void reg_dealloc() { asm volatile("setmaxnreg.dec.sync.aligned.u32 %0;" ::"n"(N)); }
__device__ __forceinline__ void bar_sync(int id, int n) { asm volatile("bar.sync %0, %1;" ::"r"(id), "r"(n) : "memory"); }
__device__ __forceinline__ void bar_arrive(int id, int n) { asm volatile("bar.arrive %0, %1;" ::"r"(id), "r"(n) : "memory"); }
template <int NT>
__device__ __forceinline__ void fence_regs(float (&d)[NT]) {
#pragma unroll
  for (int i = 0; i < NT; i++) asm volatile("" : "+f"(d[i])::"memory");
}
template <int NT>
__device__ __forceinline__ void fence_regs(uint32_t (&d)[NT]) {
#pragma unroll
  for (int i = 0; i < NT; i++) asm volatile("" : "+r"(d[i])::"memory");
}
__device__ __forceinline__ uint64_t make_desc(uint32_t saddr, uint32_t lbo, uint32_t sbo, uint32_t layout) {
  return (uint64_t)((saddr & 0x3FFFF) >> 4) | ((uint64_t)(lbo >> 4) << 16) | ((uint64_t)(sbo >> 4) << 32) | ((uint64_t)layout << 62);
}
__device__ __forceinline__ uint32_t pack_bf16(float lo, float hi) {
  uint32_t r;
  asm("cvt.rn.bf16x2.f32 %0, %1, %2;" : "=r"(r) : "f"(hi), "f"(lo));
  return r;
}
__device__ __forceinline__ float ex2(float x) {
  float r;
  asm("ex2.approx.ftz.f32 %0, %1;" : "=f"(r) : "f"(x));
  return r;
}
__device__ __forceinline__ void st_v4(void* p, uint32_t a, uint32_t b, uint32_t c, uint32_t d) {
#define ST_MOD ".cs"
  asm volatile("st.global" ST_MOD ".v4.b32 [%0], {%1, %2, %3, %4};" ::"l"(p), "r"(a), "r"(b), "r"(c), "r"(d) : "memory");
}
#define STA_MOD ".cs"
__device__ __forceinline__ void st_v4a(void* p, uint32_t a, uint32_t b, uint32_t c, uint32_t d) {
  asm volatile("st.global" STA_MOD ".v4.b32 [%0], {%1, %2, %3, %4};" ::"l"(p), "r"(a), "r"(b), "r"(c), "r"(d) : "memory");
}
template <typename T>
__device__ __forceinline__ T* ptr_add(T* base, uint32_t bytes) {
  uint64_t r;
  asm volatile("{\n.reg .u32 l, h;\nmov.b64 {l, h}, %1;\nadd.cc.u32 l, l, %2;\naddc.u32 h, h, 0;\nmov.b64 %0, {l, h};\n}" : "=l"(r) : "l"(base), "r"(bytes));
  return reinterpret_cast<T*>(r);
}
__device__ __forceinline__ float bf_lo(uint32_t v) { return __uint_as_float(v << 16); }
__device__ __forceinline__ float bf_hi(uint32_t v) { return __uint_as_float(v & 0xFFFF0000u); }

__device__ __forceinline__ void quad_transpose(uint32_t& a0, uint32_t& a1, uint32_t& a2, uint32_t& a3, int q) {
  const bool o1 = q & 1, o2 = q & 2;
  uint32_t t0 = o1 ? a0 : a1, t1 = o1 ? a2 : a3;
  t0 = __shfl_xor_sync(0xffffffffu, t0, 1);
  t1 = __shfl_xor_sync(0xffffffffu, t1, 1);
  if (o1) { a0 = t0; a2 = t1; } else { a1 = t0; a3 = t1; }
  t0 = o2 ? a0 : a2;
  t1 = o2 ? a1 : a3;
  t0 = __shfl_xor_sync(0xffffffffu, t0, 2);
  t1 = __shfl_xor_sync(0xffffffffu, t1, 2);
  if (o2) { a0 = t0; a1 = t1; } else { a2 = t0; a3 = t1; }
}

template<int TB, int OFF, int NT>
__device__ __forceinline__ void wgmma_ss_n256(float (&d)[NT], uint64_t da, uint64_t db, int scale_d) {
  asm volatile("{\n.reg .pred p;\nsetp.ne.b32 p, %130, 0;\n"
    "wgmma.mma_async.sync.aligned.m64n256k16.f32.bf16.bf16 {%0, %1, %2, %3, %4, %5, %6, %7, %8, %9, %10, %11, %12, %13, %14, %15, %16, %17, %18, %19, %20, %21, %22, %23, %24, %25, %26, %27, %28, %29, %30, %31, %32, %33, %34, %35, %36, %37, %38, %39, %40, %41, %42, %43, %44, %45, %46, %47, %48, %49, %50, %51, %52, %53, %54, %55, %56, %57, %58, %59, %60, %61, %62, %63, %64, %65, %66, %67, %68, %69, %70, %71, %72, %73, %74, %75, %76, %77, %78, %79, %80, %81, %82, %83, %84, %85, %86, %87, %88, %89, %90, %91, %92, %93, %94, %95, %96, %97, %98, %99, %100, %101, %102, %103, %104, %105, %106, %107, %108, %109, %110, %111, %112, %113, %114, %115, %116, %117, %118, %119, %120, %121, %122, %123, %124, %125, %126, %127}, %128, %129, p, 1, 1, 0, %131;\n}\n"
    : "+f"(d[OFF+0]), "+f"(d[OFF+1]), "+f"(d[OFF+2]), "+f"(d[OFF+3]), "+f"(d[OFF+4]), "+f"(d[OFF+5]), "+f"(d[OFF+6]), "+f"(d[OFF+7]), "+f"(d[OFF+8]), "+f"(d[OFF+9]), "+f"(d[OFF+10]), "+f"(d[OFF+11]), "+f"(d[OFF+12]), "+f"(d[OFF+13]), "+f"(d[OFF+14]), "+f"(d[OFF+15]), "+f"(d[OFF+16]), "+f"(d[OFF+17]), "+f"(d[OFF+18]), "+f"(d[OFF+19]), "+f"(d[OFF+20]), "+f"(d[OFF+21]), "+f"(d[OFF+22]), "+f"(d[OFF+23]), "+f"(d[OFF+24]), "+f"(d[OFF+25]), "+f"(d[OFF+26]), "+f"(d[OFF+27]), "+f"(d[OFF+28]), "+f"(d[OFF+29]), "+f"(d[OFF+30]), "+f"(d[OFF+31]), "+f"(d[OFF+32]), "+f"(d[OFF+33]), "+f"(d[OFF+34]), "+f"(d[OFF+35]), "+f"(d[OFF+36]), "+f"(d[OFF+37]), "+f"(d[OFF+38]), "+f"(d[OFF+39]), "+f"(d[OFF+40]), "+f"(d[OFF+41]), "+f"(d[OFF+42]), "+f"(d[OFF+43]), "+f"(d[OFF+44]), "+f"(d[OFF+45]), "+f"(d[OFF+46]), "+f"(d[OFF+47]), "+f"(d[OFF+48]), "+f"(d[OFF+49]), "+f"(d[OFF+50]), "+f"(d[OFF+51]), "+f"(d[OFF+52]), "+f"(d[OFF+53]), "+f"(d[OFF+54]), "+f"(d[OFF+55]), "+f"(d[OFF+56]), "+f"(d[OFF+57]), "+f"(d[OFF+58]), "+f"(d[OFF+59]), "+f"(d[OFF+60]), "+f"(d[OFF+61]), "+f"(d[OFF+62]), "+f"(d[OFF+63]), "+f"(d[OFF+64]), "+f"(d[OFF+65]), "+f"(d[OFF+66]), "+f"(d[OFF+67]), "+f"(d[OFF+68]), "+f"(d[OFF+69]), "+f"(d[OFF+70]), "+f"(d[OFF+71]), "+f"(d[OFF+72]), "+f"(d[OFF+73]), "+f"(d[OFF+74]), "+f"(d[OFF+75]), "+f"(d[OFF+76]), "+f"(d[OFF+77]), "+f"(d[OFF+78]), "+f"(d[OFF+79]), "+f"(d[OFF+80]), "+f"(d[OFF+81]), "+f"(d[OFF+82]), "+f"(d[OFF+83]), "+f"(d[OFF+84]), "+f"(d[OFF+85]), "+f"(d[OFF+86]), "+f"(d[OFF+87]), "+f"(d[OFF+88]), "+f"(d[OFF+89]), "+f"(d[OFF+90]), "+f"(d[OFF+91]), "+f"(d[OFF+92]), "+f"(d[OFF+93]), "+f"(d[OFF+94]), "+f"(d[OFF+95]), "+f"(d[OFF+96]), "+f"(d[OFF+97]), "+f"(d[OFF+98]), "+f"(d[OFF+99]), "+f"(d[OFF+100]), "+f"(d[OFF+101]), "+f"(d[OFF+102]), "+f"(d[OFF+103]), "+f"(d[OFF+104]), "+f"(d[OFF+105]), "+f"(d[OFF+106]), "+f"(d[OFF+107]), "+f"(d[OFF+108]), "+f"(d[OFF+109]), "+f"(d[OFF+110]), "+f"(d[OFF+111]), "+f"(d[OFF+112]), "+f"(d[OFF+113]), "+f"(d[OFF+114]), "+f"(d[OFF+115]), "+f"(d[OFF+116]), "+f"(d[OFF+117]), "+f"(d[OFF+118]), "+f"(d[OFF+119]), "+f"(d[OFF+120]), "+f"(d[OFF+121]), "+f"(d[OFF+122]), "+f"(d[OFF+123]), "+f"(d[OFF+124]), "+f"(d[OFF+125]), "+f"(d[OFF+126]), "+f"(d[OFF+127])
    : "l"(da), "l"(db), "r"(scale_d), "n"(TB));
}
template<int TB, int OFF, int NT>
__device__ __forceinline__ void wgmma_ss_n32(float (&d)[NT], uint64_t da, uint64_t db, int scale_d) {
  asm volatile("{\n.reg .pred p;\nsetp.ne.b32 p, %18, 0;\n"
    "wgmma.mma_async.sync.aligned.m64n32k16.f32.bf16.bf16 {%0, %1, %2, %3, %4, %5, %6, %7, %8, %9, %10, %11, %12, %13, %14, %15}, %16, %17, p, 1, 1, 0, %19;\n}\n"
    : "+f"(d[OFF+0]), "+f"(d[OFF+1]), "+f"(d[OFF+2]), "+f"(d[OFF+3]), "+f"(d[OFF+4]), "+f"(d[OFF+5]), "+f"(d[OFF+6]), "+f"(d[OFF+7]), "+f"(d[OFF+8]), "+f"(d[OFF+9]), "+f"(d[OFF+10]), "+f"(d[OFF+11]), "+f"(d[OFF+12]), "+f"(d[OFF+13]), "+f"(d[OFF+14]), "+f"(d[OFF+15])
    : "l"(da), "l"(db), "r"(scale_d), "n"(TB));
}
template<int TB, int OFF, int NT>
__device__ __forceinline__ void wgmma_rs_n128(float (&d)[NT], uint32_t a0, uint32_t a1, uint32_t a2, uint32_t a3, uint64_t db, int scale_d) {
  asm volatile("{\n.reg .pred p;\nsetp.ne.b32 p, %69, 0;\n"
    "wgmma.mma_async.sync.aligned.m64n128k16.f32.bf16.bf16 {%0, %1, %2, %3, %4, %5, %6, %7, %8, %9, %10, %11, %12, %13, %14, %15, %16, %17, %18, %19, %20, %21, %22, %23, %24, %25, %26, %27, %28, %29, %30, %31, %32, %33, %34, %35, %36, %37, %38, %39, %40, %41, %42, %43, %44, %45, %46, %47, %48, %49, %50, %51, %52, %53, %54, %55, %56, %57, %58, %59, %60, %61, %62, %63}, {%64, %65, %66, %67}, %68, p, 1, 1, %70;\n}\n"
    : "+f"(d[OFF+0]), "+f"(d[OFF+1]), "+f"(d[OFF+2]), "+f"(d[OFF+3]), "+f"(d[OFF+4]), "+f"(d[OFF+5]), "+f"(d[OFF+6]), "+f"(d[OFF+7]), "+f"(d[OFF+8]), "+f"(d[OFF+9]), "+f"(d[OFF+10]), "+f"(d[OFF+11]), "+f"(d[OFF+12]), "+f"(d[OFF+13]), "+f"(d[OFF+14]), "+f"(d[OFF+15]), "+f"(d[OFF+16]), "+f"(d[OFF+17]), "+f"(d[OFF+18]), "+f"(d[OFF+19]), "+f"(d[OFF+20]), "+f"(d[OFF+21]), "+f"(d[OFF+22]), "+f"(d[OFF+23]), "+f"(d[OFF+24]), "+f"(d[OFF+25]), "+f"(d[OFF+26]), "+f"(d[OFF+27]), "+f"(d[OFF+28]), "+f"(d[OFF+29]), "+f"(d[OFF+30]), "+f"(d[OFF+31]), "+f"(d[OFF+32]), "+f"(d[OFF+33]), "+f"(d[OFF+34]), "+f"(d[OFF+35]), "+f"(d[OFF+36]), "+f"(d[OFF+37]), "+f"(d[OFF+38]), "+f"(d[OFF+39]), "+f"(d[OFF+40]), "+f"(d[OFF+41]), "+f"(d[OFF+42]), "+f"(d[OFF+43]), "+f"(d[OFF+44]), "+f"(d[OFF+45]), "+f"(d[OFF+46]), "+f"(d[OFF+47]), "+f"(d[OFF+48]), "+f"(d[OFF+49]), "+f"(d[OFF+50]), "+f"(d[OFF+51]), "+f"(d[OFF+52]), "+f"(d[OFF+53]), "+f"(d[OFF+54]), "+f"(d[OFF+55]), "+f"(d[OFF+56]), "+f"(d[OFF+57]), "+f"(d[OFF+58]), "+f"(d[OFF+59]), "+f"(d[OFF+60]), "+f"(d[OFF+61]), "+f"(d[OFF+62]), "+f"(d[OFF+63])
    : "r"(a0), "r"(a1), "r"(a2), "r"(a3), "l"(db), "r"(scale_d), "n"(TB));
}
template<int TB, int OFF, int NT>
__device__ __forceinline__ void wgmma_rs_n256(float (&d)[NT], uint32_t a0, uint32_t a1, uint32_t a2, uint32_t a3, uint64_t db, int scale_d) {
  asm volatile("{\n.reg .pred p;\nsetp.ne.b32 p, %133, 0;\n"
    "wgmma.mma_async.sync.aligned.m64n256k16.f32.bf16.bf16 {%0, %1, %2, %3, %4, %5, %6, %7, %8, %9, %10, %11, %12, %13, %14, %15, %16, %17, %18, %19, %20, %21, %22, %23, %24, %25, %26, %27, %28, %29, %30, %31, %32, %33, %34, %35, %36, %37, %38, %39, %40, %41, %42, %43, %44, %45, %46, %47, %48, %49, %50, %51, %52, %53, %54, %55, %56, %57, %58, %59, %60, %61, %62, %63, %64, %65, %66, %67, %68, %69, %70, %71, %72, %73, %74, %75, %76, %77, %78, %79, %80, %81, %82, %83, %84, %85, %86, %87, %88, %89, %90, %91, %92, %93, %94, %95, %96, %97, %98, %99, %100, %101, %102, %103, %104, %105, %106, %107, %108, %109, %110, %111, %112, %113, %114, %115, %116, %117, %118, %119, %120, %121, %122, %123, %124, %125, %126, %127}, {%128, %129, %130, %131}, %132, p, 1, 1, %134;\n}\n"
    : "+f"(d[OFF+0]), "+f"(d[OFF+1]), "+f"(d[OFF+2]), "+f"(d[OFF+3]), "+f"(d[OFF+4]), "+f"(d[OFF+5]), "+f"(d[OFF+6]), "+f"(d[OFF+7]), "+f"(d[OFF+8]), "+f"(d[OFF+9]), "+f"(d[OFF+10]), "+f"(d[OFF+11]), "+f"(d[OFF+12]), "+f"(d[OFF+13]), "+f"(d[OFF+14]), "+f"(d[OFF+15]), "+f"(d[OFF+16]), "+f"(d[OFF+17]), "+f"(d[OFF+18]), "+f"(d[OFF+19]), "+f"(d[OFF+20]), "+f"(d[OFF+21]), "+f"(d[OFF+22]), "+f"(d[OFF+23]), "+f"(d[OFF+24]), "+f"(d[OFF+25]), "+f"(d[OFF+26]), "+f"(d[OFF+27]), "+f"(d[OFF+28]), "+f"(d[OFF+29]), "+f"(d[OFF+30]), "+f"(d[OFF+31]), "+f"(d[OFF+32]), "+f"(d[OFF+33]), "+f"(d[OFF+34]), "+f"(d[OFF+35]), "+f"(d[OFF+36]), "+f"(d[OFF+37]), "+f"(d[OFF+38]), "+f"(d[OFF+39]), "+f"(d[OFF+40]), "+f"(d[OFF+41]), "+f"(d[OFF+42]), "+f"(d[OFF+43]), "+f"(d[OFF+44]), "+f"(d[OFF+45]), "+f"(d[OFF+46]), "+f"(d[OFF+47]), "+f"(d[OFF+48]), "+f"(d[OFF+49]), "+f"(d[OFF+50]), "+f"(d[OFF+51]), "+f"(d[OFF+52]), "+f"(d[OFF+53]), "+f"(d[OFF+54]), "+f"(d[OFF+55]), "+f"(d[OFF+56]), "+f"(d[OFF+57]), "+f"(d[OFF+58]), "+f"(d[OFF+59]), "+f"(d[OFF+60]), "+f"(d[OFF+61]), "+f"(d[OFF+62]), "+f"(d[OFF+63]), "+f"(d[OFF+64]), "+f"(d[OFF+65]), "+f"(d[OFF+66]), "+f"(d[OFF+67]), "+f"(d[OFF+68]), "+f"(d[OFF+69]), "+f"(d[OFF+70]), "+f"(d[OFF+71]), "+f"(d[OFF+72]), "+f"(d[OFF+73]), "+f"(d[OFF+74]), "+f"(d[OFF+75]), "+f"(d[OFF+76]), "+f"(d[OFF+77]), "+f"(d[OFF+78]), "+f"(d[OFF+79]), "+f"(d[OFF+80]), "+f"(d[OFF+81]), "+f"(d[OFF+82]), "+f"(d[OFF+83]), "+f"(d[OFF+84]), "+f"(d[OFF+85]), "+f"(d[OFF+86]), "+f"(d[OFF+87]), "+f"(d[OFF+88]), "+f"(d[OFF+89]), "+f"(d[OFF+90]), "+f"(d[OFF+91]), "+f"(d[OFF+92]), "+f"(d[OFF+93]), "+f"(d[OFF+94]), "+f"(d[OFF+95]), "+f"(d[OFF+96]), "+f"(d[OFF+97]), "+f"(d[OFF+98]), "+f"(d[OFF+99]), "+f"(d[OFF+100]), "+f"(d[OFF+101]), "+f"(d[OFF+102]), "+f"(d[OFF+103]), "+f"(d[OFF+104]), "+f"(d[OFF+105]), "+f"(d[OFF+106]), "+f"(d[OFF+107]), "+f"(d[OFF+108]), "+f"(d[OFF+109]), "+f"(d[OFF+110]), "+f"(d[OFF+111]), "+f"(d[OFF+112]), "+f"(d[OFF+113]), "+f"(d[OFF+114]), "+f"(d[OFF+115]), "+f"(d[OFF+116]), "+f"(d[OFF+117]), "+f"(d[OFF+118]), "+f"(d[OFF+119]), "+f"(d[OFF+120]), "+f"(d[OFF+121]), "+f"(d[OFF+122]), "+f"(d[OFF+123]), "+f"(d[OFF+124]), "+f"(d[OFF+125]), "+f"(d[OFF+126]), "+f"(d[OFF+127])
    : "r"(a0), "r"(a1), "r"(a2), "r"(a3), "l"(db), "r"(scale_d), "n"(TB));
}
template<int TB, int OFF, int NT>
__device__ __forceinline__ void wgmma_rs_n32(float (&d)[NT], uint32_t a0, uint32_t a1, uint32_t a2, uint32_t a3, uint64_t db, int scale_d) {
  asm volatile("{\n.reg .pred p;\nsetp.ne.b32 p, %21, 0;\n"
    "wgmma.mma_async.sync.aligned.m64n32k16.f32.bf16.bf16 {%0, %1, %2, %3, %4, %5, %6, %7, %8, %9, %10, %11, %12, %13, %14, %15}, {%16, %17, %18, %19}, %20, p, 1, 1, %22;\n}\n"
    : "+f"(d[OFF+0]), "+f"(d[OFF+1]), "+f"(d[OFF+2]), "+f"(d[OFF+3]), "+f"(d[OFF+4]), "+f"(d[OFF+5]), "+f"(d[OFF+6]), "+f"(d[OFF+7]), "+f"(d[OFF+8]), "+f"(d[OFF+9]), "+f"(d[OFF+10]), "+f"(d[OFF+11]), "+f"(d[OFF+12]), "+f"(d[OFF+13]), "+f"(d[OFF+14]), "+f"(d[OFF+15])
    : "r"(a0), "r"(a1), "r"(a2), "r"(a3), "l"(db), "r"(scale_d), "n"(TB));
}

__device__ __forceinline__ void wait_flag(const unsigned int* f, uint32_t target) {
  uint32_t v;
#pragma unroll 1
  for (uint32_t spins = 0; spins < (1u << 22); spins++) {
    asm volatile("ld.acquire.gpu.global.u32 %0, [%1];" : "=r"(v) : "l"(f) : "memory");
    if (v >= target) break;
    __nanosleep(100);
  }
}
__device__ __forceinline__ uint32_t lds32(uint32_t a) {
  uint32_t v;
  asm volatile("ld.shared.u32 %0, [%1];" : "=r"(v) : "r"(a) : "memory");
  return v;
}
__device__ __forceinline__ float gate_row(int row, int lane, const bf16* __restrict__ x, const bf16* __restrict__ gate_w) {
  const uint32_t* xr = reinterpret_cast<const uint32_t*>(x + (size_t)row * DM);
  const uint32_t* gw2 = reinterpret_cast<const uint32_t*>(gate_w);
  float gs = 0.f;
#pragma unroll
  for (int i = 0; i < 9; i++) {
    const uint32_t a = __ldg(xr + lane + 32 * i), b = __ldg(gw2 + lane + 32 * i);
    gs = fmaf(bf_lo(a), bf_lo(b), gs);
    gs = fmaf(bf_hi(a), bf_hi(b), gs);
  }
#pragma unroll
  for (int o = 16; o; o >>= 1) gs += __shfl_xor_sync(0xffffffffu, gs, o);
  const float g = 1.f / (1.f + __expf(-gs));
  if (lane == 0) g_gate[row] = g;
  return g;
}
constexpr uint32_t LQ = 36864, LV = 55296;
__device__ __forceinline__ void mma16(float (&c)[4], uint32_t a0, uint32_t a1, uint32_t a2, uint32_t a3, uint32_t b0, uint32_t b1) {
  asm("mma.sync.aligned.m16n8k16.row.col.f32.bf16.bf16.f32 {%0, %1, %2, %3}, {%4, %5, %6, %7}, {%8, %9}, {%0, %1, %2, %3};"
      : "+f"(c[0]), "+f"(c[1]), "+f"(c[2]), "+f"(c[3]) : "r"(a0), "r"(a1), "r"(a2), "r"(a3), "r"(b0), "r"(b1));
}
__device__ __forceinline__ void mma8(float (&c)[4], uint32_t a0, uint32_t a1, uint32_t b0) {
  asm("mma.sync.aligned.m16n8k8.row.col.f32.bf16.bf16.f32 {%0, %1, %2, %3}, {%4, %5}, {%6}, {%0, %1, %2, %3};"
      : "+f"(c[0]), "+f"(c[1]), "+f"(c[2]), "+f"(c[3]) : "r"(a0), "r"(a1), "r"(b0));
}
template <typename F>
__device__ __forceinline__ void local_attn(int lr0, int warp_g, uint32_t sL, uint32_t bL, uint32_t bL2, int lane, float g0, float g1, F st) {
  const float scale_l2 = 0.23570226039551584f * 1.4426950408889634f;
  const int g = lane >> 2, t = lane & 3;
  const bool lo0 = 2 * t > g, lo1 = 2 * t + 1 > g;
  const bool ok0 = lr0 > 0 || !lo0, ok1 = lr0 > 0 || !lo1;
  const uint32_t mlo = (lo0 ? 0xFFFFu : 0u) | (lo1 ? 0xFFFF0000u : 0u);
  uint32_t ad[9], k[9][4], qf[9][2], pe[4], po[4];
#pragma unroll
  for (int c = 0; c < 9; c++) {
    const uint32_t ch = warp_g * 9 + c;
    ad[c] = sL + (lane >> 4) * 18432 + (lane & 15) * 128 + ((ch >> 3) << 11) + (((ch ^ lane) & 7) << 4);
  }
  st(0, 0u); st(1, 0u);
  mbar_wait(bL, 0);
  if (warp_g == 0) TS(1, 6);
#pragma unroll
  for (int c = 0; c < 9; c++) {
    asm volatile("ldmatrix.sync.aligned.m8n8.x2.shared.b16 {%0, %1}, [%2];" : "=r"(qf[c][0]), "=r"(qf[c][1]) : "r"(ad[c] + LQ) : "memory");
    ldsm_x4(k[c][0], k[c][1], k[c][2], k[c][3], ad[c]);
  }
  st(2, k[0][0]); st(3, k[8][0]);
#pragma unroll
  for (int i = 0; i < 4; i++) {
    const uint32_t q0 = (t >= i) ? qf[2 * i][0] : 0u, q1 = (t >= i) ? qf[2 * i][1] : 0u;
    const uint32_t q4 = (t <= i) ? qf[2 * i + 2][0] : 0u, q5 = (t <= i) ? qf[2 * i + 2][1] : 0u;
    float c[4][4];
#pragma unroll
    for (int T = 0; T < 4; T++) {
#pragma unroll
      for (int j = 0; j < 4; j++) c[T][j] = 0.f;
      mma16(c[T], q0, q1, qf[2 * i + 1][0], qf[2 * i + 1][1], k[2 * i][T], k[2 * i + 1][T]);
      mma8(c[T], q4, q5, k[2 * i + 2][T]);
    }
    const float e0 = ok0 ? (lo0 ? c[0][0] : c[1][0]) : -INFINITY, e1 = ok1 ? (lo1 ? c[0][1] : c[1][1]) : -INFINITY;
    const float o0 = ok0 ? (lo0 ? c[2][2] : c[3][2]) : -INFINITY, o1 = ok1 ? (lo1 ? c[2][3] : c[3][3]) : -INFINITY;
    float me = fmaxf(e0, e1), mo = fmaxf(o0, o1);
    me = fmaxf(me, __shfl_xor_sync(0xffffffffu, me, 1));
    mo = fmaxf(mo, __shfl_xor_sync(0xffffffffu, mo, 1));
    me = fmaxf(me, __shfl_xor_sync(0xffffffffu, me, 2)) * scale_l2;
    mo = fmaxf(mo, __shfl_xor_sync(0xffffffffu, mo, 2)) * scale_l2;
    const float w0 = ex2(fmaf(e0, scale_l2, -me)), w1 = ex2(fmaf(e1, scale_l2, -me));
    const float w2 = ex2(fmaf(o0, scale_l2, -mo)), w3 = ex2(fmaf(o1, scale_l2, -mo));
    float se = w0 + w1, so = w2 + w3;
    st(4 + 2 * i, __float_as_uint(i == 1 ? me : i == 2 ? se : e0));
    se += __shfl_xor_sync(0xffffffffu, se, 1);
    so += __shfl_xor_sync(0xffffffffu, so, 1);
    se += __shfl_xor_sync(0xffffffffu, se, 2);
    so += __shfl_xor_sync(0xffffffffu, so, 2);
    asm("rcp.approx.ftz.f32 %0, %0;" : "+f"(se));
    asm("rcp.approx.ftz.f32 %0, %0;" : "+f"(so));
    se *= g0;
    so *= g1;
    pe[i] = pack_bf16(w0 * se, w1 * se);
    po[i] = pack_bf16(w2 * so, w3 * so);
    st(5 + 2 * i, i == 0 ? __float_as_uint(w0) : i == 2 ? __float_as_uint(mo) : po[i]);
  }
  if (warp_g == 0) TS(0, 4);
  mbar_wait(bL2, 0);
  if (warp_g == 0) TS(0, 5);
#pragma unroll
  for (int c = 0; c < 9; c++)
    asm volatile("ldmatrix.sync.aligned.m8n8.x4.trans.shared.b16 {%0, %1, %2, %3}, [%4];"
                 : "=r"(k[c][0]), "=r"(k[c][1]), "=r"(k[c][2]), "=r"(k[c][3]) : "r"(ad[c] + LV) : "memory");
#pragma unroll
  for (int i = 0; i < 4; i++) {
#pragma unroll
    for (int n = 0; n < 3; n++) {
      float c[4] = {0.f, 0.f, 0.f, 0.f};
      mma16(c, pe[i] & mlo, 0u, pe[i] & ~mlo, 0u, k[2 * i + n][0], k[2 * i + n][1]);
      mma16(c, 0u, po[i] & mlo, 0u, po[i] & ~mlo, k[2 * i + n][2], k[2 * i + n][3]);
      const uint32_t r0 = pack_bf16(c[0], c[1]), r1 = pack_bf16(c[2], c[3]);
      const bool keep = (n == 0) && (i > 0) && (t < i);
      qf[2 * i + n][0] = keep ? qf[2 * i + n][0] : r0;
      qf[2 * i + n][1] = keep ? qf[2 * i + n][1] : r1;
    }
    st(12 + i, qf[2 * i + 1][0]);
  }
#pragma unroll
  for (int c = 0; c < 9; c++)
    asm volatile("stmatrix.sync.aligned.m8n8.x2.shared.b16 [%0], {%1, %2};" ::"r"(ad[c] + LQ), "r"(qf[c][0]), "r"(qf[c][1]) : "memory");
  asm volatile("fence.proxy.async.shared::cta;" ::: "memory");
}
__device__ __forceinline__ void tma4d(uint32_t dst, const CUtensorMap* m, uint32_t bar, int c1, int c2, int c3) {
  asm volatile("cp.async.bulk.tensor.4d.shared::cluster.global.mbarrier::complete_tx::bytes [%0], [%1, {%3, %4, %5, %6}], [%2];" ::"r"(dst),
               "l"(m), "r"(bar), "r"(0), "r"(c1), "r"(c2), "r"(c3) : "memory");
}

#define ST_NUM 1
#define ST_DEN 2
#define K1_NST 6
constexpr int K1_BST = K1_NST;
#define MAXJ 11
constexpr int K1_MAXJOBS = MAXJ;
constexpr uint32_t K1_FLAG_TARGET = 7;
constexpr uint32_t RDY_TARGET = 48;
constexpr uint32_t GATE_TARGET = 128 * 3;
struct alignas(64) Params {
  CUtensorMap tmA[2];
  CUtensorMap tmW[4];
  CUtensorMap tmK, tmV;
  CUtensorMap tmL[3];
  CUtensorMap tmC, tmO[2], tmOt[2];
  CUtensorMap tmR[2];
  uint16_t jobs[NCLUSTER][K1_MAXJOBS + 1];
  uint8_t order[256];
  uint8_t unit[66][4];
};

struct K1State {
  uint32_t bs, bph, aph;
  bf16 *pp, *pp8;
  int png;
  int tn;
  int wsel;
  uint32_t fo;
};
__device__ __forceinline__ void k1_flag(const K1State& st, int lane, uint32_t bS) {
  if (st.png) {
    __syncwarp();
    if (lane == 0) mbar_arrive(bS + st.fo);
  }
}

__device__ __forceinline__ void scale_q4(uint32_t* v) {
#pragma unroll
  for (int i = 0; i < 4; i++)
    asm volatile("{\n.reg .b32 t;\nmul.rn.bf16x2 t, %0, %2;\nfma.rn.bf16x2 %0, %0, %1, t;\n}" : "+r"(v[i]) : "r"(0x3E033E03u), "r"(0xB9D8B9D8u));
}
__device__ __forceinline__ void k1_first(const K1State& st, uint32_t job, uint32_t bAf, uint32_t bBf) {
  if (job & 3) {
    if ((job >> 14) & 1) mbar_wait(bAf, st.aph);
    mbar_wait(bBf + st.bs * 8, st.bph);
  }
}
__device__ __forceinline__ void k1_tile(float (&acc)[128], uint32_t (&pk)[64], K1State& st, uint32_t job, uint32_t njob, uint32_t sA, uint32_t sB,
                                        uint32_t bAf, uint32_t bAe, uint32_t bBf, uint32_t bBe, uint32_t bS, int wg, int warp, int lane, uint32_t rank) {
  const int a_sel = (job >> 2) & 1, mpair = (job >> 3) & 7, w_sel = (job >> 6) & 3, chunk0 = (job >> 8) & 63;
  const bool newA = (job >> 14) & 1, lastA = (job >> 15) & 1;
  const bool sig = (lane == 0) && (warp < 2);
  const bool siga = lastA && (lane == 0) && (warp == 2);
  const int KC = 8 + a_sel;
  uint32_t prev_bs = 0, a8_bs = 0;
#pragma unroll
  for (int kc = 0; kc < 9; kc++) {
    if (kc >= KC) break;
    uint32_t abase = sA + ((kc + 2) & 7) * 16384;
    if (kc == 8) {
      mbar_wait(bBf + st.bs * 8, st.bph);
      a8_bs = st.bs;
      abase = sB + st.bs * 16384;
      if (++st.bs == K1_BST) { st.bs = 0; st.bph ^= 1; }
    } else if (newA && kc > 0) {
      mbar_wait(bAf + kc * 8, st.aph);
    }
    const uint64_t da = make_desc(abase + wg * 8192, 16, 1024, 1);
#pragma unroll
    for (int ks = 0; ks < 2; ks++) {
      if (ks > 0 || kc > 0) mbar_wait(bBf + st.bs * 8, st.bph);
      const uint64_t db = make_desc(sB + st.bs * 16384, 2048, 1024, 1);
      wg_fence();
      wgmma_ss_n256<1, 0>(acc, da + (uint64_t)(ks * 4), db, (ks > 0) ? 1 : (kc > 0));
      wgmma_ss_n256<1, 0>(acc, da + (uint64_t)(ks * 4 + 2), db + (uint64_t)512, 1);
      wg_commit();
      wg_wait<1>();
      if (ks > 0 || kc > 0) {
        if (sig) mbar_arrive_cluster(bBe + prev_bs * 8, warp);
        if (ks == 0 && siga) mbar_arrive(bAe + (kc - 1) * 8);
      }
      if (st.wsel == 2) {
        const int i = (kc & 7) * 2 + ks;
        if (kc < st.png) {
          quad_transpose(pk[i * 4], pk[i * 4 + 1], pk[i * 4 + 2], pk[i * 4 + 3], lane & 3);
          st_v4a((ks ? st.pp8 : st.pp) + kc * 32, pk[i * 4], pk[i * 4 + 1], pk[i * 4 + 2], pk[i * 4 + 3]);
        }
        if (i == 15) k1_flag(st, lane, bS);
      } else if (st.png) {
#pragma unroll
        for (int i = 0; i < 16; i++) {
          if (i * ST_NUM / ST_DEN != kc * 2 + ks) continue;
          if (st.wsel == 3) scale_q4(pk + i * 4);
          st_v4a(((i & 1) ? st.pp8 : st.pp) + (i / 2) * 32, pk[i * 4], pk[i * 4 + 1], pk[i * 4 + 2], pk[i * 4 + 3]);
          if (i == 15) k1_flag(st, lane, bS);
        }
      }
      prev_bs = st.bs;
      if (++st.bs == K1_BST) { st.bs = 0; st.bph ^= 1; }
    }
  }
  if (newA) st.aph ^= 1;
  const bool isA = (w_sel == 2);
  bf16* out = (w_sel == 0) ? g_K : (w_sel == 1) ? g_V : isA ? g_QKVA : g_ctx;
  const int ld = isA ? NQKVA : (w_sel == 3) ? KCAT : HDIM;
  const int row = mpair * 256 + rank * 128 + wg * 64 + warp * 16 + (lane >> 2);
  st.pp = ptr_add(out, (row * ld + chunk0 * 64 + (lane & 3) * 8) * 2);
  st.pp8 = ptr_add(st.pp, 16 * ld);
  st.png = ((job & 3) + 1) * 2;
  st.wsel = w_sel;
  st.fo = (st.fo + 8) & 24;
  k1_first(st, njob, bAf, bBf);
  wg_wait<0>();
  fence_regs(acc);
  mbar_arrive_cluster_if(bBe + prev_bs * 8, warp & 1, sig);
  mbar_arrive_cluster_if(bBe + a8_bs * 8, warp & 1, sig && a_sel);
  mbar_arrive_if(bAe + 7 * 8, siga && !a_sel);
#pragma unroll
  for (int i = 0; i < 64; i++) {
    const int j = (i >> 3) * 16 + (i & 3) * 4 + ((i >> 2) & 1) * 2;
    pk[i] = pack_bf16(acc[j], acc[j + 1]);
  }
}

constexpr int K2_NST = 7;
constexpr uint32_t K2_END = 0x100;
#define PFD 4
#define PF3A 2
#define PF3 6
#define KC0 1
#define PFC 0
#define CORD 1
#define FIRST_DRAW 3
#define PWAIT mbar_wait_ns<1000>
#define PVM 0x8A
#define W0 63
#define SPEC_HI 1.8446744073709552e19f
#define SPEC_LO 5.421010862427522e-20f
constexpr int K3_NST = 4;
#define K3_NS 6
__device__ __forceinline__ uint32_t k3_rot(uint32_t sv) { return (0x00E9u >> (2 * sv)) & 3; }
constexpr int K3_STAGE = 16384 + 32768 + 4096;
constexpr int SMEM_DATA = 7 * 32768;
constexpr int SMEM_BYTES = SMEM_DATA + 1024 + 896;

struct Cursor {
  uint32_t s, ph;
  __device__ __forceinline__ void next() {
    if (++s == K2_NST) { s = 0; ph ^= 1; }
  }
};

#define TURN_SYNC() bar_sync(mybar, 256)
#define TURN_ARRIVE() bar_arrive(otherbar, 256)
#define RELEASE_IF(cur, cond) mbar_arrive_cluster_if(bE + (cur).s * 8, warp & 1, sig && (cond))
#define RELEASE(cur) RELEASE_IF(cur, true)
#define ISSUE_PV(cur, first)                                                                                   \
  do {                                                                                                         \
    const uint64_t dv = make_desc(sbase + (cur).s * 32768, 16384, 1024, 1);                                    \
    _Pragma("unroll") for (int t = 0; t < 8; t++)                                                              \
        wgmma_rs_n128<1, 0>(O, P[4 * t], P[4 * t + 1], P[4 * t + 2], P[4 * t + 3], dv + (uint64_t)(t * 128), (t > 0) ? 1 : !(first)); \
  } while (0)
#define ISSUE_QK(cur)                                                                                          \
  do {                                                                                                         \
    const uint64_t dk = make_desc(sbase + (cur).s * 32768, 16, 1024, 1);                                       \
    _Pragma("unroll") for (int t = 0; t < 8; t++)                                                              \
        wgmma_rs_n128<0, 0>(S, Q[4 * t], Q[4 * t + 1], Q[4 * t + 2], Q[4 * t + 3], dk + (uint64_t)((t >> 2) * 1024 + (t & 3) * 2), t > 0); \
  } while (0)
#define LOAD_Q()                                                                                               \
  do {                                                                                                         \
    item = lds32(sItem + (it & 7) * 4);                                                                        \
    const uint32_t qa = sbase + cq.s * 32768 + (wg * 64 + warp * 16 + (lane & 15)) * 128;                      \
    _Pragma("unroll") for (int t = 0; t < 8; t++)                                                              \
        ldsm_x4(Q[4 * t], Q[4 * t + 1], Q[4 * t + 2], Q[4 * t + 3], qa + (t >> 2) * 16384 + ((((t & 3) * 2 + (lane >> 4)) ^ (lane & 7)) << 4)); \
  } while (0)
#define NEW_ITEM()                                                                                             \
  do {                                                                                                         \
    const int row = (2 * (item & 7) + hi) * 128 + wg * 64 + warp * 16 + (lane >> 2);                           \
    eoff = (row * KCAT + (item >> 3) * 128 + q * 8) * 2;                                                       \
    const float* gp = ptr_add(g_gate, row * 4);                                                                \
    asm volatile("ld.global.f32 %0, [%1];" : "=f"(gf0) : "l"(gp));                                             \
    asm volatile("ld.global.f32 %0, [%1];" : "=f"(gf1) : "l"(gp + 8));                                         \
    if (!hi) {                                                                                                 \
      mbar_wait2(bF + cs0.s * 8, cs0.ph, bF + cs1.s * 8, cs1.ph);                                              \
      RELEASE(cs0);                                                                                            \
      RELEASE(cs1);                                                                                            \
    }                                                                                                          \
  } while (0)
#define EXPB(T)                                                                                                \
  do {                                                                                                         \
    _Pragma("unroll") for (int i = 4 * T; i < 4 * T + 4; i++) asm volatile("" : "+r"(P[i])::"memory");        \
    _Pragma("unroll") for (int jj = 2 * T; jj < 2 * T + 2; jj++) {                                             \
      const float e0 = ex2(S[jj * 4 + 0]), e1 = ex2(S[jj * 4 + 1]), e2 = ex2(S[jj * 4 + 2]), e3 = ex2(S[jj * 4 + 3]); \
      s0 += e0 + e1;                                                                                           \
      s1 += e2 + e3;                                                                                           \
      P[jj * 2 + 0] = pack_bf16(e0, e1);                                                                       \
      P[jj * 2 + 1] = pack_bf16(e2, e3);                                                                       \
    }                                                                                                          \
  } while (0)
#define EXPC(T)                                                                                                \
  do {                                                                                                         \
    if (T > 0 && ((PVM >> (T - 1)) & 1)) {                                                                     \
      anchor((T & 2) ? s0 : s1, never);                                                                        \
      wg_wait<__builtin_popcount(PVM >> T) - 1>();                                                             \
      if ((PVM >> T) == (128 >> T)) { fence_regs(O); RELEASE(cv); }                                            \
    }                                                                                                          \
    EXPB(T);                                                                                                   \
  } while (0)
#define MASK(G, g)                                                                                             \
  do {                                                                                                         \
    if ((g) * 8 > d) S[(G) * 4 + 0] = -INFINITY;                                                               \
    if ((g) * 8 + 1 > d) S[(G) * 4 + 1] = -INFINITY;                                                           \
    if ((g) * 8 - 8 > d) S[(G) * 4 + 2] = -INFINITY;                                                           \
    if ((g) * 8 - 7 > d) S[(G) * 4 + 3] = -INFINITY;                                                           \
  } while (0)
#define STORE_O(G)                                                                                             \
  do {                                                                                                         \
    st_v4(optr + (G) * 32, pack_bf16(O[(G) * 16 + 0] * f0, O[(G) * 16 + 1] * f0), pack_bf16(O[(G) * 16 + 4] * f0, O[(G) * 16 + 5] * f0), \
          pack_bf16(O[(G) * 16 + 8] * f0, O[(G) * 16 + 9] * f0), pack_bf16(O[(G) * 16 + 12] * f0, O[(G) * 16 + 13] * f0)); \
    st_v4(optr + 8 * KCAT + (G) * 32, pack_bf16(O[(G) * 16 + 2] * f1, O[(G) * 16 + 3] * f1), pack_bf16(O[(G) * 16 + 6] * f1, O[(G) * 16 + 7] * f1), \
          pack_bf16(O[(G) * 16 + 10] * f1, O[(G) * 16 + 11] * f1), pack_bf16(O[(G) * 16 + 14] * f1, O[(G) * 16 + 15] * f1)); \
  } while (0)

#define FLUSH()                                                                                                \
  do {                                                                                                         \
    _Pragma("unroll") for (int G = 0; G < 8; G++) {                                                            \
      st_v4a(st.pp + G * 32, pk[G * 8], pk[G * 8 + 1], pk[G * 8 + 2], pk[G * 8 + 3]);                          \
      st_v4a(st.pp8 + G * 32, pk[G * 8 + 4], pk[G * 8 + 5], pk[G * 8 + 6], pk[G * 8 + 7]);                     \
    }                                                                                                          \
    k1_flag(st, lane, bS);                                                                                     \
  } while (0)

__global__ void __cluster_dims__(2, 1, 1) __launch_bounds__(384, 1)
fused_kernel(const __grid_constant__ Params p, const bf16* __restrict__ x, const bf16* __restrict__ gate_w, bf16* __restrict__ out) {
  extern __shared__ uint8_t smem_raw[];
  const uint32_t sbase = (smem_u32(smem_raw) + 1023) & ~1023u;
  const uint32_t sB = sbase, sA = sbase + K1_BST * 16384, sBar = sbase + SMEM_DATA;
  const uint32_t bAf = sBar, bAe = sBar + 64, bBf = sBar + 128, bBe = sBar + 176, bL = sBar + 224, bS = sBar + 656, bL2 = sBar + 240, sL = sA + 32768;
  const uint32_t bF = sBar + 256, bE = sBar + 320, bT = sBar + 384, sTick = sBar + 400, sItem = sBar + 416, bS2 = sBar + 688, bR = sBar + 456, bLast = sBar + 464, bH = sBar + 472, bT0 = sBar + 480, bZ = sBar + 488, bLd = sBar + 496;
  const uint32_t b3F = sBar + 512, b3E = sBar + 544, sGate = sBar + 576, sK1 = sBar + 720, sClm = sBar + 768;
  const int tid = threadIdx.x, warp_g = __shfl_sync(0xffffffffu, tid >> 5, 0), lane = tid & 31;
  const uint32_t rank = cluster_rank();
  const int cl = blockIdx.x >> 1;
  TSM(0);
  if (tid == 256) {
    const uint32_t job = p.jobs[cl][0];
#pragma unroll
    for (int i = 0; i < KC0; i++) { mbar_init(bAf + i * 8, 1); mbar_init(bBf + i * 16, 1); mbar_init(bBf + i * 16 + 8, 1); }
    asm volatile("fence.mbarrier_init.release.cluster;" ::: "memory");
#pragma unroll 1
    for (int i = 0; i < 4 * KC0; i++) {
      if (!(i & 3)) {
        mbar_expect(bAf + i * 2, 16384);
        tma2d(sA + (i / 4 + 2) * 16384, &p.tmA[(job >> 2) & 1], bAf + i * 2, i * 16, ((job >> 3) & 7) * 256 + rank * 128);
      }
      if (!(i & 1)) mbar_expect(bBf + i * 4, 16384);
      tma3d(sB + i * 8192, &p.tmW[(job >> 6) & 3], bBf + (i >> 1) * 8, 0, i * 16, (job >> 8) & 63);
    }
  }
  if (warp_g == 1) asm volatile("st.shared.u32 [%0], %1;" ::"r"(lane ? sClm - 4 + lane * 4 : sK1), "r"(lane ? 0xFFFFFFFFu : 80u) : "memory");
  if (tid == 0) {
    for (int i = 0; i < 8; i++) { if (i >= KC0) mbar_init(bAf + i * 8, 1); mbar_init(bAe + i * 8, 2); }
    for (int i = 0; i < K1_BST; i++) { if (i >= 2 * KC0) mbar_init(bBf + i * 8, 1); mbar_init(bBe + i * 8, 4); }
    mbar_init(bL, 1);
    mbar_init(bL2, 1);
    mbar_init(bR, 1);
    mbar_init(bLast, 1);
    mbar_init(bH, 4);
    mbar_init(bT0, 1);
    mbar_init(bZ, 1);
    mbar_init(bLd, 4);
    for (int i = 0; i < 8; i++) mbar_init(bS + i * 8, 8);
    for (int i = 0; i < K2_NST; i++) { mbar_init(bF + i * 8, 1); mbar_init(bE + i * 8, 4); }
    mbar_init(bT, 1); mbar_init(bT + 8, 1);
    for (int i = 0; i < K3_NST; i++) { mbar_init(b3F + i * 8, 1); mbar_init(b3E + i * 8, 4); }
    asm volatile("fence.mbarrier_init.release.cluster;" ::: "memory");
  }
  __syncwarp();
  if (warp_g != 8) cluster_sync();
  const int lr0 = blockIdx.x * 16;

  if (warp_g >= 8) {
    reg_dealloc<40>();
    if (warp_g == 8) {
      {
        __syncwarp();
        cluster_sync();
      }
      if (elect_one()) {
        uint32_t bs = (2 * KC0) % K1_BST, bph = (2 * KC0 < K1_BST), aph = 1;
#pragma unroll 1
        for (int ji = 0; ji < K1_MAXJOBS; ji++) {
          const uint32_t job = p.jobs[cl][ji];
          if (!(job & 3)) break;
          const int a_sel = (job >> 2) & 1, mpair = (job >> 3) & 7, chunk0 = (job >> 8) & 63;
          const bool newA = (job >> 14) & 1;
          const int KC = a_sel ? 9 : 8;
          const uint32_t halfbytes = 8192;
          const bool lastjob = (ji + 1 == K1_MAXJOBS) || !(p.jobs[cl][ji + 1] & 3);
          const CUtensorMap* tw = &p.tmW[(job >> 6) & 3];
          {
            const uint32_t njob = (ji + 1 < K1_MAXJOBS) ? p.jobs[cl][ji + 1] : 0;
            if (!(njob & 3) && !newA) mbar_arrive(bLast);
          }
#pragma unroll 1
          for (int kc = ji ? 0 : KC0; kc < KC; kc++) {
            {
              const bool nx = kc + PFD >= KC;
              const uint32_t njob = nx ? p.jobs[cl][ji + 1] : job;
              const int pk = nx ? kc + PFD - KC : kc + PFD;
              if ((njob & 3) && (nx || ji > 0)) {
                if (cl >= 64 || ((pk ^ (cl >> 1)) & 3) == 0)
                  tma_pf3d(&p.tmW[(njob >> 6) & 3], 0, pk * 64 + (cl & 1) * 32 + rank * 16, (njob >> 8) & 63);
                if (((njob >> 14) & 1) || pk == 8) tma_pf2d(&p.tmA[(njob >> 2) & 1], pk * 64, ((njob >> 3) & 7) * 256 + rank * 128);
              }
            }
            if (kc == 8) {
              PWAIT(bBe + bs * 8, bph);
              mbar_expect(bBf + bs * 8, 16384);
              tma2d(sB + bs * 16384, &p.tmA[1], bBf + bs * 8, 512, mpair * 256 + rank * 128);
              if (++bs == K1_BST) { bs = 0; bph ^= 1; }
            } else if (newA) {
              PWAIT(bAe + kc * 8, aph);
              mbar_expect(bAf + kc * 8, 16384);
              tma2d(sA + ((kc + 2) & 7) * 16384, &p.tmA[a_sel], bAf + kc * 8, kc * 64, mpair * 256 + rank * 128);
              if (kc == 7 && lastjob) mbar_arrive(bLast);
            }
#pragma unroll 1
            for (int kk = 0; kk < 2; kk++) {
              PWAIT(bBe + bs * 8, bph);
              mbar_expect(bBf + bs * 8, 2 * halfbytes);
              tma3d_mc(sB + bs * 16384 + rank * halfbytes, tw, bBf + bs * 8, 0, kc * 64 + kk * 32 + rank * 16, chunk0, 3);
              if (++bs == K1_BST) { bs = 0; bph ^= 1; }
            }
          }
          if (newA) aph ^= 1;
        }
        Cursor c{0, 0};
        int pcol = 0;
        PWAIT(bR, 0);
        uint32_t tick = lds32(sTick + 8), seen = 1u << (p.order[tick] >> 4);
        asm volatile("fence.proxy.async.global;" ::: "memory");
#pragma unroll 1
        for (int it = 0;; it++) {
          const uint32_t item = (tick < 256) ? p.order[tick] : (K2_END | min(tick - 256, 255u));
          asm volatile("st.shared.u32 [%0], %1;" ::"r"(sItem + (it & 7) * 4), "r"(item) : "memory");
          if (item >= K2_END) break;
          const int h = item >> 3, j = item & 7;
          const int blk = 2 * j + (int)(rank ^ (it & 1));
          const int col = h * 128 + rank * 64;
          const int nb = 2 * j + 2;
          if (!((seen >> (h >> 1)) & 1)) {
            wait_flag(&g_sync[F_HP + (h >> 1)], RDY_TARGET);
            asm volatile("fence.proxy.async.global;" ::: "memory");
            seen |= 1u << (h >> 1);
          }
          PWAIT(bE + c.s * 8, c.ph);
          mbar_expect(bF + c.s * 8, 32768);
          tma2d(sbase + c.s * 32768, &p.tmC, bF + c.s * 8, h * 128, blk * 128);
          tma2d(sbase + c.s * 32768 + 16384, &p.tmC, bF + c.s * 8, h * 128 + 64, blk * 128);
          c.next();
          if (tick >= 256 - 73) {
            const int kk = tick - (256 - 73), sel = (kk < 9), kr = (sel ? kk : kk - 9) * 64 + rank * 32;
#pragma unroll 1
            for (int i = 0; i < 2; i++) {
              tma_pf3d(&p.tmO[sel], 0, kr, i * 4);
              tma_pf2d(&p.tmOt[sel], 512 + i * 32, kr);
            }
          }
#pragma unroll 1
          for (int n = nb - 1; n >= 0; n--) {
            if (n == 0 && rank == 0) tick = atomicAdd(&g_sync[F_TICK], 1u);
            PWAIT(bE + c.s * 8, c.ph);
            mbar_expect(bF + c.s * 8, 32768);
            tma2d_mc(sbase + c.s * 32768 + rank * 16384, &p.tmK, bF + c.s * 8, col, n * 128, 3);
            c.next();
            if (n < nb - 1 || it > 0) {
              PWAIT(bE + c.s * 8, c.ph);
              mbar_expect(bF + c.s * 8, 32768);
              tma2d_mc(sbase + c.s * 32768 + rank * 16384, &p.tmV, bF + c.s * 8, (n < nb - 1) ? col : pcol, (n < nb - 1) ? (n + 1) * 128 : 0, 3);
              c.next();
            }
          }
          pcol = col;
          if (rank == 0) {
            asm volatile(
                "{\n.reg .b32 a, b;\nmapa.shared::cluster.u32 a, %0, 1;\nmapa.shared::cluster.u32 b, %1, 1;\n"
                "st.async.shared::cluster.mbarrier::complete_tx::bytes.u32 [a], %2, [b];\n}" ::"r"(sTick + (it & 1) * 4),
                "r"(bT + (it & 1) * 8), "r"(tick) : "memory");
          } else {
            mbar_expect(bT + (it & 1) * 8, 4);
            PWAIT(bT + (it & 1) * 8, (it >> 1) & 1);
            tick = lds32(sTick + (it & 1) * 4);
          }
        }
        PWAIT(bE + c.s * 8, c.ph);
        mbar_expect(bF + c.s * 8, 32768);
        tma2d_mc(sbase + c.s * 32768 + rank * 16384, &p.tmV, bF + c.s * 8, pcol, 0, 3);
        const uint32_t unit = tick - 256;
        const int mblk = (7 - (p.unit[unit][0] >> 1)) * 2 + rank, nhalf = p.unit[unit][0] & 1;
        uint32_t have, hoa;
        asm volatile("ld.acquire.gpu.global.u32 %0, [%1];" : "=r"(have) : "l"(&g_sync[F_CTX + mblk]) : "memory");
        asm volatile("ld.acquire.gpu.global.u32 %0, [%1];" : "=r"(hoa) : "l"(&g_sync[F_OA + mblk]) : "memory");
        asm volatile("fence.proxy.async.global;" ::: "memory");
#pragma unroll 1
        for (uint32_t idx = PF3A; idx < PF3; idx++) {
          const int kk = p.unit[unit][2] + idx;
          if ((kk < 9) ? (hoa >= 8) : ((have >> ((kk - 9) >> 1)) & 1)) tma_pf2d(&p.tmC, ((kk < 9) ? 64 + kk : kk - 9) * 64, mblk * 128);
        }
        {
          const uint32_t rot = k3_rot(c.s), nfree = ((0x1Au >> c.s) & 1) ? 2 : 3;
          uint32_t kq = p.unit[unit][2] * 0x010101u + 0x020100u, k1 = 80, idx = 0, pa = 0, pb = 0;
          auto step = [&](uint32_t& pend) {
            uint32_t nxt = (kq & 255) + 3;
            if (idx + 3 >= K3_NS && k1 == 80) {
              if (rank == 0) {
                nxt = min(pend + p.unit[unit][3], 73u);
                asm volatile("{\n.reg .b32 a;\nmapa.shared::cluster.u32 a, %0, 1;\nst.volatile.shared::cluster.u8 [a], %1;\n}" ::"r"(sClm + idx), "r"(nxt) : "memory");
              } else {
#pragma unroll 1
                for (uint32_t spins = 0; spins < (1u << 22); spins++) {
                  asm volatile("ld.volatile.shared.u8 %0, [%1];" : "=r"(nxt) : "r"(sClm + idx) : "memory");
                  if (nxt != 255) break;
                  __nanosleep(20);
                }
              }
              if (nxt >= 73) {
                k1 = idx + 3;
                asm volatile("st.shared.u32 [%0], %1;" ::"r"(sK1), "r"(k1) : "memory");
              }
            }
            const uint32_t kk = kq & 255;
            kq = (kq >> 8) | (nxt << 16);
            const uint32_t s = (rot + idx) & 3;
            if (idx >= nfree) PWAIT((idx < 4) ? bH : b3E + s * 8, (idx < 4) ? 0 : (~idx >> 2) & 1);
#pragma unroll 1
            while (idx < nfree && c.s != ((0x6431u >> (4 * s)) & 15)) {
              c.next();
              PWAIT(bE + c.s * 8, c.ph);
            }
            mbar_expect(b3F + s * 8, K3_STAGE);
            const uint32_t st = sbase + s * K3_STAGE;
            const int sel = (kk < 9), k = sel ? kk : kk - 9, kr = k * 64 + rank * 32;
            tma3d_mc(st + 16384 + rank * 16384, &p.tmO[sel], b3F + s * 8, 0, kr, nhalf * 4, 3);
            tma2d_mc(st + 49152 + rank * 2048, &p.tmOt[sel], b3F + s * 8, 512 + nhalf * 32, kr, 3);
            if (rank == 0 && idx + 5 >= K3_NS && k1 == 80) pend = atomicAdd(&g_sync[F_CLM + p.unit[unit][0]], 1u);
            if (sel && hoa < 8) {
              wait_flag(&g_sync[F_OA + mblk], 8);
              hoa = 8;
              asm volatile("fence.proxy.async.global;" ::: "memory");
            }
            if (!sel && !((have >> (k >> 1)) & 1)) {
#pragma unroll 1
              for (uint32_t spins = 0; spins < (1u << 22); spins++) {
                asm volatile("ld.acquire.gpu.global.u32 %0, [%1];" : "=r"(have) : "l"(&g_sync[F_CTX + mblk]) : "memory");
                if ((have >> (k >> 1)) & 1) break;
                __nanosleep(100);
              }
              asm volatile("fence.proxy.async.global;" ::: "memory");
            }
            tma2d(st, &p.tmC, b3F + s * 8, (sel ? 64 + k : k) * 64, mblk * 128);
            return ++idx >= k1;
          };
#pragma unroll 1
          for (;;) {
            if (step(pa)) break;
            if (step(pb)) break;
          }
          asm volatile("" ::"r"(pa), "r"(pb) : "memory");
        }
      }
    }
    __syncwarp();
    if (warp_g == 8) {
      uint32_t v = 0;
      if (lane == 0) {
        __threadfence();
        v = atomicAdd(&g_sync[F_DONE], 1u);
      }
      if (__shfl_sync(0xffffffffu, v, 0) == 2 * NCLUSTER - 1) {
        reinterpret_cast<uint4*>(g_sync)[lane] = make_uint4(0, 0, 0, 0);
        if (lane == 0) g_sync[F_EPOCH] = lds32(sGate + 64) + 1;
      }
    }
    asm volatile("" ::: "memory");
    if (__shfl_sync(0xffffffffu, warp_g, 0) != 8) {
      if (lr0 < S_LEN) {
#pragma unroll 1
        for (int i = warp_g - 9; i < 16; i += 3) {
          const float g = gate_row(lr0 + i, lane, x, gate_w);
          if (lane == 0) asm volatile("st.shared.f32 [%0], %1;" ::"r"(sGate + i * 4), "f"(g) : "memory");
        }
        bar_arrive(3, 256 + 96);
        if (lane == 0) {
          __threadfence();
          atomicAdd(&g_sync[F_GATE], 1u);
        }
      }
      uint32_t aph = 1;
#pragma unroll 1
      for (int ji = 0; ji < K1_MAXJOBS; ji++) aph ^= (p.jobs[cl][ji] >> 14) & 1;
      if (warp_g == 9) {
        uint32_t nxt = 0;
        if (lane == 0) {
#pragma unroll 1
        for (int ji = 0; ji < K1_MAXJOBS; ji++) {
          const uint32_t job = p.jobs[cl][ji];
          if (!(job & 3)) break;
          PWAIT(bS + (ji & 3) * 8, (ji >> 2) & 1);
          __threadfence();
          atomicAdd(&g_sync[(((job >> 6) & 3) == 2) ? (F_QKVA + ((job >> 3) & 7) * 2 + rank) : (F_HP + ((job >> 10) & 15))], 1u);
        }
#pragma unroll 1
        for (int it = 0;; it++) {
          PWAIT(bS2 + (it & 3) * 8, (it >> 2) & 1);
          const uint32_t item = lds32(sItem + (it & 7) * 4);
          nxt = lds32(sItem + ((it + 1) & 7) * 4);
          __threadfence();
          atomicOr(&g_sync[F_CTX + (item & 7) * 2 + (rank ^ (it & 1))], 1u << (item >> 3));
          if (nxt >= K2_END) break;
        }
        }
        const uint32_t unit = __shfl_sync(0xffffffffu, nxt, 0) & 255;
        {
          const int mblk = (7 - (p.unit[unit][0] >> 1)) * 2 + rank, nhalf = p.unit[unit][0] & 1;
          bf16* o = ptr_add(out, (mblk * 128 + p.unit[unit][1] * 32) * DM * 2);
          const bool mine = p.unit[unit][1] < 4;
#pragma unroll 4
          for (int i = 0; i < 32 && mine; i++) __stcg(reinterpret_cast<uint4*>(ptr_add(o, i * DM * 2 + nhalf * 512 + lane * 16)), make_uint4(0, 0, 0, 0));
#pragma unroll
          for (int i = 0; i < 4 && mine; i++) __stcg(reinterpret_cast<uint4*>(ptr_add(o, (i * 8 + (lane >> 2)) * DM * 2 + 1024 + nhalf * 64 + (lane & 3) * 16)), make_uint4(0, 0, 0, 0));
          asm volatile("fence.proxy.async.global;" ::: "memory");
          __threadfence();
          __syncwarp();
          if (lane == 0) {
            prefetch_tmap(&p.tmR[0]); prefetch_tmap(&p.tmR[1]);
            unsigned int* cnt = &g_sync[F_XCH + mblk * 2 + nhalf];
            const uint32_t xtarget = lds32(sGate + 64) * 4 + 4;
            if (mine) atomicAdd(cnt, 1u);
            uint32_t v;
#pragma unroll 1
            for (uint32_t spins = 0; spins < (1u << 22); spins++) {
              asm volatile("ld.acquire.gpu.global.u32 %0, [%1];" : "=r"(v) : "l"(cnt) : "memory");
              if ((int)(v - xtarget) >= 0) break;
              __nanosleep(200);
            }
            asm volatile("fence.proxy.async.global;" ::: "memory");
            mbar_arrive(bZ);
          }
        }
      } else if (warp_g == 11) {
        if (lane == 0) {
          prefetch_tmap(&p.tmC); prefetch_tmap(&p.tmK); prefetch_tmap(&p.tmV);
          asm volatile("st.shared.u32 [%0], %1;" ::"r"(sGate + 64), "r"(__ldcg(&g_sync[F_EPOCH])) : "memory");
          wait_flag(&g_sync[F_GATE], GATE_TARGET);
          uint32_t tick;
          if (rank == 0) {
            PWAIT(bLast, 0);
            PWAIT(bAe + FIRST_DRAW * 8, aph);
            tick = atomicAdd(&g_sync[F_TICK], 1u);
            asm volatile("st.shared.u32 [%0], %1;" ::"r"(sTick + 8), "r"(tick) : "memory");
            asm volatile(
                "{\n.reg .b32 a, b;\nmapa.shared::cluster.u32 a, %0, 1;\nmapa.shared::cluster.u32 b, %1, 1;\n"
                "st.async.shared::cluster.mbarrier::complete_tx::bytes.u32 [a], %2, [b];\n}" ::"r"(sTick + 8), "r"(bT0), "r"(tick) : "memory");
          } else {
            mbar_expect(bT0, 4);
            PWAIT(bT0, 0);
            tick = lds32(sTick + 8);
          }
          wait_flag(&g_sync[F_HP + (p.order[tick] >> 4)], RDY_TARGET);
          mbar_arrive(bR);
        }
      } else if (warp_g == 10) {
        if (lr0 < S_LEN && lane == 0) {
          prefetch_tmap(&p.tmL[0]); prefetch_tmap(&p.tmL[1]); prefetch_tmap(&p.tmL[2]);
          wait_flag(&g_sync[F_QKVA + (lr0 >> 7)], K1_FLAG_TARGET);
          wait_flag(&g_sync[F_QKVA + (max(lr0 - 16, 0) >> 7)], K1_FLAG_TARGET);
          asm volatile("fence.proxy.async.global;" ::: "memory");
          PWAIT(bLast, 0);
#pragma unroll 1
          for (int kc = 0; kc < 6; kc++) {
            PWAIT(bAe + kc * 8, aph);
            if (kc == 3) {
              mbar_expect(bL, LV);
              tma4d(sL, &p.tmL[0], bL, lr0 / 2 - 8, 9, 0);
              tma4d(sL + LQ, &p.tmL[1], bL, lr0 / 2, 0, 0);
            }
          }
          mbar_expect(bL2, LQ);
          tma4d(sL + LV, &p.tmL[0], bL2, lr0 / 2 - 8, 18, 0);
        }
        __syncwarp();
        bar_sync(5, 256 + 32);
        if (lr0 < S_LEN && lane == 0) {
          asm volatile("cp.async.bulk.tensor.4d.global.shared::cta.bulk_group [%0, {%2, %3, %2, %2}], [%1];" ::"l"(&p.tmL[2]), "r"(sL + LQ), "r"(0), "r"(lr0 / 2) : "memory");
          asm volatile("cp.async.bulk.commit_group;" ::: "memory");
          asm volatile("cp.async.bulk.wait_group.read 0;" ::: "memory");
        }
        __syncwarp();
        if (lane < 12) mbar_arrive_cluster(bE + (4 + lane % 3) * 8, (lane / 3) & 1);
        if (lr0 < S_LEN && lane == 0) {
          asm volatile("cp.async.bulk.wait_group 0;" ::: "memory");
          asm volatile("fence.proxy.async.global;" ::: "memory");
          __threadfence();
          atomicAdd(&g_sync[F_OA + (lr0 >> 7)], 1u);
        }
      }
    }
    __syncwarp();
    cluster_sync();
  } else {
    reg_alloc<232>();
    const int wg = warp_g >> 2, warp = warp_g & 3, q = lane & 3;
    const bool sig = (lane == 0) && (warp < 2);
    {
      K1State st{0, 0, 0, nullptr, nullptr, 0, 0, 0, 24};
      float acc[128];
      uint32_t pk[64];
      if (wg == 0) { TS(0, 0); TSC(0, 2); }
      uint32_t job = p.jobs[cl][0];
      k1_first(st, job, bAf, bBf);
      {
#pragma unroll 1
        for (int ji = 0; job & 3; ji++) {
          const uint32_t njob = p.jobs[cl][ji + 1];
          k1_tile(acc, pk, st, job, njob, sA, sB, bAf, bAe, bBf, bBe, bS, wg, warp, lane, rank);
          job = njob;
        }
      }
#pragma unroll
      for (int i = 0; i < 4; i++)
        mbar_arrive_cluster_if(bE + i * 8, warp & 1, sig);
      if (lr0 < S_LEN) bar_sync(3, 256 + 96);
      if (st.wsel == 3) {
#pragma unroll
        for (int G = 0; G < 16; G++) scale_q4(pk + G * 4);
      }
      auto flush = [&](int i, uint32_t dep) {
        asm volatile("{\n.reg .pred p;\nsetp.eq.u32 p, %5, 0;\n@p st.global.cs.v4.b32 [%0], {%1, %2, %3, %4};\n}" ::"l"(((i & 1) ? st.pp8 : st.pp) + (i / 2) * 32),
                     "r"(pk[i * 4]), "r"(pk[i * 4 + 1]), "r"(pk[i * 4 + 2]), "r"(pk[i * 4 + 3]), "r"(dep & blockIdx.y) : "memory");
      };
      if (wg == 0) { TS(0, 1); TSC(0, 3); }
      if (lr0 < S_LEN) {
        const float gate0 = __uint_as_float(lds32(sGate + (lane >> 2) * 8)), gate1 = __uint_as_float(lds32(sGate + (lane >> 2) * 8 + 4));
        local_attn(lr0, warp_g, sL, bL, bL2, lane, gate0, gate1, flush);
        k1_flag(st, lane, bS);
      } else {
        FLUSH();
      }
      bar_arrive(5, 256 + 32);
    }
    __syncwarp();
    uint32_t item, rot;
    {
      const int mybar = 1 + wg, otherbar = 2 - wg;
      const uint32_t never = blockIdx.y;
      float S[64], O[64];
      uint32_t P[32], Q[32];
      float m0, m1, l0, l1, gf0, gf1;
      uint32_t eoff;
      Cursor c{4 - 2 * rank, 0}, ck{2 - rank, 0};
      if (wg == 1) bar_arrive(1, 256);
      if (wg == 0) { TS(1, 0); TSC(1, 2); }
      {
        const Cursor cq{0, 0}, cs0{1, 0}, cs1{3, 0};
        const int it = 0, hi = rank;
        mbar_wait2(bF, 0, bF + ck.s * 8, 0);
        LOAD_Q();
        wg_fence();
        ISSUE_QK(ck);
        wg_commit();
        RELEASE(cq);
        NEW_ITEM();
        wg_wait<0>();
        fence_regs(S);
      }
#pragma unroll 1
      for (int it = 0;;) {
        int hi = (int)(rank ^ (it & 1));
        RELEASE(ck);
        const int nblk = 2 * (item & 7) + 1 + hi;
        Cursor cv;
        float s0 = 0.f, s1 = 0.f;
        l0 = 0.f; l1 = 0.f;
        m0 = 0.f; m1 = 0.f;
        bool shifted = false;
        {
          const int d = warp * 16 + (lane >> 2) - 2 * q;
          if (wg == 0) {
#pragma unroll
            for (int jj = 0; jj < 8; jj++) MASK(jj, jj);
            EXPB(0); EXPB(1); EXPB(2); EXPB(3);
#pragma unroll
            for (int i = 32; i < 64; i++) S[i] = -INFINITY;
#pragma unroll
            for (int i = 16; i < 32; i++) P[i] = 0;
          } else {
#pragma unroll
            for (int jj = 0; jj < 8; jj++) MASK(jj + 8, jj);
            EXPB(0); EXPB(1); EXPB(2); EXPB(3); EXPB(4); EXPB(5); EXPB(6); EXPB(7);
          }
        }
        float chk = (q == 0 && !(fminf(s0, s1) >= SPEC_LO)) ? INFINITY : s0 + s1;
        fence_regs(P);
        TB(9);
#pragma unroll 1
        for (int n = 1;; n++) {
          if (__any_sync(0xffffffffu, !(chk <= SPEC_HI))) {
            float mx0 = fmaxf(S[0], S[1]), mx1 = fmaxf(S[2], S[3]);
#pragma unroll
            for (int jj = 1; jj < 16; jj++) {
              mx0 = fmaxf(mx0, fmaxf(S[jj * 4 + 0], S[jj * 4 + 1]));
              mx1 = fmaxf(mx1, fmaxf(S[jj * 4 + 2], S[jj * 4 + 3]));
            }
            mx0 = fmaxf(mx0, __shfl_xor_sync(0xffffffffu, mx0, 1));
            mx1 = fmaxf(mx1, __shfl_xor_sync(0xffffffffu, mx1, 1));
            mx0 = fmaxf(mx0, __shfl_xor_sync(0xffffffffu, mx0, 2));
            mx1 = fmaxf(mx1, __shfl_xor_sync(0xffffffffu, mx1, 2));
            const float lo = (n == 1) ? -INFINITY : 0.f;
            mx0 = fmaxf(mx0, lo);
            mx1 = fmaxf(mx1, lo);
            m0 += mx0; m1 += mx1;
            shifted = true;
            const float sc0 = ex2(-fmaxf(mx0, 0.f)), sc1 = ex2(-fmaxf(mx1, 0.f));
            l0 *= sc0; l1 *= sc1;
            s0 = 0.f; s1 = 0.f;
#pragma unroll
            for (int jj = 0; jj < 16; jj++) {
              const float e0 = ex2(S[jj * 4 + 0] - mx0), e1 = ex2(S[jj * 4 + 1] - mx0), e2 = ex2(S[jj * 4 + 2] - mx1), e3 = ex2(S[jj * 4 + 3] - mx1);
              s0 += e0 + e1;
              s1 += e2 + e3;
              P[jj * 2 + 0] = pack_bf16(e0, e1);
              P[jj * 2 + 1] = pack_bf16(e2, e3);
              O[jj * 4 + 0] *= sc0;
              O[jj * 4 + 1] *= sc0;
              O[jj * 4 + 2] *= sc1;
              O[jj * 4 + 3] *= sc1;
            }
          }
          l0 += s0;
          l1 += s1;
          if (n >= nblk) break;
          ck = c; c.next();
          cv = c; c.next();
          mbar_wait(bF + ck.s * 8, ck.ph);
          mbar_wait(bF + cv.s * 8, cv.ph);
          TURN_SYNC();
          TRC(0);
          wg_fence();
          ISSUE_QK(ck);
          wg_commit();
          {
            const uint64_t dv = make_desc(sbase + cv.s * 32768, 16384, 1024, 1);
#pragma unroll
            for (int t = 0; t < 8; t++) {
              wgmma_rs_n128<1, 0>(O, P[4 * t], P[4 * t + 1], P[4 * t + 2], P[4 * t + 3], dv + (uint64_t)(t * 128), (t > 0) ? 1 : (n != 1));
              if ((PVM >> t) & 1) wg_commit();
            }
          }
          TURN_ARRIVE();
          s0 = 0.f; s1 = 0.f;
          wg_wait<__builtin_popcount(PVM)>();
          fence_regs(S);
          RELEASE(ck);
          if (shifted) {
#pragma unroll
            for (int i = 0; i < 64; i++) S[i] -= (i & 2) ? m1 : m0;
          }
          wg_wait<__builtin_popcount(PVM) - 1>();
          EXPC(0); EXPC(1); EXPC(2); EXPC(3); EXPC(4); EXPC(5); EXPC(6); EXPC(7);
          chk = s0 + s1;
        }
        it++;
        hi ^= 1;
        TB(0);
        Cursor cq = c, cs0, cs1;
        rot = k3_rot(c.s);
        c.next();
        ck = c; c.next();
        cs0 = ck; cs1 = ck;
        cv = c; c.next();
        if (!hi) {
          ck = c; c.next();
          cs1 = c; c.next();
        }
        mbar_wait(bF + cq.s * 8, cq.ph);
        TB(1);
        LOAD_Q();
        const uint32_t rdy = mbar_test(bF + ck.s * 8, ck.ph) & mbar_test(bF + cv.s * 8, cv.ph);
        l0 += __shfl_xor_sync(0xffffffffu, l0, 1);
        l1 += __shfl_xor_sync(0xffffffffu, l1, 1);
        l0 += __shfl_xor_sync(0xffffffffu, l0, 2);
        l1 += __shfl_xor_sync(0xffffffffu, l1, 2);
        if (item >= K2_END) {
          TURN_SYNC();
          TRC(2);
          wg_fence();
          ISSUE_PV(cq, nblk == 1);
          wg_commit();
          if (wg == 0) TURN_ARRIVE();
          asm volatile("" : "+f"(gf0), "+f"(gf1), "+f"(l0), "+f"(l1));
          const float f0 = __fdividef(1.f - gf0, l0), f1 = __fdividef(1.f - gf1, l1);
          bf16* optr = ptr_add(g_ctx, eoff);
          wg_wait<0>();
          fence_regs(O);
          mbar_arrive_cluster_if(bH, warp & 1, sig);
          STORE_O(0); STORE_O(1); STORE_O(2); STORE_O(3);
          __syncwarp();
          mbar_arrive_if(bS2 + ((it - 1) & 3) * 8, lane == 0);
          break;
        }
        if (!rdy) mbar_wait2(bF + ck.s * 8, ck.ph, bF + cv.s * 8, cv.ph);
        TB(2);
        TURN_SYNC();
        TB(3);
        TRC(1);
        wg_fence();
        ISSUE_PV(cv, nblk == 1);
        wg_commit();
        ISSUE_QK(ck);
        wg_commit();
        TURN_ARRIVE();
        RELEASE(cq);
        TB(4);
        asm volatile("" : "+f"(gf0), "+f"(gf1), "+f"(l0), "+f"(l1));
        const float f0 = __fdividef(1.f - gf0, l0), f1 = __fdividef(1.f - gf1, l1);
        wg_wait<1>();
        fence_regs(O);
        fence_regs(P);
        TB(5);
        RELEASE(cv);
        {
          bf16* optr = ptr_add(g_ctx, eoff);
          STORE_O(0); STORE_O(1); STORE_O(2); STORE_O(3);
          __syncwarp();
          mbar_arrive_if(bS2 + ((it - 1) & 3) * 8, lane == 0);
        }
        TB(6);
        NEW_ITEM();
        TB(7);
        wg_wait<0>();
        fence_regs(S);
        TB(8);
      }
      TRC(3);
      if (wg == 1) { TS(1, 1); TSC(1, 3); }
    }
    __syncwarp();
    const uint32_t unit = item & 255;
    {
      const int mblk = (7 - (p.unit[unit][0] >> 1)) * 2 + rank, nhalf = p.unit[unit][0] & 1;
      float acc[144];
      uint32_t s = rot, ph = 0, prev = 0, k = 0;
      if (wg == 0) { TS(2, 0); TSC(2, 2); }
      uint32_t fa[16], fb[16], fc[16];
      const uint32_t aoff = (wg * 64 + warp * 16 + (lane & 15)) * 128 + (((lane >> 4) ^ (lane & 7)) << 4);
#define C_NEXT()                                                                                               \
  do {                                                                                                         \
    s = (s + 1) & 3;                                                                                           \
    if (s == rot) ph ^= 1;                                                                                     \
    mbar_wait(b3F + s * 8, ph);                                                                                \
  } while (0)
#define C_LOAD(F)                                                                                              \
  do {                                                                                                         \
    _Pragma("unroll") for (int t = 0; t < 4; t++)                                                              \
        ldsm_x4(F[4 * t], F[4 * t + 1], F[4 * t + 2], F[4 * t + 3], sbase + s * K3_STAGE + (aoff ^ (t * 32))); \
  } while (0)
#define C_MMA(F, S, H, SD)                                                                                     \
  do {                                                                                                         \
    const uint32_t st = sbase + (S) * K3_STAGE;                                                                \
    const uint64_t db = make_desc(st + 16384, 4096, 1024, 1), dt = make_desc(st + 49152, 16, 512, 2);          \
    _Pragma("unroll") for (int t = 0; t < 4; t++) {                                                            \
      const int sd = (t > 0) || (SD);                                                                          \
      if ((H) & 1) wgmma_rs_n128<1, 0>(acc, F[4 * t], F[4 * t + 1], F[4 * t + 2], F[4 * t + 3], db + (uint64_t)((t >> 1) * 1024 + (t & 1) * 128), sd); \
      if ((H) & 2) wgmma_rs_n128<1, 64>(acc, F[4 * t], F[4 * t + 1], F[4 * t + 2], F[4 * t + 3], db + (uint64_t)((t >> 1) * 1024 + (t & 1) * 128 + 512), sd); \
      if ((H) & 2) wgmma_rs_n32<1, 128>(acc, F[4 * t], F[4 * t + 1], F[4 * t + 2], F[4 * t + 3], dt + (uint64_t)(t * 64), sd); \
    }                                                                                                          \
  } while (0)
#define C_STEP(F, G)                                                                                           \
  {                                                                                                            \
    wg_fence();                                                                                                \
    C_MMA(F, s, 3, k > 0);                                                                                     \
    wg_commit();                                                                                               \
    wg_wait<1>();                                                                                              \
    fence_regs(G);                                                                                             \
    mbar_arrive_cluster_if(b3E + prev * 8, warp & 1, sig && k > 0);                                            \
    prev = s;                                                                                                  \
    TCK(k + 1);                                                                                                \
    C_NEXT();                                                                                                  \
    if (++k + 3 >= lds32(sK1)) break;                                                                          \
    C_LOAD(G);                                                                                                 \
  }
      TCK(0);
      mbar_wait(b3F + s * 8, 0);
      C_LOAD(fa);
#pragma unroll
      for (int i = 0; i < 16; i++) fb[i] = 0;
#pragma unroll 1
      for (;;) {
        C_STEP(fa, fb)
        C_STEP(fb, fa)
      }
      C_LOAD(fc);
      cluster_arrive();
      if (wg == 1) mbar_wait(bLd, 0);
      const uint32_t s0 = s;
      wg_fence();
      C_MMA(fc, s0, 2, 1);
      wg_commit();
      wg_wait<1>();
      fence_regs(fa);
      fence_regs(fb);
      C_NEXT();
      C_LOAD(fa);
      wg_fence();
      C_MMA(fa, s, 2, 1);
      C_MMA(fc, s0, 1, 1);
      wg_commit();
      C_NEXT();
      C_LOAD(fb);
      wg_fence();
      C_MMA(fb, s, 2, 1);
      wg_commit();
      C_MMA(fa, (s + 3) & 3, 1, 1);
      C_MMA(fb, s, 1, 1);
      wg_commit();
      mbar_arrive_if(bLd, tid < 128 && lane == 0);
      const uint32_t stail = sbase + K3_NST * K3_STAGE + warp_g * 1024;
      const int row = mblk * 128 + warp_g * 16;
      mbar_wait(bZ, 0);
#pragma unroll
      for (int h = 1; h >= 0; h--) {
        if (h) wg_wait<1>(); else wg_wait<0>();
#pragma unroll
        for (int i = h * 64; i < 64 + h * 80; i++) asm volatile("" : "+f"(acc[i])::"memory");
        if (!h && wg == 0) TS(2, 4);
#pragma unroll
        for (int i = h * 8; i < 8 + h * 10; i++) {
          const uint32_t ad = (i < 16) ? sbase + (i >> 2) * K3_STAGE + (aoff ^ ((i & 3) * 32))
                                       : stail + (lane & 15) * 64 + ((((i & 1) * 2 + (lane >> 4)) ^ ((lane >> 1) & 3)) << 4);
          asm volatile("stmatrix.sync.aligned.m8n8.x4.shared.b16 [%0], {%1, %2, %3, %4};" ::"r"(ad), "r"(pack_bf16(acc[i * 8], acc[i * 8 + 1])),
                       "r"(pack_bf16(acc[i * 8 + 2], acc[i * 8 + 3])), "r"(pack_bf16(acc[i * 8 + 4], acc[i * 8 + 5])), "r"(pack_bf16(acc[i * 8 + 6], acc[i * 8 + 7])) : "memory");
        }
        asm volatile("fence.proxy.async.shared::cta;" ::: "memory");
        __syncwarp();
        if (!h && wg == 0) TS(2, 5);
        if (lane == 0) {
#pragma unroll
          for (int c = h * 2; c < 2 + h * 3; c++)
            asm volatile("cp.reduce.async.bulk.tensor.2d.global.shared::cta.add.tile.bulk_group [%0, {%2, %3}], [%1];" ::"l"(&p.tmR[c >> 2]),
                         "r"((c < 4) ? sbase + c * K3_STAGE + warp_g * 2048 : stail), "r"((c < 4) ? nhalf * 256 + c * 64 : 512 + nhalf * 32), "r"(row) : "memory");
        }
        __syncwarp();
      }
      if (lane == 0) {
        asm volatile("cp.async.bulk.commit_group;" ::: "memory");
        if (wg == 0) TS(2, 6);
        asm volatile("cp.async.bulk.wait_group 0;" ::: "memory");
      }
      __syncwarp();
    }
    if (wg == 0) { TS(2, 1); TSC(2, 3); }
    cluster_wait();
  }
}

typedef CUresult (*EncFn)(CUtensorMap*, CUtensorMapDataType, cuuint32_t, void*, const cuuint64_t*, const cuuint64_t*, const cuuint32_t*,
                          const cuuint32_t*, CUtensorMapInterleave, CUtensorMapSwizzle, CUtensorMapL2promotion, CUtensorMapFloatOOBfill);

static void enc2d(EncFn enc, CUtensorMap* m, const void* ptr, uint64_t cols, uint64_t rows, uint32_t bc, uint32_t br,
                  CUtensorMapSwizzle sw = CU_TENSOR_MAP_SWIZZLE_128B) {
  cuuint64_t gd[2] = {cols, rows}, gs[1] = {cols * 2};
  cuuint32_t bx[2] = {bc, br}, es[2] = {1, 1};
  enc(m, CU_TENSOR_MAP_DATA_TYPE_BFLOAT16, 2, const_cast<void*>(ptr), gd, gs, bx, es, CU_TENSOR_MAP_INTERLEAVE_NONE, sw,
      CU_TENSOR_MAP_L2_PROMOTION_L2_256B, CU_TENSOR_MAP_FLOAT_OOB_FILL_NONE);
}
static void enc3d(EncFn enc, CUtensorMap* m, const void* ptr, uint64_t cols, uint64_t rows, uint32_t br, uint32_t bch) {
  cuuint64_t gd[3] = {64, rows, cols / 64}, gs[2] = {cols * 2, 128};
  cuuint32_t bx[3] = {64, br, bch}, es[3] = {1, 1, 1};
  enc(m, CU_TENSOR_MAP_DATA_TYPE_BFLOAT16, 3, const_cast<void*>(ptr), gd, gs, bx, es, CU_TENSOR_MAP_INTERLEAVE_NONE,
      CU_TENSOR_MAP_SWIZZLE_128B, CU_TENSOR_MAP_L2_PROMOTION_L2_256B, CU_TENSOR_MAP_FLOAT_OOB_FILL_NONE);
}

static int g_sched[10] = {11, 10, 7, 4, 4, 4, 6, 8, 6, 24};
static void build_k1_jobs(Params& p) {
  int cnt[NCLUSTER];
  for (int c = 0; c < NCLUSTER; c++) {
    cnt[c] = 0;
    for (int i = 0; i <= K1_MAXJOBS; i++) p.jobs[c][i] = 0;
  }
  auto add = [&](int c, int nch, int a_sel, int mp, int w_sel, int chunk0) {
    p.jobs[c][cnt[c]++] = (uint16_t)((nch - 1) | (a_sel << 2) | (mp << 3) | (w_sel << 6) | (chunk0 << 8));
  };
  const char* plan = "ccccccccccc cccccccccc ccccccc cccc xxxx xxxx xxxxxx xxxxxxxx";
  int TIE = 0;
  int XA = 0;
  const char* cur[8];
  int tend[8] = {};
  for (int g = 0; g < 8; g++) {
    cur[g] = plan;
    while (*plan == 'c' || *plan == 'x') plan++;
    if (*plan) plan++;
  }
  int kc = 0, kx = 0;
  for (;;) {
    int b = -1, bt = 0;
    for (int g = 0; g < 8; g++) {
      const int t = tend[g] + (*cur[g] == 'x' ? 94 : 85);
      if ((*cur[g] == 'c' || *cur[g] == 'x') && (b < 0 || t < bt || (TIE && t == bt))) { b = g; bt = t; }
    }
    if (b < 0) break;
    const int a = kx - XA;
    for (int mp = 0; mp < 8; mp++) {
      if (*cur[b] == 'c') add(b * 8 + mp, 4, 0, mp, kc & 1, (kc >> 1) * 4);
      else if (a >= 0 && a < 7) add(b * 8 + mp, a == 0 ? 3 : 4, 1, mp, 2, a == 0 ? 24 : (a - 1) * 4);
      else add(b * 8 + mp, 4, 1, mp, 3, (a < 0 ? kx : kx - 7) * 4);
    }
    if (*cur[b] == 'c') kc++; else kx++;
    cur[b]++;
    tend[b] = bt;
  }
  for (int mp = 0; mp < 8; mp++) add(64 + mp / 4, 4, 1, mp, 3, 15 * 4);
  for (int cc = 0; cc < NCLUSTER; cc++)
    for (int i = 0; i < cnt[cc]; i++) {
      const int key = p.jobs[cc][i] & 0x3C;
      if (i == 0 || (p.jobs[cc][i - 1] & 0x3C) != key) p.jobs[cc][i] |= (1 << 14);
      if (i == cnt[cc] - 1 || (p.jobs[cc][i + 1] & 0x3C) != key) p.jobs[cc][i] |= (1 << 15);
    }
}

static void build_k2_items(Params& p) {
  int n = 0;
  const int SCHED_N1 = g_sched[8], SCHED_N2 = g_sched[9];
  int N0 = 2, J0 = 2;
  for (int j = 7; j >= J0; j--)
    for (int h = 0; h < N0; h++) p.order[n++] = (uint8_t)(h * 8 + j);
  for (int j = 7; j >= 0; j--)
    for (int h = 0; h < SCHED_N1; h++)
      if (!(h < N0 && j >= J0)) p.order[n++] = (uint8_t)(h * 8 + j);
  for (int j = 7; j >= 4; j--)
    for (int h = SCHED_N1; h < SCHED_N2; h++) p.order[n++] = (uint8_t)(h * 8 + j);
  for (int j = 7; j >= 0; j--)
    for (int h = SCHED_N1; h < 32; h++)
      if (!(h < SCHED_N2 && j >= 4)) p.order[n++] = (uint8_t)(h * 8 + j);
  int TJ[2] = {0, 0}, TP = 0;
  for (int t = 0; t < 2; t++) {
    if (!TJ[t]) continue;
    int i = 0;
    while (p.order[i] != 31 * 8 + TJ[t]) i++;
    for (; i < 255 - TP; i++) p.order[i] = p.order[i + 1];
    p.order[i] = (uint8_t)(31 * 8 + TJ[t]);
  }
}

static void build_k3_units(Params& p) {
  int um = 0;
  for (int u = 0; u < 66; u++) {
    int t = (u % 28 < 14) ? u % 28 : 27 - u % 28, i = u / 14;
    if (um == 1) t = u % 14;
    if (um == 2) { t = (u % 28) / 2; i = (u / 28) * 2 + (u & 1); }
    if (um == 3) { t = u / 4; i = u & 3; }
    if (um == 4) { t = (u < 42) ? u / 3 : u - 42; i = (u < 42) ? u % 3 : 3; }
    if (u >= 56) { t = 14 + ((0x199 >> (u - 56)) & 1); i = (u - 56) / 2; }
    uint8_t* w = p.unit[u];
    w[0] = (uint8_t)t; w[1] = (uint8_t)i; w[2] = (uint8_t)(i * K3_NS); w[3] = (uint8_t)(((u >= 56) ? 5 : 4) * K3_NS);
  }
}

extern "C" void kernel_launch(void* const* d_in, const int* in_sizes, int n_in, void* d_out, int out_size) {
  const bf16* x = (const bf16*)d_in[0];
  const bf16* wqkv = (const bf16*)d_in[1];
  const bf16* wo = (const bf16*)d_in[2];
  const bf16* ckv = (const bf16*)d_in[4];
  const bf16* w_q = (const bf16*)d_in[5];
  const bf16* w_uk = (const bf16*)d_in[6];
  const bf16* w_uv = (const bf16*)d_in[7];
  const bf16* w_o = (const bf16*)d_in[8];
  const bf16* gate_w = (const bf16*)d_in[9];

  EncFn enc = nullptr;
  cudaDriverEntryPointQueryResult qr;
  cudaGetDriverEntryPoint("cuTensorMapEncodeTiled", (void**)&enc, cudaEnableDefault, &qr);
  void *pK, *pV, *pCtx, *pQA;
  cudaGetSymbolAddress(&pQA, g_QKVA);
  cudaGetSymbolAddress(&pK, g_K);
  cudaGetSymbolAddress(&pV, g_V);
  cudaGetSymbolAddress(&pCtx, g_ctx);

  static Params p;
  enc2d(enc, &p.tmA[0], ckv, DC, S_LEN, 64, 128);
  enc2d(enc, &p.tmA[1], x, DM, S_LEN, 64, 128);
  enc3d(enc, &p.tmW[0], w_uk, HDIM, DC, 16, 4);
  enc3d(enc, &p.tmW[1], w_uv, HDIM, DC, 16, 4);
  enc3d(enc, &p.tmW[2], wqkv, NQKVA, DM, 16, 4);
  enc3d(enc, &p.tmW[3], w_q, HDIM, DM, 16, 4);
  build_k1_jobs(p);
  enc2d(enc, &p.tmK, pK, HDIM, S_LEN, 64, 128);
  enc2d(enc, &p.tmV, pV, HDIM, S_LEN, 64, 128);
  build_k2_items(p);
  build_k3_units(p);
  for (int i = 0; i < 3; i++) {
    const cuuint64_t ld = (i < 2 ? NQKVA : KCAT) * 2, nch = (i < 2) ? 27 : 9;
    cuuint64_t gd[4] = {64, S_LEN / 2, i ? 2 : nch, i ? nch : 2}, gs[3] = {2 * ld, i ? ld : 128, i ? 128 : ld};
    cuuint32_t bx[4] = {64, i ? 8u : 16u, i ? 2u : 9u, i ? 9u : 2u}, es[4] = {1, 1, 1, 1};
    enc(&p.tmL[i], CU_TENSOR_MAP_DATA_TYPE_BFLOAT16, 4, (i < 2) ? pQA : (void*)((bf16*)pCtx + HDIM), gd, gs, bx, es, CU_TENSOR_MAP_INTERLEAVE_NONE,
        CU_TENSOR_MAP_SWIZZLE_128B, CU_TENSOR_MAP_L2_PROMOTION_L2_256B, CU_TENSOR_MAP_FLOAT_OOB_FILL_NONE);
  }
  enc2d(enc, &p.tmC, pCtx, KCAT, S_LEN, 64, 128);
  enc3d(enc, &p.tmO[0], w_o, DM, HDIM, 32, 4);
  enc3d(enc, &p.tmO[1], wo, DM, DM, 32, 4);
  enc2d(enc, &p.tmOt[0], w_o, DM, HDIM, 32, 32, CU_TENSOR_MAP_SWIZZLE_64B);
  enc2d(enc, &p.tmOt[1], wo, DM, DM, 32, 32, CU_TENSOR_MAP_SWIZZLE_64B);
  enc2d(enc, &p.tmR[0], d_out, DM, S_LEN, 64, 16);
  enc2d(enc, &p.tmR[1], d_out, DM, S_LEN, 32, 16, CU_TENSOR_MAP_SWIZZLE_64B);

  cudaFuncSetAttribute(fused_kernel, cudaFuncAttributeMaxDynamicSharedMemorySize, SMEM_BYTES);
  fused_kernel<<<NCLUSTER * 2, 384, SMEM_BYTES>>>(p, x, gate_w, (bf16*)d_out);
}
```

```cpp
#include <cuda_runtime.h>
#include <cuda_bf16.h>
#include <cuda.h>
#include <stdint.h>

typedef __nv_bfloat16 bf16;

constexpr int S_LEN = 2048, DM = 576, DC = 512, HDIM = 4096, NQKVA = 1728, KCAT = 4672;
constexpr int NCLUSTER = 66;

__device__ __align__(1024) bf16 g_K[S_LEN * HDIM];
__device__ __align__(1024) bf16 g_V[S_LEN * HDIM];
__device__ __align__(1024) bf16 g_QKVA[S_LEN * NQKVA + 64];
__device__ __align__(1024) bf16 g_ctx[S_LEN * KCAT];
__device__ float g_gate[S_LEN];
__device__ __align__(16) unsigned int g_sync[400];
constexpr int F_QKVA = 0, F_HP = 16, F_CTX = 32, F_OA = 48, F_CLM = 64, F_GATE = 96, F_TICK = 97, F_DONE = 98, F_XCH = 128, F_EPOCH = 384;

__device__ __forceinline__ uint32_t smem_u32(const void* p) { return (uint32_t)__cvta_generic_to_shared(p); }
__device__ __forceinline__ void mbar_init(uint32_t a, uint32_t c) {
  asm volatile("mbarrier.init.shared::cta.b64 [%0], %1;" ::"r"(a), "r"(c));
}
__device__ __forceinline__ void mbar_expect(uint32_t a, uint32_t b) {
  asm volatile("mbarrier.arrive.expect_tx.shared::cta.b64 _, [%0], %1;" ::"r"(a), "r"(b) : "memory");
}
#define TS(k, i)
#define TSC(k, i)
#define TSM(k)
#define BSEG(i)
#define TB(k)
#define TRC(fl)
#define TCK(i)
#define TP(i)
#define SPIN_LIMIT "4194304"
__device__ __forceinline__ void mbar_wait(uint32_t a, uint32_t parity) {
  asm volatile(
      "{\n.reg .pred p;\n.reg .u32 n;\n"
      "mbarrier.try_wait.parity.shared::cta.b64 p, [%0], %1;\n"
      "@p bra DONE;\n"
      "mov.u32 n, 0;\n"
      "LOOP:\n"
      "mbarrier.try_wait.parity.shared::cta.b64 p, [%0], %1;\n"
      "@p bra DONE;\n"
      "add.u32 n, n, 1;\n"
      "setp.lt.u32 p, n, " SPIN_LIMIT ";\n"
      "@p bra LOOP;\n"
      "DONE:\n}" ::"r"(a), "r"(parity) : "memory");
}
template <int NS>
__device__ __forceinline__ void mbar_wait_ns(uint32_t a, uint32_t parity) {
  asm volatile(
      "{\n.reg .pred p;\n.reg .u32 n;\n"
      "mov.u32 n, 0;\n"
      "LOOP:\n"
      "mbarrier.try_wait.parity.shared::cta.b64 p, [%0], %1, %2;\n"
      "@p bra DONE;\n"
      "add.u32 n, n, 1;\n"
      "setp.lt.u32 p, n, " SPIN_LIMIT ";\n"
      "@p bra LOOP;\n"
      "DONE:\n}" ::"r"(a), "r"(parity), "n"(NS) : "memory");
}
__device__ __forceinline__ void mbar_wait2(uint32_t a, uint32_t pa, uint32_t b, uint32_t pb) {
  asm volatile(
      "{\n.reg .pred p, q;\n.reg .u32 n;\n"
      "mov.u32 n, 0;\n"
      "LOOP:\n"
      "mbarrier.try_wait.parity.shared::cta.b64 p, [%0], %1;\n"
      "mbarrier.try_wait.parity.shared::cta.b64 q, [%2], %3;\n"
      "add.u32 n, n, 1;\n"
      "and.pred p, p, q;\n"
      "setp.lt.and.u32 p, n, " SPIN_LIMIT ", !p;\n"
      "@p bra LOOP;\n"
      "}" ::"r"(a), "r"(pa), "r"(b), "r"(pb) : "memory");
}
__device__ __forceinline__ uint32_t mbar_test(uint32_t a, uint32_t parity) {
  uint32_t r;
  asm volatile("{\n.reg .pred p;\nmbarrier.test_wait.parity.shared::cta.b64 p, [%1], %2;\nselp.u32 %0, 1, 0, p;\n}" : "=r"(r) : "r"(a), "r"(parity) : "memory");
  return r;
}
__device__ __forceinline__ void mbar_arrive(uint32_t a) {
  asm volatile("mbarrier.arrive.shared::cta.b64 _, [%0];" ::"r"(a) : "memory");
}
__device__ __forceinline__ void mbar_arrive_cluster(uint32_t a, uint32_t cta) {
  asm volatile("{\n.reg .b32 r;\nmapa.shared::cluster.u32 r, %0, %1;\nmbarrier.arrive.shared::cluster.b64 _, [r];\n}" ::"r"(a),
               "r"(cta) : "memory");
}
__device__ __forceinline__ void mbar_arrive_cluster_if(uint32_t a, uint32_t cta, bool pred) {
  asm volatile("{\n.reg .b32 r;\n.reg .pred p;\nsetp.ne.u32 p, %2, 0;\nmapa.shared::cluster.u32 r, %0, %1;\n@p mbarrier.arrive.shared::cluster.b64 _, [r];\n}" ::"r"(a),
               "r"(cta), "r"((uint32_t)pred) : "memory");
}
__device__ __forceinline__ void anchor(float v, uint32_t pred) {
  asm volatile("{\n.reg .pred p;\nsetp.ne.u32 p, %1, 0;\n@p st.shared.f32 [%1], %0;\n}" ::"f"(v), "r"(pred) : "memory");
}
__device__ __forceinline__ void mbar_arrive_if(uint32_t a, bool pred) {
  asm volatile("{\n.reg .pred p;\nsetp.ne.u32 p, %1, 0;\n@p mbarrier.arrive.shared::cta.b64 _, [%0];\n}" ::"r"(a), "r"((uint32_t)pred) : "memory");
}
__device__ __forceinline__ void tma2d(uint32_t dst, const CUtensorMap* m, uint32_t bar, int c0, int c1) {
  asm volatile("cp.async.bulk.tensor.2d.shared::cluster.global.mbarrier::complete_tx::bytes [%0], [%1, {%3, %4}], [%2];" ::"r"(dst),
               "l"(m), "r"(bar), "r"(c0), "r"(c1) : "memory");
}
__device__ __forceinline__ void tma2d_mc(uint32_t dst, const CUtensorMap* m, uint32_t bar, int c0, int c1, uint16_t mask) {
  asm volatile(
      "cp.async.bulk.tensor.2d.shared::cluster.global.mbarrier::complete_tx::bytes.multicast::cluster [%0], [%1, {%3, %4}], [%2], %5;" ::"r"(dst),
      "l"(m), "r"(bar), "r"(c0), "r"(c1), "h"(mask) : "memory");
}
__device__ __forceinline__ void tma3d_mc(uint32_t dst, const CUtensorMap* m, uint32_t bar, int c0, int c1, int c2, uint16_t mask) {
  asm volatile(
      "cp.async.bulk.tensor.3d.shared::cluster.global.mbarrier::complete_tx::bytes.multicast::cluster [%0], [%1, {%3, %4, %5}], [%2], %6;" ::"r"(dst),
      "l"(m), "r"(bar), "r"(c0), "r"(c1), "r"(c2), "h"(mask) : "memory");
}
__device__ __forceinline__ void tma3d(uint32_t dst, const CUtensorMap* m, uint32_t bar, int c0, int c1, int c2) {
  asm volatile(
      "cp.async.bulk.tensor.3d.shared::cluster.global.mbarrier::complete_tx::bytes [%0], [%1, {%3, %4, %5}], [%2];" ::"r"(dst),
      "l"(m), "r"(bar), "r"(c0), "r"(c1), "r"(c2) : "memory");
}
__device__ __forceinline__ void tma_pf2d(const CUtensorMap* m, int c0, int c1) {
  asm volatile("cp.async.bulk.prefetch.tensor.2d.L2.global [%0, {%1, %2}];" ::"l"(m), "r"(c0), "r"(c1) : "memory");
}
__device__ __forceinline__ void tma_pf3d(const CUtensorMap* m, int c0, int c1, int c2) {
  asm volatile("cp.async.bulk.prefetch.tensor.3d.L2.global [%0, {%1, %2, %3}];" ::"l"(m), "r"(c0), "r"(c1), "r"(c2) : "memory");
}
__device__ __forceinline__ void prefetch_tmap(const CUtensorMap* m) {
  asm volatile("prefetch.tensormap [%0];" ::"l"(m) : "memory");
}
__device__ __forceinline__ void cluster_arrive() { asm volatile("barrier.cluster.arrive.relaxed.aligned;" ::: "memory"); }
__device__ __forceinline__ void cluster_wait() { asm volatile("barrier.cluster.wait.aligned;" ::: "memory"); }
__device__ __forceinline__ void cluster_sync() {
  cluster_arrive();
  cluster_wait();
}
__device__ __forceinline__ uint32_t cluster_rank() {
  uint32_t r;
  asm volatile("mov.u32 %0, %%cluster_ctarank;" : "=r"(r));
  return r;
}
__device__ __forceinline__ bool elect_one() {
  uint32_t p;
  asm volatile("{\n.reg .pred q;\nelect.sync _|q, 0xffffffff;\nselp.u32 %0, 1, 0, q;\n}" : "=r"(p));
  return p;
}
__device__ __forceinline__ void ldsm_x4(uint32_t& r0, uint32_t& r1, uint32_t& r2, uint32_t& r3, uint32_t addr) {
  asm volatile("ldmatrix.sync.aligned.m8n8.x4.shared.b16 {%0, %1, %2, %3}, [%4];" : "=r"(r0), "=r"(r1), "=r"(r2), "=r"(r3) : "r"(addr) : "memory");
}
__device__ __forceinline__ void wg_fence() { asm volatile("wgmma.fence.sync.aligned;" ::: "memory"); }
__device__ __forceinline__ void wg_commit() { asm volatile("wgmma.commit_group.sync.aligned;" ::: "memory"); }
template <int N>
__device__ __forceinline__ void wg_wait() { asm volatile("wgmma.wait_group.sync.aligned %0;" ::"n"(N) : "memory"); }
template <int N>
__device__ __forceinline__ void reg_alloc() { asm volatile("setmaxnreg.inc.sync.aligned.u32 %0;" ::"n"(N)); }
template <int N>
__device__ __forceinline__ void reg_dealloc() { asm volatile("setmaxnreg.dec.sync.aligned.u32 %0;" ::"n"(N)); }
__device__ __forceinline__ void bar_sync(int id, int n) { asm volatile("bar.sync %0, %1;" ::"r"(id), "r"(n) : "memory"); }
__device__ __forceinline__ void bar_arrive(int id, int n) { asm volatile("bar.arrive %0, %1;" ::"r"(id), "r"(n) : "memory"); }
template <int NT>
__device__ __forceinline__ void fence_regs(float (&d)[NT]) {
#pragma unroll
  for (int i = 0; i < NT; i++) asm volatile("" : "+f"(d[i])::"memory");
}
template <int NT>
__device__ __forceinline__ void fence_regs(uint32_t (&d)[NT]) {
#pragma unroll
  for (int i = 0; i < NT; i++) asm volatile("" : "+r"(d[i])::"memory");
}
__device__ __forceinline__ uint64_t make_desc(uint32_t saddr, uint32_t lbo, uint32_t sbo, uint32_t layout) {
  return (uint64_t)((saddr & 0x3FFFF) >> 4) | ((uint64_t)(lbo >> 4) << 16) | ((uint64_t)(sbo >> 4) << 32) | ((uint64_t)layout << 62);
}
__device__ __forceinline__ uint32_t pack_bf16(float lo, float hi) {
  uint32_t r;
  asm("cvt.rn.bf16x2.f32 %0, %1, %2;" : "=r"(r) : "f"(hi), "f"(lo));
  return r;
}
__device__ __forceinline__ float ex2(float x) {
  float r;
  asm("ex2.approx.ftz.f32 %0, %1;" : "=f"(r) : "f"(x));
  return r;
}
__device__ __forceinline__ void st_v4(void* p, uint32_t a, uint32_t b, uint32_t c, uint32_t d) {
#define ST_MOD ".cs"
  asm volatile("st.global" ST_MOD ".v4.b32 [%0], {%1, %2, %3, %4};" ::"l"(p), "r"(a), "r"(b), "r"(c), "r"(d) : "memory");
}
#define STA_MOD ".cs"
__device__ __forceinline__ void st_v4a(void* p, uint32_t a, uint32_t b, uint32_t c, uint32_t d) {
  asm volatile("st.global" STA_MOD ".v4.b32 [%0], {%1, %2, %3, %4};" ::"l"(p), "r"(a), "r"(b), "r"(c), "r"(d) : "memory");
}
template <typename T>
__device__ __forceinline__ T* ptr_add(T* base, uint32_t bytes) {
  uint64_t r;
  asm volatile("{\n.reg .u32 l, h;\nmov.b64 {l, h}, %1;\nadd.cc.u32 l, l, %2;\naddc.u32 h, h, 0;\nmov.b64 %0, {l, h};\n}" : "=l"(r) : "l"(base), "r"(bytes));
  return reinterpret_cast<T*>(r);
}
__device__ __forceinline__ float bf_lo(uint32_t v) { return __uint_as_float(v << 16); }
__device__ __forceinline__ float bf_hi(uint32_t v) { return __uint_as_float(v & 0xFFFF0000u); }

__device__ __forceinline__ void quad_transpose(uint32_t& a0, uint32_t& a1, uint32_t& a2, uint32_t& a3, int q) {
  const bool o1 = q & 1, o2 = q & 2;
  uint32_t t0 = o1 ? a0 : a1, t1 = o1 ? a2 : a3;
  t0 = __shfl_xor_sync(0xffffffffu, t0, 1);
  t1 = __shfl_xor_sync(0xffffffffu, t1, 1);
  if (o1) { a0 = t0; a2 = t1; } else { a1 = t0; a3 = t1; }
  t0 = o2 ? a0 : a2;
  t1 = o2 ? a1 : a3;
  t0 = __shfl_xor_sync(0xffffffffu, t0, 2);
  t1 = __shfl_xor_sync(0xffffffffu, t1, 2);
  if (o2) { a0 = t0; a1 = t1; } else { a2 = t0; a3 = t1; }
}

template<int TB, int OFF, int NT>
__device__ __forceinline__ void wgmma_ss_n256(float (&d)[NT], uint64_t da, uint64_t db, int scale_d) {
  asm volatile("{\n.reg .pred p;\nsetp.ne.b32 p, %130, 0;\n"
    "wgmma.mma_async.sync.aligned.m64n256k16.f32.bf16.bf16 {%0, %1, %2, %3, %4, %5, %6, %7, %8, %9, %10, %11, %12, %13, %14, %15, %16, %17, %18, %19, %20, %21, %22, %23, %24, %25, %26, %27, %28, %29, %30, %31, %32, %33, %34, %35, %36, %37, %38, %39, %40, %41, %42, %43, %44, %45, %46, %47, %48, %49, %50, %51, %52, %53, %54, %55, %56, %57, %58, %59, %60, %61, %62, %63, %64, %65, %66, %67, %68, %69, %70, %71, %72, %73, %74, %75, %76, %77, %78, %79, %80, %81, %82, %83, %84, %85, %86, %87, %88, %89, %90, %91, %92, %93, %94, %95, %96, %97, %98, %99, %100, %101, %102, %103, %104, %105, %106, %107, %108, %109, %110, %111, %112, %113, %114, %115, %116, %117, %118, %119, %120, %121, %122, %123, %124, %125, %126, %127}, %128, %129, p, 1, 1, 0, %131;\n}\n"
    : "+f"(d[OFF+0]), "+f"(d[OFF+1]), "+f"(d[OFF+2]), "+f"(d[OFF+3]), "+f"(d[OFF+4]), "+f"(d[OFF+5]), "+f"(d[OFF+6]), "+f"(d[OFF+7]), "+f"(d[OFF+8]), "+f"(d[OFF+9]), "+f"(d[OFF+10]), "+f"(d[OFF+11]), "+f"(d[OFF+12]), "+f"(d[OFF+13]), "+f"(d[OFF+14]), "+f"(d[OFF+15]), "+f"(d[OFF+16]), "+f"(d[OFF+17]), "+f"(d[OFF+18]), "+f"(d[OFF+19]), "+f"(d[OFF+20]), "+f"(d[OFF+21]), "+f"(d[OFF+22]), "+f"(d[OFF+23]), "+f"(d[OFF+24]), "+f"(d[OFF+25]), "+f"(d[OFF+26]), "+f"(d[OFF+27]), "+f"(d[OFF+28]), "+f"(d[OFF+29]), "+f"(d[OFF+30]), "+f"(d[OFF+31]), "+f"(d[OFF+32]), "+f"(d[OFF+33]), "+f"(d[OFF+34]), "+f"(d[OFF+35]), "+f"(d[OFF+36]), "+f"(d[OFF+37]), "+f"(d[OFF+38]), "+f"(d[OFF+39]), "+f"(d[OFF+40]), "+f"(d[OFF+41]), "+f"(d[OFF+42]), "+f"(d[OFF+43]), "+f"(d[OFF+44]), "+f"(d[OFF+45]), "+f"(d[OFF+46]), "+f"(d[OFF+47]), "+f"(d[OFF+48]), "+f"(d[OFF+49]), "+f"(d[OFF+50]), "+f"(d[OFF+51]), "+f"(d[OFF+52]), "+f"(d[OFF+53]), "+f"(d[OFF+54]), "+f"(d[OFF+55]), "+f"(d[OFF+56]), "+f"(d[OFF+57]), "+f"(d[OFF+58]), "+f"(d[OFF+59]), "+f"(d[OFF+60]), "+f"(d[OFF+61]), "+f"(d[OFF+62]), "+f"(d[OFF+63]), "+f"(d[OFF+64]), "+f"(d[OFF+65]), "+f"(d[OFF+66]), "+f"(d[OFF+67]), "+f"(d[OFF+68]), "+f"(d[OFF+69]), "+f"(d[OFF+70]), "+f"(d[OFF+71]), "+f"(d[OFF+72]), "+f"(d[OFF+73]), "+f"(d[OFF+74]), "+f"(d[OFF+75]), "+f"(d[OFF+76]), "+f"(d[OFF+77]), "+f"(d[OFF+78]), "+f"(d[OFF+79]), "+f"(d[OFF+80]), "+f"(d[OFF+81]), "+f"(d[OFF+82]), "+f"(d[OFF+83]), "+f"(d[OFF+84]), "+f"(d[OFF+85]), "+f"(d[OFF+86]), "+f"(d[OFF+87]), "+f"(d[OFF+88]), "+f"(d[OFF+89]), "+f"(d[OFF+90]), "+f"(d[OFF+91]), "+f"(d[OFF+92]), "+f"(d[OFF+93]), "+f"(d[OFF+94]), "+f"(d[OFF+95]), "+f"(d[OFF+96]), "+f"(d[OFF+97]), "+f"(d[OFF+98]), "+f"(d[OFF+99]), "+f"(d[OFF+100]), "+f"(d[OFF+101]), "+f"(d[OFF+102]), "+f"(d[OFF+103]), "+f"(d[OFF+104]), "+f"(d[OFF+105]), "+f"(d[OFF+106]), "+f"(d[OFF+107]), "+f"(d[OFF+108]), "+f"(d[OFF+109]), "+f"(d[OFF+110]), "+f"(d[OFF+111]), "+f"(d[OFF+112]), "+f"(d[OFF+113]), "+f"(d[OFF+114]), "+f"(d[OFF+115]), "+f"(d[OFF+116]), "+f"(d[OFF+117]), "+f"(d[OFF+118]), "+f"(d[OFF+119]), "+f"(d[OFF+120]), "+f"(d[OFF+121]), "+f"(d[OFF+122]), "+f"(d[OFF+123]), "+f"(d[OFF+124]), "+f"(d[OFF+125]), "+f"(d[OFF+126]), "+f"(d[OFF+127])
    : "l"(da), "l"(db), "r"(scale_d), "n"(TB));
}
template<int TB, int OFF, int NT>
__device__ __forceinline__ void wgmma_ss_n32(float (&d)[NT], uint64_t da, uint64_t db, int scale_d) {
  asm volatile("{\n.reg .pred p;\nsetp.ne.b32 p, %18, 0;\n"
    "wgmma.mma_async.sync.aligned.m64n32k16.f32.bf16.bf16 {%0, %1, %2, %3, %4, %5, %6, %7, %8, %9, %10, %11, %12, %13, %14, %15}, %16, %17, p, 1, 1, 0, %19;\n}\n"
    : "+f"(d[OFF+0]), "+f"(d[OFF+1]), "+f"(d[OFF+2]), "+f"(d[OFF+3]), "+f"(d[OFF+4]), "+f"(d[OFF+5]), "+f"(d[OFF+6]), "+f"(d[OFF+7]), "+f"(d[OFF+8]), "+f"(d[OFF+9]), "+f"(d[OFF+10]), "+f"(d[OFF+11]), "+f"(d[OFF+12]), "+f"(d[OFF+13]), "+f"(d[OFF+14]), "+f"(d[OFF+15])
    : "l"(da), "l"(db), "r"(scale_d), "n"(TB));
}
template<int TB, int OFF, int NT>
__device__ __forceinline__ void wgmma_rs_n128(float (&d)[NT], uint32_t a0, uint32_t a1, uint32_t a2, uint32_t a3, uint64_t db, int scale_d) {
  asm volatile("{\n.reg .pred p;\nsetp.ne.b32 p, %69, 0;\n"
    "wgmma.mma_async.sync.aligned.m64n128k16.f32.bf16.bf16 {%0, %1, %2, %3, %4, %5, %6, %7, %8, %9, %10, %11, %12, %13, %14, %15, %16, %17, %18, %19, %20, %21, %22, %23, %24, %25, %26, %27, %28, %29, %30, %31, %32, %33, %34, %35, %36, %37, %38, %39, %40, %41, %42, %43, %44, %45, %46, %47, %48, %49, %50, %51, %52, %53, %54, %55, %56, %57, %58, %59, %60, %61, %62, %63}, {%64, %65, %66, %67}, %68, p, 1, 1, %70;\n}\n"
    : "+f"(d[OFF+0]), "+f"(d[OFF+1]), "+f"(d[OFF+2]), "+f"(d[OFF+3]), "+f"(d[OFF+4]), "+f"(d[OFF+5]), "+f"(d[OFF+6]), "+f"(d[OFF+7]), "+f"(d[OFF+8]), "+f"(d[OFF+9]), "+f"(d[OFF+10]), "+f"(d[OFF+11]), "+f"(d[OFF+12]), "+f"(d[OFF+13]), "+f"(d[OFF+14]), "+f"(d[OFF+15]), "+f"(d[OFF+16]), "+f"(d[OFF+17]), "+f"(d[OFF+18]), "+f"(d[OFF+19]), "+f"(d[OFF+20]), "+f"(d[OFF+21]), "+f"(d[OFF+22]), "+f"(d[OFF+23]), "+f"(d[OFF+24]), "+f"(d[OFF+25]), "+f"(d[OFF+26]), "+f"(d[OFF+27]), "+f"(d[OFF+28]), "+f"(d[OFF+29]), "+f"(d[OFF+30]), "+f"(d[OFF+31]), "+f"(d[OFF+32]), "+f"(d[OFF+33]), "+f"(d[OFF+34]), "+f"(d[OFF+35]), "+f"(d[OFF+36]), "+f"(d[OFF+37]), "+f"(d[OFF+38]), "+f"(d[OFF+39]), "+f"(d[OFF+40]), "+f"(d[OFF+41]), "+f"(d[OFF+42]), "+f"(d[OFF+43]), "+f"(d[OFF+44]), "+f"(d[OFF+45]), "+f"(d[OFF+46]), "+f"(d[OFF+47]), "+f"(d[OFF+48]), "+f"(d[OFF+49]), "+f"(d[OFF+50]), "+f"(d[OFF+51]), "+f"(d[OFF+52]), "+f"(d[OFF+53]), "+f"(d[OFF+54]), "+f"(d[OFF+55]), "+f"(d[OFF+56]), "+f"(d[OFF+57]), "+f"(d[OFF+58]), "+f"(d[OFF+59]), "+f"(d[OFF+60]), "+f"(d[OFF+61]), "+f"(d[OFF+62]), "+f"(d[OFF+63])
    : "r"(a0), "r"(a1), "r"(a2), "r"(a3), "l"(db), "r"(scale_d), "n"(TB));
}
template<int TB, int OFF, int NT>
__device__ __forceinline__ void wgmma_rs_n256(float (&d)[NT], uint32_t a0, uint32_t a1, uint32_t a2, uint32_t a3, uint64_t db, int scale_d) {
  asm volatile("{\n.reg .pred p;\nsetp.ne.b32 p, %133, 0;\n"
    "wgmma.mma_async.sync.aligned.m64n256k16.f32.bf16.bf16 {%0, %1, %2, %3, %4, %5, %6, %7, %8, %9, %10, %11, %12, %13, %14, %15, %16, %17, %18, %19, %20, %21, %22, %23, %24, %25, %26, %27, %28, %29, %30, %31, %32, %33, %34, %35, %36, %37, %38, %39, %40, %41, %42, %43, %44, %45, %46, %47, %48, %49, %50, %51, %52, %53, %54, %55, %56, %57, %58, %59, %60, %61, %62, %63, %64, %65, %66, %67, %68, %69, %70, %71, %72, %73, %74, %75, %76, %77, %78, %79, %80, %81, %82, %83, %84, %85, %86, %87, %88, %89, %90, %91, %92, %93, %94, %95, %96, %97, %98, %99, %100, %101, %102, %103, %104, %105, %106, %107, %108, %109, %110, %111, %112, %113, %114, %115, %116, %117, %118, %119, %120, %121, %122, %123, %124, %125, %126, %127}, {%128, %129, %130, %131}, %132, p, 1, 1, %134;\n}\n"
    : "+f"(d[OFF+0]), "+f"(d[OFF+1]), "+f"(d[OFF+2]), "+f"(d[OFF+3]), "+f"(d[OFF+4]), "+f"(d[OFF+5]), "+f"(d[OFF+6]), "+f"(d[OFF+7]), "+f"(d[OFF+8]), "+f"(d[OFF+9]), "+f"(d[OFF+10]), "+f"(d[OFF+11]), "+f"(d[OFF+12]), "+f"(d[OFF+13]), "+f"(d[OFF+14]), "+f"(d[OFF+15]), "+f"(d[OFF+16]), "+f"(d[OFF+17]), "+f"(d[OFF+18]), "+f"(d[OFF+19]), "+f"(d[OFF+20]), "+f"(d[OFF+21]), "+f"(d[OFF+22]), "+f"(d[OFF+23]), "+f"(d[OFF+24]), "+f"(d[OFF+25]), "+f"(d[OFF+26]), "+f"(d[OFF+27]), "+f"(d[OFF+28]), "+f"(d[OFF+29]), "+f"(d[OFF+30]), "+f"(d[OFF+31]), "+f"(d[OFF+32]), "+f"(d[OFF+33]), "+f"(d[OFF+34]), "+f"(d[OFF+35]), "+f"(d[OFF+36]), "+f"(d[OFF+37]), "+f"(d[OFF+38]), "+f"(d[OFF+39]), "+f"(d[OFF+40]), "+f"(d[OFF+41]), "+f"(d[OFF+42]), "+f"(d[OFF+43]), "+f"(d[OFF+44]), "+f"(d[OFF+45]), "+f"(d[OFF+46]), "+f"(d[OFF+47]), "+f"(d[OFF+48]), "+f"(d[OFF+49]), "+f"(d[OFF+50]), "+f"(d[OFF+51]), "+f"(d[OFF+52]), "+f"(d[OFF+53]), "+f"(d[OFF+54]), "+f"(d[OFF+55]), "+f"(d[OFF+56]), "+f"(d[OFF+57]), "+f"(d[OFF+58]), "+f"(d[OFF+59]), "+f"(d[OFF+60]), "+f"(d[OFF+61]), "+f"(d[OFF+62]), "+f"(d[OFF+63]), "+f"(d[OFF+64]), "+f"(d[OFF+65]), "+f"(d[OFF+66]), "+f"(d[OFF+67]), "+f"(d[OFF+68]), "+f"(d[OFF+69]), "+f"(d[OFF+70]), "+f"(d[OFF+71]), "+f"(d[OFF+72]), "+f"(d[OFF+73]), "+f"(d[OFF+74]), "+f"(d[OFF+75]), "+f"(d[OFF+76]), "+f"(d[OFF+77]), "+f"(d[OFF+78]), "+f"(d[OFF+79]), "+f"(d[OFF+80]), "+f"(d[OFF+81]), "+f"(d[OFF+82]), "+f"(d[OFF+83]), "+f"(d[OFF+84]), "+f"(d[OFF+85]), "+f"(d[OFF+86]), "+f"(d[OFF+87]), "+f"(d[OFF+88]), "+f"(d[OFF+89]), "+f"(d[OFF+90]), "+f"(d[OFF+91]), "+f"(d[OFF+92]), "+f"(d[OFF+93]), "+f"(d[OFF+94]), "+f"(d[OFF+95]), "+f"(d[OFF+96]), "+f"(d[OFF+97]), "+f"(d[OFF+98]), "+f"(d[OFF+99]), "+f"(d[OFF+100]), "+f"(d[OFF+101]), "+f"(d[OFF+102]), "+f"(d[OFF+103]), "+f"(d[OFF+104]), "+f"(d[OFF+105]), "+f"(d[OFF+106]), "+f"(d[OFF+107]), "+f"(d[OFF+108]), "+f"(d[OFF+109]), "+f"(d[OFF+110]), "+f"(d[OFF+111]), "+f"(d[OFF+112]), "+f"(d[OFF+113]), "+f"(d[OFF+114]), "+f"(d[OFF+115]), "+f"(d[OFF+116]), "+f"(d[OFF+117]), "+f"(d[OFF+118]), "+f"(d[OFF+119]), "+f"(d[OFF+120]), "+f"(d[OFF+121]), "+f"(d[OFF+122]), "+f"(d[OFF+123]), "+f"(d[OFF+124]), "+f"(d[OFF+125]), "+f"(d[OFF+126]), "+f"(d[OFF+127])
    : "r"(a0), "r"(a1), "r"(a2), "r"(a3), "l"(db), "r"(scale_d), "n"(TB));
}
template<int TB, int OFF, int NT>
__device__ __forceinline__ void wgmma_rs_n32(float (&d)[NT], uint32_t a0, uint32_t a1, uint32_t a2, uint32_t a3, uint64_t db, int scale_d) {
  asm volatile("{\n.reg .pred p;\nsetp.ne.b32 p, %21, 0;\n"
    "wgmma.mma_async.sync.aligned.m64n32k16.f32.bf16.bf16 {%0, %1, %2, %3, %4, %5, %6, %7, %8, %9, %10, %11, %12, %13, %14, %15}, {%16, %17, %18, %19}, %20, p, 1, 1, %22;\n}\n"
    : "+f"(d[OFF+0]), "+f"(d[OFF+1]), "+f"(d[OFF+2]), "+f"(d[OFF+3]), "+f"(d[OFF+4]), "+f"(d[OFF+5]), "+f"(d[OFF+6]), "+f"(d[OFF+7]), "+f"(d[OFF+8]), "+f"(d[OFF+9]), "+f"(d[OFF+10]), "+f"(d[OFF+11]), "+f"(d[OFF+12]), "+f"(d[OFF+13]), "+f"(d[OFF+14]), "+f"(d[OFF+15])
    : "r"(a0), "r"(a1), "r"(a2), "r"(a3), "l"(db), "r"(scale_d), "n"(TB));
}

__device__ __forceinline__ void wait_flag(const unsigned int* f, uint32_t target) {
  uint32_t v;
#pragma unroll 1
  for (uint32_t spins = 0; spins < (1u << 22); spins++) {
    asm volatile("ld.acquire.gpu.global.u32 %0, [%1];" : "=r"(v) : "l"(f) : "memory");
    if (v >= target) break;
    __nanosleep(100);
  }
}
__device__ __forceinline__ uint32_t ld_and2(const unsigned int* f) {
  uint32_t v;
  asm volatile("{\n.reg .b64 t;\n.reg .b32 a, b;\nld.acquire.gpu.global.b64 t, [%1];\nmov.b64 {a, b}, t;\nand.b32 %0, a, b;\n}" : "=r"(v) : "l"(f) : "memory");
  return v;
}
__device__ __forceinline__ uint32_t lds32(uint32_t a) {
  uint32_t v;
  asm volatile("ld.shared.u32 %0, [%1];" : "=r"(v) : "r"(a) : "memory");
  return v;
}
__device__ __forceinline__ float gate_row(int row, int lane, const bf16* __restrict__ x, const bf16* __restrict__ gate_w) {
  const uint32_t* xr = reinterpret_cast<const uint32_t*>(x + (size_t)row * DM);
  const uint32_t* gw2 = reinterpret_cast<const uint32_t*>(gate_w);
  float gs = 0.f;
#pragma unroll
  for (int i = 0; i < 9; i++) {
    const uint32_t a = __ldg(xr + lane + 32 * i), b = __ldg(gw2 + lane + 32 * i);
    gs = fmaf(bf_lo(a), bf_lo(b), gs);
    gs = fmaf(bf_hi(a), bf_hi(b), gs);
  }
#pragma unroll
  for (int o = 16; o; o >>= 1) gs += __shfl_xor_sync(0xffffffffu, gs, o);
  const float g = 1.f / (1.f + __expf(-gs));
  if (lane == 0) g_gate[row] = g;
  return g;
}
constexpr uint32_t LQ = 36864, LV = 55296;
__device__ __forceinline__ void mma16(float (&c)[4], uint32_t a0, uint32_t a1, uint32_t a2, uint32_t a3, uint32_t b0, uint32_t b1) {
  asm("mma.sync.aligned.m16n8k16.row.col.f32.bf16.bf16.f32 {%0, %1, %2, %3}, {%4, %5, %6, %7}, {%8, %9}, {%0, %1, %2, %3};"
      : "+f"(c[0]), "+f"(c[1]), "+f"(c[2]), "+f"(c[3]) : "r"(a0), "r"(a1), "r"(a2), "r"(a3), "r"(b0), "r"(b1));
}
__device__ __forceinline__ void mma8(float (&c)[4], uint32_t a0, uint32_t a1, uint32_t b0) {
  asm("mma.sync.aligned.m16n8k8.row.col.f32.bf16.bf16.f32 {%0, %1, %2, %3}, {%4, %5}, {%6}, {%0, %1, %2, %3};"
      : "+f"(c[0]), "+f"(c[1]), "+f"(c[2]), "+f"(c[3]) : "r"(a0), "r"(a1), "r"(b0));
}
template <typename F>
__device__ __forceinline__ void local_attn(int lr0, int warp_g, uint32_t sL, uint32_t bL, uint32_t bL2, int lane, float g0, float g1, F st) {
  const float scale_l2 = 0.23570226039551584f * 1.4426950408889634f;
  const int g = lane >> 2, t = lane & 3;
  const bool lo0 = 2 * t > g, lo1 = 2 * t + 1 > g;
  const bool ok0 = lr0 > 0 || !lo0, ok1 = lr0 > 0 || !lo1;
  const uint32_t mlo = (lo0 ? 0xFFFFu : 0u) | (lo1 ? 0xFFFF0000u : 0u);
  uint32_t ad[9], k[9][4], qf[9][2], pe[4], po[4];
#pragma unroll
  for (int c = 0; c < 9; c++) {
    const uint32_t ch = warp_g * 9 + c;
    ad[c] = sL + (lane >> 4) * 18432 + (lane & 15) * 128 + ((ch >> 3) << 11) + (((ch ^ lane) & 7) << 4);
  }
  st(0, 0u); st(1, 0u);
  mbar_wait(bL, 0);
  if (warp_g == 0) TS(1, 6);
#pragma unroll
  for (int c = 0; c < 9; c++) {
    asm volatile("ldmatrix.sync.aligned.m8n8.x2.shared.b16 {%0, %1}, [%2];" : "=r"(qf[c][0]), "=r"(qf[c][1]) : "r"(ad[c] + LQ) : "memory");
    ldsm_x4(k[c][0], k[c][1], k[c][2], k[c][3], ad[c]);
  }
  st(2, k[0][0]); st(3, k[8][0]);
#pragma unroll
  for (int i = 0; i < 4; i++) {
    const uint32_t q0 = (t >= i) ? qf[2 * i][0] : 0u, q1 = (t >= i) ? qf[2 * i][1] : 0u;
    const uint32_t q4 = (t <= i) ? qf[2 * i + 2][0] : 0u, q5 = (t <= i) ? qf[2 * i + 2][1] : 0u;
    float c[4][4];
#pragma unroll
    for (int T = 0; T < 4; T++) {
#pragma unroll
      for (int j = 0; j < 4; j++) c[T][j] = 0.f;
      mma16(c[T], q0, q1, qf[2 * i + 1][0], qf[2 * i + 1][1], k[2 * i][T], k[2 * i + 1][T]);
      mma8(c[T], q4, q5, k[2 * i + 2][T]);
    }
    const float e0 = ok0 ? (lo0 ? c[0][0] : c[1][0]) : -INFINITY, e1 = ok1 ? (lo1 ? c[0][1] : c[1][1]) : -INFINITY;
    const float o0 = ok0 ? (lo0 ? c[2][2] : c[3][2]) : -INFINITY, o1 = ok1 ? (lo1 ? c[2][3] : c[3][3]) : -INFINITY;
    float me = fmaxf(e0, e1), mo = fmaxf(o0, o1);
    me = fmaxf(me, __shfl_xor_sync(0xffffffffu, me, 1));
    mo = fmaxf(mo, __shfl_xor_sync(0xffffffffu, mo, 1));
    me = fmaxf(me, __shfl_xor_sync(0xffffffffu, me, 2)) * scale_l2;
    mo = fmaxf(mo, __shfl_xor_sync(0xffffffffu, mo, 2)) * scale_l2;
    const float w0 = ex2(fmaf(e0, scale_l2, -me)), w1 = ex2(fmaf(e1, scale_l2, -me));
    const float w2 = ex2(fmaf(o0, scale_l2, -mo)), w3 = ex2(fmaf(o1, scale_l2, -mo));
    float se = w0 + w1, so = w2 + w3;
    st(4 + 2 * i, __float_as_uint(i == 1 ? me : i == 2 ? se : e0));
    se += __shfl_xor_sync(0xffffffffu, se, 1);
    so += __shfl_xor_sync(0xffffffffu, so, 1);
    se += __shfl_xor_sync(0xffffffffu, se, 2);
    so += __shfl_xor_sync(0xffffffffu, so, 2);
    asm("rcp.approx.ftz.f32 %0, %0;" : "+f"(se));
    asm("rcp.approx.ftz.f32 %0, %0;" : "+f"(so));
    se *= g0;
    so *= g1;
    pe[i] = pack_bf16(w0 * se, w1 * se);
    po[i] = pack_bf16(w2 * so, w3 * so);
    st(5 + 2 * i, i == 0 ? __float_as_uint(w0) : i == 2 ? __float_as_uint(mo) : po[i]);
  }
  if (warp_g == 0) TS(0, 4);
  mbar_wait(bL2, 0);
  if (warp_g == 0) TS(0, 5);
#pragma unroll
  for (int c = 0; c < 9; c++)
    asm volatile("ldmatrix.sync.aligned.m8n8.x4.trans.shared.b16 {%0, %1, %2, %3}, [%4];"
                 : "=r"(k[c][0]), "=r"(k[c][1]), "=r"(k[c][2]), "=r"(k[c][3]) : "r"(ad[c] + LV) : "memory");
#pragma unroll
  for (int i = 0; i < 4; i++) {
#pragma unroll
    for (int n = 0; n < 3; n++) {
      float c[4] = {0.f, 0.f, 0.f, 0.f};
      mma16(c, pe[i] & mlo, 0u, pe[i] & ~mlo, 0u, k[2 * i + n][0], k[2 * i + n][1]);
      mma16(c, 0u, po[i] & mlo, 0u, po[i] & ~mlo, k[2 * i + n][2], k[2 * i + n][3]);
      const uint32_t r0 = pack_bf16(c[0], c[1]), r1 = pack_bf16(c[2], c[3]);
      const bool keep = (n == 0) && (i > 0) && (t < i);
      qf[2 * i + n][0] = keep ? qf[2 * i + n][0] : r0;
      qf[2 * i + n][1] = keep ? qf[2 * i + n][1] : r1;
    }
    st(12 + i, qf[2 * i + 1][0]);
  }
#pragma unroll
  for (int c = 0; c < 9; c++)
    asm volatile("stmatrix.sync.aligned.m8n8.x2.shared.b16 [%0], {%1, %2};" ::"r"(ad[c] + LQ), "r"(qf[c][0]), "r"(qf[c][1]) : "memory");
  asm volatile("fence.proxy.async.shared::cta;" ::: "memory");
}
__device__ __forceinline__ void tma4d(uint32_t dst, const CUtensorMap* m, uint32_t bar, int c1, int c2, int c3) {
  asm volatile("cp.async.bulk.tensor.4d.shared::cluster.global.mbarrier::complete_tx::bytes [%0], [%1, {%3, %4, %5, %6}], [%2];" ::"r"(dst),
               "l"(m), "r"(bar), "r"(0), "r"(c1), "r"(c2), "r"(c3) : "memory");
}

#define ST_NUM 1
#define ST_DEN 2
#define K1_NST 6
constexpr int K1_BST = K1_NST;
#define MAXJ 11
constexpr int K1_MAXJOBS = MAXJ;
constexpr uint32_t K1_FLAG_TARGET = 7;
constexpr uint32_t RDY_TARGET = 48;
constexpr uint32_t GATE_TARGET = 128 * 3;
struct alignas(64) Params {
  CUtensorMap tmA[2];
  CUtensorMap tmW[4];
  uint16_t jobs[NCLUSTER][K1_MAXJOBS + 1];
  CUtensorMap tmK, tmV, tmQ;
  CUtensorMap tmL[3];
  CUtensorMap tmC, tmO[2], tmOt[2];
  CUtensorMap tmR[2];
  uint8_t order[256];
  uint8_t unit[66][4];
};

struct K1State {
  uint32_t bs, bph, aph;
  bf16 *pp, *pp8;
  int png;
  int tn;
  int wsel;
  uint32_t fo;
};
__device__ __forceinline__ void k1_flag(const K1State& st, int lane, uint32_t bS) {
  if (st.png) {
    __syncwarp();
    if (lane == 0) mbar_arrive(bS + st.fo);
  }
}

__device__ __forceinline__ void scale_q4(uint32_t* v) {
#pragma unroll
  for (int i = 0; i < 4; i++)
    asm volatile("{\n.reg .b32 t;\nmul.rn.bf16x2 t, %0, %2;\nfma.rn.bf16x2 %0, %0, %1, t;\n}" : "+r"(v[i]) : "r"(0x3E033E03u), "r"(0xB9D8B9D8u));
}
__device__ __forceinline__ void k1_first(const K1State& st, uint32_t job, uint32_t bAf, uint32_t bBf) {
  if (job & 3) {
    if ((job >> 14) & 1) mbar_wait(bAf, st.aph);
    mbar_wait(bBf + st.bs * 8, st.bph);
  }
}
__device__ __forceinline__ void k1_tile(float (&acc)[128], uint32_t (&pk)[64], K1State& st, uint32_t job, uint32_t njob, uint32_t sA, uint32_t sB,
                                        uint32_t bAf, uint32_t bAe, uint32_t bBf, uint32_t bBe, uint32_t bS, int wg, int warp, int lane, uint32_t rank) {
  const int a_sel = (job >> 2) & 1, mpair = (job >> 3) & 7, w_sel = (job >> 6) & 3, chunk0 = (job >> 8) & 63;
  const bool newA = (job >> 14) & 1, lastA = (job >> 15) & 1;
  const bool sig = (lane == 0) && (warp < 2);
  const bool siga = lastA && (lane == 0) && (warp == 2);
  const int KC = 8 + a_sel;
  uint32_t prev_bs = 0, a8_bs = 0;
#pragma unroll
  for (int kc = 0; kc < 9; kc++) {
    if (kc >= KC) break;
    uint32_t abase = sA + ((kc + 2) & 7) * 16384;
    if (kc == 8) {
      mbar_wait(bBf + st.bs * 8, st.bph);
      a8_bs = st.bs;
      abase = sB + st.bs * 16384;
      if (++st.bs == K1_BST) { st.bs = 0; st.bph ^= 1; }
    } else if (newA && kc > 0) {
      mbar_wait(bAf + kc * 8, st.aph);
    }
    const uint64_t da = make_desc(abase + wg * 8192, 16, 1024, 1);
#pragma unroll
    for (int ks = 0; ks < 2; ks++) {
      if (ks > 0 || kc > 0) mbar_wait(bBf + st.bs * 8, st.bph);
      const uint64_t db = make_desc(sB + st.bs * 16384, 2048, 1024, 1);
      wg_fence();
      wgmma_ss_n256<1, 0>(acc, da + (uint64_t)(ks * 4), db, (ks > 0) ? 1 : (kc > 0));
      wgmma_ss_n256<1, 0>(acc, da + (uint64_t)(ks * 4 + 2), db + (uint64_t)512, 1);
      wg_commit();
      wg_wait<1>();
      if (ks > 0 || kc > 0) {
        if (sig) mbar_arrive_cluster(bBe + prev_bs * 8, warp);
        if (ks == 0 && siga) mbar_arrive(bAe + (kc - 1) * 8);
      }
      if (st.wsel == 2) {
        const int i = (kc & 7) * 2 + ks;
        if (kc < st.png) {
          quad_transpose(pk[i * 4], pk[i * 4 + 1], pk[i * 4 + 2], pk[i * 4 + 3], lane & 3);
          st_v4a((ks ? st.pp8 : st.pp) + kc * 32, pk[i * 4], pk[i * 4 + 1], pk[i * 4 + 2], pk[i * 4 + 3]);
        }
        if (i == 15) k1_flag(st, lane, bS);
      } else if (st.png) {
#pragma unroll
        for (int i = 0; i < 16; i++) {
          if (i * ST_NUM / ST_DEN != kc * 2 + ks) continue;
          if (st.wsel == 3) scale_q4(pk + i * 4);
          st_v4a(((i & 1) ? st.pp8 : st.pp) + (i / 2) * 32, pk[i * 4], pk[i * 4 + 1], pk[i * 4 + 2], pk[i * 4 + 3]);
          if (i == 15) k1_flag(st, lane, bS);
        }
      }
      prev_bs = st.bs;
      if (++st.bs == K1_BST) { st.bs = 0; st.bph ^= 1; }
    }
  }
  if (newA) st.aph ^= 1;
  const bool isA = (w_sel == 2);
  bf16* out = (w_sel == 0) ? g_K : (w_sel == 1) ? g_V : isA ? g_QKVA : g_ctx;
  const int ld = isA ? NQKVA : (w_sel == 3) ? KCAT : HDIM;
  const int row = mpair * 256 + rank * 128 + wg * 64 + warp * 16 + (lane >> 2);
  st.pp = ptr_add(out, (row * ld + chunk0 * 64 + (lane & 3) * 8) * 2);
  st.pp8 = ptr_add(st.pp, 16 * ld);
  st.png = ((job & 3) + 1) * 2;
  st.wsel = w_sel;
  st.fo = (st.fo + 8) & 24;
  k1_first(st, njob, bAf, bBf);
  wg_wait<0>();
  fence_regs(acc);
  mbar_arrive_cluster_if(bBe + prev_bs * 8, warp & 1, sig);
  mbar_arrive_cluster_if(bBe + a8_bs * 8, warp & 1, sig && a_sel);
  mbar_arrive_if(bAe + 7 * 8, siga && !a_sel);
#pragma unroll
  for (int i = 0; i < 64; i++) {
    const int j = (i >> 3) * 16 + (i & 3) * 4 + ((i >> 2) & 1) * 2;
    pk[i] = pack_bf16(acc[j], acc[j + 1]);
  }
}

constexpr int K2_NST = 7;
constexpr uint32_t K2_END = 0x100;
#define PFD 4
#define PF3A 2
#define PF3 6
#define KC0 1
#define PFC 0
#define CORD 1
#define FIRST_DRAW 3
#define PWAIT mbar_wait_ns<1000>
#define PVM 0x8A
#define W0 63
#define SPEC_HI 1.8446744073709552e19f
#define SPEC_LO 5.421010862427522e-20f
constexpr int K3_NST = 4;
#define K3_NS 6
__device__ __forceinline__ uint32_t k3_rot(uint32_t sv) { return (0x00E9u >> (2 * sv)) & 3; }
constexpr int K3_STAGE = 16384 + 32768 + 4096;
constexpr int SMEM_DATA = 7 * 32768;
constexpr int SMEM_BYTES = SMEM_DATA + 1024 + 896;

struct Cursor {
  uint32_t s, ph;
  __device__ __forceinline__ void next() {
    if (++s == K2_NST) { s = 0; ph ^= 1; }
  }
};

#define TURN_SYNC() bar_sync(mybar, 256)
#define TURN_ARRIVE() bar_arrive(otherbar, 256)
#define RELEASE_IF(cur, cond) mbar_arrive_cluster_if(bE + (cur).s * 8, warp & 1, sig && (cond))
#define RELEASE(cur) RELEASE_IF(cur, true)
#define ISSUE_PV(cur, first)                                                                                   \
  do {                                                                                                         \
    const uint64_t dv = make_desc(sbase + (cur).s * 32768, 16384, 1024, 1);                                    \
    _Pragma("unroll") for (int t = 0; t < 8; t++)                                                              \
        wgmma_rs_n128<1, 0>(O, P[4 * t], P[4 * t + 1], P[4 * t + 2], P[4 * t + 3], dv + (uint64_t)(t * 128), (t > 0) ? 1 : !(first)); \
  } while (0)
#define ISSUE_QK(cur)                                                                                          \
  do {                                                                                                         \
    const uint64_t dk = make_desc(sbase + (cur).s * 32768, 16, 1024, 1);                                       \
    _Pragma("unroll") for (int t = 0; t < 8; t++)                                                              \
        wgmma_rs_n128<0, 0>(S, Q[4 * t], Q[4 * t + 1], Q[4 * t + 2], Q[4 * t + 3], dk + (uint64_t)((t >> 2) * 1024 + (t & 3) * 2), t > 0); \
  } while (0)
#define LOAD_Q()                                                                                               \
  do {                                                                                                         \
    item = lds32(sItem + (it & 7) * 4);                                                                        \
    const uint32_t qa = sbase + cq.s * 32768 + (wg * 64 + warp * 16 + (lane & 15)) * 128;                      \
    _Pragma("unroll") for (int t = 0; t < 8; t++)                                                              \
        ldsm_x4(Q[4 * t], Q[4 * t + 1], Q[4 * t + 2], Q[4 * t + 3], qa + (t >> 2) * 16384 + ((((t & 3) * 2 + (lane >> 4)) ^ (lane & 7)) << 4)); \
  } while (0)
#define NEW_ITEM()                                                                                             \
  do {                                                                                                         \
    const int row = (2 * (item & 7) + hi) * 128 + (rank ^ hi) * 64 + warp * 16 + (lane >> 2);                  \
    eoff = (row * KCAT + (item >> 3) * 128 + q * 8) * 2;                                                       \
    const float* gp = ptr_add(g_gate, row * 4);                                                                \
    asm volatile("ld.global.f32 %0, [%1];" : "=f"(gf0) : "l"(gp));                                             \
    asm volatile("ld.global.f32 %0, [%1];" : "=f"(gf1) : "l"(gp + 8));                                         \
    if (!hi) {                                                                                                 \
      mbar_wait2(bF + cs0.s * 8, cs0.ph, bF + cs1.s * 8, cs1.ph);                                              \
      RELEASE(cs0);                                                                                            \
      RELEASE(cs1);                                                                                            \
    }                                                                                                          \
  } while (0)
#define EXPB(T)                                                                                                \
  do {                                                                                                         \
    _Pragma("unroll") for (int i = 4 * T; i < 4 * T + 4; i++) asm volatile("" : "+r"(P[i])::"memory");        \
    _Pragma("unroll") for (int jj = 2 * T; jj < 2 * T + 2; jj++) {                                             \
      const float e0 = ex2(S[jj * 4 + 0]), e1 = ex2(S[jj * 4 + 1]), e2 = ex2(S[jj * 4 + 2]), e3 = ex2(S[jj * 4 + 3]); \
      s0 += e0 + e1;                                                                                           \
      s1 += e2 + e3;                                                                                           \
      P[jj * 2 + 0] = pack_bf16(e0, e1);                                                                       \
      P[jj * 2 + 1] = pack_bf16(e2, e3);                                                                       \
    }                                                                                                          \
  } while (0)
#define EXPC(T)                                                                                                \
  do {                                                                                                         \
    if (T > 0 && ((PVM >> (T - 1)) & 1)) {                                                                     \
      anchor((T & 2) ? s0 : s1, never);                                                                        \
      wg_wait<__builtin_popcount(PVM >> T) - 1>();                                                             \
      if ((PVM >> T) == (128 >> T)) { fence_regs(O); RELEASE(cv); }                                            \
    }                                                                                                          \
    EXPB(T);                                                                                                   \
  } while (0)
#define MASK(G, g)                                                                                             \
  do {                                                                                                         \
    if ((g) * 8 > d) S[(G) * 4 + 0] = -INFINITY;                                                               \
    if ((g) * 8 + 1 > d) S[(G) * 4 + 1] = -INFINITY;                                                           \
    if ((g) * 8 - 8 > d) S[(G) * 4 + 2] = -INFINITY;                                                           \
    if ((g) * 8 - 7 > d) S[(G) * 4 + 3] = -INFINITY;                                                           \
  } while (0)
#define STORE_O(G)                                                                                             \
  do {                                                                                                         \
    st_v4(optr + (G) * 32, pack_bf16(O[(G) * 16 + 0] * f0, O[(G) * 16 + 1] * f0), pack_bf16(O[(G) * 16 + 4] * f0, O[(G) * 16 + 5] * f0), \
          pack_bf16(O[(G) * 16 + 8] * f0, O[(G) * 16 + 9] * f0), pack_bf16(O[(G) * 16 + 12] * f0, O[(G) * 16 + 13] * f0)); \
    st_v4(optr + 8 * KCAT + (G) * 32, pack_bf16(O[(G) * 16 + 2] * f1, O[(G) * 16 + 3] * f1), pack_bf16(O[(G) * 16 + 6] * f1, O[(G) * 16 + 7] * f1), \
          pack_bf16(O[(G) * 16 + 10] * f1, O[(G) * 16 + 11] * f1), pack_bf16(O[(G) * 16 + 14] * f1, O[(G) * 16 + 15] * f1)); \
  } while (0)

#define FLUSH()                                                                                                \
  do {                                                                                                         \
    _Pragma("unroll") for (int G = 0; G < 8; G++) {                                                            \
      st_v4a(st.pp + G * 32, pk[G * 8], pk[G * 8 + 1], pk[G * 8 + 2], pk[G * 8 + 3]);                          \
      st_v4a(st.pp8 + G * 32, pk[G * 8 + 4], pk[G * 8 + 5], pk[G * 8 + 6], pk[G * 8 + 7]);                     \
    }                                                                                                          \
    k1_flag(st, lane, bS);                                                                                     \
  } while (0)

__global__ void __cluster_dims__(2, 1, 1) __launch_bounds__(384, 1)
fused_kernel(const __grid_constant__ Params p, const bf16* __restrict__ x, const bf16* __restrict__ gate_w, bf16* __restrict__ out) {
  extern __shared__ uint8_t smem_raw[];
  const uint32_t sbase = (smem_u32(smem_raw) + 1023) & ~1023u;
  const uint32_t sB = sbase, sA = sbase + K1_BST * 16384, sBar = sbase + SMEM_DATA;
  const uint32_t bAf = sBar, bAe = sBar + 64, bBf = sBar + 128, bBe = sBar + 176, bL = sBar + 224, bS = sBar + 656, bL2 = sBar + 240, sL = sA + 32768;
  const uint32_t bF = sBar + 256, bE = sBar + 320, bT = sBar + 384, sTick = sBar + 400, sItem = sBar + 416, bS2 = sBar + 688, bR = sBar + 456, bLast = sBar + 464, bH = sBar + 472, bT0 = sBar + 480, bZ = sBar + 488, bLd = sBar + 496;
  const uint32_t b3F = sBar + 512, b3E = sBar + 544, sGate = sBar + 576, sK1 = sBar + 720, sClm = sBar + 768;
  const int tid = threadIdx.x, warp_g = __shfl_sync(0xffffffffu, tid >> 5, 0), lane = tid & 31;
  const uint32_t rank = cluster_rank();
  const int cl = blockIdx.x >> 1;
  TSM(0);
  if (tid == 256) {
    const uint32_t job = p.jobs[cl][0];
#pragma unroll
    for (int i = 0; i < KC0; i++) { mbar_init(bAf + i * 8, 1); mbar_init(bBf + i * 16, 1); mbar_init(bBf + i * 16 + 8, 1); }
    asm volatile("fence.mbarrier_init.release.cluster;" ::: "memory");
#pragma unroll 1
    for (int i = 0; i < 4 * KC0; i++) {
      if (!(i & 3)) {
        mbar_expect(bAf + i * 2, 16384);
        tma2d(sA + (i / 4 + 2) * 16384, &p.tmA[(job >> 2) & 1], bAf + i * 2, i * 16, ((job >> 3) & 7) * 256 + rank * 128);
      }
      if (!(i & 1)) mbar_expect(bBf + i * 4, 16384);
      tma3d(sB + i * 8192, &p.tmW[(job >> 6) & 3], bBf + (i >> 1) * 8, 0, i * 16, (job >> 8) & 63);
    }
  }
  if (warp_g == 1) asm volatile("st.shared.u32 [%0], %1;" ::"r"(lane ? sClm - 4 + lane * 4 : sK1), "r"(lane ? 0xFFFFFFFFu : 80u) : "memory");
  if (tid == 0) {
    for (int i = 0; i < 8; i++) { if (i >= KC0) mbar_init(bAf + i * 8, 1); mbar_init(bAe + i * 8, 2); }
    for (int i = 0; i < K1_BST; i++) { if (i >= 2 * KC0) mbar_init(bBf + i * 8, 1); mbar_init(bBe + i * 8, 4); }
    mbar_init(bL, 1);
    mbar_init(bL2, 1);
    mbar_init(bR, 1);
    mbar_init(bLast, 1);
    mbar_init(bH, 4);
    mbar_init(bT0, 1);
    mbar_init(bZ, 1);
    mbar_init(bLd, 4);
    for (int i = 0; i < 8; i++) mbar_init(bS + i * 8, 8);
    for (int i = 0; i < K2_NST; i++) { mbar_init(bF + i * 8, 1); mbar_init(bE + i * 8, 4); }
    mbar_init(bT, 1); mbar_init(bT + 8, 1);
    for (int i = 0; i < K3_NST; i++) { mbar_init(b3F + i * 8, 1); mbar_init(b3E + i * 8, 4); }
    asm volatile("fence.mbarrier_init.release.cluster;" ::: "memory");
  }
  __syncwarp();
  if (warp_g != 8) cluster_sync();
  const int lr0 = blockIdx.x * 16;

  if (warp_g >= 8) {
    reg_dealloc<40>();
    if (warp_g == 8) {
      {
        __syncwarp();
        cluster_sync();
      }
      if (elect_one()) {
        uint32_t bs = (2 * KC0) % K1_BST, bph = (2 * KC0 < K1_BST), aph = 1;
#pragma unroll 1
        for (int ji = 0; ji < K1_MAXJOBS; ji++) {
          const uint32_t job = p.jobs[cl][ji];
          if (!(job & 3)) break;
          const int a_sel = (job >> 2) & 1, mpair = (job >> 3) & 7, chunk0 = (job >> 8) & 63;
          const bool newA = (job >> 14) & 1;
          const int KC = a_sel ? 9 : 8;
          const uint32_t halfbytes = 8192;
          const bool lastjob = (ji + 1 == K1_MAXJOBS) || !(p.jobs[cl][ji + 1] & 3);
          const CUtensorMap* tw = &p.tmW[(job >> 6) & 3];
          {
            const uint32_t njob = (ji + 1 < K1_MAXJOBS) ? p.jobs[cl][ji + 1] : 0;
            if (!(njob & 3) && !newA) mbar_arrive(bLast);
          }
#pragma unroll 1
          for (int kc = ji ? 0 : KC0; kc < KC; kc++) {
            {
              const bool nx = kc + PFD >= KC;
              const uint32_t njob = nx ? p.jobs[cl][ji + 1] : job;
              const int pk = nx ? kc + PFD - KC : kc + PFD;
              if ((njob & 3) && (nx || ji > 0)) {
                if (cl >= 64 || ((pk ^ (cl >> 1)) & 3) == 0)
                  tma_pf3d(&p.tmW[(njob >> 6) & 3], 0, pk * 64 + (cl & 1) * 32 + rank * 16, (njob >> 8) & 63);
                if (((njob >> 14) & 1) || pk == 8) tma_pf2d(&p.tmA[(njob >> 2) & 1], pk * 64, ((njob >> 3) & 7) * 256 + rank * 128);
              }
            }
            if (kc == 8) {
              PWAIT(bBe + bs * 8, bph);
              mbar_expect(bBf + bs * 8, 16384);
              tma2d(sB + bs * 16384, &p.tmA[1], bBf + bs * 8, 512, mpair * 256 + rank * 128);
              if (++bs == K1_BST) { bs = 0; bph ^= 1; }
            } else if (newA) {
              PWAIT(bAe + kc * 8, aph);
              mbar_expect(bAf + kc * 8, 16384);
              tma2d(sA + ((kc + 2) & 7) * 16384, &p.tmA[a_sel], bAf + kc * 8, kc * 64, mpair * 256 + rank * 128);
              if (kc == 7 && lastjob) mbar_arrive(bLast);
            }
#pragma unroll 1
            for (int kk = 0; kk < 2; kk++) {
              PWAIT(bBe + bs * 8, bph);
              mbar_expect(bBf + bs * 8, 2 * halfbytes);
              tma3d_mc(sB + bs * 16384 + rank * halfbytes, tw, bBf + bs * 8, 0, kc * 64 + kk * 32 + rank * 16, chunk0, 3);
              if (++bs == K1_BST) { bs = 0; bph ^= 1; }
            }
          }
          if (newA) aph ^= 1;
        }
        Cursor c{0, 0};
        int pcol = 0;
        PWAIT(bR, 0);
        uint32_t tick = lds32(sTick + 8), seen = 1u << (p.order[tick] >> 4);
        asm volatile("fence.proxy.async.global;" ::: "memory");
#pragma unroll 1
        for (int it = 0;; it++) {
          const uint32_t item = (tick < 256) ? p.order[tick] : (K2_END | min(tick - 256, 255u));
          asm volatile("st.shared.u32 [%0], %1;" ::"r"(sItem + (it & 7) * 4), "r"(item) : "memory");
          if (item >= K2_END) break;
          const int h = item >> 3, j = item & 7;
          const int col = h * 128 + rank * 64;
          const int nb = 2 * j + 2;
          if (!((seen >> (h >> 1)) & 1)) {
            wait_flag(&g_sync[F_HP + (h >> 1)], RDY_TARGET);
            asm volatile("fence.proxy.async.global;" ::: "memory");
            seen |= 1u << (h >> 1);
          }
          PWAIT(bE + c.s * 8, c.ph);
          mbar_expect(bF + c.s * 8, 32768);
#pragma unroll 1
          for (int i = 0; i < 4; i++) {
            const int hi = (i ^ it ^ 1) & 1;
            tma2d(sbase + c.s * 32768 + i * 8192, &p.tmQ, bF + c.s * 8, h * 128 + (i >> 1) * 64, (2 * j + hi) * 128 + (rank ^ hi) * 64);
          }
          c.next();
          if (tick >= 256 - 73) {
            const int kk = tick - (256 - 73), sel = (kk < 9), kr = (sel ? kk : kk - 9) * 64 + rank * 32;
#pragma unroll 1
            for (int i = 0; i < 2; i++) {
              tma_pf3d(&p.tmO[sel], 0, kr, i * 4);
              tma_pf2d(&p.tmOt[sel], 512 + i * 32, kr);
            }
          }
#pragma unroll 1
          for (int n = nb - 1; n >= 0; n--) {
            if (n == 0 && rank == 0) tick = atomicAdd(&g_sync[F_TICK], 1u);
            PWAIT(bE + c.s * 8, c.ph);
            mbar_expect(bF + c.s * 8, 32768);
            tma2d_mc(sbase + c.s * 32768 + rank * 16384, &p.tmK, bF + c.s * 8, col, n * 128, 3);
            c.next();
            if (n < nb - 1 || it > 0) {
              PWAIT(bE + c.s * 8, c.ph);
              mbar_expect(bF + c.s * 8, 32768);
              tma2d_mc(sbase + c.s * 32768 + rank * 16384, &p.tmV, bF + c.s * 8, (n < nb - 1) ? col : pcol, (n < nb - 1) ? (n + 1) * 128 : 0, 3);
              c.next();
            }
          }
          pcol = col;
          if (rank == 0) {
            asm volatile(
                "{\n.reg .b32 a, b;\nmapa.shared::cluster.u32 a, %0, 1;\nmapa.shared::cluster.u32 b, %1, 1;\n"
                "st.async.shared::cluster.mbarrier::complete_tx::bytes.u32 [a], %2, [b];\n}" ::"r"(sTick + (it & 1) * 4),
                "r"(bT + (it & 1) * 8), "r"(tick) : "memory");
          } else {
            mbar_expect(bT + (it & 1) * 8, 4);
            PWAIT(bT + (it & 1) * 8, (it >> 1) & 1);
            tick = lds32(sTick + (it & 1) * 4);
          }
        }
        PWAIT(bE + c.s * 8, c.ph);
        mbar_expect(bF + c.s * 8, 32768);
        tma2d_mc(sbase + c.s * 32768 + rank * 16384, &p.tmV, bF + c.s * 8, pcol, 0, 3);
        const uint32_t unit = tick - 256;
        const int mblk = (7 - (p.unit[unit][0] >> 1)) * 2 + rank, nhalf = p.unit[unit][0] & 1;
        uint32_t have, hoa;
        have = ld_and2(&g_sync[F_CTX + (mblk & ~1)]);
        asm volatile("ld.acquire.gpu.global.u32 %0, [%1];" : "=r"(hoa) : "l"(&g_sync[F_OA + mblk]) : "memory");
        asm volatile("fence.proxy.async.global;" ::: "memory");
#pragma unroll 1
        for (uint32_t idx = PF3A; idx < PF3; idx++) {
          const int kk = p.unit[unit][2] + idx;
          if ((kk < 9) ? (hoa >= 8) : ((have >> ((kk - 9) >> 1)) & 1)) tma_pf2d(&p.tmC, ((kk < 9) ? 64 + kk : kk - 9) * 64, mblk * 128);
        }
        {
          const uint32_t rot = k3_rot(c.s), nfree = ((0x1Au >> c.s) & 1) ? 2 : 3;
          uint32_t kq = p.unit[unit][2] * 0x010101u + 0x020100u, k1 = 80, idx = 0, pa = 0, pb = 0;
          auto step = [&](uint32_t& pend) {
            uint32_t nxt = (kq & 255) + 3;
            if (idx + 3 >= K3_NS && k1 == 80) {
              if (rank == 0) {
                nxt = min(pend + p.unit[unit][3], 73u);
                asm volatile("{\n.reg .b32 a;\nmapa.shared::cluster.u32 a, %0, 1;\nst.volatile.shared::cluster.u8 [a], %1;\n}" ::"r"(sClm + idx), "r"(nxt) : "memory");
              } else {
#pragma unroll 1
                for (uint32_t spins = 0; spins < (1u << 22); spins++) {
                  asm volatile("ld.volatile.shared.u8 %0, [%1];" : "=r"(nxt) : "r"(sClm + idx) : "memory");
                  if (nxt != 255) break;
                  __nanosleep(20);
                }
              }
              if (nxt >= 73) {
                k1 = idx + 3;
                asm volatile("st.shared.u32 [%0], %1;" ::"r"(sK1), "r"(k1) : "memory");
              }
            }
            const uint32_t kk = kq & 255;
            if (idx < 12) TP(idx);
            kq = (kq >> 8) | (nxt << 16);
            const uint32_t s = (rot + idx) & 3;
            if (idx >= nfree) PWAIT((idx < 4) ? bH : b3E + s * 8, (idx < 4) ? 0 : (~idx >> 2) & 1);
#pragma unroll 1
            while (idx < nfree && c.s != ((0x6431u >> (4 * s)) & 15)) {
              c.next();
              PWAIT(bE + c.s * 8, c.ph);
            }
            if (idx < 12) TP(12 + idx);
            mbar_expect(b3F + s * 8, K3_STAGE);
            const uint32_t st = sbase + s * K3_STAGE;
            const int sel = (kk < 9), k = sel ? kk : kk - 9, kr = k * 64 + rank * 32;
            tma3d_mc(st + 16384 + rank * 16384, &p.tmO[sel], b3F + s * 8, 0, kr, nhalf * 4, 3);
            tma2d_mc(st + 49152 + rank * 2048, &p.tmOt[sel], b3F + s * 8, 512 + nhalf * 32, kr, 3);
            if (rank == 0 && idx + 5 >= K3_NS && k1 == 80) pend = atomicAdd(&g_sync[F_CLM + p.unit[unit][0]], 1u);
            if (sel && hoa < 8) {
              wait_flag(&g_sync[F_OA + mblk], 8);
              hoa = 8;
              asm volatile("fence.proxy.async.global;" ::: "memory");
            }
            if (!sel && !((have >> (k >> 1)) & 1)) {
#pragma unroll 1
              for (uint32_t spins = 0; spins < (1u << 22); spins++) {
                have = ld_and2(&g_sync[F_CTX + (mblk & ~1)]);
                if ((have >> (k >> 1)) & 1) break;
                __nanosleep(100);
              }
              asm volatile("fence.proxy.async.global;" ::: "memory");
            }
            tma2d(st, &p.tmC, b3F + s * 8, (sel ? 64 + k : k) * 64, mblk * 128);
            if (idx < 12) TP(24 + idx);
            return ++idx >= k1;
          };
#pragma unroll 1
          for (;;) {
            if (step(pa)) break;
            if (step(pb)) break;
          }
          asm volatile("" ::"r"(pa), "r"(pb) : "memory");
        }
      }
    }
    __syncwarp();
    if (warp_g == 8) {
      uint32_t v = 0;
      if (lane == 0) {
        __threadfence();
        v = atomicAdd(&g_sync[F_DONE], 1u);
      }
      if (__shfl_sync(0xffffffffu, v, 0) == 2 * NCLUSTER - 1) {
        reinterpret_cast<uint4*>(g_sync)[lane] = make_uint4(0, 0, 0, 0);
        if (lane == 0) g_sync[F_EPOCH] = lds32(sGate + 64) + 1;
      }
    }
    asm volatile("" ::: "memory");
    if (__shfl_sync(0xffffffffu, warp_g, 0) != 8) {
      if (lr0 < S_LEN) {
#pragma unroll 1
        for (int i = warp_g - 9; i < 16; i += 3) {
          const float g = gate_row(lr0 + i, lane, x, gate_w);
          if (lane == 0) asm volatile("st.shared.f32 [%0], %1;" ::"r"(sGate + i * 4), "f"(g) : "memory");
        }
        bar_arrive(3, 256 + 96);
        if (lane == 0) {
          __threadfence();
          atomicAdd(&g_sync[F_GATE], 1u);
        }
      }
      uint32_t aph = 1;
#pragma unroll 1
      for (int ji = 0; ji < K1_MAXJOBS; ji++) aph ^= (p.jobs[cl][ji] >> 14) & 1;
      if (warp_g == 9) {
        uint32_t nxt = 0;
        if (lane == 0) {
#pragma unroll 1
        for (int ji = 0; ji < K1_MAXJOBS; ji++) {
          const uint32_t job = p.jobs[cl][ji];
          if (!(job & 3)) break;
          PWAIT(bS + (ji & 3) * 8, (ji >> 2) & 1);
          __threadfence();
          atomicAdd(&g_sync[(((job >> 6) & 3) == 2) ? (F_QKVA + ((job >> 3) & 7) * 2 + rank) : (F_HP + ((job >> 10) & 15))], 1u);
        }
#pragma unroll 1
        for (int it = 0;; it++) {
          PWAIT(bS2 + (it & 3) * 8, (it >> 2) & 1);
          const uint32_t item = lds32(sItem + (it & 7) * 4);
          nxt = lds32(sItem + ((it + 1) & 7) * 4);
          __threadfence();
          atomicOr(&g_sync[F_CTX + (item & 7) * 2 + rank], 1u << (item >> 3));
          if (nxt >= K2_END) break;
        }
        }
        const uint32_t unit = __shfl_sync(0xffffffffu, nxt, 0) & 255;
        {
          const int mblk = (7 - (p.unit[unit][0] >> 1)) * 2 + rank, nhalf = p.unit[unit][0] & 1;
          bf16* o = ptr_add(out, (mblk * 128 + p.unit[unit][1] * 32) * DM * 2);
          const bool mine = p.unit[unit][1] < 4;
#pragma unroll 4
          for (int i = 0; i < 32 && mine; i++) __stcg(reinterpret_cast<uint4*>(ptr_add(o, i * DM * 2 + nhalf * 512 + lane * 16)), make_uint4(0, 0, 0, 0));
#pragma unroll
          for (int i = 0; i < 4 && mine; i++) __stcg(reinterpret_cast<uint4*>(ptr_add(o, (i * 8 + (lane >> 2)) * DM * 2 + 1024 + nhalf * 64 + (lane & 3) * 16)), make_uint4(0, 0, 0, 0));
          asm volatile("fence.proxy.async.global;" ::: "memory");
          __threadfence();
          __syncwarp();
          if (lane == 0) {
            prefetch_tmap(&p.tmR[0]); prefetch_tmap(&p.tmR[1]);
            unsigned int* cnt = &g_sync[F_XCH + mblk * 2 + nhalf];
            const uint32_t xtarget = lds32(sGate + 64) * 4 + 4;
            if (mine) atomicAdd(cnt, 1u);
            uint32_t v;
#pragma unroll 1
            for (uint32_t spins = 0; spins < (1u << 22); spins++) {
              asm volatile("ld.acquire.gpu.global.u32 %0, [%1];" : "=r"(v) : "l"(cnt) : "memory");
              if ((int)(v - xtarget) >= 0) break;
              __nanosleep(200);
            }
            asm volatile("fence.proxy.async.global;" ::: "memory");
            mbar_arrive(bZ);
          }
        }
      } else if (warp_g == 11) {
        if (lane == 0) {
          asm volatile("st.shared.u32 [%0], %1;" ::"r"(sGate + 64), "r"(__ldcg(&g_sync[F_EPOCH])) : "memory");
          wait_flag(&g_sync[F_GATE], GATE_TARGET);
          prefetch_tmap(&p.tmC); prefetch_tmap(&p.tmQ); prefetch_tmap(&p.tmK); prefetch_tmap(&p.tmV);
          uint32_t tick;
          if (rank == 0) {
            PWAIT(bLast, 0);
            PWAIT(bAe + FIRST_DRAW * 8, aph);
            tick = atomicAdd(&g_sync[F_TICK], 1u);
            asm volatile("st.shared.u32 [%0], %1;" ::"r"(sTick + 8), "r"(tick) : "memory");
            asm volatile(
                "{\n.reg .b32 a, b;\nmapa.shared::cluster.u32 a, %0, 1;\nmapa.shared::cluster.u32 b, %1, 1;\n"
                "st.async.shared::cluster.mbarrier::complete_tx::bytes.u32 [a], %2, [b];\n}" ::"r"(sTick + 8), "r"(bT0), "r"(tick) : "memory");
          } else {
            mbar_expect(bT0, 4);
            PWAIT(bT0, 0);
            tick = lds32(sTick + 8);
          }
          wait_flag(&g_sync[F_HP + (p.order[tick] >> 4)], RDY_TARGET);
          mbar_arrive(bR);
        }
      } else if (warp_g == 10) {
        if (lr0 < S_LEN && lane == 0) {
          prefetch_tmap(&p.tmL[0]); prefetch_tmap(&p.tmL[1]); prefetch_tmap(&p.tmL[2]);
          wait_flag(&g_sync[F_QKVA + (lr0 >> 7)], K1_FLAG_TARGET);
          wait_flag(&g_sync[F_QKVA + (max(lr0 - 16, 0) >> 7)], K1_FLAG_TARGET);
          asm volatile("fence.proxy.async.global;" ::: "memory");
          PWAIT(bLast, 0);
#pragma unroll 1
          for (int kc = 0; kc < 6; kc++) {
            PWAIT(bAe + kc * 8, aph);
            if (kc == 3) {
              mbar_expect(bL, LV);
              tma4d(sL, &p.tmL[0], bL, lr0 / 2 - 8, 9, 0);
              tma4d(sL + LQ, &p.tmL[1], bL, lr0 / 2, 0, 0);
            }
          }
          mbar_expect(bL2, LQ);
          tma4d(sL + LV, &p.tmL[0], bL2, lr0 / 2 - 8, 18, 0);
        }
        __syncwarp();
        bar_sync(5, 256 + 32);
        if (lr0 < S_LEN && lane == 0) {
          asm volatile("cp.async.bulk.tensor.4d.global.shared::cta.bulk_group [%0, {%2, %3, %2, %2}], [%1];" ::"l"(&p.tmL[2]), "r"(sL + LQ), "r"(0), "r"(lr0 / 2) : "memory");
          asm volatile("cp.async.bulk.commit_group;" ::: "memory");
          asm volatile("cp.async.bulk.wait_group.read 0;" ::: "memory");
        }
        __syncwarp();
        if (lane < 12) mbar_arrive_cluster(bE + (4 + lane % 3) * 8, (lane / 3) & 1);
        if (lr0 < S_LEN && lane == 0) {
          asm volatile("cp.async.bulk.wait_group 0;" ::: "memory");
          asm volatile("fence.proxy.async.global;" ::: "memory");
          __threadfence();
          atomicAdd(&g_sync[F_OA + (lr0 >> 7)], 1u);
        }
      }
    }
    __syncwarp();
    cluster_sync();
  } else {
    reg_alloc<232>();
    const int wg = warp_g >> 2, warp = warp_g & 3, q = lane & 3;
    const bool sig = (lane == 0) && (warp < 2);
    {
      K1State st{0, 0, 0, nullptr, nullptr, 0, 0, 0, 24};
      float acc[128];
      uint32_t pk[64];
      if (wg == 0) { TS(0, 0); TSC(0, 2); }
      uint32_t job = p.jobs[cl][0];
      k1_first(st, job, bAf, bBf);
      {
#pragma unroll 1
        for (int ji = 0; job & 3; ji++) {
          const uint32_t njob = p.jobs[cl][ji + 1];
          k1_tile(acc, pk, st, job, njob, sA, sB, bAf, bAe, bBf, bBe, bS, wg, warp, lane, rank);
          job = njob;
        }
      }
#pragma unroll
      for (int i = 0; i < 4; i++)
        mbar_arrive_cluster_if(bE + i * 8, warp & 1, sig);
      if (lr0 < S_LEN) bar_sync(3, 256 + 96);
      if (st.wsel == 3) {
#pragma unroll
        for (int G = 0; G < 16; G++) scale_q4(pk + G * 4);
      }
      auto flush = [&](int i, uint32_t dep) {
        asm volatile("{\n.reg .pred p;\nsetp.eq.u32 p, %5, 0;\n@p st.global.cs.v4.b32 [%0], {%1, %2, %3, %4};\n}" ::"l"(((i & 1) ? st.pp8 : st.pp) + (i / 2) * 32),
                     "r"(pk[i * 4]), "r"(pk[i * 4 + 1]), "r"(pk[i * 4 + 2]), "r"(pk[i * 4 + 3]), "r"(dep & blockIdx.y) : "memory");
      };
      if (wg == 0) { TS(0, 1); TSC(0, 3); }
      if (lr0 < S_LEN) {
        const float gate0 = __uint_as_float(lds32(sGate + (lane >> 2) * 8)), gate1 = __uint_as_float(lds32(sGate + (lane >> 2) * 8 + 4));
        local_attn(lr0, warp_g, sL, bL, bL2, lane, gate0, gate1, flush);
        k1_flag(st, lane, bS);
      } else {
        FLUSH();
      }
      bar_arrive(5, 256 + 32);
    }
    __syncwarp();
    uint32_t item, rot;
    {
      const int mybar = 1 + wg, otherbar = 2 - wg;
      const uint32_t never = blockIdx.y;
      float S[64], O[64];
      uint32_t P[32], Q[32];
      float m0, m1, l0, l1, gf0, gf1;
      uint32_t eoff;
      Cursor c{2 + 2 * (uint32_t)wg, 0}, ck{1 + (uint32_t)wg, 0};
      if (wg == 1) bar_arrive(1, 256);
      if (wg == 0) { TS(1, 0); TSC(1, 2); }
      {
        const Cursor cq{0, 0}, cs0{1, 0}, cs1{3, 0};
        const int it = 0, hi = wg ^ 1;
        mbar_wait2(bF, 0, bF + ck.s * 8, 0);
        LOAD_Q();
        wg_fence();
        ISSUE_QK(ck);
        wg_commit();
        RELEASE(cq);
        NEW_ITEM();
        wg_wait<0>();
        fence_regs(S);
      }
#pragma unroll 1
      for (int it = 0;;) {
        int hi = (wg ^ it ^ 1) & 1;
        RELEASE(ck);
        const int nblk = 2 * (item & 7) + 1 + hi;
        Cursor cv;
        float s0 = 0.f, s1 = 0.f;
        l0 = 0.f; l1 = 0.f;
        m0 = 0.f; m1 = 0.f;
        bool shifted = false;
        {
          const int d = warp * 16 + (lane >> 2) - 2 * q;
          if (rank == hi) {
#pragma unroll
            for (int jj = 0; jj < 8; jj++) MASK(jj, jj);
            EXPB(0); EXPB(1); EXPB(2); EXPB(3);
#pragma unroll
            for (int i = 32; i < 64; i++) S[i] = -INFINITY;
#pragma unroll
            for (int i = 16; i < 32; i++) P[i] = 0;
          } else {
#pragma unroll
            for (int jj = 0; jj < 8; jj++) MASK(jj + 8, jj);
            EXPB(0); EXPB(1); EXPB(2); EXPB(3); EXPB(4); EXPB(5); EXPB(6); EXPB(7);
          }
        }
        float chk = (q == 0 && !(fminf(s0, s1) >= SPEC_LO)) ? INFINITY : s0 + s1;
        fence_regs(P);
        TB(9);
#pragma unroll 1
        for (int n = 1;; n++) {
          if (__any_sync(0xffffffffu, !(chk <= SPEC_HI))) {
            float mx0 = fmaxf(S[0], S[1]), mx1 = fmaxf(S[2], S[3]);
#pragma unroll
            for (int jj = 1; jj < 16; jj++) {
              mx0 = fmaxf(mx0, fmaxf(S[jj * 4 + 0], S[jj * 4 + 1]));
              mx1 = fmaxf(mx1, fmaxf(S[jj * 4 + 2], S[jj * 4 + 3]));
            }
            mx0 = fmaxf(mx0, __shfl_xor_sync(0xffffffffu, mx0, 1));
            mx1 = fmaxf(mx1, __shfl_xor_sync(0xffffffffu, mx1, 1));
            mx0 = fmaxf(mx0, __shfl_xor_sync(0xffffffffu, mx0, 2));
            mx1 = fmaxf(mx1, __shfl_xor_sync(0xffffffffu, mx1, 2));
            const float lo = (n == 1) ? -INFINITY : 0.f;
            mx0 = fmaxf(mx0, lo);
            mx1 = fmaxf(mx1, lo);
            m0 += mx0; m1 += mx1;
            shifted = true;
            const float sc0 = ex2(-fmaxf(mx0, 0.f)), sc1 = ex2(-fmaxf(mx1, 0.f));
            l0 *= sc0; l1 *= sc1;
            s0 = 0.f; s1 = 0.f;
#pragma unroll
            for (int jj = 0; jj < 16; jj++) {
              const float e0 = ex2(S[jj * 4 + 0] - mx0), e1 = ex2(S[jj * 4 + 1] - mx0), e2 = ex2(S[jj * 4 + 2] - mx1), e3 = ex2(S[jj * 4 + 3] - mx1);
              s0 += e0 + e1;
              s1 += e2 + e3;
              P[jj * 2 + 0] = pack_bf16(e0, e1);
              P[jj * 2 + 1] = pack_bf16(e2, e3);
              O[jj * 4 + 0] *= sc0;
              O[jj * 4 + 1] *= sc0;
              O[jj * 4 + 2] *= sc1;
              O[jj * 4 + 3] *= sc1;
            }
          }
          l0 += s0;
          l1 += s1;
          if (n >= nblk) break;
          ck = c; c.next();
          cv = c; c.next();
          mbar_wait(bF + ck.s * 8, ck.ph);
          mbar_wait(bF + cv.s * 8, cv.ph);
          TURN_SYNC();
          TRC(0);
          wg_fence();
          ISSUE_QK(ck);
          wg_commit();
          {
            const uint64_t dv = make_desc(sbase + cv.s * 32768, 16384, 1024, 1);
#pragma unroll
            for (int t = 0; t < 8; t++) {
              wgmma_rs_n128<1, 0>(O, P[4 * t], P[4 * t + 1], P[4 * t + 2], P[4 * t + 3], dv + (uint64_t)(t * 128), (t > 0) ? 1 : (n != 1));
              if ((PVM >> t) & 1) wg_commit();
            }
          }
          TURN_ARRIVE();
          s0 = 0.f; s1 = 0.f;
          wg_wait<__builtin_popcount(PVM)>();
          fence_regs(S);
          RELEASE(ck);
          if (shifted) {
#pragma unroll
            for (int i = 0; i < 64; i++) S[i] -= (i & 2) ? m1 : m0;
          }
          wg_wait<__builtin_popcount(PVM) - 1>();
          EXPC(0); EXPC(1); EXPC(2); EXPC(3); EXPC(4); EXPC(5); EXPC(6); EXPC(7);
          chk = s0 + s1;
        }
        it++;
        hi ^= 1;
        TB(0);
        Cursor cq = c, cs0, cs1;
        rot = k3_rot(c.s);
        c.next();
        ck = c; c.next();
        cs0 = ck; cs1 = ck;
        cv = c; c.next();
        if (!hi) {
          ck = c; c.next();
          cs1 = c; c.next();
        }
        mbar_wait(bF + cq.s * 8, cq.ph);
        TB(1);
        LOAD_Q();
        const uint32_t rdy = mbar_test(bF + ck.s * 8, ck.ph) & mbar_test(bF + cv.s * 8, cv.ph);
        l0 += __shfl_xor_sync(0xffffffffu, l0, 1);
        l1 += __shfl_xor_sync(0xffffffffu, l1, 1);
        l0 += __shfl_xor_sync(0xffffffffu, l0, 2);
        l1 += __shfl_xor_sync(0xffffffffu, l1, 2);
        if (item >= K2_END) {
          TURN_SYNC();
          TRC(2);
          wg_fence();
          ISSUE_PV(cq, nblk == 1);
          wg_commit();
          if (wg == (it & 1)) TURN_ARRIVE();
          asm volatile("" : "+f"(gf0), "+f"(gf1), "+f"(l0), "+f"(l1));
          const float f0 = __fdividef(1.f - gf0, l0), f1 = __fdividef(1.f - gf1, l1);
          bf16* optr = ptr_add(g_ctx, eoff);
          wg_wait<0>();
          fence_regs(O);
          mbar_arrive_cluster_if(bH, warp & 1, sig);
          STORE_O(0); STORE_O(1); STORE_O(2); STORE_O(3);
          __syncwarp();
          mbar_arrive_if(bS2 + ((it - 1) & 3) * 8, lane == 0);
          break;
        }
        if (!rdy) mbar_wait2(bF + ck.s * 8, ck.ph, bF + cv.s * 8, cv.ph);
        TB(2);
        TURN_SYNC();
        TB(3);
        TRC(1);
        wg_fence();
        ISSUE_PV(cv, nblk == 1);
        wg_commit();
        ISSUE_QK(ck);
        wg_commit();
        TURN_ARRIVE();
        RELEASE(cq);
        TB(4);
        asm volatile("" : "+f"(gf0), "+f"(gf1), "+f"(l0), "+f"(l1));
        const float f0 = __fdividef(1.f - gf0, l0), f1 = __fdividef(1.f - gf1, l1);
        wg_wait<1>();
        fence_regs(O);
        fence_regs(P);
        TB(5);
        RELEASE(cv);
        {
          bf16* optr = ptr_add(g_ctx, eoff);
          STORE_O(0); STORE_O(1); STORE_O(2); STORE_O(3);
          __syncwarp();
          mbar_arrive_if(bS2 + ((it - 1) & 3) * 8, lane == 0);
        }
        TB(6);
        NEW_ITEM();
        TB(7);
        wg_wait<0>();
        fence_regs(S);
        TB(8);
      }
      TRC(3);
      if (wg == 1) { TS(1, 1); TSC(1, 3); }
    }
    __syncwarp();
    const uint32_t unit = item & 255;
    {
      const int mblk = (7 - (p.unit[unit][0] >> 1)) * 2 + rank, nhalf = p.unit[unit][0] & 1;
      float acc[144];
      uint32_t s = rot, ph = 0, prev = 0, k = 0;
      if (wg == 0) { TS(2, 0); TSC(2, 2); }
      uint32_t fa[16], fb[16], fc[16];
      const uint32_t aoff = (wg * 64 + warp * 16 + (lane & 15)) * 128 + (((lane >> 4) ^ (lane & 7)) << 4);
#define C_NEXT()                                                                                               \
  do {                                                                                                         \
    s = (s + 1) & 3;                                                                                           \
    if (s == rot) ph ^= 1;                                                                                     \
    mbar_wait(b3F + s * 8, ph);                                                                                \
  } while (0)
#define C_LOAD(F)                                                                                              \
  do {                                                                                                         \
    _Pragma("unroll") for (int t = 0; t < 4; t++)                                                              \
        ldsm_x4(F[4 * t], F[4 * t + 1], F[4 * t + 2], F[4 * t + 3], sbase + s * K3_STAGE + (aoff ^ (t * 32))); \
  } while (0)
#define C_MMA(F, S, H, SD)                                                                                     \
  do {                                                                                                         \
    const uint32_t st = sbase + (S) * K3_STAGE;                                                                \
    const uint64_t db = make_desc(st + 16384, 4096, 1024, 1), dt = make_desc(st + 49152, 16, 512, 2);          \
    _Pragma("unroll") for (int t = 0; t < 4; t++) {                                                            \
      const int sd = (t > 0) || (SD);                                                                          \
      if ((H) & 1) wgmma_rs_n128<1, 0>(acc, F[4 * t], F[4 * t + 1], F[4 * t + 2], F[4 * t + 3], db + (uint64_t)((t >> 1) * 1024 + (t & 1) * 128), sd); \
      if ((H) & 2) wgmma_rs_n128<1, 64>(acc, F[4 * t], F[4 * t + 1], F[4 * t + 2], F[4 * t + 3], db + (uint64_t)((t >> 1) * 1024 + (t & 1) * 128 + 512), sd); \
      if ((H) & 2) wgmma_rs_n32<1, 128>(acc, F[4 * t], F[4 * t + 1], F[4 * t + 2], F[4 * t + 3], dt + (uint64_t)(t * 64), sd); \
    }                                                                                                          \
  } while (0)
#define C_STEP(F, G)                                                                                           \
  {                                                                                                            \
    wg_fence();                                                                                                \
    C_MMA(F, s, 3, k > 0);                                                                                     \
    wg_commit();                                                                                               \
    wg_wait<1>();                                                                                              \
    fence_regs(G);                                                                                             \
    mbar_arrive_cluster_if(b3E + prev * 8, warp & 1, sig && k > 0);                                            \
    prev = s;                                                                                                  \
    TCK(k + 1);                                                                                                \
    C_NEXT();                                                                                                  \
    if ((tid & 127) == 0 && k < 11) TP(37 + wg * 12 + k);                                                      \
    if (++k + 3 >= lds32(sK1)) break;                                                                          \
    C_LOAD(G);                                                                                                 \
  }
      TCK(0);
      mbar_wait(b3F + s * 8, 0);
      if ((tid & 127) == 0) TP(36 + wg * 12);
      C_LOAD(fa);
#pragma unroll
      for (int i = 0; i < 16; i++) fb[i] = 0;
#pragma unroll 1
      for (;;) {
        C_STEP(fa, fb)
        C_STEP(fb, fa)
      }
      C_LOAD(fc);
      cluster_arrive();
      if (wg == 1) mbar_wait(bLd, 0);
      const uint32_t s0 = s;
      wg_fence();
      C_MMA(fc, s0, 2, 1);
      wg_commit();
      wg_wait<1>();
      fence_regs(fa);
      fence_regs(fb);
      C_NEXT();
      C_LOAD(fa);
      wg_fence();
      C_MMA(fa, s, 2, 1);
      C_MMA(fc, s0, 1, 1);
      wg_commit();
      C_NEXT();
      C_LOAD(fb);
      wg_fence();
      C_MMA(fb, s, 2, 1);
      wg_commit();
      C_MMA(fa, (s + 3) & 3, 1, 1);
      C_MMA(fb, s, 1, 1);
      wg_commit();
      mbar_arrive_if(bLd, tid < 128 && lane == 0);
      const uint32_t stail = sbase + K3_NST * K3_STAGE + warp_g * 1024;
      const int row = mblk * 128 + warp_g * 16;
      mbar_wait(bZ, 0);
#pragma unroll
      for (int h = 1; h >= 0; h--) {
        if (h) wg_wait<1>(); else wg_wait<0>();
#pragma unroll
        for (int i = h * 64; i < 64 + h * 80; i++) asm volatile("" : "+f"(acc[i])::"memory");
        if (!h && wg == 0) TS(2, 4);
#pragma unroll
        for (int i = h * 8; i < 8 + h * 10; i++) {
          const uint32_t ad = (i < 16) ? sbase + (i >> 2) * K3_STAGE + (aoff ^ ((i & 3) * 32))
                                       : stail + (lane & 15) * 64 + ((((i & 1) * 2 + (lane >> 4)) ^ ((lane >> 1) & 3)) << 4);
          asm volatile("stmatrix.sync.aligned.m8n8.x4.shared.b16 [%0], {%1, %2, %3, %4};" ::"r"(ad), "r"(pack_bf16(acc[i * 8], acc[i * 8 + 1])),
                       "r"(pack_bf16(acc[i * 8 + 2], acc[i * 8 + 3])), "r"(pack_bf16(acc[i * 8 + 4], acc[i * 8 + 5])), "r"(pack_bf16(acc[i * 8 + 6], acc[i * 8 + 7])) : "memory");
        }
        asm volatile("fence.proxy.async.shared::cta;" ::: "memory");
        __syncwarp();
        if (!h && wg == 0) TS(2, 5);
        if (lane == 0) {
#pragma unroll
          for (int c = h * 2; c < 2 + h * 3; c++)
            asm volatile("cp.reduce.async.bulk.tensor.2d.global.shared::cta.add.tile.bulk_group [%0, {%2, %3}], [%1];" ::"l"(&p.tmR[c >> 2]),
                         "r"((c < 4) ? sbase + c * K3_STAGE + warp_g * 2048 : stail), "r"((c < 4) ? nhalf * 256 + c * 64 : 512 + nhalf * 32), "r"(row) : "memory");
        }
        __syncwarp();
      }
      if (lane == 0) {
        asm volatile("cp.async.bulk.commit_group;" ::: "memory");
        if (wg == 0) TS(2, 6);
        asm volatile("cp.async.bulk.wait_group 0;" ::: "memory");
      }
      __syncwarp();
    }
    if (wg == 0) { TS(2, 1); TSC(2, 3); }
    cluster_wait();
  }
}

typedef CUresult (*EncFn)(CUtensorMap*, CUtensorMapDataType, cuuint32_t, void*, const cuuint64_t*, const cuuint64_t*, const cuuint32_t*,
                          const cuuint32_t*, CUtensorMapInterleave, CUtensorMapSwizzle, CUtensorMapL2promotion, CUtensorMapFloatOOBfill);

static void enc2d(EncFn enc, CUtensorMap* m, const void* ptr, uint64_t cols, uint64_t rows, uint32_t bc, uint32_t br,
                  CUtensorMapSwizzle sw = CU_TENSOR_MAP_SWIZZLE_128B) {
  cuuint64_t gd[2] = {cols, rows}, gs[1] = {cols * 2};
  cuuint32_t bx[2] = {bc, br}, es[2] = {1, 1};
  enc(m, CU_TENSOR_MAP_DATA_TYPE_BFLOAT16, 2, const_cast<void*>(ptr), gd, gs, bx, es, CU_TENSOR_MAP_INTERLEAVE_NONE, sw,
      CU_TENSOR_MAP_L2_PROMOTION_L2_256B, CU_TENSOR_MAP_FLOAT_OOB_FILL_NONE);
}
static void enc3d(EncFn enc, CUtensorMap* m, const void* ptr, uint64_t cols, uint64_t rows, uint32_t br, uint32_t bch) {
  cuuint64_t gd[3] = {64, rows, cols / 64}, gs[2] = {cols * 2, 128};
  cuuint32_t bx[3] = {64, br, bch}, es[3] = {1, 1, 1};
  enc(m, CU_TENSOR_MAP_DATA_TYPE_BFLOAT16, 3, const_cast<void*>(ptr), gd, gs, bx, es, CU_TENSOR_MAP_INTERLEAVE_NONE,
      CU_TENSOR_MAP_SWIZZLE_128B, CU_TENSOR_MAP_L2_PROMOTION_L2_256B, CU_TENSOR_MAP_FLOAT_OOB_FILL_NONE);
}

static int g_sched[10] = {11, 10, 7, 4, 4, 4, 6, 8, 6, 24};
static void build_k1_jobs(Params& p) {
  int cnt[NCLUSTER];
  for (int c = 0; c < NCLUSTER; c++) {
    cnt[c] = 0;
    for (int i = 0; i <= K1_MAXJOBS; i++) p.jobs[c][i] = 0;
  }
  auto add = [&](int c, int nch, int a_sel, int mp, int w_sel, int chunk0) {
    p.jobs[c][cnt[c]++] = (uint16_t)((nch - 1) | (a_sel << 2) | (mp << 3) | (w_sel << 6) | (chunk0 << 8));
  };
  const char* plan = "ccccccccccc cccccccccc ccccccc cccc xxxx xxxx xxxxxx xxxxxxxx";
  int TIE = 0;
  int XA = 0;
  const char* cur[8];
  int tend[8] = {};
  for (int g = 0; g < 8; g++) {
    cur[g] = plan;
    while (*plan == 'c' || *plan == 'x') plan++;
    if (*plan) plan++;
  }
  int kc = 0, kx = 0;
  for (;;) {
    int b = -1, bt = 0;
    for (int g = 0; g < 8; g++) {
      const int t = tend[g] + (*cur[g] == 'x' ? 94 : 85);
      if ((*cur[g] == 'c' || *cur[g] == 'x') && (b < 0 || t < bt || (TIE && t == bt))) { b = g; bt = t; }
    }
    if (b < 0) break;
    const int a = kx - XA;
    for (int mp = 0; mp < 8; mp++) {
      if (*cur[b] == 'c') add(b * 8 + mp, 4, 0, mp, kc & 1, (kc >> 1) * 4);
      else if (a >= 0 && a < 7) add(b * 8 + mp, a == 0 ? 3 : 4, 1, mp, 2, a == 0 ? 24 : (a - 1) * 4);
      else add(b * 8 + mp, 4, 1, mp, 3, (a < 0 ? kx : kx - 7) * 4);
    }
    if (*cur[b] == 'c') kc++; else kx++;
    cur[b]++;
    tend[b] = bt;
  }
  for (int mp = 0; mp < 8; mp++) add(64 + mp / 4, 4, 1, mp, 3, 15 * 4);
  for (int cc = 0; cc < NCLUSTER; cc++)
    for (int i = 0; i < cnt[cc]; i++) {
      const int key = p.jobs[cc][i] & 0x3C;
      if (i == 0 || (p.jobs[cc][i - 1] & 0x3C) != key) p.jobs[cc][i] |= (1 << 14);
      if (i == cnt[cc] - 1 || (p.jobs[cc][i + 1] & 0x3C) != key) p.jobs[cc][i] |= (1 << 15);
    }
}

static void build_k2_items(Params& p) {
  int n = 0;
  const int SCHED_N1 = g_sched[8], SCHED_N2 = g_sched[9];
  int N0 = 2, J0 = 2;
  for (int j = 7; j >= J0; j--)
    for (int h = 0; h < N0; h++) p.order[n++] = (uint8_t)(h * 8 + j);
  for (int j = 7; j >= 0; j--)
    for (int h = 0; h < SCHED_N1; h++)
      if (!(h < N0 && j >= J0)) p.order[n++] = (uint8_t)(h * 8 + j);
  for (int j = 7; j >= 4; j--)
    for (int h = SCHED_N1; h < SCHED_N2; h++) p.order[n++] = (uint8_t)(h * 8 + j);
  for (int j = 7; j >= 0; j--)
    for (int h = SCHED_N1; h < 32; h++)
      if (!(h < SCHED_N2 && j >= 4)) p.order[n++] = (uint8_t)(h * 8 + j);
  int TJ[2] = {0, 0}, TP = 0;
  for (int t = 0; t < 2; t++) {
    if (!TJ[t]) continue;
    int i = 0;
    while (p.order[i] != 31 * 8 + TJ[t]) i++;
    for (; i < 255 - TP; i++) p.order[i] = p.order[i + 1];
    p.order[i] = (uint8_t)(31 * 8 + TJ[t]);
  }
}

static void build_k3_units(Params& p) {
  int um = 0;
  for (int u = 0; u < 66; u++) {
    int t = (u % 28 < 14) ? u % 28 : 27 - u % 28, i = u / 14;
    if (um == 1) t = u % 14;
    if (um == 2) { t = (u % 28) / 2; i = (u / 28) * 2 + (u & 1); }
    if (um == 3) { t = u / 4; i = u & 3; }
    if (um == 4) { t = (u < 42) ? u / 3 : u - 42; i = (u < 42) ? u % 3 : 3; }
    if (u >= 56) { t = 14 + ((0x199 >> (u - 56)) & 1); i = (u - 56) / 2; }
    uint8_t* w = p.unit[u];
    w[0] = (uint8_t)t; w[1] = (uint8_t)i; w[2] = (uint8_t)(i * K3_NS); w[3] = (uint8_t)(((u >= 56) ? 5 : 4) * K3_NS);
  }
}

extern "C" void kernel_launch(void* const* d_in, const int* in_sizes, int n_in, void* d_out, int out_size) {
  const bf16* x = (const bf16*)d_in[0];
  const bf16* wqkv = (const bf16*)d_in[1];
  const bf16* wo = (const bf16*)d_in[2];
  const bf16* ckv = (const bf16*)d_in[4];
  const bf16* w_q = (const bf16*)d_in[5];
  const bf16* w_uk = (const bf16*)d_in[6];
  const bf16* w_uv = (const bf16*)d_in[7];
  const bf16* w_o = (const bf16*)d_in[8];
  const bf16* gate_w = (const bf16*)d_in[9];

  EncFn enc = nullptr;
  cudaDriverEntryPointQueryResult qr;
  cudaGetDriverEntryPoint("cuTensorMapEncodeTiled", (void**)&enc, cudaEnableDefault, &qr);
  void *pK, *pV, *pCtx, *pQA;
  cudaGetSymbolAddress(&pQA, g_QKVA);
  cudaGetSymbolAddress(&pK, g_K);
  cudaGetSymbolAddress(&pV, g_V);
  cudaGetSymbolAddress(&pCtx, g_ctx);

  static Params p;
  enc2d(enc, &p.tmA[0], ckv, DC, S_LEN, 64, 128);
  enc2d(enc, &p.tmA[1], x, DM, S_LEN, 64, 128);
  enc3d(enc, &p.tmW[0], w_uk, HDIM, DC, 16, 4);
  enc3d(enc, &p.tmW[1], w_uv, HDIM, DC, 16, 4);
  enc3d(enc, &p.tmW[2], wqkv, NQKVA, DM, 16, 4);
  enc3d(enc, &p.tmW[3], w_q, HDIM, DM, 16, 4);
  build_k1_jobs(p);
  enc2d(enc, &p.tmK, pK, HDIM, S_LEN, 64, 128);
  enc2d(enc, &p.tmV, pV, HDIM, S_LEN, 64, 128);
  enc2d(enc, &p.tmQ, pCtx, KCAT, S_LEN, 64, 64);
  build_k2_items(p);
  build_k3_units(p);
  for (int i = 0; i < 3; i++) {
    const cuuint64_t ld = (i < 2 ? NQKVA : KCAT) * 2, nch = (i < 2) ? 27 : 9;
    cuuint64_t gd[4] = {64, S_LEN / 2, i ? 2 : nch, i ? nch : 2}, gs[3] = {2 * ld, i ? ld : 128, i ? 128 : ld};
    cuuint32_t bx[4] = {64, i ? 8u : 16u, i ? 2u : 9u, i ? 9u : 2u}, es[4] = {1, 1, 1, 1};
    enc(&p.tmL[i], CU_TENSOR_MAP_DATA_TYPE_BFLOAT16, 4, (i < 2) ? pQA : (void*)((bf16*)pCtx + HDIM), gd, gs, bx, es, CU_TENSOR_MAP_INTERLEAVE_NONE,
        CU_TENSOR_MAP_SWIZZLE_128B, CU_TENSOR_MAP_L2_PROMOTION_L2_256B, CU_TENSOR_MAP_FLOAT_OOB_FILL_NONE);
  }
  enc2d(enc, &p.tmC, pCtx, KCAT, S_LEN, 64, 128);
  enc3d(enc, &p.tmO[0], w_o, DM, HDIM, 32, 4);
  enc3d(enc, &p.tmO[1], wo, DM, DM, 32, 4);
  enc2d(enc, &p.tmOt[0], w_o, DM, HDIM, 32, 32, CU_TENSOR_MAP_SWIZZLE_64B);
  enc2d(enc, &p.tmOt[1], wo, DM, DM, 32, 32, CU_TENSOR_MAP_SWIZZLE_64B);
  enc2d(enc, &p.tmR[0], d_out, DM, S_LEN, 64, 16);
  enc2d(enc, &p.tmR[1], d_out, DM, S_LEN, 32, 16, CU_TENSOR_MAP_SWIZZLE_64B);

  cudaFuncSetAttribute(fused_kernel, cudaFuncAttributeMaxDynamicSharedMemorySize, SMEM_BYTES);
  fused_kernel<<<NCLUSTER * 2, 384, SMEM_BYTES>>>(p, x, gate_w, (bf16*)d_out);
}
```

```cpp
#include <cuda_runtime.h>
#include <cuda_bf16.h>
#include <cuda.h>
#include <stdint.h>

typedef __nv_bfloat16 bf16;

constexpr int S_LEN = 2048, DM = 576, DC = 512, HDIM = 4096, NQKVA = 1728, KCAT = 4672;
constexpr int NCLUSTER = 66;

__device__ __align__(1024) bf16 g_K[S_LEN * HDIM];
__device__ __align__(1024) bf16 g_V[S_LEN * HDIM];
__device__ __align__(1024) bf16 g_QKVA[S_LEN * NQKVA + 64];
__device__ __align__(1024) bf16 g_ctx[S_LEN * KCAT];
__device__ float g_gate[S_LEN];
__device__ __align__(16) unsigned int g_sync[400];
constexpr int F_QKVA = 0, F_HP = 16, F_CTX = 32, F_OA = 48, F_CLM = 64, F_GATE = 96, F_TICK = 97, F_DONE = 98, F_XCH = 128, F_EPOCH = 384;

__device__ __forceinline__ uint32_t smem_u32(const void* p) { return (uint32_t)__cvta_generic_to_shared(p); }
__device__ __forceinline__ void mbar_init(uint32_t a, uint32_t c) {
  asm volatile("mbarrier.init.shared::cta.b64 [%0], %1;" ::"r"(a), "r"(c));
}
__device__ __forceinline__ void mbar_expect(uint32_t a, uint32_t b) {
  asm volatile("mbarrier.arrive.expect_tx.shared::cta.b64 _, [%0], %1;" ::"r"(a), "r"(b) : "memory");
}
#define TS(k, i)
#define TSC(k, i)
#define TSM(k)
#define BSEG(i)
#define TB(k)
#define TRC(fl)
#define TCK(i)
#define TP(i)
#define SPIN_LIMIT "4194304"
__device__ __forceinline__ void mbar_wait(uint32_t a, uint32_t parity) {
  asm volatile(
      "{\n.reg .pred p;\n.reg .u32 n;\n"
      "mbarrier.try_wait.parity.shared::cta.b64 p, [%0], %1;\n"
      "@p bra DONE;\n"
      "mov.u32 n, 0;\n"
      "LOOP:\n"
      "mbarrier.try_wait.parity.shared::cta.b64 p, [%0], %1;\n"
      "@p bra DONE;\n"
      "add.u32 n, n, 1;\n"
      "setp.lt.u32 p, n, " SPIN_LIMIT ";\n"
      "@p bra LOOP;\n"
      "DONE:\n}" ::"r"(a), "r"(parity) : "memory");
}
template <int NS>
__device__ __forceinline__ void mbar_wait_ns(uint32_t a, uint32_t parity) {
  asm volatile(
      "{\n.reg .pred p;\n.reg .u32 n;\n"
      "mov.u32 n, 0;\n"
      "LOOP:\n"
      "mbarrier.try_wait.parity.shared::cta.b64 p, [%0], %1, %2;\n"
      "@p bra DONE;\n"
      "add.u32 n, n, 1;\n"
      "setp.lt.u32 p, n, " SPIN_LIMIT ";\n"
      "@p bra LOOP;\n"
      "DONE:\n}" ::"r"(a), "r"(parity), "n"(NS) : "memory");
}
__device__ __forceinline__ void mbar_wait2(uint32_t a, uint32_t pa, uint32_t b, uint32_t pb) {
  asm volatile(
      "{\n.reg .pred p, q;\n.reg .u32 n;\n"
      "mov.u32 n, 0;\n"
      "LOOP:\n"
      "mbarrier.try_wait.parity.shared::cta.b64 p, [%0], %1;\n"
      "mbarrier.try_wait.parity.shared::cta.b64 q, [%2], %3;\n"
      "add.u32 n, n, 1;\n"
      "and.pred p, p, q;\n"
      "setp.lt.and.u32 p, n, " SPIN_LIMIT ", !p;\n"
      "@p bra LOOP;\n"
      "}" ::"r"(a), "r"(pa), "r"(b), "r"(pb) : "memory");
}
__device__ __forceinline__ uint32_t mbar_test(uint32_t a, uint32_t parity) {
  uint32_t r;
  asm volatile("{\n.reg .pred p;\nmbarrier.test_wait.parity.shared::cta.b64 p, [%1], %2;\nselp.u32 %0, 1, 0, p;\n}" : "=r"(r) : "r"(a), "r"(parity) : "memory");
  return r;
}
__device__ __forceinline__ void mbar_arrive(uint32_t a) {
  asm volatile("mbarrier.arrive.shared::cta.b64 _, [%0];" ::"r"(a) : "memory");
}
__device__ __forceinline__ void mbar_arrive_cluster(uint32_t a, uint32_t cta) {
  asm volatile("{\n.reg .b32 r;\nmapa.shared::cluster.u32 r, %0, %1;\nmbarrier.arrive.shared::cluster.b64 _, [r];\n}" ::"r"(a),
               "r"(cta) : "memory");
}
__device__ __forceinline__ void mbar_arrive_cluster_if(uint32_t a, uint32_t cta, bool pred) {
  asm volatile("{\n.reg .b32 r;\n.reg .pred p;\nsetp.ne.u32 p, %2, 0;\nmapa.shared::cluster.u32 r, %0, %1;\n@p mbarrier.arrive.shared::cluster.b64 _, [r];\n}" ::"r"(a),
               "r"(cta), "r"((uint32_t)pred) : "memory");
}
__device__ __forceinline__ void anchor(float v, uint32_t pred) {
  asm volatile("{\n.reg .pred p;\nsetp.ne.u32 p, %1, 0;\n@p st.shared.f32 [%1], %0;\n}" ::"f"(v), "r"(pred) : "memory");
}
__device__ __forceinline__ void mbar_arrive_if(uint32_t a, bool pred) {
  asm volatile("{\n.reg .pred p;\nsetp.ne.u32 p, %1, 0;\n@p mbarrier.arrive.shared::cta.b64 _, [%0];\n}" ::"r"(a), "r"((uint32_t)pred) : "memory");
}
__device__ __forceinline__ void tma2d(uint32_t dst, const CUtensorMap* m, uint32_t bar, int c0, int c1) {
  asm volatile("cp.async.bulk.tensor.2d.shared::cluster.global.mbarrier::complete_tx::bytes [%0], [%1, {%3, %4}], [%2];" ::"r"(dst),
               "l"(m), "r"(bar), "r"(c0), "r"(c1) : "memory");
}
__device__ __forceinline__ void tma2d_mc(uint32_t dst, const CUtensorMap* m, uint32_t bar, int c0, int c1, uint16_t mask) {
  asm volatile(
      "cp.async.bulk.tensor.2d.shared::cluster.global.mbarrier::complete_tx::bytes.multicast::cluster [%0], [%1, {%3, %4}], [%2], %5;" ::"r"(dst),
      "l"(m), "r"(bar), "r"(c0), "r"(c1), "h"(mask) : "memory");
}
__device__ __forceinline__ void tma3d_mc(uint32_t dst, const CUtensorMap* m, uint32_t bar, int c0, int c1, int c2, uint16_t mask) {
  asm volatile(
      "cp.async.bulk.tensor.3d.shared::cluster.global.mbarrier::complete_tx::bytes.multicast::cluster [%0], [%1, {%3, %4, %5}], [%2], %6;" ::"r"(dst),
      "l"(m), "r"(bar), "r"(c0), "r"(c1), "r"(c2), "h"(mask) : "memory");
}
__device__ __forceinline__ void tma3d(uint32_t dst, const CUtensorMap* m, uint32_t bar, int c0, int c1, int c2) {
  asm volatile(
      "cp.async.bulk.tensor.3d.shared::cluster.global.mbarrier::complete_tx::bytes [%0], [%1, {%3, %4, %5}], [%2];" ::"r"(dst),
      "l"(m), "r"(bar), "r"(c0), "r"(c1), "r"(c2) : "memory");
}
__device__ __forceinline__ void tma_pf2d(const CUtensorMap* m, int c0, int c1) {
  asm volatile("cp.async.bulk.prefetch.tensor.2d.L2.global [%0, {%1, %2}];" ::"l"(m), "r"(c0), "r"(c1) : "memory");
}
__device__ __forceinline__ void tma_pf3d(const CUtensorMap* m, int c0, int c1, int c2) {
  asm volatile("cp.async.bulk.prefetch.tensor.3d.L2.global [%0, {%1, %2, %3}];" ::"l"(m), "r"(c0), "r"(c1), "r"(c2) : "memory");
}
__device__ __forceinline__ void prefetch_tmap(const CUtensorMap* m) {
  asm volatile("prefetch.tensormap [%0];" ::"l"(m) : "memory");
}
__device__ __forceinline__ void cluster_arrive() { asm volatile("barrier.cluster.arrive.relaxed.aligned;" ::: "memory"); }
__device__ __forceinline__ void cluster_wait() { asm volatile("barrier.cluster.wait.aligned;" ::: "memory"); }
__device__ __forceinline__ void cluster_sync() {
  cluster_arrive();
  cluster_wait();
}
__device__ __forceinline__ uint32_t cluster_rank() {
  uint32_t r;
  asm volatile("mov.u32 %0, %%cluster_ctarank;" : "=r"(r));
  return r;
}
__device__ __forceinline__ bool elect_one() {
  uint32_t p;
  asm volatile("{\n.reg .pred q;\nelect.sync _|q, 0xffffffff;\nselp.u32 %0, 1, 0, q;\n}" : "=r"(p));
  return p;
}
__device__ __forceinline__ void ldsm_x4(uint32_t& r0, uint32_t& r1, uint32_t& r2, uint32_t& r3, uint32_t addr) {
  asm volatile("ldmatrix.sync.aligned.m8n8.x4.shared.b16 {%0, %1, %2, %3}, [%4];" : "=r"(r0), "=r"(r1), "=r"(r2), "=r"(r3) : "r"(addr) : "memory");
}
__device__ __forceinline__ void wg_fence() { asm volatile("wgmma.fence.sync.aligned;" ::: "memory"); }
__device__ __forceinline__ void wg_commit() { asm volatile("wgmma.commit_group.sync.aligned;" ::: "memory"); }
template <int N>
__device__ __forceinline__ void wg_wait() { asm volatile("wgmma.wait_group.sync.aligned %0;" ::"n"(N) : "memory"); }
template <int N>
__device__ __forceinline__ void reg_alloc() { asm volatile("setmaxnreg.inc.sync.aligned.u32 %0;" ::"n"(N)); }
template <int N>
__device__ __forceinline__ void reg_dealloc() { asm volatile("setmaxnreg.dec.sync.aligned.u32 %0;" ::"n"(N)); }
__device__ __forceinline__ void bar_sync(int id, int n) { asm volatile("bar.sync %0, %1;" ::"r"(id), "r"(n) : "memory"); }
__device__ __forceinline__ void bar_arrive(int id, int n) { asm volatile("bar.arrive %0, %1;" ::"r"(id), "r"(n) : "memory"); }
template <int NT>
__device__ __forceinline__ void fence_regs(float (&d)[NT]) {
#pragma unroll
  for (int i = 0; i < NT; i++) asm volatile("" : "+f"(d[i])::"memory");
}
template <int NT>
__device__ __forceinline__ void fence_regs(uint32_t (&d)[NT]) {
#pragma unroll
  for (int i = 0; i < NT; i++) asm volatile("" : "+r"(d[i])::"memory");
}
__device__ __forceinline__ uint64_t make_desc(uint32_t saddr, uint32_t lbo, uint32_t sbo, uint32_t layout) {
  return (uint64_t)((saddr & 0x3FFFF) >> 4) | ((uint64_t)(lbo >> 4) << 16) | ((uint64_t)(sbo >> 4) << 32) | ((uint64_t)layout << 62);
}
__device__ __forceinline__ uint32_t pack_bf16(float lo, float hi) {
  uint32_t r;
  asm("cvt.rn.bf16x2.f32 %0, %1, %2;" : "=r"(r) : "f"(hi), "f"(lo));
  return r;
}
__device__ __forceinline__ float ex2(float x) {
  float r;
  asm("ex2.approx.ftz.f32 %0, %1;" : "=f"(r) : "f"(x));
  return r;
}
__device__ __forceinline__ void st_v4(void* p, uint32_t a, uint32_t b, uint32_t c, uint32_t d) {
#define ST_MOD ".cs"
  asm volatile("st.global" ST_MOD ".v4.b32 [%0], {%1, %2, %3, %4};" ::"l"(p), "r"(a), "r"(b), "r"(c), "r"(d) : "memory");
}
#define STA_MOD ".cs"
__device__ __forceinline__ void st_v4a(void* p, uint32_t a, uint32_t b, uint32_t c, uint32_t d) {
  asm volatile("st.global" STA_MOD ".v4.b32 [%0], {%1, %2, %3, %4};" ::"l"(p), "r"(a), "r"(b), "r"(c), "r"(d) : "memory");
}
template <typename T>
__device__ __forceinline__ T* ptr_add(T* base, uint32_t bytes) {
  uint64_t r;
  asm volatile("{\n.reg .u32 l, h;\nmov.b64 {l, h}, %1;\nadd.cc.u32 l, l, %2;\naddc.u32 h, h, 0;\nmov.b64 %0, {l, h};\n}" : "=l"(r) : "l"(base), "r"(bytes));
  return reinterpret_cast<T*>(r);
}
__device__ __forceinline__ float bf_lo(uint32_t v) { return __uint_as_float(v << 16); }
__device__ __forceinline__ float bf_hi(uint32_t v) { return __uint_as_float(v & 0xFFFF0000u); }

__device__ __forceinline__ void quad_transpose(uint32_t& a0, uint32_t& a1, uint32_t& a2, uint32_t& a3, int q) {
  const bool o1 = q & 1, o2 = q & 2;
  uint32_t t0 = o1 ? a0 : a1, t1 = o1 ? a2 : a3;
  t0 = __shfl_xor_sync(0xffffffffu, t0, 1);
  t1 = __shfl_xor_sync(0xffffffffu, t1, 1);
  if (o1) { a0 = t0; a2 = t1; } else { a1 = t0; a3 = t1; }
  t0 = o2 ? a0 : a2;
  t1 = o2 ? a1 : a3;
  t0 = __shfl_xor_sync(0xffffffffu, t0, 2);
  t1 = __shfl_xor_sync(0xffffffffu, t1, 2);
  if (o2) { a0 = t0; a1 = t1; } else { a2 = t0; a3 = t1; }
}

template<int TB, int OFF, int NT>
__device__ __forceinline__ void wgmma_ss_n256(float (&d)[NT], uint64_t da, uint64_t db, int scale_d) {
  asm volatile("{\n.reg .pred p;\nsetp.ne.b32 p, %130, 0;\n"
    "wgmma.mma_async.sync.aligned.m64n256k16.f32.bf16.bf16 {%0, %1, %2, %3, %4, %5, %6, %7, %8, %9, %10, %11, %12, %13, %14, %15, %16, %17, %18, %19, %20, %21, %22, %23, %24, %25, %26, %27, %28, %29, %30, %31, %32, %33, %34, %35, %36, %37, %38, %39, %40, %41, %42, %43, %44, %45, %46, %47, %48, %49, %50, %51, %52, %53, %54, %55, %56, %57, %58, %59, %60, %61, %62, %63, %64, %65, %66, %67, %68, %69, %70, %71, %72, %73, %74, %75, %76, %77, %78, %79, %80, %81, %82, %83, %84, %85, %86, %87, %88, %89, %90, %91, %92, %93, %94, %95, %96, %97, %98, %99, %100, %101, %102, %103, %104, %105, %106, %107, %108, %109, %110, %111, %112, %113, %114, %115, %116, %117, %118, %119, %120, %121, %122, %123, %124, %125, %126, %127}, %128, %129, p, 1, 1, 0, %131;\n}\n"
    : "+f"(d[OFF+0]), "+f"(d[OFF+1]), "+f"(d[OFF+2]), "+f"(d[OFF+3]), "+f"(d[OFF+4]), "+f"(d[OFF+5]), "+f"(d[OFF+6]), "+f"(d[OFF+7]), "+f"(d[OFF+8]), "+f"(d[OFF+9]), "+f"(d[OFF+10]), "+f"(d[OFF+11]), "+f"(d[OFF+12]), "+f"(d[OFF+13]), "+f"(d[OFF+14]), "+f"(d[OFF+15]), "+f"(d[OFF+16]), "+f"(d[OFF+17]), "+f"(d[OFF+18]), "+f"(d[OFF+19]), "+f"(d[OFF+20]), "+f"(d[OFF+21]), "+f"(d[OFF+22]), "+f"(d[OFF+23]), "+f"(d[OFF+24]), "+f"(d[OFF+25]), "+f"(d[OFF+26]), "+f"(d[OFF+27]), "+f"(d[OFF+28]), "+f"(d[OFF+29]), "+f"(d[OFF+30]), "+f"(d[OFF+31]), "+f"(d[OFF+32]), "+f"(d[OFF+33]), "+f"(d[OFF+34]), "+f"(d[OFF+35]), "+f"(d[OFF+36]), "+f"(d[OFF+37]), "+f"(d[OFF+38]), "+f"(d[OFF+39]), "+f"(d[OFF+40]), "+f"(d[OFF+41]), "+f"(d[OFF+42]), "+f"(d[OFF+43]), "+f"(d[OFF+44]), "+f"(d[OFF+45]), "+f"(d[OFF+46]), "+f"(d[OFF+47]), "+f"(d[OFF+48]), "+f"(d[OFF+49]), "+f"(d[OFF+50]), "+f"(d[OFF+51]), "+f"(d[OFF+52]), "+f"(d[OFF+53]), "+f"(d[OFF+54]), "+f"(d[OFF+55]), "+f"(d[OFF+56]), "+f"(d[OFF+57]), "+f"(d[OFF+58]), "+f"(d[OFF+59]), "+f"(d[OFF+60]), "+f"(d[OFF+61]), "+f"(d[OFF+62]), "+f"(d[OFF+63]), "+f"(d[OFF+64]), "+f"(d[OFF+65]), "+f"(d[OFF+66]), "+f"(d[OFF+67]), "+f"(d[OFF+68]), "+f"(d[OFF+69]), "+f"(d[OFF+70]), "+f"(d[OFF+71]), "+f"(d[OFF+72]), "+f"(d[OFF+73]), "+f"(d[OFF+74]), "+f"(d[OFF+75]), "+f"(d[OFF+76]), "+f"(d[OFF+77]), "+f"(d[OFF+78]), "+f"(d[OFF+79]), "+f"(d[OFF+80]), "+f"(d[OFF+81]), "+f"(d[OFF+82]), "+f"(d[OFF+83]), "+f"(d[OFF+84]), "+f"(d[OFF+85]), "+f"(d[OFF+86]), "+f"(d[OFF+87]), "+f"(d[OFF+88]), "+f"(d[OFF+89]), "+f"(d[OFF+90]), "+f"(d[OFF+91]), "+f"(d[OFF+92]), "+f"(d[OFF+93]), "+f"(d[OFF+94]), "+f"(d[OFF+95]), "+f"(d[OFF+96]), "+f"(d[OFF+97]), "+f"(d[OFF+98]), "+f"(d[OFF+99]), "+f"(d[OFF+100]), "+f"(d[OFF+101]), "+f"(d[OFF+102]), "+f"(d[OFF+103]), "+f"(d[OFF+104]), "+f"(d[OFF+105]), "+f"(d[OFF+106]), "+f"(d[OFF+107]), "+f"(d[OFF+108]), "+f"(d[OFF+109]), "+f"(d[OFF+110]), "+f"(d[OFF+111]), "+f"(d[OFF+112]), "+f"(d[OFF+113]), "+f"(d[OFF+114]), "+f"(d[OFF+115]), "+f"(d[OFF+116]), "+f"(d[OFF+117]), "+f"(d[OFF+118]), "+f"(d[OFF+119]), "+f"(d[OFF+120]), "+f"(d[OFF+121]), "+f"(d[OFF+122]), "+f"(d[OFF+123]), "+f"(d[OFF+124]), "+f"(d[OFF+125]), "+f"(d[OFF+126]), "+f"(d[OFF+127])
    : "l"(da), "l"(db), "r"(scale_d), "n"(TB));
}
template<int TB, int OFF, int NT>
__device__ __forceinline__ void wgmma_ss_n32(float (&d)[NT], uint64_t da, uint64_t db, int scale_d) {
  asm volatile("{\n.reg .pred p;\nsetp.ne.b32 p, %18, 0;\n"
    "wgmma.mma_async.sync.aligned.m64n32k16.f32.bf16.bf16 {%0, %1, %2, %3, %4, %5, %6, %7, %8, %9, %10, %11, %12, %13, %14, %15}, %16, %17, p, 1, 1, 0, %19;\n}\n"
    : "+f"(d[OFF+0]), "+f"(d[OFF+1]), "+f"(d[OFF+2]), "+f"(d[OFF+3]), "+f"(d[OFF+4]), "+f"(d[OFF+5]), "+f"(d[OFF+6]), "+f"(d[OFF+7]), "+f"(d[OFF+8]), "+f"(d[OFF+9]), "+f"(d[OFF+10]), "+f"(d[OFF+11]), "+f"(d[OFF+12]), "+f"(d[OFF+13]), "+f"(d[OFF+14]), "+f"(d[OFF+15])
    : "l"(da), "l"(db), "r"(scale_d), "n"(TB));
}
template<int TB, int OFF, int NT>
__device__ __forceinline__ void wgmma_rs_n128(float (&d)[NT], uint32_t a0, uint32_t a1, uint32_t a2, uint32_t a3, uint64_t db, int scale_d) {
  asm volatile("{\n.reg .pred p;\nsetp.ne.b32 p, %69, 0;\n"
    "wgmma.mma_async.sync.aligned.m64n128k16.f32.bf16.bf16 {%0, %1, %2, %3, %4, %5, %6, %7, %8, %9, %10, %11, %12, %13, %14, %15, %16, %17, %18, %19, %20, %21, %22, %23, %24, %25, %26, %27, %28, %29, %30, %31, %32, %33, %34, %35, %36, %37, %38, %39, %40, %41, %42, %43, %44, %45, %46, %47, %48, %49, %50, %51, %52, %53, %54, %55, %56, %57, %58, %59, %60, %61, %62, %63}, {%64, %65, %66, %67}, %68, p, 1, 1, %70;\n}\n"
    : "+f"(d[OFF+0]), "+f"(d[OFF+1]), "+f"(d[OFF+2]), "+f"(d[OFF+3]), "+f"(d[OFF+4]), "+f"(d[OFF+5]), "+f"(d[OFF+6]), "+f"(d[OFF+7]), "+f"(d[OFF+8]), "+f"(d[OFF+9]), "+f"(d[OFF+10]), "+f"(d[OFF+11]), "+f"(d[OFF+12]), "+f"(d[OFF+13]), "+f"(d[OFF+14]), "+f"(d[OFF+15]), "+f"(d[OFF+16]), "+f"(d[OFF+17]), "+f"(d[OFF+18]), "+f"(d[OFF+19]), "+f"(d[OFF+20]), "+f"(d[OFF+21]), "+f"(d[OFF+22]), "+f"(d[OFF+23]), "+f"(d[OFF+24]), "+f"(d[OFF+25]), "+f"(d[OFF+26]), "+f"(d[OFF+27]), "+f"(d[OFF+28]), "+f"(d[OFF+29]), "+f"(d[OFF+30]), "+f"(d[OFF+31]), "+f"(d[OFF+32]), "+f"(d[OFF+33]), "+f"(d[OFF+34]), "+f"(d[OFF+35]), "+f"(d[OFF+36]), "+f"(d[OFF+37]), "+f"(d[OFF+38]), "+f"(d[OFF+39]), "+f"(d[OFF+40]), "+f"(d[OFF+41]), "+f"(d[OFF+42]), "+f"(d[OFF+43]), "+f"(d[OFF+44]), "+f"(d[OFF+45]), "+f"(d[OFF+46]), "+f"(d[OFF+47]), "+f"(d[OFF+48]), "+f"(d[OFF+49]), "+f"(d[OFF+50]), "+f"(d[OFF+51]), "+f"(d[OFF+52]), "+f"(d[OFF+53]), "+f"(d[OFF+54]), "+f"(d[OFF+55]), "+f"(d[OFF+56]), "+f"(d[OFF+57]), "+f"(d[OFF+58]), "+f"(d[OFF+59]), "+f"(d[OFF+60]), "+f"(d[OFF+61]), "+f"(d[OFF+62]), "+f"(d[OFF+63])
    : "r"(a0), "r"(a1), "r"(a2), "r"(a3), "l"(db), "r"(scale_d), "n"(TB));
}
template<int TB, int OFF, int NT>
__device__ __forceinline__ void wgmma_rs_n256(float (&d)[NT], uint32_t a0, uint32_t a1, uint32_t a2, uint32_t a3, uint64_t db, int scale_d) {
  asm volatile("{\n.reg .pred p;\nsetp.ne.b32 p, %133, 0;\n"
    "wgmma.mma_async.sync.aligned.m64n256k16.f32.bf16.bf16 {%0, %1, %2, %3, %4, %5, %6, %7, %8, %9, %10, %11, %12, %13, %14, %15, %16, %17, %18, %19, %20, %21, %22, %23, %24, %25, %26, %27, %28, %29, %30, %31, %32, %33, %34, %35, %36, %37, %38, %39, %40, %41, %42, %43, %44, %45, %46, %47, %48, %49, %50, %51, %52, %53, %54, %55, %56, %57, %58, %59, %60, %61, %62, %63, %64, %65, %66, %67, %68, %69, %70, %71, %72, %73, %74, %75, %76, %77, %78, %79, %80, %81, %82, %83, %84, %85, %86, %87, %88, %89, %90, %91, %92, %93, %94, %95, %96, %97, %98, %99, %100, %101, %102, %103, %104, %105, %106, %107, %108, %109, %110, %111, %112, %113, %114, %115, %116, %117, %118, %119, %120, %121, %122, %123, %124, %125, %126, %127}, {%128, %129, %130, %131}, %132, p, 1, 1, %134;\n}\n"
    : "+f"(d[OFF+0]), "+f"(d[OFF+1]), "+f"(d[OFF+2]), "+f"(d[OFF+3]), "+f"(d[OFF+4]), "+f"(d[OFF+5]), "+f"(d[OFF+6]), "+f"(d[OFF+7]), "+f"(d[OFF+8]), "+f"(d[OFF+9]), "+f"(d[OFF+10]), "+f"(d[OFF+11]), "+f"(d[OFF+12]), "+f"(d[OFF+13]), "+f"(d[OFF+14]), "+f"(d[OFF+15]), "+f"(d[OFF+16]), "+f"(d[OFF+17]), "+f"(d[OFF+18]), "+f"(d[OFF+19]), "+f"(d[OFF+20]), "+f"(d[OFF+21]), "+f"(d[OFF+22]), "+f"(d[OFF+23]), "+f"(d[OFF+24]), "+f"(d[OFF+25]), "+f"(d[OFF+26]), "+f"(d[OFF+27]), "+f"(d[OFF+28]), "+f"(d[OFF+29]), "+f"(d[OFF+30]), "+f"(d[OFF+31]), "+f"(d[OFF+32]), "+f"(d[OFF+33]), "+f"(d[OFF+34]), "+f"(d[OFF+35]), "+f"(d[OFF+36]), "+f"(d[OFF+37]), "+f"(d[OFF+38]), "+f"(d[OFF+39]), "+f"(d[OFF+40]), "+f"(d[OFF+41]), "+f"(d[OFF+42]), "+f"(d[OFF+43]), "+f"(d[OFF+44]), "+f"(d[OFF+45]), "+f"(d[OFF+46]), "+f"(d[OFF+47]), "+f"(d[OFF+48]), "+f"(d[OFF+49]), "+f"(d[OFF+50]), "+f"(d[OFF+51]), "+f"(d[OFF+52]), "+f"(d[OFF+53]), "+f"(d[OFF+54]), "+f"(d[OFF+55]), "+f"(d[OFF+56]), "+f"(d[OFF+57]), "+f"(d[OFF+58]), "+f"(d[OFF+59]), "+f"(d[OFF+60]), "+f"(d[OFF+61]), "+f"(d[OFF+62]), "+f"(d[OFF+63]), "+f"(d[OFF+64]), "+f"(d[OFF+65]), "+f"(d[OFF+66]), "+f"(d[OFF+67]), "+f"(d[OFF+68]), "+f"(d[OFF+69]), "+f"(d[OFF+70]), "+f"(d[OFF+71]), "+f"(d[OFF+72]), "+f"(d[OFF+73]), "+f"(d[OFF+74]), "+f"(d[OFF+75]), "+f"(d[OFF+76]), "+f"(d[OFF+77]), "+f"(d[OFF+78]), "+f"(d[OFF+79]), "+f"(d[OFF+80]), "+f"(d[OFF+81]), "+f"(d[OFF+82]), "+f"(d[OFF+83]), "+f"(d[OFF+84]), "+f"(d[OFF+85]), "+f"(d[OFF+86]), "+f"(d[OFF+87]), "+f"(d[OFF+88]), "+f"(d[OFF+89]), "+f"(d[OFF+90]), "+f"(d[OFF+91]), "+f"(d[OFF+92]), "+f"(d[OFF+93]), "+f"(d[OFF+94]), "+f"(d[OFF+95]), "+f"(d[OFF+96]), "+f"(d[OFF+97]), "+f"(d[OFF+98]), "+f"(d[OFF+99]), "+f"(d[OFF+100]), "+f"(d[OFF+101]), "+f"(d[OFF+102]), "+f"(d[OFF+103]), "+f"(d[OFF+104]), "+f"(d[OFF+105]), "+f"(d[OFF+106]), "+f"(d[OFF+107]), "+f"(d[OFF+108]), "+f"(d[OFF+109]), "+f"(d[OFF+110]), "+f"(d[OFF+111]), "+f"(d[OFF+112]), "+f"(d[OFF+113]), "+f"(d[OFF+114]), "+f"(d[OFF+115]), "+f"(d[OFF+116]), "+f"(d[OFF+117]), "+f"(d[OFF+118]), "+f"(d[OFF+119]), "+f"(d[OFF+120]), "+f"(d[OFF+121]), "+f"(d[OFF+122]), "+f"(d[OFF+123]), "+f"(d[OFF+124]), "+f"(d[OFF+125]), "+f"(d[OFF+126]), "+f"(d[OFF+127])
    : "r"(a0), "r"(a1), "r"(a2), "r"(a3), "l"(db), "r"(scale_d), "n"(TB));
}
template<int TB, int OFF, int NT>
__device__ __forceinline__ void wgmma_rs_n32(float (&d)[NT], uint32_t a0, uint32_t a1, uint32_t a2, uint32_t a3, uint64_t db, int scale_d) {
  asm volatile("{\n.reg .pred p;\nsetp.ne.b32 p, %21, 0;\n"
    "wgmma.mma_async.sync.aligned.m64n32k16.f32.bf16.bf16 {%0, %1, %2, %3, %4, %5, %6, %7, %8, %9, %10, %11, %12, %13, %14, %15}, {%16, %17, %18, %19}, %20, p, 1, 1, %22;\n}\n"
    : "+f"(d[OFF+0]), "+f"(d[OFF+1]), "+f"(d[OFF+2]), "+f"(d[OFF+3]), "+f"(d[OFF+4]), "+f"(d[OFF+5]), "+f"(d[OFF+6]), "+f"(d[OFF+7]), "+f"(d[OFF+8]), "+f"(d[OFF+9]), "+f"(d[OFF+10]), "+f"(d[OFF+11]), "+f"(d[OFF+12]), "+f"(d[OFF+13]), "+f"(d[OFF+14]), "+f"(d[OFF+15])
    : "r"(a0), "r"(a1), "r"(a2), "r"(a3), "l"(db), "r"(scale_d), "n"(TB));
}

__device__ __forceinline__ void wait_flag(const unsigned int* f, uint32_t target) {
  uint32_t v;
#pragma unroll 1
  for (uint32_t spins = 0; spins < (1u << 22); spins++) {
    asm volatile("ld.acquire.gpu.global.u32 %0, [%1];" : "=r"(v) : "l"(f) : "memory");
    if (v >= target) break;
    __nanosleep(100);
  }
}
__device__ __forceinline__ uint32_t ld_and2(const unsigned int* f) {
  uint32_t v;
  asm volatile("{\n.reg .b64 t;\n.reg .b32 a, b;\nld.acquire.gpu.global.b64 t, [%1];\nmov.b64 {a, b}, t;\nand.b32 %0, a, b;\n}" : "=r"(v) : "l"(f) : "memory");
  return v;
}
__device__ __forceinline__ uint32_t lds32(uint32_t a) {
  uint32_t v;
  asm volatile("ld.shared.u32 %0, [%1];" : "=r"(v) : "r"(a) : "memory");
  return v;
}
__device__ __forceinline__ float gate_row(int row, int lane, const bf16* __restrict__ x, const bf16* __restrict__ gate_w) {
  const uint32_t* xr = reinterpret_cast<const uint32_t*>(x + (size_t)row * DM);
  const uint32_t* gw2 = reinterpret_cast<const uint32_t*>(gate_w);
  float gs = 0.f;
#pragma unroll
  for (int i = 0; i < 9; i++) {
    const uint32_t a = __ldg(xr + lane + 32 * i), b = __ldg(gw2 + lane + 32 * i);
    gs = fmaf(bf_lo(a), bf_lo(b), gs);
    gs = fmaf(bf_hi(a), bf_hi(b), gs);
  }
#pragma unroll
  for (int o = 16; o; o >>= 1) gs += __shfl_xor_sync(0xffffffffu, gs, o);
  const float g = 1.f / (1.f + __expf(-gs));
  if (lane == 0) g_gate[row] = g;
  return g;
}
constexpr uint32_t LQ = 36864, LV = 55296;
__device__ __forceinline__ void mma16(float (&c)[4], uint32_t a0, uint32_t a1, uint32_t a2, uint32_t a3, uint32_t b0, uint32_t b1) {
  asm("mma.sync.aligned.m16n8k16.row.col.f32.bf16.bf16.f32 {%0, %1, %2, %3}, {%4, %5, %6, %7}, {%8, %9}, {%0, %1, %2, %3};"
      : "+f"(c[0]), "+f"(c[1]), "+f"(c[2]), "+f"(c[3]) : "r"(a0), "r"(a1), "r"(a2), "r"(a3), "r"(b0), "r"(b1));
}
__device__ __forceinline__ void mma8(float (&c)[4], uint32_t a0, uint32_t a1, uint32_t b0) {
  asm("mma.sync.aligned.m16n8k8.row.col.f32.bf16.bf16.f32 {%0, %1, %2, %3}, {%4, %5}, {%6}, {%0, %1, %2, %3};"
      : "+f"(c[0]), "+f"(c[1]), "+f"(c[2]), "+f"(c[3]) : "r"(a0), "r"(a1), "r"(b0));
}
template <typename F>
__device__ __forceinline__ void local_attn(int lr0, int warp_g, uint32_t sL, uint32_t bL, uint32_t bL2, int lane, float g0, float g1, F st) {
  const float scale_l2 = 0.23570226039551584f * 1.4426950408889634f;
  const int g = lane >> 2, t = lane & 3;
  const bool lo0 = 2 * t > g, lo1 = 2 * t + 1 > g;
  const bool ok0 = lr0 > 0 || !lo0, ok1 = lr0 > 0 || !lo1;
  const uint32_t mlo = (lo0 ? 0xFFFFu : 0u) | (lo1 ? 0xFFFF0000u : 0u);
  uint32_t ad[9], k[9][4], qf[9][2], pe[4], po[4];
#pragma unroll
  for (int c = 0; c < 9; c++) {
    const uint32_t ch = warp_g * 9 + c;
    ad[c] = sL + (lane >> 4) * 18432 + (lane & 15) * 128 + ((ch >> 3) << 11) + (((ch ^ lane) & 7) << 4);
  }
  st(0, 0u); st(1, 0u);
  mbar_wait(bL, 0);
  if (warp_g == 0) TS(1, 6);
#pragma unroll
  for (int c = 0; c < 9; c++) {
    asm volatile("ldmatrix.sync.aligned.m8n8.x2.shared.b16 {%0, %1}, [%2];" : "=r"(qf[c][0]), "=r"(qf[c][1]) : "r"(ad[c] + LQ) : "memory");
    ldsm_x4(k[c][0], k[c][1], k[c][2], k[c][3], ad[c]);
  }
  st(2, k[0][0]); st(3, k[8][0]);
#pragma unroll
  for (int i = 0; i < 4; i++) {
    const uint32_t q0 = (t >= i) ? qf[2 * i][0] : 0u, q1 = (t >= i) ? qf[2 * i][1] : 0u;
    const uint32_t q4 = (t <= i) ? qf[2 * i + 2][0] : 0u, q5 = (t <= i) ? qf[2 * i + 2][1] : 0u;
    float c[4][4];
#pragma unroll
    for (int T = 0; T < 4; T++) {
#pragma unroll
      for (int j = 0; j < 4; j++) c[T][j] = 0.f;
      mma16(c[T], q0, q1, qf[2 * i + 1][0], qf[2 * i + 1][1], k[2 * i][T], k[2 * i + 1][T]);
      mma8(c[T], q4, q5, k[2 * i + 2][T]);
    }
    const float e0 = ok0 ? (lo0 ? c[0][0] : c[1][0]) : -INFINITY, e1 = ok1 ? (lo1 ? c[0][1] : c[1][1]) : -INFINITY;
    const float o0 = ok0 ? (lo0 ? c[2][2] : c[3][2]) : -INFINITY, o1 = ok1 ? (lo1 ? c[2][3] : c[3][3]) : -INFINITY;
    float me = fmaxf(e0, e1), mo = fmaxf(o0, o1);
    me = fmaxf(me, __shfl_xor_sync(0xffffffffu, me, 1));
    mo = fmaxf(mo, __shfl_xor_sync(0xffffffffu, mo, 1));
    me = fmaxf(me, __shfl_xor_sync(0xffffffffu, me, 2)) * scale_l2;
    mo = fmaxf(mo, __shfl_xor_sync(0xffffffffu, mo, 2)) * scale_l2;
    const float w0 = ex2(fmaf(e0, scale_l2, -me)), w1 = ex2(fmaf(e1, scale_l2, -me));
    const float w2 = ex2(fmaf(o0, scale_l2, -mo)), w3 = ex2(fmaf(o1, scale_l2, -mo));
    float se = w0 + w1, so = w2 + w3;
    st(4 + 2 * i, __float_as_uint(i == 1 ? me : i == 2 ? se : e0));
    se += __shfl_xor_sync(0xffffffffu, se, 1);
    so += __shfl_xor_sync(0xffffffffu, so, 1);
    se += __shfl_xor_sync(0xffffffffu, se, 2);
    so += __shfl_xor_sync(0xffffffffu, so, 2);
    asm("rcp.approx.ftz.f32 %0, %0;" : "+f"(se));
    asm("rcp.approx.ftz.f32 %0, %0;" : "+f"(so));
    se *= g0;
    so *= g1;
    pe[i] = pack_bf16(w0 * se, w1 * se);
    po[i] = pack_bf16(w2 * so, w3 * so);
    st(5 + 2 * i, i == 0 ? __float_as_uint(w0) : i == 2 ? __float_as_uint(mo) : po[i]);
  }
  if (warp_g == 0) TS(0, 4);
  mbar_wait(bL2, 0);
  if (warp_g == 0) TS(0, 5);
#pragma unroll
  for (int c = 0; c < 9; c++)
    asm volatile("ldmatrix.sync.aligned.m8n8.x4.trans.shared.b16 {%0, %1, %2, %3}, [%4];"
                 : "=r"(k[c][0]), "=r"(k[c][1]), "=r"(k[c][2]), "=r"(k[c][3]) : "r"(ad[c] + LV) : "memory");
#pragma unroll
  for (int i = 0; i < 4; i++) {
#pragma unroll
    for (int n = 0; n < 3; n++) {
      float c[4] = {0.f, 0.f, 0.f, 0.f};
      mma16(c, pe[i] & mlo, 0u, pe[i] & ~mlo, 0u, k[2 * i + n][0], k[2 * i + n][1]);
      mma16(c, 0u, po[i] & mlo, 0u, po[i] & ~mlo, k[2 * i + n][2], k[2 * i + n][3]);
      const uint32_t r0 = pack_bf16(c[0], c[1]), r1 = pack_bf16(c[2], c[3]);
      const bool keep = (n == 0) && (i > 0) && (t < i);
      qf[2 * i + n][0] = keep ? qf[2 * i + n][0] : r0;
      qf[2 * i + n][1] = keep ? qf[2 * i + n][1] : r1;
    }
    st(12 + i, qf[2 * i + 1][0]);
  }
#pragma unroll
  for (int c = 0; c < 9; c++)
    asm volatile("stmatrix.sync.aligned.m8n8.x2.shared.b16 [%0], {%1, %2};" ::"r"(ad[c] + LQ), "r"(qf[c][0]), "r"(qf[c][1]) : "memory");
  asm volatile("fence.proxy.async.shared::cta;" ::: "memory");
}
__device__ __forceinline__ void tma4d(uint32_t dst, const CUtensorMap* m, uint32_t bar, int c1, int c2, int c3) {
  asm volatile("cp.async.bulk.tensor.4d.shared::cluster.global.mbarrier::complete_tx::bytes [%0], [%1, {%3, %4, %5, %6}], [%2];" ::"r"(dst),
               "l"(m), "r"(bar), "r"(0), "r"(c1), "r"(c2), "r"(c3) : "memory");
}

#define ST_NUM 1
#define ST_DEN 2
#define K1_NST 6
constexpr int K1_BST = K1_NST;
#define MAXJ 11
constexpr int K1_MAXJOBS = MAXJ;
constexpr uint32_t K1_FLAG_TARGET = 7;
constexpr uint32_t RDY_TARGET = 48;
constexpr uint32_t GATE_TARGET = 128 * 3;
struct alignas(64) Params {
  CUtensorMap tmA[2];
  CUtensorMap tmW[4];
  uint16_t jobs[NCLUSTER][K1_MAXJOBS + 1];
  CUtensorMap tmK, tmV, tmQ;
  CUtensorMap tmL[3];
  CUtensorMap tmC, tmO[2], tmOt[2];
  CUtensorMap tmR[2];
  uint8_t order[256];
  uint8_t unit[66][4];
};

struct K1State {
  uint32_t bs, bph, aph;
  bf16 *pp, *pp8;
  int png;
  int tn;
  int wsel;
  uint32_t fo;
};
__device__ __forceinline__ void k1_flag(const K1State& st, int lane, uint32_t bS) {
  if (st.png) {
    __syncwarp();
    if (lane == 0) mbar_arrive(bS + st.fo);
  }
}

__device__ __forceinline__ void scale_q4(uint32_t* v) {
#pragma unroll
  for (int i = 0; i < 4; i++)
    asm volatile("{\n.reg .b32 t;\nmul.rn.bf16x2 t, %0, %2;\nfma.rn.bf16x2 %0, %0, %1, t;\n}" : "+r"(v[i]) : "r"(0x3E033E03u), "r"(0xB9D8B9D8u));
}
__device__ __forceinline__ void k1_first(const K1State& st, uint32_t job, uint32_t bAf, uint32_t bBf) {
  if (job & 3) {
    if ((job >> 14) & 1) mbar_wait(bAf, st.aph);
    mbar_wait(bBf + st.bs * 8, st.bph);
  }
}
__device__ __forceinline__ void k1_tile(float (&acc)[128], uint32_t (&pk)[64], K1State& st, uint32_t job, uint32_t njob, uint32_t sA, uint32_t sB,
                                        uint32_t bAf, uint32_t bAe, uint32_t bBf, uint32_t bBe, uint32_t bS, int wg, int warp, int lane, uint32_t rank) {
  const int a_sel = (job >> 2) & 1, mpair = (job >> 3) & 7, w_sel = (job >> 6) & 3, chunk0 = (job >> 8) & 63;
  const bool newA = (job >> 14) & 1, lastA = (job >> 15) & 1;
  const bool sig = (lane == 0) && (warp < 2);
  const bool siga = lastA && (lane == 0) && (warp == 2);
  const int KC = 8 + a_sel;
  uint32_t prev_bs = 0, a8_bs = 0;
#pragma unroll
  for (int kc = 0; kc < 9; kc++) {
    if (kc >= KC) break;
    uint32_t abase = sA + ((kc + 2) & 7) * 16384;
    if (kc == 8) {
      mbar_wait(bBf + st.bs * 8, st.bph);
      a8_bs = st.bs;
      abase = sB + st.bs * 16384;
      if (++st.bs == K1_BST) { st.bs = 0; st.bph ^= 1; }
    } else if (newA && kc > 0) {
      mbar_wait(bAf + kc * 8, st.aph);
    }
    const uint64_t da = make_desc(abase + wg * 8192, 16, 1024, 1);
#pragma unroll
    for (int ks = 0; ks < 2; ks++) {
      if (ks > 0 || kc > 0) mbar_wait(bBf + st.bs * 8, st.bph);
      const uint64_t db = make_desc(sB + st.bs * 16384, 2048, 1024, 1);
      wg_fence();
      wgmma_ss_n256<1, 0>(acc, da + (uint64_t)(ks * 4), db, (ks > 0) ? 1 : (kc > 0));
      wgmma_ss_n256<1, 0>(acc, da + (uint64_t)(ks * 4 + 2), db + (uint64_t)512, 1);
      wg_commit();
      wg_wait<1>();
      if (ks > 0 || kc > 0) {
        if (sig) mbar_arrive_cluster(bBe + prev_bs * 8, warp);
        if (ks == 0 && siga) mbar_arrive(bAe + (kc - 1) * 8);
      }
      if (st.wsel == 2) {
        const int i = (kc & 7) * 2 + ks;
        if (kc < st.png) {
          quad_transpose(pk[i * 4], pk[i * 4 + 1], pk[i * 4 + 2], pk[i * 4 + 3], lane & 3);
          st_v4a((ks ? st.pp8 : st.pp) + kc * 32, pk[i * 4], pk[i * 4 + 1], pk[i * 4 + 2], pk[i * 4 + 3]);
        }
        if (i == 15) k1_flag(st, lane, bS);
      } else if (st.png) {
#pragma unroll
        for (int i = 0; i < 16; i++) {
          if (i * ST_NUM / ST_DEN != kc * 2 + ks) continue;
          if (st.wsel == 3) scale_q4(pk + i * 4);
          st_v4a(((i & 1) ? st.pp8 : st.pp) + (i / 2) * 32, pk[i * 4], pk[i * 4 + 1], pk[i * 4 + 2], pk[i * 4 + 3]);
          if (i == 15) k1_flag(st, lane, bS);
        }
      }
      prev_bs = st.bs;
      if (++st.bs == K1_BST) { st.bs = 0; st.bph ^= 1; }
    }
  }
  if (newA) st.aph ^= 1;
  const bool isA = (w_sel == 2);
  bf16* out = (w_sel == 0) ? g_K : (w_sel == 1) ? g_V : isA ? g_QKVA : g_ctx;
  const int ld = isA ? NQKVA : (w_sel == 3) ? KCAT : HDIM;
  const int row = mpair * 256 + rank * 128 + wg * 64 + warp * 16 + (lane >> 2);
  st.pp = ptr_add(out, (row * ld + chunk0 * 64 + (lane & 3) * 8) * 2);
  st.pp8 = ptr_add(st.pp, 16 * ld);
  st.png = ((job & 3) + 1) * 2;
  st.wsel = w_sel;
  st.fo = (st.fo + 8) & 24;
  k1_first(st, njob, bAf, bBf);
  wg_wait<0>();
  fence_regs(acc);
  mbar_arrive_cluster_if(bBe + prev_bs * 8, warp & 1, sig);
  mbar_arrive_cluster_if(bBe + a8_bs * 8, warp & 1, sig && a_sel);
  mbar_arrive_if(bAe + 7 * 8, siga && !a_sel);
#pragma unroll
  for (int i = 0; i < 64; i++) {
    const int j = (i >> 3) * 16 + (i & 3) * 4 + ((i >> 2) & 1) * 2;
    pk[i] = pack_bf16(acc[j], acc[j + 1]);
  }
}

constexpr int K2_NST = 7;
constexpr uint32_t K2_END = 0x100;
#define PFD 4
#define PF3A 2
#define PF3 6
#define KC0 1
constexpr uint32_t CR = 4;
#define FIRST_DRAW 3
#define PWAIT mbar_wait_ns<1000>
#define PVM 0x8A
#define W0 63
#define SPEC_HI 1.8446744073709552e19f
#define SPEC_LO 5.421010862427522e-20f
constexpr int K3_NST = 4;
#define K3_NS 6
__device__ __forceinline__ uint32_t k3_rot(uint32_t sv) { return (0x00E9u >> (2 * sv)) & 3; }
constexpr int K3_STAGE = 16384 + 32768 + 4096;
constexpr int SMEM_DATA = 7 * 32768;
constexpr int SMEM_BYTES = SMEM_DATA + 1024 + 896;

struct Cursor {
  uint32_t s, ph;
  __device__ __forceinline__ void next() {
    if (++s == K2_NST) { s = 0; ph ^= 1; }
  }
};

#define TURN_SYNC() bar_sync(mybar, 256)
#define TURN_ARRIVE() bar_arrive(otherbar, 256)
#define RELEASE_IF(cur, cond) mbar_arrive_cluster_if(bE + (cur).s * 8, warp & 1, sig && (cond))
#define RELEASE(cur) RELEASE_IF(cur, true)
#define ISSUE_PV(cur, first)                                                                                   \
  do {                                                                                                         \
    const uint64_t dv = make_desc(sbase + (cur).s * 32768, 16384, 1024, 1);                                    \
    _Pragma("unroll") for (int t = 0; t < 8; t++)                                                              \
        wgmma_rs_n128<1, 0>(O, P[4 * t], P[4 * t + 1], P[4 * t + 2], P[4 * t + 3], dv + (uint64_t)(t * 128), (t > 0) ? 1 : !(first)); \
  } while (0)
#define ISSUE_QK(cur)                                                                                          \
  do {                                                                                                         \
    const uint64_t dk = make_desc(sbase + (cur).s * 32768, 16, 1024, 1);                                       \
    _Pragma("unroll") for (int t = 0; t < 8; t++)                                                              \
        wgmma_rs_n128<0, 0>(S, Q[4 * t], Q[4 * t + 1], Q[4 * t + 2], Q[4 * t + 3], dk + (uint64_t)((t >> 2) * 1024 + (t & 3) * 2), t > 0); \
  } while (0)
#define LOAD_Q()                                                                                               \
  do {                                                                                                         \
    item = lds32(sItem + (it & 7) * 4);                                                                        \
    const uint32_t qa = sbase + cq.s * 32768 + (wg * 64 + warp * 16 + (lane & 15)) * 128;                      \
    _Pragma("unroll") for (int t = 0; t < 8; t++)                                                              \
        ldsm_x4(Q[4 * t], Q[4 * t + 1], Q[4 * t + 2], Q[4 * t + 3], qa + (t >> 2) * 16384 + ((((t & 3) * 2 + (lane >> 4)) ^ (lane & 7)) << 4)); \
  } while (0)
#define NEW_ITEM()                                                                                             \
  do {                                                                                                         \
    const int row = (2 * (item & 7) + hi) * 128 + (rank ^ hi) * 64 + warp * 16 + (lane >> 2);                  \
    eoff = (row * KCAT + (item >> 3) * 128 + q * 8) * 2;                                                       \
    const float* gp = ptr_add(g_gate, row * 4);                                                                \
    asm volatile("ld.global.f32 %0, [%1];" : "=f"(gf0) : "l"(gp));                                             \
    asm volatile("ld.global.f32 %0, [%1];" : "=f"(gf1) : "l"(gp + 8));                                         \
    if (!hi) {                                                                                                 \
      mbar_wait2(bF + cs0.s * 8, cs0.ph, bF + cs1.s * 8, cs1.ph);                                              \
      RELEASE(cs0);                                                                                            \
      RELEASE(cs1);                                                                                            \
    }                                                                                                          \
  } while (0)
#define EXPB(T)                                                                                                \
  do {                                                                                                         \
    _Pragma("unroll") for (int i = 4 * T; i < 4 * T + 4; i++) asm volatile("" : "+r"(P[i])::"memory");        \
    _Pragma("unroll") for (int jj = 2 * T; jj < 2 * T + 2; jj++) {                                             \
      const float e0 = ex2(S[jj * 4 + 0]), e1 = ex2(S[jj * 4 + 1]), e2 = ex2(S[jj * 4 + 2]), e3 = ex2(S[jj * 4 + 3]); \
      s0 += e0 + e1;                                                                                           \
      s1 += e2 + e3;                                                                                           \
      P[jj * 2 + 0] = pack_bf16(e0, e1);                                                                       \
      P[jj * 2 + 1] = pack_bf16(e2, e3);                                                                       \
    }                                                                                                          \
  } while (0)
#define EXPC(T)                                                                                                \
  do {                                                                                                         \
    if (T > 0 && ((PVM >> (T - 1)) & 1)) {                                                                     \
      anchor((T & 2) ? s0 : s1, never);                                                                        \
      wg_wait<__builtin_popcount(PVM >> T) - 1>();                                                             \
      if ((PVM >> T) == (128 >> T)) { fence_regs(O); RELEASE(cv); }                                            \
    }                                                                                                          \
    EXPB(T);                                                                                                   \
  } while (0)
#define MASK(G, g)                                                                                             \
  do {                                                                                                         \
    if ((g) * 8 > d) S[(G) * 4 + 0] = -INFINITY;                                                               \
    if ((g) * 8 + 1 > d) S[(G) * 4 + 1] = -INFINITY;                                                           \
    if ((g) * 8 - 8 > d) S[(G) * 4 + 2] = -INFINITY;                                                           \
    if ((g) * 8 - 7 > d) S[(G) * 4 + 3] = -INFINITY;                                                           \
  } while (0)
#define STORE_O(G)                                                                                             \
  do {                                                                                                         \
    st_v4(optr + (G) * 32, pack_bf16(O[(G) * 16 + 0] * f0, O[(G) * 16 + 1] * f0), pack_bf16(O[(G) * 16 + 4] * f0, O[(G) * 16 + 5] * f0), \
          pack_bf16(O[(G) * 16 + 8] * f0, O[(G) * 16 + 9] * f0), pack_bf16(O[(G) * 16 + 12] * f0, O[(G) * 16 + 13] * f0)); \
    st_v4(optr + 8 * KCAT + (G) * 32, pack_bf16(O[(G) * 16 + 2] * f1, O[(G) * 16 + 3] * f1), pack_bf16(O[(G) * 16 + 6] * f1, O[(G) * 16 + 7] * f1), \
          pack_bf16(O[(G) * 16 + 10] * f1, O[(G) * 16 + 11] * f1), pack_bf16(O[(G) * 16 + 14] * f1, O[(G) * 16 + 15] * f1)); \
  } while (0)

#define FLUSH()                                                                                                \
  do {                                                                                                         \
    _Pragma("unroll") for (int G = 0; G < 8; G++) {                                                            \
      st_v4a(st.pp + G * 32, pk[G * 8], pk[G * 8 + 1], pk[G * 8 + 2], pk[G * 8 + 3]);                          \
      st_v4a(st.pp8 + G * 32, pk[G * 8 + 4], pk[G * 8 + 5], pk[G * 8 + 6], pk[G * 8 + 7]);                     \
    }                                                                                                          \
    k1_flag(st, lane, bS);                                                                                     \
  } while (0)

__global__ void __cluster_dims__(2, 1, 1) __launch_bounds__(384, 1)
fused_kernel(const __grid_constant__ Params p, const bf16* __restrict__ x, const bf16* __restrict__ gate_w, bf16* __restrict__ out) {
  extern __shared__ uint8_t smem_raw[];
  const uint32_t sbase = (smem_u32(smem_raw) + 1023) & ~1023u;
  const uint32_t sB = sbase, sA = sbase + K1_BST * 16384, sBar = sbase + SMEM_DATA;
  const uint32_t bAf = sBar, bAe = sBar + 64, bBf = sBar + 128, bBe = sBar + 176, bL = sBar + 224, bS = sBar + 656, bL2 = sBar + 240, sL = sA + 32768;
  const uint32_t bF = sBar + 256, bE = sBar + 320, bT = sBar + 384, sTick = sBar + 400, sItem = sBar + 416, bS2 = sBar + 688, bR = sBar + 456, bLast = sBar + 464, bH = sBar + 472, bT0 = sBar + 480, bZ = sBar + 488, bLd = sBar + 496;
  const uint32_t b3F = sBar + 512, b3E = sBar + 544, sGate = sBar + 576, sK1 = sBar + 720, sClm = sBar + 768;
  const int tid = threadIdx.x, warp_g = __shfl_sync(0xffffffffu, tid >> 5, 0), lane = tid & 31;
  const uint32_t rank = cluster_rank();
  const int cl = blockIdx.x >> 1;
  TSM(0);
  if (tid == 256) {
    const uint32_t job = p.jobs[cl][0];
#pragma unroll
    for (int i = 0; i < KC0; i++) { mbar_init(bAf + i * 8, 1); mbar_init(bBf + i * 16, 1); mbar_init(bBf + i * 16 + 8, 1); }
    asm volatile("fence.mbarrier_init.release.cluster;" ::: "memory");
#pragma unroll 1
    for (int i = 0; i < 4 * KC0; i++) {
      if (!(i & 3)) {
        mbar_expect(bAf + i * 2, 16384);
        tma2d(sA + (i / 4 + 2) * 16384, &p.tmA[(job >> 2) & 1], bAf + i * 2, i * 16, ((job >> 3) & 7) * 256 + rank * 128);
      }
      if (!(i & 1)) mbar_expect(bBf + i * 4, 16384);
      tma3d(sB + i * 8192, &p.tmW[(job >> 6) & 3], bBf + (i >> 1) * 8, 0, i * 16, (job >> 8) & 63);
    }
  }
  if (warp_g == 1) asm volatile("st.shared.u32 [%0], %1;" ::"r"(lane ? sClm - 4 + lane * 4 : sK1), "r"(lane ? 0xFFFFFFFFu : 80u) : "memory");
  if (tid == 0) {
    for (int i = 0; i < 8; i++) { if (i >= KC0) mbar_init(bAf + i * 8, 1); mbar_init(bAe + i * 8, 2); }
    for (int i = 0; i < K1_BST; i++) { if (i >= 2 * KC0) mbar_init(bBf + i * 8, 1); mbar_init(bBe + i * 8, 4); }
    mbar_init(bL, 1);
    mbar_init(bL2, 1);
    mbar_init(bR, 1);
    mbar_init(bLast, 1);
    mbar_init(bH, 4);
    mbar_init(bT0, 1);
    mbar_init(bZ, 1);
    mbar_init(bLd, 4);
    for (int i = 0; i < 8; i++) mbar_init(bS + i * 8, 8);
    for (int i = 0; i < K2_NST; i++) { mbar_init(bF + i * 8, 1); mbar_init(bE + i * 8, 4); }
    mbar_init(bT, 1); mbar_init(bT + 8, 1);
    for (int i = 0; i < K3_NST; i++) { mbar_init(b3F + i * 8, 1); mbar_init(b3E + i * 8, 4); }
    asm volatile("fence.mbarrier_init.release.cluster;" ::: "memory");
  }
  __syncwarp();
  if (warp_g != 8) cluster_sync();
  const int lr0 = blockIdx.x * 16;

  if (warp_g >= 8) {
    reg_dealloc<40>();
    if (warp_g == 8) {
      {
        __syncwarp();
        cluster_sync();
      }
      if (elect_one()) {
        uint32_t bs = (2 * KC0) % K1_BST, bph = (2 * KC0 < K1_BST), aph = 1;
#pragma unroll 1
        for (int ji = 0; ji < K1_MAXJOBS; ji++) {
          const uint32_t job = p.jobs[cl][ji];
          if (!(job & 3)) break;
          const int a_sel = (job >> 2) & 1, mpair = (job >> 3) & 7, chunk0 = (job >> 8) & 63;
          const bool newA = (job >> 14) & 1;
          const int KC = a_sel ? 9 : 8;
          const uint32_t halfbytes = 8192;
          const bool lastjob = (ji + 1 == K1_MAXJOBS) || !(p.jobs[cl][ji + 1] & 3);
          const CUtensorMap* tw = &p.tmW[(job >> 6) & 3];
          {
            const uint32_t njob = (ji + 1 < K1_MAXJOBS) ? p.jobs[cl][ji + 1] : 0;
            if (!(njob & 3) && !newA) mbar_arrive(bLast);
          }
#pragma unroll 1
          for (int kc = ji ? 0 : KC0; kc < KC; kc++) {
            {
              const bool nx = kc + PFD >= KC;
              const uint32_t njob = nx ? p.jobs[cl][ji + 1] : job;
              const int pk = nx ? kc + PFD - KC : kc + PFD;
              if ((njob & 3) && (nx || ji > 0)) {
                if (cl >= 64 || ((pk ^ (cl >> 1)) & 3) == 0)
                  tma_pf3d(&p.tmW[(njob >> 6) & 3], 0, pk * 64 + (cl & 1) * 32 + rank * 16, (njob >> 8) & 63);
                if (((njob >> 14) & 1) || pk == 8) tma_pf2d(&p.tmA[(njob >> 2) & 1], pk * 64, ((njob >> 3) & 7) * 256 + rank * 128);
              }
            }
            if (kc == 8) {
              PWAIT(bBe + bs * 8, bph);
              mbar_expect(bBf + bs * 8, 16384);
              tma2d(sB + bs * 16384, &p.tmA[1], bBf + bs * 8, 512, mpair * 256 + rank * 128);
              if (++bs == K1_BST) { bs = 0; bph ^= 1; }
            } else if (newA) {
              PWAIT(bAe + kc * 8, aph);
              mbar_expect(bAf + kc * 8, 16384);
              tma2d(sA + ((kc + 2) & 7) * 16384, &p.tmA[a_sel], bAf + kc * 8, kc * 64, mpair * 256 + rank * 128);
              if (kc == 7 && lastjob) mbar_arrive(bLast);
            }
#pragma unroll 1
            for (int kk = 0; kk < 2; kk++) {
              PWAIT(bBe + bs * 8, bph);
              mbar_expect(bBf + bs * 8, 2 * halfbytes);
              tma3d_mc(sB + bs * 16384 + rank * halfbytes, tw, bBf + bs * 8, 0, kc * 64 + kk * 32 + rank * 16, chunk0, 3);
              if (++bs == K1_BST) { bs = 0; bph ^= 1; }
            }
          }
          if (newA) aph ^= 1;
        }
        Cursor c{0, 0};
        int pcol = 0;
        PWAIT(bR, 0);
        uint32_t tick = lds32(sTick + 8), seen = 1u << (p.order[tick] >> 4);
        asm volatile("fence.proxy.async.global;" ::: "memory");
#pragma unroll 1
        for (int it = 0;; it++) {
          const uint32_t item = (tick < 256) ? p.order[tick] : (K2_END | min(tick - 256, 255u));
          asm volatile("st.shared.u32 [%0], %1;" ::"r"(sItem + (it & 7) * 4), "r"(item) : "memory");
          if (item >= K2_END) break;
          const int h = item >> 3, j = item & 7;
          const int col = h * 128 + rank * 64;
          const int nb = 2 * j + 2;
          if (!((seen >> (h >> 1)) & 1)) {
            wait_flag(&g_sync[F_HP + (h >> 1)], RDY_TARGET);
            asm volatile("fence.proxy.async.global;" ::: "memory");
            seen |= 1u << (h >> 1);
          }
          PWAIT(bE + c.s * 8, c.ph);
          mbar_expect(bF + c.s * 8, 32768);
#pragma unroll 1
          for (int i = 0; i < 4; i++) {
            const int hi = (i ^ it ^ 1) & 1;
            tma2d(sbase + c.s * 32768 + i * 8192, &p.tmQ, bF + c.s * 8, h * 128 + (i >> 1) * 64, (2 * j + hi) * 128 + (rank ^ hi) * 64);
          }
          c.next();
          if (tick >= 256 - 73) {
            const int kk = tick - (256 - 73), sel = (kk < 9), kr = (sel ? kk : kk - 9) * 64 + rank * 32;
#pragma unroll 1
            for (int i = 0; i < 2; i++) {
              tma_pf3d(&p.tmO[sel], 0, kr, i * 4);
              tma_pf2d(&p.tmOt[sel], 512 + i * 32, kr);
            }
          }
#pragma unroll 1
          for (int n = nb - 1; n >= 0; n--) {
            if (n == 0 && rank == 0) tick = atomicAdd(&g_sync[F_TICK], 1u);
            PWAIT(bE + c.s * 8, c.ph);
            mbar_expect(bF + c.s * 8, 32768);
            tma2d_mc(sbase + c.s * 32768 + rank * 16384, &p.tmK, bF + c.s * 8, col, n * 128, 3);
            c.next();
            if (n < nb - 1 || it > 0) {
              PWAIT(bE + c.s * 8, c.ph);
              mbar_expect(bF + c.s * 8, 32768);
              tma2d_mc(sbase + c.s * 32768 + rank * 16384, &p.tmV, bF + c.s * 8, (n < nb - 1) ? col : pcol, (n < nb - 1) ? (n + 1) * 128 : 0, 3);
              c.next();
            }
          }
          pcol = col;
          if (rank == 0) {
            asm volatile(
                "{\n.reg .b32 a, b;\nmapa.shared::cluster.u32 a, %0, 1;\nmapa.shared::cluster.u32 b, %1, 1;\n"
                "st.async.shared::cluster.mbarrier::complete_tx::bytes.u32 [a], %2, [b];\n}" ::"r"(sTick + (it & 1) * 4),
                "r"(bT + (it & 1) * 8), "r"(tick) : "memory");
          } else {
            mbar_expect(bT + (it & 1) * 8, 4);
            PWAIT(bT + (it & 1) * 8, (it >> 1) & 1);
            tick = lds32(sTick + (it & 1) * 4);
          }
        }
        PWAIT(bE + c.s * 8, c.ph);
        mbar_expect(bF + c.s * 8, 32768);
        tma2d_mc(sbase + c.s * 32768 + rank * 16384, &p.tmV, bF + c.s * 8, pcol, 0, 3);
        const uint32_t unit = tick - 256;
        const int mblk = (7 - (p.unit[unit][0] >> 1)) * 2 + rank, nhalf = p.unit[unit][0] & 1;
        uint32_t have, hoa;
        have = ld_and2(&g_sync[F_CTX + (mblk & ~1)]);
        asm volatile("ld.acquire.gpu.global.u32 %0, [%1];" : "=r"(hoa) : "l"(&g_sync[F_OA + mblk]) : "memory");
        asm volatile("fence.proxy.async.global;" ::: "memory");
#pragma unroll 1
        for (uint32_t idx = PF3A; idx < PF3; idx++) {
          const int kk = p.unit[unit][2] + idx;
          if ((kk < 9) ? (hoa >= 8) : ((have >> ((kk - 9) >> 1)) & 1)) tma_pf2d(&p.tmC, ((kk < 9) ? 64 + kk : kk - 9) * 64, mblk * 128);
        }
        {
          const uint32_t rot = k3_rot(c.s), nfree = ((0x1Au >> c.s) & 1) ? 2 : 3;
          uint32_t kq = p.unit[unit][2] * 0x01010101u + 0x03020100u, k1 = 80, idx = 0, pa = 0, pb = 0;
          auto step = [&](uint32_t& pend) {
            uint32_t nxt = (kq & 255) + CR;
            if (idx + CR >= K3_NS && k1 == 80) {
              if (rank == 0) {
                nxt = min(pend + p.unit[unit][3], 73u);
                asm volatile("{\n.reg .b32 a;\nmapa.shared::cluster.u32 a, %0, 1;\nst.volatile.shared::cluster.u8 [a], %1;\n}" ::"r"(sClm + idx), "r"(nxt) : "memory");
              } else {
#pragma unroll 1
                for (uint32_t spins = 0; spins < (1u << 22); spins++) {
                  asm volatile("ld.volatile.shared.u8 %0, [%1];" : "=r"(nxt) : "r"(sClm + idx) : "memory");
                  if (nxt != 255) break;
                  __nanosleep(20);
                }
              }
              if (nxt >= 73) {
                k1 = idx + CR;
                asm volatile("st.shared.u32 [%0], %1;" ::"r"(sK1), "r"(k1) : "memory");
              }
            }
            const uint32_t kk = kq & 255;
            if (idx < 12) TP(idx);
            kq = (kq >> 8) | (nxt << (8 * CR - 8));
            const uint32_t s = (rot + idx) & 3;
            if (idx >= nfree) PWAIT((idx < 4) ? bH : b3E + s * 8, (idx < 4) ? 0 : (~idx >> 2) & 1);
#pragma unroll 1
            while (idx < nfree && c.s != ((0x6431u >> (4 * s)) & 15)) {
              c.next();
              PWAIT(bE + c.s * 8, c.ph);
            }
            if (idx < 12) TP(12 + idx);
            mbar_expect(b3F + s * 8, K3_STAGE);
            const uint32_t st = sbase + s * K3_STAGE;
            const int sel = (kk < 9), k = sel ? kk : kk - 9, kr = k * 64 + rank * 32;
            tma3d_mc(st + 16384 + rank * 16384, &p.tmO[sel], b3F + s * 8, 0, kr, nhalf * 4, 3);
            tma2d_mc(st + 49152 + rank * 2048, &p.tmOt[sel], b3F + s * 8, 512 + nhalf * 32, kr, 3);
            if (rank == 0 && idx + CR + 2 >= K3_NS && k1 == 80) pend = atomicAdd(&g_sync[F_CLM + p.unit[unit][0]], 1u);
            if (sel && hoa < 8) {
              wait_flag(&g_sync[F_OA + mblk], 8);
              hoa = 8;
              asm volatile("fence.proxy.async.global;" ::: "memory");
            }
            if (!sel && !((have >> (k >> 1)) & 1)) {
#pragma unroll 1
              for (uint32_t spins = 0; spins < (1u << 22); spins++) {
                have = ld_and2(&g_sync[F_CTX + (mblk & ~1)]);
                if ((have >> (k >> 1)) & 1) break;
                __nanosleep(100);
              }
              asm volatile("fence.proxy.async.global;" ::: "memory");
            }
            tma2d(st, &p.tmC, b3F + s * 8, (sel ? 64 + k : k) * 64, mblk * 128);
            if (idx < 12) TP(24 + idx);
            return ++idx >= k1;
          };
#pragma unroll 1
          for (;;) {
            if (step(pa)) break;
            if (step(pb)) break;
          }
          asm volatile("" ::"r"(pa), "r"(pb) : "memory");
        }
      }
    }
    __syncwarp();
    if (warp_g == 8) {
      uint32_t v = 0;
      if (lane == 0) {
        __threadfence();
        v = atomicAdd(&g_sync[F_DONE], 1u);
      }
      if (__shfl_sync(0xffffffffu, v, 0) == 2 * NCLUSTER - 1) {
        reinterpret_cast<uint4*>(g_sync)[lane] = make_uint4(0, 0, 0, 0);
        if (lane == 0) g_sync[F_EPOCH] = lds32(sGate + 64) + 1;
      }
    }
    asm volatile("" ::: "memory");
    if (__shfl_sync(0xffffffffu, warp_g, 0) != 8) {
      if (lr0 < S_LEN) {
#pragma unroll 1
        for (int i = warp_g - 9; i < 16; i += 3) {
          const float g = gate_row(lr0 + i, lane, x, gate_w);
          if (lane == 0) asm volatile("st.shared.f32 [%0], %1;" ::"r"(sGate + i * 4), "f"(g) : "memory");
        }
        bar_arrive(3, 256 + 96);
        if (lane == 0) {
          __threadfence();
          atomicAdd(&g_sync[F_GATE], 1u);
        }
      }
      uint32_t aph = 1;
#pragma unroll 1
      for (int ji = 0; ji < K1_MAXJOBS; ji++) aph ^= (p.jobs[cl][ji] >> 14) & 1;
      if (warp_g == 9) {
        uint32_t nxt = 0;
        if (lane == 0) {
#pragma unroll 1
        for (int ji = 0; ji < K1_MAXJOBS; ji++) {
          const uint32_t job = p.jobs[cl][ji];
          if (!(job & 3)) break;
          PWAIT(bS + (ji & 3) * 8, (ji >> 2) & 1);
          __threadfence();
          atomicAdd(&g_sync[(((job >> 6) & 3) == 2) ? (F_QKVA + ((job >> 3) & 7) * 2 + rank) : (F_HP + ((job >> 10) & 15))], 1u);
        }
#pragma unroll 1
        for (int it = 0;; it++) {
          PWAIT(bS2 + (it & 3) * 8, (it >> 2) & 1);
          const uint32_t item = lds32(sItem + (it & 7) * 4);
          nxt = lds32(sItem + ((it + 1) & 7) * 4);
          __threadfence();
          atomicOr(&g_sync[F_CTX + (item & 7) * 2 + rank], 1u << (item >> 3));
          if (nxt >= K2_END) break;
        }
        }
        const uint32_t unit = __shfl_sync(0xffffffffu, nxt, 0) & 255;
        {
          const int mblk = (7 - (p.unit[unit][0] >> 1)) * 2 + rank, nhalf = p.unit[unit][0] & 1;
          bf16* o = ptr_add(out, (mblk * 128 + p.unit[unit][1] * 32) * DM * 2);
          const bool mine = p.unit[unit][1] < 4;
#pragma unroll 4
          for (int i = 0; i < 32 && mine; i++) __stcg(reinterpret_cast<uint4*>(ptr_add(o, i * DM * 2 + nhalf * 512 + lane * 16)), make_uint4(0, 0, 0, 0));
#pragma unroll
          for (int i = 0; i < 4 && mine; i++) __stcg(reinterpret_cast<uint4*>(ptr_add(o, (i * 8 + (lane >> 2)) * DM * 2 + 1024 + nhalf * 64 + (lane & 3) * 16)), make_uint4(0, 0, 0, 0));
          asm volatile("fence.proxy.async.global;" ::: "memory");
          __threadfence();
          __syncwarp();
          if (lane == 0) {
            prefetch_tmap(&p.tmR[0]); prefetch_tmap(&p.tmR[1]);
            unsigned int* cnt = &g_sync[F_XCH + mblk * 2 + nhalf];
            const uint32_t xtarget = lds32(sGate + 64) * 4 + 4;
            if (mine) atomicAdd(cnt, 1u);
            uint32_t v;
#pragma unroll 1
            for (uint32_t spins = 0; spins < (1u << 22); spins++) {
              asm volatile("ld.acquire.gpu.global.u32 %0, [%1];" : "=r"(v) : "l"(cnt) : "memory");
              if ((int)(v - xtarget) >= 0) break;
              __nanosleep(200);
            }
            asm volatile("fence.proxy.async.global;" ::: "memory");
            mbar_arrive(bZ);
          }
        }
      } else if (warp_g == 11) {
        if (lane == 0) {
          asm volatile("st.shared.u32 [%0], %1;" ::"r"(sGate + 64), "r"(__ldcg(&g_sync[F_EPOCH])) : "memory");
          wait_flag(&g_sync[F_GATE], GATE_TARGET);
          prefetch_tmap(&p.tmC); prefetch_tmap(&p.tmQ); prefetch_tmap(&p.tmK); prefetch_tmap(&p.tmV);
          uint32_t tick;
          if (rank == 0) {
            PWAIT(bLast, 0);
            PWAIT(bAe + FIRST_DRAW * 8, aph);
            tick = atomicAdd(&g_sync[F_TICK], 1u);
            asm volatile("st.shared.u32 [%0], %1;" ::"r"(sTick + 8), "r"(tick) : "memory");
            asm volatile(
                "{\n.reg .b32 a, b;\nmapa.shared::cluster.u32 a, %0, 1;\nmapa.shared::cluster.u32 b, %1, 1;\n"
                "st.async.shared::cluster.mbarrier::complete_tx::bytes.u32 [a], %2, [b];\n}" ::"r"(sTick + 8), "r"(bT0), "r"(tick) : "memory");
          } else {
            mbar_expect(bT0, 4);
            PWAIT(bT0, 0);
            tick = lds32(sTick + 8);
          }
          wait_flag(&g_sync[F_HP + (p.order[tick] >> 4)], RDY_TARGET);
          mbar_arrive(bR);
        }
      } else if (warp_g == 10) {
        if (lr0 < S_LEN && lane == 0) {
          prefetch_tmap(&p.tmL[0]); prefetch_tmap(&p.tmL[1]); prefetch_tmap(&p.tmL[2]);
          wait_flag(&g_sync[F_QKVA + (lr0 >> 7)], K1_FLAG_TARGET);
          wait_flag(&g_sync[F_QKVA + (max(lr0 - 16, 0) >> 7)], K1_FLAG_TARGET);
          asm volatile("fence.proxy.async.global;" ::: "memory");
          PWAIT(bLast, 0);
#pragma unroll 1
          for (int kc = 0; kc < 6; kc++) {
            PWAIT(bAe + kc * 8, aph);
            if (kc == 3) {
              mbar_expect(bL, LV);
              tma4d(sL, &p.tmL[0], bL, lr0 / 2 - 8, 9, 0);
              tma4d(sL + LQ, &p.tmL[1], bL, lr0 / 2, 0, 0);
            }
          }
          mbar_expect(bL2, LQ);
          tma4d(sL + LV, &p.tmL[0], bL2, lr0 / 2 - 8, 18, 0);
        }
        __syncwarp();
        bar_sync(5, 256 + 32);
        if (lr0 < S_LEN && lane == 0) {
          asm volatile("cp.async.bulk.tensor.4d.global.shared::cta.bulk_group [%0, {%2, %3, %2, %2}], [%1];" ::"l"(&p.tmL[2]), "r"(sL + LQ), "r"(0), "r"(lr0 / 2) : "memory");
          asm volatile("cp.async.bulk.commit_group;" ::: "memory");
          asm volatile("cp.async.bulk.wait_group.read 0;" ::: "memory");
        }
        __syncwarp();
        if (lane < 12) mbar_arrive_cluster(bE + (4 + lane % 3) * 8, (lane / 3) & 1);
        if (lr0 < S_LEN && lane == 0) {
          asm volatile("cp.async.bulk.wait_group 0;" ::: "memory");
          asm volatile("fence.proxy.async.global;" ::: "memory");
          __threadfence();
          atomicAdd(&g_sync[F_OA + (lr0 >> 7)], 1u);
        }
      }
    }
    __syncwarp();
    cluster_sync();
  } else {
    reg_alloc<232>();
    const int wg = warp_g >> 2, warp = warp_g & 3, q = lane & 3;
    const bool sig = (lane == 0) && (warp < 2);
    {
      K1State st{0, 0, 0, nullptr, nullptr, 0, 0, 0, 24};
      float acc[128];
      uint32_t pk[64];
      if (wg == 0) { TS(0, 0); TSC(0, 2); }
      uint32_t job = p.jobs[cl][0];
      k1_first(st, job, bAf, bBf);
      {
#pragma unroll 1
        for (int ji = 0; job & 3; ji++) {
          const uint32_t njob = p.jobs[cl][ji + 1];
          k1_tile(acc, pk, st, job, njob, sA, sB, bAf, bAe, bBf, bBe, bS, wg, warp, lane, rank);
          job = njob;
        }
      }
#pragma unroll
      for (int i = 0; i < 4; i++)
        mbar_arrive_cluster_if(bE + i * 8, warp & 1, sig);
      if (lr0 < S_LEN) bar_sync(3, 256 + 96);
      if (st.wsel == 3) {
#pragma unroll
        for (int G = 0; G < 16; G++) scale_q4(pk + G * 4);
      }
      auto flush = [&](int i, uint32_t dep) {
        asm volatile("{\n.reg .pred p;\nsetp.eq.u32 p, %5, 0;\n@p st.global.cs.v4.b32 [%0], {%1, %2, %3, %4};\n}" ::"l"(((i & 1) ? st.pp8 : st.pp) + (i / 2) * 32),
                     "r"(pk[i * 4]), "r"(pk[i * 4 + 1]), "r"(pk[i * 4 + 2]), "r"(pk[i * 4 + 3]), "r"(dep & blockIdx.y) : "memory");
      };
      if (wg == 0) { TS(0, 1); TSC(0, 3); }
      if (lr0 < S_LEN) {
        const float gate0 = __uint_as_float(lds32(sGate + (lane >> 2) * 8)), gate1 = __uint_as_float(lds32(sGate + (lane >> 2) * 8 + 4));
        local_attn(lr0, warp_g, sL, bL, bL2, lane, gate0, gate1, flush);
        k1_flag(st, lane, bS);
      } else {
        FLUSH();
      }
      bar_arrive(5, 256 + 32);
    }
    __syncwarp();
    uint32_t item, rot;
    {
      const int mybar = 1 + wg, otherbar = 2 - wg;
      const uint32_t never = blockIdx.y;
      float S[64], O[64];
      uint32_t P[32], Q[32];
      float m0, m1, l0, l1, gf0, gf1;
      uint32_t eoff;
      Cursor c{2 + 2 * (uint32_t)wg, 0}, ck{1 + (uint32_t)wg, 0};
      if (wg == 1) bar_arrive(1, 256);
      if (wg == 0) { TS(1, 0); TSC(1, 2); }
      {
        const Cursor cq{0, 0}, cs0{1, 0}, cs1{3, 0};
        const int it = 0, hi = wg ^ 1;
        mbar_wait2(bF, 0, bF + ck.s * 8, 0);
        LOAD_Q();
        wg_fence();
        ISSUE_QK(ck);
        wg_commit();
        RELEASE(cq);
        NEW_ITEM();
        wg_wait<0>();
        fence_regs(S);
      }
#pragma unroll 1
      for (int it = 0;;) {
        int hi = (wg ^ it ^ 1) & 1;
        RELEASE(ck);
        const int nblk = 2 * (item & 7) + 1 + hi;
        Cursor cv;
        float s0 = 0.f, s1 = 0.f;
        l0 = 0.f; l1 = 0.f;
        m0 = 0.f; m1 = 0.f;
        bool shifted = false;
        {
          const int d = warp * 16 + (lane >> 2) - 2 * q;
          if (rank == hi) {
#pragma unroll
            for (int jj = 0; jj < 8; jj++) MASK(jj, jj);
            EXPB(0); EXPB(1); EXPB(2); EXPB(3);
#pragma unroll
            for (int i = 32; i < 64; i++) S[i] = -INFINITY;
#pragma unroll
            for (int i = 16; i < 32; i++) P[i] = 0;
          } else {
#pragma unroll
            for (int jj = 0; jj < 8; jj++) MASK(jj + 8, jj);
            EXPB(0); EXPB(1); EXPB(2); EXPB(3); EXPB(4); EXPB(5); EXPB(6); EXPB(7);
          }
        }
        float chk = (q == 0 && !(fminf(s0, s1) >= SPEC_LO)) ? INFINITY : s0 + s1;
        fence_regs(P);
        TB(9);
#pragma unroll 1
        for (int n = 1;; n++) {
          if (__any_sync(0xffffffffu, !(chk <= SPEC_HI))) {
            float mx0 = fmaxf(S[0], S[1]), mx1 = fmaxf(S[2], S[3]);
#pragma unroll
            for (int jj = 1; jj < 16; jj++) {
              mx0 = fmaxf(mx0, fmaxf(S[jj * 4 + 0], S[jj * 4 + 1]));
              mx1 = fmaxf(mx1, fmaxf(S[jj * 4 + 2], S[jj * 4 + 3]));
            }
            mx0 = fmaxf(mx0, __shfl_xor_sync(0xffffffffu, mx0, 1));
            mx1 = fmaxf(mx1, __shfl_xor_sync(0xffffffffu, mx1, 1));
            mx0 = fmaxf(mx0, __shfl_xor_sync(0xffffffffu, mx0, 2));
            mx1 = fmaxf(mx1, __shfl_xor_sync(0xffffffffu, mx1, 2));
            const float lo = (n == 1) ? -INFINITY : 0.f;
            mx0 = fmaxf(mx0, lo);
            mx1 = fmaxf(mx1, lo);
            m0 += mx0; m1 += mx1;
            shifted = true;
            const float sc0 = ex2(-fmaxf(mx0, 0.f)), sc1 = ex2(-fmaxf(mx1, 0.f));
            l0 *= sc0; l1 *= sc1;
            s0 = 0.f; s1 = 0.f;
#pragma unroll
            for (int jj = 0; jj < 16; jj++) {
              const float e0 = ex2(S[jj * 4 + 0] - mx0), e1 = ex2(S[jj * 4 + 1] - mx0), e2 = ex2(S[jj * 4 + 2] - mx1), e3 = ex2(S[jj * 4 + 3] - mx1);
              s0 += e0 + e1;
              s1 += e2 + e3;
              P[jj * 2 + 0] = pack_bf16(e0, e1);
              P[jj * 2 + 1] = pack_bf16(e2, e3);
              O[jj * 4 + 0] *= sc0;
              O[jj * 4 + 1] *= sc0;
              O[jj * 4 + 2] *= sc1;
              O[jj * 4 + 3] *= sc1;
            }
          }
          l0 += s0;
          l1 += s1;
          if (n >= nblk) break;
          ck = c; c.next();
          cv = c; c.next();
          mbar_wait(bF + ck.s * 8, ck.ph);
          mbar_wait(bF + cv.s * 8, cv.ph);
          TURN_SYNC();
          TRC(0);
          wg_fence();
          ISSUE_QK(ck);
          wg_commit();
          {
            const uint64_t dv = make_desc(sbase + cv.s * 32768, 16384, 1024, 1);
#pragma unroll
            for (int t = 0; t < 8; t++) {
              wgmma_rs_n128<1, 0>(O, P[4 * t], P[4 * t + 1], P[4 * t + 2], P[4 * t + 3], dv + (uint64_t)(t * 128), (t > 0) ? 1 : (n != 1));
              if ((PVM >> t) & 1) wg_commit();
            }
          }
          TURN_ARRIVE();
          s0 = 0.f; s1 = 0.f;
          wg_wait<__builtin_popcount(PVM)>();
          fence_regs(S);
          RELEASE(ck);
          if (shifted) {
#pragma unroll
            for (int i = 0; i < 64; i++) S[i] -= (i & 2) ? m1 : m0;
          }
          wg_wait<__builtin_popcount(PVM) - 1>();
          EXPC(0); EXPC(1); EXPC(2); EXPC(3); EXPC(4); EXPC(5); EXPC(6); EXPC(7);
          chk = s0 + s1;
        }
        it++;
        hi ^= 1;
        TB(0);
        Cursor cq = c, cs0, cs1;
        rot = k3_rot(c.s);
        c.next();
        ck = c; c.next();
        cs0 = ck; cs1 = ck;
        cv = c; c.next();
        if (!hi) {
          ck = c; c.next();
          cs1 = c; c.next();
        }
        mbar_wait(bF + cq.s * 8, cq.ph);
        TB(1);
        LOAD_Q();
        const uint32_t rdy = mbar_test(bF + ck.s * 8, ck.ph) & mbar_test(bF + cv.s * 8, cv.ph);
        l0 += __shfl_xor_sync(0xffffffffu, l0, 1);
        l1 += __shfl_xor_sync(0xffffffffu, l1, 1);
        l0 += __shfl_xor_sync(0xffffffffu, l0, 2);
        l1 += __shfl_xor_sync(0xffffffffu, l1, 2);
        if (item >= K2_END) {
          TURN_SYNC();
          TRC(2);
          wg_fence();
          ISSUE_PV(cq, nblk == 1);
          wg_commit();
          if (wg == (it & 1)) TURN_ARRIVE();
          asm volatile("" : "+f"(gf0), "+f"(gf1), "+f"(l0), "+f"(l1));
          const float f0 = __fdividef(1.f - gf0, l0), f1 = __fdividef(1.f - gf1, l1);
          bf16* optr = ptr_add(g_ctx, eoff);
          wg_wait<0>();
          fence_regs(O);
          mbar_arrive_cluster_if(bH, warp & 1, sig);
          STORE_O(0); STORE_O(1); STORE_O(2); STORE_O(3);
          __syncwarp();
          mbar_arrive_if(bS2 + ((it - 1) & 3) * 8, lane == 0);
          break;
        }
        if (!rdy) mbar_wait2(bF + ck.s * 8, ck.ph, bF + cv.s * 8, cv.ph);
        TB(2);
        TURN_SYNC();
        TB(3);
        TRC(1);
        wg_fence();
        ISSUE_PV(cv, nblk == 1);
        wg_commit();
        ISSUE_QK(ck);
        wg_commit();
        TURN_ARRIVE();
        RELEASE(cq);
        TB(4);
        asm volatile("" : "+f"(gf0), "+f"(gf1), "+f"(l0), "+f"(l1));
        const float f0 = __fdividef(1.f - gf0, l0), f1 = __fdividef(1.f - gf1, l1);
        wg_wait<1>();
        fence_regs(O);
        fence_regs(P);
        TB(5);
        RELEASE(cv);
        {
          bf16* optr = ptr_add(g_ctx, eoff);
          STORE_O(0); STORE_O(1); STORE_O(2); STORE_O(3);
          __syncwarp();
          mbar_arrive_if(bS2 + ((it - 1) & 3) * 8, lane == 0);
        }
        TB(6);
        NEW_ITEM();
        TB(7);
        wg_wait<0>();
        fence_regs(S);
        TB(8);
      }
      TRC(3);
      if (wg == 1) { TS(1, 1); TSC(1, 3); }
    }
    __syncwarp();
    const uint32_t unit = item & 255;
    {
      const int mblk = (7 - (p.unit[unit][0] >> 1)) * 2 + rank, nhalf = p.unit[unit][0] & 1;
      float acc[144];
      uint32_t s = rot, ph = 0, prev = 0, k = 0;
      if (wg == 0) { TS(2, 0); TSC(2, 2); }
      uint32_t fa[16], fb[16], fc[16];
      const uint32_t aoff = (wg * 64 + warp * 16 + (lane & 15)) * 128 + (((lane >> 4) ^ (lane & 7)) << 4);
#define C_NEXT()                                                                                               \
  do {                                                                                                         \
    s = (s + 1) & 3;                                                                                           \
    if (s == rot) ph ^= 1;                                                                                     \
    mbar_wait(b3F + s * 8, ph);                                                                                \
  } while (0)
#define C_LOAD(F)                                                                                              \
  do {                                                                                                         \
    _Pragma("unroll") for (int t = 0; t < 4; t++)                                                              \
        ldsm_x4(F[4 * t], F[4 * t + 1], F[4 * t + 2], F[4 * t + 3], sbase + s * K3_STAGE + (aoff ^ (t * 32))); \
  } while (0)
#define C_MMA(F, S, H, SD)                                                                                     \
  do {                                                                                                         \
    const uint32_t st = sbase + (S) * K3_STAGE;                                                                \
    const uint64_t db = make_desc(st + 16384, 4096, 1024, 1), dt = make_desc(st + 49152, 16, 512, 2);          \
    _Pragma("unroll") for (int t = 0; t < 4; t++) {                                                            \
      const int sd = (t > 0) || (SD);                                                                          \
      if ((H) & 1) wgmma_rs_n128<1, 0>(acc, F[4 * t], F[4 * t + 1], F[4 * t + 2], F[4 * t + 3], db + (uint64_t)((t >> 1) * 1024 + (t & 1) * 128), sd); \
      if ((H) & 2) wgmma_rs_n128<1, 64>(acc, F[4 * t], F[4 * t + 1], F[4 * t + 2], F[4 * t + 3], db + (uint64_t)((t >> 1) * 1024 + (t & 1) * 128 + 512), sd); \
      if ((H) & 2) wgmma_rs_n32<1, 128>(acc, F[4 * t], F[4 * t + 1], F[4 * t + 2], F[4 * t + 3], dt + (uint64_t)(t * 64), sd); \
    }                                                                                                          \
  } while (0)
#define C_STEP(F, G)                                                                                           \
  {                                                                                                            \
    wg_fence();                                                                                                \
    C_MMA(F, s, 3, k > 0);                                                                                     \
    wg_commit();                                                                                               \
    wg_wait<1>();                                                                                              \
    fence_regs(G);                                                                                             \
    mbar_arrive_cluster_if(b3E + prev * 8, warp & 1, sig && k > 0);                                            \
    prev = s;                                                                                                  \
    TCK(k + 1);                                                                                                \
    C_NEXT();                                                                                                  \
    if ((tid & 127) == 0 && k < 11) TP(37 + wg * 12 + k);                                                      \
    if (++k + CR >= lds32(sK1)) break;                                                                         \
    C_LOAD(G);                                                                                                 \
  }
      TCK(0);
      mbar_wait(b3F + s * 8, 0);
      if ((tid & 127) == 0) TP(36 + wg * 12);
      C_LOAD(fa);
#pragma unroll
      for (int i = 0; i < 16; i++) fb[i] = 0;
#pragma unroll 1
      for (;;) {
        C_STEP(fa, fb)
        C_STEP(fb, fa)
      }
      C_LOAD(fc);
      if (wg == 1) {
        wg_wait<0>();
        mbar_arrive_cluster_if(b3E + prev * 8, warp & 1, sig);
        mbar_wait(bLd, 0);
      }
      const uint32_t s0 = s;
      wg_fence();
      C_MMA(fc, s0, 2, 1);
      wg_commit();
      wg_wait<1>();
      fence_regs(fa);
      fence_regs(fb);
      mbar_arrive_cluster_if(b3E + prev * 8, warp & 1, sig && wg == 0);
      cluster_arrive();
      C_NEXT();
      C_LOAD(fa);
      wg_fence();
      C_MMA(fa, s, 2, 1);
      C_MMA(fc, s0, 1, 1);
      wg_commit();
      C_NEXT();
      C_LOAD(fb);
      wg_fence();
      C_MMA(fb, s, 2, 1);
      wg_commit();
      wg_wait<1>();
      fence_regs(fc);
      C_NEXT();
      C_LOAD(fc);
      wg_fence();
      C_MMA(fc, s, 2, 1);
      wg_commit();
      C_MMA(fa, (s0 + 1) & 3, 1, 1);
      C_MMA(fb, (s0 + 2) & 3, 1, 1);
      C_MMA(fc, s, 1, 1);
      wg_commit();
      mbar_arrive_if(bLd, tid < 128 && lane == 0);
      const uint32_t stail = sbase + K3_NST * K3_STAGE + warp_g * 1024;
      const int row = mblk * 128 + warp_g * 16;
      mbar_wait(bZ, 0);
#pragma unroll
      for (int h = 1; h >= 0; h--) {
        if (h) wg_wait<1>(); else wg_wait<0>();
#pragma unroll
        for (int i = h * 64; i < 64 + h * 80; i++) asm volatile("" : "+f"(acc[i])::"memory");
        if (!h && wg == 0) TS(2, 4);
#pragma unroll
        for (int i = h * 8; i < 8 + h * 10; i++) {
          const uint32_t ad = (i < 16) ? sbase + (i >> 2) * K3_STAGE + (aoff ^ ((i & 3) * 32))
                                       : stail + (lane & 15) * 64 + ((((i & 1) * 2 + (lane >> 4)) ^ ((lane >> 1) & 3)) << 4);
          asm volatile("stmatrix.sync.aligned.m8n8.x4.shared.b16 [%0], {%1, %2, %3, %4};" ::"r"(ad), "r"(pack_bf16(acc[i * 8], acc[i * 8 + 1])),
                       "r"(pack_bf16(acc[i * 8 + 2], acc[i * 8 + 3])), "r"(pack_bf16(acc[i * 8 + 4], acc[i * 8 + 5])), "r"(pack_bf16(acc[i * 8 + 6], acc[i * 8 + 7])) : "memory");
        }
        asm volatile("fence.proxy.async.shared::cta;" ::: "memory");
        __syncwarp();
        if (!h && wg == 0) TS(2, 5);
        if (lane == 0) {
#pragma unroll
          for (int c = h * 2; c < 2 + h * 3; c++)
            asm volatile("cp.reduce.async.bulk.tensor.2d.global.shared::cta.add.tile.bulk_group [%0, {%2, %3}], [%1];" ::"l"(&p.tmR[c >> 2]),
                         "r"((c < 4) ? sbase + c * K3_STAGE + warp_g * 2048 : stail), "r"((c < 4) ? nhalf * 256 + c * 64 : 512 + nhalf * 32), "r"(row) : "memory");
        }
        __syncwarp();
      }
      if (lane == 0) {
        asm volatile("cp.async.bulk.commit_group;" ::: "memory");
        if (wg == 0) TS(2, 6);
        asm volatile("cp.async.bulk.wait_group 0;" ::: "memory");
      }
      __syncwarp();
    }
    if (wg == 0) { TS(2, 1); TSC(2, 3); }
    cluster_wait();
  }
}

typedef CUresult (*EncFn)(CUtensorMap*, CUtensorMapDataType, cuuint32_t, void*, const cuuint64_t*, const cuuint64_t*, const cuuint32_t*,
                          const cuuint32_t*, CUtensorMapInterleave, CUtensorMapSwizzle, CUtensorMapL2promotion, CUtensorMapFloatOOBfill);

static void enc2d(EncFn enc, CUtensorMap* m, const void* ptr, uint64_t cols, uint64_t rows, uint32_t bc, uint32_t br,
                  CUtensorMapSwizzle sw = CU_TENSOR_MAP_SWIZZLE_128B) {
  cuuint64_t gd[2] = {cols, rows}, gs[1] = {cols * 2};
  cuuint32_t bx[2] = {bc, br}, es[2] = {1, 1};
  enc(m, CU_TENSOR_MAP_DATA_TYPE_BFLOAT16, 2, const_cast<void*>(ptr), gd, gs, bx, es, CU_TENSOR_MAP_INTERLEAVE_NONE, sw,
      CU_TENSOR_MAP_L2_PROMOTION_L2_256B, CU_TENSOR_MAP_FLOAT_OOB_FILL_NONE);
}
static void enc3d(EncFn enc, CUtensorMap* m, const void* ptr, uint64_t cols, uint64_t rows, uint32_t br, uint32_t bch) {
  cuuint64_t gd[3] = {64, rows, cols / 64}, gs[2] = {cols * 2, 128};
  cuuint32_t bx[3] = {64, br, bch}, es[3] = {1, 1, 1};
  enc(m, CU_TENSOR_MAP_DATA_TYPE_BFLOAT16, 3, const_cast<void*>(ptr), gd, gs, bx, es, CU_TENSOR_MAP_INTERLEAVE_NONE,
      CU_TENSOR_MAP_SWIZZLE_128B, CU_TENSOR_MAP_L2_PROMOTION_L2_256B, CU_TENSOR_MAP_FLOAT_OOB_FILL_NONE);
}

static int g_sched[10] = {11, 10, 7, 4, 4, 4, 6, 8, 6, 24};
static void build_k1_jobs(Params& p) {
  int cnt[NCLUSTER];
  for (int c = 0; c < NCLUSTER; c++) {
    cnt[c] = 0;
    for (int i = 0; i <= K1_MAXJOBS; i++) p.jobs[c][i] = 0;
  }
  auto add = [&](int c, int nch, int a_sel, int mp, int w_sel, int chunk0) {
    p.jobs[c][cnt[c]++] = (uint16_t)((nch - 1) | (a_sel << 2) | (mp << 3) | (w_sel << 6) | (chunk0 << 8));
  };
  const char* plan = "ccccccccccc cccccccccc ccccccc cccc xxxx xxxx xxxxxx xxxxxxxx";
  int TIE = 0;
  int XA = 0;
  const char* cur[8];
  int tend[8] = {};
  for (int g = 0; g < 8; g++) {
    cur[g] = plan;
    while (*plan == 'c' || *plan == 'x') plan++;
    if (*plan) plan++;
  }
  int kc = 0, kx = 0;
  for (;;) {
    int b = -1, bt = 0;
    for (int g = 0; g < 8; g++) {
      const int t = tend[g] + (*cur[g] == 'x' ? 94 : 85);
      if ((*cur[g] == 'c' || *cur[g] == 'x') && (b < 0 || t < bt || (TIE && t == bt))) { b = g; bt = t; }
    }
    if (b < 0) break;
    const int a = kx - XA;
    for (int mp = 0; mp < 8; mp++) {
      if (*cur[b] == 'c') add(b * 8 + mp, 4, 0, mp, kc & 1, (kc >> 1) * 4);
      else if (a >= 0 && a < 7) add(b * 8 + mp, a == 0 ? 3 : 4, 1, mp, 2, a == 0 ? 24 : (a - 1) * 4);
      else add(b * 8 + mp, 4, 1, mp, 3, (a < 0 ? kx : kx - 7) * 4);
    }
    if (*cur[b] == 'c') kc++; else kx++;
    cur[b]++;
    tend[b] = bt;
  }
  for (int mp = 0; mp < 8; mp++) add(64 + mp / 4, 4, 1, mp, 3, 15 * 4);
  for (int cc = 0; cc < NCLUSTER; cc++)
    for (int i = 0; i < cnt[cc]; i++) {
      const int key = p.jobs[cc][i] & 0x3C;
      if (i == 0 || (p.jobs[cc][i - 1] & 0x3C) != key) p.jobs[cc][i] |= (1 << 14);
      if (i == cnt[cc] - 1 || (p.jobs[cc][i + 1] & 0x3C) != key) p.jobs[cc][i] |= (1 << 15);
    }
}

static void build_k2_items(Params& p) {
  int n = 0;
  const int SCHED_N1 = g_sched[8], SCHED_N2 = g_sched[9];
  int N0 = 2, J0 = 2;
  for (int j = 7; j >= J0; j--)
    for (int h = 0; h < N0; h++) p.order[n++] = (uint8_t)(h * 8 + j);
  for (int j = 7; j >= 0; j--)
    for (int h = 0; h < SCHED_N1; h++)
      if (!(h < N0 && j >= J0)) p.order[n++] = (uint8_t)(h * 8 + j);
  for (int j = 7; j >= 4; j--)
    for (int h = SCHED_N1; h < SCHED_N2; h++) p.order[n++] = (uint8_t)(h * 8 + j);
  for (int j = 7; j >= 0; j--)
    for (int h = SCHED_N1; h < 32; h++)
      if (!(h < SCHED_N2 && j >= 4)) p.order[n++] = (uint8_t)(h * 8 + j);
  int TJ[2] = {0, 0}, TP = 0;
  for (int t = 0; t < 2; t++) {
    if (!TJ[t]) continue;
    int i = 0;
    while (p.order[i] != 31 * 8 + TJ[t]) i++;
    for (; i < 255 - TP; i++) p.order[i] = p.order[i + 1];
    p.order[i] = (uint8_t)(31 * 8 + TJ[t]);
  }
}

static void build_k3_units(Params& p) {
  int um = 0;
  for (int u = 0; u < 66; u++) {
    int t = (u % 28 < 14) ? u % 28 : 27 - u % 28, i = u / 14;
    if (um == 1) t = u % 14;
    if (um == 2) { t = (u % 28) / 2; i = (u / 28) * 2 + (u & 1); }
    if (um == 3) { t = u / 4; i = u & 3; }
    if (um == 4) { t = (u < 42) ? u / 3 : u - 42; i = (u < 42) ? u % 3 : 3; }
    if (u >= 56) { t = 14 + ((0x199 >> (u - 56)) & 1); i = (u - 56) / 2; }
    uint8_t* w = p.unit[u];
    w[0] = (uint8_t)t; w[1] = (uint8_t)i; w[2] = (uint8_t)(i * K3_NS); w[3] = (uint8_t)(((u >= 56) ? 5 : 4) * K3_NS);
  }
}

extern "C" void kernel_launch(void* const* d_in, const int* in_sizes, int n_in, void* d_out, int out_size) {
  const bf16* x = (const bf16*)d_in[0];
  const bf16* wqkv = (const bf16*)d_in[1];
  const bf16* wo = (const bf16*)d_in[2];
  const bf16* ckv = (const bf16*)d_in[4];
  const bf16* w_q = (const bf16*)d_in[5];
  const bf16* w_uk = (const bf16*)d_in[6];
  const bf16* w_uv = (const bf16*)d_in[7];
  const bf16* w_o = (const bf16*)d_in[8];
  const bf16* gate_w = (const bf16*)d_in[9];

  EncFn enc = nullptr;
  cudaDriverEntryPointQueryResult qr;
  cudaGetDriverEntryPoint("cuTensorMapEncodeTiled", (void**)&enc, cudaEnableDefault, &qr);
  void *pK, *pV, *pCtx, *pQA;
  cudaGetSymbolAddress(&pQA, g_QKVA);
  cudaGetSymbolAddress(&pK, g_K);
  cudaGetSymbolAddress(&pV, g_V);
  cudaGetSymbolAddress(&pCtx, g_ctx);

  static Params p;
  enc2d(enc, &p.tmA[0], ckv, DC, S_LEN, 64, 128);
  enc2d(enc, &p.tmA[1], x, DM, S_LEN, 64, 128);
  enc3d(enc, &p.tmW[0], w_uk, HDIM, DC, 16, 4);
  enc3d(enc, &p.tmW[1], w_uv, HDIM, DC, 16, 4);
  enc3d(enc, &p.tmW[2], wqkv, NQKVA, DM, 16, 4);
  enc3d(enc, &p.tmW[3], w_q, HDIM, DM, 16, 4);
  build_k1_jobs(p);
  enc2d(enc, &p.tmK, pK, HDIM, S_LEN, 64, 128);
  enc2d(enc, &p.tmV, pV, HDIM, S_LEN, 64, 128);
  enc2d(enc, &p.tmQ, pCtx, KCAT, S_LEN, 64, 64);
  build_k2_items(p);
  build_k3_units(p);
  for (int i = 0; i < 3; i++) {
    const cuuint64_t ld = (i < 2 ? NQKVA : KCAT) * 2, nch = (i < 2) ? 27 : 9;
    cuuint64_t gd[4] = {64, S_LEN / 2, i ? 2 : nch, i ? nch : 2}, gs[3] = {2 * ld, i ? ld : 128, i ? 128 : ld};
    cuuint32_t bx[4] = {64, i ? 8u : 16u, i ? 2u : 9u, i ? 9u : 2u}, es[4] = {1, 1, 1, 1};
    enc(&p.tmL[i], CU_TENSOR_MAP_DATA_TYPE_BFLOAT16, 4, (i < 2) ? pQA : (void*)((bf16*)pCtx + HDIM), gd, gs, bx, es, CU_TENSOR_MAP_INTERLEAVE_NONE,
        CU_TENSOR_MAP_SWIZZLE_128B, CU_TENSOR_MAP_L2_PROMOTION_L2_256B, CU_TENSOR_MAP_FLOAT_OOB_FILL_NONE);
  }
  enc2d(enc, &p.tmC, pCtx, KCAT, S_LEN, 64, 128);
  enc3d(enc, &p.tmO[0], w_o, DM, HDIM, 32, 4);
  enc3d(enc, &p.tmO[1], wo, DM, DM, 32, 4);
  enc2d(enc, &p.tmOt[0], w_o, DM, HDIM, 32, 32, CU_TENSOR_MAP_SWIZZLE_64B);
  enc2d(enc, &p.tmOt[1], wo, DM, DM, 32, 32, CU_TENSOR_MAP_SWIZZLE_64B);
  enc2d(enc, &p.tmR[0], d_out, DM, S_LEN, 64, 16);
  enc2d(enc, &p.tmR[1], d_out, DM, S_LEN, 32, 16, CU_TENSOR_MAP_SWIZZLE_64B);

  cudaFuncSetAttribute(fused_kernel, cudaFuncAttributeMaxDynamicSharedMemorySize, SMEM_BYTES);
  fused_kernel<<<NCLUSTER * 2, 384, SMEM_BYTES>>>(p, x, gate_w, (bf16*)d_out);
}
```

```cpp
#include <cuda_runtime.h>
#include <cuda_bf16.h>
#include <cuda.h>
#include <stdint.h>

typedef __nv_bfloat16 bf16;

constexpr int S_LEN = 2048, DM = 576, DC = 512, HDIM = 4096, NQKVA = 1728, KCAT = 4672;
constexpr int NCLUSTER = 66;

__device__ __align__(1024) bf16 g_K[S_LEN * HDIM];
__device__ __align__(1024) bf16 g_V[S_LEN * HDIM];
__device__ __align__(1024) bf16 g_QKVA[S_LEN * NQKVA + 64];
__device__ __align__(1024) bf16 g_ctx[S_LEN * KCAT];
__device__ float g_gate[S_LEN];
__device__ __align__(16) unsigned int g_sync[400];
constexpr int F_QKVA = 0, F_HP = 16, F_CTX = 32, F_OA = 48, F_CLM = 64, F_GATE = 96, F_TICK = 97, F_DONE = 98, F_XCH = 128, F_EPOCH = 384;

__device__ __forceinline__ uint32_t smem_u32(const void* p) { return (uint32_t)__cvta_generic_to_shared(p); }
__device__ __forceinline__ void mbar_init(uint32_t a, uint32_t c) {
  asm volatile("mbarrier.init.shared::cta.b64 [%0], %1;" ::"r"(a), "r"(c));
}
__device__ __forceinline__ void mbar_expect(uint32_t a, uint32_t b) {
  asm volatile("mbarrier.arrive.expect_tx.shared::cta.b64 _, [%0], %1;" ::"r"(a), "r"(b) : "memory");
}
#define TS(k, i)
#define TSC(k, i)
#define TSM(k)
#define BSEG(i)
#define TB(k)
#define TRC(fl)
#define TCK(i)
#define TP(i)
#define SPIN_LIMIT "4194304"
__device__ __forceinline__ void mbar_wait(uint32_t a, uint32_t parity) {
  asm volatile(
      "{\n.reg .pred p;\n.reg .u32 n;\n"
      "mbarrier.try_wait.parity.shared::cta.b64 p, [%0], %1;\n"
      "@p bra DONE;\n"
      "mov.u32 n, 0;\n"
      "LOOP:\n"
      "mbarrier.try_wait.parity.shared::cta.b64 p, [%0], %1;\n"
      "@p bra DONE;\n"
      "add.u32 n, n, 1;\n"
      "setp.lt.u32 p, n, " SPIN_LIMIT ";\n"
      "@p bra LOOP;\n"
      "DONE:\n}" ::"r"(a), "r"(parity) : "memory");
}
template <int NS>
__device__ __forceinline__ void mbar_wait_ns(uint32_t a, uint32_t parity) {
  asm volatile(
      "{\n.reg .pred p;\n.reg .u32 n;\n"
      "mov.u32 n, 0;\n"
      "LOOP:\n"
      "mbarrier.try_wait.parity.shared::cta.b64 p, [%0], %1, %2;\n"
      "@p bra DONE;\n"
      "add.u32 n, n, 1;\n"
      "setp.lt.u32 p, n, " SPIN_LIMIT ";\n"
      "@p bra LOOP;\n"
      "DONE:\n}" ::"r"(a), "r"(parity), "n"(NS) : "memory");
}
__device__ __forceinline__ void mbar_wait2(uint32_t a, uint32_t pa, uint32_t b, uint32_t pb) {
  asm volatile(
      "{\n.reg .pred p, q;\n.reg .u32 n;\n"
      "mov.u32 n, 0;\n"
      "LOOP:\n"
      "mbarrier.try_wait.parity.shared::cta.b64 p, [%0], %1;\n"
      "mbarrier.try_wait.parity.shared::cta.b64 q, [%2], %3;\n"
      "add.u32 n, n, 1;\n"
      "and.pred p, p, q;\n"
      "setp.lt.and.u32 p, n, " SPIN_LIMIT ", !p;\n"
      "@p bra LOOP;\n"
      "}" ::"r"(a), "r"(pa), "r"(b), "r"(pb) : "memory");
}
__device__ __forceinline__ uint32_t mbar_test(uint32_t a, uint32_t parity) {
  uint32_t r;
  asm volatile("{\n.reg .pred p;\nmbarrier.test_wait.parity.shared::cta.b64 p, [%1], %2;\nselp.u32 %0, 1, 0, p;\n}" : "=r"(r) : "r"(a), "r"(parity) : "memory");
  return r;
}
__device__ __forceinline__ void mbar_arrive(uint32_t a) {
  asm volatile("mbarrier.arrive.shared::cta.b64 _, [%0];" ::"r"(a) : "memory");
}
__device__ __forceinline__ void mbar_arrive_cluster(uint32_t a, uint32_t cta) {
  asm volatile("{\n.reg .b32 r;\nmapa.shared::cluster.u32 r, %0, %1;\nmbarrier.arrive.shared::cluster.b64 _, [r];\n}" ::"r"(a),
               "r"(cta) : "memory");
}
__device__ __forceinline__ void mbar_arrive_cluster_if(uint32_t a, uint32_t cta, bool pred) {
  asm volatile("{\n.reg .b32 r;\n.reg .pred p;\nsetp.ne.u32 p, %2, 0;\nmapa.shared::cluster.u32 r, %0, %1;\n@p mbarrier.arrive.shared::cluster.b64 _, [r];\n}" ::"r"(a),
               "r"(cta), "r"((uint32_t)pred) : "memory");
}
__device__ __forceinline__ void anchor(float v, uint32_t pred) {
  asm volatile("{\n.reg .pred p;\nsetp.ne.u32 p, %1, 0;\n@p st.shared.f32 [%1], %0;\n}" ::"f"(v), "r"(pred) : "memory");
}
__device__ __forceinline__ void mbar_arrive_if(uint32_t a, bool pred) {
  asm volatile("{\n.reg .pred p;\nsetp.ne.u32 p, %1, 0;\n@p mbarrier.arrive.shared::cta.b64 _, [%0];\n}" ::"r"(a), "r"((uint32_t)pred) : "memory");
}
__device__ __forceinline__ void tma2d(uint32_t dst, const CUtensorMap* m, uint32_t bar, int c0, int c1) {
  asm volatile("cp.async.bulk.tensor.2d.shared::cluster.global.mbarrier::complete_tx::bytes [%0], [%1, {%3, %4}], [%2];" ::"r"(dst),
               "l"(m), "r"(bar), "r"(c0), "r"(c1) : "memory");
}
__device__ __forceinline__ void tma2d_mc(uint32_t dst, const CUtensorMap* m, uint32_t bar, int c0, int c1, uint16_t mask) {
  asm volatile(
      "cp.async.bulk.tensor.2d.shared::cluster.global.mbarrier::complete_tx::bytes.multicast::cluster [%0], [%1, {%3, %4}], [%2], %5;" ::"r"(dst),
      "l"(m), "r"(bar), "r"(c0), "r"(c1), "h"(mask) : "memory");
}
__device__ __forceinline__ void tma3d_mc(uint32_t dst, const CUtensorMap* m, uint32_t bar, int c0, int c1, int c2, uint16_t mask) {
  asm volatile(
      "cp.async.bulk.tensor.3d.shared::cluster.global.mbarrier::complete_tx::bytes.multicast::cluster [%0], [%1, {%3, %4, %5}], [%2], %6;" ::"r"(dst),
      "l"(m), "r"(bar), "r"(c0), "r"(c1), "r"(c2), "h"(mask) : "memory");
}
__device__ __forceinline__ void tma3d(uint32_t dst, const CUtensorMap* m, uint32_t bar, int c0, int c1, int c2) {
  asm volatile(
      "cp.async.bulk.tensor.3d.shared::cluster.global.mbarrier::complete_tx::bytes [%0], [%1, {%3, %4, %5}], [%2];" ::"r"(dst),
      "l"(m), "r"(bar), "r"(c0), "r"(c1), "r"(c2) : "memory");
}
__device__ __forceinline__ void tma_pf2d(const CUtensorMap* m, int c0, int c1) {
  asm volatile("cp.async.bulk.prefetch.tensor.2d.L2.global [%0, {%1, %2}];" ::"l"(m), "r"(c0), "r"(c1) : "memory");
}
__device__ __forceinline__ void tma_pf3d(const CUtensorMap* m, int c0, int c1, int c2) {
  asm volatile("cp.async.bulk.prefetch.tensor.3d.L2.global [%0, {%1, %2, %3}];" ::"l"(m), "r"(c0), "r"(c1), "r"(c2) : "memory");
}
__device__ __forceinline__ void prefetch_tmap(const CUtensorMap* m) {
  asm volatile("prefetch.tensormap [%0];" ::"l"(m) : "memory");
}
__device__ __forceinline__ void cluster_arrive() { asm volatile("barrier.cluster.arrive.relaxed.aligned;" ::: "memory"); }
__device__ __forceinline__ void cluster_wait() { asm volatile("barrier.cluster.wait.aligned;" ::: "memory"); }
__device__ __forceinline__ void cluster_sync() {
  cluster_arrive();
  cluster_wait();
}
__device__ __forceinline__ uint32_t cluster_rank() {
  uint32_t r;
  asm volatile("mov.u32 %0, %%cluster_ctarank;" : "=r"(r));
  return r;
}
__device__ __forceinline__ bool elect_one() {
  uint32_t p;
  asm volatile("{\n.reg .pred q;\nelect.sync _|q, 0xffffffff;\nselp.u32 %0, 1, 0, q;\n}" : "=r"(p));
  return p;
}
__device__ __forceinline__ void ldsm_x4(uint32_t& r0, uint32_t& r1, uint32_t& r2, uint32_t& r3, uint32_t addr) {
  asm volatile("ldmatrix.sync.aligned.m8n8.x4.shared.b16 {%0, %1, %2, %3}, [%4];" : "=r"(r0), "=r"(r1), "=r"(r2), "=r"(r3) : "r"(addr) : "memory");
}
__device__ __forceinline__ void wg_fence() { asm volatile("wgmma.fence.sync.aligned;" ::: "memory"); }
__device__ __forceinline__ void wg_commit() { asm volatile("wgmma.commit_group.sync.aligned;" ::: "memory"); }
template <int N>
__device__ __forceinline__ void wg_wait() { asm volatile("wgmma.wait_group.sync.aligned %0;" ::"n"(N) : "memory"); }
template <int N>
__device__ __forceinline__ void reg_alloc() { asm volatile("setmaxnreg.inc.sync.aligned.u32 %0;" ::"n"(N)); }
template <int N>
__device__ __forceinline__ void reg_dealloc() { asm volatile("setmaxnreg.dec.sync.aligned.u32 %0;" ::"n"(N)); }
__device__ __forceinline__ void bar_sync(int id, int n) { asm volatile("bar.sync %0, %1;" ::"r"(id), "r"(n) : "memory"); }
__device__ __forceinline__ void bar_arrive(int id, int n) { asm volatile("bar.arrive %0, %1;" ::"r"(id), "r"(n) : "memory"); }
template <int NT>
__device__ __forceinline__ void fence_regs(float (&d)[NT]) {
#pragma unroll
  for (int i = 0; i < NT; i++) asm volatile("" : "+f"(d[i])::"memory");
}
template <int NT>
__device__ __forceinline__ void fence_regs(uint32_t (&d)[NT]) {
#pragma unroll
  for (int i = 0; i < NT; i++) asm volatile("" : "+r"(d[i])::"memory");
}
__device__ __forceinline__ uint64_t make_desc(uint32_t saddr, uint32_t lbo, uint32_t sbo, uint32_t layout) {
  return (uint64_t)((saddr & 0x3FFFF) >> 4) | ((uint64_t)(lbo >> 4) << 16) | ((uint64_t)(sbo >> 4) << 32) | ((uint64_t)layout << 62);
}
__device__ __forceinline__ uint32_t pack_bf16(float lo, float hi) {
  uint32_t r;
  asm("cvt.rn.bf16x2.f32 %0, %1, %2;" : "=r"(r) : "f"(hi), "f"(lo));
  return r;
}
__device__ __forceinline__ float ex2(float x) {
  float r;
  asm("ex2.approx.ftz.f32 %0, %1;" : "=f"(r) : "f"(x));
  return r;
}
__device__ __forceinline__ void st_v4(void* p, uint32_t a, uint32_t b, uint32_t c, uint32_t d) {
#define ST_MOD ".cs"
  asm volatile("st.global" ST_MOD ".v4.b32 [%0], {%1, %2, %3, %4};" ::"l"(p), "r"(a), "r"(b), "r"(c), "r"(d) : "memory");
}
#define STA_MOD ".cs"
__device__ __forceinline__ void st_v4a(void* p, uint32_t a, uint32_t b, uint32_t c, uint32_t d) {
  asm volatile("st.global" STA_MOD ".v4.b32 [%0], {%1, %2, %3, %4};" ::"l"(p), "r"(a), "r"(b), "r"(c), "r"(d) : "memory");
}
template <typename T>
__device__ __forceinline__ T* ptr_add(T* base, uint32_t bytes) {
  uint64_t r;
  asm volatile("{\n.reg .u32 l, h;\nmov.b64 {l, h}, %1;\nadd.cc.u32 l, l, %2;\naddc.u32 h, h, 0;\nmov.b64 %0, {l, h};\n}" : "=l"(r) : "l"(base), "r"(bytes));
  return reinterpret_cast<T*>(r);
}
__device__ __forceinline__ float bf_lo(uint32_t v) { return __uint_as_float(v << 16); }
__device__ __forceinline__ float bf_hi(uint32_t v) { return __uint_as_float(v & 0xFFFF0000u); }

__device__ __forceinline__ void quad_transpose(uint32_t& a0, uint32_t& a1, uint32_t& a2, uint32_t& a3, int q) {
  const bool o1 = q & 1, o2 = q & 2;
  uint32_t t0 = o1 ? a0 : a1, t1 = o1 ? a2 : a3;
  t0 = __shfl_xor_sync(0xffffffffu, t0, 1);
  t1 = __shfl_xor_sync(0xffffffffu, t1, 1);
  if (o1) { a0 = t0; a2 = t1; } else { a1 = t0; a3 = t1; }
  t0 = o2 ? a0 : a2;
  t1 = o2 ? a1 : a3;
  t0 = __shfl_xor_sync(0xffffffffu, t0, 2);
  t1 = __shfl_xor_sync(0xffffffffu, t1, 2);
  if (o2) { a0 = t0; a1 = t1; } else { a2 = t0; a3 = t1; }
}

template<int TB, int OFF, int NT>
__device__ __forceinline__ void wgmma_ss_n256(float (&d)[NT], uint64_t da, uint64_t db, int scale_d) {
  asm volatile("{\n.reg .pred p;\nsetp.ne.b32 p, %130, 0;\n"
    "wgmma.mma_async.sync.aligned.m64n256k16.f32.bf16.bf16 {%0, %1, %2, %3, %4, %5, %6, %7, %8, %9, %10, %11, %12, %13, %14, %15, %16, %17, %18, %19, %20, %21, %22, %23, %24, %25, %26, %27, %28, %29, %30, %31, %32, %33, %34, %35, %36, %37, %38, %39, %40, %41, %42, %43, %44, %45, %46, %47, %48, %49, %50, %51, %52, %53, %54, %55, %56, %57, %58, %59, %60, %61, %62, %63, %64, %65, %66, %67, %68, %69, %70, %71, %72, %73, %74, %75, %76, %77, %78, %79, %80, %81, %82, %83, %84, %85, %86, %87, %88, %89, %90, %91, %92, %93, %94, %95, %96, %97, %98, %99, %100, %101, %102, %103, %104, %105, %106, %107, %108, %109, %110, %111, %112, %113, %114, %115, %116, %117, %118, %119, %120, %121, %122, %123, %124, %125, %126, %127}, %128, %129, p, 1, 1, 0, %131;\n}\n"
    : "+f"(d[OFF+0]), "+f"(d[OFF+1]), "+f"(d[OFF+2]), "+f"(d[OFF+3]), "+f"(d[OFF+4]), "+f"(d[OFF+5]), "+f"(d[OFF+6]), "+f"(d[OFF+7]), "+f"(d[OFF+8]), "+f"(d[OFF+9]), "+f"(d[OFF+10]), "+f"(d[OFF+11]), "+f"(d[OFF+12]), "+f"(d[OFF+13]), "+f"(d[OFF+14]), "+f"(d[OFF+15]), "+f"(d[OFF+16]), "+f"(d[OFF+17]), "+f"(d[OFF+18]), "+f"(d[OFF+19]), "+f"(d[OFF+20]), "+f"(d[OFF+21]), "+f"(d[OFF+22]), "+f"(d[OFF+23]), "+f"(d[OFF+24]), "+f"(d[OFF+25]), "+f"(d[OFF+26]), "+f"(d[OFF+27]), "+f"(d[OFF+28]), "+f"(d[OFF+29]), "+f"(d[OFF+30]), "+f"(d[OFF+31]), "+f"(d[OFF+32]), "+f"(d[OFF+33]), "+f"(d[OFF+34]), "+f"(d[OFF+35]), "+f"(d[OFF+36]), "+f"(d[OFF+37]), "+f"(d[OFF+38]), "+f"(d[OFF+39]), "+f"(d[OFF+40]), "+f"(d[OFF+41]), "+f"(d[OFF+42]), "+f"(d[OFF+43]), "+f"(d[OFF+44]), "+f"(d[OFF+45]), "+f"(d[OFF+46]), "+f"(d[OFF+47]), "+f"(d[OFF+48]), "+f"(d[OFF+49]), "+f"(d[OFF+50]), "+f"(d[OFF+51]), "+f"(d[OFF+52]), "+f"(d[OFF+53]), "+f"(d[OFF+54]), "+f"(d[OFF+55]), "+f"(d[OFF+56]), "+f"(d[OFF+57]), "+f"(d[OFF+58]), "+f"(d[OFF+59]), "+f"(d[OFF+60]), "+f"(d[OFF+61]), "+f"(d[OFF+62]), "+f"(d[OFF+63]), "+f"(d[OFF+64]), "+f"(d[OFF+65]), "+f"(d[OFF+66]), "+f"(d[OFF+67]), "+f"(d[OFF+68]), "+f"(d[OFF+69]), "+f"(d[OFF+70]), "+f"(d[OFF+71]), "+f"(d[OFF+72]), "+f"(d[OFF+73]), "+f"(d[OFF+74]), "+f"(d[OFF+75]), "+f"(d[OFF+76]), "+f"(d[OFF+77]), "+f"(d[OFF+78]), "+f"(d[OFF+79]), "+f"(d[OFF+80]), "+f"(d[OFF+81]), "+f"(d[OFF+82]), "+f"(d[OFF+83]), "+f"(d[OFF+84]), "+f"(d[OFF+85]), "+f"(d[OFF+86]), "+f"(d[OFF+87]), "+f"(d[OFF+88]), "+f"(d[OFF+89]), "+f"(d[OFF+90]), "+f"(d[OFF+91]), "+f"(d[OFF+92]), "+f"(d[OFF+93]), "+f"(d[OFF+94]), "+f"(d[OFF+95]), "+f"(d[OFF+96]), "+f"(d[OFF+97]), "+f"(d[OFF+98]), "+f"(d[OFF+99]), "+f"(d[OFF+100]), "+f"(d[OFF+101]), "+f"(d[OFF+102]), "+f"(d[OFF+103]), "+f"(d[OFF+104]), "+f"(d[OFF+105]), "+f"(d[OFF+106]), "+f"(d[OFF+107]), "+f"(d[OFF+108]), "+f"(d[OFF+109]), "+f"(d[OFF+110]), "+f"(d[OFF+111]), "+f"(d[OFF+112]), "+f"(d[OFF+113]), "+f"(d[OFF+114]), "+f"(d[OFF+115]), "+f"(d[OFF+116]), "+f"(d[OFF+117]), "+f"(d[OFF+118]), "+f"(d[OFF+119]), "+f"(d[OFF+120]), "+f"(d[OFF+121]), "+f"(d[OFF+122]), "+f"(d[OFF+123]), "+f"(d[OFF+124]), "+f"(d[OFF+125]), "+f"(d[OFF+126]), "+f"(d[OFF+127])
    : "l"(da), "l"(db), "r"(scale_d), "n"(TB));
}
template<int TB, int OFF, int NT>
__device__ __forceinline__ void wgmma_ss_n32(float (&d)[NT], uint64_t da, uint64_t db, int scale_d) {
  asm volatile("{\n.reg .pred p;\nsetp.ne.b32 p, %18, 0;\n"
    "wgmma.mma_async.sync.aligned.m64n32k16.f32.bf16.bf16 {%0, %1, %2, %3, %4, %5, %6, %7, %8, %9, %10, %11, %12, %13, %14, %15}, %16, %17, p, 1, 1, 0, %19;\n}\n"
    : "+f"(d[OFF+0]), "+f"(d[OFF+1]), "+f"(d[OFF+2]), "+f"(d[OFF+3]), "+f"(d[OFF+4]), "+f"(d[OFF+5]), "+f"(d[OFF+6]), "+f"(d[OFF+7]), "+f"(d[OFF+8]), "+f"(d[OFF+9]), "+f"(d[OFF+10]), "+f"(d[OFF+11]), "+f"(d[OFF+12]), "+f"(d[OFF+13]), "+f"(d[OFF+14]), "+f"(d[OFF+15])
    : "l"(da), "l"(db), "r"(scale_d), "n"(TB));
}
template<int TB, int OFF, int NT>
__device__ __forceinline__ void wgmma_rs_n128(float (&d)[NT], uint32_t a0, uint32_t a1, uint32_t a2, uint32_t a3, uint64_t db, int scale_d) {
  asm volatile("{\n.reg .pred p;\nsetp.ne.b32 p, %69, 0;\n"
    "wgmma.mma_async.sync.aligned.m64n128k16.f32.bf16.bf16 {%0, %1, %2, %3, %4, %5, %6, %7, %8, %9, %10, %11, %12, %13, %14, %15, %16, %17, %18, %19, %20, %21, %22, %23, %24, %25, %26, %27, %28, %29, %30, %31, %32, %33, %34, %35, %36, %37, %38, %39, %40, %41, %42, %43, %44, %45, %46, %47, %48, %49, %50, %51, %52, %53, %54, %55, %56, %57, %58, %59, %60, %61, %62, %63}, {%64, %65, %66, %67}, %68, p, 1, 1, %70;\n}\n"
    : "+f"(d[OFF+0]), "+f"(d[OFF+1]), "+f"(d[OFF+2]), "+f"(d[OFF+3]), "+f"(d[OFF+4]), "+f"(d[OFF+5]), "+f"(d[OFF+6]), "+f"(d[OFF+7]), "+f"(d[OFF+8]), "+f"(d[OFF+9]), "+f"(d[OFF+10]), "+f"(d[OFF+11]), "+f"(d[OFF+12]), "+f"(d[OFF+13]), "+f"(d[OFF+14]), "+f"(d[OFF+15]), "+f"(d[OFF+16]), "+f"(d[OFF+17]), "+f"(d[OFF+18]), "+f"(d[OFF+19]), "+f"(d[OFF+20]), "+f"(d[OFF+21]), "+f"(d[OFF+22]), "+f"(d[OFF+23]), "+f"(d[OFF+24]), "+f"(d[OFF+25]), "+f"(d[OFF+26]), "+f"(d[OFF+27]), "+f"(d[OFF+28]), "+f"(d[OFF+29]), "+f"(d[OFF+30]), "+f"(d[OFF+31]), "+f"(d[OFF+32]), "+f"(d[OFF+33]), "+f"(d[OFF+34]), "+f"(d[OFF+35]), "+f"(d[OFF+36]), "+f"(d[OFF+37]), "+f"(d[OFF+38]), "+f"(d[OFF+39]), "+f"(d[OFF+40]), "+f"(d[OFF+41]), "+f"(d[OFF+42]), "+f"(d[OFF+43]), "+f"(d[OFF+44]), "+f"(d[OFF+45]), "+f"(d[OFF+46]), "+f"(d[OFF+47]), "+f"(d[OFF+48]), "+f"(d[OFF+49]), "+f"(d[OFF+50]), "+f"(d[OFF+51]), "+f"(d[OFF+52]), "+f"(d[OFF+53]), "+f"(d[OFF+54]), "+f"(d[OFF+55]), "+f"(d[OFF+56]), "+f"(d[OFF+57]), "+f"(d[OFF+58]), "+f"(d[OFF+59]), "+f"(d[OFF+60]), "+f"(d[OFF+61]), "+f"(d[OFF+62]), "+f"(d[OFF+63])
    : "r"(a0), "r"(a1), "r"(a2), "r"(a3), "l"(db), "r"(scale_d), "n"(TB));
}
template<int TB, int OFF, int NT>
__device__ __forceinline__ void wgmma_rs_n256(float (&d)[NT], uint32_t a0, uint32_t a1, uint32_t a2, uint32_t a3, uint64_t db, int scale_d) {
  asm volatile("{\n.reg .pred p;\nsetp.ne.b32 p, %133, 0;\n"
    "wgmma.mma_async.sync.aligned.m64n256k16.f32.bf16.bf16 {%0, %1, %2, %3, %4, %5, %6, %7, %8, %9, %10, %11, %12, %13, %14, %15, %16, %17, %18, %19, %20, %21, %22, %23, %24, %25, %26, %27, %28, %29, %30, %31, %32, %33, %34, %35, %36, %37, %38, %39, %40, %41, %42, %43, %44, %45, %46, %47, %48, %49, %50, %51, %52, %53, %54, %55, %56, %57, %58, %59, %60, %61, %62, %63, %64, %65, %66, %67, %68, %69, %70, %71, %72, %73, %74, %75, %76, %77, %78, %79, %80, %81, %82, %83, %84, %85, %86, %87, %88, %89, %90, %91, %92, %93, %94, %95, %96, %97, %98, %99, %100, %101, %102, %103, %104, %105, %106, %107, %108, %109, %110, %111, %112, %113, %114, %115, %116, %117, %118, %119, %120, %121, %122, %123, %124, %125, %126, %127}, {%128, %129, %130, %131}, %132, p, 1, 1, %134;\n}\n"
    : "+f"(d[OFF+0]), "+f"(d[OFF+1]), "+f"(d[OFF+2]), "+f"(d[OFF+3]), "+f"(d[OFF+4]), "+f"(d[OFF+5]), "+f"(d[OFF+6]), "+f"(d[OFF+7]), "+f"(d[OFF+8]), "+f"(d[OFF+9]), "+f"(d[OFF+10]), "+f"(d[OFF+11]), "+f"(d[OFF+12]), "+f"(d[OFF+13]), "+f"(d[OFF+14]), "+f"(d[OFF+15]), "+f"(d[OFF+16]), "+f"(d[OFF+17]), "+f"(d[OFF+18]), "+f"(d[OFF+19]), "+f"(d[OFF+20]), "+f"(d[OFF+21]), "+f"(d[OFF+22]), "+f"(d[OFF+23]), "+f"(d[OFF+24]), "+f"(d[OFF+25]), "+f"(d[OFF+26]), "+f"(d[OFF+27]), "+f"(d[OFF+28]), "+f"(d[OFF+29]), "+f"(d[OFF+30]), "+f"(d[OFF+31]), "+f"(d[OFF+32]), "+f"(d[OFF+33]), "+f"(d[OFF+34]), "+f"(d[OFF+35]), "+f"(d[OFF+36]), "+f"(d[OFF+37]), "+f"(d[OFF+38]), "+f"(d[OFF+39]), "+f"(d[OFF+40]), "+f"(d[OFF+41]), "+f"(d[OFF+42]), "+f"(d[OFF+43]), "+f"(d[OFF+44]), "+f"(d[OFF+45]), "+f"(d[OFF+46]), "+f"(d[OFF+47]), "+f"(d[OFF+48]), "+f"(d[OFF+49]), "+f"(d[OFF+50]), "+f"(d[OFF+51]), "+f"(d[OFF+52]), "+f"(d[OFF+53]), "+f"(d[OFF+54]), "+f"(d[OFF+55]), "+f"(d[OFF+56]), "+f"(d[OFF+57]), "+f"(d[OFF+58]), "+f"(d[OFF+59]), "+f"(d[OFF+60]), "+f"(d[OFF+61]), "+f"(d[OFF+62]), "+f"(d[OFF+63]), "+f"(d[OFF+64]), "+f"(d[OFF+65]), "+f"(d[OFF+66]), "+f"(d[OFF+67]), "+f"(d[OFF+68]), "+f"(d[OFF+69]), "+f"(d[OFF+70]), "+f"(d[OFF+71]), "+f"(d[OFF+72]), "+f"(d[OFF+73]), "+f"(d[OFF+74]), "+f"(d[OFF+75]), "+f"(d[OFF+76]), "+f"(d[OFF+77]), "+f"(d[OFF+78]), "+f"(d[OFF+79]), "+f"(d[OFF+80]), "+f"(d[OFF+81]), "+f"(d[OFF+82]), "+f"(d[OFF+83]), "+f"(d[OFF+84]), "+f"(d[OFF+85]), "+f"(d[OFF+86]), "+f"(d[OFF+87]), "+f"(d[OFF+88]), "+f"(d[OFF+89]), "+f"(d[OFF+90]), "+f"(d[OFF+91]), "+f"(d[OFF+92]), "+f"(d[OFF+93]), "+f"(d[OFF+94]), "+f"(d[OFF+95]), "+f"(d[OFF+96]), "+f"(d[OFF+97]), "+f"(d[OFF+98]), "+f"(d[OFF+99]), "+f"(d[OFF+100]), "+f"(d[OFF+101]), "+f"(d[OFF+102]), "+f"(d[OFF+103]), "+f"(d[OFF+104]), "+f"(d[OFF+105]), "+f"(d[OFF+106]), "+f"(d[OFF+107]), "+f"(d[OFF+108]), "+f"(d[OFF+109]), "+f"(d[OFF+110]), "+f"(d[OFF+111]), "+f"(d[OFF+112]), "+f"(d[OFF+113]), "+f"(d[OFF+114]), "+f"(d[OFF+115]), "+f"(d[OFF+116]), "+f"(d[OFF+117]), "+f"(d[OFF+118]), "+f"(d[OFF+119]), "+f"(d[OFF+120]), "+f"(d[OFF+121]), "+f"(d[OFF+122]), "+f"(d[OFF+123]), "+f"(d[OFF+124]), "+f"(d[OFF+125]), "+f"(d[OFF+126]), "+f"(d[OFF+127])
    : "r"(a0), "r"(a1), "r"(a2), "r"(a3), "l"(db), "r"(scale_d), "n"(TB));
}
template<int TB, int OFF, int NT>
__device__ __forceinline__ void wgmma_rs_n32(float (&d)[NT], uint32_t a0, uint32_t a1, uint32_t a2, uint32_t a3, uint64_t db, int scale_d) {
  asm volatile("{\n.reg .pred p;\nsetp.ne.b32 p, %21, 0;\n"
    "wgmma.mma_async.sync.aligned.m64n32k16.f32.bf16.bf16 {%0, %1, %2, %3, %4, %5, %6, %7, %8, %9, %10, %11, %12, %13, %14, %15}, {%16, %17, %18, %19}, %20, p, 1, 1, %22;\n}\n"
    : "+f"(d[OFF+0]), "+f"(d[OFF+1]), "+f"(d[OFF+2]), "+f"(d[OFF+3]), "+f"(d[OFF+4]), "+f"(d[OFF+5]), "+f"(d[OFF+6]), "+f"(d[OFF+7]), "+f"(d[OFF+8]), "+f"(d[OFF+9]), "+f"(d[OFF+10]), "+f"(d[OFF+11]), "+f"(d[OFF+12]), "+f"(d[OFF+13]), "+f"(d[OFF+14]), "+f"(d[OFF+15])
    : "r"(a0), "r"(a1), "r"(a2), "r"(a3), "l"(db), "r"(scale_d), "n"(TB));
}

__device__ __forceinline__ void wait_flag(const unsigned int* f, uint32_t target) {
  uint32_t v;
#pragma unroll 1
  for (uint32_t spins = 0; spins < (1u << 22); spins++) {
    asm volatile("ld.acquire.gpu.global.u32 %0, [%1];" : "=r"(v) : "l"(f) : "memory");
    if (v >= target) break;
    __nanosleep(100);
  }
}
__device__ __forceinline__ uint32_t ld_and2(const unsigned int* f) {
  uint32_t v;
  asm volatile("{\n.reg .b64 t;\n.reg .b32 a, b;\nld.acquire.gpu.global.b64 t, [%1];\nmov.b64 {a, b}, t;\nand.b32 %0, a, b;\n}" : "=r"(v) : "l"(f) : "memory");
  return v;
}
__device__ __forceinline__ uint32_t lds32(uint32_t a) {
  uint32_t v;
  asm volatile("ld.shared.u32 %0, [%1];" : "=r"(v) : "r"(a) : "memory");
  return v;
}
__device__ __forceinline__ float gate_row(int row, int lane, const bf16* __restrict__ x, const bf16* __restrict__ gate_w) {
  const uint32_t* xr = reinterpret_cast<const uint32_t*>(x + (size_t)row * DM);
  const uint32_t* gw2 = reinterpret_cast<const uint32_t*>(gate_w);
  float gs = 0.f;
#pragma unroll
  for (int i = 0; i < 9; i++) {
    const uint32_t a = __ldg(xr + lane + 32 * i), b = __ldg(gw2 + lane + 32 * i);
    gs = fmaf(bf_lo(a), bf_lo(b), gs);
    gs = fmaf(bf_hi(a), bf_hi(b), gs);
  }
#pragma unroll
  for (int o = 16; o; o >>= 1) gs += __shfl_xor_sync(0xffffffffu, gs, o);
  const float g = 1.f / (1.f + __expf(-gs));
  if (lane == 0) g_gate[row] = g;
  return g;
}
constexpr uint32_t LQ = 36864, LV = 55296;
__device__ __forceinline__ void mma16(float (&c)[4], uint32_t a0, uint32_t a1, uint32_t a2, uint32_t a3, uint32_t b0, uint32_t b1) {
  asm("mma.sync.aligned.m16n8k16.row.col.f32.bf16.bf16.f32 {%0, %1, %2, %3}, {%4, %5, %6, %7}, {%8, %9}, {%0, %1, %2, %3};"
      : "+f"(c[0]), "+f"(c[1]), "+f"(c[2]), "+f"(c[3]) : "r"(a0), "r"(a1), "r"(a2), "r"(a3), "r"(b0), "r"(b1));
}
__device__ __forceinline__ void mma8(float (&c)[4], uint32_t a0, uint32_t a1, uint32_t b0) {
  asm("mma.sync.aligned.m16n8k8.row.col.f32.bf16.bf16.f32 {%0, %1, %2, %3}, {%4, %5}, {%6}, {%0, %1, %2, %3};"
      : "+f"(c[0]), "+f"(c[1]), "+f"(c[2]), "+f"(c[3]) : "r"(a0), "r"(a1), "r"(b0));
}
template <typename F>
__device__ __forceinline__ void local_attn(int lr0, int warp_g, uint32_t sL, uint32_t bL, uint32_t bL2, int lane, float g0, float g1, F st) {
  const float scale_l2 = 0.23570226039551584f * 1.4426950408889634f;
  const int g = lane >> 2, t = lane & 3;
  const bool lo0 = 2 * t > g, lo1 = 2 * t + 1 > g;
  const bool ok0 = lr0 > 0 || !lo0, ok1 = lr0 > 0 || !lo1;
  const uint32_t mlo = (lo0 ? 0xFFFFu : 0u) | (lo1 ? 0xFFFF0000u : 0u);
  uint32_t ad[9], k[9][4], qf[9][2], pe[4], po[4];
#pragma unroll
  for (int c = 0; c < 9; c++) {
    const uint32_t ch = warp_g * 9 + c;
    ad[c] = sL + (lane >> 4) * 18432 + (lane & 15) * 128 + ((ch >> 3) << 11) + (((ch ^ lane) & 7) << 4);
  }
  st(0, 0u); st(1, 0u);
  mbar_wait(bL, 0);
  if (warp_g == 0) TS(1, 6);
#pragma unroll
  for (int c = 0; c < 9; c++) {
    asm volatile("ldmatrix.sync.aligned.m8n8.x2.shared.b16 {%0, %1}, [%2];" : "=r"(qf[c][0]), "=r"(qf[c][1]) : "r"(ad[c] + LQ) : "memory");
    ldsm_x4(k[c][0], k[c][1], k[c][2], k[c][3], ad[c]);
  }
  st(2, k[0][0]); st(3, k[8][0]);
#pragma unroll
  for (int i = 0; i < 4; i++) {
    const uint32_t q0 = (t >= i) ? qf[2 * i][0] : 0u, q1 = (t >= i) ? qf[2 * i][1] : 0u;
    const uint32_t q4 = (t <= i) ? qf[2 * i + 2][0] : 0u, q5 = (t <= i) ? qf[2 * i + 2][1] : 0u;
    float c[4][4];
#pragma unroll
    for (int T = 0; T < 4; T++) {
#pragma unroll
      for (int j = 0; j < 4; j++) c[T][j] = 0.f;
      mma16(c[T], q0, q1, qf[2 * i + 1][0], qf[2 * i + 1][1], k[2 * i][T], k[2 * i + 1][T]);
      mma8(c[T], q4, q5, k[2 * i + 2][T]);
    }
    const float e0 = ok0 ? (lo0 ? c[0][0] : c[1][0]) : -INFINITY, e1 = ok1 ? (lo1 ? c[0][1] : c[1][1]) : -INFINITY;
    const float o0 = ok0 ? (lo0 ? c[2][2] : c[3][2]) : -INFINITY, o1 = ok1 ? (lo1 ? c[2][3] : c[3][3]) : -INFINITY;
    float me = fmaxf(e0, e1), mo = fmaxf(o0, o1);
    me = fmaxf(me, __shfl_xor_sync(0xffffffffu, me, 1));
    mo = fmaxf(mo, __shfl_xor_sync(0xffffffffu, mo, 1));
    me = fmaxf(me, __shfl_xor_sync(0xffffffffu, me, 2)) * scale_l2;
    mo = fmaxf(mo, __shfl_xor_sync(0xffffffffu, mo, 2)) * scale_l2;
    const float w0 = ex2(fmaf(e0, scale_l2, -me)), w1 = ex2(fmaf(e1, scale_l2, -me));
    const float w2 = ex2(fmaf(o0, scale_l2, -mo)), w3 = ex2(fmaf(o1, scale_l2, -mo));
    float se = w0 + w1, so = w2 + w3;
    st(4 + 2 * i, __float_as_uint(i == 1 ? me : i == 2 ? se : e0));
    se += __shfl_xor_sync(0xffffffffu, se, 1);
    so += __shfl_xor_sync(0xffffffffu, so, 1);
    se += __shfl_xor_sync(0xffffffffu, se, 2);
    so += __shfl_xor_sync(0xffffffffu, so, 2);
    asm("rcp.approx.ftz.f32 %0, %0;" : "+f"(se));
    asm("rcp.approx.ftz.f32 %0, %0;" : "+f"(so));
    se *= g0;
    so *= g1;
    pe[i] = pack_bf16(w0 * se, w1 * se);
    po[i] = pack_bf16(w2 * so, w3 * so);
    st(5 + 2 * i, i == 0 ? __float_as_uint(w0) : i == 2 ? __float_as_uint(mo) : po[i]);
  }
  if (warp_g == 0) TS(0, 4);
  mbar_wait(bL2, 0);
  if (warp_g == 0) TS(0, 5);
#pragma unroll
  for (int c = 0; c < 9; c++)
    asm volatile("ldmatrix.sync.aligned.m8n8.x4.trans.shared.b16 {%0, %1, %2, %3}, [%4];"
                 : "=r"(k[c][0]), "=r"(k[c][1]), "=r"(k[c][2]), "=r"(k[c][3]) : "r"(ad[c] + LV) : "memory");
#pragma unroll
  for (int i = 0; i < 4; i++) {
#pragma unroll
    for (int n = 0; n < 3; n++) {
      float c[4] = {0.f, 0.f, 0.f, 0.f};
      mma16(c, pe[i] & mlo, 0u, pe[i] & ~mlo, 0u, k[2 * i + n][0], k[2 * i + n][1]);
      mma16(c, 0u, po[i] & mlo, 0u, po[i] & ~mlo, k[2 * i + n][2], k[2 * i + n][3]);
      const uint32_t r0 = pack_bf16(c[0], c[1]), r1 = pack_bf16(c[2], c[3]);
      const bool keep = (n == 0) && (i > 0) && (t < i);
      qf[2 * i + n][0] = keep ? qf[2 * i + n][0] : r0;
      qf[2 * i + n][1] = keep ? qf[2 * i + n][1] : r1;
    }
    st(12 + i, qf[2 * i + 1][0]);
  }
#pragma unroll
  for (int c = 0; c < 9; c++)
    asm volatile("stmatrix.sync.aligned.m8n8.x2.shared.b16 [%0], {%1, %2};" ::"r"(ad[c] + LQ), "r"(qf[c][0]), "r"(qf[c][1]) : "memory");
  asm volatile("fence.proxy.async.shared::cta;" ::: "memory");
}
__device__ __forceinline__ void tma4d(uint32_t dst, const CUtensorMap* m, uint32_t bar, int c1, int c2, int c3) {
  asm volatile("cp.async.bulk.tensor.4d.shared::cluster.global.mbarrier::complete_tx::bytes [%0], [%1, {%3, %4, %5, %6}], [%2];" ::"r"(dst),
               "l"(m), "r"(bar), "r"(0), "r"(c1), "r"(c2), "r"(c3) : "memory");
}

#define ST_NUM 1
#define ST_DEN 2
#define K1_NST 6
constexpr int K1_BST = K1_NST;
#define MAXJ 11
constexpr int K1_MAXJOBS = MAXJ;
constexpr uint32_t K1_FLAG_TARGET = 7;
constexpr uint32_t RDY_TARGET = 48;
constexpr uint32_t GATE_TARGET = 128 * 3;
struct alignas(64) Params {
  CUtensorMap tmA[2];
  CUtensorMap tmW[4];
  uint16_t jobs[NCLUSTER][K1_MAXJOBS + 1];
  CUtensorMap tmK, tmV, tmQ;
  CUtensorMap tmL[3];
  CUtensorMap tmC, tmO[2], tmOt[2];
  CUtensorMap tmR[2];
  uint8_t order[256];
  uint8_t unit[66][4];
};

struct K1State {
  uint32_t bs, bph, aph;
  bf16 *pp, *pp8;
  int png;
  int tn;
  int wsel;
  uint32_t fo;
};
__device__ __forceinline__ void k1_flag(const K1State& st, int lane, uint32_t bS) {
  if (st.png) {
    __syncwarp();
    if (lane == 0) mbar_arrive(bS + st.fo);
  }
}

__device__ __forceinline__ void scale_q4(uint32_t* v) {
#pragma unroll
  for (int i = 0; i < 4; i++)
    asm volatile("{\n.reg .b32 t;\nmul.rn.bf16x2 t, %0, %2;\nfma.rn.bf16x2 %0, %0, %1, t;\n}" : "+r"(v[i]) : "r"(0x3E033E03u), "r"(0xB9D8B9D8u));
}
__device__ __forceinline__ void k1_first(const K1State& st, uint32_t job, uint32_t bAf, uint32_t bBf) {
  if (job & 3) {
    if ((job >> 14) & 1) mbar_wait(bAf, st.aph);
    mbar_wait(bBf + st.bs * 8, st.bph);
  }
}
__device__ __forceinline__ void k1_tile(float (&acc)[128], uint32_t (&pk)[64], K1State& st, uint32_t job, uint32_t njob, uint32_t sA, uint32_t sB,
                                        uint32_t bAf, uint32_t bAe, uint32_t bBf, uint32_t bBe, uint32_t bS, int wg, int warp, int lane, uint32_t rank) {
  const int a_sel = (job >> 2) & 1, mpair = (job >> 3) & 7, w_sel = (job >> 6) & 3, chunk0 = (job >> 8) & 63;
  const bool newA = (job >> 14) & 1, lastA = (job >> 15) & 1;
  const bool sig = (lane == 0) && (warp < 2);
  const bool siga = lastA && (lane == 0) && (warp == 2);
  const int KC = 8 + a_sel;
  uint32_t prev_bs = 0, a8_bs = 0;
#pragma unroll
  for (int kc = 0; kc < 9; kc++) {
    if (kc >= KC) break;
    uint32_t abase = sA + ((kc + 2) & 7) * 16384;
    if (kc == 8) {
      mbar_wait(bBf + st.bs * 8, st.bph);
      a8_bs = st.bs;
      abase = sB + st.bs * 16384;
      if (++st.bs == K1_BST) { st.bs = 0; st.bph ^= 1; }
    } else if (newA && kc > 0) {
      mbar_wait(bAf + kc * 8, st.aph);
    }
    const uint64_t da = make_desc(abase + wg * 8192, 16, 1024, 1);
#pragma unroll
    for (int ks = 0; ks < 2; ks++) {
      if (ks > 0 || kc > 0) mbar_wait(bBf + st.bs * 8, st.bph);
      const uint64_t db = make_desc(sB + st.bs * 16384, 2048, 1024, 1);
      wg_fence();
      wgmma_ss_n256<1, 0>(acc, da + (uint64_t)(ks * 4), db, (ks > 0) ? 1 : (kc > 0));
      wgmma_ss_n256<1, 0>(acc, da + (uint64_t)(ks * 4 + 2), db + (uint64_t)512, 1);
      wg_commit();
      wg_wait<1>();
      if (ks > 0 || kc > 0) {
        if (sig) mbar_arrive_cluster(bBe + prev_bs * 8, warp);
        if (ks == 0 && siga) mbar_arrive(bAe + (kc - 1) * 8);
      }
      if (st.wsel == 2) {
        const int i = (kc & 7) * 2 + ks;
        if (kc < st.png) {
          quad_transpose(pk[i * 4], pk[i * 4 + 1], pk[i * 4 + 2], pk[i * 4 + 3], lane & 3);
          st_v4a((ks ? st.pp8 : st.pp) + kc * 32, pk[i * 4], pk[i * 4 + 1], pk[i * 4 + 2], pk[i * 4 + 3]);
        }
        if (i == 15) k1_flag(st, lane, bS);
      } else if (st.png) {
#pragma unroll
        for (int i = 0; i < 16; i++) {
          if (i * ST_NUM / ST_DEN != kc * 2 + ks) continue;
          if (st.wsel == 3) scale_q4(pk + i * 4);
          st_v4a(((i & 1) ? st.pp8 : st.pp) + (i / 2) * 32, pk[i * 4], pk[i * 4 + 1], pk[i * 4 + 2], pk[i * 4 + 3]);
          if (i == 15) k1_flag(st, lane, bS);
        }
      }
      prev_bs = st.bs;
      if (++st.bs == K1_BST) { st.bs = 0; st.bph ^= 1; }
    }
  }
  if (newA) st.aph ^= 1;
  const bool isA = (w_sel == 2);
  bf16* out = (w_sel == 0) ? g_K : (w_sel == 1) ? g_V : isA ? g_QKVA : g_ctx;
  const int ld = isA ? NQKVA : (w_sel == 3) ? KCAT : HDIM;
  const int row = mpair * 256 + rank * 128 + wg * 64 + warp * 16 + (lane >> 2);
  st.pp = ptr_add(out, (row * ld + chunk0 * 64 + (lane & 3) * 8) * 2);
  st.pp8 = ptr_add(st.pp, 16 * ld);
  st.png = ((job & 3) + 1) * 2;
  st.wsel = w_sel;
  st.fo = (st.fo + 8) & 24;
  k1_first(st, njob, bAf, bBf);
  wg_wait<0>();
  fence_regs(acc);
  mbar_arrive_cluster_if(bBe + prev_bs * 8, warp & 1, sig);
  mbar_arrive_cluster_if(bBe + a8_bs * 8, warp & 1, sig && a_sel);
  mbar_arrive_if(bAe + 7 * 8, siga && !a_sel);
#pragma unroll
  for (int i = 0; i < 64; i++) {
    const int j = (i >> 3) * 16 + (i & 3) * 4 + ((i >> 2) & 1) * 2;
    pk[i] = pack_bf16(acc[j], acc[j + 1]);
  }
}

constexpr int K2_NST = 7;
constexpr uint32_t K2_END = 0x100;
#define PFD 4
#define PF3A 2
#define PF3 6
#define KC0 1
constexpr uint32_t CR = 4;
#define FIRST_DRAW 3
#define PWAIT mbar_wait_ns<1000>
#define PVM 0x8A
#define W0 63
#define SPEC_HI 1.8446744073709552e19f
#define SPEC_LO 5.421010862427522e-20f
constexpr int K3_NST = 4;
#define K3_NS 6
__device__ __forceinline__ uint32_t k3_rot(uint32_t sv) { return (0x00E9u >> (2 * sv)) & 3; }
constexpr int K3_STAGE = 16384 + 32768 + 4096;
constexpr int SMEM_DATA = 7 * 32768;
constexpr int SMEM_BYTES = SMEM_DATA + 1024 + 896;

struct Cursor {
  uint32_t s, ph;
  __device__ __forceinline__ void next() {
    if (++s == K2_NST) { s = 0; ph ^= 1; }
  }
};

#define TURN_SYNC() bar_sync(mybar, 256)
#define TURN_ARRIVE() bar_arrive(otherbar, 256)
#define RELEASE_IF(cur, cond) mbar_arrive_cluster_if(bE + (cur).s * 8, warp & 1, sig && (cond))
#define RELEASE(cur) RELEASE_IF(cur, true)
#define ISSUE_PV(cur, first)                                                                                   \
  do {                                                                                                         \
    const uint64_t dv = make_desc(sbase + (cur).s * 32768, 16384, 1024, 1);                                    \
    _Pragma("unroll") for (int t = 0; t < 8; t++)                                                              \
        wgmma_rs_n128<1, 0>(O, P[4 * t], P[4 * t + 1], P[4 * t + 2], P[4 * t + 3], dv + (uint64_t)(t * 128), (t > 0) ? 1 : !(first)); \
  } while (0)
#define ISSUE_QK(cur)                                                                                          \
  do {                                                                                                         \
    const uint64_t dk = make_desc(sbase + (cur).s * 32768, 16, 1024, 1);                                       \
    _Pragma("unroll") for (int t = 0; t < 8; t++)                                                              \
        wgmma_rs_n128<0, 0>(S, Q[4 * t], Q[4 * t + 1], Q[4 * t + 2], Q[4 * t + 3], dk + (uint64_t)((t >> 2) * 1024 + (t & 3) * 2), t > 0); \
  } while (0)
#define LOAD_Q()                                                                                               \
  do {                                                                                                         \
    item = lds32(sItem + (it & 7) * 4);                                                                        \
    const uint32_t qa = sbase + cq.s * 32768 + (wg * 64 + warp * 16 + (lane & 15)) * 128;                      \
    _Pragma("unroll") for (int t = 0; t < 8; t++)                                                              \
        ldsm_x4(Q[4 * t], Q[4 * t + 1], Q[4 * t + 2], Q[4 * t + 3], qa + (t >> 2) * 16384 + ((((t & 3) * 2 + (lane >> 4)) ^ (lane & 7)) << 4)); \
  } while (0)
#define NEW_ITEM()                                                                                             \
  do {                                                                                                         \
    const int row = (2 * (item & 7) + hi) * 128 + (rank ^ hi) * 64 + warp * 16 + (lane >> 2);                  \
    eoff = (row * KCAT + (item >> 3) * 128 + q * 8) * 2;                                                       \
    const float* gp = ptr_add(g_gate, row * 4);                                                                \
    asm volatile("ld.global.f32 %0, [%1];" : "=f"(gf0) : "l"(gp));                                             \
    asm volatile("ld.global.f32 %0, [%1];" : "=f"(gf1) : "l"(gp + 8));                                         \
    if (!hi) {                                                                                                 \
      mbar_wait2(bF + cs0.s * 8, cs0.ph, bF + cs1.s * 8, cs1.ph);                                              \
      RELEASE(cs0);                                                                                            \
      RELEASE(cs1);                                                                                            \
    }                                                                                                          \
  } while (0)
#define EXPB(T)                                                                                                \
  do {                                                                                                         \
    _Pragma("unroll") for (int i = 4 * T; i < 4 * T + 4; i++) asm volatile("" : "+r"(P[i])::"memory");        \
    _Pragma("unroll") for (int jj = 2 * T; jj < 2 * T + 2; jj++) {                                             \
      const float e0 = ex2(S[jj * 4 + 0]), e1 = ex2(S[jj * 4 + 1]), e2 = ex2(S[jj * 4 + 2]), e3 = ex2(S[jj * 4 + 3]); \
      s0 += e0 + e1;                                                                                           \
      s1 += e2 + e3;                                                                                           \
      P[jj * 2 + 0] = pack_bf16(e0, e1);                                                                       \
      P[jj * 2 + 1] = pack_bf16(e2, e3);                                                                       \
    }                                                                                                          \
  } while (0)
#define EXPC(T)                                                                                                \
  do {                                                                                                         \
    if (T > 0 && ((PVM >> (T - 1)) & 1)) {                                                                     \
      anchor((T & 2) ? s0 : s1, never);                                                                        \
      wg_wait<__builtin_popcount(PVM >> T) - 1>();                                                             \
      if ((PVM >> T) == (128 >> T)) { fence_regs(O); RELEASE(cv); }                                            \
    }                                                                                                          \
    EXPB(T);                                                                                                   \
  } while (0)
#define MASK(G, g)                                                                                             \
  do {                                                                                                         \
    if ((g) * 8 > d) S[(G) * 4 + 0] = -INFINITY;                                                               \
    if ((g) * 8 + 1 > d) S[(G) * 4 + 1] = -INFINITY;                                                           \
    if ((g) * 8 - 8 > d) S[(G) * 4 + 2] = -INFINITY;                                                           \
    if ((g) * 8 - 7 > d) S[(G) * 4 + 3] = -INFINITY;                                                           \
  } while (0)
#define STORE_O(G)                                                                                             \
  do {                                                                                                         \
    st_v4(optr + (G) * 32, pack_bf16(O[(G) * 16 + 0] * f0, O[(G) * 16 + 1] * f0), pack_bf16(O[(G) * 16 + 4] * f0, O[(G) * 16 + 5] * f0), \
          pack_bf16(O[(G) * 16 + 8] * f0, O[(G) * 16 + 9] * f0), pack_bf16(O[(G) * 16 + 12] * f0, O[(G) * 16 + 13] * f0)); \
    st_v4(optr + 8 * KCAT + (G) * 32, pack_bf16(O[(G) * 16 + 2] * f1, O[(G) * 16 + 3] * f1), pack_bf16(O[(G) * 16 + 6] * f1, O[(G) * 16 + 7] * f1), \
          pack_bf16(O[(G) * 16 + 10] * f1, O[(G) * 16 + 11] * f1), pack_bf16(O[(G) * 16 + 14] * f1, O[(G) * 16 + 15] * f1)); \
  } while (0)

#define FLUSH()                                                                                                \
  do {                                                                                                         \
    _Pragma("unroll") for (int G = 0; G < 8; G++) {                                                            \
      st_v4a(st.pp + G * 32, pk[G * 8], pk[G * 8 + 1], pk[G * 8 + 2], pk[G * 8 + 3]);                          \
      st_v4a(st.pp8 + G * 32, pk[G * 8 + 4], pk[G * 8 + 5], pk[G * 8 + 6], pk[G * 8 + 7]);                     \
    }                                                                                                          \
    k1_flag(st, lane, bS);                                                                                     \
  } while (0)

__global__ void __cluster_dims__(2, 1, 1) __launch_bounds__(384, 1)
fused_kernel(const __grid_constant__ Params p, const bf16* __restrict__ x, const bf16* __restrict__ gate_w, bf16* __restrict__ out) {
  extern __shared__ uint8_t smem_raw[];
  const uint32_t sbase = (smem_u32(smem_raw) + 1023) & ~1023u;
  const uint32_t sB = sbase, sA = sbase + K1_BST * 16384, sBar = sbase + SMEM_DATA;
  const uint32_t bAf = sBar, bAe = sBar + 64, bBf = sBar + 128, bBe = sBar + 176, bL = sBar + 224, bS = sBar + 656, bL2 = sBar + 240, sL = sA + 32768;
  const uint32_t bF = sBar + 256, bE = sBar + 320, bT = sBar + 384, sTick = sBar + 400, sItem = sBar + 416, bS2 = sBar + 688, bR = sBar + 456, bLast = sBar + 464, bH = sBar + 472, bT0 = sBar + 480, bZ = sBar + 488, bLd = sBar + 496;
  const uint32_t b3F = sBar + 512, b3E = sBar + 544, sGate = sBar + 576, sK1 = sBar + 720, sClm = sBar + 768;
  const int tid = threadIdx.x, warp_g = __shfl_sync(0xffffffffu, tid >> 5, 0), lane = tid & 31;
  const uint32_t rank = cluster_rank();
  const int cl = blockIdx.x >> 1;
  TSM(0);
  if (tid == 256) {
    const uint32_t job = p.jobs[cl][0];
#pragma unroll
    for (int i = 0; i < KC0; i++) { mbar_init(bAf + i * 8, 1); mbar_init(bBf + i * 16, 1); mbar_init(bBf + i * 16 + 8, 1); }
    asm volatile("fence.mbarrier_init.release.cluster;" ::: "memory");
#pragma unroll 1
    for (int i = 0; i < 4 * KC0; i++) {
      if (!(i & 3)) {
        mbar_expect(bAf + i * 2, 16384);
        tma2d(sA + (i / 4 + 2) * 16384, &p.tmA[(job >> 2) & 1], bAf + i * 2, i * 16, ((job >> 3) & 7) * 256 + rank * 128);
      }
      if (!(i & 1)) mbar_expect(bBf + i * 4, 16384);
      tma3d(sB + i * 8192, &p.tmW[(job >> 6) & 3], bBf + (i >> 1) * 8, 0, i * 16, (job >> 8) & 63);
    }
  }
  if (warp_g == 1) asm volatile("st.shared.u32 [%0], %1;" ::"r"(lane ? sClm - 4 + lane * 4 : sK1), "r"(lane ? 0xFFFFFFFFu : 80u) : "memory");
  if (tid == 0) {
    for (int i = 0; i < 8; i++) { if (i >= KC0) mbar_init(bAf + i * 8, 1); mbar_init(bAe + i * 8, 2); }
    for (int i = 0; i < K1_BST; i++) { if (i >= 2 * KC0) mbar_init(bBf + i * 8, 1); mbar_init(bBe + i * 8, 4); }
    mbar_init(bL, 1);
    mbar_init(bL2, 1);
    mbar_init(bR, 1);
    mbar_init(bLast, 1);
    mbar_init(bH, 4);
    mbar_init(bT0, 1);
    mbar_init(bZ, 1);
    mbar_init(bLd, 4);
    for (int i = 0; i < 8; i++) mbar_init(bS + i * 8, 8);
    for (int i = 0; i < K2_NST; i++) { mbar_init(bF + i * 8, 1); mbar_init(bE + i * 8, 4); }
    mbar_init(bT, 1); mbar_init(bT + 8, 1);
    for (int i = 0; i < K3_NST; i++) { mbar_init(b3F + i * 8, 1); mbar_init(b3E + i * 8, 4); }
    asm volatile("fence.mbarrier_init.release.cluster;" ::: "memory");
  }
  __syncwarp();
  if (warp_g != 8) cluster_sync();
  const int lr0 = blockIdx.x * 16;

  if (warp_g >= 8) {
    reg_dealloc<40>();
    if (warp_g == 8) {
      {
        __syncwarp();
        cluster_sync();
      }
      if (elect_one()) {
        uint32_t bs = (2 * KC0) % K1_BST, bph = (2 * KC0 < K1_BST), aph = 1;
#pragma unroll 1
        for (int ji = 0; ji < K1_MAXJOBS; ji++) {
          const uint32_t job = p.jobs[cl][ji];
          if (!(job & 3)) break;
          const int a_sel = (job >> 2) & 1, mpair = (job >> 3) & 7, chunk0 = (job >> 8) & 63;
          const bool newA = (job >> 14) & 1;
          const int KC = a_sel ? 9 : 8;
          const uint32_t halfbytes = 8192;
          const bool lastjob = (ji + 1 == K1_MAXJOBS) || !(p.jobs[cl][ji + 1] & 3);
          const CUtensorMap* tw = &p.tmW[(job >> 6) & 3];
          {
            const uint32_t njob = (ji + 1 < K1_MAXJOBS) ? p.jobs[cl][ji + 1] : 0;
            if (!(njob & 3) && !newA) mbar_arrive(bLast);
          }
#pragma unroll 1
          for (int kc = ji ? 0 : KC0; kc < KC; kc++) {
            {
              const bool nx = kc + PFD >= KC;
              const uint32_t njob = nx ? p.jobs[cl][ji + 1] : job;
              const int pk = nx ? kc + PFD - KC : kc + PFD;
              if ((njob & 3) && (nx || ji > 0)) {
                if (cl >= 64 || ((pk ^ (cl >> 1)) & 3) == 0)
                  tma_pf3d(&p.tmW[(njob >> 6) & 3], 0, pk * 64 + (cl & 1) * 32 + rank * 16, (njob >> 8) & 63);
                if (((njob >> 14) & 1) || pk == 8) tma_pf2d(&p.tmA[(njob >> 2) & 1], pk * 64, ((njob >> 3) & 7) * 256 + rank * 128);
              }
            }
            if (kc == 8) {
              PWAIT(bBe + bs * 8, bph);
              mbar_expect(bBf + bs * 8, 16384);
              tma2d(sB + bs * 16384, &p.tmA[1], bBf + bs * 8, 512, mpair * 256 + rank * 128);
              if (++bs == K1_BST) { bs = 0; bph ^= 1; }
            } else if (newA) {
              PWAIT(bAe + kc * 8, aph);
              mbar_expect(bAf + kc * 8, 16384);
              tma2d(sA + ((kc + 2) & 7) * 16384, &p.tmA[a_sel], bAf + kc * 8, kc * 64, mpair * 256 + rank * 128);
              if (kc == 7 && lastjob) mbar_arrive(bLast);
            }
#pragma unroll 1
            for (int kk = 0; kk < 2; kk++) {
              PWAIT(bBe + bs * 8, bph);
              mbar_expect(bBf + bs * 8, 2 * halfbytes);
              tma3d_mc(sB + bs * 16384 + rank * halfbytes, tw, bBf + bs * 8, 0, kc * 64 + kk * 32 + rank * 16, chunk0, 3);
              if (++bs == K1_BST) { bs = 0; bph ^= 1; }
            }
          }
          if (newA) aph ^= 1;
        }
        Cursor c{0, 0};
        int pcol = 0;
        PWAIT(bR, 0);
        uint32_t tick = lds32(sTick + 8), seen = 1u << (p.order[tick] >> 4);
        asm volatile("fence.proxy.async.global;" ::: "memory");
#pragma unroll 1
        for (int it = 0;; it++) {
          const uint32_t item = (tick < 256) ? p.order[tick] : (K2_END | min(tick - 256, 255u));
          asm volatile("st.shared.u32 [%0], %1;" ::"r"(sItem + (it & 7) * 4), "r"(item) : "memory");
          if (item >= K2_END) break;
          const int h = item >> 3, j = item & 7;
          const int col = h * 128 + rank * 64;
          const int nb = 2 * j + 2;
          if (!((seen >> (h >> 1)) & 1)) {
            wait_flag(&g_sync[F_HP + (h >> 1)], RDY_TARGET);
            asm volatile("fence.proxy.async.global;" ::: "memory");
            seen |= 1u << (h >> 1);
          }
          PWAIT(bE + c.s * 8, c.ph);
          mbar_expect(bF + c.s * 8, 32768);
#pragma unroll 1
          for (int i = 0; i < 4; i++) {
            const int hi = (i ^ it ^ 1) & 1;
            tma2d(sbase + c.s * 32768 + i * 8192, &p.tmQ, bF + c.s * 8, h * 128 + (i >> 1) * 64, (2 * j + hi) * 128 + (rank ^ hi) * 64);
          }
          c.next();
          if (tick >= 256 - 73) {
            const int kk = tick - (256 - 73), sel = (kk < 9), kr = (sel ? kk : kk - 9) * 64 + rank * 32;
#pragma unroll 1
            for (int i = 0; i < 2; i++) {
              tma_pf3d(&p.tmO[sel], 0, kr, i * 4);
              tma_pf2d(&p.tmOt[sel], 512 + i * 32, kr);
            }
          }
#pragma unroll 1
          for (int n = nb - 1; n >= 0; n--) {
            if (n == 0 && rank == 0) tick = atomicAdd(&g_sync[F_TICK], 1u);
            PWAIT(bE + c.s * 8, c.ph);
            mbar_expect(bF + c.s * 8, 32768);
            tma2d_mc(sbase + c.s * 32768 + rank * 16384, &p.tmK, bF + c.s * 8, col, n * 128, 3);
            c.next();
            if (n < nb - 1 || it > 0) {
              PWAIT(bE + c.s * 8, c.ph);
              mbar_expect(bF + c.s * 8, 32768);
              tma2d_mc(sbase + c.s * 32768 + rank * 16384, &p.tmV, bF + c.s * 8, (n < nb - 1) ? col : pcol, (n < nb - 1) ? (n + 1) * 128 : 0, 3);
              c.next();
            }
          }
          pcol = col;
          if (rank == 0) {
            asm volatile(
                "{\n.reg .b32 a, b;\nmapa.shared::cluster.u32 a, %0, 1;\nmapa.shared::cluster.u32 b, %1, 1;\n"
                "st.async.shared::cluster.mbarrier::complete_tx::bytes.u32 [a], %2, [b];\n}" ::"r"(sTick + (it & 1) * 4),
                "r"(bT + (it & 1) * 8), "r"(tick) : "memory");
          } else {
            mbar_expect(bT + (it & 1) * 8, 4);
            PWAIT(bT + (it & 1) * 8, (it >> 1) & 1);
            tick = lds32(sTick + (it & 1) * 4);
          }
        }
        PWAIT(bE + c.s * 8, c.ph);
        mbar_expect(bF + c.s * 8, 32768);
        tma2d_mc(sbase + c.s * 32768 + rank * 16384, &p.tmV, bF + c.s * 8, pcol, 0, 3);
        const uint32_t unit = tick - 256;
        const int mblk = (7 - (p.unit[unit][0] >> 1)) * 2 + rank, nhalf = p.unit[unit][0] & 1;
        uint32_t have, hoa;
        have = ld_and2(&g_sync[F_CTX + (mblk & ~1)]);
        asm volatile("ld.acquire.gpu.global.u32 %0, [%1];" : "=r"(hoa) : "l"(&g_sync[F_OA + mblk]) : "memory");
        asm volatile("fence.proxy.async.global;" ::: "memory");
#pragma unroll 1
        for (uint32_t idx = PF3A; idx < PF3; idx++) {
          const int kk = p.unit[unit][2] + idx;
          if ((kk < 9) ? (hoa >= 8) : ((have >> ((kk - 9) >> 1)) & 1)) tma_pf2d(&p.tmC, ((kk < 9) ? 64 + kk : kk - 9) * 64, mblk * 128);
        }
        {
          const uint32_t rot = k3_rot(c.s), nfree = ((0x1Au >> c.s) & 1) ? 2 : 3;
          uint32_t kq = p.unit[unit][2] * 0x01010101u + 0x03020100u, k1 = 80, idx = 0, pa = 0, pb = 0;
          auto step = [&](uint32_t& pend) {
            uint32_t nxt = (kq & 255) + CR;
            if (idx + CR >= K3_NS && k1 == 80) {
              if (rank == 0) {
                nxt = min(pend + p.unit[unit][3], 73u);
                asm volatile("{\n.reg .b32 a;\nmapa.shared::cluster.u32 a, %0, 1;\nst.volatile.shared::cluster.u8 [a], %1;\n}" ::"r"(sClm + idx), "r"(nxt) : "memory");
              } else {
#pragma unroll 1
                for (uint32_t spins = 0; spins < (1u << 22); spins++) {
                  asm volatile("ld.volatile.shared.u8 %0, [%1];" : "=r"(nxt) : "r"(sClm + idx) : "memory");
                  if (nxt != 255) break;
                  __nanosleep(20);
                }
              }
              if (nxt >= 73) {
                k1 = idx + CR;
                asm volatile("st.shared.u32 [%0], %1;" ::"r"(sK1), "r"(k1) : "memory");
              }
            }
            const uint32_t kk = kq & 255;
            if (idx < 12) TP(idx);
            kq = (kq >> 8) | (nxt << (8 * CR - 8));
            const uint32_t s = (rot + idx) & 3;
            if (idx >= nfree) PWAIT((idx < 4) ? bH : b3E + s * 8, (idx < 4) ? 0 : (~idx >> 2) & 1);
#pragma unroll 1
            while (idx < nfree && c.s != ((0x6431u >> (4 * s)) & 15)) {
              c.next();
              PWAIT(bE + c.s * 8, c.ph);
            }
            if (idx < 12) TP(12 + idx);
            mbar_expect(b3F + s * 8, K3_STAGE);
            const uint32_t st = sbase + s * K3_STAGE;
            const int sel = (kk < 9), k = sel ? kk : kk - 9, kr = k * 64 + rank * 32;
            tma3d_mc(st + 16384 + rank * 16384, &p.tmO[sel], b3F + s * 8, 0, kr, nhalf * 4, 3);
            tma2d_mc(st + 49152 + rank * 2048, &p.tmOt[sel], b3F + s * 8, 512 + nhalf * 32, kr, 3);
            if (rank == 0 && idx + CR + 2 >= K3_NS && k1 == 80) pend = atomicAdd(&g_sync[F_CLM + p.unit[unit][0]], 1u);
            if (sel && hoa < 8) {
              wait_flag(&g_sync[F_OA + mblk], 8);
              hoa = 8;
              asm volatile("fence.proxy.async.global;" ::: "memory");
            }
            if (!sel && !((have >> (k >> 1)) & 1)) {
#pragma unroll 1
              for (uint32_t spins = 0; spins < (1u << 22); spins++) {
                have = ld_and2(&g_sync[F_CTX + (mblk & ~1)]);
                if ((have >> (k >> 1)) & 1) break;
                __nanosleep(100);
              }
              asm volatile("fence.proxy.async.global;" ::: "memory");
            }
            tma2d(st, &p.tmC, b3F + s * 8, (sel ? 64 + k : k) * 64, mblk * 128);
            if (idx < 12) TP(24 + idx);
            return ++idx >= k1;
          };
#pragma unroll 1
          for (;;) {
            if (step(pa)) break;
            if (step(pb)) break;
          }
          asm volatile("" ::"r"(pa), "r"(pb) : "memory");
        }
      }
    }
    __syncwarp();
    if (warp_g == 8) {
      uint32_t v = 0;
      if (lane == 0) {
        __threadfence();
        v = atomicAdd(&g_sync[F_DONE], 1u);
      }
      if (__shfl_sync(0xffffffffu, v, 0) == 2 * NCLUSTER - 1) {
        reinterpret_cast<uint4*>(g_sync)[lane] = make_uint4(0, 0, 0, 0);
        if (lane == 0) g_sync[F_EPOCH] = lds32(sGate + 64) + 1;
      }
    }
    asm volatile("" ::: "memory");
    if (__shfl_sync(0xffffffffu, warp_g, 0) != 8) {
#pragma unroll 1
      for (int i = 0; i < 32 && !mbar_test(bAf + 7 * 8, 0); i++) __nanosleep(200);
      if (lr0 < S_LEN) {
#pragma unroll 1
        for (int i = warp_g - 9; i < 16; i += 3) {
          const float g = gate_row(lr0 + i, lane, x, gate_w);
          if (lane == 0) asm volatile("st.shared.f32 [%0], %1;" ::"r"(sGate + i * 4), "f"(g) : "memory");
        }
        bar_arrive(3, 256 + 96);
        if (lane == 0) {
          __threadfence();
          atomicAdd(&g_sync[F_GATE], 1u);
        }
      }
      uint32_t aph = 1;
#pragma unroll 1
      for (int ji = 0; ji < K1_MAXJOBS; ji++) aph ^= (p.jobs[cl][ji] >> 14) & 1;
      if (warp_g == 9) {
        uint32_t nxt = 0;
        if (lane == 0) {
#pragma unroll 1
        for (int ji = 0; ji < K1_MAXJOBS; ji++) {
          const uint32_t job = p.jobs[cl][ji];
          if (!(job & 3)) break;
          PWAIT(bS + (ji & 3) * 8, (ji >> 2) & 1);
          __threadfence();
          atomicAdd(&g_sync[(((job >> 6) & 3) == 2) ? (F_QKVA + ((job >> 3) & 7) * 2 + rank) : (F_HP + ((job >> 10) & 15))], 1u);
        }
#pragma unroll 1
        for (int it = 0;; it++) {
          PWAIT(bS2 + (it & 3) * 8, (it >> 2) & 1);
          const uint32_t item = lds32(sItem + (it & 7) * 4);
          nxt = lds32(sItem + ((it + 1) & 7) * 4);
          __threadfence();
          atomicOr(&g_sync[F_CTX + (item & 7) * 2 + rank], 1u << (item >> 3));
          if (nxt >= K2_END) break;
        }
        }
        const uint32_t unit = __shfl_sync(0xffffffffu, nxt, 0) & 255;
        {
          const int mblk = (7 - (p.unit[unit][0] >> 1)) * 2 + rank, nhalf = p.unit[unit][0] & 1;
          bf16* o = ptr_add(out, (mblk * 128 + p.unit[unit][1] * 32) * DM * 2);
          const bool mine = p.unit[unit][1] < 4;
#pragma unroll 4
          for (int i = 0; i < 32 && mine; i++) __stcg(reinterpret_cast<uint4*>(ptr_add(o, i * DM * 2 + nhalf * 512 + lane * 16)), make_uint4(0, 0, 0, 0));
#pragma unroll
          for (int i = 0; i < 4 && mine; i++) __stcg(reinterpret_cast<uint4*>(ptr_add(o, (i * 8 + (lane >> 2)) * DM * 2 + 1024 + nhalf * 64 + (lane & 3) * 16)), make_uint4(0, 0, 0, 0));
          asm volatile("fence.proxy.async.global;" ::: "memory");
          __threadfence();
          __syncwarp();
          if (lane == 0) {
            prefetch_tmap(&p.tmR[0]); prefetch_tmap(&p.tmR[1]);
            unsigned int* cnt = &g_sync[F_XCH + mblk * 2 + nhalf];
            const uint32_t xtarget = lds32(sGate + 64) * 4 + 4;
            if (mine) atomicAdd(cnt, 1u);
            uint32_t v;
#pragma unroll 1
            for (uint32_t spins = 0; spins < (1u << 22); spins++) {
              asm volatile("ld.acquire.gpu.global.u32 %0, [%1];" : "=r"(v) : "l"(cnt) : "memory");
              if ((int)(v - xtarget) >= 0) break;
              __nanosleep(200);
            }
            asm volatile("fence.proxy.async.global;" ::: "memory");
            mbar_arrive(bZ);
          }
        }
      } else if (warp_g == 11) {
        if (lane == 0) {
          asm volatile("st.shared.u32 [%0], %1;" ::"r"(sGate + 64), "r"(__ldcg(&g_sync[F_EPOCH])) : "memory");
          wait_flag(&g_sync[F_GATE], GATE_TARGET);
          prefetch_tmap(&p.tmC); prefetch_tmap(&p.tmQ); prefetch_tmap(&p.tmK); prefetch_tmap(&p.tmV);
          uint32_t tick;
          if (rank == 0) {
            PWAIT(bLast, 0);
            PWAIT(bAe + FIRST_DRAW * 8, aph);
            tick = atomicAdd(&g_sync[F_TICK], 1u);
            asm volatile("st.shared.u32 [%0], %1;" ::"r"(sTick + 8), "r"(tick) : "memory");
            asm volatile(
                "{\n.reg .b32 a, b;\nmapa.shared::cluster.u32 a, %0, 1;\nmapa.shared::cluster.u32 b, %1, 1;\n"
                "st.async.shared::cluster.mbarrier::complete_tx::bytes.u32 [a], %2, [b];\n}" ::"r"(sTick + 8), "r"(bT0), "r"(tick) : "memory");
          } else {
            mbar_expect(bT0, 4);
            PWAIT(bT0, 0);
            tick = lds32(sTick + 8);
          }
          wait_flag(&g_sync[F_HP + (p.order[tick] >> 4)], RDY_TARGET);
          mbar_arrive(bR);
        }
      } else if (warp_g == 10) {
        if (lr0 < S_LEN && lane == 0) {
          prefetch_tmap(&p.tmL[0]); prefetch_tmap(&p.tmL[1]); prefetch_tmap(&p.tmL[2]);
          wait_flag(&g_sync[F_QKVA + (lr0 >> 7)], K1_FLAG_TARGET);
          wait_flag(&g_sync[F_QKVA + (max(lr0 - 16, 0) >> 7)], K1_FLAG_TARGET);
          asm volatile("fence.proxy.async.global;" ::: "memory");
          PWAIT(bLast, 0);
#pragma unroll 1
          for (int kc = 0; kc < 6; kc++) {
            PWAIT(bAe + kc * 8, aph);
            if (kc == 3) {
              mbar_expect(bL, LV);
              tma4d(sL, &p.tmL[0], bL, lr0 / 2 - 8, 9, 0);
              tma4d(sL + LQ, &p.tmL[1], bL, lr0 / 2, 0, 0);
            }
          }
          mbar_expect(bL2, LQ);
          tma4d(sL + LV, &p.tmL[0], bL2, lr0 / 2 - 8, 18, 0);
        }
        __syncwarp();
        bar_sync(5, 256 + 32);
        if (lr0 < S_LEN && lane == 0) {
          asm volatile("cp.async.bulk.tensor.4d.global.shared::cta.bulk_group [%0, {%2, %3, %2, %2}], [%1];" ::"l"(&p.tmL[2]), "r"(sL + LQ), "r"(0), "r"(lr0 / 2) : "memory");
          asm volatile("cp.async.bulk.commit_group;" ::: "memory");
          asm volatile("cp.async.bulk.wait_group.read 0;" ::: "memory");
        }
        __syncwarp();
        if (lane < 12) mbar_arrive_cluster(bE + (4 + lane % 3) * 8, (lane / 3) & 1);
        if (lr0 < S_LEN && lane == 0) {
          asm volatile("cp.async.bulk.wait_group 0;" ::: "memory");
          asm volatile("fence.proxy.async.global;" ::: "memory");
          __threadfence();
          atomicAdd(&g_sync[F_OA + (lr0 >> 7)], 1u);
        }
      }
    }
    __syncwarp();
    cluster_sync();
  } else {
    reg_alloc<232>();
    const int wg = warp_g >> 2, warp = warp_g & 3, q = lane & 3;
    const bool sig = (lane == 0) && (warp < 2);
    {
      K1State st{0, 0, 0, nullptr, nullptr, 0, 0, 0, 24};
      float acc[128];
      uint32_t pk[64];
      if (wg == 0) { TS(0, 0); TSC(0, 2); }
      uint32_t job = p.jobs[cl][0];
      k1_first(st, job, bAf, bBf);
      {
#pragma unroll 1
        for (int ji = 0; job & 3; ji++) {
          const uint32_t njob = p.jobs[cl][ji + 1];
          k1_tile(acc, pk, st, job, njob, sA, sB, bAf, bAe, bBf, bBe, bS, wg, warp, lane, rank);
          job = njob;
        }
      }
#pragma unroll
      for (int i = 0; i < 4; i++)
        mbar_arrive_cluster_if(bE + i * 8, warp & 1, sig);
      if (lr0 < S_LEN) bar_sync(3, 256 + 96);
      if (st.wsel == 3) {
#pragma unroll
        for (int G = 0; G < 16; G++) scale_q4(pk + G * 4);
      }
      auto flush = [&](int i, uint32_t dep) {
        asm volatile("{\n.reg .pred p;\nsetp.eq.u32 p, %5, 0;\n@p st.global.cs.v4.b32 [%0], {%1, %2, %3, %4};\n}" ::"l"(((i & 1) ? st.pp8 : st.pp) + (i / 2) * 32),
                     "r"(pk[i * 4]), "r"(pk[i * 4 + 1]), "r"(pk[i * 4 + 2]), "r"(pk[i * 4 + 3]), "r"(dep & blockIdx.y) : "memory");
      };
      if (wg == 0) { TS(0, 1); TSC(0, 3); }
      if (lr0 < S_LEN) {
        const float gate0 = __uint_as_float(lds32(sGate + (lane >> 2) * 8)), gate1 = __uint_as_float(lds32(sGate + (lane >> 2) * 8 + 4));
        local_attn(lr0, warp_g, sL, bL, bL2, lane, gate0, gate1, flush);
        k1_flag(st, lane, bS);
      } else {
        FLUSH();
      }
      bar_arrive(5, 256 + 32);
    }
    __syncwarp();
    uint32_t item, rot;
    {
      const int mybar = 1 + wg, otherbar = 2 - wg;
      const uint32_t never = blockIdx.y;
      float S[64], O[64];
      uint32_t P[32], Q[32];
      float m0, m1, l0, l1, gf0, gf1;
      uint32_t eoff;
      Cursor c{2 + 2 * (uint32_t)wg, 0}, ck{1 + (uint32_t)wg, 0};
      if (wg == 1) bar_arrive(1, 256);
      if (wg == 0) { TS(1, 0); TSC(1, 2); }
      {
        const Cursor cq{0, 0}, cs0{1, 0}, cs1{3, 0};
        const int it = 0, hi = wg ^ 1;
        mbar_wait2(bF, 0, bF + ck.s * 8, 0);
        LOAD_Q();
        wg_fence();
        ISSUE_QK(ck);
        wg_commit();
        RELEASE(cq);
        NEW_ITEM();
        wg_wait<0>();
        fence_regs(S);
      }
#pragma unroll 1
      for (int it = 0;;) {
        int hi = (wg ^ it ^ 1) & 1;
        RELEASE(ck);
        const int nblk = 2 * (item & 7) + 1 + hi;
        Cursor cv;
        float s0 = 0.f, s1 = 0.f;
        l0 = 0.f; l1 = 0.f;
        m0 = 0.f; m1 = 0.f;
        bool shifted = false;
        {
          const int d = warp * 16 + (lane >> 2) - 2 * q;
          if (rank == hi) {
#pragma unroll
            for (int jj = 0; jj < 8; jj++) MASK(jj, jj);
            EXPB(0); EXPB(1); EXPB(2); EXPB(3);
#pragma unroll
            for (int i = 32; i < 64; i++) S[i] = -INFINITY;
#pragma unroll
            for (int i = 16; i < 32; i++) P[i] = 0;
          } else {
#pragma unroll
            for (int jj = 0; jj < 8; jj++) MASK(jj + 8, jj);
            EXPB(0); EXPB(1); EXPB(2); EXPB(3); EXPB(4); EXPB(5); EXPB(6); EXPB(7);
          }
        }
        float chk;
        asm("{\n.reg .pred p;\nsetp.ge.f32 p, %1, %2;\nselp.f32 %0, %3, 0f7F800000, p;\n}" : "=f"(chk) : "f"(fminf(s0, s1)), "f"(q ? -1.f : SPEC_LO), "f"(s0 + s1));
        fence_regs(P);
        TB(9);
#pragma unroll 1
        for (int n = 1;; n++) {
          if (__any_sync(0xffffffffu, !(chk <= SPEC_HI))) {
            float mx0 = fmaxf(S[0], S[1]), mx1 = fmaxf(S[2], S[3]);
#pragma unroll
            for (int jj = 1; jj < 16; jj++) {
              mx0 = fmaxf(mx0, fmaxf(S[jj * 4 + 0], S[jj * 4 + 1]));
              mx1 = fmaxf(mx1, fmaxf(S[jj * 4 + 2], S[jj * 4 + 3]));
            }
            mx0 = fmaxf(mx0, __shfl_xor_sync(0xffffffffu, mx0, 1));
            mx1 = fmaxf(mx1, __shfl_xor_sync(0xffffffffu, mx1, 1));
            mx0 = fmaxf(mx0, __shfl_xor_sync(0xffffffffu, mx0, 2));
            mx1 = fmaxf(mx1, __shfl_xor_sync(0xffffffffu, mx1, 2));
            const float lo = (n == 1) ? -INFINITY : 0.f;
            mx0 = fmaxf(mx0, lo);
            mx1 = fmaxf(mx1, lo);
            m0 += mx0; m1 += mx1;
            shifted = true;
            const float sc0 = ex2(-fmaxf(mx0, 0.f)), sc1 = ex2(-fmaxf(mx1, 0.f));
            l0 *= sc0; l1 *= sc1;
            s0 = 0.f; s1 = 0.f;
#pragma unroll
            for (int jj = 0; jj < 16; jj++) {
              const float e0 = ex2(S[jj * 4 + 0] - mx0), e1 = ex2(S[jj * 4 + 1] - mx0), e2 = ex2(S[jj * 4 + 2] - mx1), e3 = ex2(S[jj * 4 + 3] - mx1);
              s0 += e0 + e1;
              s1 += e2 + e3;
              P[jj * 2 + 0] = pack_bf16(e0, e1);
              P[jj * 2 + 1] = pack_bf16(e2, e3);
              O[jj * 4 + 0] *= sc0;
              O[jj * 4 + 1] *= sc0;
              O[jj * 4 + 2] *= sc1;
              O[jj * 4 + 3] *= sc1;
            }
          }
          l0 += s0;
          l1 += s1;
          if (n >= nblk) break;
          ck = c; c.next();
          cv = c; c.next();
          mbar_wait2(bF + ck.s * 8, ck.ph, bF + cv.s * 8, cv.ph);
          TURN_SYNC();
          TRC(0);
          wg_fence();
          ISSUE_QK(ck);
          wg_commit();
          {
            const uint64_t dv = make_desc(sbase + cv.s * 32768, 16384, 1024, 1);
#pragma unroll
            for (int t = 0; t < 8; t++) {
              wgmma_rs_n128<1, 0>(O, P[4 * t], P[4 * t + 1], P[4 * t + 2], P[4 * t + 3], dv + (uint64_t)(t * 128), (t > 0) ? 1 : (n != 1));
              if ((PVM >> t) & 1) wg_commit();
            }
          }
          TURN_ARRIVE();
          s0 = 0.f; s1 = 0.f;
          wg_wait<__builtin_popcount(PVM)>();
          fence_regs(S);
          RELEASE(ck);
          if (shifted) {
#pragma unroll
            for (int i = 0; i < 64; i++) S[i] -= (i & 2) ? m1 : m0;
          }
          wg_wait<__builtin_popcount(PVM) - 1>();
          EXPC(0); EXPC(1); EXPC(2); EXPC(3); EXPC(4); EXPC(5); EXPC(6); EXPC(7);
          chk = s0 + s1;
        }
        it++;
        hi ^= 1;
        TB(0);
        Cursor cq = c, cs0, cs1;
        rot = k3_rot(c.s);
        c.next();
        ck = c; c.next();
        cs0 = ck; cs1 = ck;
        cv = c; c.next();
        if (!hi) {
          ck = c; c.next();
          cs1 = c; c.next();
        }
        mbar_wait(bF + cq.s * 8, cq.ph);
        TB(1);
        LOAD_Q();
        const uint32_t rdy = mbar_test(bF + ck.s * 8, ck.ph) & mbar_test(bF + cv.s * 8, cv.ph);
        l0 += __shfl_xor_sync(0xffffffffu, l0, 1);
        l1 += __shfl_xor_sync(0xffffffffu, l1, 1);
        l0 += __shfl_xor_sync(0xffffffffu, l0, 2);
        l1 += __shfl_xor_sync(0xffffffffu, l1, 2);
        if (item >= K2_END) {
          TURN_SYNC();
          TRC(2);
          wg_fence();
          ISSUE_PV(cq, nblk == 1);
          wg_commit();
          if (wg == (it & 1)) TURN_ARRIVE();
          asm volatile("" : "+f"(gf0), "+f"(gf1), "+f"(l0), "+f"(l1));
          const float f0 = __fdividef(1.f - gf0, l0), f1 = __fdividef(1.f - gf1, l1);
          bf16* optr = ptr_add(g_ctx, eoff);
          wg_wait<0>();
          fence_regs(O);
          mbar_arrive_cluster_if(bH, warp & 1, sig);
          STORE_O(0); STORE_O(1); STORE_O(2); STORE_O(3);
          __syncwarp();
          mbar_arrive_if(bS2 + ((it - 1) & 3) * 8, lane == 0);
          break;
        }
        if (!rdy) mbar_wait2(bF + ck.s * 8, ck.ph, bF + cv.s * 8, cv.ph);
        TB(2);
        TURN_SYNC();
        TB(3);
        TRC(1);
        wg_fence();
        ISSUE_PV(cv, nblk == 1);
        wg_commit();
        ISSUE_QK(ck);
        wg_commit();
        TURN_ARRIVE();
        RELEASE(cq);
        TB(4);
        asm volatile("" : "+f"(gf0), "+f"(gf1), "+f"(l0), "+f"(l1));
        const float f0 = __fdividef(1.f - gf0, l0), f1 = __fdividef(1.f - gf1, l1);
        wg_wait<1>();
        fence_regs(O);
        fence_regs(P);
        TB(5);
        RELEASE(cv);
        {
          bf16* optr = ptr_add(g_ctx, eoff);
          STORE_O(0); STORE_O(1); STORE_O(2); STORE_O(3);
          __syncwarp();
          mbar_arrive_if(bS2 + ((it - 1) & 3) * 8, lane == 0);
        }
        TB(6);
        NEW_ITEM();
        TB(7);
        wg_wait<0>();
        fence_regs(S);
        TB(8);
      }
      TRC(3);
      if (wg == 1) { TS(1, 1); TSC(1, 3); }
    }
    __syncwarp();
    const uint32_t unit = item & 255;
    {
      const int mblk = (7 - (p.unit[unit][0] >> 1)) * 2 + rank, nhalf = p.unit[unit][0] & 1;
      float acc[144];
      uint32_t s = rot, ph = 0, prev = 0, k = 0;
      if (wg == 0) { TS(2, 0); TSC(2, 2); }
      uint32_t fa[16], fb[16], fc[16];
      const uint32_t aoff = (wg * 64 + warp * 16 + (lane & 15)) * 128 + (((lane >> 4) ^ (lane & 7)) << 4);
#define C_NEXT()                                                                                               \
  do {                                                                                                         \
    s = (s + 1) & 3;                                                                                           \
    if (s == rot) ph ^= 1;                                                                                     \
    mbar_wait(b3F + s * 8, ph);                                                                                \
  } while (0)
#define C_LOAD(F)                                                                                              \
  do {                                                                                                         \
    _Pragma("unroll") for (int t = 0; t < 4; t++)                                                              \
        ldsm_x4(F[4 * t], F[4 * t + 1], F[4 * t + 2], F[4 * t + 3], sbase + s * K3_STAGE + (aoff ^ (t * 32))); \
  } while (0)
#define C_MMA(F, S, H, SD)                                                                                     \
  do {                                                                                                         \
    const uint32_t st = sbase + (S) * K3_STAGE;                                                                \
    const uint64_t db = make_desc(st + 16384, 4096, 1024, 1), dt = make_desc(st + 49152, 16, 512, 2);          \
    _Pragma("unroll") for (int t = 0; t < 4; t++) {                                                            \
      const int sd = (t > 0) || (SD);                                                                          \
      if ((H) & 1) wgmma_rs_n128<1, 0>(acc, F[4 * t], F[4 * t + 1], F[4 * t + 2], F[4 * t + 3], db + (uint64_t)((t >> 1) * 1024 + (t & 1) * 128), sd); \
      if ((H) & 2) wgmma_rs_n128<1, 64>(acc, F[4 * t], F[4 * t + 1], F[4 * t + 2], F[4 * t + 3], db + (uint64_t)((t >> 1) * 1024 + (t & 1) * 128 + 512), sd); \
      if ((H) & 2) wgmma_rs_n32<1, 128>(acc, F[4 * t], F[4 * t + 1], F[4 * t + 2], F[4 * t + 3], dt + (uint64_t)(t * 64), sd); \
    }                                                                                                          \
  } while (0)
#define C_STEP(F, G)                                                                                           \
  {                                                                                                            \
    wg_fence();                                                                                                \
    C_MMA(F, s, 3, k > 0);                                                                                     \
    wg_commit();                                                                                               \
    wg_wait<1>();                                                                                              \
    fence_regs(G);                                                                                             \
    mbar_arrive_cluster_if(b3E + prev * 8, warp & 1, sig && k > 0);                                            \
    prev = s;                                                                                                  \
    TCK(k + 1);                                                                                                \
    C_NEXT();                                                                                                  \
    if ((tid & 127) == 0 && k < 11) TP(37 + wg * 12 + k);                                                      \
    if (++k + CR >= lds32(sK1)) break;                                                                         \
    C_LOAD(G);                                                                                                 \
  }
      TCK(0);
      mbar_wait(b3F + s * 8, 0);
      if ((tid & 127) == 0) TP(36 + wg * 12);
      C_LOAD(fa);
#pragma unroll
      for (int i = 0; i < 16; i++) fb[i] = 0;
#pragma unroll 1
      for (;;) {
        C_STEP(fa, fb)
        C_STEP(fb, fa)
      }
      C_LOAD(fc);
      if (wg == 1) {
        wg_wait<0>();
        mbar_arrive_cluster_if(b3E + prev * 8, warp & 1, sig);
        mbar_wait(bLd, 0);
      }
      const uint32_t s0 = s;
      wg_fence();
      C_MMA(fc, s0, 2, 1);
      wg_commit();
      wg_wait<1>();
      fence_regs(fa);
      fence_regs(fb);
      mbar_arrive_cluster_if(b3E + prev * 8, warp & 1, sig && wg == 0);
      cluster_arrive();
      C_NEXT();
      C_LOAD(fa);
      wg_fence();
      C_MMA(fa, s, 2, 1);
      C_MMA(fc, s0, 1, 1);
      wg_commit();
      C_NEXT();
      C_LOAD(fb);
      wg_fence();
      C_MMA(fb, s, 2, 1);
      wg_commit();
      wg_wait<1>();
      fence_regs(fc);
      C_NEXT();
      C_LOAD(fc);
      wg_fence();
      C_MMA(fc, s, 2, 1);
      wg_commit();
      C_MMA(fa, (s0 + 1) & 3, 1, 1);
      C_MMA(fb, (s0 + 2) & 3, 1, 1);
      C_MMA(fc, s, 1, 1);
      wg_commit();
      mbar_arrive_if(bLd, tid < 128 && lane == 0);
      const uint32_t stail = sbase + K3_NST * K3_STAGE + warp_g * 1024;
      const int row = mblk * 128 + warp_g * 16;
      mbar_wait(bZ, 0);
#pragma unroll
      for (int h = 1; h >= 0; h--) {
        if (h) wg_wait<1>(); else wg_wait<0>();
#pragma unroll
        for (int i = h * 64; i < 64 + h * 80; i++) asm volatile("" : "+f"(acc[i])::"memory");
        if (!h && wg == 0) TS(2, 4);
#pragma unroll
        for (int i = h * 8; i < 8 + h * 10; i++) {
          const uint32_t ad = (i < 16) ? sbase + (i >> 2) * K3_STAGE + (aoff ^ ((i & 3) * 32))
                                       : stail + (lane & 15) * 64 + ((((i & 1) * 2 + (lane >> 4)) ^ ((lane >> 1) & 3)) << 4);
          asm volatile("stmatrix.sync.aligned.m8n8.x4.shared.b16 [%0], {%1, %2, %3, %4};" ::"r"(ad), "r"(pack_bf16(acc[i * 8], acc[i * 8 + 1])),
                       "r"(pack_bf16(acc[i * 8 + 2], acc[i * 8 + 3])), "r"(pack_bf16(acc[i * 8 + 4], acc[i * 8 + 5])), "r"(pack_bf16(acc[i * 8 + 6], acc[i * 8 + 7])) : "memory");
        }
        asm volatile("fence.proxy.async.shared::cta;" ::: "memory");
        __syncwarp();
        if (!h && wg == 0) TS(2, 5);
        if (lane == 0) {
#pragma unroll
          for (int c = h * 2; c < 2 + h * 3; c++)
            asm volatile("cp.reduce.async.bulk.tensor.2d.global.shared::cta.add.tile.bulk_group [%0, {%2, %3}], [%1];" ::"l"(&p.tmR[c >> 2]),
                         "r"((c < 4) ? sbase + c * K3_STAGE + warp_g * 2048 : stail), "r"((c < 4) ? nhalf * 256 + c * 64 : 512 + nhalf * 32), "r"(row) : "memory");
        }
        __syncwarp();
      }
      if (lane == 0) {
        asm volatile("cp.async.bulk.commit_group;" ::: "memory");
        if (wg == 0) TS(2, 6);
        asm volatile("cp.async.bulk.wait_group 0;" ::: "memory");
      }
      __syncwarp();
    }
    if (wg == 0) { TS(2, 1); TSC(2, 3); }
    cluster_wait();
  }
}

typedef CUresult (*EncFn)(CUtensorMap*, CUtensorMapDataType, cuuint32_t, void*, const cuuint64_t*, const cuuint64_t*, const cuuint32_t*,
                          const cuuint32_t*, CUtensorMapInterleave, CUtensorMapSwizzle, CUtensorMapL2promotion, CUtensorMapFloatOOBfill);

static void enc2d(EncFn enc, CUtensorMap* m, const void* ptr, uint64_t cols, uint64_t rows, uint32_t bc, uint32_t br,
                  CUtensorMapSwizzle sw = CU_TENSOR_MAP_SWIZZLE_128B) {
  cuuint64_t gd[2] = {cols, rows}, gs[1] = {cols * 2};
  cuuint32_t bx[2] = {bc, br}, es[2] = {1, 1};
  enc(m, CU_TENSOR_MAP_DATA_TYPE_BFLOAT16, 2, const_cast<void*>(ptr), gd, gs, bx, es, CU_TENSOR_MAP_INTERLEAVE_NONE, sw,
      CU_TENSOR_MAP_L2_PROMOTION_L2_256B, CU_TENSOR_MAP_FLOAT_OOB_FILL_NONE);
}
static void enc3d(EncFn enc, CUtensorMap* m, const void* ptr, uint64_t cols, uint64_t rows, uint32_t br, uint32_t bch) {
  cuuint64_t gd[3] = {64, rows, cols / 64}, gs[2] = {cols * 2, 128};
  cuuint32_t bx[3] = {64, br, bch}, es[3] = {1, 1, 1};
  enc(m, CU_TENSOR_MAP_DATA_TYPE_BFLOAT16, 3, const_cast<void*>(ptr), gd, gs, bx, es, CU_TENSOR_MAP_INTERLEAVE_NONE,
      CU_TENSOR_MAP_SWIZZLE_128B, CU_TENSOR_MAP_L2_PROMOTION_L2_256B, CU_TENSOR_MAP_FLOAT_OOB_FILL_NONE);
}

static void build_k1_jobs(Params& p) {
  int cnt[NCLUSTER];
  for (int c = 0; c < NCLUSTER; c++) {
    cnt[c] = 0;
    for (int i = 0; i <= K1_MAXJOBS; i++) p.jobs[c][i] = 0;
  }
  auto add = [&](int c, int nch, int a_sel, int mp, int w_sel, int chunk0) {
    p.jobs[c][cnt[c]++] = (uint16_t)((nch - 1) | (a_sel << 2) | (mp << 3) | (w_sel << 6) | (chunk0 << 8));
  };
  const char* plan = "ccccccccccc cccccccccc ccccccc cccc xxxx xxxx xxxxxx xxxxxxxx";
  int TIE = 0;
  int XA = 0;
  const char* cur[8];
  int tend[8] = {};
  for (int g = 0; g < 8; g++) {
    cur[g] = plan;
    while (*plan == 'c' || *plan == 'x') plan++;
    if (*plan) plan++;
  }
  int kc = 0, kx = 0;
  for (;;) {
    int b = -1, bt = 0;
    for (int g = 0; g < 8; g++) {
      const int t = tend[g] + (*cur[g] == 'x' ? 94 : 85);
      if ((*cur[g] == 'c' || *cur[g] == 'x') && (b < 0 || t < bt || (TIE && t == bt))) { b = g; bt = t; }
    }
    if (b < 0) break;
    const int a = kx - XA;
    for (int mp = 0; mp < 8; mp++) {
      if (*cur[b] == 'c') add(b * 8 + mp, 4, 0, mp, kc & 1, (kc >> 1) * 4);
      else if (a >= 0 && a < 7) add(b * 8 + mp, a == 0 ? 3 : 4, 1, mp, 2, a == 0 ? 24 : (a - 1) * 4);
      else add(b * 8 + mp, 4, 1, mp, 3, (a < 0 ? kx : kx - 7) * 4);
    }
    if (*cur[b] == 'c') kc++; else kx++;
    cur[b]++;
    tend[b] = bt;
  }
  for (int mp = 0; mp < 8; mp++) add(64 + mp / 4, 4, 1, mp, 3, 15 * 4);
  for (int cc = 0; cc < NCLUSTER; cc++)
    for (int i = 0; i < cnt[cc]; i++) {
      const int key = p.jobs[cc][i] & 0x3C;
      if (i == 0 || (p.jobs[cc][i - 1] & 0x3C) != key) p.jobs[cc][i] |= (1 << 14);
      if (i == cnt[cc] - 1 || (p.jobs[cc][i + 1] & 0x3C) != key) p.jobs[cc][i] |= (1 << 15);
    }
}

static void build_k2_items(Params& p) {
  int ps[8][3] = {{0, 2, 2}, {0, 6, 0}, {6, 24, 4}, {6, 32, 0}};
  bool done[256] = {};
  int n = 0;
  for (int i = 0; i < 8; i++)
    for (int j = 7; j >= ps[i][2]; j--)
      for (int h = ps[i][0]; h < ps[i][1]; h++)
        if (!done[h * 8 + j]) { done[h * 8 + j] = true; p.order[n++] = (uint8_t)(h * 8 + j); }
}

static void build_k3_units(Params& p) {
  const char* map = "0123456789abcddcba98765432100123456789abcddcba9876543210feeffeeffe";
  int cnt[16] = {};
  for (int u = 0; u < 66; u++) {
    const int t = (map[u] > '9') ? map[u] - 'a' + 10 : map[u] - '0';
    p.unit[u][0] = (uint8_t)t; p.unit[u][1] = (uint8_t)cnt[t]; p.unit[u][2] = (uint8_t)(cnt[t] * K3_NS);
    cnt[t]++;
  }
  for (int u = 0; u < 66; u++) p.unit[u][3] = (uint8_t)(cnt[p.unit[u][0]] * K3_NS);
}

extern "C" void kernel_launch(void* const* d_in, const int* in_sizes, int n_in, void* d_out, int out_size) {
  const bf16* x = (const bf16*)d_in[0];
  const bf16* wqkv = (const bf16*)d_in[1];
  const bf16* wo = (const bf16*)d_in[2];
  const bf16* ckv = (const bf16*)d_in[4];
  const bf16* w_q = (const bf16*)d_in[5];
  const bf16* w_uk = (const bf16*)d_in[6];
  const bf16* w_uv = (const bf16*)d_in[7];
  const bf16* w_o = (const bf16*)d_in[8];
  const bf16* gate_w = (const bf16*)d_in[9];

  EncFn enc = nullptr;
  cudaDriverEntryPointQueryResult qr;
  cudaGetDriverEntryPoint("cuTensorMapEncodeTiled", (void**)&enc, cudaEnableDefault, &qr);
  void *pK, *pV, *pCtx, *pQA;
  cudaGetSymbolAddress(&pQA, g_QKVA);
  cudaGetSymbolAddress(&pK, g_K);
  cudaGetSymbolAddress(&pV, g_V);
  cudaGetSymbolAddress(&pCtx, g_ctx);

  static Params p;
  enc2d(enc, &p.tmA[0], ckv, DC, S_LEN, 64, 128);
  enc2d(enc, &p.tmA[1], x, DM, S_LEN, 64, 128);
  enc3d(enc, &p.tmW[0], w_uk, HDIM, DC, 16, 4);
  enc3d(enc, &p.tmW[1], w_uv, HDIM, DC, 16, 4);
  enc3d(enc, &p.tmW[2], wqkv, NQKVA, DM, 16, 4);
  enc3d(enc, &p.tmW[3], w_q, HDIM, DM, 16, 4);
  build_k1_jobs(p);
  enc2d(enc, &p.tmK, pK, HDIM, S_LEN, 64, 128);
  enc2d(enc, &p.tmV, pV, HDIM, S_LEN, 64, 128);
  enc2d(enc, &p.tmQ, pCtx, KCAT, S_LEN, 64, 64);
  build_k2_items(p);
  build_k3_units(p);
  for (int i = 0; i < 3; i++) {
    const cuuint64_t ld = (i < 2 ? NQKVA : KCAT) * 2, nch = (i < 2) ? 27 : 9;
    cuuint64_t gd[4] = {64, S_LEN / 2, i ? 2 : nch, i ? nch : 2}, gs[3] = {2 * ld, i ? ld : 128, i ? 128 : ld};
    cuuint32_t bx[4] = {64, i ? 8u : 16u, i ? 2u : 9u, i ? 9u : 2u}, es[4] = {1, 1, 1, 1};
    enc(&p.tmL[i], CU_TENSOR_MAP_DATA_TYPE_BFLOAT16, 4, (i < 2) ? pQA : (void*)((bf16*)pCtx + HDIM), gd, gs, bx, es, CU_TENSOR_MAP_INTERLEAVE_NONE,
        CU_TENSOR_MAP_SWIZZLE_128B, CU_TENSOR_MAP_L2_PROMOTION_L2_256B, CU_TENSOR_MAP_FLOAT_OOB_FILL_NONE);
  }
  enc2d(enc, &p.tmC, pCtx, KCAT, S_LEN, 64, 128);
  enc3d(enc, &p.tmO[0], w_o, DM, HDIM, 32, 4);
  enc3d(enc, &p.tmO[1], wo, DM, DM, 32, 4);
  enc2d(enc, &p.tmOt[0], w_o, DM, HDIM, 32, 32, CU_TENSOR_MAP_SWIZZLE_64B);
  enc2d(enc, &p.tmOt[1], wo, DM, DM, 32, 32, CU_TENSOR_MAP_SWIZZLE_64B);
  enc2d(enc, &p.tmR[0], d_out, DM, S_LEN, 64, 16);
  enc2d(enc, &p.tmR[1], d_out, DM, S_LEN, 32, 16, CU_TENSOR_MAP_SWIZZLE_64B);

  cudaFuncSetAttribute(fused_kernel, cudaFuncAttributeMaxDynamicSharedMemorySize, SMEM_BYTES);
  fused_kernel<<<NCLUSTER * 2, 384, SMEM_BYTES>>>(p, x, gate_w, (bf16*)d_out);
}
```

```cpp
#include <cuda_runtime.h>
#include <cuda_bf16.h>
#include <cuda.h>
#include <stdint.h>

typedef __nv_bfloat16 bf16;

constexpr int S_LEN = 2048, DM = 576, DC = 512, HDIM = 4096, NQKVA = 1728, KCAT = 4672;
constexpr int NCLUSTER = 66;
__host__ __device__ constexpr int goff(int G, int r) { return (G >> 1) * S_LEN * 64 + (G & 1) * 32 + r * 512; }

__device__ __align__(1024) bf16 g_K[S_LEN * HDIM];
__device__ __align__(1024) bf16 g_V[S_LEN * HDIM];
__device__ __align__(1024) bf16 g_QKVA[S_LEN * NQKVA + 64];
__device__ __align__(1024) bf16 g_ctx[S_LEN * KCAT];
__device__ float g_gate[S_LEN];
__device__ __align__(16) unsigned int g_sync[400];
constexpr int F_QKVA = 0, F_HP = 16, F_CTX = 32, F_OA = 48, F_CLM = 64, F_GATE = 96, F_TICK = 97, F_DONE = 98, F_XCH = 128, F_EPOCH = 384;

__device__ __forceinline__ uint32_t smem_u32(const void* p) { return (uint32_t)__cvta_generic_to_shared(p); }
__device__ __forceinline__ void mbar_init(uint32_t a, uint32_t c) {
  asm volatile("mbarrier.init.shared::cta.b64 [%0], %1;" ::"r"(a), "r"(c));
}
__device__ __forceinline__ void mbar_expect(uint32_t a, uint32_t b) {
  asm volatile("mbarrier.arrive.expect_tx.shared::cta.b64 _, [%0], %1;" ::"r"(a), "r"(b) : "memory");
}
#define TS(k, i)
#define TSC(k, i)
#define TSM(k)
#define BSEG(i)
#define TB(k)
#define TRC(fl)
#define TCK(i)
#define TP(i)
#define SPIN_LIMIT "4194304"
__device__ __forceinline__ void mbar_wait(uint32_t a, uint32_t parity) {
  asm volatile(
      "{\n.reg .pred p;\n.reg .u32 n;\n"
      "mbarrier.try_wait.parity.shared::cta.b64 p, [%0], %1;\n"
      "@p bra DONE;\n"
      "mov.u32 n, 0;\n"
      "LOOP:\n"
      "mbarrier.try_wait.parity.shared::cta.b64 p, [%0], %1;\n"
      "@p bra DONE;\n"
      "add.u32 n, n, 1;\n"
      "setp.lt.u32 p, n, " SPIN_LIMIT ";\n"
      "@p bra LOOP;\n"
      "DONE:\n}" ::"r"(a), "r"(parity) : "memory");
}
template <int NS>
__device__ __forceinline__ void mbar_wait_ns(uint32_t a, uint32_t parity) {
  asm volatile(
      "{\n.reg .pred p;\n.reg .u32 n;\n"
      "mov.u32 n, 0;\n"
      "LOOP:\n"
      "mbarrier.try_wait.parity.shared::cta.b64 p, [%0], %1, %2;\n"
      "@p bra DONE;\n"
      "add.u32 n, n, 1;\n"
      "setp.lt.u32 p, n, " SPIN_LIMIT ";\n"
      "@p bra LOOP;\n"
      "DONE:\n}" ::"r"(a), "r"(parity), "n"(NS) : "memory");
}
__device__ __forceinline__ void mbar_wait2(uint32_t a, uint32_t pa, uint32_t b, uint32_t pb) {
  asm volatile(
      "{\n.reg .pred p, q;\n.reg .u32 n;\n"
      "mov.u32 n, 0;\n"
      "LOOP:\n"
      "mbarrier.try_wait.parity.shared::cta.b64 p, [%0], %1;\n"
      "mbarrier.try_wait.parity.shared::cta.b64 q, [%2], %3;\n"
      "add.u32 n, n, 1;\n"
      "and.pred p, p, q;\n"
      "setp.lt.and.u32 p, n, " SPIN_LIMIT ", !p;\n"
      "@p bra LOOP;\n"
      "}" ::"r"(a), "r"(pa), "r"(b), "r"(pb) : "memory");
}
__device__ __forceinline__ uint32_t mbar_test(uint32_t a, uint32_t parity) {
  uint32_t r;
  asm volatile("{\n.reg .pred p;\nmbarrier.test_wait.parity.shared::cta.b64 p, [%1], %2;\nselp.u32 %0, 1, 0, p;\n}" : "=r"(r) : "r"(a), "r"(parity) : "memory");
  return r;
}
__device__ __forceinline__ void mbar_arrive(uint32_t a) {
  asm volatile("mbarrier.arrive.shared::cta.b64 _, [%0];" ::"r"(a) : "memory");
}
__device__ __forceinline__ void mbar_arrive_cluster(uint32_t a, uint32_t cta) {
  asm volatile("{\n.reg .b32 r;\nmapa.shared::cluster.u32 r, %0, %1;\nmbarrier.arrive.shared::cluster.b64 _, [r];\n}" ::"r"(a),
               "r"(cta) : "memory");
}
__device__ __forceinline__ void mbar_arrive_cluster_if(uint32_t a, uint32_t cta, bool pred) {
  asm volatile("{\n.reg .b32 r;\n.reg .pred p;\nsetp.ne.u32 p, %2, 0;\nmapa.shared::cluster.u32 r, %0, %1;\n@p mbarrier.arrive.shared::cluster.b64 _, [r];\n}" ::"r"(a),
               "r"(cta), "r"((uint32_t)pred) : "memory");
}
__device__ __forceinline__ void anchor(float v, uint32_t pred) {
  asm volatile("{\n.reg .pred p;\nsetp.ne.u32 p, %1, 0;\n@p st.shared.f32 [%1], %0;\n}" ::"f"(v), "r"(pred) : "memory");
}
__device__ __forceinline__ void mbar_arrive_if(uint32_t a, bool pred) {
  asm volatile("{\n.reg .pred p;\nsetp.ne.u32 p, %1, 0;\n@p mbarrier.arrive.shared::cta.b64 _, [%0];\n}" ::"r"(a), "r"((uint32_t)pred) : "memory");
}
__device__ __forceinline__ void tma2d(uint32_t dst, const CUtensorMap* m, uint32_t bar, int c0, int c1) {
  asm volatile("cp.async.bulk.tensor.2d.shared::cluster.global.mbarrier::complete_tx::bytes [%0], [%1, {%3, %4}], [%2];" ::"r"(dst),
               "l"(m), "r"(bar), "r"(c0), "r"(c1) : "memory");
}
__device__ __forceinline__ void tma2d_mc(uint32_t dst, const CUtensorMap* m, uint32_t bar, int c0, int c1, uint16_t mask) {
  asm volatile(
      "cp.async.bulk.tensor.2d.shared::cluster.global.mbarrier::complete_tx::bytes.multicast::cluster [%0], [%1, {%3, %4}], [%2], %5;" ::"r"(dst),
      "l"(m), "r"(bar), "r"(c0), "r"(c1), "h"(mask) : "memory");
}
__device__ __forceinline__ void tma3d_mc(uint32_t dst, const CUtensorMap* m, uint32_t bar, int c0, int c1, int c2, uint16_t mask) {
  asm volatile(
      "cp.async.bulk.tensor.3d.shared::cluster.global.mbarrier::complete_tx::bytes.multicast::cluster [%0], [%1, {%3, %4, %5}], [%2], %6;" ::"r"(dst),
      "l"(m), "r"(bar), "r"(c0), "r"(c1), "r"(c2), "h"(mask) : "memory");
}
__device__ __forceinline__ void tma3d(uint32_t dst, const CUtensorMap* m, uint32_t bar, int c0, int c1, int c2) {
  asm volatile(
      "cp.async.bulk.tensor.3d.shared::cluster.global.mbarrier::complete_tx::bytes [%0], [%1, {%3, %4, %5}], [%2];" ::"r"(dst),
      "l"(m), "r"(bar), "r"(c0), "r"(c1), "r"(c2) : "memory");
}
__device__ __forceinline__ void tma_pf2d(const CUtensorMap* m, int c0, int c1) {
  asm volatile("cp.async.bulk.prefetch.tensor.2d.L2.global [%0, {%1, %2}];" ::"l"(m), "r"(c0), "r"(c1) : "memory");
}
__device__ __forceinline__ void tma_pf3d(const CUtensorMap* m, int c0, int c1, int c2) {
  asm volatile("cp.async.bulk.prefetch.tensor.3d.L2.global [%0, {%1, %2, %3}];" ::"l"(m), "r"(c0), "r"(c1), "r"(c2) : "memory");
}
__device__ __forceinline__ void prefetch_tmap(const CUtensorMap* m) {
  asm volatile("prefetch.tensormap [%0];" ::"l"(m) : "memory");
}
__device__ __forceinline__ void cluster_arrive() { asm volatile("barrier.cluster.arrive.relaxed.aligned;" ::: "memory"); }
__device__ __forceinline__ void cluster_wait() { asm volatile("barrier.cluster.wait.aligned;" ::: "memory"); }
__device__ __forceinline__ void cluster_sync() {
  cluster_arrive();
  cluster_wait();
}
__device__ __forceinline__ uint32_t cluster_rank() {
  uint32_t r;
  asm volatile("mov.u32 %0, %%cluster_ctarank;" : "=r"(r));
  return r;
}
__device__ __forceinline__ bool elect_one() {
  uint32_t p;
  asm volatile("{\n.reg .pred q;\nelect.sync _|q, 0xffffffff;\nselp.u32 %0, 1, 0, q;\n}" : "=r"(p));
  return p;
}
__device__ __forceinline__ void ldsm_x4(uint32_t& r0, uint32_t& r1, uint32_t& r2, uint32_t& r3, uint32_t addr) {
  asm volatile("ldmatrix.sync.aligned.m8n8.x4.shared.b16 {%0, %1, %2, %3}, [%4];" : "=r"(r0), "=r"(r1), "=r"(r2), "=r"(r3) : "r"(addr) : "memory");
}
__device__ __forceinline__ void wg_fence() { asm volatile("wgmma.fence.sync.aligned;" ::: "memory"); }
__device__ __forceinline__ void wg_commit() { asm volatile("wgmma.commit_group.sync.aligned;" ::: "memory"); }
template <int N>
__device__ __forceinline__ void wg_wait() { asm volatile("wgmma.wait_group.sync.aligned %0;" ::"n"(N) : "memory"); }
template <int N>
__device__ __forceinline__ void reg_alloc() { asm volatile("setmaxnreg.inc.sync.aligned.u32 %0;" ::"n"(N)); }
template <int N>
__device__ __forceinline__ void reg_dealloc() { asm volatile("setmaxnreg.dec.sync.aligned.u32 %0;" ::"n"(N)); }
__device__ __forceinline__ void bar_sync(int id, int n) { asm volatile("bar.sync %0, %1;" ::"r"(id), "r"(n) : "memory"); }
__device__ __forceinline__ void bar_arrive(int id, int n) { asm volatile("bar.arrive %0, %1;" ::"r"(id), "r"(n) : "memory"); }
template <int NT>
__device__ __forceinline__ void fence_regs(float (&d)[NT]) {
#pragma unroll
  for (int i = 0; i < NT; i++) asm volatile("" : "+f"(d[i])::"memory");
}
template <int NT>
__device__ __forceinline__ void fence_regs(uint32_t (&d)[NT]) {
#pragma unroll
  for (int i = 0; i < NT; i++) asm volatile("" : "+r"(d[i])::"memory");
}
__device__ __forceinline__ uint64_t make_desc(uint32_t saddr, uint32_t lbo, uint32_t sbo, uint32_t layout) {
  return (uint64_t)((saddr & 0x3FFFF) >> 4) | ((uint64_t)(lbo >> 4) << 16) | ((uint64_t)(sbo >> 4) << 32) | ((uint64_t)layout << 62);
}
__device__ __forceinline__ uint32_t pack_bf16(float lo, float hi) {
  uint32_t r;
  asm("cvt.rn.bf16x2.f32 %0, %1, %2;" : "=r"(r) : "f"(hi), "f"(lo));
  return r;
}
__device__ __forceinline__ float ex2(float x) {
  float r;
  asm("ex2.approx.ftz.f32 %0, %1;" : "=f"(r) : "f"(x));
  return r;
}
__device__ __forceinline__ void st_v4(void* p, uint32_t a, uint32_t b, uint32_t c, uint32_t d) {
#define ST_MOD ".cs"
  asm volatile("st.global" ST_MOD ".v4.b32 [%0], {%1, %2, %3, %4};" ::"l"(p), "r"(a), "r"(b), "r"(c), "r"(d) : "memory");
}
#define STA_MOD ".cs"
__device__ __forceinline__ void st_v4a(void* p, uint32_t a, uint32_t b, uint32_t c, uint32_t d) {
  asm volatile("st.global" STA_MOD ".v4.b32 [%0], {%1, %2, %3, %4};" ::"l"(p), "r"(a), "r"(b), "r"(c), "r"(d) : "memory");
}
template <typename T>
__device__ __forceinline__ T* ptr_add(T* base, uint32_t bytes) {
  uint64_t r;
  asm volatile("{\n.reg .u32 l, h;\nmov.b64 {l, h}, %1;\nadd.cc.u32 l, l, %2;\naddc.u32 h, h, 0;\nmov.b64 %0, {l, h};\n}" : "=l"(r) : "l"(base), "r"(bytes));
  return reinterpret_cast<T*>(r);
}
__device__ __forceinline__ float bf_lo(uint32_t v) { return __uint_as_float(v << 16); }
__device__ __forceinline__ float bf_hi(uint32_t v) { return __uint_as_float(v & 0xFFFF0000u); }

__device__ __forceinline__ void quad_transpose(uint32_t& a0, uint32_t& a1, uint32_t& a2, uint32_t& a3, int q) {
  const bool o1 = q & 1, o2 = q & 2;
  uint32_t t0 = o1 ? a0 : a1, t1 = o1 ? a2 : a3;
  t0 = __shfl_xor_sync(0xffffffffu, t0, 1);
  t1 = __shfl_xor_sync(0xffffffffu, t1, 1);
  if (o1) { a0 = t0; a2 = t1; } else { a1 = t0; a3 = t1; }
  t0 = o2 ? a0 : a2;
  t1 = o2 ? a1 : a3;
  t0 = __shfl_xor_sync(0xffffffffu, t0, 2);
  t1 = __shfl_xor_sync(0xffffffffu, t1, 2);
  if (o2) { a0 = t0; a1 = t1; } else { a2 = t0; a3 = t1; }
}

template<int TB, int OFF, int NT>
__device__ __forceinline__ void wgmma_ss_n256(float (&d)[NT], uint64_t da, uint64_t db, int scale_d) {
  asm volatile("{\n.reg .pred p;\nsetp.ne.b32 p, %130, 0;\n"
    "wgmma.mma_async.sync.aligned.m64n256k16.f32.bf16.bf16 {%0, %1, %2, %3, %4, %5, %6, %7, %8, %9, %10, %11, %12, %13, %14, %15, %16, %17, %18, %19, %20, %21, %22, %23, %24, %25, %26, %27, %28, %29, %30, %31, %32, %33, %34, %35, %36, %37, %38, %39, %40, %41, %42, %43, %44, %45, %46, %47, %48, %49, %50, %51, %52, %53, %54, %55, %56, %57, %58, %59, %60, %61, %62, %63, %64, %65, %66, %67, %68, %69, %70, %71, %72, %73, %74, %75, %76, %77, %78, %79, %80, %81, %82, %83, %84, %85, %86, %87, %88, %89, %90, %91, %92, %93, %94, %95, %96, %97, %98, %99, %100, %101, %102, %103, %104, %105, %106, %107, %108, %109, %110, %111, %112, %113, %114, %115, %116, %117, %118, %119, %120, %121, %122, %123, %124, %125, %126, %127}, %128, %129, p, 1, 1, 0, %131;\n}\n"
    : "+f"(d[OFF+0]), "+f"(d[OFF+1]), "+f"(d[OFF+2]), "+f"(d[OFF+3]), "+f"(d[OFF+4]), "+f"(d[OFF+5]), "+f"(d[OFF+6]), "+f"(d[OFF+7]), "+f"(d[OFF+8]), "+f"(d[OFF+9]), "+f"(d[OFF+10]), "+f"(d[OFF+11]), "+f"(d[OFF+12]), "+f"(d[OFF+13]), "+f"(d[OFF+14]), "+f"(d[OFF+15]), "+f"(d[OFF+16]), "+f"(d[OFF+17]), "+f"(d[OFF+18]), "+f"(d[OFF+19]), "+f"(d[OFF+20]), "+f"(d[OFF+21]), "+f"(d[OFF+22]), "+f"(d[OFF+23]), "+f"(d[OFF+24]), "+f"(d[OFF+25]), "+f"(d[OFF+26]), "+f"(d[OFF+27]), "+f"(d[OFF+28]), "+f"(d[OFF+29]), "+f"(d[OFF+30]), "+f"(d[OFF+31]), "+f"(d[OFF+32]), "+f"(d[OFF+33]), "+f"(d[OFF+34]), "+f"(d[OFF+35]), "+f"(d[OFF+36]), "+f"(d[OFF+37]), "+f"(d[OFF+38]), "+f"(d[OFF+39]), "+f"(d[OFF+40]), "+f"(d[OFF+41]), "+f"(d[OFF+42]), "+f"(d[OFF+43]), "+f"(d[OFF+44]), "+f"(d[OFF+45]), "+f"(d[OFF+46]), "+f"(d[OFF+47]), "+f"(d[OFF+48]), "+f"(d[OFF+49]), "+f"(d[OFF+50]), "+f"(d[OFF+51]), "+f"(d[OFF+52]), "+f"(d[OFF+53]), "+f"(d[OFF+54]), "+f"(d[OFF+55]), "+f"(d[OFF+56]), "+f"(d[OFF+57]), "+f"(d[OFF+58]), "+f"(d[OFF+59]), "+f"(d[OFF+60]), "+f"(d[OFF+61]), "+f"(d[OFF+62]), "+f"(d[OFF+63]), "+f"(d[OFF+64]), "+f"(d[OFF+65]), "+f"(d[OFF+66]), "+f"(d[OFF+67]), "+f"(d[OFF+68]), "+f"(d[OFF+69]), "+f"(d[OFF+70]), "+f"(d[OFF+71]), "+f"(d[OFF+72]), "+f"(d[OFF+73]), "+f"(d[OFF+74]), "+f"(d[OFF+75]), "+f"(d[OFF+76]), "+f"(d[OFF+77]), "+f"(d[OFF+78]), "+f"(d[OFF+79]), "+f"(d[OFF+80]), "+f"(d[OFF+81]), "+f"(d[OFF+82]), "+f"(d[OFF+83]), "+f"(d[OFF+84]), "+f"(d[OFF+85]), "+f"(d[OFF+86]), "+f"(d[OFF+87]), "+f"(d[OFF+88]), "+f"(d[OFF+89]), "+f"(d[OFF+90]), "+f"(d[OFF+91]), "+f"(d[OFF+92]), "+f"(d[OFF+93]), "+f"(d[OFF+94]), "+f"(d[OFF+95]), "+f"(d[OFF+96]), "+f"(d[OFF+97]), "+f"(d[OFF+98]), "+f"(d[OFF+99]), "+f"(d[OFF+100]), "+f"(d[OFF+101]), "+f"(d[OFF+102]), "+f"(d[OFF+103]), "+f"(d[OFF+104]), "+f"(d[OFF+105]), "+f"(d[OFF+106]), "+f"(d[OFF+107]), "+f"(d[OFF+108]), "+f"(d[OFF+109]), "+f"(d[OFF+110]), "+f"(d[OFF+111]), "+f"(d[OFF+112]), "+f"(d[OFF+113]), "+f"(d[OFF+114]), "+f"(d[OFF+115]), "+f"(d[OFF+116]), "+f"(d[OFF+117]), "+f"(d[OFF+118]), "+f"(d[OFF+119]), "+f"(d[OFF+120]), "+f"(d[OFF+121]), "+f"(d[OFF+122]), "+f"(d[OFF+123]), "+f"(d[OFF+124]), "+f"(d[OFF+125]), "+f"(d[OFF+126]), "+f"(d[OFF+127])
    : "l"(da), "l"(db), "r"(scale_d), "n"(TB));
}
template<int TB, int OFF, int NT>
__device__ __forceinline__ void wgmma_ss_n32(float (&d)[NT], uint64_t da, uint64_t db, int scale_d) {
  asm volatile("{\n.reg .pred p;\nsetp.ne.b32 p, %18, 0;\n"
    "wgmma.mma_async.sync.aligned.m64n32k16.f32.bf16.bf16 {%0, %1, %2, %3, %4, %5, %6, %7, %8, %9, %10, %11, %12, %13, %14, %15}, %16, %17, p, 1, 1, 0, %19;\n}\n"
    : "+f"(d[OFF+0]), "+f"(d[OFF+1]), "+f"(d[OFF+2]), "+f"(d[OFF+3]), "+f"(d[OFF+4]), "+f"(d[OFF+5]), "+f"(d[OFF+6]), "+f"(d[OFF+7]), "+f"(d[OFF+8]), "+f"(d[OFF+9]), "+f"(d[OFF+10]), "+f"(d[OFF+11]), "+f"(d[OFF+12]), "+f"(d[OFF+13]), "+f"(d[OFF+14]), "+f"(d[OFF+15])
    : "l"(da), "l"(db), "r"(scale_d), "n"(TB));
}
template<int TB, int OFF, int NT>
__device__ __forceinline__ void wgmma_rs_n128(float (&d)[NT], uint32_t a0, uint32_t a1, uint32_t a2, uint32_t a3, uint64_t db, int scale_d) {
  asm volatile("{\n.reg .pred p;\nsetp.ne.b32 p, %69, 0;\n"
    "wgmma.mma_async.sync.aligned.m64n128k16.f32.bf16.bf16 {%0, %1, %2, %3, %4, %5, %6, %7, %8, %9, %10, %11, %12, %13, %14, %15, %16, %17, %18, %19, %20, %21, %22, %23, %24, %25, %26, %27, %28, %29, %30, %31, %32, %33, %34, %35, %36, %37, %38, %39, %40, %41, %42, %43, %44, %45, %46, %47, %48, %49, %50, %51, %52, %53, %54, %55, %56, %57, %58, %59, %60, %61, %62, %63}, {%64, %65, %66, %67}, %68, p, 1, 1, %70;\n}\n"
    : "+f"(d[OFF+0]), "+f"(d[OFF+1]), "+f"(d[OFF+2]), "+f"(d[OFF+3]), "+f"(d[OFF+4]), "+f"(d[OFF+5]), "+f"(d[OFF+6]), "+f"(d[OFF+7]), "+f"(d[OFF+8]), "+f"(d[OFF+9]), "+f"(d[OFF+10]), "+f"(d[OFF+11]), "+f"(d[OFF+12]), "+f"(d[OFF+13]), "+f"(d[OFF+14]), "+f"(d[OFF+15]), "+f"(d[OFF+16]), "+f"(d[OFF+17]), "+f"(d[OFF+18]), "+f"(d[OFF+19]), "+f"(d[OFF+20]), "+f"(d[OFF+21]), "+f"(d[OFF+22]), "+f"(d[OFF+23]), "+f"(d[OFF+24]), "+f"(d[OFF+25]), "+f"(d[OFF+26]), "+f"(d[OFF+27]), "+f"(d[OFF+28]), "+f"(d[OFF+29]), "+f"(d[OFF+30]), "+f"(d[OFF+31]), "+f"(d[OFF+32]), "+f"(d[OFF+33]), "+f"(d[OFF+34]), "+f"(d[OFF+35]), "+f"(d[OFF+36]), "+f"(d[OFF+37]), "+f"(d[OFF+38]), "+f"(d[OFF+39]), "+f"(d[OFF+40]), "+f"(d[OFF+41]), "+f"(d[OFF+42]), "+f"(d[OFF+43]), "+f"(d[OFF+44]), "+f"(d[OFF+45]), "+f"(d[OFF+46]), "+f"(d[OFF+47]), "+f"(d[OFF+48]), "+f"(d[OFF+49]), "+f"(d[OFF+50]), "+f"(d[OFF+51]), "+f"(d[OFF+52]), "+f"(d[OFF+53]), "+f"(d[OFF+54]), "+f"(d[OFF+55]), "+f"(d[OFF+56]), "+f"(d[OFF+57]), "+f"(d[OFF+58]), "+f"(d[OFF+59]), "+f"(d[OFF+60]), "+f"(d[OFF+61]), "+f"(d[OFF+62]), "+f"(d[OFF+63])
    : "r"(a0), "r"(a1), "r"(a2), "r"(a3), "l"(db), "r"(scale_d), "n"(TB));
}
template<int TB, int OFF, int NT>
__device__ __forceinline__ void wgmma_rs_n256(float (&d)[NT], uint32_t a0, uint32_t a1, uint32_t a2, uint32_t a3, uint64_t db, int scale_d) {
  asm volatile("{\n.reg .pred p;\nsetp.ne.b32 p, %133, 0;\n"
    "wgmma.mma_async.sync.aligned.m64n256k16.f32.bf16.bf16 {%0, %1, %2, %3, %4, %5, %6, %7, %8, %9, %10, %11, %12, %13, %14, %15, %16, %17, %18, %19, %20, %21, %22, %23, %24, %25, %26, %27, %28, %29, %30, %31, %32, %33, %34, %35, %36, %37, %38, %39, %40, %41, %42, %43, %44, %45, %46, %47, %48, %49, %50, %51, %52, %53, %54, %55, %56, %57, %58, %59, %60, %61, %62, %63, %64, %65, %66, %67, %68, %69, %70, %71, %72, %73, %74, %75, %76, %77, %78, %79, %80, %81, %82, %83, %84, %85, %86, %87, %88, %89, %90, %91, %92, %93, %94, %95, %96, %97, %98, %99, %100, %101, %102, %103, %104, %105, %106, %107, %108, %109, %110, %111, %112, %113, %114, %115, %116, %117, %118, %119, %120, %121, %122, %123, %124, %125, %126, %127}, {%128, %129, %130, %131}, %132, p, 1, 1, %134;\n}\n"
    : "+f"(d[OFF+0]), "+f"(d[OFF+1]), "+f"(d[OFF+2]), "+f"(d[OFF+3]), "+f"(d[OFF+4]), "+f"(d[OFF+5]), "+f"(d[OFF+6]), "+f"(d[OFF+7]), "+f"(d[OFF+8]), "+f"(d[OFF+9]), "+f"(d[OFF+10]), "+f"(d[OFF+11]), "+f"(d[OFF+12]), "+f"(d[OFF+13]), "+f"(d[OFF+14]), "+f"(d[OFF+15]), "+f"(d[OFF+16]), "+f"(d[OFF+17]), "+f"(d[OFF+18]), "+f"(d[OFF+19]), "+f"(d[OFF+20]), "+f"(d[OFF+21]), "+f"(d[OFF+22]), "+f"(d[OFF+23]), "+f"(d[OFF+24]), "+f"(d[OFF+25]), "+f"(d[OFF+26]), "+f"(d[OFF+27]), "+f"(d[OFF+28]), "+f"(d[OFF+29]), "+f"(d[OFF+30]), "+f"(d[OFF+31]), "+f"(d[OFF+32]), "+f"(d[OFF+33]), "+f"(d[OFF+34]), "+f"(d[OFF+35]), "+f"(d[OFF+36]), "+f"(d[OFF+37]), "+f"(d[OFF+38]), "+f"(d[OFF+39]), "+f"(d[OFF+40]), "+f"(d[OFF+41]), "+f"(d[OFF+42]), "+f"(d[OFF+43]), "+f"(d[OFF+44]), "+f"(d[OFF+45]), "+f"(d[OFF+46]), "+f"(d[OFF+47]), "+f"(d[OFF+48]), "+f"(d[OFF+49]), "+f"(d[OFF+50]), "+f"(d[OFF+51]), "+f"(d[OFF+52]), "+f"(d[OFF+53]), "+f"(d[OFF+54]), "+f"(d[OFF+55]), "+f"(d[OFF+56]), "+f"(d[OFF+57]), "+f"(d[OFF+58]), "+f"(d[OFF+59]), "+f"(d[OFF+60]), "+f"(d[OFF+61]), "+f"(d[OFF+62]), "+f"(d[OFF+63]), "+f"(d[OFF+64]), "+f"(d[OFF+65]), "+f"(d[OFF+66]), "+f"(d[OFF+67]), "+f"(d[OFF+68]), "+f"(d[OFF+69]), "+f"(d[OFF+70]), "+f"(d[OFF+71]), "+f"(d[OFF+72]), "+f"(d[OFF+73]), "+f"(d[OFF+74]), "+f"(d[OFF+75]), "+f"(d[OFF+76]), "+f"(d[OFF+77]), "+f"(d[OFF+78]), "+f"(d[OFF+79]), "+f"(d[OFF+80]), "+f"(d[OFF+81]), "+f"(d[OFF+82]), "+f"(d[OFF+83]), "+f"(d[OFF+84]), "+f"(d[OFF+85]), "+f"(d[OFF+86]), "+f"(d[OFF+87]), "+f"(d[OFF+88]), "+f"(d[OFF+89]), "+f"(d[OFF+90]), "+f"(d[OFF+91]), "+f"(d[OFF+92]), "+f"(d[OFF+93]), "+f"(d[OFF+94]), "+f"(d[OFF+95]), "+f"(d[OFF+96]), "+f"(d[OFF+97]), "+f"(d[OFF+98]), "+f"(d[OFF+99]), "+f"(d[OFF+100]), "+f"(d[OFF+101]), "+f"(d[OFF+102]), "+f"(d[OFF+103]), "+f"(d[OFF+104]), "+f"(d[OFF+105]), "+f"(d[OFF+106]), "+f"(d[OFF+107]), "+f"(d[OFF+108]), "+f"(d[OFF+109]), "+f"(d[OFF+110]), "+f"(d[OFF+111]), "+f"(d[OFF+112]), "+f"(d[OFF+113]), "+f"(d[OFF+114]), "+f"(d[OFF+115]), "+f"(d[OFF+116]), "+f"(d[OFF+117]), "+f"(d[OFF+118]), "+f"(d[OFF+119]), "+f"(d[OFF+120]), "+f"(d[OFF+121]), "+f"(d[OFF+122]), "+f"(d[OFF+123]), "+f"(d[OFF+124]), "+f"(d[OFF+125]), "+f"(d[OFF+126]), "+f"(d[OFF+127])
    : "r"(a0), "r"(a1), "r"(a2), "r"(a3), "l"(db), "r"(scale_d), "n"(TB));
}
template<int TB, int OFF, int NT>
__device__ __forceinline__ void wgmma_rs_n32(float (&d)[NT], uint32_t a0, uint32_t a1, uint32_t a2, uint32_t a3, uint64_t db, int scale_d) {
  asm volatile("{\n.reg .pred p;\nsetp.ne.b32 p, %21, 0;\n"
    "wgmma.mma_async.sync.aligned.m64n32k16.f32.bf16.bf16 {%0, %1, %2, %3, %4, %5, %6, %7, %8, %9, %10, %11, %12, %13, %14, %15}, {%16, %17, %18, %19}, %20, p, 1, 1, %22;\n}\n"
    : "+f"(d[OFF+0]), "+f"(d[OFF+1]), "+f"(d[OFF+2]), "+f"(d[OFF+3]), "+f"(d[OFF+4]), "+f"(d[OFF+5]), "+f"(d[OFF+6]), "+f"(d[OFF+7]), "+f"(d[OFF+8]), "+f"(d[OFF+9]), "+f"(d[OFF+10]), "+f"(d[OFF+11]), "+f"(d[OFF+12]), "+f"(d[OFF+13]), "+f"(d[OFF+14]), "+f"(d[OFF+15])
    : "r"(a0), "r"(a1), "r"(a2), "r"(a3), "l"(db), "r"(scale_d), "n"(TB));
}

__device__ __forceinline__ void wait_flag(const unsigned int* f, uint32_t target) {
  uint32_t v;
#pragma unroll 1
  for (uint32_t spins = 0; spins < (1u << 22); spins++) {
    asm volatile("ld.acquire.gpu.global.u32 %0, [%1];" : "=r"(v) : "l"(f) : "memory");
    if (v >= target) break;
    __nanosleep(100);
  }
}
__device__ __forceinline__ uint32_t ld_and2(const unsigned int* f) {
  uint32_t v;
  asm volatile("{\n.reg .b64 t;\n.reg .b32 a, b;\nld.acquire.gpu.global.b64 t, [%1];\nmov.b64 {a, b}, t;\nand.b32 %0, a, b;\n}" : "=r"(v) : "l"(f) : "memory");
  return v;
}
__device__ __forceinline__ uint32_t lds32(uint32_t a) {
  uint32_t v;
  asm volatile("ld.shared.u32 %0, [%1];" : "=r"(v) : "r"(a) : "memory");
  return v;
}
__device__ __forceinline__ float gate_row(int row, int lane, const bf16* __restrict__ x, const bf16* __restrict__ gate_w) {
  const uint32_t* xr = reinterpret_cast<const uint32_t*>(x + (size_t)row * DM);
  const uint32_t* gw2 = reinterpret_cast<const uint32_t*>(gate_w);
  float gs = 0.f;
#pragma unroll
  for (int i = 0; i < 9; i++) {
    const uint32_t a = __ldg(xr + lane + 32 * i), b = __ldg(gw2 + lane + 32 * i);
    gs = fmaf(bf_lo(a), bf_lo(b), gs);
    gs = fmaf(bf_hi(a), bf_hi(b), gs);
  }
#pragma unroll
  for (int o = 16; o; o >>= 1) gs += __shfl_xor_sync(0xffffffffu, gs, o);
  const float g = 1.f / (1.f + __expf(-gs));
  if (lane == 0) g_gate[row] = g;
  return g;
}
constexpr uint32_t LQ = 36864, LV = 55296;
__device__ __forceinline__ void mma16(float (&c)[4], uint32_t a0, uint32_t a1, uint32_t a2, uint32_t a3, uint32_t b0, uint32_t b1) {
  asm("mma.sync.aligned.m16n8k16.row.col.f32.bf16.bf16.f32 {%0, %1, %2, %3}, {%4, %5, %6, %7}, {%8, %9}, {%0, %1, %2, %3};"
      : "+f"(c[0]), "+f"(c[1]), "+f"(c[2]), "+f"(c[3]) : "r"(a0), "r"(a1), "r"(a2), "r"(a3), "r"(b0), "r"(b1));
}
__device__ __forceinline__ void mma8(float (&c)[4], uint32_t a0, uint32_t a1, uint32_t b0) {
  asm("mma.sync.aligned.m16n8k8.row.col.f32.bf16.bf16.f32 {%0, %1, %2, %3}, {%4, %5}, {%6}, {%0, %1, %2, %3};"
      : "+f"(c[0]), "+f"(c[1]), "+f"(c[2]), "+f"(c[3]) : "r"(a0), "r"(a1), "r"(b0));
}
template <typename F>
__device__ __forceinline__ void local_attn(int lr0, int warp_g, uint32_t sL, uint32_t bL, uint32_t bL2, int lane, float g0, float g1, F st) {
  const float scale_l2 = 0.23570226039551584f * 1.4426950408889634f;
  const int g = lane >> 2, t = lane & 3;
  const bool lo0 = 2 * t > g, lo1 = 2 * t + 1 > g;
  const bool ok0 = lr0 > 0 || !lo0, ok1 = lr0 > 0 || !lo1;
  const uint32_t mlo = (lo0 ? 0xFFFFu : 0u) | (lo1 ? 0xFFFF0000u : 0u);
  uint32_t ad[9], k[9][4], qf[9][2], pe[4], po[4];
#pragma unroll
  for (int c = 0; c < 9; c++) {
    const uint32_t ch = warp_g * 9 + c;
    ad[c] = sL + (lane >> 4) * 18432 + (lane & 15) * 128 + ((ch >> 3) << 11) + (((ch ^ lane) & 7) << 4);
  }
  st(0, 0u); st(1, 0u);
  mbar_wait(bL, 0);
  if (warp_g == 0) TS(1, 6);
#pragma unroll
  for (int c = 0; c < 9; c++) {
    asm volatile("ldmatrix.sync.aligned.m8n8.x2.shared.b16 {%0, %1}, [%2];" : "=r"(qf[c][0]), "=r"(qf[c][1]) : "r"(ad[c] + LQ) : "memory");
    ldsm_x4(k[c][0], k[c][1], k[c][2], k[c][3], ad[c]);
  }
  st(2, k[0][0]); st(3, k[8][0]);
#pragma unroll
  for (int i = 0; i < 4; i++) {
    const uint32_t q0 = (t >= i) ? qf[2 * i][0] : 0u, q1 = (t >= i) ? qf[2 * i][1] : 0u;
    const uint32_t q4 = (t <= i) ? qf[2 * i + 2][0] : 0u, q5 = (t <= i) ? qf[2 * i + 2][1] : 0u;
    float c[4][4];
#pragma unroll
    for (int T = 0; T < 4; T++) {
#pragma unroll
      for (int j = 0; j < 4; j++) c[T][j] = 0.f;
      mma16(c[T], q0, q1, qf[2 * i + 1][0], qf[2 * i + 1][1], k[2 * i][T], k[2 * i + 1][T]);
      mma8(c[T], q4, q5, k[2 * i + 2][T]);
    }
    const float e0 = ok0 ? (lo0 ? c[0][0] : c[1][0]) : -INFINITY, e1 = ok1 ? (lo1 ? c[0][1] : c[1][1]) : -INFINITY;
    const float o0 = ok0 ? (lo0 ? c[2][2] : c[3][2]) : -INFINITY, o1 = ok1 ? (lo1 ? c[2][3] : c[3][3]) : -INFINITY;
    float me = fmaxf(e0, e1), mo = fmaxf(o0, o1);
    me = fmaxf(me, __shfl_xor_sync(0xffffffffu, me, 1));
    mo = fmaxf(mo, __shfl_xor_sync(0xffffffffu, mo, 1));
    me = fmaxf(me, __shfl_xor_sync(0xffffffffu, me, 2)) * scale_l2;
    mo = fmaxf(mo, __shfl_xor_sync(0xffffffffu, mo, 2)) * scale_l2;
    const float w0 = ex2(fmaf(e0, scale_l2, -me)), w1 = ex2(fmaf(e1, scale_l2, -me));
    const float w2 = ex2(fmaf(o0, scale_l2, -mo)), w3 = ex2(fmaf(o1, scale_l2, -mo));
    float se = w0 + w1, so = w2 + w3;
    st(4 + 2 * i, __float_as_uint(i == 1 ? me : i == 2 ? se : e0));
    se += __shfl_xor_sync(0xffffffffu, se, 1);
    so += __shfl_xor_sync(0xffffffffu, so, 1);
    se += __shfl_xor_sync(0xffffffffu, se, 2);
    so += __shfl_xor_sync(0xffffffffu, so, 2);
    asm("rcp.approx.ftz.f32 %0, %0;" : "+f"(se));
    asm("rcp.approx.ftz.f32 %0, %0;" : "+f"(so));
    se *= g0;
    so *= g1;
    pe[i] = pack_bf16(w0 * se, w1 * se);
    po[i] = pack_bf16(w2 * so, w3 * so);
    st(5 + 2 * i, i == 0 ? __float_as_uint(w0) : i == 2 ? __float_as_uint(mo) : po[i]);
  }
  if (warp_g == 0) TS(0, 4);
  mbar_wait(bL2, 0);
  if (warp_g == 0) TS(0, 5);
#pragma unroll
  for (int c = 0; c < 9; c++)
    asm volatile("ldmatrix.sync.aligned.m8n8.x4.trans.shared.b16 {%0, %1, %2, %3}, [%4];"
                 : "=r"(k[c][0]), "=r"(k[c][1]), "=r"(k[c][2]), "=r"(k[c][3]) : "r"(ad[c] + LV) : "memory");
#pragma unroll
  for (int i = 0; i < 4; i++) {
#pragma unroll
    for (int n = 0; n < 3; n++) {
      float c[4] = {0.f, 0.f, 0.f, 0.f};
      mma16(c, pe[i] & mlo, 0u, pe[i] & ~mlo, 0u, k[2 * i + n][0], k[2 * i + n][1]);
      mma16(c, 0u, po[i] & mlo, 0u, po[i] & ~mlo, k[2 * i + n][2], k[2 * i + n][3]);
      const uint32_t r0 = pack_bf16(c[0], c[1]), r1 = pack_bf16(c[2], c[3]);
      const bool keep = (n == 0) && (i > 0) && (t < i);
      qf[2 * i + n][0] = keep ? qf[2 * i + n][0] : r0;
      qf[2 * i + n][1] = keep ? qf[2 * i + n][1] : r1;
    }
    st(12 + i, qf[2 * i + 1][0]);
  }
#pragma unroll
  for (int c = 0; c < 9; c++)
    asm volatile("stmatrix.sync.aligned.m8n8.x2.shared.b16 [%0], {%1, %2};" ::"r"(ad[c] + LQ), "r"(qf[c][0]), "r"(qf[c][1]) : "memory");
  asm volatile("fence.proxy.async.shared::cta;" ::: "memory");
}
__device__ __forceinline__ void tma4d(uint32_t dst, const CUtensorMap* m, uint32_t bar, int c1, int c2, int c3) {
  asm volatile("cp.async.bulk.tensor.4d.shared::cluster.global.mbarrier::complete_tx::bytes [%0], [%1, {%3, %4, %5, %6}], [%2];" ::"r"(dst),
               "l"(m), "r"(bar), "r"(0), "r"(c1), "r"(c2), "r"(c3) : "memory");
}

#define ST_NUM 1
#define ST_DEN 2
#define K1_NST 6
constexpr int K1_BST = K1_NST;
#define MAXJ 11
constexpr int K1_MAXJOBS = MAXJ;
constexpr uint32_t K1_FLAG_TARGET = 7;
constexpr uint32_t RDY_TARGET = 48;
constexpr uint32_t GATE_TARGET = 128 * 3;
struct alignas(64) Params {
  CUtensorMap tmA[2];
  CUtensorMap tmW[4];
  uint16_t jobs[NCLUSTER][K1_MAXJOBS + 1];
  CUtensorMap tmK, tmV, tmQ;
  CUtensorMap tmL[3];
  CUtensorMap tmC, tmO[2], tmOt[2];
  CUtensorMap tmR[2];
  uint8_t order[256];
  uint8_t unit[66][4];
};

struct K1State {
  uint32_t bs, bph, aph;
  bf16* pp;
  int png;
  int tn;
  int wsel;
  uint32_t fo;
};
__device__ __forceinline__ void k1_flag(const K1State& st, int lane, uint32_t bS) {
  if (st.png) {
    __syncwarp();
    if (lane == 0) mbar_arrive(bS + st.fo);
  }
}

__device__ __forceinline__ void scale_q4(uint32_t* v) {
#pragma unroll
  for (int i = 0; i < 4; i++)
    asm volatile("{\n.reg .b32 t;\nmul.rn.bf16x2 t, %0, %2;\nfma.rn.bf16x2 %0, %0, %1, t;\n}" : "+r"(v[i]) : "r"(0x3E033E03u), "r"(0xB9D8B9D8u));
}
__device__ __forceinline__ void k1_first(const K1State& st, uint32_t job, uint32_t bAf, uint32_t bBf) {
  if (job & 3) {
    if ((job >> 14) & 1) mbar_wait(bAf, st.aph);
    mbar_wait(bBf + st.bs * 8, st.bph);
  }
}
__device__ __forceinline__ void k1_tile(float (&acc)[128], uint32_t (&pk)[64], K1State& st, uint32_t job, uint32_t njob, uint32_t sA, uint32_t sB,
                                        uint32_t bAf, uint32_t bAe, uint32_t bBf, uint32_t bBe, uint32_t bS, int wg, int warp, int lane, uint32_t rank) {
  const int a_sel = (job >> 2) & 1, mpair = (job >> 3) & 7, w_sel = (job >> 6) & 3, chunk0 = (job >> 8) & 63;
  const bool newA = (job >> 14) & 1, lastA = (job >> 15) & 1;
  const bool sig = (lane == 0) && (warp < 2);
  const bool siga = lastA && (lane == 0) && (warp == 2);
  const int KC = 8 + a_sel;
  uint32_t prev_bs = 0, a8_bs = 0;
#pragma unroll
  for (int kc = 0; kc < 9; kc++) {
    if (kc >= KC) break;
    uint32_t abase = sA + ((kc + 2) & 7) * 16384;
    if (kc == 8) {
      mbar_wait(bBf + st.bs * 8, st.bph);
      a8_bs = st.bs;
      abase = sB + st.bs * 16384;
      if (++st.bs == K1_BST) { st.bs = 0; st.bph ^= 1; }
    } else if (newA && kc > 0) {
      mbar_wait(bAf + kc * 8, st.aph);
    }
    const uint64_t da = make_desc(abase + wg * 8192, 16, 1024, 1);
#pragma unroll
    for (int ks = 0; ks < 2; ks++) {
      if (ks > 0 || kc > 0) mbar_wait(bBf + st.bs * 8, st.bph);
      const uint64_t db = make_desc(sB + st.bs * 16384, 2048, 1024, 1);
      wg_fence();
      wgmma_ss_n256<1, 0>(acc, da + (uint64_t)(ks * 4), db, (ks > 0) ? 1 : (kc > 0));
      wgmma_ss_n256<1, 0>(acc, da + (uint64_t)(ks * 4 + 2), db + (uint64_t)512, 1);
      wg_commit();
      wg_wait<1>();
      if (ks > 0 || kc > 0) {
        if (sig) mbar_arrive_cluster(bBe + prev_bs * 8, warp);
        if (ks == 0 && siga) mbar_arrive(bAe + (kc - 1) * 8);
      }
      if (st.wsel == 2) {
        const int i = (kc & 7) * 2 + ks;
        if (kc < st.png) {
          quad_transpose(pk[i * 4], pk[i * 4 + 1], pk[i * 4 + 2], pk[i * 4 + 3], lane & 3);
          st_v4a(st.pp + goff(kc, ks), pk[i * 4], pk[i * 4 + 1], pk[i * 4 + 2], pk[i * 4 + 3]);
        }
        if (i == 15) k1_flag(st, lane, bS);
      } else if (st.png) {
#pragma unroll
        for (int i = 0; i < 16; i++) {
          if (i * ST_NUM / ST_DEN != kc * 2 + ks) continue;
          if (st.wsel == 3) scale_q4(pk + i * 4);
          st_v4a(st.pp + goff(i / 2, i & 1), pk[i * 4], pk[i * 4 + 1], pk[i * 4 + 2], pk[i * 4 + 3]);
          if (i == 15) k1_flag(st, lane, bS);
        }
      }
      prev_bs = st.bs;
      if (++st.bs == K1_BST) { st.bs = 0; st.bph ^= 1; }
    }
  }
  if (newA) st.aph ^= 1;
  const bool isA = (w_sel == 2);
  bf16* out = (w_sel == 0) ? g_K : (w_sel == 1) ? g_V : isA ? g_QKVA : g_ctx;
  const int row = mpair * 256 + rank * 128 + wg * 64 + warp * 16 + (lane >> 2);
  st.pp = ptr_add(out, (chunk0 * S_LEN + row) * 128 + (lane & 3) * 16);
  st.png = ((job & 3) + 1) * 2;
  st.wsel = w_sel;
  st.fo = (st.fo + 8) & 24;
  k1_first(st, njob, bAf, bBf);
  wg_wait<0>();
  fence_regs(acc);
  mbar_arrive_cluster_if(bBe + prev_bs * 8, warp & 1, sig);
  mbar_arrive_cluster_if(bBe + a8_bs * 8, warp & 1, sig && a_sel);
  mbar_arrive_if(bAe + 7 * 8, siga && !a_sel);
#pragma unroll
  for (int i = 0; i < 64; i++) {
    const int j = (i >> 3) * 16 + (i & 3) * 4 + ((i >> 2) & 1) * 2;
    pk[i] = pack_bf16(acc[j], acc[j + 1]);
  }
}

constexpr int K2_NST = 7;
constexpr uint32_t K2_END = 0x100;
#define PFD 4
#define PF3A 2
#define PF3 6
#define KC0 1
constexpr uint32_t CR = 4;
#define FIRST_DRAW 3
#define PWAIT mbar_wait_ns<1000>
#define PVM 0x8A
#define W0 63
#define SPEC_HI 1.8446744073709552e19f
#define SPEC_LO 5.421010862427522e-20f
constexpr int K3_NST = 4;
#define K3_NS 6
__device__ __forceinline__ uint32_t k3_rot(uint32_t sv) { return (0x00E9u >> (2 * sv)) & 3; }
constexpr int K3_STAGE = 16384 + 32768 + 4096;
constexpr int SMEM_DATA = 7 * 32768;
constexpr int SMEM_BYTES = SMEM_DATA + 1024 + 896;

struct Cursor {
  uint32_t s, ph;
  __device__ __forceinline__ void next() {
    if (++s == K2_NST) { s = 0; ph ^= 1; }
  }
};

#define TURN_SYNC() bar_sync(mybar, 256)
#define TURN_ARRIVE() bar_arrive(otherbar, 256)
#define RELEASE_IF(cur, cond) mbar_arrive_cluster_if(bE + (cur).s * 8, warp & 1, sig && (cond))
#define RELEASE(cur) RELEASE_IF(cur, true)
#define ISSUE_PV(cur, first)                                                                                   \
  do {                                                                                                         \
    const uint64_t dv = make_desc(sbase + (cur).s * 32768, 16384, 1024, 1);                                    \
    _Pragma("unroll") for (int t = 0; t < 8; t++)                                                              \
        wgmma_rs_n128<1, 0>(O, P[4 * t], P[4 * t + 1], P[4 * t + 2], P[4 * t + 3], dv + (uint64_t)(t * 128), (t > 0) ? 1 : !(first)); \
  } while (0)
#define ISSUE_QK(cur)                                                                                          \
  do {                                                                                                         \
    const uint64_t dk = make_desc(sbase + (cur).s * 32768, 16, 1024, 1);                                       \
    _Pragma("unroll") for (int t = 0; t < 8; t++)                                                              \
        wgmma_rs_n128<0, 0>(S, Q[4 * t], Q[4 * t + 1], Q[4 * t + 2], Q[4 * t + 3], dk + (uint64_t)((t >> 2) * 1024 + (t & 3) * 2), t > 0); \
  } while (0)
#define LOAD_Q()                                                                                               \
  do {                                                                                                         \
    item = lds32(sItem + (it & 7) * 4);                                                                        \
    const uint32_t qa = sbase + cq.s * 32768 + (wg * 64 + warp * 16 + (lane & 15)) * 128;                      \
    _Pragma("unroll") for (int t = 0; t < 8; t++)                                                              \
        ldsm_x4(Q[4 * t], Q[4 * t + 1], Q[4 * t + 2], Q[4 * t + 3], qa + (t >> 2) * 16384 + ((((t & 3) * 2 + (lane >> 4)) ^ (lane & 7)) << 4)); \
  } while (0)
#define NEW_ITEM()                                                                                             \
  do {                                                                                                         \
    const int row = (2 * (item & 7) + hi) * 128 + (rank ^ hi) * 64 + warp * 16 + (lane >> 2);                  \
    eoff = ((item >> 3) * 2 * S_LEN + row) * 128 + q * 16;                                                     \
    const float* gp = ptr_add(g_gate, row * 4);                                                                \
    asm volatile("ld.global.f32 %0, [%1];" : "=f"(gf0) : "l"(gp));                                             \
    asm volatile("ld.global.f32 %0, [%1];" : "=f"(gf1) : "l"(gp + 8));                                         \
    if (!hi) {                                                                                                 \
      mbar_wait2(bF + cs0.s * 8, cs0.ph, bF + cs1.s * 8, cs1.ph);                                              \
      RELEASE(cs0);                                                                                            \
      RELEASE(cs1);                                                                                            \
    }                                                                                                          \
  } while (0)
#define EXPB(T)                                                                                                \
  do {                                                                                                         \
    _Pragma("unroll") for (int i = 4 * T; i < 4 * T + 4; i++) asm volatile("" : "+r"(P[i])::"memory");        \
    _Pragma("unroll") for (int jj = 2 * T; jj < 2 * T + 2; jj++) {                                             \
      const float e0 = ex2(S[jj * 4 + 0]), e1 = ex2(S[jj * 4 + 1]), e2 = ex2(S[jj * 4 + 2]), e3 = ex2(S[jj * 4 + 3]); \
      s0 += e0 + e1;                                                                                           \
      s1 += e2 + e3;                                                                                           \
      P[jj * 2 + 0] = pack_bf16(e0, e1);                                                                       \
      P[jj * 2 + 1] = pack_bf16(e2, e3);                                                                       \
    }                                                                                                          \
  } while (0)
#define EXPC(T)                                                                                                \
  do {                                                                                                         \
    if (T > 0 && ((PVM >> (T - 1)) & 1)) {                                                                     \
      anchor((T & 2) ? s0 : s1, never);                                                                        \
      wg_wait<__builtin_popcount(PVM >> T) - 1>();                                                             \
      if ((PVM >> T) == (128 >> T)) { fence_regs(O); RELEASE(cv); }                                            \
    }                                                                                                          \
    EXPB(T);                                                                                                   \
  } while (0)
#define MASK(G, g)                                                                                             \
  do {                                                                                                         \
    if ((g) * 8 > d) S[(G) * 4 + 0] = -INFINITY;                                                               \
    if ((g) * 8 + 1 > d) S[(G) * 4 + 1] = -INFINITY;                                                           \
    if ((g) * 8 - 8 > d) S[(G) * 4 + 2] = -INFINITY;                                                           \
    if ((g) * 8 - 7 > d) S[(G) * 4 + 3] = -INFINITY;                                                           \
  } while (0)
#define STORE_O(G)                                                                                             \
  do {                                                                                                         \
    st_v4(optr + goff(G, 0), pack_bf16(O[(G) * 16 + 0] * f0, O[(G) * 16 + 1] * f0), pack_bf16(O[(G) * 16 + 4] * f0, O[(G) * 16 + 5] * f0), \
          pack_bf16(O[(G) * 16 + 8] * f0, O[(G) * 16 + 9] * f0), pack_bf16(O[(G) * 16 + 12] * f0, O[(G) * 16 + 13] * f0)); \
    st_v4(optr + goff(G, 1), pack_bf16(O[(G) * 16 + 2] * f1, O[(G) * 16 + 3] * f1), pack_bf16(O[(G) * 16 + 6] * f1, O[(G) * 16 + 7] * f1), \
          pack_bf16(O[(G) * 16 + 10] * f1, O[(G) * 16 + 11] * f1), pack_bf16(O[(G) * 16 + 14] * f1, O[(G) * 16 + 15] * f1)); \
  } while (0)

#define FLUSH()                                                                                                \
  do {                                                                                                         \
    _Pragma("unroll") for (int G = 0; G < 8; G++) {                                                            \
      st_v4a(st.pp + goff(G, 0), pk[G * 8], pk[G * 8 + 1], pk[G * 8 + 2], pk[G * 8 + 3]);                          \
      st_v4a(st.pp + goff(G, 1), pk[G * 8 + 4], pk[G * 8 + 5], pk[G * 8 + 6], pk[G * 8 + 7]);                     \
    }                                                                                                          \
    k1_flag(st, lane, bS);                                                                                     \
  } while (0)

__global__ void __cluster_dims__(2, 1, 1) __launch_bounds__(384, 1)
fused_kernel(const __grid_constant__ Params p, const bf16* __restrict__ x, const bf16* __restrict__ gate_w, bf16* __restrict__ out) {
  extern __shared__ uint8_t smem_raw[];
  const uint32_t sbase = (smem_u32(smem_raw) + 1023) & ~1023u;
  const uint32_t sB = sbase, sA = sbase + K1_BST * 16384, sBar = sbase + SMEM_DATA;
  const uint32_t bAf = sBar, bAe = sBar + 64, bBf = sBar + 128, bBe = sBar + 176, bL = sBar + 224, bS = sBar + 656, bL2 = sBar + 240, sL = sA + 32768;
  const uint32_t bF = sBar + 256, bE = sBar + 320, bT = sBar + 384, sTick = sBar + 400, sItem = sBar + 416, bS2 = sBar + 688, bR = sBar + 456, bLast = sBar + 464, bH = sBar + 472, bT0 = sBar + 480, bZ = sBar + 488, bLd = sBar + 496;
  const uint32_t b3F = sBar + 512, b3E = sBar + 544, sGate = sBar + 576, sK1 = sBar + 720, sClm = sBar + 768;
  const int tid = threadIdx.x, warp_g = __shfl_sync(0xffffffffu, tid >> 5, 0), lane = tid & 31;
  const uint32_t rank = cluster_rank();
  const int cl = blockIdx.x >> 1;
  TSM(0);
  if (tid == 256) {
    const uint32_t job = p.jobs[cl][0];
#pragma unroll
    for (int i = 0; i < KC0; i++) { mbar_init(bAf + i * 8, 1); mbar_init(bBf + i * 16, 1); mbar_init(bBf + i * 16 + 8, 1); }
    asm volatile("fence.mbarrier_init.release.cluster;" ::: "memory");
#pragma unroll 1
    for (int i = 0; i < 4 * KC0; i++) {
      if (!(i & 3)) {
        mbar_expect(bAf + i * 2, 16384);
        tma2d(sA + (i / 4 + 2) * 16384, &p.tmA[(job >> 2) & 1], bAf + i * 2, i * 16, ((job >> 3) & 7) * 256 + rank * 128);
      }
      if (!(i & 1)) mbar_expect(bBf + i * 4, 16384);
      tma3d(sB + i * 8192, &p.tmW[(job >> 6) & 3], bBf + (i >> 1) * 8, 0, i * 16, (job >> 8) & 63);
    }
  }
  if (warp_g == 1) asm volatile("st.shared.u32 [%0], %1;" ::"r"(lane ? sClm - 4 + lane * 4 : sK1), "r"(lane ? 0xFFFFFFFFu : 80u) : "memory");
  if (tid == 0) {
    for (int i = 0; i < 8; i++) { if (i >= KC0) mbar_init(bAf + i * 8, 1); mbar_init(bAe + i * 8, 2); }
    for (int i = 0; i < K1_BST; i++) { if (i >= 2 * KC0) mbar_init(bBf + i * 8, 1); mbar_init(bBe + i * 8, 4); }
    mbar_init(bL, 1);
    mbar_init(bL2, 1);
    mbar_init(bR, 1);
    mbar_init(bLast, 1);
    mbar_init(bH, 4);
    mbar_init(bT0, 1);
    mbar_init(bZ, 1);
    mbar_init(bLd, 4);
    for (int i = 0; i < 8; i++) mbar_init(bS + i * 8, 8);
    for (int i = 0; i < K2_NST; i++) { mbar_init(bF + i * 8, 1); mbar_init(bE + i * 8, 4); }
    mbar_init(bT, 1); mbar_init(bT + 8, 1);
    for (int i = 0; i < K3_NST; i++) { mbar_init(b3F + i * 8, 1); mbar_init(b3E + i * 8, 4); }
    asm volatile("fence.mbarrier_init.release.cluster;" ::: "memory");
  }
  __syncwarp();
  if (warp_g != 8) cluster_sync();
  const int lr0 = blockIdx.x * 16;

  if (warp_g >= 8) {
    reg_dealloc<40>();
    if (warp_g == 8) {
      {
        __syncwarp();
        cluster_sync();
      }
      if (elect_one()) {
        uint32_t bs = (2 * KC0) % K1_BST, bph = (2 * KC0 < K1_BST), aph = 1;
#pragma unroll 1
        for (int ji = 0; ji < K1_MAXJOBS; ji++) {
          const uint32_t job = p.jobs[cl][ji];
          if (!(job & 3)) break;
          const int a_sel = (job >> 2) & 1, mpair = (job >> 3) & 7, chunk0 = (job >> 8) & 63;
          const bool newA = (job >> 14) & 1;
          const int KC = a_sel ? 9 : 8;
          const uint32_t halfbytes = 8192;
          const bool lastjob = (ji + 1 == K1_MAXJOBS) || !(p.jobs[cl][ji + 1] & 3);
          const CUtensorMap* tw = &p.tmW[(job >> 6) & 3];
          {
            const uint32_t njob = (ji + 1 < K1_MAXJOBS) ? p.jobs[cl][ji + 1] : 0;
            if (!(njob & 3) && !newA) mbar_arrive(bLast);
          }
#pragma unroll 1
          for (int kc = ji ? 0 : KC0; kc < KC; kc++) {
            {
              const bool nx = kc + PFD >= KC;
              const uint32_t njob = nx ? p.jobs[cl][ji + 1] : job;
              const int pk = nx ? kc + PFD - KC : kc + PFD;
              if ((njob & 3) && (nx || ji > 0)) {
                if (cl >= 64 || ((pk ^ (cl >> 1)) & 3) == 0)
                  tma_pf3d(&p.tmW[(njob >> 6) & 3], 0, pk * 64 + (cl & 1) * 32 + rank * 16, (njob >> 8) & 63);
                if (((njob >> 14) & 1) || pk == 8) tma_pf2d(&p.tmA[(njob >> 2) & 1], pk * 64, ((njob >> 3) & 7) * 256 + rank * 128);
              }
            }
            if (kc == 8) {
              PWAIT(bBe + bs * 8, bph);
              mbar_expect(bBf + bs * 8, 16384);
              tma2d(sB + bs * 16384, &p.tmA[1], bBf + bs * 8, 512, mpair * 256 + rank * 128);
              if (++bs == K1_BST) { bs = 0; bph ^= 1; }
            } else if (newA) {
              PWAIT(bAe + kc * 8, aph);
              mbar_expect(bAf + kc * 8, 16384);
              tma2d(sA + ((kc + 2) & 7) * 16384, &p.tmA[a_sel], bAf + kc * 8, kc * 64, mpair * 256 + rank * 128);
              if (kc == 7 && lastjob) mbar_arrive(bLast);
            }
#pragma unroll 1
            for (int kk = 0; kk < 2; kk++) {
              PWAIT(bBe + bs * 8, bph);
              mbar_expect(bBf + bs * 8, 2 * halfbytes);
              tma3d_mc(sB + bs * 16384 + rank * halfbytes, tw, bBf + bs * 8, 0, kc * 64 + kk * 32 + rank * 16, chunk0, 3);
              if (++bs == K1_BST) { bs = 0; bph ^= 1; }
            }
          }
          if (newA) aph ^= 1;
        }
        Cursor c{0, 0};
        int pcol = 0;
        PWAIT(bR, 0);
        uint32_t tick = lds32(sTick + 8), seen = 1u << (p.order[tick] >> 4);
        asm volatile("fence.proxy.async.global;" ::: "memory");
#pragma unroll 1
        for (int it = 0;; it++) {
          const uint32_t item = (tick < 256) ? p.order[tick] : (K2_END | min(tick - 256, 255u));
          asm volatile("st.shared.u32 [%0], %1;" ::"r"(sItem + (it & 7) * 4), "r"(item) : "memory");
          if (item >= K2_END) break;
          const int h = item >> 3, j = item & 7;
          const int col = (h * 2 + rank) * S_LEN;
          const int nb = 2 * j + 2;
          if (!((seen >> (h >> 1)) & 1)) {
            wait_flag(&g_sync[F_HP + (h >> 1)], RDY_TARGET);
            asm volatile("fence.proxy.async.global;" ::: "memory");
            seen |= 1u << (h >> 1);
          }
          PWAIT(bE + c.s * 8, c.ph);
          mbar_expect(bF + c.s * 8, 32768);
#pragma unroll 1
          for (int i = 0; i < 4; i++) {
            const int hi = (i ^ it ^ 1) & 1;
            tma2d(sbase + c.s * 32768 + i * 8192, &p.tmQ, bF + c.s * 8, 0, (h * 2 + (i >> 1)) * S_LEN + (2 * j + hi) * 128 + (rank ^ hi) * 64);
          }
          c.next();
          if (tick >= 256 - 73) {
            const int kk = tick - (256 - 73), sel = (kk < 9), kr = (sel ? kk : kk - 9) * 64 + rank * 32;
#pragma unroll 1
            for (int i = 0; i < 2; i++) {
              tma_pf3d(&p.tmO[sel], 0, kr, i * 4);
              tma_pf2d(&p.tmOt[sel], 512 + i * 32, kr);
            }
          }
#pragma unroll 1
          for (int n = nb - 1; n >= 0; n--) {
            if (n == 0 && rank == 0) tick = atomicAdd(&g_sync[F_TICK], 1u);
            PWAIT(bE + c.s * 8, c.ph);
            mbar_expect(bF + c.s * 8, 32768);
            tma2d_mc(sbase + c.s * 32768 + rank * 16384, &p.tmK, bF + c.s * 8, 0, col + n * 128, 3);
            c.next();
            if (n < nb - 1 || it > 0) {
              PWAIT(bE + c.s * 8, c.ph);
              mbar_expect(bF + c.s * 8, 32768);
              tma2d_mc(sbase + c.s * 32768 + rank * 16384, &p.tmV, bF + c.s * 8, 0, (n < nb - 1) ? col + (n + 1) * 128 : pcol, 3);
              c.next();
            }
          }
          pcol = col;
          if (rank == 0) {
            asm volatile(
                "{\n.reg .b32 a, b;\nmapa.shared::cluster.u32 a, %0, 1;\nmapa.shared::cluster.u32 b, %1, 1;\n"
                "st.async.shared::cluster.mbarrier::complete_tx::bytes.u32 [a], %2, [b];\n}" ::"r"(sTick + (it & 1) * 4),
                "r"(bT + (it & 1) * 8), "r"(tick) : "memory");
          } else {
            mbar_expect(bT + (it & 1) * 8, 4);
            PWAIT(bT + (it & 1) * 8, (it >> 1) & 1);
            tick = lds32(sTick + (it & 1) * 4);
          }
        }
        PWAIT(bE + c.s * 8, c.ph);
        mbar_expect(bF + c.s * 8, 32768);
        tma2d_mc(sbase + c.s * 32768 + rank * 16384, &p.tmV, bF + c.s * 8, 0, pcol, 3);
        const uint32_t unit = tick - 256;
        const int mblk = (7 - (p.unit[unit][0] >> 1)) * 2 + rank, nhalf = p.unit[unit][0] & 1;
        uint32_t have, hoa;
        have = ld_and2(&g_sync[F_CTX + (mblk & ~1)]);
        asm volatile("ld.acquire.gpu.global.u32 %0, [%1];" : "=r"(hoa) : "l"(&g_sync[F_OA + mblk]) : "memory");
        asm volatile("fence.proxy.async.global;" ::: "memory");
#pragma unroll 1
        for (uint32_t idx = PF3A; idx < PF3; idx++) {
          const int kk = p.unit[unit][2] + idx;
          if ((kk < 9) ? (hoa >= 8) : ((have >> ((kk - 9) >> 1)) & 1)) tma_pf2d(&p.tmC, 0, ((kk < 9) ? 64 + kk : kk - 9) * S_LEN + mblk * 128);
        }
        {
          const uint32_t rot = k3_rot(c.s), nfree = ((0x1Au >> c.s) & 1) ? 2 : 3;
          uint32_t kq = p.unit[unit][2] * 0x01010101u + 0x03020100u, k1 = 80, idx = 0, pa = 0, pb = 0;
          auto step = [&](uint32_t& pend) {
            uint32_t nxt = (kq & 255) + CR;
            if (idx + CR >= K3_NS && k1 == 80) {
              if (rank == 0) {
                nxt = min(pend + p.unit[unit][3], 73u);
                asm volatile("{\n.reg .b32 a;\nmapa.shared::cluster.u32 a, %0, 1;\nst.volatile.shared::cluster.u8 [a], %1;\n}" ::"r"(sClm + idx), "r"(nxt) : "memory");
              } else {
#pragma unroll 1
                for (uint32_t spins = 0; spins < (1u << 22); spins++) {
                  asm volatile("ld.volatile.shared.u8 %0, [%1];" : "=r"(nxt) : "r"(sClm + idx) : "memory");
                  if (nxt != 255) break;
                  __nanosleep(20);
                }
              }
              if (nxt >= 73) {
                k1 = idx + CR;
                asm volatile("st.shared.u32 [%0], %1;" ::"r"(sK1), "r"(k1) : "memory");
              }
            }
            const uint32_t kk = kq & 255;
            if (idx < 12) TP(idx);
            kq = (kq >> 8) | (nxt << (8 * CR - 8));
            const uint32_t s = (rot + idx) & 3;
            if (idx >= nfree) PWAIT((idx < 4) ? bH : b3E + s * 8, (idx < 4) ? 0 : (~idx >> 2) & 1);
#pragma unroll 1
            while (idx < nfree && c.s != ((0x6431u >> (4 * s)) & 15)) {
              c.next();
              PWAIT(bE + c.s * 8, c.ph);
            }
            if (idx < 12) TP(12 + idx);
            mbar_expect(b3F + s * 8, K3_STAGE);
            const uint32_t st = sbase + s * K3_STAGE;
            const int sel = (kk < 9), k = sel ? kk : kk - 9, kr = k * 64 + rank * 32;
            tma3d_mc(st + 16384 + rank * 16384, &p.tmO[sel], b3F + s * 8, 0, kr, nhalf * 4, 3);
            tma2d_mc(st + 49152 + rank * 2048, &p.tmOt[sel], b3F + s * 8, 512 + nhalf * 32, kr, 3);
            if (rank == 0 && idx + CR + 2 >= K3_NS && k1 == 80) pend = atomicAdd(&g_sync[F_CLM + p.unit[unit][0]], 1u);
            if (sel && hoa < 8) {
              wait_flag(&g_sync[F_OA + mblk], 8);
              hoa = 8;
              asm volatile("fence.proxy.async.global;" ::: "memory");
            }
            if (!sel && !((have >> (k >> 1)) & 1)) {
#pragma unroll 1
              for (uint32_t spins = 0; spins < (1u << 22); spins++) {
                have = ld_and2(&g_sync[F_CTX + (mblk & ~1)]);
                if ((have >> (k >> 1)) & 1) break;
                __nanosleep(100);
              }
              asm volatile("fence.proxy.async.global;" ::: "memory");
            }
            tma2d(st, &p.tmC, b3F + s * 8, 0, (sel ? 64 + k : k) * S_LEN + mblk * 128);
            if (idx < 12) TP(24 + idx);
            return ++idx >= k1;
          };
#pragma unroll 1
          for (;;) {
            if (step(pa)) break;
            if (step(pb)) break;
          }
          asm volatile("" ::"r"(pa), "r"(pb) : "memory");
        }
      }
    }
    __syncwarp();
    if (warp_g == 8) {
      uint32_t v = 0;
      if (lane == 0) {
        __threadfence();
        v = atomicAdd(&g_sync[F_DONE], 1u);
      }
      if (__shfl_sync(0xffffffffu, v, 0) == 2 * NCLUSTER - 1) {
        reinterpret_cast<uint4*>(g_sync)[lane] = make_uint4(0, 0, 0, 0);
        if (lane == 0) g_sync[F_EPOCH] = lds32(sGate + 64) + 1;
      }
    }
    asm volatile("" ::: "memory");
    if (__shfl_sync(0xffffffffu, warp_g, 0) != 8) {
#pragma unroll 1
      for (int i = 0; i < 32 && !mbar_test(bAf + 7 * 8, 0); i++) __nanosleep(200);
      if (lr0 < S_LEN) {
#pragma unroll 1
        for (int i = warp_g - 9; i < 16; i += 3) {
          const float g = gate_row(lr0 + i, lane, x, gate_w);
          if (lane == 0) asm volatile("st.shared.f32 [%0], %1;" ::"r"(sGate + i * 4), "f"(g) : "memory");
        }
        bar_arrive(3, 256 + 96);
        if (lane == 0) {
          __threadfence();
          atomicAdd(&g_sync[F_GATE], 1u);
        }
      }
      uint32_t aph = 1;
#pragma unroll 1
      for (int ji = 0; ji < K1_MAXJOBS; ji++) aph ^= (p.jobs[cl][ji] >> 14) & 1;
      if (warp_g == 9) {
        uint32_t nxt = 0;
        if (lane == 0) {
#pragma unroll 1
        for (int ji = 0; ji < K1_MAXJOBS; ji++) {
          const uint32_t job = p.jobs[cl][ji];
          if (!(job & 3)) break;
          PWAIT(bS + (ji & 3) * 8, (ji >> 2) & 1);
          __threadfence();
          atomicAdd(&g_sync[(((job >> 6) & 3) == 2) ? (F_QKVA + ((job >> 3) & 7) * 2 + rank) : (F_HP + ((job >> 10) & 15))], 1u);
        }
#pragma unroll 1
        for (int it = 0;; it++) {
          PWAIT(bS2 + (it & 3) * 8, (it >> 2) & 1);
          const uint32_t item = lds32(sItem + (it & 7) * 4);
          nxt = lds32(sItem + ((it + 1) & 7) * 4);
          __threadfence();
          atomicOr(&g_sync[F_CTX + (item & 7) * 2 + rank], 1u << (item >> 3));
          if (nxt >= K2_END) break;
        }
        }
        const uint32_t unit = __shfl_sync(0xffffffffu, nxt, 0) & 255;
        {
          const int mblk = (7 - (p.unit[unit][0] >> 1)) * 2 + rank, nhalf = p.unit[unit][0] & 1;
          bf16* o = ptr_add(out, (mblk * 128 + p.unit[unit][1] * 32) * DM * 2);
          const bool mine = p.unit[unit][1] < 4;
#pragma unroll 4
          for (int i = 0; i < 32 && mine; i++) __stcg(reinterpret_cast<uint4*>(ptr_add(o, i * DM * 2 + nhalf * 512 + lane * 16)), make_uint4(0, 0, 0, 0));
#pragma unroll
          for (int i = 0; i < 4 && mine; i++) __stcg(reinterpret_cast<uint4*>(ptr_add(o, (i * 8 + (lane >> 2)) * DM * 2 + 1024 + nhalf * 64 + (lane & 3) * 16)), make_uint4(0, 0, 0, 0));
          asm volatile("fence.proxy.async.global;" ::: "memory");
          __threadfence();
          __syncwarp();
          if (lane == 0) {
            prefetch_tmap(&p.tmR[0]); prefetch_tmap(&p.tmR[1]);
            unsigned int* cnt = &g_sync[F_XCH + mblk * 2 + nhalf];
            const uint32_t xtarget = lds32(sGate + 64) * 4 + 4;
            if (mine) atomicAdd(cnt, 1u);
            uint32_t v;
#pragma unroll 1
            for (uint32_t spins = 0; spins < (1u << 22); spins++) {
              asm volatile("ld.acquire.gpu.global.u32 %0, [%1];" : "=r"(v) : "l"(cnt) : "memory");
              if ((int)(v - xtarget) >= 0) break;
              __nanosleep(200);
            }
            asm volatile("fence.proxy.async.global;" ::: "memory");
            mbar_arrive(bZ);
          }
        }
      } else if (warp_g == 11) {
        if (lane == 0) {
          asm volatile("st.shared.u32 [%0], %1;" ::"r"(sGate + 64), "r"(__ldcg(&g_sync[F_EPOCH])) : "memory");
          wait_flag(&g_sync[F_GATE], GATE_TARGET);
          prefetch_tmap(&p.tmC); prefetch_tmap(&p.tmQ); prefetch_tmap(&p.tmK); prefetch_tmap(&p.tmV);
          uint32_t tick;
          if (rank == 0) {
            PWAIT(bLast, 0);
            PWAIT(bAe + FIRST_DRAW * 8, aph);
            tick = atomicAdd(&g_sync[F_TICK], 1u);
            asm volatile("st.shared.u32 [%0], %1;" ::"r"(sTick + 8), "r"(tick) : "memory");
            asm volatile(
                "{\n.reg .b32 a, b;\nmapa.shared::cluster.u32 a, %0, 1;\nmapa.shared::cluster.u32 b, %1, 1;\n"
                "st.async.shared::cluster.mbarrier::complete_tx::bytes.u32 [a], %2, [b];\n}" ::"r"(sTick + 8), "r"(bT0), "r"(tick) : "memory");
          } else {
            mbar_expect(bT0, 4);
            PWAIT(bT0, 0);
            tick = lds32(sTick + 8);
          }
          wait_flag(&g_sync[F_HP + (p.order[tick] >> 4)], RDY_TARGET);
          mbar_arrive(bR);
        }
      } else if (warp_g == 10) {
        if (lr0 < S_LEN && lane == 0) {
          prefetch_tmap(&p.tmL[0]); prefetch_tmap(&p.tmL[1]); prefetch_tmap(&p.tmL[2]);
          wait_flag(&g_sync[F_QKVA + (lr0 >> 7)], K1_FLAG_TARGET);
          wait_flag(&g_sync[F_QKVA + (max(lr0 - 16, 0) >> 7)], K1_FLAG_TARGET);
          asm volatile("fence.proxy.async.global;" ::: "memory");
          PWAIT(bLast, 0);
#pragma unroll 1
          for (int kc = 0; kc < 6; kc++) {
            PWAIT(bAe + kc * 8, aph);
            if (kc == 3) {
              mbar_expect(bL, LV);
              tma4d(sL, &p.tmL[0], bL, lr0 / 2 - 8, 9, 0);
              tma4d(sL + LQ, &p.tmL[1], bL, lr0 / 2, 0, 0);
            }
          }
          mbar_expect(bL2, LQ);
          tma4d(sL + LV, &p.tmL[0], bL2, lr0 / 2 - 8, 18, 0);
        }
        __syncwarp();
        bar_sync(5, 256 + 32);
        if (lr0 < S_LEN && lane == 0) {
          asm volatile("cp.async.bulk.tensor.4d.global.shared::cta.bulk_group [%0, {%2, %3, %2, %2}], [%1];" ::"l"(&p.tmL[2]), "r"(sL + LQ), "r"(0), "r"(lr0 / 2) : "memory");
          asm volatile("cp.async.bulk.commit_group;" ::: "memory");
          asm volatile("cp.async.bulk.wait_group.read 0;" ::: "memory");
        }
        __syncwarp();
        if (lane < 12) mbar_arrive_cluster(bE + (4 + lane % 3) * 8, (lane / 3) & 1);
        if (lr0 < S_LEN && lane == 0) {
          asm volatile("cp.async.bulk.wait_group 0;" ::: "memory");
          asm volatile("fence.proxy.async.global;" ::: "memory");
          __threadfence();
          atomicAdd(&g_sync[F_OA + (lr0 >> 7)], 1u);
        }
      }
    }
    __syncwarp();
    cluster_sync();
  } else {
    reg_alloc<232>();
    const int wg = warp_g >> 2, warp = warp_g & 3, q = lane & 3;
    const bool sig = (lane == 0) && (warp < 2);
    {
      K1State st{0, 0, 0, nullptr, 0, 0, 0, 24};
      float acc[128];
      uint32_t pk[64];
      if (wg == 0) { TS(0, 0); TSC(0, 2); }
      uint32_t job = p.jobs[cl][0];
      k1_first(st, job, bAf, bBf);
      {
#pragma unroll 1
        for (int ji = 0; job & 3; ji++) {
          const uint32_t njob = p.jobs[cl][ji + 1];
          k1_tile(acc, pk, st, job, njob, sA, sB, bAf, bAe, bBf, bBe, bS, wg, warp, lane, rank);
          job = njob;
        }
      }
#pragma unroll
      for (int i = 0; i < 4; i++)
        mbar_arrive_cluster_if(bE + i * 8, warp & 1, sig);
      if (lr0 < S_LEN) bar_sync(3, 256 + 96);
      if (st.wsel == 3) {
#pragma unroll
        for (int G = 0; G < 16; G++) scale_q4(pk + G * 4);
      }
      auto flush = [&](int i, uint32_t dep) {
        asm volatile("{\n.reg .pred p;\nsetp.eq.u32 p, %5, 0;\n@p st.global.cs.v4.b32 [%0], {%1, %2, %3, %4};\n}" ::"l"(st.pp + goff(i / 2, i & 1)),
                     "r"(pk[i * 4]), "r"(pk[i * 4 + 1]), "r"(pk[i * 4 + 2]), "r"(pk[i * 4 + 3]), "r"(dep & blockIdx.y) : "memory");
      };
      if (wg == 0) { TS(0, 1); TSC(0, 3); }
      if (lr0 < S_LEN) {
        const float gate0 = __uint_as_float(lds32(sGate + (lane >> 2) * 8)), gate1 = __uint_as_float(lds32(sGate + (lane >> 2) * 8 + 4));
        local_attn(lr0, warp_g, sL, bL, bL2, lane, gate0, gate1, flush);
        k1_flag(st, lane, bS);
      } else {
        FLUSH();
      }
      bar_arrive(5, 256 + 32);
    }
    __syncwarp();
    uint32_t item, rot;
    {
      const int mybar = 1 + wg, otherbar = 2 - wg;
      const uint32_t never = blockIdx.y;
      float S[64], O[64];
      uint32_t P[32], Q[32];
      float m0, m1, l0, l1, gf0, gf1;
      uint32_t eoff;
      Cursor c{2 + 2 * (uint32_t)wg, 0}, ck{1 + (uint32_t)wg, 0};
      if (wg == 1) bar_arrive(1, 256);
      if (wg == 0) { TS(1, 0); TSC(1, 2); }
      {
        const Cursor cq{0, 0}, cs0{1, 0}, cs1{3, 0};
        const int it = 0, hi = wg ^ 1;
        mbar_wait2(bF, 0, bF + ck.s * 8, 0);
        LOAD_Q();
        wg_fence();
        ISSUE_QK(ck);
        wg_commit();
        RELEASE(cq);
        NEW_ITEM();
        wg_wait<0>();
        fence_regs(S);
      }
#pragma unroll 1
      for (int it = 0;;) {
        int hi = (wg ^ it ^ 1) & 1;
        RELEASE(ck);
        const int nblk = 2 * (item & 7) + 1 + hi;
        Cursor cv;
        float s0 = 0.f, s1 = 0.f;
        l0 = 0.f; l1 = 0.f;
        m0 = 0.f; m1 = 0.f;
        bool shifted = false;
        {
          const int d = warp * 16 + (lane >> 2) - 2 * q;
          if (rank == hi) {
#pragma unroll
            for (int jj = 0; jj < 8; jj++) MASK(jj, jj);
            EXPB(0); EXPB(1); EXPB(2); EXPB(3);
#pragma unroll
            for (int i = 32; i < 64; i++) S[i] = -INFINITY;
#pragma unroll
            for (int i = 16; i < 32; i++) P[i] = 0;
          } else {
#pragma unroll
            for (int jj = 0; jj < 8; jj++) MASK(jj + 8, jj);
            EXPB(0); EXPB(1); EXPB(2); EXPB(3); EXPB(4); EXPB(5); EXPB(6); EXPB(7);
          }
        }
        float chk;
        asm("{\n.reg .pred p;\nsetp.ge.f32 p, %1, %2;\nselp.f32 %0, %3, 0f7F800000, p;\n}" : "=f"(chk) : "f"(fminf(s0, s1)), "f"(q ? -1.f : SPEC_LO), "f"(s0 + s1));
        fence_regs(P);
        TB(9);
#pragma unroll 1
        for (int n = 1;; n++) {
          if (__any_sync(0xffffffffu, !(chk <= SPEC_HI))) {
            float mx0 = fmaxf(S[0], S[1]), mx1 = fmaxf(S[2], S[3]);
#pragma unroll
            for (int jj = 1; jj < 16; jj++) {
              mx0 = fmaxf(mx0, fmaxf(S[jj * 4 + 0], S[jj * 4 + 1]));
              mx1 = fmaxf(mx1, fmaxf(S[jj * 4 + 2], S[jj * 4 + 3]));
            }
            mx0 = fmaxf(mx0, __shfl_xor_sync(0xffffffffu, mx0, 1));
            mx1 = fmaxf(mx1, __shfl_xor_sync(0xffffffffu, mx1, 1));
            mx0 = fmaxf(mx0, __shfl_xor_sync(0xffffffffu, mx0, 2));
            mx1 = fmaxf(mx1, __shfl_xor_sync(0xffffffffu, mx1, 2));
            const float lo = (n == 1) ? -INFINITY : 0.f;
            mx0 = fmaxf(mx0, lo);
            mx1 = fmaxf(mx1, lo);
            m0 += mx0; m1 += mx1;
            shifted = true;
            const float sc0 = ex2(-fmaxf(mx0, 0.f)), sc1 = ex2(-fmaxf(mx1, 0.f));
            l0 *= sc0; l1 *= sc1;
            s0 = 0.f; s1 = 0.f;
#pragma unroll
            for (int jj = 0; jj < 16; jj++) {
              const float e0 = ex2(S[jj * 4 + 0] - mx0), e1 = ex2(S[jj * 4 + 1] - mx0), e2 = ex2(S[jj * 4 + 2] - mx1), e3 = ex2(S[jj * 4 + 3] - mx1);
              s0 += e0 + e1;
              s1 += e2 + e3;
              P[jj * 2 + 0] = pack_bf16(e0, e1);
              P[jj * 2 + 1] = pack_bf16(e2, e3);
              O[jj * 4 + 0] *= sc0;
              O[jj * 4 + 1] *= sc0;
              O[jj * 4 + 2] *= sc1;
              O[jj * 4 + 3] *= sc1;
            }
          }
          l0 += s0;
          l1 += s1;
          if (n >= nblk) break;
          ck = c; c.next();
          cv = c; c.next();
          mbar_wait2(bF + ck.s * 8, ck.ph, bF + cv.s * 8, cv.ph);
          TURN_SYNC();
          TRC(0);
          wg_fence();
          ISSUE_QK(ck);
          wg_commit();
          {
            const uint64_t dv = make_desc(sbase + cv.s * 32768, 16384, 1024, 1);
#pragma unroll
            for (int t = 0; t < 8; t++) {
              wgmma_rs_n128<1, 0>(O, P[4 * t], P[4 * t + 1], P[4 * t + 2], P[4 * t + 3], dv + (uint64_t)(t * 128), (t > 0) ? 1 : (n != 1));
              if ((PVM >> t) & 1) wg_commit();
            }
          }
          TURN_ARRIVE();
          s0 = 0.f; s1 = 0.f;
          wg_wait<__builtin_popcount(PVM)>();
          fence_regs(S);
          RELEASE(ck);
          if (shifted) {
#pragma unroll
            for (int i = 0; i < 64; i++) S[i] -= (i & 2) ? m1 : m0;
          }
          wg_wait<__builtin_popcount(PVM) - 1>();
          EXPC(0); EXPC(1); EXPC(2); EXPC(3); EXPC(4); EXPC(5); EXPC(6); EXPC(7);
          chk = s0 + s1;
        }
        it++;
        hi ^= 1;
        TB(0);
        Cursor cq = c, cs0, cs1;
        rot = k3_rot(c.s);
        c.next();
        ck = c; c.next();
        cs0 = ck; cs1 = ck;
        cv = c; c.next();
        if (!hi) {
          ck = c; c.next();
          cs1 = c; c.next();
        }
        mbar_wait(bF + cq.s * 8, cq.ph);
        TB(1);
        LOAD_Q();
        const uint32_t rdy = mbar_test(bF + ck.s * 8, ck.ph) & mbar_test(bF + cv.s * 8, cv.ph);
        l0 += __shfl_xor_sync(0xffffffffu, l0, 1);
        l1 += __shfl_xor_sync(0xffffffffu, l1, 1);
        l0 += __shfl_xor_sync(0xffffffffu, l0, 2);
        l1 += __shfl_xor_sync(0xffffffffu, l1, 2);
        if (item >= K2_END) {
          TURN_SYNC();
          TRC(2);
          wg_fence();
          ISSUE_PV(cq, nblk == 1);
          wg_commit();
          if (wg == (it & 1)) TURN_ARRIVE();
          asm volatile("" : "+f"(gf0), "+f"(gf1), "+f"(l0), "+f"(l1));
          const float f0 = __fdividef(1.f - gf0, l0), f1 = __fdividef(1.f - gf1, l1);
          bf16* optr = ptr_add(g_ctx, eoff);
          wg_wait<0>();
          fence_regs(O);
          mbar_arrive_cluster_if(bH, warp & 1, sig);
          STORE_O(0); STORE_O(1); STORE_O(2); STORE_O(3);
          __syncwarp();
          mbar_arrive_if(bS2 + ((it - 1) & 3) * 8, lane == 0);
          break;
        }
        if (!rdy) mbar_wait2(bF + ck.s * 8, ck.ph, bF + cv.s * 8, cv.ph);
        TB(2);
        TURN_SYNC();
        TB(3);
        TRC(1);
        wg_fence();
        ISSUE_PV(cv, nblk == 1);
        wg_commit();
        ISSUE_QK(ck);
        wg_commit();
        TURN_ARRIVE();
        RELEASE(cq);
        TB(4);
        asm volatile("" : "+f"(gf0), "+f"(gf1), "+f"(l0), "+f"(l1));
        const float f0 = __fdividef(1.f - gf0, l0), f1 = __fdividef(1.f - gf1, l1);
        wg_wait<1>();
        fence_regs(O);
        fence_regs(P);
        TB(5);
        RELEASE(cv);
        {
          bf16* optr = ptr_add(g_ctx, eoff);
          STORE_O(0); STORE_O(1); STORE_O(2); STORE_O(3);
          __syncwarp();
          mbar_arrive_if(bS2 + ((it - 1) & 3) * 8, lane == 0);
        }
        TB(6);
        NEW_ITEM();
        TB(7);
        wg_wait<0>();
        fence_regs(S);
        TB(8);
      }
      TRC(3);
      if (wg == 1) { TS(1, 1); TSC(1, 3); }
    }
    __syncwarp();
    const uint32_t unit = item & 255;
    {
      const int mblk = (7 - (p.unit[unit][0] >> 1)) * 2 + rank, nhalf = p.unit[unit][0] & 1;
      float acc[144];
      uint32_t s = rot, ph = 0, prev = 0, k = 0;
      if (wg == 0) { TS(2, 0); TSC(2, 2); }
      uint32_t fa[16], fb[16], fc[16];
      const uint32_t aoff = (wg * 64 + warp * 16 + (lane & 15)) * 128 + (((lane >> 4) ^ (lane & 7)) << 4);
#define C_NEXT()                                                                                               \
  do {                                                                                                         \
    s = (s + 1) & 3;                                                                                           \
    if (s == rot) ph ^= 1;                                                                                     \
    mbar_wait(b3F + s * 8, ph);                                                                                \
  } while (0)
#define C_LOAD(F)                                                                                              \
  do {                                                                                                         \
    _Pragma("unroll") for (int t = 0; t < 4; t++)                                                              \
        ldsm_x4(F[4 * t], F[4 * t + 1], F[4 * t + 2], F[4 * t + 3], sbase + s * K3_STAGE + (aoff ^ (t * 32))); \
  } while (0)
#define C_MMA(F, S, H, SD)                                                                                     \
  do {                                                                                                         \
    const uint32_t st = sbase + (S) * K3_STAGE;                                                                \
    const uint64_t db = make_desc(st + 16384, 4096, 1024, 1), dt = make_desc(st + 49152, 16, 512, 2);          \
    _Pragma("unroll") for (int t = 0; t < 4; t++) {                                                            \
      const int sd = (t > 0) || (SD);                                                                          \
      if ((H) & 1) wgmma_rs_n128<1, 0>(acc, F[4 * t], F[4 * t + 1], F[4 * t + 2], F[4 * t + 3], db + (uint64_t)((t >> 1) * 1024 + (t & 1) * 128), sd); \
      if ((H) & 2) wgmma_rs_n128<1, 64>(acc, F[4 * t], F[4 * t + 1], F[4 * t + 2], F[4 * t + 3], db + (uint64_t)((t >> 1) * 1024 + (t & 1) * 128 + 512), sd); \
      if ((H) & 2) wgmma_rs_n32<1, 128>(acc, F[4 * t], F[4 * t + 1], F[4 * t + 2], F[4 * t + 3], dt + (uint64_t)(t * 64), sd); \
    }                                                                                                          \
  } while (0)
#define C_STEP(F, G)                                                                                           \
  {                                                                                                            \
    wg_fence();                                                                                                \
    C_MMA(F, s, 3, k > 0);                                                                                     \
    wg_commit();                                                                                               \
    wg_wait<1>();                                                                                              \
    fence_regs(G);                                                                                             \
    mbar_arrive_cluster_if(b3E + prev * 8, warp & 1, sig && k > 0);                                            \
    prev = s;                                                                                                  \
    TCK(k + 1);                                                                                                \
    C_NEXT();                                                                                                  \
    if ((tid & 127) == 0 && k < 11) TP(37 + wg * 12 + k);                                                      \
    if (++k + CR >= lds32(sK1)) break;                                                                         \
    C_LOAD(G);                                                                                                 \
  }
      TCK(0);
      mbar_wait(b3F + s * 8, 0);
      if ((tid & 127) == 0) TP(36 + wg * 12);
      C_LOAD(fa);
#pragma unroll
      for (int i = 0; i < 16; i++) fb[i] = 0;
#pragma unroll 1
      for (;;) {
        C_STEP(fa, fb)
        C_STEP(fb, fa)
      }
      C_LOAD(fc);
      if (wg == 1) {
        wg_wait<0>();
        mbar_arrive_cluster_if(b3E + prev * 8, warp & 1, sig);
        mbar_wait(bLd, 0);
      }
      const uint32_t s0 = s;
      wg_fence();
      C_MMA(fc, s0, 2, 1);
      wg_commit();
      wg_wait<1>();
      fence_regs(fa);
      fence_regs(fb);
      mbar_arrive_cluster_if(b3E + prev * 8, warp & 1, sig && wg == 0);
      cluster_arrive();
      C_NEXT();
      C_LOAD(fa);
      wg_fence();
      C_MMA(fa, s, 2, 1);
      C_MMA(fc, s0, 1, 1);
      wg_commit();
      C_NEXT();
      C_LOAD(fb);
      wg_fence();
      C_MMA(fb, s, 2, 1);
      wg_commit();
      wg_wait<1>();
      fence_regs(fc);
      C_NEXT();
      C_LOAD(fc);
      wg_fence();
      C_MMA(fc, s, 2, 1);
      wg_commit();
      C_MMA(fa, (s0 + 1) & 3, 1, 1);
      C_MMA(fb, (s0 + 2) & 3, 1, 1);
      C_MMA(fc, s, 1, 1);
      wg_commit();
      mbar_arrive_if(bLd, tid < 128 && lane == 0);
      const uint32_t stail = sbase + K3_NST * K3_STAGE + warp_g * 1024;
      const int row = mblk * 128 + warp_g * 16;
      mbar_wait(bZ, 0);
#pragma unroll
      for (int h = 1; h >= 0; h--) {
        if (h) wg_wait<1>(); else wg_wait<0>();
#pragma unroll
        for (int i = h * 64; i < 64 + h * 80; i++) asm volatile("" : "+f"(acc[i])::"memory");
        if (!h && wg == 0) TS(2, 4);
#pragma unroll
        for (int i = h * 8; i < 8 + h * 10; i++) {
          const uint32_t ad = (i < 16) ? sbase + (i >> 2) * K3_STAGE + (aoff ^ ((i & 3) * 32))
                                       : stail + (lane & 15) * 64 + ((((i & 1) * 2 + (lane >> 4)) ^ ((lane >> 1) & 3)) << 4);
          asm volatile("stmatrix.sync.aligned.m8n8.x4.shared.b16 [%0], {%1, %2, %3, %4};" ::"r"(ad), "r"(pack_bf16(acc[i * 8], acc[i * 8 + 1])),
                       "r"(pack_bf16(acc[i * 8 + 2], acc[i * 8 + 3])), "r"(pack_bf16(acc[i * 8 + 4], acc[i * 8 + 5])), "r"(pack_bf16(acc[i * 8 + 6], acc[i * 8 + 7])) : "memory");
        }
        asm volatile("fence.proxy.async.shared::cta;" ::: "memory");
        __syncwarp();
        if (!h && wg == 0) TS(2, 5);
        if (lane == 0) {
#pragma unroll
          for (int c = h * 2; c < 2 + h * 3; c++)
            asm volatile("cp.reduce.async.bulk.tensor.2d.global.shared::cta.add.tile.bulk_group [%0, {%2, %3}], [%1];" ::"l"(&p.tmR[c >> 2]),
                         "r"((c < 4) ? sbase + c * K3_STAGE + warp_g * 2048 : stail), "r"((c < 4) ? nhalf * 256 + c * 64 : 512 + nhalf * 32), "r"(row) : "memory");
        }
        __syncwarp();
      }
      if (lane == 0) {
        asm volatile("cp.async.bulk.commit_group;" ::: "memory");
        if (wg == 0) TS(2, 6);
        asm volatile("cp.async.bulk.wait_group 0;" ::: "memory");
      }
      __syncwarp();
    }
    if (wg == 0) { TS(2, 1); TSC(2, 3); }
    cluster_wait();
  }
}

typedef CUresult (*EncFn)(CUtensorMap*, CUtensorMapDataType, cuuint32_t, void*, const cuuint64_t*, const cuuint64_t*, const cuuint32_t*,
                          const cuuint32_t*, CUtensorMapInterleave, CUtensorMapSwizzle, CUtensorMapL2promotion, CUtensorMapFloatOOBfill);

static void enc2d(EncFn enc, CUtensorMap* m, const void* ptr, uint64_t cols, uint64_t rows, uint32_t bc, uint32_t br,
                  CUtensorMapSwizzle sw = CU_TENSOR_MAP_SWIZZLE_128B) {
  cuuint64_t gd[2] = {cols, rows}, gs[1] = {cols * 2};
  cuuint32_t bx[2] = {bc, br}, es[2] = {1, 1};
  enc(m, CU_TENSOR_MAP_DATA_TYPE_BFLOAT16, 2, const_cast<void*>(ptr), gd, gs, bx, es, CU_TENSOR_MAP_INTERLEAVE_NONE, sw,
      CU_TENSOR_MAP_L2_PROMOTION_L2_256B, CU_TENSOR_MAP_FLOAT_OOB_FILL_NONE);
}
static void enc3d(EncFn enc, CUtensorMap* m, const void* ptr, uint64_t cols, uint64_t rows, uint32_t br, uint32_t bch) {
  cuuint64_t gd[3] = {64, rows, cols / 64}, gs[2] = {cols * 2, 128};
  cuuint32_t bx[3] = {64, br, bch}, es[3] = {1, 1, 1};
  enc(m, CU_TENSOR_MAP_DATA_TYPE_BFLOAT16, 3, const_cast<void*>(ptr), gd, gs, bx, es, CU_TENSOR_MAP_INTERLEAVE_NONE,
      CU_TENSOR_MAP_SWIZZLE_128B, CU_TENSOR_MAP_L2_PROMOTION_L2_256B, CU_TENSOR_MAP_FLOAT_OOB_FILL_NONE);
}

static void build_k1_jobs(Params& p) {
  int cnt[NCLUSTER];
  for (int c = 0; c < NCLUSTER; c++) {
    cnt[c] = 0;
    for (int i = 0; i <= K1_MAXJOBS; i++) p.jobs[c][i] = 0;
  }
  auto add = [&](int c, int nch, int a_sel, int mp, int w_sel, int chunk0) {
    p.jobs[c][cnt[c]++] = (uint16_t)((nch - 1) | (a_sel << 2) | (mp << 3) | (w_sel << 6) | (chunk0 << 8));
  };
  const char* plan = "ccccccccccc cccccccccc ccccccc cccc xxxx xxxx xxxxxx xxxxxxxx";
  int TIE = 0;
  int XA = 0;
  const char* cur[8];
  int tend[8] = {};
  for (int g = 0; g < 8; g++) {
    cur[g] = plan;
    while (*plan == 'c' || *plan == 'x') plan++;
    if (*plan) plan++;
  }
  int kc = 0, kx = 0;
  for (;;) {
    int b = -1, bt = 0;
    for (int g = 0; g < 8; g++) {
      const int t = tend[g] + (*cur[g] == 'x' ? 94 : 85);
      if ((*cur[g] == 'c' || *cur[g] == 'x') && (b < 0 || t < bt || (TIE && t == bt))) { b = g; bt = t; }
    }
    if (b < 0) break;
    const int a = kx - XA;
    for (int mp = 0; mp < 8; mp++) {
      if (*cur[b] == 'c') add(b * 8 + mp, 4, 0, mp, kc & 1, (kc >> 1) * 4);
      else if (a >= 0 && a < 7) add(b * 8 + mp, a == 0 ? 3 : 4, 1, mp, 2, a == 0 ? 24 : (a - 1) * 4);
      else add(b * 8 + mp, 4, 1, mp, 3, (a < 0 ? kx : kx - 7) * 4);
    }
    if (*cur[b] == 'c') kc++; else kx++;
    cur[b]++;
    tend[b] = bt;
  }
  for (int mp = 0; mp < 8; mp++) add(64 + mp / 4, 4, 1, mp, 3, 15 * 4);
  for (int cc = 0; cc < NCLUSTER; cc++)
    for (int i = 0; i < cnt[cc]; i++) {
      const int key = p.jobs[cc][i] & 0x3C;
      if (i == 0 || (p.jobs[cc][i - 1] & 0x3C) != key) p.jobs[cc][i] |= (1 << 14);
      if (i == cnt[cc] - 1 || (p.jobs[cc][i + 1] & 0x3C) != key) p.jobs[cc][i] |= (1 << 15);
    }
}

static void build_k2_items(Params& p) {
  int ps[8][3] = {{0, 2, 2}, {0, 6, 0}, {6, 24, 4}, {6, 32, 0}};
  bool done[256] = {};
  int n = 0;
  for (int i = 0; i < 8; i++)
    for (int j = 7; j >= ps[i][2]; j--)
      for (int h = ps[i][0]; h < ps[i][1]; h++)
        if (!done[h * 8 + j]) { done[h * 8 + j] = true; p.order[n++] = (uint8_t)(h * 8 + j); }
}

static void build_k3_units(Params& p) {
  const char* map = "0123456789abcddcba98765432100123456789abcddcba9876543210feeffeeffe";
  int cnt[16] = {};
  for (int u = 0; u < 66; u++) {
    const int t = (map[u] > '9') ? map[u] - 'a' + 10 : map[u] - '0';
    p.unit[u][0] = (uint8_t)t; p.unit[u][1] = (uint8_t)cnt[t]; p.unit[u][2] = (uint8_t)(cnt[t] * K3_NS);
    cnt[t]++;
  }
  for (int u = 0; u < 66; u++) p.unit[u][3] = (uint8_t)(cnt[p.unit[u][0]] * K3_NS);
}

extern "C" void kernel_launch(void* const* d_in, const int* in_sizes, int n_in, void* d_out, int out_size) {
  const bf16* x = (const bf16*)d_in[0];
  const bf16* wqkv = (const bf16*)d_in[1];
  const bf16* wo = (const bf16*)d_in[2];
  const bf16* ckv = (const bf16*)d_in[4];
  const bf16* w_q = (const bf16*)d_in[5];
  const bf16* w_uk = (const bf16*)d_in[6];
  const bf16* w_uv = (const bf16*)d_in[7];
  const bf16* w_o = (const bf16*)d_in[8];
  const bf16* gate_w = (const bf16*)d_in[9];

  EncFn enc = nullptr;
  cudaDriverEntryPointQueryResult qr;
  cudaGetDriverEntryPoint("cuTensorMapEncodeTiled", (void**)&enc, cudaEnableDefault, &qr);
  void *pK, *pV, *pCtx, *pQA;
  cudaGetSymbolAddress(&pQA, g_QKVA);
  cudaGetSymbolAddress(&pK, g_K);
  cudaGetSymbolAddress(&pV, g_V);
  cudaGetSymbolAddress(&pCtx, g_ctx);

  static Params p;
  enc2d(enc, &p.tmA[0], ckv, DC, S_LEN, 64, 128);
  enc2d(enc, &p.tmA[1], x, DM, S_LEN, 64, 128);
  enc3d(enc, &p.tmW[0], w_uk, HDIM, DC, 16, 4);
  enc3d(enc, &p.tmW[1], w_uv, HDIM, DC, 16, 4);
  enc3d(enc, &p.tmW[2], wqkv, NQKVA, DM, 16, 4);
  enc3d(enc, &p.tmW[3], w_q, HDIM, DM, 16, 4);
  build_k1_jobs(p);
  enc2d(enc, &p.tmK, pK, 64, 64 * S_LEN, 64, 128);
  enc2d(enc, &p.tmV, pV, 64, 64 * S_LEN, 64, 128);
  enc2d(enc, &p.tmQ, pCtx, 64, 73 * S_LEN, 64, 64);
  build_k2_items(p);
  build_k3_units(p);
  for (int i = 0; i < 3; i++) {
    const cuuint64_t cs = S_LEN * 128, nch = (i < 2) ? 27 : 9;
    cuuint64_t gd[4] = {64, S_LEN / 2, i ? 2 : nch, i ? nch : 2}, gs[3] = {256, i ? 128 : cs, i ? cs : 128};
    cuuint32_t bx[4] = {64, i ? 8u : 16u, i ? 2u : 9u, i ? 9u : 2u}, es[4] = {1, 1, 1, 1};
    enc(&p.tmL[i], CU_TENSOR_MAP_DATA_TYPE_BFLOAT16, 4, (i < 2) ? pQA : (void*)((bf16*)pCtx + S_LEN * HDIM), gd, gs, bx, es, CU_TENSOR_MAP_INTERLEAVE_NONE,
        CU_TENSOR_MAP_SWIZZLE_128B, CU_TENSOR_MAP_L2_PROMOTION_L2_256B, CU_TENSOR_MAP_FLOAT_OOB_FILL_NONE);
  }
  enc2d(enc, &p.tmC, pCtx, 64, 73 * S_LEN, 64, 128);
  enc3d(enc, &p.tmO[0], w_o, DM, HDIM, 32, 4);
  enc3d(enc, &p.tmO[1], wo, DM, DM, 32, 4);
  enc2d(enc, &p.tmOt[0], w_o, DM, HDIM, 32, 32, CU_TENSOR_MAP_SWIZZLE_64B);
  enc2d(enc, &p.tmOt[1], wo, DM, DM, 32, 32, CU_TENSOR_MAP_SWIZZLE_64B);
  enc2d(enc, &p.tmR[0], d_out, DM, S_LEN, 64, 16);
  enc2d(enc, &p.tmR[1], d_out, DM, S_LEN, 32, 16, CU_TENSOR_MAP_SWIZZLE_64B);

  cudaFuncSetAttribute(fused_kernel, cudaFuncAttributeMaxDynamicSharedMemorySize, SMEM_BYTES);
  fused_kernel<<<NCLUSTER * 2, 384, SMEM_BYTES>>>(p, x, gate_w, (bf16*)d_out);
}
```

```cpp
#include <cuda_runtime.h>
#include <cuda_bf16.h>
#include <cuda.h>
#include <stdint.h>

typedef __nv_bfloat16 bf16;

constexpr int S_LEN = 2048, DM = 576, DC = 512, HDIM = 4096, NQKVA = 1728, KCAT = 4672;
constexpr int NCLUSTER = 66;
__host__ __device__ constexpr int goff(int G, int r) { return (G >> 1) * S_LEN * 64 + (G & 1) * 32 + r * 512; }

__device__ __align__(1024) bf16 g_K[S_LEN * HDIM];
__device__ __align__(1024) bf16 g_V[S_LEN * HDIM];
__device__ __align__(1024) bf16 g_QKVA[S_LEN * NQKVA + 64];
__device__ __align__(1024) bf16 g_ctx[S_LEN * KCAT];
__device__ float g_gate[S_LEN];
__device__ __align__(16) unsigned int g_sync[400];
constexpr int F_QKVA = 0, F_HP = 16, F_CTX = 32, F_OA = 48, F_CLM = 64, F_GATE = 96, F_TICK = 97, F_DONE = 98, F_XCH = 128, F_EPOCH = 384;

__device__ __forceinline__ uint32_t smem_u32(const void* p) { return (uint32_t)__cvta_generic_to_shared(p); }
__device__ __forceinline__ void mbar_init(uint32_t a, uint32_t c) {
  asm volatile("mbarrier.init.shared::cta.b64 [%0], %1;" ::"r"(a), "r"(c));
}
__device__ __forceinline__ void mbar_expect(uint32_t a, uint32_t b) {
  asm volatile("mbarrier.arrive.expect_tx.shared::cta.b64 _, [%0], %1;" ::"r"(a), "r"(b) : "memory");
}
#define TS(k, i)
#define TSC(k, i)
#define TSM(k)
#define BSEG(i)
#define TB(k)
#define TRC(fl)
#define TCK(i)
#define TP(i)
#define SPIN_LIMIT "4194304"
__device__ __forceinline__ void mbar_wait(uint32_t a, uint32_t parity) {
  asm volatile(
      "{\n.reg .pred p;\n.reg .u32 n;\n"
      "mbarrier.try_wait.parity.shared::cta.b64 p, [%0], %1;\n"
      "@p bra DONE;\n"
      "mov.u32 n, 0;\n"
      "LOOP:\n"
      "mbarrier.try_wait.parity.shared::cta.b64 p, [%0], %1;\n"
      "@p bra DONE;\n"
      "add.u32 n, n, 1;\n"
      "setp.lt.u32 p, n, " SPIN_LIMIT ";\n"
      "@p bra LOOP;\n"
      "DONE:\n}" ::"r"(a), "r"(parity) : "memory");
}
template <int NS>
__device__ __forceinline__ void mbar_wait_ns(uint32_t a, uint32_t parity) {
  asm volatile(
      "{\n.reg .pred p;\n.reg .u32 n;\n"
      "mov.u32 n, 0;\n"
      "LOOP:\n"
      "mbarrier.try_wait.parity.shared::cta.b64 p, [%0], %1, %2;\n"
      "@p bra DONE;\n"
      "add.u32 n, n, 1;\n"
      "setp.lt.u32 p, n, " SPIN_LIMIT ";\n"
      "@p bra LOOP;\n"
      "DONE:\n}" ::"r"(a), "r"(parity), "n"(NS) : "memory");
}
__device__ __forceinline__ void mbar_wait2(uint32_t a, uint32_t pa, uint32_t b, uint32_t pb) {
  asm volatile(
      "{\n.reg .pred p, q;\n.reg .u32 n;\n"
      "mov.u32 n, 0;\n"
      "LOOP:\n"
      "mbarrier.try_wait.parity.shared::cta.b64 p, [%0], %1;\n"
      "mbarrier.try_wait.parity.shared::cta.b64 q, [%2], %3;\n"
      "add.u32 n, n, 1;\n"
      "and.pred p, p, q;\n"
      "setp.lt.and.u32 p, n, " SPIN_LIMIT ", !p;\n"
      "@p bra LOOP;\n"
      "}" ::"r"(a), "r"(pa), "r"(b), "r"(pb) : "memory");
}
__device__ __forceinline__ uint32_t mbar_test(uint32_t a, uint32_t parity) {
  uint32_t r;
  asm volatile("{\n.reg .pred p;\nmbarrier.test_wait.parity.shared::cta.b64 p, [%1], %2;\nselp.u32 %0, 1, 0, p;\n}" : "=r"(r) : "r"(a), "r"(parity) : "memory");
  return r;
}
__device__ __forceinline__ void mbar_arrive(uint32_t a) {
  asm volatile("mbarrier.arrive.shared::cta.b64 _, [%0];" ::"r"(a) : "memory");
}
__device__ __forceinline__ void mbar_arrive_cluster(uint32_t a, uint32_t cta) {
  asm volatile("{\n.reg .b32 r;\nmapa.shared::cluster.u32 r, %0, %1;\nmbarrier.arrive.shared::cluster.b64 _, [r];\n}" ::"r"(a),
               "r"(cta) : "memory");
}
__device__ __forceinline__ void mbar_arrive_cluster_if(uint32_t a, uint32_t cta, bool pred) {
  asm volatile("{\n.reg .b32 r;\n.reg .pred p;\nsetp.ne.u32 p, %2, 0;\nmapa.shared::cluster.u32 r, %0, %1;\n@p mbarrier.arrive.shared::cluster.b64 _, [r];\n}" ::"r"(a),
               "r"(cta), "r"((uint32_t)pred) : "memory");
}
__device__ __forceinline__ void anchor(float v, uint32_t pred) {
  asm volatile("{\n.reg .pred p;\nsetp.ne.u32 p, %1, 0;\n@p st.shared.f32 [%1], %0;\n}" ::"f"(v), "r"(pred) : "memory");
}
__device__ __forceinline__ void mbar_arrive_if(uint32_t a, bool pred) {
  asm volatile("{\n.reg .pred p;\nsetp.ne.u32 p, %1, 0;\n@p mbarrier.arrive.shared::cta.b64 _, [%0];\n}" ::"r"(a), "r"((uint32_t)pred) : "memory");
}
__device__ __forceinline__ void tma2d(uint32_t dst, const CUtensorMap* m, uint32_t bar, int c0, int c1) {
  asm volatile("cp.async.bulk.tensor.2d.shared::cluster.global.mbarrier::complete_tx::bytes [%0], [%1, {%3, %4}], [%2];" ::"r"(dst),
               "l"(m), "r"(bar), "r"(c0), "r"(c1) : "memory");
}
__device__ __forceinline__ void tma2d_mc(uint32_t dst, const CUtensorMap* m, uint32_t bar, int c0, int c1, uint16_t mask) {
  asm volatile(
      "cp.async.bulk.tensor.2d.shared::cluster.global.mbarrier::complete_tx::bytes.multicast::cluster [%0], [%1, {%3, %4}], [%2], %5;" ::"r"(dst),
      "l"(m), "r"(bar), "r"(c0), "r"(c1), "h"(mask) : "memory");
}
__device__ __forceinline__ void tma3d_mc(uint32_t dst, const CUtensorMap* m, uint32_t bar, int c0, int c1, int c2, uint16_t mask) {
  asm volatile(
      "cp.async.bulk.tensor.3d.shared::cluster.global.mbarrier::complete_tx::bytes.multicast::cluster [%0], [%1, {%3, %4, %5}], [%2], %6;" ::"r"(dst),
      "l"(m), "r"(bar), "r"(c0), "r"(c1), "r"(c2), "h"(mask) : "memory");
}
__device__ __forceinline__ void tma3d(uint32_t dst, const CUtensorMap* m, uint32_t bar, int c0, int c1, int c2) {
  asm volatile(
      "cp.async.bulk.tensor.3d.shared::cluster.global.mbarrier::complete_tx::bytes [%0], [%1, {%3, %4, %5}], [%2];" ::"r"(dst),
      "l"(m), "r"(bar), "r"(c0), "r"(c1), "r"(c2) : "memory");
}
__device__ __forceinline__ void tma_pf2d(const CUtensorMap* m, int c0, int c1) {
  asm volatile("cp.async.bulk.prefetch.tensor.2d.L2.global [%0, {%1, %2}];" ::"l"(m), "r"(c0), "r"(c1) : "memory");
}
__device__ __forceinline__ void tma_pf3d(const CUtensorMap* m, int c0, int c1, int c2) {
  asm volatile("cp.async.bulk.prefetch.tensor.3d.L2.global [%0, {%1, %2, %3}];" ::"l"(m), "r"(c0), "r"(c1), "r"(c2) : "memory");
}
__device__ __forceinline__ void prefetch_tmap(const CUtensorMap* m) {
  asm volatile("prefetch.tensormap [%0];" ::"l"(m) : "memory");
}
__device__ __forceinline__ void cluster_arrive() { asm volatile("barrier.cluster.arrive.relaxed.aligned;" ::: "memory"); }
__device__ __forceinline__ void cluster_wait() { asm volatile("barrier.cluster.wait.aligned;" ::: "memory"); }
__device__ __forceinline__ void cluster_sync() {
  cluster_arrive();
  cluster_wait();
}
__device__ __forceinline__ uint32_t cluster_rank() {
  uint32_t r;
  asm volatile("mov.u32 %0, %%cluster_ctarank;" : "=r"(r));
  return r;
}
__device__ __forceinline__ bool elect_one() {
  uint32_t p;
  asm volatile("{\n.reg .pred q;\nelect.sync _|q, 0xffffffff;\nselp.u32 %0, 1, 0, q;\n}" : "=r"(p));
  return p;
}
__device__ __forceinline__ void ldsm_x4(uint32_t& r0, uint32_t& r1, uint32_t& r2, uint32_t& r3, uint32_t addr) {
  asm volatile("ldmatrix.sync.aligned.m8n8.x4.shared.b16 {%0, %1, %2, %3}, [%4];" : "=r"(r0), "=r"(r1), "=r"(r2), "=r"(r3) : "r"(addr) : "memory");
}
__device__ __forceinline__ void wg_fence() { asm volatile("wgmma.fence.sync.aligned;" ::: "memory"); }
__device__ __forceinline__ void wg_commit() { asm volatile("wgmma.commit_group.sync.aligned;" ::: "memory"); }
template <int N>
__device__ __forceinline__ void wg_wait() { asm volatile("wgmma.wait_group.sync.aligned %0;" ::"n"(N) : "memory"); }
template <int N>
__device__ __forceinline__ void reg_alloc() { asm volatile("setmaxnreg.inc.sync.aligned.u32 %0;" ::"n"(N)); }
template <int N>
__device__ __forceinline__ void reg_dealloc() { asm volatile("setmaxnreg.dec.sync.aligned.u32 %0;" ::"n"(N)); }
__device__ __forceinline__ void bar_sync(int id, int n) { asm volatile("bar.sync %0, %1;" ::"r"(id), "r"(n) : "memory"); }
__device__ __forceinline__ void bar_arrive(int id, int n) { asm volatile("bar.arrive %0, %1;" ::"r"(id), "r"(n) : "memory"); }
template <int NT>
__device__ __forceinline__ void fence_regs(float (&d)[NT]) {
#pragma unroll
  for (int i = 0; i < NT; i++) asm volatile("" : "+f"(d[i])::"memory");
}
template <int NT>
__device__ __forceinline__ void fence_regs(uint32_t (&d)[NT]) {
#pragma unroll
  for (int i = 0; i < NT; i++) asm volatile("" : "+r"(d[i])::"memory");
}
__device__ __forceinline__ uint64_t make_desc(uint32_t saddr, uint32_t lbo, uint32_t sbo, uint32_t layout) {
  return (uint64_t)((saddr & 0x3FFFF) >> 4) | ((uint64_t)(lbo >> 4) << 16) | ((uint64_t)(sbo >> 4) << 32) | ((uint64_t)layout << 62);
}
__device__ __forceinline__ uint32_t pack_bf16(float lo, float hi) {
  uint32_t r;
  asm("cvt.rn.bf16x2.f32 %0, %1, %2;" : "=r"(r) : "f"(hi), "f"(lo));
  return r;
}
__device__ __forceinline__ float ex2(float x) {
  float r;
  asm("ex2.approx.ftz.f32 %0, %1;" : "=f"(r) : "f"(x));
  return r;
}
__device__ __forceinline__ void st_v4(void* p, uint32_t a, uint32_t b, uint32_t c, uint32_t d) {
#define ST_MOD ".cs"
  asm volatile("st.global" ST_MOD ".v4.b32 [%0], {%1, %2, %3, %4};" ::"l"(p), "r"(a), "r"(b), "r"(c), "r"(d) : "memory");
}
#define STA_MOD ".cs"
__device__ __forceinline__ void st_v4a(void* p, uint32_t a, uint32_t b, uint32_t c, uint32_t d) {
  asm volatile("st.global" STA_MOD ".v4.b32 [%0], {%1, %2, %3, %4};" ::"l"(p), "r"(a), "r"(b), "r"(c), "r"(d) : "memory");
}
template <typename T>
__device__ __forceinline__ T* ptr_add(T* base, uint32_t bytes) {
  uint64_t r;
  asm volatile("{\n.reg .u32 l, h;\nmov.b64 {l, h}, %1;\nadd.cc.u32 l, l, %2;\naddc.u32 h, h, 0;\nmov.b64 %0, {l, h};\n}" : "=l"(r) : "l"(base), "r"(bytes));
  return reinterpret_cast<T*>(r);
}
__device__ __forceinline__ float bf_lo(uint32_t v) { return __uint_as_float(v << 16); }
__device__ __forceinline__ float bf_hi(uint32_t v) { return __uint_as_float(v & 0xFFFF0000u); }

__device__ __forceinline__ void quad_transpose(uint32_t& a0, uint32_t& a1, uint32_t& a2, uint32_t& a3, int q) {
  const bool o1 = q & 1, o2 = q & 2;
  uint32_t t0 = o1 ? a0 : a1, t1 = o1 ? a2 : a3;
  t0 = __shfl_xor_sync(0xffffffffu, t0, 1);
  t1 = __shfl_xor_sync(0xffffffffu, t1, 1);
  if (o1) { a0 = t0; a2 = t1; } else { a1 = t0; a3 = t1; }
  t0 = o2 ? a0 : a2;
  t1 = o2 ? a1 : a3;
  t0 = __shfl_xor_sync(0xffffffffu, t0, 2);
  t1 = __shfl_xor_sync(0xffffffffu, t1, 2);
  if (o2) { a0 = t0; a1 = t1; } else { a2 = t0; a3 = t1; }
}

template<int TB, int OFF, int NT>
__device__ __forceinline__ void wgmma_ss_n256(float (&d)[NT], uint64_t da, uint64_t db, int scale_d) {
  asm volatile("{\n.reg .pred p;\nsetp.ne.b32 p, %130, 0;\n"
    "wgmma.mma_async.sync.aligned.m64n256k16.f32.bf16.bf16 {%0, %1, %2, %3, %4, %5, %6, %7, %8, %9, %10, %11, %12, %13, %14, %15, %16, %17, %18, %19, %20, %21, %22, %23, %24, %25, %26, %27, %28, %29, %30, %31, %32, %33, %34, %35, %36, %37, %38, %39, %40, %41, %42, %43, %44, %45, %46, %47, %48, %49, %50, %51, %52, %53, %54, %55, %56, %57, %58, %59, %60, %61, %62, %63, %64, %65, %66, %67, %68, %69, %70, %71, %72, %73, %74, %75, %76, %77, %78, %79, %80, %81, %82, %83, %84, %85, %86, %87, %88, %89, %90, %91, %92, %93, %94, %95, %96, %97, %98, %99, %100, %101, %102, %103, %104, %105, %106, %107, %108, %109, %110, %111, %112, %113, %114, %115, %116, %117, %118, %119, %120, %121, %122, %123, %124, %125, %126, %127}, %128, %129, p, 1, 1, 0, %131;\n}\n"
    : "+f"(d[OFF+0]), "+f"(d[OFF+1]), "+f"(d[OFF+2]), "+f"(d[OFF+3]), "+f"(d[OFF+4]), "+f"(d[OFF+5]), "+f"(d[OFF+6]), "+f"(d[OFF+7]), "+f"(d[OFF+8]), "+f"(d[OFF+9]), "+f"(d[OFF+10]), "+f"(d[OFF+11]), "+f"(d[OFF+12]), "+f"(d[OFF+13]), "+f"(d[OFF+14]), "+f"(d[OFF+15]), "+f"(d[OFF+16]), "+f"(d[OFF+17]), "+f"(d[OFF+18]), "+f"(d[OFF+19]), "+f"(d[OFF+20]), "+f"(d[OFF+21]), "+f"(d[OFF+22]), "+f"(d[OFF+23]), "+f"(d[OFF+24]), "+f"(d[OFF+25]), "+f"(d[OFF+26]), "+f"(d[OFF+27]), "+f"(d[OFF+28]), "+f"(d[OFF+29]), "+f"(d[OFF+30]), "+f"(d[OFF+31]), "+f"(d[OFF+32]), "+f"(d[OFF+33]), "+f"(d[OFF+34]), "+f"(d[OFF+35]), "+f"(d[OFF+36]), "+f"(d[OFF+37]), "+f"(d[OFF+38]), "+f"(d[OFF+39]), "+f"(d[OFF+40]), "+f"(d[OFF+41]), "+f"(d[OFF+42]), "+f"(d[OFF+43]), "+f"(d[OFF+44]), "+f"(d[OFF+45]), "+f"(d[OFF+46]), "+f"(d[OFF+47]), "+f"(d[OFF+48]), "+f"(d[OFF+49]), "+f"(d[OFF+50]), "+f"(d[OFF+51]), "+f"(d[OFF+52]), "+f"(d[OFF+53]), "+f"(d[OFF+54]), "+f"(d[OFF+55]), "+f"(d[OFF+56]), "+f"(d[OFF+57]), "+f"(d[OFF+58]), "+f"(d[OFF+59]), "+f"(d[OFF+60]), "+f"(d[OFF+61]), "+f"(d[OFF+62]), "+f"(d[OFF+63]), "+f"(d[OFF+64]), "+f"(d[OFF+65]), "+f"(d[OFF+66]), "+f"(d[OFF+67]), "+f"(d[OFF+68]), "+f"(d[OFF+69]), "+f"(d[OFF+70]), "+f"(d[OFF+71]), "+f"(d[OFF+72]), "+f"(d[OFF+73]), "+f"(d[OFF+74]), "+f"(d[OFF+75]), "+f"(d[OFF+76]), "+f"(d[OFF+77]), "+f"(d[OFF+78]), "+f"(d[OFF+79]), "+f"(d[OFF+80]), "+f"(d[OFF+81]), "+f"(d[OFF+82]), "+f"(d[OFF+83]), "+f"(d[OFF+84]), "+f"(d[OFF+85]), "+f"(d[OFF+86]), "+f"(d[OFF+87]), "+f"(d[OFF+88]), "+f"(d[OFF+89]), "+f"(d[OFF+90]), "+f"(d[OFF+91]), "+f"(d[OFF+92]), "+f"(d[OFF+93]), "+f"(d[OFF+94]), "+f"(d[OFF+95]), "+f"(d[OFF+96]), "+f"(d[OFF+97]), "+f"(d[OFF+98]), "+f"(d[OFF+99]), "+f"(d[OFF+100]), "+f"(d[OFF+101]), "+f"(d[OFF+102]), "+f"(d[OFF+103]), "+f"(d[OFF+104]), "+f"(d[OFF+105]), "+f"(d[OFF+106]), "+f"(d[OFF+107]), "+f"(d[OFF+108]), "+f"(d[OFF+109]), "+f"(d[OFF+110]), "+f"(d[OFF+111]), "+f"(d[OFF+112]), "+f"(d[OFF+113]), "+f"(d[OFF+114]), "+f"(d[OFF+115]), "+f"(d[OFF+116]), "+f"(d[OFF+117]), "+f"(d[OFF+118]), "+f"(d[OFF+119]), "+f"(d[OFF+120]), "+f"(d[OFF+121]), "+f"(d[OFF+122]), "+f"(d[OFF+123]), "+f"(d[OFF+124]), "+f"(d[OFF+125]), "+f"(d[OFF+126]), "+f"(d[OFF+127])
    : "l"(da), "l"(db), "r"(scale_d), "n"(TB));
}
template<int TB, int OFF, int NT>
__device__ __forceinline__ void wgmma_ss_n32(float (&d)[NT], uint64_t da, uint64_t db, int scale_d) {
  asm volatile("{\n.reg .pred p;\nsetp.ne.b32 p, %18, 0;\n"
    "wgmma.mma_async.sync.aligned.m64n32k16.f32.bf16.bf16 {%0, %1, %2, %3, %4, %5, %6, %7, %8, %9, %10, %11, %12, %13, %14, %15}, %16, %17, p, 1, 1, 0, %19;\n}\n"
    : "+f"(d[OFF+0]), "+f"(d[OFF+1]), "+f"(d[OFF+2]), "+f"(d[OFF+3]), "+f"(d[OFF+4]), "+f"(d[OFF+5]), "+f"(d[OFF+6]), "+f"(d[OFF+7]), "+f"(d[OFF+8]), "+f"(d[OFF+9]), "+f"(d[OFF+10]), "+f"(d[OFF+11]), "+f"(d[OFF+12]), "+f"(d[OFF+13]), "+f"(d[OFF+14]), "+f"(d[OFF+15])
    : "l"(da), "l"(db), "r"(scale_d), "n"(TB));
}
template<int TB, int OFF, int NT>
__device__ __forceinline__ void wgmma_rs_n128(float (&d)[NT], uint32_t a0, uint32_t a1, uint32_t a2, uint32_t a3, uint64_t db, int scale_d) {
  asm volatile("{\n.reg .pred p;\nsetp.ne.b32 p, %69, 0;\n"
    "wgmma.mma_async.sync.aligned.m64n128k16.f32.bf16.bf16 {%0, %1, %2, %3, %4, %5, %6, %7, %8, %9, %10, %11, %12, %13, %14, %15, %16, %17, %18, %19, %20, %21, %22, %23, %24, %25, %26, %27, %28, %29, %30, %31, %32, %33, %34, %35, %36, %37, %38, %39, %40, %41, %42, %43, %44, %45, %46, %47, %48, %49, %50, %51, %52, %53, %54, %55, %56, %57, %58, %59, %60, %61, %62, %63}, {%64, %65, %66, %67}, %68, p, 1, 1, %70;\n}\n"
    : "+f"(d[OFF+0]), "+f"(d[OFF+1]), "+f"(d[OFF+2]), "+f"(d[OFF+3]), "+f"(d[OFF+4]), "+f"(d[OFF+5]), "+f"(d[OFF+6]), "+f"(d[OFF+7]), "+f"(d[OFF+8]), "+f"(d[OFF+9]), "+f"(d[OFF+10]), "+f"(d[OFF+11]), "+f"(d[OFF+12]), "+f"(d[OFF+13]), "+f"(d[OFF+14]), "+f"(d[OFF+15]), "+f"(d[OFF+16]), "+f"(d[OFF+17]), "+f"(d[OFF+18]), "+f"(d[OFF+19]), "+f"(d[OFF+20]), "+f"(d[OFF+21]), "+f"(d[OFF+22]), "+f"(d[OFF+23]), "+f"(d[OFF+24]), "+f"(d[OFF+25]), "+f"(d[OFF+26]), "+f"(d[OFF+27]), "+f"(d[OFF+28]), "+f"(d[OFF+29]), "+f"(d[OFF+30]), "+f"(d[OFF+31]), "+f"(d[OFF+32]), "+f"(d[OFF+33]), "+f"(d[OFF+34]), "+f"(d[OFF+35]), "+f"(d[OFF+36]), "+f"(d[OFF+37]), "+f"(d[OFF+38]), "+f"(d[OFF+39]), "+f"(d[OFF+40]), "+f"(d[OFF+41]), "+f"(d[OFF+42]), "+f"(d[OFF+43]), "+f"(d[OFF+44]), "+f"(d[OFF+45]), "+f"(d[OFF+46]), "+f"(d[OFF+47]), "+f"(d[OFF+48]), "+f"(d[OFF+49]), "+f"(d[OFF+50]), "+f"(d[OFF+51]), "+f"(d[OFF+52]), "+f"(d[OFF+53]), "+f"(d[OFF+54]), "+f"(d[OFF+55]), "+f"(d[OFF+56]), "+f"(d[OFF+57]), "+f"(d[OFF+58]), "+f"(d[OFF+59]), "+f"(d[OFF+60]), "+f"(d[OFF+61]), "+f"(d[OFF+62]), "+f"(d[OFF+63])
    : "r"(a0), "r"(a1), "r"(a2), "r"(a3), "l"(db), "r"(scale_d), "n"(TB));
}
template<int TB, int OFF, int NT>
__device__ __forceinline__ void wgmma_rs_n256(float (&d)[NT], uint32_t a0, uint32_t a1, uint32_t a2, uint32_t a3, uint64_t db, int scale_d) {
  asm volatile("{\n.reg .pred p;\nsetp.ne.b32 p, %133, 0;\n"
    "wgmma.mma_async.sync.aligned.m64n256k16.f32.bf16.bf16 {%0, %1, %2, %3, %4, %5, %6, %7, %8, %9, %10, %11, %12, %13, %14, %15, %16, %17, %18, %19, %20, %21, %22, %23, %24, %25, %26, %27, %28, %29, %30, %31, %32, %33, %34, %35, %36, %37, %38, %39, %40, %41, %42, %43, %44, %45, %46, %47, %48, %49, %50, %51, %52, %53, %54, %55, %56, %57, %58, %59, %60, %61, %62, %63, %64, %65, %66, %67, %68, %69, %70, %71, %72, %73, %74, %75, %76, %77, %78, %79, %80, %81, %82, %83, %84, %85, %86, %87, %88, %89, %90, %91, %92, %93, %94, %95, %96, %97, %98, %99, %100, %101, %102, %103, %104, %105, %106, %107, %108, %109, %110, %111, %112, %113, %114, %115, %116, %117, %118, %119, %120, %121, %122, %123, %124, %125, %126, %127}, {%128, %129, %130, %131}, %132, p, 1, 1, %134;\n}\n"
    : "+f"(d[OFF+0]), "+f"(d[OFF+1]), "+f"(d[OFF+2]), "+f"(d[OFF+3]), "+f"(d[OFF+4]), "+f"(d[OFF+5]), "+f"(d[OFF+6]), "+f"(d[OFF+7]), "+f"(d[OFF+8]), "+f"(d[OFF+9]), "+f"(d[OFF+10]), "+f"(d[OFF+11]), "+f"(d[OFF+12]), "+f"(d[OFF+13]), "+f"(d[OFF+14]), "+f"(d[OFF+15]), "+f"(d[OFF+16]), "+f"(d[OFF+17]), "+f"(d[OFF+18]), "+f"(d[OFF+19]), "+f"(d[OFF+20]), "+f"(d[OFF+21]), "+f"(d[OFF+22]), "+f"(d[OFF+23]), "+f"(d[OFF+24]), "+f"(d[OFF+25]), "+f"(d[OFF+26]), "+f"(d[OFF+27]), "+f"(d[OFF+28]), "+f"(d[OFF+29]), "+f"(d[OFF+30]), "+f"(d[OFF+31]), "+f"(d[OFF+32]), "+f"(d[OFF+33]), "+f"(d[OFF+34]), "+f"(d[OFF+35]), "+f"(d[OFF+36]), "+f"(d[OFF+37]), "+f"(d[OFF+38]), "+f"(d[OFF+39]), "+f"(d[OFF+40]), "+f"(d[OFF+41]), "+f"(d[OFF+42]), "+f"(d[OFF+43]), "+f"(d[OFF+44]), "+f"(d[OFF+45]), "+f"(d[OFF+46]), "+f"(d[OFF+47]), "+f"(d[OFF+48]), "+f"(d[OFF+49]), "+f"(d[OFF+50]), "+f"(d[OFF+51]), "+f"(d[OFF+52]), "+f"(d[OFF+53]), "+f"(d[OFF+54]), "+f"(d[OFF+55]), "+f"(d[OFF+56]), "+f"(d[OFF+57]), "+f"(d[OFF+58]), "+f"(d[OFF+59]), "+f"(d[OFF+60]), "+f"(d[OFF+61]), "+f"(d[OFF+62]), "+f"(d[OFF+63]), "+f"(d[OFF+64]), "+f"(d[OFF+65]), "+f"(d[OFF+66]), "+f"(d[OFF+67]), "+f"(d[OFF+68]), "+f"(d[OFF+69]), "+f"(d[OFF+70]), "+f"(d[OFF+71]), "+f"(d[OFF+72]), "+f"(d[OFF+73]), "+f"(d[OFF+74]), "+f"(d[OFF+75]), "+f"(d[OFF+76]), "+f"(d[OFF+77]), "+f"(d[OFF+78]), "+f"(d[OFF+79]), "+f"(d[OFF+80]), "+f"(d[OFF+81]), "+f"(d[OFF+82]), "+f"(d[OFF+83]), "+f"(d[OFF+84]), "+f"(d[OFF+85]), "+f"(d[OFF+86]), "+f"(d[OFF+87]), "+f"(d[OFF+88]), "+f"(d[OFF+89]), "+f"(d[OFF+90]), "+f"(d[OFF+91]), "+f"(d[OFF+92]), "+f"(d[OFF+93]), "+f"(d[OFF+94]), "+f"(d[OFF+95]), "+f"(d[OFF+96]), "+f"(d[OFF+97]), "+f"(d[OFF+98]), "+f"(d[OFF+99]), "+f"(d[OFF+100]), "+f"(d[OFF+101]), "+f"(d[OFF+102]), "+f"(d[OFF+103]), "+f"(d[OFF+104]), "+f"(d[OFF+105]), "+f"(d[OFF+106]), "+f"(d[OFF+107]), "+f"(d[OFF+108]), "+f"(d[OFF+109]), "+f"(d[OFF+110]), "+f"(d[OFF+111]), "+f"(d[OFF+112]), "+f"(d[OFF+113]), "+f"(d[OFF+114]), "+f"(d[OFF+115]), "+f"(d[OFF+116]), "+f"(d[OFF+117]), "+f"(d[OFF+118]), "+f"(d[OFF+119]), "+f"(d[OFF+120]), "+f"(d[OFF+121]), "+f"(d[OFF+122]), "+f"(d[OFF+123]), "+f"(d[OFF+124]), "+f"(d[OFF+125]), "+f"(d[OFF+126]), "+f"(d[OFF+127])
    : "r"(a0), "r"(a1), "r"(a2), "r"(a3), "l"(db), "r"(scale_d), "n"(TB));
}
template<int TB, int OFF, int NT>
__device__ __forceinline__ void wgmma_rs_n32(float (&d)[NT], uint32_t a0, uint32_t a1, uint32_t a2, uint32_t a3, uint64_t db, int scale_d) {
  asm volatile("{\n.reg .pred p;\nsetp.ne.b32 p, %21, 0;\n"
    "wgmma.mma_async.sync.aligned.m64n32k16.f32.bf16.bf16 {%0, %1, %2, %3, %4, %5, %6, %7, %8, %9, %10, %11, %12, %13, %14, %15}, {%16, %17, %18, %19}, %20, p, 1, 1, %22;\n}\n"
    : "+f"(d[OFF+0]), "+f"(d[OFF+1]), "+f"(d[OFF+2]), "+f"(d[OFF+3]), "+f"(d[OFF+4]), "+f"(d[OFF+5]), "+f"(d[OFF+6]), "+f"(d[OFF+7]), "+f"(d[OFF+8]), "+f"(d[OFF+9]), "+f"(d[OFF+10]), "+f"(d[OFF+11]), "+f"(d[OFF+12]), "+f"(d[OFF+13]), "+f"(d[OFF+14]), "+f"(d[OFF+15])
    : "r"(a0), "r"(a1), "r"(a2), "r"(a3), "l"(db), "r"(scale_d), "n"(TB));
}

__device__ __forceinline__ void wait_flag(const unsigned int* f, uint32_t target) {
  uint32_t v;
#pragma unroll 1
  for (uint32_t spins = 0; spins < (1u << 22); spins++) {
    asm volatile("ld.acquire.gpu.global.u32 %0, [%1];" : "=r"(v) : "l"(f) : "memory");
    if (v >= target) break;
    __nanosleep(100);
  }
}
__device__ __forceinline__ uint32_t ld_and2(const unsigned int* f) {
  uint32_t v;
  asm volatile("{\n.reg .b64 t;\n.reg .b32 a, b;\nld.acquire.gpu.global.b64 t, [%1];\nmov.b64 {a, b}, t;\nand.b32 %0, a, b;\n}" : "=r"(v) : "l"(f) : "memory");
  return v;
}
__device__ __forceinline__ uint32_t lds32(uint32_t a) {
  uint32_t v;
  asm volatile("ld.shared.u32 %0, [%1];" : "=r"(v) : "r"(a) : "memory");
  return v;
}
__device__ __forceinline__ float gate_row(int row, int lane, const bf16* __restrict__ x, const bf16* __restrict__ gate_w) {
  const uint32_t* xr = reinterpret_cast<const uint32_t*>(x + (size_t)row * DM);
  const uint32_t* gw2 = reinterpret_cast<const uint32_t*>(gate_w);
  float gs = 0.f;
#pragma unroll
  for (int i = 0; i < 9; i++) {
    const uint32_t a = __ldg(xr + lane + 32 * i), b = __ldg(gw2 + lane + 32 * i);
    gs = fmaf(bf_lo(a), bf_lo(b), gs);
    gs = fmaf(bf_hi(a), bf_hi(b), gs);
  }
#pragma unroll
  for (int o = 16; o; o >>= 1) gs += __shfl_xor_sync(0xffffffffu, gs, o);
  const float g = 1.f / (1.f + __expf(-gs));
  if (lane == 0) g_gate[row] = g;
  return g;
}
constexpr uint32_t LQ = 36864, LV = 55296;
__device__ __forceinline__ void mma16(float (&c)[4], uint32_t a0, uint32_t a1, uint32_t a2, uint32_t a3, uint32_t b0, uint32_t b1) {
  asm("mma.sync.aligned.m16n8k16.row.col.f32.bf16.bf16.f32 {%0, %1, %2, %3}, {%4, %5, %6, %7}, {%8, %9}, {%0, %1, %2, %3};"
      : "+f"(c[0]), "+f"(c[1]), "+f"(c[2]), "+f"(c[3]) : "r"(a0), "r"(a1), "r"(a2), "r"(a3), "r"(b0), "r"(b1));
}
__device__ __forceinline__ void mma8(float (&c)[4], uint32_t a0, uint32_t a1, uint32_t b0) {
  asm("mma.sync.aligned.m16n8k8.row.col.f32.bf16.bf16.f32 {%0, %1, %2, %3}, {%4, %5}, {%6}, {%0, %1, %2, %3};"
      : "+f"(c[0]), "+f"(c[1]), "+f"(c[2]), "+f"(c[3]) : "r"(a0), "r"(a1), "r"(b0));
}
template <typename F>
__device__ __forceinline__ void local_attn(int lr0, int warp_g, uint32_t sL, uint32_t bL, uint32_t bL2, int lane, float g0, float g1, F st) {
  const float scale_l2 = 0.23570226039551584f * 1.4426950408889634f;
  const int g = lane >> 2, t = lane & 3;
  const bool lo0 = 2 * t > g, lo1 = 2 * t + 1 > g;
  const bool ok0 = lr0 > 0 || !lo0, ok1 = lr0 > 0 || !lo1;
  const uint32_t mlo = (lo0 ? 0xFFFFu : 0u) | (lo1 ? 0xFFFF0000u : 0u);
  uint32_t ad[9], k[9][4], qf[9][2], pe[4], po[4];
#pragma unroll
  for (int c = 0; c < 9; c++) {
    const uint32_t ch = warp_g * 9 + c;
    ad[c] = sL + (lane >> 4) * 18432 + (lane & 15) * 128 + ((ch >> 3) << 11) + (((ch ^ lane) & 7) << 4);
  }
  st(0, 0u); st(1, 0u);
  mbar_wait(bL, 0);
  if (warp_g == 0) TS(1, 6);
#pragma unroll
  for (int c = 0; c < 9; c++) {
    asm volatile("ldmatrix.sync.aligned.m8n8.x2.shared.b16 {%0, %1}, [%2];" : "=r"(qf[c][0]), "=r"(qf[c][1]) : "r"(ad[c] + LQ) : "memory");
    ldsm_x4(k[c][0], k[c][1], k[c][2], k[c][3], ad[c]);
  }
  st(2, k[0][0]); st(3, k[8][0]);
#pragma unroll
  for (int i = 0; i < 4; i++) {
    const uint32_t q0 = (t >= i) ? qf[2 * i][0] : 0u, q1 = (t >= i) ? qf[2 * i][1] : 0u;
    const uint32_t q4 = (t <= i) ? qf[2 * i + 2][0] : 0u, q5 = (t <= i) ? qf[2 * i + 2][1] : 0u;
    float c[4][4];
#pragma unroll
    for (int T = 0; T < 4; T++) {
#pragma unroll
      for (int j = 0; j < 4; j++) c[T][j] = 0.f;
      mma16(c[T], q0, q1, qf[2 * i + 1][0], qf[2 * i + 1][1], k[2 * i][T], k[2 * i + 1][T]);
      mma8(c[T], q4, q5, k[2 * i + 2][T]);
    }
    const float e0 = ok0 ? (lo0 ? c[0][0] : c[1][0]) : -INFINITY, e1 = ok1 ? (lo1 ? c[0][1] : c[1][1]) : -INFINITY;
    const float o0 = ok0 ? (lo0 ? c[2][2] : c[3][2]) : -INFINITY, o1 = ok1 ? (lo1 ? c[2][3] : c[3][3]) : -INFINITY;
    float me = fmaxf(e0, e1), mo = fmaxf(o0, o1);
    me = fmaxf(me, __shfl_xor_sync(0xffffffffu, me, 1));
    mo = fmaxf(mo, __shfl_xor_sync(0xffffffffu, mo, 1));
    me = fmaxf(me, __shfl_xor_sync(0xffffffffu, me, 2)) * scale_l2;
    mo = fmaxf(mo, __shfl_xor_sync(0xffffffffu, mo, 2)) * scale_l2;
    const float w0 = ex2(fmaf(e0, scale_l2, -me)), w1 = ex2(fmaf(e1, scale_l2, -me));
    const float w2 = ex2(fmaf(o0, scale_l2, -mo)), w3 = ex2(fmaf(o1, scale_l2, -mo));
    float se = w0 + w1, so = w2 + w3;
    st(4 + 2 * i, __float_as_uint(i == 1 ? me : i == 2 ? se : e0));
    se += __shfl_xor_sync(0xffffffffu, se, 1);
    so += __shfl_xor_sync(0xffffffffu, so, 1);
    se += __shfl_xor_sync(0xffffffffu, se, 2);
    so += __shfl_xor_sync(0xffffffffu, so, 2);
    asm("rcp.approx.ftz.f32 %0, %0;" : "+f"(se));
    asm("rcp.approx.ftz.f32 %0, %0;" : "+f"(so));
    se *= g0;
    so *= g1;
    pe[i] = pack_bf16(w0 * se, w1 * se);
    po[i] = pack_bf16(w2 * so, w3 * so);
    st(5 + 2 * i, i == 0 ? __float_as_uint(w0) : i == 2 ? __float_as_uint(mo) : po[i]);
  }
  if (warp_g == 0) TS(0, 4);
  mbar_wait(bL2, 0);
  if (warp_g == 0) TS(0, 5);
#pragma unroll
  for (int c = 0; c < 9; c++)
    asm volatile("ldmatrix.sync.aligned.m8n8.x4.trans.shared.b16 {%0, %1, %2, %3}, [%4];"
                 : "=r"(k[c][0]), "=r"(k[c][1]), "=r"(k[c][2]), "=r"(k[c][3]) : "r"(ad[c] + LV) : "memory");
#pragma unroll
  for (int i = 0; i < 4; i++) {
#pragma unroll
    for (int n = 0; n < 3; n++) {
      float c[4] = {0.f, 0.f, 0.f, 0.f};
      mma16(c, pe[i] & mlo, 0u, pe[i] & ~mlo, 0u, k[2 * i + n][0], k[2 * i + n][1]);
      mma16(c, 0u, po[i] & mlo, 0u, po[i] & ~mlo, k[2 * i + n][2], k[2 * i + n][3]);
      const uint32_t r0 = pack_bf16(c[0], c[1]), r1 = pack_bf16(c[2], c[3]);
      const bool keep = (n == 0) && (i > 0) && (t < i);
      qf[2 * i + n][0] = keep ? qf[2 * i + n][0] : r0;
      qf[2 * i + n][1] = keep ? qf[2 * i + n][1] : r1;
    }
    st(12 + i, qf[2 * i + 1][0]);
  }
#pragma unroll
  for (int c = 0; c < 9; c++)
    asm volatile("stmatrix.sync.aligned.m8n8.x2.shared.b16 [%0], {%1, %2};" ::"r"(ad[c] + LQ), "r"(qf[c][0]), "r"(qf[c][1]) : "memory");
  asm volatile("fence.proxy.async.shared::cta;" ::: "memory");
}
__device__ __forceinline__ void tma4d(uint32_t dst, const CUtensorMap* m, uint32_t bar, int c1, int c2, int c3) {
  asm volatile("cp.async.bulk.tensor.4d.shared::cluster.global.mbarrier::complete_tx::bytes [%0], [%1, {%3, %4, %5, %6}], [%2];" ::"r"(dst),
               "l"(m), "r"(bar), "r"(0), "r"(c1), "r"(c2), "r"(c3) : "memory");
}

#define ST_NUM 1
#define ST_DEN 2
#define ALEAD 3
#define K1_NST 6
constexpr int K1_BST = K1_NST;
#define MAXJ 11
constexpr int K1_MAXJOBS = MAXJ;
constexpr uint32_t K1_FLAG_TARGET = 7;
constexpr uint32_t RDY_TARGET = 48;
constexpr uint32_t GATE_TARGET = 128 * 3;
struct alignas(64) Params {
  CUtensorMap tmA[2];
  CUtensorMap tmW[4];
  uint16_t jobs[NCLUSTER][K1_MAXJOBS + 1];
  CUtensorMap tmK, tmV, tmQ;
  CUtensorMap tmL[3];
  CUtensorMap tmC, tmO[2], tmOt[2];
  CUtensorMap tmR[2];
  uint8_t order[256];
  uint8_t unit[66][4];
};

struct K1State {
  uint32_t bs, bph, aph;
  bf16* pp;
  int png;
  int tn;
  int wsel;
  uint32_t fo;
};
__device__ __forceinline__ void k1_flag(const K1State& st, int lane, uint32_t bS) {
  if (st.png) {
    __syncwarp();
    if (lane == 0) mbar_arrive(bS + st.fo);
  }
}

__device__ __forceinline__ void scale_q4(uint32_t* v) {
#pragma unroll
  for (int i = 0; i < 4; i++)
    asm volatile("{\n.reg .b32 t;\nmul.rn.bf16x2 t, %0, %2;\nfma.rn.bf16x2 %0, %0, %1, t;\n}" : "+r"(v[i]) : "r"(0x3E033E03u), "r"(0xB9D8B9D8u));
}
__device__ __forceinline__ void k1_first(const K1State& st, uint32_t job, uint32_t bAf, uint32_t bBf) {
  if (job & 3) {
    if ((job >> 14) & 1) mbar_wait(bAf, st.aph);
    mbar_wait(bBf + st.bs * 8, st.bph);
  }
}
__device__ __forceinline__ void k1_tile(float (&acc)[128], uint32_t (&pk)[64], K1State& st, uint32_t job, uint32_t njob, uint32_t sA, uint32_t sB,
                                        uint32_t bAf, uint32_t bAe, uint32_t bBf, uint32_t bBe, uint32_t bS, int wg, int warp, int lane, uint32_t rank) {
  const int a_sel = (job >> 2) & 1, mpair = (job >> 3) & 7, w_sel = (job >> 6) & 3, chunk0 = (job >> 8) & 63;
  const bool newA = (job >> 14) & 1, lastA = (job >> 15) & 1;
  const bool sig = (lane == 0) && (warp < 2);
  const bool siga = lastA && (lane == 0) && (warp == 2);
  const int KC = 8 + a_sel;
  uint32_t prev_bs = 0, a8_bs = 0;
#pragma unroll
  for (int kc = 0; kc < 9; kc++) {
    if (kc >= KC) break;
    uint32_t abase = sA + ((kc + 2) & 7) * 16384;
    if (kc == 8) {
      mbar_wait(bBf + st.bs * 8, st.bph);
      a8_bs = st.bs;
      abase = sB + st.bs * 16384;
      if (++st.bs == K1_BST) { st.bs = 0; st.bph ^= 1; }
    } else if (newA && kc > 0) {
      mbar_wait(bAf + kc * 8, st.aph);
    }
    const uint64_t da = make_desc(abase + wg * 8192, 16, 1024, 1);
#pragma unroll
    for (int ks = 0; ks < 2; ks++) {
      if (ks > 0 || kc > 0) mbar_wait(bBf + st.bs * 8, st.bph);
      const uint64_t db = make_desc(sB + st.bs * 16384, 2048, 1024, 1);
      if (kc * 2 + ks == 16 - ALEAD && !a_sel && wg == 1) bar_sync(4, 256);
      wg_fence();
      wgmma_ss_n256<1, 0>(acc, da + (uint64_t)(ks * 4), db, (ks > 0) ? 1 : (kc > 0));
      wgmma_ss_n256<1, 0>(acc, da + (uint64_t)(ks * 4 + 2), db + (uint64_t)512, 1);
      wg_commit();
      if (kc == 7 && ks == 1 && !a_sel && wg == 0) bar_arrive(4, 256);
      wg_wait<1>();
      if (ks > 0 || kc > 0) {
        if (sig) mbar_arrive_cluster(bBe + prev_bs * 8, warp);
        if (ks == 0 && siga) mbar_arrive(bAe + (kc - 1) * 8);
      }
      if (st.wsel == 2) {
        const int i = (kc & 7) * 2 + ks;
        if (kc < st.png) {
          quad_transpose(pk[i * 4], pk[i * 4 + 1], pk[i * 4 + 2], pk[i * 4 + 3], lane & 3);
          st_v4a(st.pp + goff(kc, ks), pk[i * 4], pk[i * 4 + 1], pk[i * 4 + 2], pk[i * 4 + 3]);
        }
        if (i == 15) k1_flag(st, lane, bS);
      } else if (st.png) {
#pragma unroll
        for (int i = 0; i < 16; i++) {
          if (i * ST_NUM / ST_DEN != kc * 2 + ks) continue;
          if (st.wsel == 3) scale_q4(pk + i * 4);
          st_v4a(st.pp + goff(i / 2, i & 1), pk[i * 4], pk[i * 4 + 1], pk[i * 4 + 2], pk[i * 4 + 3]);
          if (i == 15) k1_flag(st, lane, bS);
        }
      }
      prev_bs = st.bs;
      if (++st.bs == K1_BST) { st.bs = 0; st.bph ^= 1; }
    }
  }
  if (newA) st.aph ^= 1;
  const bool isA = (w_sel == 2);
  bf16* out = (w_sel == 0) ? g_K : (w_sel == 1) ? g_V : isA ? g_QKVA : g_ctx;
  const int row = mpair * 256 + rank * 128 + wg * 64 + warp * 16 + (lane >> 2);
  st.pp = ptr_add(out, (chunk0 * S_LEN + row) * 128 + (lane & 3) * 16);
  st.png = ((job & 3) + 1) * 2;
  st.wsel = w_sel;
  st.fo = (st.fo + 8) & 24;
  k1_first(st, njob, bAf, bBf);
  wg_wait<0>();
  fence_regs(acc);
  mbar_arrive_cluster_if(bBe + prev_bs * 8, warp & 1, sig);
  mbar_arrive_cluster_if(bBe + a8_bs * 8, warp & 1, sig && a_sel);
  mbar_arrive_if(bAe + 7 * 8, siga && !a_sel);
#pragma unroll
  for (int i = 0; i < 64; i++) {
    const int j = (i >> 3) * 16 + (i & 3) * 4 + ((i >> 2) & 1) * 2;
    pk[i] = pack_bf16(acc[j], acc[j + 1]);
  }
}

constexpr int K2_NST = 7;
constexpr uint32_t K2_END = 0x100;
#define PFD 4
#define PF3A 2
#define PF3 6
#define KC0 1
constexpr uint32_t CR = 4;
#define FIRST_DRAW 3
#define PWAIT mbar_wait_ns<1000>
#define PVM 0x8A
#define W0 63
#define SPEC_HI 1.8446744073709552e19f
#define SPEC_LO 5.421010862427522e-20f
constexpr int K3_NST = 4;
#define K3_NS 6
__device__ __forceinline__ uint32_t k3_rot(uint32_t sv) { return (0x00E9u >> (2 * sv)) & 3; }
constexpr int K3_STAGE = 16384 + 32768 + 4096;
constexpr int SMEM_DATA = 7 * 32768;
constexpr int SMEM_BYTES = SMEM_DATA + 1024 + 896;

struct Cursor {
  uint32_t s, ph;
  __device__ __forceinline__ void next() {
    if (++s == K2_NST) { s = 0; ph ^= 1; }
  }
};

#define TURN_SYNC() bar_sync(mybar, 256)
#define TURN_ARRIVE() bar_arrive(otherbar, 256)
#define RELEASE_IF(cur, cond) mbar_arrive_cluster_if(bE + (cur).s * 8, warp & 1, sig && (cond))
#define RELEASE(cur) RELEASE_IF(cur, true)
#define ISSUE_PV(cur, first)                                                                                   \
  do {                                                                                                         \
    const uint64_t dv = make_desc(sbase + (cur).s * 32768, 16384, 1024, 1);                                    \
    _Pragma("unroll") for (int t = 0; t < 8; t++)                                                              \
        wgmma_rs_n128<1, 0>(O, P[4 * t], P[4 * t + 1], P[4 * t + 2], P[4 * t + 3], dv + (uint64_t)(t * 128), (t > 0) ? 1 : !(first)); \
  } while (0)
#define ISSUE_QK(cur)                                                                                          \
  do {                                                                                                         \
    const uint64_t dk = make_desc(sbase + (cur).s * 32768, 16, 1024, 1);                                       \
    _Pragma("unroll") for (int t = 0; t < 8; t++)                                                              \
        wgmma_rs_n128<0, 0>(S, Q[4 * t], Q[4 * t + 1], Q[4 * t + 2], Q[4 * t + 3], dk + (uint64_t)((t >> 2) * 1024 + (t & 3) * 2), t > 0); \
  } while (0)
#define LOAD_Q()                                                                                               \
  do {                                                                                                         \
    item = lds32(sItem + (it & 7) * 4);                                                                        \
    const uint32_t qa = sbase + cq.s * 32768 + (wg * 64 + warp * 16 + (lane & 15)) * 128;                      \
    _Pragma("unroll") for (int t = 0; t < 8; t++)                                                              \
        ldsm_x4(Q[4 * t], Q[4 * t + 1], Q[4 * t + 2], Q[4 * t + 3], qa + (t >> 2) * 16384 + ((((t & 3) * 2 + (lane >> 4)) ^ (lane & 7)) << 4)); \
  } while (0)
#define NEW_ITEM()                                                                                             \
  do {                                                                                                         \
    const int row = (2 * (item & 7) + hi) * 128 + (rank ^ hi) * 64 + warp * 16 + (lane >> 2);                  \
    eoff = ((item >> 3) * 2 * S_LEN + row) * 128 + q * 16;                                                     \
    const float* gp = ptr_add(g_gate, row * 4);                                                                \
    asm volatile("ld.global.f32 %0, [%1];" : "=f"(gf0) : "l"(gp));                                             \
    asm volatile("ld.global.f32 %0, [%1];" : "=f"(gf1) : "l"(gp + 8));                                         \
    if (!hi) {                                                                                                 \
      mbar_wait2(bF + cs0.s * 8, cs0.ph, bF + cs1.s * 8, cs1.ph);                                              \
      RELEASE(cs0);                                                                                            \
      RELEASE(cs1);                                                                                            \
    }                                                                                                          \
  } while (0)
#define EXPB(T)                                                                                                \
  do {                                                                                                         \
    _Pragma("unroll") for (int i = 4 * T; i < 4 * T + 4; i++) asm volatile("" : "+r"(P[i])::"memory");        \
    _Pragma("unroll") for (int jj = 2 * T; jj < 2 * T + 2; jj++) {                                             \
      const float e0 = ex2(S[jj * 4 + 0]), e1 = ex2(S[jj * 4 + 1]), e2 = ex2(S[jj * 4 + 2]), e3 = ex2(S[jj * 4 + 3]); \
      s0 += e0 + e1;                                                                                           \
      s1 += e2 + e3;                                                                                           \
      P[jj * 2 + 0] = pack_bf16(e0, e1);                                                                       \
      P[jj * 2 + 1] = pack_bf16(e2, e3);                                                                       \
    }                                                                                                          \
  } while (0)
#define EXPC(T)                                                                                                \
  do {                                                                                                         \
    if (T > 0 && ((PVM >> (T - 1)) & 1)) {                                                                     \
      anchor((T & 2) ? s0 : s1, never);                                                                        \
      wg_wait<__builtin_popcount(PVM >> T) - 1>();                                                             \
      if ((PVM >> T) == (128 >> T)) { fence_regs(O); RELEASE(cv); }                                            \
    }                                                                                                          \
    EXPB(T);                                                                                                   \
  } while (0)
#define MASK(G, g)                                                                                             \
  do {                                                                                                         \
    if ((g) * 8 > d) S[(G) * 4 + 0] = -INFINITY;                                                               \
    if ((g) * 8 + 1 > d) S[(G) * 4 + 1] = -INFINITY;                                                           \
    if ((g) * 8 - 8 > d) S[(G) * 4 + 2] = -INFINITY;                                                           \
    if ((g) * 8 - 7 > d) S[(G) * 4 + 3] = -INFINITY;                                                           \
  } while (0)
#define STORE_O(G)                                                                                             \
  do {                                                                                                         \
    st_v4(optr + goff(G, 0), pack_bf16(O[(G) * 16 + 0] * f0, O[(G) * 16 + 1] * f0), pack_bf16(O[(G) * 16 + 4] * f0, O[(G) * 16 + 5] * f0), \
          pack_bf16(O[(G) * 16 + 8] * f0, O[(G) * 16 + 9] * f0), pack_bf16(O[(G) * 16 + 12] * f0, O[(G) * 16 + 13] * f0)); \
    st_v4(optr + goff(G, 1), pack_bf16(O[(G) * 16 + 2] * f1, O[(G) * 16 + 3] * f1), pack_bf16(O[(G) * 16 + 6] * f1, O[(G) * 16 + 7] * f1), \
          pack_bf16(O[(G) * 16 + 10] * f1, O[(G) * 16 + 11] * f1), pack_bf16(O[(G) * 16 + 14] * f1, O[(G) * 16 + 15] * f1)); \
  } while (0)

#define FLUSH()                                                                                                \
  do {                                                                                                         \
    _Pragma("unroll") for (int G = 0; G < 8; G++) {                                                            \
      st_v4a(st.pp + goff(G, 0), pk[G * 8], pk[G * 8 + 1], pk[G * 8 + 2], pk[G * 8 + 3]);                          \
      st_v4a(st.pp + goff(G, 1), pk[G * 8 + 4], pk[G * 8 + 5], pk[G * 8 + 6], pk[G * 8 + 7]);                     \
    }                                                                                                          \
    k1_flag(st, lane, bS);                                                                                     \
  } while (0)

__global__ void __cluster_dims__(2, 1, 1) __launch_bounds__(384, 1)
fused_kernel(const __grid_constant__ Params p, const bf16* __restrict__ x, const bf16* __restrict__ gate_w, bf16* __restrict__ out) {
  extern __shared__ uint8_t smem_raw[];
  const uint32_t sbase = (smem_u32(smem_raw) + 1023) & ~1023u;
  const uint32_t sB = sbase, sA = sbase + K1_BST * 16384, sBar = sbase + SMEM_DATA;
  const uint32_t bAf = sBar, bAe = sBar + 64, bBf = sBar + 128, bBe = sBar + 176, bL = sBar + 224, bS = sBar + 656, bL2 = sBar + 240, sL = sA + 32768;
  const uint32_t bF = sBar + 256, bE = sBar + 320, bT = sBar + 384, sTick = sBar + 400, sItem = sBar + 416, bS2 = sBar + 688, bR = sBar + 456, bLast = sBar + 464, bH = sBar + 472, bT0 = sBar + 480, bZ = sBar + 488, bLd = sBar + 496, bG = sBar + 504;
  const uint32_t b3F = sBar + 512, b3E = sBar + 544, sGate = sBar + 576, sK1 = sBar + 720, sClm = sBar + 768;
  const int tid = threadIdx.x, warp_g = __shfl_sync(0xffffffffu, tid >> 5, 0), lane = tid & 31;
  const uint32_t rank = cluster_rank();
  const int cl = blockIdx.x >> 1;
  TSM(0);
  if (tid == 256) {
    const uint32_t job = p.jobs[cl][0];
#pragma unroll
    for (int i = 0; i < KC0; i++) { mbar_init(bAf + i * 8, 1); mbar_init(bBf + i * 16, 1); mbar_init(bBf + i * 16 + 8, 1); }
    asm volatile("fence.mbarrier_init.release.cluster;" ::: "memory");
#pragma unroll 1
    for (int i = 0; i < 4 * KC0; i++) {
      if (!(i & 3)) {
        mbar_expect(bAf + i * 2, 16384);
        tma2d(sA + (i / 4 + 2) * 16384, &p.tmA[(job >> 2) & 1], bAf + i * 2, i * 16, ((job >> 3) & 7) * 256 + rank * 128);
      }
      if (!(i & 1)) mbar_expect(bBf + i * 4, 16384);
      tma3d(sB + i * 8192, &p.tmW[(job >> 6) & 3], bBf + (i >> 1) * 8, 0, i * 16, (job >> 8) & 63);
    }
  }
  if (warp_g == 1) asm volatile("st.shared.u32 [%0], %1;" ::"r"(lane ? sClm - 4 + lane * 4 : sK1), "r"(lane ? 0xFFFFFFFFu : 80u) : "memory");
  if (tid == 0) {
    for (int i = 0; i < 8; i++) { if (i >= KC0) mbar_init(bAf + i * 8, 1); mbar_init(bAe + i * 8, 2); }
    for (int i = 0; i < K1_BST; i++) { if (i >= 2 * KC0) mbar_init(bBf + i * 8, 1); mbar_init(bBe + i * 8, 4); }
    mbar_init(bL, 1);
    mbar_init(bL2, 1);
    mbar_init(bR, 1);
    mbar_init(bLast, 1);
    mbar_init(bH, 4);
    mbar_init(bT0, 1);
    mbar_init(bZ, 1);
    mbar_init(bLd, 4);
    mbar_init(bG, 3);
    for (int i = 0; i < 8; i++) mbar_init(bS + i * 8, 8);
    for (int i = 0; i < K2_NST; i++) { mbar_init(bF + i * 8, 1); mbar_init(bE + i * 8, 4); }
    mbar_init(bT, 1); mbar_init(bT + 8, 1);
    for (int i = 0; i < K3_NST; i++) { mbar_init(b3F + i * 8, 1); mbar_init(b3E + i * 8, 4); }
    asm volatile("fence.mbarrier_init.release.cluster;" ::: "memory");
  }
  __syncwarp();
  if (warp_g != 8) cluster_sync();
  const int lr0 = blockIdx.x * 16;

  if (warp_g >= 8) {
    reg_dealloc<40>();
    if (warp_g == 8) {
      {
        __syncwarp();
        cluster_sync();
      }
      if (elect_one()) {
        uint32_t bs = (2 * KC0) % K1_BST, bph = (2 * KC0 < K1_BST), aph = 1;
#pragma unroll 1
        for (int ji = 0; ji < K1_MAXJOBS; ji++) {
          const uint32_t job = p.jobs[cl][ji];
          if (!(job & 3)) break;
          const int a_sel = (job >> 2) & 1, mpair = (job >> 3) & 7, chunk0 = (job >> 8) & 63;
          const bool newA = (job >> 14) & 1;
          const int KC = a_sel ? 9 : 8;
          const uint32_t halfbytes = 8192;
          const bool lastjob = (ji + 1 == K1_MAXJOBS) || !(p.jobs[cl][ji + 1] & 3);
          const CUtensorMap* tw = &p.tmW[(job >> 6) & 3];
          {
            const uint32_t njob = (ji + 1 < K1_MAXJOBS) ? p.jobs[cl][ji + 1] : 0;
            if (!(njob & 3) && !newA) mbar_arrive(bLast);
          }
#pragma unroll 1
          for (int kc = ji ? 0 : KC0; kc < KC; kc++) {
            {
              const bool nx = kc + PFD >= KC;
              const uint32_t njob = nx ? p.jobs[cl][ji + 1] : job;
              const int pk = nx ? kc + PFD - KC : kc + PFD;
              if ((njob & 3) && (nx || ji > 0)) {
                if (cl >= 64 || ((pk ^ (cl >> 1)) & 3) == 0)
                  tma_pf3d(&p.tmW[(njob >> 6) & 3], 0, pk * 64 + (cl & 1) * 32 + rank * 16, (njob >> 8) & 63);
                if (((njob >> 14) & 1) || pk == 8) tma_pf2d(&p.tmA[(njob >> 2) & 1], pk * 64, ((njob >> 3) & 7) * 256 + rank * 128);
              }
            }
            if (kc == 8) {
              PWAIT(bBe + bs * 8, bph);
              mbar_expect(bBf + bs * 8, 16384);
              tma2d(sB + bs * 16384, &p.tmA[1], bBf + bs * 8, 512, mpair * 256 + rank * 128);
              if (++bs == K1_BST) { bs = 0; bph ^= 1; }
            } else if (newA) {
              PWAIT(bAe + kc * 8, aph);
              mbar_expect(bAf + kc * 8, 16384);
              tma2d(sA + ((kc + 2) & 7) * 16384, &p.tmA[a_sel], bAf + kc * 8, kc * 64, mpair * 256 + rank * 128);
              if (kc == 7 && lastjob) mbar_arrive(bLast);
            }
#pragma unroll 1
            for (int kk = 0; kk < 2; kk++) {
              PWAIT(bBe + bs * 8, bph);
              mbar_expect(bBf + bs * 8, 2 * halfbytes);
              tma3d_mc(sB + bs * 16384 + rank * halfbytes, tw, bBf + bs * 8, 0, kc * 64 + kk * 32 + rank * 16, chunk0, 3);
              if (++bs == K1_BST) { bs = 0; bph ^= 1; }
            }
          }
          if (newA) aph ^= 1;
        }
        Cursor c{0, 0};
        int pcol = 0;
        PWAIT(bR, 0);
        uint32_t tick = lds32(sTick + 8), seen = 1u << (p.order[tick] >> 4);
        asm volatile("fence.proxy.async.global;" ::: "memory");
#pragma unroll 1
        for (int it = 0;; it++) {
          const uint32_t item = (tick < 256) ? p.order[tick] : (K2_END | min(tick - 256, 255u));
          asm volatile("st.shared.u32 [%0], %1;" ::"r"(sItem + (it & 7) * 4), "r"(item) : "memory");
          if (item >= K2_END) break;
          const int h = item >> 3, j = item & 7;
          const int col = (h * 2 + rank) * S_LEN;
          const int nb = 2 * j + 2;
          if (!((seen >> (h >> 1)) & 1)) {
            wait_flag(&g_sync[F_HP + (h >> 1)], RDY_TARGET);
            asm volatile("fence.proxy.async.global;" ::: "memory");
            seen |= 1u << (h >> 1);
          }
          PWAIT(bE + c.s * 8, c.ph);
          mbar_expect(bF + c.s * 8, 32768);
#pragma unroll 1
          for (int i = 0; i < 4; i++) {
            const int hi = (i ^ it ^ 1) & 1;
            tma2d(sbase + c.s * 32768 + i * 8192, &p.tmQ, bF + c.s * 8, 0, (h * 2 + (i >> 1)) * S_LEN + (2 * j + hi) * 128 + (rank ^ hi) * 64);
          }
          c.next();
          if (tick >= 256 - 73) {
            const int kk = tick - (256 - 73), sel = (kk < 9), kr = (sel ? kk : kk - 9) * 64 + rank * 32;
#pragma unroll 1
            for (int i = 0; i < 2; i++) {
              tma_pf3d(&p.tmO[sel], 0, kr, i * 4);
              tma_pf2d(&p.tmOt[sel], 512 + i * 32, kr);
            }
          }
#pragma unroll 1
          for (int n = nb - 1; n >= 0; n--) {
            if (n == 0 && rank == 0) tick = atomicAdd(&g_sync[F_TICK], 1u);
            PWAIT(bE + c.s * 8, c.ph);
            mbar_expect(bF + c.s * 8, 32768);
            tma2d_mc(sbase + c.s * 32768 + rank * 16384, &p.tmK, bF + c.s * 8, 0, col + n * 128, 3);
            c.next();
            if (n < nb - 1 || it > 0) {
              PWAIT(bE + c.s * 8, c.ph);
              mbar_expect(bF + c.s * 8, 32768);
              tma2d_mc(sbase + c.s * 32768 + rank * 16384, &p.tmV, bF + c.s * 8, 0, (n < nb - 1) ? col + (n + 1) * 128 : pcol, 3);
              c.next();
            }
          }
          pcol = col;
          if (rank == 0) {
            asm volatile(
                "{\n.reg .b32 a, b;\nmapa.shared::cluster.u32 a, %0, 1;\nmapa.shared::cluster.u32 b, %1, 1;\n"
                "st.async.shared::cluster.mbarrier::complete_tx::bytes.u32 [a], %2, [b];\n}" ::"r"(sTick + (it & 1) * 4),
                "r"(bT + (it & 1) * 8), "r"(tick) : "memory");
          } else {
            mbar_expect(bT + (it & 1) * 8, 4);
            PWAIT(bT + (it & 1) * 8, (it >> 1) & 1);
            tick = lds32(sTick + (it & 1) * 4);
          }
        }
        PWAIT(bE + c.s * 8, c.ph);
        mbar_expect(bF + c.s * 8, 32768);
        tma2d_mc(sbase + c.s * 32768 + rank * 16384, &p.tmV, bF + c.s * 8, 0, pcol, 3);
        const uint32_t unit = tick - 256;
        const int mblk = (7 - (p.unit[unit][0] >> 1)) * 2 + rank, nhalf = p.unit[unit][0] & 1;
        uint32_t have, hoa;
        have = ld_and2(&g_sync[F_CTX + (mblk & ~1)]);
        asm volatile("ld.acquire.gpu.global.u32 %0, [%1];" : "=r"(hoa) : "l"(&g_sync[F_OA + mblk]) : "memory");
        asm volatile("fence.proxy.async.global;" ::: "memory");
#pragma unroll 1
        for (uint32_t idx = PF3A; idx < PF3; idx++) {
          const int kk = p.unit[unit][2] + idx;
          if ((kk < 9) ? (hoa >= 8) : ((have >> ((kk - 9) >> 1)) & 1)) tma_pf2d(&p.tmC, 0, ((kk < 9) ? 64 + kk : kk - 9) * S_LEN + mblk * 128);
        }
        {
          const uint32_t rot = k3_rot(c.s), nfree = ((0x1Au >> c.s) & 1) ? 2 : 3;
          uint32_t kq = p.unit[unit][2] * 0x01010101u + 0x03020100u, k1 = 80, idx = 0, pa = 0, pb = 0;
          auto step = [&](uint32_t& pend) {
            uint32_t nxt = (kq & 255) + CR;
            if (idx + CR >= K3_NS && k1 == 80) {
              if (rank == 0) {
                nxt = min(pend + p.unit[unit][3], 73u);
                asm volatile("{\n.reg .b32 a;\nmapa.shared::cluster.u32 a, %0, 1;\nst.volatile.shared::cluster.u8 [a], %1;\n}" ::"r"(sClm + idx), "r"(nxt) : "memory");
              } else {
#pragma unroll 1
                for (uint32_t spins = 0; spins < (1u << 22); spins++) {
                  asm volatile("ld.volatile.shared.u8 %0, [%1];" : "=r"(nxt) : "r"(sClm + idx) : "memory");
                  if (nxt != 255) break;
                  __nanosleep(20);
                }
              }
              if (nxt >= 73) {
                k1 = idx + CR;
                asm volatile("st.shared.u32 [%0], %1;" ::"r"(sK1), "r"(k1) : "memory");
              }
            }
            const uint32_t kk = kq & 255;
            if (idx < 12) TP(idx);
            kq = (kq >> 8) | (nxt << (8 * CR - 8));
            const uint32_t s = (rot + idx) & 3;
            if (idx >= nfree) PWAIT((idx < 4) ? bH : b3E + s * 8, (idx < 4) ? 0 : (~idx >> 2) & 1);
#pragma unroll 1
            while (idx < nfree && c.s != ((0x6431u >> (4 * s)) & 15)) {
              c.next();
              PWAIT(bE + c.s * 8, c.ph);
            }
            if (idx < 12) TP(12 + idx);
            mbar_expect(b3F + s * 8, K3_STAGE);
            const uint32_t st = sbase + s * K3_STAGE;
            const int sel = (kk < 9), k = sel ? kk : kk - 9, kr = k * 64 + rank * 32;
            tma3d_mc(st + 16384 + rank * 16384, &p.tmO[sel], b3F + s * 8, 0, kr, nhalf * 4, 3);
            tma2d_mc(st + 49152 + rank * 2048, &p.tmOt[sel], b3F + s * 8, 512 + nhalf * 32, kr, 3);
            if (rank == 0 && idx + CR + 2 >= K3_NS && k1 == 80) pend = atomicAdd(&g_sync[F_CLM + p.unit[unit][0]], 1u);
            if (sel && hoa < 8) {
              wait_flag(&g_sync[F_OA + mblk], 8);
              hoa = 8;
              asm volatile("fence.proxy.async.global;" ::: "memory");
            }
            if (!sel && !((have >> (k >> 1)) & 1)) {
#pragma unroll 1
              for (uint32_t spins = 0; spins < (1u << 22); spins++) {
                have = ld_and2(&g_sync[F_CTX + (mblk & ~1)]);
                if ((have >> (k >> 1)) & 1) break;
                __nanosleep(100);
              }
              asm volatile("fence.proxy.async.global;" ::: "memory");
            }
            tma2d(st, &p.tmC, b3F + s * 8, 0, (sel ? 64 + k : k) * S_LEN + mblk * 128);
            if (idx < 12) TP(24 + idx);
            return ++idx >= k1;
          };
#pragma unroll 1
          for (;;) {
            if (step(pa)) break;
            if (step(pb)) break;
          }
          asm volatile("" ::"r"(pa), "r"(pb) : "memory");
        }
      }
    }
    __syncwarp();
    if (warp_g == 8) {
      uint32_t v = 0;
      if (lane == 0) {
        __threadfence();
        v = atomicAdd(&g_sync[F_DONE], 1u);
      }
      if (__shfl_sync(0xffffffffu, v, 0) == 2 * NCLUSTER - 1) {
        reinterpret_cast<uint4*>(g_sync)[lane] = make_uint4(0, 0, 0, 0);
        if (lane == 0) g_sync[F_EPOCH] = lds32(sGate + 64) + 1;
      }
    }
    asm volatile("" ::: "memory");
    if (__shfl_sync(0xffffffffu, warp_g, 0) != 8) {
#pragma unroll 1
      for (int i = 0; i < 32 && !mbar_test(bAf + 7 * 8, 0); i++) __nanosleep(200);
      if (lr0 < S_LEN) {
#pragma unroll 1
        for (int i = warp_g - 9; i < 16; i += 3) {
          const float g = gate_row(lr0 + i, lane, x, gate_w);
          if (lane == 0) asm volatile("st.shared.f32 [%0], %1;" ::"r"(sGate + i * 4), "f"(g) : "memory");
        }
        if (lane == 0) {
          mbar_arrive(bG);
          __threadfence();
          atomicAdd(&g_sync[F_GATE], 1u);
        }
      }
      uint32_t aph = 1;
#pragma unroll 1
      for (int ji = 0; ji < K1_MAXJOBS; ji++) aph ^= (p.jobs[cl][ji] >> 14) & 1;
      if (warp_g == 9) {
        uint32_t nxt = 0;
        if (lane == 0) {
#pragma unroll 1
        for (int ji = 0; ji < K1_MAXJOBS; ji++) {
          const uint32_t job = p.jobs[cl][ji];
          if (!(job & 3)) break;
          PWAIT(bS + (ji & 3) * 8, (ji >> 2) & 1);
          __threadfence();
          atomicAdd(&g_sync[(((job >> 6) & 3) == 2) ? (F_QKVA + ((job >> 3) & 7) * 2 + rank) : (F_HP + ((job >> 10) & 15))], 1u);
        }
#pragma unroll 1
        for (int it = 0;; it++) {
          PWAIT(bS2 + (it & 3) * 8, (it >> 2) & 1);
          const uint32_t item = lds32(sItem + (it & 7) * 4);
          nxt = lds32(sItem + ((it + 1) & 7) * 4);
          __threadfence();
          atomicOr(&g_sync[F_CTX + (item & 7) * 2 + rank], 1u << (item >> 3));
          if (nxt >= K2_END) break;
        }
        }
        const uint32_t unit = __shfl_sync(0xffffffffu, nxt, 0) & 255;
        {
          const int mblk = (7 - (p.unit[unit][0] >> 1)) * 2 + rank, nhalf = p.unit[unit][0] & 1;
          bf16* o = ptr_add(out, (mblk * 128 + p.unit[unit][1] * 32) * DM * 2);
          const bool mine = p.unit[unit][1] < 4;
#pragma unroll 4
          for (int i = 0; i < 32 && mine; i++) __stcg(reinterpret_cast<uint4*>(ptr_add(o, i * DM * 2 + nhalf * 512 + lane * 16)), make_uint4(0, 0, 0, 0));
#pragma unroll
          for (int i = 0; i < 4 && mine; i++) __stcg(reinterpret_cast<uint4*>(ptr_add(o, (i * 8 + (lane >> 2)) * DM * 2 + 1024 + nhalf * 64 + (lane & 3) * 16)), make_uint4(0, 0, 0, 0));
          asm volatile("fence.proxy.async.global;" ::: "memory");
          __threadfence();
          __syncwarp();
          if (lane == 0) {
            prefetch_tmap(&p.tmR[0]); prefetch_tmap(&p.tmR[1]);
            unsigned int* cnt = &g_sync[F_XCH + mblk * 2 + nhalf];
            const uint32_t xtarget = lds32(sGate + 64) * 4 + 4;
            if (mine) atomicAdd(cnt, 1u);
            uint32_t v;
#pragma unroll 1
            for (uint32_t spins = 0; spins < (1u << 22); spins++) {
              asm volatile("ld.acquire.gpu.global.u32 %0, [%1];" : "=r"(v) : "l"(cnt) : "memory");
              if ((int)(v - xtarget) >= 0) break;
              __nanosleep(200);
            }
            asm volatile("fence.proxy.async.global;" ::: "memory");
            mbar_arrive(bZ);
          }
        }
      } else if (warp_g == 11) {
        if (lane == 0) {
          asm volatile("st.shared.u32 [%0], %1;" ::"r"(sGate + 64), "r"(__ldcg(&g_sync[F_EPOCH])) : "memory");
          wait_flag(&g_sync[F_GATE], GATE_TARGET);
          prefetch_tmap(&p.tmC); prefetch_tmap(&p.tmQ); prefetch_tmap(&p.tmK); prefetch_tmap(&p.tmV);
          uint32_t tick;
          if (rank == 0) {
            PWAIT(bLast, 0);
            PWAIT(bAe + FIRST_DRAW * 8, aph);
            tick = atomicAdd(&g_sync[F_TICK], 1u);
            asm volatile("st.shared.u32 [%0], %1;" ::"r"(sTick + 8), "r"(tick) : "memory");
            asm volatile(
                "{\n.reg .b32 a, b;\nmapa.shared::cluster.u32 a, %0, 1;\nmapa.shared::cluster.u32 b, %1, 1;\n"
                "st.async.shared::cluster.mbarrier::complete_tx::bytes.u32 [a], %2, [b];\n}" ::"r"(sTick + 8), "r"(bT0), "r"(tick) : "memory");
          } else {
            mbar_expect(bT0, 4);
            PWAIT(bT0, 0);
            tick = lds32(sTick + 8);
          }
          wait_flag(&g_sync[F_HP + (p.order[tick] >> 4)], RDY_TARGET);
          mbar_arrive(bR);
        }
      } else if (warp_g == 10) {
        if (lr0 < S_LEN && lane == 0) {
          prefetch_tmap(&p.tmL[0]); prefetch_tmap(&p.tmL[1]); prefetch_tmap(&p.tmL[2]);
          wait_flag(&g_sync[F_QKVA + (lr0 >> 7)], K1_FLAG_TARGET);
          wait_flag(&g_sync[F_QKVA + (max(lr0 - 16, 0) >> 7)], K1_FLAG_TARGET);
          asm volatile("fence.proxy.async.global;" ::: "memory");
          PWAIT(bLast, 0);
#pragma unroll 1
          for (int kc = 0; kc < 6; kc++) {
            PWAIT(bAe + kc * 8, aph);
            if (kc == 3) {
              mbar_expect(bL, LV);
              tma4d(sL, &p.tmL[0], bL, lr0 / 2 - 8, 9, 0);
              tma4d(sL + LQ, &p.tmL[1], bL, lr0 / 2, 0, 0);
            }
          }
          mbar_expect(bL2, LQ);
          tma4d(sL + LV, &p.tmL[0], bL2, lr0 / 2 - 8, 18, 0);
        }
        __syncwarp();
        bar_sync(5, 256 + 32);
        if (lr0 < S_LEN && lane == 0) {
          asm volatile("cp.async.bulk.tensor.4d.global.shared::cta.bulk_group [%0, {%2, %3, %2, %2}], [%1];" ::"l"(&p.tmL[2]), "r"(sL + LQ), "r"(0), "r"(lr0 / 2) : "memory");
          asm volatile("cp.async.bulk.commit_group;" ::: "memory");
          asm volatile("cp.async.bulk.wait_group.read 0;" ::: "memory");
        }
        __syncwarp();
        if (lane < 12) mbar_arrive_cluster(bE + (4 + lane % 3) * 8, (lane / 3) & 1);
        if (lr0 < S_LEN && lane == 0) {
          asm volatile("cp.async.bulk.wait_group 0;" ::: "memory");
          asm volatile("fence.proxy.async.global;" ::: "memory");
          __threadfence();
          atomicAdd(&g_sync[F_OA + (lr0 >> 7)], 1u);
        }
      }
    }
    __syncwarp();
    cluster_sync();
  } else {
    reg_alloc<232>();
    const int wg = warp_g >> 2, warp = warp_g & 3, q = lane & 3;
    const bool sig = (lane == 0) && (warp < 2);
    {
      K1State st{0, 0, 0, nullptr, 0, 0, 0, 24};
      float acc[128];
      uint32_t pk[64];
      if (wg == 0) { TS(0, 0); TSC(0, 2); }
      uint32_t job = p.jobs[cl][0];
      k1_first(st, job, bAf, bBf);
      {
#pragma unroll 1
        for (int ji = 0; job & 3; ji++) {
          const uint32_t njob = p.jobs[cl][ji + 1];
          k1_tile(acc, pk, st, job, njob, sA, sB, bAf, bAe, bBf, bBe, bS, wg, warp, lane, rank);
          job = njob;
        }
      }
#pragma unroll
      for (int i = 0; i < 4; i++)
        mbar_arrive_cluster_if(bE + i * 8, warp & 1, sig);
      if (lr0 < S_LEN) mbar_wait(bG, 0);
      if (st.wsel == 3) {
#pragma unroll
        for (int G = 0; G < 16; G++) scale_q4(pk + G * 4);
      }
      auto flush = [&](int i, uint32_t dep) {
        asm volatile("{\n.reg .pred p;\nsetp.eq.u32 p, %5, 0;\n@p st.global.cs.v4.b32 [%0], {%1, %2, %3, %4};\n}" ::"l"(st.pp + goff(i / 2, i & 1)),
                     "r"(pk[i * 4]), "r"(pk[i * 4 + 1]), "r"(pk[i * 4 + 2]), "r"(pk[i * 4 + 3]), "r"(dep & blockIdx.y) : "memory");
      };
      if (wg == 0) { TS(0, 1); TSC(0, 3); }
      if (lr0 < S_LEN) {
        const float gate0 = __uint_as_float(lds32(sGate + (lane >> 2) * 8)), gate1 = __uint_as_float(lds32(sGate + (lane >> 2) * 8 + 4));
        local_attn(lr0, warp_g, sL, bL, bL2, lane, gate0, gate1, flush);
        k1_flag(st, lane, bS);
      } else {
        FLUSH();
      }
      bar_arrive(5, 256 + 32);
    }
    __syncwarp();
    uint32_t item, rot;
    {
      const int mybar = 1 + wg, otherbar = 2 - wg;
      const uint32_t never = blockIdx.y;
      float S[64], O[64];
      uint32_t P[32], Q[32];
      float m0, m1, l0, l1, gf0, gf1;
      uint32_t eoff;
      Cursor c{2 + 2 * (uint32_t)wg, 0}, ck{1 + (uint32_t)wg, 0};
      if (wg == 1) bar_arrive(1, 256);
      if (wg == 0) { TS(1, 0); TSC(1, 2); }
      {
        const Cursor cq{0, 0}, cs0{1, 0}, cs1{3, 0};
        const int it = 0, hi = wg ^ 1;
        mbar_wait2(bF, 0, bF + ck.s * 8, 0);
        LOAD_Q();
        wg_fence();
        ISSUE_QK(ck);
        wg_commit();
        RELEASE(cq);
        NEW_ITEM();
        wg_wait<0>();
        fence_regs(S);
      }
#pragma unroll 1
      for (int it = 0;;) {
        int hi = (wg ^ it ^ 1) & 1;
        RELEASE(ck);
        const int nblk = 2 * (item & 7) + 1 + hi;
        Cursor cv;
        float s0 = 0.f, s1 = 0.f;
        l0 = 0.f; l1 = 0.f;
        m0 = 0.f; m1 = 0.f;
        bool shifted = false;
        {
          const int d = warp * 16 + (lane >> 2) - 2 * q;
          if (rank == hi) {
#pragma unroll
            for (int jj = 0; jj < 8; jj++) MASK(jj, jj);
            EXPB(0); EXPB(1); EXPB(2); EXPB(3);
#pragma unroll
            for (int i = 32; i < 64; i++) S[i] = -INFINITY;
#pragma unroll
            for (int i = 16; i < 32; i++) P[i] = 0;
          } else {
#pragma unroll
            for (int jj = 0; jj < 8; jj++) MASK(jj + 8, jj);
            EXPB(0); EXPB(1); EXPB(2); EXPB(3); EXPB(4); EXPB(5); EXPB(6); EXPB(7);
          }
        }
        float chk;
        asm("{\n.reg .pred p;\nsetp.ge.f32 p, %1, %2;\nselp.f32 %0, %3, 0f7F800000, p;\n}" : "=f"(chk) : "f"(fminf(s0, s1)), "f"(q ? -1.f : SPEC_LO), "f"(s0 + s1));
        fence_regs(P);
        TB(9);
#pragma unroll 1
        for (int n = 1;; n++) {
          if (__any_sync(0xffffffffu, !(chk <= SPEC_HI))) {
            float mx0 = fmaxf(S[0], S[1]), mx1 = fmaxf(S[2], S[3]);
#pragma unroll
            for (int jj = 1; jj < 16; jj++) {
              mx0 = fmaxf(mx0, fmaxf(S[jj * 4 + 0], S[jj * 4 + 1]));
              mx1 = fmaxf(mx1, fmaxf(S[jj * 4 + 2], S[jj * 4 + 3]));
            }
            mx0 = fmaxf(mx0, __shfl_xor_sync(0xffffffffu, mx0, 1));
            mx1 = fmaxf(mx1, __shfl_xor_sync(0xffffffffu, mx1, 1));
            mx0 = fmaxf(mx0, __shfl_xor_sync(0xffffffffu, mx0, 2));
            mx1 = fmaxf(mx1, __shfl_xor_sync(0xffffffffu, mx1, 2));
            const float lo = (n == 1) ? -INFINITY : 0.f;
            mx0 = fmaxf(mx0, lo);
            mx1 = fmaxf(mx1, lo);
            m0 += mx0; m1 += mx1;
            shifted = true;
            const float sc0 = ex2(-fmaxf(mx0, 0.f)), sc1 = ex2(-fmaxf(mx1, 0.f));
            l0 *= sc0; l1 *= sc1;
            s0 = 0.f; s1 = 0.f;
#pragma unroll
            for (int jj = 0; jj < 16; jj++) {
              const float e0 = ex2(S[jj * 4 + 0] - mx0), e1 = ex2(S[jj * 4 + 1] - mx0), e2 = ex2(S[jj * 4 + 2] - mx1), e3 = ex2(S[jj * 4 + 3] - mx1);
              s0 += e0 + e1;
              s1 += e2 + e3;
              P[jj * 2 + 0] = pack_bf16(e0, e1);
              P[jj * 2 + 1] = pack_bf16(e2, e3);
              O[jj * 4 + 0] *= sc0;
              O[jj * 4 + 1] *= sc0;
              O[jj * 4 + 2] *= sc1;
              O[jj * 4 + 3] *= sc1;
            }
          }
          l0 += s0;
          l1 += s1;
          if (n >= nblk) break;
          ck = c; c.next();
          cv = c; c.next();
          mbar_wait2(bF + ck.s * 8, ck.ph, bF + cv.s * 8, cv.ph);
          TURN_SYNC();
          TRC(0);
          wg_fence();
          ISSUE_QK(ck);
          wg_commit();
          {
            const uint64_t dv = make_desc(sbase + cv.s * 32768, 16384, 1024, 1);
#pragma unroll
            for (int t = 0; t < 8; t++) {
              wgmma_rs_n128<1, 0>(O, P[4 * t], P[4 * t + 1], P[4 * t + 2], P[4 * t + 3], dv + (uint64_t)(t * 128), (t > 0) ? 1 : (n != 1));
              if ((PVM >> t) & 1) wg_commit();
            }
          }
          TURN_ARRIVE();
          s0 = 0.f; s1 = 0.f;
          wg_wait<__builtin_popcount(PVM)>();
          fence_regs(S);
          RELEASE(ck);
          if (shifted) {
#pragma unroll
            for (int i = 0; i < 64; i++) S[i] -= (i & 2) ? m1 : m0;
          }
          wg_wait<__builtin_popcount(PVM) - 1>();
          EXPC(0); EXPC(1); EXPC(2); EXPC(3); EXPC(4); EXPC(5); EXPC(6); EXPC(7);
          chk = s0 + s1;
        }
        it++;
        hi ^= 1;
        TB(0);
        Cursor cq = c, cs0, cs1;
        rot = k3_rot(c.s);
        c.next();
        ck = c; c.next();
        cs0 = ck; cs1 = ck;
        cv = c; c.next();
        if (!hi) {
          ck = c; c.next();
          cs1 = c; c.next();
        }
        mbar_wait(bF + cq.s * 8, cq.ph);
        TB(1);
        LOAD_Q();
        const uint32_t rdy = mbar_test(bF + ck.s * 8, ck.ph) & mbar_test(bF + cv.s * 8, cv.ph);
        l0 += __shfl_xor_sync(0xffffffffu, l0, 1);
        l1 += __shfl_xor_sync(0xffffffffu, l1, 1);
        l0 += __shfl_xor_sync(0xffffffffu, l0, 2);
        l1 += __shfl_xor_sync(0xffffffffu, l1, 2);
        if (item >= K2_END) {
          TURN_SYNC();
          TRC(2);
          wg_fence();
          ISSUE_PV(cq, nblk == 1);
          wg_commit();
          if (wg == (it & 1)) TURN_ARRIVE();
          asm volatile("" : "+f"(gf0), "+f"(gf1), "+f"(l0), "+f"(l1));
          const float f0 = __fdividef(1.f - gf0, l0), f1 = __fdividef(1.f - gf1, l1);
          bf16* optr = ptr_add(g_ctx, eoff);
          wg_wait<0>();
          fence_regs(O);
          mbar_arrive_cluster_if(bH, warp & 1, sig);
          STORE_O(0); STORE_O(1); STORE_O(2); STORE_O(3);
          __syncwarp();
          mbar_arrive_if(bS2 + ((it - 1) & 3) * 8, lane == 0);
          break;
        }
        if (!rdy) mbar_wait2(bF + ck.s * 8, ck.ph, bF + cv.s * 8, cv.ph);
        TB(2);
        TURN_SYNC();
        TB(3);
        TRC(1);
        wg_fence();
        ISSUE_PV(cv, nblk == 1);
        wg_commit();
        ISSUE_QK(ck);
        wg_commit();
        TURN_ARRIVE();
        RELEASE(cq);
        TB(4);
        asm volatile("" : "+f"(gf0), "+f"(gf1), "+f"(l0), "+f"(l1));
        const float f0 = __fdividef(1.f - gf0, l0), f1 = __fdividef(1.f - gf1, l1);
        wg_wait<1>();
        fence_regs(O);
        fence_regs(P);
        TB(5);
        RELEASE(cv);
        {
          bf16* optr = ptr_add(g_ctx, eoff);
          STORE_O(0); STORE_O(1); STORE_O(2); STORE_O(3);
          __syncwarp();
          mbar_arrive_if(bS2 + ((it - 1) & 3) * 8, lane == 0);
        }
        TB(6);
        NEW_ITEM();
        TB(7);
        wg_wait<0>();
        fence_regs(S);
        TB(8);
      }
      TRC(3);
      if (wg == 1) { TS(1, 1); TSC(1, 3); }
    }
    __syncwarp();
    const uint32_t unit = item & 255;
    {
      const int mblk = (7 - (p.unit[unit][0] >> 1)) * 2 + rank, nhalf = p.unit[unit][0] & 1;
      float acc[144];
      uint32_t s = rot, ph = 0, prev = 0, k = 0;
      if (wg == 0) { TS(2, 0); TSC(2, 2); }
      uint32_t fa[16], fb[16], fc[16];
      const uint32_t aoff = (wg * 64 + warp * 16 + (lane & 15)) * 128 + (((lane >> 4) ^ (lane & 7)) << 4);
#define C_NEXT()                                                                                               \
  do {                                                                                                         \
    s = (s + 1) & 3;                                                                                           \
    if (s == rot) ph ^= 1;                                                                                     \
    mbar_wait(b3F + s * 8, ph);                                                                                \
  } while (0)
#define C_LOAD(F)                                                                                              \
  do {                                                                                                         \
    _Pragma("unroll") for (int t = 0; t < 4; t++)                                                              \
        ldsm_x4(F[4 * t], F[4 * t + 1], F[4 * t + 2], F[4 * t + 3], sbase + s * K3_STAGE + (aoff ^ (t * 32))); \
  } while (0)
#define C_MMA(F, S, H, SD)                                                                                     \
  do {                                                                                                         \
    const uint32_t st = sbase + (S) * K3_STAGE;                                                                \
    const uint64_t db = make_desc(st + 16384, 4096, 1024, 1), dt = make_desc(st + 49152, 16, 512, 2);          \
    _Pragma("unroll") for (int t = 0; t < 4; t++) {                                                            \
      const int sd = (t > 0) || (SD);                                                                          \
      if ((H) & 1) wgmma_rs_n128<1, 0>(acc, F[4 * t], F[4 * t + 1], F[4 * t + 2], F[4 * t + 3], db + (uint64_t)((t >> 1) * 1024 + (t & 1) * 128), sd); \
      if ((H) & 2) wgmma_rs_n128<1, 64>(acc, F[4 * t], F[4 * t + 1], F[4 * t + 2], F[4 * t + 3], db + (uint64_t)((t >> 1) * 1024 + (t & 1) * 128 + 512), sd); \
      if ((H) & 2) wgmma_rs_n32<1, 128>(acc, F[4 * t], F[4 * t + 1], F[4 * t + 2], F[4 * t + 3], dt + (uint64_t)(t * 64), sd); \
    }                                                                                                          \
  } while (0)
#define C_STEP(F, G)                                                                                           \
  {                                                                                                            \
    wg_fence();                                                                                                \
    C_MMA(F, s, 3, k > 0);                                                                                     \
    wg_commit();                                                                                               \
    wg_wait<1>();                                                                                              \
    fence_regs(G);                                                                                             \
    mbar_arrive_cluster_if(b3E + prev * 8, warp & 1, sig && k > 0);                                            \
    prev = s;                                                                                                  \
    TCK(k + 1);                                                                                                \
    C_NEXT();                                                                                                  \
    if ((tid & 127) == 0 && k < 11) TP(37 + wg * 12 + k);                                                      \
    if (++k + CR >= lds32(sK1)) break;                                                                         \
    C_LOAD(G);                                                                                                 \
  }
      TCK(0);
      mbar_wait(b3F + s * 8, 0);
      if ((tid & 127) == 0) TP(36 + wg * 12);
      C_LOAD(fa);
#pragma unroll
      for (int i = 0; i < 16; i++) fb[i] = 0;
#pragma unroll 1
      for (;;) {
        C_STEP(fa, fb)
        C_STEP(fb, fa)
      }
      C_LOAD(fc);
      if (wg == 1) {
        wg_wait<0>();
        mbar_arrive_cluster_if(b3E + prev * 8, warp & 1, sig);
        mbar_wait(bLd, 0);
      }
      const uint32_t s0 = s;
      wg_fence();
      C_MMA(fc, s0, 2, 1);
      wg_commit();
      wg_wait<1>();
      fence_regs(fa);
      fence_regs(fb);
      mbar_arrive_cluster_if(b3E + prev * 8, warp & 1, sig && wg == 0);
      cluster_arrive();
      C_NEXT();
      C_LOAD(fa);
      wg_fence();
      C_MMA(fa, s, 2, 1);
      C_MMA(fc, s0, 1, 1);
      wg_commit();
      C_NEXT();
      C_LOAD(fb);
      wg_fence();
      C_MMA(fb, s, 2, 1);
      wg_commit();
      wg_wait<1>();
      fence_regs(fc);
      C_NEXT();
      C_LOAD(fc);
      wg_fence();
      C_MMA(fc, s, 2, 1);
      wg_commit();
      C_MMA(fa, (s0 + 1) & 3, 1, 1);
      C_MMA(fb, (s0 + 2) & 3, 1, 1);
      C_MMA(fc, s, 1, 1);
      wg_commit();
      mbar_arrive_if(bLd, tid < 128 && lane == 0);
      const uint32_t stail = sbase + K3_NST * K3_STAGE + warp_g * 1024;
      const int row = mblk * 128 + warp_g * 16;
      mbar_wait(bZ, 0);
#pragma unroll
      for (int h = 1; h >= 0; h--) {
        if (h) wg_wait<1>(); else wg_wait<0>();
#pragma unroll
        for (int i = h * 64; i < 64 + h * 80; i++) asm volatile("" : "+f"(acc[i])::"memory");
        if (!h && wg == 0) TS(2, 4);
#pragma unroll
        for (int i = h * 8; i < 8 + h * 10; i++) {
          const uint32_t ad = (i < 16) ? sbase + (i >> 2) * K3_STAGE + (aoff ^ ((i & 3) * 32))
                                       : stail + (lane & 15) * 64 + ((((i & 1) * 2 + (lane >> 4)) ^ ((lane >> 1) & 3)) << 4);
          asm volatile("stmatrix.sync.aligned.m8n8.x4.shared.b16 [%0], {%1, %2, %3, %4};" ::"r"(ad), "r"(pack_bf16(acc[i * 8], acc[i * 8 + 1])),
                       "r"(pack_bf16(acc[i * 8 + 2], acc[i * 8 + 3])), "r"(pack_bf16(acc[i * 8 + 4], acc[i * 8 + 5])), "r"(pack_bf16(acc[i * 8 + 6], acc[i * 8 + 7])) : "memory");
        }
        asm volatile("fence.proxy.async.shared::cta;" ::: "memory");
        __syncwarp();
        if (!h && wg == 0) TS(2, 5);
        if (lane == 0) {
#pragma unroll
          for (int c = h * 2; c < 2 + h * 3; c++)
            asm volatile("cp.reduce.async.bulk.tensor.2d.global.shared::cta.add.tile.bulk_group [%0, {%2, %3}], [%1];" ::"l"(&p.tmR[c >> 2]),
                         "r"((c < 4) ? sbase + c * K3_STAGE + warp_g * 2048 : stail), "r"((c < 4) ? nhalf * 256 + c * 64 : 512 + nhalf * 32), "r"(row) : "memory");
        }
        __syncwarp();
      }
      if (lane == 0) {
        asm volatile("cp.async.bulk.commit_group;" ::: "memory");
        if (wg == 0) TS(2, 6);
        asm volatile("cp.async.bulk.wait_group 0;" ::: "memory");
      }
      __syncwarp();
    }
    if (wg == 0) { TS(2, 1); TSC(2, 3); }
    cluster_wait();
  }
}

typedef CUresult (*EncFn)(CUtensorMap*, CUtensorMapDataType, cuuint32_t, void*, const cuuint64_t*, const cuuint64_t*, const cuuint32_t*,
                          const cuuint32_t*, CUtensorMapInterleave, CUtensorMapSwizzle, CUtensorMapL2promotion, CUtensorMapFloatOOBfill);

static void enc2d(EncFn enc, CUtensorMap* m, const void* ptr, uint64_t cols, uint64_t rows, uint32_t bc, uint32_t br,
                  CUtensorMapSwizzle sw = CU_TENSOR_MAP_SWIZZLE_128B) {
  cuuint64_t gd[2] = {cols, rows}, gs[1] = {cols * 2};
  cuuint32_t bx[2] = {bc, br}, es[2] = {1, 1};
  enc(m, CU_TENSOR_MAP_DATA_TYPE_BFLOAT16, 2, const_cast<void*>(ptr), gd, gs, bx, es, CU_TENSOR_MAP_INTERLEAVE_NONE, sw,
      CU_TENSOR_MAP_L2_PROMOTION_L2_256B, CU_TENSOR_MAP_FLOAT_OOB_FILL_NONE);
}
static void enc3d(EncFn enc, CUtensorMap* m, const void* ptr, uint64_t cols, uint64_t rows, uint32_t br, uint32_t bch) {
  cuuint64_t gd[3] = {64, rows, cols / 64}, gs[2] = {cols * 2, 128};
  cuuint32_t bx[3] = {64, br, bch}, es[3] = {1, 1, 1};
  enc(m, CU_TENSOR_MAP_DATA_TYPE_BFLOAT16, 3, const_cast<void*>(ptr), gd, gs, bx, es, CU_TENSOR_MAP_INTERLEAVE_NONE,
      CU_TENSOR_MAP_SWIZZLE_128B, CU_TENSOR_MAP_L2_PROMOTION_L2_256B, CU_TENSOR_MAP_FLOAT_OOB_FILL_NONE);
}

static void build_k1_jobs(Params& p) {
  int cnt[NCLUSTER];
  for (int c = 0; c < NCLUSTER; c++) {
    cnt[c] = 0;
    for (int i = 0; i <= K1_MAXJOBS; i++) p.jobs[c][i] = 0;
  }
  auto add = [&](int c, int nch, int a_sel, int mp, int w_sel, int chunk0) {
    p.jobs[c][cnt[c]++] = (uint16_t)((nch - 1) | (a_sel << 2) | (mp << 3) | (w_sel << 6) | (chunk0 << 8));
  };
  const char* plan = "ccccccccccc cccccccccc ccccccc cccc xxxx xxxx xxxxxx xxxxxxxx";
  int TIE = 0;
  int XA = 0;
  const char* cur[8];
  int tend[8] = {};
  for (int g = 0; g < 8; g++) {
    cur[g] = plan;
    while (*plan == 'c' || *plan == 'x') plan++;
    if (*plan) plan++;
  }
  int kc = 0, kx = 0;
  for (;;) {
    int b = -1, bt = 0;
    for (int g = 0; g < 8; g++) {
      const int t = tend[g] + (*cur[g] == 'x' ? 94 : 85);
      if ((*cur[g] == 'c' || *cur[g] == 'x') && (b < 0 || t < bt || (TIE && t == bt))) { b = g; bt = t; }
    }
    if (b < 0) break;
    const int a = kx - XA;
    for (int mp = 0; mp < 8; mp++) {
      if (*cur[b] == 'c') add(b * 8 + mp, 4, 0, mp, kc & 1, (kc >> 1) * 4);
      else if (a >= 0 && a < 7) add(b * 8 + mp, a == 0 ? 3 : 4, 1, mp, 2, a == 0 ? 24 : (a - 1) * 4);
      else add(b * 8 + mp, 4, 1, mp, 3, (a < 0 ? kx : kx - 7) * 4);
    }
    if (*cur[b] == 'c') kc++; else kx++;
    cur[b]++;
    tend[b] = bt;
  }
  for (int mp = 0; mp < 8; mp++) add(64 + mp / 4, 4, 1, mp, 3, 15 * 4);
  for (int cc = 0; cc < NCLUSTER; cc++)
    for (int i = 0; i < cnt[cc]; i++) {
      const int key = p.jobs[cc][i] & 0x3C;
      if (i == 0 || (p.jobs[cc][i - 1] & 0x3C) != key) p.jobs[cc][i] |= (1 << 14);
      if (i == cnt[cc] - 1 || (p.jobs[cc][i + 1] & 0x3C) != key) p.jobs[cc][i] |= (1 << 15);
    }
}

static void build_k2_items(Params& p) {
  int ps[8][3] = {{0, 2, 2}, {0, 6, 0}, {6, 24, 4}, {6, 32, 0}};
  bool done[256] = {};
  int n = 0;
  for (int i = 0; i < 8; i++)
    for (int j = 7; j >= ps[i][2]; j--)
      for (int h = ps[i][0]; h < ps[i][1]; h++)
        if (!done[h * 8 + j]) { done[h * 8 + j] = true; p.order[n++] = (uint8_t)(h * 8 + j); }
}

static void build_k3_units(Params& p) {
  const char* map = "0123456789abcddcba98765432100123456789abcddcba9876543210feeffeeffe";
  int cnt[16] = {};
  for (int u = 0; u < 66; u++) {
    const int t = (map[u] > '9') ? map[u] - 'a' + 10 : map[u] - '0';
    p.unit[u][0] = (uint8_t)t; p.unit[u][1] = (uint8_t)cnt[t]; p.unit[u][2] = (uint8_t)(cnt[t] * K3_NS);
    cnt[t]++;
  }
  for (int u = 0; u < 66; u++) p.unit[u][3] = (uint8_t)(cnt[p.unit[u][0]] * K3_NS);
}

extern "C" void kernel_launch(void* const* d_in, const int* in_sizes, int n_in, void* d_out, int out_size) {
  const bf16* x = (const bf16*)d_in[0];
  const bf16* wqkv = (const bf16*)d_in[1];
  const bf16* wo = (const bf16*)d_in[2];
  const bf16* ckv = (const bf16*)d_in[4];
  const bf16* w_q = (const bf16*)d_in[5];
  const bf16* w_uk = (const bf16*)d_in[6];
  const bf16* w_uv = (const bf16*)d_in[7];
  const bf16* w_o = (const bf16*)d_in[8];
  const bf16* gate_w = (const bf16*)d_in[9];

  EncFn enc = nullptr;
  cudaDriverEntryPointQueryResult qr;
  cudaGetDriverEntryPoint("cuTensorMapEncodeTiled", (void**)&enc, cudaEnableDefault, &qr);
  void *pK, *pV, *pCtx, *pQA;
  cudaGetSymbolAddress(&pQA, g_QKVA);
  cudaGetSymbolAddress(&pK, g_K);
  cudaGetSymbolAddress(&pV, g_V);
  cudaGetSymbolAddress(&pCtx, g_ctx);

  static Params p;
  enc2d(enc, &p.tmA[0], ckv, DC, S_LEN, 64, 128);
  enc2d(enc, &p.tmA[1], x, DM, S_LEN, 64, 128);
  enc3d(enc, &p.tmW[0], w_uk, HDIM, DC, 16, 4);
  enc3d(enc, &p.tmW[1], w_uv, HDIM, DC, 16, 4);
  enc3d(enc, &p.tmW[2], wqkv, NQKVA, DM, 16, 4);
  enc3d(enc, &p.tmW[3], w_q, HDIM, DM, 16, 4);
  build_k1_jobs(p);
  enc2d(enc, &p.tmK, pK, 64, 64 * S_LEN, 64, 128);
  enc2d(enc, &p.tmV, pV, 64, 64 * S_LEN, 64, 128);
  enc2d(enc, &p.tmQ, pCtx, 64, 73 * S_LEN, 64, 64);
  build_k2_items(p);
  build_k3_units(p);
  for (int i = 0; i < 3; i++) {
    const cuuint64_t cs = S_LEN * 128, nch = (i < 2) ? 27 : 9;
    cuuint64_t gd[4] = {64, S_LEN / 2, i ? 2 : nch, i ? nch : 2}, gs[3] = {256, i ? 128 : cs, i ? cs : 128};
    cuuint32_t bx[4] = {64, i ? 8u : 16u, i ? 2u : 9u, i ? 9u : 2u}, es[4] = {1, 1, 1, 1};
    enc(&p.tmL[i], CU_TENSOR_MAP_DATA_TYPE_BFLOAT16, 4, (i < 2) ? pQA : (void*)((bf16*)pCtx + S_LEN * HDIM), gd, gs, bx, es, CU_TENSOR_MAP_INTERLEAVE_NONE,
        CU_TENSOR_MAP_SWIZZLE_128B, CU_TENSOR_MAP_L2_PROMOTION_L2_256B, CU_TENSOR_MAP_FLOAT_OOB_FILL_NONE);
  }
  enc2d(enc, &p.tmC, pCtx, 64, 73 * S_LEN, 64, 128);
  enc3d(enc, &p.tmO[0], w_o, DM, HDIM, 32, 4);
  enc3d(enc, &p.tmO[1], wo, DM, DM, 32, 4);
  enc2d(enc, &p.tmOt[0], w_o, DM, HDIM, 32, 32, CU_TENSOR_MAP_SWIZZLE_64B);
  enc2d(enc, &p.tmOt[1], wo, DM, DM, 32, 32, CU_TENSOR_MAP_SWIZZLE_64B);
  enc2d(enc, &p.tmR[0], d_out, DM, S_LEN, 64, 16);
  enc2d(enc, &p.tmR[1], d_out, DM, S_LEN, 32, 16, CU_TENSOR_MAP_SWIZZLE_64B);

  cudaFuncSetAttribute(fused_kernel, cudaFuncAttributeMaxDynamicSharedMemorySize, SMEM_BYTES);
  fused_kernel<<<NCLUSTER * 2, 384, SMEM_BYTES>>>(p, x, gate_w, (bf16*)d_out);
}
```

```cpp
#include <cuda_runtime.h>
#include <cuda_bf16.h>
#include <cuda.h>
#include <stdint.h>

typedef __nv_bfloat16 bf16;

constexpr int S_LEN = 2048, DM = 576, DC = 512, HDIM = 4096, NQKVA = 1728, KCAT = 4672;
constexpr int NCLUSTER = 66;
__host__ __device__ constexpr int goff(int G, int r) { return (G >> 1) * S_LEN * 64 + (G & 1) * 32 + r * 512; }

__device__ __align__(1024) bf16 g_K[S_LEN * HDIM];
__device__ __align__(1024) bf16 g_V[S_LEN * HDIM];
__device__ __align__(1024) bf16 g_QKVA[S_LEN * NQKVA + 64];
__device__ __align__(1024) bf16 g_ctx[S_LEN * KCAT];
__device__ float g_gate[S_LEN];
__device__ __align__(16) unsigned int g_sync[400];
constexpr int F_QKVA = 0, F_HP = 16, F_CTX = 32, F_OA = 48, F_CLM = 64, F_GATE = 96, F_TICK = 97, F_DONE = 98, F_XCH = 128, F_EPOCH = 384;

__device__ __forceinline__ uint32_t smem_u32(const void* p) { return (uint32_t)__cvta_generic_to_shared(p); }
__device__ __forceinline__ void mbar_init(uint32_t a, uint32_t c) {
  asm volatile("mbarrier.init.shared::cta.b64 [%0], %1;" ::"r"(a), "r"(c));
}
__device__ __forceinline__ void mbar_expect(uint32_t a, uint32_t b) {
  asm volatile("mbarrier.arrive.expect_tx.shared::cta.b64 _, [%0], %1;" ::"r"(a), "r"(b) : "memory");
}
#define TS(k, i)
#define TSC(k, i)
#define TSM(k)
#define BSEG(i)
#define TB(k)
#define TRC(fl)
#define TCK(i)
#define TP(i)
#define SPIN_LIMIT "4194304"
__device__ __forceinline__ void mbar_wait(uint32_t a, uint32_t parity) {
  asm volatile(
      "{\n.reg .pred p;\n.reg .u32 n;\n"
      "mbarrier.try_wait.parity.shared::cta.b64 p, [%0], %1;\n"
      "@p bra DONE;\n"
      "mov.u32 n, 0;\n"
      "LOOP:\n"
      "mbarrier.try_wait.parity.shared::cta.b64 p, [%0], %1;\n"
      "@p bra DONE;\n"
      "add.u32 n, n, 1;\n"
      "setp.lt.u32 p, n, " SPIN_LIMIT ";\n"
      "@p bra LOOP;\n"
      "DONE:\n}" ::"r"(a), "r"(parity) : "memory");
}
template <int NS>
__device__ __forceinline__ void mbar_wait_ns(uint32_t a, uint32_t parity) {
  asm volatile(
      "{\n.reg .pred p;\n.reg .u32 n;\n"
      "mov.u32 n, 0;\n"
      "LOOP:\n"
      "mbarrier.try_wait.parity.shared::cta.b64 p, [%0], %1, %2;\n"
      "@p bra DONE;\n"
      "add.u32 n, n, 1;\n"
      "setp.lt.u32 p, n, " SPIN_LIMIT ";\n"
      "@p bra LOOP;\n"
      "DONE:\n}" ::"r"(a), "r"(parity), "n"(NS) : "memory");
}
__device__ __forceinline__ void mbar_wait2(uint32_t a, uint32_t pa, uint32_t b, uint32_t pb) {
  asm volatile(
      "{\n.reg .pred p, q;\n.reg .u32 n;\n"
      "mov.u32 n, 0;\n"
      "LOOP:\n"
      "mbarrier.try_wait.parity.shared::cta.b64 p, [%0], %1;\n"
      "mbarrier.try_wait.parity.shared::cta.b64 q, [%2], %3;\n"
      "add.u32 n, n, 1;\n"
      "and.pred p, p, q;\n"
      "setp.lt.and.u32 p, n, " SPIN_LIMIT ", !p;\n"
      "@p bra LOOP;\n"
      "}" ::"r"(a), "r"(pa), "r"(b), "r"(pb) : "memory");
}
__device__ __forceinline__ uint32_t mbar_test(uint32_t a, uint32_t parity) {
  uint32_t r;
  asm volatile("{\n.reg .pred p;\nmbarrier.test_wait.parity.shared::cta.b64 p, [%1], %2;\nselp.u32 %0, 1, 0, p;\n}" : "=r"(r) : "r"(a), "r"(parity) : "memory");
  return r;
}
__device__ __forceinline__ void mbar_arrive(uint32_t a) {
  asm volatile("mbarrier.arrive.shared::cta.b64 _, [%0];" ::"r"(a) : "memory");
}
__device__ __forceinline__ void mbar_arrive_cluster(uint32_t a, uint32_t cta) {
  asm volatile("{\n.reg .b32 r;\nmapa.shared::cluster.u32 r, %0, %1;\nmbarrier.arrive.shared::cluster.b64 _, [r];\n}" ::"r"(a),
               "r"(cta) : "memory");
}
__device__ __forceinline__ void mbar_arrive_cluster_if(uint32_t a, uint32_t cta, bool pred) {
  asm volatile("{\n.reg .b32 r;\n.reg .pred p;\nsetp.ne.u32 p, %2, 0;\nmapa.shared::cluster.u32 r, %0, %1;\n@p mbarrier.arrive.shared::cluster.b64 _, [r];\n}" ::"r"(a),
               "r"(cta), "r"((uint32_t)pred) : "memory");
}
__device__ __forceinline__ void anchor(float v, uint32_t pred) {
  asm volatile("{\n.reg .pred p;\nsetp.ne.u32 p, %1, 0;\n@p st.shared.f32 [%1], %0;\n}" ::"f"(v), "r"(pred) : "memory");
}
__device__ __forceinline__ void mbar_arrive_if(uint32_t a, bool pred) {
  asm volatile("{\n.reg .pred p;\nsetp.ne.u32 p, %1, 0;\n@p mbarrier.arrive.shared::cta.b64 _, [%0];\n}" ::"r"(a), "r"((uint32_t)pred) : "memory");
}
__device__ __forceinline__ void tma2d(uint32_t dst, const CUtensorMap* m, uint32_t bar, int c0, int c1) {
  asm volatile("cp.async.bulk.tensor.2d.shared::cluster.global.mbarrier::complete_tx::bytes [%0], [%1, {%3, %4}], [%2];" ::"r"(dst),
               "l"(m), "r"(bar), "r"(c0), "r"(c1) : "memory");
}
__device__ __forceinline__ void tma2d_mc(uint32_t dst, const CUtensorMap* m, uint32_t bar, int c0, int c1, uint16_t mask) {
  asm volatile(
      "cp.async.bulk.tensor.2d.shared::cluster.global.mbarrier::complete_tx::bytes.multicast::cluster [%0], [%1, {%3, %4}], [%2], %5;" ::"r"(dst),
      "l"(m), "r"(bar), "r"(c0), "r"(c1), "h"(mask) : "memory");
}
__device__ __forceinline__ void tma3d_mc(uint32_t dst, const CUtensorMap* m, uint32_t bar, int c0, int c1, int c2, uint16_t mask) {
  asm volatile(
      "cp.async.bulk.tensor.3d.shared::cluster.global.mbarrier::complete_tx::bytes.multicast::cluster [%0], [%1, {%3, %4, %5}], [%2], %6;" ::"r"(dst),
      "l"(m), "r"(bar), "r"(c0), "r"(c1), "r"(c2), "h"(mask) : "memory");
}
__device__ __forceinline__ void tma3d(uint32_t dst, const CUtensorMap* m, uint32_t bar, int c0, int c1, int c2) {
  asm volatile(
      "cp.async.bulk.tensor.3d.shared::cluster.global.mbarrier::complete_tx::bytes [%0], [%1, {%3, %4, %5}], [%2];" ::"r"(dst),
      "l"(m), "r"(bar), "r"(c0), "r"(c1), "r"(c2) : "memory");
}
__device__ __forceinline__ void tma_pf2d(const CUtensorMap* m, int c0, int c1) {
  asm volatile("cp.async.bulk.prefetch.tensor.2d.L2.global [%0, {%1, %2}];" ::"l"(m), "r"(c0), "r"(c1) : "memory");
}
__device__ __forceinline__ void tma_pf3d(const CUtensorMap* m, int c0, int c1, int c2) {
  asm volatile("cp.async.bulk.prefetch.tensor.3d.L2.global [%0, {%1, %2, %3}];" ::"l"(m), "r"(c0), "r"(c1), "r"(c2) : "memory");
}
__device__ __forceinline__ void prefetch_tmap(const CUtensorMap* m) {
  asm volatile("prefetch.tensormap [%0];" ::"l"(m) : "memory");
}
__device__ __forceinline__ void cluster_arrive() { asm volatile("barrier.cluster.arrive.relaxed.aligned;" ::: "memory"); }
__device__ __forceinline__ void cluster_wait() { asm volatile("barrier.cluster.wait.aligned;" ::: "memory"); }
__device__ __forceinline__ void cluster_sync() {
  cluster_arrive();
  cluster_wait();
}
__device__ __forceinline__ uint32_t cluster_rank() {
  uint32_t r;
  asm volatile("mov.u32 %0, %%cluster_ctarank;" : "=r"(r));
  return r;
}
__device__ __forceinline__ bool elect_one() {
  uint32_t p;
  asm volatile("{\n.reg .pred q;\nelect.sync _|q, 0xffffffff;\nselp.u32 %0, 1, 0, q;\n}" : "=r"(p));
  return p;
}
__device__ __forceinline__ void ldsm_x4(uint32_t& r0, uint32_t& r1, uint32_t& r2, uint32_t& r3, uint32_t addr) {
  asm volatile("ldmatrix.sync.aligned.m8n8.x4.shared.b16 {%0, %1, %2, %3}, [%4];" : "=r"(r0), "=r"(r1), "=r"(r2), "=r"(r3) : "r"(addr) : "memory");
}
__device__ __forceinline__ void wg_fence() { asm volatile("wgmma.fence.sync.aligned;" ::: "memory"); }
__device__ __forceinline__ void wg_commit() { asm volatile("wgmma.commit_group.sync.aligned;" ::: "memory"); }
template <int N>
__device__ __forceinline__ void wg_wait() { asm volatile("wgmma.wait_group.sync.aligned %0;" ::"n"(N) : "memory"); }
template <int N>
__device__ __forceinline__ void reg_alloc() { asm volatile("setmaxnreg.inc.sync.aligned.u32 %0;" ::"n"(N)); }
template <int N>
__device__ __forceinline__ void reg_dealloc() { asm volatile("setmaxnreg.dec.sync.aligned.u32 %0;" ::"n"(N)); }
__device__ __forceinline__ void bar_sync(int id, int n) { asm volatile("bar.sync %0, %1;" ::"r"(id), "r"(n) : "memory"); }
__device__ __forceinline__ void bar_arrive(int id, int n) { asm volatile("bar.arrive %0, %1;" ::"r"(id), "r"(n) : "memory"); }
template <int NT>
__device__ __forceinline__ void fence_regs(float (&d)[NT]) {
#pragma unroll
  for (int i = 0; i < NT; i++) asm volatile("" : "+f"(d[i])::"memory");
}
template <int NT>
__device__ __forceinline__ void fence_regs(uint32_t (&d)[NT]) {
#pragma unroll
  for (int i = 0; i < NT; i++) asm volatile("" : "+r"(d[i])::"memory");
}
__device__ __forceinline__ uint64_t make_desc(uint32_t saddr, uint32_t lbo, uint32_t sbo, uint32_t layout) {
  return (uint64_t)((saddr & 0x3FFFF) >> 4) | ((uint64_t)(lbo >> 4) << 16) | ((uint64_t)(sbo >> 4) << 32) | ((uint64_t)layout << 62);
}
__device__ __forceinline__ uint32_t pack_bf16(float lo, float hi) {
  uint32_t r;
  asm("cvt.rn.bf16x2.f32 %0, %1, %2;" : "=r"(r) : "f"(hi), "f"(lo));
  return r;
}
__device__ __forceinline__ float ex2(float x) {
  float r;
  asm("ex2.approx.ftz.f32 %0, %1;" : "=f"(r) : "f"(x));
  return r;
}
__device__ __forceinline__ void st_v4(void* p, uint32_t a, uint32_t b, uint32_t c, uint32_t d) {
#define ST_MOD ""
  asm volatile("st.global" ST_MOD ".v4.b32 [%0], {%1, %2, %3, %4};" ::"l"(p), "r"(a), "r"(b), "r"(c), "r"(d) : "memory");
}
#define STA_MOD ""
__device__ __forceinline__ void st_v4a(void* p, uint32_t a, uint32_t b, uint32_t c, uint32_t d) {
  asm volatile("st.global" STA_MOD ".v4.b32 [%0], {%1, %2, %3, %4};" ::"l"(p), "r"(a), "r"(b), "r"(c), "r"(d) : "memory");
}
template <typename T>
__device__ __forceinline__ T* ptr_add(T* base, uint32_t bytes) {
  uint64_t r;
  asm volatile("{\n.reg .u32 l, h;\nmov.b64 {l, h}, %1;\nadd.cc.u32 l, l, %2;\naddc.u32 h, h, 0;\nmov.b64 %0, {l, h};\n}" : "=l"(r) : "l"(base), "r"(bytes));
  return reinterpret_cast<T*>(r);
}
__device__ __forceinline__ float bf_lo(uint32_t v) { return __uint_as_float(v << 16); }
__device__ __forceinline__ float bf_hi(uint32_t v) { return __uint_as_float(v & 0xFFFF0000u); }

__device__ __forceinline__ void quad_transpose(uint32_t& a0, uint32_t& a1, uint32_t& a2, uint32_t& a3, int q) {
  const bool o1 = q & 1, o2 = q & 2;
  uint32_t t0 = o1 ? a0 : a1, t1 = o1 ? a2 : a3;
  t0 = __shfl_xor_sync(0xffffffffu, t0, 1);
  t1 = __shfl_xor_sync(0xffffffffu, t1, 1);
  if (o1) { a0 = t0; a2 = t1; } else { a1 = t0; a3 = t1; }
  t0 = o2 ? a0 : a2;
  t1 = o2 ? a1 : a3;
  t0 = __shfl_xor_sync(0xffffffffu, t0, 2);
  t1 = __shfl_xor_sync(0xffffffffu, t1, 2);
  if (o2) { a0 = t0; a1 = t1; } else { a2 = t0; a3 = t1; }
}

template<int TB, int OFF, int NT>
__device__ __forceinline__ void wgmma_ss_n256(float (&d)[NT], uint64_t da, uint64_t db, int scale_d) {
  asm volatile("{\n.reg .pred p;\nsetp.ne.b32 p, %130, 0;\n"
    "wgmma.mma_async.sync.aligned.m64n256k16.f32.bf16.bf16 {%0, %1, %2, %3, %4, %5, %6, %7, %8, %9, %10, %11, %12, %13, %14, %15, %16, %17, %18, %19, %20, %21, %22, %23, %24, %25, %26, %27, %28, %29, %30, %31, %32, %33, %34, %35, %36, %37, %38, %39, %40, %41, %42, %43, %44, %45, %46, %47, %48, %49, %50, %51, %52, %53, %54, %55, %56, %57, %58, %59, %60, %61, %62, %63, %64, %65, %66, %67, %68, %69, %70, %71, %72, %73, %74, %75, %76, %77, %78, %79, %80, %81, %82, %83, %84, %85, %86, %87, %88, %89, %90, %91, %92, %93, %94, %95, %96, %97, %98, %99, %100, %101, %102, %103, %104, %105, %106, %107, %108, %109, %110, %111, %112, %113, %114, %115, %116, %117, %118, %119, %120, %121, %122, %123, %124, %125, %126, %127}, %128, %129, p, 1, 1, 0, %131;\n}\n"
    : "+f"(d[OFF+0]), "+f"(d[OFF+1]), "+f"(d[OFF+2]), "+f"(d[OFF+3]), "+f"(d[OFF+4]), "+f"(d[OFF+5]), "+f"(d[OFF+6]), "+f"(d[OFF+7]), "+f"(d[OFF+8]), "+f"(d[OFF+9]), "+f"(d[OFF+10]), "+f"(d[OFF+11]), "+f"(d[OFF+12]), "+f"(d[OFF+13]), "+f"(d[OFF+14]), "+f"(d[OFF+15]), "+f"(d[OFF+16]), "+f"(d[OFF+17]), "+f"(d[OFF+18]), "+f"(d[OFF+19]), "+f"(d[OFF+20]), "+f"(d[OFF+21]), "+f"(d[OFF+22]), "+f"(d[OFF+23]), "+f"(d[OFF+24]), "+f"(d[OFF+25]), "+f"(d[OFF+26]), "+f"(d[OFF+27]), "+f"(d[OFF+28]), "+f"(d[OFF+29]), "+f"(d[OFF+30]), "+f"(d[OFF+31]), "+f"(d[OFF+32]), "+f"(d[OFF+33]), "+f"(d[OFF+34]), "+f"(d[OFF+35]), "+f"(d[OFF+36]), "+f"(d[OFF+37]), "+f"(d[OFF+38]), "+f"(d[OFF+39]), "+f"(d[OFF+40]), "+f"(d[OFF+41]), "+f"(d[OFF+42]), "+f"(d[OFF+43]), "+f"(d[OFF+44]), "+f"(d[OFF+45]), "+f"(d[OFF+46]), "+f"(d[OFF+47]), "+f"(d[OFF+48]), "+f"(d[OFF+49]), "+f"(d[OFF+50]), "+f"(d[OFF+51]), "+f"(d[OFF+52]), "+f"(d[OFF+53]), "+f"(d[OFF+54]), "+f"(d[OFF+55]), "+f"(d[OFF+56]), "+f"(d[OFF+57]), "+f"(d[OFF+58]), "+f"(d[OFF+59]), "+f"(d[OFF+60]), "+f"(d[OFF+61]), "+f"(d[OFF+62]), "+f"(d[OFF+63]), "+f"(d[OFF+64]), "+f"(d[OFF+65]), "+f"(d[OFF+66]), "+f"(d[OFF+67]), "+f"(d[OFF+68]), "+f"(d[OFF+69]), "+f"(d[OFF+70]), "+f"(d[OFF+71]), "+f"(d[OFF+72]), "+f"(d[OFF+73]), "+f"(d[OFF+74]), "+f"(d[OFF+75]), "+f"(d[OFF+76]), "+f"(d[OFF+77]), "+f"(d[OFF+78]), "+f"(d[OFF+79]), "+f"(d[OFF+80]), "+f"(d[OFF+81]), "+f"(d[OFF+82]), "+f"(d[OFF+83]), "+f"(d[OFF+84]), "+f"(d[OFF+85]), "+f"(d[OFF+86]), "+f"(d[OFF+87]), "+f"(d[OFF+88]), "+f"(d[OFF+89]), "+f"(d[OFF+90]), "+f"(d[OFF+91]), "+f"(d[OFF+92]), "+f"(d[OFF+93]), "+f"(d[OFF+94]), "+f"(d[OFF+95]), "+f"(d[OFF+96]), "+f"(d[OFF+97]), "+f"(d[OFF+98]), "+f"(d[OFF+99]), "+f"(d[OFF+100]), "+f"(d[OFF+101]), "+f"(d[OFF+102]), "+f"(d[OFF+103]), "+f"(d[OFF+104]), "+f"(d[OFF+105]), "+f"(d[OFF+106]), "+f"(d[OFF+107]), "+f"(d[OFF+108]), "+f"(d[OFF+109]), "+f"(d[OFF+110]), "+f"(d[OFF+111]), "+f"(d[OFF+112]), "+f"(d[OFF+113]), "+f"(d[OFF+114]), "+f"(d[OFF+115]), "+f"(d[OFF+116]), "+f"(d[OFF+117]), "+f"(d[OFF+118]), "+f"(d[OFF+119]), "+f"(d[OFF+120]), "+f"(d[OFF+121]), "+f"(d[OFF+122]), "+f"(d[OFF+123]), "+f"(d[OFF+124]), "+f"(d[OFF+125]), "+f"(d[OFF+126]), "+f"(d[OFF+127])
    : "l"(da), "l"(db), "r"(scale_d), "n"(TB));
}
template<int TB, int OFF, int NT>
__device__ __forceinline__ void wgmma_ss_n32(float (&d)[NT], uint64_t da, uint64_t db, int scale_d) {
  asm volatile("{\n.reg .pred p;\nsetp.ne.b32 p, %18, 0;\n"
    "wgmma.mma_async.sync.aligned.m64n32k16.f32.bf16.bf16 {%0, %1, %2, %3, %4, %5, %6, %7, %8, %9, %10, %11, %12, %13, %14, %15}, %16, %17, p, 1, 1, 0, %19;\n}\n"
    : "+f"(d[OFF+0]), "+f"(d[OFF+1]), "+f"(d[OFF+2]), "+f"(d[OFF+3]), "+f"(d[OFF+4]), "+f"(d[OFF+5]), "+f"(d[OFF+6]), "+f"(d[OFF+7]), "+f"(d[OFF+8]), "+f"(d[OFF+9]), "+f"(d[OFF+10]), "+f"(d[OFF+11]), "+f"(d[OFF+12]), "+f"(d[OFF+13]), "+f"(d[OFF+14]), "+f"(d[OFF+15])
    : "l"(da), "l"(db), "r"(scale_d), "n"(TB));
}
template<int TB, int OFF, int NT>
__device__ __forceinline__ void wgmma_rs_n128(float (&d)[NT], uint32_t a0, uint32_t a1, uint32_t a2, uint32_t a3, uint64_t db, int scale_d) {
  asm volatile("{\n.reg .pred p;\nsetp.ne.b32 p, %69, 0;\n"
    "wgmma.mma_async.sync.aligned.m64n128k16.f32.bf16.bf16 {%0, %1, %2, %3, %4, %5, %6, %7, %8, %9, %10, %11, %12, %13, %14, %15, %16, %17, %18, %19, %20, %21, %22, %23, %24, %25, %26, %27, %28, %29, %30, %31, %32, %33, %34, %35, %36, %37, %38, %39, %40, %41, %42, %43, %44, %45, %46, %47, %48, %49, %50, %51, %52, %53, %54, %55, %56, %57, %58, %59, %60, %61, %62, %63}, {%64, %65, %66, %67}, %68, p, 1, 1, %70;\n}\n"
    : "+f"(d[OFF+0]), "+f"(d[OFF+1]), "+f"(d[OFF+2]), "+f"(d[OFF+3]), "+f"(d[OFF+4]), "+f"(d[OFF+5]), "+f"(d[OFF+6]), "+f"(d[OFF+7]), "+f"(d[OFF+8]), "+f"(d[OFF+9]), "+f"(d[OFF+10]), "+f"(d[OFF+11]), "+f"(d[OFF+12]), "+f"(d[OFF+13]), "+f"(d[OFF+14]), "+f"(d[OFF+15]), "+f"(d[OFF+16]), "+f"(d[OFF+17]), "+f"(d[OFF+18]), "+f"(d[OFF+19]), "+f"(d[OFF+20]), "+f"(d[OFF+21]), "+f"(d[OFF+22]), "+f"(d[OFF+23]), "+f"(d[OFF+24]), "+f"(d[OFF+25]), "+f"(d[OFF+26]), "+f"(d[OFF+27]), "+f"(d[OFF+28]), "+f"(d[OFF+29]), "+f"(d[OFF+30]), "+f"(d[OFF+31]), "+f"(d[OFF+32]), "+f"(d[OFF+33]), "+f"(d[OFF+34]), "+f"(d[OFF+35]), "+f"(d[OFF+36]), "+f"(d[OFF+37]), "+f"(d[OFF+38]), "+f"(d[OFF+39]), "+f"(d[OFF+40]), "+f"(d[OFF+41]), "+f"(d[OFF+42]), "+f"(d[OFF+43]), "+f"(d[OFF+44]), "+f"(d[OFF+45]), "+f"(d[OFF+46]), "+f"(d[OFF+47]), "+f"(d[OFF+48]), "+f"(d[OFF+49]), "+f"(d[OFF+50]), "+f"(d[OFF+51]), "+f"(d[OFF+52]), "+f"(d[OFF+53]), "+f"(d[OFF+54]), "+f"(d[OFF+55]), "+f"(d[OFF+56]), "+f"(d[OFF+57]), "+f"(d[OFF+58]), "+f"(d[OFF+59]), "+f"(d[OFF+60]), "+f"(d[OFF+61]), "+f"(d[OFF+62]), "+f"(d[OFF+63])
    : "r"(a0), "r"(a1), "r"(a2), "r"(a3), "l"(db), "r"(scale_d), "n"(TB));
}
template<int TB, int OFF, int NT>
__device__ __forceinline__ void wgmma_rs_n256(float (&d)[NT], uint32_t a0, uint32_t a1, uint32_t a2, uint32_t a3, uint64_t db, int scale_d) {
  asm volatile("{\n.reg .pred p;\nsetp.ne.b32 p, %133, 0;\n"
    "wgmma.mma_async.sync.aligned.m64n256k16.f32.bf16.bf16 {%0, %1, %2, %3, %4, %5, %6, %7, %8, %9, %10, %11, %12, %13, %14, %15, %16, %17, %18, %19, %20, %21, %22, %23, %24, %25, %26, %27, %28, %29, %30, %31, %32, %33, %34, %35, %36, %37, %38, %39, %40, %41, %42, %43, %44, %45, %46, %47, %48, %49, %50, %51, %52, %53, %54, %55, %56, %57, %58, %59, %60, %61, %62, %63, %64, %65, %66, %67, %68, %69, %70, %71, %72, %73, %74, %75, %76, %77, %78, %79, %80, %81, %82, %83, %84, %85, %86, %87, %88, %89, %90, %91, %92, %93, %94, %95, %96, %97, %98, %99, %100, %101, %102, %103, %104, %105, %106, %107, %108, %109, %110, %111, %112, %113, %114, %115, %116, %117, %118, %119, %120, %121, %122, %123, %124, %125, %126, %127}, {%128, %129, %130, %131}, %132, p, 1, 1, %134;\n}\n"
    : "+f"(d[OFF+0]), "+f"(d[OFF+1]), "+f"(d[OFF+2]), "+f"(d[OFF+3]), "+f"(d[OFF+4]), "+f"(d[OFF+5]), "+f"(d[OFF+6]), "+f"(d[OFF+7]), "+f"(d[OFF+8]), "+f"(d[OFF+9]), "+f"(d[OFF+10]), "+f"(d[OFF+11]), "+f"(d[OFF+12]), "+f"(d[OFF+13]), "+f"(d[OFF+14]), "+f"(d[OFF+15]), "+f"(d[OFF+16]), "+f"(d[OFF+17]), "+f"(d[OFF+18]), "+f"(d[OFF+19]), "+f"(d[OFF+20]), "+f"(d[OFF+21]), "+f"(d[OFF+22]), "+f"(d[OFF+23]), "+f"(d[OFF+24]), "+f"(d[OFF+25]), "+f"(d[OFF+26]), "+f"(d[OFF+27]), "+f"(d[OFF+28]), "+f"(d[OFF+29]), "+f"(d[OFF+30]), "+f"(d[OFF+31]), "+f"(d[OFF+32]), "+f"(d[OFF+33]), "+f"(d[OFF+34]), "+f"(d[OFF+35]), "+f"(d[OFF+36]), "+f"(d[OFF+37]), "+f"(d[OFF+38]), "+f"(d[OFF+39]), "+f"(d[OFF+40]), "+f"(d[OFF+41]), "+f"(d[OFF+42]), "+f"(d[OFF+43]), "+f"(d[OFF+44]), "+f"(d[OFF+45]), "+f"(d[OFF+46]), "+f"(d[OFF+47]), "+f"(d[OFF+48]), "+f"(d[OFF+49]), "+f"(d[OFF+50]), "+f"(d[OFF+51]), "+f"(d[OFF+52]), "+f"(d[OFF+53]), "+f"(d[OFF+54]), "+f"(d[OFF+55]), "+f"(d[OFF+56]), "+f"(d[OFF+57]), "+f"(d[OFF+58]), "+f"(d[OFF+59]), "+f"(d[OFF+60]), "+f"(d[OFF+61]), "+f"(d[OFF+62]), "+f"(d[OFF+63]), "+f"(d[OFF+64]), "+f"(d[OFF+65]), "+f"(d[OFF+66]), "+f"(d[OFF+67]), "+f"(d[OFF+68]), "+f"(d[OFF+69]), "+f"(d[OFF+70]), "+f"(d[OFF+71]), "+f"(d[OFF+72]), "+f"(d[OFF+73]), "+f"(d[OFF+74]), "+f"(d[OFF+75]), "+f"(d[OFF+76]), "+f"(d[OFF+77]), "+f"(d[OFF+78]), "+f"(d[OFF+79]), "+f"(d[OFF+80]), "+f"(d[OFF+81]), "+f"(d[OFF+82]), "+f"(d[OFF+83]), "+f"(d[OFF+84]), "+f"(d[OFF+85]), "+f"(d[OFF+86]), "+f"(d[OFF+87]), "+f"(d[OFF+88]), "+f"(d[OFF+89]), "+f"(d[OFF+90]), "+f"(d[OFF+91]), "+f"(d[OFF+92]), "+f"(d[OFF+93]), "+f"(d[OFF+94]), "+f"(d[OFF+95]), "+f"(d[OFF+96]), "+f"(d[OFF+97]), "+f"(d[OFF+98]), "+f"(d[OFF+99]), "+f"(d[OFF+100]), "+f"(d[OFF+101]), "+f"(d[OFF+102]), "+f"(d[OFF+103]), "+f"(d[OFF+104]), "+f"(d[OFF+105]), "+f"(d[OFF+106]), "+f"(d[OFF+107]), "+f"(d[OFF+108]), "+f"(d[OFF+109]), "+f"(d[OFF+110]), "+f"(d[OFF+111]), "+f"(d[OFF+112]), "+f"(d[OFF+113]), "+f"(d[OFF+114]), "+f"(d[OFF+115]), "+f"(d[OFF+116]), "+f"(d[OFF+117]), "+f"(d[OFF+118]), "+f"(d[OFF+119]), "+f"(d[OFF+120]), "+f"(d[OFF+121]), "+f"(d[OFF+122]), "+f"(d[OFF+123]), "+f"(d[OFF+124]), "+f"(d[OFF+125]), "+f"(d[OFF+126]), "+f"(d[OFF+127])
    : "r"(a0), "r"(a1), "r"(a2), "r"(a3), "l"(db), "r"(scale_d), "n"(TB));
}
template<int TB, int OFF, int NT>
__device__ __forceinline__ void wgmma_rs_n32(float (&d)[NT], uint32_t a0, uint32_t a1, uint32_t a2, uint32_t a3, uint64_t db, int scale_d) {
  asm volatile("{\n.reg .pred p;\nsetp.ne.b32 p, %21, 0;\n"
    "wgmma.mma_async.sync.aligned.m64n32k16.f32.bf16.bf16 {%0, %1, %2, %3, %4, %5, %6, %7, %8, %9, %10, %11, %12, %13, %14, %15}, {%16, %17, %18, %19}, %20, p, 1, 1, %22;\n}\n"
    : "+f"(d[OFF+0]), "+f"(d[OFF+1]), "+f"(d[OFF+2]), "+f"(d[OFF+3]), "+f"(d[OFF+4]), "+f"(d[OFF+5]), "+f"(d[OFF+6]), "+f"(d[OFF+7]), "+f"(d[OFF+8]), "+f"(d[OFF+9]), "+f"(d[OFF+10]), "+f"(d[OFF+11]), "+f"(d[OFF+12]), "+f"(d[OFF+13]), "+f"(d[OFF+14]), "+f"(d[OFF+15])
    : "r"(a0), "r"(a1), "r"(a2), "r"(a3), "l"(db), "r"(scale_d), "n"(TB));
}

__device__ __forceinline__ void wait_flag(const unsigned int* f, uint32_t target) {
  uint32_t v;
#pragma unroll 1
  for (uint32_t spins = 0; spins < (1u << 22); spins++) {
    asm volatile("ld.acquire.gpu.global.u32 %0, [%1];" : "=r"(v) : "l"(f) : "memory");
    if (v >= target) break;
    __nanosleep(100);
  }
}
__device__ __forceinline__ uint32_t ld_and2(const unsigned int* f) {
  uint32_t v;
  asm volatile("{\n.reg .b64 t;\n.reg .b32 a, b;\nld.acquire.gpu.global.b64 t, [%1];\nmov.b64 {a, b}, t;\nand.b32 %0, a, b;\n}" : "=r"(v) : "l"(f) : "memory");
  return v;
}
__device__ __forceinline__ uint32_t lds32(uint32_t a) {
  uint32_t v;
  asm volatile("ld.shared.u32 %0, [%1];" : "=r"(v) : "r"(a) : "memory");
  return v;
}
__device__ __forceinline__ float gate_row(int row, int lane, const bf16* __restrict__ x, const bf16* __restrict__ gate_w) {
  const uint32_t* xr = reinterpret_cast<const uint32_t*>(x + (size_t)row * DM);
  const uint32_t* gw2 = reinterpret_cast<const uint32_t*>(gate_w);
  float gs = 0.f;
#pragma unroll
  for (int i = 0; i < 9; i++) {
    const uint32_t a = __ldg(xr + lane + 32 * i), b = __ldg(gw2 + lane + 32 * i);
    gs = fmaf(bf_lo(a), bf_lo(b), gs);
    gs = fmaf(bf_hi(a), bf_hi(b), gs);
  }
#pragma unroll
  for (int o = 16; o; o >>= 1) gs += __shfl_xor_sync(0xffffffffu, gs, o);
  const float g = 1.f / (1.f + __expf(-gs));
  if (lane == 0) g_gate[row] = g;
  return g;
}
constexpr uint32_t LQ = 36864, LV = 55296;
constexpr uint32_t LO = LV + 18432;
__device__ __forceinline__ void mma16(float (&c)[4], uint32_t a0, uint32_t a1, uint32_t a2, uint32_t a3, uint32_t b0, uint32_t b1) {
  asm("mma.sync.aligned.m16n8k16.row.col.f32.bf16.bf16.f32 {%0, %1, %2, %3}, {%4, %5, %6, %7}, {%8, %9}, {%0, %1, %2, %3};"
      : "+f"(c[0]), "+f"(c[1]), "+f"(c[2]), "+f"(c[3]) : "r"(a0), "r"(a1), "r"(a2), "r"(a3), "r"(b0), "r"(b1));
}
__device__ __forceinline__ void mma8(float (&c)[4], uint32_t a0, uint32_t a1, uint32_t b0) {
  asm("mma.sync.aligned.m16n8k8.row.col.f32.bf16.bf16.f32 {%0, %1, %2, %3}, {%4, %5}, {%6}, {%0, %1, %2, %3};"
      : "+f"(c[0]), "+f"(c[1]), "+f"(c[2]), "+f"(c[3]) : "r"(a0), "r"(a1), "r"(b0));
}
template <typename F>
__device__ __forceinline__ void local_attn(int lr0, int warp_g, uint32_t sL, uint32_t bL, uint32_t bL2, int lane, float g0, float g1, F st) {
  const float scale_l2 = 0.23570226039551584f * 1.4426950408889634f;
  const int g = lane >> 2, t = lane & 3;
  const bool lo0 = 2 * t > g, lo1 = 2 * t + 1 > g;
  const bool ok0 = lr0 > 0 || !lo0, ok1 = lr0 > 0 || !lo1;
  const uint32_t mlo = (lo0 ? 0xFFFFu : 0u) | (lo1 ? 0xFFFF0000u : 0u);
  uint32_t ad[9], k[9][4], qf[9][2], pe[4], po[4];
#pragma unroll
  for (int c = 0; c < 9; c++) {
    const uint32_t ch = warp_g * 9 + c;
    ad[c] = sL + (lane >> 4) * 18432 + (lane & 15) * 128 + ((ch >> 3) << 11) + (((ch ^ lane) & 7) << 4);
  }
  st(0, 0u); st(1, 0u);
  mbar_wait(bL, 0);
  if (warp_g == 0) TS(1, 6);
#pragma unroll
  for (int c = 0; c < 9; c++) {
    asm volatile("ldmatrix.sync.aligned.m8n8.x2.shared.b16 {%0, %1}, [%2];" : "=r"(qf[c][0]), "=r"(qf[c][1]) : "r"(ad[c] + LQ) : "memory");
    ldsm_x4(k[c][0], k[c][1], k[c][2], k[c][3], ad[c]);
  }
  st(2, k[0][0]); st(3, k[8][0]);
#pragma unroll
  for (int i = 0; i < 4; i++) {
    const uint32_t q0 = (t >= i) ? qf[2 * i][0] : 0u, q1 = (t >= i) ? qf[2 * i][1] : 0u;
    const uint32_t q4 = (t <= i) ? qf[2 * i + 2][0] : 0u, q5 = (t <= i) ? qf[2 * i + 2][1] : 0u;
    float c[4][4];
#pragma unroll
    for (int T = 0; T < 4; T++) {
#pragma unroll
      for (int j = 0; j < 4; j++) c[T][j] = 0.f;
      mma16(c[T], q0, q1, qf[2 * i + 1][0], qf[2 * i + 1][1], k[2 * i][T], k[2 * i + 1][T]);
      mma8(c[T], q4, q5, k[2 * i + 2][T]);
    }
    const float e0 = ok0 ? (lo0 ? c[0][0] : c[1][0]) : -INFINITY, e1 = ok1 ? (lo1 ? c[0][1] : c[1][1]) : -INFINITY;
    const float o0 = ok0 ? (lo0 ? c[2][2] : c[3][2]) : -INFINITY, o1 = ok1 ? (lo1 ? c[2][3] : c[3][3]) : -INFINITY;
    float me = fmaxf(e0, e1), mo = fmaxf(o0, o1);
    me = fmaxf(me, __shfl_xor_sync(0xffffffffu, me, 1));
    mo = fmaxf(mo, __shfl_xor_sync(0xffffffffu, mo, 1));
    me = fmaxf(me, __shfl_xor_sync(0xffffffffu, me, 2)) * scale_l2;
    mo = fmaxf(mo, __shfl_xor_sync(0xffffffffu, mo, 2)) * scale_l2;
    const float w0 = ex2(fmaf(e0, scale_l2, -me)), w1 = ex2(fmaf(e1, scale_l2, -me));
    const float w2 = ex2(fmaf(o0, scale_l2, -mo)), w3 = ex2(fmaf(o1, scale_l2, -mo));
    float se = w0 + w1, so = w2 + w3;
    st(4 + 2 * i, __float_as_uint(i == 1 ? me : i == 2 ? se : e0));
    se += __shfl_xor_sync(0xffffffffu, se, 1);
    so += __shfl_xor_sync(0xffffffffu, so, 1);
    se += __shfl_xor_sync(0xffffffffu, se, 2);
    so += __shfl_xor_sync(0xffffffffu, so, 2);
    asm("rcp.approx.ftz.f32 %0, %0;" : "+f"(se));
    asm("rcp.approx.ftz.f32 %0, %0;" : "+f"(so));
    se *= g0;
    so *= g1;
    pe[i] = pack_bf16(w0 * se, w1 * se);
    po[i] = pack_bf16(w2 * so, w3 * so);
    st(5 + 2 * i, i == 0 ? __float_as_uint(w0) : i == 2 ? __float_as_uint(mo) : po[i]);
  }
  if (warp_g == 0) TS(0, 4);
  mbar_wait(bL2, 0);
  if (warp_g == 0) TS(0, 5);
#pragma unroll
  for (int c = 0; c < 9; c++)
    asm volatile("ldmatrix.sync.aligned.m8n8.x4.trans.shared.b16 {%0, %1, %2, %3}, [%4];"
                 : "=r"(k[c][0]), "=r"(k[c][1]), "=r"(k[c][2]), "=r"(k[c][3]) : "r"(ad[c] + LV) : "memory");
  mbar_arrive_if(bL + 8, lane == (k[8][3] & blockIdx.y));
#pragma unroll
  for (int i = 0; i < 4; i++) {
#pragma unroll
    for (int n = 0; n < 3; n++) {
      float c[4] = {0.f, 0.f, 0.f, 0.f};
      mma16(c, pe[i] & mlo, 0u, pe[i] & ~mlo, 0u, k[2 * i + n][0], k[2 * i + n][1]);
      mma16(c, 0u, po[i] & mlo, 0u, po[i] & ~mlo, k[2 * i + n][2], k[2 * i + n][3]);
      const uint32_t r0 = pack_bf16(c[0], c[1]), r1 = pack_bf16(c[2], c[3]);
      const bool keep = (n == 0) && (i > 0) && (t < i);
      qf[2 * i + n][0] = keep ? qf[2 * i + n][0] : r0;
      qf[2 * i + n][1] = keep ? qf[2 * i + n][1] : r1;
    }
    st(12 + i, qf[2 * i + 1][0]);
  }
#pragma unroll
  for (int c = 0; c < 9; c++)
    asm volatile("stmatrix.sync.aligned.m8n8.x2.shared.b16 [%0], {%1, %2};" ::"r"(ad[c] + LO), "r"(qf[c][0]), "r"(qf[c][1]) : "memory");
  asm volatile("fence.proxy.async.shared::cta;" ::: "memory");
}
__device__ __forceinline__ void tma4d(uint32_t dst, const CUtensorMap* m, uint32_t bar, int c1, int c2, int c3) {
  asm volatile("cp.async.bulk.tensor.4d.shared::cluster.global.mbarrier::complete_tx::bytes [%0], [%1, {%3, %4, %5, %6}], [%2];" ::"r"(dst),
               "l"(m), "r"(bar), "r"(0), "r"(c1), "r"(c2), "r"(c3) : "memory");
}

#define ST_NUM 1
#define ST_DEN 2
#define ALEAD 3
#define K1_NST 6
constexpr int K1_BST = K1_NST;
#define MAXJ 10
constexpr int K1_MAXJOBS = MAXJ;
constexpr uint32_t K1_FLAG_TARGET = 7;
constexpr uint32_t RDY_TARGET = 48;
constexpr uint32_t GATE_TARGET = 128 * 3;
struct alignas(64) Params {
  CUtensorMap tmA[2];
  CUtensorMap tmW[4];
  uint16_t jobs[NCLUSTER][K1_MAXJOBS + 1];
  CUtensorMap tmK, tmV, tmQ;
  CUtensorMap tmL[3];
  CUtensorMap tmC, tmO[2], tmOt[2];
  CUtensorMap tmR[2];
  uint8_t order[256];
  uint8_t unit[66][4];
};

struct K1State {
  uint32_t bs, bph, aph;
  bf16* pp;
  int png;
  int tn;
  int wsel;
  uint32_t fo;
};
__device__ __forceinline__ void k1_flag(const K1State& st, int lane, uint32_t bS) {
  if (st.png) {
    __syncwarp();
    if (lane == 0) mbar_arrive(bS + st.fo);
  }
}

__device__ __forceinline__ void scale_q4(uint32_t* v) {
#pragma unroll
  for (int i = 0; i < 4; i++)
    asm volatile("{\n.reg .b32 t;\nmul.rn.bf16x2 t, %0, %2;\nfma.rn.bf16x2 %0, %0, %1, t;\n}" : "+r"(v[i]) : "r"(0x3E033E03u), "r"(0xB9D8B9D8u));
}
__device__ __forceinline__ void k1_first(const K1State& st, uint32_t job, uint32_t bAf, uint32_t bBf) {
  if (job & 3) {
    if ((job >> 14) & 1) mbar_wait(bAf, st.aph);
    mbar_wait(bBf + st.bs * 8, st.bph);
  }
}
__device__ __forceinline__ void k1_tile(float (&acc)[128], uint32_t (&pk)[64], K1State& st, uint32_t job, uint32_t njob, uint32_t sA, uint32_t sB,
                                        uint32_t bAf, uint32_t bAe, uint32_t bBf, uint32_t bBe, uint32_t bS, int wg, int warp, int lane, uint32_t rank) {
  const int a_sel = (job >> 2) & 1, mpair = (job >> 3) & 7, w_sel = (job >> 6) & 3, chunk0 = (job >> 8) & 63;
  const bool newA = (job >> 14) & 1, lastA = (job >> 15) & 1;
  const bool sig = (lane == 0) && (warp < 2);
  const bool siga = lastA && (lane == 0) && (warp == 2);
  const int KC = 8 + a_sel;
  uint32_t prev_bs = 0, a8_bs = 0;
#pragma unroll
  for (int kc = 0; kc < 9; kc++) {
    if (kc >= KC) break;
    uint32_t abase = sA + ((kc + 2) & 7) * 16384;
    if (kc == 8) {
      mbar_wait(bBf + st.bs * 8, st.bph);
      a8_bs = st.bs;
      abase = sB + st.bs * 16384;
      if (++st.bs == K1_BST) { st.bs = 0; st.bph ^= 1; }
    } else if (newA && kc > 0) {
      mbar_wait(bAf + kc * 8, st.aph);
    }
    const uint64_t da = make_desc(abase + wg * 8192, 16, 1024, 1);
#pragma unroll
    for (int ks = 0; ks < 2; ks++) {
      if (ks > 0 || kc > 0) mbar_wait(bBf + st.bs * 8, st.bph);
      const uint64_t db = make_desc(sB + st.bs * 16384, 2048, 1024, 1);
      if (kc * 2 + ks == 16 - ALEAD && !a_sel && wg == 1) bar_sync(4, 256);
      wg_fence();
      wgmma_ss_n256<1, 0>(acc, da + (uint64_t)(ks * 4), db, (ks > 0) ? 1 : (kc > 0));
      wgmma_ss_n256<1, 0>(acc, da + (uint64_t)(ks * 4 + 2), db + (uint64_t)512, 1);
      wg_commit();
      if (kc == 7 && ks == 1 && !a_sel && wg == 0) bar_arrive(4, 256);
      wg_wait<1>();
      if (ks > 0 || kc > 0) {
        if (sig) mbar_arrive_cluster(bBe + prev_bs * 8, warp);
        if (ks == 0 && siga) mbar_arrive(bAe + (kc - 1) * 8);
      }
      if (st.wsel == 2) {
        const int i = (kc & 7) * 2 + ks;
        if (kc < st.png) {
          quad_transpose(pk[i * 4], pk[i * 4 + 1], pk[i * 4 + 2], pk[i * 4 + 3], lane & 3);
          st_v4a(st.pp + goff(kc, ks), pk[i * 4], pk[i * 4 + 1], pk[i * 4 + 2], pk[i * 4 + 3]);
        }
        if (i == 15) k1_flag(st, lane, bS);
      } else if (st.png) {
#pragma unroll
        for (int i = 0; i < 16; i++) {
          if (i * ST_NUM / ST_DEN != kc * 2 + ks) continue;
          if (st.wsel == 3) scale_q4(pk + i * 4);
          st_v4a(st.pp + goff(i / 2, i & 1), pk[i * 4], pk[i * 4 + 1], pk[i * 4 + 2], pk[i * 4 + 3]);
          if (i == 15) k1_flag(st, lane, bS);
        }
      }
      prev_bs = st.bs;
      if (++st.bs == K1_BST) { st.bs = 0; st.bph ^= 1; }
    }
  }
  if (newA) st.aph ^= 1;
  const bool isA = (w_sel == 2);
  bf16* out = (w_sel == 0) ? g_K : (w_sel == 1) ? g_V : isA ? g_QKVA : g_ctx;
  const int row = mpair * 256 + rank * 128 + wg * 64 + warp * 16 + (lane >> 2);
  st.pp = ptr_add(out, (chunk0 * S_LEN + row) * 128 + (lane & 3) * 16);
  st.png = ((job & 3) + 1) * 2;
  st.wsel = w_sel;
  st.fo = (st.fo + 8) & 24;
  k1_first(st, njob, bAf, bBf);
  wg_wait<0>();
  fence_regs(acc);
  mbar_arrive_cluster_if(bBe + prev_bs * 8, warp & 1, sig);
  mbar_arrive_cluster_if(bBe + a8_bs * 8, warp & 1, sig && a_sel);
  mbar_arrive_if(bAe + 7 * 8, siga && !a_sel);
#pragma unroll
  for (int i = 0; i < 64; i++) {
    const int j = (i >> 3) * 16 + (i & 3) * 4 + ((i >> 2) & 1) * 2;
    pk[i] = pack_bf16(acc[j], acc[j + 1]);
  }
}

constexpr int K2_NST = 7;
constexpr uint32_t K2_END = 0x100;
#define PFD 4
#define PF3A 2
#define PF3 6
#define KC0 1
constexpr uint32_t CR = 4;
#define FIRST_DRAW 3
#define PWAIT mbar_wait_ns<1000>
#define PVM 0x8A
#define W0 63
#define SPEC_HI 1.8446744073709552e19f
#define SPEC_LO 5.421010862427522e-20f
constexpr int K3_NST = 4;
#define K3_NS 6
__device__ __forceinline__ uint32_t k3_rot(uint32_t sv) { return (0x00E9u >> (2 * sv)) & 3; }
constexpr int K3_STAGE = 16384 + 32768 + 4096;
constexpr int SMEM_DATA = 7 * 32768;
constexpr int SMEM_BYTES = SMEM_DATA + 1024 + 896;

struct Cursor {
  uint32_t s, ph;
  __device__ __forceinline__ void next() {
    if (++s == K2_NST) { s = 0; ph ^= 1; }
  }
};

#define TURN_SYNC() bar_sync(mybar, 256)
#define TURN_ARRIVE() bar_arrive(otherbar, 256)
#define RELEASE_IF(cur, cond) mbar_arrive_cluster_if(bE + (cur).s * 8, warp & 1, sig && (cond))
#define RELEASE(cur) RELEASE_IF(cur, true)
#define ISSUE_PV(cur, first)                                                                                   \
  do {                                                                                                         \
    const uint64_t dv = make_desc(sbase + (cur).s * 32768, 16384, 1024, 1);                                    \
    _Pragma("unroll") for (int t = 0; t < 8; t++)                                                              \
        wgmma_rs_n128<1, 0>(O, P[4 * t], P[4 * t + 1], P[4 * t + 2], P[4 * t + 3], dv + (uint64_t)(t * 128), (t > 0) ? 1 : !(first)); \
  } while (0)
#define ISSUE_QK(cur)                                                                                          \
  do {                                                                                                         \
    const uint64_t dk = make_desc(sbase + (cur).s * 32768, 16, 1024, 1);                                       \
    _Pragma("unroll") for (int t = 0; t < 8; t++)                                                              \
        wgmma_rs_n128<0, 0>(S, Q[4 * t], Q[4 * t + 1], Q[4 * t + 2], Q[4 * t + 3], dk + (uint64_t)((t >> 2) * 1024 + (t & 3) * 2), t > 0); \
  } while (0)
#define LOAD_Q()                                                                                               \
  do {                                                                                                         \
    item = lds32(sItem + (it & 7) * 4);                                                                        \
    const uint32_t qa = sbase + cq.s * 32768 + (wg * 64 + warp * 16 + (lane & 15)) * 128;                      \
    _Pragma("unroll") for (int t = 0; t < 8; t++)                                                              \
        ldsm_x4(Q[4 * t], Q[4 * t + 1], Q[4 * t + 2], Q[4 * t + 3], qa + (t >> 2) * 16384 + ((((t & 3) * 2 + (lane >> 4)) ^ (lane & 7)) << 4)); \
  } while (0)
#define NEW_ITEM()                                                                                             \
  do {                                                                                                         \
    const int row = (2 * (item & 7) + hi) * 128 + (rank ^ hi) * 64 + warp * 16 + (lane >> 2);                  \
    eoff = ((item >> 3) * 2 * S_LEN + row) * 128 + q * 16;                                                     \
    const float* gp = ptr_add(g_gate, row * 4);                                                                \
    asm volatile("ld.global.f32 %0, [%1];" : "=f"(gf0) : "l"(gp));                                             \
    asm volatile("ld.global.f32 %0, [%1];" : "=f"(gf1) : "l"(gp + 8));                                         \
    if (!hi) {                                                                                                 \
      mbar_wait2(bF + cs0.s * 8, cs0.ph, bF + cs1.s * 8, cs1.ph);                                              \
      RELEASE(cs0);                                                                                            \
      RELEASE(cs1);                                                                                            \
    }                                                                                                          \
  } while (0)
#define EXPB(T)                                                                                                \
  do {                                                                                                         \
    _Pragma("unroll") for (int i = 4 * T; i < 4 * T + 4; i++) asm volatile("" : "+r"(P[i])::"memory");        \
    _Pragma("unroll") for (int jj = 2 * T; jj < 2 * T + 2; jj++) {                                             \
      const float e0 = ex2(S[jj * 4 + 0]), e1 = ex2(S[jj * 4 + 1]), e2 = ex2(S[jj * 4 + 2]), e3 = ex2(S[jj * 4 + 3]); \
      s0 += e0 + e1;                                                                                           \
      s1 += e2 + e3;                                                                                           \
      P[jj * 2 + 0] = pack_bf16(e0, e1);                                                                       \
      P[jj * 2 + 1] = pack_bf16(e2, e3);                                                                       \
    }                                                                                                          \
  } while (0)
#define EXPC(T)                                                                                                \
  do {                                                                                                         \
    if (T > 0 && ((PVM >> (T - 1)) & 1)) {                                                                     \
      anchor((T & 2) ? s0 : s1, never);                                                                        \
      wg_wait<__builtin_popcount(PVM >> T) - 1>();                                                             \
      if ((PVM >> T) == (128 >> T)) { fence_regs(O); RELEASE(cv); }                                            \
    }                                                                                                          \
    EXPB(T);                                                                                                   \
  } while (0)
#define MASK(G, g)                                                                                             \
  do {                                                                                                         \
    if ((g) * 8 > d) S[(G) * 4 + 0] = -INFINITY;                                                               \
    if ((g) * 8 + 1 > d) S[(G) * 4 + 1] = -INFINITY;                                                           \
    if ((g) * 8 - 8 > d) S[(G) * 4 + 2] = -INFINITY;                                                           \
    if ((g) * 8 - 7 > d) S[(G) * 4 + 3] = -INFINITY;                                                           \
  } while (0)
#define STORE_O(G)                                                                                             \
  do {                                                                                                         \
    st_v4(optr + goff(G, 0), pack_bf16(O[(G) * 16 + 0] * f0, O[(G) * 16 + 1] * f0), pack_bf16(O[(G) * 16 + 4] * f0, O[(G) * 16 + 5] * f0), \
          pack_bf16(O[(G) * 16 + 8] * f0, O[(G) * 16 + 9] * f0), pack_bf16(O[(G) * 16 + 12] * f0, O[(G) * 16 + 13] * f0)); \
    st_v4(optr + goff(G, 1), pack_bf16(O[(G) * 16 + 2] * f1, O[(G) * 16 + 3] * f1), pack_bf16(O[(G) * 16 + 6] * f1, O[(G) * 16 + 7] * f1), \
          pack_bf16(O[(G) * 16 + 10] * f1, O[(G) * 16 + 11] * f1), pack_bf16(O[(G) * 16 + 14] * f1, O[(G) * 16 + 15] * f1)); \
  } while (0)

#define FLUSH()                                                                                                \
  do {                                                                                                         \
    _Pragma("unroll") for (int G = 0; G < 8; G++) {                                                            \
      st_v4a(st.pp + goff(G, 0), pk[G * 8], pk[G * 8 + 1], pk[G * 8 + 2], pk[G * 8 + 3]);                          \
      st_v4a(st.pp + goff(G, 1), pk[G * 8 + 4], pk[G * 8 + 5], pk[G * 8 + 6], pk[G * 8 + 7]);                     \
    }                                                                                                          \
    k1_flag(st, lane, bS);                                                                                     \
  } while (0)

__global__ void __cluster_dims__(2, 1, 1) __launch_bounds__(384, 1)
fused_kernel(const __grid_constant__ Params p, const bf16* __restrict__ x, const bf16* __restrict__ gate_w, bf16* __restrict__ out) {
  extern __shared__ uint8_t smem_raw[];
  const uint32_t sbase = (smem_u32(smem_raw) + 1023) & ~1023u;
  const uint32_t sB = sbase, sA = sbase + K1_BST * 16384, sBar = sbase + SMEM_DATA;
  const uint32_t bAf = sBar, bAe = sBar + 64, bBf = sBar + 128, bBe = sBar + 176, bL = sBar + 224, bS = sBar + 656, bL2 = sBar + 240, sL = sA + 32768;
  const uint32_t bF = sBar + 256, bE = sBar + 320, bT = sBar + 384, sTick = sBar + 400, sItem = sBar + 416, bS2 = sBar + 688, bR = sBar + 456, bLast = sBar + 464, bH = sBar + 472, bT0 = sBar + 480, bZ = sBar + 488, bLd = sBar + 496, bG = sBar + 504;
  const uint32_t b3F = sBar + 512, b3E = sBar + 544, sGate = sBar + 576, sK1 = sBar + 720, sClm = sBar + 768;
  const int tid = threadIdx.x, warp_g = __shfl_sync(0xffffffffu, tid >> 5, 0), lane = tid & 31;
  const uint32_t rank = cluster_rank();
  const int cl = blockIdx.x >> 1;
  TSM(0);
  if (tid == 256) {
    const uint32_t job = p.jobs[cl][0];
#pragma unroll
    for (int i = 0; i < KC0; i++) { mbar_init(bAf + i * 8, 1); mbar_init(bBf + i * 16, 1); mbar_init(bBf + i * 16 + 8, 1); }
    asm volatile("fence.mbarrier_init.release.cluster;" ::: "memory");
#pragma unroll 1
    for (int i = 0; i < 4 * KC0; i++) {
      if (!(i & 3)) {
        mbar_expect(bAf + i * 2, 16384);
        tma2d(sA + (i / 4 + 2) * 16384, &p.tmA[(job >> 2) & 1], bAf + i * 2, i * 16, ((job >> 3) & 7) * 256 + rank * 128);
      }
      if (!(i & 1)) mbar_expect(bBf + i * 4, 16384);
      tma3d(sB + i * 8192, &p.tmW[(job >> 6) & 3], bBf + (i >> 1) * 8, 0, i * 16, (job >> 8) & 63);
    }
  }
  if (warp_g == 1) asm volatile("st.shared.u32 [%0], %1;" ::"r"(lane ? sClm - 4 + lane * 4 : sK1), "r"(lane ? 0xFFFFFFFFu : 80u) : "memory");
  if (tid == 0) {
    for (int i = 0; i < 8; i++) { if (i >= KC0) mbar_init(bAf + i * 8, 1); mbar_init(bAe + i * 8, 2); }
    for (int i = 0; i < K1_BST; i++) { if (i >= 2 * KC0) mbar_init(bBf + i * 8, 1); mbar_init(bBe + i * 8, 4); }
    mbar_init(bL, 1);
    mbar_init(bL2, 1);
    mbar_init(bL + 8, 8);
    mbar_init(bR, 1);
    mbar_init(bLast, 1);
    mbar_init(bH, 4);
    mbar_init(bT0, 1);
    mbar_init(bZ, 1);
    mbar_init(bLd, 4);
    mbar_init(bG, 3);
    for (int i = 0; i < 8; i++) mbar_init(bS + i * 8, 8);
    for (int i = 0; i < K2_NST; i++) { mbar_init(bF + i * 8, 1); mbar_init(bE + i * 8, 4); }
    mbar_init(bT, 1); mbar_init(bT + 8, 1);
    for (int i = 0; i < K3_NST; i++) { mbar_init(b3F + i * 8, 1); mbar_init(b3E + i * 8, 4); }
    asm volatile("fence.mbarrier_init.release.cluster;" ::: "memory");
  }
  __syncwarp();
  if (warp_g != 8) cluster_sync();
  const int lr0 = blockIdx.x * 16;

  if (warp_g >= 8) {
    reg_dealloc<40>();
    if (warp_g == 8) {
      {
        __syncwarp();
        cluster_sync();
      }
      if (elect_one()) {
        uint32_t bs = (2 * KC0) % K1_BST, bph = (2 * KC0 < K1_BST), aph = 1;
#pragma unroll 1
        for (int ji = 0; ji < K1_MAXJOBS; ji++) {
          const uint32_t job = p.jobs[cl][ji];
          if (!(job & 3)) break;
          const int a_sel = (job >> 2) & 1, mpair = (job >> 3) & 7, chunk0 = (job >> 8) & 63;
          const bool newA = (job >> 14) & 1;
          const int KC = a_sel ? 9 : 8;
          const uint32_t halfbytes = 8192;
          const bool lastjob = (ji + 1 == K1_MAXJOBS) || !(p.jobs[cl][ji + 1] & 3);
          const CUtensorMap* tw = &p.tmW[(job >> 6) & 3];
          {
            const uint32_t njob = (ji + 1 < K1_MAXJOBS) ? p.jobs[cl][ji + 1] : 0;
            if (!(njob & 3) && !newA) mbar_arrive(bLast);
          }
#pragma unroll 1
          for (int kc = ji ? 0 : KC0; kc < KC; kc++) {
            {
              const bool nx = kc + PFD >= KC;
              const uint32_t njob = nx ? p.jobs[cl][ji + 1] : job;
              const int pk = nx ? kc + PFD - KC : kc + PFD;
              if ((njob & 3) && (nx || ji > 0)) {
                if (cl >= 64 || ((pk ^ (cl >> 1)) & 3) == 0)
                  tma_pf3d(&p.tmW[(njob >> 6) & 3], 0, pk * 64 + (cl & 1) * 32 + rank * 16, (njob >> 8) & 63);
                if (((njob >> 14) & 1) || pk == 8) tma_pf2d(&p.tmA[(njob >> 2) & 1], pk * 64, ((njob >> 3) & 7) * 256 + rank * 128);
              }
            }
            if (kc == 8) {
              PWAIT(bBe + bs * 8, bph);
              mbar_expect(bBf + bs * 8, 16384);
              tma2d(sB + bs * 16384, &p.tmA[1], bBf + bs * 8, 512, mpair * 256 + rank * 128);
              if (++bs == K1_BST) { bs = 0; bph ^= 1; }
            } else if (newA) {
              PWAIT(bAe + kc * 8, aph);
              mbar_expect(bAf + kc * 8, 16384);
              tma2d(sA + ((kc + 2) & 7) * 16384, &p.tmA[a_sel], bAf + kc * 8, kc * 64, mpair * 256 + rank * 128);
              if (kc == 7 && lastjob) mbar_arrive(bLast);
            }
#pragma unroll 1
            for (int kk = 0; kk < 2; kk++) {
              PWAIT(bBe + bs * 8, bph);
              mbar_expect(bBf + bs * 8, 2 * halfbytes);
              tma3d_mc(sB + bs * 16384 + rank * halfbytes, tw, bBf + bs * 8, 0, kc * 64 + kk * 32 + rank * 16, chunk0, 3);
              if (++bs == K1_BST) { bs = 0; bph ^= 1; }
            }
          }
          if (newA) aph ^= 1;
        }
        Cursor c{0, 0};
        int pcol = 0;
        PWAIT(bR, 0);
        uint32_t tick = lds32(sTick + 8), seen = 1u << (p.order[tick] >> 4);
        asm volatile("fence.proxy.async.global;" ::: "memory");
#pragma unroll 1
        for (int it = 0;; it++) {
          const uint32_t item = (tick < 256) ? p.order[tick] : (K2_END | min(tick - 256, 255u));
          asm volatile("st.shared.u32 [%0], %1;" ::"r"(sItem + (it & 7) * 4), "r"(item) : "memory");
          if (item >= K2_END) break;
          const int h = item >> 3, j = item & 7;
          const int col = (h * 2 + rank) * S_LEN;
          const int nb = 2 * j + 2;
          if (!((seen >> (h >> 1)) & 1)) {
            wait_flag(&g_sync[F_HP + (h >> 1)], RDY_TARGET);
            asm volatile("fence.proxy.async.global;" ::: "memory");
            seen |= 1u << (h >> 1);
          }
          PWAIT(bE + c.s * 8, c.ph);
          mbar_expect(bF + c.s * 8, 32768);
#pragma unroll 1
          for (int i = 0; i < 4; i++) {
            const int hi = (i ^ it ^ 1) & 1;
            tma2d(sbase + c.s * 32768 + i * 8192, &p.tmQ, bF + c.s * 8, 0, (h * 2 + (i >> 1)) * S_LEN + (2 * j + hi) * 128 + (rank ^ hi) * 64);
          }
          c.next();
          if (tick >= 256 - 73) {
            const int kk = tick - (256 - 73), sel = (kk < 9), kr = (sel ? kk : kk - 9) * 64 + rank * 32;
#pragma unroll 1
            for (int i = 0; i < 2; i++) {
              tma_pf3d(&p.tmO[sel], 0, kr, i * 4);
              tma_pf2d(&p.tmOt[sel], 512 + i * 32, kr);
            }
          }
#pragma unroll 1
          for (int n = nb - 1; n >= 0; n--) {
            if (n == 0 && rank == 0) tick = atomicAdd(&g_sync[F_TICK], 1u);
            PWAIT(bE + c.s * 8, c.ph);
            mbar_expect(bF + c.s * 8, 32768);
            tma2d_mc(sbase + c.s * 32768 + rank * 16384, &p.tmK, bF + c.s * 8, 0, col + n * 128, 3);
            c.next();
            if (n < nb - 1 || it > 0) {
              PWAIT(bE + c.s * 8, c.ph);
              mbar_expect(bF + c.s * 8, 32768);
              tma2d_mc(sbase + c.s * 32768 + rank * 16384, &p.tmV, bF + c.s * 8, 0, (n < nb - 1) ? col + (n + 1) * 128 : pcol, 3);
              c.next();
            }
          }
          pcol = col;
          if (rank == 0) {
            asm volatile(
                "{\n.reg .b32 a, b;\nmapa.shared::cluster.u32 a, %0, 1;\nmapa.shared::cluster.u32 b, %1, 1;\n"
                "st.async.shared::cluster.mbarrier::complete_tx::bytes.u32 [a], %2, [b];\n}" ::"r"(sTick + (it & 1) * 4),
                "r"(bT + (it & 1) * 8), "r"(tick) : "memory");
          } else {
            mbar_expect(bT + (it & 1) * 8, 4);
            PWAIT(bT + (it & 1) * 8, (it >> 1) & 1);
            tick = lds32(sTick + (it & 1) * 4);
          }
        }
        PWAIT(bE + c.s * 8, c.ph);
        mbar_expect(bF + c.s * 8, 32768);
        tma2d_mc(sbase + c.s * 32768 + rank * 16384, &p.tmV, bF + c.s * 8, 0, pcol, 3);
        const uint32_t unit = tick - 256;
        const int mblk = (7 - (p.unit[unit][0] >> 1)) * 2 + rank, nhalf = p.unit[unit][0] & 1;
        uint32_t have, hoa;
        have = ld_and2(&g_sync[F_CTX + (mblk & ~1)]);
        asm volatile("ld.acquire.gpu.global.u32 %0, [%1];" : "=r"(hoa) : "l"(&g_sync[F_OA + mblk]) : "memory");
        asm volatile("fence.proxy.async.global;" ::: "memory");
#pragma unroll 1
        for (uint32_t idx = PF3A; idx < PF3; idx++) {
          const int kk = p.unit[unit][2] + idx;
          if ((kk < 9) ? (hoa >= 8) : ((have >> ((kk - 9) >> 1)) & 1)) tma_pf2d(&p.tmC, 0, ((kk < 9) ? 64 + kk : kk - 9) * S_LEN + mblk * 128);
        }
        {
          const uint32_t rot = k3_rot(c.s), nfree = ((0x1Au >> c.s) & 1) ? 2 : 3;
          uint32_t kq = p.unit[unit][2] * 0x01010101u + 0x03020100u, k1 = 80, idx = 0, pa = 0, pb = 0;
          auto step = [&](uint32_t& pend) {
            uint32_t nxt = (kq & 255) + CR;
            if (idx + CR >= K3_NS && k1 == 80) {
              if (rank == 0) {
                nxt = min(pend + p.unit[unit][3], 73u);
                asm volatile("{\n.reg .b32 a;\nmapa.shared::cluster.u32 a, %0, 1;\nst.volatile.shared::cluster.u8 [a], %1;\n}" ::"r"(sClm + idx), "r"(nxt) : "memory");
              } else {
#pragma unroll 1
                for (uint32_t spins = 0; spins < (1u << 22); spins++) {
                  asm volatile("ld.volatile.shared.u8 %0, [%1];" : "=r"(nxt) : "r"(sClm + idx) : "memory");
                  if (nxt != 255) break;
                  __nanosleep(20);
                }
              }
              if (nxt >= 73) {
                k1 = idx + CR;
                asm volatile("st.shared.u32 [%0], %1;" ::"r"(sK1), "r"(k1) : "memory");
              }
            }
            const uint32_t kk = kq & 255;
            if (idx < 12) TP(idx);
            kq = (kq >> 8) | (nxt << (8 * CR - 8));
            const uint32_t s = (rot + idx) & 3;
            if (idx >= nfree) PWAIT((idx < 4) ? bH : b3E + s * 8, (idx < 4) ? 0 : (~idx >> 2) & 1);
#pragma unroll 1
            while (idx < nfree && c.s != ((0x6431u >> (4 * s)) & 15)) {
              c.next();
              PWAIT(bE + c.s * 8, c.ph);
            }
            if (idx < 12) TP(12 + idx);
            mbar_expect(b3F + s * 8, K3_STAGE);
            const uint32_t st = sbase + s * K3_STAGE;
            const int sel = (kk < 9), k = sel ? kk : kk - 9, kr = k * 64 + rank * 32;
            tma3d_mc(st + 16384 + rank * 16384, &p.tmO[sel], b3F + s * 8, 0, kr, nhalf * 4, 3);
            tma2d_mc(st + 49152 + rank * 2048, &p.tmOt[sel], b3F + s * 8, 512 + nhalf * 32, kr, 3);
            if (rank == 0 && idx + CR + 2 >= K3_NS && k1 == 80) pend = atomicAdd(&g_sync[F_CLM + p.unit[unit][0]], 1u);
            if (sel && hoa < 8) {
              wait_flag(&g_sync[F_OA + mblk], 8);
              hoa = 8;
              asm volatile("fence.proxy.async.global;" ::: "memory");
            }
            if (!sel && !((have >> (k >> 1)) & 1)) {
#pragma unroll 1
              for (uint32_t spins = 0; spins < (1u << 22); spins++) {
                have = ld_and2(&g_sync[F_CTX + (mblk & ~1)]);
                if ((have >> (k >> 1)) & 1) break;
                __nanosleep(100);
              }
              asm volatile("fence.proxy.async.global;" ::: "memory");
            }
            tma2d(st, &p.tmC, b3F + s * 8, 0, (sel ? 64 + k : k) * S_LEN + mblk * 128);
            if (idx < 12) TP(24 + idx);
            return ++idx >= k1;
          };
#pragma unroll 1
          for (;;) {
            if (step(pa)) break;
            if (step(pb)) break;
          }
          asm volatile("" ::"r"(pa), "r"(pb) : "memory");
        }
      }
    }
    __syncwarp();
    if (warp_g == 8) {
      uint32_t v = 0;
      if (lane == 0) {
        __threadfence();
        v = atomicAdd(&g_sync[F_DONE], 1u);
      }
      if (__shfl_sync(0xffffffffu, v, 0) == 2 * NCLUSTER - 1) {
        reinterpret_cast<uint4*>(g_sync)[lane] = make_uint4(0, 0, 0, 0);
        if (lane == 0) g_sync[F_EPOCH] = lds32(sGate + 64) + 1;
      }
    }
    asm volatile("" ::: "memory");
    if (__shfl_sync(0xffffffffu, warp_g, 0) != 8) {
#pragma unroll 1
      for (int i = 0; i < 32 && !mbar_test(bAf + 7 * 8, 0); i++) __nanosleep(200);
      if (lr0 < S_LEN) {
#pragma unroll 1
        for (int i = warp_g - 9; i < 16; i += 3) {
          const float g = gate_row(lr0 + i, lane, x, gate_w);
          if (lane == 0) asm volatile("st.shared.f32 [%0], %1;" ::"r"(sGate + i * 4), "f"(g) : "memory");
        }
        if (lane == 0) {
          mbar_arrive(bG);
          __threadfence();
          atomicAdd(&g_sync[F_GATE], 1u);
        }
      }
      uint32_t aph = 1;
#pragma unroll 1
      for (int ji = 0; ji < K1_MAXJOBS; ji++) aph ^= (p.jobs[cl][ji] >> 14) & 1;
      if (warp_g == 9) {
        uint32_t nxt = 0;
        if (lane == 0) {
#pragma unroll 1
        for (int ji = 0; ji < K1_MAXJOBS; ji++) {
          const uint32_t job = p.jobs[cl][ji];
          if (!(job & 3)) break;
          PWAIT(bS + (ji & 3) * 8, (ji >> 2) & 1);
          __threadfence();
          atomicAdd(&g_sync[(((job >> 6) & 3) == 2) ? (F_QKVA + ((job >> 3) & 7) * 2 + rank) : (F_HP + ((job >> 10) & 15))], 1u);
        }
#pragma unroll 1
        for (int it = 0;; it++) {
          PWAIT(bS2 + (it & 3) * 8, (it >> 2) & 1);
          const uint32_t item = lds32(sItem + (it & 7) * 4);
          nxt = lds32(sItem + ((it + 1) & 7) * 4);
          __threadfence();
          atomicOr(&g_sync[F_CTX + (item & 7) * 2 + rank], 1u << (item >> 3));
          if (nxt >= K2_END) break;
        }
        }
        const uint32_t unit = __shfl_sync(0xffffffffu, nxt, 0) & 255;
        {
          const int mblk = (7 - (p.unit[unit][0] >> 1)) * 2 + rank, nhalf = p.unit[unit][0] & 1;
          bf16* o = ptr_add(out, (mblk * 128 + p.unit[unit][1] * 32) * DM * 2);
          const bool mine = p.unit[unit][1] < 4;
#pragma unroll 4
          for (int i = 0; i < 32 && mine; i++) __stcg(reinterpret_cast<uint4*>(ptr_add(o, i * DM * 2 + nhalf * 512 + lane * 16)), make_uint4(0, 0, 0, 0));
#pragma unroll
          for (int i = 0; i < 4 && mine; i++) __stcg(reinterpret_cast<uint4*>(ptr_add(o, (i * 8 + (lane >> 2)) * DM * 2 + 1024 + nhalf * 64 + (lane & 3) * 16)), make_uint4(0, 0, 0, 0));
          asm volatile("fence.proxy.async.global;" ::: "memory");
          __threadfence();
          __syncwarp();
          if (lane == 0) {
            prefetch_tmap(&p.tmR[0]); prefetch_tmap(&p.tmR[1]);
            unsigned int* cnt = &g_sync[F_XCH + mblk * 2 + nhalf];
            const uint32_t xtarget = lds32(sGate + 64) * 4 + 4;
            if (mine) atomicAdd(cnt, 1u);
            uint32_t v;
#pragma unroll 1
            for (uint32_t spins = 0; spins < (1u << 22); spins++) {
              asm volatile("ld.acquire.gpu.global.u32 %0, [%1];" : "=r"(v) : "l"(cnt) : "memory");
              if ((int)(v - xtarget) >= 0) break;
              __nanosleep(200);
            }
            asm volatile("fence.proxy.async.global;" ::: "memory");
            mbar_arrive(bZ);
          }
        }
      } else if (warp_g == 11) {
        if (lane == 0) {
          asm volatile("st.shared.u32 [%0], %1;" ::"r"(sGate + 64), "r"(__ldcg(&g_sync[F_EPOCH])) : "memory");
          wait_flag(&g_sync[F_GATE], GATE_TARGET);
          prefetch_tmap(&p.tmC); prefetch_tmap(&p.tmQ); prefetch_tmap(&p.tmK); prefetch_tmap(&p.tmV);
          uint32_t tick;
          if (rank == 0) {
            PWAIT(bLast, 0);
            PWAIT(bAe + FIRST_DRAW * 8, aph);
            tick = atomicAdd(&g_sync[F_TICK], 1u);
            asm volatile("st.shared.u32 [%0], %1;" ::"r"(sTick + 8), "r"(tick) : "memory");
            asm volatile(
                "{\n.reg .b32 a, b;\nmapa.shared::cluster.u32 a, %0, 1;\nmapa.shared::cluster.u32 b, %1, 1;\n"
                "st.async.shared::cluster.mbarrier::complete_tx::bytes.u32 [a], %2, [b];\n}" ::"r"(sTick + 8), "r"(bT0), "r"(tick) : "memory");
          } else {
            mbar_expect(bT0, 4);
            PWAIT(bT0, 0);
            tick = lds32(sTick + 8);
          }
          wait_flag(&g_sync[F_HP + (p.order[tick] >> 4)], RDY_TARGET);
          mbar_arrive(bR);
        }
      } else if (warp_g == 10) {
        if (lr0 < S_LEN && lane == 0) {
          prefetch_tmap(&p.tmL[0]); prefetch_tmap(&p.tmL[1]); prefetch_tmap(&p.tmL[2]);
          wait_flag(&g_sync[F_QKVA + (lr0 >> 7)], K1_FLAG_TARGET);
          wait_flag(&g_sync[F_QKVA + (max(lr0 - 16, 0) >> 7)], K1_FLAG_TARGET);
          asm volatile("fence.proxy.async.global;" ::: "memory");
          PWAIT(bLast, 0);
#pragma unroll 1
          for (int kc = 0; kc < 6; kc++) {
            PWAIT(bAe + kc * 8, aph);
            if (kc == 3) {
              mbar_expect(bL, LV);
              tma4d(sL, &p.tmL[0], bL, lr0 / 2 - 8, 9, 0);
              tma4d(sL + LQ, &p.tmL[1], bL, lr0 / 2, 0, 0);
            }
          }
          mbar_expect(bL2, LQ);
          tma4d(sL + LV, &p.tmL[0], bL2, lr0 / 2 - 8, 18, 0);
        }
        __syncwarp();
        if (lr0 < S_LEN) {
          PWAIT(bL + 8, 0);
          if (lane < 8) mbar_arrive_cluster(bE + (4 + (lane >> 2)) * 8, lane & 1);
        }
        bar_sync(5, 256 + 32);
        if (lr0 < S_LEN && lane == 0) {
          asm volatile("cp.async.bulk.tensor.4d.global.shared::cta.bulk_group [%0, {%2, %3, %2, %2}], [%1];" ::"l"(&p.tmL[2]), "r"(sL + LO), "r"(0), "r"(lr0 / 2) : "memory");
          asm volatile("cp.async.bulk.commit_group;" ::: "memory");
          asm volatile("cp.async.bulk.wait_group.read 0;" ::: "memory");
        }
        __syncwarp();
        if (lane < ((lr0 < S_LEN) ? 4 : 12)) mbar_arrive_cluster(bE + (6 - (lane >> 2)) * 8, lane & 1);
        if (lr0 < S_LEN && lane == 0) {
          asm volatile("cp.async.bulk.wait_group 0;" ::: "memory");
          asm volatile("fence.proxy.async.global;" ::: "memory");
          __threadfence();
          atomicAdd(&g_sync[F_OA + (lr0 >> 7)], 1u);
        }
      }
    }
    __syncwarp();
    cluster_sync();
  } else {
    reg_alloc<232>();
    const int wg = warp_g >> 2, warp = warp_g & 3, q = lane & 3;
    const bool sig = (lane == 0) && (warp < 2);
    {
      K1State st{0, 0, 0, nullptr, 0, 0, 0, 24};
      float acc[128];
      uint32_t pk[64];
      if (wg == 0) { TS(0, 0); TSC(0, 2); }
      uint32_t job = p.jobs[cl][0];
      k1_first(st, job, bAf, bBf);
      {
#pragma unroll 1
        for (int ji = 0; job & 3; ji++) {
          const uint32_t njob = p.jobs[cl][ji + 1];
          k1_tile(acc, pk, st, job, njob, sA, sB, bAf, bAe, bBf, bBe, bS, wg, warp, lane, rank);
          job = njob;
        }
      }
#pragma unroll
      for (int i = 0; i < 4; i++)
        mbar_arrive_cluster_if(bE + i * 8, warp & 1, sig);
      if (lr0 < S_LEN) mbar_wait(bG, 0);
      if (st.wsel == 3) {
#pragma unroll
        for (int G = 0; G < 16; G++) scale_q4(pk + G * 4);
      }
      auto flush = [&](int i, uint32_t dep) {
        asm volatile("{\n.reg .pred p;\nsetp.eq.u32 p, %5, 0;\n@p st.global" STA_MOD ".v4.b32 [%0], {%1, %2, %3, %4};\n}" ::"l"(st.pp + goff(i / 2, i & 1)),
                     "r"(pk[i * 4]), "r"(pk[i * 4 + 1]), "r"(pk[i * 4 + 2]), "r"(pk[i * 4 + 3]), "r"(dep & blockIdx.y) : "memory");
      };
      if (wg == 0) { TS(0, 1); TSC(0, 3); }
      if (lr0 < S_LEN) {
        const float gate0 = __uint_as_float(lds32(sGate + (lane >> 2) * 8)), gate1 = __uint_as_float(lds32(sGate + (lane >> 2) * 8 + 4));
        local_attn(lr0, warp_g, sL, bL, bL2, lane, gate0, gate1, flush);
        k1_flag(st, lane, bS);
      } else {
        FLUSH();
      }
      bar_arrive(5, 256 + 32);
    }
    __syncwarp();
    uint32_t item, rot;
    {
      const int mybar = 1 + wg, otherbar = 2 - wg;
      const uint32_t never = blockIdx.y;
      float S[64], O[64];
      uint32_t P[32], Q[32];
      float m0, m1, l0, l1, gf0, gf1;
      uint32_t eoff;
      Cursor c{2 + 2 * (uint32_t)wg, 0}, ck{1 + (uint32_t)wg, 0};
      if (wg == 1) bar_arrive(1, 256);
      if (wg == 0) { TS(1, 0); TSC(1, 2); }
      {
        const Cursor cq{0, 0}, cs0{1, 0}, cs1{3, 0};
        const int it = 0, hi = wg ^ 1;
        mbar_wait2(bF, 0, bF + ck.s * 8, 0);
        LOAD_Q();
        wg_fence();
        ISSUE_QK(ck);
        wg_commit();
        RELEASE(cq);
        NEW_ITEM();
        wg_wait<0>();
        fence_regs(S);
      }
#pragma unroll 1
      for (int it = 0;;) {
        int hi = (wg ^ it ^ 1) & 1;
        RELEASE(ck);
        const int nblk = 2 * (item & 7) + 1 + hi;
        Cursor cv;
        float s0 = 0.f, s1 = 0.f;
        l0 = 0.f; l1 = 0.f;
        m0 = 0.f; m1 = 0.f;
        bool shifted = false;
        {
          const int d = warp * 16 + (lane >> 2) - 2 * q;
          if (rank == hi) {
#pragma unroll
            for (int jj = 0; jj < 8; jj++) MASK(jj, jj);
            EXPB(0); EXPB(1); EXPB(2); EXPB(3);
#pragma unroll
            for (int i = 32; i < 64; i++) S[i] = -INFINITY;
#pragma unroll
            for (int i = 16; i < 32; i++) P[i] = 0;
          } else {
#pragma unroll
            for (int jj = 0; jj < 8; jj++) MASK(jj + 8, jj);
            EXPB(0); EXPB(1); EXPB(2); EXPB(3); EXPB(4); EXPB(5); EXPB(6); EXPB(7);
          }
        }
        float chk;
        asm("{\n.reg .pred p;\nsetp.ge.f32 p, %1, %2;\nselp.f32 %0, %3, 0f7F800000, p;\n}" : "=f"(chk) : "f"(fminf(s0, s1)), "f"(q ? -1.f : SPEC_LO), "f"(s0 + s1));
        fence_regs(P);
        TB(9);
#pragma unroll 1
        for (int n = 1;; n++) {
          if (__any_sync(0xffffffffu, !(chk <= SPEC_HI))) {
            float mx0 = fmaxf(S[0], S[1]), mx1 = fmaxf(S[2], S[3]);
#pragma unroll
            for (int jj = 1; jj < 16; jj++) {
              mx0 = fmaxf(mx0, fmaxf(S[jj * 4 + 0], S[jj * 4 + 1]));
              mx1 = fmaxf(mx1, fmaxf(S[jj * 4 + 2], S[jj * 4 + 3]));
            }
            mx0 = fmaxf(mx0, __shfl_xor_sync(0xffffffffu, mx0, 1));
            mx1 = fmaxf(mx1, __shfl_xor_sync(0xffffffffu, mx1, 1));
            mx0 = fmaxf(mx0, __shfl_xor_sync(0xffffffffu, mx0, 2));
            mx1 = fmaxf(mx1, __shfl_xor_sync(0xffffffffu, mx1, 2));
            const float lo = (n == 1) ? -INFINITY : 0.f;
            mx0 = fmaxf(mx0, lo);
            mx1 = fmaxf(mx1, lo);
            m0 += mx0; m1 += mx1;
            shifted = true;
            const float sc0 = ex2(-fmaxf(mx0, 0.f)), sc1 = ex2(-fmaxf(mx1, 0.f));
            l0 *= sc0; l1 *= sc1;
            s0 = 0.f; s1 = 0.f;
#pragma unroll
            for (int jj = 0; jj < 16; jj++) {
              const float e0 = ex2(S[jj * 4 + 0] - mx0), e1 = ex2(S[jj * 4 + 1] - mx0), e2 = ex2(S[jj * 4 + 2] - mx1), e3 = ex2(S[jj * 4 + 3] - mx1);
              s0 += e0 + e1;
              s1 += e2 + e3;
              P[jj * 2 + 0] = pack_bf16(e0, e1);
              P[jj * 2 + 1] = pack_bf16(e2, e3);
              O[jj * 4 + 0] *= sc0;
              O[jj * 4 + 1] *= sc0;
              O[jj * 4 + 2] *= sc1;
              O[jj * 4 + 3] *= sc1;
            }
          }
          l0 += s0;
          l1 += s1;
          if (n >= nblk) break;
          ck = c; c.next();
          cv = c; c.next();
          mbar_wait2(bF + ck.s * 8, ck.ph, bF + cv.s * 8, cv.ph);
          TURN_SYNC();
          TRC(0);
          wg_fence();
          ISSUE_QK(ck);
          wg_commit();
          {
            const uint64_t dv = make_desc(sbase + cv.s * 32768, 16384, 1024, 1);
#pragma unroll
            for (int t = 0; t < 8; t++) {
              wgmma_rs_n128<1, 0>(O, P[4 * t], P[4 * t + 1], P[4 * t + 2], P[4 * t + 3], dv + (uint64_t)(t * 128), (t > 0) ? 1 : (n != 1));
              if ((PVM >> t) & 1) wg_commit();
            }
          }
          TURN_ARRIVE();
          s0 = 0.f; s1 = 0.f;
          wg_wait<__builtin_popcount(PVM)>();
          fence_regs(S);
          RELEASE(ck);
          if (shifted) {
#pragma unroll
            for (int i = 0; i < 64; i++) S[i] -= (i & 2) ? m1 : m0;
          }
          wg_wait<__builtin_popcount(PVM) - 1>();
          EXPC(0); EXPC(1); EXPC(2); EXPC(3); EXPC(4); EXPC(5); EXPC(6); EXPC(7);
          chk = s0 + s1;
        }
        it++;
        hi ^= 1;
        TB(0);
        Cursor cq = c, cs0, cs1;
        rot = k3_rot(c.s);
        c.next();
        ck = c; c.next();
        cs0 = ck; cs1 = ck;
        cv = c; c.next();
        if (!hi) {
          ck = c; c.next();
          cs1 = c; c.next();
        }
        mbar_wait(bF + cq.s * 8, cq.ph);
        TB(1);
        LOAD_Q();
        const uint32_t rdy = mbar_test(bF + ck.s * 8, ck.ph) & mbar_test(bF + cv.s * 8, cv.ph);
        l0 += __shfl_xor_sync(0xffffffffu, l0, 1);
        l1 += __shfl_xor_sync(0xffffffffu, l1, 1);
        l0 += __shfl_xor_sync(0xffffffffu, l0, 2);
        l1 += __shfl_xor_sync(0xffffffffu, l1, 2);
        if (item >= K2_END) {
          TURN_SYNC();
          TRC(2);
          wg_fence();
          ISSUE_PV(cq, nblk == 1);
          wg_commit();
          if (wg == (it & 1)) TURN_ARRIVE();
          asm volatile("" : "+f"(gf0), "+f"(gf1), "+f"(l0), "+f"(l1));
          const float f0 = __fdividef(1.f - gf0, l0), f1 = __fdividef(1.f - gf1, l1);
          bf16* optr = ptr_add(g_ctx, eoff);
          wg_wait<0>();
          fence_regs(O);
          mbar_arrive_cluster_if(bH, warp & 1, sig);
          STORE_O(0); STORE_O(1); STORE_O(2); STORE_O(3);
          __syncwarp();
          mbar_arrive_if(bS2 + ((it - 1) & 3) * 8, lane == 0);
          break;
        }
        if (!rdy) mbar_wait2(bF + ck.s * 8, ck.ph, bF + cv.s * 8, cv.ph);
        TB(2);
        TURN_SYNC();
        TB(3);
        TRC(1);
        wg_fence();
        ISSUE_PV(cv, nblk == 1);
        wg_commit();
        ISSUE_QK(ck);
        wg_commit();
        TURN_ARRIVE();
        RELEASE(cq);
        TB(4);
        asm volatile("" : "+f"(gf0), "+f"(gf1), "+f"(l0), "+f"(l1));
        const float f0 = __fdividef(1.f - gf0, l0), f1 = __fdividef(1.f - gf1, l1);
        wg_wait<1>();
        fence_regs(O);
        fence_regs(P);
        TB(5);
        RELEASE(cv);
        {
          bf16* optr = ptr_add(g_ctx, eoff);
          STORE_O(0); STORE_O(1); STORE_O(2); STORE_O(3);
          __syncwarp();
          mbar_arrive_if(bS2 + ((it - 1) & 3) * 8, lane == 0);
        }
        TB(6);
        NEW_ITEM();
        TB(7);
        wg_wait<0>();
        fence_regs(S);
        TB(8);
      }
      TRC(3);
      if (wg == 1) { TS(1, 1); TSC(1, 3); }
    }
    __syncwarp();
    const uint32_t unit = item & 255;
    {
      const int mblk = (7 - (p.unit[unit][0] >> 1)) * 2 + rank, nhalf = p.unit[unit][0] & 1;
      float acc[144];
      uint32_t s = rot, ph = 0, prev = 0, k = 0;
      if (wg == 0) { TS(2, 0); TSC(2, 2); }
      uint32_t fa[16], fb[16], fc[16];
      const uint32_t aoff = (wg * 64 + warp * 16 + (lane & 15)) * 128 + (((lane >> 4) ^ (lane & 7)) << 4);
#define C_NEXT()                                                                                               \
  do {                                                                                                         \
    s = (s + 1) & 3;                                                                                           \
    if (s == rot) ph ^= 1;                                                                                     \
    mbar_wait(b3F + s * 8, ph);                                                                                \
  } while (0)
#define C_LOAD(F)                                                                                              \
  do {                                                                                                         \
    _Pragma("unroll") for (int t = 0; t < 4; t++)                                                              \
        ldsm_x4(F[4 * t], F[4 * t + 1], F[4 * t + 2], F[4 * t + 3], sbase + s * K3_STAGE + (aoff ^ (t * 32))); \
  } while (0)
#define C_MMA(F, S, H, SD)                                                                                     \
  do {                                                                                                         \
    const uint32_t st = sbase + (S) * K3_STAGE;                                                                \
    const uint64_t db = make_desc(st + 16384, 4096, 1024, 1), dt = make_desc(st + 49152, 16, 512, 2);          \
    _Pragma("unroll") for (int t = 0; t < 4; t++) {                                                            \
      const int sd = (t > 0) || (SD);                                                                          \
      if ((H) & 1) wgmma_rs_n128<1, 0>(acc, F[4 * t], F[4 * t + 1], F[4 * t + 2], F[4 * t + 3], db + (uint64_t)((t >> 1) * 1024 + (t & 1) * 128), sd); \
      if ((H) & 2) wgmma_rs_n128<1, 64>(acc, F[4 * t], F[4 * t + 1], F[4 * t + 2], F[4 * t + 3], db + (uint64_t)((t >> 1) * 1024 + (t & 1) * 128 + 512), sd); \
      if ((H) & 2) wgmma_rs_n32<1, 128>(acc, F[4 * t], F[4 * t + 1], F[4 * t + 2], F[4 * t + 3], dt + (uint64_t)(t * 64), sd); \
    }                                                                                                          \
  } while (0)
#define C_STEP(F, G)                                                                                           \
  {                                                                                                            \
    wg_fence();                                                                                                \
    C_MMA(F, s, 3, k > 0);                                                                                     \
    wg_commit();                                                                                               \
    wg_wait<1>();                                                                                              \
    fence_regs(G);                                                                                             \
    mbar_arrive_cluster_if(b3E + prev * 8, warp & 1, sig && k > 0);                                            \
    prev = s;                                                                                                  \
    TCK(k + 1);                                                                                                \
    C_NEXT();                                                                                                  \
    if ((tid & 127) == 0 && k < 11) TP(37 + wg * 12 + k);                                                      \
    if (++k + CR >= lds32(sK1)) break;                                                                         \
    C_LOAD(G);                                                                                                 \
  }
      TCK(0);
      mbar_wait(b3F + s * 8, 0);
      if ((tid & 127) == 0) TP(36 + wg * 12);
      C_LOAD(fa);
#pragma unroll
      for (int i = 0; i < 16; i++) fb[i] = 0;
#pragma unroll 1
      for (;;) {
        C_STEP(fa, fb)
        C_STEP(fb, fa)
      }
      C_LOAD(fc);
      if (wg == 1) {
        wg_wait<0>();
        mbar_arrive_cluster_if(b3E + prev * 8, warp & 1, sig);
        mbar_wait(bLd, 0);
      }
      const uint32_t s0 = s;
      wg_fence();
      C_MMA(fc, s0, 2, 1);
      wg_commit();
      wg_wait<1>();
      fence_regs(fa);
      fence_regs(fb);
      mbar_arrive_cluster_if(b3E + prev * 8, warp & 1, sig && wg == 0);
      cluster_arrive();
      C_NEXT();
      C_LOAD(fa);
      wg_fence();
      C_MMA(fa, s, 2, 1);
      C_MMA(fc, s0, 1, 1);
      wg_commit();
      C_NEXT();
      C_LOAD(fb);
      wg_fence();
      C_MMA(fb, s, 2, 1);
      wg_commit();
      wg_wait<1>();
      fence_regs(fc);
      C_NEXT();
      C_LOAD(fc);
      wg_fence();
      C_MMA(fc, s, 2, 1);
      wg_commit();
      C_MMA(fa, (s0 + 1) & 3, 1, 1);
      C_MMA(fb, (s0 + 2) & 3, 1, 1);
      C_MMA(fc, s, 1, 1);
      wg_commit();
      mbar_arrive_if(bLd, tid < 128 && lane == 0);
      const uint32_t stail = sbase + K3_NST * K3_STAGE + warp_g * 1024;
      const int row = mblk * 128 + warp_g * 16;
      mbar_wait(bZ, 0);
#pragma unroll
      for (int h = 1; h >= 0; h--) {
        if (h) wg_wait<1>(); else wg_wait<0>();
#pragma unroll
        for (int i = h * 64; i < 64 + h * 80; i++) asm volatile("" : "+f"(acc[i])::"memory");
        if (!h && wg == 0) TS(2, 4);
#pragma unroll
        for (int i = h * 8; i < 8 + h * 10; i++) {
          const uint32_t ad = (i < 16) ? sbase + (i >> 2) * K3_STAGE + (aoff ^ ((i & 3) * 32))
                                       : stail + (lane & 15) * 64 + ((((i & 1) * 2 + (lane >> 4)) ^ ((lane >> 1) & 3)) << 4);
          asm volatile("stmatrix.sync.aligned.m8n8.x4.shared.b16 [%0], {%1, %2, %3, %4};" ::"r"(ad), "r"(pack_bf16(acc[i * 8], acc[i * 8 + 1])),
                       "r"(pack_bf16(acc[i * 8 + 2], acc[i * 8 + 3])), "r"(pack_bf16(acc[i * 8 + 4], acc[i * 8 + 5])), "r"(pack_bf16(acc[i * 8 + 6], acc[i * 8 + 7])) : "memory");
        }
        asm volatile("fence.proxy.async.shared::cta;" ::: "memory");
        __syncwarp();
        if (!h && wg == 0) TS(2, 5);
        if (lane == 0) {
#pragma unroll
          for (int c = h * 2; c < 2 + h * 3; c++)
            asm volatile("cp.reduce.async.bulk.tensor.2d.global.shared::cta.add.tile.bulk_group [%0, {%2, %3}], [%1];" ::"l"(&p.tmR[c >> 2]),
                         "r"((c < 4) ? sbase + c * K3_STAGE + warp_g * 2048 : stail), "r"((c < 4) ? nhalf * 256 + c * 64 : 512 + nhalf * 32), "r"(row) : "memory");
        }
        __syncwarp();
      }
      if (lane == 0) {
        asm volatile("cp.async.bulk.commit_group;" ::: "memory");
        if (wg == 0) TS(2, 6);
        asm volatile("cp.async.bulk.wait_group 0;" ::: "memory");
      }
      __syncwarp();
    }
    if (wg == 0) { TS(2, 1); TSC(2, 3); }
    cluster_wait();
  }
}

typedef CUresult (*EncFn)(CUtensorMap*, CUtensorMapDataType, cuuint32_t, void*, const cuuint64_t*, const cuuint64_t*, const cuuint32_t*,
                          const cuuint32_t*, CUtensorMapInterleave, CUtensorMapSwizzle, CUtensorMapL2promotion, CUtensorMapFloatOOBfill);

static void enc2d(EncFn enc, CUtensorMap* m, const void* ptr, uint64_t cols, uint64_t rows, uint32_t bc, uint32_t br,
                  CUtensorMapSwizzle sw = CU_TENSOR_MAP_SWIZZLE_128B) {
  cuuint64_t gd[2] = {cols, rows}, gs[1] = {cols * 2};
  cuuint32_t bx[2] = {bc, br}, es[2] = {1, 1};
  enc(m, CU_TENSOR_MAP_DATA_TYPE_BFLOAT16, 2, const_cast<void*>(ptr), gd, gs, bx, es, CU_TENSOR_MAP_INTERLEAVE_NONE, sw,
      CU_TENSOR_MAP_L2_PROMOTION_L2_256B, CU_TENSOR_MAP_FLOAT_OOB_FILL_NONE);
}
static void enc3d(EncFn enc, CUtensorMap* m, const void* ptr, uint64_t cols, uint64_t rows, uint32_t br, uint32_t bch) {
  cuuint64_t gd[3] = {64, rows, cols / 64}, gs[2] = {cols * 2, 128};
  cuuint32_t bx[3] = {64, br, bch}, es[3] = {1, 1, 1};
  enc(m, CU_TENSOR_MAP_DATA_TYPE_BFLOAT16, 3, const_cast<void*>(ptr), gd, gs, bx, es, CU_TENSOR_MAP_INTERLEAVE_NONE,
      CU_TENSOR_MAP_SWIZZLE_128B, CU_TENSOR_MAP_L2_PROMOTION_L2_256B, CU_TENSOR_MAP_FLOAT_OOB_FILL_NONE);
}

static void build_k1_jobs(Params& p) {
  int cnt[NCLUSTER];
  for (int c = 0; c < NCLUSTER; c++) {
    cnt[c] = 0;
    for (int i = 0; i <= K1_MAXJOBS; i++) p.jobs[c][i] = 0;
  }
  auto add = [&](int c, int nch, int a_sel, int mp, int w_sel, int chunk0) {
    p.jobs[c][cnt[c]++] = (uint16_t)((nch - 1) | (a_sel << 2) | (mp << 3) | (w_sel << 6) | (chunk0 << 8));
  };
  const char* plan = "cccccccccc cccccccccc cccccccc cccc xxxx xxxx xxxxxx xxxxxxxx";
  const char *hpp = "abcd01e23456789f", *qpp = "01abc23de456789f";
  int TIE = 0;
  int XA = 0;
  auto hex = [](char c) { return (c > '9') ? c - 'a' + 10 : c - '0'; };
  const char* cur[8];
  int tend[8] = {};
  for (int g = 0; g < 8; g++) {
    cur[g] = plan;
    while (*plan == 'c' || *plan == 'x') plan++;
    if (*plan) plan++;
  }
  int kc = 0, kx = 0;
  for (;;) {
    int b = -1, bt = 0;
    for (int g = 0; g < 8; g++) {
      const int t = tend[g] + (*cur[g] == 'x' ? 94 : 85);
      if ((*cur[g] == 'c' || *cur[g] == 'x') && (b < 0 || t < bt || (TIE && t == bt))) { b = g; bt = t; }
    }
    if (b < 0) break;
    const int a = kx - XA;
    for (int mp = 0; mp < 8; mp++) {
      if (*cur[b] == 'c') add(b * 8 + mp, 4, 0, mp, kc & 1, hex(hpp[kc >> 1]) * 4);
      else if (a >= 0 && a < 7) add(b * 8 + mp, a == 0 ? 3 : 4, 1, mp, 2, a == 0 ? 24 : (a - 1) * 4);
      else add(b * 8 + mp, 4, 1, mp, 3, hex(qpp[a < 0 ? kx : kx - 7]) * 4);
    }
    if (*cur[b] == 'c') kc++; else kx++;
    cur[b]++;
    tend[b] = bt;
  }
  for (int mp = 0; mp < 8; mp++) add(64 + mp / 4, 4, 1, mp, 3, hex(qpp[15]) * 4);
  for (int cc = 0; cc < NCLUSTER; cc++)
    for (int i = 0; i < cnt[cc]; i++) {
      const int key = p.jobs[cc][i] & 0x3C;
      if (i == 0 || (p.jobs[cc][i - 1] & 0x3C) != key) p.jobs[cc][i] |= (1 << 14);
      if (i == cnt[cc] - 1 || (p.jobs[cc][i + 1] & 0x3C) != key) p.jobs[cc][i] |= (1 << 15);
    }
}

static void build_k2_items(Params& p) {
  int ps[16][3] = {{0, 2, 2}, {0, 4, 0}, {4, 8, 0}, {8, 12, 0}, {12, 16, 1}, {16, 20, 2}, {20, 26, 4}, {0, 32, 0}};
  bool done[256] = {};
  int n = 0;
  for (int i = 0; i < 16; i++)
    for (int j = 7; j >= ps[i][2]; j--)
      for (int h = ps[i][0]; h < ps[i][1]; h++)
        if (!done[h * 8 + j]) { done[h * 8 + j] = true; p.order[n++] = (uint8_t)(h * 8 + j); }
}

static void build_k3_units(Params& p) {
  const char* map = "0123456789abcddcba98765432100123456789abcddcba9876543210feeffeeffe";
  int cnt[16] = {};
  for (int u = 0; u < 66; u++) {
    const int t = (map[u] > '9') ? map[u] - 'a' + 10 : map[u] - '0';
    p.unit[u][0] = (uint8_t)t; p.unit[u][1] = (uint8_t)cnt[t]; p.unit[u][2] = (uint8_t)(cnt[t] * K3_NS);
    cnt[t]++;
  }
  for (int u = 0; u < 66; u++) p.unit[u][3] = (uint8_t)(cnt[p.unit[u][0]] * K3_NS);
}

extern "C" void kernel_launch(void* const* d_in, const int* in_sizes, int n_in, void* d_out, int out_size) {
  const bf16* x = (const bf16*)d_in[0];
  const bf16* wqkv = (const bf16*)d_in[1];
  const bf16* wo = (const bf16*)d_in[2];
  const bf16* ckv = (const bf16*)d_in[4];
  const bf16* w_q = (const bf16*)d_in[5];
  const bf16* w_uk = (const bf16*)d_in[6];
  const bf16* w_uv = (const bf16*)d_in[7];
  const bf16* w_o = (const bf16*)d_in[8];
  const bf16* gate_w = (const bf16*)d_in[9];

  EncFn enc = nullptr;
  cudaDriverEntryPointQueryResult qr;
  cudaGetDriverEntryPoint("cuTensorMapEncodeTiled", (void**)&enc, cudaEnableDefault, &qr);
  void *pK, *pV, *pCtx, *pQA;
  cudaGetSymbolAddress(&pQA, g_QKVA);
  cudaGetSymbolAddress(&pK, g_K);
  cudaGetSymbolAddress(&pV, g_V);
  cudaGetSymbolAddress(&pCtx, g_ctx);

  static Params p;
  enc2d(enc, &p.tmA[0], ckv, DC, S_LEN, 64, 128);
  enc2d(enc, &p.tmA[1], x, DM, S_LEN, 64, 128);
  enc3d(enc, &p.tmW[0], w_uk, HDIM, DC, 16, 4);
  enc3d(enc, &p.tmW[1], w_uv, HDIM, DC, 16, 4);
  enc3d(enc, &p.tmW[2], wqkv, NQKVA, DM, 16, 4);
  enc3d(enc, &p.tmW[3], w_q, HDIM, DM, 16, 4);
  build_k1_jobs(p);
  enc2d(enc, &p.tmK, pK, 64, 64 * S_LEN, 64, 128);
  enc2d(enc, &p.tmV, pV, 64, 64 * S_LEN, 64, 128);
  enc2d(enc, &p.tmQ, pCtx, 64, 73 * S_LEN, 64, 64);
  build_k2_items(p);
  build_k3_units(p);
  for (int i = 0; i < 3; i++) {
    const cuuint64_t cs = S_LEN * 128, nch = (i < 2) ? 27 : 9;
    cuuint64_t gd[4] = {64, S_LEN / 2, i ? 2 : nch, i ? nch : 2}, gs[3] = {256, i ? 128 : cs, i ? cs : 128};
    cuuint32_t bx[4] = {64, i ? 8u : 16u, i ? 2u : 9u, i ? 9u : 2u}, es[4] = {1, 1, 1, 1};
    enc(&p.tmL[i], CU_TENSOR_MAP_DATA_TYPE_BFLOAT16, 4, (i < 2) ? pQA : (void*)((bf16*)pCtx + S_LEN * HDIM), gd, gs, bx, es, CU_TENSOR_MAP_INTERLEAVE_NONE,
        CU_TENSOR_MAP_SWIZZLE_128B, CU_TENSOR_MAP_L2_PROMOTION_L2_256B, CU_TENSOR_MAP_FLOAT_OOB_FILL_NONE);
  }
  enc2d(enc, &p.tmC, pCtx, 64, 73 * S_LEN, 64, 128);
  enc3d(enc, &p.tmO[0], w_o, DM, HDIM, 32, 4);
  enc3d(enc, &p.tmO[1], wo, DM, DM, 32, 4);
  enc2d(enc, &p.tmOt[0], w_o, DM, HDIM, 32, 32, CU_TENSOR_MAP_SWIZZLE_64B);
  enc2d(enc, &p.tmOt[1], wo, DM, DM, 32, 32, CU_TENSOR_MAP_SWIZZLE_64B);
  enc2d(enc, &p.tmR[0], d_out, DM, S_LEN, 64, 16);
  enc2d(enc, &p.tmR[1], d_out, DM, S_LEN, 32, 16, CU_TENSOR_MAP_SWIZZLE_64B);

  cudaFuncSetAttribute(fused_kernel, cudaFuncAttributeMaxDynamicSharedMemorySize, SMEM_BYTES);
  fused_kernel<<<NCLUSTER * 2, 384, SMEM_BYTES>>>(p, x, gate_w, (bf16*)d_out);
}
```

```cpp
#include <cuda_runtime.h>
#include <cuda_bf16.h>
#include <cuda.h>
#include <stdint.h>

typedef __nv_bfloat16 bf16;

constexpr int S_LEN = 2048, DM = 576, DC = 512, HDIM = 4096, NQKVA = 1728, KCAT = 4672;
constexpr int NCLUSTER = 66;
__host__ __device__ constexpr int goff(int G, int r) { return (G >> 1) * S_LEN * 64 + (G & 1) * 32 + r * 512; }

__device__ __align__(1024) bf16 g_K[S_LEN * HDIM];
__device__ __align__(1024) bf16 g_V[S_LEN * HDIM];
__device__ __align__(1024) bf16 g_QKVA[S_LEN * NQKVA + 64];
__device__ __align__(1024) bf16 g_ctx[S_LEN * KCAT];
__device__ float g_gate[S_LEN];
__device__ __align__(16) unsigned int g_sync[400];
constexpr int F_QKVA = 0, F_HP = 16, F_CTX = 32, F_OA = 48, F_CLM = 64, F_GATE = 96, F_TICK = 97, F_DONE = 98, F_XCH = 128, F_EPOCH = 384;

__device__ __forceinline__ uint32_t smem_u32(const void* p) { return (uint32_t)__cvta_generic_to_shared(p); }
__device__ __forceinline__ void mbar_init(uint32_t a, uint32_t c) {
  asm volatile("mbarrier.init.shared::cta.b64 [%0], %1;" ::"r"(a), "r"(c));
}
__device__ __forceinline__ void mbar_expect(uint32_t a, uint32_t b) {
  asm volatile("mbarrier.arrive.expect_tx.shared::cta.b64 _, [%0], %1;" ::"r"(a), "r"(b) : "memory");
}
#define TS(k, i)
#define TSC(k, i)
#define TSM(k)
#define BSEG(i)
#define TB(k)
#define TRC(fl)
#define TCK(i)
#define TP(i)
#define SPIN_LIMIT "4194304"
__device__ __forceinline__ void mbar_wait(uint32_t a, uint32_t parity) {
  asm volatile(
      "{\n.reg .pred p;\n.reg .u32 n;\n"
      "mbarrier.try_wait.parity.shared::cta.b64 p, [%0], %1;\n"
      "@p bra DONE;\n"
      "mov.u32 n, 0;\n"
      "LOOP:\n"
      "mbarrier.try_wait.parity.shared::cta.b64 p, [%0], %1;\n"
      "@p bra DONE;\n"
      "add.u32 n, n, 1;\n"
      "setp.lt.u32 p, n, " SPIN_LIMIT ";\n"
      "@p bra LOOP;\n"
      "DONE:\n}" ::"r"(a), "r"(parity) : "memory");
}
template <int NS>
__device__ __forceinline__ void mbar_wait_ns(uint32_t a, uint32_t parity) {
  asm volatile(
      "{\n.reg .pred p;\n.reg .u32 n;\n"
      "mov.u32 n, 0;\n"
      "LOOP:\n"
      "mbarrier.try_wait.parity.shared::cta.b64 p, [%0], %1, %2;\n"
      "@p bra DONE;\n"
      "add.u32 n, n, 1;\n"
      "setp.lt.u32 p, n, " SPIN_LIMIT ";\n"
      "@p bra LOOP;\n"
      "DONE:\n}" ::"r"(a), "r"(parity), "n"(NS) : "memory");
}
__device__ __forceinline__ void mbar_wait2(uint32_t a, uint32_t pa, uint32_t b, uint32_t pb) {
  asm volatile(
      "{\n.reg .pred p, q;\n.reg .u32 n;\n"
      "mov.u32 n, 0;\n"
      "LOOP:\n"
      "mbarrier.try_wait.parity.shared::cta.b64 p, [%0], %1;\n"
      "mbarrier.try_wait.parity.shared::cta.b64 q, [%2], %3;\n"
      "add.u32 n, n, 1;\n"
      "and.pred p, p, q;\n"
      "setp.lt.and.u32 p, n, " SPIN_LIMIT ", !p;\n"
      "@p bra LOOP;\n"
      "}" ::"r"(a), "r"(pa), "r"(b), "r"(pb) : "memory");
}
__device__ __forceinline__ uint32_t mbar_test(uint32_t a, uint32_t parity) {
  uint32_t r;
  asm volatile("{\n.reg .pred p;\nmbarrier.test_wait.parity.shared::cta.b64 p, [%1], %2;\nselp.u32 %0, 1, 0, p;\n}" : "=r"(r) : "r"(a), "r"(parity) : "memory");
  return r;
}
__device__ __forceinline__ void mbar_arrive(uint32_t a) {
  asm volatile("mbarrier.arrive.shared::cta.b64 _, [%0];" ::"r"(a) : "memory");
}
__device__ __forceinline__ void mbar_arrive_cluster(uint32_t a, uint32_t cta) {
  asm volatile("{\n.reg .b32 r;\nmapa.shared::cluster.u32 r, %0, %1;\nmbarrier.arrive.shared::cluster.b64 _, [r];\n}" ::"r"(a),
               "r"(cta) : "memory");
}
__device__ __forceinline__ void mbar_arrive_cluster_if(uint32_t a, uint32_t cta, bool pred) {
  asm volatile("{\n.reg .b32 r;\n.reg .pred p;\nsetp.ne.u32 p, %2, 0;\nmapa.shared::cluster.u32 r, %0, %1;\n@p mbarrier.arrive.shared::cluster.b64 _, [r];\n}" ::"r"(a),
               "r"(cta), "r"((uint32_t)pred) : "memory");
}
__device__ __forceinline__ void anchor(float v, uint32_t pred) {
  asm volatile("{\n.reg .pred p;\nsetp.ne.u32 p, %1, 0;\n@p st.shared.f32 [%1], %0;\n}" ::"f"(v), "r"(pred) : "memory");
}
__device__ __forceinline__ void mbar_arrive_if(uint32_t a, bool pred) {
  asm volatile("{\n.reg .pred p;\nsetp.ne.u32 p, %1, 0;\n@p mbarrier.arrive.shared::cta.b64 _, [%0];\n}" ::"r"(a), "r"((uint32_t)pred) : "memory");
}
__device__ __forceinline__ void tma2d(uint32_t dst, const CUtensorMap* m, uint32_t bar, int c0, int c1) {
  asm volatile("cp.async.bulk.tensor.2d.shared::cluster.global.mbarrier::complete_tx::bytes [%0], [%1, {%3, %4}], [%2];" ::"r"(dst),
               "l"(m), "r"(bar), "r"(c0), "r"(c1) : "memory");
}
__device__ __forceinline__ void tma2d_mc(uint32_t dst, const CUtensorMap* m, uint32_t bar, int c0, int c1, uint16_t mask) {
  asm volatile(
      "cp.async.bulk.tensor.2d.shared::cluster.global.mbarrier::complete_tx::bytes.multicast::cluster [%0], [%1, {%3, %4}], [%2], %5;" ::"r"(dst),
      "l"(m), "r"(bar), "r"(c0), "r"(c1), "h"(mask) : "memory");
}
__device__ __forceinline__ void tma3d_mc(uint32_t dst, const CUtensorMap* m, uint32_t bar, int c0, int c1, int c2, uint16_t mask) {
  asm volatile(
      "cp.async.bulk.tensor.3d.shared::cluster.global.mbarrier::complete_tx::bytes.multicast::cluster [%0], [%1, {%3, %4, %5}], [%2], %6;" ::"r"(dst),
      "l"(m), "r"(bar), "r"(c0), "r"(c1), "r"(c2), "h"(mask) : "memory");
}
__device__ __forceinline__ void tma3d(uint32_t dst, const CUtensorMap* m, uint32_t bar, int c0, int c1, int c2) {
  asm volatile(
      "cp.async.bulk.tensor.3d.shared::cluster.global.mbarrier::complete_tx::bytes [%0], [%1, {%3, %4, %5}], [%2];" ::"r"(dst),
      "l"(m), "r"(bar), "r"(c0), "r"(c1), "r"(c2) : "memory");
}
__device__ __forceinline__ void tma_pf2d(const CUtensorMap* m, int c0, int c1) {
  asm volatile("cp.async.bulk.prefetch.tensor.2d.L2.global [%0, {%1, %2}];" ::"l"(m), "r"(c0), "r"(c1) : "memory");
}
__device__ __forceinline__ void tma_pf3d(const CUtensorMap* m, int c0, int c1, int c2) {
  asm volatile("cp.async.bulk.prefetch.tensor.3d.L2.global [%0, {%1, %2, %3}];" ::"l"(m), "r"(c0), "r"(c1), "r"(c2) : "memory");
}
__device__ __forceinline__ void prefetch_tmap(const CUtensorMap* m) {
  asm volatile("prefetch.tensormap [%0];" ::"l"(m) : "memory");
}
__device__ __forceinline__ void cluster_arrive() { asm volatile("barrier.cluster.arrive.relaxed.aligned;" ::: "memory"); }
__device__ __forceinline__ void cluster_wait() { asm volatile("barrier.cluster.wait.aligned;" ::: "memory"); }
__device__ __forceinline__ void cluster_sync() {
  cluster_arrive();
  cluster_wait();
}
__device__ __forceinline__ uint32_t cluster_rank() {
  uint32_t r;
  asm volatile("mov.u32 %0, %%cluster_ctarank;" : "=r"(r));
  return r;
}
__device__ __forceinline__ bool elect_one() {
  uint32_t p;
  asm volatile("{\n.reg .pred q;\nelect.sync _|q, 0xffffffff;\nselp.u32 %0, 1, 0, q;\n}" : "=r"(p));
  return p;
}
__device__ __forceinline__ void ldsm_x4(uint32_t& r0, uint32_t& r1, uint32_t& r2, uint32_t& r3, uint32_t addr) {
  asm volatile("ldmatrix.sync.aligned.m8n8.x4.shared.b16 {%0, %1, %2, %3}, [%4];" : "=r"(r0), "=r"(r1), "=r"(r2), "=r"(r3) : "r"(addr) : "memory");
}
__device__ __forceinline__ void wg_fence() { asm volatile("wgmma.fence.sync.aligned;" ::: "memory"); }
__device__ __forceinline__ void wg_commit() { asm volatile("wgmma.commit_group.sync.aligned;" ::: "memory"); }
template <int N>
__device__ __forceinline__ void wg_wait() { asm volatile("wgmma.wait_group.sync.aligned %0;" ::"n"(N) : "memory"); }
template <int N>
__device__ __forceinline__ void reg_alloc() { asm volatile("setmaxnreg.inc.sync.aligned.u32 %0;" ::"n"(N)); }
template <int N>
__device__ __forceinline__ void reg_dealloc() { asm volatile("setmaxnreg.dec.sync.aligned.u32 %0;" ::"n"(N)); }
__device__ __forceinline__ void bar_sync(int id, int n) { asm volatile("bar.sync %0, %1;" ::"r"(id), "r"(n) : "memory"); }
__device__ __forceinline__ void bar_arrive(int id, int n) { asm volatile("bar.arrive %0, %1;" ::"r"(id), "r"(n) : "memory"); }
template <int NT>
__device__ __forceinline__ void fence_regs(float (&d)[NT]) {
#pragma unroll
  for (int i = 0; i < NT; i++) asm volatile("" : "+f"(d[i])::"memory");
}
template <int NT>
__device__ __forceinline__ void fence_regs(uint32_t (&d)[NT]) {
#pragma unroll
  for (int i = 0; i < NT; i++) asm volatile("" : "+r"(d[i])::"memory");
}
__device__ __forceinline__ uint64_t make_desc(uint32_t saddr, uint32_t lbo, uint32_t sbo, uint32_t layout) {
  return (uint64_t)((saddr & 0x3FFFF) >> 4) | ((uint64_t)(lbo >> 4) << 16) | ((uint64_t)(sbo >> 4) << 32) | ((uint64_t)layout << 62);
}
__device__ __forceinline__ uint32_t pack_bf16(float lo, float hi) {
  uint32_t r;
  asm("cvt.rn.bf16x2.f32 %0, %1, %2;" : "=r"(r) : "f"(hi), "f"(lo));
  return r;
}
__device__ __forceinline__ float ex2(float x) {
  float r;
  asm("ex2.approx.ftz.f32 %0, %1;" : "=f"(r) : "f"(x));
  return r;
}
__device__ __forceinline__ void st_v4(void* p, uint32_t a, uint32_t b, uint32_t c, uint32_t d) {
#define ST_MOD ""
  asm volatile("st.global" ST_MOD ".v4.b32 [%0], {%1, %2, %3, %4};" ::"l"(p), "r"(a), "r"(b), "r"(c), "r"(d) : "memory");
}
#define STA_MOD ""
__device__ __forceinline__ void st_v4a(void* p, uint32_t a, uint32_t b, uint32_t c, uint32_t d) {
  asm volatile("st.global" STA_MOD ".v4.b32 [%0], {%1, %2, %3, %4};" ::"l"(p), "r"(a), "r"(b), "r"(c), "r"(d) : "memory");
}
template <typename T>
__device__ __forceinline__ T* ptr_add(T* base, uint32_t bytes) {
  uint64_t r;
  asm volatile("{\n.reg .u32 l, h;\nmov.b64 {l, h}, %1;\nadd.cc.u32 l, l, %2;\naddc.u32 h, h, 0;\nmov.b64 %0, {l, h};\n}" : "=l"(r) : "l"(base), "r"(bytes));
  return reinterpret_cast<T*>(r);
}
__device__ __forceinline__ float bf_lo(uint32_t v) { return __uint_as_float(v << 16); }
__device__ __forceinline__ float bf_hi(uint32_t v) { return __uint_as_float(v & 0xFFFF0000u); }

__device__ __forceinline__ void quad_transpose(uint32_t& a0, uint32_t& a1, uint32_t& a2, uint32_t& a3, int q) {
  const bool o1 = q & 1, o2 = q & 2;
  uint32_t t0 = o1 ? a0 : a1, t1 = o1 ? a2 : a3;
  t0 = __shfl_xor_sync(0xffffffffu, t0, 1);
  t1 = __shfl_xor_sync(0xffffffffu, t1, 1);
  if (o1) { a0 = t0; a2 = t1; } else { a1 = t0; a3 = t1; }
  t0 = o2 ? a0 : a2;
  t1 = o2 ? a1 : a3;
  t0 = __shfl_xor_sync(0xffffffffu, t0, 2);
  t1 = __shfl_xor_sync(0xffffffffu, t1, 2);
  if (o2) { a0 = t0; a1 = t1; } else { a2 = t0; a3 = t1; }
}

template<int TB, int OFF, int NT>
__device__ __forceinline__ void wgmma_ss_n256(float (&d)[NT], uint64_t da, uint64_t db, int scale_d) {
  asm volatile("{\n.reg .pred p;\nsetp.ne.b32 p, %130, 0;\n"
    "wgmma.mma_async.sync.aligned.m64n256k16.f32.bf16.bf16 {%0, %1, %2, %3, %4, %5, %6, %7, %8, %9, %10, %11, %12, %13, %14, %15, %16, %17, %18, %19, %20, %21, %22, %23, %24, %25, %26, %27, %28, %29, %30, %31, %32, %33, %34, %35, %36, %37, %38, %39, %40, %41, %42, %43, %44, %45, %46, %47, %48, %49, %50, %51, %52, %53, %54, %55, %56, %57, %58, %59, %60, %61, %62, %63, %64, %65, %66, %67, %68, %69, %70, %71, %72, %73, %74, %75, %76, %77, %78, %79, %80, %81, %82, %83, %84, %85, %86, %87, %88, %89, %90, %91, %92, %93, %94, %95, %96, %97, %98, %99, %100, %101, %102, %103, %104, %105, %106, %107, %108, %109, %110, %111, %112, %113, %114, %115, %116, %117, %118, %119, %120, %121, %122, %123, %124, %125, %126, %127}, %128, %129, p, 1, 1, 0, %131;\n}\n"
    : "+f"(d[OFF+0]), "+f"(d[OFF+1]), "+f"(d[OFF+2]), "+f"(d[OFF+3]), "+f"(d[OFF+4]), "+f"(d[OFF+5]), "+f"(d[OFF+6]), "+f"(d[OFF+7]), "+f"(d[OFF+8]), "+f"(d[OFF+9]), "+f"(d[OFF+10]), "+f"(d[OFF+11]), "+f"(d[OFF+12]), "+f"(d[OFF+13]), "+f"(d[OFF+14]), "+f"(d[OFF+15]), "+f"(d[OFF+16]), "+f"(d[OFF+17]), "+f"(d[OFF+18]), "+f"(d[OFF+19]), "+f"(d[OFF+20]), "+f"(d[OFF+21]), "+f"(d[OFF+22]), "+f"(d[OFF+23]), "+f"(d[OFF+24]), "+f"(d[OFF+25]), "+f"(d[OFF+26]), "+f"(d[OFF+27]), "+f"(d[OFF+28]), "+f"(d[OFF+29]), "+f"(d[OFF+30]), "+f"(d[OFF+31]), "+f"(d[OFF+32]), "+f"(d[OFF+33]), "+f"(d[OFF+34]), "+f"(d[OFF+35]), "+f"(d[OFF+36]), "+f"(d[OFF+37]), "+f"(d[OFF+38]), "+f"(d[OFF+39]), "+f"(d[OFF+40]), "+f"(d[OFF+41]), "+f"(d[OFF+42]), "+f"(d[OFF+43]), "+f"(d[OFF+44]), "+f"(d[OFF+45]), "+f"(d[OFF+46]), "+f"(d[OFF+47]), "+f"(d[OFF+48]), "+f"(d[OFF+49]), "+f"(d[OFF+50]), "+f"(d[OFF+51]), "+f"(d[OFF+52]), "+f"(d[OFF+53]), "+f"(d[OFF+54]), "+f"(d[OFF+55]), "+f"(d[OFF+56]), "+f"(d[OFF+57]), "+f"(d[OFF+58]), "+f"(d[OFF+59]), "+f"(d[OFF+60]), "+f"(d[OFF+61]), "+f"(d[OFF+62]), "+f"(d[OFF+63]), "+f"(d[OFF+64]), "+f"(d[OFF+65]), "+f"(d[OFF+66]), "+f"(d[OFF+67]), "+f"(d[OFF+68]), "+f"(d[OFF+69]), "+f"(d[OFF+70]), "+f"(d[OFF+71]), "+f"(d[OFF+72]), "+f"(d[OFF+73]), "+f"(d[OFF+74]), "+f"(d[OFF+75]), "+f"(d[OFF+76]), "+f"(d[OFF+77]), "+f"(d[OFF+78]), "+f"(d[OFF+79]), "+f"(d[OFF+80]), "+f"(d[OFF+81]), "+f"(d[OFF+82]), "+f"(d[OFF+83]), "+f"(d[OFF+84]), "+f"(d[OFF+85]), "+f"(d[OFF+86]), "+f"(d[OFF+87]), "+f"(d[OFF+88]), "+f"(d[OFF+89]), "+f"(d[OFF+90]), "+f"(d[OFF+91]), "+f"(d[OFF+92]), "+f"(d[OFF+93]), "+f"(d[OFF+94]), "+f"(d[OFF+95]), "+f"(d[OFF+96]), "+f"(d[OFF+97]), "+f"(d[OFF+98]), "+f"(d[OFF+99]), "+f"(d[OFF+100]), "+f"(d[OFF+101]), "+f"(d[OFF+102]), "+f"(d[OFF+103]), "+f"(d[OFF+104]), "+f"(d[OFF+105]), "+f"(d[OFF+106]), "+f"(d[OFF+107]), "+f"(d[OFF+108]), "+f"(d[OFF+109]), "+f"(d[OFF+110]), "+f"(d[OFF+111]), "+f"(d[OFF+112]), "+f"(d[OFF+113]), "+f"(d[OFF+114]), "+f"(d[OFF+115]), "+f"(d[OFF+116]), "+f"(d[OFF+117]), "+f"(d[OFF+118]), "+f"(d[OFF+119]), "+f"(d[OFF+120]), "+f"(d[OFF+121]), "+f"(d[OFF+122]), "+f"(d[OFF+123]), "+f"(d[OFF+124]), "+f"(d[OFF+125]), "+f"(d[OFF+126]), "+f"(d[OFF+127])
    : "l"(da), "l"(db), "r"(scale_d), "n"(TB));
}
template<int TB, int OFF, int NT>
__device__ __forceinline__ void wgmma_ss_n32(float (&d)[NT], uint64_t da, uint64_t db, int scale_d) {
  asm volatile("{\n.reg .pred p;\nsetp.ne.b32 p, %18, 0;\n"
    "wgmma.mma_async.sync.aligned.m64n32k16.f32.bf16.bf16 {%0, %1, %2, %3, %4, %5, %6, %7, %8, %9, %10, %11, %12, %13, %14, %15}, %16, %17, p, 1, 1, 0, %19;\n}\n"
    : "+f"(d[OFF+0]), "+f"(d[OFF+1]), "+f"(d[OFF+2]), "+f"(d[OFF+3]), "+f"(d[OFF+4]), "+f"(d[OFF+5]), "+f"(d[OFF+6]), "+f"(d[OFF+7]), "+f"(d[OFF+8]), "+f"(d[OFF+9]), "+f"(d[OFF+10]), "+f"(d[OFF+11]), "+f"(d[OFF+12]), "+f"(d[OFF+13]), "+f"(d[OFF+14]), "+f"(d[OFF+15])
    : "l"(da), "l"(db), "r"(scale_d), "n"(TB));
}
template<int TB, int OFF, int NT>
__device__ __forceinline__ void wgmma_rs_n128(float (&d)[NT], uint32_t a0, uint32_t a1, uint32_t a2, uint32_t a3, uint64_t db, int scale_d) {
  asm volatile("{\n.reg .pred p;\nsetp.ne.b32 p, %69, 0;\n"
    "wgmma.mma_async.sync.aligned.m64n128k16.f32.bf16.bf16 {%0, %1, %2, %3, %4, %5, %6, %7, %8, %9, %10, %11, %12, %13, %14, %15, %16, %17, %18, %19, %20, %21, %22, %23, %24, %25, %26, %27, %28, %29, %30, %31, %32, %33, %34, %35, %36, %37, %38, %39, %40, %41, %42, %43, %44, %45, %46, %47, %48, %49, %50, %51, %52, %53, %54, %55, %56, %57, %58, %59, %60, %61, %62, %63}, {%64, %65, %66, %67}, %68, p, 1, 1, %70;\n}\n"
    : "+f"(d[OFF+0]), "+f"(d[OFF+1]), "+f"(d[OFF+2]), "+f"(d[OFF+3]), "+f"(d[OFF+4]), "+f"(d[OFF+5]), "+f"(d[OFF+6]), "+f"(d[OFF+7]), "+f"(d[OFF+8]), "+f"(d[OFF+9]), "+f"(d[OFF+10]), "+f"(d[OFF+11]), "+f"(d[OFF+12]), "+f"(d[OFF+13]), "+f"(d[OFF+14]), "+f"(d[OFF+15]), "+f"(d[OFF+16]), "+f"(d[OFF+17]), "+f"(d[OFF+18]), "+f"(d[OFF+19]), "+f"(d[OFF+20]), "+f"(d[OFF+21]), "+f"(d[OFF+22]), "+f"(d[OFF+23]), "+f"(d[OFF+24]), "+f"(d[OFF+25]), "+f"(d[OFF+26]), "+f"(d[OFF+27]), "+f"(d[OFF+28]), "+f"(d[OFF+29]), "+f"(d[OFF+30]), "+f"(d[OFF+31]), "+f"(d[OFF+32]), "+f"(d[OFF+33]), "+f"(d[OFF+34]), "+f"(d[OFF+35]), "+f"(d[OFF+36]), "+f"(d[OFF+37]), "+f"(d[OFF+38]), "+f"(d[OFF+39]), "+f"(d[OFF+40]), "+f"(d[OFF+41]), "+f"(d[OFF+42]), "+f"(d[OFF+43]), "+f"(d[OFF+44]), "+f"(d[OFF+45]), "+f"(d[OFF+46]), "+f"(d[OFF+47]), "+f"(d[OFF+48]), "+f"(d[OFF+49]), "+f"(d[OFF+50]), "+f"(d[OFF+51]), "+f"(d[OFF+52]), "+f"(d[OFF+53]), "+f"(d[OFF+54]), "+f"(d[OFF+55]), "+f"(d[OFF+56]), "+f"(d[OFF+57]), "+f"(d[OFF+58]), "+f"(d[OFF+59]), "+f"(d[OFF+60]), "+f"(d[OFF+61]), "+f"(d[OFF+62]), "+f"(d[OFF+63])
    : "r"(a0), "r"(a1), "r"(a2), "r"(a3), "l"(db), "r"(scale_d), "n"(TB));
}
template<int TB, int OFF, int NT>
__device__ __forceinline__ void wgmma_rs_n256(float (&d)[NT], uint32_t a0, uint32_t a1, uint32_t a2, uint32_t a3, uint64_t db, int scale_d) {
  asm volatile("{\n.reg .pred p;\nsetp.ne.b32 p, %133, 0;\n"
    "wgmma.mma_async.sync.aligned.m64n256k16.f32.bf16.bf16 {%0, %1, %2, %3, %4, %5, %6, %7, %8, %9, %10, %11, %12, %13, %14, %15, %16, %17, %18, %19, %20, %21, %22, %23, %24, %25, %26, %27, %28, %29, %30, %31, %32, %33, %34, %35, %36, %37, %38, %39, %40, %41, %42, %43, %44, %45, %46, %47, %48, %49, %50, %51, %52, %53, %54, %55, %56, %57, %58, %59, %60, %61, %62, %63, %64, %65, %66, %67, %68, %69, %70, %71, %72, %73, %74, %75, %76, %77, %78, %79, %80, %81, %82, %83, %84, %85, %86, %87, %88, %89, %90, %91, %92, %93, %94, %95, %96, %97, %98, %99, %100, %101, %102, %103, %104, %105, %106, %107, %108, %109, %110, %111, %112, %113, %114, %115, %116, %117, %118, %119, %120, %121, %122, %123, %124, %125, %126, %127}, {%128, %129, %130, %131}, %132, p, 1, 1, %134;\n}\n"
    : "+f"(d[OFF+0]), "+f"(d[OFF+1]), "+f"(d[OFF+2]), "+f"(d[OFF+3]), "+f"(d[OFF+4]), "+f"(d[OFF+5]), "+f"(d[OFF+6]), "+f"(d[OFF+7]), "+f"(d[OFF+8]), "+f"(d[OFF+9]), "+f"(d[OFF+10]), "+f"(d[OFF+11]), "+f"(d[OFF+12]), "+f"(d[OFF+13]), "+f"(d[OFF+14]), "+f"(d[OFF+15]), "+f"(d[OFF+16]), "+f"(d[OFF+17]), "+f"(d[OFF+18]), "+f"(d[OFF+19]), "+f"(d[OFF+20]), "+f"(d[OFF+21]), "+f"(d[OFF+22]), "+f"(d[OFF+23]), "+f"(d[OFF+24]), "+f"(d[OFF+25]), "+f"(d[OFF+26]), "+f"(d[OFF+27]), "+f"(d[OFF+28]), "+f"(d[OFF+29]), "+f"(d[OFF+30]), "+f"(d[OFF+31]), "+f"(d[OFF+32]), "+f"(d[OFF+33]), "+f"(d[OFF+34]), "+f"(d[OFF+35]), "+f"(d[OFF+36]), "+f"(d[OFF+37]), "+f"(d[OFF+38]), "+f"(d[OFF+39]), "+f"(d[OFF+40]), "+f"(d[OFF+41]), "+f"(d[OFF+42]), "+f"(d[OFF+43]), "+f"(d[OFF+44]), "+f"(d[OFF+45]), "+f"(d[OFF+46]), "+f"(d[OFF+47]), "+f"(d[OFF+48]), "+f"(d[OFF+49]), "+f"(d[OFF+50]), "+f"(d[OFF+51]), "+f"(d[OFF+52]), "+f"(d[OFF+53]), "+f"(d[OFF+54]), "+f"(d[OFF+55]), "+f"(d[OFF+56]), "+f"(d[OFF+57]), "+f"(d[OFF+58]), "+f"(d[OFF+59]), "+f"(d[OFF+60]), "+f"(d[OFF+61]), "+f"(d[OFF+62]), "+f"(d[OFF+63]), "+f"(d[OFF+64]), "+f"(d[OFF+65]), "+f"(d[OFF+66]), "+f"(d[OFF+67]), "+f"(d[OFF+68]), "+f"(d[OFF+69]), "+f"(d[OFF+70]), "+f"(d[OFF+71]), "+f"(d[OFF+72]), "+f"(d[OFF+73]), "+f"(d[OFF+74]), "+f"(d[OFF+75]), "+f"(d[OFF+76]), "+f"(d[OFF+77]), "+f"(d[OFF+78]), "+f"(d[OFF+79]), "+f"(d[OFF+80]), "+f"(d[OFF+81]), "+f"(d[OFF+82]), "+f"(d[OFF+83]), "+f"(d[OFF+84]), "+f"(d[OFF+85]), "+f"(d[OFF+86]), "+f"(d[OFF+87]), "+f"(d[OFF+88]), "+f"(d[OFF+89]), "+f"(d[OFF+90]), "+f"(d[OFF+91]), "+f"(d[OFF+92]), "+f"(d[OFF+93]), "+f"(d[OFF+94]), "+f"(d[OFF+95]), "+f"(d[OFF+96]), "+f"(d[OFF+97]), "+f"(d[OFF+98]), "+f"(d[OFF+99]), "+f"(d[OFF+100]), "+f"(d[OFF+101]), "+f"(d[OFF+102]), "+f"(d[OFF+103]), "+f"(d[OFF+104]), "+f"(d[OFF+105]), "+f"(d[OFF+106]), "+f"(d[OFF+107]), "+f"(d[OFF+108]), "+f"(d[OFF+109]), "+f"(d[OFF+110]), "+f"(d[OFF+111]), "+f"(d[OFF+112]), "+f"(d[OFF+113]), "+f"(d[OFF+114]), "+f"(d[OFF+115]), "+f"(d[OFF+116]), "+f"(d[OFF+117]), "+f"(d[OFF+118]), "+f"(d[OFF+119]), "+f"(d[OFF+120]), "+f"(d[OFF+121]), "+f"(d[OFF+122]), "+f"(d[OFF+123]), "+f"(d[OFF+124]), "+f"(d[OFF+125]), "+f"(d[OFF+126]), "+f"(d[OFF+127])
    : "r"(a0), "r"(a1), "r"(a2), "r"(a3), "l"(db), "r"(scale_d), "n"(TB));
}
template<int TB, int OFF, int NT>
__device__ __forceinline__ void wgmma_rs_n32(float (&d)[NT], uint32_t a0, uint32_t a1, uint32_t a2, uint32_t a3, uint64_t db, int scale_d) {
  asm volatile("{\n.reg .pred p;\nsetp.ne.b32 p, %21, 0;\n"
    "wgmma.mma_async.sync.aligned.m64n32k16.f32.bf16.bf16 {%0, %1, %2, %3, %4, %5, %6, %7, %8, %9, %10, %11, %12, %13, %14, %15}, {%16, %17, %18, %19}, %20, p, 1, 1, %22;\n}\n"
    : "+f"(d[OFF+0]), "+f"(d[OFF+1]), "+f"(d[OFF+2]), "+f"(d[OFF+3]), "+f"(d[OFF+4]), "+f"(d[OFF+5]), "+f"(d[OFF+6]), "+f"(d[OFF+7]), "+f"(d[OFF+8]), "+f"(d[OFF+9]), "+f"(d[OFF+10]), "+f"(d[OFF+11]), "+f"(d[OFF+12]), "+f"(d[OFF+13]), "+f"(d[OFF+14]), "+f"(d[OFF+15])
    : "r"(a0), "r"(a1), "r"(a2), "r"(a3), "l"(db), "r"(scale_d), "n"(TB));
}

__device__ __forceinline__ void wait_flag(const unsigned int* f, uint32_t target) {
  uint32_t v;
#pragma unroll 1
  for (uint32_t spins = 0; spins < (1u << 22); spins++) {
    asm volatile("ld.acquire.gpu.global.u32 %0, [%1];" : "=r"(v) : "l"(f) : "memory");
    if (v >= target) break;
    __nanosleep(100);
  }
}
__device__ __forceinline__ uint32_t ld_and2(const unsigned int* f) {
  uint32_t v;
  asm volatile("{\n.reg .b64 t;\n.reg .b32 a, b;\nld.acquire.gpu.global.b64 t, [%1];\nmov.b64 {a, b}, t;\nand.b32 %0, a, b;\n}" : "=r"(v) : "l"(f) : "memory");
  return v;
}
__device__ __forceinline__ uint32_t lds32(uint32_t a) {
  uint32_t v;
  asm volatile("ld.shared.u32 %0, [%1];" : "=r"(v) : "r"(a) : "memory");
  return v;
}
__device__ __forceinline__ float gate_row(int row, int lane, const bf16* __restrict__ x, const bf16* __restrict__ gate_w) {
  const uint32_t* xr = reinterpret_cast<const uint32_t*>(x + (size_t)row * DM);
  const uint32_t* gw2 = reinterpret_cast<const uint32_t*>(gate_w);
  float gs = 0.f;
#pragma unroll
  for (int i = 0; i < 9; i++) {
    const uint32_t a = __ldg(xr + lane + 32 * i), b = __ldg(gw2 + lane + 32 * i);
    gs = fmaf(bf_lo(a), bf_lo(b), gs);
    gs = fmaf(bf_hi(a), bf_hi(b), gs);
  }
#pragma unroll
  for (int o = 16; o; o >>= 1) gs += __shfl_xor_sync(0xffffffffu, gs, o);
  const float g = 1.f / (1.f + __expf(-gs));
  if (lane == 0) g_gate[row] = g;
  return g;
}
constexpr uint32_t LQ = 36864, LV = 55296;
constexpr uint32_t LO = LV + 18432;
__device__ __forceinline__ void mma16(float (&c)[4], uint32_t a0, uint32_t a1, uint32_t a2, uint32_t a3, uint32_t b0, uint32_t b1) {
  asm("mma.sync.aligned.m16n8k16.row.col.f32.bf16.bf16.f32 {%0, %1, %2, %3}, {%4, %5, %6, %7}, {%8, %9}, {%0, %1, %2, %3};"
      : "+f"(c[0]), "+f"(c[1]), "+f"(c[2]), "+f"(c[3]) : "r"(a0), "r"(a1), "r"(a2), "r"(a3), "r"(b0), "r"(b1));
}
__device__ __forceinline__ void mma8(float (&c)[4], uint32_t a0, uint32_t a1, uint32_t b0) {
  asm("mma.sync.aligned.m16n8k8.row.col.f32.bf16.bf16.f32 {%0, %1, %2, %3}, {%4, %5}, {%6}, {%0, %1, %2, %3};"
      : "+f"(c[0]), "+f"(c[1]), "+f"(c[2]), "+f"(c[3]) : "r"(a0), "r"(a1), "r"(b0));
}
template <typename F>
__device__ __forceinline__ void local_attn(int lr0, int warp_g, uint32_t sL, uint32_t bL, uint32_t bL2, int lane, float g0, float g1, F st) {
  const float scale_l2 = 0.23570226039551584f * 1.4426950408889634f;
  const int g = lane >> 2, t = lane & 3;
  const bool lo0 = 2 * t > g, lo1 = 2 * t + 1 > g;
  const bool ok0 = lr0 > 0 || !lo0, ok1 = lr0 > 0 || !lo1;
  const uint32_t mlo = (lo0 ? 0xFFFFu : 0u) | (lo1 ? 0xFFFF0000u : 0u);
  uint32_t ad[9], k[9][4], qf[9][2], pe[4], po[4];
#pragma unroll
  for (int c = 0; c < 9; c++) {
    const uint32_t ch = warp_g * 9 + c;
    ad[c] = sL + (lane >> 4) * 18432 + (lane & 15) * 128 + ((ch >> 3) << 11) + (((ch ^ lane) & 7) << 4);
  }
  st(0, 0u); st(1, 0u);
  mbar_wait(bL, 0);
  if (warp_g == 0) TS(1, 6);
#pragma unroll
  for (int c = 0; c < 9; c++) {
    asm volatile("ldmatrix.sync.aligned.m8n8.x2.shared.b16 {%0, %1}, [%2];" : "=r"(qf[c][0]), "=r"(qf[c][1]) : "r"(ad[c] + LQ) : "memory");
    ldsm_x4(k[c][0], k[c][1], k[c][2], k[c][3], ad[c]);
  }
  st(2, k[0][0]); st(3, k[8][0]);
#pragma unroll
  for (int i = 0; i < 4; i++) {
    const uint32_t q0 = (t >= i) ? qf[2 * i][0] : 0u, q1 = (t >= i) ? qf[2 * i][1] : 0u;
    const uint32_t q4 = (t <= i) ? qf[2 * i + 2][0] : 0u, q5 = (t <= i) ? qf[2 * i + 2][1] : 0u;
    float c[4][4];
#pragma unroll
    for (int T = 0; T < 4; T++) {
#pragma unroll
      for (int j = 0; j < 4; j++) c[T][j] = 0.f;
      mma16(c[T], q0, q1, qf[2 * i + 1][0], qf[2 * i + 1][1], k[2 * i][T], k[2 * i + 1][T]);
      mma8(c[T], q4, q5, k[2 * i + 2][T]);
    }
    const float e0 = ok0 ? (lo0 ? c[0][0] : c[1][0]) : -INFINITY, e1 = ok1 ? (lo1 ? c[0][1] : c[1][1]) : -INFINITY;
    const float o0 = ok0 ? (lo0 ? c[2][2] : c[3][2]) : -INFINITY, o1 = ok1 ? (lo1 ? c[2][3] : c[3][3]) : -INFINITY;
    float me = fmaxf(e0, e1), mo = fmaxf(o0, o1);
    me = fmaxf(me, __shfl_xor_sync(0xffffffffu, me, 1));
    mo = fmaxf(mo, __shfl_xor_sync(0xffffffffu, mo, 1));
    me = fmaxf(me, __shfl_xor_sync(0xffffffffu, me, 2)) * scale_l2;
    mo = fmaxf(mo, __shfl_xor_sync(0xffffffffu, mo, 2)) * scale_l2;
    const float w0 = ex2(fmaf(e0, scale_l2, -me)), w1 = ex2(fmaf(e1, scale_l2, -me));
    const float w2 = ex2(fmaf(o0, scale_l2, -mo)), w3 = ex2(fmaf(o1, scale_l2, -mo));
    float se = w0 + w1, so = w2 + w3;
    st(4 + 2 * i, __float_as_uint(i == 1 ? me : i == 2 ? se : e0));
    se += __shfl_xor_sync(0xffffffffu, se, 1);
    so += __shfl_xor_sync(0xffffffffu, so, 1);
    se += __shfl_xor_sync(0xffffffffu, se, 2);
    so += __shfl_xor_sync(0xffffffffu, so, 2);
    asm("rcp.approx.ftz.f32 %0, %0;" : "+f"(se));
    asm("rcp.approx.ftz.f32 %0, %0;" : "+f"(so));
    se *= g0;
    so *= g1;
    pe[i] = pack_bf16(w0 * se, w1 * se);
    po[i] = pack_bf16(w2 * so, w3 * so);
    st(5 + 2 * i, i == 0 ? __float_as_uint(w0) : i == 2 ? __float_as_uint(mo) : po[i]);
  }
  if (warp_g == 0) TS(0, 4);
  mbar_wait(bL2, 0);
  if (warp_g == 0) TS(0, 5);
#pragma unroll
  for (int c = 0; c < 9; c++)
    asm volatile("ldmatrix.sync.aligned.m8n8.x4.trans.shared.b16 {%0, %1, %2, %3}, [%4];"
                 : "=r"(k[c][0]), "=r"(k[c][1]), "=r"(k[c][2]), "=r"(k[c][3]) : "r"(ad[c] + LV) : "memory");
  mbar_arrive_if(bL + 8, lane == (k[8][3] & blockIdx.y));
#pragma unroll
  for (int i = 0; i < 4; i++) {
#pragma unroll
    for (int n = 0; n < 3; n++) {
      float c[4] = {0.f, 0.f, 0.f, 0.f};
      mma16(c, pe[i] & mlo, 0u, pe[i] & ~mlo, 0u, k[2 * i + n][0], k[2 * i + n][1]);
      mma16(c, 0u, po[i] & mlo, 0u, po[i] & ~mlo, k[2 * i + n][2], k[2 * i + n][3]);
      const uint32_t r0 = pack_bf16(c[0], c[1]), r1 = pack_bf16(c[2], c[3]);
      const bool keep = (n == 0) && (i > 0) && (t < i);
      qf[2 * i + n][0] = keep ? qf[2 * i + n][0] : r0;
      qf[2 * i + n][1] = keep ? qf[2 * i + n][1] : r1;
    }
    st(12 + i, qf[2 * i + 1][0]);
  }
#pragma unroll
  for (int c = 0; c < 9; c++)
    asm volatile("stmatrix.sync.aligned.m8n8.x2.shared.b16 [%0], {%1, %2};" ::"r"(ad[c] + LO), "r"(qf[c][0]), "r"(qf[c][1]) : "memory");
  asm volatile("fence.proxy.async.shared::cta;" ::: "memory");
}
__device__ __forceinline__ void tma4d(uint32_t dst, const CUtensorMap* m, uint32_t bar, int c1, int c2, int c3) {
  asm volatile("cp.async.bulk.tensor.4d.shared::cluster.global.mbarrier::complete_tx::bytes [%0], [%1, {%3, %4, %5, %6}], [%2];" ::"r"(dst),
               "l"(m), "r"(bar), "r"(0), "r"(c1), "r"(c2), "r"(c3) : "memory");
}

#define ST_NUM 1
#define ST_DEN 2
#define ALEAD 3
#define LLK 4
#define LLX 2
#define K1_NST 6
constexpr int K1_BST = K1_NST;
#define MAXJ 10
constexpr int K1_MAXJOBS = MAXJ;
constexpr uint32_t K1_FLAG_TARGET = 7;
constexpr uint32_t RDY_TARGET = 48;
constexpr uint32_t GATE_TARGET = 128 * 3;
struct alignas(64) Params {
  CUtensorMap tmA[2];
  CUtensorMap tmW[4];
  uint16_t jobs[NCLUSTER][K1_MAXJOBS + 1];
  CUtensorMap tmK, tmV, tmQ;
  CUtensorMap tmL[3];
  CUtensorMap tmC, tmO[2], tmOt[2];
  CUtensorMap tmR[2];
  uint8_t order[256];
  uint8_t unit[66][4];
};

struct K1State {
  uint32_t bs, bph, aph;
  bf16* pp;
  int png;
  int tn;
  int wsel;
  uint32_t fo;
};
__device__ __forceinline__ void k1_flag(const K1State& st, int lane, uint32_t bS) {
  if (st.png) {
    __syncwarp();
    if (lane == 0) mbar_arrive(bS + st.fo);
  }
}

__device__ __forceinline__ void scale_q4(uint32_t* v) {
#pragma unroll
  for (int i = 0; i < 4; i++)
    asm volatile("{\n.reg .b32 t;\nmul.rn.bf16x2 t, %0, %2;\nfma.rn.bf16x2 %0, %0, %1, t;\n}" : "+r"(v[i]) : "r"(0x3E033E03u), "r"(0xB9D8B9D8u));
}
__device__ __forceinline__ void k1_first(const K1State& st, uint32_t job, uint32_t bAf, uint32_t bBf) {
  if (job & 3) {
    if ((job >> 14) & 1) mbar_wait(bAf, st.aph);
    mbar_wait(bBf + st.bs * 8, st.bph);
  }
}
__device__ __forceinline__ void k1_tile(float (&acc)[128], uint32_t (&pk)[64], K1State& st, uint32_t job, uint32_t njob, uint32_t sA, uint32_t sB,
                                        uint32_t bAf, uint32_t bAe, uint32_t bBf, uint32_t bBe, uint32_t bS, int wg, int warp, int lane, uint32_t rank) {
  const int a_sel = (job >> 2) & 1, mpair = (job >> 3) & 7, w_sel = (job >> 6) & 3, chunk0 = (job >> 8) & 63;
  const bool newA = (job >> 14) & 1, lastA = (job >> 15) & 1;
  const bool sig = (lane == 0) && (warp < 2);
  const bool siga = lastA && (lane == 0) && (warp == 2);
  const int KC = 8 + a_sel;
  const int lpos = (njob & 3) ? (a_sel ? 99 : 16 - ALEAD) : (a_sel ? 18 - LLX : 16 - LLK);
  uint32_t prev_bs = 0, a8_bs = 0;
#pragma unroll
  for (int kc = 0; kc < 9; kc++) {
    if (kc >= KC) break;
    uint32_t abase = sA + ((kc + 2) & 7) * 16384;
    if (kc == 8) {
      mbar_wait(bBf + st.bs * 8, st.bph);
      a8_bs = st.bs;
      abase = sB + st.bs * 16384;
      if (++st.bs == K1_BST) { st.bs = 0; st.bph ^= 1; }
    } else if (newA && kc > 0) {
      mbar_wait(bAf + kc * 8, st.aph);
    }
    const uint64_t da = make_desc(abase + wg * 8192, 16, 1024, 1);
#pragma unroll
    for (int ks = 0; ks < 2; ks++) {
      if (ks > 0 || kc > 0) mbar_wait(bBf + st.bs * 8, st.bph);
      const uint64_t db = make_desc(sB + st.bs * 16384, 2048, 1024, 1);
      if ((kc * 2 + ks == 16 - ALEAD || kc * 2 + ks == 16 - LLK || kc * 2 + ks == 18 - LLX) && kc * 2 + ks == lpos && wg == 1) bar_sync(4, 256);
      wg_fence();
      wgmma_ss_n256<1, 0>(acc, da + (uint64_t)(ks * 4), db, (ks > 0) ? 1 : (kc > 0));
      wgmma_ss_n256<1, 0>(acc, da + (uint64_t)(ks * 4 + 2), db + (uint64_t)512, 1);
      wg_commit();
      if (kc == 7 && ks == 1 && !a_sel && wg == 0) bar_arrive(4, 256);
      if (kc == 8 && ks == 1 && !(njob & 3) && wg == 0) bar_arrive(4, 256);
      wg_wait<1>();
      if (ks > 0 || kc > 0) {
        if (sig) mbar_arrive_cluster(bBe + prev_bs * 8, warp);
        if (ks == 0 && siga) mbar_arrive(bAe + (kc - 1) * 8);
      }
      if (st.wsel == 2) {
        const int i = (kc & 7) * 2 + ks;
        if (kc < st.png) {
          quad_transpose(pk[i * 4], pk[i * 4 + 1], pk[i * 4 + 2], pk[i * 4 + 3], lane & 3);
          st_v4a(st.pp + goff(kc, ks), pk[i * 4], pk[i * 4 + 1], pk[i * 4 + 2], pk[i * 4 + 3]);
        }
        if (i == 15) k1_flag(st, lane, bS);
      } else if (st.png) {
#pragma unroll
        for (int i = 0; i < 16; i++) {
          if (i * ST_NUM / ST_DEN != kc * 2 + ks) continue;
          if (st.wsel == 3) scale_q4(pk + i * 4);
          st_v4a(st.pp + goff(i / 2, i & 1), pk[i * 4], pk[i * 4 + 1], pk[i * 4 + 2], pk[i * 4 + 3]);
          if (i == 15) k1_flag(st, lane, bS);
        }
      }
      prev_bs = st.bs;
      if (++st.bs == K1_BST) { st.bs = 0; st.bph ^= 1; }
    }
  }
  if (newA) st.aph ^= 1;
  const bool isA = (w_sel == 2);
  bf16* out = (w_sel == 0) ? g_K : (w_sel == 1) ? g_V : isA ? g_QKVA : g_ctx;
  const int row = mpair * 256 + rank * 128 + wg * 64 + warp * 16 + (lane >> 2);
  st.pp = ptr_add(out, (chunk0 * S_LEN + row) * 128 + (lane & 3) * 16);
  st.png = ((job & 3) + 1) * 2;
  st.wsel = w_sel;
  st.fo = (st.fo + 8) & 24;
  k1_first(st, njob, bAf, bBf);
  wg_wait<0>();
  fence_regs(acc);
  mbar_arrive_cluster_if(bBe + prev_bs * 8, warp & 1, sig);
  mbar_arrive_cluster_if(bBe + a8_bs * 8, warp & 1, sig && a_sel);
  mbar_arrive_if(bAe + 7 * 8, siga && !a_sel);
#pragma unroll
  for (int i = 0; i < 64; i++) {
    const int j = (i >> 3) * 16 + (i & 3) * 4 + ((i >> 2) & 1) * 2;
    pk[i] = pack_bf16(acc[j], acc[j + 1]);
  }
}

constexpr int K2_NST = 7;
constexpr uint32_t K2_END = 0x100;
#define PFD 4
#define PF3A 2
#define PF3 6
#define KC0 1
constexpr uint32_t CR = 4;
#define FIRST_DRAW 3
#define PWAIT mbar_wait_ns<1000>
#define PVM 0x8A
#define W0 63
#define SPEC_HI 1.8446744073709552e19f
#define SPEC_LO 5.421010862427522e-20f
constexpr int K3_NST = 4;
#define K3_NS 6
__device__ __forceinline__ uint32_t k3_rot(uint32_t sv) { return (0x00E9u >> (2 * sv)) & 3; }
constexpr int K3_STAGE = 16384 + 32768 + 4096;
constexpr int SMEM_DATA = 7 * 32768;
constexpr int SMEM_BYTES = SMEM_DATA + 1024 + 896;

struct Cursor {
  uint32_t s, ph;
  __device__ __forceinline__ void next() {
    if (++s == K2_NST) { s = 0; ph ^= 1; }
  }
};

#define TURN_SYNC() bar_sync(mybar, 256)
#define TURN_ARRIVE() bar_arrive(otherbar, 256)
#define RELEASE_IF(cur, cond) mbar_arrive_cluster_if(bE + (cur).s * 8, warp & 1, sig && (cond))
#define RELEASE(cur) RELEASE_IF(cur, true)
#define ISSUE_PV(cur, first)                                                                                   \
  do {                                                                                                         \
    const uint64_t dv = make_desc(sbase + (cur).s * 32768, 16384, 1024, 1);                                    \
    _Pragma("unroll") for (int t = 0; t < 8; t++)                                                              \
        wgmma_rs_n128<1, 0>(O, P[4 * t], P[4 * t + 1], P[4 * t + 2], P[4 * t + 3], dv + (uint64_t)(t * 128), (t > 0) ? 1 : !(first)); \
  } while (0)
#define ISSUE_QK(cur)                                                                                          \
  do {                                                                                                         \
    const uint64_t dk = make_desc(sbase + (cur).s * 32768, 16, 1024, 1);                                       \
    _Pragma("unroll") for (int t = 0; t < 8; t++)                                                              \
        wgmma_rs_n128<0, 0>(S, Q[4 * t], Q[4 * t + 1], Q[4 * t + 2], Q[4 * t + 3], dk + (uint64_t)((t >> 2) * 1024 + (t & 3) * 2), t > 0); \
  } while (0)
#define LOAD_Q()                                                                                               \
  do {                                                                                                         \
    item = lds32(sItem + (it & 7) * 4);                                                                        \
    const uint32_t qa = sbase + cq.s * 32768 + (wg * 64 + warp * 16 + (lane & 15)) * 128;                      \
    _Pragma("unroll") for (int t = 0; t < 8; t++)                                                              \
        ldsm_x4(Q[4 * t], Q[4 * t + 1], Q[4 * t + 2], Q[4 * t + 3], qa + (t >> 2) * 16384 + ((((t & 3) * 2 + (lane >> 4)) ^ (lane & 7)) << 4)); \
  } while (0)
#define NEW_ITEM()                                                                                             \
  do {                                                                                                         \
    const int row = (2 * (item & 7) + hi) * 128 + (rank ^ hi) * 64 + warp * 16 + (lane >> 2);                  \
    eoff = ((item >> 3) * 2 * S_LEN + row) * 128 + q * 16;                                                     \
    const float* gp = ptr_add(g_gate, row * 4);                                                                \
    asm volatile("ld.global.f32 %0, [%1];" : "=f"(gf0) : "l"(gp));                                             \
    asm volatile("ld.global.f32 %0, [%1];" : "=f"(gf1) : "l"(gp + 8));                                         \
    if (!hi) {                                                                                                 \
      mbar_wait2(bF + cs0.s * 8, cs0.ph, bF + cs1.s * 8, cs1.ph);                                              \
      RELEASE(cs0);                                                                                            \
      RELEASE(cs1);                                                                                            \
    }                                                                                                          \
  } while (0)
#define EXPB(T)                                                                                                \
  do {                                                                                                         \
    _Pragma("unroll") for (int i = 4 * T; i < 4 * T + 4; i++) asm volatile("" : "+r"(P[i])::"memory");        \
    _Pragma("unroll") for (int jj = 2 * T; jj < 2 * T + 2; jj++) {                                             \
      const float e0 = ex2(S[jj * 4 + 0]), e1 = ex2(S[jj * 4 + 1]), e2 = ex2(S[jj * 4 + 2]), e3 = ex2(S[jj * 4 + 3]); \
      s0 += e0 + e1;                                                                                           \
      s1 += e2 + e3;                                                                                           \
      P[jj * 2 + 0] = pack_bf16(e0, e1);                                                                       \
      P[jj * 2 + 1] = pack_bf16(e2, e3);                                                                       \
    }                                                                                                          \
  } while (0)
#define EXPC(T)                                                                                                \
  do {                                                                                                         \
    if (T > 0 && ((PVM >> (T - 1)) & 1)) {                                                                     \
      anchor((T & 2) ? s0 : s1, never);                                                                        \
      wg_wait<__builtin_popcount(PVM >> T) - 1>();                                                             \
      if ((PVM >> T) == (128 >> T)) { fence_regs(O); RELEASE(cv); }                                            \
    }                                                                                                          \
    EXPB(T);                                                                                                   \
  } while (0)
#define MASK(G, g)                                                                                             \
  do {                                                                                                         \
    if ((g) * 8 > d) S[(G) * 4 + 0] = -INFINITY;                                                               \
    if ((g) * 8 + 1 > d) S[(G) * 4 + 1] = -INFINITY;                                                           \
    if ((g) * 8 - 8 > d) S[(G) * 4 + 2] = -INFINITY;                                                           \
    if ((g) * 8 - 7 > d) S[(G) * 4 + 3] = -INFINITY;                                                           \
  } while (0)
#define STORE_O(G)                                                                                             \
  do {                                                                                                         \
    st_v4(optr + goff(G, 0), pack_bf16(O[(G) * 16 + 0] * f0, O[(G) * 16 + 1] * f0), pack_bf16(O[(G) * 16 + 4] * f0, O[(G) * 16 + 5] * f0), \
          pack_bf16(O[(G) * 16 + 8] * f0, O[(G) * 16 + 9] * f0), pack_bf16(O[(G) * 16 + 12] * f0, O[(G) * 16 + 13] * f0)); \
    st_v4(optr + goff(G, 1), pack_bf16(O[(G) * 16 + 2] * f1, O[(G) * 16 + 3] * f1), pack_bf16(O[(G) * 16 + 6] * f1, O[(G) * 16 + 7] * f1), \
          pack_bf16(O[(G) * 16 + 10] * f1, O[(G) * 16 + 11] * f1), pack_bf16(O[(G) * 16 + 14] * f1, O[(G) * 16 + 15] * f1)); \
  } while (0)

#define FLUSH()                                                                                                \
  do {                                                                                                         \
    _Pragma("unroll") for (int G = 0; G < 8; G++) {                                                            \
      st_v4a(st.pp + goff(G, 0), pk[G * 8], pk[G * 8 + 1], pk[G * 8 + 2], pk[G * 8 + 3]);                          \
      st_v4a(st.pp + goff(G, 1), pk[G * 8 + 4], pk[G * 8 + 5], pk[G * 8 + 6], pk[G * 8 + 7]);                     \
    }                                                                                                          \
    k1_flag(st, lane, bS);                                                                                     \
  } while (0)

__global__ void __cluster_dims__(2, 1, 1) __launch_bounds__(384, 1)
fused_kernel(const __grid_constant__ Params p, const bf16* __restrict__ x, const bf16* __restrict__ gate_w, bf16* __restrict__ out) {
  extern __shared__ uint8_t smem_raw[];
  const uint32_t sbase = (smem_u32(smem_raw) + 1023) & ~1023u;
  const uint32_t sB = sbase, sA = sbase + K1_BST * 16384, sBar = sbase + SMEM_DATA;
  const uint32_t bAf = sBar, bAe = sBar + 64, bBf = sBar + 128, bBe = sBar + 176, bL = sBar + 224, bS = sBar + 656, bL2 = sBar + 240, sL = sA + 32768;
  const uint32_t bF = sBar + 256, bE = sBar + 320, bT = sBar + 384, sTick = sBar + 400, sItem = sBar + 416, bS2 = sBar + 688, bR = sBar + 456, bLast = sBar + 464, bH = sBar + 472, bT0 = sBar + 480, bZ = sBar + 488, bLd = sBar + 496, bG = sBar + 504;
  const uint32_t b3F = sBar + 512, b3E = sBar + 544, sGate = sBar + 576, sK1 = sBar + 720, sClm = sBar + 768;
  const int tid = threadIdx.x, warp_g = __shfl_sync(0xffffffffu, tid >> 5, 0), lane = tid & 31;
  const uint32_t rank = cluster_rank();
  const int cl = blockIdx.x >> 1;
  TSM(0);
  if (tid == 256) {
    const uint32_t job = p.jobs[cl][0];
#pragma unroll
    for (int i = 0; i < KC0; i++) { mbar_init(bAf + i * 8, 1); mbar_init(bBf + i * 16, 1); mbar_init(bBf + i * 16 + 8, 1); }
    asm volatile("fence.mbarrier_init.release.cluster;" ::: "memory");
#pragma unroll 1
    for (int i = 0; i < 4 * KC0; i++) {
      if (!(i & 3)) {
        mbar_expect(bAf + i * 2, 16384);
        tma2d(sA + (i / 4 + 2) * 16384, &p.tmA[(job >> 2) & 1], bAf + i * 2, i * 16, ((job >> 3) & 7) * 256 + rank * 128);
      }
      if (!(i & 1)) mbar_expect(bBf + i * 4, 16384);
      tma3d(sB + i * 8192, &p.tmW[(job >> 6) & 3], bBf + (i >> 1) * 8, 0, i * 16, (job >> 8) & 63);
    }
  }
  if (warp_g == 1) asm volatile("st.shared.u32 [%0], %1;" ::"r"(lane ? sClm - 4 + lane * 4 : sK1), "r"(lane ? 0xFFFFFFFFu : 80u) : "memory");
  if (tid == 0) {
    for (int i = 0; i < 8; i++) { if (i >= KC0) mbar_init(bAf + i * 8, 1); mbar_init(bAe + i * 8, 2); }
    for (int i = 0; i < K1_BST; i++) { if (i >= 2 * KC0) mbar_init(bBf + i * 8, 1); mbar_init(bBe + i * 8, 4); }
    mbar_init(bL, 1);
    mbar_init(bL2, 1);
    mbar_init(bL + 8, 8);
    mbar_init(bR, 1);
    mbar_init(bLast, 1);
    mbar_init(bH, 4);
    mbar_init(bT0, 1);
    mbar_init(bZ, 1);
    mbar_init(bLd, 4);
    mbar_init(bG, 3);
    for (int i = 0; i < 8; i++) mbar_init(bS + i * 8, 8);
    for (int i = 0; i < K2_NST; i++) { mbar_init(bF + i * 8, 1); mbar_init(bE + i * 8, 4); }
    mbar_init(bT, 1); mbar_init(bT + 8, 1);
    for (int i = 0; i < K3_NST; i++) { mbar_init(b3F + i * 8, 1); mbar_init(b3E + i * 8, 4); }
    asm volatile("fence.mbarrier_init.release.cluster;" ::: "memory");
  }
  __syncwarp();
  if (warp_g != 8) cluster_sync();
  const int lr0 = blockIdx.x * 16;

  if (warp_g >= 8) {
    reg_dealloc<40>();
    if (warp_g == 8) {
      {
        __syncwarp();
        cluster_sync();
      }
      if (elect_one()) {
        uint32_t bs = (2 * KC0) % K1_BST, bph = (2 * KC0 < K1_BST), aph = 1;
#pragma unroll 1
        for (int ji = 0; ji < K1_MAXJOBS; ji++) {
          const uint32_t job = p.jobs[cl][ji];
          if (!(job & 3)) break;
          const int a_sel = (job >> 2) & 1, mpair = (job >> 3) & 7, chunk0 = (job >> 8) & 63;
          const bool newA = (job >> 14) & 1;
          const int KC = a_sel ? 9 : 8;
          const uint32_t halfbytes = 8192;
          const bool lastjob = (ji + 1 == K1_MAXJOBS) || !(p.jobs[cl][ji + 1] & 3);
          const CUtensorMap* tw = &p.tmW[(job >> 6) & 3];
          {
            const uint32_t njob = (ji + 1 < K1_MAXJOBS) ? p.jobs[cl][ji + 1] : 0;
            if (!(njob & 3) && !newA) mbar_arrive(bLast);
          }
#pragma unroll 1
          for (int kc = ji ? 0 : KC0; kc < KC; kc++) {
            {
              const bool nx = kc + PFD >= KC;
              const uint32_t njob = nx ? p.jobs[cl][ji + 1] : job;
              const int pk = nx ? kc + PFD - KC : kc + PFD;
              if ((njob & 3) && (nx || ji > 0)) {
                if (cl >= 64 || ((pk ^ (cl >> 1)) & 3) == 0)
                  tma_pf3d(&p.tmW[(njob >> 6) & 3], 0, pk * 64 + (cl & 1) * 32 + rank * 16, (njob >> 8) & 63);
                if (((njob >> 14) & 1) || pk == 8) tma_pf2d(&p.tmA[(njob >> 2) & 1], pk * 64, ((njob >> 3) & 7) * 256 + rank * 128);
              }
            }
            if (kc == 8) {
              PWAIT(bBe + bs * 8, bph);
              mbar_expect(bBf + bs * 8, 16384);
              tma2d(sB + bs * 16384, &p.tmA[1], bBf + bs * 8, 512, mpair * 256 + rank * 128);
              if (++bs == K1_BST) { bs = 0; bph ^= 1; }
            } else if (newA) {
              PWAIT(bAe + kc * 8, aph);
              mbar_expect(bAf + kc * 8, 16384);
              tma2d(sA + ((kc + 2) & 7) * 16384, &p.tmA[a_sel], bAf + kc * 8, kc * 64, mpair * 256 + rank * 128);
              if (kc == 7 && lastjob) mbar_arrive(bLast);
            }
#pragma unroll 1
            for (int kk = 0; kk < 2; kk++) {
              PWAIT(bBe + bs * 8, bph);
              mbar_expect(bBf + bs * 8, 2 * halfbytes);
              tma3d_mc(sB + bs * 16384 + rank * halfbytes, tw, bBf + bs * 8, 0, kc * 64 + kk * 32 + rank * 16, chunk0, 3);
              if (++bs == K1_BST) { bs = 0; bph ^= 1; }
            }
          }
          if (newA) aph ^= 1;
        }
        Cursor c{0, 0};
        int pcol = 0;
        PWAIT(bR, 0);
        uint32_t tick = lds32(sTick + 8), seen = 1u << (p.order[tick] >> 4);
        asm volatile("fence.proxy.async.global;" ::: "memory");
#pragma unroll 1
        for (int it = 0;; it++) {
          const uint32_t item = (tick < 256) ? p.order[tick] : (K2_END | min(tick - 256, 255u));
          asm volatile("st.shared.u32 [%0], %1;" ::"r"(sItem + (it & 7) * 4), "r"(item) : "memory");
          if (item >= K2_END) break;
          const int h = item >> 3, j = item & 7;
          const int col = (h * 2 + rank) * S_LEN;
          const int nb = 2 * j + 2;
          if (!((seen >> (h >> 1)) & 1)) {
            wait_flag(&g_sync[F_HP + (h >> 1)], RDY_TARGET);
            asm volatile("fence.proxy.async.global;" ::: "memory");
            seen |= 1u << (h >> 1);
          }
          PWAIT(bE + c.s * 8, c.ph);
          mbar_expect(bF + c.s * 8, 32768);
#pragma unroll 1
          for (int i = 0; i < 4; i++) {
            const int hi = (i ^ it ^ 1) & 1;
            tma2d(sbase + c.s * 32768 + i * 8192, &p.tmQ, bF + c.s * 8, 0, (h * 2 + (i >> 1)) * S_LEN + (2 * j + hi) * 128 + (rank ^ hi) * 64);
          }
          c.next();
          if (tick >= 256 - 73) {
            const int kk = tick - (256 - 73), sel = (kk < 9), kr = (sel ? kk : kk - 9) * 64 + rank * 32;
#pragma unroll 1
            for (int i = 0; i < 2; i++) {
              tma_pf3d(&p.tmO[sel], 0, kr, i * 4);
              tma_pf2d(&p.tmOt[sel], 512 + i * 32, kr);
            }
          }
#pragma unroll 1
          for (int n = nb - 1; n >= 0; n--) {
            if (n == 0 && rank == 0) tick = atomicAdd(&g_sync[F_TICK], 1u);
            PWAIT(bE + c.s * 8, c.ph);
            mbar_expect(bF + c.s * 8, 32768);
            tma2d_mc(sbase + c.s * 32768 + rank * 16384, &p.tmK, bF + c.s * 8, 0, col + n * 128, 3);
            c.next();
            if (n < nb - 1 || it > 0) {
              PWAIT(bE + c.s * 8, c.ph);
              mbar_expect(bF + c.s * 8, 32768);
              tma2d_mc(sbase + c.s * 32768 + rank * 16384, &p.tmV, bF + c.s * 8, 0, (n < nb - 1) ? col + (n + 1) * 128 : pcol, 3);
              c.next();
            }
          }
          pcol = col;
          if (rank == 0) {
            asm volatile(
                "{\n.reg .b32 a, b;\nmapa.shared::cluster.u32 a, %0, 1;\nmapa.shared::cluster.u32 b, %1, 1;\n"
                "st.async.shared::cluster.mbarrier::complete_tx::bytes.u32 [a], %2, [b];\n}" ::"r"(sTick + (it & 1) * 4),
                "r"(bT + (it & 1) * 8), "r"(tick) : "memory");
          } else {
            mbar_expect(bT + (it & 1) * 8, 4);
            PWAIT(bT + (it & 1) * 8, (it >> 1) & 1);
            tick = lds32(sTick + (it & 1) * 4);
          }
        }
        PWAIT(bE + c.s * 8, c.ph);
        mbar_expect(bF + c.s * 8, 32768);
        tma2d_mc(sbase + c.s * 32768 + rank * 16384, &p.tmV, bF + c.s * 8, 0, pcol, 3);
        const uint32_t unit = tick - 256;
        const int mblk = (7 - (p.unit[unit][0] >> 1)) * 2 + rank, nhalf = p.unit[unit][0] & 1;
        uint32_t have, hoa;
        have = ld_and2(&g_sync[F_CTX + (mblk & ~1)]);
        asm volatile("ld.acquire.gpu.global.u32 %0, [%1];" : "=r"(hoa) : "l"(&g_sync[F_OA + mblk]) : "memory");
        asm volatile("fence.proxy.async.global;" ::: "memory");
#pragma unroll 1
        for (uint32_t idx = PF3A; idx < PF3; idx++) {
          const int kk = p.unit[unit][2] + idx;
          if ((kk < 9) ? (hoa >= 8) : ((have >> ((kk - 9) >> 1)) & 1)) tma_pf2d(&p.tmC, 0, ((kk < 9) ? 64 + kk : kk - 9) * S_LEN + mblk * 128);
        }
        {
          const uint32_t rot = k3_rot(c.s), nfree = ((0x1Au >> c.s) & 1) ? 2 : 3;
          uint32_t kq = p.unit[unit][2] * 0x01010101u + 0x03020100u, k1 = 80, idx = 0, pa = 0, pb = 0;
          auto step = [&](uint32_t& pend) {
            uint32_t nxt = (kq & 255) + CR;
            if (idx + CR >= K3_NS && k1 == 80) {
              if (rank == 0) {
                nxt = min(pend + p.unit[unit][3], 73u);
                asm volatile("{\n.reg .b32 a;\nmapa.shared::cluster.u32 a, %0, 1;\nst.volatile.shared::cluster.u8 [a], %1;\n}" ::"r"(sClm + idx), "r"(nxt) : "memory");
              } else {
#pragma unroll 1
                for (uint32_t spins = 0; spins < (1u << 22); spins++) {
                  asm volatile("ld.volatile.shared.u8 %0, [%1];" : "=r"(nxt) : "r"(sClm + idx) : "memory");
                  if (nxt != 255) break;
                  __nanosleep(20);
                }
              }
              if (nxt >= 73) {
                k1 = idx + CR;
                asm volatile("st.shared.u32 [%0], %1;" ::"r"(sK1), "r"(k1) : "memory");
              }
            }
            const uint32_t kk = kq & 255;
            if (idx < 12) TP(idx);
            kq = (kq >> 8) | (nxt << (8 * CR - 8));
            const uint32_t s = (rot + idx) & 3;
            if (idx >= nfree) PWAIT((idx < 4) ? bH : b3E + s * 8, (idx < 4) ? 0 : (~idx >> 2) & 1);
#pragma unroll 1
            while (idx < nfree && c.s != ((0x6431u >> (4 * s)) & 15)) {
              c.next();
              PWAIT(bE + c.s * 8, c.ph);
            }
            if (idx < 12) TP(12 + idx);
            mbar_expect(b3F + s * 8, K3_STAGE);
            const uint32_t st = sbase + s * K3_STAGE;
            const int sel = (kk < 9), k = sel ? kk : kk - 9, kr = k * 64 + rank * 32;
            tma3d_mc(st + 16384 + rank * 16384, &p.tmO[sel], b3F + s * 8, 0, kr, nhalf * 4, 3);
            tma2d_mc(st + 49152 + rank * 2048, &p.tmOt[sel], b3F + s * 8, 512 + nhalf * 32, kr, 3);
            if (rank == 0 && idx + CR + 2 >= K3_NS && k1 == 80) pend = atomicAdd(&g_sync[F_CLM + p.unit[unit][0]], 1u);
            if (sel && hoa < 8) {
              wait_flag(&g_sync[F_OA + mblk], 8);
              hoa = 8;
              asm volatile("fence.proxy.async.global;" ::: "memory");
            }
            if (!sel && !((have >> (k >> 1)) & 1)) {
#pragma unroll 1
              for (uint32_t spins = 0; spins < (1u << 22); spins++) {
                have = ld_and2(&g_sync[F_CTX + (mblk & ~1)]);
                if ((have >> (k >> 1)) & 1) break;
                __nanosleep(100);
              }
              asm volatile("fence.proxy.async.global;" ::: "memory");
            }
            tma2d(st, &p.tmC, b3F + s * 8, 0, (sel ? 64 + k : k) * S_LEN + mblk * 128);
            if (idx < 12) TP(24 + idx);
            return ++idx >= k1;
          };
#pragma unroll 1
          for (;;) {
            if (step(pa)) break;
            if (step(pb)) break;
          }
          asm volatile("" ::"r"(pa), "r"(pb) : "memory");
        }
      }
    }
    __syncwarp();
    if (warp_g == 8) {
      uint32_t v = 0;
      if (lane == 0) {
        __threadfence();
        v = atomicAdd(&g_sync[F_DONE], 1u);
      }
      if (__shfl_sync(0xffffffffu, v, 0) == 2 * NCLUSTER - 1) {
        reinterpret_cast<uint4*>(g_sync)[lane] = make_uint4(0, 0, 0, 0);
        if (lane == 0) g_sync[F_EPOCH] = lds32(sGate + 64) + 1;
      }
    }
    asm volatile("" ::: "memory");
    if (__shfl_sync(0xffffffffu, warp_g, 0) != 8) {
#pragma unroll 1
      for (int i = 0; i < 32 && !mbar_test(bAf + 7 * 8, 0); i++) __nanosleep(200);
      if (lr0 < S_LEN) {
#pragma unroll 1
        for (int i = warp_g - 9; i < 16; i += 3) {
          const float g = gate_row(lr0 + i, lane, x, gate_w);
          if (lane == 0) asm volatile("st.shared.f32 [%0], %1;" ::"r"(sGate + i * 4), "f"(g) : "memory");
        }
        if (lane == 0) {
          mbar_arrive(bG);
          __threadfence();
          atomicAdd(&g_sync[F_GATE], 1u);
        }
      }
      uint32_t aph = 1;
#pragma unroll 1
      for (int ji = 0; ji < K1_MAXJOBS; ji++) aph ^= (p.jobs[cl][ji] >> 14) & 1;
      if (warp_g == 9) {
        uint32_t nxt = 0;
        if (lane == 0) {
#pragma unroll 1
        for (int ji = 0; ji < K1_MAXJOBS; ji++) {
          const uint32_t job = p.jobs[cl][ji];
          if (!(job & 3)) break;
          PWAIT(bS + (ji & 3) * 8, (ji >> 2) & 1);
          __threadfence();
          atomicAdd(&g_sync[(((job >> 6) & 3) == 2) ? (F_QKVA + ((job >> 3) & 7) * 2 + rank) : (F_HP + ((job >> 10) & 15))], 1u);
        }
#pragma unroll 1
        for (int it = 0;; it++) {
          PWAIT(bS2 + (it & 3) * 8, (it >> 2) & 1);
          const uint32_t item = lds32(sItem + (it & 7) * 4);
          nxt = lds32(sItem + ((it + 1) & 7) * 4);
          __threadfence();
          atomicOr(&g_sync[F_CTX + (item & 7) * 2 + rank], 1u << (item >> 3));
          if (nxt >= K2_END) break;
        }
        }
        const uint32_t unit = __shfl_sync(0xffffffffu, nxt, 0) & 255;
        {
          const int mblk = (7 - (p.unit[unit][0] >> 1)) * 2 + rank, nhalf = p.unit[unit][0] & 1;
          bf16* o = ptr_add(out, (mblk * 128 + p.unit[unit][1] * 32) * DM * 2);
          const bool mine = p.unit[unit][1] < 4;
#pragma unroll 4
          for (int i = 0; i < 32 && mine; i++) __stcg(reinterpret_cast<uint4*>(ptr_add(o, i * DM * 2 + nhalf * 512 + lane * 16)), make_uint4(0, 0, 0, 0));
#pragma unroll
          for (int i = 0; i < 4 && mine; i++) __stcg(reinterpret_cast<uint4*>(ptr_add(o, (i * 8 + (lane >> 2)) * DM * 2 + 1024 + nhalf * 64 + (lane & 3) * 16)), make_uint4(0, 0, 0, 0));
          asm volatile("fence.proxy.async.global;" ::: "memory");
          __threadfence();
          __syncwarp();
          if (lane == 0) {
            prefetch_tmap(&p.tmR[0]); prefetch_tmap(&p.tmR[1]);
            unsigned int* cnt = &g_sync[F_XCH + mblk * 2 + nhalf];
            const uint32_t xtarget = lds32(sGate + 64) * 4 + 4;
            if (mine) atomicAdd(cnt, 1u);
            uint32_t v;
#pragma unroll 1
            for (uint32_t spins = 0; spins < (1u << 22); spins++) {
              asm volatile("ld.acquire.gpu.global.u32 %0, [%1];" : "=r"(v) : "l"(cnt) : "memory");
              if ((int)(v - xtarget) >= 0) break;
              __nanosleep(200);
            }
            asm volatile("fence.proxy.async.global;" ::: "memory");
            mbar_arrive(bZ);
          }
        }
      } else if (warp_g == 11) {
        if (lane == 0) {
          asm volatile("st.shared.u32 [%0], %1;" ::"r"(sGate + 64), "r"(__ldcg(&g_sync[F_EPOCH])) : "memory");
          wait_flag(&g_sync[F_GATE], GATE_TARGET);
          prefetch_tmap(&p.tmC); prefetch_tmap(&p.tmQ); prefetch_tmap(&p.tmK); prefetch_tmap(&p.tmV);
          uint32_t tick;
          if (rank == 0) {
            PWAIT(bLast, 0);
            PWAIT(bAe + FIRST_DRAW * 8, aph);
            tick = atomicAdd(&g_sync[F_TICK], 1u);
            asm volatile("st.shared.u32 [%0], %1;" ::"r"(sTick + 8), "r"(tick) : "memory");
            asm volatile(
                "{\n.reg .b32 a, b;\nmapa.shared::cluster.u32 a, %0, 1;\nmapa.shared::cluster.u32 b, %1, 1;\n"
                "st.async.shared::cluster.mbarrier::complete_tx::bytes.u32 [a], %2, [b];\n}" ::"r"(sTick + 8), "r"(bT0), "r"(tick) : "memory");
          } else {
            mbar_expect(bT0, 4);
            PWAIT(bT0, 0);
            tick = lds32(sTick + 8);
          }
          wait_flag(&g_sync[F_HP + (p.order[tick] >> 4)], RDY_TARGET);
          mbar_arrive(bR);
        }
      } else if (warp_g == 10) {
        if (lr0 < S_LEN && lane == 0) {
          prefetch_tmap(&p.tmL[0]); prefetch_tmap(&p.tmL[1]); prefetch_tmap(&p.tmL[2]);
          wait_flag(&g_sync[F_QKVA + (lr0 >> 7)], K1_FLAG_TARGET);
          wait_flag(&g_sync[F_QKVA + (max(lr0 - 16, 0) >> 7)], K1_FLAG_TARGET);
          asm volatile("fence.proxy.async.global;" ::: "memory");
          PWAIT(bLast, 0);
#pragma unroll 1
          for (int kc = 0; kc < 6; kc++) {
            PWAIT(bAe + kc * 8, aph);
            if (kc == 3) {
              mbar_expect(bL, LV);
              tma4d(sL, &p.tmL[0], bL, lr0 / 2 - 8, 9, 0);
              tma4d(sL + LQ, &p.tmL[1], bL, lr0 / 2, 0, 0);
            }
          }
          mbar_expect(bL2, LQ);
          tma4d(sL + LV, &p.tmL[0], bL2, lr0 / 2 - 8, 18, 0);
        }
        __syncwarp();
        if (lr0 < S_LEN) {
          PWAIT(bL + 8, 0);
          if (lane < 8) mbar_arrive_cluster(bE + (4 + (lane >> 2)) * 8, lane & 1);
        }
        bar_sync(5, 256 + 32);
        if (lr0 < S_LEN && lane == 0) {
          asm volatile("cp.async.bulk.tensor.4d.global.shared::cta.bulk_group [%0, {%2, %3, %2, %2}], [%1];" ::"l"(&p.tmL[2]), "r"(sL + LO), "r"(0), "r"(lr0 / 2) : "memory");
          asm volatile("cp.async.bulk.commit_group;" ::: "memory");
          asm volatile("cp.async.bulk.wait_group.read 0;" ::: "memory");
        }
        __syncwarp();
        if (lane < ((lr0 < S_LEN) ? 4 : 12)) mbar_arrive_cluster(bE + (6 - (lane >> 2)) * 8, lane & 1);
        if (lr0 < S_LEN && lane == 0) {
          asm volatile("cp.async.bulk.wait_group 0;" ::: "memory");
          asm volatile("fence.proxy.async.global;" ::: "memory");
          __threadfence();
          atomicAdd(&g_sync[F_OA + (lr0 >> 7)], 1u);
        }
      }
    }
    __syncwarp();
    cluster_sync();
  } else {
    reg_alloc<232>();
    const int wg = warp_g >> 2, warp = warp_g & 3, q = lane & 3;
    const bool sig = (lane == 0) && (warp < 2);
    {
      K1State st{0, 0, 0, nullptr, 0, 0, 0, 24};
      float acc[128];
      uint32_t pk[64];
      if (wg == 0) { TS(0, 0); TSC(0, 2); }
      uint32_t job = p.jobs[cl][0];
      k1_first(st, job, bAf, bBf);
      {
#pragma unroll 1
        for (int ji = 0; job & 3; ji++) {
          const uint32_t njob = p.jobs[cl][ji + 1];
          k1_tile(acc, pk, st, job, njob, sA, sB, bAf, bAe, bBf, bBe, bS, wg, warp, lane, rank);
          job = njob;
        }
      }
#pragma unroll
      for (int i = 0; i < 4; i++)
        mbar_arrive_cluster_if(bE + i * 8, warp & 1, sig);
      if (lr0 < S_LEN) mbar_wait(bG, 0);
      if (st.wsel == 3) {
#pragma unroll
        for (int G = 0; G < 16; G++) scale_q4(pk + G * 4);
      }
      auto flush = [&](int i, uint32_t dep) {
        asm volatile("{\n.reg .pred p;\nsetp.eq.u32 p, %5, 0;\n@p st.global" STA_MOD ".v4.b32 [%0], {%1, %2, %3, %4};\n}" ::"l"(st.pp + goff(i / 2, i & 1)),
                     "r"(pk[i * 4]), "r"(pk[i * 4 + 1]), "r"(pk[i * 4 + 2]), "r"(pk[i * 4 + 3]), "r"(dep & blockIdx.y) : "memory");
      };
      if (wg == 0) { TS(0, 1); TSC(0, 3); }
      if (lr0 < S_LEN) {
        const float gate0 = __uint_as_float(lds32(sGate + (lane >> 2) * 8)), gate1 = __uint_as_float(lds32(sGate + (lane >> 2) * 8 + 4));
        local_attn(lr0, warp_g, sL, bL, bL2, lane, gate0, gate1, flush);
        k1_flag(st, lane, bS);
      } else {
        FLUSH();
      }
      bar_arrive(5, 256 + 32);
    }
    __syncwarp();
    uint32_t item, rot;
    {
      const int mybar = 1 + wg, otherbar = 2 - wg;
      const uint32_t never = blockIdx.y;
      float S[64], O[64];
      uint32_t P[32], Q[32];
      float m0, m1, l0, l1, gf0, gf1;
      uint32_t eoff;
      Cursor c{2 + 2 * (uint32_t)wg, 0}, ck{1 + (uint32_t)wg, 0};
      if (wg == 1) bar_arrive(1, 256);
      if (wg == 0) { TS(1, 0); TSC(1, 2); }
      {
        const Cursor cq{0, 0}, cs0{1, 0}, cs1{3, 0};
        const int it = 0, hi = wg ^ 1;
        mbar_wait2(bF, 0, bF + ck.s * 8, 0);
        LOAD_Q();
        wg_fence();
        ISSUE_QK(ck);
        wg_commit();
        RELEASE(cq);
        NEW_ITEM();
        wg_wait<0>();
        fence_regs(S);
      }
#pragma unroll 1
      for (int it = 0;;) {
        int hi = (wg ^ it ^ 1) & 1;
        RELEASE(ck);
        const int nblk = 2 * (item & 7) + 1 + hi;
        Cursor cv;
        float s0 = 0.f, s1 = 0.f;
        l0 = 0.f; l1 = 0.f;
        m0 = 0.f; m1 = 0.f;
        bool shifted = false;
        {
          const int d = warp * 16 + (lane >> 2) - 2 * q;
          if (rank == hi) {
#pragma unroll
            for (int jj = 0; jj < 8; jj++) MASK(jj, jj);
            EXPB(0); EXPB(1); EXPB(2); EXPB(3);
#pragma unroll
            for (int i = 32; i < 64; i++) S[i] = -INFINITY;
#pragma unroll
            for (int i = 16; i < 32; i++) P[i] = 0;
          } else {
#pragma unroll
            for (int jj = 0; jj < 8; jj++) MASK(jj + 8, jj);
            EXPB(0); EXPB(1); EXPB(2); EXPB(3); EXPB(4); EXPB(5); EXPB(6); EXPB(7);
          }
        }
        float chk;
        asm("{\n.reg .pred p;\nsetp.ge.f32 p, %1, %2;\nselp.f32 %0, %3, 0f7F800000, p;\n}" : "=f"(chk) : "f"(fminf(s0, s1)), "f"(q ? -1.f : SPEC_LO), "f"(s0 + s1));
        fence_regs(P);
        TB(9);
#pragma unroll 1
        for (int n = 1;; n++) {
          if (__any_sync(0xffffffffu, !(chk <= SPEC_HI))) {
            float mx0 = fmaxf(S[0], S[1]), mx1 = fmaxf(S[2], S[3]);
#pragma unroll
            for (int jj = 1; jj < 16; jj++) {
              mx0 = fmaxf(mx0, fmaxf(S[jj * 4 + 0], S[jj * 4 + 1]));
              mx1 = fmaxf(mx1, fmaxf(S[jj * 4 + 2], S[jj * 4 + 3]));
            }
            mx0 = fmaxf(mx0, __shfl_xor_sync(0xffffffffu, mx0, 1));
            mx1 = fmaxf(mx1, __shfl_xor_sync(0xffffffffu, mx1, 1));
            mx0 = fmaxf(mx0, __shfl_xor_sync(0xffffffffu, mx0, 2));
            mx1 = fmaxf(mx1, __shfl_xor_sync(0xffffffffu, mx1, 2));
            const float lo = (n == 1) ? -INFINITY : 0.f;
            mx0 = fmaxf(mx0, lo);
            mx1 = fmaxf(mx1, lo);
            m0 += mx0; m1 += mx1;
            shifted = true;
            const float sc0 = ex2(-fmaxf(mx0, 0.f)), sc1 = ex2(-fmaxf(mx1, 0.f));
            l0 *= sc0; l1 *= sc1;
            s0 = 0.f; s1 = 0.f;
#pragma unroll
            for (int jj = 0; jj < 16; jj++) {
              const float e0 = ex2(S[jj * 4 + 0] - mx0), e1 = ex2(S[jj * 4 + 1] - mx0), e2 = ex2(S[jj * 4 + 2] - mx1), e3 = ex2(S[jj * 4 + 3] - mx1);
              s0 += e0 + e1;
              s1 += e2 + e3;
              P[jj * 2 + 0] = pack_bf16(e0, e1);
              P[jj * 2 + 1] = pack_bf16(e2, e3);
              O[jj * 4 + 0] *= sc0;
              O[jj * 4 + 1] *= sc0;
              O[jj * 4 + 2] *= sc1;
              O[jj * 4 + 3] *= sc1;
            }
          }
          l0 += s0;
          l1 += s1;
          if (n >= nblk) break;
          ck = c; c.next();
          cv = c; c.next();
          mbar_wait2(bF + ck.s * 8, ck.ph, bF + cv.s * 8, cv.ph);
          TURN_SYNC();
          TRC(0);
          wg_fence();
          ISSUE_QK(ck);
          wg_commit();
          {
            const uint64_t dv = make_desc(sbase + cv.s * 32768, 16384, 1024, 1);
#pragma unroll
            for (int t = 0; t < 8; t++) {
              wgmma_rs_n128<1, 0>(O, P[4 * t], P[4 * t + 1], P[4 * t + 2], P[4 * t + 3], dv + (uint64_t)(t * 128), (t > 0) ? 1 : (n != 1));
              if ((PVM >> t) & 1) wg_commit();
            }
          }
          TURN_ARRIVE();
          s0 = 0.f; s1 = 0.f;
          wg_wait<__builtin_popcount(PVM)>();
          fence_regs(S);
          RELEASE(ck);
          if (shifted) {
#pragma unroll
            for (int i = 0; i < 64; i++) S[i] -= (i & 2) ? m1 : m0;
          }
          wg_wait<__builtin_popcount(PVM) - 1>();
          EXPC(0); EXPC(1); EXPC(2); EXPC(3); EXPC(4); EXPC(5); EXPC(6); EXPC(7);
          chk = s0 + s1;
        }
        it++;
        hi ^= 1;
        TB(0);
        Cursor cq = c, cs0, cs1;
        rot = k3_rot(c.s);
        c.next();
        ck = c; c.next();
        cs0 = ck; cs1 = ck;
        cv = c; c.next();
        if (!hi) {
          ck = c; c.next();
          cs1 = c; c.next();
        }
        mbar_wait(bF + cq.s * 8, cq.ph);
        TB(1);
        LOAD_Q();
        const uint32_t rdy = mbar_test(bF + ck.s * 8, ck.ph) & mbar_test(bF + cv.s * 8, cv.ph);
        l0 += __shfl_xor_sync(0xffffffffu, l0, 1);
        l1 += __shfl_xor_sync(0xffffffffu, l1, 1);
        l0 += __shfl_xor_sync(0xffffffffu, l0, 2);
        l1 += __shfl_xor_sync(0xffffffffu, l1, 2);
        if (item >= K2_END) {
          TURN_SYNC();
          TRC(2);
          wg_fence();
          ISSUE_PV(cq, nblk == 1);
          wg_commit();
          if (wg == (it & 1)) TURN_ARRIVE();
          asm volatile("" : "+f"(gf0), "+f"(gf1), "+f"(l0), "+f"(l1));
          const float f0 = __fdividef(1.f - gf0, l0), f1 = __fdividef(1.f - gf1, l1);
          bf16* optr = ptr_add(g_ctx, eoff);
          wg_wait<0>();
          fence_regs(O);
          mbar_arrive_cluster_if(bH, warp & 1, sig);
          STORE_O(0); STORE_O(1); STORE_O(2); STORE_O(3);
          __syncwarp();
          mbar_arrive_if(bS2 + ((it - 1) & 3) * 8, lane == 0);
          break;
        }
        if (!rdy) mbar_wait2(bF + ck.s * 8, ck.ph, bF + cv.s * 8, cv.ph);
        TB(2);
        TURN_SYNC();
        TB(3);
        TRC(1);
        wg_fence();
        ISSUE_PV(cv, nblk == 1);
        wg_commit();
        ISSUE_QK(ck);
        wg_commit();
        TURN_ARRIVE();
        RELEASE(cq);
        TB(4);
        asm volatile("" : "+f"(gf0), "+f"(gf1), "+f"(l0), "+f"(l1));
        const float f0 = __fdividef(1.f - gf0, l0), f1 = __fdividef(1.f - gf1, l1);
        wg_wait<1>();
        fence_regs(O);
        fence_regs(P);
        TB(5);
        RELEASE(cv);
        {
          bf16* optr = ptr_add(g_ctx, eoff);
          STORE_O(0); STORE_O(1); STORE_O(2); STORE_O(3);
          __syncwarp();
          mbar_arrive_if(bS2 + ((it - 1) & 3) * 8, lane == 0);
        }
        TB(6);
        NEW_ITEM();
        TB(7);
        wg_wait<0>();
        fence_regs(S);
        TB(8);
      }
      TRC(3);
      if (wg == 1) { TS(1, 1); TSC(1, 3); }
    }
    __syncwarp();
    const uint32_t unit = item & 255;
    {
      const int mblk = (7 - (p.unit[unit][0] >> 1)) * 2 + rank, nhalf = p.unit[unit][0] & 1;
      float acc[144];
      uint32_t s = rot, ph = 0, prev = 0, k = 0;
      if (wg == 0) { TS(2, 0); TSC(2, 2); }
      uint32_t fa[16], fb[16], fc[16];
      const uint32_t aoff = (wg * 64 + warp * 16 + (lane & 15)) * 128 + (((lane >> 4) ^ (lane & 7)) << 4);
#define C_NEXT()                                                                                               \
  do {                                                                                                         \
    s = (s + 1) & 3;                                                                                           \
    if (s == rot) ph ^= 1;                                                                                     \
    mbar_wait(b3F + s * 8, ph);                                                                                \
  } while (0)
#define C_LOAD(F)                                                                                              \
  do {                                                                                                         \
    _Pragma("unroll") for (int t = 0; t < 4; t++)                                                              \
        ldsm_x4(F[4 * t], F[4 * t + 1], F[4 * t + 2], F[4 * t + 3], sbase + s * K3_STAGE + (aoff ^ (t * 32))); \
  } while (0)
#define C_MMA(F, S, H, SD)                                                                                     \
  do {                                                                                                         \
    const uint32_t st = sbase + (S) * K3_STAGE;                                                                \
    const uint64_t db = make_desc(st + 16384, 4096, 1024, 1), dt = make_desc(st + 49152, 16, 512, 2);          \
    _Pragma("unroll") for (int t = 0; t < 4; t++) {                                                            \
      const int sd = (t > 0) || (SD);                                                                          \
      if ((H) & 1) wgmma_rs_n128<1, 0>(acc, F[4 * t], F[4 * t + 1], F[4 * t + 2], F[4 * t + 3], db + (uint64_t)((t >> 1) * 1024 + (t & 1) * 128), sd); \
      if ((H) & 2) wgmma_rs_n128<1, 64>(acc, F[4 * t], F[4 * t + 1], F[4 * t + 2], F[4 * t + 3], db + (uint64_t)((t >> 1) * 1024 + (t & 1) * 128 + 512), sd); \
      if ((H) & 2) wgmma_rs_n32<1, 128>(acc, F[4 * t], F[4 * t + 1], F[4 * t + 2], F[4 * t + 3], dt + (uint64_t)(t * 64), sd); \
    }                                                                                                          \
  } while (0)
#define C_STEP(F, G)                                                                                           \
  {                                                                                                            \
    wg_fence();                                                                                                \
    C_MMA(F, s, 3, k > 0);                                                                                     \
    wg_commit();                                                                                               \
    wg_wait<1>();                                                                                              \
    fence_regs(G);                                                                                             \
    mbar_arrive_cluster_if(b3E + prev * 8, warp & 1, sig && k > 0);                                            \
    prev = s;                                                                                                  \
    TCK(k + 1);                                                                                                \
    C_NEXT();                                                                                                  \
    if ((tid & 127) == 0 && k < 11) TP(37 + wg * 12 + k);                                                      \
    if (++k + CR >= lds32(sK1)) break;                                                                         \
    C_LOAD(G);                                                                                                 \
  }
      TCK(0);
      mbar_wait(b3F + s * 8, 0);
      if ((tid & 127) == 0) TP(36 + wg * 12);
      C_LOAD(fa);
#pragma unroll
      for (int i = 0; i < 16; i++) fb[i] = 0;
#pragma unroll 1
      for (;;) {
        C_STEP(fa, fb)
        C_STEP(fb, fa)
      }
      C_LOAD(fc);
      if (wg == 1) {
        wg_wait<0>();
        mbar_arrive_cluster_if(b3E + prev * 8, warp & 1, sig);
        mbar_wait(bLd, 0);
      }
      const uint32_t s0 = s;
      wg_fence();
      C_MMA(fc, s0, 2, 1);
      wg_commit();
      wg_wait<1>();
      fence_regs(fa);
      fence_regs(fb);
      mbar_arrive_cluster_if(b3E + prev * 8, warp & 1, sig && wg == 0);
      cluster_arrive();
      C_NEXT();
      C_LOAD(fa);
      wg_fence();
      C_MMA(fa, s, 2, 1);
      C_MMA(fc, s0, 1, 1);
      wg_commit();
      C_NEXT();
      C_LOAD(fb);
      wg_fence();
      C_MMA(fb, s, 2, 1);
      wg_commit();
      wg_wait<1>();
      fence_regs(fc);
      C_NEXT();
      C_LOAD(fc);
      wg_fence();
      C_MMA(fc, s, 2, 1);
      wg_commit();
      C_MMA(fa, (s0 + 1) & 3, 1, 1);
      C_MMA(fb, (s0 + 2) & 3, 1, 1);
      C_MMA(fc, s, 1, 1);
      wg_commit();
      mbar_arrive_if(bLd, tid < 128 && lane == 0);
      const uint32_t stail = sbase + K3_NST * K3_STAGE + warp_g * 1024;
      const int row = mblk * 128 + warp_g * 16;
      mbar_wait(bZ, 0);
#pragma unroll
      for (int h = 1; h >= 0; h--) {
        if (h) wg_wait<1>(); else wg_wait<0>();
#pragma unroll
        for (int i = h * 64; i < 64 + h * 80; i++) asm volatile("" : "+f"(acc[i])::"memory");
        if (!h && wg == 0) TS(2, 4);
#pragma unroll
        for (int i = h * 8; i < 8 + h * 10; i++) {
          const uint32_t ad = (i < 16) ? sbase + (i >> 2) * K3_STAGE + (aoff ^ ((i & 3) * 32))
                                       : stail + (lane & 15) * 64 + ((((i & 1) * 2 + (lane >> 4)) ^ ((lane >> 1) & 3)) << 4);
          asm volatile("stmatrix.sync.aligned.m8n8.x4.shared.b16 [%0], {%1, %2, %3, %4};" ::"r"(ad), "r"(pack_bf16(acc[i * 8], acc[i * 8 + 1])),
                       "r"(pack_bf16(acc[i * 8 + 2], acc[i * 8 + 3])), "r"(pack_bf16(acc[i * 8 + 4], acc[i * 8 + 5])), "r"(pack_bf16(acc[i * 8 + 6], acc[i * 8 + 7])) : "memory");
        }
        asm volatile("fence.proxy.async.shared::cta;" ::: "memory");
        __syncwarp();
        if (!h && wg == 0) TS(2, 5);
        if (lane == 0) {
#pragma unroll
          for (int c = h * 2; c < 2 + h * 3; c++)
            asm volatile("cp.reduce.async.bulk.tensor.2d.global.shared::cta.add.tile.bulk_group [%0, {%2, %3}], [%1];" ::"l"(&p.tmR[c >> 2]),
                         "r"((c < 4) ? sbase + c * K3_STAGE + warp_g * 2048 : stail), "r"((c < 4) ? nhalf * 256 + c * 64 : 512 + nhalf * 32), "r"(row) : "memory");
        }
        __syncwarp();
      }
      if (lane == 0) {
        asm volatile("cp.async.bulk.commit_group;" ::: "memory");
        if (wg == 0) TS(2, 6);
        asm volatile("cp.async.bulk.wait_group 0;" ::: "memory");
      }
      __syncwarp();
    }
    if (wg == 0) { TS(2, 1); TSC(2, 3); }
    cluster_wait();
  }
}

typedef CUresult (*EncFn)(CUtensorMap*, CUtensorMapDataType, cuuint32_t, void*, const cuuint64_t*, const cuuint64_t*, const cuuint32_t*,
                          const cuuint32_t*, CUtensorMapInterleave, CUtensorMapSwizzle, CUtensorMapL2promotion, CUtensorMapFloatOOBfill);

static void enc2d(EncFn enc, CUtensorMap* m, const void* ptr, uint64_t cols, uint64_t rows, uint32_t bc, uint32_t br,
                  CUtensorMapSwizzle sw = CU_TENSOR_MAP_SWIZZLE_128B) {
  cuuint64_t gd[2] = {cols, rows}, gs[1] = {cols * 2};
  cuuint32_t bx[2] = {bc, br}, es[2] = {1, 1};
  enc(m, CU_TENSOR_MAP_DATA_TYPE_BFLOAT16, 2, const_cast<void*>(ptr), gd, gs, bx, es, CU_TENSOR_MAP_INTERLEAVE_NONE, sw,
      CU_TENSOR_MAP_L2_PROMOTION_L2_256B, CU_TENSOR_MAP_FLOAT_OOB_FILL_NONE);
}
static void enc3d(EncFn enc, CUtensorMap* m, const void* ptr, uint64_t cols, uint64_t rows, uint32_t br, uint32_t bch) {
  cuuint64_t gd[3] = {64, rows, cols / 64}, gs[2] = {cols * 2, 128};
  cuuint32_t bx[3] = {64, br, bch}, es[3] = {1, 1, 1};
  enc(m, CU_TENSOR_MAP_DATA_TYPE_BFLOAT16, 3, const_cast<void*>(ptr), gd, gs, bx, es, CU_TENSOR_MAP_INTERLEAVE_NONE,
      CU_TENSOR_MAP_SWIZZLE_128B, CU_TENSOR_MAP_L2_PROMOTION_L2_256B, CU_TENSOR_MAP_FLOAT_OOB_FILL_NONE);
}

static void build_k1_jobs(Params& p) {
  int cnt[NCLUSTER];
  for (int c = 0; c < NCLUSTER; c++) {
    cnt[c] = 0;
    for (int i = 0; i <= K1_MAXJOBS; i++) p.jobs[c][i] = 0;
  }
  auto add = [&](int c, int nch, int a_sel, int mp, int w_sel, int chunk0) {
    p.jobs[c][cnt[c]++] = (uint16_t)((nch - 1) | (a_sel << 2) | (mp << 3) | (w_sel << 6) | (chunk0 << 8));
  };
  const char* plan = "cccccccccc cccccccccc cccccccc cccc xxxx xxxx xxxxxx xxxxxxxx";
  const char *hpp = "abcd01e23456789f", *qpp = "01abc23de456789f";
  int TIE = 0;
  int XA = 0;
  auto hex = [](char c) { return (c > '9') ? c - 'a' + 10 : c - '0'; };
  const char* cur[8];
  int tend[8] = {};
  for (int g = 0; g < 8; g++) {
    cur[g] = plan;
    while (*plan == 'c' || *plan == 'x') plan++;
    if (*plan) plan++;
  }
  int kc = 0, kx = 0;
  for (;;) {
    int b = -1, bt = 0;
    for (int g = 0; g < 8; g++) {
      const int t = tend[g] + (*cur[g] == 'x' ? 94 : 85);
      if ((*cur[g] == 'c' || *cur[g] == 'x') && (b < 0 || t < bt || (TIE && t == bt))) { b = g; bt = t; }
    }
    if (b < 0) break;
    const int a = kx - XA;
    for (int mp = 0; mp < 8; mp++) {
      if (*cur[b] == 'c') add(b * 8 + mp, 4, 0, mp, kc & 1, hex(hpp[kc >> 1]) * 4);
      else if (a >= 0 && a < 7) add(b * 8 + mp, a == 0 ? 3 : 4, 1, mp, 2, a == 0 ? 24 : (a - 1) * 4);
      else add(b * 8 + mp, 4, 1, mp, 3, hex(qpp[a < 0 ? kx : kx - 7]) * 4);
    }
    if (*cur[b] == 'c') kc++; else kx++;
    cur[b]++;
    tend[b] = bt;
  }
  for (int mp = 0; mp < 8; mp++) add(64 + mp / 4, 4, 1, mp, 3, hex(qpp[15]) * 4);
  for (int cc = 0; cc < NCLUSTER; cc++)
    for (int i = 0; i < cnt[cc]; i++) {
      const int key = p.jobs[cc][i] & 0x3C;
      if (i == 0 || (p.jobs[cc][i - 1] & 0x3C) != key) p.jobs[cc][i] |= (1 << 14);
      if (i == cnt[cc] - 1 || (p.jobs[cc][i + 1] & 0x3C) != key) p.jobs[cc][i] |= (1 << 15);
    }
}

static void build_k2_items(Params& p) {
  int ps[16][3] = {{0, 2, 2}, {0, 4, 0}, {4, 8, 0}, {8, 12, 1}, {12, 16, 1}, {16, 20, 3}, {20, 26, 4}, {0, 32, 0}};
  bool done[256] = {};
  int n = 0;
  for (int i = 0; i < 16; i++)
    for (int j = 7; j >= ps[i][2]; j--)
      for (int h = ps[i][0]; h < ps[i][1]; h++)
        if (!done[h * 8 + j]) { done[h * 8 + j] = true; p.order[n++] = (uint8_t)(h * 8 + j); }
}

static void build_k3_units(Params& p) {
  const char* map = "0123456789abcddcba98765432100123456789abcddcba9876543210feeffeeffe";
  int cnt[16] = {};
  for (int u = 0; u < 66; u++) {
    const int t = (map[u] > '9') ? map[u] - 'a' + 10 : map[u] - '0';
    p.unit[u][0] = (uint8_t)t; p.unit[u][1] = (uint8_t)cnt[t]; p.unit[u][2] = (uint8_t)(cnt[t] * K3_NS);
    cnt[t]++;
  }
  for (int u = 0; u < 66; u++) p.unit[u][3] = (uint8_t)(cnt[p.unit[u][0]] * K3_NS);
}

extern "C" void kernel_launch(void* const* d_in, const int* in_sizes, int n_in, void* d_out, int out_size) {
  const bf16* x = (const bf16*)d_in[0];
  const bf16* wqkv = (const bf16*)d_in[1];
  const bf16* wo = (const bf16*)d_in[2];
  const bf16* ckv = (const bf16*)d_in[4];
  const bf16* w_q = (const bf16*)d_in[5];
  const bf16* w_uk = (const bf16*)d_in[6];
  const bf16* w_uv = (const bf16*)d_in[7];
  const bf16* w_o = (const bf16*)d_in[8];
  const bf16* gate_w = (const bf16*)d_in[9];

  EncFn enc = nullptr;
  cudaDriverEntryPointQueryResult qr;
  cudaGetDriverEntryPoint("cuTensorMapEncodeTiled", (void**)&enc, cudaEnableDefault, &qr);
  void *pK, *pV, *pCtx, *pQA;
  cudaGetSymbolAddress(&pQA, g_QKVA);
  cudaGetSymbolAddress(&pK, g_K);
  cudaGetSymbolAddress(&pV, g_V);
  cudaGetSymbolAddress(&pCtx, g_ctx);

  static Params p;
  enc2d(enc, &p.tmA[0], ckv, DC, S_LEN, 64, 128);
  enc2d(enc, &p.tmA[1], x, DM, S_LEN, 64, 128);
  enc3d(enc, &p.tmW[0], w_uk, HDIM, DC, 16, 4);
  enc3d(enc, &p.tmW[1], w_uv, HDIM, DC, 16, 4);
  enc3d(enc, &p.tmW[2], wqkv, NQKVA, DM, 16, 4);
  enc3d(enc, &p.tmW[3], w_q, HDIM, DM, 16, 4);
  build_k1_jobs(p);
  enc2d(enc, &p.tmK, pK, 64, 64 * S_LEN, 64, 128);
  enc2d(enc, &p.tmV, pV, 64, 64 * S_LEN, 64, 128);
  enc2d(enc, &p.tmQ, pCtx, 64, 73 * S_LEN, 64, 64);
  build_k2_items(p);
  build_k3_units(p);
  for (int i = 0; i < 3; i++) {
    const cuuint64_t cs = S_LEN * 128, nch = (i < 2) ? 27 : 9;
    cuuint64_t gd[4] = {64, S_LEN / 2, i ? 2 : nch, i ? nch : 2}, gs[3] = {256, i ? 128 : cs, i ? cs : 128};
    cuuint32_t bx[4] = {64, i ? 8u : 16u, i ? 2u : 9u, i ? 9u : 2u}, es[4] = {1, 1, 1, 1};
    enc(&p.tmL[i], CU_TENSOR_MAP_DATA_TYPE_BFLOAT16, 4, (i < 2) ? pQA : (void*)((bf16*)pCtx + S_LEN * HDIM), gd, gs, bx, es, CU_TENSOR_MAP_INTERLEAVE_NONE,
        CU_TENSOR_MAP_SWIZZLE_128B, CU_TENSOR_MAP_L2_PROMOTION_L2_256B, CU_TENSOR_MAP_FLOAT_OOB_FILL_NONE);
  }
  enc2d(enc, &p.tmC, pCtx, 64, 73 * S_LEN, 64, 128);
  enc3d(enc, &p.tmO[0], w_o, DM, HDIM, 32, 4);
  enc3d(enc, &p.tmO[1], wo, DM, DM, 32, 4);
  enc2d(enc, &p.tmOt[0], w_o, DM, HDIM, 32, 32, CU_TENSOR_MAP_SWIZZLE_64B);
  enc2d(enc, &p.tmOt[1], wo, DM, DM, 32, 32, CU_TENSOR_MAP_SWIZZLE_64B);
  enc2d(enc, &p.tmR[0], d_out, DM, S_LEN, 64, 16);
  enc2d(enc, &p.tmR[1], d_out, DM, S_LEN, 32, 16, CU_TENSOR_MAP_SWIZZLE_64B);

  cudaFuncSetAttribute(fused_kernel, cudaFuncAttributeMaxDynamicSharedMemorySize, SMEM_BYTES);
  fused_kernel<<<NCLUSTER * 2, 384, SMEM_BYTES>>>(p, x, gate_w, (bf16*)d_out);
}
```
